```python
import torch

def _softmax(x, axis=-1):
    return torch.softmax(x, dim=axis)
def _gelu(x):
    return torch.nn.functional.gelu(x, approximate="tanh")
def _silu(x):
    return torch.nn.functional.silu(x)
def _sigmoid(x):
    return torch.sigmoid(x)
def _layernorm(x, axis=-1, eps=1e-5):
    m = x.mean(dim=axis, keepdim=True)
    v = x.var(dim=axis, keepdim=True, unbiased=False)
    return (x - m) / torch.sqrt(v + eps)
def _scatter_add(tgt, idx, src, axis=0):
    return tgt.clone().index_add_(axis, idx, src)
def _segment_sum(src, seg, n):
    out = torch.zeros((n,) + src.shape[1:], dtype=src.dtype)
    return out.index_add_(0, seg, src)
def _pad(x, pw):
    flat = tuple(v for pair in reversed(pw) for v in pair)
    return torch.nn.functional.pad(x, flat)

kernel_name = 'interleave_layers__sliding_local_dilated__ssm_conv_s4__prompt'

def setup_inputs():

    _w = (lambda a: (lambda t: t.to(torch.bfloat16) if t.is_floating_point() else t)(torch.as_tensor(a)))
    def _A_setup():
        B, S, D = 1, 2048, 512
        return {
            "x": _w((lambda *s: torch.randn(*s, dtype=torch.bfloat16) * 0.05)(B, S, D)),
            "wqkv": _w((lambda *s: torch.randn(*s, dtype=torch.bfloat16) * 0.05)(D, 3 * D)),
            "wo": _w((lambda *s: torch.randn(*s, dtype=torch.bfloat16) * 0.05)(D, D)),
        }
    _A_in = _A_setup()

    def _B_setup():
        B, L, D, N = 1, 2048, 512, 128
        A_re = -(lambda _x: torch.exp(torch.as_tensor(_x)))((lambda *s: torch.randn(*s, dtype=torch.bfloat16) * 3.2)(D, N))
        A_im = torch.pi * (lambda *s: torch.randn(*s, dtype=torch.bfloat16) * 0.1)(D, N)
        B_re = (lambda *s: torch.randn(*s, dtype=torch.bfloat16) * 0.1)(D, N)
        B_im = (lambda *s: torch.randn(*s, dtype=torch.bfloat16) * 0.1)(D, N)
        C_re = (lambda *s: torch.randn(*s, dtype=torch.bfloat16) * 0.1)(D, N)
        C_im = (lambda *s: torch.randn(*s, dtype=torch.bfloat16) * 0.1)(D, N)
        log_dt = (lambda *s: torch.randn(*s, dtype=torch.bfloat16) * 0.1)(D) * 0.5 - 4.0
        Dskip = (lambda *s: torch.randn(*s, dtype=torch.bfloat16) * 0.1)(D)
        return {
            "u": _w((lambda *s: torch.randn(*s, dtype=torch.bfloat16) * 0.05)(B, L, D)),
            "A_re": _w(A_re),
            "A_im": _w(A_im),
            "B_re": _w(B_re),
            "B_im": _w(B_im),
            "C_re": _w(C_re),
            "C_im": _w(C_im),
            "log_dt": _w(log_dt),
            "Dskip": _w(Dskip),
        }
    _B_in = _B_setup()

    return {
        "A_x": _A_in["x"],
        "A_wqkv": _A_in["wqkv"],
        "A_wo": _A_in["wo"],
        "B_u": _B_in["u"],
        "B_A_re": _B_in["A_re"],
        "B_A_im": _B_in["A_im"],
        "B_B_re": _B_in["B_re"],
        "B_B_im": _B_in["B_im"],
        "B_C_re": _B_in["C_re"],
        "B_C_im": _B_in["C_im"],
        "B_log_dt": _B_in["log_dt"],
        "B_Dskip": _B_in["Dskip"],
    }

def reference(A_x, A_wqkv, A_wo, B_u, B_A_re, B_A_im, B_B_re, B_B_im, B_C_re, B_C_im, B_log_dt, B_Dskip):
    def _A_ref(x, wqkv, wo):
        B, S, D = x.shape
        H = 32; Dh = D // H
        W, dil = 8, 2
        qkv = (lambda x, *d: x.permute(*d))((x @ wqkv).reshape(B, S, 3, H, Dh), 2, 0, 3, 1, 4)
        q, k, v = qkv[0], qkv[1], qkv[2]
        scale = Dh ** -0.5
        pos = torch.arange(S)
        off = torch.arange(W) * dil
        idx = pos[:, None] - off[None, :]
        mask = idx >= 0
        idx_c = torch.where(mask, idx, 0).reshape(-1)
        kg = k[:, :, idx_c, :].reshape(B, H, S, W, Dh)
        vg = v[:, :, idx_c, :].reshape(B, H, S, W, Dh)
        logits = torch.einsum("bhsd,bhswd->bhsw", q, kg) * scale
        logits = torch.where(mask[None, None, :, :], logits, -1e9)
        attn = _softmax(logits, axis=-1)
        o = torch.einsum("bhsw,bhswd->bhsd", attn, vg)
        return (lambda x, *d: x.permute(*d))(o, 0, 2, 1, 3).reshape(B, S, D) @ wo

    def _B_ref(u, A_re, A_im, B_re, B_im, C_re, C_im, log_dt, Dskip):
        Bsz, L, D = u.shape
        dt = torch.exp(log_dt)[:, None]
        A = A_re + 1j * A_im
        Bc = B_re + 1j * B_im
        Cc = C_re + 1j * C_im
        logdA = dt * A
        dB = dt * Bc
        l = (lambda x, dt: x.to(dt))(torch.arange(L), A_re.dtype)
        P = torch.exp(logdA[:, :, None] * l[None, None, :])
        K = torch.einsum("dn,dnl,dn->dl", Cc, P, dB).real
        L2 = 2 * L
        Kp = _pad(K, ((0, 0), (0, L)))
        up = (lambda x, *d: x.permute(*d))(u, 0, 2, 1)
        up = _pad(up, ((0, 0), (0, 0), (0, L)))
        Kf = (lambda x, axes=(-2,-1): torch.fft.rfft2(x.float(), dim=axes))(Kp[:, None, :], axes=(-2, -1))
        Uf = (lambda x, axes=(-2,-1): torch.fft.rfft2(x.float(), dim=axes))(up[:, :, None, :], axes=(-2, -1))
        Yf = Uf * Kf[None, :, :, :]
        y = (lambda x, s, axes=(-2,-1): torch.fft.irfft2(x, s=s, dim=axes).to(torch.bfloat16))(Yf, (1, L2), axes=(-2, -1))[:, :, 0, :L]
        y = (lambda x, *d: x.permute(*d))(y, 0, 2, 1) + u * Dskip[None, None, :]
        return y

    x = A_x
    x = x + _A_ref(_layernorm(x, axis=-1), A_wqkv, A_wo)
    x = x + _B_ref(_layernorm(x, axis=-1), B_A_re, B_A_im, B_B_re, B_B_im, B_C_re, B_C_im, B_log_dt, B_Dskip)
    x = x + _A_ref(_layernorm(x, axis=-1), A_wqkv, A_wo)
    x = x + _B_ref(_layernorm(x, axis=-1), B_A_re, B_A_im, B_B_re, B_B_im, B_C_re, B_C_im, B_log_dt, B_Dskip)
    return x
```

```cpp
#include <cuda_runtime.h>
#include <cuda_bf16.h>
#include <cuda.h>
#include <stdint.h>

typedef __nv_bfloat16 bf16;

constexpr int LSEQ = 2048;
constexpr int DM = 512;
constexpr int NCTA = 128;
constexpr int NTHREADS = 512;
#define R_CONS 192
#define R_HELP 104
#define R_AGENT 24
#define GS0 4
#define TURN0 5
#define TURN1 5

constexpr int PG = 8192;
constexpr int P_R = 25;
constexpr int SM_KC = 27 * PG;
constexpr int KC_STRIDE = 648;
constexpr int SM_CS = SM_KC + 4 * KC_STRIDE * 2;
constexpr int SM_RED = SM_CS + 768;
constexpr int SM_EP = SM_RED + 272;
constexpr int SM_STG = SM_RED + 320;
constexpr int SM_BAR = SM_STG + 1024;
constexpr int SM_TS = SM_BAR + 768;
constexpr int SM_TOTAL = SM_TS + 512;
static_assert(SM_TOTAL <= 232448 && SM_STG % 16 == 0, "shared memory");
constexpr int SM_KGB = P_R * PG;
constexpr int SM_KGT = SM_KGB + 12288;

constexpr int CV_UH = 140 * 16;
__host__ __device__ constexpr int cv_u(int lc) { return (8 + 2 * lc) * PG; }
__host__ __device__ constexpr int cv_pe(int lc) { return cv_u(lc) + 4480; }
__host__ __device__ constexpr int cv_pb1(int lc, int w) { return w ? cv_u(lc) + 8960 + (w - 1) * 2048 : 7 * PG + lc * 2048; }
__host__ __device__ constexpr int cv_wt(int lc) { return cv_u(lc) + 15104; }
__host__ __device__ constexpr int cv_dump(int lc) { return cv_u(lc) + 16256; }
__host__ __device__ constexpr int cv_pb0(int lc, int w) { return lc * PG + w * 2048; }
__host__ __device__ constexpr int cv_se(int lc) { return 4 * PG + lc * 4096; }
__host__ __device__ constexpr int cv_so(int lc) { return cv_se(lc) + 2048; }
__host__ __device__ constexpr int cv_pf(int lc) { return 6 * PG + lc * 2048; }
__host__ __device__ constexpr int cv_x(int half, int lc) { return (P_R + half) * PG + lc * 2048; }
__host__ __device__ constexpr int cv_chan(int cta, int lc) { return 2 * cta + (lc & 1) + 256 * (lc >> 1); }

enum {
  B_XF = 0,
  B_WF = 16,
  B_OF = 24,
  B_DN = 32,
  B_WOF = 48,
  B_RF = 52,
  B_HF = 54,
  B_OST = 56,
  B_PDONE = 58,
  B_GB = 60,
  B_TF = 62,
  B_CSF = 64,
  B_EP = 65,
  B_ZF = 66,
  B_KG = 67,
  B_FARM = 68,
  B_Z0 = 69,
  B_PE = 70,
  B_U = 71,
  B_S = 73,
  B_PUB = 74,
  B_R = 77,
  B_END = 80,
  B_COUNT = 81
};

enum {
  C_CS = 0,
  C_G = 1,
  C_C = 5,
  C_F = 8,
  C_O = 20,
  C_COUNT = 84
};

__device__ unsigned g_cnt[C_COUNT * 32];
__device__ __align__(1024) bf16 g_O[LSEQ * DM];
__device__ __align__(1024) bf16 g_xT[4 * DM * LSEQ];
__device__ __align__(1024) float g_stats[2 * LSEQ * 2];
__device__ __align__(1024) uint2 g_colsum[3 * DM];
__device__ __align__(1024) uint4 g_halo[2 * 32 * 8 * 384];
__device__ __align__(1024) uint4 g_part[2 * 32 * 8 * 64];
#define TS(i) do { } while (0)
#define TSW(k) do { if ((threadIdx.x & 127) == 0) TS(16 + layer * 56 + (threadIdx.x >> 7) * 20 + (k)); } while (0)

#define LTS(i) do { } while (0)

struct Params {
  CUtensorMap mapX, mapW3, mapO, mapO2, mapXT, mapOut, mapWo;
  const bf16 *wqkv, *a_re, *a_im, *b_re, *b_im, *c_re, *c_im, *log_dt, *dskip;
};

__device__ __forceinline__ uint32_t s32(const void* p) { return (uint32_t)__cvta_generic_to_shared(p); }
__device__ __forceinline__ void mbar_init(uint32_t b, int c) { asm volatile("mbarrier.init.shared::cta.b64 [%0], %1;" ::"r"(b), "r"(c) : "memory"); }
__device__ __forceinline__ void mbar_expect(uint32_t b, int bytes) { asm volatile("mbarrier.arrive.expect_tx.shared::cta.b64 _, [%0], %1;" ::"r"(b), "r"(bytes) : "memory"); }
__device__ __forceinline__ void mbar_arrive(uint32_t b) { asm volatile("mbarrier.arrive.shared::cta.b64 _, [%0];" ::"r"(b) : "memory"); }
__device__ __forceinline__ void mbar_wait(uint32_t b, int parity) {
  asm volatile("{\n.reg .pred p;\nWAIT_LOOP:\nmbarrier.try_wait.parity.shared::cta.b64 p, [%0], %1;\n@p bra WAIT_DONE;\nbra WAIT_LOOP;\nWAIT_DONE:\n}" ::"r"(b), "r"(parity) : "memory");
}
__device__ __forceinline__ int opaque_tid() { int v; asm volatile("mov.u32 %0, %%tid.x;" : "=r"(v)); return v; }
__device__ __forceinline__ bool elect_one() {
  uint32_t r;
  asm volatile("{\n.reg .pred p;\nelect.sync _|p, 0xffffffff;\nselp.u32 %0, 1, 0, p;\n}" : "=r"(r));
  return r != 0;
}
__device__ __forceinline__ void tma_ld(uint32_t dst, const CUtensorMap* m, int c0, int c1, uint32_t bar) {
  asm volatile("cp.async.bulk.tensor.2d.shared::cluster.global.mbarrier::complete_tx::bytes [%0], [%1, {%3, %4}], [%2];"
               ::"r"(dst), "l"(m), "r"(bar), "r"(c0), "r"(c1) : "memory");
}
__device__ __forceinline__ void tma_ld3(uint32_t dst, const CUtensorMap* m, int c0, int c1, int c2, uint32_t bar) {
  asm volatile("cp.async.bulk.tensor.3d.shared::cluster.global.mbarrier::complete_tx::bytes [%0], [%1, {%3, %4, %5}], [%2];"
               ::"r"(dst), "l"(m), "r"(bar), "r"(c0), "r"(c1), "r"(c2) : "memory");
}
__device__ __forceinline__ void tma_prefetch2(const CUtensorMap* m, int c0, int c1) {
  asm volatile("cp.async.bulk.prefetch.tensor.2d.L2.global.tile [%0, {%1, %2}];" ::"l"(m), "r"(c0), "r"(c1) : "memory");
}
__device__ __forceinline__ void tma_prefetch3(const CUtensorMap* m, int c0, int c1, int c2) {
  asm volatile("cp.async.bulk.prefetch.tensor.3d.L2.global.tile [%0, {%1, %2, %3}];" ::"l"(m), "r"(c0), "r"(c1), "r"(c2) : "memory");
}
__device__ __forceinline__ void tma_st(const CUtensorMap* m, int c0, int c1, uint32_t src) {
  asm volatile("cp.async.bulk.tensor.2d.global.shared::cta.bulk_group [%0, {%2, %3}], [%1];" ::"l"(m), "r"(src), "r"(c0), "r"(c1) : "memory");
}
__device__ __forceinline__ void bulk_ld(uint32_t dst, const void* src, int bytes, uint32_t bar) {
  asm volatile("cp.async.bulk.shared::cluster.global.mbarrier::complete_tx::bytes [%0], [%1], %2, [%3];" ::"r"(dst), "l"(src), "r"(bytes), "r"(bar) : "memory");
}
__device__ __forceinline__ void bulk_st(void* dst, uint32_t src, int bytes) {
  asm volatile("cp.async.bulk.global.shared::cta.bulk_group [%0], [%1], %2;" ::"l"(dst), "r"(src), "r"(bytes) : "memory");
}
__device__ __forceinline__ void bulk_red_add_f32(void* dst, uint32_t src, int bytes) {
  asm volatile("cp.reduce.async.bulk.global.shared::cta.bulk_group.add.f32 [%0], [%1], %2;" ::"l"(dst), "r"(src), "r"(bytes) : "memory");
}
__device__ __forceinline__ void bulk_commit() { asm volatile("cp.async.bulk.commit_group;" ::: "memory"); }
__device__ __forceinline__ void bulk_wait_all() { asm volatile("cp.async.bulk.wait_group 0;" ::: "memory"); }
__device__ __forceinline__ void fence_async_smem() { asm volatile("fence.proxy.async.shared::cta;" ::: "memory"); }
__device__ __forceinline__ void fence_async_global() { asm volatile("fence.proxy.async.global;" ::: "memory"); }
__device__ __forceinline__ void bar_sync(int id, int n) { asm volatile("bar.sync %0, %1;" ::"r"(id), "r"(n) : "memory"); }
__device__ __forceinline__ void bar_arrive(int id, int n) { asm volatile("bar.arrive %0, %1;" ::"r"(id), "r"(n) : "memory"); }
__device__ __forceinline__ void wg_fence() { asm volatile("wgmma.fence.sync.aligned;" ::: "memory"); }
__device__ __forceinline__ void wg_commit() { asm volatile("wgmma.commit_group.sync.aligned;" ::: "memory"); }
template <int N> __device__ __forceinline__ void wg_wait() { asm volatile("wgmma.wait_group.sync.aligned %0;" ::"n"(N) : "memory"); }
__device__ __forceinline__ uint64_t mkdesc(uint32_t addr, uint32_t lbo, uint32_t sbo, int sw) {
  return (uint64_t)((addr & 0x3FFFF) >> 4) | ((uint64_t)(lbo >> 4) << 16) | ((uint64_t)(sbo >> 4) << 32) | ((uint64_t)sw << 62);
}
__device__ __forceinline__ void ldsm4(uint32_t* r, uint32_t a) {
  asm volatile("ldmatrix.sync.aligned.m8n8.x4.shared.b16 {%0,%1,%2,%3}, [%4];" : "=r"(r[0]), "=r"(r[1]), "=r"(r[2]), "=r"(r[3]) : "r"(a) : "memory");
}
__device__ __forceinline__ void ldsm4t(uint32_t* r, uint32_t a) {
  asm volatile("ldmatrix.sync.aligned.m8n8.x4.trans.shared.b16 {%0,%1,%2,%3}, [%4];" : "=r"(r[0]), "=r"(r[1]), "=r"(r[2]), "=r"(r[3]) : "r"(a) : "memory");
}
__device__ __forceinline__ void stsm4(uint32_t a, uint32_t r0, uint32_t r1, uint32_t r2, uint32_t r3) {
  asm volatile("stmatrix.sync.aligned.m8n8.x4.shared.b16 [%0], {%1,%2,%3,%4};" ::"r"(a), "r"(r0), "r"(r1), "r"(r2), "r"(r3) : "memory");
}
__device__ __forceinline__ void stsm4t(uint32_t a, uint32_t r0, uint32_t r1, uint32_t r2, uint32_t r3) {
  asm volatile("stmatrix.sync.aligned.m8n8.x4.trans.shared.b16 [%0], {%1,%2,%3,%4};" ::"r"(a), "r"(r0), "r"(r1), "r"(r2), "r"(r3) : "memory");
}
__device__ __forceinline__ uint32_t movm_t(uint32_t a) { uint32_t r; asm volatile("movmatrix.sync.aligned.m8n8.trans.b16 %0, %1;" : "=r"(r) : "r"(a)); return r; }
__device__ __forceinline__ uint32_t lds32(uint32_t a) { uint32_t v; asm volatile("ld.shared.b32 %0, [%1];" : "=r"(v) : "r"(a) : "memory"); return v; }
__device__ __forceinline__ float2 lds64f(uint32_t a) { float2 v; asm volatile("ld.shared.v2.f32 {%0,%1}, [%2];" : "=f"(v.x), "=f"(v.y) : "r"(a) : "memory"); return v; }
__device__ __forceinline__ float4 lds128f(uint32_t a) { float4 v; asm volatile("ld.shared.v4.f32 {%0,%1,%2,%3}, [%4];" : "=f"(v.x), "=f"(v.y), "=f"(v.z), "=f"(v.w) : "r"(a) : "memory"); return v; }
__device__ __forceinline__ uint4 lds128(uint32_t a) { uint4 v; asm volatile("ld.shared.v4.b32 {%0,%1,%2,%3}, [%4];" : "=r"(v.x), "=r"(v.y), "=r"(v.z), "=r"(v.w) : "r"(a) : "memory"); return v; }
__device__ __forceinline__ void sts128(uint32_t a, uint4 v) { asm volatile("st.shared.v4.b32 [%0], {%1,%2,%3,%4};" ::"r"(a), "r"(v.x), "r"(v.y), "r"(v.z), "r"(v.w) : "memory"); }
__device__ __forceinline__ void sts128f(uint32_t a, float x, float y, float z, float w) { asm volatile("st.shared.v4.f32 [%0], {%1,%2,%3,%4};" ::"r"(a), "f"(x), "f"(y), "f"(z), "f"(w) : "memory"); }
__device__ __forceinline__ void sts32f(uint32_t a, float v) { asm volatile("st.shared.f32 [%0], %1;" ::"r"(a), "f"(v) : "memory"); }
__device__ __forceinline__ void sts16(uint32_t a, uint16_t v) { asm volatile("st.shared.u16 [%0], %1;" ::"r"(a), "h"(v) : "memory"); }
__device__ __forceinline__ uint32_t lds16(uint32_t a) { uint16_t v; asm volatile("ld.shared.u16 %0, [%1];" : "=h"(v) : "r"(a) : "memory"); return v; }
__device__ __forceinline__ uint32_t packbf(float lo, float hi) { uint32_t r; asm("cvt.rn.bf16x2.f32 %0, %1, %2;" : "=r"(r) : "f"(hi), "f"(lo)); return r; }
__device__ __forceinline__ float bf_lo(uint32_t v) { return __uint_as_float(v << 16); }
__device__ __forceinline__ float bf_hi(uint32_t v) { return __uint_as_float(v & 0xffff0000u); }
__device__ __forceinline__ float ex2(float x) { float r; asm("ex2.approx.ftz.f32 %0, %1;" : "=f"(r) : "f"(x)); return r; }
__device__ __forceinline__ float rsqrt_approx(float x) { float r; asm("rsqrt.approx.ftz.f32 %0, %1;" : "=f"(r) : "f"(x)); return r; }
__device__ __forceinline__ float rcp_approx(float x) { float r; asm("rcp.approx.ftz.f32 %0, %1;" : "=f"(r) : "f"(x)); return r; }
__device__ __forceinline__ void mma_bf16(float* d, const uint32_t* a, uint32_t b0, uint32_t b1) {
  asm("mma.sync.aligned.m16n8k16.row.col.f32.bf16.bf16.f32 {%0,%1,%2,%3}, {%4,%5,%6,%7}, {%8,%9}, {%0,%1,%2,%3};"
               : "+f"(d[0]), "+f"(d[1]), "+f"(d[2]), "+f"(d[3]) : "r"(a[0]), "r"(a[1]), "r"(a[2]), "r"(a[3]), "r"(b0), "r"(b1));
}
__device__ __forceinline__ void mma_tf32(float* d, float a0, float a1, float a2, float a3, float b0, float b1) {
  asm("mma.sync.aligned.m16n8k8.row.col.f32.tf32.tf32.f32 {%0,%1,%2,%3}, {%4,%5,%6,%7}, {%8,%9}, {%0,%1,%2,%3};"
               : "+f"(d[0]), "+f"(d[1]), "+f"(d[2]), "+f"(d[3])
               : "r"(__float_as_uint(a0)), "r"(__float_as_uint(a1)), "r"(__float_as_uint(a2)), "r"(__float_as_uint(a3)),
                 "r"(__float_as_uint(b0)), "r"(__float_as_uint(b1)));
}
__device__ __forceinline__ void red_release(unsigned* p) { asm volatile("red.release.gpu.global.add.u32 [%0], 1;" ::"l"(p) : "memory"); }
__device__ __forceinline__ void red_relaxed(unsigned* p) { asm volatile("red.relaxed.gpu.global.add.u32 [%0], 1;" ::"l"(p) : "memory"); }
__device__ __forceinline__ unsigned ld_relaxed(const unsigned* p) { unsigned v; asm volatile("ld.relaxed.gpu.global.u32 %0, [%1];" : "=r"(v) : "l"(p) : "memory"); return v; }
__device__ __forceinline__ void spin_until(const unsigned* p, unsigned target) {
  int it = 0;
  while ((int)(ld_relaxed(p) - target) < 0) {
    if (++it > (1 << 23)) __trap();
  }
}
__device__ __forceinline__ uint4 ldcg128(const void* p) { uint4 v; asm volatile("ld.global.cg.v4.b32 {%0,%1,%2,%3}, [%4];" : "=r"(v.x), "=r"(v.y), "=r"(v.z), "=r"(v.w) : "l"(p) : "memory"); return v; }
__device__ __forceinline__ uint4 ld_tagged(const uint4* p) { uint4 v; asm volatile("ld.relaxed.gpu.global.v4.u32 {%0,%1,%2,%3}, [%4];" : "=r"(v.x), "=r"(v.y), "=r"(v.z), "=r"(v.w) : "l"(p) : "memory"); return v; }
__device__ __forceinline__ void st_tagged(uint4* p, uint32_t a, uint32_t b, uint32_t tag) { asm volatile("st.relaxed.gpu.global.v4.u32 [%0], {%1,%2,%3,%2};" ::"l"(p), "r"(a), "r"(tag), "r"(b) : "memory"); }
__device__ __forceinline__ void st_tagged3(uint4* p, uint32_t a, uint32_t b, uint32_t c, uint32_t tag) { asm volatile("st.relaxed.gpu.global.v4.u32 [%0], {%1,%2,%3,%4};" ::"l"(p), "r"(a), "r"(b), "r"(c), "r"(tag) : "memory"); }
__device__ __forceinline__ uint4 poll_tagged(const uint4* p, uint32_t tag) {
  uint4 v = ld_tagged(p);
  int it = 0;
  while (v.y != tag || v.w != tag) {
    if (++it > (1 << 22)) __trap();
    v = ld_tagged(p);
  }
  return v;
}
__device__ __forceinline__ uint32_t hadd2(uint32_t a, uint32_t b) { uint32_t r; asm("add.rn.bf16x2 %0, %1, %2;" : "=r"(r) : "r"(a), "r"(b)); return r; }
__device__ __forceinline__ uint32_t hmul2(uint32_t a, uint32_t b) { uint32_t r; asm("mul.rn.bf16x2 %0, %1, %2;" : "=r"(r) : "r"(a), "r"(b)); return r; }

__device__ __forceinline__ uint32_t hfma2(uint32_t a, uint32_t b, uint32_t c) { uint32_t r; asm("fma.rn.bf16x2 %0, %1, %2, %3;" : "=r"(r) : "r"(a), "r"(b), "r"(c)); return r; }
__device__ __forceinline__ void sts32(uint32_t a, uint32_t v) { asm volatile("st.shared.u32 [%0], %1;" ::"r"(a), "r"(v) : "memory"); }

template <int N> __device__ __forceinline__ void acc_fence(float* a) {
#pragma unroll
  for (int i = 0; i < N; i++) asm volatile("" : "+f"(a[i]) :: "memory");
}

template<int N,int TB> __device__ __forceinline__ void wgmma_rs(float* d, const uint32_t* a, uint64_t db, int sd);
template<int N,int TA,int TB> __device__ __forceinline__ void wgmma_ss(float* d, uint64_t da, uint64_t db, int sd);
template<> __device__ __forceinline__ void wgmma_rs<64,0>(float* d, const uint32_t* a, uint64_t db, int sd) {
  asm volatile("{\n.reg .pred p;\nsetp.ne.b32 p, %37, 0;\nwgmma.mma_async.sync.aligned.m64n64k16.f32.bf16.bf16 {%0,%1,%2,%3,%4,%5,%6,%7,%8,%9,%10,%11,%12,%13,%14,%15,%16,%17,%18,%19,%20,%21,%22,%23,%24,%25,%26,%27,%28,%29,%30,%31}, {%32,%33,%34,%35}, %36, p, 1, 1, 0;\n}\n"
   : "+f"(d[0]),"+f"(d[1]),"+f"(d[2]),"+f"(d[3]),"+f"(d[4]),"+f"(d[5]),"+f"(d[6]),"+f"(d[7]),"+f"(d[8]),"+f"(d[9]),"+f"(d[10]),"+f"(d[11]),"+f"(d[12]),"+f"(d[13]),"+f"(d[14]),"+f"(d[15]),"+f"(d[16]),"+f"(d[17]),"+f"(d[18]),"+f"(d[19]),"+f"(d[20]),"+f"(d[21]),"+f"(d[22]),"+f"(d[23]),"+f"(d[24]),"+f"(d[25]),"+f"(d[26]),"+f"(d[27]),"+f"(d[28]),"+f"(d[29]),"+f"(d[30]),"+f"(d[31])
   : "r"(a[0]), "r"(a[1]), "r"(a[2]), "r"(a[3]), "l"(db), "r"(sd));
}
template<> __device__ __forceinline__ void wgmma_rs<56,0>(float* d, const uint32_t* a, uint64_t db, int sd) {
  asm volatile("{\n.reg .pred p;\nsetp.ne.b32 p, %33, 0;\nwgmma.mma_async.sync.aligned.m64n56k16.f32.bf16.bf16 {%0,%1,%2,%3,%4,%5,%6,%7,%8,%9,%10,%11,%12,%13,%14,%15,%16,%17,%18,%19,%20,%21,%22,%23,%24,%25,%26,%27}, {%28,%29,%30,%31}, %32, p, 1, 1, 0;\n}\n"
   : "+f"(d[0]),"+f"(d[1]),"+f"(d[2]),"+f"(d[3]),"+f"(d[4]),"+f"(d[5]),"+f"(d[6]),"+f"(d[7]),"+f"(d[8]),"+f"(d[9]),"+f"(d[10]),"+f"(d[11]),"+f"(d[12]),"+f"(d[13]),"+f"(d[14]),"+f"(d[15]),"+f"(d[16]),"+f"(d[17]),"+f"(d[18]),"+f"(d[19]),"+f"(d[20]),"+f"(d[21]),"+f"(d[22]),"+f"(d[23]),"+f"(d[24]),"+f"(d[25]),"+f"(d[26]),"+f"(d[27])
   : "r"(a[0]), "r"(a[1]), "r"(a[2]), "r"(a[3]), "l"(db), "r"(sd));
}
template<> __device__ __forceinline__ void wgmma_rs<48,0>(float* d, const uint32_t* a, uint64_t db, int sd) {
  asm volatile("{\n.reg .pred p;\nsetp.ne.b32 p, %29, 0;\nwgmma.mma_async.sync.aligned.m64n48k16.f32.bf16.bf16 {%0,%1,%2,%3,%4,%5,%6,%7,%8,%9,%10,%11,%12,%13,%14,%15,%16,%17,%18,%19,%20,%21,%22,%23}, {%24,%25,%26,%27}, %28, p, 1, 1, 0;\n}\n"
   : "+f"(d[0]),"+f"(d[1]),"+f"(d[2]),"+f"(d[3]),"+f"(d[4]),"+f"(d[5]),"+f"(d[6]),"+f"(d[7]),"+f"(d[8]),"+f"(d[9]),"+f"(d[10]),"+f"(d[11]),"+f"(d[12]),"+f"(d[13]),"+f"(d[14]),"+f"(d[15]),"+f"(d[16]),"+f"(d[17]),"+f"(d[18]),"+f"(d[19]),"+f"(d[20]),"+f"(d[21]),"+f"(d[22]),"+f"(d[23])
   : "r"(a[0]), "r"(a[1]), "r"(a[2]), "r"(a[3]), "l"(db), "r"(sd));
}
template<> __device__ __forceinline__ void wgmma_rs<40,0>(float* d, const uint32_t* a, uint64_t db, int sd) {
  asm volatile("{\n.reg .pred p;\nsetp.ne.b32 p, %25, 0;\nwgmma.mma_async.sync.aligned.m64n40k16.f32.bf16.bf16 {%0,%1,%2,%3,%4,%5,%6,%7,%8,%9,%10,%11,%12,%13,%14,%15,%16,%17,%18,%19}, {%20,%21,%22,%23}, %24, p, 1, 1, 0;\n}\n"
   : "+f"(d[0]),"+f"(d[1]),"+f"(d[2]),"+f"(d[3]),"+f"(d[4]),"+f"(d[5]),"+f"(d[6]),"+f"(d[7]),"+f"(d[8]),"+f"(d[9]),"+f"(d[10]),"+f"(d[11]),"+f"(d[12]),"+f"(d[13]),"+f"(d[14]),"+f"(d[15]),"+f"(d[16]),"+f"(d[17]),"+f"(d[18]),"+f"(d[19])
   : "r"(a[0]), "r"(a[1]), "r"(a[2]), "r"(a[3]), "l"(db), "r"(sd));
}
template<> __device__ __forceinline__ void wgmma_rs<32,0>(float* d, const uint32_t* a, uint64_t db, int sd) {
  asm volatile("{\n.reg .pred p;\nsetp.ne.b32 p, %21, 0;\nwgmma.mma_async.sync.aligned.m64n32k16.f32.bf16.bf16 {%0,%1,%2,%3,%4,%5,%6,%7,%8,%9,%10,%11,%12,%13,%14,%15}, {%16,%17,%18,%19}, %20, p, 1, 1, 0;\n}\n"
   : "+f"(d[0]),"+f"(d[1]),"+f"(d[2]),"+f"(d[3]),"+f"(d[4]),"+f"(d[5]),"+f"(d[6]),"+f"(d[7]),"+f"(d[8]),"+f"(d[9]),"+f"(d[10]),"+f"(d[11]),"+f"(d[12]),"+f"(d[13]),"+f"(d[14]),"+f"(d[15])
   : "r"(a[0]), "r"(a[1]), "r"(a[2]), "r"(a[3]), "l"(db), "r"(sd));
}
template<> __device__ __forceinline__ void wgmma_rs<24,0>(float* d, const uint32_t* a, uint64_t db, int sd) {
  asm volatile("{\n.reg .pred p;\nsetp.ne.b32 p, %17, 0;\nwgmma.mma_async.sync.aligned.m64n24k16.f32.bf16.bf16 {%0,%1,%2,%3,%4,%5,%6,%7,%8,%9,%10,%11}, {%12,%13,%14,%15}, %16, p, 1, 1, 0;\n}\n"
   : "+f"(d[0]),"+f"(d[1]),"+f"(d[2]),"+f"(d[3]),"+f"(d[4]),"+f"(d[5]),"+f"(d[6]),"+f"(d[7]),"+f"(d[8]),"+f"(d[9]),"+f"(d[10]),"+f"(d[11])
   : "r"(a[0]), "r"(a[1]), "r"(a[2]), "r"(a[3]), "l"(db), "r"(sd));
}
template<> __device__ __forceinline__ void wgmma_rs<16,0>(float* d, const uint32_t* a, uint64_t db, int sd) {
  asm volatile("{\n.reg .pred p;\nsetp.ne.b32 p, %13, 0;\nwgmma.mma_async.sync.aligned.m64n16k16.f32.bf16.bf16 {%0,%1,%2,%3,%4,%5,%6,%7}, {%8,%9,%10,%11}, %12, p, 1, 1, 0;\n}\n"
   : "+f"(d[0]),"+f"(d[1]),"+f"(d[2]),"+f"(d[3]),"+f"(d[4]),"+f"(d[5]),"+f"(d[6]),"+f"(d[7])
   : "r"(a[0]), "r"(a[1]), "r"(a[2]), "r"(a[3]), "l"(db), "r"(sd));
}
template<> __device__ __forceinline__ void wgmma_rs<8,0>(float* d, const uint32_t* a, uint64_t db, int sd) {
  asm volatile("{\n.reg .pred p;\nsetp.ne.b32 p, %9, 0;\nwgmma.mma_async.sync.aligned.m64n8k16.f32.bf16.bf16 {%0,%1,%2,%3}, {%4,%5,%6,%7}, %8, p, 1, 1, 0;\n}\n"
   : "+f"(d[0]),"+f"(d[1]),"+f"(d[2]),"+f"(d[3])
   : "r"(a[0]), "r"(a[1]), "r"(a[2]), "r"(a[3]), "l"(db), "r"(sd));
}
template<> __device__ __forceinline__ void wgmma_rs<16,1>(float* d, const uint32_t* a, uint64_t db, int sd) {
  asm volatile("{\n.reg .pred p;\nsetp.ne.b32 p, %13, 0;\nwgmma.mma_async.sync.aligned.m64n16k16.f32.bf16.bf16 {%0,%1,%2,%3,%4,%5,%6,%7}, {%8,%9,%10,%11}, %12, p, 1, 1, 1;\n}\n"
   : "+f"(d[0]),"+f"(d[1]),"+f"(d[2]),"+f"(d[3]),"+f"(d[4]),"+f"(d[5]),"+f"(d[6]),"+f"(d[7])
   : "r"(a[0]), "r"(a[1]), "r"(a[2]), "r"(a[3]), "l"(db), "r"(sd));
}
template<> __device__ __forceinline__ void wgmma_ss<64,0,1>(float* d, uint64_t da, uint64_t db, int sd) {
  asm volatile("{\n.reg .pred p;\nsetp.ne.b32 p, %34, 0;\nwgmma.mma_async.sync.aligned.m64n64k16.f32.bf16.bf16 {%0,%1,%2,%3,%4,%5,%6,%7,%8,%9,%10,%11,%12,%13,%14,%15,%16,%17,%18,%19,%20,%21,%22,%23,%24,%25,%26,%27,%28,%29,%30,%31}, %32, %33, p, 1, 1, 0, 1;\n}\n"
   : "+f"(d[0]),"+f"(d[1]),"+f"(d[2]),"+f"(d[3]),"+f"(d[4]),"+f"(d[5]),"+f"(d[6]),"+f"(d[7]),"+f"(d[8]),"+f"(d[9]),"+f"(d[10]),"+f"(d[11]),"+f"(d[12]),"+f"(d[13]),"+f"(d[14]),"+f"(d[15]),"+f"(d[16]),"+f"(d[17]),"+f"(d[18]),"+f"(d[19]),"+f"(d[20]),"+f"(d[21]),"+f"(d[22]),"+f"(d[23]),"+f"(d[24]),"+f"(d[25]),"+f"(d[26]),"+f"(d[27]),"+f"(d[28]),"+f"(d[29]),"+f"(d[30]),"+f"(d[31])
   : "l"(da), "l"(db), "r"(sd));
}
template<> __device__ __forceinline__ void wgmma_ss<192,0,1>(float* d, uint64_t da, uint64_t db, int sd) {
  asm volatile("{\n.reg .pred p;\nsetp.ne.b32 p, %98, 0;\nwgmma.mma_async.sync.aligned.m64n192k16.f32.bf16.bf16 {%0,%1,%2,%3,%4,%5,%6,%7,%8,%9,%10,%11,%12,%13,%14,%15,%16,%17,%18,%19,%20,%21,%22,%23,%24,%25,%26,%27,%28,%29,%30,%31,%32,%33,%34,%35,%36,%37,%38,%39,%40,%41,%42,%43,%44,%45,%46,%47,%48,%49,%50,%51,%52,%53,%54,%55,%56,%57,%58,%59,%60,%61,%62,%63,%64,%65,%66,%67,%68,%69,%70,%71,%72,%73,%74,%75,%76,%77,%78,%79,%80,%81,%82,%83,%84,%85,%86,%87,%88,%89,%90,%91,%92,%93,%94,%95}, %96, %97, p, 1, 1, 0, 1;\n}\n"
   : "+f"(d[0]),"+f"(d[1]),"+f"(d[2]),"+f"(d[3]),"+f"(d[4]),"+f"(d[5]),"+f"(d[6]),"+f"(d[7]),"+f"(d[8]),"+f"(d[9]),"+f"(d[10]),"+f"(d[11]),"+f"(d[12]),"+f"(d[13]),"+f"(d[14]),"+f"(d[15]),"+f"(d[16]),"+f"(d[17]),"+f"(d[18]),"+f"(d[19]),"+f"(d[20]),"+f"(d[21]),"+f"(d[22]),"+f"(d[23]),"+f"(d[24]),"+f"(d[25]),"+f"(d[26]),"+f"(d[27]),"+f"(d[28]),"+f"(d[29]),"+f"(d[30]),"+f"(d[31]),"+f"(d[32]),"+f"(d[33]),"+f"(d[34]),"+f"(d[35]),"+f"(d[36]),"+f"(d[37]),"+f"(d[38]),"+f"(d[39]),"+f"(d[40]),"+f"(d[41]),"+f"(d[42]),"+f"(d[43]),"+f"(d[44]),"+f"(d[45]),"+f"(d[46]),"+f"(d[47]),"+f"(d[48]),"+f"(d[49]),"+f"(d[50]),"+f"(d[51]),"+f"(d[52]),"+f"(d[53]),"+f"(d[54]),"+f"(d[55]),"+f"(d[56]),"+f"(d[57]),"+f"(d[58]),"+f"(d[59]),"+f"(d[60]),"+f"(d[61]),"+f"(d[62]),"+f"(d[63]),"+f"(d[64]),"+f"(d[65]),"+f"(d[66]),"+f"(d[67]),"+f"(d[68]),"+f"(d[69]),"+f"(d[70]),"+f"(d[71]),"+f"(d[72]),"+f"(d[73]),"+f"(d[74]),"+f"(d[75]),"+f"(d[76]),"+f"(d[77]),"+f"(d[78]),"+f"(d[79]),"+f"(d[80]),"+f"(d[81]),"+f"(d[82]),"+f"(d[83]),"+f"(d[84]),"+f"(d[85]),"+f"(d[86]),"+f"(d[87]),"+f"(d[88]),"+f"(d[89]),"+f"(d[90]),"+f"(d[91]),"+f"(d[92]),"+f"(d[93]),"+f"(d[94]),"+f"(d[95])
   : "l"(da), "l"(db), "r"(sd));
}
template<> __device__ __forceinline__ void wgmma_ss<192,1,1>(float* d, uint64_t da, uint64_t db, int sd) {
  asm volatile("{\n.reg .pred p;\nsetp.ne.b32 p, %98, 0;\nwgmma.mma_async.sync.aligned.m64n192k16.f32.bf16.bf16 {%0,%1,%2,%3,%4,%5,%6,%7,%8,%9,%10,%11,%12,%13,%14,%15,%16,%17,%18,%19,%20,%21,%22,%23,%24,%25,%26,%27,%28,%29,%30,%31,%32,%33,%34,%35,%36,%37,%38,%39,%40,%41,%42,%43,%44,%45,%46,%47,%48,%49,%50,%51,%52,%53,%54,%55,%56,%57,%58,%59,%60,%61,%62,%63,%64,%65,%66,%67,%68,%69,%70,%71,%72,%73,%74,%75,%76,%77,%78,%79,%80,%81,%82,%83,%84,%85,%86,%87,%88,%89,%90,%91,%92,%93,%94,%95}, %96, %97, p, 1, 1, 1, 1;\n}\n"
   : "+f"(d[0]),"+f"(d[1]),"+f"(d[2]),"+f"(d[3]),"+f"(d[4]),"+f"(d[5]),"+f"(d[6]),"+f"(d[7]),"+f"(d[8]),"+f"(d[9]),"+f"(d[10]),"+f"(d[11]),"+f"(d[12]),"+f"(d[13]),"+f"(d[14]),"+f"(d[15]),"+f"(d[16]),"+f"(d[17]),"+f"(d[18]),"+f"(d[19]),"+f"(d[20]),"+f"(d[21]),"+f"(d[22]),"+f"(d[23]),"+f"(d[24]),"+f"(d[25]),"+f"(d[26]),"+f"(d[27]),"+f"(d[28]),"+f"(d[29]),"+f"(d[30]),"+f"(d[31]),"+f"(d[32]),"+f"(d[33]),"+f"(d[34]),"+f"(d[35]),"+f"(d[36]),"+f"(d[37]),"+f"(d[38]),"+f"(d[39]),"+f"(d[40]),"+f"(d[41]),"+f"(d[42]),"+f"(d[43]),"+f"(d[44]),"+f"(d[45]),"+f"(d[46]),"+f"(d[47]),"+f"(d[48]),"+f"(d[49]),"+f"(d[50]),"+f"(d[51]),"+f"(d[52]),"+f"(d[53]),"+f"(d[54]),"+f"(d[55]),"+f"(d[56]),"+f"(d[57]),"+f"(d[58]),"+f"(d[59]),"+f"(d[60]),"+f"(d[61]),"+f"(d[62]),"+f"(d[63]),"+f"(d[64]),"+f"(d[65]),"+f"(d[66]),"+f"(d[67]),"+f"(d[68]),"+f"(d[69]),"+f"(d[70]),"+f"(d[71]),"+f"(d[72]),"+f"(d[73]),"+f"(d[74]),"+f"(d[75]),"+f"(d[76]),"+f"(d[77]),"+f"(d[78]),"+f"(d[79]),"+f"(d[80]),"+f"(d[81]),"+f"(d[82]),"+f"(d[83]),"+f"(d[84]),"+f"(d[85]),"+f"(d[86]),"+f"(d[87]),"+f"(d[88]),"+f"(d[89]),"+f"(d[90]),"+f"(d[91]),"+f"(d[92]),"+f"(d[93]),"+f"(d[94]),"+f"(d[95])
   : "l"(da), "l"(db), "r"(sd));
}

__host__ __device__ constexpr uint64_t w_pages(int layer) { return layer ? 0x0816131000161310ull : 0x0816001310161310ull; }
template <bool TR>
__device__ __forceinline__ void gemm_section(float* acc, float& mean0, float& mean1, float& rstd0, float& rstd1,
                                             uint32_t sb, int blk, int hg, int wg, int w, int lane) {
  constexpr int layer = TR ? 1 : 0;
  constexpr int TURN = TR ? TURN1 : TURN0;
  const uint32_t bar = sb + SM_BAR;
  const int g = lane >> 2, t = lane & 3;
  const bool leader = (w == 0) && (lane == 0);
  const int drain = wg ? TURN - 1 : (TR ? 2 : 8);
  const int statpos = hg < 3 ? 1 : (wg ? TURN - 1 : (TR ? 2 : 4));
  auto issue = [&](int c, int first) {
    mbar_wait(bar + 8 * (B_XF + 8 * wg + c), layer);
    mbar_wait(bar + 8 * (B_WF + c), layer);
    const uint64_t da = mkdesc(sb + (8 * wg + c) * PG, TR ? 8192 : 16, 1024, 1);
    const uint64_t db = mkdesc(sb + (uint32_t)((w_pages(layer) >> (8 * c)) & 31) * PG, 8192, 1024, 1);
    constexpr int GS = TR ? 4 : GS0;
#pragma unroll
    for (int ks = 0; ks < 4; ks++) {
      if (ks % GS == 0) { if (ks) wg_wait<1>(); wg_fence(); }
      wgmma_ss<192, TR ? 1 : 0, 1>(acc, da + (TR ? ks * 128 : ks * 2), db + ks * 128, !first || ks != 0);
      if (ks % GS == GS - 1) wg_commit();
    }
  };
  uint32_t tag = 0;
  issue(0, 1);
  TSW(0);
#pragma unroll 1
  for (int c = 1; c < 7; c++) {
    if (wg == 1 && c == TURN) bar_sync(5, 256);
    issue(c, 0);
    wg_wait<1>();
    if (leader && c != drain + 1) mbar_arrive(bar + 8 * (B_DN + 8 * wg + c - 1));
    if (c == drain) {
      wg_wait<0>();
      if (leader) mbar_arrive(bar + 8 * (B_DN + 8 * wg + c));
    }
    if (c == statpos) {
      mbar_wait(bar + 8 * B_EP, 0);
      tag = 2 * lds32(sb + SM_EP) + layer + 1;
      mbar_wait(bar + 8 * (B_XF + 8 * wg + hg), layer);
      uint32_t A[16];
      const uint32_t xb = sb + (8 * wg + hg) * PG;
#pragma unroll
      for (int ks = 0; ks < 4; ks++) {
        if (!TR) {
          const int row = 16 * w + (lane & 15), kc = 2 * ks + (lane >> 4);
          ldsm4(&A[4 * ks], xb + row * 128 + ((kc ^ (row & 7)) << 4));
        } else {
          const int k = 16 * ks + (lane & 7) + 8 * (lane >> 4), pc = 2 * w + ((lane >> 3) & 1);
          ldsm4t(&A[4 * ks], xb + k * 128 + ((pc ^ (k & 7)) << 4));
        }
      }
      float s0 = 0.f, q0 = 0.f, s1 = 0.f, q1 = 0.f;
#pragma unroll
      for (int i = 0; i < 16; i += 2) {
        const float a = bf_lo(A[i]), b = bf_hi(A[i]), c_ = bf_lo(A[i + 1]), d = bf_hi(A[i + 1]);
        s0 += a + b; q0 = fmaf(a, a, q0); q0 = fmaf(b, b, q0);
        s1 += c_ + d; q1 = fmaf(c_, c_, q1); q1 = fmaf(d, d, q1);
      }
#pragma unroll
      for (int o = 1; o <= 2; o <<= 1) {
        s0 += __shfl_xor_sync(~0u, s0, o); q0 += __shfl_xor_sync(~0u, q0, o);
        s1 += __shfl_xor_sync(~0u, s1, o); q1 += __shfl_xor_sync(~0u, q1, o);
      }
      if (t < 2)
        st_tagged(&g_part[((layer * 32 + blk) * 8 + hg) * 64 + 16 * w + g + 8 * t], __float_as_uint(t ? s1 : s0), __float_as_uint(t ? q1 : q0), tag);
    }
  }
  const uint4* psrc = &g_part[((layer * 32 + blk) * 8 + 2 * t) * 64 + 16 * w + g];
  uint4 a0 = ld_tagged(psrc), a1 = ld_tagged(psrc + 8), b0 = ld_tagged(psrc + 64), b1 = ld_tagged(psrc + 72);
  issue(7, 0);
  if (wg == 0) bar_arrive(5, 256);
  int it = 0;
  while (!__all_sync(~0u, a0.y == tag && a0.w == tag && a1.y == tag && a1.w == tag && b0.y == tag && b0.w == tag && b1.y == tag && b1.w == tag) &&
         ++it < (1 << 20)) {
    a0 = ld_tagged(psrc); a1 = ld_tagged(psrc + 8); b0 = ld_tagged(psrc + 64); b1 = ld_tagged(psrc + 72);
  }
  float s0 = __uint_as_float(a0.x) + __uint_as_float(b0.x), q0 = __uint_as_float(a0.z) + __uint_as_float(b0.z);
  float s1 = __uint_as_float(a1.x) + __uint_as_float(b1.x), q1 = __uint_as_float(a1.z) + __uint_as_float(b1.z);
#pragma unroll
  for (int o = 1; o <= 2; o <<= 1) {
    s0 += __shfl_xor_sync(~0u, s0, o); q0 += __shfl_xor_sync(~0u, q0, o);
    s1 += __shfl_xor_sync(~0u, s1, o); q1 += __shfl_xor_sync(~0u, q1, o);
  }
  mean0 = s0 * (1.f / DM); mean1 = s1 * (1.f / DM);
  rstd0 = rsqrt_approx(fmaxf(q0 * (1.f / DM) - mean0 * mean0, 0.f) + 1e-5f);
  rstd1 = rsqrt_approx(fmaxf(q1 * (1.f / DM) - mean1 * mean1, 0.f) + 1e-5f);
  mbar_wait(bar + 8 * B_CSF, 0);
  wg_wait<0>();
  acc_fence<96>(acc);
  if (leader) mbar_arrive(bar + 8 * (B_DN + 8 * wg + 7));
}

__device__ __forceinline__ void attn_phase(const Params& p, uint32_t sb, int layer, int rb, int hg, int wg, int w) {
  const int lane = opaque_tid() & 31;
  const int g = lane >> 2, t = lane & 3;
  const uint32_t bar = sb + SM_BAR;
  const int blk = 16 * wg + rb;
  float acc[96];
  float2 cs[24];
  float mean0, mean1, rstd0, rstd1;
  if (layer) gemm_section<true>(acc, mean0, mean1, rstd0, rstd1, sb, blk, hg, wg, w, lane);
  else gemm_section<false>(acc, mean0, mean1, rstd0, rstd1, sb, blk, hg, wg, w, lane);
  const uint32_t tag = 2 * lds32(sb + SM_EP) + layer + 1;
  TSW(1);
#pragma unroll
  for (int j = 8; j < 24; j++) cs[j] = lds64f(sb + SM_CS + 4 * (8 * j + 2 * t));
  const uint32_t kvx = sb + (wg ? 22 : 3) * PG;

  uint32_t kb[4][8], vb[4][8], qa[4][4];
  {
    const float nm0 = -mean0 * rstd0, nm1 = -mean1 * rstd1;
    const int st_row = 16 * w + (lane & 7) + 8 * ((lane >> 3) & 1);
    const uint32_t st_base = kvx + st_row * 256;
    const bool sender = (w == 3 && blk < 31);
    uint4* halo = &g_halo[((layer * 32 + blk) * 8 + hg) * 384 + lane];
    uint32_t r[4][2][4];
#pragma unroll
    for (int h = 0; h < 4; h++) {
#pragma unroll
      for (int kv = 0; kv < 2; kv++) {
#pragma unroll
        for (int dh = 0; dh < 2; dh++) {
          const int j = 8 + kv * 8 + 2 * h + dh;
          const float2 c2 = cs[j];
          const float v0 = fmaf(acc[4 * j + 0], rstd0, nm0 * c2.x), v1 = fmaf(acc[4 * j + 1], rstd0, nm0 * c2.y);
          const float v2 = fmaf(acc[4 * j + 2], rstd1, nm1 * c2.x), v3 = fmaf(acc[4 * j + 3], rstd1, nm1 * c2.y);
          r[h][kv][2 * dh] = packbf(v0, v1);
          r[h][kv][2 * dh + 1] = packbf(v2, v3);
        }
      }
      if (sender) {
        st_tagged3(halo + (3 * h) * 32, r[h][0][0], r[h][0][1], r[h][0][2], tag);
        st_tagged3(halo + (3 * h + 1) * 32, r[h][0][3], r[h][1][0], r[h][1][1], tag);
        st_tagged3(halo + (3 * h + 2) * 32, r[h][1][2], r[h][1][3], 0u, tag);
      }
    }
#pragma unroll
    for (int j = 0; j < 8; j++) cs[j] = lds64f(sb + SM_CS + 4 * (8 * j + 2 * t));
    mbar_wait(bar + 8 * (B_DN + 7), layer);
#pragma unroll
    for (int h = 0; h < 4; h++) {
#pragma unroll
      for (int kv = 0; kv < 2; kv++) {
        const int chunk = 4 * h + 2 * kv + (lane >> 4);
        stsm4(st_base + (((chunk & 8) | ((chunk ^ st_row) & 7)) << 4), r[h][kv][0], r[h][kv][1], r[h][kv][2], r[h][kv][3]);
      }
      kb[h][4] = r[h][0][0]; kb[h][5] = r[h][0][2]; kb[h][6] = r[h][0][1]; kb[h][7] = r[h][0][3];
      vb[h][4] = movm_t(r[h][1][0]); vb[h][5] = movm_t(r[h][1][1]); vb[h][6] = movm_t(r[h][1][2]); vb[h][7] = movm_t(r[h][1][3]);
    }
#pragma unroll
    for (int h = 0; h < 4; h++) {
#pragma unroll
      for (int dh = 0; dh < 2; dh++) {
        const int j = 2 * h + dh;
        const float2 c2 = cs[j];
        qa[h][2 * dh] = packbf(fmaf(-mean0, c2.x, acc[4 * j + 0]), fmaf(-mean0, c2.y, acc[4 * j + 1]));
        qa[h][2 * dh + 1] = packbf(fmaf(-mean1, c2.x, acc[4 * j + 2]), fmaf(-mean1, c2.y, acc[4 * j + 3]));
      }
    }
  }
  bar_sync(2 + wg, 128);
  TSW(2);
  {
    const uint32_t prev_base = kvx + (16 * w - 16) * 256;
    const int mi = lane >> 3;
    const int r = 8 * (mi >> 1) + (lane & 7), r2 = 8 * (mi & 1) + (lane & 7);
    if (w != 0) {
#pragma unroll
      for (int h = 0; h < 4; h++) {
        const int ch = 4 * h + (mi & 1), ch2 = 4 * h + 2 + (mi >> 1);
        ldsm4(&kb[h][0], prev_base + r * 256 + (((ch & 8) | ((ch ^ r) & 7)) << 4));
        ldsm4t(&vb[h][0], prev_base + r2 * 256 + (((ch2 & 8) | ((ch2 ^ r2) & 7)) << 4));
      }
    } else if (blk > 0) {
      const uint4* src = &g_halo[((layer * 32 + blk - 1) * 8 + hg) * 384 + lane];
      uint4 hv[12];
      int it = 0;
      bool ok;
      do {
        ok = true;
#pragma unroll
        for (int i = 0; i < 12; i++) hv[i] = ld_tagged(src + i * 32);
#pragma unroll
        for (int i = 0; i < 12; i++) ok = ok && hv[i].w == tag;
      } while (!__all_sync(~0u, ok) && ++it < (1 << 20));
#pragma unroll
      for (int h = 0; h < 4; h++) {
        kb[h][0] = hv[3 * h].x; kb[h][1] = hv[3 * h].z; kb[h][2] = hv[3 * h].y; kb[h][3] = hv[3 * h + 1].x;
        vb[h][0] = movm_t(hv[3 * h + 1].y); vb[h][1] = movm_t(hv[3 * h + 1].z);
        vb[h][2] = movm_t(hv[3 * h + 2].x); vb[h][3] = movm_t(hv[3 * h + 2].y);
      }
    } else {
#pragma unroll
      for (int h = 0; h < 4; h++)
#pragma unroll
        for (int k = 0; k < 4; k++) kb[h][k] = vb[h][k] = 0u;
    }
    if (w == 0 && lane == 0) mbar_arrive(bar + 8 * (B_HF + wg));
    TSW(3);
  }
  mbar_wait(bar + 8 * (B_DN + 15), layer);
  TSW(4);

  const bool first = (blk == 0 && w == 0);
  const int e = t - (g >> 1);
  const bool par = g & 1, epos = e >= 1;
  const uint32_t pmask = par ? 0xffff0000u : 0x0000ffffu;
  const uint32_t mB0 = epos ? pmask : 0u, mB1 = epos ? 0u : pmask;
  const float cl2 = 0.25f * 1.4426950408889634f;
  const float sc0 = rstd0 * cl2, sc1 = rstd1 * cl2;
  const float NEG = -INFINITY;
  float vA0[4], vB0[4], vA1[4], vB1[4];
#pragma unroll
  for (int h = 0; h < 4; h++) {
    float S[4][4];
#pragma unroll
    for (int j = 0; j < 4; j++) {
      S[j][0] = S[j][1] = S[j][2] = S[j][3] = 0.f;
      mma_bf16(S[j], qa[h], kb[h][2 * j], kb[h][2 * j + 1]);
    }
    vA0[h] = par ? S[1][1] : S[1][0];
    vB0[h] = epos ? (par ? S[0][1] : S[0][0]) : (par ? S[2][1] : S[2][0]);
    vA1[h] = par ? S[2][3] : S[2][2];
    vB1[h] = epos ? (par ? S[1][3] : S[1][2]) : (par ? S[3][3] : S[3][2]);
    if (first) { vA0[h] = NEG; if (epos) { vB0[h] = NEG; vB1[h] = NEG; } }
  }
  float m0[4], m1[4];
#pragma unroll
  for (int h = 0; h < 4; h++) { m0[h] = fmaxf(vA0[h], vB0[h]); m1[h] = fmaxf(vA1[h], vB1[h]); }
#pragma unroll
  for (int o = 1; o <= 2; o <<= 1) {
#pragma unroll
    for (int h = 0; h < 4; h++) {
      m0[h] = fmaxf(m0[h], __shfl_xor_sync(~0u, m0[h], o));
      m1[h] = fmaxf(m1[h], __shfl_xor_sync(~0u, m1[h], o));
    }
  }
  float O0[4][4], O1[4][4], Z[4][4];
#pragma unroll
  for (int h = 0; h < 4; h++) {
    const float mm0 = -m0[h] * sc0, mm1 = -m1[h] * sc1;
    const float pA0 = ex2(fmaf(vA0[h], sc0, mm0)), pB0 = ex2(fmaf(vB0[h], sc0, mm0));
    const float pA1 = ex2(fmaf(vA1[h], sc1, mm1)), pB1 = ex2(fmaf(vB1[h], sc1, mm1));
    const uint32_t hA0 = packbf(pA0, pA0), hB0 = packbf(pB0, pB0), hA1 = packbf(pA1, pA1), hB1 = packbf(pB1, pB1);
    const uint32_t P0[4] = {hB0 & mB0, 0u, hA0 & pmask, hB1 & mB0};
    const uint32_t P1[4] = {hB0 & mB1, hA1 & pmask, 0u, hB1 & mB1};
#pragma unroll
    for (int k = 0; k < 4; k++) O0[h][k] = O1[h][k] = Z[h][k] = 0.f;
    mma_bf16(O0[h], P0, vb[h][0], vb[h][1]); mma_bf16(O1[h], P0, vb[h][2], vb[h][3]); mma_bf16(Z[h], P0, 0x3f803f80u, 0x3f803f80u);
    mma_bf16(O0[h], P1, vb[h][4], vb[h][5]); mma_bf16(O1[h], P1, vb[h][6], vb[h][7]); mma_bf16(Z[h], P1, 0x3f803f80u, 0x3f803f80u);
  }
  const uint32_t ob = kvx + 2 * PG;
  const int o_row = 16 * w + (lane & 7) + 8 * ((lane >> 3) & 1);
#pragma unroll
  for (int h = 0; h < 4; h++) {
    const float i0 = rcp_approx(Z[h][0]), i1 = rcp_approx(Z[h][2]);
    const int ch = 2 * h + (lane >> 4);
    stsm4(ob + o_row * 128 + ((ch ^ (o_row & 7)) << 4), packbf(O0[h][0] * i0, O0[h][1] * i0), packbf(O0[h][2] * i1, O0[h][3] * i1),
          packbf(O1[h][0] * i0, O1[h][1] * i0), packbf(O1[h][2] * i1, O1[h][3] * i1));
  }
  TSW(5);
  fence_async_smem();
  bar_sync(2 + wg, 128);
  if (w == 0 && elect_one()) {
    tma_st(&p.mapO, hg * 64, blk * 64, ob);
    bulk_commit();
    bulk_wait_all();
    red_relaxed(&g_cnt[(C_O + layer * 32 + blk) * 32]);
    mbar_arrive(bar + 8 * (B_OST + wg));
    TSW(6);
  }
}

__device__ __forceinline__ void proj_phase(const Params& p, uint32_t sb, int layer, int rb, int q, int wg, int w) {
  const int lane = opaque_tid() & 31;
  const bool TR = layer != 0;
  const int t = lane & 3;
  const uint32_t bar = sb + SM_BAR;
  const uint32_t rbx = sb + (P_R + wg) * PG;
  const int blk = 16 * wg + rb;
  uint32_t res[16];
  mbar_wait(bar + 8 * (B_RF + wg), layer);
  if (!TR) {
#pragma unroll
    for (int j = 0; j < 8; j += 2) {
      const int mi = lane >> 3;
      const int row = 16 * w + (lane & 7) + 8 * (mi & 1), ch = j + (mi >> 1);
      ldsm4(&res[2 * j], rbx + row * 128 + ((ch ^ (row & 7)) << 4));
    }
  } else {
#pragma unroll
    for (int j = 0; j < 8; j += 2) {
      const int mi = lane >> 3;
      const int line = 8 * (j + (mi >> 1)) + (lane & 7), pc = 2 * w + (mi & 1);
      ldsm4t(&res[2 * j], rbx + line * 128 + ((pc ^ (line & 7)) << 4));
    }
  }
  float acc[32];
#pragma unroll
  for (int j = 0; j < 16; j++) { acc[2 * j] = bf_lo(res[j]); acc[2 * j + 1] = bf_hi(res[j]); }
  acc_fence<32>(acc);
#pragma unroll
  for (int c = 0; c < 4; c++) {
    mbar_wait(bar + 8 * (B_WOF + c), layer);
    mbar_wait(bar + 8 * (B_OF + 4 * wg + c), layer);
    if (c == 0) TSW(7);
    const uint64_t da = mkdesc(sb + (wg ? (c < 3 ? 2 * c : 22) : 8 + 2 * c) * PG, 16, 1024, 1);
    const uint64_t db = mkdesc(sb + (c < 3 ? 16 + 2 * c : 6) * PG, 8192, 1024, 1);
    wg_fence();
#pragma unroll
    for (int ks = 0; ks < 8; ks++) wgmma_ss<64, 0, 1>(acc, da + (ks >> 2) * 512 + (ks & 3) * 2, db + ks * 128, 1);
    wg_commit();
  }
  wg_wait<0>();
  acc_fence<32>(acc);
  TSW(8);
  if (lane == 0 && w == 0) mbar_arrive(bar + 8 * (B_PDONE + wg));
  float s0 = 0.f, q0 = 0.f, s1 = 0.f, q1 = 0.f;
  uint32_t o[16];
#pragma unroll
  for (int j = 0; j < 8; j++) {
    const float a = acc[4 * j], b = acc[4 * j + 1], c = acc[4 * j + 2], d = acc[4 * j + 3];
    o[2 * j] = packbf(a, b);
    o[2 * j + 1] = packbf(c, d);
    s0 += a + b; q0 = fmaf(a, a, q0); q0 = fmaf(b, b, q0);
    s1 += c + d; q1 = fmaf(c, c, q1); q1 = fmaf(d, d, q1);
  }
#pragma unroll
  for (int j = 0; j < 8; j += 2) {
    const int mi = lane >> 3;
    const int line = 8 * (j + (mi >> 1)) + (lane & 7), pc = 2 * w + (mi & 1);
    stsm4t(rbx + line * 128 + ((pc ^ (line & 7)) << 4), o[2 * j], o[2 * j + 1], o[2 * j + 2], o[2 * j + 3]);
  }
#pragma unroll
  for (int o2 = 1; o2 <= 2; o2 <<= 1) {
    s0 += __shfl_xor_sync(~0u, s0, o2); q0 += __shfl_xor_sync(~0u, q0, o2);
    s1 += __shfl_xor_sync(~0u, s1, o2); q1 += __shfl_xor_sync(~0u, q1, o2);
  }
  const uint32_t stg = sb + SM_STG + wg * 512;
  {
    const int row = 16 * w + (lane >> 2) + 8 * (t >> 1);
    const float v = (t == 0) ? s0 : (t == 1) ? q0 : (t == 2) ? s1 : q1;
    sts32f(stg + 4 * (((((row & 7) >> 1) * 8 + (row >> 3)) << 2) + (row & 1) * 2 + (t & 1)), v);
  }
  TSW(9);
  fence_async_smem();
  bar_sync(2 + wg, 128);
  if (w == 0 && elect_one()) {
    mbar_wait(bar + 8 * B_ZF, 0);
    tma_st(&p.mapXT, blk * 64, (2 * layer) * DM + q * 64, rbx);
    bulk_red_add_f32(g_stats + layer * LSEQ * 2 + blk * 128, stg, 512);
    bulk_commit();
    bulk_wait_all();
    red_relaxed(&g_cnt[(C_G + 2 * layer + wg) * 32]);
    TSW(10);
  }
}

template <int M0, int STEP, int CNT> __device__ __forceinline__ void conv_load(uint32_t* A, uint32_t pe) {
#pragma unroll
  for (int i = 0; i < CNT; i++) {
    const int m = M0 + STEP * i;
    A[4 * i + 2] = lds32(pe + 4 * (64 * m - 8));
    A[4 * i + 0] = lds32(pe + 4 * (64 * m));
    A[4 * i + 1] = lds32(pe + 4 * (64 * m + 8));
    asm volatile("mov.b32 %0, %1;" : "=r"(A[4 * i + 3]) : "r"(A[4 * i + 0]));
  }
}
template <int B> __device__ __forceinline__ void conv_mma0(float* acc, const uint32_t* A, uint64_t d) {
  wg_fence();
  wgmma_rs<64, 0>(acc, A + 0, d + (uint64_t)(64 + 4 * B), B != 0);
  wgmma_rs<56, 0>(acc, A + 4, d + (uint64_t)(64 + 4 * B + 8), 1);
  wgmma_rs<48, 0>(acc, A + 8, d + (uint64_t)(64 + 4 * B + 16), 1);
  wgmma_rs<40, 0>(acc, A + 12, d + (uint64_t)(64 + 4 * B + 24), 1);
  wgmma_rs<32, 0>(acc, A + 16, d + (uint64_t)(64 + 4 * B + 32), 1);
  wgmma_rs<24, 0>(acc, A + 20, d + (uint64_t)(64 + 4 * B + 40), 1);
  wgmma_rs<16, 0>(acc, A + 24, d + (uint64_t)(64 + 4 * B + 48), 1);
  wgmma_rs<8, 0>(acc, A + 28, d + (uint64_t)(64 + 4 * B + 56), 1);
  wg_commit();
}
template <int M0, int CNT> __device__ __forceinline__ void conv_mma1(float* acc, const uint32_t* A, uint64_t d) {
  wg_fence();
#pragma unroll
  for (int i = 0; i < CNT; i++) wgmma_rs<64, 0>(acc, A + 4 * i, d + (uint64_t)(4 * (M0 + i)), (M0 + i) != 0);
  wg_commit();
}
__device__ __forceinline__ void conv_store(float* acc, uint32_t pb, uint32_t over, int w) {
  acc_fence<32>(acc);
  const int l = opaque_tid() & 31, mt = l >> 3;
  int c = 2 * (63 - 8 * (mt >> 1) - (l & 7) + w) + (mt & 1);
  c ^= (c >> 3) & 1;
  const uint32_t a0 = pb + c * 16;
#pragma unroll
  for (int j = 0; j < 8; j += 2)
    stsm4t(j == 0 ? (c < 128 ? a0 : over + (c - 128) * 16) : a0 - 256 * j, packbf(acc[4 * j], acc[4 * j + 1]), packbf(acc[4 * j + 2], acc[4 * j + 3]),
           packbf(acc[4 * j + 4], acc[4 * j + 5]), packbf(acc[4 * j + 6], acc[4 * j + 7]));
}
__device__ __forceinline__ void far_load(uint32_t* a, uint32_t wt) {
  uint32_t e[9];
#pragma unroll
  for (int k = 0; k < 9; k++) e[k] = lds32(wt - 32 * k);
#pragma unroll
  for (int s = 0; s < 4; s++) {
    asm volatile("mov.b32 %0, %1;" : "=r"(a[4 * s + 0]) : "r"(e[2 * s + 1]));
    asm volatile("mov.b32 %0, %1;" : "=r"(a[4 * s + 1]) : "r"(e[2 * s]));
    asm volatile("mov.b32 %0, %1;" : "=r"(a[4 * s + 2]) : "r"(e[2 * s + 2]));
    asm volatile("mov.b32 %0, %1;" : "=r"(a[4 * s + 3]) : "r"(e[2 * s + 1]));
  }
}
__device__ __forceinline__ void conv_sums(uint32_t sb, int lc, int ht) {
  const int m = ht - 1;
  uint4 v[2][3];
#pragma unroll
  for (int c = 0; c < 2; c++)
#pragma unroll
    for (int k = 0; k < 3; k++) {
      const int mm = m - 1 + k;
      v[c][k] = lds128(sb + cv_u(lc + c) + (mm >= 0 ? (mm & 1) * CV_UH + (127 - (mm >> 1)) * 16 : 128 * 16));
    }
  const int ce = m + 2, co = m + 1;
#pragma unroll
  for (int c = 0; c < 2; c++) {
    const uint32_t x[8] = {v[c][0].z, v[c][0].w, v[c][1].x, v[c][1].y, v[c][1].z, v[c][1].w, v[c][2].x, v[c][2].y};
    float pv[16];
#pragma unroll
    for (int k = 0; k < 8; k++) { pv[2 * k] = bf_lo(x[k]); pv[2 * k + 1] = bf_hi(x[k]); }
    float t2[15], t4[13], s9[8], s7[8];
#pragma unroll
    for (int i = 0; i < 15; i++) t2[i] = pv[i] + pv[i + 1];
#pragma unroll
    for (int i = 0; i < 13; i++) t4[i] = t2[i] + t2[i + 2];
#pragma unroll
    for (int i = 0; i < 8; i++) {
      s9[i] = (t4[i] + t4[i + 4]) + pv[i + 8];
      s7[i] = (t4[i + 1] + t2[i + 5]) + pv[i + 7];
    }
    const uint4 e4 = make_uint4(packbf(s9[0], s9[1]), packbf(s9[2], s9[3]), packbf(s9[4], s9[5]), packbf(s9[6], s9[7]));
    if (ce < 128) sts128(sb + cv_se(lc + c) + (ce >> 1) * 32 + (((ce & 1) ^ ((ce >> 3) & 1)) << 4), e4);
    else sts128(sb + cv_se(lc + c), make_uint4(0, 0, 0, 0));
    sts128(sb + cv_so(lc + c) + (co >> 1) * 32 + (((co & 1) ^ ((co >> 3) & 1)) << 4),
           make_uint4(packbf(s7[0], s7[1]), packbf(s7[2], s7[3]), packbf(s7[4], s7[5]), packbf(s7[6], s7[7])));
  }
}

template <int HALF, int NCH>
__device__ __forceinline__ void conv_epi(uint32_t sb, int lc, int c) {
  uint4 v[NCH][4], xr[NCH], f[NCH];
  const uint32_t sw = (c ^ ((c >> 3) & 1)) * 16;
#pragma unroll
  for (int u = 0; u < NCH; u++) {
#pragma unroll
    for (int k = 0; k < 4; k++) v[u][k] = lds128(sb + (HALF ? cv_pb1(lc + u, k) : cv_pb0(lc + u, k)) + sw);
    xr[u] = lds128(sb + cv_x(HALF, lc + u) + c * 16);
    if (HALF) f[u] = lds128(sb + cv_pf(lc + u) + c * 16);
  }
#pragma unroll
  for (int u = 0; u < NCH; u++) {
    if (HALF) { v[u][0].x = hadd2(v[u][0].x, f[u].x); v[u][0].y = hadd2(v[u][0].y, f[u].y); v[u][0].z = hadd2(v[u][0].z, f[u].z); v[u][0].w = hadd2(v[u][0].w, f[u].w); }
    uint4 o;
    o.x = hadd2(xr[u].x, hadd2(hadd2(v[u][0].x, v[u][1].x), hadd2(v[u][2].x, v[u][3].x)));
    o.y = hadd2(xr[u].y, hadd2(hadd2(v[u][0].y, v[u][1].y), hadd2(v[u][2].y, v[u][3].y)));
    o.z = hadd2(xr[u].z, hadd2(hadd2(v[u][0].z, v[u][1].z), hadd2(v[u][2].z, v[u][3].z)));
    o.w = hadd2(xr[u].w, hadd2(hadd2(v[u][0].w, v[u][1].w), hadd2(v[u][2].w, v[u][3].w)));
    sts128(sb + cv_x(HALF, lc + u) + c * 16, o);
  }
}

__device__ __forceinline__ void conv_prep(uint32_t sb, int layer, int cta, int half, int i) {
  const int c = 128 * half + i;
  const bf16* xin = g_xT + (size_t)(2 * layer) * DM * LSEQ + c * 8;
  uint4 st[4], xr[4];
#pragma unroll
  for (int k = 0; k < 4; k++) st[k] = ldcg128(g_stats + layer * LSEQ * 2 + ((c >> 3) * 4 + k) * 32 + (c & 7) * 4);
#pragma unroll
  for (int k = 0; k < 4; k++) xr[k] = ldcg128(xin + (size_t)cv_chan(cta, k) * LSEQ);
  uint32_t rs[4], nm[4];
#pragma unroll
  for (int k = 0; k < 4; k++) {
    const float m0 = __uint_as_float(st[k].x) * (-1.f / DM), m1 = __uint_as_float(st[k].z) * (-1.f / DM);
    const float r0 = rsqrt_approx(fmaxf(fmaf(__uint_as_float(st[k].y), 1.f / DM, -m0 * m0), 0.f) + 1e-5f);
    const float r1 = rsqrt_approx(fmaxf(fmaf(__uint_as_float(st[k].w), 1.f / DM, -m1 * m1), 0.f) + 1e-5f);
    rs[k] = packbf(r0, r1);
    nm[k] = packbf(m0 * bf_lo(rs[k]), m1 * bf_hi(rs[k]));
  }
  const uint32_t ud = sb + (c & 1) * CV_UH + (127 - (c >> 1)) * 16;
#pragma unroll
  for (int k = 0; k < 4; k++)
    sts128(ud + cv_u(k), make_uint4(hfma2(xr[k].x, rs[0], nm[0]), hfma2(xr[k].y, rs[1], nm[1]), hfma2(xr[k].z, rs[2], nm[2]), hfma2(xr[k].w, rs[3], nm[3])));
  fence_async_smem();
  mbar_arrive(sb + SM_BAR + 8 * (B_U + half));
#pragma unroll
  for (int k = 0; k < 4; k++) sts128(sb + cv_x(0, k) + half * PG + i * 16, xr[k]);
}

__device__ __forceinline__ void conv_phase(const Params& p, uint32_t sb, int layer, int cta) {
  const int tid = opaque_tid();
  const int wg = __shfl_sync(~0u, tid >> 7, 0), w = __shfl_sync(~0u, (tid >> 5) & 3, 0);
  const uint32_t bar = sb + SM_BAR;
  if (wg == 0) {
    if (tid < 32) sts128(sb + cv_u(tid >> 3) + ((tid >> 2) & 1) * CV_UH + (128 + (tid & 3)) * 16, make_uint4(0, 0, 0, 0));
    mbar_wait(bar + 8 * B_GB, layer);
    TSW(11);
    conv_prep(sb, layer, cta, 0, tid);
  } else if (tid < 176) {
    const int i = tid - 128, ch = i / 12, q2 = i % 12;
    const int w2 = q2 < 2 ? 1 : q2 < 6 ? 2 : 3, cc = q2 < 2 ? q2 : q2 < 6 ? q2 - 2 : q2 - 6;
    sts128(sb + cv_pb0(ch, w2) + cc * 16, make_uint4(0, 0, 0, 0));
  }
  constexpr int CH2 = 4 * PG;
  uint32_t A0[36], A1[32];
  float acc0[32], acc1[32];
  const int l1 = opaque_tid() & 31;
  const uint32_t pe = sb + cv_pe(wg) + 4 * (16 + 16 * w + (l1 >> 2) - 2 * (l1 & 3));
  const uint64_t d0 = mkdesc(sb + cv_u(wg), CV_UH, 128, 0), d1 = d0 + (CH2 >> 4);
  const uint32_t pb1a = sb + cv_pb1(wg, w), pb1b = sb + cv_pb1(2 + wg, w);
  mbar_wait(bar + 8 * B_PE, layer);
  conv_load<0, 2, 8>(A0, pe);
  conv_load<1, 2, 8>(A1, pe);
  mbar_wait(bar + 8 * B_U, layer);
  TSW(12);
  conv_mma0<0>(acc0, A0, d0);
  conv_mma0<1>(acc0, A1, d0);
  wg_wait<1>();
  conv_load<0, 2, 8>(A0, pe + CH2);
  conv_mma0<0>(acc1, A0, d1);
  wg_wait<1>();
  conv_load<1, 2, 8>(A1, pe + CH2);
  conv_mma0<1>(acc1, A1, d1);
  mbar_wait(bar + 8 * (B_PDONE + 1), layer);
  conv_store(acc0, sb + cv_pb0(wg, w), pb1a, w);
  const uint32_t wt = pe + (cv_wt(0) - cv_pe(0)) + 4 * (73 - 16);
  wg_wait<1>();
  far_load(A0, wt);
  far_load(A0 + 16, wt + 576 - 4);
  wg_wait<0>();
  far_load(A1, wt + CH2);
  far_load(A1 + 16, wt + CH2 + 576 - 4);
  mbar_wait(bar + 8 * B_S, layer);
  {
    float F0[8], F1[8];
    const uint64_t ds = mkdesc(sb + cv_se(wg), 256, 256, 3);
    wg_fence();
#pragma unroll
    for (int k = 0; k < 8; k++) {
      wgmma_rs<16, 1>(F0, A0 + 4 * k, ds + 32 * k, k != 0);
      wgmma_rs<16, 1>(F1, A1 + 4 * k, ds + 512 + 32 * k, k != 0);
    }
    wg_commit();
    conv_store(acc1, sb + cv_pb0(2 + wg, w), pb1b, w);
    mbar_arrive(bar + 8 * B_R);
    TSW(13);
    wg_wait<0>();
    acc_fence<8>(F0); acc_fence<8>(F1);
    const int l3 = opaque_tid() & 31;
    if (w == 0 && l3 == 0) mbar_arrive(bar + 8 * B_FARM);
    conv_load<0, 1, 9>(A0, pe);
    conv_load<9, 1, 8>(A1, pe);
    const uint32_t pf = sb + cv_pf(wg) + 2 * (16 * (16 * w + (l3 >> 2)) + 2 * (l3 & 3));
#pragma unroll
    for (int k = 0; k < 4; k++) {
      sts32(pf + (k & 1) * 256 + (k >> 1) * 16, packbf(F0[2 * k], F0[2 * k + 1]));
      sts32(pf + 4096 + (k & 1) * 256 + (k >> 1) * 16, packbf(F1[2 * k], F1[2 * k + 1]));
    }
  }
  TSW(14);
  mbar_wait(bar + 8 * (B_U + 1), layer);
  TSW(15);
  conv_mma1<0, 9>(acc0, A0, d0);
  conv_mma1<9, 8>(acc0, A1, d0);
  wg_wait<1>();
  conv_load<0, 1, 9>(A0, pe + CH2);
  conv_mma1<0, 9>(acc1, A0, d1);
  wg_wait<1>();
  conv_load<9, 1, 8>(A1, pe + CH2);
  conv_mma1<9, 4>(acc1, A1, d1);
  conv_store(acc0, pb1a, sb + cv_dump(wg), w);
  mbar_arrive(bar + 8 * (B_R + 1));
  TSW(16);
  conv_mma1<13, 4>(acc1, A1 + 16, d1);
  wg_wait<0>();
  conv_store(acc1, pb1b, sb + cv_dump(2 + wg), w);
  TSW(17);
  if (wg == 0) {
    mbar_arrive(bar + 8 * (B_R + 2));
  } else {
    mbar_wait(bar + 8 * B_PUB, layer);
    bar_sync(3, 128);
    conv_epi<1, 1>(sb, 3, opaque_tid() & 127);
    fence_async_smem();
    mbar_arrive(bar + 8 * (B_PUB + 2));
    TSW(18);
  }
}

__device__ __forceinline__ void final_phase(const Params& p, uint32_t sb, int cta, int wg, int w) {
  const int lane = opaque_tid() & 31;
  const uint32_t bar = sb + SM_BAR;
  mbar_wait(bar + 8 * (B_TF + wg), 0);
  if (threadIdx.x == 128) TS(8);
  const uint32_t src = sb + (16 + wg) * PG, dst = src + 2 * PG;
  const int mi = lane >> 3;
#pragma unroll
  for (int j = 0; j < 8; j += 2) {
    uint32_t r[4];
    const int line = 8 * (j + (mi >> 1)) + (lane & 7), pc = 2 * w + (mi & 1);
    ldsm4t(r, src + line * 128 + ((pc ^ (line & 7)) << 4));
    const int row = 16 * w + (lane & 7) + 8 * (mi & 1), ch = j + (mi >> 1);
    stsm4(dst + row * 128 + ((ch ^ (row & 7)) << 4), r[0], r[1], r[2], r[3]);
  }
  fence_async_smem();
  bar_sync(2 + wg, 128);
  if (w == 0 && elect_one()) {
    tma_st(&p.mapOut, (cta >> 4) * 64, (16 * wg + (cta & 15)) * 64, dst);
    bulk_commit();
    asm volatile("cp.async.bulk.wait_group.read 0;" ::: "memory");
    if (threadIdx.x == 128) TS(9);
    if (threadIdx.x == 128) LTS(1);
  }
}

struct cplx { float r, i; };
__device__ __forceinline__ cplx cmul(cplx a, cplx b) { return {fmaf(a.r, b.r, -a.i * b.i), fmaf(a.r, b.i, a.i * b.r)}; }
__device__ __forceinline__ cplx csqr(cplx a) { return {fmaf(a.r, a.r, -a.i * a.i), (a.r + a.r) * a.i}; }
__device__ __forceinline__ cplx cexp_l(float ar2, float ai, float l) {
  const float m = ex2(ar2 * l);
  const float x = ai * l;
  return {m * __cosf(x), m * __sinf(x)};
}

__device__ __forceinline__ void colsum_cta(const Params& p, uint32_t sb, int j, int tid) {
  const uint32_t bar = sb + SM_BAR;
  auto ld = [&](int i) {
    mbar_expect(bar + 8 * i, 3 * PG);
    tma_ld3(sb + (i & 7) * 3 * PG, &p.mapW3, (2 * j + (i & 1)) * 64, (i >> 1) * 64, 0, bar + 8 * i);
  };
  if (tid == 384) {
#pragma unroll
    for (int i = 0; i < 24; i++) mbar_init(bar + 8 * i, i < 16 ? 1 : 12);
    asm volatile("fence.mbarrier_init.release.cluster;" ::: "memory");
    fence_async_smem();
#pragma unroll 1
    for (int i = 0; i < 8; i++) ld(i);
  }
  const unsigned ep = ld_relaxed(&g_cnt[C_CS * 32]);
  bar_sync(0, NTHREADS);
  if (tid == 384) {
#pragma unroll 1
    for (int i = 8; i < 16; i++) { mbar_wait(bar + 8 * (8 + i), 0); fence_async_smem(); ld(i); }
  }
  if (tid < 384) {
    const int lane = tid & 31, cc = tid & 7, r0 = (tid >> 3) & 15, part = tid >> 7;
    const uint32_t id = ((lane >> 2) == 2 * (lane & 3) ? 0x3f80u : 0u) | ((lane >> 2) == 2 * (lane & 3) + 1 ? 0x3f800000u : 0u);
    const uint32_t src = sb + part * PG + r0 * 128 + ((cc ^ (r0 & 7)) << 4);
    float s[2][2][4];
#pragma unroll
    for (int i = 0; i < 16; i++) s[i >> 3][(i >> 2) & 1][i & 3] = 0.f;
#pragma unroll 1
    for (int i2 = 0; i2 < 16; i2 += 2) {
#pragma unroll
      for (int h = 0; h < 2; h++) {
        const int i = i2 + h;
        mbar_wait(bar + 8 * i, 0);
        uint4 v[4];
#pragma unroll
        for (int k = 0; k < 4; k++) v[k] = lds128(src + (i & 7) * 3 * PG + k * 2048);
#pragma unroll
        for (int k = 0; k < 4; k++) {
          const uint32_t a[4] = {v[k].x, v[k].y, v[k].z, v[k].w};
          mma_bf16(s[h][0], a, id, 0u);
          mma_bf16(s[h][1], a, 0u, id);
        }
        __syncwarp();
        if (i < 8 && lane == 0) mbar_arrive(bar + 8 * (16 + i));
      }
    }
    const uint32_t red = sb + 24 * PG;
#pragma unroll
    for (int h = 0; h < 2; h++)
#pragma unroll
      for (int k = 0; k < 2; k++) sts128f(red + (r0 * 384 + h * 192 + part * 64 + cc * 8 + k * 4) * 4, s[h][k][0], s[h][k][1], s[h][k][2], s[h][k][3]);
    bar_sync(1, 384);
    float tot = 0.f;
#pragma unroll
    for (int k = 0; k < 16; k++) tot += __uint_as_float(lds32(red + (k * 384 + tid) * 4));
    asm volatile("st.relaxed.gpu.global.v2.u32 [%0], {%1,%2};" ::"l"(&g_colsum[j * 384 + tid]), "r"(__float_as_uint(tot)), "r"(ep / NCTA + 1) : "memory");
  }
}

struct ModeIn { uint32_t ar, ai, br, bi, cr, ci; bf16 logdt, dskip; };
__device__ __forceinline__ ModeIn load_modes(const Params& p, int d, int m) {
  const int i = d * 64 + m;
  return {((const uint32_t*)p.a_re)[i], ((const uint32_t*)p.a_im)[i], ((const uint32_t*)p.b_re)[i], ((const uint32_t*)p.b_im)[i],
          ((const uint32_t*)p.c_re)[i], ((const uint32_t*)p.c_im)[i], p.log_dt[d], p.dskip[d]};
}
__device__ __forceinline__ float4 lds128f_nv(uint32_t a) { float4 v; asm("ld.shared.v4.f32 {%0,%1,%2,%3}, [%4];" : "=f"(v.x), "=f"(v.y), "=f"(v.z), "=f"(v.w) : "r"(a)); return v; }
__device__ __forceinline__ void kernel_gen(uint32_t sb, int cta, int ht, ModeIn in, const ModeIn& in1) {
  const int w = ht >> 5, lane = ht & 31, g = lane >> 2, t = lane & 3, chn = ht >> 6, m = ht & 63;
  const uint32_t bst = sb + SM_KGB + (m >> 2) * 144 + (m & 3) * 4 + chn * 16;
  const uint64_t db = mkdesc(sb + SM_KGB, 144, 2304, 0);
  const int i0 = 16 * (w & 1) + g;
  const float e0 = (float)(8 * i0);
  float T[20];
#pragma unroll
  for (int i = 0; i < 20; i++) T[i] = 0.f;
  float k0 = 0.f;
#pragma unroll 1
  for (int pass = 0; pass < 4; pass++) {
    {
      const int sh = (pass & 1) ? 0 : 16;
      auto val = [&](uint32_t v) { return __uint_as_float((v << sh) & 0xffff0000u); };
      const float dt = __bfloat162float(__float2bfloat16_rn(expf(__bfloat162float(in.logdt))));
      const float ar2 = dt * val(in.ar) * 1.4426950408889634f, ai = dt * val(in.ai);
      const cplx c = cmul({val(in.cr), -val(in.ci)}, {dt * val(in.br), -dt * val(in.bi)});
      k0 += c.r;
      const cplx z1 = cexp_l(ar2, -ai, 1.f), z256 = cexp_l(ar2, -ai, 256.f), z64 = cexp_l(ar2, ai, 64.f);
      const cplx z2 = csqr(z1), z512 = csqr(z256);
      auto put = [&](int j, cplx v) { sts32(bst + (j >> 2) * 2304 + (j & 3) * 32, packbf(v.r, v.i)); };
      sts128f(sb + SM_KGT + ht * 16, ar2, ai, z64.r, z64.i);
      const cplx c1 = cmul(c, z1), c2 = cmul(c, z2), c3 = cmul(c1, z2), c4 = cmul(c2, z2);
      const cplx c5 = cmul(c3, z2), c6 = cmul(c4, z2), c7 = cmul(c5, z2), c8 = cmul(c6, z2);
      put(0, c1); put(1, c2); put(2, c3); put(3, c4); put(4, c5); put(5, c6); put(6, c7); put(7, c8);
      const cplx c260 = cmul(c4, z256), c264 = cmul(c8, z256), c520 = cmul(c8, z512), c776 = cmul(c264, z512);
      put(8, cmul(c2, z256)); put(9, c260); put(10, cmul(c6, z256)); put(11, c264);
      put(12, cmul(c4, z512)); put(13, c520); put(14, cmul(c260, z512)); put(15, c776);
      const cplx c1032 = cmul(c520, z512), c1288 = cmul(c776, z512);
      put(16, c1032); put(17, c1288); put(18, cmul(c1032, z512)); put(19, cmul(c1288, z512));
    }
    fence_async_smem();
    bar_sync(4, 128);
    uint32_t tb = sb + SM_KGT + (chn * 64 + t) * 16;
    asm volatile("mov.u32 %0, %0;" : "+r"(tb) :: "memory");
    uint32_t A[32];
#pragma unroll
    for (int q = 0; q < 4; q++) {
#pragma unroll
      for (int s = 4 * q; s < 4 * q + 4; s++) {
        const float4 v = lds128f_nv(tb + s * 64);
        const cplx lo = cexp_l(v.x, v.y, e0), hi = cmul(lo, {v.z, v.w});
        A[2 * s] = packbf(lo.r, lo.i);
        A[2 * s + 1] = packbf(hi.r, hi.i);
      }
      wg_fence();
      wgmma_rs<40, 0>(T, A + 8 * q, db + 36 * q, (pass & 1) | q);
      wgmma_rs<40, 0>(T, A + 8 * q + 4, db + 36 * q + 18, 1);
      wg_commit();
    }
    wg_wait<0>();
    acc_fence<20>(T);
    if (ht == 0) TS(4 + pass);
    if (pass & 1) {
      const int lc = (pass & 2) + chn;
      const uint32_t kc = sb + SM_KC + lc * KC_STRIDE * 2;
      auto put = [&](int idx, float v) {
        sts16(kc + idx * 2, __bfloat16_as_ushort(__float2bfloat16_rn(v)));
      };
#pragma unroll
      for (int hi = 0; hi < 2; hi++) {
        const int i = i0 + 8 * hi;
        float v[5];
#pragma unroll
        for (int j = 0; j < 5; j++) v[j] = chn ? T[4 * j + 2 * hi + 1] : T[4 * j + 2 * hi];
        put(8 * i + 1 + t, v[0]);
        put(8 * i + 5 + t, v[1]);
        put(257 + 4 * i + t, v[2]);
        put(385 + 2 * i + (t & 1) + 64 * (t >> 1), v[3]);
        put(513 + i + 32 * t, v[4]);
      }
#pragma unroll
      for (int o = 16; o > 0; o >>= 1) k0 += __shfl_xor_sync(~0u, k0, o);
      if (lane == 0) sts32f(sb + SM_RED + 256 + 4 * w, k0);
      bar_sync(4, 128);
      if (m == 0) put(0, k0 + __uint_as_float(lds32(sb + SM_RED + 256 + 4 * w + 4)) + __bfloat162float(in.dskip));
      k0 = 0.f;
      in = in1;
    }
  }
}

__device__ __forceinline__ void expand_taps(uint32_t sb, int ht) {
  const int ch = ht >> 5, lane = ht & 31;
  const uint32_t kc = sb + SM_KC + ch * KC_STRIDE * 2;
  const uint32_t dst0 = sb + cv_pe(ch);
  auto put = [&](int G, uint32_t v0, uint32_t v1, uint32_t v2, uint32_t v3, uint32_t v4, uint32_t v5, uint32_t v6, uint32_t v7, uint32_t v8) {
    const uint32_t dst = dst0 + G * 32;
    sts128(dst, make_uint4(v1 | (v0 << 16), v2 | (v1 << 16), v3 | (v2 << 16), v4 | (v3 << 16)));
    sts128(dst + 16, make_uint4(v5 | (v4 << 16), v6 | (v5 << 16), v7 | (v6 << 16), v8 | (v7 << 16)));
  };
  {
    const uint4 q = lds128(kc + lane * 16);
    const uint32_t pv = lane ? lds16(kc + lane * 16 - 2) : 0u;
    const uint32_t dst = dst0 + (lane + 2) * 32;
    sts128(dst, make_uint4(__byte_perm(q.x, pv, 0x5410), __byte_perm(q.x, q.x, 0x1032), __byte_perm(q.y, q.x, 0x7610), __byte_perm(q.y, q.y, 0x1032)));
    sts128(dst + 16, make_uint4(__byte_perm(q.z, q.y, 0x7610), __byte_perm(q.z, q.z, 0x1032), __byte_perm(q.w, q.z, 0x7610), __byte_perm(q.w, q.w, 0x1032)));
    if (lane < 4) sts128(dst0 + lane * 16, make_uint4(0, 0, 0, 0));
  }
  uint32_t a[5], b[2][3], ve[5][2], vo[5][2];
  {
    const uint32_t s1 = kc + 2 * (256 + 4 * lane);
#pragma unroll
    for (int k = 0; k < 5; k++) a[k] = lds16(s1 + 2 * k);
#pragma unroll
    for (int u = 0; u < 2; u++) {
      const uint32_t s2 = kc + 2 * (384 + 2 * (lane + 32 * u));
#pragma unroll
      for (int k = 0; k < 3; k++) b[u][k] = lds16(s2 + 2 * k);
    }
#pragma unroll
    for (int u = 0; u < 5; u++) {
      const int x = lane + 32 * u;
#pragma unroll
      for (int k = 0; k < 2; k++) {
        const int pp = x - k;
        ve[u][k] = (pp >= 65 && pp <= 128) ? lds16(kc + 2 * (384 + 2 * pp)) : 0u;
        vo[u][k] = (pp >= 64 && pp <= 127) ? lds16(kc + 2 * (385 + 2 * pp)) : 0u;
      }
    }
  }
  const uint32_t k255 = lds16(kc + 2 * 255), k1024 = lds16(kc + 2 * 512);
  put(34 + lane, lane == 0 ? k255 : a[0], a[0], a[0], a[1], a[2], a[2], a[2], a[3], a[4]);
#pragma unroll
  for (int u = 0; u < 2; u++) put(66 + lane + 32 * u, b[u][0], b[u][0], b[u][0], b[u][0], b[u][1], b[u][1], b[u][1], b[u][2], b[u][2]);
  if (lane < 10) {
    const uint32_t v = lane == 0 ? k1024 : 0u;
    put(130 + lane, v, v, v, v, v, v, 0u, 0u, 0u);
  }
  const uint32_t wt = sb + cv_wt(ch);
#pragma unroll
  for (int u = 0; u < 5; u++) {
    const int x = lane + 32 * u;
    if (x < 144) {
      asm volatile("st.shared.u32 [%0], %1;" ::"r"(wt + 4 * x), "r"(ve[u][0] | (ve[u][1] << 16)) : "memory");
      asm volatile("st.shared.u32 [%0], %1;" ::"r"(wt + 576 + 4 * x), "r"(vo[u][0] | (vo[u][1] << 16)) : "memory");
    }
  }
}

#define WPRE 0
#define WOGATE 1
__host__ __device__ constexpr int bar_count(int i) {
  return i == B_FARM ? 2 : i == B_END ? 3 : (i == B_PUB + 2 || i == B_R || i == B_R + 1) ? 256 : (i >= B_Z0 && i < B_END) ? 128 : 1;
}
__host__ __device__ constexpr bool bar_first(int i) { return i < B_WF + 2 && (i & 7) < 2; }

__global__ void __launch_bounds__(NTHREADS, 1) fused_kernel(const __grid_constant__ Params p) {
  extern __shared__ __align__(1024) uint8_t smem[];
  const uint32_t sb = s32(smem);
  const int tid = threadIdx.x, lane = tid & 31;
  const int warp = __shfl_sync(~0u, tid >> 5, 0);
  if (blockIdx.x < 4) {
    colsum_cta(p, sb, blockIdx.x, tid);
    return;
  }
  const int cta = blockIdx.x - 4;
  const int rb = ((cta >> 4) & 3) * 4 + ((cta >> 2) & 3), hg = (cta >> 6) * 4 + (cta & 3);
  const int rb2 = cta >> 3, q2 = cta & 7;
  const uint32_t bar = sb + SM_BAR;
  auto ld_x0 = [&](int half, int c) {
    const uint32_t b = bar + 8 * (B_XF + 8 * half + c);
    mbar_expect(b, PG);
    tma_ld(sb + (8 * half + c) * PG, &p.mapX, c * 64, (16 * half + rb) * 64, b);
  };
  auto ld_w = [&](int c, int page) {
    const uint32_t b = bar + 8 * (B_WF + c);
    mbar_expect(b, 3 * PG);
    tma_ld3(sb + page * PG, &p.mapW3, hg * 64, c * 64, 0, b);
  };

  if (tid == 0) TS(0);
  if (tid == 480) LTS(0);
  if (warp < 6 && elect_one()) {
    if (warp == 0) {
#pragma unroll
      for (int i = 0; i < B_WF + 2; i++)
        if (bar_first(i)) mbar_init(bar + 8 * i, 1);
      asm volatile("fence.mbarrier_init.release.cluster;" ::: "memory");
      fence_async_smem();
      ld_x0(0, 0); ld_w(0, 16); ld_x0(1, 0);
      ld_x0(0, 1); ld_w(1, 19); ld_x0(1, 1);
      TS(1);
    } else {
#pragma unroll
      for (int q = 0; q < 5; q++) {
        if (warp == q + 1) {
#pragma unroll
          for (int i = 0; i < B_COUNT; i++)
            if (!bar_first(i) && i % 5 == q) mbar_init(bar + 8 * i, bar_count(i));
        }
      }
      asm volatile("fence.mbarrier_init.release.cluster;" ::: "memory");
    }
  }

  if (warp < 8) {
    bar_sync(0, NTHREADS);
    asm volatile("setmaxnreg.inc.sync.aligned.u32 %0;" ::"n"(R_CONS));
    const int cw = __shfl_sync(~0u, opaque_tid() >> 5, 0);
    const int wg = cw >> 2, w = cw & 3;
    if (tid == 0) TS(2);
#pragma unroll 1
    for (int layer = 0; layer < 2; layer++) {
      attn_phase(p, sb, layer, rb, hg, wg, w);
      proj_phase(p, sb, layer, rb2, q2, wg, w);
      conv_phase(p, sb, layer, cta);
    }
    final_phase(p, sb, cta, wg, w);
  } else if (warp < 12) {
    asm volatile("setmaxnreg.dec.sync.aligned.u32 %0;" ::"n"(R_HELP));
    const int ht = tid - 256;
    {
      unsigned ep0 = 0;
      if (ht == 0) ep0 = ld_relaxed(&g_cnt[C_CS * 32]);
      const ModeIn in0 = load_modes(p, cv_chan(cta, ht >> 6), ht & 63), in1 = load_modes(p, cv_chan(cta, 2 + (ht >> 6)), ht & 63);
      bar_sync(0, NTHREADS);
      if (ht == 0) {
        sts32(sb + SM_EP, ep0 / NCTA);
        mbar_arrive(bar + 8 * B_EP);
      }
      if (hg == 0) {
        *(float4*)(g_stats + (ht >> 6) * LSEQ * 2 + rb * 256 + (ht & 63) * 4) = make_float4(0.f, 0.f, 0.f, 0.f);
      }
      mbar_arrive(bar + 8 * B_Z0);
      if (ht == 0) TS(3);
      kernel_gen(sb, cta, ht, in0, in1);
      fence_async_smem();
      bar_sync(4, 128);
      if (ht == 0) mbar_arrive(bar + 8 * B_KG);
    }
#pragma unroll 1
    for (int layer = 0; layer < 2; layer++) {
      mbar_wait(bar + 8 * B_PDONE, layer);
      expand_taps(sb, opaque_tid() - 256);
      mbar_arrive(bar + 8 * B_PE);
      TSW(0);
      mbar_wait(bar + 8 * (B_PDONE + 1), layer);
      mbar_wait(bar + 8 * B_U, layer);
      conv_sums(sb, 0, opaque_tid() - 256);
      conv_sums(sb, 2, opaque_tid() - 256);
      fence_async_smem();
      mbar_arrive(bar + 8 * B_S);
      TSW(1);
      mbar_wait(bar + 8 * (B_GB + 1), layer);
      TSW(2);
      conv_prep(sb, layer, cta, 1, opaque_tid() - 256);
      TSW(3);
      mbar_wait(bar + 8 * B_R, layer);
      conv_epi<0, 2>(sb, 0, opaque_tid() - 256);
      conv_epi<0, 2>(sb, 2, opaque_tid() - 256);
      fence_async_smem();
      mbar_arrive(bar + 8 * B_PUB);
      TSW(4);
      mbar_wait(bar + 8 * (B_R + 1), layer);
      conv_epi<1, 2>(sb, 0, opaque_tid() - 256);
      fence_async_smem();
      mbar_arrive(bar + 8 * (B_PUB + 1));
      TSW(5);
      mbar_wait(bar + 8 * (B_R + 2), layer);
      conv_epi<1, 1>(sb, 2, opaque_tid() - 256);
      fence_async_smem();
      mbar_arrive(bar + 8 * (B_PUB + 2));
      TSW(6);
    }
  } else {
    asm volatile("setmaxnreg.dec.sync.aligned.u32 %0;" ::"n"(R_AGENT));
    bar_sync(0, NTHREADS);
    auto done = [&](int half, int c, int layer) { mbar_wait(bar + 8 * (B_DN + 8 * half + c), layer); };
    if (warp == 12) {
      if (elect_one()) {
#pragma unroll 1
        for (int layer = 0; layer < 2; layer++) {
          if (layer == 0) {
            ld_x0(0, 2); ld_w(2, 22); ld_x0(1, 2);
            if (rb < 5) tma_prefetch3(&p.mapW3, hg * 64, (3 + rb) * 64, 0);
            ld_x0(0, 3); ld_x0(1, 3); ld_x0(0, 4); ld_x0(1, 4);
            done(0, 0, 0); done(1, 0, 0);
            ld_w(3, 16);
            ld_x0(0, 5); ld_x0(0, 6); ld_x0(0, 7);
            done(0, 1, 0); done(1, 1, 0);
            ld_w(4, 19);
            ld_x0(1, 5); ld_x0(1, 6); ld_x0(1, 7);
            if (rb2 < 4) tma_prefetch2(&p.mapWo, q2 * 64, rb2 * 128);
            done(0, 2, 0);
            fence_async_smem();
            ld_w(5, 0);
          } else {
            mbar_wait(bar + 8 * B_PDONE, 0);
            mbar_wait(bar + 8 * (B_PDONE + 1), 0);
            ld_w(0, 16); ld_w(1, 19); ld_w(2, 22);
            done(0, 2, 1);
            fence_async_smem();
            ld_w(3, 0);
            done(1, 0, 1);
            ld_w(4, 16);
            done(1, 1, 1);
            ld_w(5, 19);
          }
          done(1, 2, layer);
          fence_async_smem();
          ld_w(6, 22); ld_w(7, 8);
          done(0, 7, layer); done(1, 5, layer);
          mbar_wait(bar + 8 * (B_HF + WOGATE - 1), layer);
          fence_async_smem();
#pragma unroll 1
          for (int c = 0; c < 4; c++) {
            const uint32_t b = bar + 8 * (B_WOF + c);
            mbar_expect(b, 2 * PG);
            tma_ld(sb + (c < 3 ? 16 + 2 * c : 6) * PG, &p.mapWo, q2 * 64, c * 128, b);
          }
          mbar_wait(bar + 8 * B_KG, 0);
#pragma unroll 1
          for (int half = 0; half < 2; half++) {
            const uint32_t b = bar + 8 * (B_RF + half);
            mbar_expect(b, PG);
            if (layer == 0) tma_ld(sb + (P_R + half) * PG, &p.mapX, q2 * 64, (16 * half + rb2) * 64, b);
            else tma_ld(sb + (P_R + half) * PG, &p.mapXT, (16 * half + rb2) * 64, DM + q2 * 64, b);
          }
        }
      }
    } else if (warp == 13) {
      if (elect_one()) {
        mbar_wait(bar + 8 * (B_WF + 2), 0);
        asm volatile("prefetch.tensormap [%0];" ::"l"(&p.mapO) : "memory");
        asm volatile("prefetch.tensormap [%0];" ::"l"(&p.mapO2) : "memory");
        asm volatile("prefetch.tensormap [%0];" ::"l"(&p.mapXT) : "memory");
        asm volatile("prefetch.tensormap [%0];" ::"l"(&p.mapOut) : "memory");
        asm volatile("prefetch.tensormap [%0];" ::"l"(&p.mapWo) : "memory");
        mbar_wait(bar + 8 * B_EP, 0);
        const unsigned e1 = lds32(sb + SM_EP) + 1;
        auto ld_x1 = [&](int half, int c0, int c1) {
          fence_async_global();
          fence_async_smem();
#pragma unroll 1
          for (int c = c0; c < c1; c++) {
            const uint32_t b = bar + 8 * (B_XF + 8 * half + c);
            mbar_expect(b, PG);
            tma_ld(sb + (8 * half + c) * PG, &p.mapXT, (16 * half + rb) * 64, DM + c * 64, b);
          }
        };
#pragma unroll 1
        for (int layer = 0; layer < 2; layer++) {
          if (layer == 1) {
            mbar_wait(bar + 8 * B_FARM, 0);
            mbar_wait(bar + 8 * B_PUB, 0);
            spin_until(&g_cnt[C_C * 32], e1 * NCTA);
            TS(10);
            ld_x1(0, 0, 6);
            mbar_wait(bar + 8 * (B_PUB + 2), 0);
            ld_x1(0, 6, 8);
            spin_until(&g_cnt[(C_C + 1) * 32], e1 * NCTA);
            TS(11);
            ld_x1(1, 0, 4);
            spin_until(&g_cnt[(C_C + 2) * 32], e1 * NCTA);
            TS(12);
            ld_x1(1, 4, 8);
          }
#pragma unroll 1
          for (int half = 0; half < 2; half++) {
            done(1, 7, layer);
            mbar_wait(bar + 8 * B_OST, layer);
            if (half) mbar_wait(bar + 8 * (B_OST + 1), layer);
            spin_until(&g_cnt[(C_O + layer * 32 + 16 * half + rb2) * 32], e1 * 8);
            fence_async_global();
            fence_async_smem();
#pragma unroll 1
            for (int c = 0; c < 4; c++) {
              const uint32_t b = bar + 8 * (B_OF + 4 * half + c);
              mbar_expect(b, 2 * PG);
              tma_ld3(sb + (half ? (c < 3 ? 2 * c : 22) : 8 + 2 * c) * PG, &p.mapO2, 0, (16 * half + rb2) * 64, 2 * c, b);
            }
          }
        }
        mbar_wait(bar + 8 * B_PUB, 1);
#pragma unroll 1
        for (int half = 0; half < 2; half++) {
          spin_until(&g_cnt[(C_F + 4 * (half ? 1 + (cta >> 6) : 0) + ((cta >> 4) & 3)) * 32], e1 * 32);
          fence_async_global();
          mbar_expect(bar + 8 * (B_TF + half), PG);
          tma_ld(sb + (16 + half) * PG, &p.mapXT, (16 * half + (cta & 15)) * 64, 3 * DM + (cta >> 4) * 64, bar + 8 * (B_TF + half));
        }
      }
    } else if (warp == 14) {
      mbar_wait(bar + 8 * B_EP, 0);
      const unsigned e1 = lds32(sb + SM_EP) + 1;
      done(0, 1, 0);
      {
        uint2 v[6];
        bool ok;
        int it = 0;
        do {
          ok = true;
#pragma unroll
          for (int i = 0; i < 6; i++) {
            const int k = lane + 32 * i;
            asm volatile("ld.relaxed.gpu.global.v2.u32 {%0,%1}, [%2];" : "=r"(v[i].x), "=r"(v[i].y) : "l"(&g_colsum[hg * 192 + k]) : "memory");
            ok = ok && v[i].y == e1;
          }
          if (++it > (1 << 22)) __trap();
        } while (!__all_sync(~0u, ok));
#pragma unroll
        for (int i = 0; i < 6; i++) sts32f(sb + SM_CS + 4 * (lane + 32 * i), __uint_as_float(v[i].x));
      }
      __syncwarp();
      if (lane == 0) {
        mbar_arrive(bar + 8 * B_CSF);
        TS(13);
        mbar_wait(bar + 8 * B_Z0, 0);
        red_release(&g_cnt[C_CS * 32]);
        spin_until(&g_cnt[C_CS * 32], e1 * NCTA);
        mbar_arrive(bar + 8 * B_ZF);
#pragma unroll 1
        for (int i = 0; i < 4; i++) {
          mbar_wait(bar + 8 * (B_PDONE + (i & 1)), i >> 1);
          spin_until(&g_cnt[(C_G + i) * 32], e1 * NCTA);
          mbar_arrive(bar + 8 * (B_GB + (i & 1)));
        }
      }
    } else if (elect_one()) {
#pragma unroll 1
      for (int i = 0; i < 6; i++) {
        const int layer = i >= 3, k = i - 3 * layer, half = k != 0;
        bf16* xout = g_xT + (size_t)(2 * layer + 1) * DM * LSEQ + half * 1024;
        mbar_wait(bar + 8 * (B_PUB + k), layer);
#pragma unroll 1
        for (int lc = (k & 2); lc < (k == 1 ? 2 : 4); lc++) bulk_st(xout + (size_t)cv_chan(cta, lc) * LSEQ, sb + cv_x(half, lc), 2048);
        bulk_commit();
        bulk_wait_all();
        red_relaxed(&g_cnt[(layer ? C_F + 4 * k + (cta >> 5) : C_C + k) * 32]);
        TS(16 + layer * 56 + 40 + 7 + k);
      }
    }
  }
}

typedef CUresult (*EncodeFn)(CUtensorMap*, CUtensorMapDataType, cuuint32_t, void*, const cuuint64_t*, const cuuint64_t*,
                             const cuuint32_t*, const cuuint32_t*, CUtensorMapInterleave, CUtensorMapSwizzle,
                             CUtensorMapL2promotion, CUtensorMapFloatOOBfill);

static void make_map(EncodeFn enc, CUtensorMap* m, void* ptr, uint64_t cols, uint64_t rows, uint32_t box_rows) {
  cuuint64_t dims[2] = {cols, rows};
  cuuint64_t strides[1] = {cols * 2};
  cuuint32_t box[2] = {64, box_rows};
  cuuint32_t es[2] = {1, 1};
  enc(m, CU_TENSOR_MAP_DATA_TYPE_BFLOAT16, 2, ptr, dims, strides, box, es, CU_TENSOR_MAP_INTERLEAVE_NONE,
      CU_TENSOR_MAP_SWIZZLE_128B, CU_TENSOR_MAP_L2_PROMOTION_L2_128B, CU_TENSOR_MAP_FLOAT_OOB_FILL_NONE);
}
static void make_map3(EncodeFn enc, CUtensorMap* m, void* ptr, uint64_t d0, uint64_t cols, uint64_t rows, uint64_t blk_stride,
                      uint64_t nblocks, uint32_t nblk) {
  cuuint64_t dims[3] = {d0, rows, nblocks};
  cuuint64_t strides[2] = {cols * 2, blk_stride * 2};
  cuuint32_t box[3] = {64, 64, nblk};
  cuuint32_t es[3] = {1, 1, 1};
  enc(m, CU_TENSOR_MAP_DATA_TYPE_BFLOAT16, 3, ptr, dims, strides, box, es, CU_TENSOR_MAP_INTERLEAVE_NONE,
      CU_TENSOR_MAP_SWIZZLE_128B, CU_TENSOR_MAP_L2_PROMOTION_L2_128B, CU_TENSOR_MAP_FLOAT_OOB_FILL_NONE);
}

extern "C" void kernel_launch(void* const* d_in, const int* in_sizes, int n_in, void* d_out, int out_size) {
  static Params prm;
  static void* cached[13] = {nullptr};
  static bool attr_done = false;
  bool same = attr_done && cached[12] == d_out;
  for (int i = 0; i < 12 && same; i++) same = cached[i] == d_in[i];
  if (!same) {
    void* fn = nullptr;
    cudaDriverEntryPointQueryResult qr;
    cudaGetDriverEntryPoint("cuTensorMapEncodeTiled", &fn, cudaEnableDefault, &qr);
    EncodeFn enc = (EncodeFn)fn;
    void *pO, *pXT;
    cudaGetSymbolAddress(&pO, g_O);
    cudaGetSymbolAddress(&pXT, g_xT);
    make_map(enc, &prm.mapX, d_in[0], DM, LSEQ, 64);
    make_map(enc, &prm.mapO, pO, DM, LSEQ, 64);
    make_map(enc, &prm.mapXT, pXT, LSEQ, 4 * DM, 64);
    make_map(enc, &prm.mapOut, d_out, DM, LSEQ, 64);
    make_map(enc, &prm.mapWo, d_in[2], DM, DM, 128);
    make_map3(enc, &prm.mapW3, d_in[1], DM, 3 * DM, DM, DM, 3, 3);
    make_map3(enc, &prm.mapO2, pO, 64, DM, LSEQ, 64, 8, 2);
    prm.wqkv = (const bf16*)d_in[1];
    prm.a_re = (const bf16*)d_in[4]; prm.a_im = (const bf16*)d_in[5];
    prm.b_re = (const bf16*)d_in[6]; prm.b_im = (const bf16*)d_in[7];
    prm.c_re = (const bf16*)d_in[8]; prm.c_im = (const bf16*)d_in[9];
    prm.log_dt = (const bf16*)d_in[10]; prm.dskip = (const bf16*)d_in[11];
    cudaFuncSetAttribute(fused_kernel, cudaFuncAttributeMaxDynamicSharedMemorySize, SM_TOTAL);
    for (int i = 0; i < 12; i++) cached[i] = d_in[i];
    cached[12] = d_out;
    attr_done = true;
  }
  fused_kernel<<<NCTA + 4, NTHREADS, SM_TOTAL>>>(prm);
}
```

```cpp
#include <cuda_runtime.h>
#include <cuda_bf16.h>
#include <cuda.h>
#include <stdint.h>

typedef __nv_bfloat16 bf16;

constexpr int LSEQ = 2048;
constexpr int DM = 512;
constexpr int NCTA = 128;
constexpr int NTHREADS = 512;
#define R_CONS 192
#define R_HELP 104
#define R_AGENT 24
#define GPOS 4
#define TURN0 4
#define TURN1 4

constexpr int PG = 8192;
constexpr int P_R = 25;
__host__ __device__ constexpr int x_page(int half, int c) { return half ? 8 + c : c < 5 ? c : c - 5; }
__host__ __device__ constexpr int w_page(int c) { return (c & 3) < 3 ? 16 + 3 * (c & 3) : c < 4 ? 5 : 8; }
__host__ __device__ constexpr int wo_page(int c) { return c < 5 ? 3 + c : 11 + c; }
__host__ __device__ constexpr int o_page(int half, int pair) { return half ? (pair ? 17 + 2 * pair : 0) : 8 + 2 * pair; }
constexpr int SM_KGB = (P_R + 1) * PG;
constexpr int SM_KC = 27 * PG;
constexpr int KC_STRIDE = 648;
__host__ __device__ constexpr int kc_off(int lc) { return SM_KC + (lc & 1) * 2 * KC_STRIDE + (lc < 2 ? 3328 : 0); }
constexpr int SM_KGT = SM_KC + 3328 + 2592;
constexpr int SM_CS = SM_KGT + 2048;
constexpr int SM_RED = SM_CS + 768;
constexpr int SM_EP = SM_RED + 16;
constexpr int SM_STG = SM_RED + 32;
constexpr int SM_BAR = SM_STG + 1024;
constexpr int SM_TS = SM_BAR + 768;
constexpr int SM_TOTAL = SM_TS + 512;
static_assert(SM_TOTAL <= 232448 && SM_STG % 16 == 0 && SM_KGT % 16 == 0, "shared memory");

constexpr int CV_UH = 140 * 16;
__host__ __device__ constexpr int cv_u(int lc) { return (8 + 2 * lc) * PG; }
__host__ __device__ constexpr int cv_pe(int lc) { return cv_u(lc) + 4480; }
__host__ __device__ constexpr int cv_pb1(int lc, int w) { return w ? cv_u(lc) + 8960 + (w - 1) * 2048 : 7 * PG + lc * 2048; }
__host__ __device__ constexpr int cv_wt(int lc) { return cv_u(lc) + 15104; }
__host__ __device__ constexpr int cv_dump(int lc) { return cv_u(lc) + 16256; }
__host__ __device__ constexpr int cv_pb0(int lc, int w) { return lc * PG + w * 2048; }
__host__ __device__ constexpr int cv_se(int lc) { return 4 * PG + lc * 4096; }
__host__ __device__ constexpr int cv_so(int lc) { return cv_se(lc) + 2048; }
__host__ __device__ constexpr int cv_pf(int lc) { return 6 * PG + lc * 2048; }
__host__ __device__ constexpr int cv_x(int half, int lc) { return (P_R + half) * PG + lc * 2048; }
__host__ __device__ constexpr int cv_chan(int cta, int lc) { return 2 * cta + (lc & 1) + 256 * (lc >> 1); }

enum {
  B_XF = 0,
  B_WF = 16,
  B_OF = 24,
  B_DN = 32,
  B_WOF = 48,
  B_RF = 52,
  B_HF = 54,
  B_OST = 56,
  B_PDONE = 58,
  B_GB = 60,
  B_TF = 62,
  B_CSF = 64,
  B_EP = 65,
  B_ZF = 66,
  B_KG = 67,
  B_FARM = 68,
  B_Z0 = 69,
  B_PE = 70,
  B_U = 71,
  B_S = 73,
  B_PUB = 74,
  B_R = 77,
  B_END = 80,
  B_SC = 81,
  B_COUNT = 82
};

enum {
  C_CS = 0,
  C_G = 1,
  C_C = 5,
  C_F = 8,
  C_O = 20,
  C_COUNT = 84
};

__device__ unsigned g_cnt[C_COUNT * 32];
__device__ __align__(1024) bf16 g_O[LSEQ * DM];
__device__ __align__(1024) bf16 g_xT[4 * DM * LSEQ];
__device__ __align__(1024) float g_stats[2 * LSEQ * 2];
__device__ __align__(1024) uint2 g_colsum[3 * DM];
__device__ __align__(1024) uint4 g_halo[2 * 32 * 8 * 384];
__device__ __align__(1024) uint4 g_part[2 * 32 * 8 * 64];
#define TS(i) do { } while (0)
#define TSW(k) do { if ((threadIdx.x & 127) == 0) TS(16 + layer * 56 + (threadIdx.x >> 7) * 20 + (k)); } while (0)
#define TSG(k) do { } while (0)

#define LTS(i) do { } while (0)

struct Params {
  CUtensorMap mapX, mapW3, mapO, mapO2, mapXT, mapOut, mapWo;
  const bf16 *wqkv, *a_re, *a_im, *b_re, *b_im, *c_re, *c_im, *log_dt, *dskip;
};

__device__ __forceinline__ uint32_t s32(const void* p) { return (uint32_t)__cvta_generic_to_shared(p); }
__device__ __forceinline__ void mbar_init(uint32_t b, int c) { asm volatile("mbarrier.init.shared::cta.b64 [%0], %1;" ::"r"(b), "r"(c) : "memory"); }
__device__ __forceinline__ void mbar_expect(uint32_t b, int bytes) { asm volatile("mbarrier.arrive.expect_tx.shared::cta.b64 _, [%0], %1;" ::"r"(b), "r"(bytes) : "memory"); }
__device__ __forceinline__ void mbar_arrive(uint32_t b) { asm volatile("mbarrier.arrive.shared::cta.b64 _, [%0];" ::"r"(b) : "memory"); }
__device__ __forceinline__ void mbar_wait(uint32_t b, int parity) {
  asm volatile("{\n.reg .pred p;\nWAIT_LOOP:\nmbarrier.try_wait.parity.shared::cta.b64 p, [%0], %1;\n@p bra WAIT_DONE;\nbra WAIT_LOOP;\nWAIT_DONE:\n}" ::"r"(b), "r"(parity) : "memory");
}
__device__ __forceinline__ bool mbar_test(uint32_t b, int parity) {
  uint32_t ok;
  asm volatile("{\n.reg .pred p;\nmbarrier.test_wait.parity.shared::cta.b64 p, [%1], %2;\nselp.u32 %0, 1, 0, p;\n}" : "=r"(ok) : "r"(b), "r"(parity) : "memory");
  return ok != 0;
}
__device__ __forceinline__ int opaque_tid() { int v; asm volatile("mov.u32 %0, %%tid.x;" : "=r"(v)); return v; }
__device__ __forceinline__ bool elect_one() {
  uint32_t r;
  asm volatile("{\n.reg .pred p;\nelect.sync _|p, 0xffffffff;\nselp.u32 %0, 1, 0, p;\n}" : "=r"(r));
  return r != 0;
}
__device__ __forceinline__ void tma_ld(uint32_t dst, const CUtensorMap* m, int c0, int c1, uint32_t bar) {
  asm volatile("cp.async.bulk.tensor.2d.shared::cluster.global.mbarrier::complete_tx::bytes [%0], [%1, {%3, %4}], [%2];"
               ::"r"(dst), "l"(m), "r"(bar), "r"(c0), "r"(c1) : "memory");
}
__device__ __forceinline__ void tma_ld3(uint32_t dst, const CUtensorMap* m, int c0, int c1, int c2, uint32_t bar) {
  asm volatile("cp.async.bulk.tensor.3d.shared::cluster.global.mbarrier::complete_tx::bytes [%0], [%1, {%3, %4, %5}], [%2];"
               ::"r"(dst), "l"(m), "r"(bar), "r"(c0), "r"(c1), "r"(c2) : "memory");
}
__device__ __forceinline__ void tma_prefetch2(const CUtensorMap* m, int c0, int c1) {
  asm volatile("cp.async.bulk.prefetch.tensor.2d.L2.global.tile [%0, {%1, %2}];" ::"l"(m), "r"(c0), "r"(c1) : "memory");
}
__device__ __forceinline__ void tma_prefetch3(const CUtensorMap* m, int c0, int c1, int c2) {
  asm volatile("cp.async.bulk.prefetch.tensor.3d.L2.global.tile [%0, {%1, %2, %3}];" ::"l"(m), "r"(c0), "r"(c1), "r"(c2) : "memory");
}
__device__ __forceinline__ void tma_st(const CUtensorMap* m, int c0, int c1, uint32_t src) {
  asm volatile("cp.async.bulk.tensor.2d.global.shared::cta.bulk_group [%0, {%2, %3}], [%1];" ::"l"(m), "r"(src), "r"(c0), "r"(c1) : "memory");
}
__device__ __forceinline__ void bulk_ld(uint32_t dst, const void* src, int bytes, uint32_t bar) {
  asm volatile("cp.async.bulk.shared::cluster.global.mbarrier::complete_tx::bytes [%0], [%1], %2, [%3];" ::"r"(dst), "l"(src), "r"(bytes), "r"(bar) : "memory");
}
__device__ __forceinline__ void bulk_st(void* dst, uint32_t src, int bytes) {
  asm volatile("cp.async.bulk.global.shared::cta.bulk_group [%0], [%1], %2;" ::"l"(dst), "r"(src), "r"(bytes) : "memory");
}
__device__ __forceinline__ void bulk_red_add_f32(void* dst, uint32_t src, int bytes) {
  asm volatile("cp.reduce.async.bulk.global.shared::cta.bulk_group.add.f32 [%0], [%1], %2;" ::"l"(dst), "r"(src), "r"(bytes) : "memory");
}
__device__ __forceinline__ void bulk_commit() { asm volatile("cp.async.bulk.commit_group;" ::: "memory"); }
__device__ __forceinline__ void bulk_wait_all() { asm volatile("cp.async.bulk.wait_group 0;" ::: "memory"); }
__device__ __forceinline__ void fence_async_smem() { asm volatile("fence.proxy.async.shared::cta;" ::: "memory"); }
__device__ __forceinline__ void fence_async_global() { asm volatile("fence.proxy.async.global;" ::: "memory"); }
__device__ __forceinline__ void bar_sync(int id, int n) { asm volatile("bar.sync %0, %1;" ::"r"(id), "r"(n) : "memory"); }
__device__ __forceinline__ void bar_arrive(int id, int n) { asm volatile("bar.arrive %0, %1;" ::"r"(id), "r"(n) : "memory"); }
__device__ __forceinline__ void wg_fence() { asm volatile("wgmma.fence.sync.aligned;" ::: "memory"); }
__device__ __forceinline__ void wg_commit() { asm volatile("wgmma.commit_group.sync.aligned;" ::: "memory"); }
template <int N> __device__ __forceinline__ void wg_wait() { asm volatile("wgmma.wait_group.sync.aligned %0;" ::"n"(N) : "memory"); }
__device__ __forceinline__ uint64_t mkdesc(uint32_t addr, uint32_t lbo, uint32_t sbo, int sw) {
  return (uint64_t)((addr & 0x3FFFF) >> 4) | ((uint64_t)(lbo >> 4) << 16) | ((uint64_t)(sbo >> 4) << 32) | ((uint64_t)sw << 62);
}
__device__ __forceinline__ void ldsm4(uint32_t* r, uint32_t a) {
  asm volatile("ldmatrix.sync.aligned.m8n8.x4.shared.b16 {%0,%1,%2,%3}, [%4];" : "=r"(r[0]), "=r"(r[1]), "=r"(r[2]), "=r"(r[3]) : "r"(a) : "memory");
}
__device__ __forceinline__ void ldsm4t(uint32_t* r, uint32_t a) {
  asm volatile("ldmatrix.sync.aligned.m8n8.x4.trans.shared.b16 {%0,%1,%2,%3}, [%4];" : "=r"(r[0]), "=r"(r[1]), "=r"(r[2]), "=r"(r[3]) : "r"(a) : "memory");
}
__device__ __forceinline__ void stsm4(uint32_t a, uint32_t r0, uint32_t r1, uint32_t r2, uint32_t r3) {
  asm volatile("stmatrix.sync.aligned.m8n8.x4.shared.b16 [%0], {%1,%2,%3,%4};" ::"r"(a), "r"(r0), "r"(r1), "r"(r2), "r"(r3) : "memory");
}
__device__ __forceinline__ void stsm4t(uint32_t a, uint32_t r0, uint32_t r1, uint32_t r2, uint32_t r3) {
  asm volatile("stmatrix.sync.aligned.m8n8.x4.trans.shared.b16 [%0], {%1,%2,%3,%4};" ::"r"(a), "r"(r0), "r"(r1), "r"(r2), "r"(r3) : "memory");
}
__device__ __forceinline__ uint32_t movm_t(uint32_t a) { uint32_t r; asm volatile("movmatrix.sync.aligned.m8n8.trans.b16 %0, %1;" : "=r"(r) : "r"(a)); return r; }
__device__ __forceinline__ uint32_t lds32(uint32_t a) { uint32_t v; asm volatile("ld.shared.b32 %0, [%1];" : "=r"(v) : "r"(a) : "memory"); return v; }
__device__ __forceinline__ float2 lds64f(uint32_t a) { float2 v; asm volatile("ld.shared.v2.f32 {%0,%1}, [%2];" : "=f"(v.x), "=f"(v.y) : "r"(a) : "memory"); return v; }
__device__ __forceinline__ float4 lds128f(uint32_t a) { float4 v; asm volatile("ld.shared.v4.f32 {%0,%1,%2,%3}, [%4];" : "=f"(v.x), "=f"(v.y), "=f"(v.z), "=f"(v.w) : "r"(a) : "memory"); return v; }
__device__ __forceinline__ uint4 lds128(uint32_t a) { uint4 v; asm volatile("ld.shared.v4.b32 {%0,%1,%2,%3}, [%4];" : "=r"(v.x), "=r"(v.y), "=r"(v.z), "=r"(v.w) : "r"(a) : "memory"); return v; }
__device__ __forceinline__ void sts128(uint32_t a, uint4 v) { asm volatile("st.shared.v4.b32 [%0], {%1,%2,%3,%4};" ::"r"(a), "r"(v.x), "r"(v.y), "r"(v.z), "r"(v.w) : "memory"); }
__device__ __forceinline__ void sts128f(uint32_t a, float x, float y, float z, float w) { asm volatile("st.shared.v4.f32 [%0], {%1,%2,%3,%4};" ::"r"(a), "f"(x), "f"(y), "f"(z), "f"(w) : "memory"); }
__device__ __forceinline__ void sts32f(uint32_t a, float v) { asm volatile("st.shared.f32 [%0], %1;" ::"r"(a), "f"(v) : "memory"); }
__device__ __forceinline__ void sts16(uint32_t a, uint16_t v) { asm volatile("st.shared.u16 [%0], %1;" ::"r"(a), "h"(v) : "memory"); }
__device__ __forceinline__ uint32_t lds16(uint32_t a) { uint16_t v; asm volatile("ld.shared.u16 %0, [%1];" : "=h"(v) : "r"(a) : "memory"); return v; }
__device__ __forceinline__ uint32_t packbf(float lo, float hi) { uint32_t r; asm("cvt.rn.bf16x2.f32 %0, %1, %2;" : "=r"(r) : "f"(hi), "f"(lo)); return r; }
__device__ __forceinline__ float bf_lo(uint32_t v) { return __uint_as_float(v << 16); }
__device__ __forceinline__ float bf_hi(uint32_t v) { return __uint_as_float(v & 0xffff0000u); }
__device__ __forceinline__ float ex2(float x) { float r; asm("ex2.approx.ftz.f32 %0, %1;" : "=f"(r) : "f"(x)); return r; }
__device__ __forceinline__ float rsqrt_approx(float x) { float r; asm("rsqrt.approx.ftz.f32 %0, %1;" : "=f"(r) : "f"(x)); return r; }
__device__ __forceinline__ float rcp_approx(float x) { float r; asm("rcp.approx.ftz.f32 %0, %1;" : "=f"(r) : "f"(x)); return r; }
__device__ __forceinline__ void mma_bf16(float* d, const uint32_t* a, uint32_t b0, uint32_t b1) {
  asm("mma.sync.aligned.m16n8k16.row.col.f32.bf16.bf16.f32 {%0,%1,%2,%3}, {%4,%5,%6,%7}, {%8,%9}, {%0,%1,%2,%3};"
               : "+f"(d[0]), "+f"(d[1]), "+f"(d[2]), "+f"(d[3]) : "r"(a[0]), "r"(a[1]), "r"(a[2]), "r"(a[3]), "r"(b0), "r"(b1));
}
__device__ __forceinline__ void mma_tf32(float* d, float a0, float a1, float a2, float a3, float b0, float b1) {
  asm("mma.sync.aligned.m16n8k8.row.col.f32.tf32.tf32.f32 {%0,%1,%2,%3}, {%4,%5,%6,%7}, {%8,%9}, {%0,%1,%2,%3};"
               : "+f"(d[0]), "+f"(d[1]), "+f"(d[2]), "+f"(d[3])
               : "r"(__float_as_uint(a0)), "r"(__float_as_uint(a1)), "r"(__float_as_uint(a2)), "r"(__float_as_uint(a3)),
                 "r"(__float_as_uint(b0)), "r"(__float_as_uint(b1)));
}
__device__ __forceinline__ void red_release(unsigned* p) { asm volatile("red.release.gpu.global.add.u32 [%0], 1;" ::"l"(p) : "memory"); }
__device__ __forceinline__ void red_relaxed(unsigned* p) { asm volatile("red.relaxed.gpu.global.add.u32 [%0], 1;" ::"l"(p) : "memory"); }
__device__ __forceinline__ unsigned ld_relaxed(const unsigned* p) { unsigned v; asm volatile("ld.relaxed.gpu.global.u32 %0, [%1];" : "=r"(v) : "l"(p) : "memory"); return v; }
__device__ __forceinline__ void spin_until(const unsigned* p, unsigned target) {
  int it = 0;
  while ((int)(ld_relaxed(p) - target) < 0) {
    if (++it > (1 << 23)) __trap();
  }
}
__device__ __forceinline__ uint4 ldcg128(const void* p) { uint4 v; asm volatile("ld.global.cg.v4.b32 {%0,%1,%2,%3}, [%4];" : "=r"(v.x), "=r"(v.y), "=r"(v.z), "=r"(v.w) : "l"(p) : "memory"); return v; }
__device__ __forceinline__ uint4 ld_tagged(const uint4* p) { uint4 v; asm volatile("ld.relaxed.gpu.global.v4.u32 {%0,%1,%2,%3}, [%4];" : "=r"(v.x), "=r"(v.y), "=r"(v.z), "=r"(v.w) : "l"(p) : "memory"); return v; }
__device__ __forceinline__ void st_tagged(uint4* p, uint32_t a, uint32_t b, uint32_t tag) { asm volatile("st.relaxed.gpu.global.v4.u32 [%0], {%1,%2,%3,%2};" ::"l"(p), "r"(a), "r"(tag), "r"(b) : "memory"); }
__device__ __forceinline__ void st_tagged3(uint4* p, uint32_t a, uint32_t b, uint32_t c, uint32_t tag) { asm volatile("st.relaxed.gpu.global.v4.u32 [%0], {%1,%2,%3,%4};" ::"l"(p), "r"(a), "r"(b), "r"(c), "r"(tag) : "memory"); }
__device__ __forceinline__ uint4 poll_tagged(const uint4* p, uint32_t tag) {
  uint4 v = ld_tagged(p);
  int it = 0;
  while (v.y != tag || v.w != tag) {
    if (++it > (1 << 22)) __trap();
    v = ld_tagged(p);
  }
  return v;
}
__device__ __forceinline__ uint32_t hadd2(uint32_t a, uint32_t b) { uint32_t r; asm("add.rn.bf16x2 %0, %1, %2;" : "=r"(r) : "r"(a), "r"(b)); return r; }
__device__ __forceinline__ uint32_t hmul2(uint32_t a, uint32_t b) { uint32_t r; asm("mul.rn.bf16x2 %0, %1, %2;" : "=r"(r) : "r"(a), "r"(b)); return r; }

__device__ __forceinline__ uint32_t hfma2(uint32_t a, uint32_t b, uint32_t c) { uint32_t r; asm("fma.rn.bf16x2 %0, %1, %2, %3;" : "=r"(r) : "r"(a), "r"(b), "r"(c)); return r; }
__device__ __forceinline__ void sts32(uint32_t a, uint32_t v) { asm volatile("st.shared.u32 [%0], %1;" ::"r"(a), "r"(v) : "memory"); }

template <int N> __device__ __forceinline__ void acc_fence(float* a) {
#pragma unroll
  for (int i = 0; i < N; i++) asm volatile("" : "+f"(a[i]) :: "memory");
}

template<int N,int TB> __device__ __forceinline__ void wgmma_rs(float* d, const uint32_t* a, uint64_t db, int sd);
template<int N,int TA,int TB> __device__ __forceinline__ void wgmma_ss(float* d, uint64_t da, uint64_t db, int sd);
template<> __device__ __forceinline__ void wgmma_rs<64,0>(float* d, const uint32_t* a, uint64_t db, int sd) {
  asm volatile("{\n.reg .pred p;\nsetp.ne.b32 p, %37, 0;\nwgmma.mma_async.sync.aligned.m64n64k16.f32.bf16.bf16 {%0,%1,%2,%3,%4,%5,%6,%7,%8,%9,%10,%11,%12,%13,%14,%15,%16,%17,%18,%19,%20,%21,%22,%23,%24,%25,%26,%27,%28,%29,%30,%31}, {%32,%33,%34,%35}, %36, p, 1, 1, 0;\n}\n"
   : "+f"(d[0]),"+f"(d[1]),"+f"(d[2]),"+f"(d[3]),"+f"(d[4]),"+f"(d[5]),"+f"(d[6]),"+f"(d[7]),"+f"(d[8]),"+f"(d[9]),"+f"(d[10]),"+f"(d[11]),"+f"(d[12]),"+f"(d[13]),"+f"(d[14]),"+f"(d[15]),"+f"(d[16]),"+f"(d[17]),"+f"(d[18]),"+f"(d[19]),"+f"(d[20]),"+f"(d[21]),"+f"(d[22]),"+f"(d[23]),"+f"(d[24]),"+f"(d[25]),"+f"(d[26]),"+f"(d[27]),"+f"(d[28]),"+f"(d[29]),"+f"(d[30]),"+f"(d[31])
   : "r"(a[0]), "r"(a[1]), "r"(a[2]), "r"(a[3]), "l"(db), "r"(sd));
}
template<> __device__ __forceinline__ void wgmma_rs<56,0>(float* d, const uint32_t* a, uint64_t db, int sd) {
  asm volatile("{\n.reg .pred p;\nsetp.ne.b32 p, %33, 0;\nwgmma.mma_async.sync.aligned.m64n56k16.f32.bf16.bf16 {%0,%1,%2,%3,%4,%5,%6,%7,%8,%9,%10,%11,%12,%13,%14,%15,%16,%17,%18,%19,%20,%21,%22,%23,%24,%25,%26,%27}, {%28,%29,%30,%31}, %32, p, 1, 1, 0;\n}\n"
   : "+f"(d[0]),"+f"(d[1]),"+f"(d[2]),"+f"(d[3]),"+f"(d[4]),"+f"(d[5]),"+f"(d[6]),"+f"(d[7]),"+f"(d[8]),"+f"(d[9]),"+f"(d[10]),"+f"(d[11]),"+f"(d[12]),"+f"(d[13]),"+f"(d[14]),"+f"(d[15]),"+f"(d[16]),"+f"(d[17]),"+f"(d[18]),"+f"(d[19]),"+f"(d[20]),"+f"(d[21]),"+f"(d[22]),"+f"(d[23]),"+f"(d[24]),"+f"(d[25]),"+f"(d[26]),"+f"(d[27])
   : "r"(a[0]), "r"(a[1]), "r"(a[2]), "r"(a[3]), "l"(db), "r"(sd));
}
template<> __device__ __forceinline__ void wgmma_rs<48,0>(float* d, const uint32_t* a, uint64_t db, int sd) {
  asm volatile("{\n.reg .pred p;\nsetp.ne.b32 p, %29, 0;\nwgmma.mma_async.sync.aligned.m64n48k16.f32.bf16.bf16 {%0,%1,%2,%3,%4,%5,%6,%7,%8,%9,%10,%11,%12,%13,%14,%15,%16,%17,%18,%19,%20,%21,%22,%23}, {%24,%25,%26,%27}, %28, p, 1, 1, 0;\n}\n"
   : "+f"(d[0]),"+f"(d[1]),"+f"(d[2]),"+f"(d[3]),"+f"(d[4]),"+f"(d[5]),"+f"(d[6]),"+f"(d[7]),"+f"(d[8]),"+f"(d[9]),"+f"(d[10]),"+f"(d[11]),"+f"(d[12]),"+f"(d[13]),"+f"(d[14]),"+f"(d[15]),"+f"(d[16]),"+f"(d[17]),"+f"(d[18]),"+f"(d[19]),"+f"(d[20]),"+f"(d[21]),"+f"(d[22]),"+f"(d[23])
   : "r"(a[0]), "r"(a[1]), "r"(a[2]), "r"(a[3]), "l"(db), "r"(sd));
}
template<> __device__ __forceinline__ void wgmma_rs<40,0>(float* d, const uint32_t* a, uint64_t db, int sd) {
  asm volatile("{\n.reg .pred p;\nsetp.ne.b32 p, %25, 0;\nwgmma.mma_async.sync.aligned.m64n40k16.f32.bf16.bf16 {%0,%1,%2,%3,%4,%5,%6,%7,%8,%9,%10,%11,%12,%13,%14,%15,%16,%17,%18,%19}, {%20,%21,%22,%23}, %24, p, 1, 1, 0;\n}\n"
   : "+f"(d[0]),"+f"(d[1]),"+f"(d[2]),"+f"(d[3]),"+f"(d[4]),"+f"(d[5]),"+f"(d[6]),"+f"(d[7]),"+f"(d[8]),"+f"(d[9]),"+f"(d[10]),"+f"(d[11]),"+f"(d[12]),"+f"(d[13]),"+f"(d[14]),"+f"(d[15]),"+f"(d[16]),"+f"(d[17]),"+f"(d[18]),"+f"(d[19])
   : "r"(a[0]), "r"(a[1]), "r"(a[2]), "r"(a[3]), "l"(db), "r"(sd));
}
template<> __device__ __forceinline__ void wgmma_rs<32,0>(float* d, const uint32_t* a, uint64_t db, int sd) {
  asm volatile("{\n.reg .pred p;\nsetp.ne.b32 p, %21, 0;\nwgmma.mma_async.sync.aligned.m64n32k16.f32.bf16.bf16 {%0,%1,%2,%3,%4,%5,%6,%7,%8,%9,%10,%11,%12,%13,%14,%15}, {%16,%17,%18,%19}, %20, p, 1, 1, 0;\n}\n"
   : "+f"(d[0]),"+f"(d[1]),"+f"(d[2]),"+f"(d[3]),"+f"(d[4]),"+f"(d[5]),"+f"(d[6]),"+f"(d[7]),"+f"(d[8]),"+f"(d[9]),"+f"(d[10]),"+f"(d[11]),"+f"(d[12]),"+f"(d[13]),"+f"(d[14]),"+f"(d[15])
   : "r"(a[0]), "r"(a[1]), "r"(a[2]), "r"(a[3]), "l"(db), "r"(sd));
}
template<> __device__ __forceinline__ void wgmma_rs<24,0>(float* d, const uint32_t* a, uint64_t db, int sd) {
  asm volatile("{\n.reg .pred p;\nsetp.ne.b32 p, %17, 0;\nwgmma.mma_async.sync.aligned.m64n24k16.f32.bf16.bf16 {%0,%1,%2,%3,%4,%5,%6,%7,%8,%9,%10,%11}, {%12,%13,%14,%15}, %16, p, 1, 1, 0;\n}\n"
   : "+f"(d[0]),"+f"(d[1]),"+f"(d[2]),"+f"(d[3]),"+f"(d[4]),"+f"(d[5]),"+f"(d[6]),"+f"(d[7]),"+f"(d[8]),"+f"(d[9]),"+f"(d[10]),"+f"(d[11])
   : "r"(a[0]), "r"(a[1]), "r"(a[2]), "r"(a[3]), "l"(db), "r"(sd));
}
template<> __device__ __forceinline__ void wgmma_rs<16,0>(float* d, const uint32_t* a, uint64_t db, int sd) {
  asm volatile("{\n.reg .pred p;\nsetp.ne.b32 p, %13, 0;\nwgmma.mma_async.sync.aligned.m64n16k16.f32.bf16.bf16 {%0,%1,%2,%3,%4,%5,%6,%7}, {%8,%9,%10,%11}, %12, p, 1, 1, 0;\n}\n"
   : "+f"(d[0]),"+f"(d[1]),"+f"(d[2]),"+f"(d[3]),"+f"(d[4]),"+f"(d[5]),"+f"(d[6]),"+f"(d[7])
   : "r"(a[0]), "r"(a[1]), "r"(a[2]), "r"(a[3]), "l"(db), "r"(sd));
}
template<> __device__ __forceinline__ void wgmma_rs<8,0>(float* d, const uint32_t* a, uint64_t db, int sd) {
  asm volatile("{\n.reg .pred p;\nsetp.ne.b32 p, %9, 0;\nwgmma.mma_async.sync.aligned.m64n8k16.f32.bf16.bf16 {%0,%1,%2,%3}, {%4,%5,%6,%7}, %8, p, 1, 1, 0;\n}\n"
   : "+f"(d[0]),"+f"(d[1]),"+f"(d[2]),"+f"(d[3])
   : "r"(a[0]), "r"(a[1]), "r"(a[2]), "r"(a[3]), "l"(db), "r"(sd));
}
template<> __device__ __forceinline__ void wgmma_rs<16,1>(float* d, const uint32_t* a, uint64_t db, int sd) {
  asm volatile("{\n.reg .pred p;\nsetp.ne.b32 p, %13, 0;\nwgmma.mma_async.sync.aligned.m64n16k16.f32.bf16.bf16 {%0,%1,%2,%3,%4,%5,%6,%7}, {%8,%9,%10,%11}, %12, p, 1, 1, 1;\n}\n"
   : "+f"(d[0]),"+f"(d[1]),"+f"(d[2]),"+f"(d[3]),"+f"(d[4]),"+f"(d[5]),"+f"(d[6]),"+f"(d[7])
   : "r"(a[0]), "r"(a[1]), "r"(a[2]), "r"(a[3]), "l"(db), "r"(sd));
}
template<> __device__ __forceinline__ void wgmma_ss<64,0,1>(float* d, uint64_t da, uint64_t db, int sd) {
  asm volatile("{\n.reg .pred p;\nsetp.ne.b32 p, %34, 0;\nwgmma.mma_async.sync.aligned.m64n64k16.f32.bf16.bf16 {%0,%1,%2,%3,%4,%5,%6,%7,%8,%9,%10,%11,%12,%13,%14,%15,%16,%17,%18,%19,%20,%21,%22,%23,%24,%25,%26,%27,%28,%29,%30,%31}, %32, %33, p, 1, 1, 0, 1;\n}\n"
   : "+f"(d[0]),"+f"(d[1]),"+f"(d[2]),"+f"(d[3]),"+f"(d[4]),"+f"(d[5]),"+f"(d[6]),"+f"(d[7]),"+f"(d[8]),"+f"(d[9]),"+f"(d[10]),"+f"(d[11]),"+f"(d[12]),"+f"(d[13]),"+f"(d[14]),"+f"(d[15]),"+f"(d[16]),"+f"(d[17]),"+f"(d[18]),"+f"(d[19]),"+f"(d[20]),"+f"(d[21]),"+f"(d[22]),"+f"(d[23]),"+f"(d[24]),"+f"(d[25]),"+f"(d[26]),"+f"(d[27]),"+f"(d[28]),"+f"(d[29]),"+f"(d[30]),"+f"(d[31])
   : "l"(da), "l"(db), "r"(sd));
}
template<> __device__ __forceinline__ void wgmma_ss<192,0,1>(float* d, uint64_t da, uint64_t db, int sd) {
  asm volatile("{\n.reg .pred p;\nsetp.ne.b32 p, %98, 0;\nwgmma.mma_async.sync.aligned.m64n192k16.f32.bf16.bf16 {%0,%1,%2,%3,%4,%5,%6,%7,%8,%9,%10,%11,%12,%13,%14,%15,%16,%17,%18,%19,%20,%21,%22,%23,%24,%25,%26,%27,%28,%29,%30,%31,%32,%33,%34,%35,%36,%37,%38,%39,%40,%41,%42,%43,%44,%45,%46,%47,%48,%49,%50,%51,%52,%53,%54,%55,%56,%57,%58,%59,%60,%61,%62,%63,%64,%65,%66,%67,%68,%69,%70,%71,%72,%73,%74,%75,%76,%77,%78,%79,%80,%81,%82,%83,%84,%85,%86,%87,%88,%89,%90,%91,%92,%93,%94,%95}, %96, %97, p, 1, 1, 0, 1;\n}\n"
   : "+f"(d[0]),"+f"(d[1]),"+f"(d[2]),"+f"(d[3]),"+f"(d[4]),"+f"(d[5]),"+f"(d[6]),"+f"(d[7]),"+f"(d[8]),"+f"(d[9]),"+f"(d[10]),"+f"(d[11]),"+f"(d[12]),"+f"(d[13]),"+f"(d[14]),"+f"(d[15]),"+f"(d[16]),"+f"(d[17]),"+f"(d[18]),"+f"(d[19]),"+f"(d[20]),"+f"(d[21]),"+f"(d[22]),"+f"(d[23]),"+f"(d[24]),"+f"(d[25]),"+f"(d[26]),"+f"(d[27]),"+f"(d[28]),"+f"(d[29]),"+f"(d[30]),"+f"(d[31]),"+f"(d[32]),"+f"(d[33]),"+f"(d[34]),"+f"(d[35]),"+f"(d[36]),"+f"(d[37]),"+f"(d[38]),"+f"(d[39]),"+f"(d[40]),"+f"(d[41]),"+f"(d[42]),"+f"(d[43]),"+f"(d[44]),"+f"(d[45]),"+f"(d[46]),"+f"(d[47]),"+f"(d[48]),"+f"(d[49]),"+f"(d[50]),"+f"(d[51]),"+f"(d[52]),"+f"(d[53]),"+f"(d[54]),"+f"(d[55]),"+f"(d[56]),"+f"(d[57]),"+f"(d[58]),"+f"(d[59]),"+f"(d[60]),"+f"(d[61]),"+f"(d[62]),"+f"(d[63]),"+f"(d[64]),"+f"(d[65]),"+f"(d[66]),"+f"(d[67]),"+f"(d[68]),"+f"(d[69]),"+f"(d[70]),"+f"(d[71]),"+f"(d[72]),"+f"(d[73]),"+f"(d[74]),"+f"(d[75]),"+f"(d[76]),"+f"(d[77]),"+f"(d[78]),"+f"(d[79]),"+f"(d[80]),"+f"(d[81]),"+f"(d[82]),"+f"(d[83]),"+f"(d[84]),"+f"(d[85]),"+f"(d[86]),"+f"(d[87]),"+f"(d[88]),"+f"(d[89]),"+f"(d[90]),"+f"(d[91]),"+f"(d[92]),"+f"(d[93]),"+f"(d[94]),"+f"(d[95])
   : "l"(da), "l"(db), "r"(sd));
}
template<> __device__ __forceinline__ void wgmma_ss<192,1,1>(float* d, uint64_t da, uint64_t db, int sd) {
  asm volatile("{\n.reg .pred p;\nsetp.ne.b32 p, %98, 0;\nwgmma.mma_async.sync.aligned.m64n192k16.f32.bf16.bf16 {%0,%1,%2,%3,%4,%5,%6,%7,%8,%9,%10,%11,%12,%13,%14,%15,%16,%17,%18,%19,%20,%21,%22,%23,%24,%25,%26,%27,%28,%29,%30,%31,%32,%33,%34,%35,%36,%37,%38,%39,%40,%41,%42,%43,%44,%45,%46,%47,%48,%49,%50,%51,%52,%53,%54,%55,%56,%57,%58,%59,%60,%61,%62,%63,%64,%65,%66,%67,%68,%69,%70,%71,%72,%73,%74,%75,%76,%77,%78,%79,%80,%81,%82,%83,%84,%85,%86,%87,%88,%89,%90,%91,%92,%93,%94,%95}, %96, %97, p, 1, 1, 1, 1;\n}\n"
   : "+f"(d[0]),"+f"(d[1]),"+f"(d[2]),"+f"(d[3]),"+f"(d[4]),"+f"(d[5]),"+f"(d[6]),"+f"(d[7]),"+f"(d[8]),"+f"(d[9]),"+f"(d[10]),"+f"(d[11]),"+f"(d[12]),"+f"(d[13]),"+f"(d[14]),"+f"(d[15]),"+f"(d[16]),"+f"(d[17]),"+f"(d[18]),"+f"(d[19]),"+f"(d[20]),"+f"(d[21]),"+f"(d[22]),"+f"(d[23]),"+f"(d[24]),"+f"(d[25]),"+f"(d[26]),"+f"(d[27]),"+f"(d[28]),"+f"(d[29]),"+f"(d[30]),"+f"(d[31]),"+f"(d[32]),"+f"(d[33]),"+f"(d[34]),"+f"(d[35]),"+f"(d[36]),"+f"(d[37]),"+f"(d[38]),"+f"(d[39]),"+f"(d[40]),"+f"(d[41]),"+f"(d[42]),"+f"(d[43]),"+f"(d[44]),"+f"(d[45]),"+f"(d[46]),"+f"(d[47]),"+f"(d[48]),"+f"(d[49]),"+f"(d[50]),"+f"(d[51]),"+f"(d[52]),"+f"(d[53]),"+f"(d[54]),"+f"(d[55]),"+f"(d[56]),"+f"(d[57]),"+f"(d[58]),"+f"(d[59]),"+f"(d[60]),"+f"(d[61]),"+f"(d[62]),"+f"(d[63]),"+f"(d[64]),"+f"(d[65]),"+f"(d[66]),"+f"(d[67]),"+f"(d[68]),"+f"(d[69]),"+f"(d[70]),"+f"(d[71]),"+f"(d[72]),"+f"(d[73]),"+f"(d[74]),"+f"(d[75]),"+f"(d[76]),"+f"(d[77]),"+f"(d[78]),"+f"(d[79]),"+f"(d[80]),"+f"(d[81]),"+f"(d[82]),"+f"(d[83]),"+f"(d[84]),"+f"(d[85]),"+f"(d[86]),"+f"(d[87]),"+f"(d[88]),"+f"(d[89]),"+f"(d[90]),"+f"(d[91]),"+f"(d[92]),"+f"(d[93]),"+f"(d[94]),"+f"(d[95])
   : "l"(da), "l"(db), "r"(sd));
}

template <bool TR>
__device__ __forceinline__ void gemm_section(float* acc, float& mean0, float& mean1, float& rstd0, float& rstd1,
                                             uint32_t sb, int blk, int hg, int wg, int w, int lane) {
  constexpr int layer = TR ? 1 : 0;
  constexpr int TURN = TR ? TURN1 : TURN0;
  constexpr int LSTAT = TURN < 4 ? TURN - 1 : 3;
  const uint32_t bar = sb + SM_BAR;
  const int g = lane >> 2, t = lane & 3;
  const bool leader = (w == 0) && (lane == 0);
  const int statpos = hg < 3 ? 1 : wg ? LSTAT : 2;
  const bool copy = hg >= 3 && wg == 0;
  const int cut = wg ? TURN : 4;
  auto wait_full = [&](int c) {
    mbar_wait(bar + 8 * (B_XF + 8 * wg + c), layer);
    mbar_wait(bar + 8 * (B_WF + c), layer);
  };
  auto peek = [&](int c) {
    const bool x = mbar_test(bar + 8 * (B_XF + 8 * wg + c), layer), y = mbar_test(bar + 8 * (B_WF + c), layer);
    return x && y;
  };
  const uint64_t da0 = mkdesc(sb, TR ? 8192 : 16, 1024, 1), db0 = mkdesc(sb, 8192, 1024, 1);
  uint32_t xt = wg ? 0xfedcba98u : 0x21043210u;
  uint64_t wt = 0x0816131005161310ull;
  uint64_t da = da0 + ((xt & 15) << 9), db = db0 + (16 << 9);
  auto issue = [&](int c, int first) {
    TSG(2 * c);
    wg_fence();
#pragma unroll
    for (int ks = 0; ks < 4; ks++) wgmma_ss<192, TR ? 1 : 0, 1>(acc, da + (TR ? ks * 128 : ks * 2), db + ks * 128, !first || ks != 0);
    wg_commit();
    xt >>= 4; wt >>= 8;
    da = da0 + ((xt & 15) << 9); db = db0 + (((uint32_t)wt & 31) << 9);
    TSG(2 * c + 1);
  };
  uint32_t tag = 0;
  wait_full(0);
  bool ready = peek(1);
  issue(0, 1);
  TSW(0);
#pragma unroll 1
  for (int c = 1; c < cut; c++) {
    if (!ready) wait_full(c);
    issue(c, 0);
    ready = peek(c + 1);
    wg_wait<1>();
    if (leader) mbar_arrive(bar + 8 * (B_DN + 8 * wg + c - 1));
    if (wg == 1 && c == cut - 1) {
      wg_wait<0>();
      if (leader) mbar_arrive(bar + 8 * (B_DN + 8 + c));
    }
    if (c == statpos) {
      mbar_wait(bar + 8 * B_EP, 0);
      tag = 2 * lds32(sb + SM_EP) + layer + 1;
      mbar_wait(bar + 8 * (copy ? B_SC : B_XF + 8 * wg + hg), layer);
      uint32_t A[16];
      const uint32_t xb = sb + (copy ? P_R : 8 * wg + hg) * PG;
#pragma unroll
      for (int ks = 0; ks < 4; ks++) {
        if (!TR) {
          const int row = 16 * w + (lane & 15), kc = 2 * ks + (lane >> 4);
          ldsm4(&A[4 * ks], xb + row * 128 + ((kc ^ (row & 7)) << 4));
        } else {
          const int k = 16 * ks + (lane & 7) + 8 * (lane >> 4), pc = 2 * w + ((lane >> 3) & 1);
          ldsm4t(&A[4 * ks], xb + k * 128 + ((pc ^ (k & 7)) << 4));
        }
      }
      float s0 = 0.f, q0 = 0.f, s1 = 0.f, q1 = 0.f;
#pragma unroll
      for (int i = 0; i < 16; i += 2) {
        const float a = bf_lo(A[i]), b = bf_hi(A[i]), c_ = bf_lo(A[i + 1]), d = bf_hi(A[i + 1]);
        s0 += a + b; q0 = fmaf(a, a, q0); q0 = fmaf(b, b, q0);
        s1 += c_ + d; q1 = fmaf(c_, c_, q1); q1 = fmaf(d, d, q1);
      }
#pragma unroll
      for (int o = 1; o <= 2; o <<= 1) {
        s0 += __shfl_xor_sync(~0u, s0, o); q0 += __shfl_xor_sync(~0u, q0, o);
        s1 += __shfl_xor_sync(~0u, s1, o); q1 += __shfl_xor_sync(~0u, q1, o);
      }
      if (t < 2)
        st_tagged(&g_part[((layer * 32 + blk) * 8 + hg) * 64 + 16 * w + g + 8 * t], __float_as_uint(t ? s1 : s0), __float_as_uint(t ? q1 : q0), tag);
    }
  }
  if (wg == 1) mbar_wait(bar + 8 * (B_DN + GPOS), layer);
  else if (!ready) { wait_full(cut); ready = true; }
  const uint4* psrc = &g_part[((layer * 32 + blk) * 8 + 2 * t) * 64 + 16 * w + g];
  uint4 a0 = ld_tagged(psrc), a1 = ld_tagged(psrc + 8), b0 = ld_tagged(psrc + 64), b1 = ld_tagged(psrc + 72);
  if (wg == 1) {
#pragma unroll 1
    for (int c = cut; c < 8; c++) wait_full(c);
    ready = true;
    bar_sync(5, 256);
  }
#pragma unroll 1
  for (int c = cut; c < 8; c++) {
    if (!ready) wait_full(c);
    issue(c, 0);
    if (wg == 1) {
      wg_wait<2>();
      if (leader && c >= cut + 2) mbar_arrive(bar + 8 * (B_DN + 8 + c - 2));
    } else if (c == 7) {
      bar_arrive(5, 256);
    } else {
      ready = peek(c + 1);
      wg_wait<1>();
      if (leader) mbar_arrive(bar + 8 * (B_DN + c - 1));
    }
  }
  int it = 0;
  while (!__all_sync(~0u, a0.y == tag && a0.w == tag && a1.y == tag && a1.w == tag && b0.y == tag && b0.w == tag && b1.y == tag && b1.w == tag) &&
         ++it < (1 << 20)) {
    a0 = ld_tagged(psrc); a1 = ld_tagged(psrc + 8); b0 = ld_tagged(psrc + 64); b1 = ld_tagged(psrc + 72);
  }
  float s0 = __uint_as_float(a0.x) + __uint_as_float(b0.x), q0 = __uint_as_float(a0.z) + __uint_as_float(b0.z);
  float s1 = __uint_as_float(a1.x) + __uint_as_float(b1.x), q1 = __uint_as_float(a1.z) + __uint_as_float(b1.z);
#pragma unroll
  for (int o = 1; o <= 2; o <<= 1) {
    s0 += __shfl_xor_sync(~0u, s0, o); q0 += __shfl_xor_sync(~0u, q0, o);
    s1 += __shfl_xor_sync(~0u, s1, o); q1 += __shfl_xor_sync(~0u, q1, o);
  }
  mean0 = s0 * (1.f / DM); mean1 = s1 * (1.f / DM);
  rstd0 = rsqrt_approx(fmaxf(q0 * (1.f / DM) - mean0 * mean0, 0.f) + 1e-5f);
  rstd1 = rsqrt_approx(fmaxf(q1 * (1.f / DM) - mean1 * mean1, 0.f) + 1e-5f);
  TSG(16);
  mbar_wait(bar + 8 * B_CSF, 0);
  wg_wait<0>();
  acc_fence<96>(acc);
  if (leader) mbar_arrive(bar + 8 * (B_DN + 8 * wg + 7));
}

__device__ __forceinline__ void attn_phase(const Params& p, uint32_t sb, int layer, int rb, int hg, int wg, int w) {
  const int lane = opaque_tid() & 31;
  const int g = lane >> 2, t = lane & 3;
  const uint32_t bar = sb + SM_BAR;
  const int blk = 16 * wg + rb;
  float acc[96];
  float2 cs[24];
  float mean0, mean1, rstd0, rstd1;
  if (layer) gemm_section<true>(acc, mean0, mean1, rstd0, rstd1, sb, blk, hg, wg, w, lane);
  else gemm_section<false>(acc, mean0, mean1, rstd0, rstd1, sb, blk, hg, wg, w, lane);
  const uint32_t tag = 2 * lds32(sb + SM_EP) + layer + 1;
  TSW(1);
#pragma unroll
  for (int j = 8; j < 24; j++) cs[j] = lds64f(sb + SM_CS + 4 * (8 * j + 2 * t));
  const uint32_t kvx = sb + (wg ? 22 : 0) * PG;

  uint32_t kb[4][8], vb[4][8], qa[4][4];
  {
    const float nm0 = -mean0 * rstd0, nm1 = -mean1 * rstd1;
    const int st_row = 16 * w + (lane & 7) + 8 * ((lane >> 3) & 1);
    const uint32_t st_base = kvx + st_row * 256;
    const bool sender = (w == 3 && blk < 31);
    uint4* halo = &g_halo[((layer * 32 + blk) * 8 + hg) * 384 + lane];
    uint32_t r[4][2][4];
#pragma unroll
    for (int h = 0; h < 4; h++) {
#pragma unroll
      for (int kv = 0; kv < 2; kv++) {
#pragma unroll
        for (int dh = 0; dh < 2; dh++) {
          const int j = 8 + kv * 8 + 2 * h + dh;
          const float2 c2 = cs[j];
          const float v0 = fmaf(acc[4 * j + 0], rstd0, nm0 * c2.x), v1 = fmaf(acc[4 * j + 1], rstd0, nm0 * c2.y);
          const float v2 = fmaf(acc[4 * j + 2], rstd1, nm1 * c2.x), v3 = fmaf(acc[4 * j + 3], rstd1, nm1 * c2.y);
          r[h][kv][2 * dh] = packbf(v0, v1);
          r[h][kv][2 * dh + 1] = packbf(v2, v3);
        }
      }
      if (sender) {
        st_tagged3(halo + (3 * h) * 32, r[h][0][0], r[h][0][1], r[h][0][2], tag);
        st_tagged3(halo + (3 * h + 1) * 32, r[h][0][3], r[h][1][0], r[h][1][1], tag);
        st_tagged3(halo + (3 * h + 2) * 32, r[h][1][2], r[h][1][3], 0u, tag);
      }
    }
#pragma unroll
    for (int j = 0; j < 8; j++) cs[j] = lds64f(sb + SM_CS + 4 * (8 * j + 2 * t));
    mbar_wait(bar + 8 * (B_DN + 7), layer);
#pragma unroll
    for (int h = 0; h < 4; h++) {
#pragma unroll
      for (int kv = 0; kv < 2; kv++) {
        const int chunk = 4 * h + 2 * kv + (lane >> 4);
        stsm4(st_base + (((chunk & 8) | ((chunk ^ st_row) & 7)) << 4), r[h][kv][0], r[h][kv][1], r[h][kv][2], r[h][kv][3]);
      }
      kb[h][4] = r[h][0][0]; kb[h][5] = r[h][0][2]; kb[h][6] = r[h][0][1]; kb[h][7] = r[h][0][3];
      vb[h][4] = movm_t(r[h][1][0]); vb[h][5] = movm_t(r[h][1][1]); vb[h][6] = movm_t(r[h][1][2]); vb[h][7] = movm_t(r[h][1][3]);
    }
#pragma unroll
    for (int h = 0; h < 4; h++) {
#pragma unroll
      for (int dh = 0; dh < 2; dh++) {
        const int j = 2 * h + dh;
        const float2 c2 = cs[j];
        qa[h][2 * dh] = packbf(fmaf(-mean0, c2.x, acc[4 * j + 0]), fmaf(-mean0, c2.y, acc[4 * j + 1]));
        qa[h][2 * dh + 1] = packbf(fmaf(-mean1, c2.x, acc[4 * j + 2]), fmaf(-mean1, c2.y, acc[4 * j + 3]));
      }
    }
  }
  bar_sync(2 + wg, 128);
  TSW(2);
  {
    const uint32_t prev_base = kvx + (16 * w - 16) * 256;
    const int mi = lane >> 3;
    const int r = 8 * (mi >> 1) + (lane & 7), r2 = 8 * (mi & 1) + (lane & 7);
    if (w != 0) {
#pragma unroll
      for (int h = 0; h < 4; h++) {
        const int ch = 4 * h + (mi & 1), ch2 = 4 * h + 2 + (mi >> 1);
        ldsm4(&kb[h][0], prev_base + r * 256 + (((ch & 8) | ((ch ^ r) & 7)) << 4));
        ldsm4t(&vb[h][0], prev_base + r2 * 256 + (((ch2 & 8) | ((ch2 ^ r2) & 7)) << 4));
      }
    } else if (blk > 0) {
      const uint4* src = &g_halo[((layer * 32 + blk - 1) * 8 + hg) * 384 + lane];
      uint4 hv[12];
      int it = 0;
      bool ok;
      do {
        ok = true;
#pragma unroll
        for (int i = 0; i < 12; i++) hv[i] = ld_tagged(src + i * 32);
#pragma unroll
        for (int i = 0; i < 12; i++) ok = ok && hv[i].w == tag;
      } while (!__all_sync(~0u, ok) && ++it < (1 << 20));
#pragma unroll
      for (int h = 0; h < 4; h++) {
        kb[h][0] = hv[3 * h].x; kb[h][1] = hv[3 * h].z; kb[h][2] = hv[3 * h].y; kb[h][3] = hv[3 * h + 1].x;
        vb[h][0] = movm_t(hv[3 * h + 1].y); vb[h][1] = movm_t(hv[3 * h + 1].z);
        vb[h][2] = movm_t(hv[3 * h + 2].x); vb[h][3] = movm_t(hv[3 * h + 2].y);
      }
    } else {
#pragma unroll
      for (int h = 0; h < 4; h++)
#pragma unroll
        for (int k = 0; k < 4; k++) kb[h][k] = vb[h][k] = 0u;
    }
    if (w == 0 && lane == 0) mbar_arrive(bar + 8 * (B_HF + wg));
    TSW(3);
  }
  mbar_wait(bar + 8 * (B_DN + 15), layer);
  TSW(4);

  const bool first = (blk == 0 && w == 0);
  const int e = t - (g >> 1);
  const bool par = g & 1, epos = e >= 1;
  const uint32_t pmask = par ? 0xffff0000u : 0x0000ffffu;
  const uint32_t mB0 = epos ? pmask : 0u, mB1 = epos ? 0u : pmask;
  const float cl2 = 0.25f * 1.4426950408889634f;
  const float sc0 = rstd0 * cl2, sc1 = rstd1 * cl2;
  const float NEG = -INFINITY;
  float vA0[4], vB0[4], vA1[4], vB1[4];
#pragma unroll
  for (int h = 0; h < 4; h++) {
    float S[4][4];
#pragma unroll
    for (int j = 0; j < 4; j++) {
      S[j][0] = S[j][1] = S[j][2] = S[j][3] = 0.f;
      mma_bf16(S[j], qa[h], kb[h][2 * j], kb[h][2 * j + 1]);
    }
    vA0[h] = par ? S[1][1] : S[1][0];
    vB0[h] = epos ? (par ? S[0][1] : S[0][0]) : (par ? S[2][1] : S[2][0]);
    vA1[h] = par ? S[2][3] : S[2][2];
    vB1[h] = epos ? (par ? S[1][3] : S[1][2]) : (par ? S[3][3] : S[3][2]);
    if (first) { vA0[h] = NEG; if (epos) { vB0[h] = NEG; vB1[h] = NEG; } }
  }
  float m0[4], m1[4];
#pragma unroll
  for (int h = 0; h < 4; h++) { m0[h] = fmaxf(vA0[h], vB0[h]); m1[h] = fmaxf(vA1[h], vB1[h]); }
#pragma unroll
  for (int o = 1; o <= 2; o <<= 1) {
#pragma unroll
    for (int h = 0; h < 4; h++) {
      m0[h] = fmaxf(m0[h], __shfl_xor_sync(~0u, m0[h], o));
      m1[h] = fmaxf(m1[h], __shfl_xor_sync(~0u, m1[h], o));
    }
  }
  float O0[4][4], O1[4][4], Z[4][4];
#pragma unroll
  for (int h = 0; h < 4; h++) {
    const float mm0 = -m0[h] * sc0, mm1 = -m1[h] * sc1;
    const float pA0 = ex2(fmaf(vA0[h], sc0, mm0)), pB0 = ex2(fmaf(vB0[h], sc0, mm0));
    const float pA1 = ex2(fmaf(vA1[h], sc1, mm1)), pB1 = ex2(fmaf(vB1[h], sc1, mm1));
    const uint32_t hA0 = packbf(pA0, pA0), hB0 = packbf(pB0, pB0), hA1 = packbf(pA1, pA1), hB1 = packbf(pB1, pB1);
    const uint32_t P0[4] = {hB0 & mB0, 0u, hA0 & pmask, hB1 & mB0};
    const uint32_t P1[4] = {hB0 & mB1, hA1 & pmask, 0u, hB1 & mB1};
#pragma unroll
    for (int k = 0; k < 4; k++) O0[h][k] = O1[h][k] = Z[h][k] = 0.f;
    mma_bf16(O0[h], P0, vb[h][0], vb[h][1]); mma_bf16(O1[h], P0, vb[h][2], vb[h][3]); mma_bf16(Z[h], P0, 0x3f803f80u, 0x3f803f80u);
    mma_bf16(O0[h], P1, vb[h][4], vb[h][5]); mma_bf16(O1[h], P1, vb[h][6], vb[h][7]); mma_bf16(Z[h], P1, 0x3f803f80u, 0x3f803f80u);
  }
  const uint32_t ob = kvx + 2 * PG;
  const int o_row = 16 * w + (lane & 7) + 8 * ((lane >> 3) & 1);
#pragma unroll
  for (int h = 0; h < 4; h++) {
    const float i0 = rcp_approx(Z[h][0]), i1 = rcp_approx(Z[h][2]);
    const int ch = 2 * h + (lane >> 4);
    stsm4(ob + o_row * 128 + ((ch ^ (o_row & 7)) << 4), packbf(O0[h][0] * i0, O0[h][1] * i0), packbf(O0[h][2] * i1, O0[h][3] * i1),
          packbf(O1[h][0] * i0, O1[h][1] * i0), packbf(O1[h][2] * i1, O1[h][3] * i1));
  }
  TSW(5);
  fence_async_smem();
  bar_sync(2 + wg, 128);
  if (w == 0 && elect_one()) {
    tma_st(&p.mapO, hg * 64, blk * 64, ob);
    bulk_commit();
    bulk_wait_all();
    red_relaxed(&g_cnt[(C_O + layer * 32 + blk) * 32]);
    mbar_arrive(bar + 8 * (B_OST + wg));
    TSW(6);
  }
}

__device__ __forceinline__ void proj_phase(const Params& p, uint32_t sb, int layer, int rb, int q, int wg, int w) {
  const int lane = opaque_tid() & 31;
  const bool TR = layer != 0;
  const int t = lane & 3;
  const uint32_t bar = sb + SM_BAR;
  const uint32_t rbx = sb + (P_R + wg) * PG;
  const int blk = 16 * wg + rb;
  uint32_t res[16];
  mbar_wait(bar + 8 * (B_RF + wg), layer);
  if (!TR) {
#pragma unroll
    for (int j = 0; j < 8; j += 2) {
      const int mi = lane >> 3;
      const int row = 16 * w + (lane & 7) + 8 * (mi & 1), ch = j + (mi >> 1);
      ldsm4(&res[2 * j], rbx + row * 128 + ((ch ^ (row & 7)) << 4));
    }
  } else {
#pragma unroll
    for (int j = 0; j < 8; j += 2) {
      const int mi = lane >> 3;
      const int line = 8 * (j + (mi >> 1)) + (lane & 7), pc = 2 * w + (mi & 1);
      ldsm4t(&res[2 * j], rbx + line * 128 + ((pc ^ (line & 7)) << 4));
    }
  }
  float acc[32];
#pragma unroll
  for (int j = 0; j < 16; j++) { acc[2 * j] = bf_lo(res[j]); acc[2 * j + 1] = bf_hi(res[j]); }
  acc_fence<32>(acc);
#pragma unroll
  for (int c = 0; c < 4; c++) {
    mbar_wait(bar + 8 * (B_WOF + c), layer);
    mbar_wait(bar + 8 * (B_OF + 4 * wg + c), layer);
    if (c == 0) TSW(7);
    const uint64_t da = mkdesc(sb + o_page(wg, c) * PG, 16, 1024, 1);
    wg_fence();
#pragma unroll
    for (int ks = 0; ks < 8; ks++)
      wgmma_ss<64, 0, 1>(acc, da + (ks >> 2) * 512 + (ks & 3) * 2, mkdesc(sb + wo_page(2 * c + (ks >> 2)) * PG, 8192, 1024, 1) + (ks & 3) * 128, 1);
    wg_commit();
  }
  wg_wait<0>();
  acc_fence<32>(acc);
  TSW(8);
  if (lane == 0 && w == 0) mbar_arrive(bar + 8 * (B_PDONE + wg));
  float s0 = 0.f, q0 = 0.f, s1 = 0.f, q1 = 0.f;
  uint32_t o[16];
#pragma unroll
  for (int j = 0; j < 8; j++) {
    const float a = acc[4 * j], b = acc[4 * j + 1], c = acc[4 * j + 2], d = acc[4 * j + 3];
    o[2 * j] = packbf(a, b);
    o[2 * j + 1] = packbf(c, d);
    s0 += a + b; q0 = fmaf(a, a, q0); q0 = fmaf(b, b, q0);
    s1 += c + d; q1 = fmaf(c, c, q1); q1 = fmaf(d, d, q1);
  }
#pragma unroll
  for (int j = 0; j < 8; j += 2) {
    const int mi = lane >> 3;
    const int line = 8 * (j + (mi >> 1)) + (lane & 7), pc = 2 * w + (mi & 1);
    stsm4t(rbx + line * 128 + ((pc ^ (line & 7)) << 4), o[2 * j], o[2 * j + 1], o[2 * j + 2], o[2 * j + 3]);
  }
#pragma unroll
  for (int o2 = 1; o2 <= 2; o2 <<= 1) {
    s0 += __shfl_xor_sync(~0u, s0, o2); q0 += __shfl_xor_sync(~0u, q0, o2);
    s1 += __shfl_xor_sync(~0u, s1, o2); q1 += __shfl_xor_sync(~0u, q1, o2);
  }
  const uint32_t stg = sb + SM_STG + wg * 512;
  {
    const int row = 16 * w + (lane >> 2) + 8 * (t >> 1);
    const float v = (t == 0) ? s0 : (t == 1) ? q0 : (t == 2) ? s1 : q1;
    sts32f(stg + 4 * (((((row & 7) >> 1) * 8 + (row >> 3)) << 2) + (row & 1) * 2 + (t & 1)), v);
  }
  TSW(9);
  fence_async_smem();
  bar_sync(2 + wg, 128);
  if (w == 0 && elect_one()) {
    mbar_wait(bar + 8 * B_ZF, 0);
    tma_st(&p.mapXT, blk * 64, (2 * layer) * DM + q * 64, rbx);
    bulk_red_add_f32(g_stats + layer * LSEQ * 2 + blk * 128, stg, 512);
    bulk_commit();
    bulk_wait_all();
    red_relaxed(&g_cnt[(C_G + 2 * layer + wg) * 32]);
    TSW(10);
  }
}

template <int M0, int STEP, int CNT> __device__ __forceinline__ void conv_load(uint32_t* A, uint32_t pe) {
#pragma unroll
  for (int i = 0; i < CNT; i++) {
    const int m = M0 + STEP * i;
    A[4 * i + 2] = lds32(pe + 4 * (64 * m - 8));
    A[4 * i + 0] = lds32(pe + 4 * (64 * m));
    A[4 * i + 1] = lds32(pe + 4 * (64 * m + 8));
    asm volatile("mov.b32 %0, %1;" : "=r"(A[4 * i + 3]) : "r"(A[4 * i + 0]));
  }
}
template <int B> __device__ __forceinline__ void conv_mma0(float* acc, const uint32_t* A, uint64_t d) {
  wg_fence();
  wgmma_rs<64, 0>(acc, A + 0, d + (uint64_t)(64 + 4 * B), B != 0);
  wgmma_rs<56, 0>(acc, A + 4, d + (uint64_t)(64 + 4 * B + 8), 1);
  wgmma_rs<48, 0>(acc, A + 8, d + (uint64_t)(64 + 4 * B + 16), 1);
  wgmma_rs<40, 0>(acc, A + 12, d + (uint64_t)(64 + 4 * B + 24), 1);
  wgmma_rs<32, 0>(acc, A + 16, d + (uint64_t)(64 + 4 * B + 32), 1);
  wgmma_rs<24, 0>(acc, A + 20, d + (uint64_t)(64 + 4 * B + 40), 1);
  wgmma_rs<16, 0>(acc, A + 24, d + (uint64_t)(64 + 4 * B + 48), 1);
  wgmma_rs<8, 0>(acc, A + 28, d + (uint64_t)(64 + 4 * B + 56), 1);
  wg_commit();
}
template <int M0, int CNT> __device__ __forceinline__ void conv_mma1(float* acc, const uint32_t* A, uint64_t d) {
  wg_fence();
#pragma unroll
  for (int i = 0; i < CNT; i++) wgmma_rs<64, 0>(acc, A + 4 * i, d + (uint64_t)(4 * (M0 + i)), (M0 + i) != 0);
  wg_commit();
}
__device__ __forceinline__ void conv_store(float* acc, uint32_t pb, uint32_t over, int w) {
  acc_fence<32>(acc);
  const int l = opaque_tid() & 31, mt = l >> 3;
  int c = 2 * (63 - 8 * (mt >> 1) - (l & 7) + w) + (mt & 1);
  c ^= (c >> 3) & 1;
  const uint32_t a0 = pb + c * 16;
#pragma unroll
  for (int j = 0; j < 8; j += 2)
    stsm4t(j == 0 ? (c < 128 ? a0 : over + (c - 128) * 16) : a0 - 256 * j, packbf(acc[4 * j], acc[4 * j + 1]), packbf(acc[4 * j + 2], acc[4 * j + 3]),
           packbf(acc[4 * j + 4], acc[4 * j + 5]), packbf(acc[4 * j + 6], acc[4 * j + 7]));
}
__device__ __forceinline__ void far_load(uint32_t* a, uint32_t wt) {
  uint32_t e[9];
#pragma unroll
  for (int k = 0; k < 9; k++) e[k] = lds32(wt - 32 * k);
#pragma unroll
  for (int s = 0; s < 4; s++) {
    asm volatile("mov.b32 %0, %1;" : "=r"(a[4 * s + 0]) : "r"(e[2 * s + 1]));
    asm volatile("mov.b32 %0, %1;" : "=r"(a[4 * s + 1]) : "r"(e[2 * s]));
    asm volatile("mov.b32 %0, %1;" : "=r"(a[4 * s + 2]) : "r"(e[2 * s + 2]));
    asm volatile("mov.b32 %0, %1;" : "=r"(a[4 * s + 3]) : "r"(e[2 * s + 1]));
  }
}
__device__ __forceinline__ void conv_sums(uint32_t sb, int lc, int ht) {
  const int m = ht - 1;
  uint4 v[2][3];
#pragma unroll
  for (int c = 0; c < 2; c++)
#pragma unroll
    for (int k = 0; k < 3; k++) {
      const int mm = m - 1 + k;
      v[c][k] = lds128(sb + cv_u(lc + c) + (mm >= 0 ? (mm & 1) * CV_UH + (127 - (mm >> 1)) * 16 : 128 * 16));
    }
  const int ce = m + 2, co = m + 1;
#pragma unroll
  for (int c = 0; c < 2; c++) {
    const uint32_t x[8] = {v[c][0].z, v[c][0].w, v[c][1].x, v[c][1].y, v[c][1].z, v[c][1].w, v[c][2].x, v[c][2].y};
    float pv[16];
#pragma unroll
    for (int k = 0; k < 8; k++) { pv[2 * k] = bf_lo(x[k]); pv[2 * k + 1] = bf_hi(x[k]); }
    float t2[15], t4[13], s9[8], s7[8];
#pragma unroll
    for (int i = 0; i < 15; i++) t2[i] = pv[i] + pv[i + 1];
#pragma unroll
    for (int i = 0; i < 13; i++) t4[i] = t2[i] + t2[i + 2];
#pragma unroll
    for (int i = 0; i < 8; i++) {
      s9[i] = (t4[i] + t4[i + 4]) + pv[i + 8];
      s7[i] = (t4[i + 1] + t2[i + 5]) + pv[i + 7];
    }
    const uint4 e4 = make_uint4(packbf(s9[0], s9[1]), packbf(s9[2], s9[3]), packbf(s9[4], s9[5]), packbf(s9[6], s9[7]));
    if (ce < 128) sts128(sb + cv_se(lc + c) + (ce >> 1) * 32 + (((ce & 1) ^ ((ce >> 3) & 1)) << 4), e4);
    else sts128(sb + cv_se(lc + c), make_uint4(0, 0, 0, 0));
    sts128(sb + cv_so(lc + c) + (co >> 1) * 32 + (((co & 1) ^ ((co >> 3) & 1)) << 4),
           make_uint4(packbf(s7[0], s7[1]), packbf(s7[2], s7[3]), packbf(s7[4], s7[5]), packbf(s7[6], s7[7])));
  }
}

template <int HALF, int NCH>
__device__ __forceinline__ void conv_epi(uint32_t sb, int lc, int c) {
  uint4 v[NCH][4], xr[NCH], f[NCH];
  const uint32_t sw = (c ^ ((c >> 3) & 1)) * 16;
#pragma unroll
  for (int u = 0; u < NCH; u++) {
#pragma unroll
    for (int k = 0; k < 4; k++) v[u][k] = lds128(sb + (HALF ? cv_pb1(lc + u, k) : cv_pb0(lc + u, k)) + sw);
    xr[u] = lds128(sb + cv_x(HALF, lc + u) + c * 16);
    if (HALF) f[u] = lds128(sb + cv_pf(lc + u) + c * 16);
  }
#pragma unroll
  for (int u = 0; u < NCH; u++) {
    if (HALF) { v[u][0].x = hadd2(v[u][0].x, f[u].x); v[u][0].y = hadd2(v[u][0].y, f[u].y); v[u][0].z = hadd2(v[u][0].z, f[u].z); v[u][0].w = hadd2(v[u][0].w, f[u].w); }
    uint4 o;
    o.x = hadd2(xr[u].x, hadd2(hadd2(v[u][0].x, v[u][1].x), hadd2(v[u][2].x, v[u][3].x)));
    o.y = hadd2(xr[u].y, hadd2(hadd2(v[u][0].y, v[u][1].y), hadd2(v[u][2].y, v[u][3].y)));
    o.z = hadd2(xr[u].z, hadd2(hadd2(v[u][0].z, v[u][1].z), hadd2(v[u][2].z, v[u][3].z)));
    o.w = hadd2(xr[u].w, hadd2(hadd2(v[u][0].w, v[u][1].w), hadd2(v[u][2].w, v[u][3].w)));
    sts128(sb + cv_x(HALF, lc + u) + c * 16, o);
  }
}

__device__ __forceinline__ void conv_prep(uint32_t sb, int layer, int cta, int half, int i) {
  const int c = 128 * half + i;
  const bf16* xin = g_xT + (size_t)(2 * layer) * DM * LSEQ + c * 8;
  uint4 st[4], xr[4];
#pragma unroll
  for (int k = 0; k < 4; k++) st[k] = ldcg128(g_stats + layer * LSEQ * 2 + ((c >> 3) * 4 + k) * 32 + (c & 7) * 4);
#pragma unroll
  for (int k = 0; k < 4; k++) xr[k] = ldcg128(xin + (size_t)cv_chan(cta, k) * LSEQ);
  uint32_t rs[4], nm[4];
#pragma unroll
  for (int k = 0; k < 4; k++) {
    const float m0 = __uint_as_float(st[k].x) * (-1.f / DM), m1 = __uint_as_float(st[k].z) * (-1.f / DM);
    const float r0 = rsqrt_approx(fmaxf(fmaf(__uint_as_float(st[k].y), 1.f / DM, -m0 * m0), 0.f) + 1e-5f);
    const float r1 = rsqrt_approx(fmaxf(fmaf(__uint_as_float(st[k].w), 1.f / DM, -m1 * m1), 0.f) + 1e-5f);
    rs[k] = packbf(r0, r1);
    nm[k] = packbf(m0 * bf_lo(rs[k]), m1 * bf_hi(rs[k]));
  }
  const uint32_t ud = sb + (c & 1) * CV_UH + (127 - (c >> 1)) * 16;
#pragma unroll
  for (int k = 0; k < 4; k++)
    sts128(ud + cv_u(k), make_uint4(hfma2(xr[k].x, rs[0], nm[0]), hfma2(xr[k].y, rs[1], nm[1]), hfma2(xr[k].z, rs[2], nm[2]), hfma2(xr[k].w, rs[3], nm[3])));
  fence_async_smem();
  mbar_arrive(sb + SM_BAR + 8 * (B_U + half));
#pragma unroll
  for (int k = 0; k < 4; k++) sts128(sb + cv_x(0, k) + half * PG + i * 16, xr[k]);
}

__device__ __forceinline__ void conv_phase(const Params& p, uint32_t sb, int layer, int cta) {
  const int tid = opaque_tid();
  const int wg = __shfl_sync(~0u, tid >> 7, 0), w = __shfl_sync(~0u, (tid >> 5) & 3, 0);
  const uint32_t bar = sb + SM_BAR;
  if (wg == 0) {
    if (tid < 32) sts128(sb + cv_u(tid >> 3) + ((tid >> 2) & 1) * CV_UH + (128 + (tid & 3)) * 16, make_uint4(0, 0, 0, 0));
    mbar_wait(bar + 8 * B_GB, layer);
    TSW(11);
    conv_prep(sb, layer, cta, 0, tid);
  } else if (tid < 176) {
    mbar_wait(bar + 8 * B_PDONE, layer);
    const int i = tid - 128, ch = i / 12, q2 = i % 12;
    const int w2 = q2 < 2 ? 1 : q2 < 6 ? 2 : 3, cc = q2 < 2 ? q2 : q2 < 6 ? q2 - 2 : q2 - 6;
    sts128(sb + cv_pb0(ch, w2) + cc * 16, make_uint4(0, 0, 0, 0));
  }
  constexpr int CH2 = 4 * PG;
  uint32_t A0[36], A1[32];
  float acc0[32], acc1[32];
  const int l1 = opaque_tid() & 31;
  const uint32_t pe = sb + cv_pe(wg) + 4 * (16 + 16 * w + (l1 >> 2) - 2 * (l1 & 3));
  const uint64_t d0 = mkdesc(sb + cv_u(wg), CV_UH, 128, 0), d1 = d0 + (CH2 >> 4);
  const uint32_t pb1a = sb + cv_pb1(wg, w), pb1b = sb + cv_pb1(2 + wg, w);
  mbar_wait(bar + 8 * B_PE, layer);
  conv_load<0, 2, 8>(A0, pe);
  conv_load<1, 2, 8>(A1, pe);
  mbar_wait(bar + 8 * B_U, layer);
  TSW(12);
  conv_mma0<0>(acc0, A0, d0);
  conv_mma0<1>(acc0, A1, d0);
  wg_wait<1>();
  conv_load<0, 2, 8>(A0, pe + CH2);
  conv_mma0<0>(acc1, A0, d1);
  wg_wait<1>();
  conv_load<1, 2, 8>(A1, pe + CH2);
  conv_mma0<1>(acc1, A1, d1);
  mbar_wait(bar + 8 * (B_PDONE + 1), layer);
  conv_store(acc0, sb + cv_pb0(wg, w), pb1a, w);
  const uint32_t wt = pe + (cv_wt(0) - cv_pe(0)) + 4 * (73 - 16);
  wg_wait<1>();
  far_load(A0, wt);
  far_load(A0 + 16, wt + 576 - 4);
  wg_wait<0>();
  far_load(A1, wt + CH2);
  far_load(A1 + 16, wt + CH2 + 576 - 4);
  mbar_wait(bar + 8 * B_S, layer);
  {
    float F0[8], F1[8];
    const uint64_t ds = mkdesc(sb + cv_se(wg), 256, 256, 3);
    wg_fence();
#pragma unroll
    for (int k = 0; k < 8; k++) {
      wgmma_rs<16, 1>(F0, A0 + 4 * k, ds + 32 * k, k != 0);
      wgmma_rs<16, 1>(F1, A1 + 4 * k, ds + 512 + 32 * k, k != 0);
    }
    wg_commit();
    conv_store(acc1, sb + cv_pb0(2 + wg, w), pb1b, w);
    mbar_arrive(bar + 8 * B_R);
    TSW(13);
    wg_wait<0>();
    acc_fence<8>(F0); acc_fence<8>(F1);
    const int l3 = opaque_tid() & 31;
    if (w == 0 && l3 == 0) mbar_arrive(bar + 8 * B_FARM);
    conv_load<0, 1, 9>(A0, pe);
    conv_load<9, 1, 8>(A1, pe);
    const uint32_t pf = sb + cv_pf(wg) + 2 * (16 * (16 * w + (l3 >> 2)) + 2 * (l3 & 3));
#pragma unroll
    for (int k = 0; k < 4; k++) {
      sts32(pf + (k & 1) * 256 + (k >> 1) * 16, packbf(F0[2 * k], F0[2 * k + 1]));
      sts32(pf + 4096 + (k & 1) * 256 + (k >> 1) * 16, packbf(F1[2 * k], F1[2 * k + 1]));
    }
  }
  TSW(14);
  mbar_wait(bar + 8 * (B_U + 1), layer);
  TSW(15);
  conv_mma1<0, 9>(acc0, A0, d0);
  conv_mma1<9, 8>(acc0, A1, d0);
  wg_wait<1>();
  conv_load<0, 1, 9>(A0, pe + CH2);
  conv_mma1<0, 9>(acc1, A0, d1);
  wg_wait<1>();
  conv_load<9, 1, 8>(A1, pe + CH2);
  conv_mma1<9, 4>(acc1, A1, d1);
  conv_store(acc0, pb1a, sb + cv_dump(wg), w);
  mbar_arrive(bar + 8 * (B_R + 1));
  TSW(16);
  conv_mma1<13, 4>(acc1, A1 + 16, d1);
  wg_wait<0>();
  conv_store(acc1, pb1b, sb + cv_dump(2 + wg), w);
  TSW(17);
  if (wg == 0) {
    mbar_arrive(bar + 8 * (B_R + 2));
  } else {
    mbar_wait(bar + 8 * B_PUB, layer);
    bar_sync(3, 128);
    conv_epi<1, 1>(sb, 3, opaque_tid() & 127);
    fence_async_smem();
    mbar_arrive(bar + 8 * (B_PUB + 2));
    TSW(18);
  }
}

__device__ __forceinline__ void final_phase(const Params& p, uint32_t sb, int cta, int wg, int w) {
  const int lane = opaque_tid() & 31;
  const uint32_t bar = sb + SM_BAR;
  mbar_wait(bar + 8 * (B_TF + wg), 0);
  if (threadIdx.x == 128) TS(8);
  const uint32_t src = sb + (16 + wg) * PG, dst = src + 2 * PG;
  const int mi = lane >> 3;
#pragma unroll
  for (int j = 0; j < 8; j += 2) {
    uint32_t r[4];
    const int line = 8 * (j + (mi >> 1)) + (lane & 7), pc = 2 * w + (mi & 1);
    ldsm4t(r, src + line * 128 + ((pc ^ (line & 7)) << 4));
    const int row = 16 * w + (lane & 7) + 8 * (mi & 1), ch = j + (mi >> 1);
    stsm4(dst + row * 128 + ((ch ^ (row & 7)) << 4), r[0], r[1], r[2], r[3]);
  }
  fence_async_smem();
  bar_sync(2 + wg, 128);
  if (w == 0 && elect_one()) {
    tma_st(&p.mapOut, (cta >> 4) * 64, (16 * wg + (cta & 15)) * 64, dst);
    bulk_commit();
    asm volatile("cp.async.bulk.wait_group.read 0;" ::: "memory");
    if (threadIdx.x == 128) TS(9);
    if (threadIdx.x == 128) LTS(1);
  }
}

struct cplx { float r, i; };
__device__ __forceinline__ cplx cmul(cplx a, cplx b) { return {fmaf(a.r, b.r, -a.i * b.i), fmaf(a.r, b.i, a.i * b.r)}; }
__device__ __forceinline__ cplx csqr(cplx a) { return {fmaf(a.r, a.r, -a.i * a.i), (a.r + a.r) * a.i}; }
__device__ __forceinline__ cplx cexp_l(float ar2, float ai, float l) {
  const float m = ex2(ar2 * l);
  const float x = ai * l;
  return {m * __cosf(x), m * __sinf(x)};
}

__device__ __forceinline__ void colsum_cta(const Params& p, uint32_t sb, int j, int tid) {
  const uint32_t bar = sb + SM_BAR;
  auto ld = [&](int i) {
    mbar_expect(bar + 8 * i, 3 * PG);
    tma_ld3(sb + (i & 7) * 3 * PG, &p.mapW3, (2 * j + (i & 1)) * 64, (i >> 1) * 64, 0, bar + 8 * i);
  };
  if (tid == 384) {
#pragma unroll
    for (int i = 0; i < 24; i++) mbar_init(bar + 8 * i, i < 16 ? 1 : 12);
    asm volatile("fence.mbarrier_init.release.cluster;" ::: "memory");
    fence_async_smem();
#pragma unroll 1
    for (int i = 0; i < 8; i++) ld(i);
  }
  const unsigned ep = ld_relaxed(&g_cnt[C_CS * 32]);
  bar_sync(0, NTHREADS);
  if (tid == 384) {
#pragma unroll 1
    for (int i = 8; i < 16; i++) { mbar_wait(bar + 8 * (8 + i), 0); fence_async_smem(); ld(i); }
  }
  if (tid < 384) {
    const int lane = tid & 31, cc = tid & 7, r0 = (tid >> 3) & 15, part = tid >> 7;
    const uint32_t id = ((lane >> 2) == 2 * (lane & 3) ? 0x3f80u : 0u) | ((lane >> 2) == 2 * (lane & 3) + 1 ? 0x3f800000u : 0u);
    const uint32_t src = sb + part * PG + r0 * 128 + ((cc ^ (r0 & 7)) << 4);
    float s[2][2][4];
#pragma unroll
    for (int i = 0; i < 16; i++) s[i >> 3][(i >> 2) & 1][i & 3] = 0.f;
#pragma unroll 1
    for (int i2 = 0; i2 < 16; i2 += 2) {
#pragma unroll
      for (int h = 0; h < 2; h++) {
        const int i = i2 + h;
        mbar_wait(bar + 8 * i, 0);
        uint4 v[4];
#pragma unroll
        for (int k = 0; k < 4; k++) v[k] = lds128(src + (i & 7) * 3 * PG + k * 2048);
#pragma unroll
        for (int k = 0; k < 4; k++) {
          const uint32_t a[4] = {v[k].x, v[k].y, v[k].z, v[k].w};
          mma_bf16(s[h][0], a, id, 0u);
          mma_bf16(s[h][1], a, 0u, id);
        }
        __syncwarp();
        if (i < 8 && lane == 0) mbar_arrive(bar + 8 * (16 + i));
      }
    }
    const uint32_t red = sb + 24 * PG;
#pragma unroll
    for (int h = 0; h < 2; h++)
#pragma unroll
      for (int k = 0; k < 2; k++) sts128f(red + (r0 * 384 + h * 192 + part * 64 + cc * 8 + k * 4) * 4, s[h][k][0], s[h][k][1], s[h][k][2], s[h][k][3]);
    bar_sync(1, 384);
    float tot = 0.f;
#pragma unroll
    for (int k = 0; k < 16; k++) tot += __uint_as_float(lds32(red + (k * 384 + tid) * 4));
    asm volatile("st.relaxed.gpu.global.v2.u32 [%0], {%1,%2};" ::"l"(&g_colsum[j * 384 + tid]), "r"(__float_as_uint(tot)), "r"(ep / NCTA + 1) : "memory");
  }
}

struct ModeIn { uint32_t ar, ai, br, bi, cr, ci; bf16 logdt, dskip; };
__device__ __forceinline__ ModeIn load_modes(const Params& p, int d, int m) {
  const int i = d * 64 + m;
  return {((const uint32_t*)p.a_re)[i], ((const uint32_t*)p.a_im)[i], ((const uint32_t*)p.b_re)[i], ((const uint32_t*)p.b_im)[i],
          ((const uint32_t*)p.c_re)[i], ((const uint32_t*)p.c_im)[i], p.log_dt[d], p.dskip[d]};
}
__device__ __forceinline__ float4 lds128f_nv(uint32_t a) { float4 v; asm("ld.shared.v4.f32 {%0,%1,%2,%3}, [%4];" : "=f"(v.x), "=f"(v.y), "=f"(v.z), "=f"(v.w) : "r"(a)); return v; }
__device__ __forceinline__ void kernel_gen(uint32_t sb, int cta, int ht, ModeIn in, const ModeIn& in1) {
  const int w = ht >> 5, lane = ht & 31, g = lane >> 2, t = lane & 3, chn = ht >> 6, m = ht & 63;
  const uint32_t bst = sb + SM_KGB + (m >> 2) * 144 + (m & 3) * 4 + chn * 16;
  const uint64_t db = mkdesc(sb + SM_KGB, 144, 2304, 0);
  const int i0 = 16 * (w & 1) + g;
  const float e0 = (float)(8 * i0);
  float T[20];
#pragma unroll
  for (int i = 0; i < 20; i++) T[i] = 0.f;
  float k0 = 0.f;
#pragma unroll 1
  for (int pass = 0; pass < 4; pass++) {
    {
      const int sh = (pass & 1) ? 0 : 16;
      auto val = [&](uint32_t v) { return __uint_as_float((v << sh) & 0xffff0000u); };
      const float dt = __bfloat162float(__float2bfloat16_rn(expf(__bfloat162float(in.logdt))));
      const float ar2 = dt * val(in.ar) * 1.4426950408889634f, ai = dt * val(in.ai);
      const cplx c = cmul({val(in.cr), -val(in.ci)}, {dt * val(in.br), -dt * val(in.bi)});
      k0 += c.r;
      const cplx z1 = cexp_l(ar2, -ai, 1.f), z256 = cexp_l(ar2, -ai, 256.f), z64 = cexp_l(ar2, ai, 64.f);
      const cplx z2 = csqr(z1), z512 = csqr(z256);
      auto put = [&](int j, cplx v) { sts32(bst + (j >> 2) * 2304 + (j & 3) * 32, packbf(v.r, v.i)); };
      sts128f(sb + SM_KGT + ht * 16, ar2, ai, z64.r, z64.i);
      const cplx c1 = cmul(c, z1), c2 = cmul(c, z2), c3 = cmul(c1, z2), c4 = cmul(c2, z2);
      const cplx c5 = cmul(c3, z2), c6 = cmul(c4, z2), c7 = cmul(c5, z2), c8 = cmul(c6, z2);
      put(0, c1); put(1, c2); put(2, c3); put(3, c4); put(4, c5); put(5, c6); put(6, c7); put(7, c8);
      const cplx c260 = cmul(c4, z256), c264 = cmul(c8, z256), c520 = cmul(c8, z512), c776 = cmul(c264, z512);
      put(8, cmul(c2, z256)); put(9, c260); put(10, cmul(c6, z256)); put(11, c264);
      put(12, cmul(c4, z512)); put(13, c520); put(14, cmul(c260, z512)); put(15, c776);
      const cplx c1032 = cmul(c520, z512), c1288 = cmul(c776, z512);
      put(16, c1032); put(17, c1288); put(18, cmul(c1032, z512)); put(19, cmul(c1288, z512));
    }
    fence_async_smem();
    bar_sync(4, 128);
    uint32_t tb = sb + SM_KGT + (chn * 64 + t) * 16;
    asm volatile("mov.u32 %0, %0;" : "+r"(tb) :: "memory");
    uint32_t A[32];
#define KQ 4
#pragma unroll
    for (int q = 0; q < KQ; q++) {
#pragma unroll
      for (int s = 16 / KQ * q; s < 16 / KQ * (q + 1); s++) {
        const float4 v = lds128f_nv(tb + s * 64);
        const cplx lo = cexp_l(v.x, v.y, e0), hi = cmul(lo, {v.z, v.w});
        A[2 * s] = packbf(lo.r, lo.i);
        A[2 * s + 1] = packbf(hi.r, hi.i);
      }
      wg_fence();
#pragma unroll
      for (int k = 8 / KQ * q; k < 8 / KQ * (q + 1); k++) wgmma_rs<40, 0>(T, A + 4 * k, db + 18 * k, (pass & 1) | k);
      wg_commit();
    }
    wg_wait<0>();
    acc_fence<20>(T);
    if (ht == 0) TS(4 + pass);
    if (pass & 1) {
      const int lc = (pass & 2) + chn;
      const uint32_t kc = sb + kc_off(lc);
      auto put = [&](int idx, float v) {
        sts16(kc + idx * 2, __bfloat16_as_ushort(__float2bfloat16_rn(v)));
      };
#pragma unroll
      for (int hi = 0; hi < 2; hi++) {
        const int i = i0 + 8 * hi;
        float v[5];
#pragma unroll
        for (int j = 0; j < 5; j++) v[j] = chn ? T[4 * j + 2 * hi + 1] : T[4 * j + 2 * hi];
        put(8 * i + 1 + t, v[0]);
        put(8 * i + 5 + t, v[1]);
        put(257 + 4 * i + t, v[2]);
        put(385 + 2 * i + (t & 1) + 64 * (t >> 1), v[3]);
        put(513 + i + 32 * t, v[4]);
      }
#pragma unroll
      for (int o = 16; o > 0; o >>= 1) k0 += __shfl_xor_sync(~0u, k0, o);
      if (lane == 0) sts32f(sb + SM_RED + 4 * w, k0);
      bar_sync(4, 128);
      if (m == 0) put(0, k0 + __uint_as_float(lds32(sb + SM_RED + 4 * w + 4)) + __bfloat162float(in.dskip));
      k0 = 0.f;
      in = in1;
    }
  }
}

__device__ __forceinline__ void expand_taps(uint32_t sb, int ht) {
  const int ch = ht >> 5, lane = ht & 31;
  const uint32_t kc = sb + kc_off(ch);
  const uint32_t dst0 = sb + cv_pe(ch);
  auto put = [&](int G, uint32_t v0, uint32_t v1, uint32_t v2, uint32_t v3, uint32_t v4, uint32_t v5, uint32_t v6, uint32_t v7, uint32_t v8) {
    const uint32_t dst = dst0 + G * 32;
    sts128(dst, make_uint4(v1 | (v0 << 16), v2 | (v1 << 16), v3 | (v2 << 16), v4 | (v3 << 16)));
    sts128(dst + 16, make_uint4(v5 | (v4 << 16), v6 | (v5 << 16), v7 | (v6 << 16), v8 | (v7 << 16)));
  };
  {
    const uint4 q = lds128(kc + lane * 16);
    const uint32_t pv = lane ? lds16(kc + lane * 16 - 2) : 0u;
    const uint32_t dst = dst0 + (lane + 2) * 32;
    sts128(dst, make_uint4(__byte_perm(q.x, pv, 0x5410), __byte_perm(q.x, q.x, 0x1032), __byte_perm(q.y, q.x, 0x7610), __byte_perm(q.y, q.y, 0x1032)));
    sts128(dst + 16, make_uint4(__byte_perm(q.z, q.y, 0x7610), __byte_perm(q.z, q.z, 0x1032), __byte_perm(q.w, q.z, 0x7610), __byte_perm(q.w, q.w, 0x1032)));
    if (lane < 4) sts128(dst0 + lane * 16, make_uint4(0, 0, 0, 0));
  }
  uint32_t a[5], b[2][3], ve[5][2], vo[5][2];
  {
    const uint32_t s1 = kc + 2 * (256 + 4 * lane);
#pragma unroll
    for (int k = 0; k < 5; k++) a[k] = lds16(s1 + 2 * k);
#pragma unroll
    for (int u = 0; u < 2; u++) {
      const uint32_t s2 = kc + 2 * (384 + 2 * (lane + 32 * u));
#pragma unroll
      for (int k = 0; k < 3; k++) b[u][k] = lds16(s2 + 2 * k);
    }
#pragma unroll
    for (int u = 0; u < 5; u++) {
      const int x = lane + 32 * u;
#pragma unroll
      for (int k = 0; k < 2; k++) {
        const int pp = x - k;
        ve[u][k] = (pp >= 65 && pp <= 128) ? lds16(kc + 2 * (384 + 2 * pp)) : 0u;
        vo[u][k] = (pp >= 64 && pp <= 127) ? lds16(kc + 2 * (385 + 2 * pp)) : 0u;
      }
    }
  }
  const uint32_t k255 = lds16(kc + 2 * 255), k1024 = lds16(kc + 2 * 512);
  put(34 + lane, lane == 0 ? k255 : a[0], a[0], a[0], a[1], a[2], a[2], a[2], a[3], a[4]);
#pragma unroll
  for (int u = 0; u < 2; u++) put(66 + lane + 32 * u, b[u][0], b[u][0], b[u][0], b[u][0], b[u][1], b[u][1], b[u][1], b[u][2], b[u][2]);
  if (lane < 10) {
    const uint32_t v = lane == 0 ? k1024 : 0u;
    put(130 + lane, v, v, v, v, v, v, 0u, 0u, 0u);
  }
  const uint32_t wt = sb + cv_wt(ch);
#pragma unroll
  for (int u = 0; u < 5; u++) {
    const int x = lane + 32 * u;
    if (x < 144) {
      asm volatile("st.shared.u32 [%0], %1;" ::"r"(wt + 4 * x), "r"(ve[u][0] | (ve[u][1] << 16)) : "memory");
      asm volatile("st.shared.u32 [%0], %1;" ::"r"(wt + 576 + 4 * x), "r"(vo[u][0] | (vo[u][1] << 16)) : "memory");
    }
  }
}

#define WPRE 0
__host__ __device__ constexpr int bar_count(int i) {
  return i == B_FARM ? 2 : i == B_END ? 3 : (i == B_PUB + 2 || i == B_R || i == B_R + 1) ? 256 : (i >= B_Z0 && i < B_END) ? 128 : 1;
}
__host__ __device__ constexpr bool bar_first(int i) { return i < B_WF + 2 && (i & 7) < 2; }

__global__ void __launch_bounds__(NTHREADS, 1) fused_kernel(const __grid_constant__ Params p) {
  extern __shared__ __align__(1024) uint8_t smem[];
  const uint32_t sb = s32(smem);
  const int tid = threadIdx.x, lane = tid & 31;
  const int warp = __shfl_sync(~0u, tid >> 5, 0);
  if (blockIdx.x < 4) {
    colsum_cta(p, sb, blockIdx.x, tid);
    return;
  }
  const int cta = blockIdx.x - 4;
  const int rb = ((cta >> 4) & 3) * 4 + ((cta >> 2) & 3), hg = (cta >> 6) * 4 + (cta & 3);
  const int rb2 = cta >> 3, q2 = cta & 7;
  const uint32_t bar = sb + SM_BAR;
  auto ld_x0 = [&](int half, int c) {
    const uint32_t b = bar + 8 * (B_XF + 8 * half + c);
    mbar_expect(b, PG);
    tma_ld(sb + x_page(half, c) * PG, &p.mapX, c * 64, (16 * half + rb) * 64, b);
  };
  auto ld_w = [&](int c) {
    const uint32_t b = bar + 8 * (B_WF + c);
    mbar_expect(b, 3 * PG);
    tma_ld3(sb + w_page(c) * PG, &p.mapW3, hg * 64, c * 64, 0, b);
  };

  if (tid == 0) TS(0);
  if (tid == 480) LTS(0);
  if (warp < 6 && elect_one()) {
    if (warp == 0) {
#pragma unroll
      for (int i = 0; i < B_WF + 2; i++)
        if (bar_first(i)) mbar_init(bar + 8 * i, 1);
      asm volatile("fence.mbarrier_init.release.cluster;" ::: "memory");
      fence_async_smem();
      ld_x0(0, 0); ld_w(0); ld_x0(1, 0);
      ld_x0(0, 1); ld_w(1); ld_x0(1, 1);
      TS(1);
    } else {
#pragma unroll
      for (int q = 0; q < 5; q++) {
        if (warp == q + 1) {
#pragma unroll
          for (int i = 0; i < B_COUNT; i++)
            if (!bar_first(i) && i % 5 == q) mbar_init(bar + 8 * i, bar_count(i));
        }
      }
      asm volatile("fence.mbarrier_init.release.cluster;" ::: "memory");
    }
  }

  if (warp < 8) {
    bar_sync(0, NTHREADS);
    asm volatile("setmaxnreg.inc.sync.aligned.u32 %0;" ::"n"(R_CONS));
    const int cw = __shfl_sync(~0u, opaque_tid() >> 5, 0);
    const int wg = cw >> 2, w = cw & 3;
    if (tid == 0) TS(2);
#pragma unroll 1
    for (int layer = 0; layer < 2; layer++) {
      attn_phase(p, sb, layer, rb, hg, wg, w);
      proj_phase(p, sb, layer, rb2, q2, wg, w);
      conv_phase(p, sb, layer, cta);
    }
    final_phase(p, sb, cta, wg, w);
  } else if (warp < 12) {
    asm volatile("setmaxnreg.dec.sync.aligned.u32 %0;" ::"n"(R_HELP));
    const int ht = tid - 256;
    {
      unsigned ep0 = 0;
      if (ht == 0) ep0 = ld_relaxed(&g_cnt[C_CS * 32]);
      const ModeIn in0 = load_modes(p, cv_chan(cta, ht >> 6), ht & 63), in1 = load_modes(p, cv_chan(cta, 2 + (ht >> 6)), ht & 63);
      bar_sync(0, NTHREADS);
      if (ht == 0) {
        sts32(sb + SM_EP, ep0 / NCTA);
        mbar_arrive(bar + 8 * B_EP);
      }
      if (hg == 0) {
        *(float4*)(g_stats + (ht >> 6) * LSEQ * 2 + rb * 256 + (ht & 63) * 4) = make_float4(0.f, 0.f, 0.f, 0.f);
      }
      mbar_arrive(bar + 8 * B_Z0);
      if (ht == 0) TS(3);
      kernel_gen(sb, cta, ht, in0, in1);
      fence_async_smem();
      bar_sync(4, 128);
      if (ht == 0) mbar_arrive(bar + 8 * B_KG);
    }
#pragma unroll 1
    for (int layer = 0; layer < 2; layer++) {
      mbar_wait(bar + 8 * B_PDONE, layer);
      expand_taps(sb, opaque_tid() - 256);
      mbar_arrive(bar + 8 * B_PE);
      TSW(0);
      mbar_wait(bar + 8 * (B_PDONE + 1), layer);
      mbar_wait(bar + 8 * B_U, layer);
      conv_sums(sb, 0, opaque_tid() - 256);
      conv_sums(sb, 2, opaque_tid() - 256);
      fence_async_smem();
      mbar_arrive(bar + 8 * B_S);
      TSW(1);
      mbar_wait(bar + 8 * (B_GB + 1), layer);
      TSW(2);
      conv_prep(sb, layer, cta, 1, opaque_tid() - 256);
      TSW(3);
      mbar_wait(bar + 8 * B_R, layer);
      conv_epi<0, 2>(sb, 0, opaque_tid() - 256);
      conv_epi<0, 2>(sb, 2, opaque_tid() - 256);
      fence_async_smem();
      mbar_arrive(bar + 8 * B_PUB);
      TSW(4);
      mbar_wait(bar + 8 * (B_R + 1), layer);
      conv_epi<1, 2>(sb, 0, opaque_tid() - 256);
      fence_async_smem();
      mbar_arrive(bar + 8 * (B_PUB + 1));
      TSW(5);
      mbar_wait(bar + 8 * (B_R + 2), layer);
      conv_epi<1, 1>(sb, 2, opaque_tid() - 256);
      fence_async_smem();
      mbar_arrive(bar + 8 * (B_PUB + 2));
      TSW(6);
    }
  } else {
    asm volatile("setmaxnreg.dec.sync.aligned.u32 %0;" ::"n"(R_AGENT));
    bar_sync(0, NTHREADS);
    auto done = [&](int half, int c, int layer) { mbar_wait(bar + 8 * (B_DN + 8 * half + c), layer); };
    if (warp == 12) {
      if (elect_one()) {
#pragma unroll 1
        for (int layer = 0; layer < 2; layer++) {
          auto ld_xe = [&](int c) {
            const uint32_t b = bar + 8 * (B_XF + c);
            mbar_expect(b, PG);
            if (layer == 0) tma_ld(sb + (c - 5) * PG, &p.mapX, c * 64, rb * 64, b);
            else tma_ld(sb + (c - 5) * PG, &p.mapXT, rb * 64, DM + c * 64, b);
          };
          if (layer == 0) {
            ld_x0(0, 2); ld_w(2); ld_x0(1, 2);
            if (hg >= 3) {
              mbar_expect(bar + 8 * B_SC, PG);
              tma_ld(sb + P_R * PG, &p.mapX, hg * 64, rb * 64, bar + 8 * B_SC);
            }
            if (rb < 4) tma_prefetch3(&p.mapW3, hg * 64, (4 + rb) * 64, 0);
            ld_x0(0, 3); ld_w(3); ld_x0(1, 3); ld_x0(0, 4); ld_x0(1, 4);
            done(0, 0, 0); done(1, 0, 0);
            ld_w(4);
            ld_x0(1, 5); ld_x0(1, 6); ld_x0(1, 7);
            done(0, 1, 0); done(1, 1, 0);
            ld_w(5);
            if (rb2 < 8) tma_prefetch2(&p.mapWo, q2 * 64, rb2 * 64);
            done(0, 2, 0);
            fence_async_smem();
            ld_xe(5); ld_xe(6); ld_xe(7);
          } else {
            mbar_wait(bar + 8 * B_PDONE, 0);
            mbar_wait(bar + 8 * (B_PDONE + 1), 0);
            ld_w(0); ld_w(1); ld_w(2);
            mbar_wait(bar + 8 * (B_PUB + 2), 0);
            fence_async_smem();
            ld_w(3);
            done(0, 2, 1);
            fence_async_global();
            fence_async_smem();
            ld_xe(5); ld_xe(6); ld_xe(7);
            done(1, 0, 1);
            ld_w(4);
            done(1, 1, 1);
            ld_w(5);
          }
          done(1, 2, layer);
          fence_async_smem();
          ld_w(6); ld_w(7);
          auto ld_res = [&](int half) {
            const uint32_t b = bar + 8 * (B_RF + half);
            mbar_expect(b, PG);
            if (layer == 0) tma_ld(sb + (P_R + half) * PG, &p.mapX, q2 * 64, (16 * half + rb2) * 64, b);
            else tma_ld(sb + (P_R + half) * PG, &p.mapXT, (16 * half + rb2) * 64, DM + q2 * 64, b);
          };
          done(0, 4, layer); done(1, 3, layer);
          fence_async_smem();
#pragma unroll 1
          for (int c = 0; c < 8; c++) {
            const uint32_t b = bar + 8 * (B_WOF + (c >> 1));
            if (c == 5) { ld_res(0); done(1, 4, layer); }
            if ((c & 1) == 0) mbar_expect(b, 2 * PG);
            tma_ld(sb + wo_page(c) * PG, &p.mapWo, q2 * 64, c * 64, b);
          }
          mbar_wait(bar + 8 * B_KG, 0);
          fence_async_global();
          ld_res(1);
        }
      }
    } else if (warp == 13) {
      if (elect_one()) {
        mbar_wait(bar + 8 * (B_WF + 2), 0);
        asm volatile("prefetch.tensormap [%0];" ::"l"(&p.mapO) : "memory");
        asm volatile("prefetch.tensormap [%0];" ::"l"(&p.mapO2) : "memory");
        asm volatile("prefetch.tensormap [%0];" ::"l"(&p.mapXT) : "memory");
        asm volatile("prefetch.tensormap [%0];" ::"l"(&p.mapOut) : "memory");
        asm volatile("prefetch.tensormap [%0];" ::"l"(&p.mapWo) : "memory");
        mbar_wait(bar + 8 * B_EP, 0);
        const unsigned e1 = lds32(sb + SM_EP) + 1;
        auto ld_x1 = [&](int half, int c0, int c1) {
          fence_async_global();
          fence_async_smem();
#pragma unroll 1
          for (int c = c0; c < c1; c++) {
            const uint32_t b = bar + 8 * (B_XF + 8 * half + c);
            mbar_expect(b, PG);
            tma_ld(sb + x_page(half, c) * PG, &p.mapXT, (16 * half + rb) * 64, DM + c * 64, b);
          }
        };
#pragma unroll 1
        for (int layer = 0; layer < 2; layer++) {
          if (layer == 1) {
            mbar_wait(bar + 8 * B_FARM, 0);
            mbar_wait(bar + 8 * B_PUB, 0);
            spin_until(&g_cnt[C_C * 32], e1 * NCTA);
            TS(10);
            ld_x1(0, 0, 3);
            if (hg >= 3) {
              mbar_expect(bar + 8 * B_SC, PG);
              tma_ld(sb + P_R * PG, &p.mapXT, rb * 64, DM + hg * 64, bar + 8 * B_SC);
            }
            ld_x1(0, 3, 5);
            mbar_wait(bar + 8 * (B_PUB + 1), 0);
            spin_until(&g_cnt[(C_C + 1) * 32], e1 * NCTA);
            TS(11);
            ld_x1(1, 0, 4);
            spin_until(&g_cnt[(C_C + 2) * 32], e1 * NCTA);
            TS(12);
            ld_x1(1, 4, 8);
          }
#pragma unroll 1
          for (int half = 0; half < 2; half++) {
            done(1, 7, layer);
            mbar_wait(bar + 8 * B_OST, layer);
            if (half) mbar_wait(bar + 8 * (B_OST + 1), layer);
            spin_until(&g_cnt[(C_O + layer * 32 + 16 * half + rb2) * 32], e1 * 8);
            fence_async_global();
            fence_async_smem();
#pragma unroll 1
            for (int c = 0; c < 4; c++) {
              const uint32_t b = bar + 8 * (B_OF + 4 * half + c);
              mbar_expect(b, 2 * PG);
              tma_ld3(sb + o_page(half, c) * PG, &p.mapO2, 0, (16 * half + rb2) * 64, 2 * c, b);
            }
          }
        }
        mbar_wait(bar + 8 * B_PUB, 1);
#pragma unroll 1
        for (int half = 0; half < 2; half++) {
          spin_until(&g_cnt[(C_F + 4 * (half ? 1 + (cta >> 6) : 0) + ((cta >> 4) & 3)) * 32], e1 * 32);
          fence_async_global();
          mbar_expect(bar + 8 * (B_TF + half), PG);
          tma_ld(sb + (16 + half) * PG, &p.mapXT, (16 * half + (cta & 15)) * 64, 3 * DM + (cta >> 4) * 64, bar + 8 * (B_TF + half));
        }
      }
    } else if (warp == 14) {
      mbar_wait(bar + 8 * B_EP, 0);
      const unsigned e1 = lds32(sb + SM_EP) + 1;
      done(0, 1, 0);
      {
        uint2 v[6];
        bool ok;
        int it = 0;
        do {
          ok = true;
#pragma unroll
          for (int i = 0; i < 6; i++) {
            const int k = lane + 32 * i;
            asm volatile("ld.relaxed.gpu.global.v2.u32 {%0,%1}, [%2];" : "=r"(v[i].x), "=r"(v[i].y) : "l"(&g_colsum[hg * 192 + k]) : "memory");
            ok = ok && v[i].y == e1;
          }
          if (++it > (1 << 22)) __trap();
        } while (!__all_sync(~0u, ok));
#pragma unroll
        for (int i = 0; i < 6; i++) sts32f(sb + SM_CS + 4 * (lane + 32 * i), __uint_as_float(v[i].x));
      }
      __syncwarp();
      if (lane == 0) {
        mbar_arrive(bar + 8 * B_CSF);
        TS(13);
        mbar_wait(bar + 8 * B_Z0, 0);
        red_release(&g_cnt[C_CS * 32]);
        spin_until(&g_cnt[C_CS * 32], e1 * NCTA);
        mbar_arrive(bar + 8 * B_ZF);
#pragma unroll 1
        for (int i = 0; i < 4; i++) {
          mbar_wait(bar + 8 * (B_PDONE + (i & 1)), i >> 1);
          spin_until(&g_cnt[(C_G + i) * 32], e1 * NCTA);
          mbar_arrive(bar + 8 * (B_GB + (i & 1)));
        }
      }
    } else if (elect_one()) {
#pragma unroll 1
      for (int i = 0; i < 6; i++) {
        const int layer = i >= 3, k = i - 3 * layer, half = k != 0;
        bf16* xout = g_xT + (size_t)(2 * layer + 1) * DM * LSEQ + half * 1024;
        mbar_wait(bar + 8 * (B_PUB + k), layer);
#pragma unroll 1
        for (int lc = (k & 2); lc < (k == 1 ? 2 : 4); lc++) bulk_st(xout + (size_t)cv_chan(cta, lc) * LSEQ, sb + cv_x(half, lc), 2048);
        bulk_commit();
        bulk_wait_all();
        red_relaxed(&g_cnt[(layer ? C_F + 4 * k + (cta >> 5) : C_C + k) * 32]);
        TS(16 + layer * 56 + 40 + 7 + k);
      }
    }
  }
}

typedef CUresult (*EncodeFn)(CUtensorMap*, CUtensorMapDataType, cuuint32_t, void*, const cuuint64_t*, const cuuint64_t*,
                             const cuuint32_t*, const cuuint32_t*, CUtensorMapInterleave, CUtensorMapSwizzle,
                             CUtensorMapL2promotion, CUtensorMapFloatOOBfill);

static void make_map(EncodeFn enc, CUtensorMap* m, void* ptr, uint64_t cols, uint64_t rows, uint32_t box_rows) {
  cuuint64_t dims[2] = {cols, rows};
  cuuint64_t strides[1] = {cols * 2};
  cuuint32_t box[2] = {64, box_rows};
  cuuint32_t es[2] = {1, 1};
  enc(m, CU_TENSOR_MAP_DATA_TYPE_BFLOAT16, 2, ptr, dims, strides, box, es, CU_TENSOR_MAP_INTERLEAVE_NONE,
      CU_TENSOR_MAP_SWIZZLE_128B, CU_TENSOR_MAP_L2_PROMOTION_L2_128B, CU_TENSOR_MAP_FLOAT_OOB_FILL_NONE);
}
static void make_map3(EncodeFn enc, CUtensorMap* m, void* ptr, uint64_t d0, uint64_t cols, uint64_t rows, uint64_t blk_stride,
                      uint64_t nblocks, uint32_t nblk) {
  cuuint64_t dims[3] = {d0, rows, nblocks};
  cuuint64_t strides[2] = {cols * 2, blk_stride * 2};
  cuuint32_t box[3] = {64, 64, nblk};
  cuuint32_t es[3] = {1, 1, 1};
  enc(m, CU_TENSOR_MAP_DATA_TYPE_BFLOAT16, 3, ptr, dims, strides, box, es, CU_TENSOR_MAP_INTERLEAVE_NONE,
      CU_TENSOR_MAP_SWIZZLE_128B, CU_TENSOR_MAP_L2_PROMOTION_L2_128B, CU_TENSOR_MAP_FLOAT_OOB_FILL_NONE);
}

extern "C" void kernel_launch(void* const* d_in, const int* in_sizes, int n_in, void* d_out, int out_size) {
  static Params prm;
  static void* cached[13] = {nullptr};
  static bool attr_done = false;
  bool same = attr_done && cached[12] == d_out;
  for (int i = 0; i < 12 && same; i++) same = cached[i] == d_in[i];
  if (!same) {
    void* fn = nullptr;
    cudaDriverEntryPointQueryResult qr;
    cudaGetDriverEntryPoint("cuTensorMapEncodeTiled", &fn, cudaEnableDefault, &qr);
    EncodeFn enc = (EncodeFn)fn;
    void *pO, *pXT;
    cudaGetSymbolAddress(&pO, g_O);
    cudaGetSymbolAddress(&pXT, g_xT);
    make_map(enc, &prm.mapX, d_in[0], DM, LSEQ, 64);
    make_map(enc, &prm.mapO, pO, DM, LSEQ, 64);
    make_map(enc, &prm.mapXT, pXT, LSEQ, 4 * DM, 64);
    make_map(enc, &prm.mapOut, d_out, DM, LSEQ, 64);
    make_map(enc, &prm.mapWo, d_in[2], DM, DM, 64);
    make_map3(enc, &prm.mapW3, d_in[1], DM, 3 * DM, DM, DM, 3, 3);
    make_map3(enc, &prm.mapO2, pO, 64, DM, LSEQ, 64, 8, 2);
    prm.wqkv = (const bf16*)d_in[1];
    prm.a_re = (const bf16*)d_in[4]; prm.a_im = (const bf16*)d_in[5];
    prm.b_re = (const bf16*)d_in[6]; prm.b_im = (const bf16*)d_in[7];
    prm.c_re = (const bf16*)d_in[8]; prm.c_im = (const bf16*)d_in[9];
    prm.log_dt = (const bf16*)d_in[10]; prm.dskip = (const bf16*)d_in[11];
    cudaFuncSetAttribute(fused_kernel, cudaFuncAttributeMaxDynamicSharedMemorySize, SM_TOTAL);
    for (int i = 0; i < 12; i++) cached[i] = d_in[i];
    cached[12] = d_out;
    attr_done = true;
  }
  fused_kernel<<<NCTA + 4, NTHREADS, SM_TOTAL>>>(prm);
}
```

```cpp
#include <cuda_runtime.h>
#include <cuda_bf16.h>
#include <cuda.h>
#include <stdint.h>

typedef __nv_bfloat16 bf16;

constexpr int LSEQ = 2048;
constexpr int DM = 512;
constexpr int NCTA = 128;
constexpr int NTHREADS = 512;
#define R_CONS 200
#define R_HELP 88
#define R_AGENT 24
#define REL 1
#define GPOS 4
#define TURN0 3
#define TURN1 3

constexpr int PG = 8192;
constexpr int P_R = 25;
__host__ __device__ constexpr int x_page(int half, int c) { return half ? 8 + c : c < 5 ? c : c - 5; }
__host__ __device__ constexpr int w_page(int c) { return (c & 3) < 3 ? 16 + 3 * (c & 3) : c < 4 ? 5 : 8; }
__host__ __device__ constexpr int wo_page(int c) { return c < 5 ? 3 + c : 11 + c; }
__host__ __device__ constexpr int o_page(int half, int pair) { return half ? (pair ? 17 + 2 * pair : 0) : 8 + 2 * pair; }
constexpr int SM_KGB = (P_R + 1) * PG;
constexpr int SM_KC = 27 * PG;
constexpr int KC_STRIDE = 648;
__host__ __device__ constexpr int kc_off(int lc) { return SM_KC + (lc & 1) * 2 * KC_STRIDE + (lc < 2 ? 3328 : 0); }
constexpr int SM_KGT = SM_KC + 3328 + 2592;
constexpr int SM_CS = SM_KGT + 2048;
constexpr int SM_RED = SM_CS + 768;
constexpr int SM_EP = SM_RED + 16;
constexpr int SM_STG = SM_RED + 32;
constexpr int SM_BAR = SM_STG + 1024;
constexpr int SM_TS = SM_BAR + 768;
constexpr int SM_TOTAL = SM_TS + 512;
static_assert(SM_TOTAL <= 232448 && SM_STG % 16 == 0 && SM_KGT % 16 == 0, "shared memory");

constexpr int CV_UH = 140 * 16;
__host__ __device__ constexpr int cv_u(int lc) { return (8 + 2 * lc) * PG; }
__host__ __device__ constexpr int cv_pe(int lc) { return cv_u(lc) + 4480; }
__host__ __device__ constexpr int cv_pb1(int lc, int w) { return w ? cv_u(lc) + 8960 + (w - 1) * 2048 : 7 * PG + lc * 2048; }
__host__ __device__ constexpr int cv_fa(int lc) { return cv_pb1(lc, 1) + 128; }
__host__ __device__ constexpr int cv_dump(int lc) { return cv_u(lc) + 16256; }
__host__ __device__ constexpr int cv_pb0(int lc, int w) { return lc * PG + w * 2048; }
__host__ __device__ constexpr int cv_se(int lc) { return 4 * PG + lc * 4096; }
__host__ __device__ constexpr int cv_so(int lc) { return cv_se(lc) + 2048; }
__host__ __device__ constexpr int cv_pf(int lc) { return 6 * PG + lc * 2048; }
__host__ __device__ constexpr int cv_x(int half, int lc) { return (P_R + half) * PG + lc * 2048; }
constexpr int CV_ST = 7 * PG;
__host__ __device__ constexpr int cv_chan(int cta, int lc) { return 2 * cta + (lc & 1) + 256 * (lc >> 1); }

enum {
  B_XF = 0,
  B_WF = 16,
  B_OF = 24,
  B_DN = 32,
  B_WOF = 48,
  B_RF = 52,
  B_HF = 54,
  B_OST = 56,
  B_PDONE = 58,
  B_GB = 60,
  B_TF = 62,
  B_CSF = 64,
  B_EP = 65,
  B_ZF = 66,
  B_KG = 67,
  B_FARM = 68,
  B_Z0 = 69,
  B_PE = 70,
  B_U = 71,
  B_PUB = 74,
  B_R = 77,
  B_END = 80,
  B_SC = 81,
  B_COUNT = 82
};

enum {
  C_CS = 0,
  C_G = 1,
  C_C = 5,
  C_F = 8,
  C_O = 20,
  C_COUNT = 84
};

__device__ unsigned g_cnt[C_COUNT * 32];
__device__ __align__(1024) bf16 g_O[LSEQ * DM];
__device__ __align__(1024) bf16 g_xT[4 * DM * LSEQ];
__device__ __align__(1024) float g_stats[2 * LSEQ * 2];
__device__ __align__(1024) uint2 g_colsum[3 * DM];
__device__ __align__(1024) uint4 g_halo[2 * 32 * 8 * 384];
__device__ __align__(1024) uint4 g_part[2 * 32 * 8 * 64];
#define TS(i) do { } while (0)
#define TSW(k) do { if ((threadIdx.x & 127) == 0) TS(16 + layer * 56 + (threadIdx.x >> 7) * 20 + (k)); } while (0)
#define TSG(k) do { } while (0)

#define LTS(i) do { } while (0)

struct Params {
  CUtensorMap mapX, mapW3, mapO, mapO2, mapXT, mapOut, mapWo;
  const bf16 *wqkv, *a_re, *a_im, *b_re, *b_im, *c_re, *c_im, *log_dt, *dskip;
};

__device__ __forceinline__ uint32_t s32(const void* p) { return (uint32_t)__cvta_generic_to_shared(p); }
__device__ __forceinline__ void mbar_init(uint32_t b, int c) { asm volatile("mbarrier.init.shared::cta.b64 [%0], %1;" ::"r"(b), "r"(c) : "memory"); }
__device__ __forceinline__ void mbar_expect(uint32_t b, int bytes) { asm volatile("mbarrier.arrive.expect_tx.shared::cta.b64 _, [%0], %1;" ::"r"(b), "r"(bytes) : "memory"); }
__device__ __forceinline__ void mbar_arrive(uint32_t b) { asm volatile("mbarrier.arrive.shared::cta.b64 _, [%0];" ::"r"(b) : "memory"); }
__device__ __forceinline__ void mbar_wait(uint32_t b, int parity) {
  asm volatile("{\n.reg .pred p;\nWAIT_LOOP:\nmbarrier.try_wait.parity.shared::cta.b64 p, [%0], %1;\n@p bra WAIT_DONE;\nbra WAIT_LOOP;\nWAIT_DONE:\n}" ::"r"(b), "r"(parity) : "memory");
}
__device__ __forceinline__ bool mbar_test(uint32_t b, int parity) {
  uint32_t ok;
  asm volatile("{\n.reg .pred p;\nmbarrier.test_wait.parity.shared::cta.b64 p, [%1], %2;\nselp.u32 %0, 1, 0, p;\n}" : "=r"(ok) : "r"(b), "r"(parity) : "memory");
  return ok != 0;
}
__device__ __forceinline__ int opaque_tid() { int v; asm volatile("mov.u32 %0, %%tid.x;" : "=r"(v)); return v; }
__device__ __forceinline__ bool elect_one() {
  uint32_t r;
  asm volatile("{\n.reg .pred p;\nelect.sync _|p, 0xffffffff;\nselp.u32 %0, 1, 0, p;\n}" : "=r"(r));
  return r != 0;
}
__device__ __forceinline__ void tma_ld(uint32_t dst, const CUtensorMap* m, int c0, int c1, uint32_t bar) {
  asm volatile("cp.async.bulk.tensor.2d.shared::cluster.global.mbarrier::complete_tx::bytes [%0], [%1, {%3, %4}], [%2];"
               ::"r"(dst), "l"(m), "r"(bar), "r"(c0), "r"(c1) : "memory");
}
__device__ __forceinline__ void tma_ld3(uint32_t dst, const CUtensorMap* m, int c0, int c1, int c2, uint32_t bar) {
  asm volatile("cp.async.bulk.tensor.3d.shared::cluster.global.mbarrier::complete_tx::bytes [%0], [%1, {%3, %4, %5}], [%2];"
               ::"r"(dst), "l"(m), "r"(bar), "r"(c0), "r"(c1), "r"(c2) : "memory");
}
__device__ __forceinline__ void tma_prefetch2(const CUtensorMap* m, int c0, int c1) {
  asm volatile("cp.async.bulk.prefetch.tensor.2d.L2.global.tile [%0, {%1, %2}];" ::"l"(m), "r"(c0), "r"(c1) : "memory");
}
__device__ __forceinline__ void tma_prefetch3(const CUtensorMap* m, int c0, int c1, int c2) {
  asm volatile("cp.async.bulk.prefetch.tensor.3d.L2.global.tile [%0, {%1, %2, %3}];" ::"l"(m), "r"(c0), "r"(c1), "r"(c2) : "memory");
}
__device__ __forceinline__ void tma_st(const CUtensorMap* m, int c0, int c1, uint32_t src) {
  asm volatile("cp.async.bulk.tensor.2d.global.shared::cta.bulk_group [%0, {%2, %3}], [%1];" ::"l"(m), "r"(src), "r"(c0), "r"(c1) : "memory");
}
__device__ __forceinline__ void bulk_ld(uint32_t dst, const void* src, int bytes, uint32_t bar) {
  asm volatile("cp.async.bulk.shared::cluster.global.mbarrier::complete_tx::bytes [%0], [%1], %2, [%3];" ::"r"(dst), "l"(src), "r"(bytes), "r"(bar) : "memory");
}
__device__ __forceinline__ void bulk_st(void* dst, uint32_t src, int bytes) {
  asm volatile("cp.async.bulk.global.shared::cta.bulk_group [%0], [%1], %2;" ::"l"(dst), "r"(src), "r"(bytes) : "memory");
}
__device__ __forceinline__ void bulk_red_add_f32(void* dst, uint32_t src, int bytes) {
  asm volatile("cp.reduce.async.bulk.global.shared::cta.bulk_group.add.f32 [%0], [%1], %2;" ::"l"(dst), "r"(src), "r"(bytes) : "memory");
}
__device__ __forceinline__ void bulk_commit() { asm volatile("cp.async.bulk.commit_group;" ::: "memory"); }
__device__ __forceinline__ void bulk_wait_all() { asm volatile("cp.async.bulk.wait_group 0;" ::: "memory"); }
__device__ __forceinline__ void fence_async_smem() { asm volatile("fence.proxy.async.shared::cta;" ::: "memory"); }
__device__ __forceinline__ void fence_async_global() { asm volatile("fence.proxy.async.global;" ::: "memory"); }
__device__ __forceinline__ void bar_sync(int id, int n) { asm volatile("bar.sync %0, %1;" ::"r"(id), "r"(n) : "memory"); }
__device__ __forceinline__ void bar_arrive(int id, int n) { asm volatile("bar.arrive %0, %1;" ::"r"(id), "r"(n) : "memory"); }
__device__ __forceinline__ void wg_fence() { asm volatile("wgmma.fence.sync.aligned;" ::: "memory"); }
__device__ __forceinline__ void wg_commit() { asm volatile("wgmma.commit_group.sync.aligned;" ::: "memory"); }
template <int N> __device__ __forceinline__ void wg_wait() { asm volatile("wgmma.wait_group.sync.aligned %0;" ::"n"(N) : "memory"); }
__device__ __forceinline__ uint64_t mkdesc(uint32_t addr, uint32_t lbo, uint32_t sbo, int sw) {
  return (uint64_t)((addr & 0x3FFFF) >> 4) | ((uint64_t)(lbo >> 4) << 16) | ((uint64_t)(sbo >> 4) << 32) | ((uint64_t)sw << 62);
}
__device__ __forceinline__ void ldsm4(uint32_t* r, uint32_t a) {
  asm volatile("ldmatrix.sync.aligned.m8n8.x4.shared.b16 {%0,%1,%2,%3}, [%4];" : "=r"(r[0]), "=r"(r[1]), "=r"(r[2]), "=r"(r[3]) : "r"(a) : "memory");
}
__device__ __forceinline__ void ldsm4t(uint32_t* r, uint32_t a) {
  asm volatile("ldmatrix.sync.aligned.m8n8.x4.trans.shared.b16 {%0,%1,%2,%3}, [%4];" : "=r"(r[0]), "=r"(r[1]), "=r"(r[2]), "=r"(r[3]) : "r"(a) : "memory");
}
__device__ __forceinline__ void stsm4(uint32_t a, uint32_t r0, uint32_t r1, uint32_t r2, uint32_t r3) {
  asm volatile("stmatrix.sync.aligned.m8n8.x4.shared.b16 [%0], {%1,%2,%3,%4};" ::"r"(a), "r"(r0), "r"(r1), "r"(r2), "r"(r3) : "memory");
}
__device__ __forceinline__ void stsm4t(uint32_t a, uint32_t r0, uint32_t r1, uint32_t r2, uint32_t r3) {
  asm volatile("stmatrix.sync.aligned.m8n8.x4.trans.shared.b16 [%0], {%1,%2,%3,%4};" ::"r"(a), "r"(r0), "r"(r1), "r"(r2), "r"(r3) : "memory");
}
__device__ __forceinline__ uint32_t movm_t(uint32_t a) { uint32_t r; asm volatile("movmatrix.sync.aligned.m8n8.trans.b16 %0, %1;" : "=r"(r) : "r"(a)); return r; }
__device__ __forceinline__ uint32_t lds32(uint32_t a) { uint32_t v; asm volatile("ld.shared.b32 %0, [%1];" : "=r"(v) : "r"(a) : "memory"); return v; }
__device__ __forceinline__ float2 lds64f(uint32_t a) { float2 v; asm volatile("ld.shared.v2.f32 {%0,%1}, [%2];" : "=f"(v.x), "=f"(v.y) : "r"(a) : "memory"); return v; }
__device__ __forceinline__ float4 lds128f(uint32_t a) { float4 v; asm volatile("ld.shared.v4.f32 {%0,%1,%2,%3}, [%4];" : "=f"(v.x), "=f"(v.y), "=f"(v.z), "=f"(v.w) : "r"(a) : "memory"); return v; }
__device__ __forceinline__ uint4 lds128(uint32_t a) { uint4 v; asm volatile("ld.shared.v4.b32 {%0,%1,%2,%3}, [%4];" : "=r"(v.x), "=r"(v.y), "=r"(v.z), "=r"(v.w) : "r"(a) : "memory"); return v; }
__device__ __forceinline__ void sts128(uint32_t a, uint4 v) { asm volatile("st.shared.v4.b32 [%0], {%1,%2,%3,%4};" ::"r"(a), "r"(v.x), "r"(v.y), "r"(v.z), "r"(v.w) : "memory"); }
__device__ __forceinline__ void sts128f(uint32_t a, float x, float y, float z, float w) { asm volatile("st.shared.v4.f32 [%0], {%1,%2,%3,%4};" ::"r"(a), "f"(x), "f"(y), "f"(z), "f"(w) : "memory"); }
__device__ __forceinline__ void sts32f(uint32_t a, float v) { asm volatile("st.shared.f32 [%0], %1;" ::"r"(a), "f"(v) : "memory"); }
__device__ __forceinline__ void sts16(uint32_t a, uint16_t v) { asm volatile("st.shared.u16 [%0], %1;" ::"r"(a), "h"(v) : "memory"); }
__device__ __forceinline__ uint32_t lds16(uint32_t a) { uint16_t v; asm volatile("ld.shared.u16 %0, [%1];" : "=h"(v) : "r"(a) : "memory"); return v; }
__device__ __forceinline__ uint32_t packbf(float lo, float hi) { uint32_t r; asm("cvt.rn.bf16x2.f32 %0, %1, %2;" : "=r"(r) : "f"(hi), "f"(lo)); return r; }
__device__ __forceinline__ float bf_lo(uint32_t v) { return __uint_as_float(v << 16); }
__device__ __forceinline__ float bf_hi(uint32_t v) { return __uint_as_float(v & 0xffff0000u); }
__device__ __forceinline__ float ex2(float x) { float r; asm("ex2.approx.ftz.f32 %0, %1;" : "=f"(r) : "f"(x)); return r; }
__device__ __forceinline__ float rsqrt_approx(float x) { float r; asm("rsqrt.approx.ftz.f32 %0, %1;" : "=f"(r) : "f"(x)); return r; }
__device__ __forceinline__ float rcp_approx(float x) { float r; asm("rcp.approx.ftz.f32 %0, %1;" : "=f"(r) : "f"(x)); return r; }
__device__ __forceinline__ void mma_bf16(float* d, const uint32_t* a, uint32_t b0, uint32_t b1) {
  asm("mma.sync.aligned.m16n8k16.row.col.f32.bf16.bf16.f32 {%0,%1,%2,%3}, {%4,%5,%6,%7}, {%8,%9}, {%0,%1,%2,%3};"
               : "+f"(d[0]), "+f"(d[1]), "+f"(d[2]), "+f"(d[3]) : "r"(a[0]), "r"(a[1]), "r"(a[2]), "r"(a[3]), "r"(b0), "r"(b1));
}
__device__ __forceinline__ void mma_tf32(float* d, float a0, float a1, float a2, float a3, float b0, float b1) {
  asm("mma.sync.aligned.m16n8k8.row.col.f32.tf32.tf32.f32 {%0,%1,%2,%3}, {%4,%5,%6,%7}, {%8,%9}, {%0,%1,%2,%3};"
               : "+f"(d[0]), "+f"(d[1]), "+f"(d[2]), "+f"(d[3])
               : "r"(__float_as_uint(a0)), "r"(__float_as_uint(a1)), "r"(__float_as_uint(a2)), "r"(__float_as_uint(a3)),
                 "r"(__float_as_uint(b0)), "r"(__float_as_uint(b1)));
}
__device__ __forceinline__ void red_release(unsigned* p) { asm volatile("red.release.gpu.global.add.u32 [%0], 1;" ::"l"(p) : "memory"); }
__device__ __forceinline__ void red_relaxed(unsigned* p) { asm volatile("red.relaxed.gpu.global.add.u32 [%0], 1;" ::"l"(p) : "memory"); }
__device__ __forceinline__ void red_publish(unsigned* p) {
  fence_async_global();
  red_release(p);
}
__device__ __forceinline__ unsigned ld_relaxed(const unsigned* p) { unsigned v; asm volatile("ld.relaxed.gpu.global.u32 %0, [%1];" : "=r"(v) : "l"(p) : "memory"); return v; }
__device__ __forceinline__ void spin_until(const unsigned* p, unsigned target) {
  int it = 0;
  while ((int)(ld_relaxed(p) - target) < 0) {
    if (++it > (1 << 23)) __trap();
  }
}
__device__ __forceinline__ uint4 ldcg128(const void* p) { uint4 v; asm volatile("ld.global.cg.v4.b32 {%0,%1,%2,%3}, [%4];" : "=r"(v.x), "=r"(v.y), "=r"(v.z), "=r"(v.w) : "l"(p) : "memory"); return v; }
__device__ __forceinline__ uint4 ld_tagged(const uint4* p) { uint4 v; asm volatile("ld.relaxed.gpu.global.v4.u32 {%0,%1,%2,%3}, [%4];" : "=r"(v.x), "=r"(v.y), "=r"(v.z), "=r"(v.w) : "l"(p) : "memory"); return v; }
__device__ __forceinline__ void st_tagged(uint4* p, uint32_t a, uint32_t b, uint32_t tag) { asm volatile("st.relaxed.gpu.global.v4.u32 [%0], {%1,%2,%3,%2};" ::"l"(p), "r"(a), "r"(tag), "r"(b) : "memory"); }
__device__ __forceinline__ void st_tagged3(uint4* p, uint32_t a, uint32_t b, uint32_t c, uint32_t tag) { asm volatile("st.relaxed.gpu.global.v4.u32 [%0], {%1,%2,%3,%4};" ::"l"(p), "r"(a), "r"(b), "r"(c), "r"(tag) : "memory"); }
__device__ __forceinline__ uint4 poll_tagged(const uint4* p, uint32_t tag) {
  uint4 v = ld_tagged(p);
  int it = 0;
  while (v.y != tag || v.w != tag) {
    if (++it > (1 << 22)) __trap();
    v = ld_tagged(p);
  }
  return v;
}
__device__ __forceinline__ uint32_t hadd2(uint32_t a, uint32_t b) { uint32_t r; asm("add.rn.bf16x2 %0, %1, %2;" : "=r"(r) : "r"(a), "r"(b)); return r; }
__device__ __forceinline__ uint32_t hmul2(uint32_t a, uint32_t b) { uint32_t r; asm("mul.rn.bf16x2 %0, %1, %2;" : "=r"(r) : "r"(a), "r"(b)); return r; }

__device__ __forceinline__ uint32_t hfma2(uint32_t a, uint32_t b, uint32_t c) { uint32_t r; asm("fma.rn.bf16x2 %0, %1, %2, %3;" : "=r"(r) : "r"(a), "r"(b), "r"(c)); return r; }
__device__ __forceinline__ void sts32(uint32_t a, uint32_t v) { asm volatile("st.shared.u32 [%0], %1;" ::"r"(a), "r"(v) : "memory"); }

template <int N> __device__ __forceinline__ void acc_fence(float* a) {
#pragma unroll
  for (int i = 0; i < N; i++) asm volatile("" : "+f"(a[i]) :: "memory");
}

template<int N,int TB> __device__ __forceinline__ void wgmma_rs(float* d, const uint32_t* a, uint64_t db, int sd);
template<int N,int TA,int TB> __device__ __forceinline__ void wgmma_ss(float* d, uint64_t da, uint64_t db, int sd);
template<> __device__ __forceinline__ void wgmma_rs<64,0>(float* d, const uint32_t* a, uint64_t db, int sd) {
  asm volatile("{\n.reg .pred p;\nsetp.ne.b32 p, %37, 0;\nwgmma.mma_async.sync.aligned.m64n64k16.f32.bf16.bf16 {%0,%1,%2,%3,%4,%5,%6,%7,%8,%9,%10,%11,%12,%13,%14,%15,%16,%17,%18,%19,%20,%21,%22,%23,%24,%25,%26,%27,%28,%29,%30,%31}, {%32,%33,%34,%35}, %36, p, 1, 1, 0;\n}\n"
   : "+f"(d[0]),"+f"(d[1]),"+f"(d[2]),"+f"(d[3]),"+f"(d[4]),"+f"(d[5]),"+f"(d[6]),"+f"(d[7]),"+f"(d[8]),"+f"(d[9]),"+f"(d[10]),"+f"(d[11]),"+f"(d[12]),"+f"(d[13]),"+f"(d[14]),"+f"(d[15]),"+f"(d[16]),"+f"(d[17]),"+f"(d[18]),"+f"(d[19]),"+f"(d[20]),"+f"(d[21]),"+f"(d[22]),"+f"(d[23]),"+f"(d[24]),"+f"(d[25]),"+f"(d[26]),"+f"(d[27]),"+f"(d[28]),"+f"(d[29]),"+f"(d[30]),"+f"(d[31])
   : "r"(a[0]), "r"(a[1]), "r"(a[2]), "r"(a[3]), "l"(db), "r"(sd));
}
template<> __device__ __forceinline__ void wgmma_rs<56,0>(float* d, const uint32_t* a, uint64_t db, int sd) {
  asm volatile("{\n.reg .pred p;\nsetp.ne.b32 p, %33, 0;\nwgmma.mma_async.sync.aligned.m64n56k16.f32.bf16.bf16 {%0,%1,%2,%3,%4,%5,%6,%7,%8,%9,%10,%11,%12,%13,%14,%15,%16,%17,%18,%19,%20,%21,%22,%23,%24,%25,%26,%27}, {%28,%29,%30,%31}, %32, p, 1, 1, 0;\n}\n"
   : "+f"(d[0]),"+f"(d[1]),"+f"(d[2]),"+f"(d[3]),"+f"(d[4]),"+f"(d[5]),"+f"(d[6]),"+f"(d[7]),"+f"(d[8]),"+f"(d[9]),"+f"(d[10]),"+f"(d[11]),"+f"(d[12]),"+f"(d[13]),"+f"(d[14]),"+f"(d[15]),"+f"(d[16]),"+f"(d[17]),"+f"(d[18]),"+f"(d[19]),"+f"(d[20]),"+f"(d[21]),"+f"(d[22]),"+f"(d[23]),"+f"(d[24]),"+f"(d[25]),"+f"(d[26]),"+f"(d[27])
   : "r"(a[0]), "r"(a[1]), "r"(a[2]), "r"(a[3]), "l"(db), "r"(sd));
}
template<> __device__ __forceinline__ void wgmma_rs<48,0>(float* d, const uint32_t* a, uint64_t db, int sd) {
  asm volatile("{\n.reg .pred p;\nsetp.ne.b32 p, %29, 0;\nwgmma.mma_async.sync.aligned.m64n48k16.f32.bf16.bf16 {%0,%1,%2,%3,%4,%5,%6,%7,%8,%9,%10,%11,%12,%13,%14,%15,%16,%17,%18,%19,%20,%21,%22,%23}, {%24,%25,%26,%27}, %28, p, 1, 1, 0;\n}\n"
   : "+f"(d[0]),"+f"(d[1]),"+f"(d[2]),"+f"(d[3]),"+f"(d[4]),"+f"(d[5]),"+f"(d[6]),"+f"(d[7]),"+f"(d[8]),"+f"(d[9]),"+f"(d[10]),"+f"(d[11]),"+f"(d[12]),"+f"(d[13]),"+f"(d[14]),"+f"(d[15]),"+f"(d[16]),"+f"(d[17]),"+f"(d[18]),"+f"(d[19]),"+f"(d[20]),"+f"(d[21]),"+f"(d[22]),"+f"(d[23])
   : "r"(a[0]), "r"(a[1]), "r"(a[2]), "r"(a[3]), "l"(db), "r"(sd));
}
template<> __device__ __forceinline__ void wgmma_rs<40,0>(float* d, const uint32_t* a, uint64_t db, int sd) {
  asm volatile("{\n.reg .pred p;\nsetp.ne.b32 p, %25, 0;\nwgmma.mma_async.sync.aligned.m64n40k16.f32.bf16.bf16 {%0,%1,%2,%3,%4,%5,%6,%7,%8,%9,%10,%11,%12,%13,%14,%15,%16,%17,%18,%19}, {%20,%21,%22,%23}, %24, p, 1, 1, 0;\n}\n"
   : "+f"(d[0]),"+f"(d[1]),"+f"(d[2]),"+f"(d[3]),"+f"(d[4]),"+f"(d[5]),"+f"(d[6]),"+f"(d[7]),"+f"(d[8]),"+f"(d[9]),"+f"(d[10]),"+f"(d[11]),"+f"(d[12]),"+f"(d[13]),"+f"(d[14]),"+f"(d[15]),"+f"(d[16]),"+f"(d[17]),"+f"(d[18]),"+f"(d[19])
   : "r"(a[0]), "r"(a[1]), "r"(a[2]), "r"(a[3]), "l"(db), "r"(sd));
}
template<> __device__ __forceinline__ void wgmma_rs<32,0>(float* d, const uint32_t* a, uint64_t db, int sd) {
  asm volatile("{\n.reg .pred p;\nsetp.ne.b32 p, %21, 0;\nwgmma.mma_async.sync.aligned.m64n32k16.f32.bf16.bf16 {%0,%1,%2,%3,%4,%5,%6,%7,%8,%9,%10,%11,%12,%13,%14,%15}, {%16,%17,%18,%19}, %20, p, 1, 1, 0;\n}\n"
   : "+f"(d[0]),"+f"(d[1]),"+f"(d[2]),"+f"(d[3]),"+f"(d[4]),"+f"(d[5]),"+f"(d[6]),"+f"(d[7]),"+f"(d[8]),"+f"(d[9]),"+f"(d[10]),"+f"(d[11]),"+f"(d[12]),"+f"(d[13]),"+f"(d[14]),"+f"(d[15])
   : "r"(a[0]), "r"(a[1]), "r"(a[2]), "r"(a[3]), "l"(db), "r"(sd));
}
template<> __device__ __forceinline__ void wgmma_rs<24,0>(float* d, const uint32_t* a, uint64_t db, int sd) {
  asm volatile("{\n.reg .pred p;\nsetp.ne.b32 p, %17, 0;\nwgmma.mma_async.sync.aligned.m64n24k16.f32.bf16.bf16 {%0,%1,%2,%3,%4,%5,%6,%7,%8,%9,%10,%11}, {%12,%13,%14,%15}, %16, p, 1, 1, 0;\n}\n"
   : "+f"(d[0]),"+f"(d[1]),"+f"(d[2]),"+f"(d[3]),"+f"(d[4]),"+f"(d[5]),"+f"(d[6]),"+f"(d[7]),"+f"(d[8]),"+f"(d[9]),"+f"(d[10]),"+f"(d[11])
   : "r"(a[0]), "r"(a[1]), "r"(a[2]), "r"(a[3]), "l"(db), "r"(sd));
}
template<> __device__ __forceinline__ void wgmma_rs<16,0>(float* d, const uint32_t* a, uint64_t db, int sd) {
  asm volatile("{\n.reg .pred p;\nsetp.ne.b32 p, %13, 0;\nwgmma.mma_async.sync.aligned.m64n16k16.f32.bf16.bf16 {%0,%1,%2,%3,%4,%5,%6,%7}, {%8,%9,%10,%11}, %12, p, 1, 1, 0;\n}\n"
   : "+f"(d[0]),"+f"(d[1]),"+f"(d[2]),"+f"(d[3]),"+f"(d[4]),"+f"(d[5]),"+f"(d[6]),"+f"(d[7])
   : "r"(a[0]), "r"(a[1]), "r"(a[2]), "r"(a[3]), "l"(db), "r"(sd));
}
template<> __device__ __forceinline__ void wgmma_rs<8,0>(float* d, const uint32_t* a, uint64_t db, int sd) {
  asm volatile("{\n.reg .pred p;\nsetp.ne.b32 p, %9, 0;\nwgmma.mma_async.sync.aligned.m64n8k16.f32.bf16.bf16 {%0,%1,%2,%3}, {%4,%5,%6,%7}, %8, p, 1, 1, 0;\n}\n"
   : "+f"(d[0]),"+f"(d[1]),"+f"(d[2]),"+f"(d[3])
   : "r"(a[0]), "r"(a[1]), "r"(a[2]), "r"(a[3]), "l"(db), "r"(sd));
}
template<> __device__ __forceinline__ void wgmma_ss<16,0,1>(float* d, uint64_t da, uint64_t db, int sd) {
  asm volatile("{\n.reg .pred p;\nsetp.ne.b32 p, %10, 0;\nwgmma.mma_async.sync.aligned.m64n16k16.f32.bf16.bf16 {%0,%1,%2,%3,%4,%5,%6,%7}, %8, %9, p, 1, 1, 0, 1;\n}\n"
   : "+f"(d[0]),"+f"(d[1]),"+f"(d[2]),"+f"(d[3]),"+f"(d[4]),"+f"(d[5]),"+f"(d[6]),"+f"(d[7])
   : "l"(da), "l"(db), "r"(sd));
}
template<> __device__ __forceinline__ void wgmma_ss<64,0,1>(float* d, uint64_t da, uint64_t db, int sd) {
  asm volatile("{\n.reg .pred p;\nsetp.ne.b32 p, %34, 0;\nwgmma.mma_async.sync.aligned.m64n64k16.f32.bf16.bf16 {%0,%1,%2,%3,%4,%5,%6,%7,%8,%9,%10,%11,%12,%13,%14,%15,%16,%17,%18,%19,%20,%21,%22,%23,%24,%25,%26,%27,%28,%29,%30,%31}, %32, %33, p, 1, 1, 0, 1;\n}\n"
   : "+f"(d[0]),"+f"(d[1]),"+f"(d[2]),"+f"(d[3]),"+f"(d[4]),"+f"(d[5]),"+f"(d[6]),"+f"(d[7]),"+f"(d[8]),"+f"(d[9]),"+f"(d[10]),"+f"(d[11]),"+f"(d[12]),"+f"(d[13]),"+f"(d[14]),"+f"(d[15]),"+f"(d[16]),"+f"(d[17]),"+f"(d[18]),"+f"(d[19]),"+f"(d[20]),"+f"(d[21]),"+f"(d[22]),"+f"(d[23]),"+f"(d[24]),"+f"(d[25]),"+f"(d[26]),"+f"(d[27]),"+f"(d[28]),"+f"(d[29]),"+f"(d[30]),"+f"(d[31])
   : "l"(da), "l"(db), "r"(sd));
}
template<> __device__ __forceinline__ void wgmma_ss<192,0,1>(float* d, uint64_t da, uint64_t db, int sd) {
  asm volatile("{\n.reg .pred p;\nsetp.ne.b32 p, %98, 0;\nwgmma.mma_async.sync.aligned.m64n192k16.f32.bf16.bf16 {%0,%1,%2,%3,%4,%5,%6,%7,%8,%9,%10,%11,%12,%13,%14,%15,%16,%17,%18,%19,%20,%21,%22,%23,%24,%25,%26,%27,%28,%29,%30,%31,%32,%33,%34,%35,%36,%37,%38,%39,%40,%41,%42,%43,%44,%45,%46,%47,%48,%49,%50,%51,%52,%53,%54,%55,%56,%57,%58,%59,%60,%61,%62,%63,%64,%65,%66,%67,%68,%69,%70,%71,%72,%73,%74,%75,%76,%77,%78,%79,%80,%81,%82,%83,%84,%85,%86,%87,%88,%89,%90,%91,%92,%93,%94,%95}, %96, %97, p, 1, 1, 0, 1;\n}\n"
   : "+f"(d[0]),"+f"(d[1]),"+f"(d[2]),"+f"(d[3]),"+f"(d[4]),"+f"(d[5]),"+f"(d[6]),"+f"(d[7]),"+f"(d[8]),"+f"(d[9]),"+f"(d[10]),"+f"(d[11]),"+f"(d[12]),"+f"(d[13]),"+f"(d[14]),"+f"(d[15]),"+f"(d[16]),"+f"(d[17]),"+f"(d[18]),"+f"(d[19]),"+f"(d[20]),"+f"(d[21]),"+f"(d[22]),"+f"(d[23]),"+f"(d[24]),"+f"(d[25]),"+f"(d[26]),"+f"(d[27]),"+f"(d[28]),"+f"(d[29]),"+f"(d[30]),"+f"(d[31]),"+f"(d[32]),"+f"(d[33]),"+f"(d[34]),"+f"(d[35]),"+f"(d[36]),"+f"(d[37]),"+f"(d[38]),"+f"(d[39]),"+f"(d[40]),"+f"(d[41]),"+f"(d[42]),"+f"(d[43]),"+f"(d[44]),"+f"(d[45]),"+f"(d[46]),"+f"(d[47]),"+f"(d[48]),"+f"(d[49]),"+f"(d[50]),"+f"(d[51]),"+f"(d[52]),"+f"(d[53]),"+f"(d[54]),"+f"(d[55]),"+f"(d[56]),"+f"(d[57]),"+f"(d[58]),"+f"(d[59]),"+f"(d[60]),"+f"(d[61]),"+f"(d[62]),"+f"(d[63]),"+f"(d[64]),"+f"(d[65]),"+f"(d[66]),"+f"(d[67]),"+f"(d[68]),"+f"(d[69]),"+f"(d[70]),"+f"(d[71]),"+f"(d[72]),"+f"(d[73]),"+f"(d[74]),"+f"(d[75]),"+f"(d[76]),"+f"(d[77]),"+f"(d[78]),"+f"(d[79]),"+f"(d[80]),"+f"(d[81]),"+f"(d[82]),"+f"(d[83]),"+f"(d[84]),"+f"(d[85]),"+f"(d[86]),"+f"(d[87]),"+f"(d[88]),"+f"(d[89]),"+f"(d[90]),"+f"(d[91]),"+f"(d[92]),"+f"(d[93]),"+f"(d[94]),"+f"(d[95])
   : "l"(da), "l"(db), "r"(sd));
}
template<> __device__ __forceinline__ void wgmma_ss<192,1,1>(float* d, uint64_t da, uint64_t db, int sd) {
  asm volatile("{\n.reg .pred p;\nsetp.ne.b32 p, %98, 0;\nwgmma.mma_async.sync.aligned.m64n192k16.f32.bf16.bf16 {%0,%1,%2,%3,%4,%5,%6,%7,%8,%9,%10,%11,%12,%13,%14,%15,%16,%17,%18,%19,%20,%21,%22,%23,%24,%25,%26,%27,%28,%29,%30,%31,%32,%33,%34,%35,%36,%37,%38,%39,%40,%41,%42,%43,%44,%45,%46,%47,%48,%49,%50,%51,%52,%53,%54,%55,%56,%57,%58,%59,%60,%61,%62,%63,%64,%65,%66,%67,%68,%69,%70,%71,%72,%73,%74,%75,%76,%77,%78,%79,%80,%81,%82,%83,%84,%85,%86,%87,%88,%89,%90,%91,%92,%93,%94,%95}, %96, %97, p, 1, 1, 1, 1;\n}\n"
   : "+f"(d[0]),"+f"(d[1]),"+f"(d[2]),"+f"(d[3]),"+f"(d[4]),"+f"(d[5]),"+f"(d[6]),"+f"(d[7]),"+f"(d[8]),"+f"(d[9]),"+f"(d[10]),"+f"(d[11]),"+f"(d[12]),"+f"(d[13]),"+f"(d[14]),"+f"(d[15]),"+f"(d[16]),"+f"(d[17]),"+f"(d[18]),"+f"(d[19]),"+f"(d[20]),"+f"(d[21]),"+f"(d[22]),"+f"(d[23]),"+f"(d[24]),"+f"(d[25]),"+f"(d[26]),"+f"(d[27]),"+f"(d[28]),"+f"(d[29]),"+f"(d[30]),"+f"(d[31]),"+f"(d[32]),"+f"(d[33]),"+f"(d[34]),"+f"(d[35]),"+f"(d[36]),"+f"(d[37]),"+f"(d[38]),"+f"(d[39]),"+f"(d[40]),"+f"(d[41]),"+f"(d[42]),"+f"(d[43]),"+f"(d[44]),"+f"(d[45]),"+f"(d[46]),"+f"(d[47]),"+f"(d[48]),"+f"(d[49]),"+f"(d[50]),"+f"(d[51]),"+f"(d[52]),"+f"(d[53]),"+f"(d[54]),"+f"(d[55]),"+f"(d[56]),"+f"(d[57]),"+f"(d[58]),"+f"(d[59]),"+f"(d[60]),"+f"(d[61]),"+f"(d[62]),"+f"(d[63]),"+f"(d[64]),"+f"(d[65]),"+f"(d[66]),"+f"(d[67]),"+f"(d[68]),"+f"(d[69]),"+f"(d[70]),"+f"(d[71]),"+f"(d[72]),"+f"(d[73]),"+f"(d[74]),"+f"(d[75]),"+f"(d[76]),"+f"(d[77]),"+f"(d[78]),"+f"(d[79]),"+f"(d[80]),"+f"(d[81]),"+f"(d[82]),"+f"(d[83]),"+f"(d[84]),"+f"(d[85]),"+f"(d[86]),"+f"(d[87]),"+f"(d[88]),"+f"(d[89]),"+f"(d[90]),"+f"(d[91]),"+f"(d[92]),"+f"(d[93]),"+f"(d[94]),"+f"(d[95])
   : "l"(da), "l"(db), "r"(sd));
}

template <bool TR>
__device__ __forceinline__ void gemm_section(float* acc, float& mean0, float& mean1, float& rstd0, float& rstd1,
                                             uint32_t sb, int blk, int hg, int wg, int w, int lane) {
  constexpr int layer = TR ? 1 : 0;
  constexpr int TURN = TR ? TURN1 : TURN0;
  constexpr int LSTAT = TURN < 4 ? TURN - 1 : 3;
  const uint32_t bar = sb + SM_BAR;
  const int g = lane >> 2, t = lane & 3;
  const bool leader = (w == 0) && (lane == 0);
  const int statpos = hg < 3 ? 1 : wg ? LSTAT : 2;
  const bool copy = hg >= 3 && wg == 0;
  const int cut = wg ? TURN : 4;
  auto wait_full = [&](int c) {
    mbar_wait(bar + 8 * (B_XF + 8 * wg + c), layer);
    mbar_wait(bar + 8 * (B_WF + c), layer);
  };
  auto peek = [&](int c) {
    const bool x = mbar_test(bar + 8 * (B_XF + 8 * wg + c), layer), y = mbar_test(bar + 8 * (B_WF + c), layer);
    return x && y;
  };
  const uint64_t da0 = mkdesc(sb, TR ? 8192 : 16, 1024, 1), db0 = mkdesc(sb, 8192, 1024, 1);
  uint32_t xt = wg ? 0xfedcba98u : 0x21043210u;
  uint64_t wt = 0x0816131005161310ull;
  uint64_t da = da0 + ((xt & 15) << 9), db = db0 + (16 << 9);
  auto issue = [&](int c, int first) {
    TSG(2 * c);
    wg_fence();
#pragma unroll
    for (int ks = 0; ks < 4; ks++) wgmma_ss<192, TR ? 1 : 0, 1>(acc, da + (TR ? ks * 128 : ks * 2), db + ks * 128, !first || ks != 0);
    wg_commit();
    xt >>= 4; wt >>= 8;
    da = da0 + ((xt & 15) << 9); db = db0 + (((uint32_t)wt & 31) << 9);
    TSG(2 * c + 1);
  };
  uint32_t tag = 0;
  wait_full(0);
  bool ready = peek(1);
  issue(0, 1);
  TSW(0);
#pragma unroll 1
  for (int c = 1; c < cut; c++) {
    if (!ready) wait_full(c);
    issue(c, 0);
    ready = peek(c + 1);
    wg_wait<1>();
    if (leader) mbar_arrive(bar + 8 * (B_DN + 8 * wg + c - 1));
    if (wg == 1 && c == cut - 1) {
      wg_wait<0>();
      if (leader) mbar_arrive(bar + 8 * (B_DN + 8 + c));
    }
    if (c == statpos) {
      mbar_wait(bar + 8 * B_EP, 0);
      tag = 2 * lds32(sb + SM_EP) + layer + 1;
      mbar_wait(bar + 8 * (copy ? B_SC : B_XF + 8 * wg + hg), layer);
      uint32_t A[16];
      const uint32_t xb = sb + (copy ? P_R : 8 * wg + hg) * PG;
#pragma unroll
      for (int ks = 0; ks < 4; ks++) {
        if (!TR) {
          const int row = 16 * w + (lane & 15), kc = 2 * ks + (lane >> 4);
          ldsm4(&A[4 * ks], xb + row * 128 + ((kc ^ (row & 7)) << 4));
        } else {
          const int k = 16 * ks + (lane & 7) + 8 * (lane >> 4), pc = 2 * w + ((lane >> 3) & 1);
          ldsm4t(&A[4 * ks], xb + k * 128 + ((pc ^ (k & 7)) << 4));
        }
      }
      float s0 = 0.f, q0 = 0.f, s1 = 0.f, q1 = 0.f;
#pragma unroll
      for (int i = 0; i < 16; i += 2) {
        const float a = bf_lo(A[i]), b = bf_hi(A[i]), c_ = bf_lo(A[i + 1]), d = bf_hi(A[i + 1]);
        s0 += a + b; q0 = fmaf(a, a, q0); q0 = fmaf(b, b, q0);
        s1 += c_ + d; q1 = fmaf(c_, c_, q1); q1 = fmaf(d, d, q1);
      }
#pragma unroll
      for (int o = 1; o <= 2; o <<= 1) {
        s0 += __shfl_xor_sync(~0u, s0, o); q0 += __shfl_xor_sync(~0u, q0, o);
        s1 += __shfl_xor_sync(~0u, s1, o); q1 += __shfl_xor_sync(~0u, q1, o);
      }
      if (t < 2)
        st_tagged(&g_part[((layer * 32 + blk) * 8 + hg) * 64 + 16 * w + g + 8 * t], __float_as_uint(t ? s1 : s0), __float_as_uint(t ? q1 : q0), tag);
    }
  }
  if (wg == 1) mbar_wait(bar + 8 * (B_DN + GPOS), layer);
  else if (!ready) { wait_full(cut); ready = true; }
  const uint4* psrc = &g_part[((layer * 32 + blk) * 8 + 2 * t) * 64 + 16 * w + g];
  uint4 a0 = ld_tagged(psrc), a1 = ld_tagged(psrc + 8), b0 = ld_tagged(psrc + 64), b1 = ld_tagged(psrc + 72);
  if (wg == 1) {
#pragma unroll 1
    for (int c = cut; c < 8; c++) wait_full(c);
    ready = true;
    bar_sync(5, 256);
  }
#pragma unroll 1
  for (int c = cut; c < 8; c++) {
    if (!ready) wait_full(c);
    issue(c, 0);
    if (wg == 1) {
      wg_wait<2>();
      if (leader && c >= cut + 2) mbar_arrive(bar + 8 * (B_DN + 8 + c - 2));
    } else if (c == 7) {
      bar_arrive(5, 256);
    } else {
      ready = peek(c + 1);
      wg_wait<1>();
      if (leader) mbar_arrive(bar + 8 * (B_DN + c - 1));
    }
  }
  int it = 0;
  while (!__all_sync(~0u, a0.y == tag && a0.w == tag && a1.y == tag && a1.w == tag && b0.y == tag && b0.w == tag && b1.y == tag && b1.w == tag) &&
         ++it < (1 << 20)) {
    a0 = ld_tagged(psrc); a1 = ld_tagged(psrc + 8); b0 = ld_tagged(psrc + 64); b1 = ld_tagged(psrc + 72);
  }
  float s0 = __uint_as_float(a0.x) + __uint_as_float(b0.x), q0 = __uint_as_float(a0.z) + __uint_as_float(b0.z);
  float s1 = __uint_as_float(a1.x) + __uint_as_float(b1.x), q1 = __uint_as_float(a1.z) + __uint_as_float(b1.z);
#pragma unroll
  for (int o = 1; o <= 2; o <<= 1) {
    s0 += __shfl_xor_sync(~0u, s0, o); q0 += __shfl_xor_sync(~0u, q0, o);
    s1 += __shfl_xor_sync(~0u, s1, o); q1 += __shfl_xor_sync(~0u, q1, o);
  }
  mean0 = s0 * (1.f / DM); mean1 = s1 * (1.f / DM);
  rstd0 = rsqrt_approx(fmaxf(q0 * (1.f / DM) - mean0 * mean0, 0.f) + 1e-5f);
  rstd1 = rsqrt_approx(fmaxf(q1 * (1.f / DM) - mean1 * mean1, 0.f) + 1e-5f);
  TSG(16);
  mbar_wait(bar + 8 * B_CSF, 0);
  wg_wait<0>();
  acc_fence<96>(acc);
  if (leader) mbar_arrive(bar + 8 * (B_DN + 8 * wg + 7));
}

__device__ __forceinline__ void attn_phase(const Params& p, uint32_t sb, int layer, int rb, int hg, int wg, int w) {
  const int lane = opaque_tid() & 31;
  const int g = lane >> 2, t = lane & 3;
  const uint32_t bar = sb + SM_BAR;
  const int blk = 16 * wg + rb;
  float acc[96];
  float2 cs[24];
  float mean0, mean1, rstd0, rstd1;
  if (layer) gemm_section<true>(acc, mean0, mean1, rstd0, rstd1, sb, blk, hg, wg, w, lane);
  else gemm_section<false>(acc, mean0, mean1, rstd0, rstd1, sb, blk, hg, wg, w, lane);
  const uint32_t tag = 2 * lds32(sb + SM_EP) + layer + 1;
  TSW(1);
#pragma unroll
  for (int j = 8; j < 24; j++) cs[j] = lds64f(sb + SM_CS + 4 * (8 * j + 2 * t));
  const uint32_t kvx = sb + (wg ? 22 : 0) * PG;

  uint32_t kb[4][8], vb[4][8], qa[4][4];
  {
    const float nm0 = -mean0 * rstd0, nm1 = -mean1 * rstd1;
    const int st_row = 16 * w + (lane & 7) + 8 * ((lane >> 3) & 1);
    const uint32_t st_base = kvx + st_row * 256;
    const bool sender = (w == 3 && blk < 31);
    uint4* halo = &g_halo[((layer * 32 + blk) * 8 + hg) * 384 + lane];
    uint32_t r[4][2][4];
#pragma unroll
    for (int h = 0; h < 4; h++) {
#pragma unroll
      for (int kv = 0; kv < 2; kv++) {
#pragma unroll
        for (int dh = 0; dh < 2; dh++) {
          const int j = 8 + kv * 8 + 2 * h + dh;
          const float2 c2 = cs[j];
          const float v0 = fmaf(acc[4 * j + 0], rstd0, nm0 * c2.x), v1 = fmaf(acc[4 * j + 1], rstd0, nm0 * c2.y);
          const float v2 = fmaf(acc[4 * j + 2], rstd1, nm1 * c2.x), v3 = fmaf(acc[4 * j + 3], rstd1, nm1 * c2.y);
          r[h][kv][2 * dh] = packbf(v0, v1);
          r[h][kv][2 * dh + 1] = packbf(v2, v3);
        }
      }
      if (sender) {
        st_tagged3(halo + (3 * h) * 32, r[h][0][0], r[h][0][1], r[h][0][2], tag);
        st_tagged3(halo + (3 * h + 1) * 32, r[h][0][3], r[h][1][0], r[h][1][1], tag);
        st_tagged3(halo + (3 * h + 2) * 32, r[h][1][2], r[h][1][3], 0u, tag);
      }
    }
#pragma unroll
    for (int j = 0; j < 8; j++) cs[j] = lds64f(sb + SM_CS + 4 * (8 * j + 2 * t));
    mbar_wait(bar + 8 * (B_DN + 7), layer);
#pragma unroll
    for (int h = 0; h < 4; h++) {
#pragma unroll
      for (int kv = 0; kv < 2; kv++) {
        const int chunk = 4 * h + 2 * kv + (lane >> 4);
        stsm4(st_base + (((chunk & 8) | ((chunk ^ st_row) & 7)) << 4), r[h][kv][0], r[h][kv][1], r[h][kv][2], r[h][kv][3]);
      }
      kb[h][4] = r[h][0][0]; kb[h][5] = r[h][0][2]; kb[h][6] = r[h][0][1]; kb[h][7] = r[h][0][3];
      vb[h][4] = movm_t(r[h][1][0]); vb[h][5] = movm_t(r[h][1][1]); vb[h][6] = movm_t(r[h][1][2]); vb[h][7] = movm_t(r[h][1][3]);
    }
#pragma unroll
    for (int h = 0; h < 4; h++) {
#pragma unroll
      for (int dh = 0; dh < 2; dh++) {
        const int j = 2 * h + dh;
        const float2 c2 = cs[j];
        qa[h][2 * dh] = packbf(fmaf(-mean0, c2.x, acc[4 * j + 0]), fmaf(-mean0, c2.y, acc[4 * j + 1]));
        qa[h][2 * dh + 1] = packbf(fmaf(-mean1, c2.x, acc[4 * j + 2]), fmaf(-mean1, c2.y, acc[4 * j + 3]));
      }
    }
  }
  bar_sync(2 + wg, 128);
  TSW(2);
  {
    const uint32_t prev_base = kvx + (16 * w - 16) * 256;
    const int mi = lane >> 3;
    const int r = 8 * (mi >> 1) + (lane & 7), r2 = 8 * (mi & 1) + (lane & 7);
    if (w != 0) {
#pragma unroll
      for (int h = 0; h < 4; h++) {
        const int ch = 4 * h + (mi & 1), ch2 = 4 * h + 2 + (mi >> 1);
        ldsm4(&kb[h][0], prev_base + r * 256 + (((ch & 8) | ((ch ^ r) & 7)) << 4));
        ldsm4t(&vb[h][0], prev_base + r2 * 256 + (((ch2 & 8) | ((ch2 ^ r2) & 7)) << 4));
      }
    } else if (blk > 0) {
      const uint4* src = &g_halo[((layer * 32 + blk - 1) * 8 + hg) * 384 + lane];
      uint4 hv[12];
      int it = 0;
      bool ok;
      do {
        ok = true;
#pragma unroll
        for (int i = 0; i < 12; i++) hv[i] = ld_tagged(src + i * 32);
#pragma unroll
        for (int i = 0; i < 12; i++) ok = ok && hv[i].w == tag;
      } while (!__all_sync(~0u, ok) && ++it < (1 << 20));
#pragma unroll
      for (int h = 0; h < 4; h++) {
        kb[h][0] = hv[3 * h].x; kb[h][1] = hv[3 * h].z; kb[h][2] = hv[3 * h].y; kb[h][3] = hv[3 * h + 1].x;
        vb[h][0] = movm_t(hv[3 * h + 1].y); vb[h][1] = movm_t(hv[3 * h + 1].z);
        vb[h][2] = movm_t(hv[3 * h + 2].x); vb[h][3] = movm_t(hv[3 * h + 2].y);
      }
    } else {
#pragma unroll
      for (int h = 0; h < 4; h++)
#pragma unroll
        for (int k = 0; k < 4; k++) kb[h][k] = vb[h][k] = 0u;
    }
    if (w == 0 && lane == 0) mbar_arrive(bar + 8 * (B_HF + wg));
    TSW(3);
  }
  mbar_wait(bar + 8 * (B_DN + 15), layer);
  TSW(4);

  const bool first = (blk == 0 && w == 0);
  const int e = t - (g >> 1);
  const bool par = g & 1, epos = e >= 1;
  const uint32_t pmask = par ? 0xffff0000u : 0x0000ffffu;
  const uint32_t mB0 = epos ? pmask : 0u, mB1 = epos ? 0u : pmask;
  const float cl2 = 0.25f * 1.4426950408889634f;
  const float sc0 = rstd0 * cl2, sc1 = rstd1 * cl2;
  const float NEG = -INFINITY;
  float vA0[4], vB0[4], vA1[4], vB1[4];
#pragma unroll
  for (int h = 0; h < 4; h++) {
    float S[4][4];
#pragma unroll
    for (int j = 0; j < 4; j++) {
      S[j][0] = S[j][1] = S[j][2] = S[j][3] = 0.f;
      mma_bf16(S[j], qa[h], kb[h][2 * j], kb[h][2 * j + 1]);
    }
    vA0[h] = par ? S[1][1] : S[1][0];
    vB0[h] = epos ? (par ? S[0][1] : S[0][0]) : (par ? S[2][1] : S[2][0]);
    vA1[h] = par ? S[2][3] : S[2][2];
    vB1[h] = epos ? (par ? S[1][3] : S[1][2]) : (par ? S[3][3] : S[3][2]);
    if (first) { vA0[h] = NEG; if (epos) { vB0[h] = NEG; vB1[h] = NEG; } }
  }
  float m0[4], m1[4];
#pragma unroll
  for (int h = 0; h < 4; h++) { m0[h] = fmaxf(vA0[h], vB0[h]); m1[h] = fmaxf(vA1[h], vB1[h]); }
#pragma unroll
  for (int o = 1; o <= 2; o <<= 1) {
#pragma unroll
    for (int h = 0; h < 4; h++) {
      m0[h] = fmaxf(m0[h], __shfl_xor_sync(~0u, m0[h], o));
      m1[h] = fmaxf(m1[h], __shfl_xor_sync(~0u, m1[h], o));
    }
  }
  float O0[4][4], O1[4][4], Z[4][4];
#pragma unroll
  for (int h = 0; h < 4; h++) {
    const float mm0 = -m0[h] * sc0, mm1 = -m1[h] * sc1;
    const float pA0 = ex2(fmaf(vA0[h], sc0, mm0)), pB0 = ex2(fmaf(vB0[h], sc0, mm0));
    const float pA1 = ex2(fmaf(vA1[h], sc1, mm1)), pB1 = ex2(fmaf(vB1[h], sc1, mm1));
    const uint32_t hA0 = packbf(pA0, pA0), hB0 = packbf(pB0, pB0), hA1 = packbf(pA1, pA1), hB1 = packbf(pB1, pB1);
    const uint32_t P0[4] = {hB0 & mB0, 0u, hA0 & pmask, hB1 & mB0};
    const uint32_t P1[4] = {hB0 & mB1, hA1 & pmask, 0u, hB1 & mB1};
#pragma unroll
    for (int k = 0; k < 4; k++) O0[h][k] = O1[h][k] = Z[h][k] = 0.f;
    mma_bf16(O0[h], P0, vb[h][0], vb[h][1]); mma_bf16(O1[h], P0, vb[h][2], vb[h][3]); mma_bf16(Z[h], P0, 0x3f803f80u, 0x3f803f80u);
    mma_bf16(O0[h], P1, vb[h][4], vb[h][5]); mma_bf16(O1[h], P1, vb[h][6], vb[h][7]); mma_bf16(Z[h], P1, 0x3f803f80u, 0x3f803f80u);
  }
  const uint32_t ob = kvx + 2 * PG;
  const int o_row = 16 * w + (lane & 7) + 8 * ((lane >> 3) & 1);
#pragma unroll
  for (int h = 0; h < 4; h++) {
    const float i0 = rcp_approx(Z[h][0]), i1 = rcp_approx(Z[h][2]);
    const int ch = 2 * h + (lane >> 4);
    stsm4(ob + o_row * 128 + ((ch ^ (o_row & 7)) << 4), packbf(O0[h][0] * i0, O0[h][1] * i0), packbf(O0[h][2] * i1, O0[h][3] * i1),
          packbf(O1[h][0] * i0, O1[h][1] * i0), packbf(O1[h][2] * i1, O1[h][3] * i1));
  }
  TSW(5);
  fence_async_smem();
  bar_sync(2 + wg, 128);
  if (w == 0 && elect_one()) {
    tma_st(&p.mapO, hg * 64, blk * 64, ob);
    bulk_commit();
    bulk_wait_all();
    red_publish(&g_cnt[(C_O + layer * 32 + blk) * 32]);
    mbar_arrive(bar + 8 * (B_OST + wg));
    TSW(6);
  }
}

__device__ __forceinline__ void proj_phase(const Params& p, uint32_t sb, int layer, int rb, int q, int wg, int w) {
  const int lane = opaque_tid() & 31;
  const bool TR = layer != 0;
  const int t = lane & 3;
  const uint32_t bar = sb + SM_BAR;
  const uint32_t rbx = sb + (P_R + wg) * PG;
  const int blk = 16 * wg + rb;
  uint32_t res[16];
  mbar_wait(bar + 8 * (B_RF + wg), layer);
  if (!TR) {
#pragma unroll
    for (int j = 0; j < 8; j += 2) {
      const int mi = lane >> 3;
      const int row = 16 * w + (lane & 7) + 8 * (mi & 1), ch = j + (mi >> 1);
      ldsm4(&res[2 * j], rbx + row * 128 + ((ch ^ (row & 7)) << 4));
    }
  } else {
#pragma unroll
    for (int j = 0; j < 8; j += 2) {
      const int mi = lane >> 3;
      const int line = 8 * (j + (mi >> 1)) + (lane & 7), pc = 2 * w + (mi & 1);
      ldsm4t(&res[2 * j], rbx + line * 128 + ((pc ^ (line & 7)) << 4));
    }
  }
  float acc[32];
#pragma unroll
  for (int j = 0; j < 16; j++) { acc[2 * j] = bf_lo(res[j]); acc[2 * j + 1] = bf_hi(res[j]); }
  acc_fence<32>(acc);
#pragma unroll
  for (int c = 0; c < 4; c++) {
    mbar_wait(bar + 8 * (B_WOF + c), layer);
    mbar_wait(bar + 8 * (B_OF + 4 * wg + c), layer);
    if (c == 0) TSW(7);
    const uint64_t da = mkdesc(sb + o_page(wg, c) * PG, 16, 1024, 1);
    wg_fence();
#pragma unroll
    for (int ks = 0; ks < 8; ks++)
      wgmma_ss<64, 0, 1>(acc, da + (ks >> 2) * 512 + (ks & 3) * 2, mkdesc(sb + wo_page(2 * c + (ks >> 2)) * PG, 8192, 1024, 1) + (ks & 3) * 128, 1);
    wg_commit();
  }
  wg_wait<0>();
  acc_fence<32>(acc);
  TSW(8);
  if (lane == 0 && w == 0) mbar_arrive(bar + 8 * (B_PDONE + wg));
  float s0 = 0.f, q0 = 0.f, s1 = 0.f, q1 = 0.f;
  uint32_t o[16];
#pragma unroll
  for (int j = 0; j < 8; j++) {
    const float a = acc[4 * j], b = acc[4 * j + 1], c = acc[4 * j + 2], d = acc[4 * j + 3];
    o[2 * j] = packbf(a, b);
    o[2 * j + 1] = packbf(c, d);
    s0 += a + b; q0 = fmaf(a, a, q0); q0 = fmaf(b, b, q0);
    s1 += c + d; q1 = fmaf(c, c, q1); q1 = fmaf(d, d, q1);
  }
#pragma unroll
  for (int j = 0; j < 8; j += 2) {
    const int mi = lane >> 3;
    const int line = 8 * (j + (mi >> 1)) + (lane & 7), pc = 2 * w + (mi & 1);
    stsm4t(rbx + line * 128 + ((pc ^ (line & 7)) << 4), o[2 * j], o[2 * j + 1], o[2 * j + 2], o[2 * j + 3]);
  }
#pragma unroll
  for (int o2 = 1; o2 <= 2; o2 <<= 1) {
    s0 += __shfl_xor_sync(~0u, s0, o2); q0 += __shfl_xor_sync(~0u, q0, o2);
    s1 += __shfl_xor_sync(~0u, s1, o2); q1 += __shfl_xor_sync(~0u, q1, o2);
  }
  const uint32_t stg = sb + SM_STG + wg * 512;
  {
    const int row = 16 * w + (lane >> 2) + 8 * (t >> 1);
    const float v = (t == 0) ? s0 : (t == 1) ? q0 : (t == 2) ? s1 : q1;
    sts32f(stg + 4 * (((((row & 7) >> 1) * 8 + (row >> 3)) << 2) + (row & 1) * 2 + (t & 1)), v);
  }
  TSW(9);
  fence_async_smem();
  bar_sync(2 + wg, 128);
  if (w == 0 && elect_one()) {
    mbar_wait(bar + 8 * B_ZF, 0);
    tma_st(&p.mapXT, blk * 64, (2 * layer) * DM + q * 64, rbx);
    bulk_red_add_f32(g_stats + layer * LSEQ * 2 + blk * 128, stg, 512);
    bulk_commit();
    bulk_wait_all();
    red_publish(&g_cnt[(C_G + 2 * layer + wg) * 32]);
    TSW(10);
  }
}

__device__ __forceinline__ void conv_load(uint32_t* A, uint32_t pe) {
#pragma unroll
  for (int m = 0; m < 17; m++) {
    A[4 * m + 2] = lds32(pe + 4 * (64 * m - 8));
    A[4 * m + 0] = lds32(pe + 4 * (64 * m));
    A[4 * m + 1] = lds32(pe + 4 * (64 * m + 8));
    asm volatile("mov.b32 %0, %1;" : "=r"(A[4 * m + 3]) : "r"(A[4 * m + 0]));
  }
}
template <int M> __device__ __forceinline__ void conv_tri(float* acc, const uint32_t* A, uint64_t d) {
  if constexpr (M < 16) {
    wgmma_rs<64 - 8 * (M / 2), 0>(acc, A + 4 * M, d + (uint64_t)(64 + 4 * M), M != 0);
    conv_tri<M + 1>(acc, A, d);
  }
}
__device__ __forceinline__ void conv_mma0(float* acc, const uint32_t* A, uint64_t d) {
  wg_fence();
  conv_tri<0>(acc, A, d);
  wg_commit();
}
__device__ __forceinline__ void conv_mma1(float* acc, const uint32_t* A, uint64_t d) {
  wg_fence();
#pragma unroll
  for (int m = 0; m < 17; m++) wgmma_rs<64, 0>(acc, A + 4 * m, d + (uint64_t)(4 * m), m != 0);
  wg_commit();
}
__device__ __forceinline__ void conv_store(float* acc, uint32_t pb, uint32_t over, int w) {
  acc_fence<32>(acc);
  const int l = opaque_tid() & 31, mt = l >> 3;
  int c = 2 * (63 - 8 * (mt >> 1) - (l & 7) + w) + (mt & 1);
  c ^= (c >> 3) & 1;
  const uint32_t a0 = pb + c * 16;
#pragma unroll
  for (int j = 0; j < 8; j += 2)
    stsm4t(j == 0 ? (c < 128 ? a0 : over + (c - 128) * 16) : a0 - 256 * j, packbf(acc[4 * j], acc[4 * j + 1]), packbf(acc[4 * j + 2], acc[4 * j + 3]),
           packbf(acc[4 * j + 4], acc[4 * j + 5]), packbf(acc[4 * j + 6], acc[4 * j + 7]));
}
__device__ __forceinline__ void conv_far(uint32_t sb, int ht) {
  const int w = ht >> 5, l = ht & 31;
  float F[4][8];
  const uint64_t da = mkdesc(sb + cv_fa(0), 128, 128, 0), ds = mkdesc(sb + cv_se(0), 256, 256, 3);
  wg_fence();
#pragma unroll
  for (int k = 0; k < 8; k++)
#pragma unroll
    for (int c = 0; c < 4; c++) wgmma_ss<16, 0, 1>(F[c], da + c * 1024 + (k >> 2) * 128 + (k & 3) * 16, ds + c * 256 + 32 * k, k != 0);
  wg_commit();
  const uint32_t pf = sb + cv_pf(0) + (16 * w + (l & 15)) * 32 + (l >> 4) * 16;
  wg_wait<0>();
#pragma unroll
  for (int c = 0; c < 4; c++) {
    acc_fence<8>(F[c]);
    stsm4(pf + c * 2048, packbf(F[c][0], F[c][1]), packbf(F[c][2], F[c][3]), packbf(F[c][4], F[c][5]), packbf(F[c][6], F[c][7]));
  }
}
__device__ __forceinline__ void conv_sums(uint32_t sb, int lc, int ht) {
  const int m = ht - 1;
  uint4 v[2][3];
#pragma unroll
  for (int c = 0; c < 2; c++)
#pragma unroll
    for (int k = 0; k < 3; k++) {
      const int mm = m - 1 + k;
      v[c][k] = lds128(sb + cv_u(lc + c) + (mm >= 0 ? (mm & 1) * CV_UH + (127 - (mm >> 1)) * 16 : 128 * 16));
    }
  const int ce = m + 2, co = m + 1;
#pragma unroll
  for (int c = 0; c < 2; c++) {
    const uint32_t x[8] = {v[c][0].z, v[c][0].w, v[c][1].x, v[c][1].y, v[c][1].z, v[c][1].w, v[c][2].x, v[c][2].y};
    float pv[16];
#pragma unroll
    for (int k = 0; k < 8; k++) { pv[2 * k] = bf_lo(x[k]); pv[2 * k + 1] = bf_hi(x[k]); }
    float t2[15], t4[13], s9[8], s7[8];
#pragma unroll
    for (int i = 0; i < 15; i++) t2[i] = pv[i] + pv[i + 1];
#pragma unroll
    for (int i = 0; i < 13; i++) t4[i] = t2[i] + t2[i + 2];
#pragma unroll
    for (int i = 0; i < 8; i++) {
      s9[i] = (t4[i] + t4[i + 4]) + pv[i + 8];
      s7[i] = (t4[i + 1] + t2[i + 5]) + pv[i + 7];
    }
    const uint4 e4 = make_uint4(packbf(s9[0], s9[1]), packbf(s9[2], s9[3]), packbf(s9[4], s9[5]), packbf(s9[6], s9[7]));
    if (ce < 128) sts128(sb + cv_se(lc + c) + (63 - (ce >> 1)) * 32 + (((ce & 1) ^ ((ce >> 3) & 1) ^ 1) << 4), e4);
    else sts128(sb + cv_se(lc + c) + 63 * 32 + 16, make_uint4(0, 0, 0, 0));
    sts128(sb + cv_so(lc + c) + (63 - (co >> 1)) * 32 + (((co & 1) ^ ((co >> 3) & 1) ^ 1) << 4),
           make_uint4(packbf(s7[0], s7[1]), packbf(s7[2], s7[3]), packbf(s7[4], s7[5]), packbf(s7[6], s7[7])));
  }
}

template <int HALF, int NCH, int STEP = 1>
__device__ __forceinline__ void conv_epi(uint32_t sb, int lc, int c) {
  uint4 v[NCH][4], xr[NCH], f[NCH];
  const uint32_t sw = (c ^ ((c >> 3) & 1)) * 16;
#pragma unroll
  for (int u = 0; u < NCH; u++) {
#pragma unroll
    for (int k = 0; k < 4; k++) v[u][k] = lds128(sb + (HALF ? cv_pb1(lc + STEP * u, k) : cv_pb0(lc + STEP * u, k)) + sw);
    xr[u] = lds128(sb + cv_x(HALF, lc + STEP * u) + c * 16);
    if (HALF) f[u] = lds128(sb + cv_pf(lc + STEP * u) + c * 16);
  }
#pragma unroll
  for (int u = 0; u < NCH; u++) {
    if (HALF) { v[u][0].x = hadd2(v[u][0].x, f[u].x); v[u][0].y = hadd2(v[u][0].y, f[u].y); v[u][0].z = hadd2(v[u][0].z, f[u].z); v[u][0].w = hadd2(v[u][0].w, f[u].w); }
    uint4 o;
    o.x = hadd2(xr[u].x, hadd2(hadd2(v[u][0].x, v[u][1].x), hadd2(v[u][2].x, v[u][3].x)));
    o.y = hadd2(xr[u].y, hadd2(hadd2(v[u][0].y, v[u][1].y), hadd2(v[u][2].y, v[u][3].y)));
    o.z = hadd2(xr[u].z, hadd2(hadd2(v[u][0].z, v[u][1].z), hadd2(v[u][2].z, v[u][3].z)));
    o.w = hadd2(xr[u].w, hadd2(hadd2(v[u][0].w, v[u][1].w), hadd2(v[u][2].w, v[u][3].w)));
    sts128(sb + cv_x(HALF, lc + STEP * u) + c * 16, o);
  }
}

__device__ __forceinline__ void norm_factors(const uint4 (&st)[4], uint32_t (&rs)[4], uint32_t (&nm)[4]) {
#pragma unroll
  for (int k = 0; k < 4; k++) {
    const float m0 = __uint_as_float(st[k].x) * (-1.f / DM), m1 = __uint_as_float(st[k].z) * (-1.f / DM);
    const float r0 = rsqrt_approx(fmaxf(fmaf(__uint_as_float(st[k].y), 1.f / DM, -m0 * m0), 0.f) + 1e-5f);
    const float r1 = rsqrt_approx(fmaxf(fmaf(__uint_as_float(st[k].w), 1.f / DM, -m1 * m1), 0.f) + 1e-5f);
    rs[k] = packbf(r0, r1);
    nm[k] = packbf(m0 * bf_lo(rs[k]), m1 * bf_hi(rs[k]));
  }
}
__device__ __forceinline__ uint4 normalize8(uint4 x, const uint32_t (&rs)[4], const uint32_t (&nm)[4]) {
  return make_uint4(hfma2(x.x, rs[0], nm[0]), hfma2(x.y, rs[1], nm[1]), hfma2(x.z, rs[2], nm[2]), hfma2(x.w, rs[3], nm[3]));
}
__device__ __forceinline__ void conv_prep0(uint32_t sb, int layer, int cta, int c) {
  const bf16* xin = g_xT + (size_t)(2 * layer) * DM * LSEQ + c * 8;
  uint4 st[4], xr[4];
#pragma unroll
  for (int k = 0; k < 4; k++) st[k] = ldcg128(g_stats + layer * LSEQ * 2 + ((c >> 3) * 4 + k) * 32 + (c & 7) * 4);
#pragma unroll
  for (int k = 0; k < 4; k++) xr[k] = ldcg128(xin + (size_t)cv_chan(cta, k) * LSEQ);
  uint32_t rs[4], nm[4];
  norm_factors(st, rs, nm);
  const uint32_t ud = sb + (c & 1) * CV_UH + (127 - (c >> 1)) * 16;
#pragma unroll
  for (int k = 0; k < 4; k++) {
    sts128(ud + cv_u(k), normalize8(xr[k], rs, nm));
    sts128(sb + cv_x(0, k) + c * 16, xr[k]);
  }
  fence_async_smem();
  mbar_arrive(sb + SM_BAR + 8 * B_U);
}
__device__ __forceinline__ void conv_prep1(uint32_t sb, int i) {
  uint4 st[4], xr[4];
#pragma unroll
  for (int k = 0; k < 4; k++) st[k] = lds128(sb + CV_ST + ((i >> 3) * 4 + k) * 128 + (i & 7) * 16);
#pragma unroll
  for (int k = 0; k < 4; k++) xr[k] = lds128(sb + cv_x(1, k) + i * 16);
  uint32_t rs[4], nm[4];
  norm_factors(st, rs, nm);
  const uint32_t ud = sb + (i & 1) * CV_UH + (63 - (i >> 1)) * 16;
#pragma unroll
  for (int k = 0; k < 4; k++) sts128(ud + cv_u(k), normalize8(xr[k], rs, nm));
  fence_async_smem();
}

#define PP0 1
__device__ __forceinline__ void conv_phase(const Params& p, uint32_t sb, int layer, int cta) {
  const int tid = opaque_tid();
  const int wg = __shfl_sync(~0u, tid >> 7, 0), w = __shfl_sync(~0u, (tid >> 5) & 3, 0);
  const uint32_t bar = sb + SM_BAR;
  constexpr int CH2 = 4 * PG;
  uint32_t A0[68], A1[68];
  float acc[32];
  {
    const int l1 = tid & 31;
    const uint32_t pe = sb + cv_pe(wg) + 4 * (16 + 16 * w + (l1 >> 2) - 2 * (l1 & 3));
    mbar_wait(bar + 8 * B_PE, layer);
    conv_load(A0, pe);
    conv_load(A1, pe + CH2);
  }
  TSW(19);
  if (wg == 0) {
    const int i = opaque_tid();
    if (i < 32) sts128(sb + cv_u(i >> 3) + ((i >> 2) & 1) * CV_UH + (128 + (i & 3)) * 16, make_uint4(0, 0, 0, 0));
    mbar_wait(bar + 8 * B_GB, layer);
    TSW(11);
    conv_prep0(sb, layer, cta, i);
  }
  const uint64_t d0 = mkdesc(sb + cv_u(wg), CV_UH, 128, 0), d1 = d0 + (CH2 >> 4);
  mbar_wait(bar + 8 * B_U, layer);
  TSW(12);
  if (wg == 1) bar_sync(5, 256);
  conv_mma0(acc, A0, d0);
  if (wg == 0) bar_arrive(5, 256);
  mbar_wait(bar + 8 * (B_PDONE + 1), layer);
  {
    const int l = opaque_tid() & 31;
    if ((l & 15) < 2 * w) sts128(sb + cv_pb0(wg + 2 * (l >> 4), w) + (l & 15) * 16, make_uint4(0, 0, 0, 0));
  }
  wg_wait<0>();
  conv_store(acc, sb + cv_pb0(wg, w), sb + cv_pb1(wg, w), w);
  conv_mma0(acc, A1, d1);
  bar_sync(2 + wg, 128);
  conv_epi<0, 1>(sb, wg, opaque_tid() & 127);
  wg_wait<0>();
  conv_store(acc, sb + cv_pb0(2 + wg, w), sb + cv_pb1(2 + wg, w), w);
  TSW(13);
  bar_sync(2 + wg, 128);
  conv_epi<0, 1>(sb, 2 + wg, opaque_tid() & 127);
  fence_async_smem();
  mbar_arrive(bar + 8 * B_PUB);
  TSW(14);
  mbar_wait(bar + 8 * (B_GB + 1), layer);
  if (wg == 0) {
    conv_prep1(sb, opaque_tid());
    bar_sync(2, 128);
  } else {
    bar_sync(6, 256);
  }
  TSW(15);
  conv_mma1(acc, A0, d0);
  if (wg == 0) bar_arrive(6, 256);
  mbar_wait(bar + 8 * B_FARM, layer);
  wg_wait<0>();
  conv_store(acc, sb + cv_pb1(wg, w), sb + cv_dump(wg), w);
  mbar_arrive(bar + 8 * (B_R + 1));
  TSW(16);
  conv_mma1(acc, A1, d1);
  wg_wait<0>();
  conv_store(acc, sb + cv_pb1(2 + wg, w), sb + cv_dump(2 + wg), w);
  TSW(17);
  if (wg == 0) {
    mbar_arrive(bar + 8 * (B_R + 2));
  } else {
    bar_sync(3, 128);
    conv_epi<1, 1>(sb, 3, opaque_tid() & 127);
    fence_async_smem();
    mbar_arrive(bar + 8 * (B_PUB + 2));
    TSW(18);
  }
}

__device__ __forceinline__ void final_phase(const Params& p, uint32_t sb, int cta, int wg, int w) {
  const int lane = opaque_tid() & 31;
  const uint32_t bar = sb + SM_BAR;
  mbar_wait(bar + 8 * (B_TF + wg), 0);
  if (threadIdx.x == 128) TS(8);
  const uint32_t src = sb + (16 + wg) * PG, dst = src + 2 * PG;
  const int mi = lane >> 3;
#pragma unroll
  for (int j = 0; j < 8; j += 2) {
    uint32_t r[4];
    const int line = 8 * (j + (mi >> 1)) + (lane & 7), pc = 2 * w + (mi & 1);
    ldsm4t(r, src + line * 128 + ((pc ^ (line & 7)) << 4));
    const int row = 16 * w + (lane & 7) + 8 * (mi & 1), ch = j + (mi >> 1);
    stsm4(dst + row * 128 + ((ch ^ (row & 7)) << 4), r[0], r[1], r[2], r[3]);
  }
  fence_async_smem();
  bar_sync(2 + wg, 128);
  if (w == 0 && elect_one()) {
    tma_st(&p.mapOut, (cta >> 4) * 64, (16 * wg + (cta & 15)) * 64, dst);
    bulk_commit();
    asm volatile("cp.async.bulk.wait_group.read 0;" ::: "memory");
    if (threadIdx.x == 128) TS(9);
    if (threadIdx.x == 128) LTS(1);
  }
}

struct cplx { float r, i; };
__device__ __forceinline__ cplx cmul(cplx a, cplx b) { return {fmaf(a.r, b.r, -a.i * b.i), fmaf(a.r, b.i, a.i * b.r)}; }
__device__ __forceinline__ cplx csqr(cplx a) { return {fmaf(a.r, a.r, -a.i * a.i), (a.r + a.r) * a.i}; }
__device__ __forceinline__ cplx cexp_l(float ar2, float ai, float l) {
  const float m = ex2(ar2 * l);
  const float x = ai * l;
  return {m * __cosf(x), m * __sinf(x)};
}

__device__ __forceinline__ void colsum_cta(const Params& p, uint32_t sb, int j, int tid) {
  const uint32_t bar = sb + SM_BAR;
  auto ld = [&](int i) {
    mbar_expect(bar + 8 * i, 3 * PG);
    tma_ld3(sb + (i & 7) * 3 * PG, &p.mapW3, (2 * j + (i & 1)) * 64, (i >> 1) * 64, 0, bar + 8 * i);
  };
  if (tid == 384) {
#pragma unroll
    for (int i = 0; i < 24; i++) mbar_init(bar + 8 * i, i < 16 ? 1 : 12);
    asm volatile("fence.mbarrier_init.release.cluster;" ::: "memory");
    fence_async_smem();
#pragma unroll 1
    for (int i = 0; i < 8; i++) ld(i);
  }
  const unsigned ep = ld_relaxed(&g_cnt[C_CS * 32]);
  bar_sync(0, NTHREADS);
  if (tid == 384) {
#pragma unroll 1
    for (int i = 8; i < 16; i++) { mbar_wait(bar + 8 * (8 + i), 0); fence_async_smem(); ld(i); }
  }
  if (tid < 384) {
    const int lane = tid & 31, cc = tid & 7, r0 = (tid >> 3) & 15, part = tid >> 7;
    const uint32_t id = ((lane >> 2) == 2 * (lane & 3) ? 0x3f80u : 0u) | ((lane >> 2) == 2 * (lane & 3) + 1 ? 0x3f800000u : 0u);
    const uint32_t src = sb + part * PG + r0 * 128 + ((cc ^ (r0 & 7)) << 4);
    float s[2][2][4];
#pragma unroll
    for (int i = 0; i < 16; i++) s[i >> 3][(i >> 2) & 1][i & 3] = 0.f;
#pragma unroll 1
    for (int i2 = 0; i2 < 16; i2 += 2) {
#pragma unroll
      for (int h = 0; h < 2; h++) {
        const int i = i2 + h;
        mbar_wait(bar + 8 * i, 0);
        uint4 v[4];
#pragma unroll
        for (int k = 0; k < 4; k++) v[k] = lds128(src + (i & 7) * 3 * PG + k * 2048);
#pragma unroll
        for (int k = 0; k < 4; k++) {
          const uint32_t a[4] = {v[k].x, v[k].y, v[k].z, v[k].w};
          mma_bf16(s[h][0], a, id, 0u);
          mma_bf16(s[h][1], a, 0u, id);
        }
        __syncwarp();
        if (i < 8 && lane == 0) mbar_arrive(bar + 8 * (16 + i));
      }
    }
    const uint32_t red = sb + 24 * PG;
#pragma unroll
    for (int h = 0; h < 2; h++)
#pragma unroll
      for (int k = 0; k < 2; k++) sts128f(red + (r0 * 384 + h * 192 + part * 64 + cc * 8 + k * 4) * 4, s[h][k][0], s[h][k][1], s[h][k][2], s[h][k][3]);
    bar_sync(1, 384);
    float tot = 0.f;
#pragma unroll
    for (int k = 0; k < 16; k++) tot += __uint_as_float(lds32(red + (k * 384 + tid) * 4));
    asm volatile("st.relaxed.gpu.global.v2.u32 [%0], {%1,%2};" ::"l"(&g_colsum[j * 384 + tid]), "r"(__float_as_uint(tot)), "r"(ep / NCTA + 1) : "memory");
  }
}

#define KW 3
struct ModeIn { uint32_t ar, ai, br, bi, cr, ci; bf16 logdt; };
__device__ __forceinline__ ModeIn load_modes(const Params& p, int d, int m) {
  const int i = d * 64 + m;
  return {((const uint32_t*)p.a_re)[i], ((const uint32_t*)p.a_im)[i], ((const uint32_t*)p.b_re)[i], ((const uint32_t*)p.b_im)[i],
          ((const uint32_t*)p.c_re)[i], ((const uint32_t*)p.c_im)[i], p.log_dt[d]};
}
__device__ __forceinline__ float4 lds128f_nv(uint32_t a) { float4 v; asm("ld.shared.v4.f32 {%0,%1,%2,%3}, [%4];" : "=f"(v.x), "=f"(v.y), "=f"(v.z), "=f"(v.w) : "r"(a)); return v; }
__device__ __forceinline__ void kernel_gen(const Params& p, uint32_t sb, int cta, int ht, ModeIn in, const ModeIn& in1) {
  const uint32_t bst = sb + SM_KGB + ((ht & 63) >> 2) * 144 + (ht & 3) * 4 + (ht >> 6) * 16;
  const uint64_t db = mkdesc(sb + SM_KGB, 144, 2304, 0);
  const float e0 = (float)(8 * (((ht & 32) >> 1) + ((ht & 31) >> 2)));
  float T[20];
#pragma unroll
  for (int i = 0; i < 20; i++) T[i] = 0.f;
  float k0 = (ht & 63) ? 0.f : __bfloat162float(p.dskip[cv_chan(cta, ht >> 6)]);
#pragma unroll 1
  for (int pass = 0; pass < 4; pass++) {
    {
      const int sh = (pass & 1) ? 0 : 16;
      auto val = [&](uint32_t v) { return __uint_as_float((v << sh) & 0xffff0000u); };
      const float dt = __bfloat162float(__float2bfloat16_rn(expf(__bfloat162float(in.logdt))));
      const float ar2 = dt * val(in.ar) * 1.4426950408889634f, ai = dt * val(in.ai);
      const cplx c = cmul({val(in.cr), -val(in.ci)}, {dt * val(in.br), -dt * val(in.bi)});
      k0 += c.r;
      const cplx z1 = cexp_l(ar2, -ai, 1.f), z256 = cexp_l(ar2, -ai, 256.f), z64 = cexp_l(ar2, ai, 64.f);
      const cplx z2 = csqr(z1), z512 = csqr(z256);
      auto put = [&](int j, cplx v) { sts32(bst + (j >> 2) * 2304 + (j & 3) * 32, packbf(v.r, v.i)); };
      sts128f(sb + SM_KGT + ht * 16, ar2, ai, z64.r, z64.i);
      const cplx c1 = cmul(c, z1), c2 = cmul(c, z2), c3 = cmul(c1, z2), c4 = cmul(c2, z2);
      const cplx c5 = cmul(c3, z2), c6 = cmul(c4, z2), c7 = cmul(c5, z2), c8 = cmul(c6, z2);
      put(0, c1); put(1, c2); put(2, c3); put(3, c4); put(4, c5); put(5, c6); put(6, c7); put(7, c8);
      const cplx c260 = cmul(c4, z256), c264 = cmul(c8, z256), c520 = cmul(c8, z512), c776 = cmul(c264, z512);
      put(8, cmul(c2, z256)); put(9, c260); put(10, cmul(c6, z256)); put(11, c264);
      put(12, cmul(c4, z512)); put(13, c520); put(14, cmul(c260, z512)); put(15, c776);
      const cplx c1032 = cmul(c520, z512), c1288 = cmul(c776, z512);
      put(16, c1032); put(17, c1288); put(18, cmul(c1032, z512)); put(19, cmul(c1288, z512));
    }
    fence_async_smem();
    bar_sync(4, 128);
    uint32_t tb = sb + SM_KGT + (ht & 67) * 16;
    asm volatile("mov.u32 %0, %0;" : "+r"(tb) :: "memory");
#pragma unroll
    for (int q = 0; q < 4; q++) {
      uint32_t A[8];
      if (q >= KW) wg_wait<KW - 1>();
#pragma unroll
      for (int s = 0; s < 4; s++) {
        const float4 v = lds128f_nv(tb + (4 * q + s) * 64);
        const cplx lo = cexp_l(v.x, v.y, e0), hi = cmul(lo, {v.z, v.w});
        A[2 * s] = packbf(lo.r, lo.i);
        A[2 * s + 1] = packbf(hi.r, hi.i);
      }
      wg_fence();
      wgmma_rs<40, 0>(T, A, db + 36 * q, (pass & 1) | q);
      wgmma_rs<40, 0>(T, A + 4, db + 36 * q + 18, 1);
      wg_commit();
    }
    wg_wait<0>();
    acc_fence<20>(T);
    if (ht == 0) TS(4 + pass);
    if (pass & 1) {
      const int h2 = opaque_tid() - 256, w = h2 >> 5, lane = h2 & 31, t = lane & 3, chn = h2 >> 6, m = h2 & 63, i0 = 16 * (w & 1) + (lane >> 2);
      const int lc = (pass & 2) + chn;
      const uint32_t kc = sb + kc_off(lc);
      auto put = [&](int idx, float v) {
        sts16(kc + idx * 2, __bfloat16_as_ushort(__float2bfloat16_rn(v)));
      };
#pragma unroll
      for (int hi = 0; hi < 2; hi++) {
        const int i = i0 + 8 * hi;
        float v[5];
#pragma unroll
        for (int j = 0; j < 5; j++) v[j] = chn ? T[4 * j + 2 * hi + 1] : T[4 * j + 2 * hi];
        put(8 * i + 1 + t, v[0]);
        put(8 * i + 5 + t, v[1]);
        put(257 + 4 * i + t, v[2]);
        put(385 + 2 * i + (t & 1) + 64 * (t >> 1), v[3]);
        put(513 + i + 32 * t, v[4]);
      }
#pragma unroll
      for (int o = 16; o > 0; o >>= 1) k0 += __shfl_xor_sync(~0u, k0, o);
      if (lane == 0) sts32f(sb + SM_RED + 4 * w, k0);
      bar_sync(4, 128);
      if (m == 0) put(0, k0 + __uint_as_float(lds32(sb + SM_RED + 4 * w + 4)));
      k0 = m ? 0.f : __bfloat162float(p.dskip[cv_chan(cta, 2 + chn)]);
      in = in1;
    }
  }
}

__device__ __forceinline__ void expand_taps(uint32_t sb, int ht) {
  const int ch = ht >> 5, lane = ht & 31;
  const uint32_t kc = sb + kc_off(ch);
  const uint32_t dst0 = sb + cv_pe(ch);
  auto put = [&](int G, uint32_t v0, uint32_t v1, uint32_t v2, uint32_t v3, uint32_t v4, uint32_t v5, uint32_t v6, uint32_t v7, uint32_t v8) {
    const uint32_t dst = dst0 + G * 32;
    sts128(dst, make_uint4(v1 | (v0 << 16), v2 | (v1 << 16), v3 | (v2 << 16), v4 | (v3 << 16)));
    sts128(dst + 16, make_uint4(v5 | (v4 << 16), v6 | (v5 << 16), v7 | (v6 << 16), v8 | (v7 << 16)));
  };
  {
    const uint4 q = lds128(kc + lane * 16);
    const uint32_t pv = lane ? lds16(kc + lane * 16 - 2) : 0u;
    const uint32_t dst = dst0 + (lane + 2) * 32;
    sts128(dst, make_uint4(__byte_perm(q.x, pv, 0x5410), __byte_perm(q.x, q.x, 0x1032), __byte_perm(q.y, q.x, 0x7610), __byte_perm(q.y, q.y, 0x1032)));
    sts128(dst + 16, make_uint4(__byte_perm(q.z, q.y, 0x7610), __byte_perm(q.z, q.z, 0x1032), __byte_perm(q.w, q.z, 0x7610), __byte_perm(q.w, q.w, 0x1032)));
    if (lane < 4) sts128(dst0 + lane * 16, make_uint4(0, 0, 0, 0));
  }
  uint32_t a[5], b[2][3];
  {
    const uint32_t s1 = kc + 2 * (256 + 4 * lane);
#pragma unroll
    for (int k = 0; k < 5; k++) a[k] = lds16(s1 + 2 * k);
#pragma unroll
    for (int u = 0; u < 2; u++) {
      const uint32_t s2 = kc + 2 * (384 + 2 * (lane + 32 * u));
#pragma unroll
      for (int k = 0; k < 3; k++) b[u][k] = lds16(s2 + 2 * k);
    }
  }
  const uint32_t k255 = lds16(kc + 2 * 255), k1024 = lds16(kc + 2 * 512);
  put(34 + lane, lane == 0 ? k255 : a[0], a[0], a[0], a[1], a[2], a[2], a[2], a[3], a[4]);
#pragma unroll
  for (int u = 0; u < 2; u++) put(66 + lane + 32 * u, b[u][0], b[u][0], b[u][0], b[u][0], b[u][1], b[u][1], b[u][1], b[u][2], b[u][2]);
  if (lane < 10) {
    const uint32_t v = lane == 0 ? k1024 : 0u;
    put(130 + lane, v, v, v, v, v, v, 0u, 0u, 0u);
  }
}
__device__ __forceinline__ void expand_far(uint32_t sb, int ht) {
  const int ch = ht >> 5, lane = ht & 31;
  const uint32_t kc = sb + kc_off(ch) + 4 * (249 + lane), dst = sb + cv_fa(ch);
  uint32_t v[2][9];
#pragma unroll
  for (int u = 0; u < 2; u++)
#pragma unroll
    for (int k = 0; k < 9; k++) v[u][k] = lds32(kc + 4 * (32 * u + k));
#pragma unroll
  for (int k = 0; k < 8; k++) v[0][k] = lane + k < 7 ? 0u : lane + k == 7 ? v[0][k] & 0xffff0000u : v[0][k];
#pragma unroll
  for (int u = 0; u < 2; u++) {
    const uint32_t row = dst + (56 + 32 * u + lane) * 16;
    sts128(row, make_uint4(__byte_perm(v[u][1], v[u][2], 0x5410), __byte_perm(v[u][3], v[u][4], 0x5410), __byte_perm(v[u][5], v[u][6], 0x5410), __byte_perm(v[u][7], v[u][8], 0x5410)));
    sts128(row + 2048, make_uint4(__byte_perm(v[u][0], v[u][1], 0x7632), __byte_perm(v[u][2], v[u][3], 0x7632), __byte_perm(v[u][4], v[u][5], 0x7632), __byte_perm(v[u][6], v[u][7], 0x7632)));
    sts128(dst + u * 2048 + lane * 16, make_uint4(0, 0, 0, 0));
    if (lane < 24) sts128(dst + u * 2048 + (32 + lane) * 16, make_uint4(0, 0, 0, 0));
  }
}

#define WPRE 2
__host__ __device__ constexpr int bar_count(int i) {
  return i == B_END ? 3 : (i == B_PUB + 2 || i == B_PUB || i == B_R + 1) ? 256 : (i >= B_FARM && i < B_END) ? 128 : 1;
}
__host__ __device__ constexpr bool bar_first(int i) { return i < B_WF + 2 && (i & 7) < 2; }

__global__ void __launch_bounds__(NTHREADS, 1) fused_kernel(const __grid_constant__ Params p) {
  extern __shared__ __align__(1024) uint8_t smem[];
  const uint32_t sb = s32(smem);
  const int tid = threadIdx.x, lane = tid & 31;
  const int warp = __shfl_sync(~0u, tid >> 5, 0);
  if (blockIdx.x < 4) {
    colsum_cta(p, sb, blockIdx.x, tid);
    return;
  }
  const int cta = blockIdx.x - 4;
  const int rb = ((cta >> 4) & 3) * 4 + ((cta >> 2) & 3), hg = (cta >> 6) * 4 + (cta & 3);
  const int rb2 = cta >> 3, q2 = cta & 7;
  const uint32_t bar = sb + SM_BAR;
  auto ld_x0 = [&](int half, int c) {
    const uint32_t b = bar + 8 * (B_XF + 8 * half + c);
    mbar_expect(b, PG);
    tma_ld(sb + x_page(half, c) * PG, &p.mapX, c * 64, (16 * half + rb) * 64, b);
  };
  auto ld_w = [&](int c) {
    const uint32_t b = bar + 8 * (B_WF + c);
    mbar_expect(b, 3 * PG);
    tma_ld3(sb + w_page(c) * PG, &p.mapW3, hg * 64, c * 64, 0, b);
  };

  if (tid == 0) TS(0);
  if (tid == 480) LTS(0);
  if (warp < 6 && elect_one()) {
    if (warp == 0) {
#pragma unroll
      for (int i = 0; i < B_WF + 2; i++)
        if (bar_first(i)) mbar_init(bar + 8 * i, 1);
      asm volatile("fence.mbarrier_init.release.cluster;" ::: "memory");
      fence_async_smem();
      ld_x0(0, 0); ld_w(0); ld_x0(1, 0);
      ld_x0(0, 1); ld_w(1); ld_x0(1, 1);
      TS(1);
    } else {
#pragma unroll
      for (int q = 0; q < 5; q++) {
        if (warp == q + 1) {
#pragma unroll
          for (int i = 0; i < B_COUNT; i++)
            if (!bar_first(i) && i % 5 == q) mbar_init(bar + 8 * i, bar_count(i));
        }
      }
      asm volatile("fence.mbarrier_init.release.cluster;" ::: "memory");
    }
  }

  if (warp < 8) {
    bar_sync(0, NTHREADS);
    asm volatile("setmaxnreg.inc.sync.aligned.u32 %0;" ::"n"(R_CONS));
    const int cw = __shfl_sync(~0u, opaque_tid() >> 5, 0);
    const int wg = cw >> 2, w = cw & 3;
    if (tid == 0) TS(2);
#pragma unroll 1
    for (int layer = 0; layer < 2; layer++) {
      attn_phase(p, sb, layer, rb, hg, wg, w);
      proj_phase(p, sb, layer, rb2, q2, wg, w);
      conv_phase(p, sb, layer, cta);
    }
    final_phase(p, sb, cta, wg, w);
  } else if (warp < 12) {
    asm volatile("setmaxnreg.dec.sync.aligned.u32 %0;" ::"n"(R_HELP));
    const int ht = tid - 256;
    {
      unsigned ep0 = 0;
      if (ht == 0) ep0 = ld_relaxed(&g_cnt[C_CS * 32]);
      const ModeIn in0 = load_modes(p, cv_chan(cta, ht >> 6), ht & 63), in1 = load_modes(p, cv_chan(cta, 2 + (ht >> 6)), ht & 63);
      bar_sync(0, NTHREADS);
      if (ht == 0) {
        sts32(sb + SM_EP, ep0 / NCTA);
        mbar_arrive(bar + 8 * B_EP);
      }
      if (hg == 0) {
        *(float4*)(g_stats + (ht >> 6) * LSEQ * 2 + rb * 256 + (ht & 63) * 4) = make_float4(0.f, 0.f, 0.f, 0.f);
      }
      mbar_arrive(bar + 8 * B_Z0);
      if (ht == 0) TS(3);
      kernel_gen(p, sb, cta, ht, in0, in1);
      fence_async_smem();
      bar_sync(4, 128);
      if (ht == 0) mbar_arrive(bar + 8 * B_KG);
    }
#pragma unroll 1
    for (int layer = 0; layer < 2; layer++) {
      mbar_wait(bar + 8 * B_PDONE, layer);
      expand_taps(sb, opaque_tid() - 256);
      mbar_arrive(bar + 8 * B_PE);
      TSW(0);
      expand_far(sb, opaque_tid() - 256);
      mbar_wait(bar + 8 * (B_PDONE + 1), layer);
      mbar_wait(bar + 8 * B_U, layer);
#pragma unroll 1
      for (int lc = 0; lc < 4; lc += 2) {
        conv_sums(sb, lc, opaque_tid() - 256);
        TSW(1 + lc);
      }
      fence_async_smem();
      bar_sync(4, 128);
      conv_far(sb, opaque_tid() - 256);
      mbar_arrive(bar + 8 * B_FARM);
      TSW(4);
      mbar_wait(bar + 8 * (B_GB + 1), layer);
      mbar_wait(bar + 8 * (B_R + 1), layer);
      conv_epi<1, 2>(sb, 0, opaque_tid() - 256);
      fence_async_smem();
      mbar_arrive(bar + 8 * (B_PUB + 1));
      TSW(5);
      mbar_wait(bar + 8 * (B_R + 2), layer);
      conv_epi<1, 1>(sb, 2, opaque_tid() - 256);
      fence_async_smem();
      mbar_arrive(bar + 8 * (B_PUB + 2));
      TSW(6);
    }
  } else {
    asm volatile("setmaxnreg.dec.sync.aligned.u32 %0;" ::"n"(R_AGENT));
    bar_sync(0, NTHREADS);
    auto done = [&](int half, int c, int layer) { mbar_wait(bar + 8 * (B_DN + 8 * half + c), layer); };
    if (warp == 12) {
      if (elect_one()) {
#pragma unroll 1
        for (int layer = 0; layer < 2; layer++) {
          auto ld_xe = [&](int c) {
            const uint32_t b = bar + 8 * (B_XF + c);
            mbar_expect(b, PG);
            if (layer == 0) tma_ld(sb + (c - 5) * PG, &p.mapX, c * 64, rb * 64, b);
            else tma_ld(sb + (c - 5) * PG, &p.mapXT, rb * 64, DM + c * 64, b);
          };
          if (layer == 0) {
            ld_x0(0, 2); ld_w(2); ld_x0(1, 2);
            if (hg >= 3) {
              mbar_expect(bar + 8 * B_SC, PG);
              tma_ld(sb + P_R * PG, &p.mapX, hg * 64, rb * 64, bar + 8 * B_SC);
            }
            if (rb < 4) tma_prefetch3(&p.mapW3, hg * 64, (4 + rb) * 64, 0);
            ld_x0(0, 3); ld_w(3); ld_x0(1, 3); ld_x0(0, 4); ld_x0(1, 4);
            done(0, 0, 0); done(1, 0, 0);
            ld_w(4);
            ld_x0(1, 5); ld_x0(1, 6); ld_x0(1, 7);
            done(0, 1, 0); done(1, 1, 0);
            ld_w(5);
            if (rb2 < 8) tma_prefetch2(&p.mapWo, q2 * 64, rb2 * 64);
            done(0, 2, 0);
            fence_async_smem();
            ld_xe(5); ld_xe(6); ld_xe(7);
          } else {
            mbar_wait(bar + 8 * B_PDONE, 0);
            mbar_wait(bar + 8 * (B_PDONE + 1), 0);
            mbar_wait(bar + 8 * (WPRE == 1 ? B_U : B_GB + 1), 0);
            ld_w(0); ld_w(1); ld_w(2);
            mbar_wait(bar + 8 * (B_PUB + 2), 0);
            fence_async_smem();
            ld_w(3);
            done(0, 2, 1);
            fence_async_global();
            fence_async_smem();
            ld_xe(5); ld_xe(6); ld_xe(7);
            done(1, 0, 1);
            ld_w(4);
            done(1, 1, 1);
            ld_w(5);
          }
          done(1, 2, layer);
          fence_async_smem();
          ld_w(6); ld_w(7);
          auto ld_res = [&](int half) {
            const uint32_t b = bar + 8 * (B_RF + half);
            mbar_expect(b, PG);
            if (layer == 0) tma_ld(sb + (P_R + half) * PG, &p.mapX, q2 * 64, (16 * half + rb2) * 64, b);
            else tma_ld(sb + (P_R + half) * PG, &p.mapXT, (16 * half + rb2) * 64, DM + q2 * 64, b);
          };
          done(0, 4, layer); done(1, 3, layer);
          fence_async_smem();
#pragma unroll 1
          for (int c = 0; c < 8; c++) {
            const uint32_t b = bar + 8 * (B_WOF + (c >> 1));
            if (c == 5) { ld_res(0); done(1, 4, layer); }
            if ((c & 1) == 0) mbar_expect(b, 2 * PG);
            tma_ld(sb + wo_page(c) * PG, &p.mapWo, q2 * 64, c * 64, b);
          }
          mbar_wait(bar + 8 * B_KG, 0);
          fence_async_global();
          ld_res(1);
        }
      }
    } else if (warp == 13) {
      if (elect_one()) {
        mbar_wait(bar + 8 * (B_WF + 2), 0);
        asm volatile("prefetch.tensormap [%0];" ::"l"(&p.mapO) : "memory");
        asm volatile("prefetch.tensormap [%0];" ::"l"(&p.mapO2) : "memory");
        asm volatile("prefetch.tensormap [%0];" ::"l"(&p.mapXT) : "memory");
        asm volatile("prefetch.tensormap [%0];" ::"l"(&p.mapOut) : "memory");
        asm volatile("prefetch.tensormap [%0];" ::"l"(&p.mapWo) : "memory");
        mbar_wait(bar + 8 * B_EP, 0);
        const unsigned e1 = lds32(sb + SM_EP) + 1;
        auto ld_x1 = [&](int half, int c0, int c1) {
          fence_async_global();
          fence_async_smem();
#pragma unroll 1
          for (int c = c0; c < c1; c++) {
            const uint32_t b = bar + 8 * (B_XF + 8 * half + c);
            mbar_expect(b, PG);
            tma_ld(sb + x_page(half, c) * PG, &p.mapXT, (16 * half + rb) * 64, DM + c * 64, b);
          }
        };
#pragma unroll 1
        for (int layer = 0; layer < 2; layer++) {
          if (layer == 1) {
            mbar_wait(bar + 8 * B_FARM, 0);
            mbar_wait(bar + 8 * B_PUB, 0);
            spin_until(&g_cnt[C_C * 32], e1 * NCTA);
            TS(10);
            ld_x1(0, 0, 3);
            if (hg >= 3) {
              mbar_expect(bar + 8 * B_SC, PG);
              tma_ld(sb + P_R * PG, &p.mapXT, rb * 64, DM + hg * 64, bar + 8 * B_SC);
            }
            ld_x1(0, 3, 5);
            mbar_wait(bar + 8 * (B_PUB + 1), 0);
            spin_until(&g_cnt[(C_C + 1) * 32], e1 * NCTA);
            TS(11);
            ld_x1(1, 0, 4);
            spin_until(&g_cnt[(C_C + 2) * 32], e1 * NCTA);
            TS(12);
            ld_x1(1, 4, 8);
          }
#pragma unroll 1
          for (int half = 0; half < 2; half++) {
            done(1, 7, layer);
            mbar_wait(bar + 8 * B_OST, layer);
            if (half) mbar_wait(bar + 8 * (B_OST + 1), layer);
            spin_until(&g_cnt[(C_O + layer * 32 + 16 * half + rb2) * 32], e1 * 8);
            fence_async_global();
            fence_async_smem();
#pragma unroll 1
            for (int c = 0; c < 4; c++) {
              const uint32_t b = bar + 8 * (B_OF + 4 * half + c);
              mbar_expect(b, 2 * PG);
              tma_ld3(sb + o_page(half, c) * PG, &p.mapO2, 0, (16 * half + rb2) * 64, 2 * c, b);
            }
          }
        }
        mbar_wait(bar + 8 * B_PUB, 1);
#pragma unroll 1
        for (int half = 0; half < 2; half++) {
          spin_until(&g_cnt[(C_F + 4 * (half ? 1 + (cta >> 6) : 0) + ((cta >> 4) & 3)) * 32], e1 * 32);
          fence_async_global();
          mbar_expect(bar + 8 * (B_TF + half), PG);
          tma_ld(sb + (16 + half) * PG, &p.mapXT, (16 * half + (cta & 15)) * 64, 3 * DM + (cta >> 4) * 64, bar + 8 * (B_TF + half));
        }
      }
    } else if (warp == 14) {
      mbar_wait(bar + 8 * B_EP, 0);
      const unsigned e1 = lds32(sb + SM_EP) + 1;
      done(0, 1, 0);
      {
        uint2 v[6];
        bool ok;
        int it = 0;
        do {
          ok = true;
#pragma unroll
          for (int i = 0; i < 6; i++) {
            const int k = lane + 32 * i;
            asm volatile("ld.relaxed.gpu.global.v2.u32 {%0,%1}, [%2];" : "=r"(v[i].x), "=r"(v[i].y) : "l"(&g_colsum[hg * 192 + k]) : "memory");
            ok = ok && v[i].y == e1;
          }
          if (++it > (1 << 22)) __trap();
        } while (!__all_sync(~0u, ok));
#pragma unroll
        for (int i = 0; i < 6; i++) sts32f(sb + SM_CS + 4 * (lane + 32 * i), __uint_as_float(v[i].x));
      }
      __syncwarp();
      if (lane == 0) {
        mbar_arrive(bar + 8 * B_CSF);
        TS(13);
        mbar_wait(bar + 8 * B_Z0, 0);
        red_release(&g_cnt[C_CS * 32]);
        spin_until(&g_cnt[C_CS * 32], e1 * NCTA);
        mbar_arrive(bar + 8 * B_ZF);
#pragma unroll 1
        for (int i = 0; i < 4; i++) {
          mbar_wait(bar + 8 * (B_PDONE + (i & 1)), i >> 1);
          spin_until(&g_cnt[(C_G + i) * 32], e1 * NCTA);
          if (i & 1) {
            const uint32_t b = bar + 8 * (B_GB + 1);
            fence_async_global();
            fence_async_smem();
            mbar_expect(b, 2 * PG);
            bulk_ld(sb + CV_ST, g_stats + (i >> 1) * LSEQ * 2 + LSEQ, PG, b);
#pragma unroll 1
            for (int lc = 0; lc < 4; lc++) bulk_ld(sb + cv_x(1, lc), g_xT + ((size_t)(i - 1) * DM + cv_chan(cta, lc)) * LSEQ + 1024, 2048, b);
            TS(14 + (i >> 1));
          } else {
            mbar_arrive(bar + 8 * B_GB);
          }
        }
      }
    } else if (elect_one()) {
#pragma unroll 1
      for (int i = 0; i < 6; i++) {
        const int layer = i >= 3, k = i - 3 * layer, half = k != 0;
        bf16* xout = g_xT + (size_t)(2 * layer + 1) * DM * LSEQ + half * 1024;
        mbar_wait(bar + 8 * (B_PUB + k), layer);
#pragma unroll 1
        for (int lc = (k & 2); lc < (k == 1 ? 2 : 4); lc++) bulk_st(xout + (size_t)cv_chan(cta, lc) * LSEQ, sb + cv_x(half, lc), 2048);
        bulk_commit();
        bulk_wait_all();
        red_publish(&g_cnt[(layer ? C_F + 4 * k + (cta >> 5) : C_C + k) * 32]);
        TS(16 + layer * 56 + 40 + 7 + k);
      }
    }
  }
}

typedef CUresult (*EncodeFn)(CUtensorMap*, CUtensorMapDataType, cuuint32_t, void*, const cuuint64_t*, const cuuint64_t*,
                             const cuuint32_t*, const cuuint32_t*, CUtensorMapInterleave, CUtensorMapSwizzle,
                             CUtensorMapL2promotion, CUtensorMapFloatOOBfill);

static void make_map(EncodeFn enc, CUtensorMap* m, void* ptr, uint64_t cols, uint64_t rows, uint32_t box_rows) {
  cuuint64_t dims[2] = {cols, rows};
  cuuint64_t strides[1] = {cols * 2};
  cuuint32_t box[2] = {64, box_rows};
  cuuint32_t es[2] = {1, 1};
  enc(m, CU_TENSOR_MAP_DATA_TYPE_BFLOAT16, 2, ptr, dims, strides, box, es, CU_TENSOR_MAP_INTERLEAVE_NONE,
      CU_TENSOR_MAP_SWIZZLE_128B, CU_TENSOR_MAP_L2_PROMOTION_L2_128B, CU_TENSOR_MAP_FLOAT_OOB_FILL_NONE);
}
static void make_map3(EncodeFn enc, CUtensorMap* m, void* ptr, uint64_t d0, uint64_t cols, uint64_t rows, uint64_t blk_stride,
                      uint64_t nblocks, uint32_t nblk) {
  cuuint64_t dims[3] = {d0, rows, nblocks};
  cuuint64_t strides[2] = {cols * 2, blk_stride * 2};
  cuuint32_t box[3] = {64, 64, nblk};
  cuuint32_t es[3] = {1, 1, 1};
  enc(m, CU_TENSOR_MAP_DATA_TYPE_BFLOAT16, 3, ptr, dims, strides, box, es, CU_TENSOR_MAP_INTERLEAVE_NONE,
      CU_TENSOR_MAP_SWIZZLE_128B, CU_TENSOR_MAP_L2_PROMOTION_L2_128B, CU_TENSOR_MAP_FLOAT_OOB_FILL_NONE);
}

extern "C" void kernel_launch(void* const* d_in, const int* in_sizes, int n_in, void* d_out, int out_size) {
  static Params prm;
  static void* cached[13] = {nullptr};
  static bool attr_done = false;
  bool same = attr_done && cached[12] == d_out;
  for (int i = 0; i < 12 && same; i++) same = cached[i] == d_in[i];
  if (!same) {
    void* fn = nullptr;
    cudaDriverEntryPointQueryResult qr;
    cudaGetDriverEntryPoint("cuTensorMapEncodeTiled", &fn, cudaEnableDefault, &qr);
    EncodeFn enc = (EncodeFn)fn;
    void *pO, *pXT;
    cudaGetSymbolAddress(&pO, g_O);
    cudaGetSymbolAddress(&pXT, g_xT);
    make_map(enc, &prm.mapX, d_in[0], DM, LSEQ, 64);
    make_map(enc, &prm.mapO, pO, DM, LSEQ, 64);
    make_map(enc, &prm.mapXT, pXT, LSEQ, 4 * DM, 64);
    make_map(enc, &prm.mapOut, d_out, DM, LSEQ, 64);
    make_map(enc, &prm.mapWo, d_in[2], DM, DM, 64);
    make_map3(enc, &prm.mapW3, d_in[1], DM, 3 * DM, DM, DM, 3, 3);
    make_map3(enc, &prm.mapO2, pO, 64, DM, LSEQ, 64, 8, 2);
    prm.wqkv = (const bf16*)d_in[1];
    prm.a_re = (const bf16*)d_in[4]; prm.a_im = (const bf16*)d_in[5];
    prm.b_re = (const bf16*)d_in[6]; prm.b_im = (const bf16*)d_in[7];
    prm.c_re = (const bf16*)d_in[8]; prm.c_im = (const bf16*)d_in[9];
    prm.log_dt = (const bf16*)d_in[10]; prm.dskip = (const bf16*)d_in[11];
    cudaFuncSetAttribute(fused_kernel, cudaFuncAttributeMaxDynamicSharedMemorySize, SM_TOTAL);
    for (int i = 0; i < 12; i++) cached[i] = d_in[i];
    cached[12] = d_out;
    attr_done = true;
  }
  fused_kernel<<<NCTA + 4, NTHREADS, SM_TOTAL>>>(prm);
}
```

```cpp
#include <cuda_runtime.h>
#include <cuda_bf16.h>
#include <cuda.h>
#include <stdint.h>

typedef __nv_bfloat16 bf16;

constexpr int LSEQ = 2048;
constexpr int DM = 512;
constexpr int NCTA = 128;
constexpr int NTHREADS = 512;
#define R_CONS 200
#define R_HELP 88
#define R_AGENT 24
#define GPOS 4
#define TURN0 3
#define TURN1 3

constexpr int PG = 8192;
constexpr int P_R = 25;
__host__ __device__ constexpr int x_page(int half, int c) { return half ? 8 + c : c < 5 ? c : c - 5; }
__host__ __device__ constexpr int w_page(int c) { return (c & 3) < 3 ? 16 + 3 * (c & 3) : c < 4 ? 5 : 8; }
__host__ __device__ constexpr int wo_page(int c) { return c < 5 ? 3 + c : 11 + c; }
__host__ __device__ constexpr int o_page(int half, int pair) { return half ? (pair ? 17 + 2 * pair : 0) : 8 + 2 * pair; }
constexpr int SM_KGB = (P_R + 1) * PG;
constexpr int SM_KC = 27 * PG;
constexpr int KC_STRIDE = 648;
__host__ __device__ constexpr int kc_off(int lc) { return SM_KC + (lc & 1) * 2 * KC_STRIDE + (lc < 2 ? 3328 : 0); }
constexpr int SM_KGT = SM_KC + 3328 + 2592;
constexpr int SM_CS = SM_KGT + 2048;
constexpr int SM_RED = SM_CS + 768;
constexpr int SM_EP = SM_RED + 16;
constexpr int SM_STG = SM_KGT;
constexpr int SM_BAR = SM_RED + 32;
constexpr int SM_TS = SM_BAR + 768;
constexpr int SM_TOTAL = SM_TS + 512;
static_assert(SM_TOTAL <= 232448 && SM_STG % 16 == 0 && SM_KGT % 16 == 0, "shared memory");

constexpr int CV_UH = 140 * 16;
__host__ __device__ constexpr int cv_u(int lc) { return (8 + 2 * lc) * PG; }
__host__ __device__ constexpr int cv_pe(int lc) { return cv_u(lc) + 4480; }
__host__ __device__ constexpr int cv_pb1(int lc, int w) { return w ? cv_u(lc) + 8960 + (w - 1) * 2048 : 7 * PG + lc * 2048; }
__host__ __device__ constexpr int cv_fa(int lc) { return cv_pb1(lc, 1) + 128; }
__host__ __device__ constexpr int cv_dump(int lc) { return cv_u(lc) + 16256; }
__host__ __device__ constexpr int cv_pb0(int lc, int w) { return lc * PG + w * 2048; }
__host__ __device__ constexpr int cv_se(int lc) { return 4 * PG + lc * 4096; }
__host__ __device__ constexpr int cv_so(int lc) { return cv_se(lc) + 2048; }
__host__ __device__ constexpr int cv_pf(int lc) { return 6 * PG + lc * 2048; }
__host__ __device__ constexpr int cv_x(int half, int lc) { return (P_R + half) * PG + lc * 2048; }
__host__ __device__ constexpr int cv_chan(int cta, int lc) { return 2 * cta + (lc & 1) + 256 * (lc >> 1); }

enum {
  B_XF = 0,
  B_WF = 16,
  B_OF = 24,
  B_DN = 32,
  B_WOF = 48,
  B_RF = 52,
  B_PST = 54,
  B_OST = 56,
  B_PDONE = 58,
  B_GB = 60,
  B_TF = 62,
  B_CSF = 64,
  B_EP = 65,
  B_ZF = 66,
  B_KG = 67,
  B_FARM = 68,
  B_PE = 70,
  B_U = 71,
  B_PUB = 74,
  B_R = 77,
  B_END = 80,
  B_SC = 81,
  B_RT = 82,
  B_AL = 84,
  B_COUNT = 85
};

enum {
  C_CS = 0,
  C_G = 1,
  C_C = 5,
  C_F = 8,
  C_O = 20,
  C_COUNT = 84
};

__device__ unsigned g_cnt[C_COUNT * 32];
__device__ __align__(1024) bf16 g_O[LSEQ * DM];
__device__ __align__(1024) bf16 g_xT[4 * DM * LSEQ];
__device__ __align__(1024) float g_stats[2 * 32 * 192];
__device__ __align__(1024) uint2 g_colsum[3 * DM];
__device__ __align__(1024) uint4 g_halo[2 * 32 * 8 * 384];
__device__ __align__(1024) uint4 g_part[2 * 32 * 8 * 64];
#define TS(i) do { } while (0)
#define TSW(k) do { if ((threadIdx.x & 127) == 0) TS(16 + layer * 56 + (threadIdx.x >> 7) * 20 + (k)); } while (0)
#define TSG(k) do { } while (0)

#define RETRY(i) do { } while (0)
#define LTS(i) do { } while (0)

struct Params {
  CUtensorMap mapX, mapW3, mapO2, mapXT, mapOut, mapWo;
  const bf16 *wqkv, *a_re, *a_im, *b_re, *b_im, *c_re, *c_im, *log_dt, *dskip;
};

__device__ __forceinline__ uint32_t s32(const void* p) { return (uint32_t)__cvta_generic_to_shared(p); }
__device__ __forceinline__ void mbar_init(uint32_t b, int c) { asm volatile("mbarrier.init.shared::cta.b64 [%0], %1;" ::"r"(b), "r"(c) : "memory"); }
__device__ __forceinline__ void mbar_expect(uint32_t b, int bytes) { asm volatile("mbarrier.arrive.expect_tx.shared::cta.b64 _, [%0], %1;" ::"r"(b), "r"(bytes) : "memory"); }
__device__ __forceinline__ void mbar_arrive(uint32_t b) { asm volatile("mbarrier.arrive.shared::cta.b64 _, [%0];" ::"r"(b) : "memory"); }
__device__ __forceinline__ void mbar_wait(uint32_t b, int parity) {
  asm volatile("{\n.reg .pred p;\nWAIT_LOOP:\nmbarrier.try_wait.parity.shared::cta.b64 p, [%0], %1;\n@p bra WAIT_DONE;\nbra WAIT_LOOP;\nWAIT_DONE:\n}" ::"r"(b), "r"(parity) : "memory");
}
__device__ __forceinline__ bool mbar_test(uint32_t b, int parity) {
  uint32_t ok;
  asm volatile("{\n.reg .pred p;\nmbarrier.test_wait.parity.shared::cta.b64 p, [%1], %2;\nselp.u32 %0, 1, 0, p;\n}" : "=r"(ok) : "r"(b), "r"(parity) : "memory");
  return ok != 0;
}
__device__ __forceinline__ int opaque_tid() { int v; asm volatile("mov.u32 %0, %%tid.x;" : "=r"(v)); return v; }
__device__ __forceinline__ bool elect_one() {
  uint32_t r;
  asm volatile("{\n.reg .pred p;\nelect.sync _|p, 0xffffffff;\nselp.u32 %0, 1, 0, p;\n}" : "=r"(r));
  return r != 0;
}
__device__ __forceinline__ void tma_ld(uint32_t dst, const CUtensorMap* m, int c0, int c1, uint32_t bar) {
  asm volatile("cp.async.bulk.tensor.2d.shared::cluster.global.mbarrier::complete_tx::bytes [%0], [%1, {%3, %4}], [%2];"
               ::"r"(dst), "l"(m), "r"(bar), "r"(c0), "r"(c1) : "memory");
}
__device__ __forceinline__ void tma_ld3(uint32_t dst, const CUtensorMap* m, int c0, int c1, int c2, uint32_t bar) {
  asm volatile("cp.async.bulk.tensor.3d.shared::cluster.global.mbarrier::complete_tx::bytes [%0], [%1, {%3, %4, %5}], [%2];"
               ::"r"(dst), "l"(m), "r"(bar), "r"(c0), "r"(c1), "r"(c2) : "memory");
}
__device__ __forceinline__ void tma_ld5(uint32_t dst, const CUtensorMap* m, int c0, int c4, uint32_t bar) {
  asm volatile("cp.async.bulk.tensor.5d.shared::cluster.global.mbarrier::complete_tx::bytes [%0], [%1, {%3, 0, 0, 0, %4}], [%2];"
               ::"r"(dst), "l"(m), "r"(bar), "r"(c0), "r"(c4) : "memory");
}
__device__ __forceinline__ void tma_prefetch5(const CUtensorMap* m, int c0, int c4) {
  asm volatile("cp.async.bulk.prefetch.tensor.5d.L2.global.tile [%0, {%1, 0, 0, 0, %2}];" ::"l"(m), "r"(c0), "r"(c4) : "memory");
}
__device__ __forceinline__ void tma_prefetch2(const CUtensorMap* m, int c0, int c1) {
  asm volatile("cp.async.bulk.prefetch.tensor.2d.L2.global.tile [%0, {%1, %2}];" ::"l"(m), "r"(c0), "r"(c1) : "memory");
}
__device__ __forceinline__ void tma_prefetch3(const CUtensorMap* m, int c0, int c1, int c2) {
  asm volatile("cp.async.bulk.prefetch.tensor.3d.L2.global.tile [%0, {%1, %2, %3}];" ::"l"(m), "r"(c0), "r"(c1), "r"(c2) : "memory");
}
__device__ __forceinline__ void tma_st(const CUtensorMap* m, int c0, int c1, uint32_t src) {
  asm volatile("cp.async.bulk.tensor.2d.global.shared::cta.bulk_group [%0, {%2, %3}], [%1];" ::"l"(m), "r"(src), "r"(c0), "r"(c1) : "memory");
}
__device__ __forceinline__ void bulk_ld(uint32_t dst, const void* src, int bytes, uint32_t bar) {
  asm volatile("cp.async.bulk.shared::cluster.global.mbarrier::complete_tx::bytes [%0], [%1], %2, [%3];" ::"r"(dst), "l"(src), "r"(bytes), "r"(bar) : "memory");
}
__device__ __forceinline__ void bulk_st(void* dst, uint32_t src, int bytes) {
  asm volatile("cp.async.bulk.global.shared::cta.bulk_group [%0], [%1], %2;" ::"l"(dst), "r"(src), "r"(bytes) : "memory");
}
__device__ __forceinline__ void bulk_red_add_f32(void* dst, uint32_t src, int bytes) {
  asm volatile("cp.reduce.async.bulk.global.shared::cta.bulk_group.add.f32 [%0], [%1], %2;" ::"l"(dst), "r"(src), "r"(bytes) : "memory");
}
__device__ __forceinline__ void bulk_commit() { asm volatile("cp.async.bulk.commit_group;" ::: "memory"); }
__device__ __forceinline__ void bulk_wait_all() { asm volatile("cp.async.bulk.wait_group 0;" ::: "memory"); }
__device__ __forceinline__ void fence_async_smem() { asm volatile("fence.proxy.async.shared::cta;" ::: "memory"); }
__device__ __forceinline__ void fence_async_global() { asm volatile("fence.proxy.async.global;" ::: "memory"); }
__device__ __forceinline__ void bar_sync(int id, int n) { asm volatile("bar.sync %0, %1;" ::"r"(id), "r"(n) : "memory"); }
__device__ __forceinline__ void bar_arrive(int id, int n) { asm volatile("bar.arrive %0, %1;" ::"r"(id), "r"(n) : "memory"); }
__device__ __forceinline__ bool bar_or(int id, int n, bool v) {
  uint32_t r;
  asm volatile("{\n.reg .pred p, q;\nsetp.ne.u32 q, %3, 0;\nbar.red.or.pred p, %1, %2, q;\nselp.u32 %0, 1, 0, p;\n}" : "=r"(r) : "r"(id), "r"(n), "r"((uint32_t)v) : "memory");
  return r != 0;
}
__device__ __forceinline__ void bulk_wait_read() { asm volatile("cp.async.bulk.wait_group.read 0;" ::: "memory"); }
__device__ __forceinline__ void stg128(void* p, uint4 v) { asm volatile("st.relaxed.gpu.global.v4.u32 [%0], {%1,%2,%3,%4};" ::"l"(p), "r"(v.x), "r"(v.y), "r"(v.z), "r"(v.w) : "memory"); }
constexpr uint32_t UNSET = 0xffffffffu;
constexpr int MAX_RETRY = 1 << 16;
__device__ __forceinline__ void wg_fence() { asm volatile("wgmma.fence.sync.aligned;" ::: "memory"); }
__device__ __forceinline__ void wg_commit() { asm volatile("wgmma.commit_group.sync.aligned;" ::: "memory"); }
template <int N> __device__ __forceinline__ void wg_wait() { asm volatile("wgmma.wait_group.sync.aligned %0;" ::"n"(N) : "memory"); }
__device__ __forceinline__ uint64_t mkdesc(uint32_t addr, uint32_t lbo, uint32_t sbo, int sw) {
  return (uint64_t)((addr & 0x3FFFF) >> 4) | ((uint64_t)(lbo >> 4) << 16) | ((uint64_t)(sbo >> 4) << 32) | ((uint64_t)sw << 62);
}
__device__ __forceinline__ void ldsm4(uint32_t* r, uint32_t a) {
  asm volatile("ldmatrix.sync.aligned.m8n8.x4.shared.b16 {%0,%1,%2,%3}, [%4];" : "=r"(r[0]), "=r"(r[1]), "=r"(r[2]), "=r"(r[3]) : "r"(a) : "memory");
}
__device__ __forceinline__ void ldsm4t(uint32_t* r, uint32_t a) {
  asm volatile("ldmatrix.sync.aligned.m8n8.x4.trans.shared.b16 {%0,%1,%2,%3}, [%4];" : "=r"(r[0]), "=r"(r[1]), "=r"(r[2]), "=r"(r[3]) : "r"(a) : "memory");
}
__device__ __forceinline__ void stsm4(uint32_t a, uint32_t r0, uint32_t r1, uint32_t r2, uint32_t r3) {
  asm volatile("stmatrix.sync.aligned.m8n8.x4.shared.b16 [%0], {%1,%2,%3,%4};" ::"r"(a), "r"(r0), "r"(r1), "r"(r2), "r"(r3) : "memory");
}
__device__ __forceinline__ void stsm4t(uint32_t a, uint32_t r0, uint32_t r1, uint32_t r2, uint32_t r3) {
  asm volatile("stmatrix.sync.aligned.m8n8.x4.trans.shared.b16 [%0], {%1,%2,%3,%4};" ::"r"(a), "r"(r0), "r"(r1), "r"(r2), "r"(r3) : "memory");
}
__device__ __forceinline__ uint32_t movm_t(uint32_t a) { uint32_t r; asm volatile("movmatrix.sync.aligned.m8n8.trans.b16 %0, %1;" : "=r"(r) : "r"(a)); return r; }
__device__ __forceinline__ uint32_t lds32(uint32_t a) { uint32_t v; asm volatile("ld.shared.b32 %0, [%1];" : "=r"(v) : "r"(a) : "memory"); return v; }
__device__ __forceinline__ float2 lds64f(uint32_t a) { float2 v; asm volatile("ld.shared.v2.f32 {%0,%1}, [%2];" : "=f"(v.x), "=f"(v.y) : "r"(a) : "memory"); return v; }
__device__ __forceinline__ float4 lds128f(uint32_t a) { float4 v; asm volatile("ld.shared.v4.f32 {%0,%1,%2,%3}, [%4];" : "=f"(v.x), "=f"(v.y), "=f"(v.z), "=f"(v.w) : "r"(a) : "memory"); return v; }
__device__ __forceinline__ uint4 lds128(uint32_t a) { uint4 v; asm volatile("ld.shared.v4.b32 {%0,%1,%2,%3}, [%4];" : "=r"(v.x), "=r"(v.y), "=r"(v.z), "=r"(v.w) : "r"(a) : "memory"); return v; }
__device__ __forceinline__ void sts128(uint32_t a, uint4 v) { asm volatile("st.shared.v4.b32 [%0], {%1,%2,%3,%4};" ::"r"(a), "r"(v.x), "r"(v.y), "r"(v.z), "r"(v.w) : "memory"); }
__device__ __forceinline__ void sts128f(uint32_t a, float x, float y, float z, float w) { asm volatile("st.shared.v4.f32 [%0], {%1,%2,%3,%4};" ::"r"(a), "f"(x), "f"(y), "f"(z), "f"(w) : "memory"); }
__device__ __forceinline__ void sts32f(uint32_t a, float v) { asm volatile("st.shared.f32 [%0], %1;" ::"r"(a), "f"(v) : "memory"); }
__device__ __forceinline__ void sts16(uint32_t a, uint16_t v) { asm volatile("st.shared.u16 [%0], %1;" ::"r"(a), "h"(v) : "memory"); }
__device__ __forceinline__ uint32_t lds16(uint32_t a) { uint16_t v; asm volatile("ld.shared.u16 %0, [%1];" : "=h"(v) : "r"(a) : "memory"); return v; }
__device__ __forceinline__ uint32_t packbf(float lo, float hi) { uint32_t r; asm("cvt.rn.bf16x2.f32 %0, %1, %2;" : "=r"(r) : "f"(hi), "f"(lo)); return r; }
__device__ __forceinline__ float bf_lo(uint32_t v) { return __uint_as_float(v << 16); }
__device__ __forceinline__ float bf_hi(uint32_t v) { return __uint_as_float(v & 0xffff0000u); }
__device__ __forceinline__ float ex2(float x) { float r; asm("ex2.approx.ftz.f32 %0, %1;" : "=f"(r) : "f"(x)); return r; }
__device__ __forceinline__ float rsqrt_approx(float x) { float r; asm("rsqrt.approx.ftz.f32 %0, %1;" : "=f"(r) : "f"(x)); return r; }
__device__ __forceinline__ float rcp_approx(float x) { float r; asm("rcp.approx.ftz.f32 %0, %1;" : "=f"(r) : "f"(x)); return r; }
__device__ __forceinline__ void mma_bf16(float* d, const uint32_t* a, uint32_t b0, uint32_t b1) {
  asm("mma.sync.aligned.m16n8k16.row.col.f32.bf16.bf16.f32 {%0,%1,%2,%3}, {%4,%5,%6,%7}, {%8,%9}, {%0,%1,%2,%3};"
               : "+f"(d[0]), "+f"(d[1]), "+f"(d[2]), "+f"(d[3]) : "r"(a[0]), "r"(a[1]), "r"(a[2]), "r"(a[3]), "r"(b0), "r"(b1));
}
__device__ __forceinline__ void mma_tf32(float* d, float a0, float a1, float a2, float a3, float b0, float b1) {
  asm("mma.sync.aligned.m16n8k8.row.col.f32.tf32.tf32.f32 {%0,%1,%2,%3}, {%4,%5,%6,%7}, {%8,%9}, {%0,%1,%2,%3};"
               : "+f"(d[0]), "+f"(d[1]), "+f"(d[2]), "+f"(d[3])
               : "r"(__float_as_uint(a0)), "r"(__float_as_uint(a1)), "r"(__float_as_uint(a2)), "r"(__float_as_uint(a3)),
                 "r"(__float_as_uint(b0)), "r"(__float_as_uint(b1)));
}
__device__ __forceinline__ void red_release(unsigned* p) { asm volatile("red.release.gpu.global.add.u32 [%0], 1;" ::"l"(p) : "memory"); }
__device__ __forceinline__ void red_relaxed(unsigned* p) { asm volatile("red.relaxed.gpu.global.add.u32 [%0], 1;" ::"l"(p) : "memory"); }
__device__ __forceinline__ unsigned ld_relaxed(const unsigned* p) { unsigned v; asm volatile("ld.relaxed.gpu.global.u32 %0, [%1];" : "=r"(v) : "l"(p) : "memory"); return v; }
__device__ __forceinline__ void spin_until(const unsigned* p, unsigned target) {
  int it = 0;
  while ((int)(ld_relaxed(p) - target) < 0) {
    if (++it > (1 << 23)) __trap();
  }
}
__device__ __forceinline__ uint4 ldcg128(const void* p) { uint4 v; asm volatile("ld.global.cg.v4.b32 {%0,%1,%2,%3}, [%4];" : "=r"(v.x), "=r"(v.y), "=r"(v.z), "=r"(v.w) : "l"(p) : "memory"); return v; }
__device__ __forceinline__ uint4 ld_tagged(const uint4* p) { uint4 v; asm volatile("ld.relaxed.gpu.global.v4.u32 {%0,%1,%2,%3}, [%4];" : "=r"(v.x), "=r"(v.y), "=r"(v.z), "=r"(v.w) : "l"(p) : "memory"); return v; }
__device__ __forceinline__ void st_tagged(uint4* p, uint32_t a, uint32_t b, uint32_t tag) { asm volatile("st.relaxed.gpu.global.v4.u32 [%0], {%1,%2,%3,%2};" ::"l"(p), "r"(a), "r"(tag), "r"(b) : "memory"); }
__device__ __forceinline__ void st_tagged3(uint4* p, uint32_t a, uint32_t b, uint32_t c, uint32_t tag) { asm volatile("st.relaxed.gpu.global.v4.u32 [%0], {%1,%2,%3,%4};" ::"l"(p), "r"(a), "r"(b), "r"(c), "r"(tag) : "memory"); }
__device__ __forceinline__ uint4 poll_tagged(const uint4* p, uint32_t tag) {
  uint4 v = ld_tagged(p);
  int it = 0;
  while (v.y != tag || v.w != tag) {
    if (++it > (1 << 22)) __trap();
    v = ld_tagged(p);
  }
  return v;
}
__device__ __forceinline__ uint32_t hadd2(uint32_t a, uint32_t b) { uint32_t r; asm("add.rn.bf16x2 %0, %1, %2;" : "=r"(r) : "r"(a), "r"(b)); return r; }
__device__ __forceinline__ uint32_t hmul2(uint32_t a, uint32_t b) { uint32_t r; asm("mul.rn.bf16x2 %0, %1, %2;" : "=r"(r) : "r"(a), "r"(b)); return r; }

__device__ __forceinline__ uint32_t hfma2(uint32_t a, uint32_t b, uint32_t c) { uint32_t r; asm("fma.rn.bf16x2 %0, %1, %2, %3;" : "=r"(r) : "r"(a), "r"(b), "r"(c)); return r; }
__device__ __forceinline__ void sts32(uint32_t a, uint32_t v) { asm volatile("st.shared.u32 [%0], %1;" ::"r"(a), "r"(v) : "memory"); }

template <int N> __device__ __forceinline__ void acc_fence(float* a) {
#pragma unroll
  for (int i = 0; i < N; i++) asm volatile("" : "+f"(a[i]) :: "memory");
}

template<int N,int TB> __device__ __forceinline__ void wgmma_rs(float* d, const uint32_t* a, uint64_t db, int sd);
template<int N,int TA,int TB> __device__ __forceinline__ void wgmma_ss(float* d, uint64_t da, uint64_t db, int sd);
template<> __device__ __forceinline__ void wgmma_rs<64,0>(float* d, const uint32_t* a, uint64_t db, int sd) {
  asm volatile("{\n.reg .pred p;\nsetp.ne.b32 p, %37, 0;\nwgmma.mma_async.sync.aligned.m64n64k16.f32.bf16.bf16 {%0,%1,%2,%3,%4,%5,%6,%7,%8,%9,%10,%11,%12,%13,%14,%15,%16,%17,%18,%19,%20,%21,%22,%23,%24,%25,%26,%27,%28,%29,%30,%31}, {%32,%33,%34,%35}, %36, p, 1, 1, 0;\n}\n"
   : "+f"(d[0]),"+f"(d[1]),"+f"(d[2]),"+f"(d[3]),"+f"(d[4]),"+f"(d[5]),"+f"(d[6]),"+f"(d[7]),"+f"(d[8]),"+f"(d[9]),"+f"(d[10]),"+f"(d[11]),"+f"(d[12]),"+f"(d[13]),"+f"(d[14]),"+f"(d[15]),"+f"(d[16]),"+f"(d[17]),"+f"(d[18]),"+f"(d[19]),"+f"(d[20]),"+f"(d[21]),"+f"(d[22]),"+f"(d[23]),"+f"(d[24]),"+f"(d[25]),"+f"(d[26]),"+f"(d[27]),"+f"(d[28]),"+f"(d[29]),"+f"(d[30]),"+f"(d[31])
   : "r"(a[0]), "r"(a[1]), "r"(a[2]), "r"(a[3]), "l"(db), "r"(sd));
}
template<> __device__ __forceinline__ void wgmma_rs<56,0>(float* d, const uint32_t* a, uint64_t db, int sd) {
  asm volatile("{\n.reg .pred p;\nsetp.ne.b32 p, %33, 0;\nwgmma.mma_async.sync.aligned.m64n56k16.f32.bf16.bf16 {%0,%1,%2,%3,%4,%5,%6,%7,%8,%9,%10,%11,%12,%13,%14,%15,%16,%17,%18,%19,%20,%21,%22,%23,%24,%25,%26,%27}, {%28,%29,%30,%31}, %32, p, 1, 1, 0;\n}\n"
   : "+f"(d[0]),"+f"(d[1]),"+f"(d[2]),"+f"(d[3]),"+f"(d[4]),"+f"(d[5]),"+f"(d[6]),"+f"(d[7]),"+f"(d[8]),"+f"(d[9]),"+f"(d[10]),"+f"(d[11]),"+f"(d[12]),"+f"(d[13]),"+f"(d[14]),"+f"(d[15]),"+f"(d[16]),"+f"(d[17]),"+f"(d[18]),"+f"(d[19]),"+f"(d[20]),"+f"(d[21]),"+f"(d[22]),"+f"(d[23]),"+f"(d[24]),"+f"(d[25]),"+f"(d[26]),"+f"(d[27])
   : "r"(a[0]), "r"(a[1]), "r"(a[2]), "r"(a[3]), "l"(db), "r"(sd));
}
template<> __device__ __forceinline__ void wgmma_rs<48,0>(float* d, const uint32_t* a, uint64_t db, int sd) {
  asm volatile("{\n.reg .pred p;\nsetp.ne.b32 p, %29, 0;\nwgmma.mma_async.sync.aligned.m64n48k16.f32.bf16.bf16 {%0,%1,%2,%3,%4,%5,%6,%7,%8,%9,%10,%11,%12,%13,%14,%15,%16,%17,%18,%19,%20,%21,%22,%23}, {%24,%25,%26,%27}, %28, p, 1, 1, 0;\n}\n"
   : "+f"(d[0]),"+f"(d[1]),"+f"(d[2]),"+f"(d[3]),"+f"(d[4]),"+f"(d[5]),"+f"(d[6]),"+f"(d[7]),"+f"(d[8]),"+f"(d[9]),"+f"(d[10]),"+f"(d[11]),"+f"(d[12]),"+f"(d[13]),"+f"(d[14]),"+f"(d[15]),"+f"(d[16]),"+f"(d[17]),"+f"(d[18]),"+f"(d[19]),"+f"(d[20]),"+f"(d[21]),"+f"(d[22]),"+f"(d[23])
   : "r"(a[0]), "r"(a[1]), "r"(a[2]), "r"(a[3]), "l"(db), "r"(sd));
}
template<> __device__ __forceinline__ void wgmma_rs<40,0>(float* d, const uint32_t* a, uint64_t db, int sd) {
  asm volatile("{\n.reg .pred p;\nsetp.ne.b32 p, %25, 0;\nwgmma.mma_async.sync.aligned.m64n40k16.f32.bf16.bf16 {%0,%1,%2,%3,%4,%5,%6,%7,%8,%9,%10,%11,%12,%13,%14,%15,%16,%17,%18,%19}, {%20,%21,%22,%23}, %24, p, 1, 1, 0;\n}\n"
   : "+f"(d[0]),"+f"(d[1]),"+f"(d[2]),"+f"(d[3]),"+f"(d[4]),"+f"(d[5]),"+f"(d[6]),"+f"(d[7]),"+f"(d[8]),"+f"(d[9]),"+f"(d[10]),"+f"(d[11]),"+f"(d[12]),"+f"(d[13]),"+f"(d[14]),"+f"(d[15]),"+f"(d[16]),"+f"(d[17]),"+f"(d[18]),"+f"(d[19])
   : "r"(a[0]), "r"(a[1]), "r"(a[2]), "r"(a[3]), "l"(db), "r"(sd));
}
template<> __device__ __forceinline__ void wgmma_rs<32,0>(float* d, const uint32_t* a, uint64_t db, int sd) {
  asm volatile("{\n.reg .pred p;\nsetp.ne.b32 p, %21, 0;\nwgmma.mma_async.sync.aligned.m64n32k16.f32.bf16.bf16 {%0,%1,%2,%3,%4,%5,%6,%7,%8,%9,%10,%11,%12,%13,%14,%15}, {%16,%17,%18,%19}, %20, p, 1, 1, 0;\n}\n"
   : "+f"(d[0]),"+f"(d[1]),"+f"(d[2]),"+f"(d[3]),"+f"(d[4]),"+f"(d[5]),"+f"(d[6]),"+f"(d[7]),"+f"(d[8]),"+f"(d[9]),"+f"(d[10]),"+f"(d[11]),"+f"(d[12]),"+f"(d[13]),"+f"(d[14]),"+f"(d[15])
   : "r"(a[0]), "r"(a[1]), "r"(a[2]), "r"(a[3]), "l"(db), "r"(sd));
}
template<> __device__ __forceinline__ void wgmma_rs<24,0>(float* d, const uint32_t* a, uint64_t db, int sd) {
  asm volatile("{\n.reg .pred p;\nsetp.ne.b32 p, %17, 0;\nwgmma.mma_async.sync.aligned.m64n24k16.f32.bf16.bf16 {%0,%1,%2,%3,%4,%5,%6,%7,%8,%9,%10,%11}, {%12,%13,%14,%15}, %16, p, 1, 1, 0;\n}\n"
   : "+f"(d[0]),"+f"(d[1]),"+f"(d[2]),"+f"(d[3]),"+f"(d[4]),"+f"(d[5]),"+f"(d[6]),"+f"(d[7]),"+f"(d[8]),"+f"(d[9]),"+f"(d[10]),"+f"(d[11])
   : "r"(a[0]), "r"(a[1]), "r"(a[2]), "r"(a[3]), "l"(db), "r"(sd));
}
template<> __device__ __forceinline__ void wgmma_rs<16,0>(float* d, const uint32_t* a, uint64_t db, int sd) {
  asm volatile("{\n.reg .pred p;\nsetp.ne.b32 p, %13, 0;\nwgmma.mma_async.sync.aligned.m64n16k16.f32.bf16.bf16 {%0,%1,%2,%3,%4,%5,%6,%7}, {%8,%9,%10,%11}, %12, p, 1, 1, 0;\n}\n"
   : "+f"(d[0]),"+f"(d[1]),"+f"(d[2]),"+f"(d[3]),"+f"(d[4]),"+f"(d[5]),"+f"(d[6]),"+f"(d[7])
   : "r"(a[0]), "r"(a[1]), "r"(a[2]), "r"(a[3]), "l"(db), "r"(sd));
}
template<> __device__ __forceinline__ void wgmma_rs<8,0>(float* d, const uint32_t* a, uint64_t db, int sd) {
  asm volatile("{\n.reg .pred p;\nsetp.ne.b32 p, %9, 0;\nwgmma.mma_async.sync.aligned.m64n8k16.f32.bf16.bf16 {%0,%1,%2,%3}, {%4,%5,%6,%7}, %8, p, 1, 1, 0;\n}\n"
   : "+f"(d[0]),"+f"(d[1]),"+f"(d[2]),"+f"(d[3])
   : "r"(a[0]), "r"(a[1]), "r"(a[2]), "r"(a[3]), "l"(db), "r"(sd));
}
template<> __device__ __forceinline__ void wgmma_ss<16,0,1>(float* d, uint64_t da, uint64_t db, int sd) {
  asm volatile("{\n.reg .pred p;\nsetp.ne.b32 p, %10, 0;\nwgmma.mma_async.sync.aligned.m64n16k16.f32.bf16.bf16 {%0,%1,%2,%3,%4,%5,%6,%7}, %8, %9, p, 1, 1, 0, 1;\n}\n"
   : "+f"(d[0]),"+f"(d[1]),"+f"(d[2]),"+f"(d[3]),"+f"(d[4]),"+f"(d[5]),"+f"(d[6]),"+f"(d[7])
   : "l"(da), "l"(db), "r"(sd));
}
template<> __device__ __forceinline__ void wgmma_ss<64,0,1>(float* d, uint64_t da, uint64_t db, int sd) {
  asm volatile("{\n.reg .pred p;\nsetp.ne.b32 p, %34, 0;\nwgmma.mma_async.sync.aligned.m64n64k16.f32.bf16.bf16 {%0,%1,%2,%3,%4,%5,%6,%7,%8,%9,%10,%11,%12,%13,%14,%15,%16,%17,%18,%19,%20,%21,%22,%23,%24,%25,%26,%27,%28,%29,%30,%31}, %32, %33, p, 1, 1, 0, 1;\n}\n"
   : "+f"(d[0]),"+f"(d[1]),"+f"(d[2]),"+f"(d[3]),"+f"(d[4]),"+f"(d[5]),"+f"(d[6]),"+f"(d[7]),"+f"(d[8]),"+f"(d[9]),"+f"(d[10]),"+f"(d[11]),"+f"(d[12]),"+f"(d[13]),"+f"(d[14]),"+f"(d[15]),"+f"(d[16]),"+f"(d[17]),"+f"(d[18]),"+f"(d[19]),"+f"(d[20]),"+f"(d[21]),"+f"(d[22]),"+f"(d[23]),"+f"(d[24]),"+f"(d[25]),"+f"(d[26]),"+f"(d[27]),"+f"(d[28]),"+f"(d[29]),"+f"(d[30]),"+f"(d[31])
   : "l"(da), "l"(db), "r"(sd));
}
template<> __device__ __forceinline__ void wgmma_ss<192,0,1>(float* d, uint64_t da, uint64_t db, int sd) {
  asm volatile("{\n.reg .pred p;\nsetp.ne.b32 p, %98, 0;\nwgmma.mma_async.sync.aligned.m64n192k16.f32.bf16.bf16 {%0,%1,%2,%3,%4,%5,%6,%7,%8,%9,%10,%11,%12,%13,%14,%15,%16,%17,%18,%19,%20,%21,%22,%23,%24,%25,%26,%27,%28,%29,%30,%31,%32,%33,%34,%35,%36,%37,%38,%39,%40,%41,%42,%43,%44,%45,%46,%47,%48,%49,%50,%51,%52,%53,%54,%55,%56,%57,%58,%59,%60,%61,%62,%63,%64,%65,%66,%67,%68,%69,%70,%71,%72,%73,%74,%75,%76,%77,%78,%79,%80,%81,%82,%83,%84,%85,%86,%87,%88,%89,%90,%91,%92,%93,%94,%95}, %96, %97, p, 1, 1, 0, 1;\n}\n"
   : "+f"(d[0]),"+f"(d[1]),"+f"(d[2]),"+f"(d[3]),"+f"(d[4]),"+f"(d[5]),"+f"(d[6]),"+f"(d[7]),"+f"(d[8]),"+f"(d[9]),"+f"(d[10]),"+f"(d[11]),"+f"(d[12]),"+f"(d[13]),"+f"(d[14]),"+f"(d[15]),"+f"(d[16]),"+f"(d[17]),"+f"(d[18]),"+f"(d[19]),"+f"(d[20]),"+f"(d[21]),"+f"(d[22]),"+f"(d[23]),"+f"(d[24]),"+f"(d[25]),"+f"(d[26]),"+f"(d[27]),"+f"(d[28]),"+f"(d[29]),"+f"(d[30]),"+f"(d[31]),"+f"(d[32]),"+f"(d[33]),"+f"(d[34]),"+f"(d[35]),"+f"(d[36]),"+f"(d[37]),"+f"(d[38]),"+f"(d[39]),"+f"(d[40]),"+f"(d[41]),"+f"(d[42]),"+f"(d[43]),"+f"(d[44]),"+f"(d[45]),"+f"(d[46]),"+f"(d[47]),"+f"(d[48]),"+f"(d[49]),"+f"(d[50]),"+f"(d[51]),"+f"(d[52]),"+f"(d[53]),"+f"(d[54]),"+f"(d[55]),"+f"(d[56]),"+f"(d[57]),"+f"(d[58]),"+f"(d[59]),"+f"(d[60]),"+f"(d[61]),"+f"(d[62]),"+f"(d[63]),"+f"(d[64]),"+f"(d[65]),"+f"(d[66]),"+f"(d[67]),"+f"(d[68]),"+f"(d[69]),"+f"(d[70]),"+f"(d[71]),"+f"(d[72]),"+f"(d[73]),"+f"(d[74]),"+f"(d[75]),"+f"(d[76]),"+f"(d[77]),"+f"(d[78]),"+f"(d[79]),"+f"(d[80]),"+f"(d[81]),"+f"(d[82]),"+f"(d[83]),"+f"(d[84]),"+f"(d[85]),"+f"(d[86]),"+f"(d[87]),"+f"(d[88]),"+f"(d[89]),"+f"(d[90]),"+f"(d[91]),"+f"(d[92]),"+f"(d[93]),"+f"(d[94]),"+f"(d[95])
   : "l"(da), "l"(db), "r"(sd));
}
template<> __device__ __forceinline__ void wgmma_ss<192,1,1>(float* d, uint64_t da, uint64_t db, int sd) {
  asm volatile("{\n.reg .pred p;\nsetp.ne.b32 p, %98, 0;\nwgmma.mma_async.sync.aligned.m64n192k16.f32.bf16.bf16 {%0,%1,%2,%3,%4,%5,%6,%7,%8,%9,%10,%11,%12,%13,%14,%15,%16,%17,%18,%19,%20,%21,%22,%23,%24,%25,%26,%27,%28,%29,%30,%31,%32,%33,%34,%35,%36,%37,%38,%39,%40,%41,%42,%43,%44,%45,%46,%47,%48,%49,%50,%51,%52,%53,%54,%55,%56,%57,%58,%59,%60,%61,%62,%63,%64,%65,%66,%67,%68,%69,%70,%71,%72,%73,%74,%75,%76,%77,%78,%79,%80,%81,%82,%83,%84,%85,%86,%87,%88,%89,%90,%91,%92,%93,%94,%95}, %96, %97, p, 1, 1, 1, 1;\n}\n"
   : "+f"(d[0]),"+f"(d[1]),"+f"(d[2]),"+f"(d[3]),"+f"(d[4]),"+f"(d[5]),"+f"(d[6]),"+f"(d[7]),"+f"(d[8]),"+f"(d[9]),"+f"(d[10]),"+f"(d[11]),"+f"(d[12]),"+f"(d[13]),"+f"(d[14]),"+f"(d[15]),"+f"(d[16]),"+f"(d[17]),"+f"(d[18]),"+f"(d[19]),"+f"(d[20]),"+f"(d[21]),"+f"(d[22]),"+f"(d[23]),"+f"(d[24]),"+f"(d[25]),"+f"(d[26]),"+f"(d[27]),"+f"(d[28]),"+f"(d[29]),"+f"(d[30]),"+f"(d[31]),"+f"(d[32]),"+f"(d[33]),"+f"(d[34]),"+f"(d[35]),"+f"(d[36]),"+f"(d[37]),"+f"(d[38]),"+f"(d[39]),"+f"(d[40]),"+f"(d[41]),"+f"(d[42]),"+f"(d[43]),"+f"(d[44]),"+f"(d[45]),"+f"(d[46]),"+f"(d[47]),"+f"(d[48]),"+f"(d[49]),"+f"(d[50]),"+f"(d[51]),"+f"(d[52]),"+f"(d[53]),"+f"(d[54]),"+f"(d[55]),"+f"(d[56]),"+f"(d[57]),"+f"(d[58]),"+f"(d[59]),"+f"(d[60]),"+f"(d[61]),"+f"(d[62]),"+f"(d[63]),"+f"(d[64]),"+f"(d[65]),"+f"(d[66]),"+f"(d[67]),"+f"(d[68]),"+f"(d[69]),"+f"(d[70]),"+f"(d[71]),"+f"(d[72]),"+f"(d[73]),"+f"(d[74]),"+f"(d[75]),"+f"(d[76]),"+f"(d[77]),"+f"(d[78]),"+f"(d[79]),"+f"(d[80]),"+f"(d[81]),"+f"(d[82]),"+f"(d[83]),"+f"(d[84]),"+f"(d[85]),"+f"(d[86]),"+f"(d[87]),"+f"(d[88]),"+f"(d[89]),"+f"(d[90]),"+f"(d[91]),"+f"(d[92]),"+f"(d[93]),"+f"(d[94]),"+f"(d[95])
   : "l"(da), "l"(db), "r"(sd));
}

#define OREL 1
#define HINT_P 1
template <bool TR>
__device__ __forceinline__ void gemm_section(float* acc, float& mean0, float& mean1, float& rstd0, float& rstd1,
                                             uint32_t sb, int blk, int hg, int wg, int w, int lane) {
  constexpr int layer = TR ? 1 : 0;
  constexpr int TURN = TR ? TURN1 : TURN0;
  constexpr int LSTAT = TURN < 4 ? TURN - 1 : 3;
  const uint32_t bar = sb + SM_BAR;
  const int g = lane >> 2, t = lane & 3;
  const bool leader = (w == 0) && (lane == 0);
  const int statpos = hg < 3 ? 1 : wg ? LSTAT : 2;
  const bool copy = hg >= 3 && wg == 0;
  const int cut = wg ? TURN : 4;
  auto wait_full = [&](int c) {
    mbar_wait(bar + 8 * (B_XF + 8 * wg + c), layer);
    mbar_wait(bar + 8 * (B_WF + c), layer);
  };
  auto peek = [&](int c) {
    const bool x = mbar_test(bar + 8 * (B_XF + 8 * wg + c), layer), y = mbar_test(bar + 8 * (B_WF + c), layer);
    return x && y;
  };
  const uint64_t da0 = mkdesc(sb, TR ? 8192 : 16, 1024, 1), db0 = mkdesc(sb, 8192, 1024, 1);
  uint32_t xt = wg ? 0xfedcba98u : 0x21043210u;
  uint64_t wt = 0x0816131005161310ull;
  uint64_t da = da0 + ((xt & 15) << 9), db = db0 + (16 << 9);
  auto issue = [&](int c, int first) {
    TSG(2 * c);
    wg_fence();
#pragma unroll
    for (int ks = 0; ks < 4; ks++) wgmma_ss<192, TR ? 1 : 0, 1>(acc, da + (TR ? ks * 128 : ks * 2), db + ks * 128, !first || ks != 0);
    wg_commit();
    xt >>= 4; wt >>= 8;
    da = da0 + ((xt & 15) << 9); db = db0 + (((uint32_t)wt & 31) << 9);
    TSG(2 * c + 1);
  };
  uint32_t tag = 0;
  wait_full(0);
  bool ready = peek(1);
  issue(0, 1);
  TSW(0);
#pragma unroll 1
  for (int c = 1; c < cut; c++) {
    if (!ready) wait_full(c);
    issue(c, 0);
    ready = peek(c + 1);
    wg_wait<1>();
    if (leader) mbar_arrive(bar + 8 * (B_DN + 8 * wg + c - 1));
    if (wg == 1 && c == cut - 1) {
      wg_wait<0>();
      if (leader) mbar_arrive(bar + 8 * (B_DN + 8 + c));
    }
    if (c == statpos) {
      mbar_wait(bar + 8 * B_EP, 0);
      tag = 2 * lds32(sb + SM_EP) + layer + 1;
      mbar_wait(bar + 8 * (copy ? B_SC : B_XF + 8 * wg + hg), layer);
      uint32_t A[16];
      const uint32_t xb = sb + (copy ? P_R : 8 * wg + hg) * PG;
#pragma unroll
      for (int ks = 0; ks < 4; ks++) {
        if (!TR) {
          const int row = 16 * w + (lane & 15), kc = 2 * ks + (lane >> 4);
          ldsm4(&A[4 * ks], xb + row * 128 + ((kc ^ (row & 7)) << 4));
        } else {
          const int k = 16 * ks + (lane & 7) + 8 * (lane >> 4), pc = 2 * w + ((lane >> 3) & 1);
          ldsm4t(&A[4 * ks], xb + k * 128 + ((pc ^ (k & 7)) << 4));
        }
      }
      float s0 = 0.f, q0 = 0.f, s1 = 0.f, q1 = 0.f;
#pragma unroll
      for (int i = 0; i < 16; i += 2) {
        const float a = bf_lo(A[i]), b = bf_hi(A[i]), c_ = bf_lo(A[i + 1]), d = bf_hi(A[i + 1]);
        s0 += a + b; q0 = fmaf(a, a, q0); q0 = fmaf(b, b, q0);
        s1 += c_ + d; q1 = fmaf(c_, c_, q1); q1 = fmaf(d, d, q1);
      }
#pragma unroll
      for (int o = 1; o <= 2; o <<= 1) {
        s0 += __shfl_xor_sync(~0u, s0, o); q0 += __shfl_xor_sync(~0u, q0, o);
        s1 += __shfl_xor_sync(~0u, s1, o); q1 += __shfl_xor_sync(~0u, q1, o);
      }
      if (t < 2)
        st_tagged(&g_part[((layer * 32 + blk) * 8 + hg) * 64 + 16 * w + g + 8 * t], __float_as_uint(t ? s1 : s0), __float_as_uint(t ? q1 : q0), tag);
    }
  }
  if (wg == 1) mbar_wait(bar + 8 * (B_DN + GPOS), layer);
  else if (!ready) { wait_full(cut); ready = true; }
  const uint4* psrc = &g_part[((layer * 32 + blk) * 8 + 2 * t) * 64 + 16 * w + g];
  uint4 a0 = ld_tagged(psrc), a1 = ld_tagged(psrc + 8), b0 = ld_tagged(psrc + 64), b1 = ld_tagged(psrc + 72);
  if (wg == 1) {
#pragma unroll 1
    for (int c = cut; c < 8; c++) wait_full(c);
    ready = true;
    bar_sync(5, 256);
  }
#pragma unroll 1
  for (int c = cut; c < 8; c++) {
    if (!ready) wait_full(c);
    issue(c, 0);
    if (wg == 1) {
      wg_wait<2>();
      if (leader && c >= cut + 2) mbar_arrive(bar + 8 * (B_DN + 8 + c - 2));
    } else if (c == 7) {
      bar_arrive(5, 256);
    } else {
      ready = peek(c + 1);
      wg_wait<1>();
      if (leader) mbar_arrive(bar + 8 * (B_DN + c - 1));
    }
  }
  int it = 0;
  while (!__all_sync(~0u, a0.y == tag && a0.w == tag && a1.y == tag && a1.w == tag && b0.y == tag && b0.w == tag && b1.y == tag && b1.w == tag) &&
         ++it < (1 << 20)) {
    a0 = ld_tagged(psrc); a1 = ld_tagged(psrc + 8); b0 = ld_tagged(psrc + 64); b1 = ld_tagged(psrc + 72);
  }
  float s0 = __uint_as_float(a0.x) + __uint_as_float(b0.x), q0 = __uint_as_float(a0.z) + __uint_as_float(b0.z);
  float s1 = __uint_as_float(a1.x) + __uint_as_float(b1.x), q1 = __uint_as_float(a1.z) + __uint_as_float(b1.z);
#pragma unroll
  for (int o = 1; o <= 2; o <<= 1) {
    s0 += __shfl_xor_sync(~0u, s0, o); q0 += __shfl_xor_sync(~0u, q0, o);
    s1 += __shfl_xor_sync(~0u, s1, o); q1 += __shfl_xor_sync(~0u, q1, o);
  }
  mean0 = s0 * (1.f / DM); mean1 = s1 * (1.f / DM);
  rstd0 = rsqrt_approx(fmaxf(q0 * (1.f / DM) - mean0 * mean0, 0.f) + 1e-5f);
  rstd1 = rsqrt_approx(fmaxf(q1 * (1.f / DM) - mean1 * mean1, 0.f) + 1e-5f);
  TSG(16);
  mbar_wait(bar + 8 * B_CSF, 0);
  wg_wait<0>();
  acc_fence<96>(acc);
  if (leader) mbar_arrive(bar + 8 * (B_DN + 8 * wg + 7));
}

__device__ __forceinline__ void attn_phase(const Params& p, uint32_t sb, int layer, int rb, int hg, int wg, int w) {
  const int lane = opaque_tid() & 31;
  const int g = lane >> 2, t = lane & 3;
  const uint32_t bar = sb + SM_BAR;
  const int blk = 16 * wg + rb;
  float acc[96];
  float2 cs[24];
  float mean0, mean1, rstd0, rstd1;
  if (layer) gemm_section<true>(acc, mean0, mean1, rstd0, rstd1, sb, blk, hg, wg, w, lane);
  else gemm_section<false>(acc, mean0, mean1, rstd0, rstd1, sb, blk, hg, wg, w, lane);
  const uint32_t tag = 2 * lds32(sb + SM_EP) + layer + 1;
  TSW(1);
#pragma unroll
  for (int j = 8; j < 24; j++) cs[j] = lds64f(sb + SM_CS + 4 * (8 * j + 2 * t));
  const uint32_t kvx = sb + (wg ? 22 : 0) * PG;

  uint32_t kb[4][8], vb[4][8], qa[4][4];
  {
    const float nm0 = -mean0 * rstd0, nm1 = -mean1 * rstd1;
    const int st_row = 16 * w + (lane & 7) + 8 * ((lane >> 3) & 1);
    const uint32_t st_base = kvx + st_row * 256;
    const bool sender = (w == 3 && blk < 31);
    uint4* halo = &g_halo[((layer * 32 + blk) * 8 + hg) * 384 + lane];
    uint32_t r[4][2][4];
#pragma unroll
    for (int h = 0; h < 4; h++) {
#pragma unroll
      for (int kv = 0; kv < 2; kv++) {
#pragma unroll
        for (int dh = 0; dh < 2; dh++) {
          const int j = 8 + kv * 8 + 2 * h + dh;
          const float2 c2 = cs[j];
          const float v0 = fmaf(acc[4 * j + 0], rstd0, nm0 * c2.x), v1 = fmaf(acc[4 * j + 1], rstd0, nm0 * c2.y);
          const float v2 = fmaf(acc[4 * j + 2], rstd1, nm1 * c2.x), v3 = fmaf(acc[4 * j + 3], rstd1, nm1 * c2.y);
          r[h][kv][2 * dh] = packbf(v0, v1);
          r[h][kv][2 * dh + 1] = packbf(v2, v3);
        }
      }
      if (sender) {
        st_tagged3(halo + (3 * h) * 32, r[h][0][0], r[h][0][1], r[h][0][2], tag);
        st_tagged3(halo + (3 * h + 1) * 32, r[h][0][3], r[h][1][0], r[h][1][1], tag);
        st_tagged3(halo + (3 * h + 2) * 32, r[h][1][2], r[h][1][3], 0u, tag);
      }
    }
#pragma unroll
    for (int j = 0; j < 8; j++) cs[j] = lds64f(sb + SM_CS + 4 * (8 * j + 2 * t));
    mbar_wait(bar + 8 * (B_DN + 7), layer);
#pragma unroll
    for (int h = 0; h < 4; h++) {
#pragma unroll
      for (int kv = 0; kv < 2; kv++) {
        const int chunk = 4 * h + 2 * kv + (lane >> 4);
        stsm4(st_base + (((chunk & 8) | ((chunk ^ st_row) & 7)) << 4), r[h][kv][0], r[h][kv][1], r[h][kv][2], r[h][kv][3]);
      }
      kb[h][4] = r[h][0][0]; kb[h][5] = r[h][0][2]; kb[h][6] = r[h][0][1]; kb[h][7] = r[h][0][3];
      vb[h][4] = movm_t(r[h][1][0]); vb[h][5] = movm_t(r[h][1][1]); vb[h][6] = movm_t(r[h][1][2]); vb[h][7] = movm_t(r[h][1][3]);
    }
#pragma unroll
    for (int h = 0; h < 4; h++) {
#pragma unroll
      for (int dh = 0; dh < 2; dh++) {
        const int j = 2 * h + dh;
        const float2 c2 = cs[j];
        qa[h][2 * dh] = packbf(fmaf(-mean0, c2.x, acc[4 * j + 0]), fmaf(-mean0, c2.y, acc[4 * j + 1]));
        qa[h][2 * dh + 1] = packbf(fmaf(-mean1, c2.x, acc[4 * j + 2]), fmaf(-mean1, c2.y, acc[4 * j + 3]));
      }
    }
  }
  bar_sync(2 + wg, 128);
  TSW(2);
  {
    const uint32_t prev_base = kvx + (16 * w - 16) * 256;
    const int mi = lane >> 3;
    const int r = 8 * (mi >> 1) + (lane & 7), r2 = 8 * (mi & 1) + (lane & 7);
    if (w != 0) {
#pragma unroll
      for (int h = 0; h < 4; h++) {
        const int ch = 4 * h + (mi & 1), ch2 = 4 * h + 2 + (mi >> 1);
        ldsm4(&kb[h][0], prev_base + r * 256 + (((ch & 8) | ((ch ^ r) & 7)) << 4));
        ldsm4t(&vb[h][0], prev_base + r2 * 256 + (((ch2 & 8) | ((ch2 ^ r2) & 7)) << 4));
      }
    } else if (blk > 0) {
      const uint4* src = &g_halo[((layer * 32 + blk - 1) * 8 + hg) * 384 + lane];
      uint4 hv[12];
      int it = 0;
      bool ok;
      do {
        ok = true;
#pragma unroll
        for (int i = 0; i < 12; i++) hv[i] = ld_tagged(src + i * 32);
#pragma unroll
        for (int i = 0; i < 12; i++) ok = ok && (i % 3 == 2 ? hv[i].w | hv[i].z : hv[i].w) == tag;
      } while (!__all_sync(~0u, ok) && ++it < (1 << 20));
#pragma unroll
      for (int h = 0; h < 4; h++) {
        kb[h][0] = hv[3 * h].x; kb[h][1] = hv[3 * h].z; kb[h][2] = hv[3 * h].y; kb[h][3] = hv[3 * h + 1].x;
        vb[h][0] = movm_t(hv[3 * h + 1].y); vb[h][1] = movm_t(hv[3 * h + 1].z);
        vb[h][2] = movm_t(hv[3 * h + 2].x); vb[h][3] = movm_t(hv[3 * h + 2].y);
      }
    } else {
#pragma unroll
      for (int h = 0; h < 4; h++)
#pragma unroll
        for (int k = 0; k < 4; k++) kb[h][k] = vb[h][k] = 0u;
    }
    TSW(3);
  }
  mbar_wait(bar + 8 * (B_DN + 15), layer);
  TSW(4);

  const bool first = (blk == 0 && w == 0);
  const int e = t - (g >> 1);
  const bool par = g & 1, epos = e >= 1;
  const uint32_t pmask = par ? 0xffff0000u : 0x0000ffffu;
  const uint32_t mB0 = epos ? pmask : 0u, mB1 = epos ? 0u : pmask;
  const float cl2 = 0.25f * 1.4426950408889634f;
  const float sc0 = rstd0 * cl2, sc1 = rstd1 * cl2;
  const float NEG = -INFINITY;
  float vA0[4], vB0[4], vA1[4], vB1[4];
#pragma unroll
  for (int h = 0; h < 4; h++) {
    float S[4][4];
#pragma unroll
    for (int j = 0; j < 4; j++) {
      S[j][0] = S[j][1] = S[j][2] = S[j][3] = 0.f;
      mma_bf16(S[j], qa[h], kb[h][2 * j], kb[h][2 * j + 1]);
    }
    vA0[h] = par ? S[1][1] : S[1][0];
    vB0[h] = epos ? (par ? S[0][1] : S[0][0]) : (par ? S[2][1] : S[2][0]);
    vA1[h] = par ? S[2][3] : S[2][2];
    vB1[h] = epos ? (par ? S[1][3] : S[1][2]) : (par ? S[3][3] : S[3][2]);
    if (first) { vA0[h] = NEG; if (epos) { vB0[h] = NEG; vB1[h] = NEG; } }
  }
  float m0[4], m1[4];
#pragma unroll
  for (int h = 0; h < 4; h++) { m0[h] = fmaxf(vA0[h], vB0[h]); m1[h] = fmaxf(vA1[h], vB1[h]); }
#pragma unroll
  for (int o = 1; o <= 2; o <<= 1) {
#pragma unroll
    for (int h = 0; h < 4; h++) {
      m0[h] = fmaxf(m0[h], __shfl_xor_sync(~0u, m0[h], o));
      m1[h] = fmaxf(m1[h], __shfl_xor_sync(~0u, m1[h], o));
    }
  }
  float O0[4][4], O1[4][4], Z[4][4];
#pragma unroll
  for (int h = 0; h < 4; h++) {
    const float mm0 = -m0[h] * sc0, mm1 = -m1[h] * sc1;
    const float pA0 = ex2(fmaf(vA0[h], sc0, mm0)), pB0 = ex2(fmaf(vB0[h], sc0, mm0));
    const float pA1 = ex2(fmaf(vA1[h], sc1, mm1)), pB1 = ex2(fmaf(vB1[h], sc1, mm1));
    const uint32_t hA0 = packbf(pA0, pA0), hB0 = packbf(pB0, pB0), hA1 = packbf(pA1, pA1), hB1 = packbf(pB1, pB1);
    const uint32_t P0[4] = {hB0 & mB0, 0u, hA0 & pmask, hB1 & mB0};
    const uint32_t P1[4] = {hB0 & mB1, hA1 & pmask, 0u, hB1 & mB1};
#pragma unroll
    for (int k = 0; k < 4; k++) O0[h][k] = O1[h][k] = Z[h][k] = 0.f;
    mma_bf16(O0[h], P0, vb[h][0], vb[h][1]); mma_bf16(O1[h], P0, vb[h][2], vb[h][3]); mma_bf16(Z[h], P0, 0x3f803f80u, 0x3f803f80u);
    mma_bf16(O0[h], P1, vb[h][4], vb[h][5]); mma_bf16(O1[h], P1, vb[h][6], vb[h][7]); mma_bf16(Z[h], P1, 0x3f803f80u, 0x3f803f80u);
  }
  if (lane == 0) mbar_arrive(bar + 8 * (B_OST + wg));
  bf16* op = g_O + (blk * 64 + 16 * w + g) * DM + hg * 64 + 8 * t;
#pragma unroll
  for (int h = 0; h < 4; h += 2) {
    const float i0 = rcp_approx(Z[h][0]), i1 = rcp_approx(Z[h][2]), j0 = rcp_approx(Z[h + 1][0]), j1 = rcp_approx(Z[h + 1][2]);
    stg128(op + 16 * h, make_uint4(packbf(O0[h][0] * i0, O0[h][1] * i0), packbf(O1[h][0] * i0, O1[h][1] * i0),
                                   packbf(O0[h + 1][0] * j0, O0[h + 1][1] * j0), packbf(O1[h + 1][0] * j0, O1[h + 1][1] * j0)));
    stg128(op + 8 * DM + 16 * h, make_uint4(packbf(O0[h][2] * i1, O0[h][3] * i1), packbf(O1[h][2] * i1, O1[h][3] * i1),
                                            packbf(O0[h + 1][2] * j1, O0[h + 1][3] * j1), packbf(O1[h + 1][2] * j1, O1[h + 1][3] * j1)));
  }
  TSW(5);
  if (w == 0) {
    bar_sync(7 + wg, 128);
    if (lane == 0) red_release(&g_cnt[(C_O + layer * 32 + blk) * 32]);
    __syncwarp();
  } else {
    bar_arrive(7 + wg, 128);
  }
  TSW(6);
}

__device__ __forceinline__ void proj_phase(const Params& p, uint32_t sb, int layer, int rb, int q, int wg, int w) {
  const int lane = opaque_tid() & 31;
  const bool TR = layer != 0;
  const int t = lane & 3;
  const uint32_t bar = sb + SM_BAR;
  const uint32_t rbx = sb + (P_R + wg) * PG;
  const int blk = 16 * wg + rb;
  uint32_t res[16];
  mbar_wait(bar + 8 * (B_RF + wg), layer);
  if (!TR) {
#pragma unroll
    for (int j = 0; j < 8; j += 2) {
      const int mi = lane >> 3;
      const int row = 16 * w + (lane & 7) + 8 * (mi & 1), ch = j + (mi >> 1);
      ldsm4(&res[2 * j], rbx + row * 128 + ((ch ^ (row & 7)) << 4));
    }
  } else {
#pragma unroll
    for (int j = 0; j < 8; j += 2) {
      const int mi = lane >> 3;
      const int line = 8 * (j + (mi >> 1)) + (lane & 7), pc = 2 * w + (mi & 1);
      ldsm4t(&res[2 * j], rbx + line * 128 + ((pc ^ (line & 7)) << 4));
    }
  }
  mbar_wait(bar + 8 * B_KG, 0);
  const uint32_t stg = sb + SM_STG + wg * 768;
  float acc[32];
#pragma unroll
  for (int j = 0; j < 16; j++) { acc[2 * j] = bf_lo(res[j]); acc[2 * j + 1] = bf_hi(res[j]); }
  acc_fence<32>(acc);
#pragma unroll
  for (int c = 0; c < 4; c++) {
    mbar_wait(bar + 8 * (B_WOF + c), layer);
    mbar_wait(bar + 8 * (B_OF + 4 * wg + c), layer);
    if (c == 0) TSW(7);
    const uint64_t da = mkdesc(sb + o_page(wg, c) * PG, 16, 1024, 1);
    wg_fence();
#pragma unroll
    for (int ks = 0; ks < 8; ks++)
      wgmma_ss<64, 0, 1>(acc, da + (ks >> 2) * 512 + (ks & 3) * 2, mkdesc(sb + wo_page(2 * c + (ks >> 2)) * PG, 8192, 1024, 1) + (ks & 3) * 128, 1);
    wg_commit();
  }
  wg_wait<0>();
  acc_fence<32>(acc);
  TSW(8);
  if (lane == 0 && w == 0) {
    mbar_arrive(bar + 8 * (B_PDONE + wg));
  }
  float s0 = 0.f, q0 = 0.f, s1 = 0.f, q1 = 0.f;
  uint32_t o[16];
#pragma unroll
  for (int j = 0; j < 8; j++) {
    const float a = acc[4 * j], b = acc[4 * j + 1], c = acc[4 * j + 2], d = acc[4 * j + 3];
    o[2 * j] = packbf(a, b);
    o[2 * j + 1] = packbf(c, d);
    s0 += a + b; q0 = fmaf(a, a, q0); q0 = fmaf(b, b, q0);
    s1 += c + d; q1 = fmaf(c, c, q1); q1 = fmaf(d, d, q1);
  }
#pragma unroll
  for (int j = 0; j < 8; j += 2) {
    const int mi = lane >> 3;
    const int line = 8 * (j + (mi >> 1)) + (lane & 7), pc = 2 * w + (mi & 1);
    stsm4t(rbx + line * 128 + ((pc ^ (line & 7)) << 4), o[2 * j], o[2 * j + 1], o[2 * j + 2], o[2 * j + 3]);
  }
#pragma unroll
  for (int o2 = 1; o2 <= 2; o2 <<= 1) {
    s0 += __shfl_xor_sync(~0u, s0, o2); q0 += __shfl_xor_sync(~0u, q0, o2);
    s1 += __shfl_xor_sync(~0u, s1, o2); q1 += __shfl_xor_sync(~0u, q1, o2);
  }
  {
    const int i = 2 * (lane >> 2) + (t & 1), k = (i * 11) >> 5;
    const float v = (t == 0) ? s0 : (t == 1) ? q0 : (t == 2) ? s1 : q1;
    sts32f(stg + k * 128 + (2 * w + (t >> 1)) * 16 + (i - 3 * k) * 4, v);
  }
  TSW(9);
  fence_async_smem();
  bar_sync(2 + wg, 128);
  if (w == 0 && elect_one()) {
    mbar_wait(bar + 8 * B_ZF, 0);
    tma_st(&p.mapXT, blk * 64, (2 * layer) * DM + q * 64, rbx);
    bulk_red_add_f32(g_stats + (layer * 32 + blk) * 192, stg, 768);
    bulk_commit();
    bulk_wait_all();
    red_relaxed(&g_cnt[(C_G + 2 * layer + wg) * 32]);
    bulk_wait_read();
    mbar_arrive(bar + 8 * (B_PST + wg));
    TSW(10);
  }
}

__device__ __forceinline__ void conv_load(uint32_t* A, uint32_t pe) {
#pragma unroll
  for (int m = 0; m < 17; m++) {
    A[4 * m + 2] = lds32(pe + 4 * (64 * m - 8));
    A[4 * m + 0] = lds32(pe + 4 * (64 * m));
    A[4 * m + 1] = lds32(pe + 4 * (64 * m + 8));
    asm volatile("mov.b32 %0, %1;" : "=r"(A[4 * m + 3]) : "r"(A[4 * m + 0]));
  }
}
template <int M> __device__ __forceinline__ void conv_tri(float* acc, const uint32_t* A, uint64_t d) {
  if constexpr (M < 16) {
    wgmma_rs<64 - 8 * (M / 2), 0>(acc, A + 4 * M, d + (uint64_t)(64 + 4 * M), M != 0);
    conv_tri<M + 1>(acc, A, d);
  }
}
__device__ __forceinline__ void conv_mma0(float* acc, const uint32_t* A, uint64_t d) {
  wg_fence();
  conv_tri<0>(acc, A, d);
  wg_commit();
}
__device__ __forceinline__ void conv_mma1(float* acc, const uint32_t* A, uint64_t d) {
  wg_fence();
#pragma unroll
  for (int m = 0; m < 17; m++) wgmma_rs<64, 0>(acc, A + 4 * m, d + (uint64_t)(4 * m), m != 0);
  wg_commit();
}
__device__ __forceinline__ void conv_store(float* acc, uint32_t pb, uint32_t over, int w) {
  acc_fence<32>(acc);
  const int l = opaque_tid() & 31, mt = l >> 3;
  int c = 2 * (63 - 8 * (mt >> 1) - (l & 7) + w) + (mt & 1);
  c ^= (c >> 3) & 1;
  const uint32_t a0 = pb + c * 16;
#pragma unroll
  for (int j = 0; j < 8; j += 2)
    stsm4t(j == 0 ? (c < 128 ? a0 : over + (c - 128) * 16) : a0 - 256 * j, packbf(acc[4 * j], acc[4 * j + 1]), packbf(acc[4 * j + 2], acc[4 * j + 3]),
           packbf(acc[4 * j + 4], acc[4 * j + 5]), packbf(acc[4 * j + 6], acc[4 * j + 7]));
}
__device__ __forceinline__ void conv_far(uint32_t sb, int ht) {
  const int w = ht >> 5, l = ht & 31;
  float F[4][8];
  const uint64_t da = mkdesc(sb + cv_fa(0), 128, 128, 0), ds = mkdesc(sb + cv_se(0), 256, 256, 3);
  wg_fence();
#pragma unroll
  for (int k = 0; k < 8; k++)
#pragma unroll
    for (int c = 0; c < 4; c++) wgmma_ss<16, 0, 1>(F[c], da + c * 1024 + (k >> 2) * 128 + (k & 3) * 16, ds + c * 256 + 32 * k, k != 0);
  wg_commit();
  const uint32_t pf = sb + cv_pf(0) + (16 * w + (l & 15)) * 32 + (l >> 4) * 16;
  wg_wait<0>();
#pragma unroll
  for (int c = 0; c < 4; c++) {
    acc_fence<8>(F[c]);
    stsm4(pf + c * 2048, packbf(F[c][0], F[c][1]), packbf(F[c][2], F[c][3]), packbf(F[c][4], F[c][5]), packbf(F[c][6], F[c][7]));
  }
}
__device__ __forceinline__ void conv_sums(uint32_t sb, int lc, int ht) {
  const int m = ht - 1;
  uint4 v[2][3];
#pragma unroll
  for (int c = 0; c < 2; c++)
#pragma unroll
    for (int k = 0; k < 3; k++) {
      const int mm = m - 1 + k;
      v[c][k] = lds128(sb + cv_u(lc + c) + (mm >= 0 ? (mm & 1) * CV_UH + (127 - (mm >> 1)) * 16 : 128 * 16));
    }
  const int ce = m + 2, co = m + 1;
#pragma unroll
  for (int c = 0; c < 2; c++) {
    const uint32_t x[8] = {v[c][0].z, v[c][0].w, v[c][1].x, v[c][1].y, v[c][1].z, v[c][1].w, v[c][2].x, v[c][2].y};
    float pv[16];
#pragma unroll
    for (int k = 0; k < 8; k++) { pv[2 * k] = bf_lo(x[k]); pv[2 * k + 1] = bf_hi(x[k]); }
    float t2[15], t4[13], s9[8], s7[8];
#pragma unroll
    for (int i = 0; i < 15; i++) t2[i] = pv[i] + pv[i + 1];
#pragma unroll
    for (int i = 0; i < 13; i++) t4[i] = t2[i] + t2[i + 2];
#pragma unroll
    for (int i = 0; i < 8; i++) {
      s9[i] = (t4[i] + t4[i + 4]) + pv[i + 8];
      s7[i] = (t4[i + 1] + t2[i + 5]) + pv[i + 7];
    }
    const uint4 e4 = make_uint4(packbf(s9[0], s9[1]), packbf(s9[2], s9[3]), packbf(s9[4], s9[5]), packbf(s9[6], s9[7]));
    if (ce < 128) sts128(sb + cv_se(lc + c) + (63 - (ce >> 1)) * 32 + (((ce & 1) ^ ((ce >> 3) & 1) ^ 1) << 4), e4);
    else sts128(sb + cv_se(lc + c) + 63 * 32 + 16, make_uint4(0, 0, 0, 0));
    sts128(sb + cv_so(lc + c) + (63 - (co >> 1)) * 32 + (((co & 1) ^ ((co >> 3) & 1) ^ 1) << 4),
           make_uint4(packbf(s7[0], s7[1]), packbf(s7[2], s7[3]), packbf(s7[4], s7[5]), packbf(s7[6], s7[7])));
  }
}

template <int HALF, int NCH, int STEP = 1>
__device__ __forceinline__ void conv_epi(uint32_t sb, bf16* out, int lc, int c) {
  uint4 v[NCH][4], xr[NCH], f[NCH];
  const uint32_t sw = (c ^ ((c >> 3) & 1)) * 16;
#pragma unroll
  for (int u = 0; u < NCH; u++) {
#pragma unroll
    for (int k = 0; k < 4; k++) v[u][k] = lds128(sb + (HALF ? cv_pb1(lc + STEP * u, k) : cv_pb0(lc + STEP * u, k)) + sw);
    xr[u] = lds128(sb + cv_x(HALF, lc + STEP * u) + c * 16);
    if (HALF) f[u] = lds128(sb + cv_pf(lc + STEP * u) + c * 16);
  }
#pragma unroll
  for (int u = 0; u < NCH; u++) {
    if (HALF) { v[u][0].x = hadd2(v[u][0].x, f[u].x); v[u][0].y = hadd2(v[u][0].y, f[u].y); v[u][0].z = hadd2(v[u][0].z, f[u].z); v[u][0].w = hadd2(v[u][0].w, f[u].w); }
    uint4 o;
    o.x = hadd2(xr[u].x, hadd2(hadd2(v[u][0].x, v[u][1].x), hadd2(v[u][2].x, v[u][3].x)));
    o.y = hadd2(xr[u].y, hadd2(hadd2(v[u][0].y, v[u][1].y), hadd2(v[u][2].y, v[u][3].y)));
    o.z = hadd2(xr[u].z, hadd2(hadd2(v[u][0].z, v[u][1].z), hadd2(v[u][2].z, v[u][3].z)));
    o.w = hadd2(xr[u].w, hadd2(hadd2(v[u][0].w, v[u][1].w), hadd2(v[u][2].w, v[u][3].w)));
    stg128(out + cv_chan(0, lc + STEP * u) * LSEQ + HALF * 1024 + c * 8, o);
  }
}

__device__ __forceinline__ bool prep_valid(const uint4 (&st)[6], const uint4 (&xr)[4]) {
  const uint32_t n = __float_as_uint(8.f);
  return st[0].w == n && st[1].w == n && st[2].w == n && st[3].w == n && st[4].w == n && (st[5].w | st[5].y | st[5].z) == n &&
         xr[0].x != UNSET && xr[1].x != UNSET && xr[2].x != UNSET && xr[3].x != UNSET;
}
template <int HALF>
__device__ __forceinline__ void conv_prep(uint32_t sb, int layer, int cta, int i) {
  uint4 st[6], xr[4];
  bool ok = false;
  if (HALF) {
#pragma unroll
    for (int k = 0; k < 6; k++) st[k] = lds128(sb + cv_pe(i >> 5) + ((i >> 3) & 3) * 768 + k * 128 + (i & 7) * 16);
#pragma unroll
    for (int k = 0; k < 4; k++) xr[k] = lds128(sb + cv_x(1, k) + i * 16);
    ok = __all_sync(~0u, prep_valid(st, xr));
  }
  if (!ok) {
    const uint4* sp = (const uint4*)g_stats + (layer * 32 + HALF * 16 + (i >> 3)) * 48 + (i & 7);
    const uint4* xp = (const uint4*)g_xT + (2 * layer * DM + 2 * cta) * (LSEQ / 8) + HALF * 128 + i;
    int it = 0;
    do {
#pragma unroll
      for (int k = 0; k < 6; k++) st[k] = ld_tagged(sp + 8 * k);
#pragma unroll
      for (int k = 0; k < 4; k++) xr[k] = ld_tagged(xp + cv_chan(0, k) * (LSEQ / 8));
      if (HALF || it) RETRY(1);
    } while (!__all_sync(~0u, prep_valid(st, xr)) && ++it < MAX_RETRY);
#pragma unroll
    for (int k = 0; k < 4; k++) sts128(sb + cv_x(HALF, k) + i * 16, xr[k]);
  }
  const uint32_t v[16] = {st[0].x, st[0].y, st[0].z, st[1].x, st[1].y, st[1].z, st[2].x, st[2].y, st[2].z, st[3].x, st[3].y, st[3].z, st[4].x, st[4].y, st[4].z, st[5].x};
  uint32_t rs[4], nm[4];
#pragma unroll
  for (int k = 0; k < 4; k++) {
    const float m0 = __uint_as_float(v[4 * k]) * (-1.f / DM), m1 = __uint_as_float(v[4 * k + 2]) * (-1.f / DM);
    const float r0 = rsqrt_approx(fmaxf(fmaf(__uint_as_float(v[4 * k + 1]), 1.f / DM, -m0 * m0), 0.f) + 1e-5f);
    const float r1 = rsqrt_approx(fmaxf(fmaf(__uint_as_float(v[4 * k + 3]), 1.f / DM, -m1 * m1), 0.f) + 1e-5f);
    rs[k] = packbf(r0, r1);
    nm[k] = packbf(m0 * bf_lo(rs[k]), m1 * bf_hi(rs[k]));
  }
  const uint32_t ud = sb + (i & 1) * CV_UH + (127 - 64 * HALF - (i >> 1)) * 16;
#pragma unroll
  for (int k = 0; k < 4; k++)
    sts128(ud + cv_u(k), make_uint4(hfma2(xr[k].x, rs[0], nm[0]), hfma2(xr[k].y, rs[1], nm[1]), hfma2(xr[k].z, rs[2], nm[2]), hfma2(xr[k].w, rs[3], nm[3])));
  fence_async_smem();
}

#define PP0 1
__device__ __forceinline__ void conv_phase(const Params& p, uint32_t sb, int layer, int cta) {
  const int tid = opaque_tid();
  const int wg = __shfl_sync(~0u, tid >> 7, 0), w = __shfl_sync(~0u, (tid >> 5) & 3, 0);
  const uint32_t bar = sb + SM_BAR;
  constexpr int CH2 = 4 * PG;
  bf16* xout = g_xT + ((2 * layer + 1) * DM + 2 * cta) * LSEQ;
  uint32_t A0[68], A1[68];
  float acc[32];
  {
    const int l1 = tid & 31;
    const uint32_t pe = sb + cv_pe(wg) + 4 * (16 + 16 * w + (l1 >> 2) - 2 * (l1 & 3));
    mbar_wait(bar + 8 * B_PE, layer);
    conv_load(A0, pe);
    conv_load(A1, pe + CH2);
    __syncwarp();
    if (l1 == 0) mbar_arrive(bar + 8 * B_AL);
  }
  TSW(19);
  if (wg == 0) {
    const int i = opaque_tid();
    if (i < 32) sts128(sb + cv_u(i >> 3) + ((i >> 2) & 1) * CV_UH + (128 + (i & 3)) * 16, make_uint4(0, 0, 0, 0));
    mbar_wait(bar + 8 * B_GB, layer);
    TSW(11);
    conv_prep<0>(sb, layer, cta, i);
    mbar_arrive(bar + 8 * B_U);
  }
  const uint64_t d0 = mkdesc(sb + cv_u(wg), CV_UH, 128, 0), d1 = d0 + (CH2 >> 4);
  mbar_wait(bar + 8 * B_U, layer);
  TSW(12);
  if (wg == 1) bar_sync(5, 256);
  conv_mma0(acc, A0, d0);
  if (wg == 0) bar_arrive(5, 256);
  mbar_wait(bar + 8 * (B_PDONE + 1), layer);
  {
    const int l = opaque_tid() & 31;
    if ((l & 15) < 2 * w) sts128(sb + cv_pb0(wg + 2 * (l >> 4), w) + (l & 15) * 16, make_uint4(0, 0, 0, 0));
  }
  wg_wait<0>();
  conv_store(acc, sb + cv_pb0(wg, w), sb + cv_pb1(wg, w), w);
  conv_mma0(acc, A1, d1);
  bar_sync(2 + wg, 128);
  conv_epi<0, 1>(sb, xout, wg, opaque_tid() & 127);
  wg_wait<0>();
  conv_store(acc, sb + cv_pb0(2 + wg, w), sb + cv_pb1(2 + wg, w), w);
  TSW(13);
  bar_sync(2 + wg, 128);
  conv_epi<0, 1>(sb, xout, 2 + wg, opaque_tid() & 127);
  mbar_arrive(bar + 8 * B_PUB);
  TSW(14);
  mbar_wait(bar + 8 * (B_GB + 1), layer);
  if (wg == 0) {
    conv_prep<1>(sb, layer, cta, opaque_tid());
    bar_sync(2, 128);
  } else {
    bar_sync(6, 256);
  }
  TSW(15);
  conv_mma1(acc, A0, d0);
  if (wg == 0) bar_arrive(6, 256);
  mbar_wait(bar + 8 * B_FARM, layer);
  wg_wait<0>();
  conv_store(acc, sb + cv_pb1(wg, w), sb + cv_dump(wg), w);
  mbar_arrive(bar + 8 * (B_R + 1));
  TSW(16);
  conv_mma1(acc, A1, d1);
  wg_wait<0>();
  conv_store(acc, sb + cv_pb1(2 + wg, w), sb + cv_dump(2 + wg), w);
  TSW(17);
  if (wg == 0) {
    mbar_arrive(bar + 8 * (B_R + 2));
  } else {
    bar_sync(3, 128);
    conv_epi<1, 1>(sb, xout, 3, opaque_tid() & 127);
    mbar_arrive(bar + 8 * (B_PUB + 2));
    TSW(18);
  }
}

__device__ __forceinline__ void final_phase(const Params& p, uint32_t sb, int cta, int wg, int w) {
  const int lane = opaque_tid() & 31;
  const uint32_t bar = sb + SM_BAR;
  mbar_wait(bar + 8 * (B_TF + wg), 0);
  if (threadIdx.x == 128) TS(8);
  const uint32_t src = sb + (16 + wg) * PG, dst = src + 2 * PG;
  const int mi = lane >> 3;
#pragma unroll 1
  for (int attempt = 0; attempt < MAX_RETRY; attempt++) {
    uint32_t m = 0;
#pragma unroll
    for (int j = 0; j < 8; j += 2) {
      uint32_t r[4];
      const int line = 8 * (j + (mi >> 1)) + (lane & 7), pc = 2 * w + (mi & 1);
      ldsm4t(r, src + line * 128 + ((pc ^ (line & 7)) << 4));
      const int row = 16 * w + (lane & 7) + 8 * (mi & 1), ch = j + (mi >> 1);
      stsm4(dst + row * 128 + ((ch ^ (row & 7)) << 4), r[0], r[1], r[2], r[3]);
#pragma unroll
      for (int k = 0; k < 4; k++) asm("max.u16x2 %0, %0, %1;" : "+r"(m) : "r"(r[k]));
    }
    fence_async_smem();
    if (!bar_or(2 + wg, 128, m >= 0xffff0000u || (m & 0xffffu) == 0xffffu)) break;
    if (w == 0 && elect_one()) {
      mbar_expect(bar + 8 * (B_RT + wg), PG);
      tma_ld(src, &p.mapXT, (16 * wg + (cta & 15)) * 64, 3 * DM + (cta >> 4) * 64, bar + 8 * (B_RT + wg));
    }
    mbar_wait(bar + 8 * (B_RT + wg), attempt & 1);
    RETRY(2);
  }
  if (w == 0 && elect_one()) {
    tma_st(&p.mapOut, (cta >> 4) * 64, (16 * wg + (cta & 15)) * 64, dst);
    bulk_commit();
    asm volatile("cp.async.bulk.wait_group.read 0;" ::: "memory");
    if (threadIdx.x == 128) TS(9);
    if (threadIdx.x == 128) LTS(1);
  }
}

struct cplx { float r, i; };
__device__ __forceinline__ cplx cmul(cplx a, cplx b) { return {fmaf(a.r, b.r, -a.i * b.i), fmaf(a.r, b.i, a.i * b.r)}; }
__device__ __forceinline__ cplx csqr(cplx a) { return {fmaf(a.r, a.r, -a.i * a.i), (a.r + a.r) * a.i}; }
__device__ __forceinline__ cplx cexp_l(float ar2, float ai, float l) {
  const float m = ex2(ar2 * l);
  const float x = ai * l;
  return {m * __cosf(x), m * __sinf(x)};
}

__device__ __forceinline__ void colsum_cta(const Params& p, uint32_t sb, int j, int tid) {
  const uint32_t bar = sb + SM_BAR;
  auto ld = [&](int i) {
    mbar_expect(bar + 8 * i, 3 * PG);
    tma_ld3(sb + (i & 7) * 3 * PG, &p.mapW3, (2 * j + (i & 1)) * 64, (i >> 1) * 64, 0, bar + 8 * i);
  };
  if (tid == 384) {
#pragma unroll
    for (int i = 0; i < 24; i++) mbar_init(bar + 8 * i, i < 16 ? 1 : 12);
    asm volatile("fence.mbarrier_init.release.cluster;" ::: "memory");
    fence_async_smem();
#pragma unroll 1
    for (int i = 0; i < 8; i++) ld(i);
  }
  const unsigned ep = ld_relaxed(&g_cnt[C_CS * 32]);
  bar_sync(0, NTHREADS);
  if (tid == 384) {
#pragma unroll 1
    for (int i = 8; i < 16; i++) { mbar_wait(bar + 8 * (8 + i), 0); fence_async_smem(); ld(i); }
  }
  if (tid < 384) {
    const int lane = tid & 31, cc = tid & 7, r0 = (tid >> 3) & 15, part = tid >> 7;
    const uint32_t id = ((lane >> 2) == 2 * (lane & 3) ? 0x3f80u : 0u) | ((lane >> 2) == 2 * (lane & 3) + 1 ? 0x3f800000u : 0u);
    const uint32_t src = sb + part * PG + r0 * 128 + ((cc ^ (r0 & 7)) << 4);
    float s[2][2][4];
#pragma unroll
    for (int i = 0; i < 16; i++) s[i >> 3][(i >> 2) & 1][i & 3] = 0.f;
#pragma unroll 1
    for (int i2 = 0; i2 < 16; i2 += 2) {
#pragma unroll
      for (int h = 0; h < 2; h++) {
        const int i = i2 + h;
        mbar_wait(bar + 8 * i, 0);
        uint4 v[4];
#pragma unroll
        for (int k = 0; k < 4; k++) v[k] = lds128(src + (i & 7) * 3 * PG + k * 2048);
#pragma unroll
        for (int k = 0; k < 4; k++) {
          const uint32_t a[4] = {v[k].x, v[k].y, v[k].z, v[k].w};
          mma_bf16(s[h][0], a, id, 0u);
          mma_bf16(s[h][1], a, 0u, id);
        }
        __syncwarp();
        if (i < 8 && lane == 0) mbar_arrive(bar + 8 * (16 + i));
      }
    }
    const uint32_t red = sb + 24 * PG;
#pragma unroll
    for (int h = 0; h < 2; h++)
#pragma unroll
      for (int k = 0; k < 2; k++) sts128f(red + (r0 * 384 + h * 192 + part * 64 + cc * 8 + k * 4) * 4, s[h][k][0], s[h][k][1], s[h][k][2], s[h][k][3]);
    bar_sync(1, 384);
    float tot = 0.f;
#pragma unroll
    for (int k = 0; k < 16; k++) tot += __uint_as_float(lds32(red + (k * 384 + tid) * 4));
    asm volatile("st.relaxed.gpu.global.v2.u32 [%0], {%1,%2};" ::"l"(&g_colsum[j * 384 + tid]), "r"(__float_as_uint(tot)), "r"(ep / NCTA + 1) : "memory");
  }
}

#define KW 3
struct ModeIn { uint32_t ar, ai, br, bi, cr, ci; bf16 logdt; };
__device__ __forceinline__ ModeIn load_modes(const Params& p, int d, int m) {
  const int i = d * 64 + m;
  return {((const uint32_t*)p.a_re)[i], ((const uint32_t*)p.a_im)[i], ((const uint32_t*)p.b_re)[i], ((const uint32_t*)p.b_im)[i],
          ((const uint32_t*)p.c_re)[i], ((const uint32_t*)p.c_im)[i], p.log_dt[d]};
}
__device__ __forceinline__ float4 lds128f_nv(uint32_t a) { float4 v; asm("ld.shared.v4.f32 {%0,%1,%2,%3}, [%4];" : "=f"(v.x), "=f"(v.y), "=f"(v.z), "=f"(v.w) : "r"(a)); return v; }
__device__ __forceinline__ void kernel_gen(const Params& p, uint32_t sb, int cta, int ht, ModeIn in, const ModeIn& in1) {
  const uint32_t bst = sb + SM_KGB + ((ht & 63) >> 2) * 144 + (ht & 3) * 4 + (ht >> 6) * 16;
  const uint64_t db = mkdesc(sb + SM_KGB, 144, 2304, 0);
  const float e0 = (float)(8 * (((ht & 32) >> 1) + ((ht & 31) >> 2)));
  float T[20];
#pragma unroll
  for (int i = 0; i < 20; i++) T[i] = 0.f;
  float k0 = (ht & 63) ? 0.f : __bfloat162float(p.dskip[cv_chan(cta, ht >> 6)]);
#pragma unroll 1
  for (int pass = 0; pass < 4; pass++) {
    {
      const int sh = (pass & 1) ? 0 : 16;
      auto val = [&](uint32_t v) { return __uint_as_float((v << sh) & 0xffff0000u); };
      const float dt = __bfloat162float(__float2bfloat16_rn(expf(__bfloat162float(in.logdt))));
      const float ar2 = dt * val(in.ar) * 1.4426950408889634f, ai = dt * val(in.ai);
      const cplx c = cmul({val(in.cr), -val(in.ci)}, {dt * val(in.br), -dt * val(in.bi)});
      k0 += c.r;
      const cplx z1 = cexp_l(ar2, -ai, 1.f), z256 = cexp_l(ar2, -ai, 256.f), z64 = cexp_l(ar2, ai, 64.f);
      const cplx z2 = csqr(z1), z512 = csqr(z256);
      auto put = [&](int j, cplx v) { sts32(bst + (j >> 2) * 2304 + (j & 3) * 32, packbf(v.r, v.i)); };
      sts128f(sb + SM_KGT + ht * 16, ar2, ai, z64.r, z64.i);
      const cplx c1 = cmul(c, z1), c2 = cmul(c, z2), c3 = cmul(c1, z2), c4 = cmul(c2, z2);
      const cplx c5 = cmul(c3, z2), c6 = cmul(c4, z2), c7 = cmul(c5, z2), c8 = cmul(c6, z2);
      put(0, c1); put(1, c2); put(2, c3); put(3, c4); put(4, c5); put(5, c6); put(6, c7); put(7, c8);
      const cplx c260 = cmul(c4, z256), c264 = cmul(c8, z256), c520 = cmul(c8, z512), c776 = cmul(c264, z512);
      put(8, cmul(c2, z256)); put(9, c260); put(10, cmul(c6, z256)); put(11, c264);
      put(12, cmul(c4, z512)); put(13, c520); put(14, cmul(c260, z512)); put(15, c776);
      const cplx c1032 = cmul(c520, z512), c1288 = cmul(c776, z512);
      put(16, c1032); put(17, c1288); put(18, cmul(c1032, z512)); put(19, cmul(c1288, z512));
    }
    fence_async_smem();
    bar_sync(4, 128);
    uint32_t tb = sb + SM_KGT + (ht & 67) * 16;
    asm volatile("mov.u32 %0, %0;" : "+r"(tb) :: "memory");
#pragma unroll
    for (int q = 0; q < 4; q++) {
      uint32_t A[8];
      if (q >= KW) wg_wait<KW - 1>();
#pragma unroll
      for (int s = 0; s < 4; s++) {
        const float4 v = lds128f_nv(tb + (4 * q + s) * 64);
        const cplx lo = cexp_l(v.x, v.y, e0), hi = cmul(lo, {v.z, v.w});
        A[2 * s] = packbf(lo.r, lo.i);
        A[2 * s + 1] = packbf(hi.r, hi.i);
      }
      wg_fence();
      wgmma_rs<40, 0>(T, A, db + 36 * q, (pass & 1) | q);
      wgmma_rs<40, 0>(T, A + 4, db + 36 * q + 18, 1);
      wg_commit();
    }
    wg_wait<0>();
    acc_fence<20>(T);
    if (ht == 0) TS(4 + pass);
    if (pass & 1) {
      const int h2 = opaque_tid() - 256, w = h2 >> 5, lane = h2 & 31, t = lane & 3, chn = h2 >> 6, m = h2 & 63, i0 = 16 * (w & 1) + (lane >> 2);
      const int lc = (pass & 2) + chn;
      const uint32_t kc = sb + kc_off(lc);
      auto put = [&](int idx, float v) {
        sts16(kc + idx * 2, __bfloat16_as_ushort(__float2bfloat16_rn(v)));
      };
#pragma unroll
      for (int hi = 0; hi < 2; hi++) {
        const int i = i0 + 8 * hi;
        float v[5];
#pragma unroll
        for (int j = 0; j < 5; j++) v[j] = chn ? T[4 * j + 2 * hi + 1] : T[4 * j + 2 * hi];
        put(8 * i + 1 + t, v[0]);
        put(8 * i + 5 + t, v[1]);
        put(257 + 4 * i + t, v[2]);
        put(385 + 2 * i + (t & 1) + 64 * (t >> 1), v[3]);
        put(513 + i + 32 * t, v[4]);
      }
#pragma unroll
      for (int o = 16; o > 0; o >>= 1) k0 += __shfl_xor_sync(~0u, k0, o);
      if (lane == 0) sts32f(sb + SM_RED + 4 * w, k0);
      bar_sync(4, 128);
      if (m == 0) put(0, k0 + __uint_as_float(lds32(sb + SM_RED + 4 * w + 4)));
      k0 = m ? 0.f : __bfloat162float(p.dskip[cv_chan(cta, 2 + chn)]);
      in = in1;
    }
  }
}

__device__ __forceinline__ void expand_taps(uint32_t sb, int ht) {
  const int ch = ht >> 5, lane = ht & 31;
  const uint32_t kc = sb + kc_off(ch);
  const uint32_t dst0 = sb + cv_pe(ch);
  auto put = [&](int G, uint32_t v0, uint32_t v1, uint32_t v2, uint32_t v3, uint32_t v4, uint32_t v5, uint32_t v6, uint32_t v7, uint32_t v8) {
    const uint32_t dst = dst0 + G * 32;
    sts128(dst, make_uint4(v1 | (v0 << 16), v2 | (v1 << 16), v3 | (v2 << 16), v4 | (v3 << 16)));
    sts128(dst + 16, make_uint4(v5 | (v4 << 16), v6 | (v5 << 16), v7 | (v6 << 16), v8 | (v7 << 16)));
  };
  {
    const uint4 q = lds128(kc + lane * 16);
    const uint32_t pv = lane ? lds16(kc + lane * 16 - 2) : 0u;
    const uint32_t dst = dst0 + (lane + 2) * 32;
    sts128(dst, make_uint4(__byte_perm(q.x, pv, 0x5410), __byte_perm(q.x, q.x, 0x1032), __byte_perm(q.y, q.x, 0x7610), __byte_perm(q.y, q.y, 0x1032)));
    sts128(dst + 16, make_uint4(__byte_perm(q.z, q.y, 0x7610), __byte_perm(q.z, q.z, 0x1032), __byte_perm(q.w, q.z, 0x7610), __byte_perm(q.w, q.w, 0x1032)));
    if (lane < 4) sts128(dst0 + lane * 16, make_uint4(0, 0, 0, 0));
  }
  uint32_t a[5], b[2][3];
  {
    const uint32_t s1 = kc + 2 * (256 + 4 * lane);
#pragma unroll
    for (int k = 0; k < 5; k++) a[k] = lds16(s1 + 2 * k);
#pragma unroll
    for (int u = 0; u < 2; u++) {
      const uint32_t s2 = kc + 2 * (384 + 2 * (lane + 32 * u));
#pragma unroll
      for (int k = 0; k < 3; k++) b[u][k] = lds16(s2 + 2 * k);
    }
  }
  const uint32_t k255 = lds16(kc + 2 * 255), k1024 = lds16(kc + 2 * 512);
  put(34 + lane, lane == 0 ? k255 : a[0], a[0], a[0], a[1], a[2], a[2], a[2], a[3], a[4]);
#pragma unroll
  for (int u = 0; u < 2; u++) put(66 + lane + 32 * u, b[u][0], b[u][0], b[u][0], b[u][0], b[u][1], b[u][1], b[u][1], b[u][2], b[u][2]);
  if (lane < 10) {
    const uint32_t v = lane == 0 ? k1024 : 0u;
    put(130 + lane, v, v, v, v, v, v, 0u, 0u, 0u);
  }
}
__device__ __forceinline__ void expand_far(uint32_t sb, int ht) {
  const int ch = ht >> 5, lane = ht & 31;
  const uint32_t kc = sb + kc_off(ch) + 4 * (249 + lane), dst = sb + cv_fa(ch);
  uint32_t v[2][9];
#pragma unroll
  for (int u = 0; u < 2; u++)
#pragma unroll
    for (int k = 0; k < 9; k++) v[u][k] = lds32(kc + 4 * (32 * u + k));
#pragma unroll
  for (int k = 0; k < 8; k++) v[0][k] = lane + k < 7 ? 0u : lane + k == 7 ? v[0][k] & 0xffff0000u : v[0][k];
#pragma unroll
  for (int u = 0; u < 2; u++) {
    const uint32_t row = dst + (56 + 32 * u + lane) * 16;
    sts128(row, make_uint4(__byte_perm(v[u][1], v[u][2], 0x5410), __byte_perm(v[u][3], v[u][4], 0x5410), __byte_perm(v[u][5], v[u][6], 0x5410), __byte_perm(v[u][7], v[u][8], 0x5410)));
    sts128(row + 2048, make_uint4(__byte_perm(v[u][0], v[u][1], 0x7632), __byte_perm(v[u][2], v[u][3], 0x7632), __byte_perm(v[u][4], v[u][5], 0x7632), __byte_perm(v[u][6], v[u][7], 0x7632)));
    sts128(dst + u * 2048 + lane * 16, make_uint4(0, 0, 0, 0));
    if (lane < 24) sts128(dst + u * 2048 + (32 + lane) * 16, make_uint4(0, 0, 0, 0));
  }
}

#define NFILL 32
#define FILL0 1
#define FILL1 2
#define WPRE 2
__host__ __device__ constexpr int bar_count(int i) {
  return i == B_END ? 3 : i == B_AL ? 8 : (i == B_OST || i == B_OST + 1) ? 4 : (i == B_PUB + 2 || i == B_PUB || i == B_R + 1) ? 256 : (i >= B_FARM && i < B_END) ? 128 : 1;
}
__host__ __device__ constexpr bool bar_first(int i) { return i < B_WF + 2 && (i & 7) < 2; }

__global__ void __launch_bounds__(NTHREADS, 1) fused_kernel(const __grid_constant__ Params p) {
  extern __shared__ __align__(1024) uint8_t smem[];
  const uint32_t sb = s32(smem);
  const int tid = threadIdx.x, lane = tid & 31;
  const int warp = __shfl_sync(~0u, tid >> 5, 0);
  if (blockIdx.x < 4) {
    colsum_cta(p, sb, blockIdx.x, tid);
    return;
  }
  const int cta = blockIdx.x - 4;
  const int rb = ((cta >> 4) & 3) * 4 + ((cta >> 2) & 3), hg = (cta >> 6) * 4 + (cta & 3);
  const int rb2 = cta >> 3, q2 = cta & 7;
  const uint32_t bar = sb + SM_BAR;
  auto ld_x0 = [&](int half, int c) {
    const uint32_t b = bar + 8 * (B_XF + 8 * half + c);
    mbar_expect(b, PG);
    tma_ld(sb + x_page(half, c) * PG, &p.mapX, c * 64, (16 * half + rb) * 64, b);
  };
  auto ld_w = [&](int c) {
    const uint32_t b = bar + 8 * (B_WF + c);
    mbar_expect(b, 3 * PG);
    tma_ld3(sb + w_page(c) * PG, &p.mapW3, hg * 64, c * 64, 0, b);
  };

  if (tid == 0) TS(0);
  if (tid == 480) LTS(0);
  if (warp < 6 && elect_one()) {
    if (warp == 0) {
#pragma unroll
      for (int i = 0; i < B_WF + 2; i++)
        if (bar_first(i)) mbar_init(bar + 8 * i, 1);
      asm volatile("fence.mbarrier_init.release.cluster;" ::: "memory");
      fence_async_smem();
      ld_x0(0, 0); ld_w(0); ld_x0(1, 0);
      ld_x0(0, 1); ld_w(1); ld_x0(1, 1);
      TS(1);
    } else {
#pragma unroll
      for (int q = 0; q < 5; q++) {
        if (warp == q + 1) {
#pragma unroll
          for (int i = 0; i < B_COUNT; i++)
            if (!bar_first(i) && i % 5 == q) mbar_init(bar + 8 * i, bar_count(i));
        }
      }
      asm volatile("fence.mbarrier_init.release.cluster;" ::: "memory");
    }
  }

  if (warp < 8) {
    bar_sync(0, NTHREADS);
    asm volatile("setmaxnreg.inc.sync.aligned.u32 %0;" ::"n"(R_CONS));
    const int cw = __shfl_sync(~0u, opaque_tid() >> 5, 0);
    const int wg = cw >> 2, w = cw & 3;
    if (tid == 0) TS(2);
#pragma unroll 1
    for (int layer = 0; layer < 2; layer++) {
      attn_phase(p, sb, layer, rb, hg, wg, w);
      proj_phase(p, sb, layer, rb2, q2, wg, w);
      conv_phase(p, sb, layer, cta);
    }
    final_phase(p, sb, cta, wg, w);
  } else if (warp < 12) {
    asm volatile("setmaxnreg.dec.sync.aligned.u32 %0;" ::"n"(R_HELP));
    const int ht = tid - 256;
    {
      unsigned ep0 = 0;
      if (ht == 0) ep0 = ld_relaxed(&g_cnt[C_CS * 32]);
      const ModeIn in0 = load_modes(p, cv_chan(cta, ht >> 6), ht & 63), in1 = load_modes(p, cv_chan(cta, 2 + (ht >> 6)), ht & 63);
      bar_sync(0, NTHREADS);
      if (ht == 0) {
        sts32(sb + SM_EP, ep0 / NCTA);
        mbar_arrive(bar + 8 * B_EP);
      }
      kernel_gen(p, sb, cta, ht, in0, in1);
      if (ht < 96) sts128f(sb + SM_STG + ht * 16, 0.f, 0.f, 0.f, 1.f);
      fence_async_smem();
      bar_sync(4, 128);
      if (ht == 0) mbar_arrive(bar + 8 * B_KG);
    }
#pragma unroll 1
    for (int layer = 0; layer < 2; layer++) {
      bf16* xout = g_xT + ((2 * layer + 1) * DM + 2 * cta) * LSEQ;
      mbar_wait(bar + 8 * B_PDONE, layer);
      expand_taps(sb, opaque_tid() - 256);
      mbar_arrive(bar + 8 * B_PE);
      TSW(0);
      expand_far(sb, opaque_tid() - 256);
      mbar_wait(bar + 8 * (B_PDONE + 1), layer);
      mbar_wait(bar + 8 * B_U, layer);
#pragma unroll 1
      for (int lc = 0; lc < 4; lc += 2) {
        conv_sums(sb, lc, opaque_tid() - 256);
        TSW(1 + lc);
      }
      fence_async_smem();
      bar_sync(4, 128);
      conv_far(sb, opaque_tid() - 256);
      mbar_arrive(bar + 8 * B_FARM);
      TSW(4);
      mbar_wait(bar + 8 * (B_R + 1), layer);
      conv_epi<1, 2>(sb, xout, 0, opaque_tid() - 256);
      mbar_arrive(bar + 8 * (B_PUB + 1));
      TSW(5);
      mbar_wait(bar + 8 * (B_R + 2), layer);
      conv_epi<1, 1>(sb, xout, 2, opaque_tid() - 256);
      mbar_arrive(bar + 8 * (B_PUB + 2));
      TSW(6);
    }
  } else {
    asm volatile("setmaxnreg.dec.sync.aligned.u32 %0;" ::"n"(R_AGENT));
    bar_sync(0, NTHREADS);
    auto done = [&](int half, int c, int layer) { mbar_wait(bar + 8 * (B_DN + 8 * half + c), layer); };
    auto publish = [&](int layer, int k) {
      mbar_wait(bar + 8 * (B_PUB + k), layer);
      if (layer == 0) {
        red_release(&g_cnt[(C_C + k) * 32]);
      }
      else red_relaxed(&g_cnt[(C_F + 4 * k + (cta >> 5)) * 32]);
      TS(16 + layer * 56 + 40 + 7 + k);
    };
    if (warp == 12) {
      if (elect_one()) {
#pragma unroll 1
        for (int layer = 0; layer < 2; layer++) {
          auto ld_xe = [&](int c) {
            const uint32_t b = bar + 8 * (B_XF + c);
            mbar_expect(b, PG);
            if (layer == 0) tma_ld(sb + (c - 5) * PG, &p.mapX, c * 64, rb * 64, b);
            else tma_ld(sb + (c - 5) * PG, &p.mapXT, rb * 64, DM + c * 64, b);
          };
          if (layer == 0) {
            ld_x0(0, 2); ld_w(2); ld_x0(1, 2);
            if (hg >= 3) {
              mbar_expect(bar + 8 * B_SC, PG);
              tma_ld(sb + P_R * PG, &p.mapX, hg * 64, rb * 64, bar + 8 * B_SC);
            }
            if (rb < 4) tma_prefetch3(&p.mapW3, hg * 64, (4 + rb) * 64, 0);
            ld_x0(0, 3); ld_w(3); ld_x0(1, 3); ld_x0(0, 4); ld_x0(1, 4);
            done(0, 0, 0); done(1, 0, 0);
            ld_w(4);
            ld_x0(1, 5); ld_x0(1, 6); ld_x0(1, 7);
            done(0, 1, 0); done(1, 1, 0);
            ld_w(5);
            if (rb2 < 8) tma_prefetch5(&p.mapWo, q2 * 64, rb2 * 2);
            done(0, 2, 0);
            fence_async_smem();
            ld_xe(5); ld_xe(6); ld_xe(7);
          } else {
            mbar_wait(bar + 8 * B_PDONE, 0);
            mbar_wait(bar + 8 * (B_PDONE + 1), 0);
            mbar_wait(bar + 8 * (WPRE == 1 ? B_U : B_GB + 1), 0);
            ld_w(0); ld_w(1); ld_w(2);
            mbar_wait(bar + 8 * (B_PUB + 2), 0);
            fence_async_smem();
            ld_w(3);
            done(0, 2, 1);
            fence_async_global();
            fence_async_smem();
            ld_xe(5); ld_xe(6); ld_xe(7);
            done(1, 0, 1);
            ld_w(4);
            done(1, 1, 1);
            ld_w(5);
          }
          done(1, 2, layer);
          fence_async_smem();
          ld_w(6); ld_w(7);
          auto ld_res = [&](int half) {
            const uint32_t b = bar + 8 * (B_RF + half);
            mbar_expect(b, PG);
            if (layer == 0) tma_ld(sb + (P_R + half) * PG, &p.mapX, q2 * 64, (16 * half + rb2) * 64, b);
            else tma_ld(sb + (P_R + half) * PG, &p.mapXT, (16 * half + rb2) * 64, DM + q2 * 64, b);
          };
          done(0, 4, layer); done(1, 3, layer);
          fence_async_smem();
#pragma unroll 1
          for (int c = 0; c < 8; c++) {
            const uint32_t b = bar + 8 * (B_WOF + (c >> 1));
            if (c == 5) { ld_res(0); done(1, 4, layer); }
            if ((c & 1) == 0) mbar_expect(b, 2 * PG);
            tma_ld5(sb + wo_page(c) * PG, &p.mapWo, q2 * 64, c * 2, b);
          }
          mbar_wait(bar + 8 * B_KG, 0);
          fence_async_global();
          ld_res(1);
        }
      }
    } else if (warp == 13) {
      if (elect_one()) {
        mbar_wait(bar + 8 * (B_WF + 2), 0);
        asm volatile("prefetch.tensormap [%0];" ::"l"(&p.mapO2) : "memory");
        asm volatile("prefetch.tensormap [%0];" ::"l"(&p.mapXT) : "memory");
        asm volatile("prefetch.tensormap [%0];" ::"l"(&p.mapOut) : "memory");
        asm volatile("prefetch.tensormap [%0];" ::"l"(&p.mapWo) : "memory");
        mbar_wait(bar + 8 * B_EP, 0);
        const unsigned e1 = lds32(sb + SM_EP) + 1;
        auto ld_x1 = [&](int half, int c0, int c1) {
          fence_async_global();
          fence_async_smem();
#pragma unroll 1
          for (int c = c0; c < c1; c++) {
            const uint32_t b = bar + 8 * (B_XF + 8 * half + c);
            mbar_expect(b, PG);
            tma_ld(sb + x_page(half, c) * PG, &p.mapXT, (16 * half + rb) * 64, DM + c * 64, b);
          }
        };
#pragma unroll 1
        for (int layer = 0; layer < 2; layer++) {
          if (layer == 1) {
            mbar_wait(bar + 8 * B_FARM, 0);
            mbar_wait(bar + 8 * B_PUB, 0);
            spin_until(&g_cnt[C_C * 32], e1 * NCTA);
            TS(10);
            ld_x1(0, 0, 3);
            if (hg >= 3) {
              mbar_expect(bar + 8 * B_SC, PG);
              tma_ld(sb + P_R * PG, &p.mapXT, rb * 64, DM + hg * 64, bar + 8 * B_SC);
            }
            ld_x1(0, 3, 5);
            mbar_wait(bar + 8 * (B_PUB + 1), 0);
            spin_until(&g_cnt[(C_C + 1) * 32], e1 * NCTA);
            TS(11);
            ld_x1(1, 0, 4);
            spin_until(&g_cnt[(C_C + 2) * 32], e1 * NCTA);
            TS(12);
            ld_x1(1, 4, 8);
          }
#pragma unroll 1
          for (int half = 0; half < 2; half++) {
            done(1, 7, layer);
            mbar_wait(bar + 8 * B_OST, layer);
            if (half) mbar_wait(bar + 8 * (B_OST + 1), layer);
            spin_until(&g_cnt[(C_O + layer * 32 + 16 * half + rb2) * 32], e1 * (OREL ? 8 : 32));
            fence_async_global();
            fence_async_smem();
#pragma unroll 1
            for (int c = 0; c < 4; c++) {
              const uint32_t b = bar + 8 * (B_OF + 4 * half + c);
              mbar_expect(b, 2 * PG);
              tma_ld3(sb + o_page(half, c) * PG, &p.mapO2, 0, (16 * half + rb2) * 64, 2 * c, b);
            }
          }
        }
        mbar_wait(bar + 8 * B_PUB, 1);
#pragma unroll 1
        for (int half = 0; half < 2; half++) {
          spin_until(&g_cnt[(C_F + 4 * (half ? 1 + (cta >> 6) : 0) + ((cta >> 4) & 3)) * 32], e1 * 32);
          fence_async_global();
          mbar_expect(bar + 8 * (B_TF + half), PG);
          tma_ld(sb + (16 + half) * PG, &p.mapXT, (16 * half + (cta & 15)) * 64, 3 * DM + (cta >> 4) * 64, bar + 8 * (B_TF + half));
        }
      }
    } else if (warp == 14) {
      mbar_wait(bar + 8 * B_EP, 0);
      const unsigned e1 = lds32(sb + SM_EP) + 1;
      done(0, 1, 0);
      {
        uint2 v[6];
        bool ok;
        int it = 0;
        do {
          ok = true;
#pragma unroll
          for (int i = 0; i < 6; i++) {
            const int k = lane + 32 * i;
            asm volatile("ld.relaxed.gpu.global.v2.u32 {%0,%1}, [%2];" : "=r"(v[i].x), "=r"(v[i].y) : "l"(&g_colsum[hg * 192 + k]) : "memory");
            ok = ok && v[i].y == e1;
          }
          if (++it > (1 << 22)) __trap();
        } while (!__all_sync(~0u, ok));
#pragma unroll
        for (int i = 0; i < 6; i++) sts32f(sb + SM_CS + 4 * (lane + 32 * i), __uint_as_float(v[i].x));
      }
      __syncwarp();
      if (lane == 0) {
        mbar_arrive(bar + 8 * B_CSF);
        TS(13);
#pragma unroll 1
        for (int i = 0; i < 4; i++) {
          const int layer = i >> 1;
          mbar_wait(bar + 8 * (B_PST + (i & 1)), layer);
          if (i & 1) mbar_wait(bar + 8 * B_AL, layer);
          spin_until(&g_cnt[(C_G + i) * 32], e1 * NCTA);
          if (i & 1) {
            const uint32_t b = bar + 8 * (B_GB + 1);
            fence_async_smem();
            mbar_expect(b, 4 * (3072 + 2048));
#pragma unroll 1
            for (int lc = 0; lc < 4; lc++) {
              bulk_ld(sb + cv_pe(lc), g_stats + (layer * 32 + 16 + 4 * lc) * 192, 3072, b);
              bulk_ld(sb + cv_x(1, lc), g_xT + ((size_t)(i - 1) * DM + cv_chan(cta, lc)) * LSEQ + 1024, 2048, b);
            }
            TS(14 + layer);
            publish(layer, 1);
          } else {
            mbar_arrive(bar + 8 * B_GB);
          }
        }
      }
    } else {
      auto reset = [&](bf16* buf) {
        uint4* dst = (uint4*)buf + cta * 1024 + lane;
#pragma unroll 4
        for (int i = 0; i < NFILL; i++) stg128(dst + 32 * i, make_uint4(UNSET, UNSET, UNSET, UNSET));
      };
      mbar_wait(bar + 8 * (B_WF + FILL0), 0);
      if (lane < 24) stg128((uint4*)g_stats + cta * 24 + lane, make_uint4(0, 0, 0, 0));
      reset(g_xT);
      __syncwarp();
      if (lane == 0) {
        mbar_wait(bar + 8 * B_CSF, 0);
        const unsigned e1 = lds32(sb + SM_EP) + 1;
        red_release(&g_cnt[C_CS * 32]);
        spin_until(&g_cnt[C_CS * 32], e1 * NCTA);
        mbar_arrive(bar + 8 * B_ZF);
        TS(3);
      }
      __syncwarp();
      if (FILL1 == 2) mbar_wait(bar + 8 * B_U, 0);
      reset(g_xT + 2 * LSEQ * DM); reset(g_xT + 3 * LSEQ * DM);
      __syncwarp();
      if (lane == 0) {
#pragma unroll 1
        for (int i = 0; i < 4; i++) publish(i >> 1, 2 * (i & 1));
      }
    }
  }
}

typedef CUresult (*EncodeFn)(CUtensorMap*, CUtensorMapDataType, cuuint32_t, void*, const cuuint64_t*, const cuuint64_t*,
                             const cuuint32_t*, const cuuint32_t*, CUtensorMapInterleave, CUtensorMapSwizzle,
                             CUtensorMapL2promotion, CUtensorMapFloatOOBfill);

static void make_map(EncodeFn enc, CUtensorMap* m, void* ptr, uint64_t cols, uint64_t rows, uint32_t box_rows) {
  cuuint64_t dims[2] = {cols, rows};
  cuuint64_t strides[1] = {cols * 2};
  cuuint32_t box[2] = {64, box_rows};
  cuuint32_t es[2] = {1, 1};
  enc(m, CU_TENSOR_MAP_DATA_TYPE_BFLOAT16, 2, ptr, dims, strides, box, es, CU_TENSOR_MAP_INTERLEAVE_NONE,
      CU_TENSOR_MAP_SWIZZLE_128B, CU_TENSOR_MAP_L2_PROMOTION_L2_128B, CU_TENSOR_MAP_FLOAT_OOB_FILL_NONE);
}
static void make_map3(EncodeFn enc, CUtensorMap* m, void* ptr, uint64_t d0, uint64_t cols, uint64_t rows, uint64_t blk_stride,
                      uint64_t nblocks, uint32_t nblk) {
  cuuint64_t dims[3] = {d0, rows, nblocks};
  cuuint64_t strides[2] = {cols * 2, blk_stride * 2};
  cuuint32_t box[3] = {64, 64, nblk};
  cuuint32_t es[3] = {1, 1, 1};
  enc(m, CU_TENSOR_MAP_DATA_TYPE_BFLOAT16, 3, ptr, dims, strides, box, es, CU_TENSOR_MAP_INTERLEAVE_NONE,
      CU_TENSOR_MAP_SWIZZLE_128B, CU_TENSOR_MAP_L2_PROMOTION_L2_128B, CU_TENSOR_MAP_FLOAT_OOB_FILL_NONE);
}

extern "C" void kernel_launch(void* const* d_in, const int* in_sizes, int n_in, void* d_out, int out_size) {
  static Params prm;
  static void* cached[13] = {nullptr};
  static bool attr_done = false;
  bool same = attr_done && cached[12] == d_out;
  for (int i = 0; i < 12 && same; i++) same = cached[i] == d_in[i];
  if (!same) {
    void* fn = nullptr;
    cudaDriverEntryPointQueryResult qr;
    cudaGetDriverEntryPoint("cuTensorMapEncodeTiled", &fn, cudaEnableDefault, &qr);
    EncodeFn enc = (EncodeFn)fn;
    void *pO, *pXT;
    cudaGetSymbolAddress(&pO, g_O);
    cudaGetSymbolAddress(&pXT, g_xT);
    make_map(enc, &prm.mapX, d_in[0], DM, LSEQ, 64);
    make_map(enc, &prm.mapXT, pXT, LSEQ, 4 * DM, 64);
    make_map(enc, &prm.mapOut, d_out, DM, LSEQ, 64);
    {
      cuuint64_t dims[5] = {DM, 2, 4, 4, 16};
      cuuint64_t strides[4] = {DM * 2, 8 * DM * 2, 2 * DM * 2, 32 * DM * 2};
      cuuint32_t box[5] = {64, 2, 4, 4, 2};
      cuuint32_t es[5] = {1, 1, 1, 1, 1};
      enc(&prm.mapWo, CU_TENSOR_MAP_DATA_TYPE_BFLOAT16, 5, d_in[2], dims, strides, box, es, CU_TENSOR_MAP_INTERLEAVE_NONE,
          CU_TENSOR_MAP_SWIZZLE_128B, CU_TENSOR_MAP_L2_PROMOTION_L2_128B, CU_TENSOR_MAP_FLOAT_OOB_FILL_NONE);
    }
    make_map3(enc, &prm.mapW3, d_in[1], DM, 3 * DM, DM, DM, 3, 3);
    make_map3(enc, &prm.mapO2, pO, 64, DM, LSEQ, 64, 8, 2);
    prm.wqkv = (const bf16*)d_in[1];
    prm.a_re = (const bf16*)d_in[4]; prm.a_im = (const bf16*)d_in[5];
    prm.b_re = (const bf16*)d_in[6]; prm.b_im = (const bf16*)d_in[7];
    prm.c_re = (const bf16*)d_in[8]; prm.c_im = (const bf16*)d_in[9];
    prm.log_dt = (const bf16*)d_in[10]; prm.dskip = (const bf16*)d_in[11];
    cudaFuncSetAttribute(fused_kernel, cudaFuncAttributeMaxDynamicSharedMemorySize, SM_TOTAL);
    for (int i = 0; i < 12; i++) cached[i] = d_in[i];
    cached[12] = d_out;
    attr_done = true;
  }
  fused_kernel<<<NCTA + 4, NTHREADS, SM_TOTAL>>>(prm);
}
```

```cpp
#include <cuda_runtime.h>
#include <cuda_bf16.h>
#include <cuda.h>
#include <stdint.h>

typedef __nv_bfloat16 bf16;

constexpr int LSEQ = 2048;
constexpr int DM = 512;
constexpr int NCTA = 128;
constexpr int NTHREADS = 512;
#define R_CONS 200
#define R_HELP 88
#define R_AGENT 24
#define GPOS 4
#define TURN0 4
#define TURN1 4

constexpr int PG = 8192;
constexpr int P_R = 25;
__host__ __device__ constexpr int x_page(int half, int c) { return half ? 8 + c : c < 5 ? c : c - 5; }
__host__ __device__ constexpr int w_page(int c) { return (c & 3) < 3 ? 16 + 3 * (c & 3) : c < 4 ? 5 : 8; }
__host__ __device__ constexpr int wo_page(int c) { return c < 5 ? 3 + c : 11 + c; }
__host__ __device__ constexpr int o_page(int half, int pair) { return half ? (pair ? 17 + 2 * pair : 0) : 8 + 2 * pair; }
constexpr int SM_KGB = (P_R + 1) * PG;
constexpr int SM_KC = 27 * PG;
constexpr int KC_STRIDE = 648;
__host__ __device__ constexpr int kc_off(int lc) { return SM_KC + (lc & 1) * 2 * KC_STRIDE + (lc < 2 ? 3328 : 0); }
constexpr int SM_KGT = SM_KC + 3328 + 2592;
constexpr int SM_CS = SM_KGT + 2048;
constexpr int SM_RED = SM_CS + 768;
constexpr int SM_EP = SM_RED + 16;
constexpr int SM_STG = SM_KGT;
constexpr int SM_BAR = SM_RED + 32;
constexpr int SM_TS = SM_BAR + 768;
constexpr int SM_TOTAL = SM_TS + 512;
static_assert(SM_TOTAL <= 232448 && SM_STG % 16 == 0 && SM_KGT % 16 == 0, "shared memory");

constexpr int CV_UH = 140 * 16;
__host__ __device__ constexpr int cv_u(int lc) { return (8 + 2 * lc) * PG; }
__host__ __device__ constexpr int cv_pe(int lc) { return cv_u(lc) + 4480; }
__host__ __device__ constexpr int cv_pb1(int lc, int w) { return w ? cv_u(lc) + 8960 + (w - 1) * 2048 : 7 * PG + lc * 2048; }
__host__ __device__ constexpr int cv_fa(int lc) { return cv_pb1(lc, 1) + 128; }
__host__ __device__ constexpr int cv_dump(int lc) { return cv_u(lc) + 16256; }
__host__ __device__ constexpr int cv_pb0(int lc, int w) { return lc * PG + w * 2048; }
__host__ __device__ constexpr int cv_se(int lc) { return 4 * PG + lc * 4096; }
__host__ __device__ constexpr int cv_so(int lc) { return cv_se(lc) + 2048; }
__host__ __device__ constexpr int cv_pf(int lc) { return 6 * PG + lc * 2048; }
__host__ __device__ constexpr int cv_x(int half, int lc) { return (P_R + half) * PG + lc * 2048; }
__host__ __device__ constexpr int cv_chan(int cta, int lc) { return 2 * cta + (lc & 1) + 256 * (lc >> 1); }

enum {
  B_XF = 0,
  B_WF = 16,
  B_OF = 24,
  B_DN = 32,
  B_WOF = 48,
  B_RF = 52,
  B_PST = 54,
  B_OST = 56,
  B_PDONE = 58,
  B_GB = 60,
  B_TF = 62,
  B_CSF = 64,
  B_EP = 65,
  B_Z0 = 66,
  B_KG = 67,
  B_FARM = 68,
  B_PE = 70,
  B_U = 71,
  B_PUB = 74,
  B_R = 77,
  B_END = 80,
  B_SC = 81,
  B_RT = 82,
  B_AL = 84,
  B_COUNT = 85
};

enum {
  C_CS = 0,
  C_G = 1,
  C_C = 5,
  C_F = 8,
  C_O = 20,
  C_Z = 84,
  C_COUNT = 85
};

__device__ unsigned g_cnt[C_COUNT * 32];
__device__ __align__(1024) bf16 g_O[2 * LSEQ * DM];
__device__ __align__(1024) bf16 g_xT[4 * DM * LSEQ];
__device__ __align__(1024) float g_stats[2 * 32 * 192];
__device__ __align__(1024) uint2 g_colsum[3 * DM];
__device__ __align__(1024) uint4 g_halo[2 * 32 * 8 * 256];
__device__ __align__(1024) uint4 g_part[2 * 32 * 8 * 64];
#define TS(i) do { } while (0)
#define TSW(k) do { if ((threadIdx.x & 127) == 0) TS(16 + layer * 56 + (threadIdx.x >> 7) * 20 + (k)); } while (0)
#define TSG(k) do { } while (0)

#define RETRY(i) do { } while (0)
#define LTS(i) do { } while (0)

struct Params {
  CUtensorMap mapX, mapW3, mapO2, mapXT, mapOut, mapWo;
  const bf16 *wqkv, *a_re, *a_im, *b_re, *b_im, *c_re, *c_im, *log_dt, *dskip;
};

__device__ __forceinline__ uint32_t s32(const void* p) { return (uint32_t)__cvta_generic_to_shared(p); }
__device__ __forceinline__ void mbar_init(uint32_t b, int c) { asm volatile("mbarrier.init.shared::cta.b64 [%0], %1;" ::"r"(b), "r"(c) : "memory"); }
__device__ __forceinline__ void mbar_expect(uint32_t b, int bytes) { asm volatile("mbarrier.arrive.expect_tx.shared::cta.b64 _, [%0], %1;" ::"r"(b), "r"(bytes) : "memory"); }
__device__ __forceinline__ void mbar_arrive(uint32_t b) { asm volatile("mbarrier.arrive.shared::cta.b64 _, [%0];" ::"r"(b) : "memory"); }
__device__ __forceinline__ void mbar_wait(uint32_t b, int parity) {
  asm volatile("{\n.reg .pred p;\nWAIT_LOOP:\nmbarrier.try_wait.parity.shared::cta.b64 p, [%0], %1;\n@p bra WAIT_DONE;\nbra WAIT_LOOP;\nWAIT_DONE:\n}" ::"r"(b), "r"(parity) : "memory");
}
__device__ __forceinline__ bool mbar_test(uint32_t b, int parity) {
  uint32_t ok;
  asm volatile("{\n.reg .pred p;\nmbarrier.test_wait.parity.shared::cta.b64 p, [%1], %2;\nselp.u32 %0, 1, 0, p;\n}" : "=r"(ok) : "r"(b), "r"(parity) : "memory");
  return ok != 0;
}
__device__ __forceinline__ int opaque_tid() { int v; asm volatile("mov.u32 %0, %%tid.x;" : "=r"(v)); return v; }
__device__ __forceinline__ bool elect_one() {
  uint32_t r;
  asm volatile("{\n.reg .pred p;\nelect.sync _|p, 0xffffffff;\nselp.u32 %0, 1, 0, p;\n}" : "=r"(r));
  return r != 0;
}
__device__ __forceinline__ void tma_ld(uint32_t dst, const CUtensorMap* m, int c0, int c1, uint32_t bar) {
  asm volatile("cp.async.bulk.tensor.2d.shared::cluster.global.mbarrier::complete_tx::bytes [%0], [%1, {%3, %4}], [%2];"
               ::"r"(dst), "l"(m), "r"(bar), "r"(c0), "r"(c1) : "memory");
}
__device__ __forceinline__ void tma_ld3(uint32_t dst, const CUtensorMap* m, int c0, int c1, int c2, uint32_t bar) {
  asm volatile("cp.async.bulk.tensor.3d.shared::cluster.global.mbarrier::complete_tx::bytes [%0], [%1, {%3, %4, %5}], [%2];"
               ::"r"(dst), "l"(m), "r"(bar), "r"(c0), "r"(c1), "r"(c2) : "memory");
}
__device__ __forceinline__ void tma_ld5(uint32_t dst, const CUtensorMap* m, int c0, int c4, uint32_t bar) {
  asm volatile("cp.async.bulk.tensor.5d.shared::cluster.global.mbarrier::complete_tx::bytes [%0], [%1, {%3, 0, 0, 0, %4}], [%2];"
               ::"r"(dst), "l"(m), "r"(bar), "r"(c0), "r"(c4) : "memory");
}
__device__ __forceinline__ void tma_prefetch5(const CUtensorMap* m, int c0, int c4) {
  asm volatile("cp.async.bulk.prefetch.tensor.5d.L2.global.tile [%0, {%1, 0, 0, 0, %2}];" ::"l"(m), "r"(c0), "r"(c4) : "memory");
}
__device__ __forceinline__ void tma_prefetch2(const CUtensorMap* m, int c0, int c1) {
  asm volatile("cp.async.bulk.prefetch.tensor.2d.L2.global.tile [%0, {%1, %2}];" ::"l"(m), "r"(c0), "r"(c1) : "memory");
}
__device__ __forceinline__ void tma_prefetch3(const CUtensorMap* m, int c0, int c1, int c2) {
  asm volatile("cp.async.bulk.prefetch.tensor.3d.L2.global.tile [%0, {%1, %2, %3}];" ::"l"(m), "r"(c0), "r"(c1), "r"(c2) : "memory");
}
__device__ __forceinline__ void tma_st(const CUtensorMap* m, int c0, int c1, uint32_t src) {
  asm volatile("cp.async.bulk.tensor.2d.global.shared::cta.bulk_group [%0, {%2, %3}], [%1];" ::"l"(m), "r"(src), "r"(c0), "r"(c1) : "memory");
}
__device__ __forceinline__ void bulk_ld(uint32_t dst, const void* src, int bytes, uint32_t bar) {
  asm volatile("cp.async.bulk.shared::cluster.global.mbarrier::complete_tx::bytes [%0], [%1], %2, [%3];" ::"r"(dst), "l"(src), "r"(bytes), "r"(bar) : "memory");
}
__device__ __forceinline__ void bulk_st(void* dst, uint32_t src, int bytes) {
  asm volatile("cp.async.bulk.global.shared::cta.bulk_group [%0], [%1], %2;" ::"l"(dst), "r"(src), "r"(bytes) : "memory");
}
__device__ __forceinline__ void bulk_red_add_f32(void* dst, uint32_t src, int bytes) {
  asm volatile("cp.reduce.async.bulk.global.shared::cta.bulk_group.add.f32 [%0], [%1], %2;" ::"l"(dst), "r"(src), "r"(bytes) : "memory");
}
__device__ __forceinline__ void bulk_commit() { asm volatile("cp.async.bulk.commit_group;" ::: "memory"); }
__device__ __forceinline__ void bulk_wait_all() { asm volatile("cp.async.bulk.wait_group 0;" ::: "memory"); }
__device__ __forceinline__ void fence_async_smem() { asm volatile("fence.proxy.async.shared::cta;" ::: "memory"); }
__device__ __forceinline__ void fence_async_global() { asm volatile("fence.proxy.async.global;" ::: "memory"); }
__device__ __forceinline__ void bar_sync(int id, int n) { asm volatile("bar.sync %0, %1;" ::"r"(id), "r"(n) : "memory"); }
__device__ __forceinline__ void bar_arrive(int id, int n) { asm volatile("bar.arrive %0, %1;" ::"r"(id), "r"(n) : "memory"); }
__device__ __forceinline__ bool bar_or(int id, int n, bool v) {
  uint32_t r;
  asm volatile("{\n.reg .pred p, q;\nsetp.ne.u32 q, %3, 0;\nbar.red.or.pred p, %1, %2, q;\nselp.u32 %0, 1, 0, p;\n}" : "=r"(r) : "r"(id), "r"(n), "r"((uint32_t)v) : "memory");
  return r != 0;
}
__device__ __forceinline__ void bulk_wait_read() { asm volatile("cp.async.bulk.wait_group.read 0;" ::: "memory"); }
__device__ __forceinline__ void stg128(void* p, uint4 v) { asm volatile("st.relaxed.gpu.global.v4.u32 [%0], {%1,%2,%3,%4};" ::"l"(p), "r"(v.x), "r"(v.y), "r"(v.z), "r"(v.w) : "memory"); }
constexpr uint32_t UNSET = 0xffffffffu;
constexpr int MAX_RETRY = 1 << 16;
__device__ __forceinline__ void wg_fence() { asm volatile("wgmma.fence.sync.aligned;" ::: "memory"); }
__device__ __forceinline__ void wg_commit() { asm volatile("wgmma.commit_group.sync.aligned;" ::: "memory"); }
template <int N> __device__ __forceinline__ void wg_wait() { asm volatile("wgmma.wait_group.sync.aligned %0;" ::"n"(N) : "memory"); }
__device__ __forceinline__ uint64_t mkdesc(uint32_t addr, uint32_t lbo, uint32_t sbo, int sw) {
  return (uint64_t)((addr & 0x3FFFF) >> 4) | ((uint64_t)(lbo >> 4) << 16) | ((uint64_t)(sbo >> 4) << 32) | ((uint64_t)sw << 62);
}
__device__ __forceinline__ void ldsm4(uint32_t* r, uint32_t a) {
  asm volatile("ldmatrix.sync.aligned.m8n8.x4.shared.b16 {%0,%1,%2,%3}, [%4];" : "=r"(r[0]), "=r"(r[1]), "=r"(r[2]), "=r"(r[3]) : "r"(a) : "memory");
}
__device__ __forceinline__ void ldsm4t(uint32_t* r, uint32_t a) {
  asm volatile("ldmatrix.sync.aligned.m8n8.x4.trans.shared.b16 {%0,%1,%2,%3}, [%4];" : "=r"(r[0]), "=r"(r[1]), "=r"(r[2]), "=r"(r[3]) : "r"(a) : "memory");
}
__device__ __forceinline__ void stsm4(uint32_t a, uint32_t r0, uint32_t r1, uint32_t r2, uint32_t r3) {
  asm volatile("stmatrix.sync.aligned.m8n8.x4.shared.b16 [%0], {%1,%2,%3,%4};" ::"r"(a), "r"(r0), "r"(r1), "r"(r2), "r"(r3) : "memory");
}
__device__ __forceinline__ void stsm4t(uint32_t a, uint32_t r0, uint32_t r1, uint32_t r2, uint32_t r3) {
  asm volatile("stmatrix.sync.aligned.m8n8.x4.trans.shared.b16 [%0], {%1,%2,%3,%4};" ::"r"(a), "r"(r0), "r"(r1), "r"(r2), "r"(r3) : "memory");
}
__device__ __forceinline__ uint32_t movm_t(uint32_t a) { uint32_t r; asm volatile("movmatrix.sync.aligned.m8n8.trans.b16 %0, %1;" : "=r"(r) : "r"(a)); return r; }
__device__ __forceinline__ uint32_t lds32(uint32_t a) { uint32_t v; asm volatile("ld.shared.b32 %0, [%1];" : "=r"(v) : "r"(a) : "memory"); return v; }
__device__ __forceinline__ float2 lds64f(uint32_t a) { float2 v; asm volatile("ld.shared.v2.f32 {%0,%1}, [%2];" : "=f"(v.x), "=f"(v.y) : "r"(a) : "memory"); return v; }
__device__ __forceinline__ float4 lds128f(uint32_t a) { float4 v; asm volatile("ld.shared.v4.f32 {%0,%1,%2,%3}, [%4];" : "=f"(v.x), "=f"(v.y), "=f"(v.z), "=f"(v.w) : "r"(a) : "memory"); return v; }
__device__ __forceinline__ uint4 lds128(uint32_t a) { uint4 v; asm volatile("ld.shared.v4.b32 {%0,%1,%2,%3}, [%4];" : "=r"(v.x), "=r"(v.y), "=r"(v.z), "=r"(v.w) : "r"(a) : "memory"); return v; }
__device__ __forceinline__ void sts128(uint32_t a, uint4 v) { asm volatile("st.shared.v4.b32 [%0], {%1,%2,%3,%4};" ::"r"(a), "r"(v.x), "r"(v.y), "r"(v.z), "r"(v.w) : "memory"); }
__device__ __forceinline__ void sts128f(uint32_t a, float x, float y, float z, float w) { asm volatile("st.shared.v4.f32 [%0], {%1,%2,%3,%4};" ::"r"(a), "f"(x), "f"(y), "f"(z), "f"(w) : "memory"); }
__device__ __forceinline__ void sts32f(uint32_t a, float v) { asm volatile("st.shared.f32 [%0], %1;" ::"r"(a), "f"(v) : "memory"); }
__device__ __forceinline__ void sts16(uint32_t a, uint16_t v) { asm volatile("st.shared.u16 [%0], %1;" ::"r"(a), "h"(v) : "memory"); }
__device__ __forceinline__ uint32_t lds16(uint32_t a) { uint16_t v; asm volatile("ld.shared.u16 %0, [%1];" : "=h"(v) : "r"(a) : "memory"); return v; }
__device__ __forceinline__ uint32_t packbf(float lo, float hi) { uint32_t r; asm("cvt.rn.bf16x2.f32 %0, %1, %2;" : "=r"(r) : "f"(hi), "f"(lo)); return r; }
__device__ __forceinline__ float bf_lo(uint32_t v) { return __uint_as_float(v << 16); }
__device__ __forceinline__ float bf_hi(uint32_t v) { return __uint_as_float(v & 0xffff0000u); }
__device__ __forceinline__ float ex2(float x) { float r; asm("ex2.approx.ftz.f32 %0, %1;" : "=f"(r) : "f"(x)); return r; }
__device__ __forceinline__ float rsqrt_approx(float x) { float r; asm("rsqrt.approx.ftz.f32 %0, %1;" : "=f"(r) : "f"(x)); return r; }
__device__ __forceinline__ float rcp_approx(float x) { float r; asm("rcp.approx.ftz.f32 %0, %1;" : "=f"(r) : "f"(x)); return r; }
__device__ __forceinline__ void mma_bf16(float* d, const uint32_t* a, uint32_t b0, uint32_t b1) {
  asm("mma.sync.aligned.m16n8k16.row.col.f32.bf16.bf16.f32 {%0,%1,%2,%3}, {%4,%5,%6,%7}, {%8,%9}, {%0,%1,%2,%3};"
               : "+f"(d[0]), "+f"(d[1]), "+f"(d[2]), "+f"(d[3]) : "r"(a[0]), "r"(a[1]), "r"(a[2]), "r"(a[3]), "r"(b0), "r"(b1));
}
__device__ __forceinline__ void mma_tf32(float* d, float a0, float a1, float a2, float a3, float b0, float b1) {
  asm("mma.sync.aligned.m16n8k8.row.col.f32.tf32.tf32.f32 {%0,%1,%2,%3}, {%4,%5,%6,%7}, {%8,%9}, {%0,%1,%2,%3};"
               : "+f"(d[0]), "+f"(d[1]), "+f"(d[2]), "+f"(d[3])
               : "r"(__float_as_uint(a0)), "r"(__float_as_uint(a1)), "r"(__float_as_uint(a2)), "r"(__float_as_uint(a3)),
                 "r"(__float_as_uint(b0)), "r"(__float_as_uint(b1)));
}
__device__ __forceinline__ void red_release(unsigned* p) { asm volatile("red.release.gpu.global.add.u32 [%0], 1;" ::"l"(p) : "memory"); }
__device__ __forceinline__ void red_relaxed(unsigned* p) { asm volatile("red.relaxed.gpu.global.add.u32 [%0], 1;" ::"l"(p) : "memory"); }
__device__ __forceinline__ unsigned ld_relaxed(const unsigned* p) { unsigned v; asm volatile("ld.relaxed.gpu.global.u32 %0, [%1];" : "=r"(v) : "l"(p) : "memory"); return v; }
__device__ __forceinline__ void spin_until(const unsigned* p, unsigned target) {
  int it = 0;
  while ((int)(ld_relaxed(p) - target) < 0) {
    if (++it > (1 << 23)) __trap();
  }
}
__device__ __forceinline__ uint4 ldcg128(const void* p) { uint4 v; asm volatile("ld.global.cg.v4.b32 {%0,%1,%2,%3}, [%4];" : "=r"(v.x), "=r"(v.y), "=r"(v.z), "=r"(v.w) : "l"(p) : "memory"); return v; }
__device__ __forceinline__ uint4 ld_tagged(const uint4* p) { uint4 v; asm volatile("ld.relaxed.gpu.global.v4.u32 {%0,%1,%2,%3}, [%4];" : "=r"(v.x), "=r"(v.y), "=r"(v.z), "=r"(v.w) : "l"(p) : "memory"); return v; }
__device__ __forceinline__ void st_tagged(uint4* p, uint32_t a, uint32_t b, uint32_t tag) { asm volatile("st.relaxed.gpu.global.v4.u32 [%0], {%1,%2,%3,%2};" ::"l"(p), "r"(a), "r"(tag), "r"(b) : "memory"); }
__device__ __forceinline__ void st_tagged3(uint4* p, uint32_t a, uint32_t b, uint32_t c, uint32_t tag) { asm volatile("st.relaxed.gpu.global.v4.u32 [%0], {%1,%2,%3,%4};" ::"l"(p), "r"(a), "r"(b), "r"(c), "r"(tag) : "memory"); }
__device__ __forceinline__ uint4 poll_tagged(const uint4* p, uint32_t tag) {
  uint4 v = ld_tagged(p);
  int it = 0;
  while (v.y != tag || v.w != tag) {
    if (++it > (1 << 22)) __trap();
    v = ld_tagged(p);
  }
  return v;
}
__device__ __forceinline__ uint32_t hadd2(uint32_t a, uint32_t b) { uint32_t r; asm("add.rn.bf16x2 %0, %1, %2;" : "=r"(r) : "r"(a), "r"(b)); return r; }
__device__ __forceinline__ uint32_t hmul2(uint32_t a, uint32_t b) { uint32_t r; asm("mul.rn.bf16x2 %0, %1, %2;" : "=r"(r) : "r"(a), "r"(b)); return r; }

__device__ __forceinline__ uint32_t hfma2(uint32_t a, uint32_t b, uint32_t c) { uint32_t r; asm("fma.rn.bf16x2 %0, %1, %2, %3;" : "=r"(r) : "r"(a), "r"(b), "r"(c)); return r; }
__device__ __forceinline__ void sts32(uint32_t a, uint32_t v) { asm volatile("st.shared.u32 [%0], %1;" ::"r"(a), "r"(v) : "memory"); }

template <int N> __device__ __forceinline__ void acc_fence(float* a) {
#pragma unroll
  for (int i = 0; i < N; i++) asm volatile("" : "+f"(a[i]) :: "memory");
}

template<int N,int TB> __device__ __forceinline__ void wgmma_rs(float* d, const uint32_t* a, uint64_t db, int sd);
template<int N,int TA,int TB> __device__ __forceinline__ void wgmma_ss(float* d, uint64_t da, uint64_t db, int sd);
template<> __device__ __forceinline__ void wgmma_rs<64,0>(float* d, const uint32_t* a, uint64_t db, int sd) {
  asm volatile("{\n.reg .pred p;\nsetp.ne.b32 p, %37, 0;\nwgmma.mma_async.sync.aligned.m64n64k16.f32.bf16.bf16 {%0,%1,%2,%3,%4,%5,%6,%7,%8,%9,%10,%11,%12,%13,%14,%15,%16,%17,%18,%19,%20,%21,%22,%23,%24,%25,%26,%27,%28,%29,%30,%31}, {%32,%33,%34,%35}, %36, p, 1, 1, 0;\n}\n"
   : "+f"(d[0]),"+f"(d[1]),"+f"(d[2]),"+f"(d[3]),"+f"(d[4]),"+f"(d[5]),"+f"(d[6]),"+f"(d[7]),"+f"(d[8]),"+f"(d[9]),"+f"(d[10]),"+f"(d[11]),"+f"(d[12]),"+f"(d[13]),"+f"(d[14]),"+f"(d[15]),"+f"(d[16]),"+f"(d[17]),"+f"(d[18]),"+f"(d[19]),"+f"(d[20]),"+f"(d[21]),"+f"(d[22]),"+f"(d[23]),"+f"(d[24]),"+f"(d[25]),"+f"(d[26]),"+f"(d[27]),"+f"(d[28]),"+f"(d[29]),"+f"(d[30]),"+f"(d[31])
   : "r"(a[0]), "r"(a[1]), "r"(a[2]), "r"(a[3]), "l"(db), "r"(sd));
}
template<> __device__ __forceinline__ void wgmma_rs<56,0>(float* d, const uint32_t* a, uint64_t db, int sd) {
  asm volatile("{\n.reg .pred p;\nsetp.ne.b32 p, %33, 0;\nwgmma.mma_async.sync.aligned.m64n56k16.f32.bf16.bf16 {%0,%1,%2,%3,%4,%5,%6,%7,%8,%9,%10,%11,%12,%13,%14,%15,%16,%17,%18,%19,%20,%21,%22,%23,%24,%25,%26,%27}, {%28,%29,%30,%31}, %32, p, 1, 1, 0;\n}\n"
   : "+f"(d[0]),"+f"(d[1]),"+f"(d[2]),"+f"(d[3]),"+f"(d[4]),"+f"(d[5]),"+f"(d[6]),"+f"(d[7]),"+f"(d[8]),"+f"(d[9]),"+f"(d[10]),"+f"(d[11]),"+f"(d[12]),"+f"(d[13]),"+f"(d[14]),"+f"(d[15]),"+f"(d[16]),"+f"(d[17]),"+f"(d[18]),"+f"(d[19]),"+f"(d[20]),"+f"(d[21]),"+f"(d[22]),"+f"(d[23]),"+f"(d[24]),"+f"(d[25]),"+f"(d[26]),"+f"(d[27])
   : "r"(a[0]), "r"(a[1]), "r"(a[2]), "r"(a[3]), "l"(db), "r"(sd));
}
template<> __device__ __forceinline__ void wgmma_rs<48,0>(float* d, const uint32_t* a, uint64_t db, int sd) {
  asm volatile("{\n.reg .pred p;\nsetp.ne.b32 p, %29, 0;\nwgmma.mma_async.sync.aligned.m64n48k16.f32.bf16.bf16 {%0,%1,%2,%3,%4,%5,%6,%7,%8,%9,%10,%11,%12,%13,%14,%15,%16,%17,%18,%19,%20,%21,%22,%23}, {%24,%25,%26,%27}, %28, p, 1, 1, 0;\n}\n"
   : "+f"(d[0]),"+f"(d[1]),"+f"(d[2]),"+f"(d[3]),"+f"(d[4]),"+f"(d[5]),"+f"(d[6]),"+f"(d[7]),"+f"(d[8]),"+f"(d[9]),"+f"(d[10]),"+f"(d[11]),"+f"(d[12]),"+f"(d[13]),"+f"(d[14]),"+f"(d[15]),"+f"(d[16]),"+f"(d[17]),"+f"(d[18]),"+f"(d[19]),"+f"(d[20]),"+f"(d[21]),"+f"(d[22]),"+f"(d[23])
   : "r"(a[0]), "r"(a[1]), "r"(a[2]), "r"(a[3]), "l"(db), "r"(sd));
}
template<> __device__ __forceinline__ void wgmma_rs<40,0>(float* d, const uint32_t* a, uint64_t db, int sd) {
  asm volatile("{\n.reg .pred p;\nsetp.ne.b32 p, %25, 0;\nwgmma.mma_async.sync.aligned.m64n40k16.f32.bf16.bf16 {%0,%1,%2,%3,%4,%5,%6,%7,%8,%9,%10,%11,%12,%13,%14,%15,%16,%17,%18,%19}, {%20,%21,%22,%23}, %24, p, 1, 1, 0;\n}\n"
   : "+f"(d[0]),"+f"(d[1]),"+f"(d[2]),"+f"(d[3]),"+f"(d[4]),"+f"(d[5]),"+f"(d[6]),"+f"(d[7]),"+f"(d[8]),"+f"(d[9]),"+f"(d[10]),"+f"(d[11]),"+f"(d[12]),"+f"(d[13]),"+f"(d[14]),"+f"(d[15]),"+f"(d[16]),"+f"(d[17]),"+f"(d[18]),"+f"(d[19])
   : "r"(a[0]), "r"(a[1]), "r"(a[2]), "r"(a[3]), "l"(db), "r"(sd));
}
template<> __device__ __forceinline__ void wgmma_rs<32,0>(float* d, const uint32_t* a, uint64_t db, int sd) {
  asm volatile("{\n.reg .pred p;\nsetp.ne.b32 p, %21, 0;\nwgmma.mma_async.sync.aligned.m64n32k16.f32.bf16.bf16 {%0,%1,%2,%3,%4,%5,%6,%7,%8,%9,%10,%11,%12,%13,%14,%15}, {%16,%17,%18,%19}, %20, p, 1, 1, 0;\n}\n"
   : "+f"(d[0]),"+f"(d[1]),"+f"(d[2]),"+f"(d[3]),"+f"(d[4]),"+f"(d[5]),"+f"(d[6]),"+f"(d[7]),"+f"(d[8]),"+f"(d[9]),"+f"(d[10]),"+f"(d[11]),"+f"(d[12]),"+f"(d[13]),"+f"(d[14]),"+f"(d[15])
   : "r"(a[0]), "r"(a[1]), "r"(a[2]), "r"(a[3]), "l"(db), "r"(sd));
}
template<> __device__ __forceinline__ void wgmma_rs<24,0>(float* d, const uint32_t* a, uint64_t db, int sd) {
  asm volatile("{\n.reg .pred p;\nsetp.ne.b32 p, %17, 0;\nwgmma.mma_async.sync.aligned.m64n24k16.f32.bf16.bf16 {%0,%1,%2,%3,%4,%5,%6,%7,%8,%9,%10,%11}, {%12,%13,%14,%15}, %16, p, 1, 1, 0;\n}\n"
   : "+f"(d[0]),"+f"(d[1]),"+f"(d[2]),"+f"(d[3]),"+f"(d[4]),"+f"(d[5]),"+f"(d[6]),"+f"(d[7]),"+f"(d[8]),"+f"(d[9]),"+f"(d[10]),"+f"(d[11])
   : "r"(a[0]), "r"(a[1]), "r"(a[2]), "r"(a[3]), "l"(db), "r"(sd));
}
template<> __device__ __forceinline__ void wgmma_rs<16,0>(float* d, const uint32_t* a, uint64_t db, int sd) {
  asm volatile("{\n.reg .pred p;\nsetp.ne.b32 p, %13, 0;\nwgmma.mma_async.sync.aligned.m64n16k16.f32.bf16.bf16 {%0,%1,%2,%3,%4,%5,%6,%7}, {%8,%9,%10,%11}, %12, p, 1, 1, 0;\n}\n"
   : "+f"(d[0]),"+f"(d[1]),"+f"(d[2]),"+f"(d[3]),"+f"(d[4]),"+f"(d[5]),"+f"(d[6]),"+f"(d[7])
   : "r"(a[0]), "r"(a[1]), "r"(a[2]), "r"(a[3]), "l"(db), "r"(sd));
}
template<> __device__ __forceinline__ void wgmma_rs<8,0>(float* d, const uint32_t* a, uint64_t db, int sd) {
  asm volatile("{\n.reg .pred p;\nsetp.ne.b32 p, %9, 0;\nwgmma.mma_async.sync.aligned.m64n8k16.f32.bf16.bf16 {%0,%1,%2,%3}, {%4,%5,%6,%7}, %8, p, 1, 1, 0;\n}\n"
   : "+f"(d[0]),"+f"(d[1]),"+f"(d[2]),"+f"(d[3])
   : "r"(a[0]), "r"(a[1]), "r"(a[2]), "r"(a[3]), "l"(db), "r"(sd));
}
template<> __device__ __forceinline__ void wgmma_ss<16,0,1>(float* d, uint64_t da, uint64_t db, int sd) {
  asm volatile("{\n.reg .pred p;\nsetp.ne.b32 p, %10, 0;\nwgmma.mma_async.sync.aligned.m64n16k16.f32.bf16.bf16 {%0,%1,%2,%3,%4,%5,%6,%7}, %8, %9, p, 1, 1, 0, 1;\n}\n"
   : "+f"(d[0]),"+f"(d[1]),"+f"(d[2]),"+f"(d[3]),"+f"(d[4]),"+f"(d[5]),"+f"(d[6]),"+f"(d[7])
   : "l"(da), "l"(db), "r"(sd));
}
template<> __device__ __forceinline__ void wgmma_ss<64,0,1>(float* d, uint64_t da, uint64_t db, int sd) {
  asm volatile("{\n.reg .pred p;\nsetp.ne.b32 p, %34, 0;\nwgmma.mma_async.sync.aligned.m64n64k16.f32.bf16.bf16 {%0,%1,%2,%3,%4,%5,%6,%7,%8,%9,%10,%11,%12,%13,%14,%15,%16,%17,%18,%19,%20,%21,%22,%23,%24,%25,%26,%27,%28,%29,%30,%31}, %32, %33, p, 1, 1, 0, 1;\n}\n"
   : "+f"(d[0]),"+f"(d[1]),"+f"(d[2]),"+f"(d[3]),"+f"(d[4]),"+f"(d[5]),"+f"(d[6]),"+f"(d[7]),"+f"(d[8]),"+f"(d[9]),"+f"(d[10]),"+f"(d[11]),"+f"(d[12]),"+f"(d[13]),"+f"(d[14]),"+f"(d[15]),"+f"(d[16]),"+f"(d[17]),"+f"(d[18]),"+f"(d[19]),"+f"(d[20]),"+f"(d[21]),"+f"(d[22]),"+f"(d[23]),"+f"(d[24]),"+f"(d[25]),"+f"(d[26]),"+f"(d[27]),"+f"(d[28]),"+f"(d[29]),"+f"(d[30]),"+f"(d[31])
   : "l"(da), "l"(db), "r"(sd));
}
template<> __device__ __forceinline__ void wgmma_ss<192,0,1>(float* d, uint64_t da, uint64_t db, int sd) {
  asm volatile("{\n.reg .pred p;\nsetp.ne.b32 p, %98, 0;\nwgmma.mma_async.sync.aligned.m64n192k16.f32.bf16.bf16 {%0,%1,%2,%3,%4,%5,%6,%7,%8,%9,%10,%11,%12,%13,%14,%15,%16,%17,%18,%19,%20,%21,%22,%23,%24,%25,%26,%27,%28,%29,%30,%31,%32,%33,%34,%35,%36,%37,%38,%39,%40,%41,%42,%43,%44,%45,%46,%47,%48,%49,%50,%51,%52,%53,%54,%55,%56,%57,%58,%59,%60,%61,%62,%63,%64,%65,%66,%67,%68,%69,%70,%71,%72,%73,%74,%75,%76,%77,%78,%79,%80,%81,%82,%83,%84,%85,%86,%87,%88,%89,%90,%91,%92,%93,%94,%95}, %96, %97, p, 1, 1, 0, 1;\n}\n"
   : "+f"(d[0]),"+f"(d[1]),"+f"(d[2]),"+f"(d[3]),"+f"(d[4]),"+f"(d[5]),"+f"(d[6]),"+f"(d[7]),"+f"(d[8]),"+f"(d[9]),"+f"(d[10]),"+f"(d[11]),"+f"(d[12]),"+f"(d[13]),"+f"(d[14]),"+f"(d[15]),"+f"(d[16]),"+f"(d[17]),"+f"(d[18]),"+f"(d[19]),"+f"(d[20]),"+f"(d[21]),"+f"(d[22]),"+f"(d[23]),"+f"(d[24]),"+f"(d[25]),"+f"(d[26]),"+f"(d[27]),"+f"(d[28]),"+f"(d[29]),"+f"(d[30]),"+f"(d[31]),"+f"(d[32]),"+f"(d[33]),"+f"(d[34]),"+f"(d[35]),"+f"(d[36]),"+f"(d[37]),"+f"(d[38]),"+f"(d[39]),"+f"(d[40]),"+f"(d[41]),"+f"(d[42]),"+f"(d[43]),"+f"(d[44]),"+f"(d[45]),"+f"(d[46]),"+f"(d[47]),"+f"(d[48]),"+f"(d[49]),"+f"(d[50]),"+f"(d[51]),"+f"(d[52]),"+f"(d[53]),"+f"(d[54]),"+f"(d[55]),"+f"(d[56]),"+f"(d[57]),"+f"(d[58]),"+f"(d[59]),"+f"(d[60]),"+f"(d[61]),"+f"(d[62]),"+f"(d[63]),"+f"(d[64]),"+f"(d[65]),"+f"(d[66]),"+f"(d[67]),"+f"(d[68]),"+f"(d[69]),"+f"(d[70]),"+f"(d[71]),"+f"(d[72]),"+f"(d[73]),"+f"(d[74]),"+f"(d[75]),"+f"(d[76]),"+f"(d[77]),"+f"(d[78]),"+f"(d[79]),"+f"(d[80]),"+f"(d[81]),"+f"(d[82]),"+f"(d[83]),"+f"(d[84]),"+f"(d[85]),"+f"(d[86]),"+f"(d[87]),"+f"(d[88]),"+f"(d[89]),"+f"(d[90]),"+f"(d[91]),"+f"(d[92]),"+f"(d[93]),"+f"(d[94]),"+f"(d[95])
   : "l"(da), "l"(db), "r"(sd));
}
template<> __device__ __forceinline__ void wgmma_ss<192,1,1>(float* d, uint64_t da, uint64_t db, int sd) {
  asm volatile("{\n.reg .pred p;\nsetp.ne.b32 p, %98, 0;\nwgmma.mma_async.sync.aligned.m64n192k16.f32.bf16.bf16 {%0,%1,%2,%3,%4,%5,%6,%7,%8,%9,%10,%11,%12,%13,%14,%15,%16,%17,%18,%19,%20,%21,%22,%23,%24,%25,%26,%27,%28,%29,%30,%31,%32,%33,%34,%35,%36,%37,%38,%39,%40,%41,%42,%43,%44,%45,%46,%47,%48,%49,%50,%51,%52,%53,%54,%55,%56,%57,%58,%59,%60,%61,%62,%63,%64,%65,%66,%67,%68,%69,%70,%71,%72,%73,%74,%75,%76,%77,%78,%79,%80,%81,%82,%83,%84,%85,%86,%87,%88,%89,%90,%91,%92,%93,%94,%95}, %96, %97, p, 1, 1, 1, 1;\n}\n"
   : "+f"(d[0]),"+f"(d[1]),"+f"(d[2]),"+f"(d[3]),"+f"(d[4]),"+f"(d[5]),"+f"(d[6]),"+f"(d[7]),"+f"(d[8]),"+f"(d[9]),"+f"(d[10]),"+f"(d[11]),"+f"(d[12]),"+f"(d[13]),"+f"(d[14]),"+f"(d[15]),"+f"(d[16]),"+f"(d[17]),"+f"(d[18]),"+f"(d[19]),"+f"(d[20]),"+f"(d[21]),"+f"(d[22]),"+f"(d[23]),"+f"(d[24]),"+f"(d[25]),"+f"(d[26]),"+f"(d[27]),"+f"(d[28]),"+f"(d[29]),"+f"(d[30]),"+f"(d[31]),"+f"(d[32]),"+f"(d[33]),"+f"(d[34]),"+f"(d[35]),"+f"(d[36]),"+f"(d[37]),"+f"(d[38]),"+f"(d[39]),"+f"(d[40]),"+f"(d[41]),"+f"(d[42]),"+f"(d[43]),"+f"(d[44]),"+f"(d[45]),"+f"(d[46]),"+f"(d[47]),"+f"(d[48]),"+f"(d[49]),"+f"(d[50]),"+f"(d[51]),"+f"(d[52]),"+f"(d[53]),"+f"(d[54]),"+f"(d[55]),"+f"(d[56]),"+f"(d[57]),"+f"(d[58]),"+f"(d[59]),"+f"(d[60]),"+f"(d[61]),"+f"(d[62]),"+f"(d[63]),"+f"(d[64]),"+f"(d[65]),"+f"(d[66]),"+f"(d[67]),"+f"(d[68]),"+f"(d[69]),"+f"(d[70]),"+f"(d[71]),"+f"(d[72]),"+f"(d[73]),"+f"(d[74]),"+f"(d[75]),"+f"(d[76]),"+f"(d[77]),"+f"(d[78]),"+f"(d[79]),"+f"(d[80]),"+f"(d[81]),"+f"(d[82]),"+f"(d[83]),"+f"(d[84]),"+f"(d[85]),"+f"(d[86]),"+f"(d[87]),"+f"(d[88]),"+f"(d[89]),"+f"(d[90]),"+f"(d[91]),"+f"(d[92]),"+f"(d[93]),"+f"(d[94]),"+f"(d[95])
   : "l"(da), "l"(db), "r"(sd));
}

#define HINT_P 0
template <bool TR>
__device__ __forceinline__ void gemm_section(float* acc, float& mean0, float& mean1, float& rstd0, float& rstd1,
                                             uint32_t sb, int blk, int hg, int wg, int w, int lane) {
  constexpr int layer = TR ? 1 : 0;
  constexpr int TURN = TR ? TURN1 : TURN0;
  constexpr int LSTAT = TURN < 4 ? TURN - 1 : 3;
  const uint32_t bar = sb + SM_BAR;
  const int g = lane >> 2, t = lane & 3;
  const bool leader = (w == 0) && (lane == 0);
  const int statpos = hg < 3 ? 1 : wg ? LSTAT : 2;
  const bool copy = hg >= 3 && wg == 0;
  const int cut = wg ? TURN : 4;
  auto wait_full = [&](int c) {
    mbar_wait(bar + 8 * (B_XF + 8 * wg + c), layer);
    mbar_wait(bar + 8 * (B_WF + c), layer);
  };
  auto peek = [&](int c) {
    const bool x = mbar_test(bar + 8 * (B_XF + 8 * wg + c), layer), y = mbar_test(bar + 8 * (B_WF + c), layer);
    return x && y;
  };
  const uint64_t da0 = mkdesc(sb, TR ? 8192 : 16, 1024, 1), db0 = mkdesc(sb, 8192, 1024, 1);
  uint32_t xt = wg ? 0xfedcba98u : 0x21043210u;
  uint64_t wt = 0x0816131005161310ull;
  uint64_t da = da0 + ((xt & 15) << 9), db = db0 + (16 << 9);
  auto issue = [&](int c, int first) {
    TSG(2 * c);
    wg_fence();
#pragma unroll
    for (int ks = 0; ks < 4; ks++) wgmma_ss<192, TR ? 1 : 0, 1>(acc, da + (TR ? ks * 128 : ks * 2), db + ks * 128, !first || ks != 0);
    wg_commit();
    xt >>= 4; wt >>= 8;
    da = da0 + ((xt & 15) << 9); db = db0 + (((uint32_t)wt & 31) << 9);
    TSG(2 * c + 1);
  };
  uint32_t tag = 0;
  wait_full(0);
  bool ready = peek(1);
  issue(0, 1);
  TSW(0);
#pragma unroll 1
  for (int c = 1; c < cut; c++) {
    if (!ready) wait_full(c);
    issue(c, 0);
    ready = peek(c + 1);
    wg_wait<1>();
    if (leader) mbar_arrive(bar + 8 * (B_DN + 8 * wg + c - 1));
    if (wg == 1 && c == cut - 1) {
      wg_wait<0>();
      if (leader) mbar_arrive(bar + 8 * (B_DN + 8 + c));
    }
    if (c == statpos) {
      mbar_wait(bar + 8 * B_EP, 0);
      tag = 2 * lds32(sb + SM_EP) + layer + 1;
      mbar_wait(bar + 8 * (copy ? B_SC : B_XF + 8 * wg + hg), layer);
      uint32_t A[16];
      const uint32_t xb = sb + (copy ? P_R : 8 * wg + hg) * PG;
#pragma unroll
      for (int ks = 0; ks < 4; ks++) {
        if (!TR) {
          const int row = 16 * w + (lane & 15), kc = 2 * ks + (lane >> 4);
          ldsm4(&A[4 * ks], xb + row * 128 + ((kc ^ (row & 7)) << 4));
        } else {
          const int k = 16 * ks + (lane & 7) + 8 * (lane >> 4), pc = 2 * w + ((lane >> 3) & 1);
          ldsm4t(&A[4 * ks], xb + k * 128 + ((pc ^ (k & 7)) << 4));
        }
      }
      float s0 = 0.f, q0 = 0.f, s1 = 0.f, q1 = 0.f;
#pragma unroll
      for (int i = 0; i < 16; i += 2) {
        const float a = bf_lo(A[i]), b = bf_hi(A[i]), c_ = bf_lo(A[i + 1]), d = bf_hi(A[i + 1]);
        s0 += a + b; q0 = fmaf(a, a, q0); q0 = fmaf(b, b, q0);
        s1 += c_ + d; q1 = fmaf(c_, c_, q1); q1 = fmaf(d, d, q1);
      }
#pragma unroll
      for (int o = 1; o <= 2; o <<= 1) {
        s0 += __shfl_xor_sync(~0u, s0, o); q0 += __shfl_xor_sync(~0u, q0, o);
        s1 += __shfl_xor_sync(~0u, s1, o); q1 += __shfl_xor_sync(~0u, q1, o);
      }
      if (t < 2)
        st_tagged(&g_part[((layer * 32 + blk) * 8 + hg) * 64 + 16 * w + g + 8 * t], __float_as_uint(t ? s1 : s0), __float_as_uint(t ? q1 : q0), tag);
    }
  }
  if (wg == 1) mbar_wait(bar + 8 * (B_DN + GPOS), layer);
  else if (!ready) { wait_full(cut); ready = true; }
  const uint4* psrc = &g_part[((layer * 32 + blk) * 8 + 2 * t) * 64 + 16 * w + g];
  uint4 a0 = ld_tagged(psrc), a1 = ld_tagged(psrc + 8), b0 = ld_tagged(psrc + 64), b1 = ld_tagged(psrc + 72);
  if (wg == 1) {
#pragma unroll 1
    for (int c = cut; c < 8; c++) wait_full(c);
    ready = true;
    bar_sync(5, 256);
  }
#pragma unroll 1
  for (int c = cut; c < 8; c++) {
    if (!ready) wait_full(c);
    issue(c, 0);
    if (wg == 1) {
      wg_wait<2>();
      if (leader && c >= cut + 2) mbar_arrive(bar + 8 * (B_DN + 8 + c - 2));
    } else if (c == 7) {
      bar_arrive(5, 256);
    } else {
      ready = peek(c + 1);
      wg_wait<1>();
      if (leader) mbar_arrive(bar + 8 * (B_DN + c - 1));
    }
  }
  int it = 0;
  while (!__all_sync(~0u, a0.y == tag && a0.w == tag && a1.y == tag && a1.w == tag && b0.y == tag && b0.w == tag && b1.y == tag && b1.w == tag) &&
         ++it < (1 << 20)) {
    a0 = ld_tagged(psrc); a1 = ld_tagged(psrc + 8); b0 = ld_tagged(psrc + 64); b1 = ld_tagged(psrc + 72);
  }
  float s0 = __uint_as_float(a0.x) + __uint_as_float(b0.x), q0 = __uint_as_float(a0.z) + __uint_as_float(b0.z);
  float s1 = __uint_as_float(a1.x) + __uint_as_float(b1.x), q1 = __uint_as_float(a1.z) + __uint_as_float(b1.z);
#pragma unroll
  for (int o = 1; o <= 2; o <<= 1) {
    s0 += __shfl_xor_sync(~0u, s0, o); q0 += __shfl_xor_sync(~0u, q0, o);
    s1 += __shfl_xor_sync(~0u, s1, o); q1 += __shfl_xor_sync(~0u, q1, o);
  }
  mean0 = s0 * (1.f / DM); mean1 = s1 * (1.f / DM);
  rstd0 = rsqrt_approx(fmaxf(q0 * (1.f / DM) - mean0 * mean0, 0.f) + 1e-5f);
  rstd1 = rsqrt_approx(fmaxf(q1 * (1.f / DM) - mean1 * mean1, 0.f) + 1e-5f);
  TSG(16);
  mbar_wait(bar + 8 * B_CSF, 0);
  wg_wait<0>();
  acc_fence<96>(acc);
  if (leader) mbar_arrive(bar + 8 * (B_DN + 8 * wg + 7));
}

__device__ __forceinline__ void attn_phase(const Params& p, uint32_t sb, int layer, int rb, int hg, int wg, int w) {
  const int lane = opaque_tid() & 31;
  const int g = lane >> 2, t = lane & 3;
  const uint32_t bar = sb + SM_BAR;
  const int blk = 16 * wg + rb;
  float acc[96];
  float2 cs[24];
  float mean0, mean1, rstd0, rstd1;
  if (layer) gemm_section<true>(acc, mean0, mean1, rstd0, rstd1, sb, blk, hg, wg, w, lane);
  else gemm_section<false>(acc, mean0, mean1, rstd0, rstd1, sb, blk, hg, wg, w, lane);
  TSW(1);
#pragma unroll
  for (int j = 8; j < 24; j++) cs[j] = lds64f(sb + SM_CS + 4 * (8 * j + 2 * t));
  const uint32_t kvx = sb + (wg ? 22 : 0) * PG;

  uint32_t kb[4][8], vb[4][8], qa[4][4];
  {
    const float nm0 = -mean0 * rstd0, nm1 = -mean1 * rstd1;
    const int st_row = 16 * w + (lane & 7) + 8 * ((lane >> 3) & 1);
    const uint32_t st_base = kvx + st_row * 256;
    const bool sender = (w == 3 && blk < 31);
    uint4* halo = &g_halo[((layer * 32 + blk) * 8 + hg) * 256 + lane];
    uint32_t r[4][2][4];
#pragma unroll
    for (int h = 0; h < 4; h++) {
#pragma unroll
      for (int kv = 0; kv < 2; kv++) {
#pragma unroll
        for (int dh = 0; dh < 2; dh++) {
          const int j = 8 + kv * 8 + 2 * h + dh;
          const float2 c2 = cs[j];
          const float v0 = fmaf(acc[4 * j + 0], rstd0, nm0 * c2.x), v1 = fmaf(acc[4 * j + 1], rstd0, nm0 * c2.y);
          const float v2 = fmaf(acc[4 * j + 2], rstd1, nm1 * c2.x), v3 = fmaf(acc[4 * j + 3], rstd1, nm1 * c2.y);
          r[h][kv][2 * dh] = packbf(v0, v1);
          r[h][kv][2 * dh + 1] = packbf(v2, v3);
        }
      }
      if (sender) {
        stg128(halo + (2 * h) * 32, make_uint4(r[h][0][0], r[h][0][2], r[h][0][1], r[h][0][3]));
        stg128(halo + (2 * h + 1) * 32, make_uint4(r[h][1][0], r[h][1][1], r[h][1][2], r[h][1][3]));
      }
    }
#pragma unroll
    for (int j = 0; j < 8; j++) cs[j] = lds64f(sb + SM_CS + 4 * (8 * j + 2 * t));
    mbar_wait(bar + 8 * (B_DN + 7), layer);
#pragma unroll
    for (int h = 0; h < 4; h++) {
#pragma unroll
      for (int kv = 0; kv < 2; kv++) {
        const int chunk = 4 * h + 2 * kv + (lane >> 4);
        stsm4(st_base + (((chunk & 8) | ((chunk ^ st_row) & 7)) << 4), r[h][kv][0], r[h][kv][1], r[h][kv][2], r[h][kv][3]);
      }
      kb[h][4] = r[h][0][0]; kb[h][5] = r[h][0][2]; kb[h][6] = r[h][0][1]; kb[h][7] = r[h][0][3];
      vb[h][4] = movm_t(r[h][1][0]); vb[h][5] = movm_t(r[h][1][1]); vb[h][6] = movm_t(r[h][1][2]); vb[h][7] = movm_t(r[h][1][3]);
    }
#pragma unroll
    for (int h = 0; h < 4; h++) {
#pragma unroll
      for (int dh = 0; dh < 2; dh++) {
        const int j = 2 * h + dh;
        const float2 c2 = cs[j];
        qa[h][2 * dh] = packbf(fmaf(-mean0, c2.x, acc[4 * j + 0]), fmaf(-mean0, c2.y, acc[4 * j + 1]));
        qa[h][2 * dh + 1] = packbf(fmaf(-mean1, c2.x, acc[4 * j + 2]), fmaf(-mean1, c2.y, acc[4 * j + 3]));
      }
    }
  }
  bar_sync(2 + wg, 128);
  TSW(2);
  {
    const uint32_t prev_base = kvx + (16 * w - 16) * 256;
    const int mi = lane >> 3;
    const int r = 8 * (mi >> 1) + (lane & 7), r2 = 8 * (mi & 1) + (lane & 7);
    if (w != 0) {
#pragma unroll
      for (int h = 0; h < 4; h++) {
        const int ch = 4 * h + (mi & 1), ch2 = 4 * h + 2 + (mi >> 1);
        ldsm4(&kb[h][0], prev_base + r * 256 + (((ch & 8) | ((ch ^ r) & 7)) << 4));
        ldsm4t(&vb[h][0], prev_base + r2 * 256 + (((ch2 & 8) | ((ch2 ^ r2) & 7)) << 4));
      }
    } else if (blk > 0) {
      const uint4* src = &g_halo[((layer * 32 + blk - 1) * 8 + hg) * 256 + lane];
      uint4 hv[8];
      int it = 0;
      bool ok;
      do {
        ok = true;
#pragma unroll
        for (int i = 0; i < 8; i++) hv[i] = ld_tagged(src + i * 32);
#pragma unroll
        for (int i = 0; i < 8; i++) ok = ok && hv[i].x != UNSET;
      } while (!__all_sync(~0u, ok) && ++it < (1 << 20));
#pragma unroll
      for (int h = 0; h < 4; h++) {
        kb[h][0] = hv[2 * h].x; kb[h][1] = hv[2 * h].y; kb[h][2] = hv[2 * h].z; kb[h][3] = hv[2 * h].w;
        vb[h][0] = movm_t(hv[2 * h + 1].x); vb[h][1] = movm_t(hv[2 * h + 1].y);
        vb[h][2] = movm_t(hv[2 * h + 1].z); vb[h][3] = movm_t(hv[2 * h + 1].w);
      }
    } else {
#pragma unroll
      for (int h = 0; h < 4; h++)
#pragma unroll
        for (int k = 0; k < 4; k++) kb[h][k] = vb[h][k] = 0u;
    }
    TSW(3);
  }
  mbar_wait(bar + 8 * (B_DN + 15), layer);
  TSW(4);

  const bool first = (blk == 0 && w == 0);
  const int e = t - (g >> 1);
  const bool par = g & 1, epos = e >= 1;
  const uint32_t pmask = par ? 0xffff0000u : 0x0000ffffu;
  const uint32_t mB0 = epos ? pmask : 0u, mB1 = epos ? 0u : pmask;
  const float cl2 = 0.25f * 1.4426950408889634f;
  const float sc0 = rstd0 * cl2, sc1 = rstd1 * cl2;
  const float NEG = -INFINITY;
  float vA0[4], vB0[4], vA1[4], vB1[4];
#pragma unroll
  for (int h = 0; h < 4; h++) {
    float S[4][4];
#pragma unroll
    for (int j = 0; j < 4; j++) {
      S[j][0] = S[j][1] = S[j][2] = S[j][3] = 0.f;
      mma_bf16(S[j], qa[h], kb[h][2 * j], kb[h][2 * j + 1]);
    }
    vA0[h] = par ? S[1][1] : S[1][0];
    vB0[h] = epos ? (par ? S[0][1] : S[0][0]) : (par ? S[2][1] : S[2][0]);
    vA1[h] = par ? S[2][3] : S[2][2];
    vB1[h] = epos ? (par ? S[1][3] : S[1][2]) : (par ? S[3][3] : S[3][2]);
    if (first) { vA0[h] = NEG; if (epos) { vB0[h] = NEG; vB1[h] = NEG; } }
  }
  float m0[4], m1[4];
#pragma unroll
  for (int h = 0; h < 4; h++) { m0[h] = fmaxf(vA0[h], vB0[h]); m1[h] = fmaxf(vA1[h], vB1[h]); }
#pragma unroll
  for (int o = 1; o <= 2; o <<= 1) {
#pragma unroll
    for (int h = 0; h < 4; h++) {
      m0[h] = fmaxf(m0[h], __shfl_xor_sync(~0u, m0[h], o));
      m1[h] = fmaxf(m1[h], __shfl_xor_sync(~0u, m1[h], o));
    }
  }
  float O0[4][4], O1[4][4], Z[4][4];
#pragma unroll
  for (int h = 0; h < 4; h++) {
    const float mm0 = -m0[h] * sc0, mm1 = -m1[h] * sc1;
    const float pA0 = ex2(fmaf(vA0[h], sc0, mm0)), pB0 = ex2(fmaf(vB0[h], sc0, mm0));
    const float pA1 = ex2(fmaf(vA1[h], sc1, mm1)), pB1 = ex2(fmaf(vB1[h], sc1, mm1));
    const uint32_t hA0 = packbf(pA0, pA0), hB0 = packbf(pB0, pB0), hA1 = packbf(pA1, pA1), hB1 = packbf(pB1, pB1);
    const uint32_t P0[4] = {hB0 & mB0, 0u, hA0 & pmask, hB1 & mB0};
    const uint32_t P1[4] = {hB0 & mB1, hA1 & pmask, 0u, hB1 & mB1};
#pragma unroll
    for (int k = 0; k < 4; k++) O0[h][k] = O1[h][k] = Z[h][k] = 0.f;
    mma_bf16(O0[h], P0, vb[h][0], vb[h][1]); mma_bf16(O1[h], P0, vb[h][2], vb[h][3]); mma_bf16(Z[h], P0, 0x3f803f80u, 0x3f803f80u);
    mma_bf16(O0[h], P1, vb[h][4], vb[h][5]); mma_bf16(O1[h], P1, vb[h][6], vb[h][7]); mma_bf16(Z[h], P1, 0x3f803f80u, 0x3f803f80u);
  }
  if (lane == 0) mbar_arrive(bar + 8 * (B_OST + wg));
  bf16* op = g_O + ((layer * 32 + blk) * 64 + 16 * w + g) * DM + hg * 64 + 8 * t;
#pragma unroll
  for (int h = 0; h < 4; h += 2) {
    const float i0 = rcp_approx(Z[h][0]), i1 = rcp_approx(Z[h][2]), j0 = rcp_approx(Z[h + 1][0]), j1 = rcp_approx(Z[h + 1][2]);
    stg128(op + 16 * h, make_uint4(packbf(O0[h][0] * i0, O0[h][1] * i0), packbf(O1[h][0] * i0, O1[h][1] * i0),
                                   packbf(O0[h + 1][0] * j0, O0[h + 1][1] * j0), packbf(O1[h + 1][0] * j0, O1[h + 1][1] * j0)));
    stg128(op + 8 * DM + 16 * h, make_uint4(packbf(O0[h][2] * i1, O0[h][3] * i1), packbf(O1[h][2] * i1, O1[h][3] * i1),
                                            packbf(O0[h + 1][2] * j1, O0[h + 1][3] * j1), packbf(O1[h + 1][2] * j1, O1[h + 1][3] * j1)));
  }
  TSW(5);
  __syncwarp();
  if (lane == 0) red_relaxed(&g_cnt[(C_O + layer * 32 + blk) * 32]);
  TSW(6);
}

__device__ __forceinline__ void proj_phase(const Params& p, uint32_t sb, int layer, int rb, int q, int wg, int w, int& rtp) {
  const int lane = opaque_tid() & 31;
  const bool TR = layer != 0;
  const int t = lane & 3;
  const uint32_t bar = sb + SM_BAR;
  const uint32_t rbx = sb + (P_R + wg) * PG;
  const int blk = 16 * wg + rb;
  uint32_t res[16];
  mbar_wait(bar + 8 * (B_RF + wg), layer);
  if (!TR) {
#pragma unroll
    for (int j = 0; j < 8; j += 2) {
      const int mi = lane >> 3;
      const int row = 16 * w + (lane & 7) + 8 * (mi & 1), ch = j + (mi >> 1);
      ldsm4(&res[2 * j], rbx + row * 128 + ((ch ^ (row & 7)) << 4));
    }
  } else {
#pragma unroll
    for (int j = 0; j < 8; j += 2) {
      const int mi = lane >> 3;
      const int line = 8 * (j + (mi >> 1)) + (lane & 7), pc = 2 * w + (mi & 1);
      ldsm4t(&res[2 * j], rbx + line * 128 + ((pc ^ (line & 7)) << 4));
    }
  }
  mbar_wait(bar + 8 * B_KG, 0);
  fence_async_global();
  const uint32_t stg = sb + SM_STG + wg * 768;
#pragma unroll 1
  for (int attempt = 0; attempt < MAX_RETRY; attempt++) {
  float acc[32];
#pragma unroll
  for (int j = 0; j < 16; j++) { acc[2 * j] = bf_lo(res[j]); acc[2 * j + 1] = bf_hi(res[j]); }
  acc_fence<32>(acc);
#pragma unroll
  for (int c = 0; c < 4; c++) {
    mbar_wait(bar + 8 * (B_WOF + c), layer);
    mbar_wait(bar + 8 * (B_OF + 4 * wg + c), layer);
    if (c == 0) TSW(7);
    const uint64_t da = mkdesc(sb + o_page(wg, c) * PG, 16, 1024, 1);
    wg_fence();
#pragma unroll
    for (int ks = 0; ks < 8; ks++)
      wgmma_ss<64, 0, 1>(acc, da + (ks >> 2) * 512 + (ks & 3) * 2, mkdesc(sb + wo_page(2 * c + (ks >> 2)) * PG, 8192, 1024, 1) + (ks & 3) * 128, 1);
    wg_commit();
  }
  wg_wait<0>();
  acc_fence<32>(acc);
  TSW(8);
  float s0 = 0.f, q0 = 0.f, s1 = 0.f, q1 = 0.f;
  uint32_t o[16];
#pragma unroll
  for (int j = 0; j < 8; j++) {
    const float a = acc[4 * j], b = acc[4 * j + 1], c = acc[4 * j + 2], d = acc[4 * j + 3];
    o[2 * j] = packbf(a, b);
    o[2 * j + 1] = packbf(c, d);
    s0 += a + b; q0 = fmaf(a, a, q0); q0 = fmaf(b, b, q0);
    s1 += c + d; q1 = fmaf(c, c, q1); q1 = fmaf(d, d, q1);
  }
#pragma unroll
  for (int j = 0; j < 8; j += 2) {
    const int mi = lane >> 3;
    const int line = 8 * (j + (mi >> 1)) + (lane & 7), pc = 2 * w + (mi & 1);
    stsm4t(rbx + line * 128 + ((pc ^ (line & 7)) << 4), o[2 * j], o[2 * j + 1], o[2 * j + 2], o[2 * j + 3]);
  }
#pragma unroll
  for (int o2 = 1; o2 <= 2; o2 <<= 1) {
    s0 += __shfl_xor_sync(~0u, s0, o2); q0 += __shfl_xor_sync(~0u, q0, o2);
    s1 += __shfl_xor_sync(~0u, s1, o2); q1 += __shfl_xor_sync(~0u, q1, o2);
  }
  {
    const int i = 2 * (lane >> 2) + (t & 1), k = (i * 11) >> 5;
    const float v = (t == 0) ? s0 : (t == 1) ? q0 : (t == 2) ? s1 : q1;
    sts32f(stg + k * 128 + (2 * w + (t >> 1)) * 16 + (i - 3 * k) * 4, v);
  }
  TSW(9);
  fence_async_smem();
  const float chk = s0 + s1;
  if (!bar_or(2 + wg, 128, chk != chk)) break;
  bool unset = false;
#pragma unroll 4
  for (int i = 0; i < 32; i++) unset |= lds32(sb + o_page(wg, i >> 3) * PG + ((i & 7) * 128 + 32 * w + lane) * 16 + (lane >> 3) * 4) == UNSET;
  if (!bar_or(2 + wg, 128, unset)) break;
  if (w == 0 && elect_one()) {
    fence_async_smem();
    mbar_expect(bar + 8 * (B_RT + wg), 8 * PG);
#pragma unroll 1
    for (int c = 0; c < 4; c++) tma_ld3(sb + o_page(wg, c) * PG, &p.mapO2, 0, (layer * 32 + blk) * 64, 2 * c, bar + 8 * (B_RT + wg));
  }
  mbar_wait(bar + 8 * (B_RT + wg), rtp);
  rtp ^= 1;
  RETRY(0);
  }
  if (w == 0 && elect_one()) {
    tma_st(&p.mapXT, blk * 64, (2 * layer) * DM + q * 64, rbx);
    bulk_red_add_f32(g_stats + (layer * 32 + blk) * 192, stg, 768);
    bulk_commit();
    mbar_arrive(bar + 8 * (B_PDONE + wg));
    red_relaxed(&g_cnt[(C_G + 2 * layer + wg) * 32]);
    bulk_wait_read();
    mbar_arrive(bar + 8 * (B_PST + wg));
    TSW(10);
  }
}

__device__ __forceinline__ void conv_load(uint32_t* A, uint32_t pe) {
#pragma unroll
  for (int m = 0; m < 17; m++) {
    A[4 * m + 2] = lds32(pe + 4 * (64 * m - 8));
    A[4 * m + 0] = lds32(pe + 4 * (64 * m));
    A[4 * m + 1] = lds32(pe + 4 * (64 * m + 8));
    asm volatile("mov.b32 %0, %1;" : "=r"(A[4 * m + 3]) : "r"(A[4 * m + 0]));
  }
}
template <int M> __device__ __forceinline__ void conv_tri(float* acc, const uint32_t* A, uint64_t d) {
  if constexpr (M < 16) {
    wgmma_rs<64 - 8 * (M / 2), 0>(acc, A + 4 * M, d + (uint64_t)(64 + 4 * M), M != 0);
    conv_tri<M + 1>(acc, A, d);
  }
}
__device__ __forceinline__ void conv_mma0(float* acc, const uint32_t* A, uint64_t d) {
  wg_fence();
  conv_tri<0>(acc, A, d);
  wg_commit();
}
__device__ __forceinline__ void conv_mma1(float* acc, const uint32_t* A, uint64_t d) {
  wg_fence();
#pragma unroll
  for (int m = 0; m < 17; m++) wgmma_rs<64, 0>(acc, A + 4 * m, d + (uint64_t)(4 * m), m != 0);
  wg_commit();
}
__device__ __forceinline__ void conv_store(float* acc, uint32_t pb, uint32_t over, int w) {
  acc_fence<32>(acc);
  const int l = opaque_tid() & 31, mt = l >> 3;
  int c = 2 * (63 - 8 * (mt >> 1) - (l & 7) + w) + (mt & 1);
  c ^= (c >> 3) & 1;
  const uint32_t a0 = pb + c * 16;
#pragma unroll
  for (int j = 0; j < 8; j += 2)
    stsm4t(j == 0 ? (c < 128 ? a0 : over + (c - 128) * 16) : a0 - 256 * j, packbf(acc[4 * j], acc[4 * j + 1]), packbf(acc[4 * j + 2], acc[4 * j + 3]),
           packbf(acc[4 * j + 4], acc[4 * j + 5]), packbf(acc[4 * j + 6], acc[4 * j + 7]));
}
__device__ __forceinline__ void conv_far(uint32_t sb, int ht) {
  const int w = ht >> 5, l = ht & 31;
  float F[4][8];
  const uint64_t da = mkdesc(sb + cv_fa(0), 128, 128, 0), ds = mkdesc(sb + cv_se(0), 256, 256, 3);
  wg_fence();
#pragma unroll
  for (int k = 0; k < 8; k++)
#pragma unroll
    for (int c = 0; c < 4; c++) wgmma_ss<16, 0, 1>(F[c], da + c * 1024 + (k >> 2) * 128 + (k & 3) * 16, ds + c * 256 + 32 * k, k != 0);
  wg_commit();
  const uint32_t pf = sb + cv_pf(0) + (16 * w + (l & 15)) * 32 + (l >> 4) * 16;
  wg_wait<0>();
#pragma unroll
  for (int c = 0; c < 4; c++) {
    acc_fence<8>(F[c]);
    stsm4(pf + c * 2048, packbf(F[c][0], F[c][1]), packbf(F[c][2], F[c][3]), packbf(F[c][4], F[c][5]), packbf(F[c][6], F[c][7]));
  }
}
__device__ __forceinline__ void conv_sums(uint32_t sb, int lc, int ht) {
  const int m = ht - 1;
  uint4 v[2][3];
#pragma unroll
  for (int c = 0; c < 2; c++)
#pragma unroll
    for (int k = 0; k < 3; k++) {
      const int mm = m - 1 + k;
      v[c][k] = lds128(sb + cv_u(lc + c) + (mm >= 0 ? (mm & 1) * CV_UH + (127 - (mm >> 1)) * 16 : 128 * 16));
    }
  const int ce = m + 2, co = m + 1;
#pragma unroll
  for (int c = 0; c < 2; c++) {
    const uint32_t x[8] = {v[c][0].z, v[c][0].w, v[c][1].x, v[c][1].y, v[c][1].z, v[c][1].w, v[c][2].x, v[c][2].y};
    float pv[16];
#pragma unroll
    for (int k = 0; k < 8; k++) { pv[2 * k] = bf_lo(x[k]); pv[2 * k + 1] = bf_hi(x[k]); }
    float t2[15], t4[13], s9[8], s7[8];
#pragma unroll
    for (int i = 0; i < 15; i++) t2[i] = pv[i] + pv[i + 1];
#pragma unroll
    for (int i = 0; i < 13; i++) t4[i] = t2[i] + t2[i + 2];
#pragma unroll
    for (int i = 0; i < 8; i++) {
      s9[i] = (t4[i] + t4[i + 4]) + pv[i + 8];
      s7[i] = (t4[i + 1] + t2[i + 5]) + pv[i + 7];
    }
    const uint4 e4 = make_uint4(packbf(s9[0], s9[1]), packbf(s9[2], s9[3]), packbf(s9[4], s9[5]), packbf(s9[6], s9[7]));
    if (ce < 128) sts128(sb + cv_se(lc + c) + (63 - (ce >> 1)) * 32 + (((ce & 1) ^ ((ce >> 3) & 1) ^ 1) << 4), e4);
    else sts128(sb + cv_se(lc + c) + 63 * 32 + 16, make_uint4(0, 0, 0, 0));
    sts128(sb + cv_so(lc + c) + (63 - (co >> 1)) * 32 + (((co & 1) ^ ((co >> 3) & 1) ^ 1) << 4),
           make_uint4(packbf(s7[0], s7[1]), packbf(s7[2], s7[3]), packbf(s7[4], s7[5]), packbf(s7[6], s7[7])));
  }
}

template <int HALF, int NCH, int STEP = 1>
__device__ __forceinline__ void conv_epi(uint32_t sb, bf16* out, int lc, int c) {
  uint4 v[NCH][4], xr[NCH], f[NCH];
  const uint32_t sw = (c ^ ((c >> 3) & 1)) * 16;
#pragma unroll
  for (int u = 0; u < NCH; u++) {
#pragma unroll
    for (int k = 0; k < 4; k++) v[u][k] = lds128(sb + (HALF ? cv_pb1(lc + STEP * u, k) : cv_pb0(lc + STEP * u, k)) + sw);
    xr[u] = lds128(sb + cv_x(HALF, lc + STEP * u) + c * 16);
    if (HALF) f[u] = lds128(sb + cv_pf(lc + STEP * u) + c * 16);
  }
#pragma unroll
  for (int u = 0; u < NCH; u++) {
    if (HALF) { v[u][0].x = hadd2(v[u][0].x, f[u].x); v[u][0].y = hadd2(v[u][0].y, f[u].y); v[u][0].z = hadd2(v[u][0].z, f[u].z); v[u][0].w = hadd2(v[u][0].w, f[u].w); }
    uint4 o;
    o.x = hadd2(xr[u].x, hadd2(hadd2(v[u][0].x, v[u][1].x), hadd2(v[u][2].x, v[u][3].x)));
    o.y = hadd2(xr[u].y, hadd2(hadd2(v[u][0].y, v[u][1].y), hadd2(v[u][2].y, v[u][3].y)));
    o.z = hadd2(xr[u].z, hadd2(hadd2(v[u][0].z, v[u][1].z), hadd2(v[u][2].z, v[u][3].z)));
    o.w = hadd2(xr[u].w, hadd2(hadd2(v[u][0].w, v[u][1].w), hadd2(v[u][2].w, v[u][3].w)));
    stg128(out + cv_chan(0, lc + STEP * u) * LSEQ + HALF * 1024 + c * 8, o);
  }
}

__device__ __forceinline__ bool prep_valid(const uint4 (&st)[6], const uint4 (&xr)[4]) {
  const uint32_t n = __float_as_uint(8.f);
  return st[0].w == n && st[1].w == n && st[2].w == n && st[3].w == n && st[4].w == n && (st[5].w | st[5].y | st[5].z) == n &&
         xr[0].x != UNSET && xr[1].x != UNSET && xr[2].x != UNSET && xr[3].x != UNSET;
}
template <int HALF>
__device__ __forceinline__ void conv_prep(uint32_t sb, int layer, int cta, int i) {
  uint4 st[6], xr[4];
  bool ok = false;
  if (HALF) {
#pragma unroll
    for (int k = 0; k < 6; k++) st[k] = lds128(sb + cv_pe(i >> 5) + ((i >> 3) & 3) * 768 + k * 128 + (i & 7) * 16);
#pragma unroll
    for (int k = 0; k < 4; k++) xr[k] = lds128(sb + cv_x(1, k) + i * 16);
    ok = __all_sync(~0u, prep_valid(st, xr));
  }
  if (!ok) {
    const uint4* sp = (const uint4*)g_stats + (layer * 32 + HALF * 16 + (i >> 3)) * 48 + (i & 7);
    const uint4* xp = (const uint4*)g_xT + (2 * layer * DM + 2 * cta) * (LSEQ / 8) + HALF * 128 + i;
    int it = 0;
    do {
#pragma unroll
      for (int k = 0; k < 6; k++) st[k] = ld_tagged(sp + 8 * k);
#pragma unroll
      for (int k = 0; k < 4; k++) xr[k] = ld_tagged(xp + cv_chan(0, k) * (LSEQ / 8));
      if (HALF || it) RETRY(1);
    } while (!__all_sync(~0u, prep_valid(st, xr)) && ++it < MAX_RETRY);
#pragma unroll
    for (int k = 0; k < 4; k++) sts128(sb + cv_x(HALF, k) + i * 16, xr[k]);
  }
  const uint32_t v[16] = {st[0].x, st[0].y, st[0].z, st[1].x, st[1].y, st[1].z, st[2].x, st[2].y, st[2].z, st[3].x, st[3].y, st[3].z, st[4].x, st[4].y, st[4].z, st[5].x};
  uint32_t rs[4], nm[4];
#pragma unroll
  for (int k = 0; k < 4; k++) {
    const float m0 = __uint_as_float(v[4 * k]) * (-1.f / DM), m1 = __uint_as_float(v[4 * k + 2]) * (-1.f / DM);
    const float r0 = rsqrt_approx(fmaxf(fmaf(__uint_as_float(v[4 * k + 1]), 1.f / DM, -m0 * m0), 0.f) + 1e-5f);
    const float r1 = rsqrt_approx(fmaxf(fmaf(__uint_as_float(v[4 * k + 3]), 1.f / DM, -m1 * m1), 0.f) + 1e-5f);
    rs[k] = packbf(r0, r1);
    nm[k] = packbf(m0 * bf_lo(rs[k]), m1 * bf_hi(rs[k]));
  }
  const uint32_t ud = sb + (i & 1) * CV_UH + (127 - 64 * HALF - (i >> 1)) * 16;
#pragma unroll
  for (int k = 0; k < 4; k++)
    sts128(ud + cv_u(k), make_uint4(hfma2(xr[k].x, rs[0], nm[0]), hfma2(xr[k].y, rs[1], nm[1]), hfma2(xr[k].z, rs[2], nm[2]), hfma2(xr[k].w, rs[3], nm[3])));
  fence_async_smem();
}

#define PP0 1
__device__ __forceinline__ void conv_phase(const Params& p, uint32_t sb, int layer, int cta) {
  const int tid = opaque_tid();
  const int wg = __shfl_sync(~0u, tid >> 7, 0), w = __shfl_sync(~0u, (tid >> 5) & 3, 0);
  const uint32_t bar = sb + SM_BAR;
  constexpr int CH2 = 4 * PG;
  bf16* xout = g_xT + ((2 * layer + 1) * DM + 2 * cta) * LSEQ;
  uint32_t A0[68], A1[68];
  float acc[32];
  {
    const int l1 = tid & 31;
    const uint32_t pe = sb + cv_pe(wg) + 4 * (16 + 16 * w + (l1 >> 2) - 2 * (l1 & 3));
    mbar_wait(bar + 8 * B_PE, layer);
    conv_load(A0, pe);
    conv_load(A1, pe + CH2);
    __syncwarp();
    if (l1 == 0) mbar_arrive(bar + 8 * B_AL);
  }
  TSW(19);
  if (wg == 0) {
    const int i = opaque_tid();
    if (i < 32) sts128(sb + cv_u(i >> 3) + ((i >> 2) & 1) * CV_UH + (128 + (i & 3)) * 16, make_uint4(0, 0, 0, 0));
    mbar_wait(bar + 8 * B_GB, layer);
    TSW(11);
    conv_prep<0>(sb, layer, cta, i);
    mbar_arrive(bar + 8 * B_U);
  }
  const uint64_t d0 = mkdesc(sb + cv_u(wg), CV_UH, 128, 0), d1 = d0 + (CH2 >> 4);
  mbar_wait(bar + 8 * B_U, layer);
  TSW(12);
  if (wg == 1) bar_sync(5, 256);
  conv_mma0(acc, A0, d0);
  if (wg == 0) bar_arrive(5, 256);
  mbar_wait(bar + 8 * (B_PDONE + 1), layer);
  {
    const int l = opaque_tid() & 31;
    if ((l & 15) < 2 * w) sts128(sb + cv_pb0(wg + 2 * (l >> 4), w) + (l & 15) * 16, make_uint4(0, 0, 0, 0));
  }
  wg_wait<0>();
  conv_store(acc, sb + cv_pb0(wg, w), sb + cv_pb1(wg, w), w);
  conv_mma0(acc, A1, d1);
  bar_sync(2 + wg, 128);
  conv_epi<0, 1>(sb, xout, wg, opaque_tid() & 127);
  wg_wait<0>();
  conv_store(acc, sb + cv_pb0(2 + wg, w), sb + cv_pb1(2 + wg, w), w);
  TSW(13);
  bar_sync(2 + wg, 128);
  conv_epi<0, 1>(sb, xout, 2 + wg, opaque_tid() & 127);
  mbar_arrive(bar + 8 * B_PUB);
  TSW(14);
  mbar_wait(bar + 8 * (B_GB + 1), layer);
  if (wg == 0) {
    conv_prep<1>(sb, layer, cta, opaque_tid());
    bar_sync(2, 128);
  } else {
    bar_sync(6, 256);
  }
  TSW(15);
  conv_mma1(acc, A0, d0);
  if (wg == 0) bar_arrive(6, 256);
  mbar_wait(bar + 8 * B_FARM, layer);
  wg_wait<0>();
  conv_store(acc, sb + cv_pb1(wg, w), sb + cv_dump(wg), w);
  mbar_arrive(bar + 8 * (B_R + 1));
  TSW(16);
  conv_mma1(acc, A1, d1);
  wg_wait<0>();
  conv_store(acc, sb + cv_pb1(2 + wg, w), sb + cv_dump(2 + wg), w);
  TSW(17);
  if (wg == 0) {
    mbar_arrive(bar + 8 * (B_R + 2));
  } else {
    bar_sync(3, 128);
    conv_epi<1, 1>(sb, xout, 3, opaque_tid() & 127);
    mbar_arrive(bar + 8 * (B_PUB + 2));
    TSW(18);
  }
}

__device__ __forceinline__ void final_phase(const Params& p, uint32_t sb, int cta, int wg, int w, int rtp) {
  const int lane = opaque_tid() & 31;
  const uint32_t bar = sb + SM_BAR;
  mbar_wait(bar + 8 * (B_TF + wg), 0);
  if (threadIdx.x == 128) TS(8);
  const uint32_t src = sb + (16 + wg) * PG, dst = src + 2 * PG;
  const int mi = lane >> 3;
#pragma unroll 1
  for (int attempt = 0; attempt < MAX_RETRY; attempt++) {
    uint32_t m = 0;
#pragma unroll
    for (int j = 0; j < 8; j += 2) {
      uint32_t r[4];
      const int line = 8 * (j + (mi >> 1)) + (lane & 7), pc = 2 * w + (mi & 1);
      ldsm4t(r, src + line * 128 + ((pc ^ (line & 7)) << 4));
      const int row = 16 * w + (lane & 7) + 8 * (mi & 1), ch = j + (mi >> 1);
      stsm4(dst + row * 128 + ((ch ^ (row & 7)) << 4), r[0], r[1], r[2], r[3]);
#pragma unroll
      for (int k = 0; k < 4; k++) asm("max.u16x2 %0, %0, %1;" : "+r"(m) : "r"(r[k]));
    }
    fence_async_smem();
    if (!bar_or(2 + wg, 128, m >= 0xffff0000u || (m & 0xffffu) == 0xffffu)) break;
    if (w == 0 && elect_one()) {
      mbar_expect(bar + 8 * (B_RT + wg), PG);
      tma_ld(src, &p.mapXT, (16 * wg + (cta & 15)) * 64, 3 * DM + (cta >> 4) * 64, bar + 8 * (B_RT + wg));
    }
    mbar_wait(bar + 8 * (B_RT + wg), (rtp + attempt) & 1);
    RETRY(2);
  }
  if (w == 0 && elect_one()) {
    tma_st(&p.mapOut, (cta >> 4) * 64, (16 * wg + (cta & 15)) * 64, dst);
    bulk_commit();
    asm volatile("cp.async.bulk.wait_group.read 0;" ::: "memory");
    if (threadIdx.x == 128) TS(9);
    if (threadIdx.x == 128) LTS(1);
  }
}

struct cplx { float r, i; };
__device__ __forceinline__ cplx cmul(cplx a, cplx b) { return {fmaf(a.r, b.r, -a.i * b.i), fmaf(a.r, b.i, a.i * b.r)}; }
__device__ __forceinline__ cplx csqr(cplx a) { return {fmaf(a.r, a.r, -a.i * a.i), (a.r + a.r) * a.i}; }
__device__ __forceinline__ cplx cexp_l(float ar2, float ai, float l) {
  const float m = ex2(ar2 * l);
  const float x = ai * l;
  return {m * __cosf(x), m * __sinf(x)};
}

__device__ __forceinline__ void colsum_cta(const Params& p, uint32_t sb, int j, int tid) {
  const uint32_t bar = sb + SM_BAR;
  auto ld = [&](int i) {
    mbar_expect(bar + 8 * i, 3 * PG);
    tma_ld3(sb + (i & 7) * 3 * PG, &p.mapW3, (2 * j + (i & 1)) * 64, (i >> 1) * 64, 0, bar + 8 * i);
  };
  if (tid == 384) {
#pragma unroll
    for (int i = 0; i < 24; i++) mbar_init(bar + 8 * i, i < 16 ? 1 : 12);
    asm volatile("fence.mbarrier_init.release.cluster;" ::: "memory");
    fence_async_smem();
#pragma unroll 1
    for (int i = 0; i < 8; i++) ld(i);
  }
  const unsigned ep = ld_relaxed(&g_cnt[C_CS * 32]);
  bar_sync(0, NTHREADS);
  if (tid == 384) {
#pragma unroll 1
    for (int i = 8; i < 16; i++) { mbar_wait(bar + 8 * (8 + i), 0); fence_async_smem(); ld(i); }
  }
  if (tid < 384) {
    const int lane = tid & 31, cc = tid & 7, r0 = (tid >> 3) & 15, part = tid >> 7;
    const uint32_t id = ((lane >> 2) == 2 * (lane & 3) ? 0x3f80u : 0u) | ((lane >> 2) == 2 * (lane & 3) + 1 ? 0x3f800000u : 0u);
    const uint32_t src = sb + part * PG + r0 * 128 + ((cc ^ (r0 & 7)) << 4);
    float s[2][2][4];
#pragma unroll
    for (int i = 0; i < 16; i++) s[i >> 3][(i >> 2) & 1][i & 3] = 0.f;
#pragma unroll 1
    for (int i2 = 0; i2 < 16; i2 += 2) {
#pragma unroll
      for (int h = 0; h < 2; h++) {
        const int i = i2 + h;
        mbar_wait(bar + 8 * i, 0);
        uint4 v[4];
#pragma unroll
        for (int k = 0; k < 4; k++) v[k] = lds128(src + (i & 7) * 3 * PG + k * 2048);
#pragma unroll
        for (int k = 0; k < 4; k++) {
          const uint32_t a[4] = {v[k].x, v[k].y, v[k].z, v[k].w};
          mma_bf16(s[h][0], a, id, 0u);
          mma_bf16(s[h][1], a, 0u, id);
        }
        __syncwarp();
        if (i < 8 && lane == 0) mbar_arrive(bar + 8 * (16 + i));
      }
    }
    const uint32_t red = sb + 24 * PG;
#pragma unroll
    for (int h = 0; h < 2; h++)
#pragma unroll
      for (int k = 0; k < 2; k++) sts128f(red + (r0 * 384 + h * 192 + part * 64 + cc * 8 + k * 4) * 4, s[h][k][0], s[h][k][1], s[h][k][2], s[h][k][3]);
    bar_sync(1, 384);
    float tot = 0.f;
#pragma unroll
    for (int k = 0; k < 16; k++) tot += __uint_as_float(lds32(red + (k * 384 + tid) * 4));
    asm volatile("st.relaxed.gpu.global.v2.u32 [%0], {%1,%2};" ::"l"(&g_colsum[j * 384 + tid]), "r"(__float_as_uint(tot)), "r"(ep / NCTA + 1) : "memory");
  }
}

#define KW 3
struct ModeIn { uint32_t ar, ai, br, bi, cr, ci; bf16 logdt; };
__device__ __forceinline__ ModeIn load_modes(const Params& p, int d, int m) {
  const int i = d * 64 + m;
  return {((const uint32_t*)p.a_re)[i], ((const uint32_t*)p.a_im)[i], ((const uint32_t*)p.b_re)[i], ((const uint32_t*)p.b_im)[i],
          ((const uint32_t*)p.c_re)[i], ((const uint32_t*)p.c_im)[i], p.log_dt[d]};
}
__device__ __forceinline__ float4 lds128f_nv(uint32_t a) { float4 v; asm("ld.shared.v4.f32 {%0,%1,%2,%3}, [%4];" : "=f"(v.x), "=f"(v.y), "=f"(v.z), "=f"(v.w) : "r"(a)); return v; }
__device__ __forceinline__ void kernel_gen(const Params& p, uint32_t sb, int cta, int ht, ModeIn in, const ModeIn& in1) {
  const uint32_t bst = sb + SM_KGB + ((ht & 63) >> 2) * 144 + (ht & 3) * 4 + (ht >> 6) * 16;
  const uint64_t db = mkdesc(sb + SM_KGB, 144, 2304, 0);
  const float e0 = (float)(8 * (((ht & 32) >> 1) + ((ht & 31) >> 2)));
  float T[20];
#pragma unroll
  for (int i = 0; i < 20; i++) T[i] = 0.f;
  float k0 = (ht & 63) ? 0.f : __bfloat162float(p.dskip[cv_chan(cta, ht >> 6)]);
#pragma unroll 1
  for (int pass = 0; pass < 4; pass++) {
    {
      const int sh = (pass & 1) ? 0 : 16;
      auto val = [&](uint32_t v) { return __uint_as_float((v << sh) & 0xffff0000u); };
      const float dt = __bfloat162float(__float2bfloat16_rn(expf(__bfloat162float(in.logdt))));
      const float ar2 = dt * val(in.ar) * 1.4426950408889634f, ai = dt * val(in.ai);
      const cplx c = cmul({val(in.cr), -val(in.ci)}, {dt * val(in.br), -dt * val(in.bi)});
      k0 += c.r;
      const cplx z1 = cexp_l(ar2, -ai, 1.f), z256 = cexp_l(ar2, -ai, 256.f), z64 = cexp_l(ar2, ai, 64.f);
      const cplx z2 = csqr(z1), z512 = csqr(z256);
      auto put = [&](int j, cplx v) { sts32(bst + (j >> 2) * 2304 + (j & 3) * 32, packbf(v.r, v.i)); };
      sts128f(sb + SM_KGT + ht * 16, ar2, ai, z64.r, z64.i);
      const cplx c1 = cmul(c, z1), c2 = cmul(c, z2), c3 = cmul(c1, z2), c4 = cmul(c2, z2);
      const cplx c5 = cmul(c3, z2), c6 = cmul(c4, z2), c7 = cmul(c5, z2), c8 = cmul(c6, z2);
      put(0, c1); put(1, c2); put(2, c3); put(3, c4); put(4, c5); put(5, c6); put(6, c7); put(7, c8);
      const cplx c260 = cmul(c4, z256), c264 = cmul(c8, z256), c520 = cmul(c8, z512), c776 = cmul(c264, z512);
      put(8, cmul(c2, z256)); put(9, c260); put(10, cmul(c6, z256)); put(11, c264);
      put(12, cmul(c4, z512)); put(13, c520); put(14, cmul(c260, z512)); put(15, c776);
      const cplx c1032 = cmul(c520, z512), c1288 = cmul(c776, z512);
      put(16, c1032); put(17, c1288); put(18, cmul(c1032, z512)); put(19, cmul(c1288, z512));
    }
    fence_async_smem();
    bar_sync(4, 128);
    uint32_t tb = sb + SM_KGT + (ht & 67) * 16;
    asm volatile("mov.u32 %0, %0;" : "+r"(tb) :: "memory");
#pragma unroll
    for (int q = 0; q < 4; q++) {
      uint32_t A[8];
      if (q >= KW) wg_wait<KW - 1>();
#pragma unroll
      for (int s = 0; s < 4; s++) {
        const float4 v = lds128f_nv(tb + (4 * q + s) * 64);
        const cplx lo = cexp_l(v.x, v.y, e0), hi = cmul(lo, {v.z, v.w});
        A[2 * s] = packbf(lo.r, lo.i);
        A[2 * s + 1] = packbf(hi.r, hi.i);
      }
      wg_fence();
      wgmma_rs<40, 0>(T, A, db + 36 * q, (pass & 1) | q);
      wgmma_rs<40, 0>(T, A + 4, db + 36 * q + 18, 1);
      wg_commit();
    }
    wg_wait<0>();
    acc_fence<20>(T);
    if (ht == 0) TS(4 + pass);
    if (pass & 1) {
      const int h2 = opaque_tid() - 256, w = h2 >> 5, lane = h2 & 31, t = lane & 3, chn = h2 >> 6, m = h2 & 63, i0 = 16 * (w & 1) + (lane >> 2);
      const int lc = (pass & 2) + chn;
      const uint32_t kc = sb + kc_off(lc);
      auto put = [&](int idx, float v) {
        sts16(kc + idx * 2, __bfloat16_as_ushort(__float2bfloat16_rn(v)));
      };
#pragma unroll
      for (int hi = 0; hi < 2; hi++) {
        const int i = i0 + 8 * hi;
        float v[5];
#pragma unroll
        for (int j = 0; j < 5; j++) v[j] = chn ? T[4 * j + 2 * hi + 1] : T[4 * j + 2 * hi];
        put(8 * i + 1 + t, v[0]);
        put(8 * i + 5 + t, v[1]);
        put(257 + 4 * i + t, v[2]);
        put(385 + 2 * i + (t & 1) + 64 * (t >> 1), v[3]);
        put(513 + i + 32 * t, v[4]);
      }
#pragma unroll
      for (int o = 16; o > 0; o >>= 1) k0 += __shfl_xor_sync(~0u, k0, o);
      if (lane == 0) sts32f(sb + SM_RED + 4 * w, k0);
      bar_sync(4, 128);
      if (m == 0) put(0, k0 + __uint_as_float(lds32(sb + SM_RED + 4 * w + 4)));
      k0 = m ? 0.f : __bfloat162float(p.dskip[cv_chan(cta, 2 + chn)]);
      in = in1;
    }
  }
}

__device__ __forceinline__ void expand_taps(uint32_t sb, int ht) {
  const int ch = ht >> 5, lane = ht & 31;
  const uint32_t kc = sb + kc_off(ch);
  const uint32_t dst0 = sb + cv_pe(ch);
  auto put = [&](int G, uint32_t v0, uint32_t v1, uint32_t v2, uint32_t v3, uint32_t v4, uint32_t v5, uint32_t v6, uint32_t v7, uint32_t v8) {
    const uint32_t dst = dst0 + G * 32;
    sts128(dst, make_uint4(v1 | (v0 << 16), v2 | (v1 << 16), v3 | (v2 << 16), v4 | (v3 << 16)));
    sts128(dst + 16, make_uint4(v5 | (v4 << 16), v6 | (v5 << 16), v7 | (v6 << 16), v8 | (v7 << 16)));
  };
  {
    const uint4 q = lds128(kc + lane * 16);
    const uint32_t pv = lane ? lds16(kc + lane * 16 - 2) : 0u;
    const uint32_t dst = dst0 + (lane + 2) * 32;
    sts128(dst, make_uint4(__byte_perm(q.x, pv, 0x5410), __byte_perm(q.x, q.x, 0x1032), __byte_perm(q.y, q.x, 0x7610), __byte_perm(q.y, q.y, 0x1032)));
    sts128(dst + 16, make_uint4(__byte_perm(q.z, q.y, 0x7610), __byte_perm(q.z, q.z, 0x1032), __byte_perm(q.w, q.z, 0x7610), __byte_perm(q.w, q.w, 0x1032)));
    if (lane < 4) sts128(dst0 + lane * 16, make_uint4(0, 0, 0, 0));
  }
  uint32_t a[5], b[2][3];
  {
    const uint32_t s1 = kc + 2 * (256 + 4 * lane);
#pragma unroll
    for (int k = 0; k < 5; k++) a[k] = lds16(s1 + 2 * k);
#pragma unroll
    for (int u = 0; u < 2; u++) {
      const uint32_t s2 = kc + 2 * (384 + 2 * (lane + 32 * u));
#pragma unroll
      for (int k = 0; k < 3; k++) b[u][k] = lds16(s2 + 2 * k);
    }
  }
  const uint32_t k255 = lds16(kc + 2 * 255), k1024 = lds16(kc + 2 * 512);
  put(34 + lane, lane == 0 ? k255 : a[0], a[0], a[0], a[1], a[2], a[2], a[2], a[3], a[4]);
#pragma unroll
  for (int u = 0; u < 2; u++) put(66 + lane + 32 * u, b[u][0], b[u][0], b[u][0], b[u][0], b[u][1], b[u][1], b[u][1], b[u][2], b[u][2]);
  if (lane < 10) {
    const uint32_t v = lane == 0 ? k1024 : 0u;
    put(130 + lane, v, v, v, v, v, v, 0u, 0u, 0u);
  }
}
__device__ __forceinline__ void expand_far(uint32_t sb, int ht) {
  const int ch = ht >> 5, lane = ht & 31;
  const uint32_t kc = sb + kc_off(ch) + 4 * (249 + lane), dst = sb + cv_fa(ch);
  uint32_t v[2][9];
#pragma unroll
  for (int u = 0; u < 2; u++)
#pragma unroll
    for (int k = 0; k < 9; k++) v[u][k] = lds32(kc + 4 * (32 * u + k));
#pragma unroll
  for (int k = 0; k < 8; k++) v[0][k] = lane + k < 7 ? 0u : lane + k == 7 ? v[0][k] & 0xffff0000u : v[0][k];
#pragma unroll
  for (int u = 0; u < 2; u++) {
    const uint32_t row = dst + (56 + 32 * u + lane) * 16;
    sts128(row, make_uint4(__byte_perm(v[u][1], v[u][2], 0x5410), __byte_perm(v[u][3], v[u][4], 0x5410), __byte_perm(v[u][5], v[u][6], 0x5410), __byte_perm(v[u][7], v[u][8], 0x5410)));
    sts128(row + 2048, make_uint4(__byte_perm(v[u][0], v[u][1], 0x7632), __byte_perm(v[u][2], v[u][3], 0x7632), __byte_perm(v[u][4], v[u][5], 0x7632), __byte_perm(v[u][6], v[u][7], 0x7632)));
    sts128(dst + u * 2048 + lane * 16, make_uint4(0, 0, 0, 0));
    if (lane < 24) sts128(dst + u * 2048 + (32 + lane) * 16, make_uint4(0, 0, 0, 0));
  }
}

#define FILL1 B_U
#define WPRE 2
__host__ __device__ constexpr int bar_count(int i) {
  return i == B_END ? 3 : i == B_AL ? 8 : (i == B_OST || i == B_OST + 1) ? 4 : (i == B_Z0 || i == B_PUB + 2 || i == B_PUB || i == B_R + 1) ? 256 : (i >= B_FARM && i < B_END) ? 128 : 1;
}
__host__ __device__ constexpr bool bar_first(int i) { return i < B_WF + 2 && (i & 7) < 2; }

__global__ void __launch_bounds__(NTHREADS, 1) fused_kernel(const __grid_constant__ Params p) {
  extern __shared__ __align__(1024) uint8_t smem[];
  const uint32_t sb = s32(smem);
  const int tid = threadIdx.x, lane = tid & 31;
  const int warp = __shfl_sync(~0u, tid >> 5, 0);
  if (blockIdx.x < 4) {
    colsum_cta(p, sb, blockIdx.x, tid);
    return;
  }
  const int cta = blockIdx.x - 4;
  const int rb = ((cta >> 4) & 3) * 4 + ((cta >> 2) & 3), hg = (cta >> 6) * 4 + (cta & 3);
  const int rb2 = cta >> 3, q2 = cta & 7;
  const uint32_t bar = sb + SM_BAR;
  auto ld_x0 = [&](int half, int c) {
    const uint32_t b = bar + 8 * (B_XF + 8 * half + c);
    mbar_expect(b, PG);
    tma_ld(sb + x_page(half, c) * PG, &p.mapX, c * 64, (16 * half + rb) * 64, b);
  };
  auto ld_w = [&](int c) {
    const uint32_t b = bar + 8 * (B_WF + c);
    mbar_expect(b, 3 * PG);
    tma_ld3(sb + w_page(c) * PG, &p.mapW3, hg * 64, c * 64, 0, b);
  };

  if (tid == 0) TS(0);
  if (tid == 480) LTS(0);
  if (warp < 6 && elect_one()) {
    if (warp == 0) {
#pragma unroll
      for (int i = 0; i < B_WF + 2; i++)
        if (bar_first(i)) mbar_init(bar + 8 * i, 1);
      asm volatile("fence.mbarrier_init.release.cluster;" ::: "memory");
      fence_async_smem();
      ld_x0(0, 0); ld_w(0); ld_x0(1, 0);
      ld_x0(0, 1); ld_w(1); ld_x0(1, 1);
      TS(1);
    } else {
#pragma unroll
      for (int q = 0; q < 5; q++) {
        if (warp == q + 1) {
#pragma unroll
          for (int i = 0; i < B_COUNT; i++)
            if (!bar_first(i) && i % 5 == q) mbar_init(bar + 8 * i, bar_count(i));
        }
      }
      asm volatile("fence.mbarrier_init.release.cluster;" ::: "memory");
    }
  }

  if (warp < 8) {
    bar_sync(0, NTHREADS);
    asm volatile("setmaxnreg.inc.sync.aligned.u32 %0;" ::"n"(R_CONS));
    const int cw = __shfl_sync(~0u, opaque_tid() >> 5, 0);
    const int wg = cw >> 2, w = cw & 3;
    if (tid == 0) TS(2);
    {
      const uint4 u = make_uint4(UNSET, UNSET, UNSET, UNSET);
#pragma unroll
      for (int i = 0; i < 2; i++) stg128(g_halo + cta * 512 + i * 256 + tid, u);
#pragma unroll
      for (int i = 0; i < 4; i++) stg128((uint4*)g_O + cta * 1024 + i * 256 + tid, u);
#pragma unroll
      for (int i = 0; i < 4; i++) stg128((uint4*)g_xT + cta * 1024 + i * 256 + tid, u);
      if (tid < 24) stg128((uint4*)g_stats + cta * 24 + tid, make_uint4(0, 0, 0, 0));
      mbar_arrive(bar + 8 * B_Z0);
    }
    int rtp = 0;
#pragma unroll 1
    for (int layer = 0; layer < 2; layer++) {
      attn_phase(p, sb, layer, rb, hg, wg, w);
      proj_phase(p, sb, layer, rb2, q2, wg, w, rtp);
      conv_phase(p, sb, layer, cta);
    }
    final_phase(p, sb, cta, wg, w, rtp);
  } else if (warp < 12) {
    asm volatile("setmaxnreg.dec.sync.aligned.u32 %0;" ::"n"(R_HELP));
    const int ht = tid - 256;
    {
      unsigned ep0 = 0;
      if (ht == 0) ep0 = ld_relaxed(&g_cnt[C_CS * 32]);
      const ModeIn in0 = load_modes(p, cv_chan(cta, ht >> 6), ht & 63), in1 = load_modes(p, cv_chan(cta, 2 + (ht >> 6)), ht & 63);
      bar_sync(0, NTHREADS);
      if (ht == 0) {
        sts32(sb + SM_EP, ep0 / NCTA);
        mbar_arrive(bar + 8 * B_EP);
      }
      kernel_gen(p, sb, cta, ht, in0, in1);
      if (ht < 96) sts128f(sb + SM_STG + ht * 16, 0.f, 0.f, 0.f, 1.f);
      fence_async_smem();
      bar_sync(4, 128);
      if (ht == 0) mbar_arrive(bar + 8 * B_KG);
    }
#pragma unroll 1
    for (int layer = 0; layer < 2; layer++) {
      bf16* xout = g_xT + ((2 * layer + 1) * DM + 2 * cta) * LSEQ;
      mbar_wait(bar + 8 * B_PDONE, layer);
      expand_taps(sb, opaque_tid() - 256);
      mbar_arrive(bar + 8 * B_PE);
      TSW(0);
      expand_far(sb, opaque_tid() - 256);
      mbar_wait(bar + 8 * (B_PDONE + 1), layer);
      mbar_wait(bar + 8 * B_U, layer);
#pragma unroll 1
      for (int lc = 0; lc < 4; lc += 2) {
        conv_sums(sb, lc, opaque_tid() - 256);
        TSW(1 + lc);
      }
      fence_async_smem();
      bar_sync(4, 128);
      conv_far(sb, opaque_tid() - 256);
      mbar_arrive(bar + 8 * B_FARM);
      TSW(4);
      mbar_wait(bar + 8 * (B_R + 1), layer);
      conv_epi<1, 2>(sb, xout, 0, opaque_tid() - 256);
      mbar_arrive(bar + 8 * (B_PUB + 1));
      TSW(5);
      mbar_wait(bar + 8 * (B_R + 2), layer);
      conv_epi<1, 1>(sb, xout, 2, opaque_tid() - 256);
      mbar_arrive(bar + 8 * (B_PUB + 2));
      TSW(6);
    }
  } else {
    asm volatile("setmaxnreg.dec.sync.aligned.u32 %0;" ::"n"(R_AGENT));
    bar_sync(0, NTHREADS);
    auto done = [&](int half, int c, int layer) { mbar_wait(bar + 8 * (B_DN + 8 * half + c), layer); };
    auto publish = [&](int layer, int k) {
      mbar_wait(bar + 8 * (B_PUB + k), layer);
      if (layer == 0) {
        red_release(&g_cnt[(C_C + k) * 32]);
      }
      else red_relaxed(&g_cnt[(C_F + 4 * k + (cta >> 5)) * 32]);
      TS(16 + layer * 56 + 40 + 7 + k);
    };
    if (warp == 12) {
      if (elect_one()) {
#pragma unroll 1
        for (int layer = 0; layer < 2; layer++) {
          auto ld_xe = [&](int c) {
            const uint32_t b = bar + 8 * (B_XF + c);
            mbar_expect(b, PG);
            if (layer == 0) tma_ld(sb + (c - 5) * PG, &p.mapX, c * 64, rb * 64, b);
            else tma_ld(sb + (c - 5) * PG, &p.mapXT, rb * 64, DM + c * 64, b);
          };
          if (layer == 0) {
            ld_x0(0, 2); ld_w(2); ld_x0(1, 2);
            if (hg >= 3) {
              mbar_expect(bar + 8 * B_SC, PG);
              tma_ld(sb + P_R * PG, &p.mapX, hg * 64, rb * 64, bar + 8 * B_SC);
            }
            if (rb < 4) tma_prefetch3(&p.mapW3, hg * 64, (4 + rb) * 64, 0);
            ld_x0(0, 3); ld_w(3); ld_x0(1, 3); ld_x0(0, 4); ld_x0(1, 4);
            done(0, 0, 0); done(1, 0, 0);
            ld_w(4);
            ld_x0(1, 5); ld_x0(1, 6); ld_x0(1, 7);
            done(0, 1, 0); done(1, 1, 0);
            ld_w(5);
            if (rb2 < 8) tma_prefetch5(&p.mapWo, q2 * 64, rb2 * 2);
            done(0, 2, 0);
            fence_async_smem();
            ld_xe(5); ld_xe(6); ld_xe(7);
          } else {
            mbar_wait(bar + 8 * B_PDONE, 0);
            mbar_wait(bar + 8 * (B_PDONE + 1), 0);
            mbar_wait(bar + 8 * (WPRE == 1 ? B_U : B_GB + 1), 0);
            ld_w(0); ld_w(1); ld_w(2);
            mbar_wait(bar + 8 * (B_PUB + 2), 0);
            fence_async_smem();
            ld_w(3);
            done(0, 2, 1);
            fence_async_global();
            fence_async_smem();
            ld_xe(5); ld_xe(6); ld_xe(7);
            done(1, 0, 1);
            ld_w(4);
            done(1, 1, 1);
            ld_w(5);
          }
          done(1, 2, layer);
          fence_async_smem();
          ld_w(6); ld_w(7);
          auto ld_res = [&](int half) {
            const uint32_t b = bar + 8 * (B_RF + half);
            mbar_expect(b, PG);
            if (layer == 0) tma_ld(sb + (P_R + half) * PG, &p.mapX, q2 * 64, (16 * half + rb2) * 64, b);
            else tma_ld(sb + (P_R + half) * PG, &p.mapXT, (16 * half + rb2) * 64, DM + q2 * 64, b);
          };
          done(0, 4, layer); done(1, 3, layer);
          fence_async_smem();
#pragma unroll 1
          for (int c = 0; c < 8; c++) {
            const uint32_t b = bar + 8 * (B_WOF + (c >> 1));
            if (c == 5) { ld_res(0); done(1, 4, layer); }
            if ((c & 1) == 0) mbar_expect(b, 2 * PG);
            tma_ld5(sb + wo_page(c) * PG, &p.mapWo, q2 * 64, c * 2, b);
          }
          mbar_wait(bar + 8 * B_KG, 0);
          fence_async_global();
          ld_res(1);
        }
      }
    } else if (warp == 13) {
      if (elect_one()) {
        mbar_wait(bar + 8 * (B_WF + 2), 0);
        asm volatile("prefetch.tensormap [%0];" ::"l"(&p.mapO2) : "memory");
        asm volatile("prefetch.tensormap [%0];" ::"l"(&p.mapXT) : "memory");
        asm volatile("prefetch.tensormap [%0];" ::"l"(&p.mapOut) : "memory");
        asm volatile("prefetch.tensormap [%0];" ::"l"(&p.mapWo) : "memory");
        mbar_wait(bar + 8 * B_EP, 0);
        const unsigned e1 = lds32(sb + SM_EP) + 1;
        auto ld_x1 = [&](int half, int c0, int c1) {
          fence_async_global();
          fence_async_smem();
#pragma unroll 1
          for (int c = c0; c < c1; c++) {
            const uint32_t b = bar + 8 * (B_XF + 8 * half + c);
            mbar_expect(b, PG);
            tma_ld(sb + x_page(half, c) * PG, &p.mapXT, (16 * half + rb) * 64, DM + c * 64, b);
          }
        };
#pragma unroll 1
        for (int layer = 0; layer < 2; layer++) {
          if (layer == 1) {
            mbar_wait(bar + 8 * B_FARM, 0);
            mbar_wait(bar + 8 * B_PUB, 0);
            spin_until(&g_cnt[C_C * 32], e1 * NCTA);
            TS(10);
            ld_x1(0, 0, 3);
            if (hg >= 3) {
              mbar_expect(bar + 8 * B_SC, PG);
              tma_ld(sb + P_R * PG, &p.mapXT, rb * 64, DM + hg * 64, bar + 8 * B_SC);
            }
            ld_x1(0, 3, 5);
            mbar_wait(bar + 8 * (B_PUB + 1), 0);
            spin_until(&g_cnt[(C_C + 1) * 32], e1 * NCTA);
            TS(11);
            ld_x1(1, 0, 4);
            spin_until(&g_cnt[(C_C + 2) * 32], e1 * NCTA);
            TS(12);
            ld_x1(1, 4, 8);
          }
#pragma unroll 1
          for (int half = 0; half < 2; half++) {
            done(1, 7, layer);
            mbar_wait(bar + 8 * B_OST, layer);
            if (half) mbar_wait(bar + 8 * (B_OST + 1), layer);
            spin_until(&g_cnt[(C_O + layer * 32 + 16 * half + rb2) * 32], e1 * 32);
            fence_async_global();
            fence_async_smem();
#pragma unroll 1
            for (int c = 0; c < 4; c++) {
              const uint32_t b = bar + 8 * (B_OF + 4 * half + c);
              mbar_expect(b, 2 * PG);
              tma_ld3(sb + o_page(half, c) * PG, &p.mapO2, 0, (layer * 32 + 16 * half + rb2) * 64, 2 * c, b);
            }
          }
        }
        mbar_wait(bar + 8 * B_PUB, 1);
#pragma unroll 1
        for (int half = 0; half < 2; half++) {
          spin_until(&g_cnt[(C_F + 4 * (half ? 1 + (cta >> 6) : 0) + ((cta >> 4) & 3)) * 32], e1 * 32);
          fence_async_global();
          mbar_expect(bar + 8 * (B_TF + half), PG);
          tma_ld(sb + (16 + half) * PG, &p.mapXT, (16 * half + (cta & 15)) * 64, 3 * DM + (cta >> 4) * 64, bar + 8 * (B_TF + half));
        }
      }
    } else if (warp == 14) {
      mbar_wait(bar + 8 * B_EP, 0);
      const unsigned e1 = lds32(sb + SM_EP) + 1;
      done(0, 0, 0);
      if (lane == 0) { spin_until(&g_cnt[C_Z * 32], e1 * NCTA); TS(3); }
      __syncwarp();
      {
        const uint2* cp = g_colsum + (hg * 192 + lane);
        uint2 v[6];
        bool ok;
        int it = 0;
        do {
          ok = true;
#pragma unroll
          for (int i = 0; i < 6; i++) {
            asm volatile("ld.relaxed.gpu.global.v2.u32 {%0,%1}, [%2];" : "=r"(v[i].x), "=r"(v[i].y) : "l"(cp + 32 * i) : "memory");
            ok = ok && v[i].y == e1;
          }
          if (++it > (1 << 22)) __trap();
        } while (!__all_sync(~0u, ok));
#pragma unroll
        for (int i = 0; i < 6; i++) sts32f(sb + SM_CS + 4 * (lane + 32 * i), __uint_as_float(v[i].x));
      }
      __syncwarp();
      if (lane == 0) {
        mbar_arrive(bar + 8 * B_CSF);
        red_relaxed(&g_cnt[C_CS * 32]);
        TS(13);
#pragma unroll 1
        for (int i = 0; i < 4; i++) {
          const int layer = i >> 1;
          mbar_wait(bar + 8 * (B_PST + (i & 1)), layer);
          if (i & 1) mbar_wait(bar + 8 * B_AL, layer);
          spin_until(&g_cnt[(C_G + i) * 32], e1 * NCTA);
          if (i & 1) {
            const uint32_t b = bar + 8 * (B_GB + 1);
            fence_async_smem();
            mbar_expect(b, 4 * (3072 + 2048));
#pragma unroll 1
            for (int lc = 0; lc < 4; lc++) {
              bulk_ld(sb + cv_pe(lc), g_stats + (layer * 32 + 16 + 4 * lc) * 192, 3072, b);
              bulk_ld(sb + cv_x(1, lc), g_xT + ((size_t)(i - 1) * DM + cv_chan(cta, lc)) * LSEQ + 1024, 2048, b);
            }
            TS(14 + layer);
            publish(layer, 1);
          } else {
            mbar_arrive(bar + 8 * B_GB);
          }
        }
      }
    } else {
      if (lane == 0) {
        mbar_wait(bar + 8 * B_Z0, 0);
        red_release(&g_cnt[C_Z * 32]);
      }
      __syncwarp();
      auto reset = [&](void* buf, int n) {
        uint4* dst = (uint4*)buf + cta * 32 * n + lane;
#pragma unroll 4
        for (int i = 0; i < n; i++) stg128(dst + 32 * i, make_uint4(UNSET, UNSET, UNSET, UNSET));
      };
      mbar_wait(bar + 8 * (FILL1), 0);
      reset(g_halo + 128 * 512, 16);
      reset(g_O + LSEQ * DM, 32);
      reset(g_xT + 2 * LSEQ * DM, 64);
      __syncwarp();
      if (lane == 0) {
        TS(16 + 40 + 10);
#pragma unroll 1
        for (int i = 0; i < 4; i++) publish(i >> 1, 2 * (i & 1));
      }
    }
  }
}

typedef CUresult (*EncodeFn)(CUtensorMap*, CUtensorMapDataType, cuuint32_t, void*, const cuuint64_t*, const cuuint64_t*,
                             const cuuint32_t*, const cuuint32_t*, CUtensorMapInterleave, CUtensorMapSwizzle,
                             CUtensorMapL2promotion, CUtensorMapFloatOOBfill);

static void make_map(EncodeFn enc, CUtensorMap* m, void* ptr, uint64_t cols, uint64_t rows, uint32_t box_rows) {
  cuuint64_t dims[2] = {cols, rows};
  cuuint64_t strides[1] = {cols * 2};
  cuuint32_t box[2] = {64, box_rows};
  cuuint32_t es[2] = {1, 1};
  enc(m, CU_TENSOR_MAP_DATA_TYPE_BFLOAT16, 2, ptr, dims, strides, box, es, CU_TENSOR_MAP_INTERLEAVE_NONE,
      CU_TENSOR_MAP_SWIZZLE_128B, CU_TENSOR_MAP_L2_PROMOTION_L2_128B, CU_TENSOR_MAP_FLOAT_OOB_FILL_NONE);
}
static void make_map3(EncodeFn enc, CUtensorMap* m, void* ptr, uint64_t d0, uint64_t cols, uint64_t rows, uint64_t blk_stride,
                      uint64_t nblocks, uint32_t nblk) {
  cuuint64_t dims[3] = {d0, rows, nblocks};
  cuuint64_t strides[2] = {cols * 2, blk_stride * 2};
  cuuint32_t box[3] = {64, 64, nblk};
  cuuint32_t es[3] = {1, 1, 1};
  enc(m, CU_TENSOR_MAP_DATA_TYPE_BFLOAT16, 3, ptr, dims, strides, box, es, CU_TENSOR_MAP_INTERLEAVE_NONE,
      CU_TENSOR_MAP_SWIZZLE_128B, CU_TENSOR_MAP_L2_PROMOTION_L2_128B, CU_TENSOR_MAP_FLOAT_OOB_FILL_NONE);
}

extern "C" void kernel_launch(void* const* d_in, const int* in_sizes, int n_in, void* d_out, int out_size) {
  static Params prm;
  static void* cached[13] = {nullptr};
  static bool attr_done = false;
  bool same = attr_done && cached[12] == d_out;
  for (int i = 0; i < 12 && same; i++) same = cached[i] == d_in[i];
  if (!same) {
    void* fn = nullptr;
    cudaDriverEntryPointQueryResult qr;
    cudaGetDriverEntryPoint("cuTensorMapEncodeTiled", &fn, cudaEnableDefault, &qr);
    EncodeFn enc = (EncodeFn)fn;
    void *pO, *pXT;
    cudaGetSymbolAddress(&pO, g_O);
    cudaGetSymbolAddress(&pXT, g_xT);
    make_map(enc, &prm.mapX, d_in[0], DM, LSEQ, 64);
    make_map(enc, &prm.mapXT, pXT, LSEQ, 4 * DM, 64);
    make_map(enc, &prm.mapOut, d_out, DM, LSEQ, 64);
    {
      cuuint64_t dims[5] = {DM, 2, 4, 4, 16};
      cuuint64_t strides[4] = {DM * 2, 8 * DM * 2, 2 * DM * 2, 32 * DM * 2};
      cuuint32_t box[5] = {64, 2, 4, 4, 2};
      cuuint32_t es[5] = {1, 1, 1, 1, 1};
      enc(&prm.mapWo, CU_TENSOR_MAP_DATA_TYPE_BFLOAT16, 5, d_in[2], dims, strides, box, es, CU_TENSOR_MAP_INTERLEAVE_NONE,
          CU_TENSOR_MAP_SWIZZLE_128B, CU_TENSOR_MAP_L2_PROMOTION_L2_128B, CU_TENSOR_MAP_FLOAT_OOB_FILL_NONE);
    }
    make_map3(enc, &prm.mapW3, d_in[1], DM, 3 * DM, DM, DM, 3, 3);
    make_map3(enc, &prm.mapO2, pO, 64, DM, 2 * LSEQ, 64, 8, 2);
    prm.wqkv = (const bf16*)d_in[1];
    prm.a_re = (const bf16*)d_in[4]; prm.a_im = (const bf16*)d_in[5];
    prm.b_re = (const bf16*)d_in[6]; prm.b_im = (const bf16*)d_in[7];
    prm.c_re = (const bf16*)d_in[8]; prm.c_im = (const bf16*)d_in[9];
    prm.log_dt = (const bf16*)d_in[10]; prm.dskip = (const bf16*)d_in[11];
    cudaFuncSetAttribute(fused_kernel, cudaFuncAttributeMaxDynamicSharedMemorySize, SM_TOTAL);
    for (int i = 0; i < 12; i++) cached[i] = d_in[i];
    cached[12] = d_out;
    attr_done = true;
  }
  fused_kernel<<<NCTA + 4, NTHREADS, SM_TOTAL>>>(prm);
}
```

```cpp
#include <cuda_runtime.h>
#include <cuda_bf16.h>
#include <cuda.h>
#include <stdint.h>

typedef __nv_bfloat16 bf16;

constexpr int LSEQ = 2048;
constexpr int DM = 512;
constexpr int NCTA = 128;
constexpr int NTHREADS = 512;
#define R_CONS 200
#define R_HELP 88
#define R_AGENT 24
#define GPOS 4
#define TURN0 4
#define TURN1 4

constexpr int PG = 8192;
constexpr int P_R = 25;
__host__ __device__ constexpr int x_page(int half, int c) { return half ? 8 + c : c < 5 ? c : c - 5; }
__host__ __device__ constexpr int w_page(int c) { return (c & 3) < 3 ? 16 + 3 * (c & 3) : c < 4 ? 5 : 8; }
__host__ __device__ constexpr int wo_page(int c) { return c < 5 ? 3 + c : 11 + c; }
__host__ __device__ constexpr int o_page(int half, int pair) { return half ? (pair ? 17 + 2 * pair : 0) : 8 + 2 * pair; }
constexpr int SM_KGB = (P_R + 1) * PG;
constexpr int SM_KC = 27 * PG;
constexpr int KC_STRIDE = 648;
__host__ __device__ constexpr int kc_off(int lc) { return SM_KC + (lc & 1) * 2 * KC_STRIDE + (lc < 2 ? 3328 : 0); }
constexpr int SM_KGT = SM_KC + 3328 + 2592;
constexpr int SM_CS = SM_KGT + 2048;
constexpr int SM_RED = SM_CS + 768;
constexpr int SM_EP = SM_RED + 16;
constexpr int SM_STG = SM_KGT;
constexpr int SM_BAR = SM_RED + 32;
constexpr int SM_TS = SM_BAR + 768;
constexpr int SM_TOTAL = SM_TS + 512;
static_assert(SM_TOTAL <= 232448 && SM_STG % 16 == 0 && SM_KGT % 16 == 0, "shared memory");

constexpr int CV_UH = 140 * 16;
__host__ __device__ constexpr int cv_u(int lc) { return (8 + 2 * lc) * PG; }
__host__ __device__ constexpr int cv_pe(int lc) { return cv_u(lc) + 4480; }
__host__ __device__ constexpr int cv_pb1(int lc, int w) { return w ? cv_u(lc) + 8960 + (w - 1) * 2048 : 7 * PG + lc * 2048; }
__host__ __device__ constexpr int cv_fa(int lc) { return cv_pb1(lc, 1) + 128; }
__host__ __device__ constexpr int cv_dump(int lc) { return cv_u(lc) + 16256; }
__host__ __device__ constexpr int cv_pb0(int lc, int w) { return lc * PG + w * 2048; }
__host__ __device__ constexpr int cv_se(int lc) { return 4 * PG + lc * 4096; }
__host__ __device__ constexpr int cv_so(int lc) { return cv_se(lc) + 2048; }
__host__ __device__ constexpr int cv_pf(int lc) { return 6 * PG + lc * 2048; }
__host__ __device__ constexpr int cv_x(int half, int lc) { return (P_R + half) * PG + lc * 2048; }
__host__ __device__ constexpr int cv_chan(int cta, int lc) { return 2 * cta + (lc & 1) + 256 * (lc >> 1); }

enum {
  B_XF = 0,
  B_WF = 16,
  B_OF = 24,
  B_DN = 32,
  B_WOF = 48,
  B_RF = 52,
  B_PST = 54,
  B_OST = 56,
  B_PDONE = 58,
  B_GB = 60,
  B_TF = 62,
  B_CSF = 64,
  B_EP = 65,
  B_KG = 67,
  B_FARM = 68,
  B_PE = 70,
  B_U = 71,
  B_PUB = 74,
  B_R = 77,
  B_END = 80,
  B_SC = 81,
  B_RT = 82,
  B_AL = 84,
  B_RS = 85,
  B_COUNT = 88
};

enum {
  C_CS = 0,
  C_G = 1,
  C_C = 5,
  C_F = 8,
  C_O = 20,
  C_Z = 84,
  C_R = 85,
  C_COUNT = 88
};

__device__ unsigned g_cnt[C_COUNT * 32];
__device__ __align__(1024) bf16 g_O[2 * LSEQ * DM];
__device__ __align__(1024) bf16 g_xT[4 * DM * LSEQ];
__device__ __align__(1024) float g_stats[2 * 32 * 192];
__device__ __align__(1024) uint2 g_colsum[3 * DM];
__device__ __align__(1024) uint4 g_halo[2 * 32 * 8 * 256];
__device__ __align__(1024) uint4 g_part[2 * 32 * 8 * 64];
#define TS(i) do { } while (0)
#define TSW(k) do { if ((threadIdx.x & 127) == 0) TS(16 + layer * 56 + (threadIdx.x >> 7) * 20 + (k)); } while (0)
#define TSG(k) do { } while (0)

#define RETRY(i) do { } while (0)
#define LTS(i) do { } while (0)

struct Params {
  CUtensorMap mapX, mapW3, mapXT, mapOut, mapWo;
  const bf16 *wqkv, *a_re, *a_im, *b_re, *b_im, *c_re, *c_im, *log_dt, *dskip;
};

__device__ __forceinline__ uint32_t s32(const void* p) { return (uint32_t)__cvta_generic_to_shared(p); }
__device__ __forceinline__ void mbar_init(uint32_t b, int c) { asm volatile("mbarrier.init.shared::cta.b64 [%0], %1;" ::"r"(b), "r"(c) : "memory"); }
__device__ __forceinline__ void mbar_expect(uint32_t b, int bytes) { asm volatile("mbarrier.arrive.expect_tx.shared::cta.b64 _, [%0], %1;" ::"r"(b), "r"(bytes) : "memory"); }
__device__ __forceinline__ void mbar_arrive(uint32_t b) { asm volatile("mbarrier.arrive.shared::cta.b64 _, [%0];" ::"r"(b) : "memory"); }
__device__ __forceinline__ void mbar_wait(uint32_t b, int parity) {
  asm volatile("{\n.reg .pred p;\nWAIT_LOOP:\nmbarrier.try_wait.parity.shared::cta.b64 p, [%0], %1;\n@p bra WAIT_DONE;\nbra WAIT_LOOP;\nWAIT_DONE:\n}" ::"r"(b), "r"(parity) : "memory");
}
__device__ __forceinline__ bool mbar_test(uint32_t b, int parity) {
  uint32_t ok;
  asm volatile("{\n.reg .pred p;\nmbarrier.test_wait.parity.shared::cta.b64 p, [%1], %2;\nselp.u32 %0, 1, 0, p;\n}" : "=r"(ok) : "r"(b), "r"(parity) : "memory");
  return ok != 0;
}
__device__ __forceinline__ int opaque_tid() { int v; asm volatile("mov.u32 %0, %%tid.x;" : "=r"(v)); return v; }
__device__ __forceinline__ bool elect_one() {
  uint32_t r;
  asm volatile("{\n.reg .pred p;\nelect.sync _|p, 0xffffffff;\nselp.u32 %0, 1, 0, p;\n}" : "=r"(r));
  return r != 0;
}
__device__ __forceinline__ void tma_ld(uint32_t dst, const CUtensorMap* m, int c0, int c1, uint32_t bar) {
  asm volatile("cp.async.bulk.tensor.2d.shared::cluster.global.mbarrier::complete_tx::bytes [%0], [%1, {%3, %4}], [%2];"
               ::"r"(dst), "l"(m), "r"(bar), "r"(c0), "r"(c1) : "memory");
}
__device__ __forceinline__ void tma_ld3(uint32_t dst, const CUtensorMap* m, int c0, int c1, int c2, uint32_t bar) {
  asm volatile("cp.async.bulk.tensor.3d.shared::cluster.global.mbarrier::complete_tx::bytes [%0], [%1, {%3, %4, %5}], [%2];"
               ::"r"(dst), "l"(m), "r"(bar), "r"(c0), "r"(c1), "r"(c2) : "memory");
}
__device__ __forceinline__ void tma_ld5(uint32_t dst, const CUtensorMap* m, int c0, int c4, uint32_t bar) {
  asm volatile("cp.async.bulk.tensor.5d.shared::cluster.global.mbarrier::complete_tx::bytes [%0], [%1, {%3, 0, 0, 0, %4}], [%2];"
               ::"r"(dst), "l"(m), "r"(bar), "r"(c0), "r"(c4) : "memory");
}
__device__ __forceinline__ void tma_prefetch5(const CUtensorMap* m, int c0, int c4) {
  asm volatile("cp.async.bulk.prefetch.tensor.5d.L2.global.tile [%0, {%1, 0, 0, 0, %2}];" ::"l"(m), "r"(c0), "r"(c4) : "memory");
}
__device__ __forceinline__ void tma_prefetch2(const CUtensorMap* m, int c0, int c1) {
  asm volatile("cp.async.bulk.prefetch.tensor.2d.L2.global.tile [%0, {%1, %2}];" ::"l"(m), "r"(c0), "r"(c1) : "memory");
}
__device__ __forceinline__ void tma_prefetch3(const CUtensorMap* m, int c0, int c1, int c2) {
  asm volatile("cp.async.bulk.prefetch.tensor.3d.L2.global.tile [%0, {%1, %2, %3}];" ::"l"(m), "r"(c0), "r"(c1), "r"(c2) : "memory");
}
__device__ __forceinline__ void tma_st(const CUtensorMap* m, int c0, int c1, uint32_t src) {
  asm volatile("cp.async.bulk.tensor.2d.global.shared::cta.bulk_group [%0, {%2, %3}], [%1];" ::"l"(m), "r"(src), "r"(c0), "r"(c1) : "memory");
}
__device__ __forceinline__ void bulk_ld(uint32_t dst, const void* src, int bytes, uint32_t bar) {
  asm volatile("cp.async.bulk.shared::cluster.global.mbarrier::complete_tx::bytes [%0], [%1], %2, [%3];" ::"r"(dst), "l"(src), "r"(bytes), "r"(bar) : "memory");
}
__device__ __forceinline__ void bulk_st(void* dst, uint32_t src, int bytes) {
  asm volatile("cp.async.bulk.global.shared::cta.bulk_group [%0], [%1], %2;" ::"l"(dst), "r"(src), "r"(bytes) : "memory");
}
__device__ __forceinline__ void bulk_red_add_f32(void* dst, uint32_t src, int bytes) {
  asm volatile("cp.reduce.async.bulk.global.shared::cta.bulk_group.add.f32 [%0], [%1], %2;" ::"l"(dst), "r"(src), "r"(bytes) : "memory");
}
__device__ __forceinline__ void bulk_commit() { asm volatile("cp.async.bulk.commit_group;" ::: "memory"); }
__device__ __forceinline__ void bulk_wait_all() { asm volatile("cp.async.bulk.wait_group 0;" ::: "memory"); }
__device__ __forceinline__ void fence_async_smem() { asm volatile("fence.proxy.async.shared::cta;" ::: "memory"); }
__device__ __forceinline__ void fence_async_global() { asm volatile("fence.proxy.async.global;" ::: "memory"); }
__device__ __forceinline__ void bar_sync(int id, int n) { asm volatile("bar.sync %0, %1;" ::"r"(id), "r"(n) : "memory"); }
__device__ __forceinline__ void bar_arrive(int id, int n) { asm volatile("bar.arrive %0, %1;" ::"r"(id), "r"(n) : "memory"); }
__device__ __forceinline__ bool bar_or(int id, int n, bool v) {
  uint32_t r;
  asm volatile("{\n.reg .pred p, q;\nsetp.ne.u32 q, %3, 0;\nbar.red.or.pred p, %1, %2, q;\nselp.u32 %0, 1, 0, p;\n}" : "=r"(r) : "r"(id), "r"(n), "r"((uint32_t)v) : "memory");
  return r != 0;
}
__device__ __forceinline__ void bulk_wait_read() { asm volatile("cp.async.bulk.wait_group.read 0;" ::: "memory"); }
__device__ __forceinline__ void stg128(void* p, uint4 v) { asm volatile("st.relaxed.gpu.global.v4.u32 [%0], {%1,%2,%3,%4};" ::"l"(p), "r"(v.x), "r"(v.y), "r"(v.z), "r"(v.w) : "memory"); }
constexpr uint32_t UNSET = 0xffffffffu;
constexpr int MAX_RETRY = 1 << 16;
__device__ __forceinline__ void wg_fence() { asm volatile("wgmma.fence.sync.aligned;" ::: "memory"); }
__device__ __forceinline__ void wg_commit() { asm volatile("wgmma.commit_group.sync.aligned;" ::: "memory"); }
template <int N> __device__ __forceinline__ void wg_wait() { asm volatile("wgmma.wait_group.sync.aligned %0;" ::"n"(N) : "memory"); }
__device__ __forceinline__ uint64_t mkdesc(uint32_t addr, uint32_t lbo, uint32_t sbo, int sw) {
  return (uint64_t)((addr & 0x3FFFF) >> 4) | ((uint64_t)(lbo >> 4) << 16) | ((uint64_t)(sbo >> 4) << 32) | ((uint64_t)sw << 62);
}
__device__ __forceinline__ void ldsm4(uint32_t* r, uint32_t a) {
  asm volatile("ldmatrix.sync.aligned.m8n8.x4.shared.b16 {%0,%1,%2,%3}, [%4];" : "=r"(r[0]), "=r"(r[1]), "=r"(r[2]), "=r"(r[3]) : "r"(a) : "memory");
}
__device__ __forceinline__ void ldsm4t(uint32_t* r, uint32_t a) {
  asm volatile("ldmatrix.sync.aligned.m8n8.x4.trans.shared.b16 {%0,%1,%2,%3}, [%4];" : "=r"(r[0]), "=r"(r[1]), "=r"(r[2]), "=r"(r[3]) : "r"(a) : "memory");
}
__device__ __forceinline__ void stsm4(uint32_t a, uint32_t r0, uint32_t r1, uint32_t r2, uint32_t r3) {
  asm volatile("stmatrix.sync.aligned.m8n8.x4.shared.b16 [%0], {%1,%2,%3,%4};" ::"r"(a), "r"(r0), "r"(r1), "r"(r2), "r"(r3) : "memory");
}
__device__ __forceinline__ void stsm4t(uint32_t a, uint32_t r0, uint32_t r1, uint32_t r2, uint32_t r3) {
  asm volatile("stmatrix.sync.aligned.m8n8.x4.trans.shared.b16 [%0], {%1,%2,%3,%4};" ::"r"(a), "r"(r0), "r"(r1), "r"(r2), "r"(r3) : "memory");
}
__device__ __forceinline__ uint32_t movm_t(uint32_t a) { uint32_t r; asm volatile("movmatrix.sync.aligned.m8n8.trans.b16 %0, %1;" : "=r"(r) : "r"(a)); return r; }
__device__ __forceinline__ uint32_t lds32(uint32_t a) { uint32_t v; asm volatile("ld.shared.b32 %0, [%1];" : "=r"(v) : "r"(a) : "memory"); return v; }
__device__ __forceinline__ float2 lds64f(uint32_t a) { float2 v; asm volatile("ld.shared.v2.f32 {%0,%1}, [%2];" : "=f"(v.x), "=f"(v.y) : "r"(a) : "memory"); return v; }
__device__ __forceinline__ float4 lds128f(uint32_t a) { float4 v; asm volatile("ld.shared.v4.f32 {%0,%1,%2,%3}, [%4];" : "=f"(v.x), "=f"(v.y), "=f"(v.z), "=f"(v.w) : "r"(a) : "memory"); return v; }
__device__ __forceinline__ uint4 lds128(uint32_t a) { uint4 v; asm volatile("ld.shared.v4.b32 {%0,%1,%2,%3}, [%4];" : "=r"(v.x), "=r"(v.y), "=r"(v.z), "=r"(v.w) : "r"(a) : "memory"); return v; }
__device__ __forceinline__ void sts128(uint32_t a, uint4 v) { asm volatile("st.shared.v4.b32 [%0], {%1,%2,%3,%4};" ::"r"(a), "r"(v.x), "r"(v.y), "r"(v.z), "r"(v.w) : "memory"); }
__device__ __forceinline__ void sts128f(uint32_t a, float x, float y, float z, float w) { asm volatile("st.shared.v4.f32 [%0], {%1,%2,%3,%4};" ::"r"(a), "f"(x), "f"(y), "f"(z), "f"(w) : "memory"); }
__device__ __forceinline__ void sts32f(uint32_t a, float v) { asm volatile("st.shared.f32 [%0], %1;" ::"r"(a), "f"(v) : "memory"); }
__device__ __forceinline__ void sts16(uint32_t a, uint16_t v) { asm volatile("st.shared.u16 [%0], %1;" ::"r"(a), "h"(v) : "memory"); }
__device__ __forceinline__ uint32_t lds16(uint32_t a) { uint16_t v; asm volatile("ld.shared.u16 %0, [%1];" : "=h"(v) : "r"(a) : "memory"); return v; }
__device__ __forceinline__ uint32_t packbf(float lo, float hi) { uint32_t r; asm("cvt.rn.bf16x2.f32 %0, %1, %2;" : "=r"(r) : "f"(hi), "f"(lo)); return r; }
__device__ __forceinline__ float bf_lo(uint32_t v) { return __uint_as_float(v << 16); }
__device__ __forceinline__ float bf_hi(uint32_t v) { return __uint_as_float(v & 0xffff0000u); }
__device__ __forceinline__ float ex2(float x) { float r; asm("ex2.approx.ftz.f32 %0, %1;" : "=f"(r) : "f"(x)); return r; }
__device__ __forceinline__ float rsqrt_approx(float x) { float r; asm("rsqrt.approx.ftz.f32 %0, %1;" : "=f"(r) : "f"(x)); return r; }
__device__ __forceinline__ float rcp_approx(float x) { float r; asm("rcp.approx.ftz.f32 %0, %1;" : "=f"(r) : "f"(x)); return r; }
__device__ __forceinline__ void mma_bf16(float* d, const uint32_t* a, uint32_t b0, uint32_t b1) {
  asm("mma.sync.aligned.m16n8k16.row.col.f32.bf16.bf16.f32 {%0,%1,%2,%3}, {%4,%5,%6,%7}, {%8,%9}, {%0,%1,%2,%3};"
               : "+f"(d[0]), "+f"(d[1]), "+f"(d[2]), "+f"(d[3]) : "r"(a[0]), "r"(a[1]), "r"(a[2]), "r"(a[3]), "r"(b0), "r"(b1));
}
__device__ __forceinline__ void mma_tf32(float* d, float a0, float a1, float a2, float a3, float b0, float b1) {
  asm("mma.sync.aligned.m16n8k8.row.col.f32.tf32.tf32.f32 {%0,%1,%2,%3}, {%4,%5,%6,%7}, {%8,%9}, {%0,%1,%2,%3};"
               : "+f"(d[0]), "+f"(d[1]), "+f"(d[2]), "+f"(d[3])
               : "r"(__float_as_uint(a0)), "r"(__float_as_uint(a1)), "r"(__float_as_uint(a2)), "r"(__float_as_uint(a3)),
                 "r"(__float_as_uint(b0)), "r"(__float_as_uint(b1)));
}
__device__ __forceinline__ void red_release(unsigned* p) { asm volatile("red.release.gpu.global.add.u32 [%0], 1;" ::"l"(p) : "memory"); }
__device__ __forceinline__ void red_relaxed(unsigned* p) { asm volatile("red.relaxed.gpu.global.add.u32 [%0], 1;" ::"l"(p) : "memory"); }
__device__ __forceinline__ unsigned ld_relaxed(const unsigned* p) { unsigned v; asm volatile("ld.relaxed.gpu.global.u32 %0, [%1];" : "=r"(v) : "l"(p) : "memory"); return v; }
__device__ __forceinline__ void spin_until(const unsigned* p, unsigned target) {
  int it = 0;
  while ((int)(ld_relaxed(p) - target) < 0) {
    if (++it > (1 << 23)) __trap();
  }
}
__device__ __forceinline__ uint4 ldcg128(const void* p) { uint4 v; asm volatile("ld.global.cg.v4.b32 {%0,%1,%2,%3}, [%4];" : "=r"(v.x), "=r"(v.y), "=r"(v.z), "=r"(v.w) : "l"(p) : "memory"); return v; }
__device__ __forceinline__ uint4 ld_tagged(const uint4* p) { uint4 v; asm volatile("ld.relaxed.gpu.global.v4.u32 {%0,%1,%2,%3}, [%4];" : "=r"(v.x), "=r"(v.y), "=r"(v.z), "=r"(v.w) : "l"(p) : "memory"); return v; }
__device__ __forceinline__ void st_tagged(uint4* p, uint32_t a, uint32_t b, uint32_t tag) { asm volatile("st.relaxed.gpu.global.v4.u32 [%0], {%1,%2,%3,%2};" ::"l"(p), "r"(a), "r"(tag), "r"(b) : "memory"); }
__device__ __forceinline__ void st_tagged3(uint4* p, uint32_t a, uint32_t b, uint32_t c, uint32_t tag) { asm volatile("st.relaxed.gpu.global.v4.u32 [%0], {%1,%2,%3,%4};" ::"l"(p), "r"(a), "r"(b), "r"(c), "r"(tag) : "memory"); }
__device__ __forceinline__ uint4 poll_tagged(const uint4* p, uint32_t tag) {
  uint4 v = ld_tagged(p);
  int it = 0;
  while (v.y != tag || v.w != tag) {
    if (++it > (1 << 22)) __trap();
    v = ld_tagged(p);
  }
  return v;
}
__device__ __forceinline__ uint32_t hadd2(uint32_t a, uint32_t b) { uint32_t r; asm("add.rn.bf16x2 %0, %1, %2;" : "=r"(r) : "r"(a), "r"(b)); return r; }
__device__ __forceinline__ uint32_t hmul2(uint32_t a, uint32_t b) { uint32_t r; asm("mul.rn.bf16x2 %0, %1, %2;" : "=r"(r) : "r"(a), "r"(b)); return r; }

__device__ __forceinline__ uint32_t hfma2(uint32_t a, uint32_t b, uint32_t c) { uint32_t r; asm("fma.rn.bf16x2 %0, %1, %2, %3;" : "=r"(r) : "r"(a), "r"(b), "r"(c)); return r; }
__device__ __forceinline__ void sts32(uint32_t a, uint32_t v) { asm volatile("st.shared.u32 [%0], %1;" ::"r"(a), "r"(v) : "memory"); }

template <int N> __device__ __forceinline__ void acc_fence(float* a) {
#pragma unroll
  for (int i = 0; i < N; i++) asm volatile("" : "+f"(a[i]) :: "memory");
}

template<int N,int TB> __device__ __forceinline__ void wgmma_rs(float* d, const uint32_t* a, uint64_t db, int sd);
template<int N,int TA,int TB> __device__ __forceinline__ void wgmma_ss(float* d, uint64_t da, uint64_t db, int sd);
template<> __device__ __forceinline__ void wgmma_rs<64,0>(float* d, const uint32_t* a, uint64_t db, int sd) {
  asm volatile("{\n.reg .pred p;\nsetp.ne.b32 p, %37, 0;\nwgmma.mma_async.sync.aligned.m64n64k16.f32.bf16.bf16 {%0,%1,%2,%3,%4,%5,%6,%7,%8,%9,%10,%11,%12,%13,%14,%15,%16,%17,%18,%19,%20,%21,%22,%23,%24,%25,%26,%27,%28,%29,%30,%31}, {%32,%33,%34,%35}, %36, p, 1, 1, 0;\n}\n"
   : "+f"(d[0]),"+f"(d[1]),"+f"(d[2]),"+f"(d[3]),"+f"(d[4]),"+f"(d[5]),"+f"(d[6]),"+f"(d[7]),"+f"(d[8]),"+f"(d[9]),"+f"(d[10]),"+f"(d[11]),"+f"(d[12]),"+f"(d[13]),"+f"(d[14]),"+f"(d[15]),"+f"(d[16]),"+f"(d[17]),"+f"(d[18]),"+f"(d[19]),"+f"(d[20]),"+f"(d[21]),"+f"(d[22]),"+f"(d[23]),"+f"(d[24]),"+f"(d[25]),"+f"(d[26]),"+f"(d[27]),"+f"(d[28]),"+f"(d[29]),"+f"(d[30]),"+f"(d[31])
   : "r"(a[0]), "r"(a[1]), "r"(a[2]), "r"(a[3]), "l"(db), "r"(sd));
}
template<> __device__ __forceinline__ void wgmma_rs<56,0>(float* d, const uint32_t* a, uint64_t db, int sd) {
  asm volatile("{\n.reg .pred p;\nsetp.ne.b32 p, %33, 0;\nwgmma.mma_async.sync.aligned.m64n56k16.f32.bf16.bf16 {%0,%1,%2,%3,%4,%5,%6,%7,%8,%9,%10,%11,%12,%13,%14,%15,%16,%17,%18,%19,%20,%21,%22,%23,%24,%25,%26,%27}, {%28,%29,%30,%31}, %32, p, 1, 1, 0;\n}\n"
   : "+f"(d[0]),"+f"(d[1]),"+f"(d[2]),"+f"(d[3]),"+f"(d[4]),"+f"(d[5]),"+f"(d[6]),"+f"(d[7]),"+f"(d[8]),"+f"(d[9]),"+f"(d[10]),"+f"(d[11]),"+f"(d[12]),"+f"(d[13]),"+f"(d[14]),"+f"(d[15]),"+f"(d[16]),"+f"(d[17]),"+f"(d[18]),"+f"(d[19]),"+f"(d[20]),"+f"(d[21]),"+f"(d[22]),"+f"(d[23]),"+f"(d[24]),"+f"(d[25]),"+f"(d[26]),"+f"(d[27])
   : "r"(a[0]), "r"(a[1]), "r"(a[2]), "r"(a[3]), "l"(db), "r"(sd));
}
template<> __device__ __forceinline__ void wgmma_rs<48,0>(float* d, const uint32_t* a, uint64_t db, int sd) {
  asm volatile("{\n.reg .pred p;\nsetp.ne.b32 p, %29, 0;\nwgmma.mma_async.sync.aligned.m64n48k16.f32.bf16.bf16 {%0,%1,%2,%3,%4,%5,%6,%7,%8,%9,%10,%11,%12,%13,%14,%15,%16,%17,%18,%19,%20,%21,%22,%23}, {%24,%25,%26,%27}, %28, p, 1, 1, 0;\n}\n"
   : "+f"(d[0]),"+f"(d[1]),"+f"(d[2]),"+f"(d[3]),"+f"(d[4]),"+f"(d[5]),"+f"(d[6]),"+f"(d[7]),"+f"(d[8]),"+f"(d[9]),"+f"(d[10]),"+f"(d[11]),"+f"(d[12]),"+f"(d[13]),"+f"(d[14]),"+f"(d[15]),"+f"(d[16]),"+f"(d[17]),"+f"(d[18]),"+f"(d[19]),"+f"(d[20]),"+f"(d[21]),"+f"(d[22]),"+f"(d[23])
   : "r"(a[0]), "r"(a[1]), "r"(a[2]), "r"(a[3]), "l"(db), "r"(sd));
}
template<> __device__ __forceinline__ void wgmma_rs<40,0>(float* d, const uint32_t* a, uint64_t db, int sd) {
  asm volatile("{\n.reg .pred p;\nsetp.ne.b32 p, %25, 0;\nwgmma.mma_async.sync.aligned.m64n40k16.f32.bf16.bf16 {%0,%1,%2,%3,%4,%5,%6,%7,%8,%9,%10,%11,%12,%13,%14,%15,%16,%17,%18,%19}, {%20,%21,%22,%23}, %24, p, 1, 1, 0;\n}\n"
   : "+f"(d[0]),"+f"(d[1]),"+f"(d[2]),"+f"(d[3]),"+f"(d[4]),"+f"(d[5]),"+f"(d[6]),"+f"(d[7]),"+f"(d[8]),"+f"(d[9]),"+f"(d[10]),"+f"(d[11]),"+f"(d[12]),"+f"(d[13]),"+f"(d[14]),"+f"(d[15]),"+f"(d[16]),"+f"(d[17]),"+f"(d[18]),"+f"(d[19])
   : "r"(a[0]), "r"(a[1]), "r"(a[2]), "r"(a[3]), "l"(db), "r"(sd));
}
template<> __device__ __forceinline__ void wgmma_rs<32,0>(float* d, const uint32_t* a, uint64_t db, int sd) {
  asm volatile("{\n.reg .pred p;\nsetp.ne.b32 p, %21, 0;\nwgmma.mma_async.sync.aligned.m64n32k16.f32.bf16.bf16 {%0,%1,%2,%3,%4,%5,%6,%7,%8,%9,%10,%11,%12,%13,%14,%15}, {%16,%17,%18,%19}, %20, p, 1, 1, 0;\n}\n"
   : "+f"(d[0]),"+f"(d[1]),"+f"(d[2]),"+f"(d[3]),"+f"(d[4]),"+f"(d[5]),"+f"(d[6]),"+f"(d[7]),"+f"(d[8]),"+f"(d[9]),"+f"(d[10]),"+f"(d[11]),"+f"(d[12]),"+f"(d[13]),"+f"(d[14]),"+f"(d[15])
   : "r"(a[0]), "r"(a[1]), "r"(a[2]), "r"(a[3]), "l"(db), "r"(sd));
}
template<> __device__ __forceinline__ void wgmma_rs<24,0>(float* d, const uint32_t* a, uint64_t db, int sd) {
  asm volatile("{\n.reg .pred p;\nsetp.ne.b32 p, %17, 0;\nwgmma.mma_async.sync.aligned.m64n24k16.f32.bf16.bf16 {%0,%1,%2,%3,%4,%5,%6,%7,%8,%9,%10,%11}, {%12,%13,%14,%15}, %16, p, 1, 1, 0;\n}\n"
   : "+f"(d[0]),"+f"(d[1]),"+f"(d[2]),"+f"(d[3]),"+f"(d[4]),"+f"(d[5]),"+f"(d[6]),"+f"(d[7]),"+f"(d[8]),"+f"(d[9]),"+f"(d[10]),"+f"(d[11])
   : "r"(a[0]), "r"(a[1]), "r"(a[2]), "r"(a[3]), "l"(db), "r"(sd));
}
template<> __device__ __forceinline__ void wgmma_rs<16,0>(float* d, const uint32_t* a, uint64_t db, int sd) {
  asm volatile("{\n.reg .pred p;\nsetp.ne.b32 p, %13, 0;\nwgmma.mma_async.sync.aligned.m64n16k16.f32.bf16.bf16 {%0,%1,%2,%3,%4,%5,%6,%7}, {%8,%9,%10,%11}, %12, p, 1, 1, 0;\n}\n"
   : "+f"(d[0]),"+f"(d[1]),"+f"(d[2]),"+f"(d[3]),"+f"(d[4]),"+f"(d[5]),"+f"(d[6]),"+f"(d[7])
   : "r"(a[0]), "r"(a[1]), "r"(a[2]), "r"(a[3]), "l"(db), "r"(sd));
}
template<> __device__ __forceinline__ void wgmma_rs<8,0>(float* d, const uint32_t* a, uint64_t db, int sd) {
  asm volatile("{\n.reg .pred p;\nsetp.ne.b32 p, %9, 0;\nwgmma.mma_async.sync.aligned.m64n8k16.f32.bf16.bf16 {%0,%1,%2,%3}, {%4,%5,%6,%7}, %8, p, 1, 1, 0;\n}\n"
   : "+f"(d[0]),"+f"(d[1]),"+f"(d[2]),"+f"(d[3])
   : "r"(a[0]), "r"(a[1]), "r"(a[2]), "r"(a[3]), "l"(db), "r"(sd));
}
template<> __device__ __forceinline__ void wgmma_ss<16,0,1>(float* d, uint64_t da, uint64_t db, int sd) {
  asm volatile("{\n.reg .pred p;\nsetp.ne.b32 p, %10, 0;\nwgmma.mma_async.sync.aligned.m64n16k16.f32.bf16.bf16 {%0,%1,%2,%3,%4,%5,%6,%7}, %8, %9, p, 1, 1, 0, 1;\n}\n"
   : "+f"(d[0]),"+f"(d[1]),"+f"(d[2]),"+f"(d[3]),"+f"(d[4]),"+f"(d[5]),"+f"(d[6]),"+f"(d[7])
   : "l"(da), "l"(db), "r"(sd));
}
template<> __device__ __forceinline__ void wgmma_ss<64,0,1>(float* d, uint64_t da, uint64_t db, int sd) {
  asm volatile("{\n.reg .pred p;\nsetp.ne.b32 p, %34, 0;\nwgmma.mma_async.sync.aligned.m64n64k16.f32.bf16.bf16 {%0,%1,%2,%3,%4,%5,%6,%7,%8,%9,%10,%11,%12,%13,%14,%15,%16,%17,%18,%19,%20,%21,%22,%23,%24,%25,%26,%27,%28,%29,%30,%31}, %32, %33, p, 1, 1, 0, 1;\n}\n"
   : "+f"(d[0]),"+f"(d[1]),"+f"(d[2]),"+f"(d[3]),"+f"(d[4]),"+f"(d[5]),"+f"(d[6]),"+f"(d[7]),"+f"(d[8]),"+f"(d[9]),"+f"(d[10]),"+f"(d[11]),"+f"(d[12]),"+f"(d[13]),"+f"(d[14]),"+f"(d[15]),"+f"(d[16]),"+f"(d[17]),"+f"(d[18]),"+f"(d[19]),"+f"(d[20]),"+f"(d[21]),"+f"(d[22]),"+f"(d[23]),"+f"(d[24]),"+f"(d[25]),"+f"(d[26]),"+f"(d[27]),"+f"(d[28]),"+f"(d[29]),"+f"(d[30]),"+f"(d[31])
   : "l"(da), "l"(db), "r"(sd));
}
template<> __device__ __forceinline__ void wgmma_ss<192,0,1>(float* d, uint64_t da, uint64_t db, int sd) {
  asm volatile("{\n.reg .pred p;\nsetp.ne.b32 p, %98, 0;\nwgmma.mma_async.sync.aligned.m64n192k16.f32.bf16.bf16 {%0,%1,%2,%3,%4,%5,%6,%7,%8,%9,%10,%11,%12,%13,%14,%15,%16,%17,%18,%19,%20,%21,%22,%23,%24,%25,%26,%27,%28,%29,%30,%31,%32,%33,%34,%35,%36,%37,%38,%39,%40,%41,%42,%43,%44,%45,%46,%47,%48,%49,%50,%51,%52,%53,%54,%55,%56,%57,%58,%59,%60,%61,%62,%63,%64,%65,%66,%67,%68,%69,%70,%71,%72,%73,%74,%75,%76,%77,%78,%79,%80,%81,%82,%83,%84,%85,%86,%87,%88,%89,%90,%91,%92,%93,%94,%95}, %96, %97, p, 1, 1, 0, 1;\n}\n"
   : "+f"(d[0]),"+f"(d[1]),"+f"(d[2]),"+f"(d[3]),"+f"(d[4]),"+f"(d[5]),"+f"(d[6]),"+f"(d[7]),"+f"(d[8]),"+f"(d[9]),"+f"(d[10]),"+f"(d[11]),"+f"(d[12]),"+f"(d[13]),"+f"(d[14]),"+f"(d[15]),"+f"(d[16]),"+f"(d[17]),"+f"(d[18]),"+f"(d[19]),"+f"(d[20]),"+f"(d[21]),"+f"(d[22]),"+f"(d[23]),"+f"(d[24]),"+f"(d[25]),"+f"(d[26]),"+f"(d[27]),"+f"(d[28]),"+f"(d[29]),"+f"(d[30]),"+f"(d[31]),"+f"(d[32]),"+f"(d[33]),"+f"(d[34]),"+f"(d[35]),"+f"(d[36]),"+f"(d[37]),"+f"(d[38]),"+f"(d[39]),"+f"(d[40]),"+f"(d[41]),"+f"(d[42]),"+f"(d[43]),"+f"(d[44]),"+f"(d[45]),"+f"(d[46]),"+f"(d[47]),"+f"(d[48]),"+f"(d[49]),"+f"(d[50]),"+f"(d[51]),"+f"(d[52]),"+f"(d[53]),"+f"(d[54]),"+f"(d[55]),"+f"(d[56]),"+f"(d[57]),"+f"(d[58]),"+f"(d[59]),"+f"(d[60]),"+f"(d[61]),"+f"(d[62]),"+f"(d[63]),"+f"(d[64]),"+f"(d[65]),"+f"(d[66]),"+f"(d[67]),"+f"(d[68]),"+f"(d[69]),"+f"(d[70]),"+f"(d[71]),"+f"(d[72]),"+f"(d[73]),"+f"(d[74]),"+f"(d[75]),"+f"(d[76]),"+f"(d[77]),"+f"(d[78]),"+f"(d[79]),"+f"(d[80]),"+f"(d[81]),"+f"(d[82]),"+f"(d[83]),"+f"(d[84]),"+f"(d[85]),"+f"(d[86]),"+f"(d[87]),"+f"(d[88]),"+f"(d[89]),"+f"(d[90]),"+f"(d[91]),"+f"(d[92]),"+f"(d[93]),"+f"(d[94]),"+f"(d[95])
   : "l"(da), "l"(db), "r"(sd));
}
template<> __device__ __forceinline__ void wgmma_ss<192,1,1>(float* d, uint64_t da, uint64_t db, int sd) {
  asm volatile("{\n.reg .pred p;\nsetp.ne.b32 p, %98, 0;\nwgmma.mma_async.sync.aligned.m64n192k16.f32.bf16.bf16 {%0,%1,%2,%3,%4,%5,%6,%7,%8,%9,%10,%11,%12,%13,%14,%15,%16,%17,%18,%19,%20,%21,%22,%23,%24,%25,%26,%27,%28,%29,%30,%31,%32,%33,%34,%35,%36,%37,%38,%39,%40,%41,%42,%43,%44,%45,%46,%47,%48,%49,%50,%51,%52,%53,%54,%55,%56,%57,%58,%59,%60,%61,%62,%63,%64,%65,%66,%67,%68,%69,%70,%71,%72,%73,%74,%75,%76,%77,%78,%79,%80,%81,%82,%83,%84,%85,%86,%87,%88,%89,%90,%91,%92,%93,%94,%95}, %96, %97, p, 1, 1, 1, 1;\n}\n"
   : "+f"(d[0]),"+f"(d[1]),"+f"(d[2]),"+f"(d[3]),"+f"(d[4]),"+f"(d[5]),"+f"(d[6]),"+f"(d[7]),"+f"(d[8]),"+f"(d[9]),"+f"(d[10]),"+f"(d[11]),"+f"(d[12]),"+f"(d[13]),"+f"(d[14]),"+f"(d[15]),"+f"(d[16]),"+f"(d[17]),"+f"(d[18]),"+f"(d[19]),"+f"(d[20]),"+f"(d[21]),"+f"(d[22]),"+f"(d[23]),"+f"(d[24]),"+f"(d[25]),"+f"(d[26]),"+f"(d[27]),"+f"(d[28]),"+f"(d[29]),"+f"(d[30]),"+f"(d[31]),"+f"(d[32]),"+f"(d[33]),"+f"(d[34]),"+f"(d[35]),"+f"(d[36]),"+f"(d[37]),"+f"(d[38]),"+f"(d[39]),"+f"(d[40]),"+f"(d[41]),"+f"(d[42]),"+f"(d[43]),"+f"(d[44]),"+f"(d[45]),"+f"(d[46]),"+f"(d[47]),"+f"(d[48]),"+f"(d[49]),"+f"(d[50]),"+f"(d[51]),"+f"(d[52]),"+f"(d[53]),"+f"(d[54]),"+f"(d[55]),"+f"(d[56]),"+f"(d[57]),"+f"(d[58]),"+f"(d[59]),"+f"(d[60]),"+f"(d[61]),"+f"(d[62]),"+f"(d[63]),"+f"(d[64]),"+f"(d[65]),"+f"(d[66]),"+f"(d[67]),"+f"(d[68]),"+f"(d[69]),"+f"(d[70]),"+f"(d[71]),"+f"(d[72]),"+f"(d[73]),"+f"(d[74]),"+f"(d[75]),"+f"(d[76]),"+f"(d[77]),"+f"(d[78]),"+f"(d[79]),"+f"(d[80]),"+f"(d[81]),"+f"(d[82]),"+f"(d[83]),"+f"(d[84]),"+f"(d[85]),"+f"(d[86]),"+f"(d[87]),"+f"(d[88]),"+f"(d[89]),"+f"(d[90]),"+f"(d[91]),"+f"(d[92]),"+f"(d[93]),"+f"(d[94]),"+f"(d[95])
   : "l"(da), "l"(db), "r"(sd));
}

#define HINT_P 0
template <bool TR>
__device__ __forceinline__ void gemm_section(float* acc, float& mean0, float& mean1, float& rstd0, float& rstd1,
                                             uint32_t sb, int blk, int hg, int wg, int w, int lane) {
  constexpr int layer = TR ? 1 : 0;
  constexpr int TURN = TR ? TURN1 : TURN0;
  constexpr int LSTAT = TURN < 4 ? TURN - 1 : 3;
  const uint32_t bar = sb + SM_BAR;
  const int g = lane >> 2, t = lane & 3;
  const bool leader = (w == 0) && (lane == 0);
  const int statpos = hg < 3 ? 1 : wg ? LSTAT : 2;
  const bool copy = hg >= 3 && wg == 0;
  const int cut = wg ? TURN : 4;
  auto wait_full = [&](int c) {
    mbar_wait(bar + 8 * (B_XF + 8 * wg + c), layer);
    mbar_wait(bar + 8 * (B_WF + c), layer);
  };
  auto peek = [&](int c) {
    const bool x = mbar_test(bar + 8 * (B_XF + 8 * wg + c), layer), y = mbar_test(bar + 8 * (B_WF + c), layer);
    return x && y;
  };
  const uint64_t da0 = mkdesc(sb, TR ? 8192 : 16, 1024, 1), db0 = mkdesc(sb, 8192, 1024, 1);
  uint32_t xt = wg ? 0xfedcba98u : 0x21043210u;
  uint64_t wt = 0x0816131005161310ull;
  uint64_t da = da0 + ((xt & 15) << 9), db = db0 + (16 << 9);
  auto issue = [&](int c, int first) {
    TSG(2 * c);
    wg_fence();
#pragma unroll
    for (int ks = 0; ks < 4; ks++) wgmma_ss<192, TR ? 1 : 0, 1>(acc, da + (TR ? ks * 128 : ks * 2), db + ks * 128, !first || ks != 0);
    wg_commit();
    xt >>= 4; wt >>= 8;
    da = da0 + ((xt & 15) << 9); db = db0 + (((uint32_t)wt & 31) << 9);
    TSG(2 * c + 1);
  };
  uint32_t tag = 0;
  wait_full(0);
  bool ready = peek(1);
  issue(0, 1);
  TSW(0);
#pragma unroll 1
  for (int c = 1; c < cut; c++) {
    if (!ready) wait_full(c);
    issue(c, 0);
    ready = peek(c + 1);
    wg_wait<1>();
    if (leader) mbar_arrive(bar + 8 * (B_DN + 8 * wg + c - 1));
    if (wg == 1 && c == cut - 1) {
      wg_wait<0>();
      if (leader) mbar_arrive(bar + 8 * (B_DN + 8 + c));
    }
    if (c == statpos) {
      mbar_wait(bar + 8 * B_EP, 0);
      tag = 2 * lds32(sb + SM_EP) + layer + 1;
      mbar_wait(bar + 8 * (copy ? B_SC : B_XF + 8 * wg + hg), layer);
      uint32_t A[16];
      const uint32_t xb = sb + (copy ? P_R : 8 * wg + hg) * PG;
#pragma unroll
      for (int ks = 0; ks < 4; ks++) {
        if (!TR) {
          const int row = 16 * w + (lane & 15), kc = 2 * ks + (lane >> 4);
          ldsm4(&A[4 * ks], xb + row * 128 + ((kc ^ (row & 7)) << 4));
        } else {
          const int k = 16 * ks + (lane & 7) + 8 * (lane >> 4), pc = 2 * w + ((lane >> 3) & 1);
          ldsm4t(&A[4 * ks], xb + k * 128 + ((pc ^ (k & 7)) << 4));
        }
      }
      float s0 = 0.f, q0 = 0.f, s1 = 0.f, q1 = 0.f;
#pragma unroll
      for (int i = 0; i < 16; i += 2) {
        const float a = bf_lo(A[i]), b = bf_hi(A[i]), c_ = bf_lo(A[i + 1]), d = bf_hi(A[i + 1]);
        s0 += a + b; q0 = fmaf(a, a, q0); q0 = fmaf(b, b, q0);
        s1 += c_ + d; q1 = fmaf(c_, c_, q1); q1 = fmaf(d, d, q1);
      }
#pragma unroll
      for (int o = 1; o <= 2; o <<= 1) {
        s0 += __shfl_xor_sync(~0u, s0, o); q0 += __shfl_xor_sync(~0u, q0, o);
        s1 += __shfl_xor_sync(~0u, s1, o); q1 += __shfl_xor_sync(~0u, q1, o);
      }
      if (t < 2)
        st_tagged(&g_part[((layer * 32 + blk) * 8 + hg) * 64 + 16 * w + g + 8 * t], __float_as_uint(t ? s1 : s0), __float_as_uint(t ? q1 : q0), tag);
    }
  }
  if (wg == 1) mbar_wait(bar + 8 * (B_DN + GPOS), layer);
  else if (!ready) { wait_full(cut); ready = true; }
  const uint4* psrc = &g_part[((layer * 32 + blk) * 8 + 2 * t) * 64 + 16 * w + g];
  uint4 a0 = ld_tagged(psrc), a1 = ld_tagged(psrc + 8), b0 = ld_tagged(psrc + 64), b1 = ld_tagged(psrc + 72);
  if (wg == 1) {
#pragma unroll 1
    for (int c = cut; c < 8; c++) wait_full(c);
    ready = true;
    bar_sync(5, 256);
  }
#pragma unroll 1
  for (int c = cut; c < 8; c++) {
    if (!ready) wait_full(c);
    issue(c, 0);
    if (wg == 1) {
      wg_wait<2>();
      if (leader && c >= cut + 2) mbar_arrive(bar + 8 * (B_DN + 8 + c - 2));
    } else if (c == 7) {
      bar_arrive(5, 256);
    } else {
      ready = peek(c + 1);
      wg_wait<1>();
      if (leader) mbar_arrive(bar + 8 * (B_DN + c - 1));
    }
  }
  int it = 0;
  while (!__all_sync(~0u, a0.y == tag && a0.w == tag && a1.y == tag && a1.w == tag && b0.y == tag && b0.w == tag && b1.y == tag && b1.w == tag) &&
         ++it < (1 << 20)) {
    a0 = ld_tagged(psrc); a1 = ld_tagged(psrc + 8); b0 = ld_tagged(psrc + 64); b1 = ld_tagged(psrc + 72);
  }
  float s0 = __uint_as_float(a0.x) + __uint_as_float(b0.x), q0 = __uint_as_float(a0.z) + __uint_as_float(b0.z);
  float s1 = __uint_as_float(a1.x) + __uint_as_float(b1.x), q1 = __uint_as_float(a1.z) + __uint_as_float(b1.z);
#pragma unroll
  for (int o = 1; o <= 2; o <<= 1) {
    s0 += __shfl_xor_sync(~0u, s0, o); q0 += __shfl_xor_sync(~0u, q0, o);
    s1 += __shfl_xor_sync(~0u, s1, o); q1 += __shfl_xor_sync(~0u, q1, o);
  }
  mean0 = s0 * (1.f / DM); mean1 = s1 * (1.f / DM);
  rstd0 = rsqrt_approx(fmaxf(q0 * (1.f / DM) - mean0 * mean0, 0.f) + 1e-5f);
  rstd1 = rsqrt_approx(fmaxf(q1 * (1.f / DM) - mean1 * mean1, 0.f) + 1e-5f);
  TSG(16);
  mbar_wait(bar + 8 * (TR ? B_RS : B_CSF), 0);
  wg_wait<0>();
  acc_fence<96>(acc);
  if (leader) mbar_arrive(bar + 8 * (B_DN + 8 * wg + 7));
}

__device__ __forceinline__ void attn_phase(const Params& p, uint32_t sb, int layer, int rb, int hg, int wg, int w) {
  const int lane = opaque_tid() & 31;
  const int g = lane >> 2, t = lane & 3;
  const uint32_t bar = sb + SM_BAR;
  const int blk = 16 * wg + rb;
  float acc[96];
  float2 cs[24];
  float mean0, mean1, rstd0, rstd1;
  if (layer) gemm_section<true>(acc, mean0, mean1, rstd0, rstd1, sb, blk, hg, wg, w, lane);
  else gemm_section<false>(acc, mean0, mean1, rstd0, rstd1, sb, blk, hg, wg, w, lane);
  TSW(1);
#pragma unroll
  for (int j = 8; j < 24; j++) cs[j] = lds64f(sb + SM_CS + 4 * (8 * j + 2 * t));
  const uint32_t kvx = sb + (wg ? 22 : 0) * PG;

  uint32_t kb[4][8], vb[4][8], qa[4][4];
  {
    const float nm0 = -mean0 * rstd0, nm1 = -mean1 * rstd1;
    const int st_row = 16 * w + (lane & 7) + 8 * ((lane >> 3) & 1);
    const uint32_t st_base = kvx + st_row * 256;
    const bool sender = (w == 3 && blk < 31);
    uint4* halo = &g_halo[((layer * 32 + blk) * 8 + hg) * 256 + lane];
    uint32_t r[4][2][4];
#pragma unroll
    for (int h = 0; h < 4; h++) {
#pragma unroll
      for (int kv = 0; kv < 2; kv++) {
#pragma unroll
        for (int dh = 0; dh < 2; dh++) {
          const int j = 8 + kv * 8 + 2 * h + dh;
          const float2 c2 = cs[j];
          const float v0 = fmaf(acc[4 * j + 0], rstd0, nm0 * c2.x), v1 = fmaf(acc[4 * j + 1], rstd0, nm0 * c2.y);
          const float v2 = fmaf(acc[4 * j + 2], rstd1, nm1 * c2.x), v3 = fmaf(acc[4 * j + 3], rstd1, nm1 * c2.y);
          r[h][kv][2 * dh] = packbf(v0, v1);
          r[h][kv][2 * dh + 1] = packbf(v2, v3);
        }
      }
      if (sender) {
        stg128(halo + (2 * h) * 32, make_uint4(r[h][0][0], r[h][0][2], r[h][0][1], r[h][0][3]));
        stg128(halo + (2 * h + 1) * 32, make_uint4(r[h][1][0], r[h][1][1], r[h][1][2], r[h][1][3]));
      }
    }
#pragma unroll
    for (int j = 0; j < 8; j++) cs[j] = lds64f(sb + SM_CS + 4 * (8 * j + 2 * t));
    mbar_wait(bar + 8 * (B_DN + 7), layer);
#pragma unroll
    for (int h = 0; h < 4; h++) {
#pragma unroll
      for (int kv = 0; kv < 2; kv++) {
        const int chunk = 4 * h + 2 * kv + (lane >> 4);
        stsm4(st_base + (((chunk & 8) | ((chunk ^ st_row) & 7)) << 4), r[h][kv][0], r[h][kv][1], r[h][kv][2], r[h][kv][3]);
      }
      kb[h][4] = r[h][0][0]; kb[h][5] = r[h][0][2]; kb[h][6] = r[h][0][1]; kb[h][7] = r[h][0][3];
      vb[h][4] = movm_t(r[h][1][0]); vb[h][5] = movm_t(r[h][1][1]); vb[h][6] = movm_t(r[h][1][2]); vb[h][7] = movm_t(r[h][1][3]);
    }
#pragma unroll
    for (int h = 0; h < 4; h++) {
#pragma unroll
      for (int dh = 0; dh < 2; dh++) {
        const int j = 2 * h + dh;
        const float2 c2 = cs[j];
        qa[h][2 * dh] = packbf(fmaf(-mean0, c2.x, acc[4 * j + 0]), fmaf(-mean0, c2.y, acc[4 * j + 1]));
        qa[h][2 * dh + 1] = packbf(fmaf(-mean1, c2.x, acc[4 * j + 2]), fmaf(-mean1, c2.y, acc[4 * j + 3]));
      }
    }
  }
  bar_sync(2 + wg, 128);
  TSW(2);
  {
    const uint32_t prev_base = kvx + (16 * w - 16) * 256;
    const int mi = lane >> 3;
    const int r = 8 * (mi >> 1) + (lane & 7), r2 = 8 * (mi & 1) + (lane & 7);
    if (w != 0) {
#pragma unroll
      for (int h = 0; h < 4; h++) {
        const int ch = 4 * h + (mi & 1), ch2 = 4 * h + 2 + (mi >> 1);
        ldsm4(&kb[h][0], prev_base + r * 256 + (((ch & 8) | ((ch ^ r) & 7)) << 4));
        ldsm4t(&vb[h][0], prev_base + r2 * 256 + (((ch2 & 8) | ((ch2 ^ r2) & 7)) << 4));
      }
    } else if (blk > 0) {
      const uint4* src = &g_halo[((layer * 32 + blk - 1) * 8 + hg) * 256 + lane];
      uint4 hv[8];
      int it = 0;
      bool ok;
      do {
        ok = true;
#pragma unroll
        for (int i = 0; i < 8; i++) hv[i] = ld_tagged(src + i * 32);
#pragma unroll
        for (int i = 0; i < 8; i++) ok = ok && hv[i].x != UNSET;
      } while (!__all_sync(~0u, ok) && ++it < (1 << 20));
#pragma unroll
      for (int h = 0; h < 4; h++) {
        kb[h][0] = hv[2 * h].x; kb[h][1] = hv[2 * h].y; kb[h][2] = hv[2 * h].z; kb[h][3] = hv[2 * h].w;
        vb[h][0] = movm_t(hv[2 * h + 1].x); vb[h][1] = movm_t(hv[2 * h + 1].y);
        vb[h][2] = movm_t(hv[2 * h + 1].z); vb[h][3] = movm_t(hv[2 * h + 1].w);
      }
    } else {
#pragma unroll
      for (int h = 0; h < 4; h++)
#pragma unroll
        for (int k = 0; k < 4; k++) kb[h][k] = vb[h][k] = 0u;
    }
    TSW(3);
  }
  mbar_wait(bar + 8 * (B_DN + 15), layer);
  TSW(4);

  const bool first = (blk == 0 && w == 0);
  const int e = t - (g >> 1);
  const bool par = g & 1, epos = e >= 1;
  const uint32_t pmask = par ? 0xffff0000u : 0x0000ffffu;
  const uint32_t mB0 = epos ? pmask : 0u, mB1 = epos ? 0u : pmask;
  const float cl2 = 0.25f * 1.4426950408889634f;
  const float sc0 = rstd0 * cl2, sc1 = rstd1 * cl2;
  const float NEG = -INFINITY;
  float vA0[4], vB0[4], vA1[4], vB1[4];
#pragma unroll
  for (int h = 0; h < 4; h++) {
    float S[4][4];
#pragma unroll
    for (int j = 0; j < 4; j++) {
      S[j][0] = S[j][1] = S[j][2] = S[j][3] = 0.f;
      mma_bf16(S[j], qa[h], kb[h][2 * j], kb[h][2 * j + 1]);
    }
    vA0[h] = par ? S[1][1] : S[1][0];
    vB0[h] = epos ? (par ? S[0][1] : S[0][0]) : (par ? S[2][1] : S[2][0]);
    vA1[h] = par ? S[2][3] : S[2][2];
    vB1[h] = epos ? (par ? S[1][3] : S[1][2]) : (par ? S[3][3] : S[3][2]);
    if (first) { vA0[h] = NEG; if (epos) { vB0[h] = NEG; vB1[h] = NEG; } }
  }
  float m0[4], m1[4];
#pragma unroll
  for (int h = 0; h < 4; h++) { m0[h] = fmaxf(vA0[h], vB0[h]); m1[h] = fmaxf(vA1[h], vB1[h]); }
#pragma unroll
  for (int o = 1; o <= 2; o <<= 1) {
#pragma unroll
    for (int h = 0; h < 4; h++) {
      m0[h] = fmaxf(m0[h], __shfl_xor_sync(~0u, m0[h], o));
      m1[h] = fmaxf(m1[h], __shfl_xor_sync(~0u, m1[h], o));
    }
  }
  float O0[4][4], O1[4][4], Z[4][4];
#pragma unroll
  for (int h = 0; h < 4; h++) {
    const float mm0 = -m0[h] * sc0, mm1 = -m1[h] * sc1;
    const float pA0 = ex2(fmaf(vA0[h], sc0, mm0)), pB0 = ex2(fmaf(vB0[h], sc0, mm0));
    const float pA1 = ex2(fmaf(vA1[h], sc1, mm1)), pB1 = ex2(fmaf(vB1[h], sc1, mm1));
    const uint32_t hA0 = packbf(pA0, pA0), hB0 = packbf(pB0, pB0), hA1 = packbf(pA1, pA1), hB1 = packbf(pB1, pB1);
    const uint32_t P0[4] = {hB0 & mB0, 0u, hA0 & pmask, hB1 & mB0};
    const uint32_t P1[4] = {hB0 & mB1, hA1 & pmask, 0u, hB1 & mB1};
#pragma unroll
    for (int k = 0; k < 4; k++) O0[h][k] = O1[h][k] = Z[h][k] = 0.f;
    mma_bf16(O0[h], P0, vb[h][0], vb[h][1]); mma_bf16(O1[h], P0, vb[h][2], vb[h][3]); mma_bf16(Z[h], P0, 0x3f803f80u, 0x3f803f80u);
    mma_bf16(O0[h], P1, vb[h][4], vb[h][5]); mma_bf16(O1[h], P1, vb[h][6], vb[h][7]); mma_bf16(Z[h], P1, 0x3f803f80u, 0x3f803f80u);
  }
  if (lane == 0) mbar_arrive(bar + 8 * (B_OST + wg));
  uint4* op = (uint4*)g_O + ((layer * 32 + blk) * 8 + hg) * 512 + 64 * t + 16 * w + g;
#pragma unroll
  for (int h = 0; h < 4; h += 2) {
    const float i0 = rcp_approx(Z[h][0]), i1 = rcp_approx(Z[h][2]), j0 = rcp_approx(Z[h + 1][0]), j1 = rcp_approx(Z[h + 1][2]);
    stg128(op + 128 * h, make_uint4(packbf(O0[h][0] * i0, O0[h][1] * i0), packbf(O1[h][0] * i0, O1[h][1] * i0),
                                   packbf(O0[h + 1][0] * j0, O0[h + 1][1] * j0), packbf(O1[h + 1][0] * j0, O1[h + 1][1] * j0)));
    stg128(op + 128 * h + 8, make_uint4(packbf(O0[h][2] * i1, O0[h][3] * i1), packbf(O1[h][2] * i1, O1[h][3] * i1),
                                            packbf(O0[h + 1][2] * j1, O0[h + 1][3] * j1), packbf(O1[h + 1][2] * j1, O1[h + 1][3] * j1)));
  }
  TSW(5);
  __syncwarp();
  if (lane == 0) red_relaxed(&g_cnt[(C_O + layer * 32 + blk) * 32]);
  TSW(6);
}

__device__ __forceinline__ void proj_phase(const Params& p, uint32_t sb, int layer, int rb, int q, int wg, int w, int& rtp) {
  const int lane = opaque_tid() & 31;
  const bool TR = layer != 0;
  const int t = lane & 3;
  const uint32_t bar = sb + SM_BAR;
  const uint32_t rbx = sb + (P_R + wg) * PG;
  const int blk = 16 * wg + rb;
  uint32_t res[16];
  mbar_wait(bar + 8 * (B_RF + wg), layer);
  if (!TR) {
#pragma unroll
    for (int j = 0; j < 8; j += 2) {
      const int mi = lane >> 3;
      const int row = 16 * w + (lane & 7) + 8 * (mi & 1), ch = j + (mi >> 1);
      ldsm4(&res[2 * j], rbx + row * 128 + ((ch ^ (row & 7)) << 4));
    }
  } else {
#pragma unroll
    for (int j = 0; j < 8; j += 2) {
      const int mi = lane >> 3;
      const int line = 8 * (j + (mi >> 1)) + (lane & 7), pc = 2 * w + (mi & 1);
      ldsm4t(&res[2 * j], rbx + line * 128 + ((pc ^ (line & 7)) << 4));
    }
  }
  mbar_wait(bar + 8 * B_KG, 0);
  if (layer) mbar_wait(bar + 8 * (B_RS + 1), 0);
  fence_async_global();
  const uint32_t stg = sb + SM_STG + wg * 768;
#pragma unroll 1
  for (int attempt = 0; attempt < MAX_RETRY; attempt++) {
  float acc[32];
#pragma unroll
  for (int j = 0; j < 16; j++) { acc[2 * j] = bf_lo(res[j]); acc[2 * j + 1] = bf_hi(res[j]); }
  acc_fence<32>(acc);
#pragma unroll
  for (int c = 0; c < 4; c++) {
    mbar_wait(bar + 8 * (B_WOF + c), layer);
    mbar_wait(bar + 8 * (B_OF + 4 * wg + c), layer);
    if (c == 0) TSW(7);
    const uint64_t da = mkdesc(sb + o_page(wg, c) * PG, 1024, 128, 0);
    wg_fence();
#pragma unroll
    for (int ks = 0; ks < 8; ks++)
      wgmma_ss<64, 0, 1>(acc, da + ks * 128, mkdesc(sb + wo_page(2 * c + (ks >> 2)) * PG, 8192, 1024, 1) + (ks & 3) * 128, 1);
    wg_commit();
  }
  wg_wait<0>();
  acc_fence<32>(acc);
  TSW(8);
  float s0 = 0.f, q0 = 0.f, s1 = 0.f, q1 = 0.f;
  uint32_t o[16];
#pragma unroll
  for (int j = 0; j < 8; j++) {
    const float a = acc[4 * j], b = acc[4 * j + 1], c = acc[4 * j + 2], d = acc[4 * j + 3];
    o[2 * j] = packbf(a, b);
    o[2 * j + 1] = packbf(c, d);
    s0 += a + b; q0 = fmaf(a, a, q0); q0 = fmaf(b, b, q0);
    s1 += c + d; q1 = fmaf(c, c, q1); q1 = fmaf(d, d, q1);
  }
#pragma unroll
  for (int j = 0; j < 8; j += 2) {
    const int mi = lane >> 3;
    const int line = 8 * (j + (mi >> 1)) + (lane & 7), pc = 2 * w + (mi & 1);
    stsm4t(rbx + line * 128 + ((pc ^ (line & 7)) << 4), o[2 * j], o[2 * j + 1], o[2 * j + 2], o[2 * j + 3]);
  }
#pragma unroll
  for (int o2 = 1; o2 <= 2; o2 <<= 1) {
    s0 += __shfl_xor_sync(~0u, s0, o2); q0 += __shfl_xor_sync(~0u, q0, o2);
    s1 += __shfl_xor_sync(~0u, s1, o2); q1 += __shfl_xor_sync(~0u, q1, o2);
  }
  {
    const int i = 2 * (lane >> 2) + (t & 1), k = (i * 11) >> 5;
    const float v = (t == 0) ? s0 : (t == 1) ? q0 : (t == 2) ? s1 : q1;
    sts32f(stg + k * 128 + (2 * w + (t >> 1)) * 16 + (i - 3 * k) * 4, v);
  }
  TSW(9);
  fence_async_smem();
  const float chk = s0 + s1;
  if (!bar_or(2 + wg, 128, chk != chk)) break;
  bool unset = false;
#pragma unroll
  for (int i = 0; i < 4; i++) unset |= lds32(sb + o_page(wg, i) * PG + (32 * w + lane) * 128) == UNSET;
  if (!bar_or(2 + wg, 128, unset)) break;
  if (w == 0 && elect_one()) {
    fence_async_smem();
    mbar_expect(bar + 8 * (B_RT + wg), 8 * PG);
#pragma unroll 1
    for (int c = 0; c < 4; c++) bulk_ld(sb + o_page(wg, c) * PG, g_O + ((layer * 32 + blk) * 4 + c) * PG, 2 * PG, bar + 8 * (B_RT + wg));
  }
  mbar_wait(bar + 8 * (B_RT + wg), rtp);
  rtp ^= 1;
  RETRY(0);
  }
  if (w == 0 && elect_one()) {
    tma_st(&p.mapXT, blk * 64, (2 * layer) * DM + q * 64, rbx);
    bulk_red_add_f32(g_stats + (layer * 32 + blk) * 192, stg, 768);
    bulk_commit();
    mbar_arrive(bar + 8 * (B_PDONE + wg));
    red_relaxed(&g_cnt[(C_G + 2 * layer + wg) * 32]);
    bulk_wait_read();
    mbar_arrive(bar + 8 * (B_PST + wg));
    TSW(10);
  }
}

__device__ __forceinline__ void conv_load(uint32_t* A, uint32_t pe) {
#pragma unroll
  for (int m = 0; m < 17; m++) {
    A[4 * m + 2] = lds32(pe + 4 * (64 * m - 8));
    A[4 * m + 0] = lds32(pe + 4 * (64 * m));
    A[4 * m + 1] = lds32(pe + 4 * (64 * m + 8));
    asm volatile("mov.b32 %0, %1;" : "=r"(A[4 * m + 3]) : "r"(A[4 * m + 0]));
  }
}
template <int M> __device__ __forceinline__ void conv_tri(float* acc, const uint32_t* A, uint64_t d) {
  if constexpr (M < 16) {
    wgmma_rs<64 - 8 * (M / 2), 0>(acc, A + 4 * M, d + (uint64_t)(64 + 4 * M), M != 0);
    conv_tri<M + 1>(acc, A, d);
  }
}
__device__ __forceinline__ void conv_mma0(float* acc, const uint32_t* A, uint64_t d) {
  wg_fence();
  conv_tri<0>(acc, A, d);
  wg_commit();
}
__device__ __forceinline__ void conv_mma1(float* acc, const uint32_t* A, uint64_t d) {
  wg_fence();
#pragma unroll
  for (int m = 0; m < 17; m++) wgmma_rs<64, 0>(acc, A + 4 * m, d + (uint64_t)(4 * m), m != 0);
  wg_commit();
}
__device__ __forceinline__ void conv_store(float* acc, uint32_t pb, uint32_t over, int w) {
  acc_fence<32>(acc);
  const int l = opaque_tid() & 31, mt = l >> 3;
  int c = 2 * (63 - 8 * (mt >> 1) - (l & 7) + w) + (mt & 1);
  c ^= (c >> 3) & 1;
  const uint32_t a0 = pb + c * 16;
#pragma unroll
  for (int j = 0; j < 8; j += 2)
    stsm4t(j == 0 ? (c < 128 ? a0 : over + (c - 128) * 16) : a0 - 256 * j, packbf(acc[4 * j], acc[4 * j + 1]), packbf(acc[4 * j + 2], acc[4 * j + 3]),
           packbf(acc[4 * j + 4], acc[4 * j + 5]), packbf(acc[4 * j + 6], acc[4 * j + 7]));
}
__device__ __forceinline__ void conv_far(uint32_t sb, int ht) {
  const int w = ht >> 5, l = ht & 31;
  float F[4][8];
  const uint64_t da = mkdesc(sb + cv_fa(0), 128, 128, 0), ds = mkdesc(sb + cv_se(0), 256, 256, 3);
  wg_fence();
#pragma unroll
  for (int k = 0; k < 8; k++)
#pragma unroll
    for (int c = 0; c < 4; c++) wgmma_ss<16, 0, 1>(F[c], da + c * 1024 + (k >> 2) * 128 + (k & 3) * 16, ds + c * 256 + 32 * k, k != 0);
  wg_commit();
  const uint32_t pf = sb + cv_pf(0) + (16 * w + (l & 15)) * 32 + (l >> 4) * 16;
  wg_wait<0>();
#pragma unroll
  for (int c = 0; c < 4; c++) {
    acc_fence<8>(F[c]);
    stsm4(pf + c * 2048, packbf(F[c][0], F[c][1]), packbf(F[c][2], F[c][3]), packbf(F[c][4], F[c][5]), packbf(F[c][6], F[c][7]));
  }
}
__device__ __forceinline__ void conv_sums(uint32_t sb, int lc, int ht) {
  const int m = ht - 1;
  uint4 v[2][3];
#pragma unroll
  for (int c = 0; c < 2; c++)
#pragma unroll
    for (int k = 0; k < 3; k++) {
      const int mm = m - 1 + k;
      v[c][k] = lds128(sb + cv_u(lc + c) + (mm >= 0 ? (mm & 1) * CV_UH + (127 - (mm >> 1)) * 16 : 128 * 16));
    }
  const int ce = m + 2, co = m + 1;
#pragma unroll
  for (int c = 0; c < 2; c++) {
    const uint32_t x[8] = {v[c][0].z, v[c][0].w, v[c][1].x, v[c][1].y, v[c][1].z, v[c][1].w, v[c][2].x, v[c][2].y};
    float pv[16];
#pragma unroll
    for (int k = 0; k < 8; k++) { pv[2 * k] = bf_lo(x[k]); pv[2 * k + 1] = bf_hi(x[k]); }
    float t2[15], t4[13], s9[8], s7[8];
#pragma unroll
    for (int i = 0; i < 15; i++) t2[i] = pv[i] + pv[i + 1];
#pragma unroll
    for (int i = 0; i < 13; i++) t4[i] = t2[i] + t2[i + 2];
#pragma unroll
    for (int i = 0; i < 8; i++) {
      s9[i] = (t4[i] + t4[i + 4]) + pv[i + 8];
      s7[i] = (t4[i + 1] + t2[i + 5]) + pv[i + 7];
    }
    const uint4 e4 = make_uint4(packbf(s9[0], s9[1]), packbf(s9[2], s9[3]), packbf(s9[4], s9[5]), packbf(s9[6], s9[7]));
    if (ce < 128) sts128(sb + cv_se(lc + c) + (63 - (ce >> 1)) * 32 + (((ce & 1) ^ ((ce >> 3) & 1) ^ 1) << 4), e4);
    else sts128(sb + cv_se(lc + c) + 63 * 32 + 16, make_uint4(0, 0, 0, 0));
    sts128(sb + cv_so(lc + c) + (63 - (co >> 1)) * 32 + (((co & 1) ^ ((co >> 3) & 1) ^ 1) << 4),
           make_uint4(packbf(s7[0], s7[1]), packbf(s7[2], s7[3]), packbf(s7[4], s7[5]), packbf(s7[6], s7[7])));
  }
}

template <int HALF, int NCH, int STEP = 1>
__device__ __forceinline__ void conv_epi(uint32_t sb, bf16* out, int lc, int c) {
  uint4 v[NCH][4], xr[NCH], f[NCH];
  const uint32_t sw = (c ^ ((c >> 3) & 1)) * 16;
#pragma unroll
  for (int u = 0; u < NCH; u++) {
#pragma unroll
    for (int k = 0; k < 4; k++) v[u][k] = lds128(sb + (HALF ? cv_pb1(lc + STEP * u, k) : cv_pb0(lc + STEP * u, k)) + sw);
    xr[u] = lds128(sb + cv_x(HALF, lc + STEP * u) + c * 16);
    if (HALF) f[u] = lds128(sb + cv_pf(lc + STEP * u) + c * 16);
  }
#pragma unroll
  for (int u = 0; u < NCH; u++) {
    if (HALF) { v[u][0].x = hadd2(v[u][0].x, f[u].x); v[u][0].y = hadd2(v[u][0].y, f[u].y); v[u][0].z = hadd2(v[u][0].z, f[u].z); v[u][0].w = hadd2(v[u][0].w, f[u].w); }
    uint4 o;
    o.x = hadd2(xr[u].x, hadd2(hadd2(v[u][0].x, v[u][1].x), hadd2(v[u][2].x, v[u][3].x)));
    o.y = hadd2(xr[u].y, hadd2(hadd2(v[u][0].y, v[u][1].y), hadd2(v[u][2].y, v[u][3].y)));
    o.z = hadd2(xr[u].z, hadd2(hadd2(v[u][0].z, v[u][1].z), hadd2(v[u][2].z, v[u][3].z)));
    o.w = hadd2(xr[u].w, hadd2(hadd2(v[u][0].w, v[u][1].w), hadd2(v[u][2].w, v[u][3].w)));
    stg128(out + cv_chan(0, lc + STEP * u) * LSEQ + HALF * 1024 + c * 8, o);
  }
}

__device__ __forceinline__ bool prep_valid(const uint4 (&st)[6], const uint4 (&xr)[4]) {
  const uint32_t n = __float_as_uint(8.f);
  return st[0].w == n && st[1].w == n && st[2].w == n && st[3].w == n && st[4].w == n && (st[5].w | st[5].y | st[5].z) == n &&
         xr[0].x != UNSET && xr[1].x != UNSET && xr[2].x != UNSET && xr[3].x != UNSET;
}
template <int HALF>
__device__ __forceinline__ void conv_prep(uint32_t sb, int layer, int cta, int i) {
  uint4 st[6], xr[4];
  bool ok = false;
  if (HALF) {
#pragma unroll
    for (int k = 0; k < 6; k++) st[k] = lds128(sb + cv_pe(i >> 5) + ((i >> 3) & 3) * 768 + k * 128 + (i & 7) * 16);
#pragma unroll
    for (int k = 0; k < 4; k++) xr[k] = lds128(sb + cv_x(1, k) + i * 16);
    ok = __all_sync(~0u, prep_valid(st, xr));
  }
  if (!ok) {
    const uint4* sp = (const uint4*)g_stats + (layer * 32 + HALF * 16 + (i >> 3)) * 48 + (i & 7);
    const uint4* xp = (const uint4*)g_xT + (2 * layer * DM + 2 * cta) * (LSEQ / 8) + HALF * 128 + i;
    int it = 0;
    do {
#pragma unroll
      for (int k = 0; k < 6; k++) st[k] = ld_tagged(sp + 8 * k);
#pragma unroll
      for (int k = 0; k < 4; k++) xr[k] = ld_tagged(xp + cv_chan(0, k) * (LSEQ / 8));
      if (HALF || it) RETRY(1);
    } while (!__all_sync(~0u, prep_valid(st, xr)) && ++it < MAX_RETRY);
#pragma unroll
    for (int k = 0; k < 4; k++) sts128(sb + cv_x(HALF, k) + i * 16, xr[k]);
  }
  const uint32_t v[16] = {st[0].x, st[0].y, st[0].z, st[1].x, st[1].y, st[1].z, st[2].x, st[2].y, st[2].z, st[3].x, st[3].y, st[3].z, st[4].x, st[4].y, st[4].z, st[5].x};
  uint32_t rs[4], nm[4];
#pragma unroll
  for (int k = 0; k < 4; k++) {
    const float m0 = __uint_as_float(v[4 * k]) * (-1.f / DM), m1 = __uint_as_float(v[4 * k + 2]) * (-1.f / DM);
    const float r0 = rsqrt_approx(fmaxf(fmaf(__uint_as_float(v[4 * k + 1]), 1.f / DM, -m0 * m0), 0.f) + 1e-5f);
    const float r1 = rsqrt_approx(fmaxf(fmaf(__uint_as_float(v[4 * k + 3]), 1.f / DM, -m1 * m1), 0.f) + 1e-5f);
    rs[k] = packbf(r0, r1);
    nm[k] = packbf(m0 * bf_lo(rs[k]), m1 * bf_hi(rs[k]));
  }
  const uint32_t ud = sb + (i & 1) * CV_UH + (127 - 64 * HALF - (i >> 1)) * 16;
#pragma unroll
  for (int k = 0; k < 4; k++)
    sts128(ud + cv_u(k), make_uint4(hfma2(xr[k].x, rs[0], nm[0]), hfma2(xr[k].y, rs[1], nm[1]), hfma2(xr[k].z, rs[2], nm[2]), hfma2(xr[k].w, rs[3], nm[3])));
  fence_async_smem();
}

#define PP0 1
__device__ __forceinline__ void conv_phase(const Params& p, uint32_t sb, int layer, int cta) {
  const int tid = opaque_tid();
  const int wg = __shfl_sync(~0u, tid >> 7, 0), w = __shfl_sync(~0u, (tid >> 5) & 3, 0);
  const uint32_t bar = sb + SM_BAR;
  constexpr int CH2 = 4 * PG;
  bf16* xout = g_xT + ((2 * layer + 1) * DM + 2 * cta) * LSEQ;
  uint32_t A0[68], A1[68];
  float acc[32];
  {
    const int l1 = tid & 31;
    const uint32_t pe = sb + cv_pe(wg) + 4 * (16 + 16 * w + (l1 >> 2) - 2 * (l1 & 3));
    if (layer) mbar_wait(bar + 8 * (B_RS + 2), 0);
    mbar_wait(bar + 8 * B_PE, layer);
    conv_load(A0, pe);
    conv_load(A1, pe + CH2);
    __syncwarp();
    if (l1 == 0) mbar_arrive(bar + 8 * B_AL);
  }
  TSW(19);
  if (wg == 0) {
    const int i = opaque_tid();
    if (i < 32) sts128(sb + cv_u(i >> 3) + ((i >> 2) & 1) * CV_UH + (128 + (i & 3)) * 16, make_uint4(0, 0, 0, 0));
    mbar_wait(bar + 8 * B_GB, layer);
    TSW(11);
    conv_prep<0>(sb, layer, cta, i);
    mbar_arrive(bar + 8 * B_U);
  }
  const uint64_t d0 = mkdesc(sb + cv_u(wg), CV_UH, 128, 0), d1 = d0 + (CH2 >> 4);
  mbar_wait(bar + 8 * B_U, layer);
  TSW(12);
  if (wg == 1) bar_sync(5, 256);
  conv_mma0(acc, A0, d0);
  if (wg == 0) bar_arrive(5, 256);
  mbar_wait(bar + 8 * (B_PDONE + 1), layer);
  {
    const int l = opaque_tid() & 31;
    if ((l & 15) < 2 * w) sts128(sb + cv_pb0(wg + 2 * (l >> 4), w) + (l & 15) * 16, make_uint4(0, 0, 0, 0));
  }
  wg_wait<0>();
  conv_store(acc, sb + cv_pb0(wg, w), sb + cv_pb1(wg, w), w);
  conv_mma0(acc, A1, d1);
  bar_sync(2 + wg, 128);
  conv_epi<0, 1>(sb, xout, wg, opaque_tid() & 127);
  wg_wait<0>();
  conv_store(acc, sb + cv_pb0(2 + wg, w), sb + cv_pb1(2 + wg, w), w);
  TSW(13);
  bar_sync(2 + wg, 128);
  conv_epi<0, 1>(sb, xout, 2 + wg, opaque_tid() & 127);
  mbar_arrive(bar + 8 * B_PUB);
  TSW(14);
  mbar_wait(bar + 8 * (B_GB + 1), layer);
  if (wg == 0) {
    conv_prep<1>(sb, layer, cta, opaque_tid());
    bar_sync(2, 128);
  } else {
    bar_sync(6, 256);
  }
  TSW(15);
  conv_mma1(acc, A0, d0);
  if (wg == 0) bar_arrive(6, 256);
  mbar_wait(bar + 8 * B_FARM, layer);
  wg_wait<0>();
  conv_store(acc, sb + cv_pb1(wg, w), sb + cv_dump(wg), w);
  mbar_arrive(bar + 8 * (B_R + 1));
  TSW(16);
  conv_mma1(acc, A1, d1);
  wg_wait<0>();
  conv_store(acc, sb + cv_pb1(2 + wg, w), sb + cv_dump(2 + wg), w);
  TSW(17);
  if (wg == 0) {
    mbar_arrive(bar + 8 * (B_R + 2));
  } else {
    bar_sync(3, 128);
    conv_epi<1, 1>(sb, xout, 3, opaque_tid() & 127);
    mbar_arrive(bar + 8 * (B_PUB + 2));
    TSW(18);
  }
}

__device__ __forceinline__ void final_phase(const Params& p, uint32_t sb, int cta, int wg, int w, int rtp) {
  const int lane = opaque_tid() & 31;
  const uint32_t bar = sb + SM_BAR;
  mbar_wait(bar + 8 * (B_TF + wg), 0);
  if (threadIdx.x == 128) TS(8);
  const uint32_t src = sb + (16 + wg) * PG, dst = src + 2 * PG;
  const int mi = lane >> 3;
#pragma unroll 1
  for (int attempt = 0; attempt < MAX_RETRY; attempt++) {
    uint32_t m = 0;
#pragma unroll
    for (int j = 0; j < 8; j += 2) {
      uint32_t r[4];
      const int line = 8 * (j + (mi >> 1)) + (lane & 7), pc = 2 * w + (mi & 1);
      ldsm4t(r, src + line * 128 + ((pc ^ (line & 7)) << 4));
      const int row = 16 * w + (lane & 7) + 8 * (mi & 1), ch = j + (mi >> 1);
      stsm4(dst + row * 128 + ((ch ^ (row & 7)) << 4), r[0], r[1], r[2], r[3]);
#pragma unroll
      for (int k = 0; k < 4; k++) asm("max.u16x2 %0, %0, %1;" : "+r"(m) : "r"(r[k]));
    }
    fence_async_smem();
    if (!bar_or(2 + wg, 128, m >= 0xffff0000u || (m & 0xffffu) == 0xffffu)) break;
    if (w == 0 && elect_one()) {
      mbar_expect(bar + 8 * (B_RT + wg), PG);
      tma_ld(src, &p.mapXT, (16 * wg + (cta & 15)) * 64, 3 * DM + (cta >> 4) * 64, bar + 8 * (B_RT + wg));
    }
    mbar_wait(bar + 8 * (B_RT + wg), (rtp + attempt) & 1);
    RETRY(2);
  }
  if (w == 0 && elect_one()) {
    tma_st(&p.mapOut, (cta >> 4) * 64, (16 * wg + (cta & 15)) * 64, dst);
    bulk_commit();
    asm volatile("cp.async.bulk.wait_group.read 0;" ::: "memory");
    if (threadIdx.x == 128) TS(9);
    if (threadIdx.x == 128) LTS(1);
  }
}

struct cplx { float r, i; };
__device__ __forceinline__ cplx cmul(cplx a, cplx b) { return {fmaf(a.r, b.r, -a.i * b.i), fmaf(a.r, b.i, a.i * b.r)}; }
__device__ __forceinline__ cplx csqr(cplx a) { return {fmaf(a.r, a.r, -a.i * a.i), (a.r + a.r) * a.i}; }
__device__ __forceinline__ cplx cexp_l(float ar2, float ai, float l) {
  const float m = ex2(ar2 * l);
  const float x = ai * l;
  return {m * __cosf(x), m * __sinf(x)};
}

__device__ __forceinline__ void colsum_cta(const Params& p, uint32_t sb, int j, int tid) {
  const uint32_t bar = sb + SM_BAR;
  auto ld = [&](int i) {
    mbar_expect(bar + 8 * i, 3 * PG);
    tma_ld3(sb + (i & 7) * 3 * PG, &p.mapW3, (2 * j + (i & 1)) * 64, (i >> 1) * 64, 0, bar + 8 * i);
  };
  if (tid == 384) {
#pragma unroll
    for (int i = 0; i < 24; i++) mbar_init(bar + 8 * i, i < 16 ? 1 : 12);
    asm volatile("fence.mbarrier_init.release.cluster;" ::: "memory");
    fence_async_smem();
#pragma unroll 1
    for (int i = 0; i < 8; i++) ld(i);
  }
  const unsigned ep = ld_relaxed(&g_cnt[C_CS * 32]);
  bar_sync(0, NTHREADS);
  if (tid == 384) {
#pragma unroll 1
    for (int i = 8; i < 16; i++) { mbar_wait(bar + 8 * (8 + i), 0); fence_async_smem(); ld(i); }
  }
  if (tid < 384) {
    const int lane = tid & 31, cc = tid & 7, r0 = (tid >> 3) & 15, part = tid >> 7;
    const uint32_t id = ((lane >> 2) == 2 * (lane & 3) ? 0x3f80u : 0u) | ((lane >> 2) == 2 * (lane & 3) + 1 ? 0x3f800000u : 0u);
    const uint32_t src = sb + part * PG + r0 * 128 + ((cc ^ (r0 & 7)) << 4);
    float s[2][2][4];
#pragma unroll
    for (int i = 0; i < 16; i++) s[i >> 3][(i >> 2) & 1][i & 3] = 0.f;
#pragma unroll 1
    for (int i2 = 0; i2 < 16; i2 += 2) {
#pragma unroll
      for (int h = 0; h < 2; h++) {
        const int i = i2 + h;
        mbar_wait(bar + 8 * i, 0);
        uint4 v[4];
#pragma unroll
        for (int k = 0; k < 4; k++) v[k] = lds128(src + (i & 7) * 3 * PG + k * 2048);
#pragma unroll
        for (int k = 0; k < 4; k++) {
          const uint32_t a[4] = {v[k].x, v[k].y, v[k].z, v[k].w};
          mma_bf16(s[h][0], a, id, 0u);
          mma_bf16(s[h][1], a, 0u, id);
        }
        __syncwarp();
        if (i < 8 && lane == 0) mbar_arrive(bar + 8 * (16 + i));
      }
    }
    const uint32_t red = sb + 24 * PG;
#pragma unroll
    for (int h = 0; h < 2; h++)
#pragma unroll
      for (int k = 0; k < 2; k++) sts128f(red + (r0 * 384 + h * 192 + part * 64 + cc * 8 + k * 4) * 4, s[h][k][0], s[h][k][1], s[h][k][2], s[h][k][3]);
    bar_sync(1, 384);
    float tot = 0.f;
#pragma unroll
    for (int k = 0; k < 16; k++) tot += __uint_as_float(lds32(red + (k * 384 + tid) * 4));
    asm volatile("st.relaxed.gpu.global.v2.u32 [%0], {%1,%2};" ::"l"(&g_colsum[j * 384 + tid]), "r"(__float_as_uint(tot)), "r"(ep / NCTA + 1) : "memory");
    const uint4 u = make_uint4(UNSET, UNSET, UNSET, UNSET);
    if (tid < 256) {
#pragma unroll 4
      for (int i = 0; i < 64; i++) stg128(g_halo + 65536 + j * 16384 + i * 256 + tid, u);
#pragma unroll 1
      for (int s = 0; s < 3; s++) {
        uint4* dst = (s ? (uint4*)g_xT + (s + 1) * 131072 : (uint4*)g_O + 131072) + j * 32768 + (tid >> 1) * 8 + (tid & 1);
#pragma unroll 4
        for (int i = 0; i < 32; i++) stg128(dst + i * 1024, u);
        bar_sync(2, 256);
        if (tid == 32 * s) red_release(&g_cnt[(C_R + s) * 32]);
      }
    }
  }
}

#define KW 3
struct ModeIn { uint32_t ar, ai, br, bi, cr, ci; bf16 logdt; };
__device__ __forceinline__ ModeIn load_modes(const Params& p, int d, int m) {
  const int i = d * 64 + m;
  return {((const uint32_t*)p.a_re)[i], ((const uint32_t*)p.a_im)[i], ((const uint32_t*)p.b_re)[i], ((const uint32_t*)p.b_im)[i],
          ((const uint32_t*)p.c_re)[i], ((const uint32_t*)p.c_im)[i], p.log_dt[d]};
}
__device__ __forceinline__ float4 lds128f_nv(uint32_t a) { float4 v; asm("ld.shared.v4.f32 {%0,%1,%2,%3}, [%4];" : "=f"(v.x), "=f"(v.y), "=f"(v.z), "=f"(v.w) : "r"(a)); return v; }
__device__ __forceinline__ void kernel_gen(const Params& p, uint32_t sb, int cta, int ht, ModeIn in, const ModeIn& in1) {
  const uint32_t bst = sb + SM_KGB + ((ht & 63) >> 2) * 144 + (ht & 3) * 4 + (ht >> 6) * 16;
  const uint64_t db = mkdesc(sb + SM_KGB, 144, 2304, 0);
  const float e0 = (float)(8 * (((ht & 32) >> 1) + ((ht & 31) >> 2)));
  float T[20];
#pragma unroll
  for (int i = 0; i < 20; i++) T[i] = 0.f;
  float k0 = (ht & 63) ? 0.f : __bfloat162float(p.dskip[cv_chan(cta, ht >> 6)]);
#pragma unroll 1
  for (int pass = 0; pass < 4; pass++) {
    {
      const int sh = (pass & 1) ? 0 : 16;
      auto val = [&](uint32_t v) { return __uint_as_float((v << sh) & 0xffff0000u); };
      const float dt = __bfloat162float(__float2bfloat16_rn(expf(__bfloat162float(in.logdt))));
      const float ar2 = dt * val(in.ar) * 1.4426950408889634f, ai = dt * val(in.ai);
      const cplx c = cmul({val(in.cr), -val(in.ci)}, {dt * val(in.br), -dt * val(in.bi)});
      k0 += c.r;
      const cplx z1 = cexp_l(ar2, -ai, 1.f), z256 = cexp_l(ar2, -ai, 256.f), z64 = cexp_l(ar2, ai, 64.f);
      const cplx z2 = csqr(z1), z512 = csqr(z256);
      auto put = [&](int j, cplx v) { sts32(bst + (j >> 2) * 2304 + (j & 3) * 32, packbf(v.r, v.i)); };
      sts128f(sb + SM_KGT + ht * 16, ar2, ai, z64.r, z64.i);
      const cplx c1 = cmul(c, z1), c2 = cmul(c, z2), c3 = cmul(c1, z2), c4 = cmul(c2, z2);
      const cplx c5 = cmul(c3, z2), c6 = cmul(c4, z2), c7 = cmul(c5, z2), c8 = cmul(c6, z2);
      put(0, c1); put(1, c2); put(2, c3); put(3, c4); put(4, c5); put(5, c6); put(6, c7); put(7, c8);
      const cplx c260 = cmul(c4, z256), c264 = cmul(c8, z256), c520 = cmul(c8, z512), c776 = cmul(c264, z512);
      put(8, cmul(c2, z256)); put(9, c260); put(10, cmul(c6, z256)); put(11, c264);
      put(12, cmul(c4, z512)); put(13, c520); put(14, cmul(c260, z512)); put(15, c776);
      const cplx c1032 = cmul(c520, z512), c1288 = cmul(c776, z512);
      put(16, c1032); put(17, c1288); put(18, cmul(c1032, z512)); put(19, cmul(c1288, z512));
    }
    fence_async_smem();
    bar_sync(4, 128);
    uint32_t tb = sb + SM_KGT + (ht & 67) * 16;
    asm volatile("mov.u32 %0, %0;" : "+r"(tb) :: "memory");
#pragma unroll
    for (int q = 0; q < 4; q++) {
      uint32_t A[8];
      if (q >= KW) wg_wait<KW - 1>();
#pragma unroll
      for (int s = 0; s < 4; s++) {
        const float4 v = lds128f_nv(tb + (4 * q + s) * 64);
        const cplx lo = cexp_l(v.x, v.y, e0), hi = cmul(lo, {v.z, v.w});
        A[2 * s] = packbf(lo.r, lo.i);
        A[2 * s + 1] = packbf(hi.r, hi.i);
      }
      wg_fence();
      wgmma_rs<40, 0>(T, A, db + 36 * q, (pass & 1) | q);
      wgmma_rs<40, 0>(T, A + 4, db + 36 * q + 18, 1);
      wg_commit();
    }
    wg_wait<0>();
    acc_fence<20>(T);
    if (ht == 0) TS(4 + pass);
    if (pass & 1) {
      const int h2 = opaque_tid() - 256, w = h2 >> 5, lane = h2 & 31, t = lane & 3, chn = h2 >> 6, m = h2 & 63, i0 = 16 * (w & 1) + (lane >> 2);
      const int lc = (pass & 2) + chn;
      const uint32_t kc = sb + kc_off(lc);
      auto put = [&](int idx, float v) {
        sts16(kc + idx * 2, __bfloat16_as_ushort(__float2bfloat16_rn(v)));
      };
#pragma unroll
      for (int hi = 0; hi < 2; hi++) {
        const int i = i0 + 8 * hi;
        float v[5];
#pragma unroll
        for (int j = 0; j < 5; j++) v[j] = chn ? T[4 * j + 2 * hi + 1] : T[4 * j + 2 * hi];
        put(8 * i + 1 + t, v[0]);
        put(8 * i + 5 + t, v[1]);
        put(257 + 4 * i + t, v[2]);
        put(385 + 2 * i + (t & 1) + 64 * (t >> 1), v[3]);
        put(513 + i + 32 * t, v[4]);
      }
#pragma unroll
      for (int o = 16; o > 0; o >>= 1) k0 += __shfl_xor_sync(~0u, k0, o);
      if (lane == 0) sts32f(sb + SM_RED + 4 * w, k0);
      bar_sync(4, 128);
      if (m == 0) put(0, k0 + __uint_as_float(lds32(sb + SM_RED + 4 * w + 4)));
      k0 = m ? 0.f : __bfloat162float(p.dskip[cv_chan(cta, 2 + chn)]);
      in = in1;
    }
  }
}

__device__ __forceinline__ void expand_taps(uint32_t sb, int ht) {
  const int ch = ht >> 5, lane = ht & 31;
  const uint32_t kc = sb + kc_off(ch);
  const uint32_t dst0 = sb + cv_pe(ch);
  auto put = [&](int G, uint32_t v0, uint32_t v1, uint32_t v2, uint32_t v3, uint32_t v4, uint32_t v5, uint32_t v6, uint32_t v7, uint32_t v8) {
    const uint32_t dst = dst0 + G * 32;
    sts128(dst, make_uint4(v1 | (v0 << 16), v2 | (v1 << 16), v3 | (v2 << 16), v4 | (v3 << 16)));
    sts128(dst + 16, make_uint4(v5 | (v4 << 16), v6 | (v5 << 16), v7 | (v6 << 16), v8 | (v7 << 16)));
  };
  {
    const uint4 q = lds128(kc + lane * 16);
    const uint32_t pv = lane ? lds16(kc + lane * 16 - 2) : 0u;
    const uint32_t dst = dst0 + (lane + 2) * 32;
    sts128(dst, make_uint4(__byte_perm(q.x, pv, 0x5410), __byte_perm(q.x, q.x, 0x1032), __byte_perm(q.y, q.x, 0x7610), __byte_perm(q.y, q.y, 0x1032)));
    sts128(dst + 16, make_uint4(__byte_perm(q.z, q.y, 0x7610), __byte_perm(q.z, q.z, 0x1032), __byte_perm(q.w, q.z, 0x7610), __byte_perm(q.w, q.w, 0x1032)));
    if (lane < 4) sts128(dst0 + lane * 16, make_uint4(0, 0, 0, 0));
  }
  uint32_t a[5], b[2][3];
  {
    const uint32_t s1 = kc + 2 * (256 + 4 * lane);
#pragma unroll
    for (int k = 0; k < 5; k++) a[k] = lds16(s1 + 2 * k);
#pragma unroll
    for (int u = 0; u < 2; u++) {
      const uint32_t s2 = kc + 2 * (384 + 2 * (lane + 32 * u));
#pragma unroll
      for (int k = 0; k < 3; k++) b[u][k] = lds16(s2 + 2 * k);
    }
  }
  const uint32_t k255 = lds16(kc + 2 * 255), k1024 = lds16(kc + 2 * 512);
  put(34 + lane, lane == 0 ? k255 : a[0], a[0], a[0], a[1], a[2], a[2], a[2], a[3], a[4]);
#pragma unroll
  for (int u = 0; u < 2; u++) put(66 + lane + 32 * u, b[u][0], b[u][0], b[u][0], b[u][0], b[u][1], b[u][1], b[u][1], b[u][2], b[u][2]);
  if (lane < 10) {
    const uint32_t v = lane == 0 ? k1024 : 0u;
    put(130 + lane, v, v, v, v, v, v, 0u, 0u, 0u);
  }
}
__device__ __forceinline__ void expand_far(uint32_t sb, int ht) {
  const int ch = ht >> 5, lane = ht & 31;
  const uint32_t kc = sb + kc_off(ch) + 4 * (249 + lane), dst = sb + cv_fa(ch);
  uint32_t v[2][9];
#pragma unroll
  for (int u = 0; u < 2; u++)
#pragma unroll
    for (int k = 0; k < 9; k++) v[u][k] = lds32(kc + 4 * (32 * u + k));
#pragma unroll
  for (int k = 0; k < 8; k++) v[0][k] = lane + k < 7 ? 0u : lane + k == 7 ? v[0][k] & 0xffff0000u : v[0][k];
#pragma unroll
  for (int u = 0; u < 2; u++) {
    const uint32_t row = dst + (56 + 32 * u + lane) * 16;
    sts128(row, make_uint4(__byte_perm(v[u][1], v[u][2], 0x5410), __byte_perm(v[u][3], v[u][4], 0x5410), __byte_perm(v[u][5], v[u][6], 0x5410), __byte_perm(v[u][7], v[u][8], 0x5410)));
    sts128(row + 2048, make_uint4(__byte_perm(v[u][0], v[u][1], 0x7632), __byte_perm(v[u][2], v[u][3], 0x7632), __byte_perm(v[u][4], v[u][5], 0x7632), __byte_perm(v[u][6], v[u][7], 0x7632)));
    sts128(dst + u * 2048 + lane * 16, make_uint4(0, 0, 0, 0));
    if (lane < 24) sts128(dst + u * 2048 + (32 + lane) * 16, make_uint4(0, 0, 0, 0));
  }
}

#define WPRE 2
__host__ __device__ constexpr int bar_count(int i) {
  return i == B_END ? 3 : i == B_AL ? 8 : (i == B_OST || i == B_OST + 1) ? 4 : (i == B_PUB + 2 || i == B_PUB || i == B_R + 1) ? 256 : (i >= B_FARM && i < B_END) ? 128 : 1;
}
__host__ __device__ constexpr bool bar_first(int i) { return i < B_WF + 2 && (i & 7) < 2; }

__global__ void __launch_bounds__(NTHREADS, 1) fused_kernel(const __grid_constant__ Params p) {
  extern __shared__ __align__(1024) uint8_t smem[];
  const uint32_t sb = s32(smem);
  const int tid = threadIdx.x, lane = tid & 31;
  const int warp = __shfl_sync(~0u, tid >> 5, 0);
  if (blockIdx.x < 4) {
    colsum_cta(p, sb, blockIdx.x, tid);
    return;
  }
  const int cta = blockIdx.x - 4;
  const int rb = ((cta >> 4) & 3) * 4 + ((cta >> 2) & 3), hg = (cta >> 6) * 4 + (cta & 3);
  const int rb2 = cta >> 3, q2 = cta & 7;
  const uint32_t bar = sb + SM_BAR;
  auto ld_x0 = [&](int half, int c) {
    const uint32_t b = bar + 8 * (B_XF + 8 * half + c);
    mbar_expect(b, PG);
    tma_ld(sb + x_page(half, c) * PG, &p.mapX, c * 64, (16 * half + rb) * 64, b);
  };
  auto ld_w = [&](int c) {
    const uint32_t b = bar + 8 * (B_WF + c);
    mbar_expect(b, 3 * PG);
    tma_ld3(sb + w_page(c) * PG, &p.mapW3, hg * 64, c * 64, 0, b);
  };

  if (tid == 0) TS(0);
  if (tid == 480) LTS(0);
  if (warp < 6 && elect_one()) {
    if (warp == 0) {
#pragma unroll
      for (int i = 0; i < B_WF + 2; i++)
        if (bar_first(i)) mbar_init(bar + 8 * i, 1);
      asm volatile("fence.mbarrier_init.release.cluster;" ::: "memory");
      fence_async_smem();
      ld_x0(0, 0); ld_w(0); ld_x0(1, 0);
      ld_x0(0, 1); ld_w(1); ld_x0(1, 1);
      TS(1);
    } else {
#pragma unroll
      for (int q = 0; q < 5; q++) {
        if (warp == q + 1) {
#pragma unroll
          for (int i = 0; i < B_COUNT; i++)
            if (!bar_first(i) && i % 5 == q) mbar_init(bar + 8 * i, bar_count(i));
        }
      }
      asm volatile("fence.mbarrier_init.release.cluster;" ::: "memory");
    }
  }

  if (warp < 8) {
    bar_sync(0, NTHREADS);
    asm volatile("setmaxnreg.inc.sync.aligned.u32 %0;" ::"n"(R_CONS));
    const int cw = __shfl_sync(~0u, opaque_tid() >> 5, 0);
    const int wg = cw >> 2, w = cw & 3;
    if (tid == 0) TS(2);
    int rtp = 0;
#pragma unroll 1
    for (int layer = 0; layer < 2; layer++) {
      attn_phase(p, sb, layer, rb, hg, wg, w);
      proj_phase(p, sb, layer, rb2, q2, wg, w, rtp);
      conv_phase(p, sb, layer, cta);
    }
    final_phase(p, sb, cta, wg, w, rtp);
  } else if (warp < 12) {
    asm volatile("setmaxnreg.dec.sync.aligned.u32 %0;" ::"n"(R_HELP));
    const int ht = tid - 256;
    {
      unsigned ep0 = 0;
      if (ht == 0) ep0 = ld_relaxed(&g_cnt[C_CS * 32]);
      const ModeIn in0 = load_modes(p, cv_chan(cta, ht >> 6), ht & 63), in1 = load_modes(p, cv_chan(cta, 2 + (ht >> 6)), ht & 63);
      bar_sync(0, NTHREADS);
      if (ht == 0) {
        sts32(sb + SM_EP, ep0 / NCTA);
        mbar_arrive(bar + 8 * B_EP);
      }
      kernel_gen(p, sb, cta, ht, in0, in1);
      if (ht < 96) sts128f(sb + SM_STG + ht * 16, 0.f, 0.f, 0.f, 1.f);
      fence_async_smem();
      bar_sync(4, 128);
      if (ht == 0) mbar_arrive(bar + 8 * B_KG);
    }
#pragma unroll 1
    for (int layer = 0; layer < 2; layer++) {
      bf16* xout = g_xT + ((2 * layer + 1) * DM + 2 * cta) * LSEQ;
      mbar_wait(bar + 8 * B_PDONE, layer);
      expand_taps(sb, opaque_tid() - 256);
      mbar_arrive(bar + 8 * B_PE);
      TSW(0);
      expand_far(sb, opaque_tid() - 256);
      if (layer) mbar_wait(bar + 8 * (B_RS + 2), 0);
      mbar_wait(bar + 8 * (B_PDONE + 1), layer);
      mbar_wait(bar + 8 * B_U, layer);
#pragma unroll 1
      for (int lc = 0; lc < 4; lc += 2) {
        conv_sums(sb, lc, opaque_tid() - 256);
        TSW(1 + lc);
      }
      fence_async_smem();
      bar_sync(4, 128);
      conv_far(sb, opaque_tid() - 256);
      mbar_arrive(bar + 8 * B_FARM);
      TSW(4);
      mbar_wait(bar + 8 * (B_R + 1), layer);
      conv_epi<1, 2>(sb, xout, 0, opaque_tid() - 256);
      mbar_arrive(bar + 8 * (B_PUB + 1));
      TSW(5);
      mbar_wait(bar + 8 * (B_R + 2), layer);
      conv_epi<1, 1>(sb, xout, 2, opaque_tid() - 256);
      mbar_arrive(bar + 8 * (B_PUB + 2));
      TSW(6);
    }
  } else {
    asm volatile("setmaxnreg.dec.sync.aligned.u32 %0;" ::"n"(R_AGENT));
    bar_sync(0, NTHREADS);
    auto done = [&](int half, int c, int layer) { mbar_wait(bar + 8 * (B_DN + 8 * half + c), layer); };
    auto publish = [&](int layer, int k) {
      mbar_wait(bar + 8 * (B_PUB + k), layer);
      if (layer == 0) {
        red_release(&g_cnt[(C_C + k) * 32]);
      }
      else red_relaxed(&g_cnt[(C_F + 4 * k + (cta >> 5)) * 32]);
      TS(16 + layer * 56 + 40 + 7 + k);
    };
    if (warp == 12) {
      if (elect_one()) {
#pragma unroll 1
        for (int layer = 0; layer < 2; layer++) {
          auto ld_xe = [&](int c) {
            const uint32_t b = bar + 8 * (B_XF + c);
            mbar_expect(b, PG);
            if (layer == 0) tma_ld(sb + (c - 5) * PG, &p.mapX, c * 64, rb * 64, b);
            else tma_ld(sb + (c - 5) * PG, &p.mapXT, rb * 64, DM + c * 64, b);
          };
          if (layer == 0) {
            ld_x0(0, 2); ld_w(2); ld_x0(1, 2);
            if (hg >= 3) {
              mbar_expect(bar + 8 * B_SC, PG);
              tma_ld(sb + P_R * PG, &p.mapX, hg * 64, rb * 64, bar + 8 * B_SC);
            }
            if (rb < 4) tma_prefetch3(&p.mapW3, hg * 64, (4 + rb) * 64, 0);
            ld_x0(0, 3); ld_w(3); ld_x0(1, 3); ld_x0(0, 4); ld_x0(1, 4);
            done(0, 0, 0); done(1, 0, 0);
            ld_w(4);
            ld_x0(1, 5); ld_x0(1, 6); ld_x0(1, 7);
            done(0, 1, 0); done(1, 1, 0);
            ld_w(5);
            if (rb2 < 8) tma_prefetch5(&p.mapWo, q2 * 64, rb2 * 2);
            done(0, 2, 0);
            fence_async_smem();
            ld_xe(5); ld_xe(6); ld_xe(7);
          } else {
            mbar_wait(bar + 8 * B_PDONE, 0);
            mbar_wait(bar + 8 * (B_PDONE + 1), 0);
            mbar_wait(bar + 8 * (WPRE == 1 ? B_U : B_GB + 1), 0);
            ld_w(0); ld_w(1); ld_w(2);
            mbar_wait(bar + 8 * (B_PUB + 2), 0);
            fence_async_smem();
            ld_w(3);
            done(0, 2, 1);
            fence_async_global();
            fence_async_smem();
            ld_xe(5); ld_xe(6); ld_xe(7);
            done(1, 0, 1);
            ld_w(4);
            done(1, 1, 1);
            ld_w(5);
          }
          done(1, 2, layer);
          fence_async_smem();
          ld_w(6); ld_w(7);
          auto ld_res = [&](int half) {
            const uint32_t b = bar + 8 * (B_RF + half);
            mbar_expect(b, PG);
            if (layer == 0) tma_ld(sb + (P_R + half) * PG, &p.mapX, q2 * 64, (16 * half + rb2) * 64, b);
            else tma_ld(sb + (P_R + half) * PG, &p.mapXT, (16 * half + rb2) * 64, DM + q2 * 64, b);
          };
          done(0, 4, layer); done(1, 3, layer);
          fence_async_smem();
#pragma unroll 1
          for (int c = 0; c < 8; c++) {
            const uint32_t b = bar + 8 * (B_WOF + (c >> 1));
            if (c == 5) { ld_res(0); done(1, 4, layer); }
            if ((c & 1) == 0) mbar_expect(b, 2 * PG);
            tma_ld5(sb + wo_page(c) * PG, &p.mapWo, q2 * 64, c * 2, b);
          }
          mbar_wait(bar + 8 * B_KG, 0);
          fence_async_global();
          ld_res(1);
        }
      }
    } else if (warp == 13) {
      if (elect_one()) {
        mbar_wait(bar + 8 * (B_WF + 2), 0);
        asm volatile("prefetch.tensormap [%0];" ::"l"(&p.mapXT) : "memory");
        asm volatile("prefetch.tensormap [%0];" ::"l"(&p.mapOut) : "memory");
        asm volatile("prefetch.tensormap [%0];" ::"l"(&p.mapWo) : "memory");
        mbar_wait(bar + 8 * B_EP, 0);
        const unsigned e1 = lds32(sb + SM_EP) + 1;
        auto ld_x1 = [&](int half, int c0, int c1) {
          fence_async_global();
          fence_async_smem();
#pragma unroll 1
          for (int c = c0; c < c1; c++) {
            const uint32_t b = bar + 8 * (B_XF + 8 * half + c);
            mbar_expect(b, PG);
            tma_ld(sb + x_page(half, c) * PG, &p.mapXT, (16 * half + rb) * 64, DM + c * 64, b);
          }
        };
#pragma unroll 1
        for (int layer = 0; layer < 2; layer++) {
          if (layer == 1) {
            mbar_wait(bar + 8 * B_FARM, 0);
            mbar_wait(bar + 8 * B_PUB, 0);
            spin_until(&g_cnt[C_C * 32], e1 * NCTA);
            TS(10);
            ld_x1(0, 0, 3);
            if (hg >= 3) {
              mbar_expect(bar + 8 * B_SC, PG);
              tma_ld(sb + P_R * PG, &p.mapXT, rb * 64, DM + hg * 64, bar + 8 * B_SC);
            }
            ld_x1(0, 3, 5);
            mbar_wait(bar + 8 * (B_PUB + 1), 0);
            spin_until(&g_cnt[(C_C + 1) * 32], e1 * NCTA);
            TS(11);
            ld_x1(1, 0, 4);
            spin_until(&g_cnt[(C_C + 2) * 32], e1 * NCTA);
            TS(12);
            ld_x1(1, 4, 8);
          }
#pragma unroll 1
          for (int half = 0; half < 2; half++) {
            done(1, 7, layer);
            mbar_wait(bar + 8 * B_OST, layer);
            if (half) mbar_wait(bar + 8 * (B_OST + 1), layer);
            spin_until(&g_cnt[(C_O + layer * 32 + 16 * half + rb2) * 32], e1 * 32);
            fence_async_global();
            fence_async_smem();
#pragma unroll 1
            for (int c = 0; c < 4; c++) {
              const uint32_t b = bar + 8 * (B_OF + 4 * half + c);
              mbar_expect(b, 2 * PG);
              bulk_ld(sb + o_page(half, c) * PG, g_O + ((layer * 32 + 16 * half + rb2) * 4 + c) * PG, 2 * PG, b);
            }
          }
        }
        mbar_wait(bar + 8 * B_PUB, 1);
#pragma unroll 1
        for (int half = 0; half < 2; half++) {
          spin_until(&g_cnt[(C_F + 4 * (half ? 1 + (cta >> 6) : 0) + ((cta >> 4) & 3)) * 32], e1 * 32);
          fence_async_global();
          mbar_expect(bar + 8 * (B_TF + half), PG);
          tma_ld(sb + (16 + half) * PG, &p.mapXT, (16 * half + (cta & 15)) * 64, 3 * DM + (cta >> 4) * 64, bar + 8 * (B_TF + half));
        }
      }
    } else if (warp == 14) {
      mbar_wait(bar + 8 * B_EP, 0);
      const unsigned e1 = lds32(sb + SM_EP) + 1;
      done(0, 0, 0);
      if (lane == 0) { spin_until(&g_cnt[C_Z * 32], e1 * NCTA); TS(3); }
      __syncwarp();
      {
        const uint2* cp = g_colsum + (hg * 192 + lane);
        uint2 v[6];
        bool ok;
        int it = 0;
        do {
          ok = true;
#pragma unroll
          for (int i = 0; i < 6; i++) {
            asm volatile("ld.relaxed.gpu.global.v2.u32 {%0,%1}, [%2];" : "=r"(v[i].x), "=r"(v[i].y) : "l"(cp + 32 * i) : "memory");
            ok = ok && v[i].y == e1;
          }
          if (++it > (1 << 22)) __trap();
        } while (!__all_sync(~0u, ok));
#pragma unroll
        for (int i = 0; i < 6; i++) sts32f(sb + SM_CS + 4 * (lane + 32 * i), __uint_as_float(v[i].x));
      }
      __syncwarp();
      if (lane == 0) {
        mbar_arrive(bar + 8 * B_CSF);
        red_relaxed(&g_cnt[C_CS * 32]);
        TS(13);
#pragma unroll 1
        for (int i = 0; i < 4; i++) {
          const int layer = i >> 1;
          mbar_wait(bar + 8 * (B_PST + (i & 1)), layer);
          if (i & 1) mbar_wait(bar + 8 * B_AL, layer);
          spin_until(&g_cnt[(C_G + i) * 32], e1 * NCTA);
          if (i & 1) {
            const uint32_t b = bar + 8 * (B_GB + 1);
            fence_async_smem();
            mbar_expect(b, 4 * (3072 + 2048));
#pragma unroll 1
            for (int lc = 0; lc < 4; lc++) {
              bulk_ld(sb + cv_pe(lc), g_stats + (layer * 32 + 16 + 4 * lc) * 192, 3072, b);
              bulk_ld(sb + cv_x(1, lc), g_xT + ((size_t)(i - 1) * DM + cv_chan(cta, lc)) * LSEQ + 1024, 2048, b);
            }
            TS(14 + layer);
            publish(layer, 1);
          } else {
            mbar_arrive(bar + 8 * B_GB);
          }
        }
      }
    } else {
      const uint4 u = make_uint4(UNSET, UNSET, UNSET, UNSET);
      if (lane < 24) stg128((uint4*)g_stats + cta * 24 + lane, make_uint4(0, 0, 0, 0));
#pragma unroll 4
      for (int i = 0; i < 16; i++) stg128(g_halo + cta * 512 + 32 * i + lane, u);
#pragma unroll 4
      for (int i = 0; i < 16; i++) stg128(((i & 8) ? (uint4*)g_xT : (uint4*)g_O) + cta * 1024 + (i & 7) * 128 + (lane >> 1) * 8 + (lane & 1), u);
      __syncwarp();
      if (lane == 0) {
        red_release(&g_cnt[C_Z * 32]);
        publish(0, 0);
        publish(0, 2);
        const unsigned e1 = lds32(sb + SM_EP) + 1;
#pragma unroll 1
        for (int s = 0; s < 3; s++) {
          spin_until(&g_cnt[(C_R + s) * 32], e1 * 4);
          mbar_arrive(bar + 8 * (B_RS + s));
          TS(16 + 40 + 10 + s);
        }
        publish(1, 0);
        publish(1, 2);
      }
    }
  }
}

typedef CUresult (*EncodeFn)(CUtensorMap*, CUtensorMapDataType, cuuint32_t, void*, const cuuint64_t*, const cuuint64_t*,
                             const cuuint32_t*, const cuuint32_t*, CUtensorMapInterleave, CUtensorMapSwizzle,
                             CUtensorMapL2promotion, CUtensorMapFloatOOBfill);

static void make_map(EncodeFn enc, CUtensorMap* m, void* ptr, uint64_t cols, uint64_t rows, uint32_t box_rows) {
  cuuint64_t dims[2] = {cols, rows};
  cuuint64_t strides[1] = {cols * 2};
  cuuint32_t box[2] = {64, box_rows};
  cuuint32_t es[2] = {1, 1};
  enc(m, CU_TENSOR_MAP_DATA_TYPE_BFLOAT16, 2, ptr, dims, strides, box, es, CU_TENSOR_MAP_INTERLEAVE_NONE,
      CU_TENSOR_MAP_SWIZZLE_128B, CU_TENSOR_MAP_L2_PROMOTION_L2_128B, CU_TENSOR_MAP_FLOAT_OOB_FILL_NONE);
}
static void make_map3(EncodeFn enc, CUtensorMap* m, void* ptr, uint64_t d0, uint64_t cols, uint64_t rows, uint64_t blk_stride,
                      uint64_t nblocks, uint32_t nblk) {
  cuuint64_t dims[3] = {d0, rows, nblocks};
  cuuint64_t strides[2] = {cols * 2, blk_stride * 2};
  cuuint32_t box[3] = {64, 64, nblk};
  cuuint32_t es[3] = {1, 1, 1};
  enc(m, CU_TENSOR_MAP_DATA_TYPE_BFLOAT16, 3, ptr, dims, strides, box, es, CU_TENSOR_MAP_INTERLEAVE_NONE,
      CU_TENSOR_MAP_SWIZZLE_128B, CU_TENSOR_MAP_L2_PROMOTION_L2_128B, CU_TENSOR_MAP_FLOAT_OOB_FILL_NONE);
}

extern "C" void kernel_launch(void* const* d_in, const int* in_sizes, int n_in, void* d_out, int out_size) {
  static Params prm;
  static void* cached[13] = {nullptr};
  static bool attr_done = false;
  bool same = attr_done && cached[12] == d_out;
  for (int i = 0; i < 12 && same; i++) same = cached[i] == d_in[i];
  if (!same) {
    void* fn = nullptr;
    cudaDriverEntryPointQueryResult qr;
    cudaGetDriverEntryPoint("cuTensorMapEncodeTiled", &fn, cudaEnableDefault, &qr);
    EncodeFn enc = (EncodeFn)fn;
    void* pXT;
    cudaGetSymbolAddress(&pXT, g_xT);
    make_map(enc, &prm.mapX, d_in[0], DM, LSEQ, 64);
    make_map(enc, &prm.mapXT, pXT, LSEQ, 4 * DM, 64);
    make_map(enc, &prm.mapOut, d_out, DM, LSEQ, 64);
    {
      cuuint64_t dims[5] = {DM, 2, 4, 4, 16};
      cuuint64_t strides[4] = {DM * 2, 8 * DM * 2, 2 * DM * 2, 32 * DM * 2};
      cuuint32_t box[5] = {64, 2, 4, 4, 2};
      cuuint32_t es[5] = {1, 1, 1, 1, 1};
      enc(&prm.mapWo, CU_TENSOR_MAP_DATA_TYPE_BFLOAT16, 5, d_in[2], dims, strides, box, es, CU_TENSOR_MAP_INTERLEAVE_NONE,
          CU_TENSOR_MAP_SWIZZLE_128B, CU_TENSOR_MAP_L2_PROMOTION_L2_128B, CU_TENSOR_MAP_FLOAT_OOB_FILL_NONE);
    }
    make_map3(enc, &prm.mapW3, d_in[1], DM, 3 * DM, DM, DM, 3, 3);
    prm.wqkv = (const bf16*)d_in[1];
    prm.a_re = (const bf16*)d_in[4]; prm.a_im = (const bf16*)d_in[5];
    prm.b_re = (const bf16*)d_in[6]; prm.b_im = (const bf16*)d_in[7];
    prm.c_re = (const bf16*)d_in[8]; prm.c_im = (const bf16*)d_in[9];
    prm.log_dt = (const bf16*)d_in[10]; prm.dskip = (const bf16*)d_in[11];
    cudaFuncSetAttribute(fused_kernel, cudaFuncAttributeMaxDynamicSharedMemorySize, SM_TOTAL);
    for (int i = 0; i < 12; i++) cached[i] = d_in[i];
    cached[12] = d_out;
    attr_done = true;
  }
  fused_kernel<<<NCTA + 4, NTHREADS, SM_TOTAL>>>(prm);
}
```

```cpp
#include <cuda_runtime.h>
#include <cuda_bf16.h>
#include <cuda.h>
#include <stdint.h>

typedef __nv_bfloat16 bf16;

constexpr int LSEQ = 2048;
constexpr int DM = 512;
constexpr int NCTA = 128;
constexpr int NTHREADS = 512;
#define R_CONS 200
#define R_HELP 88
#define R_AGENT 24
#define GPOS 4
#define TURN0 4
#define TURN1 4

constexpr int PG = 8192;
constexpr int P_R = 25;
__host__ __device__ constexpr int x_page(int half, int c) { return half ? 8 + c : c < 5 ? c : c - 5; }
__host__ __device__ constexpr int w_page(int c) { return (c & 3) < 3 ? 16 + 3 * (c & 3) : c < 4 ? 5 : 8; }
__host__ __device__ constexpr int wo_page(int c) { return c < 5 ? 3 + c : 11 + c; }
__host__ __device__ constexpr int o_page(int half, int pair) { return half ? (pair ? 17 + 2 * pair : 0) : 8 + 2 * pair; }
constexpr int SM_KGB = (P_R + 1) * PG;
constexpr int SM_KC = 27 * PG;
constexpr int KC_STRIDE = 648;
__host__ __device__ constexpr int kc_off(int lc) { return SM_KC + (lc & 1) * 2 * KC_STRIDE + (lc < 2 ? 3328 : 0); }
constexpr int SM_KGT = SM_KC + 3328 + 2592;
constexpr int SM_CS = SM_KGT + 2048;
constexpr int SM_RED = SM_CS + 768;
constexpr int SM_EP = SM_RED + 16;
constexpr int SM_STG = SM_KGT;
constexpr int SM_BAR = SM_RED + 32;
constexpr int SM_TS = SM_BAR + 768;
constexpr int SM_TOTAL = SM_TS + 512;
static_assert(SM_TOTAL <= 232448 && SM_STG % 16 == 0 && SM_KGT % 16 == 0, "shared memory");

constexpr int CV_UH = 140 * 16;
__host__ __device__ constexpr int cv_u(int lc) { return (8 + 2 * lc) * PG; }
__host__ __device__ constexpr int cv_pe(int lc) { return cv_u(lc) + 4480; }
__host__ __device__ constexpr int cv_pb1(int lc, int w) { return w ? cv_u(lc) + 8960 + (w - 1) * 2048 : 7 * PG + lc * 2048; }
__host__ __device__ constexpr int cv_fa(int lc) { return cv_pb1(lc, 1) + 128; }
__host__ __device__ constexpr int cv_dump(int lc) { return cv_u(lc) + 16256; }
__host__ __device__ constexpr int cv_pb0(int lc, int w) { return lc * PG + w * 2048; }
__host__ __device__ constexpr int cv_se(int lc) { return 4 * PG + lc * 4096; }
__host__ __device__ constexpr int cv_so(int lc) { return cv_se(lc) + 2048; }
__host__ __device__ constexpr int cv_pf(int lc) { return 6 * PG + lc * 2048; }
__host__ __device__ constexpr int cv_x(int half, int lc) { return (P_R + half) * PG + lc * 2048; }
constexpr int CV_ST = 22 * PG;
__host__ __device__ constexpr int cv_chan(int cta, int lc) { return 2 * cta + (lc & 1) + 256 * (lc >> 1); }

enum {
  B_XF = 0,
  B_WF = 16,
  B_OF = 24,
  B_DN = 32,
  B_WOF = 48,
  B_RF = 52,
  B_PST = 54,
  B_OST = 56,
  B_PDONE = 58,
  B_GB = 60,
  B_TF = 62,
  B_CSF = 64,
  B_EP = 65,
  B_KG = 67,
  B_FARM = 68,
  B_PE = 70,
  B_U = 71,
  B_PUB = 74,
  B_R = 77,
  B_END = 80,
  B_SC = 81,
  B_RT = 82,
  B_U1 = 84,
  B_RS = 85,
  B_COUNT = 88
};

enum {
  C_CS = 0,
  C_G = 1,
  C_C = 5,
  C_F = 8,
  C_O = 20,
  C_Z = 84,
  C_R = 85,
  C_COUNT = 88
};

__device__ unsigned g_cnt[C_COUNT * 32];
__device__ __align__(1024) bf16 g_O[2 * LSEQ * DM];
__device__ __align__(1024) bf16 g_xT[4 * DM * LSEQ];
__device__ __align__(1024) float g_stats[2 * 32 * 192];
__device__ __align__(1024) uint2 g_colsum[3 * DM];
__device__ __align__(1024) uint4 g_halo[2 * 32 * 8 * 256];
__device__ __align__(1024) uint4 g_part[2 * 32 * 8 * 64];
#define TS(i) do { } while (0)
#define TSW(k) do { if ((threadIdx.x & 127) == 0) TS(16 + layer * 56 + (threadIdx.x >> 7) * 20 + (k)); } while (0)
#define TSG(k) do { } while (0)

#define RETRY(i) do { } while (0)
#define LTS(i) do { } while (0)

struct Params {
  CUtensorMap mapX, mapW3, mapXT, mapOut, mapWo;
  const bf16 *wqkv, *a_re, *a_im, *b_re, *b_im, *c_re, *c_im, *log_dt, *dskip;
  int first;
};

__device__ __forceinline__ uint32_t s32(const void* p) { return (uint32_t)__cvta_generic_to_shared(p); }
__device__ __forceinline__ void mbar_init(uint32_t b, int c) { asm volatile("mbarrier.init.shared::cta.b64 [%0], %1;" ::"r"(b), "r"(c) : "memory"); }
__device__ __forceinline__ void mbar_expect(uint32_t b, int bytes) { asm volatile("mbarrier.arrive.expect_tx.shared::cta.b64 _, [%0], %1;" ::"r"(b), "r"(bytes) : "memory"); }
__device__ __forceinline__ void mbar_arrive(uint32_t b) { asm volatile("mbarrier.arrive.shared::cta.b64 _, [%0];" ::"r"(b) : "memory"); }
__device__ __forceinline__ void mbar_wait(uint32_t b, int parity) {
  asm volatile("{\n.reg .pred p;\nWAIT_LOOP:\nmbarrier.try_wait.parity.shared::cta.b64 p, [%0], %1;\n@p bra WAIT_DONE;\nbra WAIT_LOOP;\nWAIT_DONE:\n}" ::"r"(b), "r"(parity) : "memory");
}
__device__ __forceinline__ bool mbar_test(uint32_t b, int parity) {
  uint32_t ok;
  asm volatile("{\n.reg .pred p;\nmbarrier.test_wait.parity.shared::cta.b64 p, [%1], %2;\nselp.u32 %0, 1, 0, p;\n}" : "=r"(ok) : "r"(b), "r"(parity) : "memory");
  return ok != 0;
}
__device__ __forceinline__ int opaque_tid() { int v; asm volatile("mov.u32 %0, %%tid.x;" : "=r"(v)); return v; }
__device__ __forceinline__ bool elect_one() {
  uint32_t r;
  asm volatile("{\n.reg .pred p;\nelect.sync _|p, 0xffffffff;\nselp.u32 %0, 1, 0, p;\n}" : "=r"(r));
  return r != 0;
}
__device__ __forceinline__ void tma_ld(uint32_t dst, const CUtensorMap* m, int c0, int c1, uint32_t bar) {
  asm volatile("cp.async.bulk.tensor.2d.shared::cluster.global.mbarrier::complete_tx::bytes [%0], [%1, {%3, %4}], [%2];"
               ::"r"(dst), "l"(m), "r"(bar), "r"(c0), "r"(c1) : "memory");
}
__device__ __forceinline__ void tma_ld3(uint32_t dst, const CUtensorMap* m, int c0, int c1, int c2, uint32_t bar) {
  asm volatile("cp.async.bulk.tensor.3d.shared::cluster.global.mbarrier::complete_tx::bytes [%0], [%1, {%3, %4, %5}], [%2];"
               ::"r"(dst), "l"(m), "r"(bar), "r"(c0), "r"(c1), "r"(c2) : "memory");
}
__device__ __forceinline__ void tma_ld5(uint32_t dst, const CUtensorMap* m, int c0, int c4, uint32_t bar) {
  asm volatile("cp.async.bulk.tensor.5d.shared::cluster.global.mbarrier::complete_tx::bytes [%0], [%1, {%3, 0, 0, 0, %4}], [%2];"
               ::"r"(dst), "l"(m), "r"(bar), "r"(c0), "r"(c4) : "memory");
}
__device__ __forceinline__ void tma_prefetch5(const CUtensorMap* m, int c0, int c4) {
  asm volatile("cp.async.bulk.prefetch.tensor.5d.L2.global.tile [%0, {%1, 0, 0, 0, %2}];" ::"l"(m), "r"(c0), "r"(c4) : "memory");
}
__device__ __forceinline__ void tma_prefetch2(const CUtensorMap* m, int c0, int c1) {
  asm volatile("cp.async.bulk.prefetch.tensor.2d.L2.global.tile [%0, {%1, %2}];" ::"l"(m), "r"(c0), "r"(c1) : "memory");
}
__device__ __forceinline__ void tma_prefetch3(const CUtensorMap* m, int c0, int c1, int c2) {
  asm volatile("cp.async.bulk.prefetch.tensor.3d.L2.global.tile [%0, {%1, %2, %3}];" ::"l"(m), "r"(c0), "r"(c1), "r"(c2) : "memory");
}
__device__ __forceinline__ void tma_st(const CUtensorMap* m, int c0, int c1, uint32_t src) {
  asm volatile("cp.async.bulk.tensor.2d.global.shared::cta.bulk_group [%0, {%2, %3}], [%1];" ::"l"(m), "r"(src), "r"(c0), "r"(c1) : "memory");
}
__device__ __forceinline__ void bulk_ld(uint32_t dst, const void* src, int bytes, uint32_t bar) {
  asm volatile("cp.async.bulk.shared::cluster.global.mbarrier::complete_tx::bytes [%0], [%1], %2, [%3];" ::"r"(dst), "l"(src), "r"(bytes), "r"(bar) : "memory");
}
__device__ __forceinline__ void bulk_st(void* dst, uint32_t src, int bytes) {
  asm volatile("cp.async.bulk.global.shared::cta.bulk_group [%0], [%1], %2;" ::"l"(dst), "r"(src), "r"(bytes) : "memory");
}
__device__ __forceinline__ void bulk_red_add_f32(void* dst, uint32_t src, int bytes) {
  asm volatile("cp.reduce.async.bulk.global.shared::cta.bulk_group.add.f32 [%0], [%1], %2;" ::"l"(dst), "r"(src), "r"(bytes) : "memory");
}
__device__ __forceinline__ void bulk_commit() { asm volatile("cp.async.bulk.commit_group;" ::: "memory"); }
__device__ __forceinline__ void bulk_wait_all() { asm volatile("cp.async.bulk.wait_group 0;" ::: "memory"); }
__device__ __forceinline__ void fence_async_smem() { asm volatile("fence.proxy.async.shared::cta;" ::: "memory"); }
__device__ __forceinline__ void fence_async_global() { asm volatile("fence.proxy.async.global;" ::: "memory"); }
__device__ __forceinline__ void bar_sync(int id, int n) { asm volatile("bar.sync %0, %1;" ::"r"(id), "r"(n) : "memory"); }
__device__ __forceinline__ void bar_arrive(int id, int n) { asm volatile("bar.arrive %0, %1;" ::"r"(id), "r"(n) : "memory"); }
__device__ __forceinline__ bool bar_or(int id, int n, bool v) {
  uint32_t r;
  asm volatile("{\n.reg .pred p, q;\nsetp.ne.u32 q, %3, 0;\nbar.red.or.pred p, %1, %2, q;\nselp.u32 %0, 1, 0, p;\n}" : "=r"(r) : "r"(id), "r"(n), "r"((uint32_t)v) : "memory");
  return r != 0;
}
__device__ __forceinline__ void bulk_wait_read() { asm volatile("cp.async.bulk.wait_group.read 0;" ::: "memory"); }
__device__ __forceinline__ void stg128(void* p, uint4 v) { asm volatile("st.relaxed.gpu.global.v4.u32 [%0], {%1,%2,%3,%4};" ::"l"(p), "r"(v.x), "r"(v.y), "r"(v.z), "r"(v.w) : "memory"); }
constexpr uint32_t UNSET = 0xffffffffu;
constexpr int MAX_RETRY = 1 << 16;
__device__ __forceinline__ void wg_fence() { asm volatile("wgmma.fence.sync.aligned;" ::: "memory"); }
__device__ __forceinline__ void wg_commit() { asm volatile("wgmma.commit_group.sync.aligned;" ::: "memory"); }
template <int N> __device__ __forceinline__ void wg_wait() { asm volatile("wgmma.wait_group.sync.aligned %0;" ::"n"(N) : "memory"); }
__device__ __forceinline__ uint64_t mkdesc(uint32_t addr, uint32_t lbo, uint32_t sbo, int sw) {
  return (uint64_t)((addr & 0x3FFFF) >> 4) | ((uint64_t)(lbo >> 4) << 16) | ((uint64_t)(sbo >> 4) << 32) | ((uint64_t)sw << 62);
}
__device__ __forceinline__ void ldsm4(uint32_t* r, uint32_t a) {
  asm volatile("ldmatrix.sync.aligned.m8n8.x4.shared.b16 {%0,%1,%2,%3}, [%4];" : "=r"(r[0]), "=r"(r[1]), "=r"(r[2]), "=r"(r[3]) : "r"(a) : "memory");
}
__device__ __forceinline__ void ldsm4t(uint32_t* r, uint32_t a) {
  asm volatile("ldmatrix.sync.aligned.m8n8.x4.trans.shared.b16 {%0,%1,%2,%3}, [%4];" : "=r"(r[0]), "=r"(r[1]), "=r"(r[2]), "=r"(r[3]) : "r"(a) : "memory");
}
__device__ __forceinline__ void stsm4(uint32_t a, uint32_t r0, uint32_t r1, uint32_t r2, uint32_t r3) {
  asm volatile("stmatrix.sync.aligned.m8n8.x4.shared.b16 [%0], {%1,%2,%3,%4};" ::"r"(a), "r"(r0), "r"(r1), "r"(r2), "r"(r3) : "memory");
}
__device__ __forceinline__ void stsm4t(uint32_t a, uint32_t r0, uint32_t r1, uint32_t r2, uint32_t r3) {
  asm volatile("stmatrix.sync.aligned.m8n8.x4.trans.shared.b16 [%0], {%1,%2,%3,%4};" ::"r"(a), "r"(r0), "r"(r1), "r"(r2), "r"(r3) : "memory");
}
__device__ __forceinline__ uint32_t movm_t(uint32_t a) { uint32_t r; asm volatile("movmatrix.sync.aligned.m8n8.trans.b16 %0, %1;" : "=r"(r) : "r"(a)); return r; }
__device__ __forceinline__ uint32_t lds32(uint32_t a) { uint32_t v; asm volatile("ld.shared.b32 %0, [%1];" : "=r"(v) : "r"(a) : "memory"); return v; }
__device__ __forceinline__ float2 lds64f(uint32_t a) { float2 v; asm volatile("ld.shared.v2.f32 {%0,%1}, [%2];" : "=f"(v.x), "=f"(v.y) : "r"(a) : "memory"); return v; }
__device__ __forceinline__ float4 lds128f(uint32_t a) { float4 v; asm volatile("ld.shared.v4.f32 {%0,%1,%2,%3}, [%4];" : "=f"(v.x), "=f"(v.y), "=f"(v.z), "=f"(v.w) : "r"(a) : "memory"); return v; }
__device__ __forceinline__ uint4 lds128(uint32_t a) { uint4 v; asm volatile("ld.shared.v4.b32 {%0,%1,%2,%3}, [%4];" : "=r"(v.x), "=r"(v.y), "=r"(v.z), "=r"(v.w) : "r"(a) : "memory"); return v; }
__device__ __forceinline__ void sts128(uint32_t a, uint4 v) { asm volatile("st.shared.v4.b32 [%0], {%1,%2,%3,%4};" ::"r"(a), "r"(v.x), "r"(v.y), "r"(v.z), "r"(v.w) : "memory"); }
__device__ __forceinline__ void sts128f(uint32_t a, float x, float y, float z, float w) { asm volatile("st.shared.v4.f32 [%0], {%1,%2,%3,%4};" ::"r"(a), "f"(x), "f"(y), "f"(z), "f"(w) : "memory"); }
__device__ __forceinline__ void sts32f(uint32_t a, float v) { asm volatile("st.shared.f32 [%0], %1;" ::"r"(a), "f"(v) : "memory"); }
__device__ __forceinline__ void sts16(uint32_t a, uint16_t v) { asm volatile("st.shared.u16 [%0], %1;" ::"r"(a), "h"(v) : "memory"); }
__device__ __forceinline__ uint32_t lds16(uint32_t a) { uint16_t v; asm volatile("ld.shared.u16 %0, [%1];" : "=h"(v) : "r"(a) : "memory"); return v; }
__device__ __forceinline__ uint32_t packbf(float lo, float hi) { uint32_t r; asm("cvt.rn.bf16x2.f32 %0, %1, %2;" : "=r"(r) : "f"(hi), "f"(lo)); return r; }
__device__ __forceinline__ float bf_lo(uint32_t v) { return __uint_as_float(v << 16); }
__device__ __forceinline__ float bf_hi(uint32_t v) { return __uint_as_float(v & 0xffff0000u); }
__device__ __forceinline__ float ex2(float x) { float r; asm("ex2.approx.ftz.f32 %0, %1;" : "=f"(r) : "f"(x)); return r; }
__device__ __forceinline__ float rsqrt_approx(float x) { float r; asm("rsqrt.approx.ftz.f32 %0, %1;" : "=f"(r) : "f"(x)); return r; }
__device__ __forceinline__ float rcp_approx(float x) { float r; asm("rcp.approx.ftz.f32 %0, %1;" : "=f"(r) : "f"(x)); return r; }
__device__ __forceinline__ void mma_bf16(float* d, const uint32_t* a, uint32_t b0, uint32_t b1) {
  asm("mma.sync.aligned.m16n8k16.row.col.f32.bf16.bf16.f32 {%0,%1,%2,%3}, {%4,%5,%6,%7}, {%8,%9}, {%0,%1,%2,%3};"
               : "+f"(d[0]), "+f"(d[1]), "+f"(d[2]), "+f"(d[3]) : "r"(a[0]), "r"(a[1]), "r"(a[2]), "r"(a[3]), "r"(b0), "r"(b1));
}
__device__ __forceinline__ void mma_tf32(float* d, float a0, float a1, float a2, float a3, float b0, float b1) {
  asm("mma.sync.aligned.m16n8k8.row.col.f32.tf32.tf32.f32 {%0,%1,%2,%3}, {%4,%5,%6,%7}, {%8,%9}, {%0,%1,%2,%3};"
               : "+f"(d[0]), "+f"(d[1]), "+f"(d[2]), "+f"(d[3])
               : "r"(__float_as_uint(a0)), "r"(__float_as_uint(a1)), "r"(__float_as_uint(a2)), "r"(__float_as_uint(a3)),
                 "r"(__float_as_uint(b0)), "r"(__float_as_uint(b1)));
}
__device__ __forceinline__ void red_release(unsigned* p) { asm volatile("red.release.gpu.global.add.u32 [%0], 1;" ::"l"(p) : "memory"); }
__device__ __forceinline__ void red_relaxed(unsigned* p) { asm volatile("red.relaxed.gpu.global.add.u32 [%0], 1;" ::"l"(p) : "memory"); }
__device__ __forceinline__ unsigned ld_relaxed(const unsigned* p) { unsigned v; asm volatile("ld.relaxed.gpu.global.u32 %0, [%1];" : "=r"(v) : "l"(p) : "memory"); return v; }
__device__ __forceinline__ void spin_until(const unsigned* p, unsigned target) {
  int it = 0;
  while ((int)(ld_relaxed(p) - target) < 0) {
    if (++it > (1 << 23)) __trap();
  }
}
__device__ __forceinline__ uint4 ldcg128(const void* p) { uint4 v; asm volatile("ld.global.cg.v4.b32 {%0,%1,%2,%3}, [%4];" : "=r"(v.x), "=r"(v.y), "=r"(v.z), "=r"(v.w) : "l"(p) : "memory"); return v; }
__device__ __forceinline__ uint4 ld_tagged(const uint4* p) { uint4 v; asm volatile("ld.relaxed.gpu.global.v4.u32 {%0,%1,%2,%3}, [%4];" : "=r"(v.x), "=r"(v.y), "=r"(v.z), "=r"(v.w) : "l"(p) : "memory"); return v; }
__device__ __forceinline__ void st_tagged(uint4* p, uint32_t a, uint32_t b, uint32_t tag) { asm volatile("st.relaxed.gpu.global.v4.u32 [%0], {%1,%2,%3,%2};" ::"l"(p), "r"(a), "r"(tag), "r"(b) : "memory"); }
__device__ __forceinline__ void st_tagged3(uint4* p, uint32_t a, uint32_t b, uint32_t c, uint32_t tag) { asm volatile("st.relaxed.gpu.global.v4.u32 [%0], {%1,%2,%3,%4};" ::"l"(p), "r"(a), "r"(b), "r"(c), "r"(tag) : "memory"); }
__device__ __forceinline__ uint4 poll_tagged(const uint4* p, uint32_t tag) {
  uint4 v = ld_tagged(p);
  int it = 0;
  while (v.y != tag || v.w != tag) {
    if (++it > (1 << 22)) __trap();
    v = ld_tagged(p);
  }
  return v;
}
__device__ __forceinline__ uint32_t hadd2(uint32_t a, uint32_t b) { uint32_t r; asm("add.rn.bf16x2 %0, %1, %2;" : "=r"(r) : "r"(a), "r"(b)); return r; }
__device__ __forceinline__ uint32_t hmul2(uint32_t a, uint32_t b) { uint32_t r; asm("mul.rn.bf16x2 %0, %1, %2;" : "=r"(r) : "r"(a), "r"(b)); return r; }

__device__ __forceinline__ uint32_t hfma2(uint32_t a, uint32_t b, uint32_t c) { uint32_t r; asm("fma.rn.bf16x2 %0, %1, %2, %3;" : "=r"(r) : "r"(a), "r"(b), "r"(c)); return r; }
__device__ __forceinline__ void sts32(uint32_t a, uint32_t v) { asm volatile("st.shared.u32 [%0], %1;" ::"r"(a), "r"(v) : "memory"); }

template <int N> __device__ __forceinline__ void acc_fence(float* a) {
#pragma unroll
  for (int i = 0; i < N; i++) asm volatile("" : "+f"(a[i]) :: "memory");
}

template<int N,int TB> __device__ __forceinline__ void wgmma_rs(float* d, const uint32_t* a, uint64_t db, int sd);
template<int N,int TA,int TB> __device__ __forceinline__ void wgmma_ss(float* d, uint64_t da, uint64_t db, int sd);
template<> __device__ __forceinline__ void wgmma_rs<64,0>(float* d, const uint32_t* a, uint64_t db, int sd) {
  asm volatile("{\n.reg .pred p;\nsetp.ne.b32 p, %37, 0;\nwgmma.mma_async.sync.aligned.m64n64k16.f32.bf16.bf16 {%0,%1,%2,%3,%4,%5,%6,%7,%8,%9,%10,%11,%12,%13,%14,%15,%16,%17,%18,%19,%20,%21,%22,%23,%24,%25,%26,%27,%28,%29,%30,%31}, {%32,%33,%34,%35}, %36, p, 1, 1, 0;\n}\n"
   : "+f"(d[0]),"+f"(d[1]),"+f"(d[2]),"+f"(d[3]),"+f"(d[4]),"+f"(d[5]),"+f"(d[6]),"+f"(d[7]),"+f"(d[8]),"+f"(d[9]),"+f"(d[10]),"+f"(d[11]),"+f"(d[12]),"+f"(d[13]),"+f"(d[14]),"+f"(d[15]),"+f"(d[16]),"+f"(d[17]),"+f"(d[18]),"+f"(d[19]),"+f"(d[20]),"+f"(d[21]),"+f"(d[22]),"+f"(d[23]),"+f"(d[24]),"+f"(d[25]),"+f"(d[26]),"+f"(d[27]),"+f"(d[28]),"+f"(d[29]),"+f"(d[30]),"+f"(d[31])
   : "r"(a[0]), "r"(a[1]), "r"(a[2]), "r"(a[3]), "l"(db), "r"(sd));
}
template<> __device__ __forceinline__ void wgmma_rs<56,0>(float* d, const uint32_t* a, uint64_t db, int sd) {
  asm volatile("{\n.reg .pred p;\nsetp.ne.b32 p, %33, 0;\nwgmma.mma_async.sync.aligned.m64n56k16.f32.bf16.bf16 {%0,%1,%2,%3,%4,%5,%6,%7,%8,%9,%10,%11,%12,%13,%14,%15,%16,%17,%18,%19,%20,%21,%22,%23,%24,%25,%26,%27}, {%28,%29,%30,%31}, %32, p, 1, 1, 0;\n}\n"
   : "+f"(d[0]),"+f"(d[1]),"+f"(d[2]),"+f"(d[3]),"+f"(d[4]),"+f"(d[5]),"+f"(d[6]),"+f"(d[7]),"+f"(d[8]),"+f"(d[9]),"+f"(d[10]),"+f"(d[11]),"+f"(d[12]),"+f"(d[13]),"+f"(d[14]),"+f"(d[15]),"+f"(d[16]),"+f"(d[17]),"+f"(d[18]),"+f"(d[19]),"+f"(d[20]),"+f"(d[21]),"+f"(d[22]),"+f"(d[23]),"+f"(d[24]),"+f"(d[25]),"+f"(d[26]),"+f"(d[27])
   : "r"(a[0]), "r"(a[1]), "r"(a[2]), "r"(a[3]), "l"(db), "r"(sd));
}
template<> __device__ __forceinline__ void wgmma_rs<48,0>(float* d, const uint32_t* a, uint64_t db, int sd) {
  asm volatile("{\n.reg .pred p;\nsetp.ne.b32 p, %29, 0;\nwgmma.mma_async.sync.aligned.m64n48k16.f32.bf16.bf16 {%0,%1,%2,%3,%4,%5,%6,%7,%8,%9,%10,%11,%12,%13,%14,%15,%16,%17,%18,%19,%20,%21,%22,%23}, {%24,%25,%26,%27}, %28, p, 1, 1, 0;\n}\n"
   : "+f"(d[0]),"+f"(d[1]),"+f"(d[2]),"+f"(d[3]),"+f"(d[4]),"+f"(d[5]),"+f"(d[6]),"+f"(d[7]),"+f"(d[8]),"+f"(d[9]),"+f"(d[10]),"+f"(d[11]),"+f"(d[12]),"+f"(d[13]),"+f"(d[14]),"+f"(d[15]),"+f"(d[16]),"+f"(d[17]),"+f"(d[18]),"+f"(d[19]),"+f"(d[20]),"+f"(d[21]),"+f"(d[22]),"+f"(d[23])
   : "r"(a[0]), "r"(a[1]), "r"(a[2]), "r"(a[3]), "l"(db), "r"(sd));
}
template<> __device__ __forceinline__ void wgmma_rs<40,0>(float* d, const uint32_t* a, uint64_t db, int sd) {
  asm volatile("{\n.reg .pred p;\nsetp.ne.b32 p, %25, 0;\nwgmma.mma_async.sync.aligned.m64n40k16.f32.bf16.bf16 {%0,%1,%2,%3,%4,%5,%6,%7,%8,%9,%10,%11,%12,%13,%14,%15,%16,%17,%18,%19}, {%20,%21,%22,%23}, %24, p, 1, 1, 0;\n}\n"
   : "+f"(d[0]),"+f"(d[1]),"+f"(d[2]),"+f"(d[3]),"+f"(d[4]),"+f"(d[5]),"+f"(d[6]),"+f"(d[7]),"+f"(d[8]),"+f"(d[9]),"+f"(d[10]),"+f"(d[11]),"+f"(d[12]),"+f"(d[13]),"+f"(d[14]),"+f"(d[15]),"+f"(d[16]),"+f"(d[17]),"+f"(d[18]),"+f"(d[19])
   : "r"(a[0]), "r"(a[1]), "r"(a[2]), "r"(a[3]), "l"(db), "r"(sd));
}
template<> __device__ __forceinline__ void wgmma_rs<32,0>(float* d, const uint32_t* a, uint64_t db, int sd) {
  asm volatile("{\n.reg .pred p;\nsetp.ne.b32 p, %21, 0;\nwgmma.mma_async.sync.aligned.m64n32k16.f32.bf16.bf16 {%0,%1,%2,%3,%4,%5,%6,%7,%8,%9,%10,%11,%12,%13,%14,%15}, {%16,%17,%18,%19}, %20, p, 1, 1, 0;\n}\n"
   : "+f"(d[0]),"+f"(d[1]),"+f"(d[2]),"+f"(d[3]),"+f"(d[4]),"+f"(d[5]),"+f"(d[6]),"+f"(d[7]),"+f"(d[8]),"+f"(d[9]),"+f"(d[10]),"+f"(d[11]),"+f"(d[12]),"+f"(d[13]),"+f"(d[14]),"+f"(d[15])
   : "r"(a[0]), "r"(a[1]), "r"(a[2]), "r"(a[3]), "l"(db), "r"(sd));
}
template<> __device__ __forceinline__ void wgmma_rs<24,0>(float* d, const uint32_t* a, uint64_t db, int sd) {
  asm volatile("{\n.reg .pred p;\nsetp.ne.b32 p, %17, 0;\nwgmma.mma_async.sync.aligned.m64n24k16.f32.bf16.bf16 {%0,%1,%2,%3,%4,%5,%6,%7,%8,%9,%10,%11}, {%12,%13,%14,%15}, %16, p, 1, 1, 0;\n}\n"
   : "+f"(d[0]),"+f"(d[1]),"+f"(d[2]),"+f"(d[3]),"+f"(d[4]),"+f"(d[5]),"+f"(d[6]),"+f"(d[7]),"+f"(d[8]),"+f"(d[9]),"+f"(d[10]),"+f"(d[11])
   : "r"(a[0]), "r"(a[1]), "r"(a[2]), "r"(a[3]), "l"(db), "r"(sd));
}
template<> __device__ __forceinline__ void wgmma_rs<16,0>(float* d, const uint32_t* a, uint64_t db, int sd) {
  asm volatile("{\n.reg .pred p;\nsetp.ne.b32 p, %13, 0;\nwgmma.mma_async.sync.aligned.m64n16k16.f32.bf16.bf16 {%0,%1,%2,%3,%4,%5,%6,%7}, {%8,%9,%10,%11}, %12, p, 1, 1, 0;\n}\n"
   : "+f"(d[0]),"+f"(d[1]),"+f"(d[2]),"+f"(d[3]),"+f"(d[4]),"+f"(d[5]),"+f"(d[6]),"+f"(d[7])
   : "r"(a[0]), "r"(a[1]), "r"(a[2]), "r"(a[3]), "l"(db), "r"(sd));
}
template<> __device__ __forceinline__ void wgmma_rs<8,0>(float* d, const uint32_t* a, uint64_t db, int sd) {
  asm volatile("{\n.reg .pred p;\nsetp.ne.b32 p, %9, 0;\nwgmma.mma_async.sync.aligned.m64n8k16.f32.bf16.bf16 {%0,%1,%2,%3}, {%4,%5,%6,%7}, %8, p, 1, 1, 0;\n}\n"
   : "+f"(d[0]),"+f"(d[1]),"+f"(d[2]),"+f"(d[3])
   : "r"(a[0]), "r"(a[1]), "r"(a[2]), "r"(a[3]), "l"(db), "r"(sd));
}
template<> __device__ __forceinline__ void wgmma_ss<16,0,1>(float* d, uint64_t da, uint64_t db, int sd) {
  asm volatile("{\n.reg .pred p;\nsetp.ne.b32 p, %10, 0;\nwgmma.mma_async.sync.aligned.m64n16k16.f32.bf16.bf16 {%0,%1,%2,%3,%4,%5,%6,%7}, %8, %9, p, 1, 1, 0, 1;\n}\n"
   : "+f"(d[0]),"+f"(d[1]),"+f"(d[2]),"+f"(d[3]),"+f"(d[4]),"+f"(d[5]),"+f"(d[6]),"+f"(d[7])
   : "l"(da), "l"(db), "r"(sd));
}
template<> __device__ __forceinline__ void wgmma_ss<64,0,1>(float* d, uint64_t da, uint64_t db, int sd) {
  asm volatile("{\n.reg .pred p;\nsetp.ne.b32 p, %34, 0;\nwgmma.mma_async.sync.aligned.m64n64k16.f32.bf16.bf16 {%0,%1,%2,%3,%4,%5,%6,%7,%8,%9,%10,%11,%12,%13,%14,%15,%16,%17,%18,%19,%20,%21,%22,%23,%24,%25,%26,%27,%28,%29,%30,%31}, %32, %33, p, 1, 1, 0, 1;\n}\n"
   : "+f"(d[0]),"+f"(d[1]),"+f"(d[2]),"+f"(d[3]),"+f"(d[4]),"+f"(d[5]),"+f"(d[6]),"+f"(d[7]),"+f"(d[8]),"+f"(d[9]),"+f"(d[10]),"+f"(d[11]),"+f"(d[12]),"+f"(d[13]),"+f"(d[14]),"+f"(d[15]),"+f"(d[16]),"+f"(d[17]),"+f"(d[18]),"+f"(d[19]),"+f"(d[20]),"+f"(d[21]),"+f"(d[22]),"+f"(d[23]),"+f"(d[24]),"+f"(d[25]),"+f"(d[26]),"+f"(d[27]),"+f"(d[28]),"+f"(d[29]),"+f"(d[30]),"+f"(d[31])
   : "l"(da), "l"(db), "r"(sd));
}
template<> __device__ __forceinline__ void wgmma_ss<192,0,1>(float* d, uint64_t da, uint64_t db, int sd) {
  asm volatile("{\n.reg .pred p;\nsetp.ne.b32 p, %98, 0;\nwgmma.mma_async.sync.aligned.m64n192k16.f32.bf16.bf16 {%0,%1,%2,%3,%4,%5,%6,%7,%8,%9,%10,%11,%12,%13,%14,%15,%16,%17,%18,%19,%20,%21,%22,%23,%24,%25,%26,%27,%28,%29,%30,%31,%32,%33,%34,%35,%36,%37,%38,%39,%40,%41,%42,%43,%44,%45,%46,%47,%48,%49,%50,%51,%52,%53,%54,%55,%56,%57,%58,%59,%60,%61,%62,%63,%64,%65,%66,%67,%68,%69,%70,%71,%72,%73,%74,%75,%76,%77,%78,%79,%80,%81,%82,%83,%84,%85,%86,%87,%88,%89,%90,%91,%92,%93,%94,%95}, %96, %97, p, 1, 1, 0, 1;\n}\n"
   : "+f"(d[0]),"+f"(d[1]),"+f"(d[2]),"+f"(d[3]),"+f"(d[4]),"+f"(d[5]),"+f"(d[6]),"+f"(d[7]),"+f"(d[8]),"+f"(d[9]),"+f"(d[10]),"+f"(d[11]),"+f"(d[12]),"+f"(d[13]),"+f"(d[14]),"+f"(d[15]),"+f"(d[16]),"+f"(d[17]),"+f"(d[18]),"+f"(d[19]),"+f"(d[20]),"+f"(d[21]),"+f"(d[22]),"+f"(d[23]),"+f"(d[24]),"+f"(d[25]),"+f"(d[26]),"+f"(d[27]),"+f"(d[28]),"+f"(d[29]),"+f"(d[30]),"+f"(d[31]),"+f"(d[32]),"+f"(d[33]),"+f"(d[34]),"+f"(d[35]),"+f"(d[36]),"+f"(d[37]),"+f"(d[38]),"+f"(d[39]),"+f"(d[40]),"+f"(d[41]),"+f"(d[42]),"+f"(d[43]),"+f"(d[44]),"+f"(d[45]),"+f"(d[46]),"+f"(d[47]),"+f"(d[48]),"+f"(d[49]),"+f"(d[50]),"+f"(d[51]),"+f"(d[52]),"+f"(d[53]),"+f"(d[54]),"+f"(d[55]),"+f"(d[56]),"+f"(d[57]),"+f"(d[58]),"+f"(d[59]),"+f"(d[60]),"+f"(d[61]),"+f"(d[62]),"+f"(d[63]),"+f"(d[64]),"+f"(d[65]),"+f"(d[66]),"+f"(d[67]),"+f"(d[68]),"+f"(d[69]),"+f"(d[70]),"+f"(d[71]),"+f"(d[72]),"+f"(d[73]),"+f"(d[74]),"+f"(d[75]),"+f"(d[76]),"+f"(d[77]),"+f"(d[78]),"+f"(d[79]),"+f"(d[80]),"+f"(d[81]),"+f"(d[82]),"+f"(d[83]),"+f"(d[84]),"+f"(d[85]),"+f"(d[86]),"+f"(d[87]),"+f"(d[88]),"+f"(d[89]),"+f"(d[90]),"+f"(d[91]),"+f"(d[92]),"+f"(d[93]),"+f"(d[94]),"+f"(d[95])
   : "l"(da), "l"(db), "r"(sd));
}
template<> __device__ __forceinline__ void wgmma_ss<192,1,1>(float* d, uint64_t da, uint64_t db, int sd) {
  asm volatile("{\n.reg .pred p;\nsetp.ne.b32 p, %98, 0;\nwgmma.mma_async.sync.aligned.m64n192k16.f32.bf16.bf16 {%0,%1,%2,%3,%4,%5,%6,%7,%8,%9,%10,%11,%12,%13,%14,%15,%16,%17,%18,%19,%20,%21,%22,%23,%24,%25,%26,%27,%28,%29,%30,%31,%32,%33,%34,%35,%36,%37,%38,%39,%40,%41,%42,%43,%44,%45,%46,%47,%48,%49,%50,%51,%52,%53,%54,%55,%56,%57,%58,%59,%60,%61,%62,%63,%64,%65,%66,%67,%68,%69,%70,%71,%72,%73,%74,%75,%76,%77,%78,%79,%80,%81,%82,%83,%84,%85,%86,%87,%88,%89,%90,%91,%92,%93,%94,%95}, %96, %97, p, 1, 1, 1, 1;\n}\n"
   : "+f"(d[0]),"+f"(d[1]),"+f"(d[2]),"+f"(d[3]),"+f"(d[4]),"+f"(d[5]),"+f"(d[6]),"+f"(d[7]),"+f"(d[8]),"+f"(d[9]),"+f"(d[10]),"+f"(d[11]),"+f"(d[12]),"+f"(d[13]),"+f"(d[14]),"+f"(d[15]),"+f"(d[16]),"+f"(d[17]),"+f"(d[18]),"+f"(d[19]),"+f"(d[20]),"+f"(d[21]),"+f"(d[22]),"+f"(d[23]),"+f"(d[24]),"+f"(d[25]),"+f"(d[26]),"+f"(d[27]),"+f"(d[28]),"+f"(d[29]),"+f"(d[30]),"+f"(d[31]),"+f"(d[32]),"+f"(d[33]),"+f"(d[34]),"+f"(d[35]),"+f"(d[36]),"+f"(d[37]),"+f"(d[38]),"+f"(d[39]),"+f"(d[40]),"+f"(d[41]),"+f"(d[42]),"+f"(d[43]),"+f"(d[44]),"+f"(d[45]),"+f"(d[46]),"+f"(d[47]),"+f"(d[48]),"+f"(d[49]),"+f"(d[50]),"+f"(d[51]),"+f"(d[52]),"+f"(d[53]),"+f"(d[54]),"+f"(d[55]),"+f"(d[56]),"+f"(d[57]),"+f"(d[58]),"+f"(d[59]),"+f"(d[60]),"+f"(d[61]),"+f"(d[62]),"+f"(d[63]),"+f"(d[64]),"+f"(d[65]),"+f"(d[66]),"+f"(d[67]),"+f"(d[68]),"+f"(d[69]),"+f"(d[70]),"+f"(d[71]),"+f"(d[72]),"+f"(d[73]),"+f"(d[74]),"+f"(d[75]),"+f"(d[76]),"+f"(d[77]),"+f"(d[78]),"+f"(d[79]),"+f"(d[80]),"+f"(d[81]),"+f"(d[82]),"+f"(d[83]),"+f"(d[84]),"+f"(d[85]),"+f"(d[86]),"+f"(d[87]),"+f"(d[88]),"+f"(d[89]),"+f"(d[90]),"+f"(d[91]),"+f"(d[92]),"+f"(d[93]),"+f"(d[94]),"+f"(d[95])
   : "l"(da), "l"(db), "r"(sd));
}

template <bool TR>
__device__ __forceinline__ void gemm_section(float* acc, float& mean0, float& mean1, float& rstd0, float& rstd1,
                                             uint32_t sb, int blk, int hg, int wg, int w, int lane) {
  constexpr int layer = TR ? 1 : 0;
  constexpr int TURN = TR ? TURN1 : TURN0;
  constexpr int LSTAT = TURN < 4 ? TURN - 1 : 3;
  const uint32_t bar = sb + SM_BAR;
  const int g = lane >> 2, t = lane & 3;
  const bool leader = (w == 0) && (lane == 0);
  const int statpos = hg < 3 ? 1 : wg ? LSTAT : 2;
  const bool copy = hg >= 3 && wg == 0;
  const int cut = wg ? TURN : 4;
  auto wait_full = [&](int c) {
    mbar_wait(bar + 8 * (B_XF + 8 * wg + c), layer);
    mbar_wait(bar + 8 * (B_WF + c), layer);
  };
  auto peek = [&](int c) {
    const bool x = mbar_test(bar + 8 * (B_XF + 8 * wg + c), layer), y = mbar_test(bar + 8 * (B_WF + c), layer);
    return x && y;
  };
  const uint64_t da0 = mkdesc(sb, TR ? 8192 : 16, 1024, 1), db0 = mkdesc(sb, 8192, 1024, 1);
  uint32_t xt = wg ? 0xfedcba98u : 0x21043210u;
  uint64_t wt = 0x0816131005161310ull;
  uint64_t da = da0 + ((xt & 15) << 9), db = db0 + (16 << 9);
  auto issue = [&](int c, int first) {
    TSG(2 * c);
    wg_fence();
#pragma unroll
    for (int ks = 0; ks < 4; ks++) wgmma_ss<192, TR ? 1 : 0, 1>(acc, da + (TR ? ks * 128 : ks * 2), db + ks * 128, !first || ks != 0);
    wg_commit();
    xt >>= 4; wt >>= 8;
    da = da0 + ((xt & 15) << 9); db = db0 + (((uint32_t)wt & 31) << 9);
    TSG(2 * c + 1);
  };
  uint32_t tag = 0;
  wait_full(0);
  bool ready = peek(1);
  issue(0, 1);
  TSW(0);
#pragma unroll 1
  for (int c = 1; c < cut; c++) {
    if (!ready) wait_full(c);
    issue(c, 0);
    ready = peek(c + 1);
    wg_wait<1>();
    if (leader) mbar_arrive(bar + 8 * (B_DN + 8 * wg + c - 1));
    if (wg == 1 && c == cut - 1) {
      wg_wait<0>();
      if (leader) mbar_arrive(bar + 8 * (B_DN + 8 + c));
    }
    if (c == statpos) {
      mbar_wait(bar + 8 * B_EP, 0);
      tag = 2 * lds32(sb + SM_EP) + layer + 1;
      mbar_wait(bar + 8 * (copy ? B_SC : B_XF + 8 * wg + hg), layer);
      uint32_t A[16];
      const uint32_t xb = sb + (copy ? P_R : 8 * wg + hg) * PG;
#pragma unroll
      for (int ks = 0; ks < 4; ks++) {
        if (!TR) {
          const int row = 16 * w + (lane & 15), kc = 2 * ks + (lane >> 4);
          ldsm4(&A[4 * ks], xb + row * 128 + ((kc ^ (row & 7)) << 4));
        } else {
          const int k = 16 * ks + (lane & 7) + 8 * (lane >> 4), pc = 2 * w + ((lane >> 3) & 1);
          ldsm4t(&A[4 * ks], xb + k * 128 + ((pc ^ (k & 7)) << 4));
        }
      }
      float s0 = 0.f, q0 = 0.f, s1 = 0.f, q1 = 0.f;
#pragma unroll
      for (int i = 0; i < 16; i += 2) {
        const float a = bf_lo(A[i]), b = bf_hi(A[i]), c_ = bf_lo(A[i + 1]), d = bf_hi(A[i + 1]);
        s0 += a + b; q0 = fmaf(a, a, q0); q0 = fmaf(b, b, q0);
        s1 += c_ + d; q1 = fmaf(c_, c_, q1); q1 = fmaf(d, d, q1);
      }
#pragma unroll
      for (int o = 1; o <= 2; o <<= 1) {
        s0 += __shfl_xor_sync(~0u, s0, o); q0 += __shfl_xor_sync(~0u, q0, o);
        s1 += __shfl_xor_sync(~0u, s1, o); q1 += __shfl_xor_sync(~0u, q1, o);
      }
      if (t < 2)
        st_tagged(&g_part[((layer * 32 + blk) * 8 + hg) * 64 + 16 * w + g + 8 * t], __float_as_uint(t ? s1 : s0), __float_as_uint(t ? q1 : q0), tag);
    }
  }
  if (wg == 1) mbar_wait(bar + 8 * (B_DN + GPOS), layer);
  else if (!ready) { wait_full(cut); ready = true; }
  const uint4* psrc = &g_part[((layer * 32 + blk) * 8 + 2 * t) * 64 + 16 * w + g];
  uint4 a0 = ld_tagged(psrc), a1 = ld_tagged(psrc + 8), b0 = ld_tagged(psrc + 64), b1 = ld_tagged(psrc + 72);
  if (wg == 1) {
#pragma unroll 1
    for (int c = cut; c < 8; c++) wait_full(c);
    ready = true;
    bar_sync(5, 256);
  }
#pragma unroll 1
  for (int c = cut; c < 8; c++) {
    if (!ready) wait_full(c);
    issue(c, 0);
    if (wg == 1) {
      wg_wait<2>();
      if (leader && c >= cut + 2) mbar_arrive(bar + 8 * (B_DN + 8 + c - 2));
    } else if (c == 7) {
      bar_arrive(5, 256);
    } else {
      ready = peek(c + 1);
      wg_wait<1>();
      if (leader) mbar_arrive(bar + 8 * (B_DN + c - 1));
    }
  }
  int it = 0;
  while (!__all_sync(~0u, a0.y == tag && a0.w == tag && a1.y == tag && a1.w == tag && b0.y == tag && b0.w == tag && b1.y == tag && b1.w == tag) &&
         ++it < (1 << 20)) {
    a0 = ld_tagged(psrc); a1 = ld_tagged(psrc + 8); b0 = ld_tagged(psrc + 64); b1 = ld_tagged(psrc + 72);
  }
  float s0 = __uint_as_float(a0.x) + __uint_as_float(b0.x), q0 = __uint_as_float(a0.z) + __uint_as_float(b0.z);
  float s1 = __uint_as_float(a1.x) + __uint_as_float(b1.x), q1 = __uint_as_float(a1.z) + __uint_as_float(b1.z);
#pragma unroll
  for (int o = 1; o <= 2; o <<= 1) {
    s0 += __shfl_xor_sync(~0u, s0, o); q0 += __shfl_xor_sync(~0u, q0, o);
    s1 += __shfl_xor_sync(~0u, s1, o); q1 += __shfl_xor_sync(~0u, q1, o);
  }
  mean0 = s0 * (1.f / DM); mean1 = s1 * (1.f / DM);
  rstd0 = rsqrt_approx(fmaxf(q0 * (1.f / DM) - mean0 * mean0, 0.f) + 1e-5f);
  rstd1 = rsqrt_approx(fmaxf(q1 * (1.f / DM) - mean1 * mean1, 0.f) + 1e-5f);
  TSG(16);
  mbar_wait(bar + 8 * (TR ? B_RS : B_CSF), 0);
  wg_wait<0>();
  acc_fence<96>(acc);
  if (leader) mbar_arrive(bar + 8 * (B_DN + 8 * wg + 7));
}

__device__ __forceinline__ void attn_phase(const Params& p, uint32_t sb, int layer, int rb, int hg, int wg, int w) {
  const int lane = opaque_tid() & 31;
  const int g = lane >> 2, t = lane & 3;
  const uint32_t bar = sb + SM_BAR;
  const int blk = 16 * wg + rb;
  float acc[96];
  float2 cs[24];
  float mean0, mean1, rstd0, rstd1;
  if (layer) gemm_section<true>(acc, mean0, mean1, rstd0, rstd1, sb, blk, hg, wg, w, lane);
  else gemm_section<false>(acc, mean0, mean1, rstd0, rstd1, sb, blk, hg, wg, w, lane);
  TSW(1);
#pragma unroll
  for (int j = 8; j < 24; j++) cs[j] = lds64f(sb + SM_CS + 4 * (8 * j + 2 * t));
  const uint32_t kvx = sb + (wg ? 22 : 0) * PG;

  uint32_t kb[4][8], vb[4][8], qa[4][4];
  {
    const float nm0 = -mean0 * rstd0, nm1 = -mean1 * rstd1;
    const int st_row = 16 * w + (lane & 7) + 8 * ((lane >> 3) & 1);
    const uint32_t st_base = kvx + st_row * 256;
    const bool sender = (w == 3 && blk < 31);
    uint4* halo = &g_halo[((layer * 32 + blk) * 8 + hg) * 256 + lane];
    uint32_t r[4][2][4];
#pragma unroll
    for (int h = 0; h < 4; h++) {
#pragma unroll
      for (int kv = 0; kv < 2; kv++) {
#pragma unroll
        for (int dh = 0; dh < 2; dh++) {
          const int j = 8 + kv * 8 + 2 * h + dh;
          const float2 c2 = cs[j];
          const float v0 = fmaf(acc[4 * j + 0], rstd0, nm0 * c2.x), v1 = fmaf(acc[4 * j + 1], rstd0, nm0 * c2.y);
          const float v2 = fmaf(acc[4 * j + 2], rstd1, nm1 * c2.x), v3 = fmaf(acc[4 * j + 3], rstd1, nm1 * c2.y);
          r[h][kv][2 * dh] = packbf(v0, v1);
          r[h][kv][2 * dh + 1] = packbf(v2, v3);
        }
      }
      if (sender) {
        stg128(halo + (2 * h) * 32, make_uint4(r[h][0][0], r[h][0][2], r[h][0][1], r[h][0][3]));
        stg128(halo + (2 * h + 1) * 32, make_uint4(r[h][1][0], r[h][1][1], r[h][1][2], r[h][1][3]));
      }
    }
#pragma unroll
    for (int j = 0; j < 8; j++) cs[j] = lds64f(sb + SM_CS + 4 * (8 * j + 2 * t));
    mbar_wait(bar + 8 * (B_DN + 7), layer);
#pragma unroll
    for (int h = 0; h < 4; h++) {
#pragma unroll
      for (int kv = 0; kv < 2; kv++) {
        const int chunk = 4 * h + 2 * kv + (lane >> 4);
        stsm4(st_base + (((chunk & 8) | ((chunk ^ st_row) & 7)) << 4), r[h][kv][0], r[h][kv][1], r[h][kv][2], r[h][kv][3]);
      }
      kb[h][4] = r[h][0][0]; kb[h][5] = r[h][0][2]; kb[h][6] = r[h][0][1]; kb[h][7] = r[h][0][3];
      vb[h][4] = movm_t(r[h][1][0]); vb[h][5] = movm_t(r[h][1][1]); vb[h][6] = movm_t(r[h][1][2]); vb[h][7] = movm_t(r[h][1][3]);
    }
#pragma unroll
    for (int h = 0; h < 4; h++) {
#pragma unroll
      for (int dh = 0; dh < 2; dh++) {
        const int j = 2 * h + dh;
        const float2 c2 = cs[j];
        qa[h][2 * dh] = packbf(fmaf(-mean0, c2.x, acc[4 * j + 0]), fmaf(-mean0, c2.y, acc[4 * j + 1]));
        qa[h][2 * dh + 1] = packbf(fmaf(-mean1, c2.x, acc[4 * j + 2]), fmaf(-mean1, c2.y, acc[4 * j + 3]));
      }
    }
  }
  bar_sync(2 + wg, 128);
  TSW(2);
  {
    const uint32_t prev_base = kvx + (16 * w - 16) * 256;
    const int mi = lane >> 3;
    const int r = 8 * (mi >> 1) + (lane & 7), r2 = 8 * (mi & 1) + (lane & 7);
    if (w != 0) {
#pragma unroll
      for (int h = 0; h < 4; h++) {
        const int ch = 4 * h + (mi & 1), ch2 = 4 * h + 2 + (mi >> 1);
        ldsm4(&kb[h][0], prev_base + r * 256 + (((ch & 8) | ((ch ^ r) & 7)) << 4));
        ldsm4t(&vb[h][0], prev_base + r2 * 256 + (((ch2 & 8) | ((ch2 ^ r2) & 7)) << 4));
      }
    } else if (blk > 0) {
      const uint4* src = &g_halo[((layer * 32 + blk - 1) * 8 + hg) * 256 + lane];
      uint4 hv[8];
      int it = 0;
      bool ok;
      do {
        ok = true;
#pragma unroll
        for (int i = 0; i < 8; i++) hv[i] = ld_tagged(src + i * 32);
#pragma unroll
        for (int i = 0; i < 8; i++) ok = ok && hv[i].x != UNSET;
      } while (!__all_sync(~0u, ok) && ++it < (1 << 20));
#pragma unroll
      for (int h = 0; h < 4; h++) {
        kb[h][0] = hv[2 * h].x; kb[h][1] = hv[2 * h].y; kb[h][2] = hv[2 * h].z; kb[h][3] = hv[2 * h].w;
        vb[h][0] = movm_t(hv[2 * h + 1].x); vb[h][1] = movm_t(hv[2 * h + 1].y);
        vb[h][2] = movm_t(hv[2 * h + 1].z); vb[h][3] = movm_t(hv[2 * h + 1].w);
      }
    } else {
#pragma unroll
      for (int h = 0; h < 4; h++)
#pragma unroll
        for (int k = 0; k < 4; k++) kb[h][k] = vb[h][k] = 0u;
    }
    TSW(3);
  }
  mbar_wait(bar + 8 * (B_DN + 15), layer);
  TSW(4);

  const bool first = (blk == 0 && w == 0);
  const int e = t - (g >> 1);
  const bool par = g & 1, epos = e >= 1;
  const uint32_t pmask = par ? 0xffff0000u : 0x0000ffffu;
  const uint32_t mB0 = epos ? pmask : 0u, mB1 = epos ? 0u : pmask;
  const float cl2 = 0.25f * 1.4426950408889634f;
  const float sc0 = rstd0 * cl2, sc1 = rstd1 * cl2;
  const float NEG = -INFINITY;
  float vA0[4], vB0[4], vA1[4], vB1[4];
#pragma unroll
  for (int h = 0; h < 4; h++) {
    float S[4][4];
#pragma unroll
    for (int j = 0; j < 4; j++) {
      S[j][0] = S[j][1] = S[j][2] = S[j][3] = 0.f;
      mma_bf16(S[j], qa[h], kb[h][2 * j], kb[h][2 * j + 1]);
    }
    vA0[h] = par ? S[1][1] : S[1][0];
    vB0[h] = epos ? (par ? S[0][1] : S[0][0]) : (par ? S[2][1] : S[2][0]);
    vA1[h] = par ? S[2][3] : S[2][2];
    vB1[h] = epos ? (par ? S[1][3] : S[1][2]) : (par ? S[3][3] : S[3][2]);
    if (first) { vA0[h] = NEG; if (epos) { vB0[h] = NEG; vB1[h] = NEG; } }
  }
  float m0[4], m1[4];
#pragma unroll
  for (int h = 0; h < 4; h++) { m0[h] = fmaxf(vA0[h], vB0[h]); m1[h] = fmaxf(vA1[h], vB1[h]); }
#pragma unroll
  for (int o = 1; o <= 2; o <<= 1) {
#pragma unroll
    for (int h = 0; h < 4; h++) {
      m0[h] = fmaxf(m0[h], __shfl_xor_sync(~0u, m0[h], o));
      m1[h] = fmaxf(m1[h], __shfl_xor_sync(~0u, m1[h], o));
    }
  }
  float O0[4][4], O1[4][4], Z[4][4];
#pragma unroll
  for (int h = 0; h < 4; h++) {
    const float mm0 = -m0[h] * sc0, mm1 = -m1[h] * sc1;
    const float pA0 = ex2(fmaf(vA0[h], sc0, mm0)), pB0 = ex2(fmaf(vB0[h], sc0, mm0));
    const float pA1 = ex2(fmaf(vA1[h], sc1, mm1)), pB1 = ex2(fmaf(vB1[h], sc1, mm1));
    const uint32_t hA0 = packbf(pA0, pA0), hB0 = packbf(pB0, pB0), hA1 = packbf(pA1, pA1), hB1 = packbf(pB1, pB1);
    const uint32_t P0[4] = {hB0 & mB0, 0u, hA0 & pmask, hB1 & mB0};
    const uint32_t P1[4] = {hB0 & mB1, hA1 & pmask, 0u, hB1 & mB1};
#pragma unroll
    for (int k = 0; k < 4; k++) O0[h][k] = O1[h][k] = Z[h][k] = 0.f;
    mma_bf16(O0[h], P0, vb[h][0], vb[h][1]); mma_bf16(O1[h], P0, vb[h][2], vb[h][3]); mma_bf16(Z[h], P0, 0x3f803f80u, 0x3f803f80u);
    mma_bf16(O0[h], P1, vb[h][4], vb[h][5]); mma_bf16(O1[h], P1, vb[h][6], vb[h][7]); mma_bf16(Z[h], P1, 0x3f803f80u, 0x3f803f80u);
  }
  if (lane == 0) mbar_arrive(bar + 8 * (B_OST + wg));
  uint4* op = (uint4*)g_O + ((layer * 32 + blk) * 8 + hg) * 512 + 64 * t + 16 * w + g;
#pragma unroll
  for (int h = 0; h < 4; h += 2) {
    const float i0 = rcp_approx(Z[h][0]), i1 = rcp_approx(Z[h][2]), j0 = rcp_approx(Z[h + 1][0]), j1 = rcp_approx(Z[h + 1][2]);
    stg128(op + 128 * h, make_uint4(packbf(O0[h][0] * i0, O0[h][1] * i0), packbf(O1[h][0] * i0, O1[h][1] * i0),
                                   packbf(O0[h + 1][0] * j0, O0[h + 1][1] * j0), packbf(O1[h + 1][0] * j0, O1[h + 1][1] * j0)));
    stg128(op + 128 * h + 8, make_uint4(packbf(O0[h][2] * i1, O0[h][3] * i1), packbf(O1[h][2] * i1, O1[h][3] * i1),
                                            packbf(O0[h + 1][2] * j1, O0[h + 1][3] * j1), packbf(O1[h + 1][2] * j1, O1[h + 1][3] * j1)));
  }
  TSW(5);
  __syncwarp();
  if (lane == 0) red_relaxed(&g_cnt[(C_O + layer * 32 + blk) * 32]);
  TSW(6);
}

#define PGATE 2
__device__ __forceinline__ void proj_phase(const Params& p, uint32_t sb, int layer, int rb, int q, int wg, int w, int& rtp) {
  const int lane = opaque_tid() & 31;
  const bool TR = layer != 0;
  const int t = lane & 3;
  const uint32_t bar = sb + SM_BAR;
  const uint32_t rbx = sb + (P_R + wg) * PG;
  const int blk = 16 * wg + rb;
  uint32_t res[16];
  mbar_wait(bar + 8 * (B_RF + wg), layer);
  if (!TR) {
#pragma unroll
    for (int j = 0; j < 8; j += 2) {
      const int mi = lane >> 3;
      const int row = 16 * w + (lane & 7) + 8 * (mi & 1), ch = j + (mi >> 1);
      ldsm4(&res[2 * j], rbx + row * 128 + ((ch ^ (row & 7)) << 4));
    }
  } else {
#pragma unroll
    for (int j = 0; j < 8; j += 2) {
      const int mi = lane >> 3;
      const int line = 8 * (j + (mi >> 1)) + (lane & 7), pc = 2 * w + (mi & 1);
      ldsm4t(&res[2 * j], rbx + line * 128 + ((pc ^ (line & 7)) << 4));
    }
  }
  if (layer) mbar_wait(bar + 8 * (B_RS + 1), 0);
  fence_async_global();
  const uint32_t stg = sb + SM_STG + wg * 768;
  if (wg) mbar_wait(bar + 8 * B_PST, layer);
  if (wg) mbar_wait(bar + 8 * B_PE, layer);
  bool clean = false;
#pragma unroll 1
  for (int attempt = 0; attempt < MAX_RETRY; attempt++) {
  float acc[32];
#pragma unroll
  for (int j = 0; j < 16; j++) { acc[2 * j] = bf_lo(res[j]); acc[2 * j + 1] = bf_hi(res[j]); }
  acc_fence<32>(acc);
#pragma unroll
  for (int c = 0; c < 4; c++) {
    mbar_wait(bar + 8 * (B_WOF + c), layer);
    mbar_wait(bar + 8 * (B_OF + 4 * wg + c), layer);
    if (c == 0) TSW(7);
    const uint64_t da = mkdesc(sb + o_page(wg, c) * PG, 1024, 128, 0);
    wg_fence();
#pragma unroll
    for (int ks = 0; ks < 8; ks++)
      wgmma_ss<64, 0, 1>(acc, da + ks * 128, mkdesc(sb + wo_page(2 * c + (ks >> 2)) * PG, 8192, 1024, 1) + (ks & 3) * 128, 1);
    wg_commit();
  }
  mbar_wait(bar + 8 * B_KG, 0);
  wg_wait<0>();
  acc_fence<32>(acc);
  TSW(8);
  if (!clean) {
    const float chk = acc[0] + acc[2];
    clean = __all_sync(~0u, chk == chk);
    if (clean && lane == 0) mbar_arrive(bar + 8 * (B_PDONE + wg));
  }
  float s0 = 0.f, q0 = 0.f, s1 = 0.f, q1 = 0.f;
  uint32_t o[16];
#pragma unroll
  for (int j = 0; j < 8; j++) {
    const float a = acc[4 * j], b = acc[4 * j + 1], c = acc[4 * j + 2], d = acc[4 * j + 3];
    o[2 * j] = packbf(a, b);
    o[2 * j + 1] = packbf(c, d);
    s0 += a + b; q0 = fmaf(a, a, q0); q0 = fmaf(b, b, q0);
    s1 += c + d; q1 = fmaf(c, c, q1); q1 = fmaf(d, d, q1);
  }
#pragma unroll
  for (int j = 0; j < 8; j += 2) {
    const int mi = lane >> 3;
    const int line = 8 * (j + (mi >> 1)) + (lane & 7), pc = 2 * w + (mi & 1);
    stsm4t(rbx + line * 128 + ((pc ^ (line & 7)) << 4), o[2 * j], o[2 * j + 1], o[2 * j + 2], o[2 * j + 3]);
  }
#pragma unroll
  for (int o2 = 1; o2 <= 2; o2 <<= 1) {
    s0 += __shfl_xor_sync(~0u, s0, o2); q0 += __shfl_xor_sync(~0u, q0, o2);
    s1 += __shfl_xor_sync(~0u, s1, o2); q1 += __shfl_xor_sync(~0u, q1, o2);
  }
  {
    const int i = 2 * (lane >> 2) + (t & 1), k = (i * 11) >> 5;
    const float v = (t == 0) ? s0 : (t == 1) ? q0 : (t == 2) ? s1 : q1;
    sts32f(stg + k * 128 + (2 * w + (t >> 1)) * 16 + (i - 3 * k) * 4, v);
  }
  TSW(9);
  fence_async_smem();
  if (!bar_or(2 + wg, 128, !clean)) break;
  bool unset = false;
#pragma unroll
  for (int i = 0; i < 4; i++) unset |= lds32(sb + o_page(wg, i) * PG + (32 * w + lane) * 128) == UNSET;
  if (!bar_or(2 + wg, 128, unset)) break;
  if (w == 0 && elect_one()) {
    fence_async_smem();
    mbar_expect(bar + 8 * (B_RT + wg), 8 * PG);
#pragma unroll 1
    for (int c = 0; c < 4; c++) bulk_ld(sb + o_page(wg, c) * PG, g_O + ((layer * 32 + blk) * 4 + c) * PG, 2 * PG, bar + 8 * (B_RT + wg));
  }
  mbar_wait(bar + 8 * (B_RT + wg), rtp);
  rtp ^= 1;
  RETRY(0);
  }
  if (!clean && lane == 0) mbar_arrive(bar + 8 * (B_PDONE + wg));
  if (w == 0 && lane == 0) {
    tma_st(&p.mapXT, blk * 64, (2 * layer) * DM + q * 64, rbx);
    bulk_red_add_f32(g_stats + (layer * 32 + blk) * 192, stg, 768);
    bulk_commit();
    red_relaxed(&g_cnt[(C_G + 2 * layer + wg) * 32]);
  }
  TSW(10);
}

__device__ __forceinline__ void conv_load(uint32_t* A, uint32_t pe) {
#pragma unroll
  for (int m = 0; m < 17; m++) {
    A[4 * m + 2] = lds32(pe + 4 * (64 * m - 8));
    A[4 * m + 0] = lds32(pe + 4 * (64 * m));
    A[4 * m + 1] = lds32(pe + 4 * (64 * m + 8));
    asm volatile("mov.b32 %0, %1;" : "=r"(A[4 * m + 3]) : "r"(A[4 * m + 0]));
  }
}
template <int M> __device__ __forceinline__ void conv_tri(float* acc, const uint32_t* A, uint64_t d) {
  if constexpr (M < 16) {
    wgmma_rs<64 - 8 * (M / 2), 0>(acc, A + 4 * M, d + (uint64_t)(64 + 4 * M), M != 0);
    conv_tri<M + 1>(acc, A, d);
  }
}
__device__ __forceinline__ void conv_mma0(float* acc, const uint32_t* A, uint64_t d) {
  wg_fence();
  conv_tri<0>(acc, A, d);
  wg_commit();
}
__device__ __forceinline__ void conv_mma1(float* acc, const uint32_t* A, uint64_t d) {
  wg_fence();
#pragma unroll
  for (int m = 0; m < 17; m++) wgmma_rs<64, 0>(acc, A + 4 * m, d + (uint64_t)(4 * m), m != 0);
  wg_commit();
}
__device__ __forceinline__ void conv_store(float* acc, uint32_t pb, uint32_t over, int w) {
  acc_fence<32>(acc);
  const int l = opaque_tid() & 31, mt = l >> 3;
  int c = 2 * (63 - 8 * (mt >> 1) - (l & 7) + w) + (mt & 1);
  c ^= (c >> 3) & 1;
  const uint32_t a0 = pb + c * 16;
#pragma unroll
  for (int j = 0; j < 8; j += 2)
    stsm4t(j == 0 ? (c < 128 ? a0 : over + (c - 128) * 16) : a0 - 256 * j, packbf(acc[4 * j], acc[4 * j + 1]), packbf(acc[4 * j + 2], acc[4 * j + 3]),
           packbf(acc[4 * j + 4], acc[4 * j + 5]), packbf(acc[4 * j + 6], acc[4 * j + 7]));
}
#define FARG 1
__device__ __forceinline__ void conv_far(uint32_t sb, int ht) {
  const int w = ht >> 5, l = ht & 31;
  float F[4][8];
  const uint64_t da = mkdesc(sb + cv_fa(0), 128, 128, 0), ds = mkdesc(sb + cv_se(0), 256, 256, 3);
#pragma unroll
  for (int k = 0; k < 8; k++) {
    if (k % FARG == 0) { if (k) wg_wait<0>(); wg_fence(); }
#pragma unroll
    for (int c = 0; c < 4; c++) wgmma_ss<16, 0, 1>(F[c], da + c * 1024 + (k >> 2) * 128 + (k & 3) * 16, ds + c * 256 + 32 * k, k != 0);
    if (k % FARG == FARG - 1) wg_commit();
  }
  const uint32_t pf = sb + cv_pf(0) + (16 * w + (l & 15)) * 32 + (l >> 4) * 16;
  wg_wait<0>();
#pragma unroll
  for (int c = 0; c < 4; c++) {
    acc_fence<8>(F[c]);
    stsm4(pf + c * 2048, packbf(F[c][0], F[c][1]), packbf(F[c][2], F[c][3]), packbf(F[c][4], F[c][5]), packbf(F[c][6], F[c][7]));
  }
}
__device__ __forceinline__ void conv_sums(uint32_t sb, int lc, int ht) {
  const int m = ht - 1;
  uint4 v[2][3];
#pragma unroll
  for (int c = 0; c < 2; c++)
#pragma unroll
    for (int k = 0; k < 3; k++) {
      const int mm = m - 1 + k;
      v[c][k] = lds128(sb + cv_u(lc + c) + (mm >= 0 ? (mm & 1) * CV_UH + (127 - (mm >> 1)) * 16 : 128 * 16));
    }
  const int ce = m + 2, co = m + 1;
#pragma unroll
  for (int c = 0; c < 2; c++) {
    const uint32_t x[8] = {v[c][0].z, v[c][0].w, v[c][1].x, v[c][1].y, v[c][1].z, v[c][1].w, v[c][2].x, v[c][2].y};
    float pv[16];
#pragma unroll
    for (int k = 0; k < 8; k++) { pv[2 * k] = bf_lo(x[k]); pv[2 * k + 1] = bf_hi(x[k]); }
    float t2[15], t4[13], s9[8], s7[8];
#pragma unroll
    for (int i = 0; i < 15; i++) t2[i] = pv[i] + pv[i + 1];
#pragma unroll
    for (int i = 0; i < 13; i++) t4[i] = t2[i] + t2[i + 2];
#pragma unroll
    for (int i = 0; i < 8; i++) {
      s9[i] = (t4[i] + t4[i + 4]) + pv[i + 8];
      s7[i] = (t4[i + 1] + t2[i + 5]) + pv[i + 7];
    }
    const uint4 e4 = make_uint4(packbf(s9[0], s9[1]), packbf(s9[2], s9[3]), packbf(s9[4], s9[5]), packbf(s9[6], s9[7]));
    if (ce < 128) sts128(sb + cv_se(lc + c) + (63 - (ce >> 1)) * 32 + (((ce & 1) ^ ((ce >> 3) & 1) ^ 1) << 4), e4);
    else sts128(sb + cv_se(lc + c) + 63 * 32 + 16, make_uint4(0, 0, 0, 0));
    sts128(sb + cv_so(lc + c) + (63 - (co >> 1)) * 32 + (((co & 1) ^ ((co >> 3) & 1) ^ 1) << 4),
           make_uint4(packbf(s7[0], s7[1]), packbf(s7[2], s7[3]), packbf(s7[4], s7[5]), packbf(s7[6], s7[7])));
  }
}

template <int HALF, int NCH, int STEP = 1>
__device__ __forceinline__ void conv_epi(uint32_t sb, bf16* out, int lc, int c) {
  uint4 v[NCH][4], xr[NCH], f[NCH];
  const uint32_t sw = (c ^ ((c >> 3) & 1)) * 16;
#pragma unroll
  for (int u = 0; u < NCH; u++) {
#pragma unroll
    for (int k = 0; k < 4; k++) v[u][k] = lds128(sb + (HALF ? cv_pb1(lc + STEP * u, k) : cv_pb0(lc + STEP * u, k)) + sw);
    xr[u] = lds128(sb + cv_x(HALF, lc + STEP * u) + c * 16);
    if (HALF) f[u] = lds128(sb + cv_pf(lc + STEP * u) + c * 16);
  }
#pragma unroll
  for (int u = 0; u < NCH; u++) {
    if (HALF) { v[u][0].x = hadd2(v[u][0].x, f[u].x); v[u][0].y = hadd2(v[u][0].y, f[u].y); v[u][0].z = hadd2(v[u][0].z, f[u].z); v[u][0].w = hadd2(v[u][0].w, f[u].w); }
    uint4 o;
    o.x = hadd2(xr[u].x, hadd2(hadd2(v[u][0].x, v[u][1].x), hadd2(v[u][2].x, v[u][3].x)));
    o.y = hadd2(xr[u].y, hadd2(hadd2(v[u][0].y, v[u][1].y), hadd2(v[u][2].y, v[u][3].y)));
    o.z = hadd2(xr[u].z, hadd2(hadd2(v[u][0].z, v[u][1].z), hadd2(v[u][2].z, v[u][3].z)));
    o.w = hadd2(xr[u].w, hadd2(hadd2(v[u][0].w, v[u][1].w), hadd2(v[u][2].w, v[u][3].w)));
    stg128(out + cv_chan(0, lc + STEP * u) * LSEQ + HALF * 1024 + c * 8, o);
  }
}

__device__ __forceinline__ bool prep_valid(const uint4 (&st)[6], const uint4 (&xr)[4]) {
  const uint32_t n = __float_as_uint(8.f);
  return st[0].w == n && st[1].w == n && st[2].w == n && st[3].w == n && st[4].w == n && (st[5].w | st[5].y | st[5].z) == n &&
         xr[0].x != UNSET && xr[1].x != UNSET && xr[2].x != UNSET && xr[3].x != UNSET;
}
template <int HALF, typename F>
__device__ __forceinline__ void conv_prep(uint32_t sb, int layer, int cta, int i, F meanwhile) {
  uint4 st[6], xr[4];
  const uint4* sp = (const uint4*)g_stats + (layer * 32 + HALF * 16 + (i >> 3)) * 48 + (i & 7);
  const uint4* xp = (const uint4*)g_xT + (2 * layer * DM + 2 * cta) * (LSEQ / 8) + HALF * 128 + i;
  auto fetch = [&]() {
#pragma unroll
    for (int k = 0; k < 6; k++) st[k] = ld_tagged(sp + 8 * k);
#pragma unroll
    for (int k = 0; k < 4; k++) xr[k] = ld_tagged(xp + cv_chan(0, k) * (LSEQ / 8));
  };
  if (HALF) {
#pragma unroll
    for (int k = 0; k < 6; k++) st[k] = lds128(sb + CV_ST + (i >> 3) * 768 + k * 128 + (i & 7) * 16);
#pragma unroll
    for (int k = 0; k < 4; k++) xr[k] = lds128(sb + cv_x(1, k) + i * 16);
  } else {
    fetch();
  }
  meanwhile();
  int it = 0;
  while (!__all_sync(~0u, prep_valid(st, xr)) && ++it < MAX_RETRY) { fetch(); RETRY(1); }
  if (!HALF || it) {
#pragma unroll
    for (int k = 0; k < 4; k++) sts128(sb + cv_x(HALF, k) + i * 16, xr[k]);
  }
  const uint32_t v[16] = {st[0].x, st[0].y, st[0].z, st[1].x, st[1].y, st[1].z, st[2].x, st[2].y, st[2].z, st[3].x, st[3].y, st[3].z, st[4].x, st[4].y, st[4].z, st[5].x};
  uint32_t rs[4], nm[4];
#pragma unroll
  for (int k = 0; k < 4; k++) {
    const float m0 = __uint_as_float(v[4 * k]) * (-1.f / DM), m1 = __uint_as_float(v[4 * k + 2]) * (-1.f / DM);
    const float r0 = rsqrt_approx(fmaxf(fmaf(__uint_as_float(v[4 * k + 1]), 1.f / DM, -m0 * m0), 0.f) + 1e-5f);
    const float r1 = rsqrt_approx(fmaxf(fmaf(__uint_as_float(v[4 * k + 3]), 1.f / DM, -m1 * m1), 0.f) + 1e-5f);
    rs[k] = packbf(r0, r1);
    nm[k] = packbf(m0 * bf_lo(rs[k]), m1 * bf_hi(rs[k]));
  }
  const uint32_t ud = sb + (i & 1) * CV_UH + (127 - 64 * HALF - (i >> 1)) * 16;
#pragma unroll
  for (int k = 0; k < 4; k++)
    sts128(ud + cv_u(k), make_uint4(hfma2(xr[k].x, rs[0], nm[0]), hfma2(xr[k].y, rs[1], nm[1]), hfma2(xr[k].z, rs[2], nm[2]), hfma2(xr[k].w, rs[3], nm[3])));
  fence_async_smem();
}

#define ALATE 2
#define PP0 1
__device__ __forceinline__ void conv_phase(const Params& p, uint32_t sb, int layer, int cta) {
  const int tid = opaque_tid();
  const int wg = __shfl_sync(~0u, tid >> 7, 0), w = __shfl_sync(~0u, (tid >> 5) & 3, 0);
  const uint32_t bar = sb + SM_BAR;
  constexpr int CH2 = 4 * PG;
  bf16* xout = g_xT + ((2 * layer + 1) * DM + 2 * cta) * LSEQ;
  uint32_t A0[68], A1[68];
  float acc[32];
  const uint32_t pe = sb + cv_pe(wg) + 4 * (16 + 16 * w + ((tid & 31) >> 2) - 2 * (tid & 3));
  auto staged = [&]() {
    if ((tid & 127) == 0) { bulk_wait_read(); mbar_arrive(bar + 8 * (B_PST + wg)); }
    __syncwarp();
  };
  if (layer) mbar_wait(bar + 8 * (B_RS + 2), 0);
  if (wg == 0) {
    staged();
    if (tid < 32) sts128(sb + cv_u(tid >> 3) + ((tid >> 2) & 1) * CV_UH + (128 + (tid & 3)) * 16, make_uint4(0, 0, 0, 0));
    mbar_wait(bar + 8 * B_PE, layer);
    TSW(19);
    mbar_wait(bar + 8 * B_GB, layer);
    TSW(11);
    conv_prep<0>(sb, layer, cta, tid, [&]() {
      conv_load(A0, pe);
      conv_load(A1, pe + CH2);
    });
    mbar_arrive(bar + 8 * B_U);
  } else {
    mbar_wait(bar + 8 * B_PE, layer);
    conv_load(A0, pe);
    staged();
    conv_load(A1, pe + CH2);
    TSW(19);
  }
  const uint64_t d0 = mkdesc(sb + cv_u(wg), CV_UH, 128, 0), d1 = d0 + (CH2 >> 4);
  mbar_wait(bar + 8 * B_U, layer);
  TSW(12);
  if (wg == 1) bar_sync(5, 256);
  conv_mma0(acc, A0, d0);
  if (wg == 0) bar_arrive(5, 256);
  mbar_wait(bar + 8 * (B_PDONE + 1), layer);
  {
    const int l = opaque_tid() & 31;
    if ((l & 15) < 2 * w) sts128(sb + cv_pb0(wg + 2 * (l >> 4), w) + (l & 15) * 16, make_uint4(0, 0, 0, 0));
  }
  wg_wait<0>();
  conv_store(acc, sb + cv_pb0(wg, w), sb + cv_pb1(wg, w), w);
  conv_mma0(acc, A1, d1);
  bar_sync(2 + wg, 128);
  conv_epi<0, 1>(sb, xout, wg, opaque_tid() & 127);
  wg_wait<0>();
  conv_store(acc, sb + cv_pb0(2 + wg, w), sb + cv_pb1(2 + wg, w), w);
  TSW(13);
  bar_sync(2 + wg, 128);
  conv_epi<0, 1>(sb, xout, 2 + wg, opaque_tid() & 127);
  mbar_arrive(bar + 8 * B_PUB);
  TSW(14);
  mbar_wait(bar + 8 * (B_GB + 1), layer);
  if (wg == 0) {
    conv_prep<1>(sb, layer, cta, opaque_tid(), []() {});
    bar_sync(2, 128);
    if (w == 0 && elect_one()) mbar_arrive(bar + 8 * B_U1);
  } else {
    bar_sync(6, 256);
  }
  TSW(15);
  conv_mma1(acc, A0, d0);
  if (wg == 0) bar_arrive(6, 256);
  mbar_wait(bar + 8 * B_FARM, layer);
  wg_wait<0>();
  conv_store(acc, sb + cv_pb1(wg, w), sb + cv_dump(wg), w);
  mbar_arrive(bar + 8 * (B_R + 1));
  TSW(16);
  conv_mma1(acc, A1, d1);
  wg_wait<0>();
  conv_store(acc, sb + cv_pb1(2 + wg, w), sb + cv_dump(2 + wg), w);
  TSW(17);
  if (wg == 0) {
    mbar_arrive(bar + 8 * (B_R + 2));
  } else {
    bar_sync(3, 128);
    conv_epi<1, 1>(sb, xout, 3, opaque_tid() & 127);
    mbar_arrive(bar + 8 * (B_PUB + 2));
    TSW(18);
  }
}

__device__ __forceinline__ void final_phase(const Params& p, uint32_t sb, int cta, int wg, int w, int rtp) {
  const int lane = opaque_tid() & 31;
  const uint32_t bar = sb + SM_BAR;
  mbar_wait(bar + 8 * (B_TF + wg), 0);
  if (threadIdx.x == 128) TS(8);
  const uint32_t src = sb + (16 + wg) * PG, dst = src + 2 * PG;
  const int mi = lane >> 3;
#pragma unroll 1
  for (int attempt = 0; attempt < MAX_RETRY; attempt++) {
    uint32_t m = 0;
#pragma unroll
    for (int j = 0; j < 8; j += 2) {
      uint32_t r[4];
      const int line = 8 * (j + (mi >> 1)) + (lane & 7), pc = 2 * w + (mi & 1);
      ldsm4t(r, src + line * 128 + ((pc ^ (line & 7)) << 4));
      const int row = 16 * w + (lane & 7) + 8 * (mi & 1), ch = j + (mi >> 1);
      stsm4(dst + row * 128 + ((ch ^ (row & 7)) << 4), r[0], r[1], r[2], r[3]);
#pragma unroll
      for (int k = 0; k < 4; k++) asm("max.u16x2 %0, %0, %1;" : "+r"(m) : "r"(r[k]));
    }
    fence_async_smem();
    if (!bar_or(2 + wg, 128, m >= 0xffff0000u || (m & 0xffffu) == 0xffffu)) break;
    if (w == 0 && elect_one()) {
      mbar_expect(bar + 8 * (B_RT + wg), PG);
      tma_ld(src, &p.mapXT, (16 * wg + (cta & 15)) * 64, 3 * DM + (cta >> 4) * 64, bar + 8 * (B_RT + wg));
    }
    mbar_wait(bar + 8 * (B_RT + wg), (rtp + attempt) & 1);
    RETRY(2);
  }
  if (w == 0 && elect_one()) {
    tma_st(&p.mapOut, (cta >> 4) * 64, (16 * wg + (cta & 15)) * 64, dst);
    bulk_commit();
    asm volatile("cp.async.bulk.wait_group.read 0;" ::: "memory");
    if (threadIdx.x == 128) TS(9);
    if (threadIdx.x == 128) LTS(1);
  }
}

struct cplx { float r, i; };
__device__ __forceinline__ cplx cmul(cplx a, cplx b) { return {fmaf(a.r, b.r, -a.i * b.i), fmaf(a.r, b.i, a.i * b.r)}; }
__device__ __forceinline__ cplx csqr(cplx a) { return {fmaf(a.r, a.r, -a.i * a.i), (a.r + a.r) * a.i}; }
__device__ __forceinline__ cplx cexp_l(float ar2, float ai, float l) {
  const float m = ex2(ar2 * l);
  const float x = ai * l;
  return {m * __cosf(x), m * __sinf(x)};
}

__device__ __forceinline__ void colsum_cta(const Params& p, uint32_t sb, int j, int tid) {
  const uint32_t bar = sb + SM_BAR;
  auto ld = [&](int i) {
    mbar_expect(bar + 8 * i, 3 * PG);
    tma_ld3(sb + (i & 7) * 3 * PG, &p.mapW3, (2 * j + (i & 1)) * 64, (i >> 1) * 64, 0, bar + 8 * i);
  };
  if (tid == 384) {
#pragma unroll
    for (int i = 0; i < 24; i++) mbar_init(bar + 8 * i, i < 16 ? 1 : 12);
    asm volatile("fence.mbarrier_init.release.cluster;" ::: "memory");
    fence_async_smem();
#pragma unroll 1
    for (int i = 0; i < 8; i++) ld(i);
  }
  const unsigned ep = ld_relaxed(&g_cnt[C_CS * 32]);
  bar_sync(0, NTHREADS);
  if (tid == 384) {
#pragma unroll 1
    for (int i = 8; i < 16; i++) { mbar_wait(bar + 8 * (8 + i), 0); fence_async_smem(); ld(i); }
  }
  if (tid < 384) {
    const int lane = tid & 31, cc = tid & 7, r0 = (tid >> 3) & 15, part = tid >> 7;
    const uint32_t id = ((lane >> 2) == 2 * (lane & 3) ? 0x3f80u : 0u) | ((lane >> 2) == 2 * (lane & 3) + 1 ? 0x3f800000u : 0u);
    const uint32_t src = sb + part * PG + r0 * 128 + ((cc ^ (r0 & 7)) << 4);
    float s[2][2][4];
#pragma unroll
    for (int i = 0; i < 16; i++) s[i >> 3][(i >> 2) & 1][i & 3] = 0.f;
#pragma unroll 1
    for (int i2 = 0; i2 < 16; i2 += 2) {
#pragma unroll
      for (int h = 0; h < 2; h++) {
        const int i = i2 + h;
        mbar_wait(bar + 8 * i, 0);
        uint4 v[4];
#pragma unroll
        for (int k = 0; k < 4; k++) v[k] = lds128(src + (i & 7) * 3 * PG + k * 2048);
#pragma unroll
        for (int k = 0; k < 4; k++) {
          const uint32_t a[4] = {v[k].x, v[k].y, v[k].z, v[k].w};
          mma_bf16(s[h][0], a, id, 0u);
          mma_bf16(s[h][1], a, 0u, id);
        }
        __syncwarp();
        if (i < 8 && lane == 0) mbar_arrive(bar + 8 * (16 + i));
      }
    }
    const uint32_t red = sb + 24 * PG;
#pragma unroll
    for (int h = 0; h < 2; h++)
#pragma unroll
      for (int k = 0; k < 2; k++) sts128f(red + (r0 * 384 + h * 192 + part * 64 + cc * 8 + k * 4) * 4, s[h][k][0], s[h][k][1], s[h][k][2], s[h][k][3]);
    bar_sync(1, 384);
    float tot = 0.f;
#pragma unroll
    for (int k = 0; k < 16; k++) tot += __uint_as_float(lds32(red + (k * 384 + tid) * 4));
    asm volatile("st.relaxed.gpu.global.v2.u32 [%0], {%1,%2};" ::"l"(&g_colsum[j * 384 + tid]), "r"(__float_as_uint(tot)), "r"(ep / NCTA + 1) : "memory");
    const uint4 u = make_uint4(UNSET, UNSET, UNSET, UNSET);
    if (tid < 256) {
#pragma unroll 4
      for (int i = 0; i < 64; i++) stg128(g_halo + 65536 + j * 16384 + i * 256 + tid, u);
#pragma unroll 1
      for (int s = 0; s < 3; s++) {
        uint4* dst = (s ? (uint4*)g_xT + (s + 1) * 131072 : (uint4*)g_O + 131072) + j * 32768 + (tid >> 1) * 8 + (tid & 1);
#pragma unroll 4
        for (int i = 0; i < 32; i++) stg128(dst + i * 1024, u);
        bar_sync(2, 256);
        if (tid == 32 * s) red_release(&g_cnt[(C_R + s) * 32]);
      }
    }
  }
}

#define KW 3
struct ModeIn { uint32_t ar, ai, br, bi, cr, ci; bf16 logdt; };
__device__ __forceinline__ ModeIn load_modes(const Params& p, int d, int m) {
  const int i = d * 64 + m;
  return {((const uint32_t*)p.a_re)[i], ((const uint32_t*)p.a_im)[i], ((const uint32_t*)p.b_re)[i], ((const uint32_t*)p.b_im)[i],
          ((const uint32_t*)p.c_re)[i], ((const uint32_t*)p.c_im)[i], p.log_dt[d]};
}
__device__ __forceinline__ float4 lds128f_nv(uint32_t a) { float4 v; asm("ld.shared.v4.f32 {%0,%1,%2,%3}, [%4];" : "=f"(v.x), "=f"(v.y), "=f"(v.z), "=f"(v.w) : "r"(a)); return v; }
__device__ __forceinline__ void kernel_gen(const Params& p, uint32_t sb, int cta, int ht, ModeIn in, const ModeIn& in1) {
  const uint32_t bst = sb + SM_KGB + ((ht & 63) >> 2) * 144 + (ht & 3) * 4 + (ht >> 6) * 16;
  const uint64_t db = mkdesc(sb + SM_KGB, 144, 2304, 0);
  const float e0 = (float)(8 * (((ht & 32) >> 1) + ((ht & 31) >> 2)));
  float T[20];
#pragma unroll
  for (int i = 0; i < 20; i++) T[i] = 0.f;
  float k0 = (ht & 63) ? 0.f : __bfloat162float(p.dskip[cv_chan(cta, ht >> 6)]);
#pragma unroll 1
  for (int pass = 0; pass < 4; pass++) {
    {
      const int sh = (pass & 1) ? 0 : 16;
      auto val = [&](uint32_t v) { return __uint_as_float((v << sh) & 0xffff0000u); };
      const float dt = __bfloat162float(__float2bfloat16_rn(expf(__bfloat162float(in.logdt))));
      const float ar2 = dt * val(in.ar) * 1.4426950408889634f, ai = dt * val(in.ai);
      const cplx c = cmul({val(in.cr), -val(in.ci)}, {dt * val(in.br), -dt * val(in.bi)});
      k0 += c.r;
      const cplx z1 = cexp_l(ar2, -ai, 1.f), z256 = cexp_l(ar2, -ai, 256.f), z64 = cexp_l(ar2, ai, 64.f);
      const cplx z2 = csqr(z1), z512 = csqr(z256);
      auto put = [&](int j, cplx v) { sts32(bst + (j >> 2) * 2304 + (j & 3) * 32, packbf(v.r, v.i)); };
      sts128f(sb + SM_KGT + ht * 16, ar2, ai, z64.r, z64.i);
      const cplx c1 = cmul(c, z1), c2 = cmul(c, z2), c3 = cmul(c1, z2), c4 = cmul(c2, z2);
      const cplx c5 = cmul(c3, z2), c6 = cmul(c4, z2), c7 = cmul(c5, z2), c8 = cmul(c6, z2);
      put(0, c1); put(1, c2); put(2, c3); put(3, c4); put(4, c5); put(5, c6); put(6, c7); put(7, c8);
      const cplx c260 = cmul(c4, z256), c264 = cmul(c8, z256), c520 = cmul(c8, z512), c776 = cmul(c264, z512);
      put(8, cmul(c2, z256)); put(9, c260); put(10, cmul(c6, z256)); put(11, c264);
      put(12, cmul(c4, z512)); put(13, c520); put(14, cmul(c260, z512)); put(15, c776);
      const cplx c1032 = cmul(c520, z512), c1288 = cmul(c776, z512);
      put(16, c1032); put(17, c1288); put(18, cmul(c1032, z512)); put(19, cmul(c1288, z512));
    }
    fence_async_smem();
    bar_sync(4, 128);
    uint32_t tb = sb + SM_KGT + (ht & 67) * 16;
    asm volatile("mov.u32 %0, %0;" : "+r"(tb) :: "memory");
#pragma unroll
    for (int q = 0; q < 4; q++) {
      uint32_t A[8];
      if (q >= KW) wg_wait<KW - 1>();
#pragma unroll
      for (int s = 0; s < 4; s++) {
        const float4 v = lds128f_nv(tb + (4 * q + s) * 64);
        const cplx lo = cexp_l(v.x, v.y, e0), hi = cmul(lo, {v.z, v.w});
        A[2 * s] = packbf(lo.r, lo.i);
        A[2 * s + 1] = packbf(hi.r, hi.i);
      }
      wg_fence();
      wgmma_rs<40, 0>(T, A, db + 36 * q, (pass & 1) | q);
      wgmma_rs<40, 0>(T, A + 4, db + 36 * q + 18, 1);
      wg_commit();
    }
    wg_wait<0>();
    acc_fence<20>(T);
    if (ht == 0) TS(4 + pass);
    if (pass & 1) {
      const int h2 = opaque_tid() - 256, w = h2 >> 5, lane = h2 & 31, t = lane & 3, chn = h2 >> 6, m = h2 & 63, i0 = 16 * (w & 1) + (lane >> 2);
      const int lc = (pass & 2) + chn;
      const uint32_t kc = sb + kc_off(lc);
      auto put = [&](int idx, float v) {
        sts16(kc + idx * 2, __bfloat16_as_ushort(__float2bfloat16_rn(v)));
      };
#pragma unroll
      for (int hi = 0; hi < 2; hi++) {
        const int i = i0 + 8 * hi;
        float v[5];
#pragma unroll
        for (int j = 0; j < 5; j++) v[j] = chn ? T[4 * j + 2 * hi + 1] : T[4 * j + 2 * hi];
        put(8 * i + 1 + t, v[0]);
        put(8 * i + 5 + t, v[1]);
        put(257 + 4 * i + t, v[2]);
        put(385 + 2 * i + (t & 1) + 64 * (t >> 1), v[3]);
        put(513 + i + 32 * t, v[4]);
      }
#pragma unroll
      for (int o = 16; o > 0; o >>= 1) k0 += __shfl_xor_sync(~0u, k0, o);
      if (lane == 0) sts32f(sb + SM_RED + 4 * w, k0);
      bar_sync(4, 128);
      if (m == 0) put(0, k0 + __uint_as_float(lds32(sb + SM_RED + 4 * w + 4)));
      k0 = m ? 0.f : __bfloat162float(p.dskip[cv_chan(cta, 2 + chn)]);
      in = in1;
    }
  }
}

__device__ __forceinline__ void expand_taps(uint32_t sb, int ht) {
  const int ch = ht >> 5, lane = ht & 31;
  const uint32_t kc = sb + kc_off(ch);
  const uint32_t dst0 = sb + cv_pe(ch);
  auto put = [&](int G, uint32_t v0, uint32_t v1, uint32_t v2, uint32_t v3, uint32_t v4, uint32_t v5, uint32_t v6, uint32_t v7, uint32_t v8) {
    const uint32_t dst = dst0 + G * 32;
    sts128(dst, make_uint4(v1 | (v0 << 16), v2 | (v1 << 16), v3 | (v2 << 16), v4 | (v3 << 16)));
    sts128(dst + 16, make_uint4(v5 | (v4 << 16), v6 | (v5 << 16), v7 | (v6 << 16), v8 | (v7 << 16)));
  };
  {
    const uint4 q = lds128(kc + lane * 16);
    const uint32_t pv = lane ? lds16(kc + lane * 16 - 2) : 0u;
    const uint32_t dst = dst0 + (lane + 2) * 32;
    sts128(dst, make_uint4(__byte_perm(q.x, pv, 0x5410), __byte_perm(q.x, q.x, 0x1032), __byte_perm(q.y, q.x, 0x7610), __byte_perm(q.y, q.y, 0x1032)));
    sts128(dst + 16, make_uint4(__byte_perm(q.z, q.y, 0x7610), __byte_perm(q.z, q.z, 0x1032), __byte_perm(q.w, q.z, 0x7610), __byte_perm(q.w, q.w, 0x1032)));
    if (lane < 4) sts128(dst0 + lane * 16, make_uint4(0, 0, 0, 0));
  }
  uint32_t a[5], b[2][3];
  {
    const uint32_t s1 = kc + 2 * (256 + 4 * lane);
#pragma unroll
    for (int k = 0; k < 5; k++) a[k] = lds16(s1 + 2 * k);
#pragma unroll
    for (int u = 0; u < 2; u++) {
      const uint32_t s2 = kc + 2 * (384 + 2 * (lane + 32 * u));
#pragma unroll
      for (int k = 0; k < 3; k++) b[u][k] = lds16(s2 + 2 * k);
    }
  }
  const uint32_t k255 = lds16(kc + 2 * 255), k1024 = lds16(kc + 2 * 512);
  put(34 + lane, lane == 0 ? k255 : a[0], a[0], a[0], a[1], a[2], a[2], a[2], a[3], a[4]);
#pragma unroll
  for (int u = 0; u < 2; u++) put(66 + lane + 32 * u, b[u][0], b[u][0], b[u][0], b[u][0], b[u][1], b[u][1], b[u][1], b[u][2], b[u][2]);
  if (lane < 10) {
    const uint32_t v = lane == 0 ? k1024 : 0u;
    put(130 + lane, v, v, v, v, v, v, 0u, 0u, 0u);
  }
}
__device__ __forceinline__ void expand_far(uint32_t sb, int ht) {
  const int ch = ht >> 5, lane = ht & 31;
  const uint32_t kc = sb + kc_off(ch) + 4 * (249 + lane), dst = sb + cv_fa(ch);
  uint32_t v[2][9];
#pragma unroll
  for (int u = 0; u < 2; u++)
#pragma unroll
    for (int k = 0; k < 9; k++) v[u][k] = lds32(kc + 4 * (32 * u + k));
#pragma unroll
  for (int k = 0; k < 8; k++) v[0][k] = lane + k < 7 ? 0u : lane + k == 7 ? v[0][k] & 0xffff0000u : v[0][k];
#pragma unroll
  for (int u = 0; u < 2; u++) {
    const uint32_t row = dst + (56 + 32 * u + lane) * 16;
    sts128(row, make_uint4(__byte_perm(v[u][1], v[u][2], 0x5410), __byte_perm(v[u][3], v[u][4], 0x5410), __byte_perm(v[u][5], v[u][6], 0x5410), __byte_perm(v[u][7], v[u][8], 0x5410)));
    sts128(row + 2048, make_uint4(__byte_perm(v[u][0], v[u][1], 0x7632), __byte_perm(v[u][2], v[u][3], 0x7632), __byte_perm(v[u][4], v[u][5], 0x7632), __byte_perm(v[u][6], v[u][7], 0x7632)));
    sts128(dst + u * 2048 + lane * 16, make_uint4(0, 0, 0, 0));
    if (lane < 24) sts128(dst + u * 2048 + (32 + lane) * 16, make_uint4(0, 0, 0, 0));
  }
}

#define MAPF 0
#define PMAP 1
#define FIRST 0
#define WPRE 2
__host__ __device__ constexpr int bar_count(int i) {
  return i == B_END ? 3 : i == B_CSF ? 2 : (i >= B_OST && i < B_PDONE + 2) ? 4 : (i == B_PUB + 2 || i == B_PUB || i == B_R + 1) ? 256 : (i >= B_FARM && i < B_END) ? 128 : 1;
}
__host__ __device__ constexpr bool bar_first(int i) { return i < B_WF + 2 && (i & 7) < 2; }

__global__ void __launch_bounds__(NTHREADS, 1) fused_kernel(const __grid_constant__ Params p) {
  extern __shared__ __align__(1024) uint8_t smem[];
  const uint32_t sb = s32(smem);
  const int tid = threadIdx.x, lane = tid & 31;
  const int warp = __shfl_sync(~0u, tid >> 5, 0);
  const int cta = blockIdx.x - p.first;
  if ((unsigned)cta >= NCTA) {
    colsum_cta(p, sb, blockIdx.x & 3, tid);
    return;
  }
  const int rb = ((cta >> 4) & 3) * 4 + ((cta >> 2) & 3), hg = (cta >> 6) * 4 + (cta & 3);
  const int rb2 = rb, q2 = hg;
  const uint32_t bar = sb + SM_BAR;
  auto ld_x0 = [&](int half, int c) {
    const uint32_t b = bar + 8 * (B_XF + 8 * half + c);
    mbar_expect(b, PG);
    tma_ld(sb + x_page(half, c) * PG, &p.mapX, c * 64, (16 * half + rb) * 64, b);
  };
  auto ld_w = [&](int c) {
    const uint32_t b = bar + 8 * (B_WF + c);
    mbar_expect(b, 3 * PG);
    tma_ld3(sb + w_page(c) * PG, &p.mapW3, hg * 64, c * 64, 0, b);
  };

  if (tid == 0) TS(0);
  if (tid == 480) LTS(0);
  if (warp < 6 && elect_one()) {
    if (warp == 0) {
#pragma unroll
      for (int i = 0; i < B_WF + 2; i++)
        if (bar_first(i)) mbar_init(bar + 8 * i, 1);
      asm volatile("fence.mbarrier_init.release.cluster;" ::: "memory");
      fence_async_smem();
      ld_x0(0, 0); ld_w(0); ld_x0(1, 0);
      ld_x0(0, 1); ld_w(1); ld_x0(1, 1);
      TS(1);
    } else {
#pragma unroll
      for (int q = 0; q < 5; q++) {
        if (warp == q + 1) {
#pragma unroll
          for (int i = 0; i < B_COUNT; i++)
            if (!bar_first(i) && i % 5 == q) mbar_init(bar + 8 * i, bar_count(i));
        }
      }
      asm volatile("fence.mbarrier_init.release.cluster;" ::: "memory");
    }
  }

  if (warp < 8) {
    bar_sync(0, NTHREADS);
    asm volatile("setmaxnreg.inc.sync.aligned.u32 %0;" ::"n"(R_CONS));
    const int cw = __shfl_sync(~0u, opaque_tid() >> 5, 0);
    const int wg = cw >> 2, w = cw & 3;
    if (tid == 0) TS(2);
    int rtp = 0;
#pragma unroll 1
    for (int layer = 0; layer < 2; layer++) {
      attn_phase(p, sb, layer, rb, hg, wg, w);
      proj_phase(p, sb, layer, rb2, q2, wg, w, rtp);
      conv_phase(p, sb, layer, cta);
    }
    final_phase(p, sb, cta, wg, w, rtp);
  } else if (warp < 12) {
    asm volatile("setmaxnreg.dec.sync.aligned.u32 %0;" ::"n"(R_HELP));
    const int ht = tid - 256;
    {
      unsigned ep0 = 0;
      if (ht == 0) ep0 = ld_relaxed(&g_cnt[C_CS * 32]);
      const ModeIn in0 = load_modes(p, cv_chan(cta, ht >> 6), ht & 63), in1 = load_modes(p, cv_chan(cta, 2 + (ht >> 6)), ht & 63);
      bar_sync(0, NTHREADS);
      if (ht == 0) {
        sts32(sb + SM_EP, ep0 / NCTA);
        mbar_arrive(bar + 8 * B_EP);
      }
      kernel_gen(p, sb, cta, ht, in0, in1);
      if (ht < 96) sts128f(sb + SM_STG + ht * 16, 0.f, 0.f, 0.f, 1.f);
      fence_async_smem();
      bar_sync(4, 128);
      if (ht == 0) mbar_arrive(bar + 8 * B_KG);
    }
#pragma unroll 1
    for (int layer = 0; layer < 2; layer++) {
      bf16* xout = g_xT + ((2 * layer + 1) * DM + 2 * cta) * LSEQ;
      mbar_wait(bar + 8 * B_PDONE, layer);
      expand_taps(sb, opaque_tid() - 256);
      mbar_arrive(bar + 8 * B_PE);
      TSW(0);
      expand_far(sb, opaque_tid() - 256);
      if (layer) mbar_wait(bar + 8 * (B_RS + 2), 0);
      mbar_wait(bar + 8 * (B_PDONE + 1), layer);
      mbar_wait(bar + 8 * B_U, layer);
#pragma unroll 1
      for (int lc = 0; lc < 4; lc += 2) {
        conv_sums(sb, lc, opaque_tid() - 256);
        TSW(1 + lc);
      }
      fence_async_smem();
      bar_sync(4, 128);
      conv_far(sb, opaque_tid() - 256);
      mbar_arrive(bar + 8 * B_FARM);
      TSW(4);
      mbar_wait(bar + 8 * (B_R + 1), layer);
      conv_epi<1, 2>(sb, xout, 0, opaque_tid() - 256);
      mbar_arrive(bar + 8 * (B_PUB + 1));
      TSW(5);
      mbar_wait(bar + 8 * (B_R + 2), layer);
      conv_epi<1, 1>(sb, xout, 2, opaque_tid() - 256);
      mbar_arrive(bar + 8 * (B_PUB + 2));
      TSW(6);
    }
  } else {
    asm volatile("setmaxnreg.dec.sync.aligned.u32 %0;" ::"n"(R_AGENT));
    bar_sync(0, NTHREADS);
    auto done = [&](int half, int c, int layer) { mbar_wait(bar + 8 * (B_DN + 8 * half + c), layer); };
    auto publish = [&](int layer, int k) {
      mbar_wait(bar + 8 * (B_PUB + k), layer);
      if (layer == 0) {
        red_release(&g_cnt[(C_C + k) * 32]);
      }
      else red_relaxed(&g_cnt[(C_F + 4 * k + (cta >> 5)) * 32]);
      TS(16 + layer * 56 + 40 + 7 + k);
    };
    if (warp == 12) {
      if (elect_one()) {
#pragma unroll 1
        for (int layer = 0; layer < 2; layer++) {
          auto ld_xe = [&](int c) {
            const uint32_t b = bar + 8 * (B_XF + c);
            mbar_expect(b, PG);
            if (layer == 0) tma_ld(sb + (c - 5) * PG, &p.mapX, c * 64, rb * 64, b);
            else tma_ld(sb + (c - 5) * PG, &p.mapXT, rb * 64, DM + c * 64, b);
          };
          if (layer == 0) {
            ld_x0(0, 2); ld_w(2); ld_x0(1, 2);
            if (hg >= 3) {
              mbar_expect(bar + 8 * B_SC, PG);
              tma_ld(sb + P_R * PG, &p.mapX, hg * 64, rb * 64, bar + 8 * B_SC);
            }
            if (rb < 4) tma_prefetch3(&p.mapW3, hg * 64, (4 + rb) * 64, 0);
            ld_x0(0, 3); ld_w(3); ld_x0(1, 3); ld_x0(0, 4); ld_x0(1, 4);
            done(0, 0, 0); done(1, 0, 0);
            ld_w(4);
            ld_x0(1, 5); ld_x0(1, 6); ld_x0(1, 7);
            done(0, 1, 0); done(1, 1, 0);
            ld_w(5);
            if (rb2 < 8) tma_prefetch5(&p.mapWo, q2 * 64, rb2 * 2);
            done(0, 2, 0);
            fence_async_smem();
            ld_xe(5); ld_xe(6); ld_xe(7);
          } else {
            mbar_wait(bar + 8 * B_PDONE, 0);
            mbar_wait(bar + 8 * (B_PDONE + 1), 0);
            mbar_wait(bar + 8 * (WPRE == 1 ? B_U : B_GB + 1), 0);
            ld_w(0); ld_w(1);
            mbar_wait(bar + 8 * B_U1, 0);
            fence_async_smem();
            ld_w(2);
            mbar_wait(bar + 8 * (B_PUB + 2), 0);
            fence_async_smem();
            ld_w(3);
            done(0, 2, 1);
            fence_async_global();
            fence_async_smem();
            ld_xe(5); ld_xe(6); ld_xe(7);
            done(1, 0, 1);
            ld_w(4);
            done(1, 1, 1);
            ld_w(5);
          }
          done(1, 2, layer);
          fence_async_smem();
          ld_w(6); ld_w(7);
          auto ld_res = [&](int half) {
            const uint32_t b = bar + 8 * (B_RF + half);
            mbar_expect(b, PG);
            if (layer == 0) tma_ld(sb + (P_R + half) * PG, &p.mapX, q2 * 64, (16 * half + rb2) * 64, b);
            else tma_ld(sb + (P_R + half) * PG, &p.mapXT, (16 * half + rb2) * 64, DM + q2 * 64, b);
          };
          done(0, 4, layer); done(1, 3, layer);
          fence_async_smem();
#pragma unroll 1
          for (int c = 0; c < 8; c++) {
            const uint32_t b = bar + 8 * (B_WOF + (c >> 1));
            if (c == 5) { ld_res(0); done(1, 4, layer); }
            if ((c & 1) == 0) mbar_expect(b, 2 * PG);
            tma_ld5(sb + wo_page(c) * PG, &p.mapWo, q2 * 64, c * 2, b);
          }
          mbar_wait(bar + 8 * B_KG, 0);
          fence_async_global();
          ld_res(1);
        }
      }
    } else if (warp == 13) {
      if (elect_one()) {
        mbar_wait(bar + 8 * (B_WF + 2), 0);
        asm volatile("prefetch.tensormap [%0];" ::"l"(&p.mapXT) : "memory");
        asm volatile("prefetch.tensormap [%0];" ::"l"(&p.mapOut) : "memory");
        asm volatile("prefetch.tensormap [%0];" ::"l"(&p.mapWo) : "memory");
        mbar_wait(bar + 8 * B_EP, 0);
        const unsigned e1 = lds32(sb + SM_EP) + 1;
        spin_until(&g_cnt[C_Z * 32], e1 * NCTA);
        mbar_arrive(bar + 8 * B_CSF);
        TS(3);
        auto ld_x1 = [&](int half, int c0, int c1) {
          fence_async_global();
          fence_async_smem();
#pragma unroll 1
          for (int c = c0; c < c1; c++) {
            const uint32_t b = bar + 8 * (B_XF + 8 * half + c);
            mbar_expect(b, PG);
            tma_ld(sb + x_page(half, c) * PG, &p.mapXT, (16 * half + rb) * 64, DM + c * 64, b);
          }
        };
#pragma unroll 1
        for (int layer = 0; layer < 2; layer++) {
          if (layer == 1) {
            mbar_wait(bar + 8 * B_FARM, 0);
            mbar_wait(bar + 8 * B_PUB, 0);
            spin_until(&g_cnt[C_C * 32], e1 * NCTA);
            TS(10);
            ld_x1(0, 0, 3);
            if (hg >= 3) {
              mbar_expect(bar + 8 * B_SC, PG);
              tma_ld(sb + P_R * PG, &p.mapXT, rb * 64, DM + hg * 64, bar + 8 * B_SC);
            }
            ld_x1(0, 3, 5);
            mbar_wait(bar + 8 * (B_PUB + 1), 0);
            spin_until(&g_cnt[(C_C + 1) * 32], e1 * NCTA);
            TS(11);
            ld_x1(1, 0, 4);
            spin_until(&g_cnt[(C_C + 2) * 32], e1 * NCTA);
            TS(12);
            ld_x1(1, 4, 8);
          }
#pragma unroll 1
          for (int half = 0; half < 2; half++) {
            done(1, 7, layer);
            mbar_wait(bar + 8 * B_OST, layer);
            if (half) mbar_wait(bar + 8 * (B_OST + 1), layer);
            spin_until(&g_cnt[(C_O + layer * 32 + 16 * half + rb2) * 32], e1 * 32);
            fence_async_global();
            fence_async_smem();
#pragma unroll 1
            for (int c = 0; c < 4; c++) {
              const uint32_t b = bar + 8 * (B_OF + 4 * half + c);
              mbar_expect(b, 2 * PG);
              bulk_ld(sb + o_page(half, c) * PG, g_O + ((layer * 32 + 16 * half + rb2) * 4 + c) * PG, 2 * PG, b);
            }
          }
        }
        mbar_wait(bar + 8 * B_PUB, 1);
#pragma unroll 1
        for (int half = 0; half < 2; half++) {
          spin_until(&g_cnt[(C_F + 4 * (half ? 1 + (cta >> 6) : 0) + ((cta >> 4) & 3)) * 32], e1 * 32);
          fence_async_global();
          mbar_expect(bar + 8 * (B_TF + half), PG);
          tma_ld(sb + (16 + half) * PG, &p.mapXT, (16 * half + (cta & 15)) * 64, 3 * DM + (cta >> 4) * 64, bar + 8 * (B_TF + half));
        }
      }
    } else if (warp == 14) {
      mbar_wait(bar + 8 * B_EP, 0);
      const unsigned e1 = lds32(sb + SM_EP) + 1;
      done(0, 1, 0);
      {
        const uint2* cp = g_colsum + (hg * 192 + lane);
        uint2 v[6];
        bool ok;
        int it = 0;
        do {
          ok = true;
#pragma unroll
          for (int i = 0; i < 6; i++) {
            asm volatile("ld.relaxed.gpu.global.v2.u32 {%0,%1}, [%2];" : "=r"(v[i].x), "=r"(v[i].y) : "l"(cp + 32 * i) : "memory");
            ok = ok && v[i].y == e1;
          }
          if (++it > (1 << 22)) __trap();
        } while (!__all_sync(~0u, ok));
#pragma unroll
        for (int i = 0; i < 6; i++) sts32f(sb + SM_CS + 4 * (lane + 32 * i), __uint_as_float(v[i].x));
      }
      __syncwarp();
      if (lane == 0) {
        mbar_arrive(bar + 8 * B_CSF);
        red_relaxed(&g_cnt[C_CS * 32]);
        TS(13);
#pragma unroll 1
        for (int i = 0; i < 4; i++) {
          const int layer = i >> 1;
          mbar_wait(bar + 8 * (B_PST + (i & 1)), layer);
          const uint32_t b = bar + 8 * (B_GB + 1);
          const bf16* xin = g_xT + ((size_t)2 * layer * DM + 2 * cta) * LSEQ + 1024;
          if (i & 1) {
            fence_async_smem();
            mbar_expect(b, 12288 + PG);
          }
          spin_until(&g_cnt[(C_G + i) * 32], e1 * NCTA);
          if (i & 1) {
            bulk_ld(sb + CV_ST, g_stats + (layer * 32 + 16) * 192, 12288, b);
#pragma unroll
            for (int lc = 0; lc < 4; lc++) bulk_ld(sb + cv_x(1, lc), xin + cv_chan(0, lc) * LSEQ, 2048, b);
            TS(14 + layer);
            publish(layer, 1);
          } else {
            mbar_arrive(bar + 8 * B_GB);
          }
        }
      }
    } else {
      const uint4 u = make_uint4(UNSET, UNSET, UNSET, UNSET);
      if (lane < 24) stg128((uint4*)g_stats + cta * 24 + lane, make_uint4(0, 0, 0, 0));
#pragma unroll 4
      for (int i = 0; i < 16; i++) stg128(g_halo + cta * 512 + 32 * i + lane, u);
#pragma unroll 4
      for (int i = 0; i < 16; i++) stg128(((i & 8) ? (uint4*)g_xT : (uint4*)g_O) + cta * 1024 + (i & 7) * 128 + (lane >> 1) * 8 + (lane & 1), u);
      __syncwarp();
      if (lane == 0) {
        red_release(&g_cnt[C_Z * 32]);
        publish(0, 0);
        publish(0, 2);
        const unsigned e1 = lds32(sb + SM_EP) + 1;
#pragma unroll 1
        for (int s = 0; s < 3; s++) {
          spin_until(&g_cnt[(C_R + s) * 32], e1 * 4);
          mbar_arrive(bar + 8 * (B_RS + s));
          TS(16 + 40 + 10 + s);
        }
        publish(1, 0);
        publish(1, 2);
      }
    }
  }
}

typedef CUresult (*EncodeFn)(CUtensorMap*, CUtensorMapDataType, cuuint32_t, void*, const cuuint64_t*, const cuuint64_t*,
                             const cuuint32_t*, const cuuint32_t*, CUtensorMapInterleave, CUtensorMapSwizzle,
                             CUtensorMapL2promotion, CUtensorMapFloatOOBfill);

static void make_map(EncodeFn enc, CUtensorMap* m, void* ptr, uint64_t cols, uint64_t rows, uint32_t box_rows) {
  cuuint64_t dims[2] = {cols, rows};
  cuuint64_t strides[1] = {cols * 2};
  cuuint32_t box[2] = {64, box_rows};
  cuuint32_t es[2] = {1, 1};
  enc(m, CU_TENSOR_MAP_DATA_TYPE_BFLOAT16, 2, ptr, dims, strides, box, es, CU_TENSOR_MAP_INTERLEAVE_NONE,
      CU_TENSOR_MAP_SWIZZLE_128B, CU_TENSOR_MAP_L2_PROMOTION_L2_128B, CU_TENSOR_MAP_FLOAT_OOB_FILL_NONE);
}
static void make_map3(EncodeFn enc, CUtensorMap* m, void* ptr, uint64_t d0, uint64_t cols, uint64_t rows, uint64_t blk_stride,
                      uint64_t nblocks, uint32_t nblk) {
  cuuint64_t dims[3] = {d0, rows, nblocks};
  cuuint64_t strides[2] = {cols * 2, blk_stride * 2};
  cuuint32_t box[3] = {64, 64, nblk};
  cuuint32_t es[3] = {1, 1, 1};
  enc(m, CU_TENSOR_MAP_DATA_TYPE_BFLOAT16, 3, ptr, dims, strides, box, es, CU_TENSOR_MAP_INTERLEAVE_NONE,
      CU_TENSOR_MAP_SWIZZLE_128B, CU_TENSOR_MAP_L2_PROMOTION_L2_128B, CU_TENSOR_MAP_FLOAT_OOB_FILL_NONE);
}

extern "C" void kernel_launch(void* const* d_in, const int* in_sizes, int n_in, void* d_out, int out_size) {
  static Params prm;
  static void* cached[13] = {nullptr};
  static bool attr_done = false;
  bool same = attr_done && cached[12] == d_out;
  for (int i = 0; i < 12 && same; i++) same = cached[i] == d_in[i];
  if (!same) {
    void* fn = nullptr;
    cudaDriverEntryPointQueryResult qr;
    cudaGetDriverEntryPoint("cuTensorMapEncodeTiled", &fn, cudaEnableDefault, &qr);
    EncodeFn enc = (EncodeFn)fn;
    void* pXT;
    cudaGetSymbolAddress(&pXT, g_xT);
    make_map(enc, &prm.mapX, d_in[0], DM, LSEQ, 64);
    make_map(enc, &prm.mapXT, pXT, LSEQ, 4 * DM, 64);
    make_map(enc, &prm.mapOut, d_out, DM, LSEQ, 64);
    {
      cuuint64_t dims[5] = {DM, 2, 4, 4, 16};
      cuuint64_t strides[4] = {DM * 2, 8 * DM * 2, 2 * DM * 2, 32 * DM * 2};
      cuuint32_t box[5] = {64, 2, 4, 4, 2};
      cuuint32_t es[5] = {1, 1, 1, 1, 1};
      enc(&prm.mapWo, CU_TENSOR_MAP_DATA_TYPE_BFLOAT16, 5, d_in[2], dims, strides, box, es, CU_TENSOR_MAP_INTERLEAVE_NONE,
          CU_TENSOR_MAP_SWIZZLE_128B, CU_TENSOR_MAP_L2_PROMOTION_L2_128B, CU_TENSOR_MAP_FLOAT_OOB_FILL_NONE);
    }
    make_map3(enc, &prm.mapW3, d_in[1], DM, 3 * DM, DM, DM, 3, 3);
    prm.wqkv = (const bf16*)d_in[1];
    prm.a_re = (const bf16*)d_in[4]; prm.a_im = (const bf16*)d_in[5];
    prm.b_re = (const bf16*)d_in[6]; prm.b_im = (const bf16*)d_in[7];
    prm.c_re = (const bf16*)d_in[8]; prm.c_im = (const bf16*)d_in[9];
    prm.log_dt = (const bf16*)d_in[10]; prm.dskip = (const bf16*)d_in[11];
    int dev = 0, sms = 0;
    cudaGetDevice(&dev);
    cudaDeviceGetAttribute(&sms, cudaDevAttrMultiProcessorCount, dev);
    prm.first = sms >= NCTA + 4 ? FIRST : 4;
    cudaFuncSetAttribute(fused_kernel, cudaFuncAttributeMaxDynamicSharedMemorySize, SM_TOTAL);
    for (int i = 0; i < 12; i++) cached[i] = d_in[i];
    cached[12] = d_out;
    attr_done = true;
  }
  fused_kernel<<<NCTA + 4, NTHREADS, SM_TOTAL>>>(prm);
}
```

```cpp
#include <cuda_runtime.h>
#include <cuda_bf16.h>
#include <cuda.h>
#include <stdint.h>

typedef __nv_bfloat16 bf16;

constexpr int LSEQ = 2048;
constexpr int DM = 512;
constexpr int NCTA = 128;
constexpr int NTHREADS = 512;
#define R_CONS 200
#define R_HELP 88
#define R_AGENT 24
#define GPOS 4
#define TURN0 4
#define TURN1 4

constexpr int PG = 8192;
constexpr int P_R = 25;
__host__ __device__ constexpr int x_page(int half, int c) { return half ? 8 + c : c < 5 ? c : c - 5; }
__host__ __device__ constexpr int w_page(int c) { return (c & 3) < 3 ? 16 + 3 * (c & 3) : c < 4 ? 5 : 8; }
__host__ __device__ constexpr int wo_page(int c) { return c < 5 ? 3 + c : 11 + c; }
__host__ __device__ constexpr int o_page(int half, int pair) { return half ? (pair ? 17 + 2 * pair : 0) : 8 + 2 * pair; }
constexpr int SM_KGB = (P_R + 1) * PG;
constexpr int SM_KC = 27 * PG;
constexpr int KC_STRIDE = 648;
__host__ __device__ constexpr int kc_off(int lc) { return SM_KC + (lc & 1) * 2 * KC_STRIDE + (lc < 2 ? 3328 : 0); }
constexpr int SM_KGT = SM_KC + 3328 + 2592;
constexpr int SM_CS = SM_KGT + 2048;
constexpr int SM_RED = SM_CS + 768;
constexpr int SM_EP = SM_RED + 16;
constexpr int SM_STG = SM_RED + 32;
constexpr int SM_BAR = SM_STG + 768;
constexpr int SM_TS = SM_BAR + 768;
constexpr int SM_TOTAL = SM_TS + 512;
static_assert(SM_TOTAL <= 232448 && SM_STG % 16 == 0 && SM_KGT % 16 == 0, "shared memory");

constexpr int CV_UH = 140 * 16;
__host__ __device__ constexpr int cv_u(int lc) { return (8 + 2 * lc) * PG; }
__host__ __device__ constexpr int cv_pe(int lc) { return cv_u(lc) + 4480; }
__host__ __device__ constexpr int cv_pb1(int lc, int w) { return w ? cv_u(lc) + 8960 + (w - 1) * 2048 : 7 * PG + lc * 2048; }
__host__ __device__ constexpr int cv_fa(int lc) { return cv_pb1(lc, 1) + 128; }
__host__ __device__ constexpr int cv_dump(int lc) { return cv_u(lc) + 16256; }
__host__ __device__ constexpr int cv_pb0(int lc, int w) { return lc * PG + w * 2048; }
__host__ __device__ constexpr int cv_se(int lc) { return 4 * PG + lc * 4096; }
__host__ __device__ constexpr int cv_so(int lc) { return cv_se(lc) + 2048; }
__host__ __device__ constexpr int cv_pf(int lc) { return 6 * PG + lc * 2048; }
__host__ __device__ constexpr int cv_x(int half, int lc) { return (P_R + half) * PG + lc * 2048; }
constexpr int CV_ST = 22 * PG;
__host__ __device__ constexpr int cv_chan(int cta, int lc) { return 2 * cta + (lc & 1) + 256 * (lc >> 1); }

enum {
  B_XF = 0,
  B_WF = 16,
  B_OF = 24,
  B_DN = 32,
  B_WOF = 48,
  B_RF = 52,
  B_PST = 54,
  B_OST = 56,
  B_PDONE = 58,
  B_GB = 60,
  B_TF = 62,
  B_CSF = 64,
  B_EP = 65,
  B_KG = 67,
  B_FARM = 68,
  B_PE = 70,
  B_U = 71,
  B_PUB = 74,
  B_R = 77,
  B_END = 80,
  B_SC = 81,
  B_RT = 82,
  B_U1 = 84,
  B_RS = 85,
  B_COUNT = 88
};

enum {
  C_CS = 0,
  C_G = 1,
  C_C = 5,
  C_F = 8,
  C_O = 20,
  C_Z = 84,
  C_R = 85,
  C_COUNT = 88
};

__device__ unsigned g_cnt[C_COUNT * 32];
__device__ __align__(1024) bf16 g_O[2 * LSEQ * DM];
__device__ __align__(1024) bf16 g_xT[4 * DM * LSEQ];
__device__ __align__(1024) float g_stats[2 * 32 * 192];
__device__ __align__(1024) uint2 g_colsum[3 * DM];
__device__ __align__(1024) uint4 g_halo[2 * 32 * 8 * 256];
__device__ __align__(1024) uint4 g_part[2 * 32 * 8 * 64];
#define TS(i) do { } while (0)
#define TSW(k) do { if ((threadIdx.x & 127) == 0) TS(16 + layer * 56 + (threadIdx.x >> 7) * 20 + (k)); } while (0)
#define TSG(k) do { } while (0)

#define RETRY(i) do { } while (0)
#define LTS(i) do { } while (0)

struct Params {
  CUtensorMap mapX, mapW3, mapXT, mapOut, mapWo;
  const bf16 *wqkv, *a_re, *a_im, *b_re, *b_im, *c_re, *c_im, *log_dt, *dskip;
  int first;
};

__device__ __forceinline__ uint32_t s32(const void* p) { return (uint32_t)__cvta_generic_to_shared(p); }
__device__ __forceinline__ void mbar_init(uint32_t b, int c) { asm volatile("mbarrier.init.shared::cta.b64 [%0], %1;" ::"r"(b), "r"(c) : "memory"); }
__device__ __forceinline__ void mbar_expect(uint32_t b, int bytes) { asm volatile("mbarrier.arrive.expect_tx.shared::cta.b64 _, [%0], %1;" ::"r"(b), "r"(bytes) : "memory"); }
__device__ __forceinline__ void mbar_arrive(uint32_t b) { asm volatile("mbarrier.arrive.shared::cta.b64 _, [%0];" ::"r"(b) : "memory"); }
__device__ __forceinline__ void mbar_wait(uint32_t b, int parity) {
  asm volatile("{\n.reg .pred p;\nWAIT_LOOP:\nmbarrier.try_wait.parity.shared::cta.b64 p, [%0], %1;\n@p bra WAIT_DONE;\nbra WAIT_LOOP;\nWAIT_DONE:\n}" ::"r"(b), "r"(parity) : "memory");
}
__device__ __forceinline__ bool mbar_test(uint32_t b, int parity) {
  uint32_t ok;
  asm volatile("{\n.reg .pred p;\nmbarrier.test_wait.parity.shared::cta.b64 p, [%1], %2;\nselp.u32 %0, 1, 0, p;\n}" : "=r"(ok) : "r"(b), "r"(parity) : "memory");
  return ok != 0;
}
__device__ __forceinline__ int opaque_tid() { int v; asm volatile("mov.u32 %0, %%tid.x;" : "=r"(v)); return v; }
__device__ __forceinline__ bool elect_one() {
  uint32_t r;
  asm volatile("{\n.reg .pred p;\nelect.sync _|p, 0xffffffff;\nselp.u32 %0, 1, 0, p;\n}" : "=r"(r));
  return r != 0;
}
__device__ __forceinline__ void tma_ld(uint32_t dst, const CUtensorMap* m, int c0, int c1, uint32_t bar) {
  asm volatile("cp.async.bulk.tensor.2d.shared::cluster.global.mbarrier::complete_tx::bytes [%0], [%1, {%3, %4}], [%2];"
               ::"r"(dst), "l"(m), "r"(bar), "r"(c0), "r"(c1) : "memory");
}
__device__ __forceinline__ void tma_ld3(uint32_t dst, const CUtensorMap* m, int c0, int c1, int c2, uint32_t bar) {
  asm volatile("cp.async.bulk.tensor.3d.shared::cluster.global.mbarrier::complete_tx::bytes [%0], [%1, {%3, %4, %5}], [%2];"
               ::"r"(dst), "l"(m), "r"(bar), "r"(c0), "r"(c1), "r"(c2) : "memory");
}
__device__ __forceinline__ void tma_ld5(uint32_t dst, const CUtensorMap* m, int c0, int c4, uint32_t bar) {
  asm volatile("cp.async.bulk.tensor.5d.shared::cluster.global.mbarrier::complete_tx::bytes [%0], [%1, {%3, 0, 0, 0, %4}], [%2];"
               ::"r"(dst), "l"(m), "r"(bar), "r"(c0), "r"(c4) : "memory");
}
__device__ __forceinline__ void tma_prefetch5(const CUtensorMap* m, int c0, int c4) {
  asm volatile("cp.async.bulk.prefetch.tensor.5d.L2.global.tile [%0, {%1, 0, 0, 0, %2}];" ::"l"(m), "r"(c0), "r"(c4) : "memory");
}
__device__ __forceinline__ void tma_prefetch2(const CUtensorMap* m, int c0, int c1) {
  asm volatile("cp.async.bulk.prefetch.tensor.2d.L2.global.tile [%0, {%1, %2}];" ::"l"(m), "r"(c0), "r"(c1) : "memory");
}
__device__ __forceinline__ void tma_prefetch3(const CUtensorMap* m, int c0, int c1, int c2) {
  asm volatile("cp.async.bulk.prefetch.tensor.3d.L2.global.tile [%0, {%1, %2, %3}];" ::"l"(m), "r"(c0), "r"(c1), "r"(c2) : "memory");
}
__device__ __forceinline__ void tma_st(const CUtensorMap* m, int c0, int c1, uint32_t src) {
  asm volatile("cp.async.bulk.tensor.2d.global.shared::cta.bulk_group [%0, {%2, %3}], [%1];" ::"l"(m), "r"(src), "r"(c0), "r"(c1) : "memory");
}
__device__ __forceinline__ void bulk_ld(uint32_t dst, const void* src, int bytes, uint32_t bar) {
  asm volatile("cp.async.bulk.shared::cluster.global.mbarrier::complete_tx::bytes [%0], [%1], %2, [%3];" ::"r"(dst), "l"(src), "r"(bytes), "r"(bar) : "memory");
}
__device__ __forceinline__ void bulk_st(void* dst, uint32_t src, int bytes) {
  asm volatile("cp.async.bulk.global.shared::cta.bulk_group [%0], [%1], %2;" ::"l"(dst), "r"(src), "r"(bytes) : "memory");
}
__device__ __forceinline__ void bulk_red_add_f32(void* dst, uint32_t src, int bytes) {
  asm volatile("cp.reduce.async.bulk.global.shared::cta.bulk_group.add.f32 [%0], [%1], %2;" ::"l"(dst), "r"(src), "r"(bytes) : "memory");
}
__device__ __forceinline__ void bulk_commit() { asm volatile("cp.async.bulk.commit_group;" ::: "memory"); }
__device__ __forceinline__ void bulk_wait_all() { asm volatile("cp.async.bulk.wait_group 0;" ::: "memory"); }
__device__ __forceinline__ void fence_async_smem() { asm volatile("fence.proxy.async.shared::cta;" ::: "memory"); }
__device__ __forceinline__ void fence_async_global() { asm volatile("fence.proxy.async.global;" ::: "memory"); }
__device__ __forceinline__ void bar_sync(int id, int n) { asm volatile("bar.sync %0, %1;" ::"r"(id), "r"(n) : "memory"); }
__device__ __forceinline__ void bar_arrive(int id, int n) { asm volatile("bar.arrive %0, %1;" ::"r"(id), "r"(n) : "memory"); }
__device__ __forceinline__ bool bar_or(int id, int n, bool v) {
  uint32_t r;
  asm volatile("{\n.reg .pred p, q;\nsetp.ne.u32 q, %3, 0;\nbar.red.or.pred p, %1, %2, q;\nselp.u32 %0, 1, 0, p;\n}" : "=r"(r) : "r"(id), "r"(n), "r"((uint32_t)v) : "memory");
  return r != 0;
}
__device__ __forceinline__ void bulk_wait_read() { asm volatile("cp.async.bulk.wait_group.read 0;" ::: "memory"); }
__device__ __forceinline__ void stg128(void* p, uint4 v) { asm volatile("st.relaxed.gpu.global.v4.u32 [%0], {%1,%2,%3,%4};" ::"l"(p), "r"(v.x), "r"(v.y), "r"(v.z), "r"(v.w) : "memory"); }
constexpr uint32_t UNSET = 0xffffffffu;
constexpr int MAX_RETRY = 1 << 16;
__device__ __forceinline__ void wg_fence() { asm volatile("wgmma.fence.sync.aligned;" ::: "memory"); }
__device__ __forceinline__ void wg_commit() { asm volatile("wgmma.commit_group.sync.aligned;" ::: "memory"); }
template <int N> __device__ __forceinline__ void wg_wait() { asm volatile("wgmma.wait_group.sync.aligned %0;" ::"n"(N) : "memory"); }
__device__ __forceinline__ uint64_t mkdesc(uint32_t addr, uint32_t lbo, uint32_t sbo, int sw) {
  return (uint64_t)((addr & 0x3FFFF) >> 4) | ((uint64_t)(lbo >> 4) << 16) | ((uint64_t)(sbo >> 4) << 32) | ((uint64_t)sw << 62);
}
__device__ __forceinline__ void ldsm4(uint32_t* r, uint32_t a) {
  asm volatile("ldmatrix.sync.aligned.m8n8.x4.shared.b16 {%0,%1,%2,%3}, [%4];" : "=r"(r[0]), "=r"(r[1]), "=r"(r[2]), "=r"(r[3]) : "r"(a) : "memory");
}
__device__ __forceinline__ void ldsm4t(uint32_t* r, uint32_t a) {
  asm volatile("ldmatrix.sync.aligned.m8n8.x4.trans.shared.b16 {%0,%1,%2,%3}, [%4];" : "=r"(r[0]), "=r"(r[1]), "=r"(r[2]), "=r"(r[3]) : "r"(a) : "memory");
}
__device__ __forceinline__ void stsm4(uint32_t a, uint32_t r0, uint32_t r1, uint32_t r2, uint32_t r3) {
  asm volatile("stmatrix.sync.aligned.m8n8.x4.shared.b16 [%0], {%1,%2,%3,%4};" ::"r"(a), "r"(r0), "r"(r1), "r"(r2), "r"(r3) : "memory");
}
__device__ __forceinline__ void stsm4t(uint32_t a, uint32_t r0, uint32_t r1, uint32_t r2, uint32_t r3) {
  asm volatile("stmatrix.sync.aligned.m8n8.x4.trans.shared.b16 [%0], {%1,%2,%3,%4};" ::"r"(a), "r"(r0), "r"(r1), "r"(r2), "r"(r3) : "memory");
}
__device__ __forceinline__ uint32_t movm_t(uint32_t a) { uint32_t r; asm volatile("movmatrix.sync.aligned.m8n8.trans.b16 %0, %1;" : "=r"(r) : "r"(a)); return r; }
__device__ __forceinline__ uint32_t lds32(uint32_t a) { uint32_t v; asm volatile("ld.shared.b32 %0, [%1];" : "=r"(v) : "r"(a) : "memory"); return v; }
__device__ __forceinline__ float2 lds64f(uint32_t a) { float2 v; asm volatile("ld.shared.v2.f32 {%0,%1}, [%2];" : "=f"(v.x), "=f"(v.y) : "r"(a) : "memory"); return v; }
__device__ __forceinline__ float4 lds128f(uint32_t a) { float4 v; asm volatile("ld.shared.v4.f32 {%0,%1,%2,%3}, [%4];" : "=f"(v.x), "=f"(v.y), "=f"(v.z), "=f"(v.w) : "r"(a) : "memory"); return v; }
__device__ __forceinline__ uint4 lds128(uint32_t a) { uint4 v; asm volatile("ld.shared.v4.b32 {%0,%1,%2,%3}, [%4];" : "=r"(v.x), "=r"(v.y), "=r"(v.z), "=r"(v.w) : "r"(a) : "memory"); return v; }
__device__ __forceinline__ void sts128(uint32_t a, uint4 v) { asm volatile("st.shared.v4.b32 [%0], {%1,%2,%3,%4};" ::"r"(a), "r"(v.x), "r"(v.y), "r"(v.z), "r"(v.w) : "memory"); }
__device__ __forceinline__ void sts128f(uint32_t a, float x, float y, float z, float w) { asm volatile("st.shared.v4.f32 [%0], {%1,%2,%3,%4};" ::"r"(a), "f"(x), "f"(y), "f"(z), "f"(w) : "memory"); }
__device__ __forceinline__ void sts32f(uint32_t a, float v) { asm volatile("st.shared.f32 [%0], %1;" ::"r"(a), "f"(v) : "memory"); }
__device__ __forceinline__ void sts16(uint32_t a, uint16_t v) { asm volatile("st.shared.u16 [%0], %1;" ::"r"(a), "h"(v) : "memory"); }
__device__ __forceinline__ uint32_t lds16(uint32_t a) { uint16_t v; asm volatile("ld.shared.u16 %0, [%1];" : "=h"(v) : "r"(a) : "memory"); return v; }
__device__ __forceinline__ uint32_t packbf(float lo, float hi) { uint32_t r; asm("cvt.rn.bf16x2.f32 %0, %1, %2;" : "=r"(r) : "f"(hi), "f"(lo)); return r; }
__device__ __forceinline__ float bf_lo(uint32_t v) { return __uint_as_float(v << 16); }
__device__ __forceinline__ float bf_hi(uint32_t v) { return __uint_as_float(v & 0xffff0000u); }
__device__ __forceinline__ float ex2(float x) { float r; asm("ex2.approx.ftz.f32 %0, %1;" : "=f"(r) : "f"(x)); return r; }
__device__ __forceinline__ float rsqrt_approx(float x) { float r; asm("rsqrt.approx.ftz.f32 %0, %1;" : "=f"(r) : "f"(x)); return r; }
__device__ __forceinline__ float rcp_approx(float x) { float r; asm("rcp.approx.ftz.f32 %0, %1;" : "=f"(r) : "f"(x)); return r; }
__device__ __forceinline__ void mma_bf16(float* d, const uint32_t* a, uint32_t b0, uint32_t b1) {
  asm("mma.sync.aligned.m16n8k16.row.col.f32.bf16.bf16.f32 {%0,%1,%2,%3}, {%4,%5,%6,%7}, {%8,%9}, {%0,%1,%2,%3};"
               : "+f"(d[0]), "+f"(d[1]), "+f"(d[2]), "+f"(d[3]) : "r"(a[0]), "r"(a[1]), "r"(a[2]), "r"(a[3]), "r"(b0), "r"(b1));
}
__device__ __forceinline__ void mma_tf32(float* d, float a0, float a1, float a2, float a3, float b0, float b1) {
  asm("mma.sync.aligned.m16n8k8.row.col.f32.tf32.tf32.f32 {%0,%1,%2,%3}, {%4,%5,%6,%7}, {%8,%9}, {%0,%1,%2,%3};"
               : "+f"(d[0]), "+f"(d[1]), "+f"(d[2]), "+f"(d[3])
               : "r"(__float_as_uint(a0)), "r"(__float_as_uint(a1)), "r"(__float_as_uint(a2)), "r"(__float_as_uint(a3)),
                 "r"(__float_as_uint(b0)), "r"(__float_as_uint(b1)));
}
__device__ __forceinline__ void red_release(unsigned* p) { asm volatile("red.release.gpu.global.add.u32 [%0], 1;" ::"l"(p) : "memory"); }
__device__ __forceinline__ void red_relaxed(unsigned* p) { asm volatile("red.relaxed.gpu.global.add.u32 [%0], 1;" ::"l"(p) : "memory"); }
__device__ __forceinline__ unsigned ld_relaxed(const unsigned* p) { unsigned v; asm volatile("ld.relaxed.gpu.global.u32 %0, [%1];" : "=r"(v) : "l"(p) : "memory"); return v; }
__device__ __forceinline__ void spin_until(const unsigned* p, unsigned target) {
  int it = 0;
  while ((int)(ld_relaxed(p) - target) < 0) {
    if (++it > (1 << 23)) __trap();
  }
}
__device__ __forceinline__ uint4 ldcg128(const void* p) { uint4 v; asm volatile("ld.global.cg.v4.b32 {%0,%1,%2,%3}, [%4];" : "=r"(v.x), "=r"(v.y), "=r"(v.z), "=r"(v.w) : "l"(p) : "memory"); return v; }
__device__ __forceinline__ uint4 ld_tagged(const uint4* p) { uint4 v; asm volatile("ld.relaxed.gpu.global.v4.u32 {%0,%1,%2,%3}, [%4];" : "=r"(v.x), "=r"(v.y), "=r"(v.z), "=r"(v.w) : "l"(p) : "memory"); return v; }
__device__ __forceinline__ void st_tagged(uint4* p, uint32_t a, uint32_t b, uint32_t tag) { asm volatile("st.relaxed.gpu.global.v4.u32 [%0], {%1,%2,%3,%2};" ::"l"(p), "r"(a), "r"(tag), "r"(b) : "memory"); }
__device__ __forceinline__ void st_tagged3(uint4* p, uint32_t a, uint32_t b, uint32_t c, uint32_t tag) { asm volatile("st.relaxed.gpu.global.v4.u32 [%0], {%1,%2,%3,%4};" ::"l"(p), "r"(a), "r"(b), "r"(c), "r"(tag) : "memory"); }
__device__ __forceinline__ uint4 poll_tagged(const uint4* p, uint32_t tag) {
  uint4 v = ld_tagged(p);
  int it = 0;
  while (v.y != tag || v.w != tag) {
    if (++it > (1 << 22)) __trap();
    v = ld_tagged(p);
  }
  return v;
}
__device__ __forceinline__ uint32_t hadd2(uint32_t a, uint32_t b) { uint32_t r; asm("add.rn.bf16x2 %0, %1, %2;" : "=r"(r) : "r"(a), "r"(b)); return r; }
__device__ __forceinline__ uint32_t hmul2(uint32_t a, uint32_t b) { uint32_t r; asm("mul.rn.bf16x2 %0, %1, %2;" : "=r"(r) : "r"(a), "r"(b)); return r; }

__device__ __forceinline__ uint32_t hfma2(uint32_t a, uint32_t b, uint32_t c) { uint32_t r; asm("fma.rn.bf16x2 %0, %1, %2, %3;" : "=r"(r) : "r"(a), "r"(b), "r"(c)); return r; }
__device__ __forceinline__ void sts32(uint32_t a, uint32_t v) { asm volatile("st.shared.u32 [%0], %1;" ::"r"(a), "r"(v) : "memory"); }

template <int N> __device__ __forceinline__ void acc_fence(float* a) {
#pragma unroll
  for (int i = 0; i < N; i++) asm volatile("" : "+f"(a[i]) :: "memory");
}

template<int N,int TB> __device__ __forceinline__ void wgmma_rs(float* d, const uint32_t* a, uint64_t db, int sd);
template<int N,int TA,int TB> __device__ __forceinline__ void wgmma_ss(float* d, uint64_t da, uint64_t db, int sd);
template<> __device__ __forceinline__ void wgmma_rs<64,0>(float* d, const uint32_t* a, uint64_t db, int sd) {
  asm volatile("{\n.reg .pred p;\nsetp.ne.b32 p, %37, 0;\nwgmma.mma_async.sync.aligned.m64n64k16.f32.bf16.bf16 {%0,%1,%2,%3,%4,%5,%6,%7,%8,%9,%10,%11,%12,%13,%14,%15,%16,%17,%18,%19,%20,%21,%22,%23,%24,%25,%26,%27,%28,%29,%30,%31}, {%32,%33,%34,%35}, %36, p, 1, 1, 0;\n}\n"
   : "+f"(d[0]),"+f"(d[1]),"+f"(d[2]),"+f"(d[3]),"+f"(d[4]),"+f"(d[5]),"+f"(d[6]),"+f"(d[7]),"+f"(d[8]),"+f"(d[9]),"+f"(d[10]),"+f"(d[11]),"+f"(d[12]),"+f"(d[13]),"+f"(d[14]),"+f"(d[15]),"+f"(d[16]),"+f"(d[17]),"+f"(d[18]),"+f"(d[19]),"+f"(d[20]),"+f"(d[21]),"+f"(d[22]),"+f"(d[23]),"+f"(d[24]),"+f"(d[25]),"+f"(d[26]),"+f"(d[27]),"+f"(d[28]),"+f"(d[29]),"+f"(d[30]),"+f"(d[31])
   : "r"(a[0]), "r"(a[1]), "r"(a[2]), "r"(a[3]), "l"(db), "r"(sd));
}
template<> __device__ __forceinline__ void wgmma_rs<56,0>(float* d, const uint32_t* a, uint64_t db, int sd) {
  asm volatile("{\n.reg .pred p;\nsetp.ne.b32 p, %33, 0;\nwgmma.mma_async.sync.aligned.m64n56k16.f32.bf16.bf16 {%0,%1,%2,%3,%4,%5,%6,%7,%8,%9,%10,%11,%12,%13,%14,%15,%16,%17,%18,%19,%20,%21,%22,%23,%24,%25,%26,%27}, {%28,%29,%30,%31}, %32, p, 1, 1, 0;\n}\n"
   : "+f"(d[0]),"+f"(d[1]),"+f"(d[2]),"+f"(d[3]),"+f"(d[4]),"+f"(d[5]),"+f"(d[6]),"+f"(d[7]),"+f"(d[8]),"+f"(d[9]),"+f"(d[10]),"+f"(d[11]),"+f"(d[12]),"+f"(d[13]),"+f"(d[14]),"+f"(d[15]),"+f"(d[16]),"+f"(d[17]),"+f"(d[18]),"+f"(d[19]),"+f"(d[20]),"+f"(d[21]),"+f"(d[22]),"+f"(d[23]),"+f"(d[24]),"+f"(d[25]),"+f"(d[26]),"+f"(d[27])
   : "r"(a[0]), "r"(a[1]), "r"(a[2]), "r"(a[3]), "l"(db), "r"(sd));
}
template<> __device__ __forceinline__ void wgmma_rs<48,0>(float* d, const uint32_t* a, uint64_t db, int sd) {
  asm volatile("{\n.reg .pred p;\nsetp.ne.b32 p, %29, 0;\nwgmma.mma_async.sync.aligned.m64n48k16.f32.bf16.bf16 {%0,%1,%2,%3,%4,%5,%6,%7,%8,%9,%10,%11,%12,%13,%14,%15,%16,%17,%18,%19,%20,%21,%22,%23}, {%24,%25,%26,%27}, %28, p, 1, 1, 0;\n}\n"
   : "+f"(d[0]),"+f"(d[1]),"+f"(d[2]),"+f"(d[3]),"+f"(d[4]),"+f"(d[5]),"+f"(d[6]),"+f"(d[7]),"+f"(d[8]),"+f"(d[9]),"+f"(d[10]),"+f"(d[11]),"+f"(d[12]),"+f"(d[13]),"+f"(d[14]),"+f"(d[15]),"+f"(d[16]),"+f"(d[17]),"+f"(d[18]),"+f"(d[19]),"+f"(d[20]),"+f"(d[21]),"+f"(d[22]),"+f"(d[23])
   : "r"(a[0]), "r"(a[1]), "r"(a[2]), "r"(a[3]), "l"(db), "r"(sd));
}
template<> __device__ __forceinline__ void wgmma_rs<40,0>(float* d, const uint32_t* a, uint64_t db, int sd) {
  asm volatile("{\n.reg .pred p;\nsetp.ne.b32 p, %25, 0;\nwgmma.mma_async.sync.aligned.m64n40k16.f32.bf16.bf16 {%0,%1,%2,%3,%4,%5,%6,%7,%8,%9,%10,%11,%12,%13,%14,%15,%16,%17,%18,%19}, {%20,%21,%22,%23}, %24, p, 1, 1, 0;\n}\n"
   : "+f"(d[0]),"+f"(d[1]),"+f"(d[2]),"+f"(d[3]),"+f"(d[4]),"+f"(d[5]),"+f"(d[6]),"+f"(d[7]),"+f"(d[8]),"+f"(d[9]),"+f"(d[10]),"+f"(d[11]),"+f"(d[12]),"+f"(d[13]),"+f"(d[14]),"+f"(d[15]),"+f"(d[16]),"+f"(d[17]),"+f"(d[18]),"+f"(d[19])
   : "r"(a[0]), "r"(a[1]), "r"(a[2]), "r"(a[3]), "l"(db), "r"(sd));
}
template<> __device__ __forceinline__ void wgmma_rs<32,0>(float* d, const uint32_t* a, uint64_t db, int sd) {
  asm volatile("{\n.reg .pred p;\nsetp.ne.b32 p, %21, 0;\nwgmma.mma_async.sync.aligned.m64n32k16.f32.bf16.bf16 {%0,%1,%2,%3,%4,%5,%6,%7,%8,%9,%10,%11,%12,%13,%14,%15}, {%16,%17,%18,%19}, %20, p, 1, 1, 0;\n}\n"
   : "+f"(d[0]),"+f"(d[1]),"+f"(d[2]),"+f"(d[3]),"+f"(d[4]),"+f"(d[5]),"+f"(d[6]),"+f"(d[7]),"+f"(d[8]),"+f"(d[9]),"+f"(d[10]),"+f"(d[11]),"+f"(d[12]),"+f"(d[13]),"+f"(d[14]),"+f"(d[15])
   : "r"(a[0]), "r"(a[1]), "r"(a[2]), "r"(a[3]), "l"(db), "r"(sd));
}
template<> __device__ __forceinline__ void wgmma_rs<24,0>(float* d, const uint32_t* a, uint64_t db, int sd) {
  asm volatile("{\n.reg .pred p;\nsetp.ne.b32 p, %17, 0;\nwgmma.mma_async.sync.aligned.m64n24k16.f32.bf16.bf16 {%0,%1,%2,%3,%4,%5,%6,%7,%8,%9,%10,%11}, {%12,%13,%14,%15}, %16, p, 1, 1, 0;\n}\n"
   : "+f"(d[0]),"+f"(d[1]),"+f"(d[2]),"+f"(d[3]),"+f"(d[4]),"+f"(d[5]),"+f"(d[6]),"+f"(d[7]),"+f"(d[8]),"+f"(d[9]),"+f"(d[10]),"+f"(d[11])
   : "r"(a[0]), "r"(a[1]), "r"(a[2]), "r"(a[3]), "l"(db), "r"(sd));
}
template<> __device__ __forceinline__ void wgmma_rs<16,0>(float* d, const uint32_t* a, uint64_t db, int sd) {
  asm volatile("{\n.reg .pred p;\nsetp.ne.b32 p, %13, 0;\nwgmma.mma_async.sync.aligned.m64n16k16.f32.bf16.bf16 {%0,%1,%2,%3,%4,%5,%6,%7}, {%8,%9,%10,%11}, %12, p, 1, 1, 0;\n}\n"
   : "+f"(d[0]),"+f"(d[1]),"+f"(d[2]),"+f"(d[3]),"+f"(d[4]),"+f"(d[5]),"+f"(d[6]),"+f"(d[7])
   : "r"(a[0]), "r"(a[1]), "r"(a[2]), "r"(a[3]), "l"(db), "r"(sd));
}
template<> __device__ __forceinline__ void wgmma_rs<8,0>(float* d, const uint32_t* a, uint64_t db, int sd) {
  asm volatile("{\n.reg .pred p;\nsetp.ne.b32 p, %9, 0;\nwgmma.mma_async.sync.aligned.m64n8k16.f32.bf16.bf16 {%0,%1,%2,%3}, {%4,%5,%6,%7}, %8, p, 1, 1, 0;\n}\n"
   : "+f"(d[0]),"+f"(d[1]),"+f"(d[2]),"+f"(d[3])
   : "r"(a[0]), "r"(a[1]), "r"(a[2]), "r"(a[3]), "l"(db), "r"(sd));
}
template<> __device__ __forceinline__ void wgmma_ss<16,0,1>(float* d, uint64_t da, uint64_t db, int sd) {
  asm volatile("{\n.reg .pred p;\nsetp.ne.b32 p, %10, 0;\nwgmma.mma_async.sync.aligned.m64n16k16.f32.bf16.bf16 {%0,%1,%2,%3,%4,%5,%6,%7}, %8, %9, p, 1, 1, 0, 1;\n}\n"
   : "+f"(d[0]),"+f"(d[1]),"+f"(d[2]),"+f"(d[3]),"+f"(d[4]),"+f"(d[5]),"+f"(d[6]),"+f"(d[7])
   : "l"(da), "l"(db), "r"(sd));
}
template<> __device__ __forceinline__ void wgmma_ss<64,0,1>(float* d, uint64_t da, uint64_t db, int sd) {
  asm volatile("{\n.reg .pred p;\nsetp.ne.b32 p, %34, 0;\nwgmma.mma_async.sync.aligned.m64n64k16.f32.bf16.bf16 {%0,%1,%2,%3,%4,%5,%6,%7,%8,%9,%10,%11,%12,%13,%14,%15,%16,%17,%18,%19,%20,%21,%22,%23,%24,%25,%26,%27,%28,%29,%30,%31}, %32, %33, p, 1, 1, 0, 1;\n}\n"
   : "+f"(d[0]),"+f"(d[1]),"+f"(d[2]),"+f"(d[3]),"+f"(d[4]),"+f"(d[5]),"+f"(d[6]),"+f"(d[7]),"+f"(d[8]),"+f"(d[9]),"+f"(d[10]),"+f"(d[11]),"+f"(d[12]),"+f"(d[13]),"+f"(d[14]),"+f"(d[15]),"+f"(d[16]),"+f"(d[17]),"+f"(d[18]),"+f"(d[19]),"+f"(d[20]),"+f"(d[21]),"+f"(d[22]),"+f"(d[23]),"+f"(d[24]),"+f"(d[25]),"+f"(d[26]),"+f"(d[27]),"+f"(d[28]),"+f"(d[29]),"+f"(d[30]),"+f"(d[31])
   : "l"(da), "l"(db), "r"(sd));
}
template<> __device__ __forceinline__ void wgmma_ss<192,0,1>(float* d, uint64_t da, uint64_t db, int sd) {
  asm volatile("{\n.reg .pred p;\nsetp.ne.b32 p, %98, 0;\nwgmma.mma_async.sync.aligned.m64n192k16.f32.bf16.bf16 {%0,%1,%2,%3,%4,%5,%6,%7,%8,%9,%10,%11,%12,%13,%14,%15,%16,%17,%18,%19,%20,%21,%22,%23,%24,%25,%26,%27,%28,%29,%30,%31,%32,%33,%34,%35,%36,%37,%38,%39,%40,%41,%42,%43,%44,%45,%46,%47,%48,%49,%50,%51,%52,%53,%54,%55,%56,%57,%58,%59,%60,%61,%62,%63,%64,%65,%66,%67,%68,%69,%70,%71,%72,%73,%74,%75,%76,%77,%78,%79,%80,%81,%82,%83,%84,%85,%86,%87,%88,%89,%90,%91,%92,%93,%94,%95}, %96, %97, p, 1, 1, 0, 1;\n}\n"
   : "+f"(d[0]),"+f"(d[1]),"+f"(d[2]),"+f"(d[3]),"+f"(d[4]),"+f"(d[5]),"+f"(d[6]),"+f"(d[7]),"+f"(d[8]),"+f"(d[9]),"+f"(d[10]),"+f"(d[11]),"+f"(d[12]),"+f"(d[13]),"+f"(d[14]),"+f"(d[15]),"+f"(d[16]),"+f"(d[17]),"+f"(d[18]),"+f"(d[19]),"+f"(d[20]),"+f"(d[21]),"+f"(d[22]),"+f"(d[23]),"+f"(d[24]),"+f"(d[25]),"+f"(d[26]),"+f"(d[27]),"+f"(d[28]),"+f"(d[29]),"+f"(d[30]),"+f"(d[31]),"+f"(d[32]),"+f"(d[33]),"+f"(d[34]),"+f"(d[35]),"+f"(d[36]),"+f"(d[37]),"+f"(d[38]),"+f"(d[39]),"+f"(d[40]),"+f"(d[41]),"+f"(d[42]),"+f"(d[43]),"+f"(d[44]),"+f"(d[45]),"+f"(d[46]),"+f"(d[47]),"+f"(d[48]),"+f"(d[49]),"+f"(d[50]),"+f"(d[51]),"+f"(d[52]),"+f"(d[53]),"+f"(d[54]),"+f"(d[55]),"+f"(d[56]),"+f"(d[57]),"+f"(d[58]),"+f"(d[59]),"+f"(d[60]),"+f"(d[61]),"+f"(d[62]),"+f"(d[63]),"+f"(d[64]),"+f"(d[65]),"+f"(d[66]),"+f"(d[67]),"+f"(d[68]),"+f"(d[69]),"+f"(d[70]),"+f"(d[71]),"+f"(d[72]),"+f"(d[73]),"+f"(d[74]),"+f"(d[75]),"+f"(d[76]),"+f"(d[77]),"+f"(d[78]),"+f"(d[79]),"+f"(d[80]),"+f"(d[81]),"+f"(d[82]),"+f"(d[83]),"+f"(d[84]),"+f"(d[85]),"+f"(d[86]),"+f"(d[87]),"+f"(d[88]),"+f"(d[89]),"+f"(d[90]),"+f"(d[91]),"+f"(d[92]),"+f"(d[93]),"+f"(d[94]),"+f"(d[95])
   : "l"(da), "l"(db), "r"(sd));
}
template<> __device__ __forceinline__ void wgmma_ss<192,1,1>(float* d, uint64_t da, uint64_t db, int sd) {
  asm volatile("{\n.reg .pred p;\nsetp.ne.b32 p, %98, 0;\nwgmma.mma_async.sync.aligned.m64n192k16.f32.bf16.bf16 {%0,%1,%2,%3,%4,%5,%6,%7,%8,%9,%10,%11,%12,%13,%14,%15,%16,%17,%18,%19,%20,%21,%22,%23,%24,%25,%26,%27,%28,%29,%30,%31,%32,%33,%34,%35,%36,%37,%38,%39,%40,%41,%42,%43,%44,%45,%46,%47,%48,%49,%50,%51,%52,%53,%54,%55,%56,%57,%58,%59,%60,%61,%62,%63,%64,%65,%66,%67,%68,%69,%70,%71,%72,%73,%74,%75,%76,%77,%78,%79,%80,%81,%82,%83,%84,%85,%86,%87,%88,%89,%90,%91,%92,%93,%94,%95}, %96, %97, p, 1, 1, 1, 1;\n}\n"
   : "+f"(d[0]),"+f"(d[1]),"+f"(d[2]),"+f"(d[3]),"+f"(d[4]),"+f"(d[5]),"+f"(d[6]),"+f"(d[7]),"+f"(d[8]),"+f"(d[9]),"+f"(d[10]),"+f"(d[11]),"+f"(d[12]),"+f"(d[13]),"+f"(d[14]),"+f"(d[15]),"+f"(d[16]),"+f"(d[17]),"+f"(d[18]),"+f"(d[19]),"+f"(d[20]),"+f"(d[21]),"+f"(d[22]),"+f"(d[23]),"+f"(d[24]),"+f"(d[25]),"+f"(d[26]),"+f"(d[27]),"+f"(d[28]),"+f"(d[29]),"+f"(d[30]),"+f"(d[31]),"+f"(d[32]),"+f"(d[33]),"+f"(d[34]),"+f"(d[35]),"+f"(d[36]),"+f"(d[37]),"+f"(d[38]),"+f"(d[39]),"+f"(d[40]),"+f"(d[41]),"+f"(d[42]),"+f"(d[43]),"+f"(d[44]),"+f"(d[45]),"+f"(d[46]),"+f"(d[47]),"+f"(d[48]),"+f"(d[49]),"+f"(d[50]),"+f"(d[51]),"+f"(d[52]),"+f"(d[53]),"+f"(d[54]),"+f"(d[55]),"+f"(d[56]),"+f"(d[57]),"+f"(d[58]),"+f"(d[59]),"+f"(d[60]),"+f"(d[61]),"+f"(d[62]),"+f"(d[63]),"+f"(d[64]),"+f"(d[65]),"+f"(d[66]),"+f"(d[67]),"+f"(d[68]),"+f"(d[69]),"+f"(d[70]),"+f"(d[71]),"+f"(d[72]),"+f"(d[73]),"+f"(d[74]),"+f"(d[75]),"+f"(d[76]),"+f"(d[77]),"+f"(d[78]),"+f"(d[79]),"+f"(d[80]),"+f"(d[81]),"+f"(d[82]),"+f"(d[83]),"+f"(d[84]),"+f"(d[85]),"+f"(d[86]),"+f"(d[87]),"+f"(d[88]),"+f"(d[89]),"+f"(d[90]),"+f"(d[91]),"+f"(d[92]),"+f"(d[93]),"+f"(d[94]),"+f"(d[95])
   : "l"(da), "l"(db), "r"(sd));
}

template <bool TR>
__device__ __forceinline__ void gemm_section(float* acc, float& mean0, float& mean1, float& rstd0, float& rstd1,
                                             uint32_t sb, int blk, int hg, int wg, int w, int lane) {
  constexpr int layer = TR ? 1 : 0;
  constexpr int TURN = TR ? TURN1 : TURN0;
  constexpr int LSTAT = TURN < 4 ? TURN - 1 : 3;
  const uint32_t bar = sb + SM_BAR;
  const int g = lane >> 2, t = lane & 3;
  const bool leader = (w == 0) && (lane == 0);
  const int statpos = hg < 3 ? 1 : wg ? LSTAT : 2;
  const bool copy = hg >= 3 && wg == 0;
  const int cut = wg ? TURN : 4;
  auto wait_full = [&](int c) {
    mbar_wait(bar + 8 * (B_XF + 8 * wg + c), layer);
    mbar_wait(bar + 8 * (B_WF + c), layer);
  };
  auto peek = [&](int c) {
    const bool x = mbar_test(bar + 8 * (B_XF + 8 * wg + c), layer), y = mbar_test(bar + 8 * (B_WF + c), layer);
    return x && y;
  };
  const uint64_t da0 = mkdesc(sb, TR ? 8192 : 16, 1024, 1), db0 = mkdesc(sb, 8192, 1024, 1);
  uint32_t xt = wg ? 0xfedcba98u : 0x21043210u;
  uint64_t wt = 0x0816131005161310ull;
  uint64_t da = da0 + ((xt & 15) << 9), db = db0 + (16 << 9);
  auto issue = [&](int c, int first) {
    TSG(2 * c);
    wg_fence();
#pragma unroll
    for (int ks = 0; ks < 4; ks++) wgmma_ss<192, TR ? 1 : 0, 1>(acc, da + (TR ? ks * 128 : ks * 2), db + ks * 128, !first || ks != 0);
    wg_commit();
    xt >>= 4; wt >>= 8;
    da = da0 + ((xt & 15) << 9); db = db0 + (((uint32_t)wt & 31) << 9);
    TSG(2 * c + 1);
  };
  uint32_t tag = 0;
  wait_full(0);
  bool ready = peek(1);
  issue(0, 1);
  TSW(0);
#pragma unroll 1
  for (int c = 1; c < cut; c++) {
    if (!ready) wait_full(c);
    issue(c, 0);
    ready = peek(c + 1);
    wg_wait<1>();
    if (leader) mbar_arrive(bar + 8 * (B_DN + 8 * wg + c - 1));
    if (wg == 1 && c == cut - 1) {
      wg_wait<0>();
      if (leader) mbar_arrive(bar + 8 * (B_DN + 8 + c));
    }
    if (c == statpos) {
      mbar_wait(bar + 8 * B_EP, 0);
      tag = 2 * lds32(sb + SM_EP) + layer + 1;
      mbar_wait(bar + 8 * (copy ? B_SC : B_XF + 8 * wg + hg), layer);
      uint32_t A[16];
      const uint32_t xb = sb + (copy ? P_R : 8 * wg + hg) * PG;
#pragma unroll
      for (int ks = 0; ks < 4; ks++) {
        if (!TR) {
          const int row = 16 * w + (lane & 15), kc = 2 * ks + (lane >> 4);
          ldsm4(&A[4 * ks], xb + row * 128 + ((kc ^ (row & 7)) << 4));
        } else {
          const int k = 16 * ks + (lane & 7) + 8 * (lane >> 4), pc = 2 * w + ((lane >> 3) & 1);
          ldsm4t(&A[4 * ks], xb + k * 128 + ((pc ^ (k & 7)) << 4));
        }
      }
      float s0 = 0.f, q0 = 0.f, s1 = 0.f, q1 = 0.f;
#pragma unroll
      for (int i = 0; i < 16; i += 2) {
        const float a = bf_lo(A[i]), b = bf_hi(A[i]), c_ = bf_lo(A[i + 1]), d = bf_hi(A[i + 1]);
        s0 += a + b; q0 = fmaf(a, a, q0); q0 = fmaf(b, b, q0);
        s1 += c_ + d; q1 = fmaf(c_, c_, q1); q1 = fmaf(d, d, q1);
      }
#pragma unroll
      for (int o = 1; o <= 2; o <<= 1) {
        s0 += __shfl_xor_sync(~0u, s0, o); q0 += __shfl_xor_sync(~0u, q0, o);
        s1 += __shfl_xor_sync(~0u, s1, o); q1 += __shfl_xor_sync(~0u, q1, o);
      }
      if (t < 2)
        st_tagged(&g_part[((layer * 32 + blk) * 8 + hg) * 64 + 16 * w + g + 8 * t], __float_as_uint(t ? s1 : s0), __float_as_uint(t ? q1 : q0), tag);
    }
  }
  if (wg == 1) mbar_wait(bar + 8 * (B_DN + GPOS), layer);
  else if (!ready) { wait_full(cut); ready = true; }
  const uint4* psrc = &g_part[((layer * 32 + blk) * 8 + 2 * t) * 64 + 16 * w + g];
  uint4 a0 = ld_tagged(psrc), a1 = ld_tagged(psrc + 8), b0 = ld_tagged(psrc + 64), b1 = ld_tagged(psrc + 72);
  if (wg == 1) {
#pragma unroll 1
    for (int c = cut; c < 8; c++) wait_full(c);
    ready = true;
    bar_sync(5, 256);
  }
#pragma unroll 1
  for (int c = cut; c < 8; c++) {
    if (!ready) wait_full(c);
    issue(c, 0);
    if (wg == 1) {
      wg_wait<2>();
      if (leader && c >= cut + 2) mbar_arrive(bar + 8 * (B_DN + 8 + c - 2));
    } else if (c == 7) {
      bar_arrive(5, 256);
    } else {
      ready = peek(c + 1);
      wg_wait<1>();
      if (leader) mbar_arrive(bar + 8 * (B_DN + c - 1));
    }
  }
  int it = 0;
  while (!__all_sync(~0u, a0.y == tag && a0.w == tag && a1.y == tag && a1.w == tag && b0.y == tag && b0.w == tag && b1.y == tag && b1.w == tag) &&
         ++it < (1 << 20)) {
    a0 = ld_tagged(psrc); a1 = ld_tagged(psrc + 8); b0 = ld_tagged(psrc + 64); b1 = ld_tagged(psrc + 72);
  }
  float s0 = __uint_as_float(a0.x) + __uint_as_float(b0.x), q0 = __uint_as_float(a0.z) + __uint_as_float(b0.z);
  float s1 = __uint_as_float(a1.x) + __uint_as_float(b1.x), q1 = __uint_as_float(a1.z) + __uint_as_float(b1.z);
#pragma unroll
  for (int o = 1; o <= 2; o <<= 1) {
    s0 += __shfl_xor_sync(~0u, s0, o); q0 += __shfl_xor_sync(~0u, q0, o);
    s1 += __shfl_xor_sync(~0u, s1, o); q1 += __shfl_xor_sync(~0u, q1, o);
  }
  mean0 = s0 * (1.f / DM); mean1 = s1 * (1.f / DM);
  rstd0 = rsqrt_approx(fmaxf(q0 * (1.f / DM) - mean0 * mean0, 0.f) + 1e-5f);
  rstd1 = rsqrt_approx(fmaxf(q1 * (1.f / DM) - mean1 * mean1, 0.f) + 1e-5f);
  TSG(16);
  mbar_wait(bar + 8 * (TR ? B_RS : B_CSF), 0);
  wg_wait<0>();
  acc_fence<96>(acc);
  if (leader) mbar_arrive(bar + 8 * (B_DN + 8 * wg + 7));
}

__device__ __forceinline__ void attn_phase(const Params& p, uint32_t sb, int layer, int rb, int hg, int wg, int w) {
  const int lane = opaque_tid() & 31;
  const int g = lane >> 2, t = lane & 3;
  const uint32_t bar = sb + SM_BAR;
  const int blk = 16 * wg + rb;
  float acc[96];
  float2 cs[24];
  float mean0, mean1, rstd0, rstd1;
  if (layer) gemm_section<true>(acc, mean0, mean1, rstd0, rstd1, sb, blk, hg, wg, w, lane);
  else gemm_section<false>(acc, mean0, mean1, rstd0, rstd1, sb, blk, hg, wg, w, lane);
  TSW(1);
#pragma unroll
  for (int j = 8; j < 24; j++) cs[j] = lds64f(sb + SM_CS + 4 * (8 * j + 2 * t));
  const uint32_t kvx = sb + (wg ? 22 : 0) * PG;

  uint32_t kb[4][8], vb[4][8], qa[4][4];
  {
    const float nm0 = -mean0 * rstd0, nm1 = -mean1 * rstd1;
    const int st_row = 16 * w + (lane & 7) + 8 * ((lane >> 3) & 1);
    const uint32_t st_base = kvx + st_row * 256;
    const bool sender = (w == 3 && blk < 31);
    uint4* halo = &g_halo[((layer * 32 + blk) * 8 + hg) * 256 + lane];
    uint32_t r[4][2][4];
#pragma unroll
    for (int h = 0; h < 4; h++) {
#pragma unroll
      for (int kv = 0; kv < 2; kv++) {
#pragma unroll
        for (int dh = 0; dh < 2; dh++) {
          const int j = 8 + kv * 8 + 2 * h + dh;
          const float2 c2 = cs[j];
          const float v0 = fmaf(acc[4 * j + 0], rstd0, nm0 * c2.x), v1 = fmaf(acc[4 * j + 1], rstd0, nm0 * c2.y);
          const float v2 = fmaf(acc[4 * j + 2], rstd1, nm1 * c2.x), v3 = fmaf(acc[4 * j + 3], rstd1, nm1 * c2.y);
          r[h][kv][2 * dh] = packbf(v0, v1);
          r[h][kv][2 * dh + 1] = packbf(v2, v3);
        }
      }
      if (sender) {
        stg128(halo + (2 * h) * 32, make_uint4(r[h][0][0], r[h][0][2], r[h][0][1], r[h][0][3]));
        stg128(halo + (2 * h + 1) * 32, make_uint4(r[h][1][0], r[h][1][1], r[h][1][2], r[h][1][3]));
      }
    }
#pragma unroll
    for (int j = 0; j < 8; j++) cs[j] = lds64f(sb + SM_CS + 4 * (8 * j + 2 * t));
    mbar_wait(bar + 8 * (B_DN + 7), layer);
#pragma unroll
    for (int h = 0; h < 4; h++) {
#pragma unroll
      for (int kv = 0; kv < 2; kv++) {
        const int chunk = 4 * h + 2 * kv + (lane >> 4);
        stsm4(st_base + (((chunk & 8) | ((chunk ^ st_row) & 7)) << 4), r[h][kv][0], r[h][kv][1], r[h][kv][2], r[h][kv][3]);
      }
      kb[h][4] = r[h][0][0]; kb[h][5] = r[h][0][2]; kb[h][6] = r[h][0][1]; kb[h][7] = r[h][0][3];
      vb[h][4] = movm_t(r[h][1][0]); vb[h][5] = movm_t(r[h][1][1]); vb[h][6] = movm_t(r[h][1][2]); vb[h][7] = movm_t(r[h][1][3]);
    }
#pragma unroll
    for (int h = 0; h < 4; h++) {
#pragma unroll
      for (int dh = 0; dh < 2; dh++) {
        const int j = 2 * h + dh;
        const float2 c2 = cs[j];
        qa[h][2 * dh] = packbf(fmaf(-mean0, c2.x, acc[4 * j + 0]), fmaf(-mean0, c2.y, acc[4 * j + 1]));
        qa[h][2 * dh + 1] = packbf(fmaf(-mean1, c2.x, acc[4 * j + 2]), fmaf(-mean1, c2.y, acc[4 * j + 3]));
      }
    }
  }
  bar_sync(2 + wg, 128);
  TSW(2);
  {
    const uint32_t prev_base = kvx + (16 * w - 16) * 256;
    const int mi = lane >> 3;
    const int r = 8 * (mi >> 1) + (lane & 7), r2 = 8 * (mi & 1) + (lane & 7);
    if (w != 0) {
#pragma unroll
      for (int h = 0; h < 4; h++) {
        const int ch = 4 * h + (mi & 1), ch2 = 4 * h + 2 + (mi >> 1);
        ldsm4(&kb[h][0], prev_base + r * 256 + (((ch & 8) | ((ch ^ r) & 7)) << 4));
        ldsm4t(&vb[h][0], prev_base + r2 * 256 + (((ch2 & 8) | ((ch2 ^ r2) & 7)) << 4));
      }
    } else if (blk > 0) {
      const uint4* src = &g_halo[((layer * 32 + blk - 1) * 8 + hg) * 256 + lane];
      uint4 hv[8];
      int it = 0;
      bool ok;
      do {
        ok = true;
#pragma unroll
        for (int i = 0; i < 8; i++) hv[i] = ld_tagged(src + i * 32);
#pragma unroll
        for (int i = 0; i < 8; i++) ok = ok && hv[i].x != UNSET;
      } while (!__all_sync(~0u, ok) && ++it < (1 << 20));
#pragma unroll
      for (int h = 0; h < 4; h++) {
        kb[h][0] = hv[2 * h].x; kb[h][1] = hv[2 * h].y; kb[h][2] = hv[2 * h].z; kb[h][3] = hv[2 * h].w;
        vb[h][0] = movm_t(hv[2 * h + 1].x); vb[h][1] = movm_t(hv[2 * h + 1].y);
        vb[h][2] = movm_t(hv[2 * h + 1].z); vb[h][3] = movm_t(hv[2 * h + 1].w);
      }
    } else {
#pragma unroll
      for (int h = 0; h < 4; h++)
#pragma unroll
        for (int k = 0; k < 4; k++) kb[h][k] = vb[h][k] = 0u;
    }
    TSW(3);
  }
  mbar_wait(bar + 8 * (B_DN + 15), layer);
  TSW(4);

  const bool first = (blk == 0 && w == 0);
  const int e = t - (g >> 1);
  const bool par = g & 1, epos = e >= 1;
  const uint32_t pmask = par ? 0xffff0000u : 0x0000ffffu;
  const uint32_t mB0 = epos ? pmask : 0u, mB1 = epos ? 0u : pmask;
  const float cl2 = 0.25f * 1.4426950408889634f;
  const float sc0 = rstd0 * cl2, sc1 = rstd1 * cl2;
  const float NEG = -INFINITY;
  float vA0[4], vB0[4], vA1[4], vB1[4];
#pragma unroll
  for (int h = 0; h < 4; h++) {
    float S[4][4];
#pragma unroll
    for (int j = 0; j < 4; j++) {
      S[j][0] = S[j][1] = S[j][2] = S[j][3] = 0.f;
      mma_bf16(S[j], qa[h], kb[h][2 * j], kb[h][2 * j + 1]);
    }
    vA0[h] = par ? S[1][1] : S[1][0];
    vB0[h] = epos ? (par ? S[0][1] : S[0][0]) : (par ? S[2][1] : S[2][0]);
    vA1[h] = par ? S[2][3] : S[2][2];
    vB1[h] = epos ? (par ? S[1][3] : S[1][2]) : (par ? S[3][3] : S[3][2]);
    if (first) { vA0[h] = NEG; if (epos) { vB0[h] = NEG; vB1[h] = NEG; } }
  }
  float m0[4], m1[4];
#pragma unroll
  for (int h = 0; h < 4; h++) { m0[h] = fmaxf(vA0[h], vB0[h]); m1[h] = fmaxf(vA1[h], vB1[h]); }
#pragma unroll
  for (int o = 1; o <= 2; o <<= 1) {
#pragma unroll
    for (int h = 0; h < 4; h++) {
      m0[h] = fmaxf(m0[h], __shfl_xor_sync(~0u, m0[h], o));
      m1[h] = fmaxf(m1[h], __shfl_xor_sync(~0u, m1[h], o));
    }
  }
  float O0[4][4], O1[4][4], Z[4][4];
#pragma unroll
  for (int h = 0; h < 4; h++) {
    const float mm0 = -m0[h] * sc0, mm1 = -m1[h] * sc1;
    const float pA0 = ex2(fmaf(vA0[h], sc0, mm0)), pB0 = ex2(fmaf(vB0[h], sc0, mm0));
    const float pA1 = ex2(fmaf(vA1[h], sc1, mm1)), pB1 = ex2(fmaf(vB1[h], sc1, mm1));
    const uint32_t hA0 = packbf(pA0, pA0), hB0 = packbf(pB0, pB0), hA1 = packbf(pA1, pA1), hB1 = packbf(pB1, pB1);
    const uint32_t P0[4] = {hB0 & mB0, 0u, hA0 & pmask, hB1 & mB0};
    const uint32_t P1[4] = {hB0 & mB1, hA1 & pmask, 0u, hB1 & mB1};
#pragma unroll
    for (int k = 0; k < 4; k++) O0[h][k] = O1[h][k] = Z[h][k] = 0.f;
    mma_bf16(O0[h], P0, vb[h][0], vb[h][1]); mma_bf16(O1[h], P0, vb[h][2], vb[h][3]); mma_bf16(Z[h], P0, 0x3f803f80u, 0x3f803f80u);
    mma_bf16(O0[h], P1, vb[h][4], vb[h][5]); mma_bf16(O1[h], P1, vb[h][6], vb[h][7]); mma_bf16(Z[h], P1, 0x3f803f80u, 0x3f803f80u);
  }
  if (lane == 0) mbar_arrive(bar + 8 * (B_OST + wg));
  uint4* op = (uint4*)g_O + ((layer * 32 + blk) * 8 + hg) * 512 + 64 * t + 16 * w + g;
#pragma unroll
  for (int h = 0; h < 4; h += 2) {
    const float i0 = rcp_approx(Z[h][0]), i1 = rcp_approx(Z[h][2]), j0 = rcp_approx(Z[h + 1][0]), j1 = rcp_approx(Z[h + 1][2]);
    stg128(op + 128 * h, make_uint4(packbf(O0[h][0] * i0, O0[h][1] * i0), packbf(O1[h][0] * i0, O1[h][1] * i0),
                                   packbf(O0[h + 1][0] * j0, O0[h + 1][1] * j0), packbf(O1[h + 1][0] * j0, O1[h + 1][1] * j0)));
    stg128(op + 128 * h + 8, make_uint4(packbf(O0[h][2] * i1, O0[h][3] * i1), packbf(O1[h][2] * i1, O1[h][3] * i1),
                                            packbf(O0[h + 1][2] * j1, O0[h + 1][3] * j1), packbf(O1[h + 1][2] * j1, O1[h + 1][3] * j1)));
  }
  TSW(5);
  __syncwarp();
  if (lane == 0) red_relaxed(&g_cnt[(C_O + layer * 32 + blk) * 32]);
  TSW(6);
}

#define PGATE 1
__device__ __forceinline__ void proj_phase(const Params& p, uint32_t sb, int layer, int rb, int q, int wg, int w, int& rtp) {
  const int lane = opaque_tid() & 31;
  const bool TR = layer != 0;
  const int t = lane & 3;
  const uint32_t bar = sb + SM_BAR;
  const uint32_t rbx = sb + (P_R + wg) * PG;
  const uint32_t rsrc = sb + (wg ? 2 : P_R) * PG;
  const int blk = 16 * wg + rb;
  uint32_t res[16];
  mbar_wait(bar + 8 * (B_RF + wg), layer);
  if (!TR) {
#pragma unroll
    for (int j = 0; j < 8; j += 2) {
      const int mi = lane >> 3;
      const int row = 16 * w + (lane & 7) + 8 * (mi & 1), ch = j + (mi >> 1);
      ldsm4(&res[2 * j], rsrc + row * 128 + ((ch ^ (row & 7)) << 4));
    }
  } else {
#pragma unroll
    for (int j = 0; j < 8; j += 2) {
      const int mi = lane >> 3;
      const int line = 8 * (j + (mi >> 1)) + (lane & 7), pc = 2 * w + (mi & 1);
      ldsm4t(&res[2 * j], rsrc + line * 128 + ((pc ^ (line & 7)) << 4));
    }
  }
  if (layer) mbar_wait(bar + 8 * (B_RS + 1), 0);
  fence_async_global();
  const uint32_t stg = sb + (wg ? SM_KGT : SM_STG);
  if (wg) mbar_wait(bar + 8 * B_PST, layer);
  bool clean = false;
#pragma unroll 1
  for (int attempt = 0; attempt < MAX_RETRY; attempt++) {
  float acc[32];
#pragma unroll
  for (int j = 0; j < 16; j++) { acc[2 * j] = bf_lo(res[j]); acc[2 * j + 1] = bf_hi(res[j]); }
  acc_fence<32>(acc);
#pragma unroll
  for (int c = 0; c < 4; c++) {
    mbar_wait(bar + 8 * (B_WOF + c), layer);
    mbar_wait(bar + 8 * (B_OF + 4 * wg + c), layer);
    if (c == 0) TSW(7);
    const uint64_t da = mkdesc(sb + o_page(wg, c) * PG, 1024, 128, 0);
    wg_fence();
#pragma unroll
    for (int ks = 0; ks < 8; ks++)
      wgmma_ss<64, 0, 1>(acc, da + ks * 128, mkdesc(sb + wo_page(2 * c + (ks >> 2)) * PG, 8192, 1024, 1) + (ks & 3) * 128, 1);
    wg_commit();
  }
  if (wg) mbar_wait(bar + 8 * B_KG, 0);
  wg_wait<0>();
  acc_fence<32>(acc);
  TSW(8);
  if (!clean) {
    const float chk = acc[0] + acc[2];
    clean = __all_sync(~0u, chk == chk);
    if (clean && lane == 0) mbar_arrive(bar + 8 * (B_PDONE + wg));
  }
  float s0 = 0.f, q0 = 0.f, s1 = 0.f, q1 = 0.f;
  uint32_t o[16];
#pragma unroll
  for (int j = 0; j < 8; j++) {
    const float a = acc[4 * j], b = acc[4 * j + 1], c = acc[4 * j + 2], d = acc[4 * j + 3];
    o[2 * j] = packbf(a, b);
    o[2 * j + 1] = packbf(c, d);
    s0 += a + b; q0 = fmaf(a, a, q0); q0 = fmaf(b, b, q0);
    s1 += c + d; q1 = fmaf(c, c, q1); q1 = fmaf(d, d, q1);
  }
#pragma unroll
  for (int j = 0; j < 8; j += 2) {
    const int mi = lane >> 3;
    const int line = 8 * (j + (mi >> 1)) + (lane & 7), pc = 2 * w + (mi & 1);
    stsm4t(rbx + line * 128 + ((pc ^ (line & 7)) << 4), o[2 * j], o[2 * j + 1], o[2 * j + 2], o[2 * j + 3]);
  }
#pragma unroll
  for (int o2 = 1; o2 <= 2; o2 <<= 1) {
    s0 += __shfl_xor_sync(~0u, s0, o2); q0 += __shfl_xor_sync(~0u, q0, o2);
    s1 += __shfl_xor_sync(~0u, s1, o2); q1 += __shfl_xor_sync(~0u, q1, o2);
  }
  {
    const int i = 2 * (lane >> 2) + (t & 1), k = (i * 11) >> 5;
    const float v = (t == 0) ? s0 : (t == 1) ? q0 : (t == 2) ? s1 : q1;
    sts32f(stg + k * 128 + (2 * w + (t >> 1)) * 16 + (i - 3 * k) * 4, v);
  }
  TSW(9);
  fence_async_smem();
  if (!bar_or(2 + wg, 128, !clean)) break;
  bool unset = false;
#pragma unroll
  for (int i = 0; i < 4; i++) unset |= lds32(sb + o_page(wg, i) * PG + (32 * w + lane) * 128) == UNSET;
  if (!bar_or(2 + wg, 128, unset)) break;
  if (w == 0 && elect_one()) {
    fence_async_smem();
    mbar_expect(bar + 8 * (B_RT + wg), 8 * PG);
#pragma unroll 1
    for (int c = 0; c < 4; c++) bulk_ld(sb + o_page(wg, c) * PG, g_O + ((layer * 32 + blk) * 4 + c) * PG, 2 * PG, bar + 8 * (B_RT + wg));
  }
  mbar_wait(bar + 8 * (B_RT + wg), rtp);
  rtp ^= 1;
  RETRY(0);
  }
  if (!clean && lane == 0) mbar_arrive(bar + 8 * (B_PDONE + wg));
  if (w == 0 && lane == 0) {
    tma_st(&p.mapXT, blk * 64, (2 * layer) * DM + q * 64, rbx);
    bulk_red_add_f32(g_stats + (layer * 32 + blk) * 192, stg, 768);
    bulk_commit();
    red_relaxed(&g_cnt[(C_G + 2 * layer + wg) * 32]);
  }
  TSW(10);
}

__device__ __forceinline__ void conv_load(uint32_t* A, uint32_t pe) {
#pragma unroll
  for (int m = 0; m < 17; m++) {
    A[4 * m + 2] = lds32(pe + 4 * (64 * m - 8));
    A[4 * m + 0] = lds32(pe + 4 * (64 * m));
    A[4 * m + 1] = lds32(pe + 4 * (64 * m + 8));
    asm volatile("mov.b32 %0, %1;" : "=r"(A[4 * m + 3]) : "r"(A[4 * m + 0]));
  }
}
template <int M> __device__ __forceinline__ void conv_tri(float* acc, const uint32_t* A, uint64_t d) {
  if constexpr (M < 16) {
    wgmma_rs<64 - 8 * (M / 2), 0>(acc, A + 4 * M, d + (uint64_t)(64 + 4 * M), M != 0);
    conv_tri<M + 1>(acc, A, d);
  }
}
__device__ __forceinline__ void conv_mma0(float* acc, const uint32_t* A, uint64_t d) {
  wg_fence();
  conv_tri<0>(acc, A, d);
  wg_commit();
}
__device__ __forceinline__ void conv_mma1(float* acc, const uint32_t* A, uint64_t d) {
  wg_fence();
#pragma unroll
  for (int m = 0; m < 17; m++) wgmma_rs<64, 0>(acc, A + 4 * m, d + (uint64_t)(4 * m), m != 0);
  wg_commit();
}
__device__ __forceinline__ void conv_store(float* acc, uint32_t pb, uint32_t over, int w) {
  acc_fence<32>(acc);
  const int l = opaque_tid() & 31, mt = l >> 3;
  int c = 2 * (63 - 8 * (mt >> 1) - (l & 7) + w) + (mt & 1);
  c ^= (c >> 3) & 1;
  const uint32_t a0 = pb + c * 16;
#pragma unroll
  for (int j = 0; j < 8; j += 2)
    stsm4t(j == 0 ? (c < 128 ? a0 : over + (c - 128) * 16) : a0 - 256 * j, packbf(acc[4 * j], acc[4 * j + 1]), packbf(acc[4 * j + 2], acc[4 * j + 3]),
           packbf(acc[4 * j + 4], acc[4 * j + 5]), packbf(acc[4 * j + 6], acc[4 * j + 7]));
}
#define FARG 1
__device__ __forceinline__ void conv_far(uint32_t sb, int ht) {
  const int w = ht >> 5, l = ht & 31;
  float F[4][8];
  const uint64_t da = mkdesc(sb + cv_fa(0), 128, 128, 0), ds = mkdesc(sb + cv_se(0), 256, 256, 3);
#pragma unroll
  for (int k = 0; k < 8; k++) {
    if (k % FARG == 0) { if (k) wg_wait<0>(); wg_fence(); }
#pragma unroll
    for (int c = 0; c < 4; c++) wgmma_ss<16, 0, 1>(F[c], da + c * 1024 + (k >> 2) * 128 + (k & 3) * 16, ds + c * 256 + 32 * k, k != 0);
    if (k % FARG == FARG - 1) wg_commit();
  }
  const uint32_t pf = sb + cv_pf(0) + (16 * w + (l & 15)) * 32 + (l >> 4) * 16;
  wg_wait<0>();
#pragma unroll
  for (int c = 0; c < 4; c++) {
    acc_fence<8>(F[c]);
    stsm4(pf + c * 2048, packbf(F[c][0], F[c][1]), packbf(F[c][2], F[c][3]), packbf(F[c][4], F[c][5]), packbf(F[c][6], F[c][7]));
  }
}
__device__ __forceinline__ void conv_sums(uint32_t sb, int lc, int ht) {
  const int m = ht - 1;
  uint4 v[2][3];
#pragma unroll
  for (int c = 0; c < 2; c++)
#pragma unroll
    for (int k = 0; k < 3; k++) {
      const int mm = m - 1 + k;
      v[c][k] = lds128(sb + cv_u(lc + c) + (mm >= 0 ? (mm & 1) * CV_UH + (127 - (mm >> 1)) * 16 : 128 * 16));
    }
  const int ce = m + 2, co = m + 1;
#pragma unroll
  for (int c = 0; c < 2; c++) {
    const uint32_t x[8] = {v[c][0].z, v[c][0].w, v[c][1].x, v[c][1].y, v[c][1].z, v[c][1].w, v[c][2].x, v[c][2].y};
    float pv[16];
#pragma unroll
    for (int k = 0; k < 8; k++) { pv[2 * k] = bf_lo(x[k]); pv[2 * k + 1] = bf_hi(x[k]); }
    float t2[15], t4[13], s9[8], s7[8];
#pragma unroll
    for (int i = 0; i < 15; i++) t2[i] = pv[i] + pv[i + 1];
#pragma unroll
    for (int i = 0; i < 13; i++) t4[i] = t2[i] + t2[i + 2];
#pragma unroll
    for (int i = 0; i < 8; i++) {
      s9[i] = (t4[i] + t4[i + 4]) + pv[i + 8];
      s7[i] = (t4[i + 1] + t2[i + 5]) + pv[i + 7];
    }
    const uint4 e4 = make_uint4(packbf(s9[0], s9[1]), packbf(s9[2], s9[3]), packbf(s9[4], s9[5]), packbf(s9[6], s9[7]));
    if (ce < 128) sts128(sb + cv_se(lc + c) + (63 - (ce >> 1)) * 32 + (((ce & 1) ^ ((ce >> 3) & 1) ^ 1) << 4), e4);
    else sts128(sb + cv_se(lc + c) + 63 * 32 + 16, make_uint4(0, 0, 0, 0));
    sts128(sb + cv_so(lc + c) + (63 - (co >> 1)) * 32 + (((co & 1) ^ ((co >> 3) & 1) ^ 1) << 4),
           make_uint4(packbf(s7[0], s7[1]), packbf(s7[2], s7[3]), packbf(s7[4], s7[5]), packbf(s7[6], s7[7])));
  }
}

template <int HALF, int NCH, int STEP = 1>
__device__ __forceinline__ void conv_epi(uint32_t sb, bf16* out, int lc, int c) {
  uint4 v[NCH][4], xr[NCH], f[NCH];
  const uint32_t sw = (c ^ ((c >> 3) & 1)) * 16;
#pragma unroll
  for (int u = 0; u < NCH; u++) {
#pragma unroll
    for (int k = 0; k < 4; k++) v[u][k] = lds128(sb + (HALF ? cv_pb1(lc + STEP * u, k) : cv_pb0(lc + STEP * u, k)) + sw);
    xr[u] = lds128(sb + cv_x(HALF, lc + STEP * u) + c * 16);
    if (HALF) f[u] = lds128(sb + cv_pf(lc + STEP * u) + c * 16);
  }
#pragma unroll
  for (int u = 0; u < NCH; u++) {
    if (HALF) { v[u][0].x = hadd2(v[u][0].x, f[u].x); v[u][0].y = hadd2(v[u][0].y, f[u].y); v[u][0].z = hadd2(v[u][0].z, f[u].z); v[u][0].w = hadd2(v[u][0].w, f[u].w); }
    uint4 o;
    o.x = hadd2(xr[u].x, hadd2(hadd2(v[u][0].x, v[u][1].x), hadd2(v[u][2].x, v[u][3].x)));
    o.y = hadd2(xr[u].y, hadd2(hadd2(v[u][0].y, v[u][1].y), hadd2(v[u][2].y, v[u][3].y)));
    o.z = hadd2(xr[u].z, hadd2(hadd2(v[u][0].z, v[u][1].z), hadd2(v[u][2].z, v[u][3].z)));
    o.w = hadd2(xr[u].w, hadd2(hadd2(v[u][0].w, v[u][1].w), hadd2(v[u][2].w, v[u][3].w)));
    stg128(out + cv_chan(0, lc + STEP * u) * LSEQ + HALF * 1024 + c * 8, o);
  }
}

__device__ __forceinline__ bool prep_valid(const uint4 (&st)[6], const uint4 (&xr)[4]) {
  const uint32_t n = __float_as_uint(8.f);
  return st[0].w == n && st[1].w == n && st[2].w == n && st[3].w == n && st[4].w == n && (st[5].w | st[5].y | st[5].z) == n &&
         xr[0].x != UNSET && xr[1].x != UNSET && xr[2].x != UNSET && xr[3].x != UNSET;
}
template <int HALF, typename F>
__device__ __forceinline__ void conv_prep(uint32_t sb, int layer, int cta, int i, F meanwhile) {
  uint4 st[6], xr[4];
  const uint4* sp = (const uint4*)g_stats + (layer * 32 + HALF * 16 + (i >> 3)) * 48 + (i & 7);
  const uint4* xp = (const uint4*)g_xT + (2 * layer * DM + 2 * cta) * (LSEQ / 8) + HALF * 128 + i;
  auto fetch = [&]() {
#pragma unroll
    for (int k = 0; k < 6; k++) st[k] = ld_tagged(sp + 8 * k);
#pragma unroll
    for (int k = 0; k < 4; k++) xr[k] = ld_tagged(xp + cv_chan(0, k) * (LSEQ / 8));
  };
  if (HALF) {
#pragma unroll
    for (int k = 0; k < 6; k++) st[k] = lds128(sb + CV_ST + (i >> 3) * 768 + k * 128 + (i & 7) * 16);
#pragma unroll
    for (int k = 0; k < 4; k++) xr[k] = lds128(sb + cv_x(1, k) + i * 16);
  } else {
    fetch();
  }
  meanwhile();
  int it = 0;
  while (!__all_sync(~0u, prep_valid(st, xr)) && ++it < MAX_RETRY) { fetch(); RETRY(1); }
  if (!HALF || it) {
#pragma unroll
    for (int k = 0; k < 4; k++) sts128(sb + cv_x(HALF, k) + i * 16, xr[k]);
  }
  const uint32_t v[16] = {st[0].x, st[0].y, st[0].z, st[1].x, st[1].y, st[1].z, st[2].x, st[2].y, st[2].z, st[3].x, st[3].y, st[3].z, st[4].x, st[4].y, st[4].z, st[5].x};
  uint32_t rs[4], nm[4];
#pragma unroll
  for (int k = 0; k < 4; k++) {
    const float m0 = __uint_as_float(v[4 * k]) * (-1.f / DM), m1 = __uint_as_float(v[4 * k + 2]) * (-1.f / DM);
    const float r0 = rsqrt_approx(fmaxf(fmaf(__uint_as_float(v[4 * k + 1]), 1.f / DM, -m0 * m0), 0.f) + 1e-5f);
    const float r1 = rsqrt_approx(fmaxf(fmaf(__uint_as_float(v[4 * k + 3]), 1.f / DM, -m1 * m1), 0.f) + 1e-5f);
    rs[k] = packbf(r0, r1);
    nm[k] = packbf(m0 * bf_lo(rs[k]), m1 * bf_hi(rs[k]));
  }
  const uint32_t ud = sb + (i & 1) * CV_UH + (127 - 64 * HALF - (i >> 1)) * 16;
#pragma unroll
  for (int k = 0; k < 4; k++)
    sts128(ud + cv_u(k), make_uint4(hfma2(xr[k].x, rs[0], nm[0]), hfma2(xr[k].y, rs[1], nm[1]), hfma2(xr[k].z, rs[2], nm[2]), hfma2(xr[k].w, rs[3], nm[3])));
  fence_async_smem();
}

#define ALATE 2
#define PP0 1
__device__ __forceinline__ void conv_phase(const Params& p, uint32_t sb, int layer, int cta) {
  const int tid = opaque_tid();
  const int wg = __shfl_sync(~0u, tid >> 7, 0), w = __shfl_sync(~0u, (tid >> 5) & 3, 0);
  const uint32_t bar = sb + SM_BAR;
  constexpr int CH2 = 4 * PG;
  bf16* xout = g_xT + ((2 * layer + 1) * DM + 2 * cta) * LSEQ;
  uint32_t A0[68], A1[68];
  float acc[32];
  const uint32_t pe = sb + cv_pe(wg) + 4 * (16 + 16 * w + ((tid & 31) >> 2) - 2 * (tid & 3));
  auto staged = [&]() {
    if ((tid & 127) == 0) { bulk_wait_read(); mbar_arrive(bar + 8 * (B_PST + wg)); }
    __syncwarp();
  };
  if (layer) mbar_wait(bar + 8 * (B_RS + 2), 0);
  if (wg == 0) {
    staged();
    if (tid < 32) sts128(sb + cv_u(tid >> 3) + ((tid >> 2) & 1) * CV_UH + (128 + (tid & 3)) * 16, make_uint4(0, 0, 0, 0));
    mbar_wait(bar + 8 * B_PE, layer);
    TSW(19);
    mbar_wait(bar + 8 * B_GB, layer);
    TSW(11);
    conv_prep<0>(sb, layer, cta, tid, [&]() {
      conv_load(A0, pe);
      conv_load(A1, pe + CH2);
    });
    mbar_arrive(bar + 8 * B_U);
  } else {
    mbar_wait(bar + 8 * B_PE, layer);
    conv_load(A0, pe);
    staged();
    conv_load(A1, pe + CH2);
    TSW(19);
  }
  const uint64_t d0 = mkdesc(sb + cv_u(wg), CV_UH, 128, 0), d1 = d0 + (CH2 >> 4);
  mbar_wait(bar + 8 * B_U, layer);
  TSW(12);
  if (wg == 1) bar_sync(5, 256);
  conv_mma0(acc, A0, d0);
  if (wg == 0) bar_arrive(5, 256);
  mbar_wait(bar + 8 * (B_PDONE + 1), layer);
  {
    const int l = opaque_tid() & 31;
    if ((l & 15) < 2 * w) sts128(sb + cv_pb0(wg + 2 * (l >> 4), w) + (l & 15) * 16, make_uint4(0, 0, 0, 0));
  }
  wg_wait<0>();
  conv_store(acc, sb + cv_pb0(wg, w), sb + cv_pb1(wg, w), w);
  conv_mma0(acc, A1, d1);
  bar_sync(2 + wg, 128);
  conv_epi<0, 1>(sb, xout, wg, opaque_tid() & 127);
  wg_wait<0>();
  conv_store(acc, sb + cv_pb0(2 + wg, w), sb + cv_pb1(2 + wg, w), w);
  TSW(13);
  bar_sync(2 + wg, 128);
  conv_epi<0, 1>(sb, xout, 2 + wg, opaque_tid() & 127);
  mbar_arrive(bar + 8 * B_PUB);
  TSW(14);
  mbar_wait(bar + 8 * (B_GB + 1), layer);
  if (wg == 0) {
    conv_prep<1>(sb, layer, cta, opaque_tid(), []() {});
    bar_sync(2, 128);
    if (w == 0 && elect_one()) mbar_arrive(bar + 8 * B_U1);
  } else {
    bar_sync(6, 256);
  }
  TSW(15);
  conv_mma1(acc, A0, d0);
  if (wg == 0) bar_arrive(6, 256);
  mbar_wait(bar + 8 * B_FARM, layer);
  wg_wait<0>();
  conv_store(acc, sb + cv_pb1(wg, w), sb + cv_dump(wg), w);
  mbar_arrive(bar + 8 * (B_R + 1));
  TSW(16);
  conv_mma1(acc, A1, d1);
  wg_wait<0>();
  conv_store(acc, sb + cv_pb1(2 + wg, w), sb + cv_dump(2 + wg), w);
  TSW(17);
  if (wg == 0) {
    mbar_arrive(bar + 8 * (B_R + 2));
  } else {
    bar_sync(3, 128);
    conv_epi<1, 1>(sb, xout, 3, opaque_tid() & 127);
    mbar_arrive(bar + 8 * (B_PUB + 2));
    TSW(18);
  }
}

__device__ __forceinline__ void final_phase(const Params& p, uint32_t sb, int cta, int wg, int w, int rtp) {
  const int lane = opaque_tid() & 31;
  const uint32_t bar = sb + SM_BAR;
  mbar_wait(bar + 8 * (B_TF + wg), 0);
  if (threadIdx.x == 128) TS(8);
  const uint32_t src = sb + (16 + wg) * PG, dst = src + 2 * PG;
  const int mi = lane >> 3;
#pragma unroll 1
  for (int attempt = 0; attempt < MAX_RETRY; attempt++) {
    uint32_t m = 0;
#pragma unroll
    for (int j = 0; j < 8; j += 2) {
      uint32_t r[4];
      const int line = 8 * (j + (mi >> 1)) + (lane & 7), pc = 2 * w + (mi & 1);
      ldsm4t(r, src + line * 128 + ((pc ^ (line & 7)) << 4));
      const int row = 16 * w + (lane & 7) + 8 * (mi & 1), ch = j + (mi >> 1);
      stsm4(dst + row * 128 + ((ch ^ (row & 7)) << 4), r[0], r[1], r[2], r[3]);
#pragma unroll
      for (int k = 0; k < 4; k++) asm("max.u16x2 %0, %0, %1;" : "+r"(m) : "r"(r[k]));
    }
    fence_async_smem();
    if (!bar_or(2 + wg, 128, m >= 0xffff0000u || (m & 0xffffu) == 0xffffu)) break;
    if (w == 0 && elect_one()) {
      mbar_expect(bar + 8 * (B_RT + wg), PG);
      tma_ld(src, &p.mapXT, (16 * wg + (cta & 15)) * 64, 3 * DM + (cta >> 4) * 64, bar + 8 * (B_RT + wg));
    }
    mbar_wait(bar + 8 * (B_RT + wg), (rtp + attempt) & 1);
    RETRY(2);
  }
  if (w == 0 && elect_one()) {
    tma_st(&p.mapOut, (cta >> 4) * 64, (16 * wg + (cta & 15)) * 64, dst);
    bulk_commit();
    asm volatile("cp.async.bulk.wait_group.read 0;" ::: "memory");
    if (threadIdx.x == 128) TS(9);
    if (threadIdx.x == 128) LTS(1);
  }
}

struct cplx { float r, i; };
__device__ __forceinline__ cplx cmul(cplx a, cplx b) { return {fmaf(a.r, b.r, -a.i * b.i), fmaf(a.r, b.i, a.i * b.r)}; }
__device__ __forceinline__ cplx csqr(cplx a) { return {fmaf(a.r, a.r, -a.i * a.i), (a.r + a.r) * a.i}; }
__device__ __forceinline__ cplx cexp_l(float ar2, float ai, float l) {
  const float m = ex2(ar2 * l);
  const float x = ai * l;
  return {m * __cosf(x), m * __sinf(x)};
}

__device__ __forceinline__ void colsum_cta(const Params& p, uint32_t sb, int j, int tid) {
  const uint32_t bar = sb + SM_BAR;
  auto ld = [&](int i) {
    mbar_expect(bar + 8 * i, 3 * PG);
    tma_ld3(sb + (i & 7) * 3 * PG, &p.mapW3, (2 * j + (i & 1)) * 64, (i >> 1) * 64, 0, bar + 8 * i);
  };
  if (tid == 384) {
#pragma unroll
    for (int i = 0; i < 24; i++) mbar_init(bar + 8 * i, i < 16 ? 1 : 12);
    asm volatile("fence.mbarrier_init.release.cluster;" ::: "memory");
    fence_async_smem();
#pragma unroll 1
    for (int i = 0; i < 8; i++) ld(i);
  }
  const unsigned ep = ld_relaxed(&g_cnt[C_CS * 32]);
  bar_sync(0, NTHREADS);
  if (tid == 384) {
#pragma unroll 1
    for (int i = 8; i < 16; i++) { mbar_wait(bar + 8 * (8 + i), 0); fence_async_smem(); ld(i); }
  }
  if (tid < 384) {
    const int lane = tid & 31, cc = tid & 7, r0 = (tid >> 3) & 15, part = tid >> 7;
    const uint32_t id = ((lane >> 2) == 2 * (lane & 3) ? 0x3f80u : 0u) | ((lane >> 2) == 2 * (lane & 3) + 1 ? 0x3f800000u : 0u);
    const uint32_t src = sb + part * PG + r0 * 128 + ((cc ^ (r0 & 7)) << 4);
    float s[2][2][4];
#pragma unroll
    for (int i = 0; i < 16; i++) s[i >> 3][(i >> 2) & 1][i & 3] = 0.f;
#pragma unroll 1
    for (int i2 = 0; i2 < 16; i2 += 2) {
#pragma unroll
      for (int h = 0; h < 2; h++) {
        const int i = i2 + h;
        mbar_wait(bar + 8 * i, 0);
        uint4 v[4];
#pragma unroll
        for (int k = 0; k < 4; k++) v[k] = lds128(src + (i & 7) * 3 * PG + k * 2048);
#pragma unroll
        for (int k = 0; k < 4; k++) {
          const uint32_t a[4] = {v[k].x, v[k].y, v[k].z, v[k].w};
          mma_bf16(s[h][0], a, id, 0u);
          mma_bf16(s[h][1], a, 0u, id);
        }
        __syncwarp();
        if (i < 8 && lane == 0) mbar_arrive(bar + 8 * (16 + i));
      }
    }
    const uint32_t red = sb + 24 * PG;
#pragma unroll
    for (int h = 0; h < 2; h++)
#pragma unroll
      for (int k = 0; k < 2; k++) sts128f(red + (r0 * 384 + h * 192 + part * 64 + cc * 8 + k * 4) * 4, s[h][k][0], s[h][k][1], s[h][k][2], s[h][k][3]);
    bar_sync(1, 384);
    float tot = 0.f;
#pragma unroll
    for (int k = 0; k < 16; k++) tot += __uint_as_float(lds32(red + (k * 384 + tid) * 4));
    asm volatile("st.relaxed.gpu.global.v2.u32 [%0], {%1,%2};" ::"l"(&g_colsum[j * 384 + tid]), "r"(__float_as_uint(tot)), "r"(ep / NCTA + 1) : "memory");
    const uint4 u = make_uint4(UNSET, UNSET, UNSET, UNSET);
    if (tid < 256) {
#pragma unroll 4
      for (int i = 0; i < 64; i++) stg128(g_halo + 65536 + j * 16384 + i * 256 + tid, u);
#pragma unroll 1
      for (int s = 0; s < 3; s++) {
        uint4* dst = (s ? (uint4*)g_xT + (s + 1) * 131072 : (uint4*)g_O + 131072) + j * 32768 + (tid >> 1) * 8 + (tid & 1);
#pragma unroll 4
        for (int i = 0; i < 32; i++) stg128(dst + i * 1024, u);
        bar_sync(2, 256);
        if (tid == 32 * s) red_release(&g_cnt[(C_R + s) * 32]);
      }
    }
  }
}

#define KW 3
struct ModeIn { uint32_t ar, ai, br, bi, cr, ci; bf16 logdt; };
__device__ __forceinline__ ModeIn load_modes(const Params& p, int d, int m) {
  const int i = d * 64 + m;
  return {((const uint32_t*)p.a_re)[i], ((const uint32_t*)p.a_im)[i], ((const uint32_t*)p.b_re)[i], ((const uint32_t*)p.b_im)[i],
          ((const uint32_t*)p.c_re)[i], ((const uint32_t*)p.c_im)[i], p.log_dt[d]};
}
__device__ __forceinline__ float4 lds128f_nv(uint32_t a) { float4 v; asm("ld.shared.v4.f32 {%0,%1,%2,%3}, [%4];" : "=f"(v.x), "=f"(v.y), "=f"(v.z), "=f"(v.w) : "r"(a)); return v; }
__device__ __forceinline__ void kernel_gen(const Params& p, uint32_t sb, int cta, int ht, ModeIn in, const ModeIn& in1) {
  const uint32_t bst = sb + SM_KGB + ((ht & 63) >> 2) * 144 + (ht & 3) * 4 + (ht >> 6) * 16;
  const uint64_t db = mkdesc(sb + SM_KGB, 144, 2304, 0);
  const float e0 = (float)(8 * (((ht & 32) >> 1) + ((ht & 31) >> 2)));
  float T[20];
#pragma unroll
  for (int i = 0; i < 20; i++) T[i] = 0.f;
  float k0 = (ht & 63) ? 0.f : __bfloat162float(p.dskip[cv_chan(cta, ht >> 6)]);
#pragma unroll 1
  for (int pass = 0; pass < 4; pass++) {
    {
      const int sh = (pass & 1) ? 0 : 16;
      auto val = [&](uint32_t v) { return __uint_as_float((v << sh) & 0xffff0000u); };
      const float dt = __bfloat162float(__float2bfloat16_rn(expf(__bfloat162float(in.logdt))));
      const float ar2 = dt * val(in.ar) * 1.4426950408889634f, ai = dt * val(in.ai);
      const cplx c = cmul({val(in.cr), -val(in.ci)}, {dt * val(in.br), -dt * val(in.bi)});
      k0 += c.r;
      const cplx z1 = cexp_l(ar2, -ai, 1.f), z256 = cexp_l(ar2, -ai, 256.f), z64 = cexp_l(ar2, ai, 64.f);
      const cplx z2 = csqr(z1), z512 = csqr(z256);
      auto put = [&](int j, cplx v) { sts32(bst + (j >> 2) * 2304 + (j & 3) * 32, packbf(v.r, v.i)); };
      sts128f(sb + SM_KGT + ht * 16, ar2, ai, z64.r, z64.i);
      const cplx c1 = cmul(c, z1), c2 = cmul(c, z2), c3 = cmul(c1, z2), c4 = cmul(c2, z2);
      const cplx c5 = cmul(c3, z2), c6 = cmul(c4, z2), c7 = cmul(c5, z2), c8 = cmul(c6, z2);
      put(0, c1); put(1, c2); put(2, c3); put(3, c4); put(4, c5); put(5, c6); put(6, c7); put(7, c8);
      const cplx c260 = cmul(c4, z256), c264 = cmul(c8, z256), c520 = cmul(c8, z512), c776 = cmul(c264, z512);
      put(8, cmul(c2, z256)); put(9, c260); put(10, cmul(c6, z256)); put(11, c264);
      put(12, cmul(c4, z512)); put(13, c520); put(14, cmul(c260, z512)); put(15, c776);
      const cplx c1032 = cmul(c520, z512), c1288 = cmul(c776, z512);
      put(16, c1032); put(17, c1288); put(18, cmul(c1032, z512)); put(19, cmul(c1288, z512));
    }
    fence_async_smem();
    bar_sync(4, 128);
    uint32_t tb = sb + SM_KGT + (ht & 67) * 16;
    asm volatile("mov.u32 %0, %0;" : "+r"(tb) :: "memory");
#pragma unroll
    for (int q = 0; q < 4; q++) {
      uint32_t A[8];
      if (q >= KW) wg_wait<KW - 1>();
#pragma unroll
      for (int s = 0; s < 4; s++) {
        const float4 v = lds128f_nv(tb + (4 * q + s) * 64);
        const cplx lo = cexp_l(v.x, v.y, e0), hi = cmul(lo, {v.z, v.w});
        A[2 * s] = packbf(lo.r, lo.i);
        A[2 * s + 1] = packbf(hi.r, hi.i);
      }
      wg_fence();
      wgmma_rs<40, 0>(T, A, db + 36 * q, (pass & 1) | q);
      wgmma_rs<40, 0>(T, A + 4, db + 36 * q + 18, 1);
      wg_commit();
    }
    wg_wait<0>();
    acc_fence<20>(T);
    if (ht == 0) TS(4 + pass);
    if (pass & 1) {
      const int h2 = opaque_tid() - 256, w = h2 >> 5, lane = h2 & 31, t = lane & 3, chn = h2 >> 6, m = h2 & 63, i0 = 16 * (w & 1) + (lane >> 2);
      const int lc = (pass & 2) + chn;
      const uint32_t kc = sb + kc_off(lc);
      auto put = [&](int idx, float v) {
        sts16(kc + idx * 2, __bfloat16_as_ushort(__float2bfloat16_rn(v)));
      };
#pragma unroll
      for (int hi = 0; hi < 2; hi++) {
        const int i = i0 + 8 * hi;
        float v[5];
#pragma unroll
        for (int j = 0; j < 5; j++) v[j] = chn ? T[4 * j + 2 * hi + 1] : T[4 * j + 2 * hi];
        put(8 * i + 1 + t, v[0]);
        put(8 * i + 5 + t, v[1]);
        put(257 + 4 * i + t, v[2]);
        put(385 + 2 * i + (t & 1) + 64 * (t >> 1), v[3]);
        put(513 + i + 32 * t, v[4]);
      }
#pragma unroll
      for (int o = 16; o > 0; o >>= 1) k0 += __shfl_xor_sync(~0u, k0, o);
      if (lane == 0) sts32f(sb + SM_RED + 4 * w, k0);
      bar_sync(4, 128);
      if (m == 0) put(0, k0 + __uint_as_float(lds32(sb + SM_RED + 4 * w + 4)));
      k0 = m ? 0.f : __bfloat162float(p.dskip[cv_chan(cta, 2 + chn)]);
      in = in1;
    }
  }
}

__device__ __forceinline__ void expand_taps(uint32_t sb, int ht) {
  const int ch = ht >> 5, lane = ht & 31;
  const uint32_t kc = sb + kc_off(ch);
  const uint32_t dst0 = sb + cv_pe(ch);
  auto put = [&](int G, uint32_t v0, uint32_t v1, uint32_t v2, uint32_t v3, uint32_t v4, uint32_t v5, uint32_t v6, uint32_t v7, uint32_t v8) {
    const uint32_t dst = dst0 + G * 32;
    sts128(dst, make_uint4(v1 | (v0 << 16), v2 | (v1 << 16), v3 | (v2 << 16), v4 | (v3 << 16)));
    sts128(dst + 16, make_uint4(v5 | (v4 << 16), v6 | (v5 << 16), v7 | (v6 << 16), v8 | (v7 << 16)));
  };
  {
    const uint4 q = lds128(kc + lane * 16);
    const uint32_t pv = lane ? lds16(kc + lane * 16 - 2) : 0u;
    const uint32_t dst = dst0 + (lane + 2) * 32;
    sts128(dst, make_uint4(__byte_perm(q.x, pv, 0x5410), __byte_perm(q.x, q.x, 0x1032), __byte_perm(q.y, q.x, 0x7610), __byte_perm(q.y, q.y, 0x1032)));
    sts128(dst + 16, make_uint4(__byte_perm(q.z, q.y, 0x7610), __byte_perm(q.z, q.z, 0x1032), __byte_perm(q.w, q.z, 0x7610), __byte_perm(q.w, q.w, 0x1032)));
    if (lane < 4) sts128(dst0 + lane * 16, make_uint4(0, 0, 0, 0));
  }
  uint32_t a[5], b[2][3];
  {
    const uint32_t s1 = kc + 2 * (256 + 4 * lane);
#pragma unroll
    for (int k = 0; k < 5; k++) a[k] = lds16(s1 + 2 * k);
#pragma unroll
    for (int u = 0; u < 2; u++) {
      const uint32_t s2 = kc + 2 * (384 + 2 * (lane + 32 * u));
#pragma unroll
      for (int k = 0; k < 3; k++) b[u][k] = lds16(s2 + 2 * k);
    }
  }
  const uint32_t k255 = lds16(kc + 2 * 255), k1024 = lds16(kc + 2 * 512);
  put(34 + lane, lane == 0 ? k255 : a[0], a[0], a[0], a[1], a[2], a[2], a[2], a[3], a[4]);
#pragma unroll
  for (int u = 0; u < 2; u++) put(66 + lane + 32 * u, b[u][0], b[u][0], b[u][0], b[u][0], b[u][1], b[u][1], b[u][1], b[u][2], b[u][2]);
  if (lane < 10) {
    const uint32_t v = lane == 0 ? k1024 : 0u;
    put(130 + lane, v, v, v, v, v, v, 0u, 0u, 0u);
  }
}
__device__ __forceinline__ void expand_far(uint32_t sb, int ht) {
  const int ch = ht >> 5, lane = ht & 31;
  const uint32_t kc = sb + kc_off(ch) + 4 * (249 + lane), dst = sb + cv_fa(ch);
  uint32_t v[2][9];
#pragma unroll
  for (int u = 0; u < 2; u++)
#pragma unroll
    for (int k = 0; k < 9; k++) v[u][k] = lds32(kc + 4 * (32 * u + k));
#pragma unroll
  for (int k = 0; k < 8; k++) v[0][k] = lane + k < 7 ? 0u : lane + k == 7 ? v[0][k] & 0xffff0000u : v[0][k];
#pragma unroll
  for (int u = 0; u < 2; u++) {
    const uint32_t row = dst + (56 + 32 * u + lane) * 16;
    sts128(row, make_uint4(__byte_perm(v[u][1], v[u][2], 0x5410), __byte_perm(v[u][3], v[u][4], 0x5410), __byte_perm(v[u][5], v[u][6], 0x5410), __byte_perm(v[u][7], v[u][8], 0x5410)));
    sts128(row + 2048, make_uint4(__byte_perm(v[u][0], v[u][1], 0x7632), __byte_perm(v[u][2], v[u][3], 0x7632), __byte_perm(v[u][4], v[u][5], 0x7632), __byte_perm(v[u][6], v[u][7], 0x7632)));
    sts128(dst + u * 2048 + lane * 16, make_uint4(0, 0, 0, 0));
    if (lane < 24) sts128(dst + u * 2048 + (32 + lane) * 16, make_uint4(0, 0, 0, 0));
  }
}

#define MAPF 0
#define PMAP 1
#define FIRST 0
#define WOCS 0
#define WPRE 2
__host__ __device__ constexpr int bar_count(int i) {
  return i == B_END ? 3 : i == B_CSF ? 2 : (i >= B_OST && i < B_PDONE + 2) ? 4 : (i == B_PUB + 2 || i == B_PUB || i == B_R + 1) ? 256 : (i >= B_FARM && i < B_END) ? 128 : 1;
}
__host__ __device__ constexpr bool bar_first(int i) { return i < B_WF + 2 && (i & 7) < 2; }

__global__ void __launch_bounds__(NTHREADS, 1) fused_kernel(const __grid_constant__ Params p) {
  extern __shared__ __align__(1024) uint8_t smem[];
  const uint32_t sb = s32(smem);
  const int tid = threadIdx.x, lane = tid & 31;
  const int warp = __shfl_sync(~0u, tid >> 5, 0);
  const int cta = blockIdx.x - p.first;
  if ((unsigned)cta >= NCTA) {
    colsum_cta(p, sb, blockIdx.x & 3, tid);
    return;
  }
  const int rb = ((cta >> 4) & 3) * 4 + ((cta >> 2) & 3), hg = (cta >> 6) * 4 + (cta & 3);
  const int rb2 = rb, q2 = hg;
  const uint32_t bar = sb + SM_BAR;
  auto ld_x0 = [&](int half, int c) {
    const uint32_t b = bar + 8 * (B_XF + 8 * half + c);
    mbar_expect(b, PG);
    tma_ld(sb + x_page(half, c) * PG, &p.mapX, c * 64, (16 * half + rb) * 64, b);
  };
  auto ld_w = [&](int c) {
    const uint32_t b = bar + 8 * (B_WF + c);
    mbar_expect(b, 3 * PG);
    tma_ld3(sb + w_page(c) * PG, &p.mapW3, hg * 64, c * 64, 0, b);
  };

  if (tid == 0) TS(0);
  if (tid == 480) LTS(0);
  if (warp < 6 && elect_one()) {
    if (warp == 0) {
#pragma unroll
      for (int i = 0; i < B_WF + 2; i++)
        if (bar_first(i)) mbar_init(bar + 8 * i, 1);
      asm volatile("fence.mbarrier_init.release.cluster;" ::: "memory");
      fence_async_smem();
      ld_x0(0, 0); ld_w(0); ld_x0(1, 0);
      ld_x0(0, 1); ld_w(1); ld_x0(1, 1);
      TS(1);
    } else {
#pragma unroll
      for (int q = 0; q < 5; q++) {
        if (warp == q + 1) {
#pragma unroll
          for (int i = 0; i < B_COUNT; i++)
            if (!bar_first(i) && i % 5 == q) mbar_init(bar + 8 * i, bar_count(i));
        }
      }
      asm volatile("fence.mbarrier_init.release.cluster;" ::: "memory");
    }
  }

  if (warp < 8) {
    bar_sync(0, NTHREADS);
    asm volatile("setmaxnreg.inc.sync.aligned.u32 %0;" ::"n"(R_CONS));
    const int cw = __shfl_sync(~0u, opaque_tid() >> 5, 0);
    const int wg = cw >> 2, w = cw & 3;
    if (tid == 0) TS(2);
    int rtp = 0;
#pragma unroll 1
    for (int layer = 0; layer < 2; layer++) {
      attn_phase(p, sb, layer, rb, hg, wg, w);
      proj_phase(p, sb, layer, rb2, q2, wg, w, rtp);
      conv_phase(p, sb, layer, cta);
    }
    final_phase(p, sb, cta, wg, w, rtp);
  } else if (warp < 12) {
    asm volatile("setmaxnreg.dec.sync.aligned.u32 %0;" ::"n"(R_HELP));
    const int ht = tid - 256;
    {
      unsigned ep0 = 0;
      if (ht == 0) ep0 = ld_relaxed(&g_cnt[C_CS * 32]);
      const ModeIn in0 = load_modes(p, cv_chan(cta, ht >> 6), ht & 63), in1 = load_modes(p, cv_chan(cta, 2 + (ht >> 6)), ht & 63);
      if (ht < 48) sts128f(sb + SM_STG + ht * 16, 0.f, 0.f, 0.f, 1.f);
      bar_sync(0, NTHREADS);
      if (ht == 0) {
        sts32(sb + SM_EP, ep0 / NCTA);
        mbar_arrive(bar + 8 * B_EP);
      }
      kernel_gen(p, sb, cta, ht, in0, in1);
      if (ht < 48) sts128f(sb + SM_KGT + ht * 16, 0.f, 0.f, 0.f, 1.f);
      fence_async_smem();
      bar_sync(4, 128);
      if (ht == 0) mbar_arrive(bar + 8 * B_KG);
    }
#pragma unroll 1
    for (int layer = 0; layer < 2; layer++) {
      bf16* xout = g_xT + ((2 * layer + 1) * DM + 2 * cta) * LSEQ;
      mbar_wait(bar + 8 * B_PDONE, layer);
      expand_taps(sb, opaque_tid() - 256);
      mbar_arrive(bar + 8 * B_PE);
      TSW(0);
      expand_far(sb, opaque_tid() - 256);
      if (layer) mbar_wait(bar + 8 * (B_RS + 2), 0);
      mbar_wait(bar + 8 * (B_PDONE + 1), layer);
      mbar_wait(bar + 8 * B_U, layer);
#pragma unroll 1
      for (int lc = 0; lc < 4; lc += 2) {
        conv_sums(sb, lc, opaque_tid() - 256);
        TSW(1 + lc);
      }
      fence_async_smem();
      bar_sync(4, 128);
      conv_far(sb, opaque_tid() - 256);
      mbar_arrive(bar + 8 * B_FARM);
      TSW(4);
      mbar_wait(bar + 8 * (B_R + 1), layer);
      conv_epi<1, 2>(sb, xout, 0, opaque_tid() - 256);
      mbar_arrive(bar + 8 * (B_PUB + 1));
      TSW(5);
      mbar_wait(bar + 8 * (B_R + 2), layer);
      conv_epi<1, 1>(sb, xout, 2, opaque_tid() - 256);
      mbar_arrive(bar + 8 * (B_PUB + 2));
      TSW(6);
    }
  } else {
    asm volatile("setmaxnreg.dec.sync.aligned.u32 %0;" ::"n"(R_AGENT));
    bar_sync(0, NTHREADS);
    auto done = [&](int half, int c, int layer) { mbar_wait(bar + 8 * (B_DN + 8 * half + c), layer); };
    auto publish = [&](int layer, int k) {
      mbar_wait(bar + 8 * (B_PUB + k), layer);
      if (layer == 0) {
        red_release(&g_cnt[(C_C + k) * 32]);
      }
      else red_relaxed(&g_cnt[(C_F + 4 * k + (cta >> 5)) * 32]);
      TS(16 + layer * 56 + 40 + 7 + k);
    };
    if (warp == 12) {
      if (elect_one()) {
#pragma unroll 1
        for (int layer = 0; layer < 2; layer++) {
          auto ld_xe = [&](int c) {
            const uint32_t b = bar + 8 * (B_XF + c);
            mbar_expect(b, PG);
            if (layer == 0) tma_ld(sb + (c - 5) * PG, &p.mapX, c * 64, rb * 64, b);
            else tma_ld(sb + (c - 5) * PG, &p.mapXT, rb * 64, DM + c * 64, b);
          };
          if (layer == 0) {
            ld_x0(0, 2); ld_w(2); ld_x0(1, 2);
            if (hg >= 3) {
              mbar_expect(bar + 8 * B_SC, PG);
              tma_ld(sb + P_R * PG, &p.mapX, hg * 64, rb * 64, bar + 8 * B_SC);
            }
            if (rb < 4) tma_prefetch3(&p.mapW3, hg * 64, (4 + rb) * 64, 0);
            ld_x0(0, 3); ld_w(3); ld_x0(1, 3); ld_x0(0, 4); ld_x0(1, 4);
            done(0, 0, 0); done(1, 0, 0);
            ld_w(4);
            ld_x0(1, 5); ld_x0(1, 6); ld_x0(1, 7);
            done(0, 1, 0); done(1, 1, 0);
            ld_w(5);
            if (rb2 < 8) tma_prefetch5(&p.mapWo, q2 * 64, rb2 * 2);
            done(0, 2, 0);
            fence_async_smem();
            ld_xe(5); ld_xe(6); ld_xe(7);
          } else {
            mbar_wait(bar + 8 * B_PDONE, 0);
            mbar_wait(bar + 8 * (B_PDONE + 1), 0);
            mbar_wait(bar + 8 * (WPRE == 1 ? B_U : B_GB + 1), 0);
            ld_w(0); ld_w(1);
            mbar_wait(bar + 8 * B_U1, 0);
            fence_async_smem();
            ld_w(2);
            mbar_wait(bar + 8 * (B_PUB + 2), 0);
            fence_async_smem();
            ld_w(3);
            done(0, 2, 1);
            fence_async_global();
            fence_async_smem();
            ld_xe(5); ld_xe(6); ld_xe(7);
            done(1, 0, 1);
            ld_w(4);
            done(1, 1, 1);
            ld_w(5);
          }
          done(1, 2, layer);
          fence_async_smem();
          ld_w(6); ld_w(7);
          auto ld_res = [&](int half) {
            const uint32_t b = bar + 8 * (B_RF + half);
            mbar_expect(b, PG);
            if (layer == 0) tma_ld(sb + (half ? 2 : P_R) * PG, &p.mapX, q2 * 64, (16 * half + rb2) * 64, b);
            else tma_ld(sb + (half ? 2 : P_R) * PG, &p.mapXT, (16 * half + rb2) * 64, DM + q2 * 64, b);
          };
          done(0, 4, layer); done(1, 3, layer);
          fence_async_smem();
#pragma unroll 1
          for (int c = 0; c < 8; c++) {
            const uint32_t b = bar + 8 * (B_WOF + (c >> 1));
            if (c == 5) { ld_res(0); done(1, 4, layer); }
            if ((c & 1) == 0) mbar_expect(b, 2 * PG);
            tma_ld5(sb + wo_page(c) * PG, &p.mapWo, q2 * 64, c * 2, b);
          }
          done(0, 7, layer);
          fence_async_global();
          ld_res(1);
        }
      }
    } else if (warp == 13) {
      if (elect_one()) {
        mbar_wait(bar + 8 * (B_WF + 2), 0);
        asm volatile("prefetch.tensormap [%0];" ::"l"(&p.mapXT) : "memory");
        asm volatile("prefetch.tensormap [%0];" ::"l"(&p.mapOut) : "memory");
        asm volatile("prefetch.tensormap [%0];" ::"l"(&p.mapWo) : "memory");
        mbar_wait(bar + 8 * B_EP, 0);
        const unsigned e1 = lds32(sb + SM_EP) + 1;
        spin_until(&g_cnt[C_Z * 32], e1 * NCTA);
        mbar_arrive(bar + 8 * B_CSF);
        TS(3);
        auto ld_x1 = [&](int half, int c0, int c1) {
          fence_async_global();
          fence_async_smem();
#pragma unroll 1
          for (int c = c0; c < c1; c++) {
            const uint32_t b = bar + 8 * (B_XF + 8 * half + c);
            mbar_expect(b, PG);
            tma_ld(sb + x_page(half, c) * PG, &p.mapXT, (16 * half + rb) * 64, DM + c * 64, b);
          }
        };
#pragma unroll 1
        for (int layer = 0; layer < 2; layer++) {
          if (layer == 1) {
            mbar_wait(bar + 8 * B_FARM, 0);
            mbar_wait(bar + 8 * B_PUB, 0);
            spin_until(&g_cnt[C_C * 32], e1 * NCTA);
            TS(10);
            ld_x1(0, 0, 3);
            if (hg >= 3) {
              mbar_expect(bar + 8 * B_SC, PG);
              tma_ld(sb + P_R * PG, &p.mapXT, rb * 64, DM + hg * 64, bar + 8 * B_SC);
            }
            ld_x1(0, 3, 5);
            mbar_wait(bar + 8 * (B_PUB + 1), 0);
            spin_until(&g_cnt[(C_C + 1) * 32], e1 * NCTA);
            TS(11);
            ld_x1(1, 0, 4);
            spin_until(&g_cnt[(C_C + 2) * 32], e1 * NCTA);
            TS(12);
            ld_x1(1, 4, 8);
          }
#pragma unroll 1
          for (int half = 0; half < 2; half++) {
            done(1, 7, layer);
            mbar_wait(bar + 8 * B_OST, layer);
            if (half) mbar_wait(bar + 8 * (B_OST + 1), layer);
            spin_until(&g_cnt[(C_O + layer * 32 + 16 * half + rb2) * 32], e1 * 32);
            fence_async_global();
            fence_async_smem();
#pragma unroll 1
            for (int c = 0; c < 4; c++) {
              const uint32_t b = bar + 8 * (B_OF + 4 * half + c);
              mbar_expect(b, 2 * PG);
              bulk_ld(sb + o_page(half, c) * PG, g_O + ((layer * 32 + 16 * half + rb2) * 4 + c) * PG, 2 * PG, b);
            }
          }
        }
        mbar_wait(bar + 8 * B_PUB, 1);
#pragma unroll 1
        for (int half = 0; half < 2; half++) {
          spin_until(&g_cnt[(C_F + 4 * (half ? 1 + (cta >> 6) : 0) + ((cta >> 4) & 3)) * 32], e1 * 32);
          fence_async_global();
          mbar_expect(bar + 8 * (B_TF + half), PG);
          tma_ld(sb + (16 + half) * PG, &p.mapXT, (16 * half + (cta & 15)) * 64, 3 * DM + (cta >> 4) * 64, bar + 8 * (B_TF + half));
        }
      }
    } else if (warp == 14) {
      mbar_wait(bar + 8 * B_EP, 0);
      const unsigned e1 = lds32(sb + SM_EP) + 1;
      done(0, 1, 0);
      {
        const uint2* cp = g_colsum + (hg * 192 + lane);
        uint2 v[6];
        bool ok;
        int it = 0;
        do {
          ok = true;
#pragma unroll
          for (int i = 0; i < 6; i++) {
            asm volatile("ld.relaxed.gpu.global.v2.u32 {%0,%1}, [%2];" : "=r"(v[i].x), "=r"(v[i].y) : "l"(cp + 32 * i) : "memory");
            ok = ok && v[i].y == e1;
          }
          if (++it > (1 << 22)) __trap();
        } while (!__all_sync(~0u, ok));
#pragma unroll
        for (int i = 0; i < 6; i++) sts32f(sb + SM_CS + 4 * (lane + 32 * i), __uint_as_float(v[i].x));
      }
      __syncwarp();
      if (lane == 0) {
        mbar_arrive(bar + 8 * B_CSF);
        red_relaxed(&g_cnt[C_CS * 32]);
        TS(13);
#pragma unroll 1
        for (int i = 0; i < 4; i++) {
          const int layer = i >> 1;
          mbar_wait(bar + 8 * (B_PST + (i & 1)), layer);
          const uint32_t b = bar + 8 * (B_GB + 1);
          const bf16* xin = g_xT + ((size_t)2 * layer * DM + 2 * cta) * LSEQ + 1024;
          if (i & 1) {
            fence_async_smem();
            mbar_expect(b, 12288 + PG);
          }
          spin_until(&g_cnt[(C_G + i) * 32], e1 * NCTA);
          if (i & 1) {
            bulk_ld(sb + CV_ST, g_stats + (layer * 32 + 16) * 192, 12288, b);
#pragma unroll
            for (int lc = 0; lc < 4; lc++) bulk_ld(sb + cv_x(1, lc), xin + cv_chan(0, lc) * LSEQ, 2048, b);
            TS(14 + layer);
            publish(layer, 1);
          } else {
            mbar_arrive(bar + 8 * B_GB);
          }
        }
      }
    } else {
      const uint4 u = make_uint4(UNSET, UNSET, UNSET, UNSET);
      if (lane < 24) stg128((uint4*)g_stats + cta * 24 + lane, make_uint4(0, 0, 0, 0));
#pragma unroll 4
      for (int i = 0; i < 16; i++) stg128(g_halo + cta * 512 + 32 * i + lane, u);
#pragma unroll 4
      for (int i = 0; i < 16; i++) stg128(((i & 8) ? (uint4*)g_xT : (uint4*)g_O) + cta * 1024 + (i & 7) * 128 + (lane >> 1) * 8 + (lane & 1), u);
      __syncwarp();
      if (lane == 0) {
        red_release(&g_cnt[C_Z * 32]);
        publish(0, 0);
        publish(0, 2);
        const unsigned e1 = lds32(sb + SM_EP) + 1;
#pragma unroll 1
        for (int s = 0; s < 3; s++) {
          spin_until(&g_cnt[(C_R + s) * 32], e1 * 4);
          mbar_arrive(bar + 8 * (B_RS + s));
          TS(16 + 40 + 10 + s);
        }
        publish(1, 0);
        publish(1, 2);
      }
    }
  }
}

typedef CUresult (*EncodeFn)(CUtensorMap*, CUtensorMapDataType, cuuint32_t, void*, const cuuint64_t*, const cuuint64_t*,
                             const cuuint32_t*, const cuuint32_t*, CUtensorMapInterleave, CUtensorMapSwizzle,
                             CUtensorMapL2promotion, CUtensorMapFloatOOBfill);

static void make_map(EncodeFn enc, CUtensorMap* m, void* ptr, uint64_t cols, uint64_t rows, uint32_t box_rows) {
  cuuint64_t dims[2] = {cols, rows};
  cuuint64_t strides[1] = {cols * 2};
  cuuint32_t box[2] = {64, box_rows};
  cuuint32_t es[2] = {1, 1};
  enc(m, CU_TENSOR_MAP_DATA_TYPE_BFLOAT16, 2, ptr, dims, strides, box, es, CU_TENSOR_MAP_INTERLEAVE_NONE,
      CU_TENSOR_MAP_SWIZZLE_128B, CU_TENSOR_MAP_L2_PROMOTION_L2_128B, CU_TENSOR_MAP_FLOAT_OOB_FILL_NONE);
}
static void make_map3(EncodeFn enc, CUtensorMap* m, void* ptr, uint64_t d0, uint64_t cols, uint64_t rows, uint64_t blk_stride,
                      uint64_t nblocks, uint32_t nblk) {
  cuuint64_t dims[3] = {d0, rows, nblocks};
  cuuint64_t strides[2] = {cols * 2, blk_stride * 2};
  cuuint32_t box[3] = {64, 64, nblk};
  cuuint32_t es[3] = {1, 1, 1};
  enc(m, CU_TENSOR_MAP_DATA_TYPE_BFLOAT16, 3, ptr, dims, strides, box, es, CU_TENSOR_MAP_INTERLEAVE_NONE,
      CU_TENSOR_MAP_SWIZZLE_128B, CU_TENSOR_MAP_L2_PROMOTION_L2_128B, CU_TENSOR_MAP_FLOAT_OOB_FILL_NONE);
}

extern "C" void kernel_launch(void* const* d_in, const int* in_sizes, int n_in, void* d_out, int out_size) {
  static Params prm;
  static void* cached[13] = {nullptr};
  static bool attr_done = false;
  bool same = attr_done && cached[12] == d_out;
  for (int i = 0; i < 12 && same; i++) same = cached[i] == d_in[i];
  if (!same) {
    void* fn = nullptr;
    cudaDriverEntryPointQueryResult qr;
    cudaGetDriverEntryPoint("cuTensorMapEncodeTiled", &fn, cudaEnableDefault, &qr);
    EncodeFn enc = (EncodeFn)fn;
    void* pXT;
    cudaGetSymbolAddress(&pXT, g_xT);
    make_map(enc, &prm.mapX, d_in[0], DM, LSEQ, 64);
    make_map(enc, &prm.mapXT, pXT, LSEQ, 4 * DM, 64);
    make_map(enc, &prm.mapOut, d_out, DM, LSEQ, 64);
    {
      cuuint64_t dims[5] = {DM, 2, 4, 4, 16};
      cuuint64_t strides[4] = {DM * 2, 8 * DM * 2, 2 * DM * 2, 32 * DM * 2};
      cuuint32_t box[5] = {64, 2, 4, 4, 2};
      cuuint32_t es[5] = {1, 1, 1, 1, 1};
      enc(&prm.mapWo, CU_TENSOR_MAP_DATA_TYPE_BFLOAT16, 5, d_in[2], dims, strides, box, es, CU_TENSOR_MAP_INTERLEAVE_NONE,
          CU_TENSOR_MAP_SWIZZLE_128B, CU_TENSOR_MAP_L2_PROMOTION_L2_128B, CU_TENSOR_MAP_FLOAT_OOB_FILL_NONE);
    }
    make_map3(enc, &prm.mapW3, d_in[1], DM, 3 * DM, DM, DM, 3, 3);
    prm.wqkv = (const bf16*)d_in[1];
    prm.a_re = (const bf16*)d_in[4]; prm.a_im = (const bf16*)d_in[5];
    prm.b_re = (const bf16*)d_in[6]; prm.b_im = (const bf16*)d_in[7];
    prm.c_re = (const bf16*)d_in[8]; prm.c_im = (const bf16*)d_in[9];
    prm.log_dt = (const bf16*)d_in[10]; prm.dskip = (const bf16*)d_in[11];
    int dev = 0, sms = 0;
    cudaGetDevice(&dev);
    cudaDeviceGetAttribute(&sms, cudaDevAttrMultiProcessorCount, dev);
    prm.first = sms >= NCTA + 4 ? FIRST : 4;
    cudaFuncSetAttribute(fused_kernel, cudaFuncAttributeMaxDynamicSharedMemorySize, SM_TOTAL);
    for (int i = 0; i < 12; i++) cached[i] = d_in[i];
    cached[12] = d_out;
    attr_done = true;
  }
  fused_kernel<<<NCTA + 4, NTHREADS, SM_TOTAL>>>(prm);
}
```

```cpp
#include <cuda_runtime.h>
#include <cuda_bf16.h>
#include <cuda.h>
#include <stdint.h>

typedef __nv_bfloat16 bf16;

constexpr int LSEQ = 2048;
constexpr int DM = 512;
constexpr int NCTA = 128;
constexpr int NTHREADS = 512;
#define R_CONS 200
#define R_HELP 88
#define R_AGENT 24
#define GPOS 4
#define TURN0 4
#define TURN1 4

constexpr int PG = 8192;
constexpr int P_R = 25;
__host__ __device__ constexpr int x_page(int half, int c) { return half ? 8 + c : c < 5 ? c : c - 5; }
__host__ __device__ constexpr int w_page(int c) { return (c & 3) < 3 ? 16 + 3 * (c & 3) : c < 4 ? 5 : 8; }
__host__ __device__ constexpr int wo_page(int c) { return c < 5 ? 3 + c : 11 + c; }
__host__ __device__ constexpr int o_page(int half, int pair) { return half ? (pair ? 17 + 2 * pair : 0) : 8 + 2 * pair; }
constexpr int SM_KGB = (P_R + 1) * PG;
constexpr int SM_KC = 27 * PG;
constexpr int KC_STRIDE = 648;
__host__ __device__ constexpr int kc_off(int lc) { return SM_KC + (lc & 1) * 2 * KC_STRIDE + (lc < 2 ? 3328 : 0); }
constexpr int SM_KGT = SM_KC + 3328 + 2592;
constexpr int SM_CS = SM_KGT + 2048;
constexpr int SM_RED = SM_CS + 768;
constexpr int SM_EP = SM_RED + 16;
constexpr int SM_STG = SM_RED + 32;
constexpr int SM_BAR = SM_STG + 768;
constexpr int SM_TS = SM_BAR + 768;
constexpr int SM_TOTAL = SM_TS + 512;
static_assert(SM_TOTAL <= 232448 && SM_STG % 16 == 0 && SM_KGT % 16 == 0, "shared memory");

constexpr int CV_UH = 140 * 16;
__host__ __device__ constexpr int cv_u(int lc) { return (8 + 2 * lc) * PG; }
__host__ __device__ constexpr int cv_pe(int lc) { return cv_u(lc) + 4480; }
__host__ __device__ constexpr int cv_pb1(int lc, int w) { return w ? cv_u(lc) + 8960 + (w - 1) * 2048 : 7 * PG + lc * 2048; }
__host__ __device__ constexpr int cv_fa(int lc) { return cv_pb1(lc, 1) + 128; }
__host__ __device__ constexpr int cv_dump(int lc) { return cv_u(lc) + 16256; }
__host__ __device__ constexpr int cv_pb0(int lc, int w) { return lc * PG + w * 2048; }
__host__ __device__ constexpr int cv_se(int lc) { return 5 * PG + lc * 4096; }
__host__ __device__ constexpr int cv_so(int lc) { return cv_se(lc) + 2048; }
__host__ __device__ constexpr int cv_x(int half, int lc) { return (P_R + half) * PG + lc * 2048; }
constexpr int CV_ST = 22 * PG;
__host__ __device__ constexpr int cv_chan(int cta, int lc) { return 2 * cta + (lc & 1) + 256 * (lc >> 1); }

enum {
  B_XF = 0,
  B_WF = 16,
  B_OF = 24,
  B_DN = 32,
  B_WOF = 48,
  B_RF = 52,
  B_PST = 54,
  B_OST = 56,
  B_PDONE = 58,
  B_GB = 60,
  B_TF = 62,
  B_CSF = 64,
  B_EP = 65,
  B_KG = 67,
  B_S = 68,
  B_PE = 70,
  B_U = 71,
  B_R0 = 72,
  B_PUB = 74,
  B_R = 77,
  B_END = 80,
  B_SC = 81,
  B_RT = 82,
  B_U1 = 84,
  B_RS = 85,
  B_COUNT = 88
};

enum {
  C_CS = 0,
  C_G = 1,
  C_C = 5,
  C_F = 8,
  C_O = 20,
  C_Z = 84,
  C_R = 85,
  C_COUNT = 88
};

__device__ unsigned g_cnt[C_COUNT * 32];
__device__ __align__(1024) bf16 g_O[2 * LSEQ * DM];
__device__ __align__(1024) bf16 g_xT[4 * DM * LSEQ];
__device__ __align__(1024) float g_stats[2 * 32 * 192];
__device__ __align__(1024) uint2 g_colsum[3 * DM];
__device__ __align__(1024) uint4 g_halo[2 * 32 * 8 * 256];
__device__ __align__(1024) uint4 g_part[2 * 32 * 8 * 64];
#define TS(i) do { } while (0)
#define TSW(k) do { if ((threadIdx.x & 127) == 0) TS(16 + layer * 56 + (threadIdx.x >> 7) * 20 + (k)); } while (0)
#define TSG(k) do { } while (0)

#define RETRY(i) do { } while (0)
#define LTS(i) do { } while (0)

struct Params {
  CUtensorMap mapX, mapW3, mapXT, mapOut, mapWo;
  const bf16 *wqkv, *a_re, *a_im, *b_re, *b_im, *c_re, *c_im, *log_dt, *dskip;
  int first;
};

__device__ __forceinline__ uint32_t s32(const void* p) { return (uint32_t)__cvta_generic_to_shared(p); }
__device__ __forceinline__ void mbar_init(uint32_t b, int c) { asm volatile("mbarrier.init.shared::cta.b64 [%0], %1;" ::"r"(b), "r"(c) : "memory"); }
__device__ __forceinline__ void mbar_expect(uint32_t b, int bytes) { asm volatile("mbarrier.arrive.expect_tx.shared::cta.b64 _, [%0], %1;" ::"r"(b), "r"(bytes) : "memory"); }
__device__ __forceinline__ void mbar_arrive(uint32_t b) { asm volatile("mbarrier.arrive.shared::cta.b64 _, [%0];" ::"r"(b) : "memory"); }
__device__ __forceinline__ void mbar_wait(uint32_t b, int parity) {
  asm volatile("{\n.reg .pred p;\nWAIT_LOOP:\nmbarrier.try_wait.parity.shared::cta.b64 p, [%0], %1;\n@p bra WAIT_DONE;\nbra WAIT_LOOP;\nWAIT_DONE:\n}" ::"r"(b), "r"(parity) : "memory");
}
__device__ __forceinline__ bool mbar_test(uint32_t b, int parity) {
  uint32_t ok;
  asm volatile("{\n.reg .pred p;\nmbarrier.test_wait.parity.shared::cta.b64 p, [%1], %2;\nselp.u32 %0, 1, 0, p;\n}" : "=r"(ok) : "r"(b), "r"(parity) : "memory");
  return ok != 0;
}
__device__ __forceinline__ int opaque_tid() { int v; asm volatile("mov.u32 %0, %%tid.x;" : "=r"(v)); return v; }
__device__ __forceinline__ bool elect_one() {
  uint32_t r;
  asm volatile("{\n.reg .pred p;\nelect.sync _|p, 0xffffffff;\nselp.u32 %0, 1, 0, p;\n}" : "=r"(r));
  return r != 0;
}
__device__ __forceinline__ void tma_ld(uint32_t dst, const CUtensorMap* m, int c0, int c1, uint32_t bar) {
  asm volatile("cp.async.bulk.tensor.2d.shared::cluster.global.mbarrier::complete_tx::bytes [%0], [%1, {%3, %4}], [%2];"
               ::"r"(dst), "l"(m), "r"(bar), "r"(c0), "r"(c1) : "memory");
}
__device__ __forceinline__ void tma_ld3(uint32_t dst, const CUtensorMap* m, int c0, int c1, int c2, uint32_t bar) {
  asm volatile("cp.async.bulk.tensor.3d.shared::cluster.global.mbarrier::complete_tx::bytes [%0], [%1, {%3, %4, %5}], [%2];"
               ::"r"(dst), "l"(m), "r"(bar), "r"(c0), "r"(c1), "r"(c2) : "memory");
}
__device__ __forceinline__ void tma_ld5(uint32_t dst, const CUtensorMap* m, int c0, int c4, uint32_t bar) {
  asm volatile("cp.async.bulk.tensor.5d.shared::cluster.global.mbarrier::complete_tx::bytes [%0], [%1, {%3, 0, 0, 0, %4}], [%2];"
               ::"r"(dst), "l"(m), "r"(bar), "r"(c0), "r"(c4) : "memory");
}
__device__ __forceinline__ void tma_prefetch5(const CUtensorMap* m, int c0, int c4) {
  asm volatile("cp.async.bulk.prefetch.tensor.5d.L2.global.tile [%0, {%1, 0, 0, 0, %2}];" ::"l"(m), "r"(c0), "r"(c4) : "memory");
}
__device__ __forceinline__ void tma_prefetch2(const CUtensorMap* m, int c0, int c1) {
  asm volatile("cp.async.bulk.prefetch.tensor.2d.L2.global.tile [%0, {%1, %2}];" ::"l"(m), "r"(c0), "r"(c1) : "memory");
}
__device__ __forceinline__ void tma_prefetch3(const CUtensorMap* m, int c0, int c1, int c2) {
  asm volatile("cp.async.bulk.prefetch.tensor.3d.L2.global.tile [%0, {%1, %2, %3}];" ::"l"(m), "r"(c0), "r"(c1), "r"(c2) : "memory");
}
__device__ __forceinline__ void tma_st(const CUtensorMap* m, int c0, int c1, uint32_t src) {
  asm volatile("cp.async.bulk.tensor.2d.global.shared::cta.bulk_group [%0, {%2, %3}], [%1];" ::"l"(m), "r"(src), "r"(c0), "r"(c1) : "memory");
}
__device__ __forceinline__ void bulk_ld(uint32_t dst, const void* src, int bytes, uint32_t bar) {
  asm volatile("cp.async.bulk.shared::cluster.global.mbarrier::complete_tx::bytes [%0], [%1], %2, [%3];" ::"r"(dst), "l"(src), "r"(bytes), "r"(bar) : "memory");
}
__device__ __forceinline__ void bulk_st(void* dst, uint32_t src, int bytes) {
  asm volatile("cp.async.bulk.global.shared::cta.bulk_group [%0], [%1], %2;" ::"l"(dst), "r"(src), "r"(bytes) : "memory");
}
__device__ __forceinline__ void bulk_red_add_f32(void* dst, uint32_t src, int bytes) {
  asm volatile("cp.reduce.async.bulk.global.shared::cta.bulk_group.add.f32 [%0], [%1], %2;" ::"l"(dst), "r"(src), "r"(bytes) : "memory");
}
__device__ __forceinline__ void bulk_commit() { asm volatile("cp.async.bulk.commit_group;" ::: "memory"); }
__device__ __forceinline__ void bulk_wait_all() { asm volatile("cp.async.bulk.wait_group 0;" ::: "memory"); }
__device__ __forceinline__ void fence_async_smem() { asm volatile("fence.proxy.async.shared::cta;" ::: "memory"); }
__device__ __forceinline__ void fence_async_global() { asm volatile("fence.proxy.async.global;" ::: "memory"); }
__device__ __forceinline__ void bar_sync(int id, int n) { asm volatile("bar.sync %0, %1;" ::"r"(id), "r"(n) : "memory"); }
__device__ __forceinline__ void bar_arrive(int id, int n) { asm volatile("bar.arrive %0, %1;" ::"r"(id), "r"(n) : "memory"); }
__device__ __forceinline__ bool bar_or(int id, int n, bool v) {
  uint32_t r;
  asm volatile("{\n.reg .pred p, q;\nsetp.ne.u32 q, %3, 0;\nbar.red.or.pred p, %1, %2, q;\nselp.u32 %0, 1, 0, p;\n}" : "=r"(r) : "r"(id), "r"(n), "r"((uint32_t)v) : "memory");
  return r != 0;
}
__device__ __forceinline__ void bulk_wait_read() { asm volatile("cp.async.bulk.wait_group.read 0;" ::: "memory"); }
__device__ __forceinline__ void stg128(void* p, uint4 v) { asm volatile("st.relaxed.gpu.global.v4.u32 [%0], {%1,%2,%3,%4};" ::"l"(p), "r"(v.x), "r"(v.y), "r"(v.z), "r"(v.w) : "memory"); }
constexpr uint32_t UNSET = 0xffffffffu;
constexpr int MAX_RETRY = 1 << 16;
__device__ __forceinline__ void wg_fence() { asm volatile("wgmma.fence.sync.aligned;" ::: "memory"); }
__device__ __forceinline__ void wg_commit() { asm volatile("wgmma.commit_group.sync.aligned;" ::: "memory"); }
template <int N> __device__ __forceinline__ void wg_wait() { asm volatile("wgmma.wait_group.sync.aligned %0;" ::"n"(N) : "memory"); }
__device__ __forceinline__ uint64_t mkdesc(uint32_t addr, uint32_t lbo, uint32_t sbo, int sw) {
  return (uint64_t)((addr & 0x3FFFF) >> 4) | ((uint64_t)(lbo >> 4) << 16) | ((uint64_t)(sbo >> 4) << 32) | ((uint64_t)sw << 62);
}
__device__ __forceinline__ void ldsm4(uint32_t* r, uint32_t a) {
  asm volatile("ldmatrix.sync.aligned.m8n8.x4.shared.b16 {%0,%1,%2,%3}, [%4];" : "=r"(r[0]), "=r"(r[1]), "=r"(r[2]), "=r"(r[3]) : "r"(a) : "memory");
}
__device__ __forceinline__ void ldsm4t(uint32_t* r, uint32_t a) {
  asm volatile("ldmatrix.sync.aligned.m8n8.x4.trans.shared.b16 {%0,%1,%2,%3}, [%4];" : "=r"(r[0]), "=r"(r[1]), "=r"(r[2]), "=r"(r[3]) : "r"(a) : "memory");
}
__device__ __forceinline__ void stsm4(uint32_t a, uint32_t r0, uint32_t r1, uint32_t r2, uint32_t r3) {
  asm volatile("stmatrix.sync.aligned.m8n8.x4.shared.b16 [%0], {%1,%2,%3,%4};" ::"r"(a), "r"(r0), "r"(r1), "r"(r2), "r"(r3) : "memory");
}
__device__ __forceinline__ void stsm4t(uint32_t a, uint32_t r0, uint32_t r1, uint32_t r2, uint32_t r3) {
  asm volatile("stmatrix.sync.aligned.m8n8.x4.trans.shared.b16 [%0], {%1,%2,%3,%4};" ::"r"(a), "r"(r0), "r"(r1), "r"(r2), "r"(r3) : "memory");
}
__device__ __forceinline__ uint32_t movm_t(uint32_t a) { uint32_t r; asm volatile("movmatrix.sync.aligned.m8n8.trans.b16 %0, %1;" : "=r"(r) : "r"(a)); return r; }
__device__ __forceinline__ uint32_t lds32(uint32_t a) { uint32_t v; asm volatile("ld.shared.b32 %0, [%1];" : "=r"(v) : "r"(a) : "memory"); return v; }
__device__ __forceinline__ float2 lds64f(uint32_t a) { float2 v; asm volatile("ld.shared.v2.f32 {%0,%1}, [%2];" : "=f"(v.x), "=f"(v.y) : "r"(a) : "memory"); return v; }
__device__ __forceinline__ float4 lds128f(uint32_t a) { float4 v; asm volatile("ld.shared.v4.f32 {%0,%1,%2,%3}, [%4];" : "=f"(v.x), "=f"(v.y), "=f"(v.z), "=f"(v.w) : "r"(a) : "memory"); return v; }
__device__ __forceinline__ uint4 lds128(uint32_t a) { uint4 v; asm volatile("ld.shared.v4.b32 {%0,%1,%2,%3}, [%4];" : "=r"(v.x), "=r"(v.y), "=r"(v.z), "=r"(v.w) : "r"(a) : "memory"); return v; }
__device__ __forceinline__ void sts128(uint32_t a, uint4 v) { asm volatile("st.shared.v4.b32 [%0], {%1,%2,%3,%4};" ::"r"(a), "r"(v.x), "r"(v.y), "r"(v.z), "r"(v.w) : "memory"); }
__device__ __forceinline__ void sts128f(uint32_t a, float x, float y, float z, float w) { asm volatile("st.shared.v4.f32 [%0], {%1,%2,%3,%4};" ::"r"(a), "f"(x), "f"(y), "f"(z), "f"(w) : "memory"); }
__device__ __forceinline__ void sts32f(uint32_t a, float v) { asm volatile("st.shared.f32 [%0], %1;" ::"r"(a), "f"(v) : "memory"); }
__device__ __forceinline__ void sts16(uint32_t a, uint16_t v) { asm volatile("st.shared.u16 [%0], %1;" ::"r"(a), "h"(v) : "memory"); }
__device__ __forceinline__ uint32_t lds16(uint32_t a) { uint16_t v; asm volatile("ld.shared.u16 %0, [%1];" : "=h"(v) : "r"(a) : "memory"); return v; }
__device__ __forceinline__ uint32_t packbf(float lo, float hi) { uint32_t r; asm("cvt.rn.bf16x2.f32 %0, %1, %2;" : "=r"(r) : "f"(hi), "f"(lo)); return r; }
__device__ __forceinline__ float bf_lo(uint32_t v) { return __uint_as_float(v << 16); }
__device__ __forceinline__ float bf_hi(uint32_t v) { return __uint_as_float(v & 0xffff0000u); }
__device__ __forceinline__ float ex2(float x) { float r; asm("ex2.approx.ftz.f32 %0, %1;" : "=f"(r) : "f"(x)); return r; }
__device__ __forceinline__ float rsqrt_approx(float x) { float r; asm("rsqrt.approx.ftz.f32 %0, %1;" : "=f"(r) : "f"(x)); return r; }
__device__ __forceinline__ float rcp_approx(float x) { float r; asm("rcp.approx.ftz.f32 %0, %1;" : "=f"(r) : "f"(x)); return r; }
__device__ __forceinline__ void mma_bf16(float* d, const uint32_t* a, uint32_t b0, uint32_t b1) {
  asm("mma.sync.aligned.m16n8k16.row.col.f32.bf16.bf16.f32 {%0,%1,%2,%3}, {%4,%5,%6,%7}, {%8,%9}, {%0,%1,%2,%3};"
               : "+f"(d[0]), "+f"(d[1]), "+f"(d[2]), "+f"(d[3]) : "r"(a[0]), "r"(a[1]), "r"(a[2]), "r"(a[3]), "r"(b0), "r"(b1));
}
__device__ __forceinline__ void mma_tf32(float* d, float a0, float a1, float a2, float a3, float b0, float b1) {
  asm("mma.sync.aligned.m16n8k8.row.col.f32.tf32.tf32.f32 {%0,%1,%2,%3}, {%4,%5,%6,%7}, {%8,%9}, {%0,%1,%2,%3};"
               : "+f"(d[0]), "+f"(d[1]), "+f"(d[2]), "+f"(d[3])
               : "r"(__float_as_uint(a0)), "r"(__float_as_uint(a1)), "r"(__float_as_uint(a2)), "r"(__float_as_uint(a3)),
                 "r"(__float_as_uint(b0)), "r"(__float_as_uint(b1)));
}
__device__ __forceinline__ void red_release(unsigned* p) { asm volatile("red.release.gpu.global.add.u32 [%0], 1;" ::"l"(p) : "memory"); }
__device__ __forceinline__ void red_relaxed(unsigned* p) { asm volatile("red.relaxed.gpu.global.add.u32 [%0], 1;" ::"l"(p) : "memory"); }
__device__ __forceinline__ unsigned ld_relaxed(const unsigned* p) { unsigned v; asm volatile("ld.relaxed.gpu.global.u32 %0, [%1];" : "=r"(v) : "l"(p) : "memory"); return v; }
__device__ __forceinline__ void spin_until(const unsigned* p, unsigned target) {
  int it = 0;
  while ((int)(ld_relaxed(p) - target) < 0) {
    if (++it > (1 << 23)) __trap();
  }
}
__device__ __forceinline__ uint4 ldcg128(const void* p) { uint4 v; asm volatile("ld.global.cg.v4.b32 {%0,%1,%2,%3}, [%4];" : "=r"(v.x), "=r"(v.y), "=r"(v.z), "=r"(v.w) : "l"(p) : "memory"); return v; }
__device__ __forceinline__ uint4 ld_tagged(const uint4* p) { uint4 v; asm volatile("ld.relaxed.gpu.global.v4.u32 {%0,%1,%2,%3}, [%4];" : "=r"(v.x), "=r"(v.y), "=r"(v.z), "=r"(v.w) : "l"(p) : "memory"); return v; }
__device__ __forceinline__ void st_tagged(uint4* p, uint32_t a, uint32_t b, uint32_t tag) { asm volatile("st.relaxed.gpu.global.v4.u32 [%0], {%1,%2,%3,%2};" ::"l"(p), "r"(a), "r"(tag), "r"(b) : "memory"); }
__device__ __forceinline__ void st_tagged3(uint4* p, uint32_t a, uint32_t b, uint32_t c, uint32_t tag) { asm volatile("st.relaxed.gpu.global.v4.u32 [%0], {%1,%2,%3,%4};" ::"l"(p), "r"(a), "r"(b), "r"(c), "r"(tag) : "memory"); }
__device__ __forceinline__ uint4 poll_tagged(const uint4* p, uint32_t tag) {
  uint4 v = ld_tagged(p);
  int it = 0;
  while (v.y != tag || v.w != tag) {
    if (++it > (1 << 22)) __trap();
    v = ld_tagged(p);
  }
  return v;
}
__device__ __forceinline__ uint32_t hadd2(uint32_t a, uint32_t b) { uint32_t r; asm("add.rn.bf16x2 %0, %1, %2;" : "=r"(r) : "r"(a), "r"(b)); return r; }
__device__ __forceinline__ uint32_t hmul2(uint32_t a, uint32_t b) { uint32_t r; asm("mul.rn.bf16x2 %0, %1, %2;" : "=r"(r) : "r"(a), "r"(b)); return r; }

__device__ __forceinline__ uint32_t hfma2(uint32_t a, uint32_t b, uint32_t c) { uint32_t r; asm("fma.rn.bf16x2 %0, %1, %2, %3;" : "=r"(r) : "r"(a), "r"(b), "r"(c)); return r; }
__device__ __forceinline__ void sts32(uint32_t a, uint32_t v) { asm volatile("st.shared.u32 [%0], %1;" ::"r"(a), "r"(v) : "memory"); }

template <int N> __device__ __forceinline__ void acc_fence(float* a) {
#pragma unroll
  for (int i = 0; i < N; i++) asm volatile("" : "+f"(a[i]) :: "memory");
}

template<int N,int TB> __device__ __forceinline__ void wgmma_rs(float* d, const uint32_t* a, uint64_t db, int sd);
template<int N,int TA,int TB> __device__ __forceinline__ void wgmma_ss(float* d, uint64_t da, uint64_t db, int sd);
template<> __device__ __forceinline__ void wgmma_rs<64,0>(float* d, const uint32_t* a, uint64_t db, int sd) {
  asm volatile("{\n.reg .pred p;\nsetp.ne.b32 p, %37, 0;\nwgmma.mma_async.sync.aligned.m64n64k16.f32.bf16.bf16 {%0,%1,%2,%3,%4,%5,%6,%7,%8,%9,%10,%11,%12,%13,%14,%15,%16,%17,%18,%19,%20,%21,%22,%23,%24,%25,%26,%27,%28,%29,%30,%31}, {%32,%33,%34,%35}, %36, p, 1, 1, 0;\n}\n"
   : "+f"(d[0]),"+f"(d[1]),"+f"(d[2]),"+f"(d[3]),"+f"(d[4]),"+f"(d[5]),"+f"(d[6]),"+f"(d[7]),"+f"(d[8]),"+f"(d[9]),"+f"(d[10]),"+f"(d[11]),"+f"(d[12]),"+f"(d[13]),"+f"(d[14]),"+f"(d[15]),"+f"(d[16]),"+f"(d[17]),"+f"(d[18]),"+f"(d[19]),"+f"(d[20]),"+f"(d[21]),"+f"(d[22]),"+f"(d[23]),"+f"(d[24]),"+f"(d[25]),"+f"(d[26]),"+f"(d[27]),"+f"(d[28]),"+f"(d[29]),"+f"(d[30]),"+f"(d[31])
   : "r"(a[0]), "r"(a[1]), "r"(a[2]), "r"(a[3]), "l"(db), "r"(sd));
}
template<> __device__ __forceinline__ void wgmma_rs<56,0>(float* d, const uint32_t* a, uint64_t db, int sd) {
  asm volatile("{\n.reg .pred p;\nsetp.ne.b32 p, %33, 0;\nwgmma.mma_async.sync.aligned.m64n56k16.f32.bf16.bf16 {%0,%1,%2,%3,%4,%5,%6,%7,%8,%9,%10,%11,%12,%13,%14,%15,%16,%17,%18,%19,%20,%21,%22,%23,%24,%25,%26,%27}, {%28,%29,%30,%31}, %32, p, 1, 1, 0;\n}\n"
   : "+f"(d[0]),"+f"(d[1]),"+f"(d[2]),"+f"(d[3]),"+f"(d[4]),"+f"(d[5]),"+f"(d[6]),"+f"(d[7]),"+f"(d[8]),"+f"(d[9]),"+f"(d[10]),"+f"(d[11]),"+f"(d[12]),"+f"(d[13]),"+f"(d[14]),"+f"(d[15]),"+f"(d[16]),"+f"(d[17]),"+f"(d[18]),"+f"(d[19]),"+f"(d[20]),"+f"(d[21]),"+f"(d[22]),"+f"(d[23]),"+f"(d[24]),"+f"(d[25]),"+f"(d[26]),"+f"(d[27])
   : "r"(a[0]), "r"(a[1]), "r"(a[2]), "r"(a[3]), "l"(db), "r"(sd));
}
template<> __device__ __forceinline__ void wgmma_rs<48,0>(float* d, const uint32_t* a, uint64_t db, int sd) {
  asm volatile("{\n.reg .pred p;\nsetp.ne.b32 p, %29, 0;\nwgmma.mma_async.sync.aligned.m64n48k16.f32.bf16.bf16 {%0,%1,%2,%3,%4,%5,%6,%7,%8,%9,%10,%11,%12,%13,%14,%15,%16,%17,%18,%19,%20,%21,%22,%23}, {%24,%25,%26,%27}, %28, p, 1, 1, 0;\n}\n"
   : "+f"(d[0]),"+f"(d[1]),"+f"(d[2]),"+f"(d[3]),"+f"(d[4]),"+f"(d[5]),"+f"(d[6]),"+f"(d[7]),"+f"(d[8]),"+f"(d[9]),"+f"(d[10]),"+f"(d[11]),"+f"(d[12]),"+f"(d[13]),"+f"(d[14]),"+f"(d[15]),"+f"(d[16]),"+f"(d[17]),"+f"(d[18]),"+f"(d[19]),"+f"(d[20]),"+f"(d[21]),"+f"(d[22]),"+f"(d[23])
   : "r"(a[0]), "r"(a[1]), "r"(a[2]), "r"(a[3]), "l"(db), "r"(sd));
}
template<> __device__ __forceinline__ void wgmma_rs<40,0>(float* d, const uint32_t* a, uint64_t db, int sd) {
  asm volatile("{\n.reg .pred p;\nsetp.ne.b32 p, %25, 0;\nwgmma.mma_async.sync.aligned.m64n40k16.f32.bf16.bf16 {%0,%1,%2,%3,%4,%5,%6,%7,%8,%9,%10,%11,%12,%13,%14,%15,%16,%17,%18,%19}, {%20,%21,%22,%23}, %24, p, 1, 1, 0;\n}\n"
   : "+f"(d[0]),"+f"(d[1]),"+f"(d[2]),"+f"(d[3]),"+f"(d[4]),"+f"(d[5]),"+f"(d[6]),"+f"(d[7]),"+f"(d[8]),"+f"(d[9]),"+f"(d[10]),"+f"(d[11]),"+f"(d[12]),"+f"(d[13]),"+f"(d[14]),"+f"(d[15]),"+f"(d[16]),"+f"(d[17]),"+f"(d[18]),"+f"(d[19])
   : "r"(a[0]), "r"(a[1]), "r"(a[2]), "r"(a[3]), "l"(db), "r"(sd));
}
template<> __device__ __forceinline__ void wgmma_rs<32,0>(float* d, const uint32_t* a, uint64_t db, int sd) {
  asm volatile("{\n.reg .pred p;\nsetp.ne.b32 p, %21, 0;\nwgmma.mma_async.sync.aligned.m64n32k16.f32.bf16.bf16 {%0,%1,%2,%3,%4,%5,%6,%7,%8,%9,%10,%11,%12,%13,%14,%15}, {%16,%17,%18,%19}, %20, p, 1, 1, 0;\n}\n"
   : "+f"(d[0]),"+f"(d[1]),"+f"(d[2]),"+f"(d[3]),"+f"(d[4]),"+f"(d[5]),"+f"(d[6]),"+f"(d[7]),"+f"(d[8]),"+f"(d[9]),"+f"(d[10]),"+f"(d[11]),"+f"(d[12]),"+f"(d[13]),"+f"(d[14]),"+f"(d[15])
   : "r"(a[0]), "r"(a[1]), "r"(a[2]), "r"(a[3]), "l"(db), "r"(sd));
}
template<> __device__ __forceinline__ void wgmma_rs<24,0>(float* d, const uint32_t* a, uint64_t db, int sd) {
  asm volatile("{\n.reg .pred p;\nsetp.ne.b32 p, %17, 0;\nwgmma.mma_async.sync.aligned.m64n24k16.f32.bf16.bf16 {%0,%1,%2,%3,%4,%5,%6,%7,%8,%9,%10,%11}, {%12,%13,%14,%15}, %16, p, 1, 1, 0;\n}\n"
   : "+f"(d[0]),"+f"(d[1]),"+f"(d[2]),"+f"(d[3]),"+f"(d[4]),"+f"(d[5]),"+f"(d[6]),"+f"(d[7]),"+f"(d[8]),"+f"(d[9]),"+f"(d[10]),"+f"(d[11])
   : "r"(a[0]), "r"(a[1]), "r"(a[2]), "r"(a[3]), "l"(db), "r"(sd));
}
template<> __device__ __forceinline__ void wgmma_rs<16,0>(float* d, const uint32_t* a, uint64_t db, int sd) {
  asm volatile("{\n.reg .pred p;\nsetp.ne.b32 p, %13, 0;\nwgmma.mma_async.sync.aligned.m64n16k16.f32.bf16.bf16 {%0,%1,%2,%3,%4,%5,%6,%7}, {%8,%9,%10,%11}, %12, p, 1, 1, 0;\n}\n"
   : "+f"(d[0]),"+f"(d[1]),"+f"(d[2]),"+f"(d[3]),"+f"(d[4]),"+f"(d[5]),"+f"(d[6]),"+f"(d[7])
   : "r"(a[0]), "r"(a[1]), "r"(a[2]), "r"(a[3]), "l"(db), "r"(sd));
}
template<> __device__ __forceinline__ void wgmma_rs<8,0>(float* d, const uint32_t* a, uint64_t db, int sd) {
  asm volatile("{\n.reg .pred p;\nsetp.ne.b32 p, %9, 0;\nwgmma.mma_async.sync.aligned.m64n8k16.f32.bf16.bf16 {%0,%1,%2,%3}, {%4,%5,%6,%7}, %8, p, 1, 1, 0;\n}\n"
   : "+f"(d[0]),"+f"(d[1]),"+f"(d[2]),"+f"(d[3])
   : "r"(a[0]), "r"(a[1]), "r"(a[2]), "r"(a[3]), "l"(db), "r"(sd));
}
template<> __device__ __forceinline__ void wgmma_ss<64,1,0>(float* d, uint64_t da, uint64_t db, int sd) {
  asm volatile("{\n.reg .pred p;\nsetp.ne.b32 p, %34, 0;\nwgmma.mma_async.sync.aligned.m64n64k16.f32.bf16.bf16 {%0,%1,%2,%3,%4,%5,%6,%7,%8,%9,%10,%11,%12,%13,%14,%15,%16,%17,%18,%19,%20,%21,%22,%23,%24,%25,%26,%27,%28,%29,%30,%31}, %32, %33, p, 1, 1, 1, 0;\n}\n"
   : "+f"(d[0]),"+f"(d[1]),"+f"(d[2]),"+f"(d[3]),"+f"(d[4]),"+f"(d[5]),"+f"(d[6]),"+f"(d[7]),"+f"(d[8]),"+f"(d[9]),"+f"(d[10]),"+f"(d[11]),"+f"(d[12]),"+f"(d[13]),"+f"(d[14]),"+f"(d[15]),"+f"(d[16]),"+f"(d[17]),"+f"(d[18]),"+f"(d[19]),"+f"(d[20]),"+f"(d[21]),"+f"(d[22]),"+f"(d[23]),"+f"(d[24]),"+f"(d[25]),"+f"(d[26]),"+f"(d[27]),"+f"(d[28]),"+f"(d[29]),"+f"(d[30]),"+f"(d[31])
   : "l"(da), "l"(db), "r"(sd));
}
template<> __device__ __forceinline__ void wgmma_ss<64,0,1>(float* d, uint64_t da, uint64_t db, int sd) {
  asm volatile("{\n.reg .pred p;\nsetp.ne.b32 p, %34, 0;\nwgmma.mma_async.sync.aligned.m64n64k16.f32.bf16.bf16 {%0,%1,%2,%3,%4,%5,%6,%7,%8,%9,%10,%11,%12,%13,%14,%15,%16,%17,%18,%19,%20,%21,%22,%23,%24,%25,%26,%27,%28,%29,%30,%31}, %32, %33, p, 1, 1, 0, 1;\n}\n"
   : "+f"(d[0]),"+f"(d[1]),"+f"(d[2]),"+f"(d[3]),"+f"(d[4]),"+f"(d[5]),"+f"(d[6]),"+f"(d[7]),"+f"(d[8]),"+f"(d[9]),"+f"(d[10]),"+f"(d[11]),"+f"(d[12]),"+f"(d[13]),"+f"(d[14]),"+f"(d[15]),"+f"(d[16]),"+f"(d[17]),"+f"(d[18]),"+f"(d[19]),"+f"(d[20]),"+f"(d[21]),"+f"(d[22]),"+f"(d[23]),"+f"(d[24]),"+f"(d[25]),"+f"(d[26]),"+f"(d[27]),"+f"(d[28]),"+f"(d[29]),"+f"(d[30]),"+f"(d[31])
   : "l"(da), "l"(db), "r"(sd));
}
template<> __device__ __forceinline__ void wgmma_ss<192,0,1>(float* d, uint64_t da, uint64_t db, int sd) {
  asm volatile("{\n.reg .pred p;\nsetp.ne.b32 p, %98, 0;\nwgmma.mma_async.sync.aligned.m64n192k16.f32.bf16.bf16 {%0,%1,%2,%3,%4,%5,%6,%7,%8,%9,%10,%11,%12,%13,%14,%15,%16,%17,%18,%19,%20,%21,%22,%23,%24,%25,%26,%27,%28,%29,%30,%31,%32,%33,%34,%35,%36,%37,%38,%39,%40,%41,%42,%43,%44,%45,%46,%47,%48,%49,%50,%51,%52,%53,%54,%55,%56,%57,%58,%59,%60,%61,%62,%63,%64,%65,%66,%67,%68,%69,%70,%71,%72,%73,%74,%75,%76,%77,%78,%79,%80,%81,%82,%83,%84,%85,%86,%87,%88,%89,%90,%91,%92,%93,%94,%95}, %96, %97, p, 1, 1, 0, 1;\n}\n"
   : "+f"(d[0]),"+f"(d[1]),"+f"(d[2]),"+f"(d[3]),"+f"(d[4]),"+f"(d[5]),"+f"(d[6]),"+f"(d[7]),"+f"(d[8]),"+f"(d[9]),"+f"(d[10]),"+f"(d[11]),"+f"(d[12]),"+f"(d[13]),"+f"(d[14]),"+f"(d[15]),"+f"(d[16]),"+f"(d[17]),"+f"(d[18]),"+f"(d[19]),"+f"(d[20]),"+f"(d[21]),"+f"(d[22]),"+f"(d[23]),"+f"(d[24]),"+f"(d[25]),"+f"(d[26]),"+f"(d[27]),"+f"(d[28]),"+f"(d[29]),"+f"(d[30]),"+f"(d[31]),"+f"(d[32]),"+f"(d[33]),"+f"(d[34]),"+f"(d[35]),"+f"(d[36]),"+f"(d[37]),"+f"(d[38]),"+f"(d[39]),"+f"(d[40]),"+f"(d[41]),"+f"(d[42]),"+f"(d[43]),"+f"(d[44]),"+f"(d[45]),"+f"(d[46]),"+f"(d[47]),"+f"(d[48]),"+f"(d[49]),"+f"(d[50]),"+f"(d[51]),"+f"(d[52]),"+f"(d[53]),"+f"(d[54]),"+f"(d[55]),"+f"(d[56]),"+f"(d[57]),"+f"(d[58]),"+f"(d[59]),"+f"(d[60]),"+f"(d[61]),"+f"(d[62]),"+f"(d[63]),"+f"(d[64]),"+f"(d[65]),"+f"(d[66]),"+f"(d[67]),"+f"(d[68]),"+f"(d[69]),"+f"(d[70]),"+f"(d[71]),"+f"(d[72]),"+f"(d[73]),"+f"(d[74]),"+f"(d[75]),"+f"(d[76]),"+f"(d[77]),"+f"(d[78]),"+f"(d[79]),"+f"(d[80]),"+f"(d[81]),"+f"(d[82]),"+f"(d[83]),"+f"(d[84]),"+f"(d[85]),"+f"(d[86]),"+f"(d[87]),"+f"(d[88]),"+f"(d[89]),"+f"(d[90]),"+f"(d[91]),"+f"(d[92]),"+f"(d[93]),"+f"(d[94]),"+f"(d[95])
   : "l"(da), "l"(db), "r"(sd));
}
template<> __device__ __forceinline__ void wgmma_ss<192,1,1>(float* d, uint64_t da, uint64_t db, int sd) {
  asm volatile("{\n.reg .pred p;\nsetp.ne.b32 p, %98, 0;\nwgmma.mma_async.sync.aligned.m64n192k16.f32.bf16.bf16 {%0,%1,%2,%3,%4,%5,%6,%7,%8,%9,%10,%11,%12,%13,%14,%15,%16,%17,%18,%19,%20,%21,%22,%23,%24,%25,%26,%27,%28,%29,%30,%31,%32,%33,%34,%35,%36,%37,%38,%39,%40,%41,%42,%43,%44,%45,%46,%47,%48,%49,%50,%51,%52,%53,%54,%55,%56,%57,%58,%59,%60,%61,%62,%63,%64,%65,%66,%67,%68,%69,%70,%71,%72,%73,%74,%75,%76,%77,%78,%79,%80,%81,%82,%83,%84,%85,%86,%87,%88,%89,%90,%91,%92,%93,%94,%95}, %96, %97, p, 1, 1, 1, 1;\n}\n"
   : "+f"(d[0]),"+f"(d[1]),"+f"(d[2]),"+f"(d[3]),"+f"(d[4]),"+f"(d[5]),"+f"(d[6]),"+f"(d[7]),"+f"(d[8]),"+f"(d[9]),"+f"(d[10]),"+f"(d[11]),"+f"(d[12]),"+f"(d[13]),"+f"(d[14]),"+f"(d[15]),"+f"(d[16]),"+f"(d[17]),"+f"(d[18]),"+f"(d[19]),"+f"(d[20]),"+f"(d[21]),"+f"(d[22]),"+f"(d[23]),"+f"(d[24]),"+f"(d[25]),"+f"(d[26]),"+f"(d[27]),"+f"(d[28]),"+f"(d[29]),"+f"(d[30]),"+f"(d[31]),"+f"(d[32]),"+f"(d[33]),"+f"(d[34]),"+f"(d[35]),"+f"(d[36]),"+f"(d[37]),"+f"(d[38]),"+f"(d[39]),"+f"(d[40]),"+f"(d[41]),"+f"(d[42]),"+f"(d[43]),"+f"(d[44]),"+f"(d[45]),"+f"(d[46]),"+f"(d[47]),"+f"(d[48]),"+f"(d[49]),"+f"(d[50]),"+f"(d[51]),"+f"(d[52]),"+f"(d[53]),"+f"(d[54]),"+f"(d[55]),"+f"(d[56]),"+f"(d[57]),"+f"(d[58]),"+f"(d[59]),"+f"(d[60]),"+f"(d[61]),"+f"(d[62]),"+f"(d[63]),"+f"(d[64]),"+f"(d[65]),"+f"(d[66]),"+f"(d[67]),"+f"(d[68]),"+f"(d[69]),"+f"(d[70]),"+f"(d[71]),"+f"(d[72]),"+f"(d[73]),"+f"(d[74]),"+f"(d[75]),"+f"(d[76]),"+f"(d[77]),"+f"(d[78]),"+f"(d[79]),"+f"(d[80]),"+f"(d[81]),"+f"(d[82]),"+f"(d[83]),"+f"(d[84]),"+f"(d[85]),"+f"(d[86]),"+f"(d[87]),"+f"(d[88]),"+f"(d[89]),"+f"(d[90]),"+f"(d[91]),"+f"(d[92]),"+f"(d[93]),"+f"(d[94]),"+f"(d[95])
   : "l"(da), "l"(db), "r"(sd));
}

template <bool TR>
__device__ __forceinline__ void gemm_section(float* acc, float& mean0, float& mean1, float& rstd0, float& rstd1,
                                             uint32_t sb, int blk, int hg, int wg, int w, int lane) {
  constexpr int layer = TR ? 1 : 0;
  constexpr int TURN = TR ? TURN1 : TURN0;
  constexpr int LSTAT = TURN < 4 ? TURN - 1 : 3;
  const uint32_t bar = sb + SM_BAR;
  const int g = lane >> 2, t = lane & 3;
  const bool leader = (w == 0) && (lane == 0);
  const int statpos = hg < 3 ? 1 : wg ? LSTAT : 2;
  const bool copy = hg >= 3 && wg == 0;
  const int cut = wg ? TURN : 4;
  auto wait_full = [&](int c) {
    mbar_wait(bar + 8 * (B_XF + 8 * wg + c), layer);
    mbar_wait(bar + 8 * (B_WF + c), layer);
  };
  auto peek = [&](int c) {
    const bool x = mbar_test(bar + 8 * (B_XF + 8 * wg + c), layer), y = mbar_test(bar + 8 * (B_WF + c), layer);
    return x && y;
  };
  const uint64_t da0 = mkdesc(sb, TR ? 8192 : 16, 1024, 1), db0 = mkdesc(sb, 8192, 1024, 1);
  uint32_t xt = wg ? 0xfedcba98u : 0x21043210u;
  uint64_t wt = 0x0816131005161310ull;
  uint64_t da = da0 + ((xt & 15) << 9), db = db0 + (16 << 9);
  auto issue = [&](int c, int first) {
    TSG(2 * c);
    wg_fence();
#pragma unroll
    for (int ks = 0; ks < 4; ks++) wgmma_ss<192, TR ? 1 : 0, 1>(acc, da + (TR ? ks * 128 : ks * 2), db + ks * 128, !first || ks != 0);
    wg_commit();
    xt >>= 4; wt >>= 8;
    da = da0 + ((xt & 15) << 9); db = db0 + (((uint32_t)wt & 31) << 9);
    TSG(2 * c + 1);
  };
  uint32_t tag = 0;
  wait_full(0);
  bool ready = peek(1);
  issue(0, 1);
  TSW(0);
#pragma unroll 1
  for (int c = 1; c < cut; c++) {
    if (!ready) wait_full(c);
    issue(c, 0);
    ready = peek(c + 1);
    wg_wait<1>();
    if (leader) mbar_arrive(bar + 8 * (B_DN + 8 * wg + c - 1));
    if (wg == 1 && c == cut - 1) {
      wg_wait<0>();
      if (leader) mbar_arrive(bar + 8 * (B_DN + 8 + c));
    }
    if (c == statpos) {
      mbar_wait(bar + 8 * B_EP, 0);
      tag = 2 * lds32(sb + SM_EP) + layer + 1;
      mbar_wait(bar + 8 * (copy ? B_SC : B_XF + 8 * wg + hg), layer);
      uint32_t A[16];
      const uint32_t xb = sb + (copy ? P_R : 8 * wg + hg) * PG;
#pragma unroll
      for (int ks = 0; ks < 4; ks++) {
        if (!TR) {
          const int row = 16 * w + (lane & 15), kc = 2 * ks + (lane >> 4);
          ldsm4(&A[4 * ks], xb + row * 128 + ((kc ^ (row & 7)) << 4));
        } else {
          const int k = 16 * ks + (lane & 7) + 8 * (lane >> 4), pc = 2 * w + ((lane >> 3) & 1);
          ldsm4t(&A[4 * ks], xb + k * 128 + ((pc ^ (k & 7)) << 4));
        }
      }
      float s0 = 0.f, q0 = 0.f, s1 = 0.f, q1 = 0.f;
#pragma unroll
      for (int i = 0; i < 16; i += 2) {
        const float a = bf_lo(A[i]), b = bf_hi(A[i]), c_ = bf_lo(A[i + 1]), d = bf_hi(A[i + 1]);
        s0 += a + b; q0 = fmaf(a, a, q0); q0 = fmaf(b, b, q0);
        s1 += c_ + d; q1 = fmaf(c_, c_, q1); q1 = fmaf(d, d, q1);
      }
#pragma unroll
      for (int o = 1; o <= 2; o <<= 1) {
        s0 += __shfl_xor_sync(~0u, s0, o); q0 += __shfl_xor_sync(~0u, q0, o);
        s1 += __shfl_xor_sync(~0u, s1, o); q1 += __shfl_xor_sync(~0u, q1, o);
      }
      if (t < 2)
        st_tagged(&g_part[((layer * 32 + blk) * 8 + hg) * 64 + 16 * w + g + 8 * t], __float_as_uint(t ? s1 : s0), __float_as_uint(t ? q1 : q0), tag);
    }
  }
  if (wg == 1) mbar_wait(bar + 8 * (B_DN + GPOS), layer);
  else if (!ready) { wait_full(cut); ready = true; }
  const uint4* psrc = &g_part[((layer * 32 + blk) * 8 + 2 * t) * 64 + 16 * w + g];
  uint4 a0 = ld_tagged(psrc), a1 = ld_tagged(psrc + 8), b0 = ld_tagged(psrc + 64), b1 = ld_tagged(psrc + 72);
  if (wg == 1) {
#pragma unroll 1
    for (int c = cut; c < 8; c++) wait_full(c);
    ready = true;
    bar_sync(5, 256);
  }
#pragma unroll 1
  for (int c = cut; c < 8; c++) {
    if (!ready) wait_full(c);
    issue(c, 0);
    if (wg == 1) {
      wg_wait<2>();
      if (leader && c >= cut + 2) mbar_arrive(bar + 8 * (B_DN + 8 + c - 2));
    } else if (c == 7) {
      bar_arrive(5, 256);
    } else {
      ready = peek(c + 1);
      wg_wait<1>();
      if (leader) mbar_arrive(bar + 8 * (B_DN + c - 1));
    }
  }
  int it = 0;
  while (!__all_sync(~0u, a0.y == tag && a0.w == tag && a1.y == tag && a1.w == tag && b0.y == tag && b0.w == tag && b1.y == tag && b1.w == tag) &&
         ++it < (1 << 20)) {
    a0 = ld_tagged(psrc); a1 = ld_tagged(psrc + 8); b0 = ld_tagged(psrc + 64); b1 = ld_tagged(psrc + 72);
  }
  float s0 = __uint_as_float(a0.x) + __uint_as_float(b0.x), q0 = __uint_as_float(a0.z) + __uint_as_float(b0.z);
  float s1 = __uint_as_float(a1.x) + __uint_as_float(b1.x), q1 = __uint_as_float(a1.z) + __uint_as_float(b1.z);
#pragma unroll
  for (int o = 1; o <= 2; o <<= 1) {
    s0 += __shfl_xor_sync(~0u, s0, o); q0 += __shfl_xor_sync(~0u, q0, o);
    s1 += __shfl_xor_sync(~0u, s1, o); q1 += __shfl_xor_sync(~0u, q1, o);
  }
  mean0 = s0 * (1.f / DM); mean1 = s1 * (1.f / DM);
  rstd0 = rsqrt_approx(fmaxf(q0 * (1.f / DM) - mean0 * mean0, 0.f) + 1e-5f);
  rstd1 = rsqrt_approx(fmaxf(q1 * (1.f / DM) - mean1 * mean1, 0.f) + 1e-5f);
  TSG(16);
  mbar_wait(bar + 8 * (TR ? B_RS : B_CSF), 0);
  wg_wait<0>();
  acc_fence<96>(acc);
  if (leader) mbar_arrive(bar + 8 * (B_DN + 8 * wg + 7));
}

__device__ __forceinline__ void attn_phase(const Params& p, uint32_t sb, int layer, int rb, int hg, int wg, int w) {
  const int lane = opaque_tid() & 31;
  const int g = lane >> 2, t = lane & 3;
  const uint32_t bar = sb + SM_BAR;
  const int blk = 16 * wg + rb;
  float acc[96];
  float2 cs[24];
  float mean0, mean1, rstd0, rstd1;
  if (layer) gemm_section<true>(acc, mean0, mean1, rstd0, rstd1, sb, blk, hg, wg, w, lane);
  else gemm_section<false>(acc, mean0, mean1, rstd0, rstd1, sb, blk, hg, wg, w, lane);
  TSW(1);
#pragma unroll
  for (int j = 8; j < 24; j++) cs[j] = lds64f(sb + SM_CS + 4 * (8 * j + 2 * t));
  const uint32_t kvx = sb + (wg ? 22 : 0) * PG;

  uint32_t kb[4][8], vb[4][8], qa[4][4];
  {
    const float nm0 = -mean0 * rstd0, nm1 = -mean1 * rstd1;
    const int st_row = 16 * w + (lane & 7) + 8 * ((lane >> 3) & 1);
    const uint32_t st_base = kvx + st_row * 256;
    const bool sender = (w == 3 && blk < 31);
    uint4* halo = &g_halo[((layer * 32 + blk) * 8 + hg) * 256 + lane];
    uint32_t r[4][2][4];
#pragma unroll
    for (int h = 0; h < 4; h++) {
#pragma unroll
      for (int kv = 0; kv < 2; kv++) {
#pragma unroll
        for (int dh = 0; dh < 2; dh++) {
          const int j = 8 + kv * 8 + 2 * h + dh;
          const float2 c2 = cs[j];
          const float v0 = fmaf(acc[4 * j + 0], rstd0, nm0 * c2.x), v1 = fmaf(acc[4 * j + 1], rstd0, nm0 * c2.y);
          const float v2 = fmaf(acc[4 * j + 2], rstd1, nm1 * c2.x), v3 = fmaf(acc[4 * j + 3], rstd1, nm1 * c2.y);
          r[h][kv][2 * dh] = packbf(v0, v1);
          r[h][kv][2 * dh + 1] = packbf(v2, v3);
        }
      }
      if (sender) {
        stg128(halo + (2 * h) * 32, make_uint4(r[h][0][0], r[h][0][2], r[h][0][1], r[h][0][3]));
        stg128(halo + (2 * h + 1) * 32, make_uint4(r[h][1][0], r[h][1][1], r[h][1][2], r[h][1][3]));
      }
    }
#pragma unroll
    for (int j = 0; j < 8; j++) cs[j] = lds64f(sb + SM_CS + 4 * (8 * j + 2 * t));
    mbar_wait(bar + 8 * (B_DN + 7), layer);
#pragma unroll
    for (int h = 0; h < 4; h++) {
#pragma unroll
      for (int kv = 0; kv < 2; kv++) {
        const int chunk = 4 * h + 2 * kv + (lane >> 4);
        stsm4(st_base + (((chunk & 8) | ((chunk ^ st_row) & 7)) << 4), r[h][kv][0], r[h][kv][1], r[h][kv][2], r[h][kv][3]);
      }
      kb[h][4] = r[h][0][0]; kb[h][5] = r[h][0][2]; kb[h][6] = r[h][0][1]; kb[h][7] = r[h][0][3];
      vb[h][4] = movm_t(r[h][1][0]); vb[h][5] = movm_t(r[h][1][1]); vb[h][6] = movm_t(r[h][1][2]); vb[h][7] = movm_t(r[h][1][3]);
    }
#pragma unroll
    for (int h = 0; h < 4; h++) {
#pragma unroll
      for (int dh = 0; dh < 2; dh++) {
        const int j = 2 * h + dh;
        const float2 c2 = cs[j];
        qa[h][2 * dh] = packbf(fmaf(-mean0, c2.x, acc[4 * j + 0]), fmaf(-mean0, c2.y, acc[4 * j + 1]));
        qa[h][2 * dh + 1] = packbf(fmaf(-mean1, c2.x, acc[4 * j + 2]), fmaf(-mean1, c2.y, acc[4 * j + 3]));
      }
    }
  }
  bar_sync(2 + wg, 128);
  TSW(2);
  {
    const uint32_t prev_base = kvx + (16 * w - 16) * 256;
    const int mi = lane >> 3;
    const int r = 8 * (mi >> 1) + (lane & 7), r2 = 8 * (mi & 1) + (lane & 7);
    if (w != 0) {
#pragma unroll
      for (int h = 0; h < 4; h++) {
        const int ch = 4 * h + (mi & 1), ch2 = 4 * h + 2 + (mi >> 1);
        ldsm4(&kb[h][0], prev_base + r * 256 + (((ch & 8) | ((ch ^ r) & 7)) << 4));
        ldsm4t(&vb[h][0], prev_base + r2 * 256 + (((ch2 & 8) | ((ch2 ^ r2) & 7)) << 4));
      }
    } else if (blk > 0) {
      const uint4* src = &g_halo[((layer * 32 + blk - 1) * 8 + hg) * 256 + lane];
      uint4 hv[8];
      int it = 0;
      bool ok;
      do {
        ok = true;
#pragma unroll
        for (int i = 0; i < 8; i++) hv[i] = ld_tagged(src + i * 32);
#pragma unroll
        for (int i = 0; i < 8; i++) ok = ok && hv[i].x != UNSET;
      } while (!__all_sync(~0u, ok) && ++it < (1 << 20));
#pragma unroll
      for (int h = 0; h < 4; h++) {
        kb[h][0] = hv[2 * h].x; kb[h][1] = hv[2 * h].y; kb[h][2] = hv[2 * h].z; kb[h][3] = hv[2 * h].w;
        vb[h][0] = movm_t(hv[2 * h + 1].x); vb[h][1] = movm_t(hv[2 * h + 1].y);
        vb[h][2] = movm_t(hv[2 * h + 1].z); vb[h][3] = movm_t(hv[2 * h + 1].w);
      }
    } else {
#pragma unroll
      for (int h = 0; h < 4; h++)
#pragma unroll
        for (int k = 0; k < 4; k++) kb[h][k] = vb[h][k] = 0u;
    }
    TSW(3);
  }
  mbar_wait(bar + 8 * (B_DN + 15), layer);
  TSW(4);

  const bool first = (blk == 0 && w == 0);
  const int e = t - (g >> 1);
  const bool par = g & 1, epos = e >= 1;
  const uint32_t pmask = par ? 0xffff0000u : 0x0000ffffu;
  const uint32_t mB0 = epos ? pmask : 0u, mB1 = epos ? 0u : pmask;
  const float cl2 = 0.25f * 1.4426950408889634f;
  const float sc0 = rstd0 * cl2, sc1 = rstd1 * cl2;
  const float NEG = -INFINITY;
  float vA0[4], vB0[4], vA1[4], vB1[4];
#pragma unroll
  for (int h = 0; h < 4; h++) {
    float S[4][4];
#pragma unroll
    for (int j = 0; j < 4; j++) {
      S[j][0] = S[j][1] = S[j][2] = S[j][3] = 0.f;
      mma_bf16(S[j], qa[h], kb[h][2 * j], kb[h][2 * j + 1]);
    }
    vA0[h] = par ? S[1][1] : S[1][0];
    vB0[h] = epos ? (par ? S[0][1] : S[0][0]) : (par ? S[2][1] : S[2][0]);
    vA1[h] = par ? S[2][3] : S[2][2];
    vB1[h] = epos ? (par ? S[1][3] : S[1][2]) : (par ? S[3][3] : S[3][2]);
    if (first) { vA0[h] = NEG; if (epos) { vB0[h] = NEG; vB1[h] = NEG; } }
  }
  float m0[4], m1[4];
#pragma unroll
  for (int h = 0; h < 4; h++) { m0[h] = fmaxf(vA0[h], vB0[h]); m1[h] = fmaxf(vA1[h], vB1[h]); }
#pragma unroll
  for (int o = 1; o <= 2; o <<= 1) {
#pragma unroll
    for (int h = 0; h < 4; h++) {
      m0[h] = fmaxf(m0[h], __shfl_xor_sync(~0u, m0[h], o));
      m1[h] = fmaxf(m1[h], __shfl_xor_sync(~0u, m1[h], o));
    }
  }
  float O0[4][4], O1[4][4], Z[4][4];
#pragma unroll
  for (int h = 0; h < 4; h++) {
    const float mm0 = -m0[h] * sc0, mm1 = -m1[h] * sc1;
    const float pA0 = ex2(fmaf(vA0[h], sc0, mm0)), pB0 = ex2(fmaf(vB0[h], sc0, mm0));
    const float pA1 = ex2(fmaf(vA1[h], sc1, mm1)), pB1 = ex2(fmaf(vB1[h], sc1, mm1));
    const uint32_t hA0 = packbf(pA0, pA0), hB0 = packbf(pB0, pB0), hA1 = packbf(pA1, pA1), hB1 = packbf(pB1, pB1);
    const uint32_t P0[4] = {hB0 & mB0, 0u, hA0 & pmask, hB1 & mB0};
    const uint32_t P1[4] = {hB0 & mB1, hA1 & pmask, 0u, hB1 & mB1};
#pragma unroll
    for (int k = 0; k < 4; k++) O0[h][k] = O1[h][k] = Z[h][k] = 0.f;
    mma_bf16(O0[h], P0, vb[h][0], vb[h][1]); mma_bf16(O1[h], P0, vb[h][2], vb[h][3]); mma_bf16(Z[h], P0, 0x3f803f80u, 0x3f803f80u);
    mma_bf16(O0[h], P1, vb[h][4], vb[h][5]); mma_bf16(O1[h], P1, vb[h][6], vb[h][7]); mma_bf16(Z[h], P1, 0x3f803f80u, 0x3f803f80u);
  }
  if (lane == 0) mbar_arrive(bar + 8 * (B_OST + wg));
  uint4* op = (uint4*)g_O + ((layer * 32 + blk) * 8 + hg) * 512 + 64 * t + 16 * w + g;
#pragma unroll
  for (int h = 0; h < 4; h += 2) {
    const float i0 = rcp_approx(Z[h][0]), i1 = rcp_approx(Z[h][2]), j0 = rcp_approx(Z[h + 1][0]), j1 = rcp_approx(Z[h + 1][2]);
    stg128(op + 128 * h, make_uint4(packbf(O0[h][0] * i0, O0[h][1] * i0), packbf(O1[h][0] * i0, O1[h][1] * i0),
                                   packbf(O0[h + 1][0] * j0, O0[h + 1][1] * j0), packbf(O1[h + 1][0] * j0, O1[h + 1][1] * j0)));
    stg128(op + 128 * h + 8, make_uint4(packbf(O0[h][2] * i1, O0[h][3] * i1), packbf(O1[h][2] * i1, O1[h][3] * i1),
                                            packbf(O0[h + 1][2] * j1, O0[h + 1][3] * j1), packbf(O1[h + 1][2] * j1, O1[h + 1][3] * j1)));
  }
  TSW(5);
  __syncwarp();
  if (lane == 0) red_relaxed(&g_cnt[(C_O + layer * 32 + blk) * 32]);
  TSW(6);
}

#define PGATE 1
__device__ __forceinline__ void proj_phase(const Params& p, uint32_t sb, int layer, int rb, int q, int wg, int w, int& rtp) {
  const int lane = opaque_tid() & 31;
  const bool TR = layer != 0;
  const int t = lane & 3;
  const uint32_t bar = sb + SM_BAR;
  const uint32_t rbx = sb + (P_R + wg) * PG;
  const uint32_t rsrc = sb + (wg ? 2 : P_R) * PG;
  const int blk = 16 * wg + rb;
  uint32_t res[16];
  mbar_wait(bar + 8 * (B_RF + wg), layer);
  if (!TR) {
#pragma unroll
    for (int j = 0; j < 8; j += 2) {
      const int mi = lane >> 3;
      const int row = 16 * w + (lane & 7) + 8 * (mi & 1), ch = j + (mi >> 1);
      ldsm4(&res[2 * j], rsrc + row * 128 + ((ch ^ (row & 7)) << 4));
    }
  } else {
#pragma unroll
    for (int j = 0; j < 8; j += 2) {
      const int mi = lane >> 3;
      const int line = 8 * (j + (mi >> 1)) + (lane & 7), pc = 2 * w + (mi & 1);
      ldsm4t(&res[2 * j], rsrc + line * 128 + ((pc ^ (line & 7)) << 4));
    }
  }
  if (layer) mbar_wait(bar + 8 * (B_RS + 1), 0);
  fence_async_global();
  const uint32_t stg = sb + (wg ? SM_KGT : SM_STG);
  if (wg) mbar_wait(bar + 8 * B_PST, layer);
  bool clean = false;
#pragma unroll 1
  for (int attempt = 0; attempt < MAX_RETRY; attempt++) {
  float acc[32];
#pragma unroll
  for (int j = 0; j < 16; j++) { acc[2 * j] = bf_lo(res[j]); acc[2 * j + 1] = bf_hi(res[j]); }
  acc_fence<32>(acc);
#pragma unroll
  for (int c = 0; c < 4; c++) {
    mbar_wait(bar + 8 * (B_WOF + c), layer);
    mbar_wait(bar + 8 * (B_OF + 4 * wg + c), layer);
    if (c == 0) TSW(7);
    const uint64_t da = mkdesc(sb + o_page(wg, c) * PG, 1024, 128, 0);
    wg_fence();
#pragma unroll
    for (int ks = 0; ks < 8; ks++)
      wgmma_ss<64, 0, 1>(acc, da + ks * 128, mkdesc(sb + wo_page(2 * c + (ks >> 2)) * PG, 8192, 1024, 1) + (ks & 3) * 128, 1);
    wg_commit();
  }
  if (wg) mbar_wait(bar + 8 * B_KG, 0);
  wg_wait<0>();
  acc_fence<32>(acc);
  TSW(8);
  if (!clean) {
    const float chk = acc[0] + acc[2];
    clean = __all_sync(~0u, chk == chk);
    if (clean && lane == 0) mbar_arrive(bar + 8 * (B_PDONE + wg));
  }
  float s0 = 0.f, q0 = 0.f, s1 = 0.f, q1 = 0.f;
  uint32_t o[16];
#pragma unroll
  for (int j = 0; j < 8; j++) {
    const float a = acc[4 * j], b = acc[4 * j + 1], c = acc[4 * j + 2], d = acc[4 * j + 3];
    o[2 * j] = packbf(a, b);
    o[2 * j + 1] = packbf(c, d);
    s0 += a + b; q0 = fmaf(a, a, q0); q0 = fmaf(b, b, q0);
    s1 += c + d; q1 = fmaf(c, c, q1); q1 = fmaf(d, d, q1);
  }
#pragma unroll
  for (int j = 0; j < 8; j += 2) {
    const int mi = lane >> 3;
    const int line = 8 * (j + (mi >> 1)) + (lane & 7), pc = 2 * w + (mi & 1);
    stsm4t(rbx + line * 128 + ((pc ^ (line & 7)) << 4), o[2 * j], o[2 * j + 1], o[2 * j + 2], o[2 * j + 3]);
  }
#pragma unroll
  for (int o2 = 1; o2 <= 2; o2 <<= 1) {
    s0 += __shfl_xor_sync(~0u, s0, o2); q0 += __shfl_xor_sync(~0u, q0, o2);
    s1 += __shfl_xor_sync(~0u, s1, o2); q1 += __shfl_xor_sync(~0u, q1, o2);
  }
  {
    const int i = 2 * (lane >> 2) + (t & 1), k = (i * 11) >> 5;
    const float v = (t == 0) ? s0 : (t == 1) ? q0 : (t == 2) ? s1 : q1;
    sts32f(stg + k * 128 + (2 * w + (t >> 1)) * 16 + (i - 3 * k) * 4, v);
  }
  TSW(9);
  fence_async_smem();
  if (!bar_or(2 + wg, 128, !clean)) break;
  bool unset = false;
#pragma unroll
  for (int i = 0; i < 4; i++) unset |= lds32(sb + o_page(wg, i) * PG + (32 * w + lane) * 128) == UNSET;
  if (!bar_or(2 + wg, 128, unset)) break;
  if (w == 0 && elect_one()) {
    fence_async_smem();
    mbar_expect(bar + 8 * (B_RT + wg), 8 * PG);
#pragma unroll 1
    for (int c = 0; c < 4; c++) bulk_ld(sb + o_page(wg, c) * PG, g_O + ((layer * 32 + blk) * 4 + c) * PG, 2 * PG, bar + 8 * (B_RT + wg));
  }
  mbar_wait(bar + 8 * (B_RT + wg), rtp);
  rtp ^= 1;
  RETRY(0);
  }
  if (!clean && lane == 0) mbar_arrive(bar + 8 * (B_PDONE + wg));
  if (w == 0 && lane == 0) {
    tma_st(&p.mapXT, blk * 64, (2 * layer) * DM + q * 64, rbx);
    bulk_red_add_f32(g_stats + (layer * 32 + blk) * 192, stg, 768);
    bulk_commit();
    red_relaxed(&g_cnt[(C_G + 2 * layer + wg) * 32]);
  }
  TSW(10);
}

__device__ __forceinline__ void conv_load(uint32_t* A, uint32_t pe) {
#pragma unroll
  for (int m = 0; m < 17; m++) {
    A[4 * m + 2] = lds32(pe + 4 * (64 * m - 8));
    A[4 * m + 0] = lds32(pe + 4 * (64 * m));
    A[4 * m + 1] = lds32(pe + 4 * (64 * m + 8));
    asm volatile("mov.b32 %0, %1;" : "=r"(A[4 * m + 3]) : "r"(A[4 * m + 0]));
  }
}
template <int M> __device__ __forceinline__ void conv_tri(float* acc, const uint32_t* A, uint64_t d) {
  if constexpr (M < 16) {
    wgmma_rs<64 - 8 * (M / 2), 0>(acc, A + 4 * M, d + (uint64_t)(64 + 4 * M), M != 0);
    conv_tri<M + 1>(acc, A, d);
  }
}
__device__ __forceinline__ void conv_mma0(float* acc, const uint32_t* A, uint64_t d) {
  wg_fence();
  conv_tri<0>(acc, A, d);
  wg_commit();
}
__device__ __forceinline__ void conv_mma1(float* acc, const uint32_t* A, uint64_t d, uint64_t ds, uint64_t df) {
  wg_fence();
#pragma unroll
  for (int m = 0; m < 17; m++) wgmma_rs<64, 0>(acc, A + 4 * m, d + (uint64_t)(4 * m), m != 0);
  wgmma_ss<64, 1, 0>(acc, ds, df, 1);
  wgmma_ss<64, 1, 0>(acc, ds + 128, df + 128, 1);
  wg_commit();
}
__device__ __forceinline__ void conv_store(float* acc, uint32_t pb, uint32_t over, int w) {
  acc_fence<32>(acc);
  const int l = opaque_tid() & 31, mt = l >> 3;
  int c = 2 * (63 - 8 * (mt >> 1) - (l & 7) + w) + (mt & 1);
  c ^= (c >> 3) & 1;
  const uint32_t a0 = pb + c * 16;
#pragma unroll
  for (int j = 0; j < 8; j += 2)
    stsm4t(j == 0 ? (c < 128 ? a0 : over + (c - 128) * 16) : a0 - 256 * j, packbf(acc[4 * j], acc[4 * j + 1]), packbf(acc[4 * j + 2], acc[4 * j + 3]),
           packbf(acc[4 * j + 4], acc[4 * j + 5]), packbf(acc[4 * j + 6], acc[4 * j + 7]));
}
__device__ __forceinline__ void conv_sums(uint32_t sb, int lc, int ht) {
  const int m = ht - 1;
  uint4 v[2][3];
#pragma unroll
  for (int c = 0; c < 2; c++)
#pragma unroll
    for (int k = 0; k < 3; k++) {
      const int mm = m - 1 + k;
      v[c][k] = lds128(sb + cv_u(lc + c) + (mm >= 0 ? (mm & 1) * CV_UH + (127 - (mm >> 1)) * 16 : 128 * 16));
    }
  const int ce = m + 2, co = m + 1;
#pragma unroll
  for (int c = 0; c < 2; c++) {
    const uint32_t x[8] = {v[c][0].z, v[c][0].w, v[c][1].x, v[c][1].y, v[c][1].z, v[c][1].w, v[c][2].x, v[c][2].y};
    float pv[16];
#pragma unroll
    for (int k = 0; k < 8; k++) { pv[2 * k] = bf_lo(x[k]); pv[2 * k + 1] = bf_hi(x[k]); }
    float t2[15], t4[13], s9[8], s7[8];
#pragma unroll
    for (int i = 0; i < 15; i++) t2[i] = pv[i] + pv[i + 1];
#pragma unroll
    for (int i = 0; i < 13; i++) t4[i] = t2[i] + t2[i + 2];
#pragma unroll
    for (int i = 0; i < 8; i++) {
      s9[i] = (t4[i] + t4[i + 4]) + pv[i + 8];
      s7[i] = (t4[i + 1] + t2[i + 5]) + pv[i + 7];
    }
    const uint4 e4 = make_uint4(packbf(s9[0], s9[1]), packbf(s9[2], s9[3]), packbf(s9[4], s9[5]), packbf(s9[6], s9[7]));
    if (ce < 128) sts128(sb + cv_se(lc + c) + ((ce ^ ((ce >> 3) & 7)) << 4), e4);
    else sts128(sb + cv_se(lc + c), make_uint4(0, 0, 0, 0));
    sts128(sb + cv_so(lc + c) + ((co ^ ((co >> 3) & 7)) << 4),
           make_uint4(packbf(s7[0], s7[1]), packbf(s7[2], s7[3]), packbf(s7[4], s7[5]), packbf(s7[6], s7[7])));
  }
}

template <int HALF, int NCH, int STEP = 1>
__device__ __forceinline__ void conv_epi(uint32_t sb, bf16* out, int lc, int c) {
  uint4 v[NCH][4], xr[NCH];
  const uint32_t sw = (c ^ ((c >> 3) & 1)) * 16;
#pragma unroll
  for (int u = 0; u < NCH; u++) {
#pragma unroll
    for (int k = 0; k < 4; k++) v[u][k] = lds128(sb + (HALF ? cv_pb1(lc + STEP * u, k) : cv_pb0(lc + STEP * u, k)) + sw);
    xr[u] = lds128(sb + cv_x(HALF, lc + STEP * u) + c * 16);
  }
#pragma unroll
  for (int u = 0; u < NCH; u++) {
    uint4 o;
    o.x = hadd2(xr[u].x, hadd2(hadd2(v[u][0].x, v[u][1].x), hadd2(v[u][2].x, v[u][3].x)));
    o.y = hadd2(xr[u].y, hadd2(hadd2(v[u][0].y, v[u][1].y), hadd2(v[u][2].y, v[u][3].y)));
    o.z = hadd2(xr[u].z, hadd2(hadd2(v[u][0].z, v[u][1].z), hadd2(v[u][2].z, v[u][3].z)));
    o.w = hadd2(xr[u].w, hadd2(hadd2(v[u][0].w, v[u][1].w), hadd2(v[u][2].w, v[u][3].w)));
    stg128(out + cv_chan(0, lc + STEP * u) * LSEQ + HALF * 1024 + c * 8, o);
  }
}

__device__ __forceinline__ bool prep_valid(const uint4 (&st)[6], const uint4 (&xr)[4]) {
  const uint32_t n = __float_as_uint(8.f);
  return st[0].w == n && st[1].w == n && st[2].w == n && st[3].w == n && st[4].w == n && (st[5].w | st[5].y | st[5].z) == n &&
         xr[0].x != UNSET && xr[1].x != UNSET && xr[2].x != UNSET && xr[3].x != UNSET;
}
template <int HALF, typename F>
__device__ __forceinline__ void conv_prep(uint32_t sb, int layer, int cta, int i, F meanwhile) {
  uint4 st[6], xr[4];
  const uint4* sp = (const uint4*)g_stats + (layer * 32 + HALF * 16 + (i >> 3)) * 48 + (i & 7);
  const uint4* xp = (const uint4*)g_xT + (2 * layer * DM + 2 * cta) * (LSEQ / 8) + HALF * 128 + i;
  auto fetch = [&]() {
#pragma unroll
    for (int k = 0; k < 6; k++) st[k] = ld_tagged(sp + 8 * k);
#pragma unroll
    for (int k = 0; k < 4; k++) xr[k] = ld_tagged(xp + cv_chan(0, k) * (LSEQ / 8));
  };
  if (HALF) {
#pragma unroll
    for (int k = 0; k < 6; k++) st[k] = lds128(sb + CV_ST + (i >> 3) * 768 + k * 128 + (i & 7) * 16);
#pragma unroll
    for (int k = 0; k < 4; k++) xr[k] = lds128(sb + cv_x(1, k) + i * 16);
  } else {
    fetch();
  }
  meanwhile();
  int it = 0;
  while (!__all_sync(~0u, prep_valid(st, xr)) && ++it < MAX_RETRY) { fetch(); RETRY(1); }
  if (!HALF || it) {
#pragma unroll
    for (int k = 0; k < 4; k++) sts128(sb + cv_x(HALF, k) + i * 16, xr[k]);
  }
  const uint32_t v[16] = {st[0].x, st[0].y, st[0].z, st[1].x, st[1].y, st[1].z, st[2].x, st[2].y, st[2].z, st[3].x, st[3].y, st[3].z, st[4].x, st[4].y, st[4].z, st[5].x};
  uint32_t rs[4], nm[4];
#pragma unroll
  for (int k = 0; k < 4; k++) {
    const float m0 = __uint_as_float(v[4 * k]) * (-1.f / DM), m1 = __uint_as_float(v[4 * k + 2]) * (-1.f / DM);
    const float r0 = rsqrt_approx(fmaxf(fmaf(__uint_as_float(v[4 * k + 1]), 1.f / DM, -m0 * m0), 0.f) + 1e-5f);
    const float r1 = rsqrt_approx(fmaxf(fmaf(__uint_as_float(v[4 * k + 3]), 1.f / DM, -m1 * m1), 0.f) + 1e-5f);
    rs[k] = packbf(r0, r1);
    nm[k] = packbf(m0 * bf_lo(rs[k]), m1 * bf_hi(rs[k]));
  }
  const uint32_t ud = sb + (i & 1) * CV_UH + (127 - 64 * HALF - (i >> 1)) * 16;
#pragma unroll
  for (int k = 0; k < 4; k++)
    sts128(ud + cv_u(k), make_uint4(hfma2(xr[k].x, rs[0], nm[0]), hfma2(xr[k].y, rs[1], nm[1]), hfma2(xr[k].z, rs[2], nm[2]), hfma2(xr[k].w, rs[3], nm[3])));
  fence_async_smem();
}

#define ALATE 2
#define EPI0 1
#define PP0 1
__device__ __forceinline__ void conv_phase(const Params& p, uint32_t sb, int layer, int cta) {
  const int tid = opaque_tid();
  const int wg = __shfl_sync(~0u, tid >> 7, 0), w = __shfl_sync(~0u, (tid >> 5) & 3, 0);
  const uint32_t bar = sb + SM_BAR;
  constexpr int CH2 = 4 * PG;
  bf16* xout = g_xT + ((2 * layer + 1) * DM + 2 * cta) * LSEQ;
  uint32_t A0[68], A1[68];
  float acc[32];
  const uint32_t pe = sb + cv_pe(wg) + 4 * (16 + 16 * w + ((tid & 31) >> 2) - 2 * (tid & 3));
  auto staged = [&]() {
    if ((tid & 127) == 0) { bulk_wait_read(); mbar_arrive(bar + 8 * (B_PST + wg)); }
    __syncwarp();
  };
  if (layer) mbar_wait(bar + 8 * (B_RS + 2), 0);
  if (wg == 0) {
    staged();
    if (tid < 32) sts128(sb + cv_u(tid >> 3) + ((tid >> 2) & 1) * CV_UH + (128 + (tid & 3)) * 16, make_uint4(0, 0, 0, 0));
    mbar_wait(bar + 8 * B_PE, layer);
    TSW(19);
    mbar_wait(bar + 8 * B_GB, layer);
    TSW(11);
    conv_prep<0>(sb, layer, cta, tid, [&]() {
      conv_load(A0, pe);
      conv_load(A1, pe + CH2);
    });
    mbar_arrive(bar + 8 * B_U);
  } else {
    mbar_wait(bar + 8 * B_PE, layer);
    conv_load(A0, pe);
    staged();
    conv_load(A1, pe + CH2);
    TSW(19);
  }
  const uint64_t d0 = mkdesc(sb + cv_u(wg), CV_UH, 128, 0), d1 = d0 + (CH2 >> 4);
  mbar_wait(bar + 8 * B_U, layer);
  TSW(12);
  if (wg == 1) bar_sync(5, 256);
  conv_mma0(acc, A0, d0);
  if (wg == 0) bar_arrive(5, 256);
  mbar_wait(bar + 8 * (B_PDONE + 1), layer);
  {
    const int l = opaque_tid() & 31;
    if ((l & 15) < 2 * w) sts128(sb + cv_pb0(wg + 2 * (l >> 4), w) + (l & 15) * 16, make_uint4(0, 0, 0, 0));
  }
  wg_wait<0>();
  conv_store(acc, sb + cv_pb0(wg, w), sb + cv_pb1(wg, w), w);
  mbar_arrive(bar + 8 * B_R0);
  conv_mma0(acc, A1, d1);
  wg_wait<0>();
  conv_store(acc, sb + cv_pb0(2 + wg, w), sb + cv_pb1(2 + wg, w), w);
  mbar_arrive(bar + 8 * B_R);
  TSW(13);
  mbar_wait(bar + 8 * B_S, layer);
  mbar_wait(bar + 8 * (B_GB + 1), layer);
  if (wg == 0) {
    conv_prep<1>(sb, layer, cta, opaque_tid(), []() {});
    bar_sync(2, 128);
    if (w == 0 && elect_one()) mbar_arrive(bar + 8 * B_U1);
  } else {
    bar_sync(6, 256);
  }
  TSW(15);
  const uint64_t ds = mkdesc(sb + cv_se(wg), 8192, 1024, 1), df = mkdesc(sb + cv_fa(wg), 512, 128, 0);
  conv_mma1(acc, A0, d0, ds, df);
  if (wg == 0) bar_arrive(6, 256);
  wg_wait<0>();
  conv_store(acc, sb + cv_pb1(wg, w), sb + cv_dump(wg), w);
  mbar_arrive(bar + 8 * (B_R + 1));
  TSW(16);
  conv_mma1(acc, A1, d1, ds + 512, df + (CH2 >> 4));
  wg_wait<0>();
  conv_store(acc, sb + cv_pb1(2 + wg, w), sb + cv_dump(2 + wg), w);
  TSW(17);
  if (wg == 0) {
    mbar_arrive(bar + 8 * (B_R + 2));
  } else {
    bar_sync(3, 128);
    conv_epi<1, 1>(sb, xout, 3, opaque_tid() & 127);
    mbar_arrive(bar + 8 * (B_PUB + 2));
    TSW(18);
  }
}

__device__ __forceinline__ void final_phase(const Params& p, uint32_t sb, int cta, int wg, int w, int rtp) {
  const int lane = opaque_tid() & 31;
  const uint32_t bar = sb + SM_BAR;
  mbar_wait(bar + 8 * (B_TF + wg), 0);
  if (threadIdx.x == 128) TS(8);
  const uint32_t src = sb + (16 + wg) * PG, dst = src + 2 * PG;
  const int mi = lane >> 3;
#pragma unroll 1
  for (int attempt = 0; attempt < MAX_RETRY; attempt++) {
    uint32_t m = 0;
#pragma unroll
    for (int j = 0; j < 8; j += 2) {
      uint32_t r[4];
      const int line = 8 * (j + (mi >> 1)) + (lane & 7), pc = 2 * w + (mi & 1);
      ldsm4t(r, src + line * 128 + ((pc ^ (line & 7)) << 4));
      const int row = 16 * w + (lane & 7) + 8 * (mi & 1), ch = j + (mi >> 1);
      stsm4(dst + row * 128 + ((ch ^ (row & 7)) << 4), r[0], r[1], r[2], r[3]);
#pragma unroll
      for (int k = 0; k < 4; k++) asm("max.u16x2 %0, %0, %1;" : "+r"(m) : "r"(r[k]));
    }
    fence_async_smem();
    if (!bar_or(2 + wg, 128, m >= 0xffff0000u || (m & 0xffffu) == 0xffffu)) break;
    if (w == 0 && elect_one()) {
      mbar_expect(bar + 8 * (B_RT + wg), PG);
      tma_ld(src, &p.mapXT, (16 * wg + (cta & 15)) * 64, 3 * DM + (cta >> 4) * 64, bar + 8 * (B_RT + wg));
    }
    mbar_wait(bar + 8 * (B_RT + wg), (rtp + attempt) & 1);
    RETRY(2);
  }
  if (w == 0 && elect_one()) {
    tma_st(&p.mapOut, (cta >> 4) * 64, (16 * wg + (cta & 15)) * 64, dst);
    bulk_commit();
    asm volatile("cp.async.bulk.wait_group.read 0;" ::: "memory");
    if (threadIdx.x == 128) TS(9);
    if (threadIdx.x == 128) LTS(1);
  }
}

struct cplx { float r, i; };
__device__ __forceinline__ cplx cmul(cplx a, cplx b) { return {fmaf(a.r, b.r, -a.i * b.i), fmaf(a.r, b.i, a.i * b.r)}; }
__device__ __forceinline__ cplx csqr(cplx a) { return {fmaf(a.r, a.r, -a.i * a.i), (a.r + a.r) * a.i}; }
__device__ __forceinline__ cplx cexp_l(float ar2, float ai, float l) {
  const float m = ex2(ar2 * l);
  const float x = ai * l;
  return {m * __cosf(x), m * __sinf(x)};
}

__device__ __forceinline__ void colsum_cta(const Params& p, uint32_t sb, int j, int tid) {
  const uint32_t bar = sb + SM_BAR;
  auto ld = [&](int i) {
    mbar_expect(bar + 8 * i, 3 * PG);
    tma_ld3(sb + (i & 7) * 3 * PG, &p.mapW3, (2 * j + (i & 1)) * 64, (i >> 1) * 64, 0, bar + 8 * i);
  };
  if (tid == 384) {
#pragma unroll
    for (int i = 0; i < 24; i++) mbar_init(bar + 8 * i, i < 16 ? 1 : 12);
    asm volatile("fence.mbarrier_init.release.cluster;" ::: "memory");
    fence_async_smem();
#pragma unroll 1
    for (int i = 0; i < 8; i++) ld(i);
  }
  const unsigned ep = ld_relaxed(&g_cnt[C_CS * 32]);
  bar_sync(0, NTHREADS);
  if (tid == 384) {
#pragma unroll 1
    for (int i = 8; i < 16; i++) { mbar_wait(bar + 8 * (8 + i), 0); fence_async_smem(); ld(i); }
  }
  if (tid < 384) {
    const int lane = tid & 31, cc = tid & 7, r0 = (tid >> 3) & 15, part = tid >> 7;
    const uint32_t id = ((lane >> 2) == 2 * (lane & 3) ? 0x3f80u : 0u) | ((lane >> 2) == 2 * (lane & 3) + 1 ? 0x3f800000u : 0u);
    const uint32_t src = sb + part * PG + r0 * 128 + ((cc ^ (r0 & 7)) << 4);
    float s[2][2][4];
#pragma unroll
    for (int i = 0; i < 16; i++) s[i >> 3][(i >> 2) & 1][i & 3] = 0.f;
#pragma unroll 1
    for (int i2 = 0; i2 < 16; i2 += 2) {
#pragma unroll
      for (int h = 0; h < 2; h++) {
        const int i = i2 + h;
        mbar_wait(bar + 8 * i, 0);
        uint4 v[4];
#pragma unroll
        for (int k = 0; k < 4; k++) v[k] = lds128(src + (i & 7) * 3 * PG + k * 2048);
#pragma unroll
        for (int k = 0; k < 4; k++) {
          const uint32_t a[4] = {v[k].x, v[k].y, v[k].z, v[k].w};
          mma_bf16(s[h][0], a, id, 0u);
          mma_bf16(s[h][1], a, 0u, id);
        }
        __syncwarp();
        if (i < 8 && lane == 0) mbar_arrive(bar + 8 * (16 + i));
      }
    }
    const uint32_t red = sb + 24 * PG;
#pragma unroll
    for (int h = 0; h < 2; h++)
#pragma unroll
      for (int k = 0; k < 2; k++) sts128f(red + (r0 * 384 + h * 192 + part * 64 + cc * 8 + k * 4) * 4, s[h][k][0], s[h][k][1], s[h][k][2], s[h][k][3]);
    bar_sync(1, 384);
    float tot = 0.f;
#pragma unroll
    for (int k = 0; k < 16; k++) tot += __uint_as_float(lds32(red + (k * 384 + tid) * 4));
    asm volatile("st.relaxed.gpu.global.v2.u32 [%0], {%1,%2};" ::"l"(&g_colsum[j * 384 + tid]), "r"(__float_as_uint(tot)), "r"(ep / NCTA + 1) : "memory");
    const uint4 u = make_uint4(UNSET, UNSET, UNSET, UNSET);
    if (tid < 256) {
#pragma unroll 4
      for (int i = 0; i < 64; i++) stg128(g_halo + 65536 + j * 16384 + i * 256 + tid, u);
#pragma unroll 1
      for (int s = 0; s < 3; s++) {
        uint4* dst = (s ? (uint4*)g_xT + (s + 1) * 131072 : (uint4*)g_O + 131072) + j * 32768 + (tid >> 1) * 8 + (tid & 1);
#pragma unroll 4
        for (int i = 0; i < 32; i++) stg128(dst + i * 1024, u);
        bar_sync(2, 256);
        if (tid == 32 * s) red_release(&g_cnt[(C_R + s) * 32]);
      }
    }
  }
}

#define KW 3
struct ModeIn { uint32_t ar, ai, br, bi, cr, ci; bf16 logdt; };
__device__ __forceinline__ ModeIn load_modes(const Params& p, int d, int m) {
  const int i = d * 64 + m;
  return {((const uint32_t*)p.a_re)[i], ((const uint32_t*)p.a_im)[i], ((const uint32_t*)p.b_re)[i], ((const uint32_t*)p.b_im)[i],
          ((const uint32_t*)p.c_re)[i], ((const uint32_t*)p.c_im)[i], p.log_dt[d]};
}
__device__ __forceinline__ float4 lds128f_nv(uint32_t a) { float4 v; asm("ld.shared.v4.f32 {%0,%1,%2,%3}, [%4];" : "=f"(v.x), "=f"(v.y), "=f"(v.z), "=f"(v.w) : "r"(a)); return v; }
__device__ __forceinline__ void kernel_gen(const Params& p, uint32_t sb, int cta, int ht, ModeIn in, const ModeIn& in1) {
  const uint32_t bst = sb + SM_KGB + ((ht & 63) >> 2) * 144 + (ht & 3) * 4 + (ht >> 6) * 16;
  const uint64_t db = mkdesc(sb + SM_KGB, 144, 2304, 0);
  const float e0 = (float)(8 * (((ht & 32) >> 1) + ((ht & 31) >> 2)));
  float T[20];
#pragma unroll
  for (int i = 0; i < 20; i++) T[i] = 0.f;
  float k0 = (ht & 63) ? 0.f : __bfloat162float(p.dskip[cv_chan(cta, ht >> 6)]);
#pragma unroll 1
  for (int pass = 0; pass < 4; pass++) {
    {
      const int sh = (pass & 1) ? 0 : 16;
      auto val = [&](uint32_t v) { return __uint_as_float((v << sh) & 0xffff0000u); };
      const float dt = __bfloat162float(__float2bfloat16_rn(expf(__bfloat162float(in.logdt))));
      const float ar2 = dt * val(in.ar) * 1.4426950408889634f, ai = dt * val(in.ai);
      const cplx c = cmul({val(in.cr), -val(in.ci)}, {dt * val(in.br), -dt * val(in.bi)});
      k0 += c.r;
      const cplx z1 = cexp_l(ar2, -ai, 1.f), z256 = cexp_l(ar2, -ai, 256.f), z64 = cexp_l(ar2, ai, 64.f);
      const cplx z2 = csqr(z1), z512 = csqr(z256);
      auto put = [&](int j, cplx v) { sts32(bst + (j >> 2) * 2304 + (j & 3) * 32, packbf(v.r, v.i)); };
      sts128f(sb + SM_KGT + ht * 16, ar2, ai, z64.r, z64.i);
      const cplx c1 = cmul(c, z1), c2 = cmul(c, z2), c3 = cmul(c1, z2), c4 = cmul(c2, z2);
      const cplx c5 = cmul(c3, z2), c6 = cmul(c4, z2), c7 = cmul(c5, z2), c8 = cmul(c6, z2);
      put(0, c1); put(1, c2); put(2, c3); put(3, c4); put(4, c5); put(5, c6); put(6, c7); put(7, c8);
      const cplx c260 = cmul(c4, z256), c264 = cmul(c8, z256), c520 = cmul(c8, z512), c776 = cmul(c264, z512);
      put(8, cmul(c2, z256)); put(9, c260); put(10, cmul(c6, z256)); put(11, c264);
      put(12, cmul(c4, z512)); put(13, c520); put(14, cmul(c260, z512)); put(15, c776);
      const cplx c1032 = cmul(c520, z512), c1288 = cmul(c776, z512);
      put(16, c1032); put(17, c1288); put(18, cmul(c1032, z512)); put(19, cmul(c1288, z512));
    }
    fence_async_smem();
    bar_sync(4, 128);
    uint32_t tb = sb + SM_KGT + (ht & 67) * 16;
    asm volatile("mov.u32 %0, %0;" : "+r"(tb) :: "memory");
#pragma unroll
    for (int q = 0; q < 4; q++) {
      uint32_t A[8];
      if (q >= KW) wg_wait<KW - 1>();
#pragma unroll
      for (int s = 0; s < 4; s++) {
        const float4 v = lds128f_nv(tb + (4 * q + s) * 64);
        const cplx lo = cexp_l(v.x, v.y, e0), hi = cmul(lo, {v.z, v.w});
        A[2 * s] = packbf(lo.r, lo.i);
        A[2 * s + 1] = packbf(hi.r, hi.i);
      }
      wg_fence();
      wgmma_rs<40, 0>(T, A, db + 36 * q, (pass & 1) | q);
      wgmma_rs<40, 0>(T, A + 4, db + 36 * q + 18, 1);
      wg_commit();
    }
    wg_wait<0>();
    acc_fence<20>(T);
    if (ht == 0) TS(4 + pass);
    if (pass & 1) {
      const int h2 = opaque_tid() - 256, w = h2 >> 5, lane = h2 & 31, t = lane & 3, chn = h2 >> 6, m = h2 & 63, i0 = 16 * (w & 1) + (lane >> 2);
      const int lc = (pass & 2) + chn;
      const uint32_t kc = sb + kc_off(lc);
      auto put = [&](int idx, float v) {
        sts16(kc + idx * 2, __bfloat16_as_ushort(__float2bfloat16_rn(v)));
      };
#pragma unroll
      for (int hi = 0; hi < 2; hi++) {
        const int i = i0 + 8 * hi;
        float v[5];
#pragma unroll
        for (int j = 0; j < 5; j++) v[j] = chn ? T[4 * j + 2 * hi + 1] : T[4 * j + 2 * hi];
        put(8 * i + 1 + t, v[0]);
        put(8 * i + 5 + t, v[1]);
        put(257 + 4 * i + t, v[2]);
        put(385 + 2 * i + (t & 1) + 64 * (t >> 1), v[3]);
        put(513 + i + 32 * t, v[4]);
      }
#pragma unroll
      for (int o = 16; o > 0; o >>= 1) k0 += __shfl_xor_sync(~0u, k0, o);
      if (lane == 0) sts32f(sb + SM_RED + 4 * w, k0);
      bar_sync(4, 128);
      if (m == 0) put(0, k0 + __uint_as_float(lds32(sb + SM_RED + 4 * w + 4)));
      k0 = m ? 0.f : __bfloat162float(p.dskip[cv_chan(cta, 2 + chn)]);
      in = in1;
    }
  }
}

__device__ __forceinline__ void expand_taps(uint32_t sb, int ht) {
  const int ch = ht >> 5, lane = ht & 31;
  const uint32_t kc = sb + kc_off(ch);
  const uint32_t dst0 = sb + cv_pe(ch);
  auto put = [&](int G, uint32_t v0, uint32_t v1, uint32_t v2, uint32_t v3, uint32_t v4, uint32_t v5, uint32_t v6, uint32_t v7, uint32_t v8) {
    const uint32_t dst = dst0 + G * 32;
    sts128(dst, make_uint4(v1 | (v0 << 16), v2 | (v1 << 16), v3 | (v2 << 16), v4 | (v3 << 16)));
    sts128(dst + 16, make_uint4(v5 | (v4 << 16), v6 | (v5 << 16), v7 | (v6 << 16), v8 | (v7 << 16)));
  };
  {
    const uint4 q = lds128(kc + lane * 16);
    const uint32_t pv = lane ? lds16(kc + lane * 16 - 2) : 0u;
    const uint32_t dst = dst0 + (lane + 2) * 32;
    sts128(dst, make_uint4(__byte_perm(q.x, pv, 0x5410), __byte_perm(q.x, q.x, 0x1032), __byte_perm(q.y, q.x, 0x7610), __byte_perm(q.y, q.y, 0x1032)));
    sts128(dst + 16, make_uint4(__byte_perm(q.z, q.y, 0x7610), __byte_perm(q.z, q.z, 0x1032), __byte_perm(q.w, q.z, 0x7610), __byte_perm(q.w, q.w, 0x1032)));
    if (lane < 4) sts128(dst0 + lane * 16, make_uint4(0, 0, 0, 0));
  }
  uint32_t a[5], b[2][3];
  {
    const uint32_t s1 = kc + 2 * (256 + 4 * lane);
#pragma unroll
    for (int k = 0; k < 5; k++) a[k] = lds16(s1 + 2 * k);
#pragma unroll
    for (int u = 0; u < 2; u++) {
      const uint32_t s2 = kc + 2 * (384 + 2 * (lane + 32 * u));
#pragma unroll
      for (int k = 0; k < 3; k++) b[u][k] = lds16(s2 + 2 * k);
    }
  }
  const uint32_t k255 = lds16(kc + 2 * 255), k1024 = lds16(kc + 2 * 512);
  put(34 + lane, lane == 0 ? k255 : a[0], a[0], a[0], a[1], a[2], a[2], a[2], a[3], a[4]);
#pragma unroll
  for (int u = 0; u < 2; u++) put(66 + lane + 32 * u, b[u][0], b[u][0], b[u][0], b[u][0], b[u][1], b[u][1], b[u][1], b[u][2], b[u][2]);
  if (lane < 10) {
    const uint32_t v = lane == 0 ? k1024 : 0u;
    put(130 + lane, v, v, v, v, v, v, 0u, 0u, 0u);
  }
}
__device__ __forceinline__ void expand_far(uint32_t sb, int ht) {
  const int ch = ht >> 5, lane = ht & 31;
  const uint32_t kc = sb + kc_off(ch) + 2 * (513 + 2 * (63 - lane)), dst = sb + cv_fa(ch) + lane * 16;
#pragma unroll
  for (int ty = 0; ty < 2; ty++) {
    uint32_t v[16];
#pragma unroll
    for (int k = 0; k < 16; k++) v[k] = (k < 8 || 63 - lane - 4 * k >= 0) ? lds16(kc + 2 * (1 - ty) - 16 * k) : 0u;
#pragma unroll
    for (int u = 0; u < 2; u++)
      sts128(dst + ty * 2048 + u * 512, make_uint4(v[8 * u] | (v[8 * u + 1] << 16), v[8 * u + 2] | (v[8 * u + 3] << 16), v[8 * u + 4] | (v[8 * u + 5] << 16), v[8 * u + 6] | (v[8 * u + 7] << 16)));
    sts128(dst + ty * 2048 + 1024, make_uint4(0, 0, 0, 0));
  }
}

#define MAPF 0
#define PMAP 1
#define FIRST 0
#define WOCS 0
#define WPRE 2
__host__ __device__ constexpr int bar_count(int i) {
  return i == B_END ? 3 : i == B_CSF ? 2 : (i >= B_OST && i < B_PDONE + 2) ? 4 : (i == B_PUB + 2 || (i == B_PUB && !EPI0) || i == B_R0 || i == B_R || i == B_R + 1) ? 256 : (i >= B_S && i < B_END) ? 128 : 1;
}
__host__ __device__ constexpr bool bar_first(int i) { return i < B_WF + 2 && (i & 7) < 2; }

__global__ void __launch_bounds__(NTHREADS, 1) fused_kernel(const __grid_constant__ Params p) {
  extern __shared__ __align__(1024) uint8_t smem[];
  const uint32_t sb = s32(smem);
  const int tid = threadIdx.x, lane = tid & 31;
  const int warp = __shfl_sync(~0u, tid >> 5, 0);
  const int cta = blockIdx.x - p.first;
  if ((unsigned)cta >= NCTA) {
    colsum_cta(p, sb, blockIdx.x & 3, tid);
    return;
  }
  const int rb = ((cta >> 4) & 3) * 4 + ((cta >> 2) & 3), hg = (cta >> 6) * 4 + (cta & 3);
  const int rb2 = rb, q2 = hg;
  const uint32_t bar = sb + SM_BAR;
  auto ld_x0 = [&](int half, int c) {
    const uint32_t b = bar + 8 * (B_XF + 8 * half + c);
    mbar_expect(b, PG);
    tma_ld(sb + x_page(half, c) * PG, &p.mapX, c * 64, (16 * half + rb) * 64, b);
  };
  auto ld_w = [&](int c) {
    const uint32_t b = bar + 8 * (B_WF + c);
    mbar_expect(b, 3 * PG);
    tma_ld3(sb + w_page(c) * PG, &p.mapW3, hg * 64, c * 64, 0, b);
  };

  if (tid == 0) TS(0);
  if (tid == 480) LTS(0);
  if (warp < 6 && elect_one()) {
    if (warp == 0) {
#pragma unroll
      for (int i = 0; i < B_WF + 2; i++)
        if (bar_first(i)) mbar_init(bar + 8 * i, 1);
      asm volatile("fence.mbarrier_init.release.cluster;" ::: "memory");
      fence_async_smem();
      ld_x0(0, 0); ld_w(0); ld_x0(1, 0);
      ld_x0(0, 1); ld_w(1); ld_x0(1, 1);
      TS(1);
    } else {
#pragma unroll
      for (int q = 0; q < 5; q++) {
        if (warp == q + 1) {
#pragma unroll
          for (int i = 0; i < B_COUNT; i++)
            if (!bar_first(i) && i % 5 == q) mbar_init(bar + 8 * i, bar_count(i));
        }
      }
      asm volatile("fence.mbarrier_init.release.cluster;" ::: "memory");
    }
  }

  if (warp < 8) {
    bar_sync(0, NTHREADS);
    asm volatile("setmaxnreg.inc.sync.aligned.u32 %0;" ::"n"(R_CONS));
    const int cw = __shfl_sync(~0u, opaque_tid() >> 5, 0);
    const int wg = cw >> 2, w = cw & 3;
    if (tid == 0) TS(2);
    int rtp = 0;
#pragma unroll 1
    for (int layer = 0; layer < 2; layer++) {
      attn_phase(p, sb, layer, rb, hg, wg, w);
      proj_phase(p, sb, layer, rb2, q2, wg, w, rtp);
      conv_phase(p, sb, layer, cta);
    }
    final_phase(p, sb, cta, wg, w, rtp);
  } else if (warp < 12) {
    asm volatile("setmaxnreg.dec.sync.aligned.u32 %0;" ::"n"(R_HELP));
    const int ht = tid - 256;
    {
      unsigned ep0 = 0;
      if (ht == 0) ep0 = ld_relaxed(&g_cnt[C_CS * 32]);
      const ModeIn in0 = load_modes(p, cv_chan(cta, ht >> 6), ht & 63), in1 = load_modes(p, cv_chan(cta, 2 + (ht >> 6)), ht & 63);
      if (ht < 48) sts128f(sb + SM_STG + ht * 16, 0.f, 0.f, 0.f, 1.f);
      bar_sync(0, NTHREADS);
      if (ht == 0) {
        sts32(sb + SM_EP, ep0 / NCTA);
        mbar_arrive(bar + 8 * B_EP);
      }
      kernel_gen(p, sb, cta, ht, in0, in1);
      if (ht < 48) sts128f(sb + SM_KGT + ht * 16, 0.f, 0.f, 0.f, 1.f);
      fence_async_smem();
      bar_sync(4, 128);
      if (ht == 0) mbar_arrive(bar + 8 * B_KG);
    }
#pragma unroll 1
    for (int layer = 0; layer < 2; layer++) {
      bf16* xout = g_xT + ((2 * layer + 1) * DM + 2 * cta) * LSEQ;
      mbar_wait(bar + 8 * B_PDONE, layer);
      expand_taps(sb, opaque_tid() - 256);
      mbar_arrive(bar + 8 * B_PE);
      TSW(0);
      expand_far(sb, opaque_tid() - 256);
      if (layer) mbar_wait(bar + 8 * (B_RS + 2), 0);
      mbar_wait(bar + 8 * (B_PDONE + 1), layer);
      mbar_wait(bar + 8 * B_U, layer);
#pragma unroll 1
      for (int lc = 0; lc < 4; lc += 2) {
        conv_sums(sb, lc, opaque_tid() - 256);
        TSW(1 + lc);
      }
      fence_async_smem();
      mbar_arrive(bar + 8 * B_S);
      mbar_wait(bar + 8 * B_R0, layer);
      conv_epi<0, 2>(sb, xout, 0, opaque_tid() - 256);
      TSW(2);
      mbar_wait(bar + 8 * B_R, layer);
      conv_epi<0, 2>(sb, xout, 2, opaque_tid() - 256);
      mbar_arrive(bar + 8 * B_PUB);
      TSW(4);
      mbar_wait(bar + 8 * (B_R + 1), layer);
      conv_epi<1, 2>(sb, xout, 0, opaque_tid() - 256);
      mbar_arrive(bar + 8 * (B_PUB + 1));
      TSW(5);
      mbar_wait(bar + 8 * (B_R + 2), layer);
      conv_epi<1, 1>(sb, xout, 2, opaque_tid() - 256);
      mbar_arrive(bar + 8 * (B_PUB + 2));
      TSW(6);
    }
  } else {
    asm volatile("setmaxnreg.dec.sync.aligned.u32 %0;" ::"n"(R_AGENT));
    bar_sync(0, NTHREADS);
    auto done = [&](int half, int c, int layer) { mbar_wait(bar + 8 * (B_DN + 8 * half + c), layer); };
    auto publish = [&](int layer, int k) {
      mbar_wait(bar + 8 * (B_PUB + k), layer);
      if (layer == 0) {
        red_release(&g_cnt[(C_C + k) * 32]);
      }
      else red_relaxed(&g_cnt[(C_F + 4 * k + (cta >> 5)) * 32]);
      TS(16 + layer * 56 + 40 + 7 + k);
    };
    if (warp == 12) {
      if (elect_one()) {
#pragma unroll 1
        for (int layer = 0; layer < 2; layer++) {
          auto ld_xe = [&](int c) {
            const uint32_t b = bar + 8 * (B_XF + c);
            mbar_expect(b, PG);
            if (layer == 0) tma_ld(sb + (c - 5) * PG, &p.mapX, c * 64, rb * 64, b);
            else tma_ld(sb + (c - 5) * PG, &p.mapXT, rb * 64, DM + c * 64, b);
          };
          if (layer == 0) {
            ld_x0(0, 2); ld_w(2); ld_x0(1, 2);
            if (hg >= 3) {
              mbar_expect(bar + 8 * B_SC, PG);
              tma_ld(sb + P_R * PG, &p.mapX, hg * 64, rb * 64, bar + 8 * B_SC);
            }
            if (rb < 4) tma_prefetch3(&p.mapW3, hg * 64, (4 + rb) * 64, 0);
            ld_x0(0, 3); ld_w(3); ld_x0(1, 3); ld_x0(0, 4); ld_x0(1, 4);
            done(0, 0, 0); done(1, 0, 0);
            ld_w(4);
            ld_x0(1, 5); ld_x0(1, 6); ld_x0(1, 7);
            done(0, 1, 0); done(1, 1, 0);
            ld_w(5);
            if (rb2 < 8) tma_prefetch5(&p.mapWo, q2 * 64, rb2 * 2);
            done(0, 2, 0);
            fence_async_smem();
            ld_xe(5); ld_xe(6); ld_xe(7);
          } else {
            mbar_wait(bar + 8 * B_PDONE, 0);
            mbar_wait(bar + 8 * (B_PDONE + 1), 0);
            mbar_wait(bar + 8 * (WPRE == 1 ? B_U : B_GB + 1), 0);
            ld_w(0); ld_w(1);
            mbar_wait(bar + 8 * B_U1, 0);
            fence_async_smem();
            ld_w(2);
            mbar_wait(bar + 8 * (B_PUB + 2), 0);
            fence_async_smem();
            ld_w(3);
            done(0, 2, 1);
            fence_async_global();
            fence_async_smem();
            ld_xe(5); ld_xe(6); ld_xe(7);
            done(1, 0, 1);
            ld_w(4);
            done(1, 1, 1);
            ld_w(5);
          }
          done(1, 2, layer);
          fence_async_smem();
          ld_w(6); ld_w(7);
          auto ld_res = [&](int half) {
            const uint32_t b = bar + 8 * (B_RF + half);
            mbar_expect(b, PG);
            if (layer == 0) tma_ld(sb + (half ? 2 : P_R) * PG, &p.mapX, q2 * 64, (16 * half + rb2) * 64, b);
            else tma_ld(sb + (half ? 2 : P_R) * PG, &p.mapXT, (16 * half + rb2) * 64, DM + q2 * 64, b);
          };
          done(0, 4, layer); done(1, 3, layer);
          fence_async_smem();
#pragma unroll 1
          for (int c = 0; c < 8; c++) {
            const uint32_t b = bar + 8 * (B_WOF + (c >> 1));
            if (c == 5) { ld_res(0); done(1, 4, layer); }
            if ((c & 1) == 0) mbar_expect(b, 2 * PG);
            tma_ld5(sb + wo_page(c) * PG, &p.mapWo, q2 * 64, c * 2, b);
          }
          done(0, 7, layer);
          fence_async_global();
          ld_res(1);
        }
      }
    } else if (warp == 13) {
      if (elect_one()) {
        mbar_wait(bar + 8 * (B_WF + 2), 0);
        asm volatile("prefetch.tensormap [%0];" ::"l"(&p.mapXT) : "memory");
        asm volatile("prefetch.tensormap [%0];" ::"l"(&p.mapOut) : "memory");
        asm volatile("prefetch.tensormap [%0];" ::"l"(&p.mapWo) : "memory");
        mbar_wait(bar + 8 * B_EP, 0);
        const unsigned e1 = lds32(sb + SM_EP) + 1;
        spin_until(&g_cnt[C_Z * 32], e1 * NCTA);
        mbar_arrive(bar + 8 * B_CSF);
        TS(3);
        auto ld_x1 = [&](int half, int c0, int c1) {
          fence_async_global();
          fence_async_smem();
#pragma unroll 1
          for (int c = c0; c < c1; c++) {
            const uint32_t b = bar + 8 * (B_XF + 8 * half + c);
            mbar_expect(b, PG);
            tma_ld(sb + x_page(half, c) * PG, &p.mapXT, (16 * half + rb) * 64, DM + c * 64, b);
          }
        };
#pragma unroll 1
        for (int layer = 0; layer < 2; layer++) {
          if (layer == 1) {
            mbar_wait(bar + 8 * B_PUB, 0);
            spin_until(&g_cnt[C_C * 32], e1 * NCTA);
            TS(10);
            ld_x1(0, 0, 3);
            if (hg >= 3) {
              mbar_expect(bar + 8 * B_SC, PG);
              tma_ld(sb + P_R * PG, &p.mapXT, rb * 64, DM + hg * 64, bar + 8 * B_SC);
            }
            ld_x1(0, 3, 5);
            mbar_wait(bar + 8 * (B_PUB + 1), 0);
            spin_until(&g_cnt[(C_C + 1) * 32], e1 * NCTA);
            TS(11);
            ld_x1(1, 0, 4);
            spin_until(&g_cnt[(C_C + 2) * 32], e1 * NCTA);
            TS(12);
            ld_x1(1, 4, 8);
          }
#pragma unroll 1
          for (int half = 0; half < 2; half++) {
            done(1, 7, layer);
            mbar_wait(bar + 8 * B_OST, layer);
            if (half) mbar_wait(bar + 8 * (B_OST + 1), layer);
            spin_until(&g_cnt[(C_O + layer * 32 + 16 * half + rb2) * 32], e1 * 32);
            fence_async_global();
            fence_async_smem();
#pragma unroll 1
            for (int c = 0; c < 4; c++) {
              const uint32_t b = bar + 8 * (B_OF + 4 * half + c);
              mbar_expect(b, 2 * PG);
              bulk_ld(sb + o_page(half, c) * PG, g_O + ((layer * 32 + 16 * half + rb2) * 4 + c) * PG, 2 * PG, b);
            }
          }
        }
        mbar_wait(bar + 8 * B_PUB, 1);
#pragma unroll 1
        for (int half = 0; half < 2; half++) {
          spin_until(&g_cnt[(C_F + 4 * (half ? 1 + (cta >> 6) : 0) + ((cta >> 4) & 3)) * 32], e1 * 32);
          fence_async_global();
          mbar_expect(bar + 8 * (B_TF + half), PG);
          tma_ld(sb + (16 + half) * PG, &p.mapXT, (16 * half + (cta & 15)) * 64, 3 * DM + (cta >> 4) * 64, bar + 8 * (B_TF + half));
        }
      }
    } else if (warp == 14) {
      mbar_wait(bar + 8 * B_EP, 0);
      const unsigned e1 = lds32(sb + SM_EP) + 1;
      done(0, 1, 0);
      {
        const uint2* cp = g_colsum + (hg * 192 + lane);
        uint2 v[6];
        bool ok;
        int it = 0;
        do {
          ok = true;
#pragma unroll
          for (int i = 0; i < 6; i++) {
            asm volatile("ld.relaxed.gpu.global.v2.u32 {%0,%1}, [%2];" : "=r"(v[i].x), "=r"(v[i].y) : "l"(cp + 32 * i) : "memory");
            ok = ok && v[i].y == e1;
          }
          if (++it > (1 << 22)) __trap();
        } while (!__all_sync(~0u, ok));
#pragma unroll
        for (int i = 0; i < 6; i++) sts32f(sb + SM_CS + 4 * (lane + 32 * i), __uint_as_float(v[i].x));
      }
      __syncwarp();
      if (lane == 0) {
        mbar_arrive(bar + 8 * B_CSF);
        red_relaxed(&g_cnt[C_CS * 32]);
        TS(13);
#pragma unroll 1
        for (int i = 0; i < 4; i++) {
          const int layer = i >> 1;
          mbar_wait(bar + 8 * (B_PST + (i & 1)), layer);
          const uint32_t b = bar + 8 * (B_GB + 1);
          const bf16* xin = g_xT + ((size_t)2 * layer * DM + 2 * cta) * LSEQ + 1024;
          if (i & 1) {
            fence_async_smem();
            mbar_expect(b, 12288 + PG);
          }
          spin_until(&g_cnt[(C_G + i) * 32], e1 * NCTA);
          if (i & 1) {
            bulk_ld(sb + CV_ST, g_stats + (layer * 32 + 16) * 192, 12288, b);
#pragma unroll
            for (int lc = 0; lc < 4; lc++) bulk_ld(sb + cv_x(1, lc), xin + cv_chan(0, lc) * LSEQ, 2048, b);
            TS(14 + layer);
            publish(layer, 1);
          } else {
            mbar_arrive(bar + 8 * B_GB);
          }
        }
      }
    } else {
      const uint4 u = make_uint4(UNSET, UNSET, UNSET, UNSET);
      if (lane < 24) stg128((uint4*)g_stats + cta * 24 + lane, make_uint4(0, 0, 0, 0));
#pragma unroll 4
      for (int i = 0; i < 16; i++) stg128(g_halo + cta * 512 + 32 * i + lane, u);
#pragma unroll 4
      for (int i = 0; i < 16; i++) stg128(((i & 8) ? (uint4*)g_xT : (uint4*)g_O) + cta * 1024 + (i & 7) * 128 + (lane >> 1) * 8 + (lane & 1), u);
      __syncwarp();
      if (lane == 0) {
        red_release(&g_cnt[C_Z * 32]);
        publish(0, 0);
        publish(0, 2);
        const unsigned e1 = lds32(sb + SM_EP) + 1;
#pragma unroll 1
        for (int s = 0; s < 3; s++) {
          spin_until(&g_cnt[(C_R + s) * 32], e1 * 4);
          mbar_arrive(bar + 8 * (B_RS + s));
          TS(16 + 40 + 10 + s);
        }
        publish(1, 0);
        publish(1, 2);
      }
    }
  }
}

typedef CUresult (*EncodeFn)(CUtensorMap*, CUtensorMapDataType, cuuint32_t, void*, const cuuint64_t*, const cuuint64_t*,
                             const cuuint32_t*, const cuuint32_t*, CUtensorMapInterleave, CUtensorMapSwizzle,
                             CUtensorMapL2promotion, CUtensorMapFloatOOBfill);

static void make_map(EncodeFn enc, CUtensorMap* m, void* ptr, uint64_t cols, uint64_t rows, uint32_t box_rows) {
  cuuint64_t dims[2] = {cols, rows};
  cuuint64_t strides[1] = {cols * 2};
  cuuint32_t box[2] = {64, box_rows};
  cuuint32_t es[2] = {1, 1};
  enc(m, CU_TENSOR_MAP_DATA_TYPE_BFLOAT16, 2, ptr, dims, strides, box, es, CU_TENSOR_MAP_INTERLEAVE_NONE,
      CU_TENSOR_MAP_SWIZZLE_128B, CU_TENSOR_MAP_L2_PROMOTION_L2_128B, CU_TENSOR_MAP_FLOAT_OOB_FILL_NONE);
}
static void make_map3(EncodeFn enc, CUtensorMap* m, void* ptr, uint64_t d0, uint64_t cols, uint64_t rows, uint64_t blk_stride,
                      uint64_t nblocks, uint32_t nblk) {
  cuuint64_t dims[3] = {d0, rows, nblocks};
  cuuint64_t strides[2] = {cols * 2, blk_stride * 2};
  cuuint32_t box[3] = {64, 64, nblk};
  cuuint32_t es[3] = {1, 1, 1};
  enc(m, CU_TENSOR_MAP_DATA_TYPE_BFLOAT16, 3, ptr, dims, strides, box, es, CU_TENSOR_MAP_INTERLEAVE_NONE,
      CU_TENSOR_MAP_SWIZZLE_128B, CU_TENSOR_MAP_L2_PROMOTION_L2_128B, CU_TENSOR_MAP_FLOAT_OOB_FILL_NONE);
}

extern "C" void kernel_launch(void* const* d_in, const int* in_sizes, int n_in, void* d_out, int out_size) {
  static Params prm;
  static void* cached[13] = {nullptr};
  static bool attr_done = false;
  bool same = attr_done && cached[12] == d_out;
  for (int i = 0; i < 12 && same; i++) same = cached[i] == d_in[i];
  if (!same) {
    void* fn = nullptr;
    cudaDriverEntryPointQueryResult qr;
    cudaGetDriverEntryPoint("cuTensorMapEncodeTiled", &fn, cudaEnableDefault, &qr);
    EncodeFn enc = (EncodeFn)fn;
    void* pXT;
    cudaGetSymbolAddress(&pXT, g_xT);
    make_map(enc, &prm.mapX, d_in[0], DM, LSEQ, 64);
    make_map(enc, &prm.mapXT, pXT, LSEQ, 4 * DM, 64);
    make_map(enc, &prm.mapOut, d_out, DM, LSEQ, 64);
    {
      cuuint64_t dims[5] = {DM, 2, 4, 4, 16};
      cuuint64_t strides[4] = {DM * 2, 8 * DM * 2, 2 * DM * 2, 32 * DM * 2};
      cuuint32_t box[5] = {64, 2, 4, 4, 2};
      cuuint32_t es[5] = {1, 1, 1, 1, 1};
      enc(&prm.mapWo, CU_TENSOR_MAP_DATA_TYPE_BFLOAT16, 5, d_in[2], dims, strides, box, es, CU_TENSOR_MAP_INTERLEAVE_NONE,
          CU_TENSOR_MAP_SWIZZLE_128B, CU_TENSOR_MAP_L2_PROMOTION_L2_128B, CU_TENSOR_MAP_FLOAT_OOB_FILL_NONE);
    }
    make_map3(enc, &prm.mapW3, d_in[1], DM, 3 * DM, DM, DM, 3, 3);
    prm.wqkv = (const bf16*)d_in[1];
    prm.a_re = (const bf16*)d_in[4]; prm.a_im = (const bf16*)d_in[5];
    prm.b_re = (const bf16*)d_in[6]; prm.b_im = (const bf16*)d_in[7];
    prm.c_re = (const bf16*)d_in[8]; prm.c_im = (const bf16*)d_in[9];
    prm.log_dt = (const bf16*)d_in[10]; prm.dskip = (const bf16*)d_in[11];
    int dev = 0, sms = 0;
    cudaGetDevice(&dev);
    cudaDeviceGetAttribute(&sms, cudaDevAttrMultiProcessorCount, dev);
    prm.first = sms >= NCTA + 4 ? FIRST : 4;
    cudaFuncSetAttribute(fused_kernel, cudaFuncAttributeMaxDynamicSharedMemorySize, SM_TOTAL);
    for (int i = 0; i < 12; i++) cached[i] = d_in[i];
    cached[12] = d_out;
    attr_done = true;
  }
  fused_kernel<<<NCTA + 4, NTHREADS, SM_TOTAL>>>(prm);
}
```

```cpp
#include <cuda_runtime.h>
#include <cuda_bf16.h>
#include <cuda.h>
#include <stdint.h>

typedef __nv_bfloat16 bf16;

constexpr int LSEQ = 2048;
constexpr int DM = 512;
constexpr int NCTA = 128;
constexpr int NTHREADS = 512;
#define R_CONS 200
#define R_HELP 88
#define R_AGENT 24
#define TURN0 4
#define TURN1 4

constexpr int PG = 8192;
constexpr int P_R = 25;
__host__ __device__ constexpr int x_page(int half, int c) { return half ? 8 + c : c < 5 ? c : c - 5; }
__host__ __device__ constexpr int w_page(int c) { return (c & 3) < 3 ? 16 + 3 * (c & 3) : c < 4 ? 5 : 8; }
__host__ __device__ constexpr int wo_page(int c) { return c < 5 ? 3 + c : 11 + c; }
__host__ __device__ constexpr int o_page(int half, int pair) { return half ? (pair ? 17 + 2 * pair : 0) : 8 + 2 * pair; }
constexpr int SM_KGB = (P_R + 1) * PG;
constexpr int SM_KC = 27 * PG;
constexpr int KC_STRIDE = 648;
__host__ __device__ constexpr int kc_off(int lc) { return SM_KC + (lc & 1) * 2 * KC_STRIDE + (lc < 2 ? 3328 : 0); }
constexpr int SM_KGT = SM_KC + 3328 + 2592;
constexpr int SM_CS = SM_KGT + 2048;
constexpr int SM_RED = SM_CS + 768;
constexpr int SM_EP = SM_RED + 16;
constexpr int SM_STG = SM_RED + 32;
constexpr int SM_LN = SM_STG + 768;
__host__ __device__ constexpr int ln_off(int half) { return half ? PG + 4096 : SM_LN; }
constexpr int SM_BAR = SM_LN + 512;
constexpr int SM_TS = SM_BAR + 704;
constexpr int SM_TOTAL = SM_TS + 512;
static_assert(SM_TOTAL <= 232448 && SM_STG % 16 == 0 && SM_KGT % 16 == 0, "shared memory");

constexpr int CV_UH = 140 * 16;
__host__ __device__ constexpr int cv_u(int lc) { return (8 + 2 * lc) * PG; }
__host__ __device__ constexpr int cv_pe(int lc) { return cv_u(lc) + 4480; }
__host__ __device__ constexpr int cv_pb1(int lc, int w) { return w ? cv_u(lc) + 8960 + (w - 1) * 2048 : 7 * PG + lc * 2048; }
__host__ __device__ constexpr int cv_fa(int lc) { return cv_pb1(lc, 1) + 128; }
__host__ __device__ constexpr int cv_dump(int lc) { return cv_u(lc) + 16256; }
__host__ __device__ constexpr int cv_pb0(int lc, int w) { return lc * PG + w * 2048; }
__host__ __device__ constexpr int cv_se(int lc) { return 5 * PG + lc * 4096; }
__host__ __device__ constexpr int cv_so(int lc) { return cv_se(lc) + 2048; }
__host__ __device__ constexpr int cv_x(int half, int lc) { return (P_R + half) * PG + lc * 2048; }
constexpr int CV_ST = 22 * PG;
__host__ __device__ constexpr int cv_chan(int cta, int lc) { return 2 * cta + (lc & 1) + 256 * (lc >> 1); }

enum {
  B_XF = 0,
  B_WF = 16,
  B_OF = 24,
  B_DN = 32,
  B_WOF = 48,
  B_RF = 52,
  B_PST = 54,
  B_OST = 56,
  B_PDONE = 58,
  B_GB = 60,
  B_TF = 62,
  B_ZF = 64,
  B_EP = 65,
  B_KG = 67,
  B_U1 = 68,
  B_PE = 70,
  B_U = 71,
  B_LN = 72,
  B_PUB = 74,
  B_R = 77,
  B_END = 80,
  B_SC = 81,
  B_RT = 82,
  B_RS = 85,
  B_COUNT = 88
};

enum {
  C_CS = 0,
  C_G = 1,
  C_C = 5,
  C_F = 8,
  C_O = 20,
  C_Z = 84,
  C_R = 85,
  C_COUNT = 88
};

__device__ unsigned g_cnt[C_COUNT * 32];
__device__ __align__(1024) bf16 g_O[2 * LSEQ * DM];
__device__ __align__(1024) bf16 g_xT[4 * DM * LSEQ];
__device__ __align__(1024) float g_stats[2 * 32 * 192];
__device__ __align__(1024) uint2 g_colsum[3 * DM];
__device__ __align__(1024) uint4 g_halo[2 * 32 * 8 * 256];
__device__ __align__(1024) uint4 g_rows[2 * LSEQ];
#define TS(i) do { } while (0)
#define TSW(k) do { if ((threadIdx.x & 127) == 0) TS(16 + layer * 56 + (threadIdx.x >> 7) * 20 + (k)); } while (0)
#define TSG(k) do { } while (0)

#define RETRY(i) do { } while (0)
#define LTS(i) do { } while (0)

struct Params {
  CUtensorMap mapX, mapW3, mapXT, mapOut, mapWo;
  const bf16 *wqkv, *a_re, *a_im, *b_re, *b_im, *c_re, *c_im, *log_dt, *dskip;
  int first;
};

__device__ __forceinline__ uint32_t s32(const void* p) { return (uint32_t)__cvta_generic_to_shared(p); }
__device__ __forceinline__ void mbar_init(uint32_t b, int c) { asm volatile("mbarrier.init.shared::cta.b64 [%0], %1;" ::"r"(b), "r"(c) : "memory"); }
__device__ __forceinline__ void mbar_expect(uint32_t b, int bytes) { asm volatile("mbarrier.arrive.expect_tx.shared::cta.b64 _, [%0], %1;" ::"r"(b), "r"(bytes) : "memory"); }
__device__ __forceinline__ void mbar_arrive(uint32_t b) { asm volatile("mbarrier.arrive.shared::cta.b64 _, [%0];" ::"r"(b) : "memory"); }
__device__ __forceinline__ void mbar_wait(uint32_t b, int parity) {
  asm volatile("{\n.reg .pred p;\nWAIT_LOOP:\nmbarrier.try_wait.parity.shared::cta.b64 p, [%0], %1;\n@p bra WAIT_DONE;\nbra WAIT_LOOP;\nWAIT_DONE:\n}" ::"r"(b), "r"(parity) : "memory");
}
__device__ __forceinline__ bool mbar_test(uint32_t b, int parity) {
  uint32_t ok;
  asm volatile("{\n.reg .pred p;\nmbarrier.test_wait.parity.shared::cta.b64 p, [%1], %2;\nselp.u32 %0, 1, 0, p;\n}" : "=r"(ok) : "r"(b), "r"(parity) : "memory");
  return ok != 0;
}
__device__ __forceinline__ int opaque_tid() { int v; asm volatile("mov.u32 %0, %%tid.x;" : "=r"(v)); return v; }
__device__ __forceinline__ bool elect_one() {
  uint32_t r;
  asm volatile("{\n.reg .pred p;\nelect.sync _|p, 0xffffffff;\nselp.u32 %0, 1, 0, p;\n}" : "=r"(r));
  return r != 0;
}
__device__ __forceinline__ void tma_ld(uint32_t dst, const CUtensorMap* m, int c0, int c1, uint32_t bar) {
  asm volatile("cp.async.bulk.tensor.2d.shared::cluster.global.mbarrier::complete_tx::bytes [%0], [%1, {%3, %4}], [%2];"
               ::"r"(dst), "l"(m), "r"(bar), "r"(c0), "r"(c1) : "memory");
}
__device__ __forceinline__ void tma_ld3(uint32_t dst, const CUtensorMap* m, int c0, int c1, int c2, uint32_t bar) {
  asm volatile("cp.async.bulk.tensor.3d.shared::cluster.global.mbarrier::complete_tx::bytes [%0], [%1, {%3, %4, %5}], [%2];"
               ::"r"(dst), "l"(m), "r"(bar), "r"(c0), "r"(c1), "r"(c2) : "memory");
}
__device__ __forceinline__ void tma_ld5(uint32_t dst, const CUtensorMap* m, int c0, int c4, uint32_t bar) {
  asm volatile("cp.async.bulk.tensor.5d.shared::cluster.global.mbarrier::complete_tx::bytes [%0], [%1, {%3, 0, 0, 0, %4}], [%2];"
               ::"r"(dst), "l"(m), "r"(bar), "r"(c0), "r"(c4) : "memory");
}
__device__ __forceinline__ void tma_prefetch5(const CUtensorMap* m, int c0, int c4) {
  asm volatile("cp.async.bulk.prefetch.tensor.5d.L2.global.tile [%0, {%1, 0, 0, 0, %2}];" ::"l"(m), "r"(c0), "r"(c4) : "memory");
}
__device__ __forceinline__ void tma_prefetch2(const CUtensorMap* m, int c0, int c1) {
  asm volatile("cp.async.bulk.prefetch.tensor.2d.L2.global.tile [%0, {%1, %2}];" ::"l"(m), "r"(c0), "r"(c1) : "memory");
}
__device__ __forceinline__ void tma_prefetch3(const CUtensorMap* m, int c0, int c1, int c2) {
  asm volatile("cp.async.bulk.prefetch.tensor.3d.L2.global.tile [%0, {%1, %2, %3}];" ::"l"(m), "r"(c0), "r"(c1), "r"(c2) : "memory");
}
__device__ __forceinline__ void tma_st(const CUtensorMap* m, int c0, int c1, uint32_t src) {
  asm volatile("cp.async.bulk.tensor.2d.global.shared::cta.bulk_group [%0, {%2, %3}], [%1];" ::"l"(m), "r"(src), "r"(c0), "r"(c1) : "memory");
}
__device__ __forceinline__ void bulk_ld(uint32_t dst, const void* src, int bytes, uint32_t bar) {
  asm volatile("cp.async.bulk.shared::cluster.global.mbarrier::complete_tx::bytes [%0], [%1], %2, [%3];" ::"r"(dst), "l"(src), "r"(bytes), "r"(bar) : "memory");
}
__device__ __forceinline__ void bulk_st(void* dst, uint32_t src, int bytes) {
  asm volatile("cp.async.bulk.global.shared::cta.bulk_group [%0], [%1], %2;" ::"l"(dst), "r"(src), "r"(bytes) : "memory");
}
__device__ __forceinline__ void bulk_red_add_f32(void* dst, uint32_t src, int bytes) {
  asm volatile("cp.reduce.async.bulk.global.shared::cta.bulk_group.add.f32 [%0], [%1], %2;" ::"l"(dst), "r"(src), "r"(bytes) : "memory");
}
__device__ __forceinline__ void bulk_commit() { asm volatile("cp.async.bulk.commit_group;" ::: "memory"); }
__device__ __forceinline__ void bulk_wait_all() { asm volatile("cp.async.bulk.wait_group 0;" ::: "memory"); }
__device__ __forceinline__ void fence_async_smem() { asm volatile("fence.proxy.async.shared::cta;" ::: "memory"); }
__device__ __forceinline__ void fence_async_global() { asm volatile("fence.proxy.async.global;" ::: "memory"); }
__device__ __forceinline__ void bar_sync(int id, int n) { asm volatile("bar.sync %0, %1;" ::"r"(id), "r"(n) : "memory"); }
__device__ __forceinline__ void bar_arrive(int id, int n) { asm volatile("bar.arrive %0, %1;" ::"r"(id), "r"(n) : "memory"); }
__device__ __forceinline__ bool bar_or(int id, int n, bool v) {
  uint32_t r;
  asm volatile("{\n.reg .pred p, q;\nsetp.ne.u32 q, %3, 0;\nbar.red.or.pred p, %1, %2, q;\nselp.u32 %0, 1, 0, p;\n}" : "=r"(r) : "r"(id), "r"(n), "r"((uint32_t)v) : "memory");
  return r != 0;
}
__device__ __forceinline__ void bulk_wait_read() { asm volatile("cp.async.bulk.wait_group.read 0;" ::: "memory"); }
__device__ __forceinline__ void stg128(void* p, uint4 v) { asm volatile("st.relaxed.gpu.global.v4.u32 [%0], {%1,%2,%3,%4};" ::"l"(p), "r"(v.x), "r"(v.y), "r"(v.z), "r"(v.w) : "memory"); }
constexpr uint32_t UNSET = 0xffffffffu;
constexpr int MAX_RETRY = 1 << 16;
__device__ __forceinline__ void wg_fence() { asm volatile("wgmma.fence.sync.aligned;" ::: "memory"); }
__device__ __forceinline__ void wg_commit() { asm volatile("wgmma.commit_group.sync.aligned;" ::: "memory"); }
template <int N> __device__ __forceinline__ void wg_wait() { asm volatile("wgmma.wait_group.sync.aligned %0;" ::"n"(N) : "memory"); }
__device__ __forceinline__ uint64_t mkdesc(uint32_t addr, uint32_t lbo, uint32_t sbo, int sw) {
  return (uint64_t)((addr & 0x3FFFF) >> 4) | ((uint64_t)(lbo >> 4) << 16) | ((uint64_t)(sbo >> 4) << 32) | ((uint64_t)sw << 62);
}
__device__ __forceinline__ void ldsm4(uint32_t* r, uint32_t a) {
  asm volatile("ldmatrix.sync.aligned.m8n8.x4.shared.b16 {%0,%1,%2,%3}, [%4];" : "=r"(r[0]), "=r"(r[1]), "=r"(r[2]), "=r"(r[3]) : "r"(a) : "memory");
}
__device__ __forceinline__ void ldsm4t(uint32_t* r, uint32_t a) {
  asm volatile("ldmatrix.sync.aligned.m8n8.x4.trans.shared.b16 {%0,%1,%2,%3}, [%4];" : "=r"(r[0]), "=r"(r[1]), "=r"(r[2]), "=r"(r[3]) : "r"(a) : "memory");
}
__device__ __forceinline__ void stsm4(uint32_t a, uint32_t r0, uint32_t r1, uint32_t r2, uint32_t r3) {
  asm volatile("stmatrix.sync.aligned.m8n8.x4.shared.b16 [%0], {%1,%2,%3,%4};" ::"r"(a), "r"(r0), "r"(r1), "r"(r2), "r"(r3) : "memory");
}
__device__ __forceinline__ void stsm4t(uint32_t a, uint32_t r0, uint32_t r1, uint32_t r2, uint32_t r3) {
  asm volatile("stmatrix.sync.aligned.m8n8.x4.trans.shared.b16 [%0], {%1,%2,%3,%4};" ::"r"(a), "r"(r0), "r"(r1), "r"(r2), "r"(r3) : "memory");
}
__device__ __forceinline__ uint32_t movm_t(uint32_t a) { uint32_t r; asm volatile("movmatrix.sync.aligned.m8n8.trans.b16 %0, %1;" : "=r"(r) : "r"(a)); return r; }
__device__ __forceinline__ uint32_t lds32(uint32_t a) { uint32_t v; asm volatile("ld.shared.b32 %0, [%1];" : "=r"(v) : "r"(a) : "memory"); return v; }
__device__ __forceinline__ float2 lds64f(uint32_t a) { float2 v; asm volatile("ld.shared.v2.f32 {%0,%1}, [%2];" : "=f"(v.x), "=f"(v.y) : "r"(a) : "memory"); return v; }
__device__ __forceinline__ float4 lds128f(uint32_t a) { float4 v; asm volatile("ld.shared.v4.f32 {%0,%1,%2,%3}, [%4];" : "=f"(v.x), "=f"(v.y), "=f"(v.z), "=f"(v.w) : "r"(a) : "memory"); return v; }
__device__ __forceinline__ uint4 lds128(uint32_t a) { uint4 v; asm volatile("ld.shared.v4.b32 {%0,%1,%2,%3}, [%4];" : "=r"(v.x), "=r"(v.y), "=r"(v.z), "=r"(v.w) : "r"(a) : "memory"); return v; }
__device__ __forceinline__ void sts128(uint32_t a, uint4 v) { asm volatile("st.shared.v4.b32 [%0], {%1,%2,%3,%4};" ::"r"(a), "r"(v.x), "r"(v.y), "r"(v.z), "r"(v.w) : "memory"); }
__device__ __forceinline__ void sts128f(uint32_t a, float x, float y, float z, float w) { asm volatile("st.shared.v4.f32 [%0], {%1,%2,%3,%4};" ::"r"(a), "f"(x), "f"(y), "f"(z), "f"(w) : "memory"); }
__device__ __forceinline__ void sts32f(uint32_t a, float v) { asm volatile("st.shared.f32 [%0], %1;" ::"r"(a), "f"(v) : "memory"); }
__device__ __forceinline__ void sts16(uint32_t a, uint16_t v) { asm volatile("st.shared.u16 [%0], %1;" ::"r"(a), "h"(v) : "memory"); }
__device__ __forceinline__ uint32_t lds16(uint32_t a) { uint16_t v; asm volatile("ld.shared.u16 %0, [%1];" : "=h"(v) : "r"(a) : "memory"); return v; }
__device__ __forceinline__ uint32_t packbf(float lo, float hi) { uint32_t r; asm("cvt.rn.bf16x2.f32 %0, %1, %2;" : "=r"(r) : "f"(hi), "f"(lo)); return r; }
__device__ __forceinline__ float bf_lo(uint32_t v) { return __uint_as_float(v << 16); }
__device__ __forceinline__ float bf_hi(uint32_t v) { return __uint_as_float(v & 0xffff0000u); }
__device__ __forceinline__ float ex2(float x) { float r; asm("ex2.approx.ftz.f32 %0, %1;" : "=f"(r) : "f"(x)); return r; }
__device__ __forceinline__ float rsqrt_approx(float x) { float r; asm("rsqrt.approx.ftz.f32 %0, %1;" : "=f"(r) : "f"(x)); return r; }
__device__ __forceinline__ float rcp_approx(float x) { float r; asm("rcp.approx.ftz.f32 %0, %1;" : "=f"(r) : "f"(x)); return r; }
__device__ __forceinline__ void mma_bf16(float* d, const uint32_t* a, uint32_t b0, uint32_t b1) {
  asm("mma.sync.aligned.m16n8k16.row.col.f32.bf16.bf16.f32 {%0,%1,%2,%3}, {%4,%5,%6,%7}, {%8,%9}, {%0,%1,%2,%3};"
               : "+f"(d[0]), "+f"(d[1]), "+f"(d[2]), "+f"(d[3]) : "r"(a[0]), "r"(a[1]), "r"(a[2]), "r"(a[3]), "r"(b0), "r"(b1));
}
__device__ __forceinline__ void mma_tf32(float* d, float a0, float a1, float a2, float a3, float b0, float b1) {
  asm("mma.sync.aligned.m16n8k8.row.col.f32.tf32.tf32.f32 {%0,%1,%2,%3}, {%4,%5,%6,%7}, {%8,%9}, {%0,%1,%2,%3};"
               : "+f"(d[0]), "+f"(d[1]), "+f"(d[2]), "+f"(d[3])
               : "r"(__float_as_uint(a0)), "r"(__float_as_uint(a1)), "r"(__float_as_uint(a2)), "r"(__float_as_uint(a3)),
                 "r"(__float_as_uint(b0)), "r"(__float_as_uint(b1)));
}
__device__ __forceinline__ void red_release(unsigned* p) { asm volatile("red.release.gpu.global.add.u32 [%0], 1;" ::"l"(p) : "memory"); }
__device__ __forceinline__ void red_relaxed(unsigned* p) { asm volatile("red.relaxed.gpu.global.add.u32 [%0], 1;" ::"l"(p) : "memory"); }
__device__ __forceinline__ unsigned ld_relaxed(const unsigned* p) { unsigned v; asm volatile("ld.relaxed.gpu.global.u32 %0, [%1];" : "=r"(v) : "l"(p) : "memory"); return v; }
__device__ __forceinline__ void spin_until(const unsigned* p, unsigned target) {
  int it = 0;
  while ((int)(ld_relaxed(p) - target) < 0) {
    if (++it > (1 << 23)) __trap();
  }
}
__device__ __forceinline__ uint4 ldcg128(const void* p) { uint4 v; asm volatile("ld.global.cg.v4.b32 {%0,%1,%2,%3}, [%4];" : "=r"(v.x), "=r"(v.y), "=r"(v.z), "=r"(v.w) : "l"(p) : "memory"); return v; }
__device__ __forceinline__ uint4 ld_tagged(const uint4* p) { uint4 v; asm volatile("ld.relaxed.gpu.global.v4.u32 {%0,%1,%2,%3}, [%4];" : "=r"(v.x), "=r"(v.y), "=r"(v.z), "=r"(v.w) : "l"(p) : "memory"); return v; }
__device__ __forceinline__ void st_tagged(uint4* p, uint32_t a, uint32_t b, uint32_t tag) { asm volatile("st.relaxed.gpu.global.v4.u32 [%0], {%1,%2,%3,%2};" ::"l"(p), "r"(a), "r"(tag), "r"(b) : "memory"); }
__device__ __forceinline__ void st_tagged3(uint4* p, uint32_t a, uint32_t b, uint32_t c, uint32_t tag) { asm volatile("st.relaxed.gpu.global.v4.u32 [%0], {%1,%2,%3,%4};" ::"l"(p), "r"(a), "r"(b), "r"(c), "r"(tag) : "memory"); }
__device__ __forceinline__ uint4 poll_tagged(const uint4* p, uint32_t tag) {
  uint4 v = ld_tagged(p);
  int it = 0;
  while (v.y != tag || v.w != tag) {
    if (++it > (1 << 22)) __trap();
    v = ld_tagged(p);
  }
  return v;
}
__device__ __forceinline__ uint32_t hadd2(uint32_t a, uint32_t b) { uint32_t r; asm("add.rn.bf16x2 %0, %1, %2;" : "=r"(r) : "r"(a), "r"(b)); return r; }
__device__ __forceinline__ uint32_t hmul2(uint32_t a, uint32_t b) { uint32_t r; asm("mul.rn.bf16x2 %0, %1, %2;" : "=r"(r) : "r"(a), "r"(b)); return r; }

__device__ __forceinline__ uint32_t hfma2(uint32_t a, uint32_t b, uint32_t c) { uint32_t r; asm("fma.rn.bf16x2 %0, %1, %2, %3;" : "=r"(r) : "r"(a), "r"(b), "r"(c)); return r; }
__device__ __forceinline__ void sts32(uint32_t a, uint32_t v) { asm volatile("st.shared.u32 [%0], %1;" ::"r"(a), "r"(v) : "memory"); }

template <int N> __device__ __forceinline__ void acc_fence(float* a) {
#pragma unroll
  for (int i = 0; i < N; i++) asm volatile("" : "+f"(a[i]) :: "memory");
}

template<int N,int TB> __device__ __forceinline__ void wgmma_rs(float* d, const uint32_t* a, uint64_t db, int sd);
template<int N,int TA,int TB> __device__ __forceinline__ void wgmma_ss(float* d, uint64_t da, uint64_t db, int sd);
template<> __device__ __forceinline__ void wgmma_rs<64,0>(float* d, const uint32_t* a, uint64_t db, int sd) {
  asm volatile("{\n.reg .pred p;\nsetp.ne.b32 p, %37, 0;\nwgmma.mma_async.sync.aligned.m64n64k16.f32.bf16.bf16 {%0,%1,%2,%3,%4,%5,%6,%7,%8,%9,%10,%11,%12,%13,%14,%15,%16,%17,%18,%19,%20,%21,%22,%23,%24,%25,%26,%27,%28,%29,%30,%31}, {%32,%33,%34,%35}, %36, p, 1, 1, 0;\n}\n"
   : "+f"(d[0]),"+f"(d[1]),"+f"(d[2]),"+f"(d[3]),"+f"(d[4]),"+f"(d[5]),"+f"(d[6]),"+f"(d[7]),"+f"(d[8]),"+f"(d[9]),"+f"(d[10]),"+f"(d[11]),"+f"(d[12]),"+f"(d[13]),"+f"(d[14]),"+f"(d[15]),"+f"(d[16]),"+f"(d[17]),"+f"(d[18]),"+f"(d[19]),"+f"(d[20]),"+f"(d[21]),"+f"(d[22]),"+f"(d[23]),"+f"(d[24]),"+f"(d[25]),"+f"(d[26]),"+f"(d[27]),"+f"(d[28]),"+f"(d[29]),"+f"(d[30]),"+f"(d[31])
   : "r"(a[0]), "r"(a[1]), "r"(a[2]), "r"(a[3]), "l"(db), "r"(sd));
}
template<> __device__ __forceinline__ void wgmma_rs<56,0>(float* d, const uint32_t* a, uint64_t db, int sd) {
  asm volatile("{\n.reg .pred p;\nsetp.ne.b32 p, %33, 0;\nwgmma.mma_async.sync.aligned.m64n56k16.f32.bf16.bf16 {%0,%1,%2,%3,%4,%5,%6,%7,%8,%9,%10,%11,%12,%13,%14,%15,%16,%17,%18,%19,%20,%21,%22,%23,%24,%25,%26,%27}, {%28,%29,%30,%31}, %32, p, 1, 1, 0;\n}\n"
   : "+f"(d[0]),"+f"(d[1]),"+f"(d[2]),"+f"(d[3]),"+f"(d[4]),"+f"(d[5]),"+f"(d[6]),"+f"(d[7]),"+f"(d[8]),"+f"(d[9]),"+f"(d[10]),"+f"(d[11]),"+f"(d[12]),"+f"(d[13]),"+f"(d[14]),"+f"(d[15]),"+f"(d[16]),"+f"(d[17]),"+f"(d[18]),"+f"(d[19]),"+f"(d[20]),"+f"(d[21]),"+f"(d[22]),"+f"(d[23]),"+f"(d[24]),"+f"(d[25]),"+f"(d[26]),"+f"(d[27])
   : "r"(a[0]), "r"(a[1]), "r"(a[2]), "r"(a[3]), "l"(db), "r"(sd));
}
template<> __device__ __forceinline__ void wgmma_rs<48,0>(float* d, const uint32_t* a, uint64_t db, int sd) {
  asm volatile("{\n.reg .pred p;\nsetp.ne.b32 p, %29, 0;\nwgmma.mma_async.sync.aligned.m64n48k16.f32.bf16.bf16 {%0,%1,%2,%3,%4,%5,%6,%7,%8,%9,%10,%11,%12,%13,%14,%15,%16,%17,%18,%19,%20,%21,%22,%23}, {%24,%25,%26,%27}, %28, p, 1, 1, 0;\n}\n"
   : "+f"(d[0]),"+f"(d[1]),"+f"(d[2]),"+f"(d[3]),"+f"(d[4]),"+f"(d[5]),"+f"(d[6]),"+f"(d[7]),"+f"(d[8]),"+f"(d[9]),"+f"(d[10]),"+f"(d[11]),"+f"(d[12]),"+f"(d[13]),"+f"(d[14]),"+f"(d[15]),"+f"(d[16]),"+f"(d[17]),"+f"(d[18]),"+f"(d[19]),"+f"(d[20]),"+f"(d[21]),"+f"(d[22]),"+f"(d[23])
   : "r"(a[0]), "r"(a[1]), "r"(a[2]), "r"(a[3]), "l"(db), "r"(sd));
}
template<> __device__ __forceinline__ void wgmma_rs<40,0>(float* d, const uint32_t* a, uint64_t db, int sd) {
  asm volatile("{\n.reg .pred p;\nsetp.ne.b32 p, %25, 0;\nwgmma.mma_async.sync.aligned.m64n40k16.f32.bf16.bf16 {%0,%1,%2,%3,%4,%5,%6,%7,%8,%9,%10,%11,%12,%13,%14,%15,%16,%17,%18,%19}, {%20,%21,%22,%23}, %24, p, 1, 1, 0;\n}\n"
   : "+f"(d[0]),"+f"(d[1]),"+f"(d[2]),"+f"(d[3]),"+f"(d[4]),"+f"(d[5]),"+f"(d[6]),"+f"(d[7]),"+f"(d[8]),"+f"(d[9]),"+f"(d[10]),"+f"(d[11]),"+f"(d[12]),"+f"(d[13]),"+f"(d[14]),"+f"(d[15]),"+f"(d[16]),"+f"(d[17]),"+f"(d[18]),"+f"(d[19])
   : "r"(a[0]), "r"(a[1]), "r"(a[2]), "r"(a[3]), "l"(db), "r"(sd));
}
template<> __device__ __forceinline__ void wgmma_rs<32,0>(float* d, const uint32_t* a, uint64_t db, int sd) {
  asm volatile("{\n.reg .pred p;\nsetp.ne.b32 p, %21, 0;\nwgmma.mma_async.sync.aligned.m64n32k16.f32.bf16.bf16 {%0,%1,%2,%3,%4,%5,%6,%7,%8,%9,%10,%11,%12,%13,%14,%15}, {%16,%17,%18,%19}, %20, p, 1, 1, 0;\n}\n"
   : "+f"(d[0]),"+f"(d[1]),"+f"(d[2]),"+f"(d[3]),"+f"(d[4]),"+f"(d[5]),"+f"(d[6]),"+f"(d[7]),"+f"(d[8]),"+f"(d[9]),"+f"(d[10]),"+f"(d[11]),"+f"(d[12]),"+f"(d[13]),"+f"(d[14]),"+f"(d[15])
   : "r"(a[0]), "r"(a[1]), "r"(a[2]), "r"(a[3]), "l"(db), "r"(sd));
}
template<> __device__ __forceinline__ void wgmma_rs<24,0>(float* d, const uint32_t* a, uint64_t db, int sd) {
  asm volatile("{\n.reg .pred p;\nsetp.ne.b32 p, %17, 0;\nwgmma.mma_async.sync.aligned.m64n24k16.f32.bf16.bf16 {%0,%1,%2,%3,%4,%5,%6,%7,%8,%9,%10,%11}, {%12,%13,%14,%15}, %16, p, 1, 1, 0;\n}\n"
   : "+f"(d[0]),"+f"(d[1]),"+f"(d[2]),"+f"(d[3]),"+f"(d[4]),"+f"(d[5]),"+f"(d[6]),"+f"(d[7]),"+f"(d[8]),"+f"(d[9]),"+f"(d[10]),"+f"(d[11])
   : "r"(a[0]), "r"(a[1]), "r"(a[2]), "r"(a[3]), "l"(db), "r"(sd));
}
template<> __device__ __forceinline__ void wgmma_rs<16,0>(float* d, const uint32_t* a, uint64_t db, int sd) {
  asm volatile("{\n.reg .pred p;\nsetp.ne.b32 p, %13, 0;\nwgmma.mma_async.sync.aligned.m64n16k16.f32.bf16.bf16 {%0,%1,%2,%3,%4,%5,%6,%7}, {%8,%9,%10,%11}, %12, p, 1, 1, 0;\n}\n"
   : "+f"(d[0]),"+f"(d[1]),"+f"(d[2]),"+f"(d[3]),"+f"(d[4]),"+f"(d[5]),"+f"(d[6]),"+f"(d[7])
   : "r"(a[0]), "r"(a[1]), "r"(a[2]), "r"(a[3]), "l"(db), "r"(sd));
}
template<> __device__ __forceinline__ void wgmma_rs<8,0>(float* d, const uint32_t* a, uint64_t db, int sd) {
  asm volatile("{\n.reg .pred p;\nsetp.ne.b32 p, %9, 0;\nwgmma.mma_async.sync.aligned.m64n8k16.f32.bf16.bf16 {%0,%1,%2,%3}, {%4,%5,%6,%7}, %8, p, 1, 1, 0;\n}\n"
   : "+f"(d[0]),"+f"(d[1]),"+f"(d[2]),"+f"(d[3])
   : "r"(a[0]), "r"(a[1]), "r"(a[2]), "r"(a[3]), "l"(db), "r"(sd));
}
template<> __device__ __forceinline__ void wgmma_ss<64,1,0>(float* d, uint64_t da, uint64_t db, int sd) {
  asm volatile("{\n.reg .pred p;\nsetp.ne.b32 p, %34, 0;\nwgmma.mma_async.sync.aligned.m64n64k16.f32.bf16.bf16 {%0,%1,%2,%3,%4,%5,%6,%7,%8,%9,%10,%11,%12,%13,%14,%15,%16,%17,%18,%19,%20,%21,%22,%23,%24,%25,%26,%27,%28,%29,%30,%31}, %32, %33, p, 1, 1, 1, 0;\n}\n"
   : "+f"(d[0]),"+f"(d[1]),"+f"(d[2]),"+f"(d[3]),"+f"(d[4]),"+f"(d[5]),"+f"(d[6]),"+f"(d[7]),"+f"(d[8]),"+f"(d[9]),"+f"(d[10]),"+f"(d[11]),"+f"(d[12]),"+f"(d[13]),"+f"(d[14]),"+f"(d[15]),"+f"(d[16]),"+f"(d[17]),"+f"(d[18]),"+f"(d[19]),"+f"(d[20]),"+f"(d[21]),"+f"(d[22]),"+f"(d[23]),"+f"(d[24]),"+f"(d[25]),"+f"(d[26]),"+f"(d[27]),"+f"(d[28]),"+f"(d[29]),"+f"(d[30]),"+f"(d[31])
   : "l"(da), "l"(db), "r"(sd));
}
template<> __device__ __forceinline__ void wgmma_ss<64,0,1>(float* d, uint64_t da, uint64_t db, int sd) {
  asm volatile("{\n.reg .pred p;\nsetp.ne.b32 p, %34, 0;\nwgmma.mma_async.sync.aligned.m64n64k16.f32.bf16.bf16 {%0,%1,%2,%3,%4,%5,%6,%7,%8,%9,%10,%11,%12,%13,%14,%15,%16,%17,%18,%19,%20,%21,%22,%23,%24,%25,%26,%27,%28,%29,%30,%31}, %32, %33, p, 1, 1, 0, 1;\n}\n"
   : "+f"(d[0]),"+f"(d[1]),"+f"(d[2]),"+f"(d[3]),"+f"(d[4]),"+f"(d[5]),"+f"(d[6]),"+f"(d[7]),"+f"(d[8]),"+f"(d[9]),"+f"(d[10]),"+f"(d[11]),"+f"(d[12]),"+f"(d[13]),"+f"(d[14]),"+f"(d[15]),"+f"(d[16]),"+f"(d[17]),"+f"(d[18]),"+f"(d[19]),"+f"(d[20]),"+f"(d[21]),"+f"(d[22]),"+f"(d[23]),"+f"(d[24]),"+f"(d[25]),"+f"(d[26]),"+f"(d[27]),"+f"(d[28]),"+f"(d[29]),"+f"(d[30]),"+f"(d[31])
   : "l"(da), "l"(db), "r"(sd));
}
template<> __device__ __forceinline__ void wgmma_ss<192,0,1>(float* d, uint64_t da, uint64_t db, int sd) {
  asm volatile("{\n.reg .pred p;\nsetp.ne.b32 p, %98, 0;\nwgmma.mma_async.sync.aligned.m64n192k16.f32.bf16.bf16 {%0,%1,%2,%3,%4,%5,%6,%7,%8,%9,%10,%11,%12,%13,%14,%15,%16,%17,%18,%19,%20,%21,%22,%23,%24,%25,%26,%27,%28,%29,%30,%31,%32,%33,%34,%35,%36,%37,%38,%39,%40,%41,%42,%43,%44,%45,%46,%47,%48,%49,%50,%51,%52,%53,%54,%55,%56,%57,%58,%59,%60,%61,%62,%63,%64,%65,%66,%67,%68,%69,%70,%71,%72,%73,%74,%75,%76,%77,%78,%79,%80,%81,%82,%83,%84,%85,%86,%87,%88,%89,%90,%91,%92,%93,%94,%95}, %96, %97, p, 1, 1, 0, 1;\n}\n"
   : "+f"(d[0]),"+f"(d[1]),"+f"(d[2]),"+f"(d[3]),"+f"(d[4]),"+f"(d[5]),"+f"(d[6]),"+f"(d[7]),"+f"(d[8]),"+f"(d[9]),"+f"(d[10]),"+f"(d[11]),"+f"(d[12]),"+f"(d[13]),"+f"(d[14]),"+f"(d[15]),"+f"(d[16]),"+f"(d[17]),"+f"(d[18]),"+f"(d[19]),"+f"(d[20]),"+f"(d[21]),"+f"(d[22]),"+f"(d[23]),"+f"(d[24]),"+f"(d[25]),"+f"(d[26]),"+f"(d[27]),"+f"(d[28]),"+f"(d[29]),"+f"(d[30]),"+f"(d[31]),"+f"(d[32]),"+f"(d[33]),"+f"(d[34]),"+f"(d[35]),"+f"(d[36]),"+f"(d[37]),"+f"(d[38]),"+f"(d[39]),"+f"(d[40]),"+f"(d[41]),"+f"(d[42]),"+f"(d[43]),"+f"(d[44]),"+f"(d[45]),"+f"(d[46]),"+f"(d[47]),"+f"(d[48]),"+f"(d[49]),"+f"(d[50]),"+f"(d[51]),"+f"(d[52]),"+f"(d[53]),"+f"(d[54]),"+f"(d[55]),"+f"(d[56]),"+f"(d[57]),"+f"(d[58]),"+f"(d[59]),"+f"(d[60]),"+f"(d[61]),"+f"(d[62]),"+f"(d[63]),"+f"(d[64]),"+f"(d[65]),"+f"(d[66]),"+f"(d[67]),"+f"(d[68]),"+f"(d[69]),"+f"(d[70]),"+f"(d[71]),"+f"(d[72]),"+f"(d[73]),"+f"(d[74]),"+f"(d[75]),"+f"(d[76]),"+f"(d[77]),"+f"(d[78]),"+f"(d[79]),"+f"(d[80]),"+f"(d[81]),"+f"(d[82]),"+f"(d[83]),"+f"(d[84]),"+f"(d[85]),"+f"(d[86]),"+f"(d[87]),"+f"(d[88]),"+f"(d[89]),"+f"(d[90]),"+f"(d[91]),"+f"(d[92]),"+f"(d[93]),"+f"(d[94]),"+f"(d[95])
   : "l"(da), "l"(db), "r"(sd));
}
template<> __device__ __forceinline__ void wgmma_ss<192,1,1>(float* d, uint64_t da, uint64_t db, int sd) {
  asm volatile("{\n.reg .pred p;\nsetp.ne.b32 p, %98, 0;\nwgmma.mma_async.sync.aligned.m64n192k16.f32.bf16.bf16 {%0,%1,%2,%3,%4,%5,%6,%7,%8,%9,%10,%11,%12,%13,%14,%15,%16,%17,%18,%19,%20,%21,%22,%23,%24,%25,%26,%27,%28,%29,%30,%31,%32,%33,%34,%35,%36,%37,%38,%39,%40,%41,%42,%43,%44,%45,%46,%47,%48,%49,%50,%51,%52,%53,%54,%55,%56,%57,%58,%59,%60,%61,%62,%63,%64,%65,%66,%67,%68,%69,%70,%71,%72,%73,%74,%75,%76,%77,%78,%79,%80,%81,%82,%83,%84,%85,%86,%87,%88,%89,%90,%91,%92,%93,%94,%95}, %96, %97, p, 1, 1, 1, 1;\n}\n"
   : "+f"(d[0]),"+f"(d[1]),"+f"(d[2]),"+f"(d[3]),"+f"(d[4]),"+f"(d[5]),"+f"(d[6]),"+f"(d[7]),"+f"(d[8]),"+f"(d[9]),"+f"(d[10]),"+f"(d[11]),"+f"(d[12]),"+f"(d[13]),"+f"(d[14]),"+f"(d[15]),"+f"(d[16]),"+f"(d[17]),"+f"(d[18]),"+f"(d[19]),"+f"(d[20]),"+f"(d[21]),"+f"(d[22]),"+f"(d[23]),"+f"(d[24]),"+f"(d[25]),"+f"(d[26]),"+f"(d[27]),"+f"(d[28]),"+f"(d[29]),"+f"(d[30]),"+f"(d[31]),"+f"(d[32]),"+f"(d[33]),"+f"(d[34]),"+f"(d[35]),"+f"(d[36]),"+f"(d[37]),"+f"(d[38]),"+f"(d[39]),"+f"(d[40]),"+f"(d[41]),"+f"(d[42]),"+f"(d[43]),"+f"(d[44]),"+f"(d[45]),"+f"(d[46]),"+f"(d[47]),"+f"(d[48]),"+f"(d[49]),"+f"(d[50]),"+f"(d[51]),"+f"(d[52]),"+f"(d[53]),"+f"(d[54]),"+f"(d[55]),"+f"(d[56]),"+f"(d[57]),"+f"(d[58]),"+f"(d[59]),"+f"(d[60]),"+f"(d[61]),"+f"(d[62]),"+f"(d[63]),"+f"(d[64]),"+f"(d[65]),"+f"(d[66]),"+f"(d[67]),"+f"(d[68]),"+f"(d[69]),"+f"(d[70]),"+f"(d[71]),"+f"(d[72]),"+f"(d[73]),"+f"(d[74]),"+f"(d[75]),"+f"(d[76]),"+f"(d[77]),"+f"(d[78]),"+f"(d[79]),"+f"(d[80]),"+f"(d[81]),"+f"(d[82]),"+f"(d[83]),"+f"(d[84]),"+f"(d[85]),"+f"(d[86]),"+f"(d[87]),"+f"(d[88]),"+f"(d[89]),"+f"(d[90]),"+f"(d[91]),"+f"(d[92]),"+f"(d[93]),"+f"(d[94]),"+f"(d[95])
   : "l"(da), "l"(db), "r"(sd));
}

template <bool TR>
__device__ __forceinline__ void gemm_section(float* acc, float& mean0, float& mean1, float& rstd0, float& rstd1,
                                             uint32_t sb, int blk, int hg, int wg, int w, int lane) {
  constexpr int layer = TR ? 1 : 0;
  constexpr int TURN = TR ? TURN1 : TURN0;
  constexpr int LSTAT = TURN < 4 ? TURN - 1 : 3;
  const uint32_t bar = sb + SM_BAR;
  const int g = lane >> 2, t = lane & 3;
  const bool leader = (w == 0) && (lane == 0);
  const int statpos = hg < 3 ? 1 : wg ? LSTAT : 2;
  const bool copy = hg >= 3 && wg == 0;
  const int cut = wg ? TURN : 4;
  auto wait_full = [&](int c) {
    mbar_wait(bar + 8 * (B_XF + 8 * wg + c), layer);
    mbar_wait(bar + 8 * (B_WF + c), layer);
  };
  auto peek = [&](int c) {
    const bool x = mbar_test(bar + 8 * (B_XF + 8 * wg + c), layer), y = mbar_test(bar + 8 * (B_WF + c), layer);
    return x && y;
  };
  const uint64_t da0 = mkdesc(sb, TR ? 8192 : 16, 1024, 1), db0 = mkdesc(sb, 8192, 1024, 1);
  uint32_t xt = wg ? 0xfedcba98u : 0x21043210u;
  uint64_t wt = 0x0816131005161310ull;
  uint64_t da = da0 + ((xt & 15) << 9), db = db0 + (16 << 9);
  auto issue = [&](int c, int first) {
    wg_fence();
#pragma unroll
    for (int ks = 0; ks < 4; ks++) wgmma_ss<192, TR ? 1 : 0, 1>(acc, da + (TR ? ks * 128 : ks * 2), db + ks * 128, !first || ks != 0);
    wg_commit();
    xt >>= 4; wt >>= 8;
    da = da0 + ((xt & 15) << 9); db = db0 + (((uint32_t)wt & 31) << 9);
  };
  wait_full(0);
  bool ready = peek(1);
  issue(0, 1);
  TSW(0);
#pragma unroll 1
  for (int c = 1; c < cut; c++) {
    if (!ready) wait_full(c);
    issue(c, 0);
    ready = peek(c + 1);
    wg_wait<1>();
    if (leader) mbar_arrive(bar + 8 * (B_DN + 8 * wg + c - 1));
    if (wg == 1 && c == cut - 1) {
      wg_wait<0>();
      if (leader) mbar_arrive(bar + 8 * (B_DN + 8 + c));
    }
    if (c == statpos) {
      mbar_wait(bar + 8 * (copy ? B_SC : B_XF + 8 * wg + hg), layer);
      uint32_t A[16];
      const uint32_t xb = sb + (copy ? P_R : 8 * wg + hg) * PG;
#pragma unroll
      for (int ks = 0; ks < 4; ks++) {
        if (!TR) {
          const int row = 16 * w + (lane & 15), kc = 2 * ks + (lane >> 4);
          ldsm4(&A[4 * ks], xb + row * 128 + ((kc ^ (row & 7)) << 4));
        } else {
          const int k = 16 * ks + (lane & 7) + 8 * (lane >> 4), pc = 2 * w + ((lane >> 3) & 1);
          ldsm4t(&A[4 * ks], xb + k * 128 + ((pc ^ (k & 7)) << 4));
        }
      }
      float s0 = 0.f, q0 = 0.f, s1 = 0.f, q1 = 0.f;
#pragma unroll
      for (int i = 0; i < 16; i += 2) {
        const float a = bf_lo(A[i]), b = bf_hi(A[i]), c_ = bf_lo(A[i + 1]), d = bf_hi(A[i + 1]);
        s0 += a + b; q0 = fmaf(a, a, q0); q0 = fmaf(b, b, q0);
        s1 += c_ + d; q1 = fmaf(c_, c_, q1); q1 = fmaf(d, d, q1);
      }
#pragma unroll
      for (int o = 1; o <= 2; o <<= 1) {
        s0 += __shfl_xor_sync(~0u, s0, o); q0 += __shfl_xor_sync(~0u, q0, o);
        s1 += __shfl_xor_sync(~0u, s1, o); q1 += __shfl_xor_sync(~0u, q1, o);
      }
      if (t < 2)
        asm volatile("red.relaxed.gpu.global.add.v4.f32 [%0], {%1,%2,%3,%4};" ::"l"(g_rows + layer * LSEQ + blk * 64 + 16 * w + g + 8 * t),
                     "f"(t ? s1 : s0), "f"(t ? q1 : q0), "f"(1.f), "f"(0.f) : "memory");
    }
  }
  if (wg == 1) {
#pragma unroll 1
    for (int c = cut; c < 8; c++) wait_full(c);
    ready = true;
    bar_sync(5, 256);
  }
#pragma unroll 1
  for (int c = cut; c < 8; c++) {
    if (!ready) wait_full(c);
    issue(c, 0);
    if (wg == 1) {
      wg_wait<2>();
      if (leader && c >= cut + 2) mbar_arrive(bar + 8 * (B_DN + 8 + c - 2));
    } else if (c == 7) {
      bar_arrive(5, 256);
    } else {
      ready = peek(c + 1);
      wg_wait<1>();
      if (leader) mbar_arrive(bar + 8 * (B_DN + c - 1));
    }
  }
  mbar_wait(bar + 8 * (B_LN + wg), layer);
  const float4 ln = lds128f(sb + ln_off(wg) + (8 * w + g) * 16);
  mean0 = ln.x; rstd0 = ln.y; mean1 = ln.z; rstd1 = ln.w;
  wg_wait<0>();
  acc_fence<96>(acc);
  if (leader) mbar_arrive(bar + 8 * (B_DN + 8 * wg + 7));
}

__device__ __forceinline__ void attn_phase(const Params& p, uint32_t sb, int layer, int rb, int hg, int wg, int w) {
  const int lane = opaque_tid() & 31;
  const int g = lane >> 2, t = lane & 3;
  const uint32_t bar = sb + SM_BAR;
  const int blk = 16 * wg + rb;
  float acc[96];
  float2 cs[24];
  float mean0, mean1, rstd0, rstd1;
  if (layer) gemm_section<true>(acc, mean0, mean1, rstd0, rstd1, sb, blk, hg, wg, w, lane);
  else gemm_section<false>(acc, mean0, mean1, rstd0, rstd1, sb, blk, hg, wg, w, lane);
  TSW(1);
#pragma unroll
  for (int j = 8; j < 24; j++) cs[j] = lds64f(sb + SM_CS + 4 * (8 * j + 2 * t));
  const uint32_t kvx = sb + (wg ? 22 : 0) * PG;

  uint32_t kb[4][8], vb[4][8], qa[4][4];
  {
    const float nm0 = -mean0 * rstd0, nm1 = -mean1 * rstd1;
    const int st_row = 16 * w + (lane & 7) + 8 * ((lane >> 3) & 1);
    const uint32_t st_base = kvx + st_row * 256;
    const bool sender = (w == 3 && blk < 31);
    uint4* halo = &g_halo[((layer * 32 + blk) * 8 + hg) * 256 + lane];
    uint32_t r[4][2][4];
#pragma unroll
    for (int h = 0; h < 4; h++) {
#pragma unroll
      for (int kv = 0; kv < 2; kv++) {
#pragma unroll
        for (int dh = 0; dh < 2; dh++) {
          const int j = 8 + kv * 8 + 2 * h + dh;
          const float2 c2 = cs[j];
          const float v0 = fmaf(acc[4 * j + 0], rstd0, nm0 * c2.x), v1 = fmaf(acc[4 * j + 1], rstd0, nm0 * c2.y);
          const float v2 = fmaf(acc[4 * j + 2], rstd1, nm1 * c2.x), v3 = fmaf(acc[4 * j + 3], rstd1, nm1 * c2.y);
          r[h][kv][2 * dh] = packbf(v0, v1);
          r[h][kv][2 * dh + 1] = packbf(v2, v3);
        }
      }
      if (sender) {
        stg128(halo + (2 * h) * 32, make_uint4(r[h][0][0], r[h][0][2], r[h][0][1], r[h][0][3]));
        stg128(halo + (2 * h + 1) * 32, make_uint4(r[h][1][0], r[h][1][1], r[h][1][2], r[h][1][3]));
      }
    }
#pragma unroll
    for (int j = 0; j < 8; j++) cs[j] = lds64f(sb + SM_CS + 4 * (8 * j + 2 * t));
    mbar_wait(bar + 8 * (B_DN + 7), layer);
#pragma unroll
    for (int h = 0; h < 4; h++) {
#pragma unroll
      for (int kv = 0; kv < 2; kv++) {
        const int chunk = 4 * h + 2 * kv + (lane >> 4);
        if (w < 3) stsm4(st_base + (((chunk & 8) | ((chunk ^ st_row) & 7)) << 4), r[h][kv][0], r[h][kv][1], r[h][kv][2], r[h][kv][3]);
      }
      kb[h][4] = r[h][0][0]; kb[h][5] = r[h][0][2]; kb[h][6] = r[h][0][1]; kb[h][7] = r[h][0][3];
      vb[h][4] = movm_t(r[h][1][0]); vb[h][5] = movm_t(r[h][1][1]); vb[h][6] = movm_t(r[h][1][2]); vb[h][7] = movm_t(r[h][1][3]);
    }
#pragma unroll
    for (int h = 0; h < 4; h++) {
#pragma unroll
      for (int dh = 0; dh < 2; dh++) {
        const int j = 2 * h + dh;
        const float2 c2 = cs[j];
        qa[h][2 * dh] = packbf(fmaf(-mean0, c2.x, acc[4 * j + 0]), fmaf(-mean0, c2.y, acc[4 * j + 1]));
        qa[h][2 * dh + 1] = packbf(fmaf(-mean1, c2.x, acc[4 * j + 2]), fmaf(-mean1, c2.y, acc[4 * j + 3]));
      }
    }
  }
  bar_sync(2 + wg, 128);
  TSW(2);
  {
    const uint32_t prev_base = kvx + (16 * w - 16) * 256;
    const int mi = lane >> 3;
    const int r = 8 * (mi >> 1) + (lane & 7), r2 = 8 * (mi & 1) + (lane & 7);
    if (w != 0) {
#pragma unroll
      for (int h = 0; h < 4; h++) {
        const int ch = 4 * h + (mi & 1), ch2 = 4 * h + 2 + (mi >> 1);
        ldsm4(&kb[h][0], prev_base + r * 256 + (((ch & 8) | ((ch ^ r) & 7)) << 4));
        ldsm4t(&vb[h][0], prev_base + r2 * 256 + (((ch2 & 8) | ((ch2 ^ r2) & 7)) << 4));
      }
    } else if (blk > 0) {
      const uint4* src = &g_halo[((layer * 32 + blk - 1) * 8 + hg) * 256 + lane];
      uint4 hv[8];
      int it = 0;
      bool ok;
      do {
        ok = true;
#pragma unroll
        for (int i = 0; i < 8; i++) hv[i] = ld_tagged(src + i * 32);
#pragma unroll
        for (int i = 0; i < 8; i++) ok = ok && hv[i].x != UNSET;
      } while (!__all_sync(~0u, ok) && ++it < (1 << 20));
#pragma unroll
      for (int h = 0; h < 4; h++) {
        kb[h][0] = hv[2 * h].x; kb[h][1] = hv[2 * h].y; kb[h][2] = hv[2 * h].z; kb[h][3] = hv[2 * h].w;
        vb[h][0] = movm_t(hv[2 * h + 1].x); vb[h][1] = movm_t(hv[2 * h + 1].y);
        vb[h][2] = movm_t(hv[2 * h + 1].z); vb[h][3] = movm_t(hv[2 * h + 1].w);
      }
    } else {
#pragma unroll
      for (int h = 0; h < 4; h++)
#pragma unroll
        for (int k = 0; k < 4; k++) kb[h][k] = vb[h][k] = 0u;
    }
    TSW(3);
  }
  mbar_wait(bar + 8 * (B_DN + 15), layer);
  TSW(4);

  const bool first = (blk == 0 && w == 0);
  const int e = t - (g >> 1);
  const bool par = g & 1, epos = e >= 1;
  const uint32_t pmask = par ? 0xffff0000u : 0x0000ffffu;
  const uint32_t mB0 = epos ? pmask : 0u, mB1 = epos ? 0u : pmask;
  const float cl2 = 0.25f * 1.4426950408889634f;
  const float sc0 = rstd0 * cl2, sc1 = rstd1 * cl2;
  const float NEG = -INFINITY;
  float vA0[4], vB0[4], vA1[4], vB1[4];
#pragma unroll
  for (int h = 0; h < 4; h++) {
    float S[4][4];
#pragma unroll
    for (int j = 0; j < 4; j++) {
      S[j][0] = S[j][1] = S[j][2] = S[j][3] = 0.f;
      mma_bf16(S[j], qa[h], kb[h][2 * j], kb[h][2 * j + 1]);
    }
    vA0[h] = par ? S[1][1] : S[1][0];
    vB0[h] = epos ? (par ? S[0][1] : S[0][0]) : (par ? S[2][1] : S[2][0]);
    vA1[h] = par ? S[2][3] : S[2][2];
    vB1[h] = epos ? (par ? S[1][3] : S[1][2]) : (par ? S[3][3] : S[3][2]);
    if (first) { vA0[h] = NEG; if (epos) { vB0[h] = NEG; vB1[h] = NEG; } }
  }
  float m0[4], m1[4];
#pragma unroll
  for (int h = 0; h < 4; h++) { m0[h] = fmaxf(vA0[h], vB0[h]); m1[h] = fmaxf(vA1[h], vB1[h]); }
#pragma unroll
  for (int o = 1; o <= 2; o <<= 1) {
#pragma unroll
    for (int h = 0; h < 4; h++) {
      m0[h] = fmaxf(m0[h], __shfl_xor_sync(~0u, m0[h], o));
      m1[h] = fmaxf(m1[h], __shfl_xor_sync(~0u, m1[h], o));
    }
  }
  float O0[4][4], O1[4][4], Z[4][4];
#pragma unroll
  for (int h = 0; h < 4; h++) {
    const float mm0 = -m0[h] * sc0, mm1 = -m1[h] * sc1;
    const float pA0 = ex2(fmaf(vA0[h], sc0, mm0)), pB0 = ex2(fmaf(vB0[h], sc0, mm0));
    const float pA1 = ex2(fmaf(vA1[h], sc1, mm1)), pB1 = ex2(fmaf(vB1[h], sc1, mm1));
    const uint32_t hA0 = packbf(pA0, pA0), hB0 = packbf(pB0, pB0), hA1 = packbf(pA1, pA1), hB1 = packbf(pB1, pB1);
    const uint32_t P0[4] = {hB0 & mB0, 0u, hA0 & pmask, hB1 & mB0};
    const uint32_t P1[4] = {hB0 & mB1, hA1 & pmask, 0u, hB1 & mB1};
#pragma unroll
    for (int k = 0; k < 4; k++) O0[h][k] = O1[h][k] = Z[h][k] = 0.f;
    mma_bf16(O0[h], P0, vb[h][0], vb[h][1]); mma_bf16(O1[h], P0, vb[h][2], vb[h][3]); mma_bf16(Z[h], P0, 0x3f803f80u, 0x3f803f80u);
    mma_bf16(O0[h], P1, vb[h][4], vb[h][5]); mma_bf16(O1[h], P1, vb[h][6], vb[h][7]); mma_bf16(Z[h], P1, 0x3f803f80u, 0x3f803f80u);
  }
  if (lane == 0) mbar_arrive(bar + 8 * (B_OST + wg));
  uint4* op = (uint4*)g_O + ((layer * 32 + blk) * 8 + hg) * 512 + 64 * t + 16 * w + g;
#pragma unroll
  for (int h = 0; h < 4; h += 2) {
    const float i0 = rcp_approx(Z[h][0]), i1 = rcp_approx(Z[h][2]), j0 = rcp_approx(Z[h + 1][0]), j1 = rcp_approx(Z[h + 1][2]);
    stg128(op + 128 * h, make_uint4(packbf(O0[h][0] * i0, O0[h][1] * i0), packbf(O1[h][0] * i0, O1[h][1] * i0),
                                   packbf(O0[h + 1][0] * j0, O0[h + 1][1] * j0), packbf(O1[h + 1][0] * j0, O1[h + 1][1] * j0)));
    stg128(op + 128 * h + 8, make_uint4(packbf(O0[h][2] * i1, O0[h][3] * i1), packbf(O1[h][2] * i1, O1[h][3] * i1),
                                            packbf(O0[h + 1][2] * j1, O0[h + 1][3] * j1), packbf(O1[h + 1][2] * j1, O1[h + 1][3] * j1)));
  }
  TSW(5);
  __syncwarp();
  if (lane == 0) red_relaxed(&g_cnt[(C_O + layer * 32 + blk) * 32]);
  TSW(6);
}

#define PDELAY 0
#define PGATE 1
__device__ __forceinline__ void proj_phase(const Params& p, uint32_t sb, int layer, int rb, int q, int wg, int w, int& rtp) {
  const int lane = opaque_tid() & 31;
  const bool TR = layer != 0;
  const int t = lane & 3;
  const uint32_t bar = sb + SM_BAR;
  const uint32_t rbx = sb + (P_R + wg) * PG;
  const uint32_t rsrc = sb + (wg ? 2 : P_R) * PG;
  const int blk = 16 * wg + rb;
  uint32_t res[16];
  mbar_wait(bar + 8 * (B_RF + wg), layer);
  if (!TR) {
#pragma unroll
    for (int j = 0; j < 8; j += 2) {
      const int mi = lane >> 3;
      const int row = 16 * w + (lane & 7) + 8 * (mi & 1), ch = j + (mi >> 1);
      ldsm4(&res[2 * j], rsrc + row * 128 + ((ch ^ (row & 7)) << 4));
    }
  } else {
#pragma unroll
    for (int j = 0; j < 8; j += 2) {
      const int mi = lane >> 3;
      const int line = 8 * (j + (mi >> 1)) + (lane & 7), pc = 2 * w + (mi & 1);
      ldsm4t(&res[2 * j], rsrc + line * 128 + ((pc ^ (line & 7)) << 4));
    }
  }
  if (layer) mbar_wait(bar + 8 * (B_RS + 1), 0);
  fence_async_global();
  const uint32_t stg = sb + (wg ? SM_KGT : SM_STG);
  if (wg) mbar_wait(bar + 8 * B_PST, layer);
  bool clean = false;
#pragma unroll 1
  for (int attempt = 0; attempt < MAX_RETRY; attempt++) {
  float acc[32];
#pragma unroll
  for (int j = 0; j < 16; j++) { acc[2 * j] = bf_lo(res[j]); acc[2 * j + 1] = bf_hi(res[j]); }
  acc_fence<32>(acc);
#pragma unroll
  for (int c = 0; c < 4; c++) {
    mbar_wait(bar + 8 * (B_WOF + c), layer);
    mbar_wait(bar + 8 * (B_OF + 4 * wg + c), layer);
    if (c == 0) TSW(7);
    const uint64_t da = mkdesc(sb + o_page(wg, c) * PG, 1024, 128, 0);
    wg_fence();
#pragma unroll
    for (int ks = 0; ks < 8; ks++)
      wgmma_ss<64, 0, 1>(acc, da + ks * 128, mkdesc(sb + wo_page(2 * c + (ks >> 2)) * PG, 8192, 1024, 1) + (ks & 3) * 128, 1);
    wg_commit();
  }
  if (wg) mbar_wait(bar + 8 * B_KG, 0);
  wg_wait<0>();
  acc_fence<32>(acc);
  TSW(8);
  if (!clean) {
    const float chk = acc[0] + acc[2];
    clean = __all_sync(~0u, chk == chk);
    if (clean && lane == 0) mbar_arrive(bar + 8 * (B_PDONE + wg));
  }
  float s0 = 0.f, q0 = 0.f, s1 = 0.f, q1 = 0.f;
  uint32_t o[16];
#pragma unroll
  for (int j = 0; j < 8; j++) {
    const float a = acc[4 * j], b = acc[4 * j + 1], c = acc[4 * j + 2], d = acc[4 * j + 3];
    o[2 * j] = packbf(a, b);
    o[2 * j + 1] = packbf(c, d);
    s0 += a + b; q0 = fmaf(a, a, q0); q0 = fmaf(b, b, q0);
    s1 += c + d; q1 = fmaf(c, c, q1); q1 = fmaf(d, d, q1);
  }
#pragma unroll
  for (int j = 0; j < 8; j += 2) {
    const int mi = lane >> 3;
    const int line = 8 * (j + (mi >> 1)) + (lane & 7), pc = 2 * w + (mi & 1);
    stsm4t(rbx + line * 128 + ((pc ^ (line & 7)) << 4), o[2 * j], o[2 * j + 1], o[2 * j + 2], o[2 * j + 3]);
  }
#pragma unroll
  for (int o2 = 1; o2 <= 2; o2 <<= 1) {
    s0 += __shfl_xor_sync(~0u, s0, o2); q0 += __shfl_xor_sync(~0u, q0, o2);
    s1 += __shfl_xor_sync(~0u, s1, o2); q1 += __shfl_xor_sync(~0u, q1, o2);
  }
  {
    const int i = 2 * (lane >> 2) + (t & 1), k = (i * 11) >> 5;
    const float v = (t == 0) ? s0 : (t == 1) ? q0 : (t == 2) ? s1 : q1;
    sts32f(stg + k * 128 + (2 * w + (t >> 1)) * 16 + (i - 3 * k) * 4, v);
  }
  TSW(9);
  fence_async_smem();
  if (!bar_or(2 + wg, 128, !clean)) break;
  bool unset = false;
#pragma unroll
  for (int i = 0; i < 4; i++) unset |= lds32(sb + o_page(wg, i) * PG + (32 * w + lane) * 128) == UNSET;
  if (!bar_or(2 + wg, 128, unset)) break;
  if (w == 0 && elect_one()) {
    fence_async_smem();
    mbar_expect(bar + 8 * (B_RT + wg), 8 * PG);
#pragma unroll 1
    for (int c = 0; c < 4; c++) bulk_ld(sb + o_page(wg, c) * PG, g_O + ((layer * 32 + blk) * 4 + c) * PG, 2 * PG, bar + 8 * (B_RT + wg));
  }
  mbar_wait(bar + 8 * (B_RT + wg), rtp);
  rtp ^= 1;
  RETRY(0);
  }
  if (!clean && lane == 0) mbar_arrive(bar + 8 * (B_PDONE + wg));
  if (w == 0 && elect_one()) {
    tma_st(&p.mapXT, blk * 64, (2 * layer) * DM + q * 64, rbx);
    bulk_red_add_f32(g_stats + (layer * 32 + blk) * 192, stg, 768);
    bulk_commit();
    red_relaxed(&g_cnt[(C_G + 2 * layer + wg) * 32]);
  }
  TSW(10);
}

__device__ __forceinline__ void conv_load(uint32_t* A, uint32_t pe) {
#pragma unroll
  for (int m = 0; m < 17; m++) {
    A[4 * m + 2] = lds32(pe + 4 * (64 * m - 8));
    A[4 * m + 0] = lds32(pe + 4 * (64 * m));
    A[4 * m + 1] = lds32(pe + 4 * (64 * m + 8));
    asm volatile("mov.b32 %0, %1;" : "=r"(A[4 * m + 3]) : "r"(A[4 * m + 0]));
  }
}
template <int M> __device__ __forceinline__ void conv_tri(float* acc, const uint32_t* A, uint64_t d) {
  if constexpr (M < 16) {
    wgmma_rs<64 - 8 * (M / 2), 0>(acc, A + 4 * M, d + (uint64_t)(64 + 4 * M), M != 0);
    conv_tri<M + 1>(acc, A, d);
  }
}
__device__ __forceinline__ void conv_mma0(float* acc, const uint32_t* A, uint64_t d) {
  wg_fence();
  conv_tri<0>(acc, A, d);
  wg_commit();
}
__device__ __forceinline__ void conv_mma1(float* acc, const uint32_t* A, uint64_t d, uint64_t ds, uint64_t df) {
  wg_fence();
#pragma unroll
  for (int m = 0; m < 17; m++) wgmma_rs<64, 0>(acc, A + 4 * m, d + (uint64_t)(4 * m), m != 0);
  wgmma_ss<64, 1, 0>(acc, ds, df, 1);
  wgmma_ss<64, 1, 0>(acc, ds + 128, df + 128, 1);
  wg_commit();
}
__device__ __forceinline__ void conv_store(float* acc, uint32_t pb, uint32_t over, int w) {
  acc_fence<32>(acc);
  const int l = opaque_tid() & 31, mt = l >> 3;
  int c = 2 * (63 - 8 * (mt >> 1) - (l & 7) + w) + (mt & 1);
  c ^= (c >> 3) & 1;
  const uint32_t a0 = pb + c * 16;
#pragma unroll
  for (int j = 0; j < 8; j += 2)
    stsm4t(j == 0 ? (c < 128 ? a0 : over + (c - 128) * 16) : a0 - 256 * j, packbf(acc[4 * j], acc[4 * j + 1]), packbf(acc[4 * j + 2], acc[4 * j + 3]),
           packbf(acc[4 * j + 4], acc[4 * j + 5]), packbf(acc[4 * j + 6], acc[4 * j + 7]));
}
__device__ __forceinline__ void conv_sums(uint32_t sb, int lc, int ht) {
  const int m = ht - 1;
  uint4 v[2][3];
#pragma unroll
  for (int c = 0; c < 2; c++)
#pragma unroll
    for (int k = 0; k < 3; k++) {
      const int mm = m - 1 + k;
      v[c][k] = lds128(sb + cv_u(lc + c) + (mm >= 0 ? (mm & 1) * CV_UH + (127 - (mm >> 1)) * 16 : 128 * 16));
    }
  const int ce = m + 2, co = m + 1;
#pragma unroll
  for (int c = 0; c < 2; c++) {
    const uint32_t x[8] = {v[c][0].z, v[c][0].w, v[c][1].x, v[c][1].y, v[c][1].z, v[c][1].w, v[c][2].x, v[c][2].y};
    float pv[16];
#pragma unroll
    for (int k = 0; k < 8; k++) { pv[2 * k] = bf_lo(x[k]); pv[2 * k + 1] = bf_hi(x[k]); }
    float t2[15], t4[13], s9[8], s7[8];
#pragma unroll
    for (int i = 0; i < 15; i++) t2[i] = pv[i] + pv[i + 1];
#pragma unroll
    for (int i = 0; i < 13; i++) t4[i] = t2[i] + t2[i + 2];
#pragma unroll
    for (int i = 0; i < 8; i++) {
      s9[i] = (t4[i] + t4[i + 4]) + pv[i + 8];
      s7[i] = (t4[i + 1] + t2[i + 5]) + pv[i + 7];
    }
    const uint4 e4 = make_uint4(packbf(s9[0], s9[1]), packbf(s9[2], s9[3]), packbf(s9[4], s9[5]), packbf(s9[6], s9[7]));
    if (ce < 128) sts128(sb + cv_se(lc + c) + ((ce ^ ((ce >> 3) & 7)) << 4), e4);
    else sts128(sb + cv_se(lc + c), make_uint4(0, 0, 0, 0));
    sts128(sb + cv_so(lc + c) + ((co ^ ((co >> 3) & 7)) << 4),
           make_uint4(packbf(s7[0], s7[1]), packbf(s7[2], s7[3]), packbf(s7[4], s7[5]), packbf(s7[6], s7[7])));
  }
}

template <int HALF, int NCH, int STEP = 1>
__device__ __forceinline__ void conv_epi(uint32_t sb, bf16* out, int lc, int c) {
  uint4 v[NCH][4], xr[NCH];
  const uint32_t sw = (c ^ ((c >> 3) & 1)) * 16;
#pragma unroll
  for (int u = 0; u < NCH; u++) {
#pragma unroll
    for (int k = 0; k < 4; k++) v[u][k] = lds128(sb + (HALF ? cv_pb1(lc + STEP * u, k) : cv_pb0(lc + STEP * u, k)) + sw);
    xr[u] = lds128(sb + cv_x(HALF, lc + STEP * u) + c * 16);
  }
#pragma unroll
  for (int u = 0; u < NCH; u++) {
    uint4 o;
    o.x = hadd2(xr[u].x, hadd2(hadd2(v[u][0].x, v[u][1].x), hadd2(v[u][2].x, v[u][3].x)));
    o.y = hadd2(xr[u].y, hadd2(hadd2(v[u][0].y, v[u][1].y), hadd2(v[u][2].y, v[u][3].y)));
    o.z = hadd2(xr[u].z, hadd2(hadd2(v[u][0].z, v[u][1].z), hadd2(v[u][2].z, v[u][3].z)));
    o.w = hadd2(xr[u].w, hadd2(hadd2(v[u][0].w, v[u][1].w), hadd2(v[u][2].w, v[u][3].w)));
    stg128(out + cv_chan(0, lc + STEP * u) * LSEQ + HALF * 1024 + c * 8, o);
  }
}

__device__ __forceinline__ bool prep_valid(const uint4 (&st)[6], const uint4 (&xr)[4]) {
  const uint32_t n = __float_as_uint(8.f);
  return st[0].w == n && st[1].w == n && st[2].w == n && st[3].w == n && st[4].w == n && (st[5].w | st[5].y | st[5].z) == n &&
         xr[0].x != UNSET && xr[1].x != UNSET && xr[2].x != UNSET && xr[3].x != UNSET;
}
template <int HALF>
__device__ __forceinline__ void conv_prep(uint32_t sb, int layer, int cta, int i) {
  uint4 st[6], xr[4];
  const uint4* sp = (const uint4*)g_stats + (layer * 32 + HALF * 16 + (i >> 3)) * 48 + (i & 7);
  const uint4* xp = (const uint4*)g_xT + (2 * layer * DM + 2 * cta) * (LSEQ / 8) + HALF * 128 + i;
  auto fetch = [&]() {
#pragma unroll
    for (int k = 0; k < 6; k++) st[k] = ld_tagged(sp + 8 * k);
#pragma unroll
    for (int k = 0; k < 4; k++) xr[k] = ld_tagged(xp + cv_chan(0, k) * (LSEQ / 8));
  };
  if (HALF) {
#pragma unroll
    for (int k = 0; k < 6; k++) st[k] = lds128(sb + CV_ST + (i >> 3) * 768 + k * 128 + (i & 7) * 16);
#pragma unroll
    for (int k = 0; k < 4; k++) xr[k] = lds128(sb + cv_x(1, k) + i * 16);
  } else {
    fetch();
  }
  int it = 0;
  while (!__all_sync(~0u, prep_valid(st, xr)) && ++it < MAX_RETRY) { fetch(); RETRY(1); }
  if (!HALF || it) {
#pragma unroll
    for (int k = 0; k < 4; k++) sts128(sb + cv_x(HALF, k) + i * 16, xr[k]);
  }
  const uint32_t v[16] = {st[0].x, st[0].y, st[0].z, st[1].x, st[1].y, st[1].z, st[2].x, st[2].y, st[2].z, st[3].x, st[3].y, st[3].z, st[4].x, st[4].y, st[4].z, st[5].x};
  uint32_t rs[4], nm[4];
#pragma unroll
  for (int k = 0; k < 4; k++) {
    const float m0 = __uint_as_float(v[4 * k]) * (-1.f / DM), m1 = __uint_as_float(v[4 * k + 2]) * (-1.f / DM);
    const float r0 = rsqrt_approx(fmaxf(fmaf(__uint_as_float(v[4 * k + 1]), 1.f / DM, -m0 * m0), 0.f) + 1e-5f);
    const float r1 = rsqrt_approx(fmaxf(fmaf(__uint_as_float(v[4 * k + 3]), 1.f / DM, -m1 * m1), 0.f) + 1e-5f);
    rs[k] = packbf(r0, r1);
    nm[k] = packbf(m0 * bf_lo(rs[k]), m1 * bf_hi(rs[k]));
  }
  const uint32_t ud = sb + (i & 1) * CV_UH + (127 - 64 * HALF - (i >> 1)) * 16;
#pragma unroll
  for (int k = 0; k < 4; k++)
    sts128(ud + cv_u(k), make_uint4(hfma2(xr[k].x, rs[0], nm[0]), hfma2(xr[k].y, rs[1], nm[1]), hfma2(xr[k].z, rs[2], nm[2]), hfma2(xr[k].w, rs[3], nm[3])));
  fence_async_smem();
}

#define AGATE 1
#define PP0 1
__device__ __forceinline__ void conv_phase(const Params& p, uint32_t sb, int layer, int cta) {
  const int tid = opaque_tid();
  const int wg = __shfl_sync(~0u, tid >> 7, 0), w = __shfl_sync(~0u, (tid >> 5) & 3, 0);
  const uint32_t bar = sb + SM_BAR;
  constexpr int CH2 = 4 * PG;
  bf16* xout = g_xT + ((2 * layer + 1) * DM + 2 * cta) * LSEQ;
  uint32_t A0[68], A1[68];
  float acc[32];
  const uint32_t pe = sb + cv_pe(wg) + 4 * (16 + 16 * w + ((tid & 31) >> 2) - 2 * (tid & 3));
  auto staged = [&]() {
    if (w == 0) {
      bulk_wait_read();
      __syncwarp();
      if (elect_one()) mbar_arrive(bar + 8 * (B_PST + wg));
    }
  };
  if (wg == 0) staged();
  mbar_wait(bar + 8 * (B_PDONE + 1), layer);
  mbar_wait(bar + 8 * B_PE, layer);
  conv_load(A0, pe);
  if (wg == 1) staged();
  conv_load(A1, pe + CH2);
  TSW(19);
  const uint64_t d0 = mkdesc(sb + cv_u(wg), CV_UH, 128, 0), d1 = d0 + (CH2 >> 4);
  mbar_wait(bar + 8 * B_U, layer);
  TSW(12);
  if (wg == 1) bar_sync(5, 256);
  conv_mma0(acc, A0, d0);
  if (wg == 0) bar_arrive(5, 256);
  mbar_wait(bar + 8 * (B_PDONE + 1), layer);
  {
    const int l = opaque_tid() & 31;
    if ((l & 15) < 2 * w) sts128(sb + cv_pb0(wg + 2 * (l >> 4), w) + (l & 15) * 16, make_uint4(0, 0, 0, 0));
  }
  wg_wait<0>();
  conv_store(acc, sb + cv_pb0(wg, w), sb + cv_pb1(wg, w), w);
  conv_mma0(acc, A1, d1);
  wg_wait<0>();
  conv_store(acc, sb + cv_pb0(2 + wg, w), sb + cv_pb1(2 + wg, w), w);
  TSW(13);
  bar_sync(2 + wg, 128);
  conv_epi<0, 2, 2>(sb, xout, wg, opaque_tid() & 127);
  TSW(14);
  mbar_arrive(bar + 8 * B_PUB);
  if (wg == 0) mbar_wait(bar + 8 * B_U1, layer);
  else bar_sync(6, 256);
  TSW(15);
  const uint64_t ds = mkdesc(sb + cv_se(wg), 8192, 1024, 1), df = mkdesc(sb + cv_fa(wg), 512, 128, 0);
  conv_mma1(acc, A0, d0, ds, df);
  if (wg == 0) bar_arrive(6, 256);
  wg_wait<0>();
  conv_store(acc, sb + cv_pb1(wg, w), sb + cv_dump(wg), w);
  mbar_arrive(bar + 8 * (B_R + 1));
  TSW(16);
  conv_mma1(acc, A1, d1, ds + 512, df + (CH2 >> 4));
  wg_wait<0>();
  conv_store(acc, sb + cv_pb1(2 + wg, w), sb + cv_dump(2 + wg), w);
  TSW(17);
  if (wg == 0) {
    mbar_arrive(bar + 8 * (B_R + 2));
  } else {
    bar_sync(3, 128);
    conv_epi<1, 1>(sb, xout, 3, opaque_tid() & 127);
    mbar_arrive(bar + 8 * (B_PUB + 2));
    TSW(18);
  }
}

__device__ __forceinline__ void final_phase(const Params& p, uint32_t sb, int cta, int wg, int w, int rtp) {
  const int lane = opaque_tid() & 31;
  const uint32_t bar = sb + SM_BAR;
  mbar_wait(bar + 8 * (B_TF + wg), 0);
  if (threadIdx.x == 128) TS(8);
  const uint32_t src = sb + (16 + wg) * PG, dst = src + 2 * PG;
  const int mi = lane >> 3;
#pragma unroll 1
  for (int attempt = 0; attempt < MAX_RETRY; attempt++) {
    uint32_t m = 0;
#pragma unroll
    for (int j = 0; j < 8; j += 2) {
      uint32_t r[4];
      const int line = 8 * (j + (mi >> 1)) + (lane & 7), pc = 2 * w + (mi & 1);
      ldsm4t(r, src + line * 128 + ((pc ^ (line & 7)) << 4));
      const int row = 16 * w + (lane & 7) + 8 * (mi & 1), ch = j + (mi >> 1);
      stsm4(dst + row * 128 + ((ch ^ (row & 7)) << 4), r[0], r[1], r[2], r[3]);
#pragma unroll
      for (int k = 0; k < 4; k++) asm("max.u16x2 %0, %0, %1;" : "+r"(m) : "r"(r[k]));
    }
    fence_async_smem();
    if (!bar_or(2 + wg, 128, m >= 0xffff0000u || (m & 0xffffu) == 0xffffu)) break;
    if (w == 0 && elect_one()) {
      mbar_expect(bar + 8 * (B_RT + wg), PG);
      tma_ld(src, &p.mapXT, (16 * wg + (cta & 15)) * 64, 3 * DM + (cta >> 4) * 64, bar + 8 * (B_RT + wg));
    }
    mbar_wait(bar + 8 * (B_RT + wg), (rtp + attempt) & 1);
    RETRY(2);
  }
  if (w == 0 && elect_one()) {
    tma_st(&p.mapOut, (cta >> 4) * 64, (16 * wg + (cta & 15)) * 64, dst);
    bulk_commit();
    asm volatile("cp.async.bulk.wait_group.read 0;" ::: "memory");
    if (threadIdx.x == 128) TS(9);
    if (threadIdx.x == 128) LTS(1);
  }
}

struct cplx { float r, i; };
__device__ __forceinline__ cplx cmul(cplx a, cplx b) { return {fmaf(a.r, b.r, -a.i * b.i), fmaf(a.r, b.i, a.i * b.r)}; }
__device__ __forceinline__ cplx csqr(cplx a) { return {fmaf(a.r, a.r, -a.i * a.i), (a.r + a.r) * a.i}; }
__device__ __forceinline__ cplx cexp_l(float ar2, float ai, float l) {
  const float m = ex2(ar2 * l);
  const float x = ai * l;
  return {m * __cosf(x), m * __sinf(x)};
}

__device__ __forceinline__ void colsum_cta(const Params& p, uint32_t sb, int j, int tid) {
  const uint32_t bar = sb + SM_BAR;
  auto ld = [&](int i) {
    mbar_expect(bar + 8 * i, 3 * PG);
    tma_ld3(sb + (i & 7) * 3 * PG, &p.mapW3, (2 * j + (i & 1)) * 64, (i >> 1) * 64, 0, bar + 8 * i);
  };
  if (tid == 384) {
#pragma unroll
    for (int i = 0; i < 24; i++) mbar_init(bar + 8 * i, i < 16 ? 1 : 12);
    asm volatile("fence.mbarrier_init.release.cluster;" ::: "memory");
    fence_async_smem();
#pragma unroll 1
    for (int i = 0; i < 8; i++) ld(i);
  }
  const unsigned ep = ld_relaxed(&g_cnt[C_CS * 32]);
  bar_sync(0, NTHREADS);
  if (tid == 384) {
#pragma unroll 1
    for (int i = 8; i < 16; i++) { mbar_wait(bar + 8 * (8 + i), 0); fence_async_smem(); ld(i); }
  }
  if (tid < 384) {
    const int lane = tid & 31, cc = tid & 7, r0 = (tid >> 3) & 15, part = tid >> 7;
    const uint32_t id = ((lane >> 2) == 2 * (lane & 3) ? 0x3f80u : 0u) | ((lane >> 2) == 2 * (lane & 3) + 1 ? 0x3f800000u : 0u);
    const uint32_t src = sb + part * PG + r0 * 128 + ((cc ^ (r0 & 7)) << 4);
    float s[2][2][4];
#pragma unroll
    for (int i = 0; i < 16; i++) s[i >> 3][(i >> 2) & 1][i & 3] = 0.f;
#pragma unroll 1
    for (int i2 = 0; i2 < 16; i2 += 2) {
#pragma unroll
      for (int h = 0; h < 2; h++) {
        const int i = i2 + h;
        mbar_wait(bar + 8 * i, 0);
        uint4 v[4];
#pragma unroll
        for (int k = 0; k < 4; k++) v[k] = lds128(src + (i & 7) * 3 * PG + k * 2048);
#pragma unroll
        for (int k = 0; k < 4; k++) {
          const uint32_t a[4] = {v[k].x, v[k].y, v[k].z, v[k].w};
          mma_bf16(s[h][0], a, id, 0u);
          mma_bf16(s[h][1], a, 0u, id);
        }
        __syncwarp();
        if (i < 8 && lane == 0) mbar_arrive(bar + 8 * (16 + i));
      }
    }
    const uint32_t red = sb + 24 * PG;
#pragma unroll
    for (int h = 0; h < 2; h++)
#pragma unroll
      for (int k = 0; k < 2; k++) sts128f(red + (r0 * 384 + h * 192 + part * 64 + cc * 8 + k * 4) * 4, s[h][k][0], s[h][k][1], s[h][k][2], s[h][k][3]);
    bar_sync(1, 384);
    float tot = 0.f;
#pragma unroll
    for (int k = 0; k < 16; k++) tot += __uint_as_float(lds32(red + (k * 384 + tid) * 4));
    asm volatile("st.relaxed.gpu.global.v2.u32 [%0], {%1,%2};" ::"l"(&g_colsum[j * 384 + tid]), "r"(__float_as_uint(tot)), "r"(ep / NCTA + 1) : "memory");
    const uint4 u = make_uint4(UNSET, UNSET, UNSET, UNSET);
    if (tid < 256) {
#pragma unroll 4
      for (int i = 0; i < 64; i++) stg128(g_halo + 65536 + j * 16384 + i * 256 + tid, u);
#pragma unroll 1
      for (int s = 0; s < 3; s++) {
        uint4* dst = (s ? (uint4*)g_xT + (s + 1) * 131072 : (uint4*)g_O + 131072) + j * 32768 + (tid >> 1) * 8 + (tid & 1);
#pragma unroll 4
        for (int i = 0; i < 32; i++) stg128(dst + i * 1024, u);
        bar_sync(2, 256);
        if (tid == 32 * s) red_release(&g_cnt[(C_R + s) * 32]);
      }
    }
  }
}

#define KW 3
struct ModeIn { uint32_t ar, ai, br, bi, cr, ci; bf16 logdt; };
__device__ __forceinline__ ModeIn load_modes(const Params& p, int d, int m) {
  const int i = d * 64 + m;
  return {((const uint32_t*)p.a_re)[i], ((const uint32_t*)p.a_im)[i], ((const uint32_t*)p.b_re)[i], ((const uint32_t*)p.b_im)[i],
          ((const uint32_t*)p.c_re)[i], ((const uint32_t*)p.c_im)[i], p.log_dt[d]};
}
__device__ __forceinline__ float4 lds128f_nv(uint32_t a) { float4 v; asm("ld.shared.v4.f32 {%0,%1,%2,%3}, [%4];" : "=f"(v.x), "=f"(v.y), "=f"(v.z), "=f"(v.w) : "r"(a)); return v; }
__device__ __forceinline__ void kernel_gen(const Params& p, uint32_t sb, int cta, int ht, ModeIn in, const ModeIn& in1) {
  const uint32_t bst = sb + SM_KGB + ((ht & 63) >> 2) * 144 + (ht & 3) * 4 + (ht >> 6) * 16;
  const uint64_t db = mkdesc(sb + SM_KGB, 144, 2304, 0);
  const float e0 = (float)(8 * (((ht & 32) >> 1) + ((ht & 31) >> 2)));
  float T[20];
#pragma unroll
  for (int i = 0; i < 20; i++) T[i] = 0.f;
  float k0 = (ht & 63) ? 0.f : __bfloat162float(p.dskip[cv_chan(cta, ht >> 6)]);
#pragma unroll 1
  for (int pass = 0; pass < 4; pass++) {
    {
      const int sh = (pass & 1) ? 0 : 16;
      auto val = [&](uint32_t v) { return __uint_as_float((v << sh) & 0xffff0000u); };
      const float dt = __bfloat162float(__float2bfloat16_rn(expf(__bfloat162float(in.logdt))));
      const float ar2 = dt * val(in.ar) * 1.4426950408889634f, ai = dt * val(in.ai);
      const cplx c = cmul({val(in.cr), -val(in.ci)}, {dt * val(in.br), -dt * val(in.bi)});
      k0 += c.r;
      const cplx z1 = cexp_l(ar2, -ai, 1.f), z256 = cexp_l(ar2, -ai, 256.f), z64 = cexp_l(ar2, ai, 64.f);
      const cplx z2 = csqr(z1), z512 = csqr(z256);
      auto put = [&](int j, cplx v) { sts32(bst + (j >> 2) * 2304 + (j & 3) * 32, packbf(v.r, v.i)); };
      sts128f(sb + SM_KGT + ht * 16, ar2, ai, z64.r, z64.i);
      const cplx c1 = cmul(c, z1), c2 = cmul(c, z2), c3 = cmul(c1, z2), c4 = cmul(c2, z2);
      const cplx c5 = cmul(c3, z2), c6 = cmul(c4, z2), c7 = cmul(c5, z2), c8 = cmul(c6, z2);
      put(0, c1); put(1, c2); put(2, c3); put(3, c4); put(4, c5); put(5, c6); put(6, c7); put(7, c8);
      const cplx c260 = cmul(c4, z256), c264 = cmul(c8, z256), c520 = cmul(c8, z512), c776 = cmul(c264, z512);
      put(8, cmul(c2, z256)); put(9, c260); put(10, cmul(c6, z256)); put(11, c264);
      put(12, cmul(c4, z512)); put(13, c520); put(14, cmul(c260, z512)); put(15, c776);
      const cplx c1032 = cmul(c520, z512), c1288 = cmul(c776, z512);
      put(16, c1032); put(17, c1288); put(18, cmul(c1032, z512)); put(19, cmul(c1288, z512));
    }
    fence_async_smem();
    bar_sync(4, 128);
    uint32_t tb = sb + SM_KGT + (ht & 67) * 16;
    asm volatile("mov.u32 %0, %0;" : "+r"(tb) :: "memory");
#pragma unroll
    for (int q = 0; q < 4; q++) {
      uint32_t A[8];
      if (q >= KW) wg_wait<KW - 1>();
#pragma unroll
      for (int s = 0; s < 4; s++) {
        const float4 v = lds128f_nv(tb + (4 * q + s) * 64);
        const cplx lo = cexp_l(v.x, v.y, e0), hi = cmul(lo, {v.z, v.w});
        A[2 * s] = packbf(lo.r, lo.i);
        A[2 * s + 1] = packbf(hi.r, hi.i);
      }
      wg_fence();
      wgmma_rs<40, 0>(T, A, db + 36 * q, (pass & 1) | q);
      wgmma_rs<40, 0>(T, A + 4, db + 36 * q + 18, 1);
      wg_commit();
    }
    wg_wait<0>();
    acc_fence<20>(T);
    if (ht == 0) TS(4 + pass);
    if (pass & 1) {
      const int h2 = opaque_tid() - 256, w = h2 >> 5, lane = h2 & 31, t = lane & 3, chn = h2 >> 6, m = h2 & 63, i0 = 16 * (w & 1) + (lane >> 2);
      const int lc = (pass & 2) + chn;
      const uint32_t kc = sb + kc_off(lc);
      auto put = [&](int idx, float v) {
        sts16(kc + idx * 2, __bfloat16_as_ushort(__float2bfloat16_rn(v)));
      };
#pragma unroll
      for (int hi = 0; hi < 2; hi++) {
        const int i = i0 + 8 * hi;
        float v[5];
#pragma unroll
        for (int j = 0; j < 5; j++) v[j] = chn ? T[4 * j + 2 * hi + 1] : T[4 * j + 2 * hi];
        put(8 * i + 1 + t, v[0]);
        put(8 * i + 5 + t, v[1]);
        put(257 + 4 * i + t, v[2]);
        put(385 + 2 * i + (t & 1) + 64 * (t >> 1), v[3]);
        put(513 + i + 32 * t, v[4]);
      }
#pragma unroll
      for (int o = 16; o > 0; o >>= 1) k0 += __shfl_xor_sync(~0u, k0, o);
      if (lane == 0) sts32f(sb + SM_RED + 4 * w, k0);
      bar_sync(4, 128);
      if (m == 0) put(0, k0 + __uint_as_float(lds32(sb + SM_RED + 4 * w + 4)));
      k0 = m ? 0.f : __bfloat162float(p.dskip[cv_chan(cta, 2 + chn)]);
      in = in1;
    }
  }
}

__device__ __forceinline__ void expand_taps(uint32_t sb, int ht) {
  const int ch = ht >> 5, lane = ht & 31;
  const uint32_t kc = sb + kc_off(ch);
  const uint32_t dst0 = sb + cv_pe(ch);
  auto put = [&](int G, uint32_t v0, uint32_t v1, uint32_t v2, uint32_t v3, uint32_t v4, uint32_t v5, uint32_t v6, uint32_t v7, uint32_t v8) {
    const uint32_t dst = dst0 + G * 32;
    sts128(dst, make_uint4(v1 | (v0 << 16), v2 | (v1 << 16), v3 | (v2 << 16), v4 | (v3 << 16)));
    sts128(dst + 16, make_uint4(v5 | (v4 << 16), v6 | (v5 << 16), v7 | (v6 << 16), v8 | (v7 << 16)));
  };
  {
    const uint4 q = lds128(kc + lane * 16);
    const uint32_t pv = lane ? lds16(kc + lane * 16 - 2) : 0u;
    const uint32_t dst = dst0 + (lane + 2) * 32;
    sts128(dst, make_uint4(__byte_perm(q.x, pv, 0x5410), __byte_perm(q.x, q.x, 0x1032), __byte_perm(q.y, q.x, 0x7610), __byte_perm(q.y, q.y, 0x1032)));
    sts128(dst + 16, make_uint4(__byte_perm(q.z, q.y, 0x7610), __byte_perm(q.z, q.z, 0x1032), __byte_perm(q.w, q.z, 0x7610), __byte_perm(q.w, q.w, 0x1032)));
    if (lane < 4) sts128(dst0 + lane * 16, make_uint4(0, 0, 0, 0));
  }
  uint32_t a[5], b[2][3];
  {
    const uint32_t s1 = kc + 2 * (256 + 4 * lane);
#pragma unroll
    for (int k = 0; k < 5; k++) a[k] = lds16(s1 + 2 * k);
#pragma unroll
    for (int u = 0; u < 2; u++) {
      const uint32_t s2 = kc + 2 * (384 + 2 * (lane + 32 * u));
#pragma unroll
      for (int k = 0; k < 3; k++) b[u][k] = lds16(s2 + 2 * k);
    }
  }
  const uint32_t k255 = lds16(kc + 2 * 255), k1024 = lds16(kc + 2 * 512);
  put(34 + lane, lane == 0 ? k255 : a[0], a[0], a[0], a[1], a[2], a[2], a[2], a[3], a[4]);
#pragma unroll
  for (int u = 0; u < 2; u++) put(66 + lane + 32 * u, b[u][0], b[u][0], b[u][0], b[u][0], b[u][1], b[u][1], b[u][1], b[u][2], b[u][2]);
  if (lane < 10) {
    const uint32_t v = lane == 0 ? k1024 : 0u;
    put(130 + lane, v, v, v, v, v, v, 0u, 0u, 0u);
  }
}
__device__ __forceinline__ void expand_far(uint32_t sb, int ht) {
  const int ch = ht >> 5, lane = ht & 31;
  const uint32_t kc = sb + kc_off(ch) + 2 * (513 + 2 * (63 - lane)), dst = sb + cv_fa(ch) + lane * 16;
#pragma unroll
  for (int ty = 0; ty < 2; ty++) {
    uint32_t v[16];
#pragma unroll
    for (int k = 0; k < 16; k++) v[k] = (k < 8 || 63 - lane - 4 * k >= 0) ? lds16(kc + 2 * (1 - ty) - 16 * k) : 0u;
#pragma unroll
    for (int u = 0; u < 2; u++)
      sts128(dst + ty * 2048 + u * 512, make_uint4(v[8 * u] | (v[8 * u + 1] << 16), v[8 * u + 2] | (v[8 * u + 3] << 16), v[8 * u + 4] | (v[8 * u + 5] << 16), v[8 * u + 6] | (v[8 * u + 7] << 16)));
    sts128(dst + ty * 2048 + 1024, make_uint4(0, 0, 0, 0));
  }
}

#define MAPF 0
#define PMAP 1
#define FIRST 0
#define WPRE 1
__host__ __device__ constexpr int bar_count(int i) {
  return i == B_END ? 3 : i == B_LN ? 2 : (i >= B_OST && i < B_PDONE + 2) ? 4 : (i == B_PUB + 2 || i == B_PUB || i == B_R + 1) ? 256 : (i >= B_U1 && i < B_END && i != B_LN && i != B_LN + 1) ? 128 : 1;
}
__host__ __device__ constexpr bool bar_first(int i) { return i < B_WF + 2 && (i & 7) < 2; }

__global__ void __launch_bounds__(NTHREADS, 1) fused_kernel(const __grid_constant__ Params p) {
  extern __shared__ __align__(1024) uint8_t smem[];
  const uint32_t sb = s32(smem);
  const int tid = threadIdx.x, lane = tid & 31;
  const int warp = __shfl_sync(~0u, tid >> 5, 0);
  const int cta = blockIdx.x - p.first;
  if ((unsigned)cta >= NCTA) {
    colsum_cta(p, sb, blockIdx.x & 3, tid);
    return;
  }
  const int rb = ((cta >> 4) & 3) * 4 + ((cta >> 2) & 3), hg = (cta >> 6) * 4 + (cta & 3);
  const int rb2 = rb, q2 = hg;
  const uint32_t bar = sb + SM_BAR;
  auto ld_x0 = [&](int half, int c) {
    const uint32_t b = bar + 8 * (B_XF + 8 * half + c);
    mbar_expect(b, PG);
    tma_ld(sb + x_page(half, c) * PG, &p.mapX, c * 64, (16 * half + rb) * 64, b);
  };
  auto ld_w = [&](int c) {
    const uint32_t b = bar + 8 * (B_WF + c);
    mbar_expect(b, 3 * PG);
    tma_ld3(sb + w_page(c) * PG, &p.mapW3, hg * 64, c * 64, 0, b);
  };

  if (tid == 0) TS(0);
  if (tid == 480) LTS(0);
  if (warp < 6 && elect_one()) {
    if (warp == 0) {
#pragma unroll
      for (int i = 0; i < B_WF + 2; i++)
        if (bar_first(i)) mbar_init(bar + 8 * i, 1);
      asm volatile("fence.mbarrier_init.release.cluster;" ::: "memory");
      fence_async_smem();
      ld_x0(0, 0); ld_w(0); ld_x0(1, 0);
      ld_x0(0, 1); ld_w(1); ld_x0(1, 1);
      TS(1);
    } else {
#pragma unroll
      for (int q = 0; q < 5; q++) {
        if (warp == q + 1) {
#pragma unroll
          for (int i = 0; i < B_COUNT; i++)
            if (!bar_first(i) && i % 5 == q) mbar_init(bar + 8 * i, bar_count(i));
        }
      }
      asm volatile("fence.mbarrier_init.release.cluster;" ::: "memory");
    }
  }

  if (warp < 8) {
    bar_sync(0, NTHREADS);
    asm volatile("setmaxnreg.inc.sync.aligned.u32 %0;" ::"n"(R_CONS));
    const int cw = __shfl_sync(~0u, opaque_tid() >> 5, 0);
    const int wg = cw >> 2, w = cw & 3;
    if (tid == 0) TS(2);
    int rtp = 0;
#pragma unroll 1
    for (int layer = 0; layer < 2; layer++) {
      attn_phase(p, sb, layer, rb, hg, wg, w);
      proj_phase(p, sb, layer, rb2, q2, wg, w, rtp);
      conv_phase(p, sb, layer, cta);
    }
    final_phase(p, sb, cta, wg, w, rtp);
  } else if (warp < 12) {
    asm volatile("setmaxnreg.dec.sync.aligned.u32 %0;" ::"n"(R_HELP));
    const int ht = tid - 256;
    {
      unsigned ep0 = 0;
      if (ht == 0) ep0 = ld_relaxed(&g_cnt[C_CS * 32]);
      const ModeIn in0 = load_modes(p, cv_chan(cta, ht >> 6), ht & 63), in1 = load_modes(p, cv_chan(cta, 2 + (ht >> 6)), ht & 63);
      if (ht < 48) sts128f(sb + SM_STG + ht * 16, 0.f, 0.f, 0.f, 1.f);
      bar_sync(0, NTHREADS);
      if (ht == 0) {
        sts32(sb + SM_EP, ep0 / NCTA);
        mbar_arrive(bar + 8 * B_EP);
      }
      kernel_gen(p, sb, cta, ht, in0, in1);
      if (ht < 48) sts128f(sb + SM_KGT + ht * 16, 0.f, 0.f, 0.f, 1.f);
      fence_async_smem();
      bar_sync(4, 128);
      if (ht == 0) mbar_arrive(bar + 8 * B_KG);
    }
#pragma unroll 1
    for (int layer = 0; layer < 2; layer++) {
      bf16* xout = g_xT + ((2 * layer + 1) * DM + 2 * cta) * LSEQ;
      mbar_wait(bar + 8 * B_PDONE, layer);
      expand_taps(sb, opaque_tid() - 256);
      mbar_arrive(bar + 8 * B_PE);
      TSW(0);
      expand_far(sb, opaque_tid() - 256);
      {
        const int i = opaque_tid() - 256;
        if (i < 32) sts128(sb + cv_u(i >> 3) + ((i >> 2) & 1) * CV_UH + (128 + (i & 3)) * 16, make_uint4(0, 0, 0, 0));
        if (layer) mbar_wait(bar + 8 * (B_RS + 2), 0);
        mbar_wait(bar + 8 * B_GB, layer);
        TSW(13);
        conv_prep<0>(sb, layer, cta, i);
        mbar_arrive(bar + 8 * B_U);
      }
      mbar_wait(bar + 8 * (B_PDONE + 1), layer);
      bar_sync(4, 128);
#pragma unroll 1
      for (int lc = 0; lc < 4; lc += 2) {
        conv_sums(sb, lc, opaque_tid() - 256);
        TSW(1 + lc);
      }
      mbar_wait(bar + 8 * (B_GB + 1), layer);
      conv_prep<1>(sb, layer, cta, opaque_tid() - 256);
      mbar_arrive(bar + 8 * B_U1);
      TSW(4);
      mbar_wait(bar + 8 * (B_R + 1), layer);
      conv_epi<1, 2>(sb, xout, 0, opaque_tid() - 256);
      mbar_arrive(bar + 8 * (B_PUB + 1));
      TSW(5);
      mbar_wait(bar + 8 * (B_R + 2), layer);
      conv_epi<1, 1>(sb, xout, 2, opaque_tid() - 256);
      mbar_arrive(bar + 8 * (B_PUB + 2));
      TSW(6);
    }
  } else {
    asm volatile("setmaxnreg.dec.sync.aligned.u32 %0;" ::"n"(R_AGENT));
    bar_sync(0, NTHREADS);
    auto done = [&](int half, int c, int layer) { mbar_wait(bar + 8 * (B_DN + 8 * half + c), layer); };
    auto publish = [&](int layer, int k) {
      mbar_wait(bar + 8 * (B_PUB + k), layer);
      if (layer == 0) {
        red_release(&g_cnt[(C_C + k) * 32]);
      }
      else red_relaxed(&g_cnt[(C_F + 4 * k + (cta >> 5)) * 32]);
      TS(16 + layer * 56 + 40 + 7 + k);
    };
    if (warp == 12) {
      if (elect_one()) {
#pragma unroll 1
        for (int layer = 0; layer < 2; layer++) {
          auto ld_xe = [&](int c) {
            const uint32_t b = bar + 8 * (B_XF + c);
            mbar_expect(b, PG);
            if (layer == 0) tma_ld(sb + (c - 5) * PG, &p.mapX, c * 64, rb * 64, b);
            else tma_ld(sb + (c - 5) * PG, &p.mapXT, rb * 64, DM + c * 64, b);
          };
          if (layer == 0) {
            ld_x0(0, 2); ld_w(2); ld_x0(1, 2);
            if (hg >= 3) {
              mbar_expect(bar + 8 * B_SC, PG);
              tma_ld(sb + P_R * PG, &p.mapX, hg * 64, rb * 64, bar + 8 * B_SC);
            }
            if (rb < 4) tma_prefetch3(&p.mapW3, hg * 64, (4 + rb) * 64, 0);
            ld_x0(0, 3); ld_w(3); ld_x0(1, 3); ld_x0(0, 4); ld_x0(1, 4);
            done(0, 0, 0); done(1, 0, 0);
            ld_w(4);
            ld_x0(1, 5); ld_x0(1, 6); ld_x0(1, 7);
            done(0, 1, 0); done(1, 1, 0);
            ld_w(5);
            if (rb2 < 8) tma_prefetch5(&p.mapWo, q2 * 64, rb2 * 2);
            done(0, 2, 0);
            fence_async_smem();
            ld_xe(5); ld_xe(6); ld_xe(7);
          } else {
            mbar_wait(bar + 8 * B_PDONE, 0);
            mbar_wait(bar + 8 * (B_PDONE + 1), 0);
            mbar_wait(bar + 8 * (WPRE == 1 ? B_U : B_GB + 1), 0);
            ld_w(0); ld_w(1);
            mbar_wait(bar + 8 * B_U1, 0);
            fence_async_smem();
            ld_w(2);
            mbar_wait(bar + 8 * (B_PUB + 2), 0);
            fence_async_smem();
            ld_w(3);
            done(0, 2, 1);
            fence_async_global();
            fence_async_smem();
            ld_xe(5); ld_xe(6); ld_xe(7);
            done(1, 0, 1);
            ld_w(4);
            done(1, 1, 1);
            ld_w(5);
          }
          done(1, 2, layer);
          fence_async_smem();
          ld_w(6); ld_w(7);
          auto ld_res = [&](int half) {
            const uint32_t b = bar + 8 * (B_RF + half);
            mbar_expect(b, PG);
            if (layer == 0) tma_ld(sb + (half ? 2 : P_R) * PG, &p.mapX, q2 * 64, (16 * half + rb2) * 64, b);
            else tma_ld(sb + (half ? 2 : P_R) * PG, &p.mapXT, (16 * half + rb2) * 64, DM + q2 * 64, b);
          };
          done(0, 4, layer); done(1, 3, layer);
          fence_async_smem();
#pragma unroll 1
          for (int c = 0; c < 8; c++) {
            const uint32_t b = bar + 8 * (B_WOF + (c >> 1));
            if (c == 5) { ld_res(0); done(1, 4, layer); }
            if ((c & 1) == 0) mbar_expect(b, 2 * PG);
            tma_ld5(sb + wo_page(c) * PG, &p.mapWo, q2 * 64, c * 2, b);
          }
          done(0, 7, layer);
          fence_async_global();
          ld_res(1);
        }
      }
    } else if (warp == 13) {
      if (elect_one()) {
        mbar_wait(bar + 8 * (B_WF + 2), 0);
        asm volatile("prefetch.tensormap [%0];" ::"l"(&p.mapXT) : "memory");
        asm volatile("prefetch.tensormap [%0];" ::"l"(&p.mapOut) : "memory");
        asm volatile("prefetch.tensormap [%0];" ::"l"(&p.mapWo) : "memory");
        mbar_wait(bar + 8 * B_EP, 0);
        const unsigned e1 = lds32(sb + SM_EP) + 1;
        spin_until(&g_cnt[C_Z * 32], e1 * NCTA);
        mbar_arrive(bar + 8 * B_ZF);
        TS(3);
        auto ld_x1 = [&](int half, int c0, int c1) {
          fence_async_global();
          fence_async_smem();
#pragma unroll 1
          for (int c = c0; c < c1; c++) {
            const uint32_t b = bar + 8 * (B_XF + 8 * half + c);
            mbar_expect(b, PG);
            tma_ld(sb + x_page(half, c) * PG, &p.mapXT, (16 * half + rb) * 64, DM + c * 64, b);
          }
        };
#pragma unroll 1
        for (int layer = 0; layer < 2; layer++) {
          if (layer == 1) {
            mbar_wait(bar + 8 * B_PUB, 0);
            spin_until(&g_cnt[C_C * 32], e1 * NCTA);
            TS(10);
            ld_x1(0, 0, 3);
            if (hg >= 3) {
              mbar_expect(bar + 8 * B_SC, PG);
              tma_ld(sb + P_R * PG, &p.mapXT, rb * 64, DM + hg * 64, bar + 8 * B_SC);
            }
            ld_x1(0, 3, 5);
            mbar_wait(bar + 8 * (B_PUB + 1), 0);
            spin_until(&g_cnt[(C_C + 1) * 32], e1 * NCTA);
            TS(11);
            ld_x1(1, 0, 4);
            spin_until(&g_cnt[(C_C + 2) * 32], e1 * NCTA);
            TS(12);
            ld_x1(1, 4, 8);
          }
#pragma unroll 1
          for (int half = 0; half < 2; half++) {
            done(1, 7, layer);
            mbar_wait(bar + 8 * B_OST, layer);
            if (half) mbar_wait(bar + 8 * (B_OST + 1), layer);
            spin_until(&g_cnt[(C_O + layer * 32 + 16 * half + rb2) * 32], e1 * 32);
            fence_async_global();
            fence_async_smem();
#pragma unroll 1
            for (int c = 0; c < 4; c++) {
              const uint32_t b = bar + 8 * (B_OF + 4 * half + c);
              mbar_expect(b, 2 * PG);
              bulk_ld(sb + o_page(half, c) * PG, g_O + ((layer * 32 + 16 * half + rb2) * 4 + c) * PG, 2 * PG, b);
            }
          }
        }
        mbar_wait(bar + 8 * B_PUB, 1);
#pragma unroll 1
        for (int half = 0; half < 2; half++) {
          spin_until(&g_cnt[(C_F + 4 * (half ? 1 + (cta >> 6) : 0) + ((cta >> 4) & 3)) * 32], e1 * 32);
          fence_async_global();
          mbar_expect(bar + 8 * (B_TF + half), PG);
          tma_ld(sb + (16 + half) * PG, &p.mapXT, (16 * half + (cta & 15)) * 64, 3 * DM + (cta >> 4) * 64, bar + 8 * (B_TF + half));
        }
      }
    } else if (warp == 14) {
      mbar_wait(bar + 8 * B_EP, 0);
      const unsigned e1 = lds32(sb + SM_EP) + 1;
      done(0, 1, 0);
      {
        const uint2* cp = g_colsum + (hg * 192 + lane);
        uint2 v[6];
        bool ok;
        int it = 0;
        do {
          ok = true;
#pragma unroll
          for (int i = 0; i < 6; i++) {
            asm volatile("ld.relaxed.gpu.global.v2.u32 {%0,%1}, [%2];" : "=r"(v[i].x), "=r"(v[i].y) : "l"(cp + 32 * i) : "memory");
            ok = ok && v[i].y == e1;
          }
          if (++it > (1 << 22)) __trap();
        } while (!__all_sync(~0u, ok));
#pragma unroll
        for (int i = 0; i < 6; i++) sts32f(sb + SM_CS + 4 * (lane + 32 * i), __uint_as_float(v[i].x));
      }
      __syncwarp();
      if (elect_one()) {
        mbar_wait(bar + 8 * B_ZF, 0);
        mbar_arrive(bar + 8 * B_LN);
        red_relaxed(&g_cnt[C_CS * 32]);
        TS(13);
#pragma unroll 1
        for (int i = 0; i < 4; i++) {
          const int layer = i >> 1;
          mbar_wait(bar + 8 * (B_PST + (i & 1)), layer);
          const uint32_t b = bar + 8 * (B_GB + 1);
          const bf16* xin = g_xT + ((size_t)2 * layer * DM + 2 * cta) * LSEQ + 1024;
          if (i & 1) {
            fence_async_smem();
            mbar_expect(b, 12288 + PG);
          }
          spin_until(&g_cnt[(C_G + i) * 32], e1 * NCTA);
          if (i & 1) {
            bulk_ld(sb + CV_ST, g_stats + (layer * 32 + 16) * 192, 12288, b);
#pragma unroll
            for (int lc = 0; lc < 4; lc++) bulk_ld(sb + cv_x(1, lc), xin + cv_chan(0, lc) * LSEQ, 2048, b);
            TS(14 + layer);
            publish(layer, 1);
          } else {
            mbar_arrive(bar + 8 * B_GB);
          }
        }
      }
    } else {
      const uint4 u = make_uint4(UNSET, UNSET, UNSET, UNSET);
      if (lane < 24) stg128((uint4*)g_stats + cta * 24 + lane, make_uint4(0, 0, 0, 0));
      if (lane < 16) stg128(g_rows + LSEQ + cta * 16 + lane, make_uint4(0, 0, 0, 0));
#pragma unroll 4
      for (int i = 0; i < 16; i++) stg128(g_halo + cta * 512 + 32 * i + lane, u);
#pragma unroll 4
      for (int i = 0; i < 16; i++) stg128(((i & 8) ? (uint4*)g_xT : (uint4*)g_O) + cta * 1024 + (i & 7) * 128 + (lane >> 1) * 8 + (lane & 1), u);
      __syncwarp();
      if (elect_one()) red_release(&g_cnt[C_Z * 32]);
      __syncwarp();
#pragma unroll 1
      for (int layer = 0; layer < 2; layer++) {
        auto reset_done = [&](int s) {
          spin_until(&g_cnt[(C_R + s) * 32], lds32(sb + SM_EP) * 4 + 4);
          mbar_arrive(bar + 8 * (s ? B_RS + s : B_LN));
          TS(16 + 40 + 10 + s);
        };
        if (layer && elect_one()) reset_done(0);
        __syncwarp();
#pragma unroll 1
        for (int half = 0; half < 2; half++) {
          done(half, 2, layer);
          const uint4* src = g_rows + layer * LSEQ + (16 * half + rb) * 64 + lane;
          uint4 a, b;
          int it = 0;
          do {
            a = ld_tagged(src); b = ld_tagged(src + 32);
          } while (!__all_sync(~0u, (a.z | a.w) == __float_as_uint(8.f) && (b.z | b.w) == __float_as_uint(8.f)) && ++it < (1 << 20));
          float m0 = __uint_as_float(a.x) * (1.f / DM), m1 = __uint_as_float(b.x) * (1.f / DM);
          float r0 = rsqrt_approx(fmaxf(__uint_as_float(a.y) * (1.f / DM) - m0 * m0, 0.f) + 1e-5f);
          float r1 = rsqrt_approx(fmaxf(__uint_as_float(b.y) * (1.f / DM) - m1 * m1, 0.f) + 1e-5f);
          if (half) done(0, 7, layer);
          const uint32_t dst = sb + ln_off(half) + ((lane >> 4) * 8 + (lane & 7)) * 16 + (lane & 8);
          asm volatile("st.shared.v2.f32 [%0], {%1,%2};" ::"r"(dst), "f"(m0), "f"(r0) : "memory");
          asm volatile("st.shared.v2.f32 [%0], {%1,%2};" ::"r"(dst + 256), "f"(m1), "f"(r1) : "memory");
          __syncwarp();
          if (elect_one()) { mbar_arrive(bar + 8 * (B_LN + half)); TS(16 + layer * 56 + 40 + 14 + half); }
        }
        if (layer && lane < 16) stg128(g_rows + cta * 16 + lane, make_uint4(0, 0, 0, 0));
        if (elect_one()) {
          if (layer) { reset_done(1); reset_done(2); }
          publish(layer, 0);
          publish(layer, 2);
        }
        __syncwarp();
      }
    }
  }
}

typedef CUresult (*EncodeFn)(CUtensorMap*, CUtensorMapDataType, cuuint32_t, void*, const cuuint64_t*, const cuuint64_t*,
                             const cuuint32_t*, const cuuint32_t*, CUtensorMapInterleave, CUtensorMapSwizzle,
                             CUtensorMapL2promotion, CUtensorMapFloatOOBfill);

static void make_map(EncodeFn enc, CUtensorMap* m, void* ptr, uint64_t cols, uint64_t rows, uint32_t box_rows) {
  cuuint64_t dims[2] = {cols, rows};
  cuuint64_t strides[1] = {cols * 2};
  cuuint32_t box[2] = {64, box_rows};
  cuuint32_t es[2] = {1, 1};
  enc(m, CU_TENSOR_MAP_DATA_TYPE_BFLOAT16, 2, ptr, dims, strides, box, es, CU_TENSOR_MAP_INTERLEAVE_NONE,
      CU_TENSOR_MAP_SWIZZLE_128B, CU_TENSOR_MAP_L2_PROMOTION_L2_128B, CU_TENSOR_MAP_FLOAT_OOB_FILL_NONE);
}
static void make_map3(EncodeFn enc, CUtensorMap* m, void* ptr, uint64_t d0, uint64_t cols, uint64_t rows, uint64_t blk_stride,
                      uint64_t nblocks, uint32_t nblk) {
  cuuint64_t dims[3] = {d0, rows, nblocks};
  cuuint64_t strides[2] = {cols * 2, blk_stride * 2};
  cuuint32_t box[3] = {64, 64, nblk};
  cuuint32_t es[3] = {1, 1, 1};
  enc(m, CU_TENSOR_MAP_DATA_TYPE_BFLOAT16, 3, ptr, dims, strides, box, es, CU_TENSOR_MAP_INTERLEAVE_NONE,
      CU_TENSOR_MAP_SWIZZLE_128B, CU_TENSOR_MAP_L2_PROMOTION_L2_128B, CU_TENSOR_MAP_FLOAT_OOB_FILL_NONE);
}

extern "C" void kernel_launch(void* const* d_in, const int* in_sizes, int n_in, void* d_out, int out_size) {
  static Params prm;
  static void* cached[13] = {nullptr};
  static bool attr_done = false;
  bool same = attr_done && cached[12] == d_out;
  for (int i = 0; i < 12 && same; i++) same = cached[i] == d_in[i];
  if (!same) {
    void* fn = nullptr;
    cudaDriverEntryPointQueryResult qr;
    cudaGetDriverEntryPoint("cuTensorMapEncodeTiled", &fn, cudaEnableDefault, &qr);
    EncodeFn enc = (EncodeFn)fn;
    void* pXT;
    cudaGetSymbolAddress(&pXT, g_xT);
    make_map(enc, &prm.mapX, d_in[0], DM, LSEQ, 64);
    make_map(enc, &prm.mapXT, pXT, LSEQ, 4 * DM, 64);
    make_map(enc, &prm.mapOut, d_out, DM, LSEQ, 64);
    {
      cuuint64_t dims[5] = {DM, 2, 4, 4, 16};
      cuuint64_t strides[4] = {DM * 2, 8 * DM * 2, 2 * DM * 2, 32 * DM * 2};
      cuuint32_t box[5] = {64, 2, 4, 4, 2};
      cuuint32_t es[5] = {1, 1, 1, 1, 1};
      enc(&prm.mapWo, CU_TENSOR_MAP_DATA_TYPE_BFLOAT16, 5, d_in[2], dims, strides, box, es, CU_TENSOR_MAP_INTERLEAVE_NONE,
          CU_TENSOR_MAP_SWIZZLE_128B, CU_TENSOR_MAP_L2_PROMOTION_L2_128B, CU_TENSOR_MAP_FLOAT_OOB_FILL_NONE);
    }
    make_map3(enc, &prm.mapW3, d_in[1], DM, 3 * DM, DM, DM, 3, 3);
    prm.wqkv = (const bf16*)d_in[1];
    prm.a_re = (const bf16*)d_in[4]; prm.a_im = (const bf16*)d_in[5];
    prm.b_re = (const bf16*)d_in[6]; prm.b_im = (const bf16*)d_in[7];
    prm.c_re = (const bf16*)d_in[8]; prm.c_im = (const bf16*)d_in[9];
    prm.log_dt = (const bf16*)d_in[10]; prm.dskip = (const bf16*)d_in[11];
    int dev = 0, sms = 0;
    cudaGetDevice(&dev);
    cudaDeviceGetAttribute(&sms, cudaDevAttrMultiProcessorCount, dev);
    prm.first = sms >= NCTA + 4 ? FIRST : 4;
    cudaFuncSetAttribute(fused_kernel, cudaFuncAttributeMaxDynamicSharedMemorySize, SM_TOTAL);
    for (int i = 0; i < 12; i++) cached[i] = d_in[i];
    cached[12] = d_out;
    attr_done = true;
  }
  fused_kernel<<<NCTA + 4, NTHREADS, SM_TOTAL>>>(prm);
}
```

```cpp
#include <cuda_runtime.h>
#include <cuda_bf16.h>
#include <cuda.h>
#include <stdint.h>

typedef __nv_bfloat16 bf16;

constexpr int LSEQ = 2048;
constexpr int DM = 512;
constexpr int NCTA = 128;
constexpr int NTHREADS = 512;
#define R_CONS 200
#define R_HELP 88
#define R_AGENT 24
#define TURN0 4
#define TURN1 4

constexpr int PG = 8192;
constexpr int P_R = 25;
__host__ __device__ constexpr int x_page(int half, int c) { return half ? 8 + c : c < 5 ? c : c - 5; }
__host__ __device__ constexpr int w_page(int c) { return (c & 3) < 3 ? 16 + 3 * (c & 3) : c < 4 ? 5 : 8; }
__host__ __device__ constexpr int wo_page(int c) { return c < 5 ? 3 + c : 11 + c; }
__host__ __device__ constexpr int o_page(int half, int pair) { return half ? (pair ? 17 + 2 * pair : 0) : 8 + 2 * pair; }
constexpr int SM_KGB = (P_R + 1) * PG;
constexpr int SM_KC = 27 * PG;
constexpr int KC_STRIDE = 648;
__host__ __device__ constexpr int kc_off(int lc) { return SM_KC + (lc & 1) * 2 * KC_STRIDE + (lc < 2 ? 3328 : 0); }
constexpr int SM_KGT = SM_KC + 3328 + 2592;
constexpr int SM_CS = SM_KGT + 2048;
constexpr int SM_RED = SM_CS + 768;
constexpr int SM_EP = SM_RED + 16;
constexpr int SM_STG = SM_RED + 32;
constexpr int SM_LN = SM_STG + 768;
__host__ __device__ constexpr int ln_off(int half) { return half ? PG + 4096 : SM_LN; }
constexpr int SM_BAR = SM_LN + 512;
constexpr int SM_TS = SM_BAR + 704;
constexpr int SM_TOTAL = SM_TS + 512;
static_assert(SM_TOTAL <= 232448 && SM_STG % 16 == 0 && SM_KGT % 16 == 0, "shared memory");

constexpr int CV_UH = 140 * 16;
__host__ __device__ constexpr int cv_u(int lc) { return (8 + 2 * lc) * PG; }
__host__ __device__ constexpr int cv_pe(int lc) { return cv_u(lc) + 4480; }
__host__ __device__ constexpr int cv_pb1(int lc, int w) { return w ? cv_u(lc) + 8960 + (w - 1) * 2048 : 7 * PG + lc * 2048; }
__host__ __device__ constexpr int cv_fa(int lc) { return cv_pb1(lc, 1) + 128; }
__host__ __device__ constexpr int cv_dump(int lc) { return cv_u(lc) + 16256; }
__host__ __device__ constexpr int cv_pb0(int lc, int w) { return lc * PG + w * 2048; }
__host__ __device__ constexpr int cv_se(int lc) { return 5 * PG + lc * 4096; }
__host__ __device__ constexpr int cv_so(int lc) { return cv_se(lc) + 2048; }
__host__ __device__ constexpr int cv_x(int half, int lc) { return (P_R + half) * PG + lc * 2048; }
constexpr int CV_ST = 22 * PG;
__host__ __device__ constexpr int cv_chan(int cta, int lc) { return 2 * cta + (lc & 1) + 256 * (lc >> 1); }

enum {
  B_XF = 0,
  B_WF = 16,
  B_OF = 24,
  B_DN = 32,
  B_XR = 48,
  B_RF = 56,
  B_PST = 58,
  B_GB = 60,
  B_TF = 62,
  B_RT = 64,
  B_RS = 66,
  B_RC = 67,
  B_WOF = 68,
  B_ZF = 69,
  B_EP = 70,
  B_KG = 71,
  B_SC = 72,
  B_LN = 73,
  B_END = 75,
  B_OST = 76,
  B_PDONE = 78,
  B_PE = 80,
  B_U = 81,
  B_U1 = 82,
  B_PUB = 83,
  B_R = 86,
  B_COUNT = 88
};

enum {
  C_CS = 0,
  C_G = 1,
  C_C = 5,
  C_F = 9,
  C_O = 21,
  C_Z = 85,
  C_R = 86,
  C_COUNT = 90
};

__device__ unsigned g_cnt[C_COUNT * 32];
__device__ __align__(1024) bf16 g_O[2 * LSEQ * DM];
__device__ __align__(1024) bf16 g_xT[4 * DM * LSEQ];
__device__ __align__(1024) float g_stats[2 * 32 * 192];
__device__ __align__(1024) uint2 g_colsum[3 * DM];
__device__ __align__(1024) uint4 g_halo[32 * 8 * 256];
__device__ __align__(1024) uint4 g_rows[2 * LSEQ];
#define TS(i) do { } while (0)
#define TSW(k) do { if ((threadIdx.x & 127) == 0) TS(16 + layer * 56 + (threadIdx.x >> 7) * 20 + (k)); } while (0)
#define TSG(k) do { } while (0)

#define RETRY(i) do { } while (0)
#define LTS(i) do { } while (0)

struct Params {
  CUtensorMap mapX, mapW3, mapXT, mapOut, mapWo;
  const bf16 *wqkv, *a_re, *a_im, *b_re, *b_im, *c_re, *c_im, *log_dt, *dskip;
  int first;
};

__device__ __forceinline__ uint32_t s32(const void* p) { return (uint32_t)__cvta_generic_to_shared(p); }
__device__ __forceinline__ void mbar_init(uint32_t b, int c) { asm volatile("mbarrier.init.shared::cta.b64 [%0], %1;" ::"r"(b), "r"(c) : "memory"); }
__device__ __forceinline__ void mbar_expect(uint32_t b, int bytes) { asm volatile("mbarrier.arrive.expect_tx.shared::cta.b64 _, [%0], %1;" ::"r"(b), "r"(bytes) : "memory"); }
__device__ __forceinline__ void mbar_arrive(uint32_t b) { asm volatile("mbarrier.arrive.shared::cta.b64 _, [%0];" ::"r"(b) : "memory"); }
__device__ __forceinline__ void mbar_wait(uint32_t b, int parity) {
  asm volatile("{\n.reg .pred p;\nWAIT_LOOP:\nmbarrier.try_wait.parity.shared::cta.b64 p, [%0], %1;\n@p bra WAIT_DONE;\nbra WAIT_LOOP;\nWAIT_DONE:\n}" ::"r"(b), "r"(parity) : "memory");
}
__device__ __forceinline__ bool mbar_test(uint32_t b, int parity) {
  uint32_t ok;
  asm volatile("{\n.reg .pred p;\nmbarrier.test_wait.parity.shared::cta.b64 p, [%1], %2;\nselp.u32 %0, 1, 0, p;\n}" : "=r"(ok) : "r"(b), "r"(parity) : "memory");
  return ok != 0;
}
__device__ __forceinline__ int opaque_tid() { int v; asm volatile("mov.u32 %0, %%tid.x;" : "=r"(v)); return v; }
__device__ __forceinline__ bool elect_one() {
  uint32_t r;
  asm volatile("{\n.reg .pred p;\nelect.sync _|p, 0xffffffff;\nselp.u32 %0, 1, 0, p;\n}" : "=r"(r));
  return r != 0;
}
__device__ __forceinline__ void tma_ld(uint32_t dst, const CUtensorMap* m, int c0, int c1, uint32_t bar) {
  asm volatile("cp.async.bulk.tensor.2d.shared::cluster.global.mbarrier::complete_tx::bytes [%0], [%1, {%3, %4}], [%2];"
               ::"r"(dst), "l"(m), "r"(bar), "r"(c0), "r"(c1) : "memory");
}
__device__ __forceinline__ void tma_ld3(uint32_t dst, const CUtensorMap* m, int c0, int c1, int c2, uint32_t bar) {
  asm volatile("cp.async.bulk.tensor.3d.shared::cluster.global.mbarrier::complete_tx::bytes [%0], [%1, {%3, %4, %5}], [%2];"
               ::"r"(dst), "l"(m), "r"(bar), "r"(c0), "r"(c1), "r"(c2) : "memory");
}
__device__ __forceinline__ void tma_ld5(uint32_t dst, const CUtensorMap* m, int c0, int c4, uint32_t bar) {
  asm volatile("cp.async.bulk.tensor.5d.shared::cluster.global.mbarrier::complete_tx::bytes [%0], [%1, {%3, 0, 0, 0, %4}], [%2];"
               ::"r"(dst), "l"(m), "r"(bar), "r"(c0), "r"(c4) : "memory");
}
__device__ __forceinline__ void tma_prefetch5(const CUtensorMap* m, int c0, int c4) {
  asm volatile("cp.async.bulk.prefetch.tensor.5d.L2.global.tile [%0, {%1, 0, 0, 0, %2}];" ::"l"(m), "r"(c0), "r"(c4) : "memory");
}
__device__ __forceinline__ void tma_prefetch2(const CUtensorMap* m, int c0, int c1) {
  asm volatile("cp.async.bulk.prefetch.tensor.2d.L2.global.tile [%0, {%1, %2}];" ::"l"(m), "r"(c0), "r"(c1) : "memory");
}
__device__ __forceinline__ void tma_prefetch3(const CUtensorMap* m, int c0, int c1, int c2) {
  asm volatile("cp.async.bulk.prefetch.tensor.3d.L2.global.tile [%0, {%1, %2, %3}];" ::"l"(m), "r"(c0), "r"(c1), "r"(c2) : "memory");
}
__device__ __forceinline__ void tma_st(const CUtensorMap* m, int c0, int c1, uint32_t src) {
  asm volatile("cp.async.bulk.tensor.2d.global.shared::cta.bulk_group [%0, {%2, %3}], [%1];" ::"l"(m), "r"(src), "r"(c0), "r"(c1) : "memory");
}
__device__ __forceinline__ void bulk_ld(uint32_t dst, const void* src, int bytes, uint32_t bar) {
  asm volatile("cp.async.bulk.shared::cluster.global.mbarrier::complete_tx::bytes [%0], [%1], %2, [%3];" ::"r"(dst), "l"(src), "r"(bytes), "r"(bar) : "memory");
}
__device__ __forceinline__ void bulk_st(void* dst, uint32_t src, int bytes) {
  asm volatile("cp.async.bulk.global.shared::cta.bulk_group [%0], [%1], %2;" ::"l"(dst), "r"(src), "r"(bytes) : "memory");
}
__device__ __forceinline__ void bulk_red_add_f32(void* dst, uint32_t src, int bytes) {
  asm volatile("cp.reduce.async.bulk.global.shared::cta.bulk_group.add.f32 [%0], [%1], %2;" ::"l"(dst), "r"(src), "r"(bytes) : "memory");
}
__device__ __forceinline__ void bulk_commit() { asm volatile("cp.async.bulk.commit_group;" ::: "memory"); }
__device__ __forceinline__ void bulk_wait_all() { asm volatile("cp.async.bulk.wait_group 0;" ::: "memory"); }
__device__ __forceinline__ void fence_async_smem() { asm volatile("fence.proxy.async.shared::cta;" ::: "memory"); }
__device__ __forceinline__ void fence_async_global() { asm volatile("fence.proxy.async.global;" ::: "memory"); }
__device__ __forceinline__ void bar_sync(int id, int n) { asm volatile("bar.sync %0, %1;" ::"r"(id), "r"(n) : "memory"); }
__device__ __forceinline__ void bar_arrive(int id, int n) { asm volatile("bar.arrive %0, %1;" ::"r"(id), "r"(n) : "memory"); }
__device__ __forceinline__ bool bar_or(int id, int n, bool v) {
  uint32_t r;
  asm volatile("{\n.reg .pred p, q;\nsetp.ne.u32 q, %3, 0;\nbar.red.or.pred p, %1, %2, q;\nselp.u32 %0, 1, 0, p;\n}" : "=r"(r) : "r"(id), "r"(n), "r"((uint32_t)v) : "memory");
  return r != 0;
}
__device__ __forceinline__ void bulk_wait_read() { asm volatile("cp.async.bulk.wait_group.read 0;" ::: "memory"); }
__device__ __forceinline__ void stg128(void* p, uint4 v) { asm volatile("st.relaxed.gpu.global.v4.u32 [%0], {%1,%2,%3,%4};" ::"l"(p), "r"(v.x), "r"(v.y), "r"(v.z), "r"(v.w) : "memory"); }
constexpr uint32_t UNSET = 0xffffffffu;
constexpr int MAX_RETRY = 1 << 16;
__device__ __forceinline__ void wg_fence() { asm volatile("wgmma.fence.sync.aligned;" ::: "memory"); }
__device__ __forceinline__ void wg_commit() { asm volatile("wgmma.commit_group.sync.aligned;" ::: "memory"); }
template <int N> __device__ __forceinline__ void wg_wait() { asm volatile("wgmma.wait_group.sync.aligned %0;" ::"n"(N) : "memory"); }
__device__ __forceinline__ uint64_t mkdesc(uint32_t addr, uint32_t lbo, uint32_t sbo, int sw) {
  return (uint64_t)((addr & 0x3FFFF) >> 4) | ((uint64_t)(lbo >> 4) << 16) | ((uint64_t)(sbo >> 4) << 32) | ((uint64_t)sw << 62);
}
__device__ __forceinline__ void ldsm4(uint32_t* r, uint32_t a) {
  asm volatile("ldmatrix.sync.aligned.m8n8.x4.shared.b16 {%0,%1,%2,%3}, [%4];" : "=r"(r[0]), "=r"(r[1]), "=r"(r[2]), "=r"(r[3]) : "r"(a) : "memory");
}
__device__ __forceinline__ void ldsm4t(uint32_t* r, uint32_t a) {
  asm volatile("ldmatrix.sync.aligned.m8n8.x4.trans.shared.b16 {%0,%1,%2,%3}, [%4];" : "=r"(r[0]), "=r"(r[1]), "=r"(r[2]), "=r"(r[3]) : "r"(a) : "memory");
}
__device__ __forceinline__ void stsm4(uint32_t a, uint32_t r0, uint32_t r1, uint32_t r2, uint32_t r3) {
  asm volatile("stmatrix.sync.aligned.m8n8.x4.shared.b16 [%0], {%1,%2,%3,%4};" ::"r"(a), "r"(r0), "r"(r1), "r"(r2), "r"(r3) : "memory");
}
__device__ __forceinline__ void stsm4t(uint32_t a, uint32_t r0, uint32_t r1, uint32_t r2, uint32_t r3) {
  asm volatile("stmatrix.sync.aligned.m8n8.x4.trans.shared.b16 [%0], {%1,%2,%3,%4};" ::"r"(a), "r"(r0), "r"(r1), "r"(r2), "r"(r3) : "memory");
}
__device__ __forceinline__ uint32_t movm_t(uint32_t a) { uint32_t r; asm volatile("movmatrix.sync.aligned.m8n8.trans.b16 %0, %1;" : "=r"(r) : "r"(a)); return r; }
__device__ __forceinline__ uint32_t lds32(uint32_t a) { uint32_t v; asm volatile("ld.shared.b32 %0, [%1];" : "=r"(v) : "r"(a) : "memory"); return v; }
__device__ __forceinline__ float2 lds64f(uint32_t a) { float2 v; asm volatile("ld.shared.v2.f32 {%0,%1}, [%2];" : "=f"(v.x), "=f"(v.y) : "r"(a) : "memory"); return v; }
__device__ __forceinline__ float4 lds128f(uint32_t a) { float4 v; asm volatile("ld.shared.v4.f32 {%0,%1,%2,%3}, [%4];" : "=f"(v.x), "=f"(v.y), "=f"(v.z), "=f"(v.w) : "r"(a) : "memory"); return v; }
__device__ __forceinline__ uint4 lds128(uint32_t a) { uint4 v; asm volatile("ld.shared.v4.b32 {%0,%1,%2,%3}, [%4];" : "=r"(v.x), "=r"(v.y), "=r"(v.z), "=r"(v.w) : "r"(a) : "memory"); return v; }
__device__ __forceinline__ void sts128(uint32_t a, uint4 v) { asm volatile("st.shared.v4.b32 [%0], {%1,%2,%3,%4};" ::"r"(a), "r"(v.x), "r"(v.y), "r"(v.z), "r"(v.w) : "memory"); }
__device__ __forceinline__ void sts128f(uint32_t a, float x, float y, float z, float w) { asm volatile("st.shared.v4.f32 [%0], {%1,%2,%3,%4};" ::"r"(a), "f"(x), "f"(y), "f"(z), "f"(w) : "memory"); }
__device__ __forceinline__ void sts32f(uint32_t a, float v) { asm volatile("st.shared.f32 [%0], %1;" ::"r"(a), "f"(v) : "memory"); }
__device__ __forceinline__ void sts16(uint32_t a, uint16_t v) { asm volatile("st.shared.u16 [%0], %1;" ::"r"(a), "h"(v) : "memory"); }
__device__ __forceinline__ uint32_t lds16(uint32_t a) { uint16_t v; asm volatile("ld.shared.u16 %0, [%1];" : "=h"(v) : "r"(a) : "memory"); return v; }
__device__ __forceinline__ uint32_t packbf(float lo, float hi) { uint32_t r; asm("cvt.rn.bf16x2.f32 %0, %1, %2;" : "=r"(r) : "f"(hi), "f"(lo)); return r; }
__device__ __forceinline__ float bf_lo(uint32_t v) { return __uint_as_float(v << 16); }
__device__ __forceinline__ float bf_hi(uint32_t v) { return __uint_as_float(v & 0xffff0000u); }
__device__ __forceinline__ float ex2(float x) { float r; asm("ex2.approx.ftz.f32 %0, %1;" : "=f"(r) : "f"(x)); return r; }
__device__ __forceinline__ float rsqrt_approx(float x) { float r; asm("rsqrt.approx.ftz.f32 %0, %1;" : "=f"(r) : "f"(x)); return r; }
__device__ __forceinline__ float rcp_approx(float x) { float r; asm("rcp.approx.ftz.f32 %0, %1;" : "=f"(r) : "f"(x)); return r; }
__device__ __forceinline__ void mma_bf16(float* d, const uint32_t* a, uint32_t b0, uint32_t b1) {
  asm("mma.sync.aligned.m16n8k16.row.col.f32.bf16.bf16.f32 {%0,%1,%2,%3}, {%4,%5,%6,%7}, {%8,%9}, {%0,%1,%2,%3};"
               : "+f"(d[0]), "+f"(d[1]), "+f"(d[2]), "+f"(d[3]) : "r"(a[0]), "r"(a[1]), "r"(a[2]), "r"(a[3]), "r"(b0), "r"(b1));
}
__device__ __forceinline__ void mma_tf32(float* d, float a0, float a1, float a2, float a3, float b0, float b1) {
  asm("mma.sync.aligned.m16n8k8.row.col.f32.tf32.tf32.f32 {%0,%1,%2,%3}, {%4,%5,%6,%7}, {%8,%9}, {%0,%1,%2,%3};"
               : "+f"(d[0]), "+f"(d[1]), "+f"(d[2]), "+f"(d[3])
               : "r"(__float_as_uint(a0)), "r"(__float_as_uint(a1)), "r"(__float_as_uint(a2)), "r"(__float_as_uint(a3)),
                 "r"(__float_as_uint(b0)), "r"(__float_as_uint(b1)));
}
__device__ __forceinline__ void red_release(unsigned* p) { asm volatile("red.release.gpu.global.add.u32 [%0], 1;" ::"l"(p) : "memory"); }
__device__ __forceinline__ void red_relaxed(unsigned* p) { asm volatile("red.relaxed.gpu.global.add.u32 [%0], 1;" ::"l"(p) : "memory"); }
__device__ __forceinline__ unsigned ld_relaxed(const unsigned* p) { unsigned v; asm volatile("ld.relaxed.gpu.global.u32 %0, [%1];" : "=r"(v) : "l"(p) : "memory"); return v; }
__device__ __forceinline__ void spin_until(const unsigned* p, unsigned target) {
  int it = 0;
  while ((int)(ld_relaxed(p) - target) < 0) {
    if (++it > (1 << 23)) __trap();
  }
}
__device__ __forceinline__ uint4 ldcg128(const void* p) { uint4 v; asm volatile("ld.global.cg.v4.b32 {%0,%1,%2,%3}, [%4];" : "=r"(v.x), "=r"(v.y), "=r"(v.z), "=r"(v.w) : "l"(p) : "memory"); return v; }
__device__ __forceinline__ uint4 ld_tagged(const uint4* p) { uint4 v; asm volatile("ld.relaxed.gpu.global.v4.u32 {%0,%1,%2,%3}, [%4];" : "=r"(v.x), "=r"(v.y), "=r"(v.z), "=r"(v.w) : "l"(p) : "memory"); return v; }
__device__ __forceinline__ void st_tagged(uint4* p, uint32_t a, uint32_t b, uint32_t tag) { asm volatile("st.relaxed.gpu.global.v4.u32 [%0], {%1,%2,%3,%2};" ::"l"(p), "r"(a), "r"(tag), "r"(b) : "memory"); }
__device__ __forceinline__ void st_tagged3(uint4* p, uint32_t a, uint32_t b, uint32_t c, uint32_t tag) { asm volatile("st.relaxed.gpu.global.v4.u32 [%0], {%1,%2,%3,%4};" ::"l"(p), "r"(a), "r"(b), "r"(c), "r"(tag) : "memory"); }
__device__ __forceinline__ uint4 poll_tagged(const uint4* p, uint32_t tag) {
  uint4 v = ld_tagged(p);
  int it = 0;
  while (v.y != tag || v.w != tag) {
    if (++it > (1 << 22)) __trap();
    v = ld_tagged(p);
  }
  return v;
}
__device__ __forceinline__ uint32_t hadd2(uint32_t a, uint32_t b) { uint32_t r; asm("add.rn.bf16x2 %0, %1, %2;" : "=r"(r) : "r"(a), "r"(b)); return r; }
__device__ __forceinline__ uint32_t hmul2(uint32_t a, uint32_t b) { uint32_t r; asm("mul.rn.bf16x2 %0, %1, %2;" : "=r"(r) : "r"(a), "r"(b)); return r; }

__device__ __forceinline__ uint32_t hfma2(uint32_t a, uint32_t b, uint32_t c) { uint32_t r; asm("fma.rn.bf16x2 %0, %1, %2, %3;" : "=r"(r) : "r"(a), "r"(b), "r"(c)); return r; }
__device__ __forceinline__ void sts32(uint32_t a, uint32_t v) { asm volatile("st.shared.u32 [%0], %1;" ::"r"(a), "r"(v) : "memory"); }

template <int N> __device__ __forceinline__ void acc_fence(float* a) {
#pragma unroll
  for (int i = 0; i < N; i++) asm volatile("" : "+f"(a[i]) :: "memory");
}

template<int N,int TB> __device__ __forceinline__ void wgmma_rs(float* d, const uint32_t* a, uint64_t db, int sd);
template<int N,int TA,int TB> __device__ __forceinline__ void wgmma_ss(float* d, uint64_t da, uint64_t db, int sd);
template<> __device__ __forceinline__ void wgmma_rs<64,0>(float* d, const uint32_t* a, uint64_t db, int sd) {
  asm volatile("{\n.reg .pred p;\nsetp.ne.b32 p, %37, 0;\nwgmma.mma_async.sync.aligned.m64n64k16.f32.bf16.bf16 {%0,%1,%2,%3,%4,%5,%6,%7,%8,%9,%10,%11,%12,%13,%14,%15,%16,%17,%18,%19,%20,%21,%22,%23,%24,%25,%26,%27,%28,%29,%30,%31}, {%32,%33,%34,%35}, %36, p, 1, 1, 0;\n}\n"
   : "+f"(d[0]),"+f"(d[1]),"+f"(d[2]),"+f"(d[3]),"+f"(d[4]),"+f"(d[5]),"+f"(d[6]),"+f"(d[7]),"+f"(d[8]),"+f"(d[9]),"+f"(d[10]),"+f"(d[11]),"+f"(d[12]),"+f"(d[13]),"+f"(d[14]),"+f"(d[15]),"+f"(d[16]),"+f"(d[17]),"+f"(d[18]),"+f"(d[19]),"+f"(d[20]),"+f"(d[21]),"+f"(d[22]),"+f"(d[23]),"+f"(d[24]),"+f"(d[25]),"+f"(d[26]),"+f"(d[27]),"+f"(d[28]),"+f"(d[29]),"+f"(d[30]),"+f"(d[31])
   : "r"(a[0]), "r"(a[1]), "r"(a[2]), "r"(a[3]), "l"(db), "r"(sd));
}
template<> __device__ __forceinline__ void wgmma_rs<56,0>(float* d, const uint32_t* a, uint64_t db, int sd) {
  asm volatile("{\n.reg .pred p;\nsetp.ne.b32 p, %33, 0;\nwgmma.mma_async.sync.aligned.m64n56k16.f32.bf16.bf16 {%0,%1,%2,%3,%4,%5,%6,%7,%8,%9,%10,%11,%12,%13,%14,%15,%16,%17,%18,%19,%20,%21,%22,%23,%24,%25,%26,%27}, {%28,%29,%30,%31}, %32, p, 1, 1, 0;\n}\n"
   : "+f"(d[0]),"+f"(d[1]),"+f"(d[2]),"+f"(d[3]),"+f"(d[4]),"+f"(d[5]),"+f"(d[6]),"+f"(d[7]),"+f"(d[8]),"+f"(d[9]),"+f"(d[10]),"+f"(d[11]),"+f"(d[12]),"+f"(d[13]),"+f"(d[14]),"+f"(d[15]),"+f"(d[16]),"+f"(d[17]),"+f"(d[18]),"+f"(d[19]),"+f"(d[20]),"+f"(d[21]),"+f"(d[22]),"+f"(d[23]),"+f"(d[24]),"+f"(d[25]),"+f"(d[26]),"+f"(d[27])
   : "r"(a[0]), "r"(a[1]), "r"(a[2]), "r"(a[3]), "l"(db), "r"(sd));
}
template<> __device__ __forceinline__ void wgmma_rs<48,0>(float* d, const uint32_t* a, uint64_t db, int sd) {
  asm volatile("{\n.reg .pred p;\nsetp.ne.b32 p, %29, 0;\nwgmma.mma_async.sync.aligned.m64n48k16.f32.bf16.bf16 {%0,%1,%2,%3,%4,%5,%6,%7,%8,%9,%10,%11,%12,%13,%14,%15,%16,%17,%18,%19,%20,%21,%22,%23}, {%24,%25,%26,%27}, %28, p, 1, 1, 0;\n}\n"
   : "+f"(d[0]),"+f"(d[1]),"+f"(d[2]),"+f"(d[3]),"+f"(d[4]),"+f"(d[5]),"+f"(d[6]),"+f"(d[7]),"+f"(d[8]),"+f"(d[9]),"+f"(d[10]),"+f"(d[11]),"+f"(d[12]),"+f"(d[13]),"+f"(d[14]),"+f"(d[15]),"+f"(d[16]),"+f"(d[17]),"+f"(d[18]),"+f"(d[19]),"+f"(d[20]),"+f"(d[21]),"+f"(d[22]),"+f"(d[23])
   : "r"(a[0]), "r"(a[1]), "r"(a[2]), "r"(a[3]), "l"(db), "r"(sd));
}
template<> __device__ __forceinline__ void wgmma_rs<40,0>(float* d, const uint32_t* a, uint64_t db, int sd) {
  asm volatile("{\n.reg .pred p;\nsetp.ne.b32 p, %25, 0;\nwgmma.mma_async.sync.aligned.m64n40k16.f32.bf16.bf16 {%0,%1,%2,%3,%4,%5,%6,%7,%8,%9,%10,%11,%12,%13,%14,%15,%16,%17,%18,%19}, {%20,%21,%22,%23}, %24, p, 1, 1, 0;\n}\n"
   : "+f"(d[0]),"+f"(d[1]),"+f"(d[2]),"+f"(d[3]),"+f"(d[4]),"+f"(d[5]),"+f"(d[6]),"+f"(d[7]),"+f"(d[8]),"+f"(d[9]),"+f"(d[10]),"+f"(d[11]),"+f"(d[12]),"+f"(d[13]),"+f"(d[14]),"+f"(d[15]),"+f"(d[16]),"+f"(d[17]),"+f"(d[18]),"+f"(d[19])
   : "r"(a[0]), "r"(a[1]), "r"(a[2]), "r"(a[3]), "l"(db), "r"(sd));
}
template<> __device__ __forceinline__ void wgmma_rs<32,0>(float* d, const uint32_t* a, uint64_t db, int sd) {
  asm volatile("{\n.reg .pred p;\nsetp.ne.b32 p, %21, 0;\nwgmma.mma_async.sync.aligned.m64n32k16.f32.bf16.bf16 {%0,%1,%2,%3,%4,%5,%6,%7,%8,%9,%10,%11,%12,%13,%14,%15}, {%16,%17,%18,%19}, %20, p, 1, 1, 0;\n}\n"
   : "+f"(d[0]),"+f"(d[1]),"+f"(d[2]),"+f"(d[3]),"+f"(d[4]),"+f"(d[5]),"+f"(d[6]),"+f"(d[7]),"+f"(d[8]),"+f"(d[9]),"+f"(d[10]),"+f"(d[11]),"+f"(d[12]),"+f"(d[13]),"+f"(d[14]),"+f"(d[15])
   : "r"(a[0]), "r"(a[1]), "r"(a[2]), "r"(a[3]), "l"(db), "r"(sd));
}
template<> __device__ __forceinline__ void wgmma_rs<24,0>(float* d, const uint32_t* a, uint64_t db, int sd) {
  asm volatile("{\n.reg .pred p;\nsetp.ne.b32 p, %17, 0;\nwgmma.mma_async.sync.aligned.m64n24k16.f32.bf16.bf16 {%0,%1,%2,%3,%4,%5,%6,%7,%8,%9,%10,%11}, {%12,%13,%14,%15}, %16, p, 1, 1, 0;\n}\n"
   : "+f"(d[0]),"+f"(d[1]),"+f"(d[2]),"+f"(d[3]),"+f"(d[4]),"+f"(d[5]),"+f"(d[6]),"+f"(d[7]),"+f"(d[8]),"+f"(d[9]),"+f"(d[10]),"+f"(d[11])
   : "r"(a[0]), "r"(a[1]), "r"(a[2]), "r"(a[3]), "l"(db), "r"(sd));
}
template<> __device__ __forceinline__ void wgmma_rs<16,0>(float* d, const uint32_t* a, uint64_t db, int sd) {
  asm volatile("{\n.reg .pred p;\nsetp.ne.b32 p, %13, 0;\nwgmma.mma_async.sync.aligned.m64n16k16.f32.bf16.bf16 {%0,%1,%2,%3,%4,%5,%6,%7}, {%8,%9,%10,%11}, %12, p, 1, 1, 0;\n}\n"
   : "+f"(d[0]),"+f"(d[1]),"+f"(d[2]),"+f"(d[3]),"+f"(d[4]),"+f"(d[5]),"+f"(d[6]),"+f"(d[7])
   : "r"(a[0]), "r"(a[1]), "r"(a[2]), "r"(a[3]), "l"(db), "r"(sd));
}
template<> __device__ __forceinline__ void wgmma_rs<8,0>(float* d, const uint32_t* a, uint64_t db, int sd) {
  asm volatile("{\n.reg .pred p;\nsetp.ne.b32 p, %9, 0;\nwgmma.mma_async.sync.aligned.m64n8k16.f32.bf16.bf16 {%0,%1,%2,%3}, {%4,%5,%6,%7}, %8, p, 1, 1, 0;\n}\n"
   : "+f"(d[0]),"+f"(d[1]),"+f"(d[2]),"+f"(d[3])
   : "r"(a[0]), "r"(a[1]), "r"(a[2]), "r"(a[3]), "l"(db), "r"(sd));
}
template<> __device__ __forceinline__ void wgmma_ss<64,1,0>(float* d, uint64_t da, uint64_t db, int sd) {
  asm volatile("{\n.reg .pred p;\nsetp.ne.b32 p, %34, 0;\nwgmma.mma_async.sync.aligned.m64n64k16.f32.bf16.bf16 {%0,%1,%2,%3,%4,%5,%6,%7,%8,%9,%10,%11,%12,%13,%14,%15,%16,%17,%18,%19,%20,%21,%22,%23,%24,%25,%26,%27,%28,%29,%30,%31}, %32, %33, p, 1, 1, 1, 0;\n}\n"
   : "+f"(d[0]),"+f"(d[1]),"+f"(d[2]),"+f"(d[3]),"+f"(d[4]),"+f"(d[5]),"+f"(d[6]),"+f"(d[7]),"+f"(d[8]),"+f"(d[9]),"+f"(d[10]),"+f"(d[11]),"+f"(d[12]),"+f"(d[13]),"+f"(d[14]),"+f"(d[15]),"+f"(d[16]),"+f"(d[17]),"+f"(d[18]),"+f"(d[19]),"+f"(d[20]),"+f"(d[21]),"+f"(d[22]),"+f"(d[23]),"+f"(d[24]),"+f"(d[25]),"+f"(d[26]),"+f"(d[27]),"+f"(d[28]),"+f"(d[29]),"+f"(d[30]),"+f"(d[31])
   : "l"(da), "l"(db), "r"(sd));
}
template<> __device__ __forceinline__ void wgmma_ss<64,0,1>(float* d, uint64_t da, uint64_t db, int sd) {
  asm volatile("{\n.reg .pred p;\nsetp.ne.b32 p, %34, 0;\nwgmma.mma_async.sync.aligned.m64n64k16.f32.bf16.bf16 {%0,%1,%2,%3,%4,%5,%6,%7,%8,%9,%10,%11,%12,%13,%14,%15,%16,%17,%18,%19,%20,%21,%22,%23,%24,%25,%26,%27,%28,%29,%30,%31}, %32, %33, p, 1, 1, 0, 1;\n}\n"
   : "+f"(d[0]),"+f"(d[1]),"+f"(d[2]),"+f"(d[3]),"+f"(d[4]),"+f"(d[5]),"+f"(d[6]),"+f"(d[7]),"+f"(d[8]),"+f"(d[9]),"+f"(d[10]),"+f"(d[11]),"+f"(d[12]),"+f"(d[13]),"+f"(d[14]),"+f"(d[15]),"+f"(d[16]),"+f"(d[17]),"+f"(d[18]),"+f"(d[19]),"+f"(d[20]),"+f"(d[21]),"+f"(d[22]),"+f"(d[23]),"+f"(d[24]),"+f"(d[25]),"+f"(d[26]),"+f"(d[27]),"+f"(d[28]),"+f"(d[29]),"+f"(d[30]),"+f"(d[31])
   : "l"(da), "l"(db), "r"(sd));
}
template<> __device__ __forceinline__ void wgmma_ss<192,0,1>(float* d, uint64_t da, uint64_t db, int sd) {
  asm volatile("{\n.reg .pred p;\nsetp.ne.b32 p, %98, 0;\nwgmma.mma_async.sync.aligned.m64n192k16.f32.bf16.bf16 {%0,%1,%2,%3,%4,%5,%6,%7,%8,%9,%10,%11,%12,%13,%14,%15,%16,%17,%18,%19,%20,%21,%22,%23,%24,%25,%26,%27,%28,%29,%30,%31,%32,%33,%34,%35,%36,%37,%38,%39,%40,%41,%42,%43,%44,%45,%46,%47,%48,%49,%50,%51,%52,%53,%54,%55,%56,%57,%58,%59,%60,%61,%62,%63,%64,%65,%66,%67,%68,%69,%70,%71,%72,%73,%74,%75,%76,%77,%78,%79,%80,%81,%82,%83,%84,%85,%86,%87,%88,%89,%90,%91,%92,%93,%94,%95}, %96, %97, p, 1, 1, 0, 1;\n}\n"
   : "+f"(d[0]),"+f"(d[1]),"+f"(d[2]),"+f"(d[3]),"+f"(d[4]),"+f"(d[5]),"+f"(d[6]),"+f"(d[7]),"+f"(d[8]),"+f"(d[9]),"+f"(d[10]),"+f"(d[11]),"+f"(d[12]),"+f"(d[13]),"+f"(d[14]),"+f"(d[15]),"+f"(d[16]),"+f"(d[17]),"+f"(d[18]),"+f"(d[19]),"+f"(d[20]),"+f"(d[21]),"+f"(d[22]),"+f"(d[23]),"+f"(d[24]),"+f"(d[25]),"+f"(d[26]),"+f"(d[27]),"+f"(d[28]),"+f"(d[29]),"+f"(d[30]),"+f"(d[31]),"+f"(d[32]),"+f"(d[33]),"+f"(d[34]),"+f"(d[35]),"+f"(d[36]),"+f"(d[37]),"+f"(d[38]),"+f"(d[39]),"+f"(d[40]),"+f"(d[41]),"+f"(d[42]),"+f"(d[43]),"+f"(d[44]),"+f"(d[45]),"+f"(d[46]),"+f"(d[47]),"+f"(d[48]),"+f"(d[49]),"+f"(d[50]),"+f"(d[51]),"+f"(d[52]),"+f"(d[53]),"+f"(d[54]),"+f"(d[55]),"+f"(d[56]),"+f"(d[57]),"+f"(d[58]),"+f"(d[59]),"+f"(d[60]),"+f"(d[61]),"+f"(d[62]),"+f"(d[63]),"+f"(d[64]),"+f"(d[65]),"+f"(d[66]),"+f"(d[67]),"+f"(d[68]),"+f"(d[69]),"+f"(d[70]),"+f"(d[71]),"+f"(d[72]),"+f"(d[73]),"+f"(d[74]),"+f"(d[75]),"+f"(d[76]),"+f"(d[77]),"+f"(d[78]),"+f"(d[79]),"+f"(d[80]),"+f"(d[81]),"+f"(d[82]),"+f"(d[83]),"+f"(d[84]),"+f"(d[85]),"+f"(d[86]),"+f"(d[87]),"+f"(d[88]),"+f"(d[89]),"+f"(d[90]),"+f"(d[91]),"+f"(d[92]),"+f"(d[93]),"+f"(d[94]),"+f"(d[95])
   : "l"(da), "l"(db), "r"(sd));
}
template<> __device__ __forceinline__ void wgmma_ss<192,1,1>(float* d, uint64_t da, uint64_t db, int sd) {
  asm volatile("{\n.reg .pred p;\nsetp.ne.b32 p, %98, 0;\nwgmma.mma_async.sync.aligned.m64n192k16.f32.bf16.bf16 {%0,%1,%2,%3,%4,%5,%6,%7,%8,%9,%10,%11,%12,%13,%14,%15,%16,%17,%18,%19,%20,%21,%22,%23,%24,%25,%26,%27,%28,%29,%30,%31,%32,%33,%34,%35,%36,%37,%38,%39,%40,%41,%42,%43,%44,%45,%46,%47,%48,%49,%50,%51,%52,%53,%54,%55,%56,%57,%58,%59,%60,%61,%62,%63,%64,%65,%66,%67,%68,%69,%70,%71,%72,%73,%74,%75,%76,%77,%78,%79,%80,%81,%82,%83,%84,%85,%86,%87,%88,%89,%90,%91,%92,%93,%94,%95}, %96, %97, p, 1, 1, 1, 1;\n}\n"
   : "+f"(d[0]),"+f"(d[1]),"+f"(d[2]),"+f"(d[3]),"+f"(d[4]),"+f"(d[5]),"+f"(d[6]),"+f"(d[7]),"+f"(d[8]),"+f"(d[9]),"+f"(d[10]),"+f"(d[11]),"+f"(d[12]),"+f"(d[13]),"+f"(d[14]),"+f"(d[15]),"+f"(d[16]),"+f"(d[17]),"+f"(d[18]),"+f"(d[19]),"+f"(d[20]),"+f"(d[21]),"+f"(d[22]),"+f"(d[23]),"+f"(d[24]),"+f"(d[25]),"+f"(d[26]),"+f"(d[27]),"+f"(d[28]),"+f"(d[29]),"+f"(d[30]),"+f"(d[31]),"+f"(d[32]),"+f"(d[33]),"+f"(d[34]),"+f"(d[35]),"+f"(d[36]),"+f"(d[37]),"+f"(d[38]),"+f"(d[39]),"+f"(d[40]),"+f"(d[41]),"+f"(d[42]),"+f"(d[43]),"+f"(d[44]),"+f"(d[45]),"+f"(d[46]),"+f"(d[47]),"+f"(d[48]),"+f"(d[49]),"+f"(d[50]),"+f"(d[51]),"+f"(d[52]),"+f"(d[53]),"+f"(d[54]),"+f"(d[55]),"+f"(d[56]),"+f"(d[57]),"+f"(d[58]),"+f"(d[59]),"+f"(d[60]),"+f"(d[61]),"+f"(d[62]),"+f"(d[63]),"+f"(d[64]),"+f"(d[65]),"+f"(d[66]),"+f"(d[67]),"+f"(d[68]),"+f"(d[69]),"+f"(d[70]),"+f"(d[71]),"+f"(d[72]),"+f"(d[73]),"+f"(d[74]),"+f"(d[75]),"+f"(d[76]),"+f"(d[77]),"+f"(d[78]),"+f"(d[79]),"+f"(d[80]),"+f"(d[81]),"+f"(d[82]),"+f"(d[83]),"+f"(d[84]),"+f"(d[85]),"+f"(d[86]),"+f"(d[87]),"+f"(d[88]),"+f"(d[89]),"+f"(d[90]),"+f"(d[91]),"+f"(d[92]),"+f"(d[93]),"+f"(d[94]),"+f"(d[95])
   : "l"(da), "l"(db), "r"(sd));
}

template <bool TR>
__device__ __forceinline__ void gemm_section(float* acc, float& mean0, float& mean1, float& rstd0, float& rstd1,
                                             uint32_t sb, int blk, int hg, int wg, int w, int lane) {
  constexpr int layer = TR ? 1 : 0;
  constexpr int TURN = TR ? TURN1 : TURN0;
  constexpr int LSTAT = TURN < 4 ? TURN - 1 : 3;
  const uint32_t bar = sb + SM_BAR;
  const int g = lane >> 2, t = lane & 3;
  const bool leader = (w == 0) && (lane == 0);
  const int statpos = hg < 3 ? 1 : wg ? LSTAT : TR ? 3 : 2;
  const bool copy = hg >= 3 && wg == 0;
  const int cut = wg ? TURN : 4;
  auto wait_full = [&](int c) {
    mbar_wait(bar + 8 * (B_XF + 8 * wg + c), layer);
    mbar_wait(bar + 8 * (B_WF + c), layer);
  };
  auto peek = [&](int c) {
    const bool x = mbar_test(bar + 8 * (B_XF + 8 * wg + c), layer), y = mbar_test(bar + 8 * (B_WF + c), layer);
    return x && y;
  };
  const uint64_t da0 = mkdesc(sb, TR ? 8192 : 16, 1024, 1), db0 = mkdesc(sb, 8192, 1024, 1);
  uint32_t xt = wg ? 0xfedcba98u : 0x21043210u;
  uint64_t wt = 0x0816131005161310ull;
  uint64_t da = da0 + ((xt & 15) << 9), db = db0 + (16 << 9);
  auto issue = [&](int c, int first) {
    wg_fence();
#pragma unroll
    for (int ks = 0; ks < 4; ks++) wgmma_ss<192, TR ? 1 : 0, 1>(acc, da + (TR ? ks * 128 : ks * 2), db + ks * 128, !first || ks != 0);
    wg_commit();
    xt >>= 4; wt >>= 8;
    da = da0 + ((xt & 15) << 9); db = db0 + (((uint32_t)wt & 31) << 9);
  };
  wait_full(0);
  bool ready = peek(1);
  issue(0, 1);
  TSW(0);
#pragma unroll 1
  for (int c = 1; c < cut; c++) {
    if (!ready) wait_full(c);
    issue(c, 0);
    ready = peek(c + 1);
    wg_wait<1>();
    if (leader) mbar_arrive(bar + 8 * (B_DN + 8 * wg + c - 1));
    if (wg == 1 && c == cut - 1) {
      wg_wait<0>();
      if (leader) mbar_arrive(bar + 8 * (B_DN + 8 + c));
    }
    if (c == statpos) {
      mbar_wait(bar + 8 * (copy ? B_SC : B_XF + 8 * wg + hg), layer);
      uint32_t A[16];
      const uint32_t xb = sb + (copy ? P_R : 8 * wg + hg) * PG;
#pragma unroll
      for (int ks = 0; ks < 4; ks++) {
        if (!TR) {
          const int row = 16 * w + (lane & 15), kc = 2 * ks + (lane >> 4);
          ldsm4(&A[4 * ks], xb + row * 128 + ((kc ^ (row & 7)) << 4));
        } else {
          const int k = 16 * ks + (lane & 7) + 8 * (lane >> 4), pc = 2 * w + ((lane >> 3) & 1);
          ldsm4t(&A[4 * ks], xb + k * 128 + ((pc ^ (k & 7)) << 4));
        }
      }
      float s0 = 0.f, q0 = 0.f, s1 = 0.f, q1 = 0.f;
#pragma unroll
      for (int i = 0; i < 16; i += 2) {
        const float a = bf_lo(A[i]), b = bf_hi(A[i]), c_ = bf_lo(A[i + 1]), d = bf_hi(A[i + 1]);
        s0 += a + b; q0 = fmaf(a, a, q0); q0 = fmaf(b, b, q0);
        s1 += c_ + d; q1 = fmaf(c_, c_, q1); q1 = fmaf(d, d, q1);
      }
#pragma unroll
      for (int o = 1; o <= 2; o <<= 1) {
        s0 += __shfl_xor_sync(~0u, s0, o); q0 += __shfl_xor_sync(~0u, q0, o);
        s1 += __shfl_xor_sync(~0u, s1, o); q1 += __shfl_xor_sync(~0u, q1, o);
      }
      if (t < 2)
        asm volatile("red.relaxed.gpu.global.add.v4.f32 [%0], {%1,%2,%3,%4};" ::"l"(g_rows + layer * LSEQ + blk * 64 + 16 * w + g + 8 * t),
                     "f"(t ? s1 : s0), "f"(t ? q1 : q0), "f"(1.f), "f"(0.f) : "memory");
    }
  }
  if (wg == 1) {
#pragma unroll 1
    for (int c = cut; c < 8; c++) wait_full(c);
    ready = true;
    bar_sync(5, 256);
  }
#pragma unroll 1
  for (int c = cut; c < 8; c++) {
    if (!ready) wait_full(c);
    issue(c, 0);
    if (wg == 1) {
      wg_wait<2>();
      if (leader && c >= cut + 2) mbar_arrive(bar + 8 * (B_DN + 8 + c - 2));
    } else if (c == 7) {
      bar_arrive(5, 256);
    } else {
      ready = peek(c + 1);
      wg_wait<1>();
      if (leader) mbar_arrive(bar + 8 * (B_DN + c - 1));
    }
  }
  mbar_wait(bar + 8 * (B_LN + wg), layer);
  const float4 ln = lds128f(sb + ln_off(wg) + (8 * w + g) * 16);
  mean0 = ln.x; rstd0 = ln.y; mean1 = ln.z; rstd1 = ln.w;
  wg_wait<0>();
  acc_fence<96>(acc);
  if (leader) mbar_arrive(bar + 8 * (B_DN + 8 * wg + 7));
}

__device__ __forceinline__ void attn_phase(const Params& p, uint32_t sb, int layer, int rb, int hg, int wg, int w) {
  const int lane = opaque_tid() & 31;
  const int g = lane >> 2, t = lane & 3;
  const uint32_t bar = sb + SM_BAR;
  const int blk = 16 * wg + rb;
  float acc[96];
  float2 cs[24];
  float mean0, mean1, rstd0, rstd1;
  if (layer) gemm_section<true>(acc, mean0, mean1, rstd0, rstd1, sb, blk, hg, wg, w, lane);
  else gemm_section<false>(acc, mean0, mean1, rstd0, rstd1, sb, blk, hg, wg, w, lane);
  TSW(1);
#pragma unroll
  for (int j = 8; j < 24; j++) cs[j] = lds64f(sb + SM_CS + 4 * (8 * j + 2 * t));
  const uint32_t kvx = sb + (wg ? 22 : 0) * PG;

  uint32_t kb[4][8], vb[4][8], qa[4][4];
  {
    const float nm0 = -mean0 * rstd0, nm1 = -mean1 * rstd1;
    const int st_row = 16 * w + (lane & 7) + 8 * ((lane >> 3) & 1);
    const uint32_t st_base = kvx + st_row * 256;
    const bool sender = (w == 3 && blk < 31);
    uint4* halo = &g_halo[(blk * 8 + hg) * 256 + lane];
    uint32_t r[4][2][4];
#pragma unroll
    for (int h = 0; h < 4; h++) {
#pragma unroll
      for (int kv = 0; kv < 2; kv++) {
#pragma unroll
        for (int dh = 0; dh < 2; dh++) {
          const int j = 8 + kv * 8 + 2 * h + dh;
          const float2 c2 = cs[j];
          const float v0 = fmaf(acc[4 * j + 0], rstd0, nm0 * c2.x), v1 = fmaf(acc[4 * j + 1], rstd0, nm0 * c2.y);
          const float v2 = fmaf(acc[4 * j + 2], rstd1, nm1 * c2.x), v3 = fmaf(acc[4 * j + 3], rstd1, nm1 * c2.y);
          r[h][kv][2 * dh] = packbf(v0, v1);
          r[h][kv][2 * dh + 1] = packbf(v2, v3);
        }
      }
      if (sender) {
        stg128(halo + (2 * h) * 32, make_uint4(r[h][0][0], r[h][0][2], r[h][0][1], r[h][0][3]));
        stg128(halo + (2 * h + 1) * 32, make_uint4(r[h][1][0], r[h][1][1], r[h][1][2], r[h][1][3]));
      }
    }
#pragma unroll
    for (int j = 0; j < 8; j++) cs[j] = lds64f(sb + SM_CS + 4 * (8 * j + 2 * t));
    mbar_wait(bar + 8 * (B_DN + 7), layer);
#pragma unroll
    for (int h = 0; h < 4; h++) {
#pragma unroll
      for (int kv = 0; kv < 2; kv++) {
        const int chunk = 4 * h + 2 * kv + (lane >> 4);
        if (w < 3) stsm4(st_base + (((chunk & 8) | ((chunk ^ st_row) & 7)) << 4), r[h][kv][0], r[h][kv][1], r[h][kv][2], r[h][kv][3]);
      }
      kb[h][4] = r[h][0][0]; kb[h][5] = r[h][0][2]; kb[h][6] = r[h][0][1]; kb[h][7] = r[h][0][3];
      vb[h][4] = movm_t(r[h][1][0]); vb[h][5] = movm_t(r[h][1][1]); vb[h][6] = movm_t(r[h][1][2]); vb[h][7] = movm_t(r[h][1][3]);
    }
#pragma unroll
    for (int h = 0; h < 4; h++) {
#pragma unroll
      for (int dh = 0; dh < 2; dh++) {
        const int j = 2 * h + dh;
        const float2 c2 = cs[j];
        qa[h][2 * dh] = packbf(fmaf(-mean0, c2.x, acc[4 * j + 0]), fmaf(-mean0, c2.y, acc[4 * j + 1]));
        qa[h][2 * dh + 1] = packbf(fmaf(-mean1, c2.x, acc[4 * j + 2]), fmaf(-mean1, c2.y, acc[4 * j + 3]));
      }
    }
  }
  bar_sync(2 + wg, 128);
  TSW(2);
  {
    const uint32_t prev_base = kvx + (16 * w - 16) * 256;
    const int mi = lane >> 3;
    const int r = 8 * (mi >> 1) + (lane & 7), r2 = 8 * (mi & 1) + (lane & 7);
    if (w != 0) {
#pragma unroll
      for (int h = 0; h < 4; h++) {
        const int ch = 4 * h + (mi & 1), ch2 = 4 * h + 2 + (mi >> 1);
        ldsm4(&kb[h][0], prev_base + r * 256 + (((ch & 8) | ((ch ^ r) & 7)) << 4));
        ldsm4t(&vb[h][0], prev_base + r2 * 256 + (((ch2 & 8) | ((ch2 ^ r2) & 7)) << 4));
      }
    } else if (blk > 0) {
      uint4* src = &g_halo[((blk - 1) * 8 + hg) * 256 + lane];
      uint4 hv[8];
      int it = 0;
      bool ok;
      do {
        ok = true;
#pragma unroll
        for (int i = 0; i < 8; i++) hv[i] = ld_tagged(src + i * 32);
#pragma unroll
        for (int i = 0; i < 8; i++) ok = ok && hv[i].x != UNSET;
      } while (!__all_sync(~0u, ok) && ++it < (1 << 20));
      if (layer == 0) {
#pragma unroll
        for (int i = 0; i < 2; i++) stg128(src + i * 128 + (lane >> 1) * 6, make_uint4(UNSET, UNSET, UNSET, UNSET));
      }
#pragma unroll
      for (int h = 0; h < 4; h++) {
        kb[h][0] = hv[2 * h].x; kb[h][1] = hv[2 * h].y; kb[h][2] = hv[2 * h].z; kb[h][3] = hv[2 * h].w;
        vb[h][0] = movm_t(hv[2 * h + 1].x); vb[h][1] = movm_t(hv[2 * h + 1].y);
        vb[h][2] = movm_t(hv[2 * h + 1].z); vb[h][3] = movm_t(hv[2 * h + 1].w);
      }
    } else {
#pragma unroll
      for (int h = 0; h < 4; h++)
#pragma unroll
        for (int k = 0; k < 4; k++) kb[h][k] = vb[h][k] = 0u;
    }
    TSW(3);
  }
  mbar_wait(bar + 8 * (B_DN + 15), layer);
  TSW(4);

  const bool first = (blk == 0 && w == 0);
  const int e = t - (g >> 1);
  const bool par = g & 1, epos = e >= 1;
  const uint32_t pmask = par ? 0xffff0000u : 0x0000ffffu;
  const uint32_t mB0 = epos ? pmask : 0u, mB1 = epos ? 0u : pmask;
  const float cl2 = 0.25f * 1.4426950408889634f;
  const float sc0 = rstd0 * cl2, sc1 = rstd1 * cl2;
  const float NEG = -INFINITY;
  float vA0[4], vB0[4], vA1[4], vB1[4];
#pragma unroll
  for (int h = 0; h < 4; h++) {
    float S[4][4];
#pragma unroll
    for (int j = 0; j < 4; j++) {
      S[j][0] = S[j][1] = S[j][2] = S[j][3] = 0.f;
      mma_bf16(S[j], qa[h], kb[h][2 * j], kb[h][2 * j + 1]);
    }
    vA0[h] = par ? S[1][1] : S[1][0];
    vB0[h] = epos ? (par ? S[0][1] : S[0][0]) : (par ? S[2][1] : S[2][0]);
    vA1[h] = par ? S[2][3] : S[2][2];
    vB1[h] = epos ? (par ? S[1][3] : S[1][2]) : (par ? S[3][3] : S[3][2]);
    if (first) { vA0[h] = NEG; if (epos) { vB0[h] = NEG; vB1[h] = NEG; } }
  }
  float m0[4], m1[4];
#pragma unroll
  for (int h = 0; h < 4; h++) { m0[h] = fmaxf(vA0[h], vB0[h]); m1[h] = fmaxf(vA1[h], vB1[h]); }
#pragma unroll
  for (int o = 1; o <= 2; o <<= 1) {
#pragma unroll
    for (int h = 0; h < 4; h++) {
      m0[h] = fmaxf(m0[h], __shfl_xor_sync(~0u, m0[h], o));
      m1[h] = fmaxf(m1[h], __shfl_xor_sync(~0u, m1[h], o));
    }
  }
  float O0[4][4], O1[4][4], Z[4][4];
#pragma unroll
  for (int h = 0; h < 4; h++) {
    const float mm0 = -m0[h] * sc0, mm1 = -m1[h] * sc1;
    const float pA0 = ex2(fmaf(vA0[h], sc0, mm0)), pB0 = ex2(fmaf(vB0[h], sc0, mm0));
    const float pA1 = ex2(fmaf(vA1[h], sc1, mm1)), pB1 = ex2(fmaf(vB1[h], sc1, mm1));
    const uint32_t hA0 = packbf(pA0, pA0), hB0 = packbf(pB0, pB0), hA1 = packbf(pA1, pA1), hB1 = packbf(pB1, pB1);
    const uint32_t P0[4] = {hB0 & mB0, 0u, hA0 & pmask, hB1 & mB0};
    const uint32_t P1[4] = {hB0 & mB1, hA1 & pmask, 0u, hB1 & mB1};
#pragma unroll
    for (int k = 0; k < 4; k++) O0[h][k] = O1[h][k] = Z[h][k] = 0.f;
    mma_bf16(O0[h], P0, vb[h][0], vb[h][1]); mma_bf16(O1[h], P0, vb[h][2], vb[h][3]); mma_bf16(Z[h], P0, 0x3f803f80u, 0x3f803f80u);
    mma_bf16(O0[h], P1, vb[h][4], vb[h][5]); mma_bf16(O1[h], P1, vb[h][6], vb[h][7]); mma_bf16(Z[h], P1, 0x3f803f80u, 0x3f803f80u);
  }
  if (lane == 0) mbar_arrive(bar + 8 * (B_OST + wg));
  uint4* op = (uint4*)g_O + ((layer * 32 + blk) * 8 + hg) * 512 + 64 * t + 16 * w + g;
#pragma unroll
  for (int h = 0; h < 4; h += 2) {
    const float i0 = rcp_approx(Z[h][0]), i1 = rcp_approx(Z[h][2]), j0 = rcp_approx(Z[h + 1][0]), j1 = rcp_approx(Z[h + 1][2]);
    stg128(op + 128 * h, make_uint4(packbf(O0[h][0] * i0, O0[h][1] * i0), packbf(O1[h][0] * i0, O1[h][1] * i0),
                                   packbf(O0[h + 1][0] * j0, O0[h + 1][1] * j0), packbf(O1[h + 1][0] * j0, O1[h + 1][1] * j0)));
    stg128(op + 128 * h + 8, make_uint4(packbf(O0[h][2] * i1, O0[h][3] * i1), packbf(O1[h][2] * i1, O1[h][3] * i1),
                                            packbf(O0[h + 1][2] * j1, O0[h + 1][3] * j1), packbf(O1[h + 1][2] * j1, O1[h + 1][3] * j1)));
  }
  TSW(5);
  __syncwarp();
  if (lane == 0) red_relaxed(&g_cnt[(C_O + layer * 32 + blk) * 32]);
  TSW(6);
}

#define PDELAY 0
#define PGATE 1
__device__ __forceinline__ void proj_phase(const Params& p, uint32_t sb, int layer, int rb, int q, int wg, int w, int& rtp) {
  const int lane = opaque_tid() & 31;
  const bool TR = layer != 0;
  const int t = lane & 3;
  const uint32_t bar = sb + SM_BAR;
  const uint32_t rbx = sb + (P_R + wg) * PG;
  const uint32_t rsrc = sb + (wg ? 2 : P_R) * PG;
  const int blk = 16 * wg + rb;
  uint32_t res[16];
  mbar_wait(bar + 8 * (B_RF + wg), layer);
  if (!TR) {
#pragma unroll
    for (int j = 0; j < 8; j += 2) {
      const int mi = lane >> 3;
      const int row = 16 * w + (lane & 7) + 8 * (mi & 1), ch = j + (mi >> 1);
      ldsm4(&res[2 * j], rsrc + row * 128 + ((ch ^ (row & 7)) << 4));
    }
  } else {
#pragma unroll
    for (int j = 0; j < 8; j += 2) {
      const int mi = lane >> 3;
      const int line = 8 * (j + (mi >> 1)) + (lane & 7), pc = 2 * w + (mi & 1);
      ldsm4t(&res[2 * j], rsrc + line * 128 + ((pc ^ (line & 7)) << 4));
    }
  }
  if (layer) mbar_wait(bar + 8 * B_RS, 0);
  mbar_wait(bar + 8 * B_WOF, layer);
  fence_async_global();
  const uint32_t stg = sb + (wg ? SM_KGT : SM_STG);
  if (wg) mbar_wait(bar + 8 * B_PST, layer);
  bool clean = false;
#pragma unroll 1
  for (int attempt = 0; attempt < MAX_RETRY; attempt++) {
  float acc[32];
#pragma unroll
  for (int j = 0; j < 16; j++) { acc[2 * j] = bf_lo(res[j]); acc[2 * j + 1] = bf_hi(res[j]); }
  acc_fence<32>(acc);
#pragma unroll
  for (int c = 0; c < 4; c++) {
    mbar_wait(bar + 8 * (B_OF + 4 * wg + c), layer);
    if (c == 0) TSW(7);
    const uint64_t da = mkdesc(sb + o_page(wg, c) * PG, 1024, 128, 0);
    wg_fence();
#pragma unroll
    for (int ks = 0; ks < 8; ks++)
      wgmma_ss<64, 0, 1>(acc, da + ks * 128, mkdesc(sb + wo_page(2 * c + (ks >> 2)) * PG, 8192, 1024, 1) + (ks & 3) * 128, 1);
    wg_commit();
  }
  if (wg) mbar_wait(bar + 8 * B_KG, 0);
  wg_wait<0>();
  acc_fence<32>(acc);
  TSW(8);
  if (!clean) {
    const float chk = acc[0] + acc[2];
    clean = __all_sync(~0u, chk == chk);
    if (clean && lane == 0) mbar_arrive(bar + 8 * (B_PDONE + wg));
  }
  float s0 = 0.f, q0 = 0.f, s1 = 0.f, q1 = 0.f;
  uint32_t o[16];
#pragma unroll
  for (int j = 0; j < 8; j++) {
    const float a = acc[4 * j], b = acc[4 * j + 1], c = acc[4 * j + 2], d = acc[4 * j + 3];
    o[2 * j] = packbf(a, b);
    o[2 * j + 1] = packbf(c, d);
    s0 += a + b; q0 = fmaf(a, a, q0); q0 = fmaf(b, b, q0);
    s1 += c + d; q1 = fmaf(c, c, q1); q1 = fmaf(d, d, q1);
  }
#pragma unroll
  for (int j = 0; j < 8; j += 2) {
    const int mi = lane >> 3;
    const int line = 8 * (j + (mi >> 1)) + (lane & 7), pc = 2 * w + (mi & 1);
    stsm4t(rbx + line * 128 + ((pc ^ (line & 7)) << 4), o[2 * j], o[2 * j + 1], o[2 * j + 2], o[2 * j + 3]);
  }
#pragma unroll
  for (int o2 = 1; o2 <= 2; o2 <<= 1) {
    s0 += __shfl_xor_sync(~0u, s0, o2); q0 += __shfl_xor_sync(~0u, q0, o2);
    s1 += __shfl_xor_sync(~0u, s1, o2); q1 += __shfl_xor_sync(~0u, q1, o2);
  }
  {
    const int i = 2 * (lane >> 2) + (t & 1), k = (i * 11) >> 5;
    const float v = (t == 0) ? s0 : (t == 1) ? q0 : (t == 2) ? s1 : q1;
    sts32f(stg + k * 128 + (2 * w + (t >> 1)) * 16 + (i - 3 * k) * 4, v);
  }
  TSW(9);
  fence_async_smem();
  if (!bar_or(2 + wg, 128, !clean)) break;
  bool unset = false;
#pragma unroll
  for (int i = 0; i < 4; i++) unset |= lds32(sb + o_page(wg, i) * PG + (32 * w + lane) * 128) == UNSET;
  if (!bar_or(2 + wg, 128, unset)) break;
  if (w == 0 && elect_one()) {
    fence_async_smem();
    mbar_expect(bar + 8 * (B_RT + wg), 8 * PG);
#pragma unroll 1
    for (int c = 0; c < 4; c++) bulk_ld(sb + o_page(wg, c) * PG, g_O + ((layer * 32 + blk) * 4 + c) * PG, 2 * PG, bar + 8 * (B_RT + wg));
  }
  mbar_wait(bar + 8 * (B_RT + wg), rtp);
  rtp ^= 1;
  RETRY(0);
  }
  if (!clean && lane == 0) mbar_arrive(bar + 8 * (B_PDONE + wg));
  if (w == 0 && elect_one()) {
    tma_st(&p.mapXT, blk * 64, (2 * layer) * DM + q * 64, rbx);
    bulk_red_add_f32(g_stats + (layer * 32 + blk) * 192, stg, 768);
    bulk_commit();
    red_relaxed(&g_cnt[(C_G + 2 * layer + wg) * 32]);
  }
  TSW(10);
}

__device__ __forceinline__ void conv_load(uint32_t* A, uint32_t pe) {
#pragma unroll
  for (int m = 0; m < 17; m++) {
    A[4 * m + 2] = lds32(pe + 4 * (64 * m - 8));
    A[4 * m + 0] = lds32(pe + 4 * (64 * m));
    A[4 * m + 1] = lds32(pe + 4 * (64 * m + 8));
    asm volatile("mov.b32 %0, %1;" : "=r"(A[4 * m + 3]) : "r"(A[4 * m + 0]));
  }
}
template <int M> __device__ __forceinline__ void conv_tri(float* acc, const uint32_t* A, uint64_t d) {
  if constexpr (M < 16) {
    wgmma_rs<64 - 8 * (M / 2), 0>(acc, A + 4 * M, d + (uint64_t)(64 + 4 * M), M != 0);
    conv_tri<M + 1>(acc, A, d);
  }
}
__device__ __forceinline__ void conv_mma0(float* acc, const uint32_t* A, uint64_t d) {
  wg_fence();
  conv_tri<0>(acc, A, d);
  wg_commit();
}
__device__ __forceinline__ void conv_mma1(float* acc, const uint32_t* A, uint64_t d, uint64_t ds, uint64_t df) {
  wg_fence();
#pragma unroll
  for (int m = 0; m < 17; m++) wgmma_rs<64, 0>(acc, A + 4 * m, d + (uint64_t)(4 * m), m != 0);
  wgmma_ss<64, 1, 0>(acc, ds, df, 1);
  wgmma_ss<64, 1, 0>(acc, ds + 128, df + 128, 1);
  wg_commit();
}
__device__ __forceinline__ void conv_store(float* acc, uint32_t pb, uint32_t over, int w) {
  acc_fence<32>(acc);
  const int l = opaque_tid() & 31, mt = l >> 3;
  int c = 2 * (63 - 8 * (mt >> 1) - (l & 7) + w) + (mt & 1);
  c ^= (c >> 3) & 1;
  const uint32_t a0 = pb + c * 16;
#pragma unroll
  for (int j = 0; j < 8; j += 2)
    stsm4t(j == 0 ? (c < 128 ? a0 : over + (c - 128) * 16) : a0 - 256 * j, packbf(acc[4 * j], acc[4 * j + 1]), packbf(acc[4 * j + 2], acc[4 * j + 3]),
           packbf(acc[4 * j + 4], acc[4 * j + 5]), packbf(acc[4 * j + 6], acc[4 * j + 7]));
}
__device__ __forceinline__ void conv_sums(uint32_t sb, int lc, int ht) {
  const int m = ht - 1;
  uint4 v[2][3];
#pragma unroll
  for (int c = 0; c < 2; c++)
#pragma unroll
    for (int k = 0; k < 3; k++) {
      const int mm = m - 1 + k;
      v[c][k] = lds128(sb + cv_u(lc + c) + (mm >= 0 ? (mm & 1) * CV_UH + (127 - (mm >> 1)) * 16 : 128 * 16));
    }
  const int ce = m + 2, co = m + 1;
#pragma unroll
  for (int c = 0; c < 2; c++) {
    const uint32_t x[8] = {v[c][0].z, v[c][0].w, v[c][1].x, v[c][1].y, v[c][1].z, v[c][1].w, v[c][2].x, v[c][2].y};
    float pv[16];
#pragma unroll
    for (int k = 0; k < 8; k++) { pv[2 * k] = bf_lo(x[k]); pv[2 * k + 1] = bf_hi(x[k]); }
    float t2[15], t4[13], s9[8], s7[8];
#pragma unroll
    for (int i = 0; i < 15; i++) t2[i] = pv[i] + pv[i + 1];
#pragma unroll
    for (int i = 0; i < 13; i++) t4[i] = t2[i] + t2[i + 2];
#pragma unroll
    for (int i = 0; i < 8; i++) {
      s9[i] = (t4[i] + t4[i + 4]) + pv[i + 8];
      s7[i] = (t4[i + 1] + t2[i + 5]) + pv[i + 7];
    }
    const uint4 e4 = make_uint4(packbf(s9[0], s9[1]), packbf(s9[2], s9[3]), packbf(s9[4], s9[5]), packbf(s9[6], s9[7]));
    if (ce < 128) sts128(sb + cv_se(lc + c) + ((ce ^ ((ce >> 3) & 7)) << 4), e4);
    else sts128(sb + cv_se(lc + c), make_uint4(0, 0, 0, 0));
    sts128(sb + cv_so(lc + c) + ((co ^ ((co >> 3) & 7)) << 4),
           make_uint4(packbf(s7[0], s7[1]), packbf(s7[2], s7[3]), packbf(s7[4], s7[5]), packbf(s7[6], s7[7])));
  }
}

template <int HALF, int NCH, int STEP = 1>
__device__ __forceinline__ void conv_epi(uint32_t sb, bf16* out, int lc, int c) {
  uint4 v[NCH][4], xr[NCH];
  const uint32_t sw = (c ^ ((c >> 3) & 1)) * 16;
#pragma unroll
  for (int u = 0; u < NCH; u++) {
#pragma unroll
    for (int k = 0; k < 4; k++) v[u][k] = lds128(sb + (HALF ? cv_pb1(lc + STEP * u, k) : cv_pb0(lc + STEP * u, k)) + sw);
    xr[u] = lds128(sb + cv_x(HALF, lc + STEP * u) + c * 16);
  }
#pragma unroll
  for (int u = 0; u < NCH; u++) {
    uint4 o;
    o.x = hadd2(xr[u].x, hadd2(hadd2(v[u][0].x, v[u][1].x), hadd2(v[u][2].x, v[u][3].x)));
    o.y = hadd2(xr[u].y, hadd2(hadd2(v[u][0].y, v[u][1].y), hadd2(v[u][2].y, v[u][3].y)));
    o.z = hadd2(xr[u].z, hadd2(hadd2(v[u][0].z, v[u][1].z), hadd2(v[u][2].z, v[u][3].z)));
    o.w = hadd2(xr[u].w, hadd2(hadd2(v[u][0].w, v[u][1].w), hadd2(v[u][2].w, v[u][3].w)));
    stg128(out + cv_chan(0, lc + STEP * u) * LSEQ + HALF * 1024 + c * 8, o);
  }
}

__device__ __forceinline__ bool prep_valid(const uint4 (&st)[6], const uint4 (&xr)[4]) {
  const uint32_t n = __float_as_uint(8.f);
  return st[0].w == n && st[1].w == n && st[2].w == n && st[3].w == n && st[4].w == n && (st[5].w | st[5].y | st[5].z) == n &&
         xr[0].x != UNSET && xr[1].x != UNSET && xr[2].x != UNSET && xr[3].x != UNSET;
}
template <int HALF>
__device__ __forceinline__ void conv_prep(uint32_t sb, int layer, int cta, int i) {
  uint4 st[6], xr[4];
  const uint4* sp = (const uint4*)g_stats + (layer * 32 + HALF * 16 + (i >> 3)) * 48 + (i & 7);
  const uint4* xp = (const uint4*)g_xT + (2 * layer * DM + 2 * cta) * (LSEQ / 8) + HALF * 128 + i;
  auto fetch = [&]() {
#pragma unroll
    for (int k = 0; k < 6; k++) st[k] = ld_tagged(sp + 8 * k);
#pragma unroll
    for (int k = 0; k < 4; k++) xr[k] = ld_tagged(xp + cv_chan(0, k) * (LSEQ / 8));
  };
  if (HALF) {
#pragma unroll
    for (int k = 0; k < 6; k++) st[k] = lds128(sb + CV_ST + (i >> 3) * 768 + k * 128 + (i & 7) * 16);
#pragma unroll
    for (int k = 0; k < 4; k++) xr[k] = lds128(sb + cv_x(1, k) + i * 16);
  } else {
    fetch();
  }
  int it = 0;
  while (!__all_sync(~0u, prep_valid(st, xr)) && ++it < MAX_RETRY) { fetch(); RETRY(1); }
  if (!HALF || it) {
#pragma unroll
    for (int k = 0; k < 4; k++) sts128(sb + cv_x(HALF, k) + i * 16, xr[k]);
  }
  const uint32_t v[16] = {st[0].x, st[0].y, st[0].z, st[1].x, st[1].y, st[1].z, st[2].x, st[2].y, st[2].z, st[3].x, st[3].y, st[3].z, st[4].x, st[4].y, st[4].z, st[5].x};
  uint32_t rs[4], nm[4];
#pragma unroll
  for (int k = 0; k < 4; k++) {
    const float m0 = __uint_as_float(v[4 * k]) * (-1.f / DM), m1 = __uint_as_float(v[4 * k + 2]) * (-1.f / DM);
    const float r0 = rsqrt_approx(fmaxf(fmaf(__uint_as_float(v[4 * k + 1]), 1.f / DM, -m0 * m0), 0.f) + 1e-5f);
    const float r1 = rsqrt_approx(fmaxf(fmaf(__uint_as_float(v[4 * k + 3]), 1.f / DM, -m1 * m1), 0.f) + 1e-5f);
    rs[k] = packbf(r0, r1);
    nm[k] = packbf(m0 * bf_lo(rs[k]), m1 * bf_hi(rs[k]));
  }
  const uint32_t ud = sb + (i & 1) * CV_UH + (127 - 64 * HALF - (i >> 1)) * 16;
#pragma unroll
  for (int k = 0; k < 4; k++)
    sts128(ud + cv_u(k), make_uint4(hfma2(xr[k].x, rs[0], nm[0]), hfma2(xr[k].y, rs[1], nm[1]), hfma2(xr[k].z, rs[2], nm[2]), hfma2(xr[k].w, rs[3], nm[3])));
  fence_async_smem();
}

#define AGATE 1
#define PP0 1
__device__ __forceinline__ void conv_phase(const Params& p, uint32_t sb, int layer, int cta) {
  const int tid = opaque_tid();
  const int wg = __shfl_sync(~0u, tid >> 7, 0), w = __shfl_sync(~0u, (tid >> 5) & 3, 0);
  const uint32_t bar = sb + SM_BAR;
  constexpr int CH2 = 4 * PG;
  bf16* xout = g_xT + ((2 * layer + 1) * DM + 2 * cta) * LSEQ;
  uint32_t A0[68], A1[68];
  float acc[32];
  const uint32_t pe = sb + cv_pe(wg) + 4 * (16 + 16 * w + ((tid & 31) >> 2) - 2 * (tid & 3));
  auto staged = [&]() {
    if (w == 0) {
      bulk_wait_read();
      __syncwarp();
      if (elect_one()) mbar_arrive(bar + 8 * (B_PST + wg));
    }
  };
  if (wg == 0) staged();
  mbar_wait(bar + 8 * (B_PDONE + 1), layer);
  mbar_wait(bar + 8 * B_PE, layer);
  conv_load(A0, pe);
  if (wg == 1) staged();
  conv_load(A1, pe + CH2);
  TSW(19);
  const uint64_t d0 = mkdesc(sb + cv_u(wg), CV_UH, 128, 0), d1 = d0 + (CH2 >> 4);
  mbar_wait(bar + 8 * B_U, layer);
  TSW(12);
  if (wg == 1) bar_sync(5, 256);
  conv_mma0(acc, A0, d0);
  if (wg == 0) bar_arrive(5, 256);
  mbar_wait(bar + 8 * (B_PDONE + 1), layer);
  {
    const int l = opaque_tid() & 31;
    if ((l & 15) < 2 * w) sts128(sb + cv_pb0(wg + 2 * (l >> 4), w) + (l & 15) * 16, make_uint4(0, 0, 0, 0));
  }
  wg_wait<0>();
  conv_store(acc, sb + cv_pb0(wg, w), sb + cv_pb1(wg, w), w);
  conv_mma0(acc, A1, d1);
  wg_wait<0>();
  conv_store(acc, sb + cv_pb0(2 + wg, w), sb + cv_pb1(2 + wg, w), w);
  TSW(13);
  bar_sync(2 + wg, 128);
  conv_epi<0, 2, 2>(sb, xout, wg, opaque_tid() & 127);
  TSW(14);
  mbar_arrive(bar + 8 * B_PUB);
  if (wg == 0) mbar_wait(bar + 8 * B_U1, layer);
  else bar_sync(6, 256);
  TSW(15);
  const uint64_t ds = mkdesc(sb + cv_se(wg), 8192, 1024, 1), df = mkdesc(sb + cv_fa(wg), 512, 128, 0);
  conv_mma1(acc, A0, d0, ds, df);
  if (wg == 0) bar_arrive(6, 256);
  wg_wait<0>();
  conv_store(acc, sb + cv_pb1(wg, w), sb + cv_dump(wg), w);
  mbar_arrive(bar + 8 * B_R);
  TSW(16);
  conv_mma1(acc, A1, d1, ds + 512, df + (CH2 >> 4));
  wg_wait<0>();
  conv_store(acc, sb + cv_pb1(2 + wg, w), sb + cv_dump(2 + wg), w);
  TSW(17);
  if (wg == 0) {
    mbar_arrive(bar + 8 * (B_R + 1));
  } else {
    bar_sync(3, 128);
    conv_epi<1, 1>(sb, xout, 3, opaque_tid() & 127);
    mbar_arrive(bar + 8 * (B_PUB + 2));
    TSW(18);
  }
}

__device__ __forceinline__ void final_phase(const Params& p, uint32_t sb, int cta, int wg, int w, int rtp) {
  const int lane = opaque_tid() & 31;
  const uint32_t bar = sb + SM_BAR;
  mbar_wait(bar + 8 * (B_TF + wg), 0);
  if (threadIdx.x == 128) TS(8);
  const uint32_t src = sb + (16 + wg) * PG, dst = src + 2 * PG;
  const int mi = lane >> 3;
#pragma unroll 1
  for (int attempt = 0; attempt < MAX_RETRY; attempt++) {
    uint32_t m = 0;
#pragma unroll
    for (int j = 0; j < 8; j += 2) {
      uint32_t r[4];
      const int line = 8 * (j + (mi >> 1)) + (lane & 7), pc = 2 * w + (mi & 1);
      ldsm4t(r, src + line * 128 + ((pc ^ (line & 7)) << 4));
      const int row = 16 * w + (lane & 7) + 8 * (mi & 1), ch = j + (mi >> 1);
      stsm4(dst + row * 128 + ((ch ^ (row & 7)) << 4), r[0], r[1], r[2], r[3]);
#pragma unroll
      for (int k = 0; k < 4; k++) asm("max.u16x2 %0, %0, %1;" : "+r"(m) : "r"(r[k]));
    }
    fence_async_smem();
    if (!bar_or(2 + wg, 128, m >= 0xffff0000u || (m & 0xffffu) == 0xffffu)) break;
    if (w == 0 && elect_one()) {
      mbar_expect(bar + 8 * (B_RT + wg), PG);
      tma_ld(src, &p.mapXT, (16 * wg + (cta & 15)) * 64, 3 * DM + (cta >> 4) * 64, bar + 8 * (B_RT + wg));
    }
    mbar_wait(bar + 8 * (B_RT + wg), (rtp + attempt) & 1);
    RETRY(2);
  }
  if (w == 0 && elect_one()) {
    tma_st(&p.mapOut, (cta >> 4) * 64, (16 * wg + (cta & 15)) * 64, dst);
    bulk_commit();
    asm volatile("cp.async.bulk.wait_group.read 0;" ::: "memory");
    if (threadIdx.x == 128) TS(9);
    if (threadIdx.x == 128) LTS(1);
  }
}

struct cplx { float r, i; };
__device__ __forceinline__ cplx cmul(cplx a, cplx b) { return {fmaf(a.r, b.r, -a.i * b.i), fmaf(a.r, b.i, a.i * b.r)}; }
__device__ __forceinline__ cplx csqr(cplx a) { return {fmaf(a.r, a.r, -a.i * a.i), (a.r + a.r) * a.i}; }
__device__ __forceinline__ cplx cexp_l(float ar2, float ai, float l) {
  const float m = ex2(ar2 * l);
  const float x = ai * l;
  return {m * __cosf(x), m * __sinf(x)};
}

__device__ __forceinline__ void colsum_cta(const Params& p, uint32_t sb, int j, int tid) {
  const uint32_t bar = sb + SM_BAR;
  auto ld = [&](int i) {
    mbar_expect(bar + 8 * i, 3 * PG);
    tma_ld3(sb + (i & 7) * 3 * PG, &p.mapW3, (2 * j + (i & 1)) * 64, (i >> 1) * 64, 0, bar + 8 * i);
  };
  if (tid == 384) {
#pragma unroll
    for (int i = 0; i < 24; i++) mbar_init(bar + 8 * i, i < 16 ? 1 : 12);
    asm volatile("fence.mbarrier_init.release.cluster;" ::: "memory");
    fence_async_smem();
#pragma unroll 1
    for (int i = 0; i < 8; i++) ld(i);
  }
  const unsigned ep = ld_relaxed(&g_cnt[C_CS * 32]);
  bar_sync(0, NTHREADS);
  if (tid == 384) {
#pragma unroll 1
    for (int i = 8; i < 16; i++) { mbar_wait(bar + 8 * (8 + i), 0); fence_async_smem(); ld(i); }
  }
  if (tid < 384) {
    const int lane = tid & 31, cc = tid & 7, r0 = (tid >> 3) & 15, part = tid >> 7;
    const uint32_t id = ((lane >> 2) == 2 * (lane & 3) ? 0x3f80u : 0u) | ((lane >> 2) == 2 * (lane & 3) + 1 ? 0x3f800000u : 0u);
    const uint32_t src = sb + part * PG + r0 * 128 + ((cc ^ (r0 & 7)) << 4);
    float s[2][2][4];
#pragma unroll
    for (int i = 0; i < 16; i++) s[i >> 3][(i >> 2) & 1][i & 3] = 0.f;
#pragma unroll 1
    for (int i2 = 0; i2 < 16; i2 += 2) {
#pragma unroll
      for (int h = 0; h < 2; h++) {
        const int i = i2 + h;
        mbar_wait(bar + 8 * i, 0);
        uint4 v[4];
#pragma unroll
        for (int k = 0; k < 4; k++) v[k] = lds128(src + (i & 7) * 3 * PG + k * 2048);
#pragma unroll
        for (int k = 0; k < 4; k++) {
          const uint32_t a[4] = {v[k].x, v[k].y, v[k].z, v[k].w};
          mma_bf16(s[h][0], a, id, 0u);
          mma_bf16(s[h][1], a, 0u, id);
        }
        __syncwarp();
        if (i < 8 && lane == 0) mbar_arrive(bar + 8 * (16 + i));
      }
    }
    const uint32_t red = sb + 24 * PG;
#pragma unroll
    for (int h = 0; h < 2; h++)
#pragma unroll
      for (int k = 0; k < 2; k++) sts128f(red + (r0 * 384 + h * 192 + part * 64 + cc * 8 + k * 4) * 4, s[h][k][0], s[h][k][1], s[h][k][2], s[h][k][3]);
    bar_sync(1, 384);
    float tot = 0.f;
#pragma unroll
    for (int k = 0; k < 16; k++) tot += __uint_as_float(lds32(red + (k * 384 + tid) * 4));
    asm volatile("st.relaxed.gpu.global.v2.u32 [%0], {%1,%2};" ::"l"(&g_colsum[j * 384 + tid]), "r"(__float_as_uint(tot)), "r"(ep / NCTA + 1) : "memory");
    const uint4 u = make_uint4(UNSET, UNSET, UNSET, UNSET);
    if (tid < 256) {
#pragma unroll 1
      for (int s = 0; s < 4; s++) {
        const int n = s ? 32 : 16;
        uint4* dst = (s == 1 ? (uint4*)g_O + 131072 : (uint4*)g_xT + (s + !s) * 131072) + j * n * 1024 + (tid >> 1) * 8 + (tid & 1);
#pragma unroll 4
        for (int i = 0; i < n; i++) stg128(dst + i * 1024, u);
        bar_sync(2, 256);
        if (tid == 32 * s) red_release(&g_cnt[(C_R + s) * 32]);
      }
    }
  }
}

#define KW 3
struct ModeIn { uint32_t ar, ai, br, bi, cr, ci; bf16 logdt; };
__device__ __forceinline__ ModeIn load_modes(const Params& p, int d, int m) {
  const int i = d * 64 + m;
  return {((const uint32_t*)p.a_re)[i], ((const uint32_t*)p.a_im)[i], ((const uint32_t*)p.b_re)[i], ((const uint32_t*)p.b_im)[i],
          ((const uint32_t*)p.c_re)[i], ((const uint32_t*)p.c_im)[i], p.log_dt[d]};
}
__device__ __forceinline__ float4 lds128f_nv(uint32_t a) { float4 v; asm("ld.shared.v4.f32 {%0,%1,%2,%3}, [%4];" : "=f"(v.x), "=f"(v.y), "=f"(v.z), "=f"(v.w) : "r"(a)); return v; }
__device__ __forceinline__ void kernel_gen(const Params& p, uint32_t sb, int cta, int ht, ModeIn in, const ModeIn& in1) {
  const uint32_t bst = sb + SM_KGB + ((ht & 63) >> 2) * 144 + (ht & 3) * 4 + (ht >> 6) * 16;
  const uint64_t db = mkdesc(sb + SM_KGB, 144, 2304, 0);
  const float e0 = (float)(8 * (((ht & 32) >> 1) + ((ht & 31) >> 2)));
  float T[20];
#pragma unroll
  for (int i = 0; i < 20; i++) T[i] = 0.f;
  float k0 = (ht & 63) ? 0.f : __bfloat162float(p.dskip[cv_chan(cta, ht >> 6)]);
#pragma unroll 1
  for (int pass = 0; pass < 4; pass++) {
    {
      const int sh = (pass & 1) ? 0 : 16;
      auto val = [&](uint32_t v) { return __uint_as_float((v << sh) & 0xffff0000u); };
      const float dt = __bfloat162float(__float2bfloat16_rn(expf(__bfloat162float(in.logdt))));
      const float ar2 = dt * val(in.ar) * 1.4426950408889634f, ai = dt * val(in.ai);
      const cplx c = cmul({val(in.cr), -val(in.ci)}, {dt * val(in.br), -dt * val(in.bi)});
      k0 += c.r;
      const cplx z1 = cexp_l(ar2, -ai, 1.f), z256 = cexp_l(ar2, -ai, 256.f), z64 = cexp_l(ar2, ai, 64.f);
      const cplx z2 = csqr(z1), z512 = csqr(z256);
      auto put = [&](int j, cplx v) { sts32(bst + (j >> 2) * 2304 + (j & 3) * 32, packbf(v.r, v.i)); };
      sts128f(sb + SM_KGT + ht * 16, ar2, ai, z64.r, z64.i);
      const cplx c1 = cmul(c, z1), c2 = cmul(c, z2), c3 = cmul(c1, z2), c4 = cmul(c2, z2);
      const cplx c5 = cmul(c3, z2), c6 = cmul(c4, z2), c7 = cmul(c5, z2), c8 = cmul(c6, z2);
      put(0, c1); put(1, c2); put(2, c3); put(3, c4); put(4, c5); put(5, c6); put(6, c7); put(7, c8);
      const cplx c260 = cmul(c4, z256), c264 = cmul(c8, z256), c520 = cmul(c8, z512), c776 = cmul(c264, z512);
      put(8, cmul(c2, z256)); put(9, c260); put(10, cmul(c6, z256)); put(11, c264);
      put(12, cmul(c4, z512)); put(13, c520); put(14, cmul(c260, z512)); put(15, c776);
      const cplx c1032 = cmul(c520, z512), c1288 = cmul(c776, z512);
      put(16, c1032); put(17, c1288); put(18, cmul(c1032, z512)); put(19, cmul(c1288, z512));
    }
    fence_async_smem();
    bar_sync(4, 128);
    uint32_t tb = sb + SM_KGT + (ht & 67) * 16;
    asm volatile("mov.u32 %0, %0;" : "+r"(tb) :: "memory");
#pragma unroll
    for (int q = 0; q < 4; q++) {
      uint32_t A[8];
      if (q >= KW) wg_wait<KW - 1>();
#pragma unroll
      for (int s = 0; s < 4; s++) {
        const float4 v = lds128f_nv(tb + (4 * q + s) * 64);
        const cplx lo = cexp_l(v.x, v.y, e0), hi = cmul(lo, {v.z, v.w});
        A[2 * s] = packbf(lo.r, lo.i);
        A[2 * s + 1] = packbf(hi.r, hi.i);
      }
      wg_fence();
      wgmma_rs<40, 0>(T, A, db + 36 * q, (pass & 1) | q);
      wgmma_rs<40, 0>(T, A + 4, db + 36 * q + 18, 1);
      wg_commit();
    }
    wg_wait<0>();
    acc_fence<20>(T);
    if (ht == 0) TS(4 + pass);
    if (pass & 1) {
      const int h2 = opaque_tid() - 256, w = h2 >> 5, lane = h2 & 31, t = lane & 3, chn = h2 >> 6, m = h2 & 63, i0 = 16 * (w & 1) + (lane >> 2);
      const int lc = (pass & 2) + chn;
      const uint32_t kc = sb + kc_off(lc);
      auto put = [&](int idx, float v) {
        sts16(kc + idx * 2, __bfloat16_as_ushort(__float2bfloat16_rn(v)));
      };
#pragma unroll
      for (int hi = 0; hi < 2; hi++) {
        const int i = i0 + 8 * hi;
        float v[5];
#pragma unroll
        for (int j = 0; j < 5; j++) v[j] = chn ? T[4 * j + 2 * hi + 1] : T[4 * j + 2 * hi];
        put(8 * i + 1 + t, v[0]);
        put(8 * i + 5 + t, v[1]);
        put(257 + 4 * i + t, v[2]);
        put(385 + 2 * i + (t & 1) + 64 * (t >> 1), v[3]);
        put(513 + i + 32 * t, v[4]);
      }
#pragma unroll
      for (int o = 16; o > 0; o >>= 1) k0 += __shfl_xor_sync(~0u, k0, o);
      if (lane == 0) sts32f(sb + SM_RED + 4 * w, k0);
      bar_sync(4, 128);
      if (m == 0) put(0, k0 + __uint_as_float(lds32(sb + SM_RED + 4 * w + 4)));
      k0 = m ? 0.f : __bfloat162float(p.dskip[cv_chan(cta, 2 + chn)]);
      in = in1;
    }
  }
}

__device__ __forceinline__ void expand_taps(uint32_t sb, int ht) {
  const int ch = ht >> 5, lane = ht & 31;
  const uint32_t kc = sb + kc_off(ch);
  const uint32_t dst0 = sb + cv_pe(ch);
  auto put = [&](int G, uint32_t v0, uint32_t v1, uint32_t v2, uint32_t v3, uint32_t v4, uint32_t v5, uint32_t v6, uint32_t v7, uint32_t v8) {
    const uint32_t dst = dst0 + G * 32;
    sts128(dst, make_uint4(v1 | (v0 << 16), v2 | (v1 << 16), v3 | (v2 << 16), v4 | (v3 << 16)));
    sts128(dst + 16, make_uint4(v5 | (v4 << 16), v6 | (v5 << 16), v7 | (v6 << 16), v8 | (v7 << 16)));
  };
  {
    const uint4 q = lds128(kc + lane * 16);
    const uint32_t pv = lane ? lds16(kc + lane * 16 - 2) : 0u;
    const uint32_t dst = dst0 + (lane + 2) * 32;
    sts128(dst, make_uint4(__byte_perm(q.x, pv, 0x5410), __byte_perm(q.x, q.x, 0x1032), __byte_perm(q.y, q.x, 0x7610), __byte_perm(q.y, q.y, 0x1032)));
    sts128(dst + 16, make_uint4(__byte_perm(q.z, q.y, 0x7610), __byte_perm(q.z, q.z, 0x1032), __byte_perm(q.w, q.z, 0x7610), __byte_perm(q.w, q.w, 0x1032)));
    if (lane < 4) sts128(dst0 + lane * 16, make_uint4(0, 0, 0, 0));
  }
  uint32_t a[5], b[2][3];
  {
    const uint32_t s1 = kc + 2 * (256 + 4 * lane);
#pragma unroll
    for (int k = 0; k < 5; k++) a[k] = lds16(s1 + 2 * k);
#pragma unroll
    for (int u = 0; u < 2; u++) {
      const uint32_t s2 = kc + 2 * (384 + 2 * (lane + 32 * u));
#pragma unroll
      for (int k = 0; k < 3; k++) b[u][k] = lds16(s2 + 2 * k);
    }
  }
  const uint32_t k255 = lds16(kc + 2 * 255), k1024 = lds16(kc + 2 * 512);
  put(34 + lane, lane == 0 ? k255 : a[0], a[0], a[0], a[1], a[2], a[2], a[2], a[3], a[4]);
#pragma unroll
  for (int u = 0; u < 2; u++) put(66 + lane + 32 * u, b[u][0], b[u][0], b[u][0], b[u][0], b[u][1], b[u][1], b[u][1], b[u][2], b[u][2]);
  if (lane < 10) {
    const uint32_t v = lane == 0 ? k1024 : 0u;
    put(130 + lane, v, v, v, v, v, v, 0u, 0u, 0u);
  }
}
__device__ __forceinline__ void expand_far(uint32_t sb, int ht) {
  const int ch = ht >> 5, lane = ht & 31;
  const uint32_t kc = sb + kc_off(ch) + 2 * (513 + 2 * (63 - lane)), dst = sb + cv_fa(ch) + lane * 16;
#pragma unroll
  for (int ty = 0; ty < 2; ty++) {
    uint32_t v[16];
#pragma unroll
    for (int k = 0; k < 16; k++) v[k] = (k < 8 || 63 - lane - 4 * k >= 0) ? lds16(kc + 2 * (1 - ty) - 16 * k) : 0u;
#pragma unroll
    for (int u = 0; u < 2; u++)
      sts128(dst + ty * 2048 + u * 512, make_uint4(v[8 * u] | (v[8 * u + 1] << 16), v[8 * u + 2] | (v[8 * u + 3] << 16), v[8 * u + 4] | (v[8 * u + 5] << 16), v[8 * u + 6] | (v[8 * u + 7] << 16)));
    sts128(dst + ty * 2048 + 1024, make_uint4(0, 0, 0, 0));
  }
}

#define FIRST 0
#define WPRE 1
__host__ __device__ constexpr int bar_count(int i) {
  return i == B_END ? 3 : i == B_LN ? 2 : i < B_OST ? 1 : i < B_PE ? 4 : (i == B_PUB || i == B_PUB + 2 || i == B_R) ? 256 : 128;
}
__host__ __device__ constexpr bool bar_first(int i) { return i < B_WF + 2 && (i & 7) < 2; }

__global__ void __launch_bounds__(NTHREADS, 1) fused_kernel(const __grid_constant__ Params p) {
  extern __shared__ __align__(1024) uint8_t smem[];
  const uint32_t sb = s32(smem);
  const int tid = threadIdx.x, lane = tid & 31;
  const int warp = __shfl_sync(~0u, tid >> 5, 0);
  const int cta = blockIdx.x - p.first;
  if ((unsigned)cta >= NCTA) {
    colsum_cta(p, sb, blockIdx.x & 3, tid);
    return;
  }
  const int rb = ((cta >> 4) & 3) * 4 + ((cta >> 2) & 3), hg = (cta >> 6) * 4 + (cta & 3);
  const uint32_t bar = sb + SM_BAR;
  auto ld_x0 = [&](int half, int c) {
    const uint32_t b = bar + 8 * (B_XF + 8 * half + c);
    mbar_expect(b, PG);
    tma_ld(sb + x_page(half, c) * PG, &p.mapX, c * 64, (16 * half + rb) * 64, b);
  };
  auto ld_x1 = [&](int half, int c, int b0) {
    const uint32_t b = bar + 8 * b0;
    mbar_expect(b, PG);
    tma_ld(sb + (8 * half + c) * PG, &p.mapXT, (16 * half + rb) * 64, DM + c * 64, b);
  };
  auto ld_w = [&](int c) {
    const uint32_t b = bar + 8 * (B_WF + c);
    mbar_expect(b, 3 * PG);
    tma_ld3(sb + w_page(c) * PG, &p.mapW3, hg * 64, c * 64, 0, b);
  };

  if (tid == 0) TS(0);
  if (tid == 480) LTS(0);
  if (warp < 6 && elect_one()) {
    if (warp == 0) {
#pragma unroll
      for (int i = 0; i < B_WF + 2; i++)
        if (bar_first(i)) mbar_init(bar + 8 * i, 1);
      asm volatile("fence.mbarrier_init.release.cluster;" ::: "memory");
      fence_async_smem();
      ld_x0(0, 0); ld_w(0); ld_x0(1, 0);
      ld_x0(0, 1); ld_w(1); ld_x0(1, 1);
      TS(1);
    } else {
#pragma unroll
      for (int q = 0; q < 5; q++) {
        if (warp == q + 1) {
#pragma unroll
          for (int i = 0; i < B_COUNT; i++)
            if (!bar_first(i) && i % 5 == q) mbar_init(bar + 8 * i, bar_count(i));
        }
      }
      asm volatile("fence.mbarrier_init.release.cluster;" ::: "memory");
    }
  }

  if (warp < 8) {
    bar_sync(0, NTHREADS);
    asm volatile("setmaxnreg.inc.sync.aligned.u32 %0;" ::"n"(R_CONS));
    const int cw = __shfl_sync(~0u, opaque_tid() >> 5, 0);
    const int wg = cw >> 2, w = cw & 3;
    if (tid == 0) TS(2);
    int rtp = 0;
#pragma unroll 1
    for (int layer = 0; layer < 2; layer++) {
      attn_phase(p, sb, layer, rb, hg, wg, w);
      proj_phase(p, sb, layer, rb, hg, wg, w, rtp);
      conv_phase(p, sb, layer, cta);
    }
    final_phase(p, sb, cta, wg, w, rtp);
  } else if (warp < 12) {
    asm volatile("setmaxnreg.dec.sync.aligned.u32 %0;" ::"n"(R_HELP));
    const int ht = tid - 256;
    {
      unsigned ep0 = 0;
      if (ht == 0) ep0 = ld_relaxed(&g_cnt[C_CS * 32]);
      const ModeIn in0 = load_modes(p, cv_chan(cta, ht >> 6), ht & 63), in1 = load_modes(p, cv_chan(cta, 2 + (ht >> 6)), ht & 63);
      if (ht < 48) sts128f(sb + SM_STG + ht * 16, 0.f, 0.f, 0.f, 1.f);
      bar_sync(0, NTHREADS);
      if (ht == 0) {
        sts32(sb + SM_EP, ep0 / NCTA);
        mbar_arrive(bar + 8 * B_EP);
      }
      kernel_gen(p, sb, cta, ht, in0, in1);
      if (ht < 48) sts128f(sb + SM_KGT + ht * 16, 0.f, 0.f, 0.f, 1.f);
      fence_async_smem();
      bar_sync(4, 128);
      if (ht == 0) mbar_arrive(bar + 8 * B_KG);
    }
#pragma unroll 1
    for (int layer = 0; layer < 2; layer++) {
      bf16* xout = g_xT + ((2 * layer + 1) * DM + 2 * cta) * LSEQ;
      mbar_wait(bar + 8 * B_PDONE, layer);
      expand_taps(sb, opaque_tid() - 256);
      mbar_arrive(bar + 8 * B_PE);
      TSW(0);
      expand_far(sb, opaque_tid() - 256);
      {
        const int i = opaque_tid() - 256;
        if (i < 32) sts128(sb + cv_u(i >> 3) + ((i >> 2) & 1) * CV_UH + (128 + (i & 3)) * 16, make_uint4(0, 0, 0, 0));
        mbar_wait(bar + 8 * B_RC, layer);
        mbar_wait(bar + 8 * B_GB, layer);
        TSW(13);
        conv_prep<0>(sb, layer, cta, i);
        mbar_arrive(bar + 8 * B_U);
      }
      mbar_wait(bar + 8 * (B_PDONE + 1), layer);
      bar_sync(4, 128);
#pragma unroll 1
      for (int lc = 0; lc < 4; lc += 2) {
        conv_sums(sb, lc, opaque_tid() - 256);
        TSW(1 + lc);
      }
      mbar_wait(bar + 8 * (B_GB + 1), layer);
      conv_prep<1>(sb, layer, cta, opaque_tid() - 256);
      mbar_arrive(bar + 8 * B_U1);
      TSW(4);
      mbar_wait(bar + 8 * B_R, layer);
      conv_epi<1, 2>(sb, xout, 0, opaque_tid() - 256);
      mbar_arrive(bar + 8 * (B_PUB + 1));
      TSW(5);
      mbar_wait(bar + 8 * (B_R + 1), layer);
      conv_epi<1, 1>(sb, xout, 2, opaque_tid() - 256);
      mbar_arrive(bar + 8 * (B_PUB + 2));
      TSW(6);
      if (layer == 0) {
        const int c = __shfl_sync(~0u, (opaque_tid() >> 5) & 3, 0);
#pragma unroll 1
        for (int half = 0; half < 2; half++) {
          const uint32_t a = sb + (8 * half + c) * PG + lane * 128 + (lane & 7) * 16 + (lane >> 3) * 4;
#pragma unroll 1
          for (int it = 0; it < MAX_RETRY; it++) {
            mbar_wait(bar + 8 * (B_XR + 4 * half + c), it & 1);
            const uint32_t v0 = lds32(a), v1 = lds32(a + 4096);
            if (__all_sync(~0u, v0 != UNSET && v1 != UNSET)) break;
            if (elect_one()) { fence_async_smem(); ld_x1(half, c, B_XR + 4 * half + c); }
            __syncwarp();
            RETRY(3);
          }
          if (lane == 0) mbar_arrive(bar + 8 * (B_XF + 8 * half + c));
        }
      }
    }
  } else {
    asm volatile("setmaxnreg.dec.sync.aligned.u32 %0;" ::"n"(R_AGENT));
    bar_sync(0, NTHREADS);
    auto done = [&](int half, int c, int layer) { mbar_wait(bar + 8 * (B_DN + 8 * half + c), layer); };
    auto publish = [&](int layer, int k) {
      mbar_wait(bar + 8 * (B_PUB + k), layer);
      if (layer || k < 2) red_relaxed(&g_cnt[(layer ? C_F + 4 * k + (cta >> 5) : C_C + k) * 32]);
      if (!layer && k != 1) red_release(&g_cnt[(C_C + 3 - (k >> 1)) * 32]);
      TS(16 + layer * 56 + 40 + 7 + k);
    };
    if (warp == 12) {
      if (elect_one()) {
#pragma unroll 1
        for (int layer = 0; layer < 2; layer++) {
          auto ld_xe = [&](int c) {
            const uint32_t b = bar + 8 * (B_XF + c);
            mbar_expect(b, PG);
            if (layer == 0) tma_ld(sb + x_page(0, c) * PG, &p.mapX, c * 64, rb * 64, b);
            else tma_ld(sb + x_page(0, c) * PG, &p.mapXT, rb * 64, DM + c * 64, b);
          };
          if (layer == 0) {
            ld_x0(0, 2); ld_w(2); ld_x0(1, 2);
            if (hg >= 3) {
              mbar_expect(bar + 8 * B_SC, PG);
              tma_ld(sb + P_R * PG, &p.mapX, hg * 64, rb * 64, bar + 8 * B_SC);
            }
            if (rb < 4) tma_prefetch3(&p.mapW3, hg * 64, (4 + rb) * 64, 0);
            ld_x0(0, 3); ld_w(3); ld_x0(1, 3); ld_x0(0, 4); ld_x0(1, 4);
            done(0, 0, 0); done(1, 0, 0);
            ld_w(4);
            ld_x0(1, 5); ld_x0(1, 6); ld_x0(1, 7);
            done(0, 1, 0); done(1, 1, 0);
            ld_w(5);
            if (rb < 8) tma_prefetch5(&p.mapWo, hg * 64, rb * 2);
            done(0, 2, 0);
            fence_async_smem();
            ld_xe(5); ld_xe(6); ld_xe(7);
          } else {
            mbar_wait(bar + 8 * B_PDONE, 0);
            mbar_wait(bar + 8 * (B_PDONE + 1), 0);
            mbar_wait(bar + 8 * (WPRE == 1 ? B_U : B_GB + 1), 0);
            ld_w(0); ld_w(1);
            mbar_wait(bar + 8 * B_U1, 0);
            fence_async_smem();
            ld_w(2);
            mbar_wait(bar + 8 * (B_PUB + 2), 0);
            fence_async_smem();
            ld_w(3);
            spin_until(&g_cnt[(C_C + 3) * 32], (lds32(sb + SM_EP) + 1) * NCTA);
            fence_async_global();
            if (hg >= 3) {
              mbar_expect(bar + 8 * B_SC, PG);
              tma_ld(sb + P_R * PG, &p.mapXT, rb * 64, DM + hg * 64, bar + 8 * B_SC);
            }
            ld_xe(4);
            done(0, 2, 1);
            fence_async_smem();
            ld_xe(5); ld_xe(6); ld_xe(7);
            done(1, 0, 1);
            ld_w(4);
            done(1, 1, 1);
            ld_w(5);
          }
          done(1, 2, layer);
          fence_async_smem();
          ld_w(6); ld_w(7);
          auto ld_res = [&](int half) {
            const uint32_t b = bar + 8 * (B_RF + half);
            mbar_expect(b, PG);
            if (layer == 0) tma_ld(sb + (half ? 2 : P_R) * PG, &p.mapX, hg * 64, (16 * half + rb) * 64, b);
            else tma_ld(sb + (half ? 2 : P_R) * PG, &p.mapXT, (16 * half + rb) * 64, DM + hg * 64, b);
          };
          done(0, 4, layer); done(1, 3, layer);
          fence_async_smem();
          mbar_expect(bar + 8 * B_WOF, 8 * PG);
#pragma unroll 1
          for (int c = 0; c < 8; c++) {
            if (c == 5) { ld_res(0); done(1, 4, layer); }
            tma_ld5(sb + wo_page(c) * PG, &p.mapWo, hg * 64, c * 2, bar + 8 * B_WOF);
          }
          done(0, 7, layer);
          fence_async_global();
          ld_res(1);
        }
      }
    } else if (warp == 13) {
      mbar_wait(bar + 8 * B_EP, 0);
      const unsigned e1 = lds32(sb + SM_EP) + 1;
      auto ld_o = [&](int layer) {
#pragma unroll 1
        for (int half = 0; half < 2; half++) {
          done(1, 7, layer);
          mbar_wait(bar + 8 * B_OST, layer);
          if (half) mbar_wait(bar + 8 * (B_OST + 1), layer);
          fence_async_smem();
#pragma unroll
          for (int c = 0; c < 4; c++) mbar_expect(bar + 8 * (B_OF + 4 * half + c), 2 * PG);
          spin_until(&g_cnt[(C_O + layer * 32 + 16 * half + rb) * 32], e1 * 32);
#pragma unroll
          for (int c = 0; c < 4; c++)
            bulk_ld(sb + o_page(half, c) * PG, g_O + ((layer * 32 + 16 * half + rb) * 4 + c) * PG, 2 * PG, bar + 8 * (B_OF + 4 * half + c));
        }
      };
      if (elect_one()) {
        mbar_wait(bar + 8 * (B_WF + 2), 0);
        asm volatile("prefetch.tensormap [%0];" ::"l"(&p.mapXT) : "memory");
        asm volatile("prefetch.tensormap [%0];" ::"l"(&p.mapOut) : "memory");
        asm volatile("prefetch.tensormap [%0];" ::"l"(&p.mapWo) : "memory");
        spin_until(&g_cnt[C_Z * 32], e1 * NCTA);
        mbar_arrive(bar + 8 * B_ZF);
        TS(3);
        ld_o(0);
#pragma unroll 1
        for (int k = 0; k < 3; k++) {
          mbar_wait(bar + 8 * (B_PUB + k), 0);
          fence_async_smem();
          spin_until(&g_cnt[(C_C + k) * 32], e1 * NCTA);
          TS(10 + k);
          if (k == 2) fence_async_global();
#pragma unroll
          for (int c = 0; c < 4; c++) ld_x1(k != 0, (k & 2) * 2 + c, k < 2 ? B_XR + 4 * k + c : B_XF + 12 + c);
        }
        ld_o(1);
        mbar_wait(bar + 8 * B_PUB, 1);
#pragma unroll 1
        for (int half = 0; half < 2; half++) {
          mbar_expect(bar + 8 * (B_TF + half), PG);
          spin_until(&g_cnt[(C_F + 4 * (half ? 1 + (cta >> 6) : 0) + ((cta >> 4) & 3)) * 32], e1 * 32);
          tma_ld(sb + (16 + half) * PG, &p.mapXT, (16 * half + (cta & 15)) * 64, 3 * DM + (cta >> 4) * 64, bar + 8 * (B_TF + half));
        }
      }
    } else if (warp == 14) {
      mbar_wait(bar + 8 * B_EP, 0);
      const unsigned e1 = lds32(sb + SM_EP) + 1;
      done(0, 1, 0);
      {
        const uint2* cp = g_colsum + (hg * 192 + lane);
        uint2 v[6];
        bool ok;
        int it = 0;
        do {
          ok = true;
#pragma unroll
          for (int i = 0; i < 6; i++) {
            asm volatile("ld.relaxed.gpu.global.v2.u32 {%0,%1}, [%2];" : "=r"(v[i].x), "=r"(v[i].y) : "l"(cp + 32 * i) : "memory");
            ok = ok && v[i].y == e1;
          }
          if (++it > (1 << 22)) __trap();
        } while (!__all_sync(~0u, ok));
#pragma unroll
        for (int i = 0; i < 6; i++) sts32f(sb + SM_CS + 4 * (lane + 32 * i), __uint_as_float(v[i].x));
      }
      __syncwarp();
      if (elect_one()) {
        mbar_wait(bar + 8 * B_ZF, 0);
        mbar_arrive(bar + 8 * B_LN);
        red_relaxed(&g_cnt[C_CS * 32]);
        TS(13);
#pragma unroll 1
        for (int i = 0; i < 4; i++) {
          const int layer = i >> 1;
          mbar_wait(bar + 8 * (B_PST + (i & 1)), layer);
          const uint32_t b = bar + 8 * (B_GB + 1);
          const bf16* xin = g_xT + ((size_t)2 * layer * DM + 2 * cta) * LSEQ + 1024;
          if (i & 1) {
            fence_async_smem();
            mbar_expect(b, 12288 + PG);
          }
          spin_until(&g_cnt[(C_G + i) * 32], e1 * NCTA);
          if (i & 1) {
            bulk_ld(sb + CV_ST, g_stats + (layer * 32 + 16) * 192, 12288, b);
#pragma unroll
            for (int lc = 0; lc < 4; lc++) bulk_ld(sb + cv_x(1, lc), xin + cv_chan(0, lc) * LSEQ, 2048, b);
            TS(14 + layer);
            publish(layer, 1);
          } else {
            mbar_arrive(bar + 8 * B_GB);
          }
        }
      }
    } else {
      const uint4 u = make_uint4(UNSET, UNSET, UNSET, UNSET);
      if (lane < 24) stg128((uint4*)g_stats + cta * 24 + lane, make_uint4(0, 0, 0, 0));
      if (lane < 16) stg128(g_rows + LSEQ + cta * 16 + lane, make_uint4(0, 0, 0, 0));
#pragma unroll 4
      for (int i = 0; i < 16; i++) stg128(g_halo + cta * 512 + 32 * i + lane, u);
#pragma unroll 4
      for (int i = 0; i < 16; i++) stg128(((i & 8) ? (uint4*)g_xT : (uint4*)g_O) + cta * 1024 + (i & 7) * 128 + (lane >> 1) * 8 + (lane & 1), u);
      __syncwarp();
      if (elect_one()) red_release(&g_cnt[C_Z * 32]);
      __syncwarp();
#pragma unroll 1
      for (int layer = 0; layer < 2; layer++) {
        auto reset_done = [&](int s) {
          spin_until(&g_cnt[(C_R + s) * 32], lds32(sb + SM_EP) * 4 + 4);
          mbar_arrive(bar + 8 * (s == 1 ? B_LN : s == 2 ? B_RS : B_RC));
          if (s) TS(16 + 40 + 9 + s);
        };
        if (layer && elect_one()) reset_done(1);
        __syncwarp();
#pragma unroll 1
        for (int half = 0; half < 2; half++) {
          done(half, 2, layer);
          const uint4* src = g_rows + layer * LSEQ + (16 * half + rb) * 64 + lane;
          uint4 a, b;
          int it = 0;
          do {
            a = ld_tagged(src); b = ld_tagged(src + 32);
          } while (!__all_sync(~0u, (a.z | a.w) == __float_as_uint(8.f) && (b.z | b.w) == __float_as_uint(8.f)) && ++it < (1 << 20));
          float m0 = __uint_as_float(a.x) * (1.f / DM), m1 = __uint_as_float(b.x) * (1.f / DM);
          float r0 = rsqrt_approx(fmaxf(__uint_as_float(a.y) * (1.f / DM) - m0 * m0, 0.f) + 1e-5f);
          float r1 = rsqrt_approx(fmaxf(__uint_as_float(b.y) * (1.f / DM) - m1 * m1, 0.f) + 1e-5f);
          if (half) done(0, 7, layer);
          const uint32_t dst = sb + ln_off(half) + ((lane >> 4) * 8 + (lane & 7)) * 16 + (lane & 8);
          asm volatile("st.shared.v2.f32 [%0], {%1,%2};" ::"r"(dst), "f"(m0), "f"(r0) : "memory");
          asm volatile("st.shared.v2.f32 [%0], {%1,%2};" ::"r"(dst + 256), "f"(m1), "f"(r1) : "memory");
          __syncwarp();
          if (elect_one()) { mbar_arrive(bar + 8 * (B_LN + half)); TS(16 + layer * 56 + 40 + 14 + half); }
        }
        if (layer && lane < 16) stg128(g_rows + cta * 16 + lane, make_uint4(0, 0, 0, 0));
        if (elect_one()) {
          if (layer) reset_done(2);
          reset_done(3 * layer);
          publish(layer, 0);
          publish(layer, 2);
        }
        __syncwarp();
      }
    }
  }
}

typedef CUresult (*EncodeFn)(CUtensorMap*, CUtensorMapDataType, cuuint32_t, void*, const cuuint64_t*, const cuuint64_t*,
                             const cuuint32_t*, const cuuint32_t*, CUtensorMapInterleave, CUtensorMapSwizzle,
                             CUtensorMapL2promotion, CUtensorMapFloatOOBfill);

static void make_map(EncodeFn enc, CUtensorMap* m, void* ptr, uint64_t cols, uint64_t rows, uint32_t box_rows) {
  cuuint64_t dims[2] = {cols, rows};
  cuuint64_t strides[1] = {cols * 2};
  cuuint32_t box[2] = {64, box_rows};
  cuuint32_t es[2] = {1, 1};
  enc(m, CU_TENSOR_MAP_DATA_TYPE_BFLOAT16, 2, ptr, dims, strides, box, es, CU_TENSOR_MAP_INTERLEAVE_NONE,
      CU_TENSOR_MAP_SWIZZLE_128B, CU_TENSOR_MAP_L2_PROMOTION_L2_128B, CU_TENSOR_MAP_FLOAT_OOB_FILL_NONE);
}
static void make_map3(EncodeFn enc, CUtensorMap* m, void* ptr, uint64_t d0, uint64_t cols, uint64_t rows, uint64_t blk_stride,
                      uint64_t nblocks, uint32_t nblk) {
  cuuint64_t dims[3] = {d0, rows, nblocks};
  cuuint64_t strides[2] = {cols * 2, blk_stride * 2};
  cuuint32_t box[3] = {64, 64, nblk};
  cuuint32_t es[3] = {1, 1, 1};
  enc(m, CU_TENSOR_MAP_DATA_TYPE_BFLOAT16, 3, ptr, dims, strides, box, es, CU_TENSOR_MAP_INTERLEAVE_NONE,
      CU_TENSOR_MAP_SWIZZLE_128B, CU_TENSOR_MAP_L2_PROMOTION_L2_128B, CU_TENSOR_MAP_FLOAT_OOB_FILL_NONE);
}

extern "C" void kernel_launch(void* const* d_in, const int* in_sizes, int n_in, void* d_out, int out_size) {
  static Params prm;
  static void* cached[13] = {nullptr};
  static bool attr_done = false;
  bool same = attr_done && cached[12] == d_out;
  for (int i = 0; i < 12 && same; i++) same = cached[i] == d_in[i];
  if (!same) {
    void* fn = nullptr;
    cudaDriverEntryPointQueryResult qr;
    cudaGetDriverEntryPoint("cuTensorMapEncodeTiled", &fn, cudaEnableDefault, &qr);
    EncodeFn enc = (EncodeFn)fn;
    void* pXT;
    cudaGetSymbolAddress(&pXT, g_xT);
    make_map(enc, &prm.mapX, d_in[0], DM, LSEQ, 64);
    make_map(enc, &prm.mapXT, pXT, LSEQ, 4 * DM, 64);
    make_map(enc, &prm.mapOut, d_out, DM, LSEQ, 64);
    {
      cuuint64_t dims[5] = {DM, 2, 4, 4, 16};
      cuuint64_t strides[4] = {DM * 2, 8 * DM * 2, 2 * DM * 2, 32 * DM * 2};
      cuuint32_t box[5] = {64, 2, 4, 4, 2};
      cuuint32_t es[5] = {1, 1, 1, 1, 1};
      enc(&prm.mapWo, CU_TENSOR_MAP_DATA_TYPE_BFLOAT16, 5, d_in[2], dims, strides, box, es, CU_TENSOR_MAP_INTERLEAVE_NONE,
          CU_TENSOR_MAP_SWIZZLE_128B, CU_TENSOR_MAP_L2_PROMOTION_L2_128B, CU_TENSOR_MAP_FLOAT_OOB_FILL_NONE);
    }
    make_map3(enc, &prm.mapW3, d_in[1], DM, 3 * DM, DM, DM, 3, 3);
    prm.wqkv = (const bf16*)d_in[1];
    prm.a_re = (const bf16*)d_in[4]; prm.a_im = (const bf16*)d_in[5];
    prm.b_re = (const bf16*)d_in[6]; prm.b_im = (const bf16*)d_in[7];
    prm.c_re = (const bf16*)d_in[8]; prm.c_im = (const bf16*)d_in[9];
    prm.log_dt = (const bf16*)d_in[10]; prm.dskip = (const bf16*)d_in[11];
    int dev = 0, sms = 0;
    cudaGetDevice(&dev);
    cudaDeviceGetAttribute(&sms, cudaDevAttrMultiProcessorCount, dev);
    prm.first = sms >= NCTA + 4 ? FIRST : 4;
    cudaFuncSetAttribute(fused_kernel, cudaFuncAttributeMaxDynamicSharedMemorySize, SM_TOTAL);
    for (int i = 0; i < 12; i++) cached[i] = d_in[i];
    cached[12] = d_out;
    attr_done = true;
  }
  fused_kernel<<<NCTA + 4, NTHREADS, SM_TOTAL>>>(prm);
}
```

```cpp
#include <cuda_runtime.h>
#include <cuda_bf16.h>
#include <cuda.h>
#include <stdint.h>

typedef __nv_bfloat16 bf16;

constexpr int LSEQ = 2048;
constexpr int DM = 512;
constexpr int NCTA = 128;
constexpr int NTHREADS = 512;
#define R_CONS 200
#define R_HELP 88
#define R_AGENT 24
#define TURN0 4
#define TURN1 4

constexpr int PG = 8192;
constexpr int P_R = 25;
__host__ __device__ constexpr int x_page(int half, int c) { return half ? 8 + c : c < 5 ? c : c - 5; }
__host__ __device__ constexpr int w_page(int c) { return (c & 3) < 3 ? 16 + 3 * (c & 3) : c < 4 ? 5 : 8; }
__host__ __device__ constexpr int wo_page(int c) { return c < 5 ? 3 + c : 11 + c; }
__host__ __device__ constexpr int o_page(int half, int pair) { return half ? (pair ? 17 + 2 * pair : 0) : 8 + 2 * pair; }
constexpr int SM_KGB = (P_R + 1) * PG;
constexpr int SM_KC = 27 * PG;
constexpr int KC_STRIDE = 648;
__host__ __device__ constexpr int kc_off(int lc) { return SM_KC + (lc & 1) * 2 * KC_STRIDE + (lc < 2 ? 3328 : 0); }
constexpr int SM_KGT = SM_KC + 3328 + 2592;
constexpr int SM_CS = SM_KGT + 2048;
constexpr int SM_RED = SM_CS + 768;
constexpr int SM_EP = SM_RED + 16;
constexpr int SM_STG = SM_RED + 32;
constexpr int SM_LN = SM_STG + 768;
__host__ __device__ constexpr int ln_off(int half) { return half ? PG + 4096 : SM_LN; }
constexpr int SM_BAR = SM_LN + 512;
constexpr int SM_TS = SM_BAR + 704;
constexpr int SM_TOTAL = SM_TS + 512;
static_assert(SM_TOTAL <= 232448 && SM_STG % 16 == 0 && SM_KGT % 16 == 0, "shared memory");

constexpr int CV_UH = 140 * 16;
__host__ __device__ constexpr int cv_u(int lc) { return (8 + 2 * lc) * PG; }
__host__ __device__ constexpr int cv_pe(int lc) { return cv_u(lc) + 4480; }
__host__ __device__ constexpr int cv_pb1(int lc, int w) { return w ? cv_u(lc) + 8960 + (w - 1) * 2048 : 7 * PG + lc * 2048; }
__host__ __device__ constexpr int cv_fa(int lc) { return cv_pb1(lc, 1) + 128; }
__host__ __device__ constexpr int cv_dump(int lc) { return cv_u(lc) + 16256; }
__host__ __device__ constexpr int cv_pb0(int lc, int w) { return lc * PG + w * 2048; }
__host__ __device__ constexpr int cv_se(int lc) { return 5 * PG + lc * 4096; }
__host__ __device__ constexpr int cv_so(int lc) { return cv_se(lc) + 2048; }
__host__ __device__ constexpr int cv_x(int half, int lc) { return (P_R + half) * PG + lc * 2048; }
constexpr int CV_ST = 22 * PG;
__host__ __device__ constexpr int cv_chan(int cta, int lc) { return 2 * cta + (lc & 1) + 256 * (lc >> 1); }

enum {
  B_XF = 0,
  B_WF = 16,
  B_OF = 24,
  B_DN = 32,
  B_XR = 48,
  B_RF = 56,
  B_PST = 58,
  B_GB = 60,
  B_TF = 62,
  B_RT = 64,
  B_RS = 66,
  B_RC = 67,
  B_WOF = 68,
  B_ZF = 69,
  B_EP = 70,
  B_KG = 71,
  B_SC = 72,
  B_LN = 73,
  B_END = 75,
  B_OST = 76,
  B_PDONE = 78,
  B_PE = 80,
  B_U = 81,
  B_U1 = 82,
  B_PUB = 83,
  B_R = 86,
  B_COUNT = 88
};

enum {
  C_CS = 0,
  C_G = 1,
  C_C = 5,
  C_F = 9,
  C_O = 21,
  C_Z = 85,
  C_R = 86,
  C_COUNT = 90
};

__device__ unsigned g_cnt[C_COUNT * 32];
__device__ __align__(1024) bf16 g_O[2 * LSEQ * DM];
__device__ __align__(1024) bf16 g_xT[4 * DM * LSEQ];
__device__ __align__(1024) float g_stats[2 * 32 * 192];
__device__ __align__(1024) uint2 g_colsum[3 * DM];
__device__ __align__(1024) uint4 g_halo[32 * 8 * 256];
__device__ __align__(1024) uint4 g_rows[2 * LSEQ];
#define TS(i) do { } while (0)
#define TSW(k) do { if ((threadIdx.x & 127) == 0) TS(16 + layer * 56 + (threadIdx.x >> 7) * 20 + (k)); } while (0)
#define TSG(k) do { } while (0)

#define RETRY(i) do { } while (0)
#define LTS(i) do { } while (0)

struct Params {
  CUtensorMap mapX, mapW3, mapXT, mapOut, mapWo;
  const bf16 *wqkv, *a_re, *a_im, *b_re, *b_im, *c_re, *c_im, *log_dt, *dskip;
};

__device__ __forceinline__ uint32_t s32(const void* p) { return (uint32_t)__cvta_generic_to_shared(p); }
__device__ __forceinline__ void mbar_init(uint32_t b, int c) { asm volatile("mbarrier.init.shared::cta.b64 [%0], %1;" ::"r"(b), "r"(c) : "memory"); }
__device__ __forceinline__ void mbar_expect(uint32_t b, int bytes) { asm volatile("mbarrier.arrive.expect_tx.shared::cta.b64 _, [%0], %1;" ::"r"(b), "r"(bytes) : "memory"); }
__device__ __forceinline__ void mbar_arrive(uint32_t b) { asm volatile("mbarrier.arrive.shared::cta.b64 _, [%0];" ::"r"(b) : "memory"); }
__device__ __forceinline__ void mbar_wait(uint32_t b, int parity) {
  asm volatile("{\n.reg .pred p;\nWAIT_LOOP:\nmbarrier.try_wait.parity.shared::cta.b64 p, [%0], %1;\n@p bra WAIT_DONE;\nbra WAIT_LOOP;\nWAIT_DONE:\n}" ::"r"(b), "r"(parity) : "memory");
}
__device__ __forceinline__ bool mbar_test(uint32_t b, int parity) {
  uint32_t ok;
  asm volatile("{\n.reg .pred p;\nmbarrier.test_wait.parity.shared::cta.b64 p, [%1], %2;\nselp.u32 %0, 1, 0, p;\n}" : "=r"(ok) : "r"(b), "r"(parity) : "memory");
  return ok != 0;
}
__device__ __forceinline__ int opaque_tid() { int v; asm volatile("mov.u32 %0, %%tid.x;" : "=r"(v)); return v; }
__device__ __forceinline__ bool elect_one() {
  uint32_t r;
  asm volatile("{\n.reg .pred p;\nelect.sync _|p, 0xffffffff;\nselp.u32 %0, 1, 0, p;\n}" : "=r"(r));
  return r != 0;
}
__device__ __forceinline__ void tma_ld(uint32_t dst, const CUtensorMap* m, int c0, int c1, uint32_t bar) {
  asm volatile("cp.async.bulk.tensor.2d.shared::cluster.global.mbarrier::complete_tx::bytes [%0], [%1, {%3, %4}], [%2];"
               ::"r"(dst), "l"(m), "r"(bar), "r"(c0), "r"(c1) : "memory");
}
__device__ __forceinline__ void tma_ld3(uint32_t dst, const CUtensorMap* m, int c0, int c1, int c2, uint32_t bar) {
  asm volatile("cp.async.bulk.tensor.3d.shared::cluster.global.mbarrier::complete_tx::bytes [%0], [%1, {%3, %4, %5}], [%2];"
               ::"r"(dst), "l"(m), "r"(bar), "r"(c0), "r"(c1), "r"(c2) : "memory");
}
__device__ __forceinline__ void tma_ld5(uint32_t dst, const CUtensorMap* m, int c0, int c4, uint32_t bar) {
  asm volatile("cp.async.bulk.tensor.5d.shared::cluster.global.mbarrier::complete_tx::bytes [%0], [%1, {%3, 0, 0, 0, %4}], [%2];"
               ::"r"(dst), "l"(m), "r"(bar), "r"(c0), "r"(c4) : "memory");
}
__device__ __forceinline__ void tma_prefetch5(const CUtensorMap* m, int c0, int c4) {
  asm volatile("cp.async.bulk.prefetch.tensor.5d.L2.global.tile [%0, {%1, 0, 0, 0, %2}];" ::"l"(m), "r"(c0), "r"(c4) : "memory");
}
__device__ __forceinline__ void tma_prefetch2(const CUtensorMap* m, int c0, int c1) {
  asm volatile("cp.async.bulk.prefetch.tensor.2d.L2.global.tile [%0, {%1, %2}];" ::"l"(m), "r"(c0), "r"(c1) : "memory");
}
__device__ __forceinline__ void tma_prefetch3(const CUtensorMap* m, int c0, int c1, int c2) {
  asm volatile("cp.async.bulk.prefetch.tensor.3d.L2.global.tile [%0, {%1, %2, %3}];" ::"l"(m), "r"(c0), "r"(c1), "r"(c2) : "memory");
}
__device__ __forceinline__ void tma_st(const CUtensorMap* m, int c0, int c1, uint32_t src) {
  asm volatile("cp.async.bulk.tensor.2d.global.shared::cta.bulk_group [%0, {%2, %3}], [%1];" ::"l"(m), "r"(src), "r"(c0), "r"(c1) : "memory");
}
__device__ __forceinline__ void bulk_ld(uint32_t dst, const void* src, int bytes, uint32_t bar) {
  asm volatile("cp.async.bulk.shared::cluster.global.mbarrier::complete_tx::bytes [%0], [%1], %2, [%3];" ::"r"(dst), "l"(src), "r"(bytes), "r"(bar) : "memory");
}
__device__ __forceinline__ void bulk_st(void* dst, uint32_t src, int bytes) {
  asm volatile("cp.async.bulk.global.shared::cta.bulk_group [%0], [%1], %2;" ::"l"(dst), "r"(src), "r"(bytes) : "memory");
}
__device__ __forceinline__ void bulk_red_add_f32(void* dst, uint32_t src, int bytes) {
  asm volatile("cp.reduce.async.bulk.global.shared::cta.bulk_group.add.f32 [%0], [%1], %2;" ::"l"(dst), "r"(src), "r"(bytes) : "memory");
}
__device__ __forceinline__ void bulk_commit() { asm volatile("cp.async.bulk.commit_group;" ::: "memory"); }
__device__ __forceinline__ void bulk_wait_all() { asm volatile("cp.async.bulk.wait_group 0;" ::: "memory"); }
__device__ __forceinline__ void fence_async_smem() { asm volatile("fence.proxy.async.shared::cta;" ::: "memory"); }
__device__ __forceinline__ void fence_async_global() { asm volatile("fence.proxy.async.global;" ::: "memory"); }
__device__ __forceinline__ void bar_sync(int id, int n) { asm volatile("bar.sync %0, %1;" ::"r"(id), "r"(n) : "memory"); }
__device__ __forceinline__ void bar_arrive(int id, int n) { asm volatile("bar.arrive %0, %1;" ::"r"(id), "r"(n) : "memory"); }
__device__ __forceinline__ bool bar_or(int id, int n, bool v) {
  uint32_t r;
  asm volatile("{\n.reg .pred p, q;\nsetp.ne.u32 q, %3, 0;\nbar.red.or.pred p, %1, %2, q;\nselp.u32 %0, 1, 0, p;\n}" : "=r"(r) : "r"(id), "r"(n), "r"((uint32_t)v) : "memory");
  return r != 0;
}
__device__ __forceinline__ void bulk_wait_read() { asm volatile("cp.async.bulk.wait_group.read 0;" ::: "memory"); }
__device__ __forceinline__ void stg128(void* p, uint4 v) { asm volatile("st.relaxed.gpu.global.v4.u32 [%0], {%1,%2,%3,%4};" ::"l"(p), "r"(v.x), "r"(v.y), "r"(v.z), "r"(v.w) : "memory"); }
constexpr uint32_t UNSET = 0xffffffffu;
constexpr int MAX_RETRY = 1 << 16;
__device__ __forceinline__ void wg_fence() { asm volatile("wgmma.fence.sync.aligned;" ::: "memory"); }
__device__ __forceinline__ void wg_commit() { asm volatile("wgmma.commit_group.sync.aligned;" ::: "memory"); }
template <int N> __device__ __forceinline__ void wg_wait() { asm volatile("wgmma.wait_group.sync.aligned %0;" ::"n"(N) : "memory"); }
__device__ __forceinline__ uint64_t mkdesc(uint32_t addr, uint32_t lbo, uint32_t sbo, int sw) {
  return (uint64_t)((addr & 0x3FFFF) >> 4) | ((uint64_t)(lbo >> 4) << 16) | ((uint64_t)(sbo >> 4) << 32) | ((uint64_t)sw << 62);
}
__device__ __forceinline__ void ldsm4(uint32_t* r, uint32_t a) {
  asm volatile("ldmatrix.sync.aligned.m8n8.x4.shared.b16 {%0,%1,%2,%3}, [%4];" : "=r"(r[0]), "=r"(r[1]), "=r"(r[2]), "=r"(r[3]) : "r"(a) : "memory");
}
__device__ __forceinline__ void ldsm4t(uint32_t* r, uint32_t a) {
  asm volatile("ldmatrix.sync.aligned.m8n8.x4.trans.shared.b16 {%0,%1,%2,%3}, [%4];" : "=r"(r[0]), "=r"(r[1]), "=r"(r[2]), "=r"(r[3]) : "r"(a) : "memory");
}
__device__ __forceinline__ void stsm4(uint32_t a, uint32_t r0, uint32_t r1, uint32_t r2, uint32_t r3) {
  asm volatile("stmatrix.sync.aligned.m8n8.x4.shared.b16 [%0], {%1,%2,%3,%4};" ::"r"(a), "r"(r0), "r"(r1), "r"(r2), "r"(r3) : "memory");
}
__device__ __forceinline__ void stsm4t(uint32_t a, uint32_t r0, uint32_t r1, uint32_t r2, uint32_t r3) {
  asm volatile("stmatrix.sync.aligned.m8n8.x4.trans.shared.b16 [%0], {%1,%2,%3,%4};" ::"r"(a), "r"(r0), "r"(r1), "r"(r2), "r"(r3) : "memory");
}
__device__ __forceinline__ uint32_t movm_t(uint32_t a) { uint32_t r; asm volatile("movmatrix.sync.aligned.m8n8.trans.b16 %0, %1;" : "=r"(r) : "r"(a)); return r; }
__device__ __forceinline__ uint32_t lds32(uint32_t a) { uint32_t v; asm volatile("ld.shared.b32 %0, [%1];" : "=r"(v) : "r"(a) : "memory"); return v; }
__device__ __forceinline__ float2 lds64f(uint32_t a) { float2 v; asm volatile("ld.shared.v2.f32 {%0,%1}, [%2];" : "=f"(v.x), "=f"(v.y) : "r"(a) : "memory"); return v; }
__device__ __forceinline__ float4 lds128f(uint32_t a) { float4 v; asm volatile("ld.shared.v4.f32 {%0,%1,%2,%3}, [%4];" : "=f"(v.x), "=f"(v.y), "=f"(v.z), "=f"(v.w) : "r"(a) : "memory"); return v; }
__device__ __forceinline__ uint4 lds128(uint32_t a) { uint4 v; asm volatile("ld.shared.v4.b32 {%0,%1,%2,%3}, [%4];" : "=r"(v.x), "=r"(v.y), "=r"(v.z), "=r"(v.w) : "r"(a) : "memory"); return v; }
__device__ __forceinline__ void sts128(uint32_t a, uint4 v) { asm volatile("st.shared.v4.b32 [%0], {%1,%2,%3,%4};" ::"r"(a), "r"(v.x), "r"(v.y), "r"(v.z), "r"(v.w) : "memory"); }
__device__ __forceinline__ void sts128f(uint32_t a, float x, float y, float z, float w) { asm volatile("st.shared.v4.f32 [%0], {%1,%2,%3,%4};" ::"r"(a), "f"(x), "f"(y), "f"(z), "f"(w) : "memory"); }
__device__ __forceinline__ void sts32f(uint32_t a, float v) { asm volatile("st.shared.f32 [%0], %1;" ::"r"(a), "f"(v) : "memory"); }
__device__ __forceinline__ void sts16(uint32_t a, uint16_t v) { asm volatile("st.shared.u16 [%0], %1;" ::"r"(a), "h"(v) : "memory"); }
__device__ __forceinline__ uint32_t lds16(uint32_t a) { uint16_t v; asm volatile("ld.shared.u16 %0, [%1];" : "=h"(v) : "r"(a) : "memory"); return v; }
__device__ __forceinline__ uint32_t packbf(float lo, float hi) { uint32_t r; asm("cvt.rn.bf16x2.f32 %0, %1, %2;" : "=r"(r) : "f"(hi), "f"(lo)); return r; }
__device__ __forceinline__ float bf_lo(uint32_t v) { return __uint_as_float(v << 16); }
__device__ __forceinline__ float bf_hi(uint32_t v) { return __uint_as_float(v & 0xffff0000u); }
__device__ __forceinline__ float ex2(float x) { float r; asm("ex2.approx.ftz.f32 %0, %1;" : "=f"(r) : "f"(x)); return r; }
__device__ __forceinline__ float rsqrt_approx(float x) { float r; asm("rsqrt.approx.ftz.f32 %0, %1;" : "=f"(r) : "f"(x)); return r; }
__device__ __forceinline__ float rcp_approx(float x) { float r; asm("rcp.approx.ftz.f32 %0, %1;" : "=f"(r) : "f"(x)); return r; }
__device__ __forceinline__ void mma_bf16(float* d, const uint32_t* a, uint32_t b0, uint32_t b1) {
  asm("mma.sync.aligned.m16n8k16.row.col.f32.bf16.bf16.f32 {%0,%1,%2,%3}, {%4,%5,%6,%7}, {%8,%9}, {%0,%1,%2,%3};"
               : "+f"(d[0]), "+f"(d[1]), "+f"(d[2]), "+f"(d[3]) : "r"(a[0]), "r"(a[1]), "r"(a[2]), "r"(a[3]), "r"(b0), "r"(b1));
}
__device__ __forceinline__ void mma_tf32(float* d, float a0, float a1, float a2, float a3, float b0, float b1) {
  asm("mma.sync.aligned.m16n8k8.row.col.f32.tf32.tf32.f32 {%0,%1,%2,%3}, {%4,%5,%6,%7}, {%8,%9}, {%0,%1,%2,%3};"
               : "+f"(d[0]), "+f"(d[1]), "+f"(d[2]), "+f"(d[3])
               : "r"(__float_as_uint(a0)), "r"(__float_as_uint(a1)), "r"(__float_as_uint(a2)), "r"(__float_as_uint(a3)),
                 "r"(__float_as_uint(b0)), "r"(__float_as_uint(b1)));
}
__device__ __forceinline__ void red_release(unsigned* p) { asm volatile("red.release.gpu.global.add.u32 [%0], 1;" ::"l"(p) : "memory"); }
__device__ __forceinline__ void red_relaxed(unsigned* p) { asm volatile("red.relaxed.gpu.global.add.u32 [%0], 1;" ::"l"(p) : "memory"); }
__device__ __forceinline__ unsigned ld_relaxed(const unsigned* p) { unsigned v; asm volatile("ld.relaxed.gpu.global.u32 %0, [%1];" : "=r"(v) : "l"(p) : "memory"); return v; }
__device__ __forceinline__ void spin_until(const unsigned* p, unsigned target) {
  int it = 0;
  while ((int)(ld_relaxed(p) - target) < 0) {
    if (++it > (1 << 23)) __trap();
  }
}
__device__ __forceinline__ uint4 ldcg128(const void* p) { uint4 v; asm volatile("ld.global.cg.v4.b32 {%0,%1,%2,%3}, [%4];" : "=r"(v.x), "=r"(v.y), "=r"(v.z), "=r"(v.w) : "l"(p) : "memory"); return v; }
__device__ __forceinline__ uint4 ld_tagged(const uint4* p) { uint4 v; asm volatile("ld.relaxed.gpu.global.v4.u32 {%0,%1,%2,%3}, [%4];" : "=r"(v.x), "=r"(v.y), "=r"(v.z), "=r"(v.w) : "l"(p) : "memory"); return v; }
__device__ __forceinline__ void st_tagged(uint4* p, uint32_t a, uint32_t b, uint32_t tag) { asm volatile("st.relaxed.gpu.global.v4.u32 [%0], {%1,%2,%3,%2};" ::"l"(p), "r"(a), "r"(tag), "r"(b) : "memory"); }
__device__ __forceinline__ void st_tagged3(uint4* p, uint32_t a, uint32_t b, uint32_t c, uint32_t tag) { asm volatile("st.relaxed.gpu.global.v4.u32 [%0], {%1,%2,%3,%4};" ::"l"(p), "r"(a), "r"(b), "r"(c), "r"(tag) : "memory"); }
__device__ __forceinline__ uint4 poll_tagged(const uint4* p, uint32_t tag) {
  uint4 v = ld_tagged(p);
  int it = 0;
  while (v.y != tag || v.w != tag) {
    if (++it > (1 << 22)) __trap();
    v = ld_tagged(p);
  }
  return v;
}
__device__ __forceinline__ uint32_t hadd2(uint32_t a, uint32_t b) { uint32_t r; asm("add.rn.bf16x2 %0, %1, %2;" : "=r"(r) : "r"(a), "r"(b)); return r; }
__device__ __forceinline__ uint32_t hmul2(uint32_t a, uint32_t b) { uint32_t r; asm("mul.rn.bf16x2 %0, %1, %2;" : "=r"(r) : "r"(a), "r"(b)); return r; }

__device__ __forceinline__ uint32_t hfma2(uint32_t a, uint32_t b, uint32_t c) { uint32_t r; asm("fma.rn.bf16x2 %0, %1, %2, %3;" : "=r"(r) : "r"(a), "r"(b), "r"(c)); return r; }
__device__ __forceinline__ void sts32(uint32_t a, uint32_t v) { asm volatile("st.shared.u32 [%0], %1;" ::"r"(a), "r"(v) : "memory"); }

template <int N> __device__ __forceinline__ void acc_fence(float* a) {
#pragma unroll
  for (int i = 0; i < N; i++) asm volatile("" : "+f"(a[i]) :: "memory");
}

template<int N,int TB> __device__ __forceinline__ void wgmma_rs(float* d, const uint32_t* a, uint64_t db, int sd);
template<int N,int TA,int TB> __device__ __forceinline__ void wgmma_ss(float* d, uint64_t da, uint64_t db, int sd);
template<> __device__ __forceinline__ void wgmma_rs<64,0>(float* d, const uint32_t* a, uint64_t db, int sd) {
  asm volatile("{\n.reg .pred p;\nsetp.ne.b32 p, %37, 0;\nwgmma.mma_async.sync.aligned.m64n64k16.f32.bf16.bf16 {%0,%1,%2,%3,%4,%5,%6,%7,%8,%9,%10,%11,%12,%13,%14,%15,%16,%17,%18,%19,%20,%21,%22,%23,%24,%25,%26,%27,%28,%29,%30,%31}, {%32,%33,%34,%35}, %36, p, 1, 1, 0;\n}\n"
   : "+f"(d[0]),"+f"(d[1]),"+f"(d[2]),"+f"(d[3]),"+f"(d[4]),"+f"(d[5]),"+f"(d[6]),"+f"(d[7]),"+f"(d[8]),"+f"(d[9]),"+f"(d[10]),"+f"(d[11]),"+f"(d[12]),"+f"(d[13]),"+f"(d[14]),"+f"(d[15]),"+f"(d[16]),"+f"(d[17]),"+f"(d[18]),"+f"(d[19]),"+f"(d[20]),"+f"(d[21]),"+f"(d[22]),"+f"(d[23]),"+f"(d[24]),"+f"(d[25]),"+f"(d[26]),"+f"(d[27]),"+f"(d[28]),"+f"(d[29]),"+f"(d[30]),"+f"(d[31])
   : "r"(a[0]), "r"(a[1]), "r"(a[2]), "r"(a[3]), "l"(db), "r"(sd));
}
template<> __device__ __forceinline__ void wgmma_rs<56,0>(float* d, const uint32_t* a, uint64_t db, int sd) {
  asm volatile("{\n.reg .pred p;\nsetp.ne.b32 p, %33, 0;\nwgmma.mma_async.sync.aligned.m64n56k16.f32.bf16.bf16 {%0,%1,%2,%3,%4,%5,%6,%7,%8,%9,%10,%11,%12,%13,%14,%15,%16,%17,%18,%19,%20,%21,%22,%23,%24,%25,%26,%27}, {%28,%29,%30,%31}, %32, p, 1, 1, 0;\n}\n"
   : "+f"(d[0]),"+f"(d[1]),"+f"(d[2]),"+f"(d[3]),"+f"(d[4]),"+f"(d[5]),"+f"(d[6]),"+f"(d[7]),"+f"(d[8]),"+f"(d[9]),"+f"(d[10]),"+f"(d[11]),"+f"(d[12]),"+f"(d[13]),"+f"(d[14]),"+f"(d[15]),"+f"(d[16]),"+f"(d[17]),"+f"(d[18]),"+f"(d[19]),"+f"(d[20]),"+f"(d[21]),"+f"(d[22]),"+f"(d[23]),"+f"(d[24]),"+f"(d[25]),"+f"(d[26]),"+f"(d[27])
   : "r"(a[0]), "r"(a[1]), "r"(a[2]), "r"(a[3]), "l"(db), "r"(sd));
}
template<> __device__ __forceinline__ void wgmma_rs<48,0>(float* d, const uint32_t* a, uint64_t db, int sd) {
  asm volatile("{\n.reg .pred p;\nsetp.ne.b32 p, %29, 0;\nwgmma.mma_async.sync.aligned.m64n48k16.f32.bf16.bf16 {%0,%1,%2,%3,%4,%5,%6,%7,%8,%9,%10,%11,%12,%13,%14,%15,%16,%17,%18,%19,%20,%21,%22,%23}, {%24,%25,%26,%27}, %28, p, 1, 1, 0;\n}\n"
   : "+f"(d[0]),"+f"(d[1]),"+f"(d[2]),"+f"(d[3]),"+f"(d[4]),"+f"(d[5]),"+f"(d[6]),"+f"(d[7]),"+f"(d[8]),"+f"(d[9]),"+f"(d[10]),"+f"(d[11]),"+f"(d[12]),"+f"(d[13]),"+f"(d[14]),"+f"(d[15]),"+f"(d[16]),"+f"(d[17]),"+f"(d[18]),"+f"(d[19]),"+f"(d[20]),"+f"(d[21]),"+f"(d[22]),"+f"(d[23])
   : "r"(a[0]), "r"(a[1]), "r"(a[2]), "r"(a[3]), "l"(db), "r"(sd));
}
template<> __device__ __forceinline__ void wgmma_rs<40,0>(float* d, const uint32_t* a, uint64_t db, int sd) {
  asm volatile("{\n.reg .pred p;\nsetp.ne.b32 p, %25, 0;\nwgmma.mma_async.sync.aligned.m64n40k16.f32.bf16.bf16 {%0,%1,%2,%3,%4,%5,%6,%7,%8,%9,%10,%11,%12,%13,%14,%15,%16,%17,%18,%19}, {%20,%21,%22,%23}, %24, p, 1, 1, 0;\n}\n"
   : "+f"(d[0]),"+f"(d[1]),"+f"(d[2]),"+f"(d[3]),"+f"(d[4]),"+f"(d[5]),"+f"(d[6]),"+f"(d[7]),"+f"(d[8]),"+f"(d[9]),"+f"(d[10]),"+f"(d[11]),"+f"(d[12]),"+f"(d[13]),"+f"(d[14]),"+f"(d[15]),"+f"(d[16]),"+f"(d[17]),"+f"(d[18]),"+f"(d[19])
   : "r"(a[0]), "r"(a[1]), "r"(a[2]), "r"(a[3]), "l"(db), "r"(sd));
}
template<> __device__ __forceinline__ void wgmma_rs<32,0>(float* d, const uint32_t* a, uint64_t db, int sd) {
  asm volatile("{\n.reg .pred p;\nsetp.ne.b32 p, %21, 0;\nwgmma.mma_async.sync.aligned.m64n32k16.f32.bf16.bf16 {%0,%1,%2,%3,%4,%5,%6,%7,%8,%9,%10,%11,%12,%13,%14,%15}, {%16,%17,%18,%19}, %20, p, 1, 1, 0;\n}\n"
   : "+f"(d[0]),"+f"(d[1]),"+f"(d[2]),"+f"(d[3]),"+f"(d[4]),"+f"(d[5]),"+f"(d[6]),"+f"(d[7]),"+f"(d[8]),"+f"(d[9]),"+f"(d[10]),"+f"(d[11]),"+f"(d[12]),"+f"(d[13]),"+f"(d[14]),"+f"(d[15])
   : "r"(a[0]), "r"(a[1]), "r"(a[2]), "r"(a[3]), "l"(db), "r"(sd));
}
template<> __device__ __forceinline__ void wgmma_rs<24,0>(float* d, const uint32_t* a, uint64_t db, int sd) {
  asm volatile("{\n.reg .pred p;\nsetp.ne.b32 p, %17, 0;\nwgmma.mma_async.sync.aligned.m64n24k16.f32.bf16.bf16 {%0,%1,%2,%3,%4,%5,%6,%7,%8,%9,%10,%11}, {%12,%13,%14,%15}, %16, p, 1, 1, 0;\n}\n"
   : "+f"(d[0]),"+f"(d[1]),"+f"(d[2]),"+f"(d[3]),"+f"(d[4]),"+f"(d[5]),"+f"(d[6]),"+f"(d[7]),"+f"(d[8]),"+f"(d[9]),"+f"(d[10]),"+f"(d[11])
   : "r"(a[0]), "r"(a[1]), "r"(a[2]), "r"(a[3]), "l"(db), "r"(sd));
}
template<> __device__ __forceinline__ void wgmma_rs<16,0>(float* d, const uint32_t* a, uint64_t db, int sd) {
  asm volatile("{\n.reg .pred p;\nsetp.ne.b32 p, %13, 0;\nwgmma.mma_async.sync.aligned.m64n16k16.f32.bf16.bf16 {%0,%1,%2,%3,%4,%5,%6,%7}, {%8,%9,%10,%11}, %12, p, 1, 1, 0;\n}\n"
   : "+f"(d[0]),"+f"(d[1]),"+f"(d[2]),"+f"(d[3]),"+f"(d[4]),"+f"(d[5]),"+f"(d[6]),"+f"(d[7])
   : "r"(a[0]), "r"(a[1]), "r"(a[2]), "r"(a[3]), "l"(db), "r"(sd));
}
template<> __device__ __forceinline__ void wgmma_rs<8,0>(float* d, const uint32_t* a, uint64_t db, int sd) {
  asm volatile("{\n.reg .pred p;\nsetp.ne.b32 p, %9, 0;\nwgmma.mma_async.sync.aligned.m64n8k16.f32.bf16.bf16 {%0,%1,%2,%3}, {%4,%5,%6,%7}, %8, p, 1, 1, 0;\n}\n"
   : "+f"(d[0]),"+f"(d[1]),"+f"(d[2]),"+f"(d[3])
   : "r"(a[0]), "r"(a[1]), "r"(a[2]), "r"(a[3]), "l"(db), "r"(sd));
}
template<> __device__ __forceinline__ void wgmma_ss<64,1,0>(float* d, uint64_t da, uint64_t db, int sd) {
  asm volatile("{\n.reg .pred p;\nsetp.ne.b32 p, %34, 0;\nwgmma.mma_async.sync.aligned.m64n64k16.f32.bf16.bf16 {%0,%1,%2,%3,%4,%5,%6,%7,%8,%9,%10,%11,%12,%13,%14,%15,%16,%17,%18,%19,%20,%21,%22,%23,%24,%25,%26,%27,%28,%29,%30,%31}, %32, %33, p, 1, 1, 1, 0;\n}\n"
   : "+f"(d[0]),"+f"(d[1]),"+f"(d[2]),"+f"(d[3]),"+f"(d[4]),"+f"(d[5]),"+f"(d[6]),"+f"(d[7]),"+f"(d[8]),"+f"(d[9]),"+f"(d[10]),"+f"(d[11]),"+f"(d[12]),"+f"(d[13]),"+f"(d[14]),"+f"(d[15]),"+f"(d[16]),"+f"(d[17]),"+f"(d[18]),"+f"(d[19]),"+f"(d[20]),"+f"(d[21]),"+f"(d[22]),"+f"(d[23]),"+f"(d[24]),"+f"(d[25]),"+f"(d[26]),"+f"(d[27]),"+f"(d[28]),"+f"(d[29]),"+f"(d[30]),"+f"(d[31])
   : "l"(da), "l"(db), "r"(sd));
}
template<> __device__ __forceinline__ void wgmma_ss<64,0,1>(float* d, uint64_t da, uint64_t db, int sd) {
  asm volatile("{\n.reg .pred p;\nsetp.ne.b32 p, %34, 0;\nwgmma.mma_async.sync.aligned.m64n64k16.f32.bf16.bf16 {%0,%1,%2,%3,%4,%5,%6,%7,%8,%9,%10,%11,%12,%13,%14,%15,%16,%17,%18,%19,%20,%21,%22,%23,%24,%25,%26,%27,%28,%29,%30,%31}, %32, %33, p, 1, 1, 0, 1;\n}\n"
   : "+f"(d[0]),"+f"(d[1]),"+f"(d[2]),"+f"(d[3]),"+f"(d[4]),"+f"(d[5]),"+f"(d[6]),"+f"(d[7]),"+f"(d[8]),"+f"(d[9]),"+f"(d[10]),"+f"(d[11]),"+f"(d[12]),"+f"(d[13]),"+f"(d[14]),"+f"(d[15]),"+f"(d[16]),"+f"(d[17]),"+f"(d[18]),"+f"(d[19]),"+f"(d[20]),"+f"(d[21]),"+f"(d[22]),"+f"(d[23]),"+f"(d[24]),"+f"(d[25]),"+f"(d[26]),"+f"(d[27]),"+f"(d[28]),"+f"(d[29]),"+f"(d[30]),"+f"(d[31])
   : "l"(da), "l"(db), "r"(sd));
}
template<> __device__ __forceinline__ void wgmma_ss<192,0,1>(float* d, uint64_t da, uint64_t db, int sd) {
  asm volatile("{\n.reg .pred p;\nsetp.ne.b32 p, %98, 0;\nwgmma.mma_async.sync.aligned.m64n192k16.f32.bf16.bf16 {%0,%1,%2,%3,%4,%5,%6,%7,%8,%9,%10,%11,%12,%13,%14,%15,%16,%17,%18,%19,%20,%21,%22,%23,%24,%25,%26,%27,%28,%29,%30,%31,%32,%33,%34,%35,%36,%37,%38,%39,%40,%41,%42,%43,%44,%45,%46,%47,%48,%49,%50,%51,%52,%53,%54,%55,%56,%57,%58,%59,%60,%61,%62,%63,%64,%65,%66,%67,%68,%69,%70,%71,%72,%73,%74,%75,%76,%77,%78,%79,%80,%81,%82,%83,%84,%85,%86,%87,%88,%89,%90,%91,%92,%93,%94,%95}, %96, %97, p, 1, 1, 0, 1;\n}\n"
   : "+f"(d[0]),"+f"(d[1]),"+f"(d[2]),"+f"(d[3]),"+f"(d[4]),"+f"(d[5]),"+f"(d[6]),"+f"(d[7]),"+f"(d[8]),"+f"(d[9]),"+f"(d[10]),"+f"(d[11]),"+f"(d[12]),"+f"(d[13]),"+f"(d[14]),"+f"(d[15]),"+f"(d[16]),"+f"(d[17]),"+f"(d[18]),"+f"(d[19]),"+f"(d[20]),"+f"(d[21]),"+f"(d[22]),"+f"(d[23]),"+f"(d[24]),"+f"(d[25]),"+f"(d[26]),"+f"(d[27]),"+f"(d[28]),"+f"(d[29]),"+f"(d[30]),"+f"(d[31]),"+f"(d[32]),"+f"(d[33]),"+f"(d[34]),"+f"(d[35]),"+f"(d[36]),"+f"(d[37]),"+f"(d[38]),"+f"(d[39]),"+f"(d[40]),"+f"(d[41]),"+f"(d[42]),"+f"(d[43]),"+f"(d[44]),"+f"(d[45]),"+f"(d[46]),"+f"(d[47]),"+f"(d[48]),"+f"(d[49]),"+f"(d[50]),"+f"(d[51]),"+f"(d[52]),"+f"(d[53]),"+f"(d[54]),"+f"(d[55]),"+f"(d[56]),"+f"(d[57]),"+f"(d[58]),"+f"(d[59]),"+f"(d[60]),"+f"(d[61]),"+f"(d[62]),"+f"(d[63]),"+f"(d[64]),"+f"(d[65]),"+f"(d[66]),"+f"(d[67]),"+f"(d[68]),"+f"(d[69]),"+f"(d[70]),"+f"(d[71]),"+f"(d[72]),"+f"(d[73]),"+f"(d[74]),"+f"(d[75]),"+f"(d[76]),"+f"(d[77]),"+f"(d[78]),"+f"(d[79]),"+f"(d[80]),"+f"(d[81]),"+f"(d[82]),"+f"(d[83]),"+f"(d[84]),"+f"(d[85]),"+f"(d[86]),"+f"(d[87]),"+f"(d[88]),"+f"(d[89]),"+f"(d[90]),"+f"(d[91]),"+f"(d[92]),"+f"(d[93]),"+f"(d[94]),"+f"(d[95])
   : "l"(da), "l"(db), "r"(sd));
}
template<> __device__ __forceinline__ void wgmma_ss<192,1,1>(float* d, uint64_t da, uint64_t db, int sd) {
  asm volatile("{\n.reg .pred p;\nsetp.ne.b32 p, %98, 0;\nwgmma.mma_async.sync.aligned.m64n192k16.f32.bf16.bf16 {%0,%1,%2,%3,%4,%5,%6,%7,%8,%9,%10,%11,%12,%13,%14,%15,%16,%17,%18,%19,%20,%21,%22,%23,%24,%25,%26,%27,%28,%29,%30,%31,%32,%33,%34,%35,%36,%37,%38,%39,%40,%41,%42,%43,%44,%45,%46,%47,%48,%49,%50,%51,%52,%53,%54,%55,%56,%57,%58,%59,%60,%61,%62,%63,%64,%65,%66,%67,%68,%69,%70,%71,%72,%73,%74,%75,%76,%77,%78,%79,%80,%81,%82,%83,%84,%85,%86,%87,%88,%89,%90,%91,%92,%93,%94,%95}, %96, %97, p, 1, 1, 1, 1;\n}\n"
   : "+f"(d[0]),"+f"(d[1]),"+f"(d[2]),"+f"(d[3]),"+f"(d[4]),"+f"(d[5]),"+f"(d[6]),"+f"(d[7]),"+f"(d[8]),"+f"(d[9]),"+f"(d[10]),"+f"(d[11]),"+f"(d[12]),"+f"(d[13]),"+f"(d[14]),"+f"(d[15]),"+f"(d[16]),"+f"(d[17]),"+f"(d[18]),"+f"(d[19]),"+f"(d[20]),"+f"(d[21]),"+f"(d[22]),"+f"(d[23]),"+f"(d[24]),"+f"(d[25]),"+f"(d[26]),"+f"(d[27]),"+f"(d[28]),"+f"(d[29]),"+f"(d[30]),"+f"(d[31]),"+f"(d[32]),"+f"(d[33]),"+f"(d[34]),"+f"(d[35]),"+f"(d[36]),"+f"(d[37]),"+f"(d[38]),"+f"(d[39]),"+f"(d[40]),"+f"(d[41]),"+f"(d[42]),"+f"(d[43]),"+f"(d[44]),"+f"(d[45]),"+f"(d[46]),"+f"(d[47]),"+f"(d[48]),"+f"(d[49]),"+f"(d[50]),"+f"(d[51]),"+f"(d[52]),"+f"(d[53]),"+f"(d[54]),"+f"(d[55]),"+f"(d[56]),"+f"(d[57]),"+f"(d[58]),"+f"(d[59]),"+f"(d[60]),"+f"(d[61]),"+f"(d[62]),"+f"(d[63]),"+f"(d[64]),"+f"(d[65]),"+f"(d[66]),"+f"(d[67]),"+f"(d[68]),"+f"(d[69]),"+f"(d[70]),"+f"(d[71]),"+f"(d[72]),"+f"(d[73]),"+f"(d[74]),"+f"(d[75]),"+f"(d[76]),"+f"(d[77]),"+f"(d[78]),"+f"(d[79]),"+f"(d[80]),"+f"(d[81]),"+f"(d[82]),"+f"(d[83]),"+f"(d[84]),"+f"(d[85]),"+f"(d[86]),"+f"(d[87]),"+f"(d[88]),"+f"(d[89]),"+f"(d[90]),"+f"(d[91]),"+f"(d[92]),"+f"(d[93]),"+f"(d[94]),"+f"(d[95])
   : "l"(da), "l"(db), "r"(sd));
}

template <bool TR>
__device__ __forceinline__ void gemm_section(float* acc, float& mean0, float& mean1, float& rstd0, float& rstd1,
                                             uint32_t sb, int blk, int hg, int wg, int w, int lane) {
  constexpr int layer = TR ? 1 : 0;
  constexpr int TURN = TR ? TURN1 : TURN0;
  constexpr int LSTAT = TURN < 4 ? TURN - 1 : 3;
  const uint32_t bar = sb + SM_BAR;
  const int g = lane >> 2, t = lane & 3;
  const bool leader = (w == 0) && (lane == 0);
  const int statpos = hg < 3 ? 1 : wg ? LSTAT : TR ? 3 : 2;
  const bool copy = hg >= 3 && wg == 0;
  const int cut = wg ? TURN : 4;
  auto wait_full = [&](int c) {
    mbar_wait(bar + 8 * (B_XF + 8 * wg + c), layer);
    mbar_wait(bar + 8 * (B_WF + c), layer);
  };
  auto peek = [&](int c) {
    const bool x = mbar_test(bar + 8 * (B_XF + 8 * wg + c), layer), y = mbar_test(bar + 8 * (B_WF + c), layer);
    return x && y;
  };
  const uint64_t da0 = mkdesc(sb, TR ? 8192 : 16, 1024, 1), db0 = mkdesc(sb, 8192, 1024, 1);
  uint32_t xt = wg ? 0xfedcba98u : 0x21043210u;
  uint64_t wt = 0x0816131005161310ull;
  uint64_t da = da0 + ((xt & 15) << 9), db = db0 + (16 << 9);
  auto issue = [&](int c, int first) {
    wg_fence();
#pragma unroll
    for (int ks = 0; ks < 4; ks++) wgmma_ss<192, TR ? 1 : 0, 1>(acc, da + (TR ? ks * 128 : ks * 2), db + ks * 128, !first || ks != 0);
    wg_commit();
    xt >>= 4; wt >>= 8;
    da = da0 + ((xt & 15) << 9); db = db0 + (((uint32_t)wt & 31) << 9);
  };
  TSG(0);
  wait_full(0);
  TSG(1);
  bool ready = peek(1);
  issue(0, 1);
  TSW(0);
#pragma unroll 1
  for (int c = 1; c < cut; c++) {
    if (!ready) wait_full(c);
    issue(c, 0);
    ready = peek(c + 1);
    wg_wait<1>();
    if (leader) mbar_arrive(bar + 8 * (B_DN + 8 * wg + c - 1));
    if (wg == 1 && c == cut - 1) {
      wg_wait<0>();
      if (leader) mbar_arrive(bar + 8 * (B_DN + 8 + c));
    }
    if (c == statpos) {
      mbar_wait(bar + 8 * (copy ? B_SC : B_XF + 8 * wg + hg), layer);
      uint32_t A[16];
      const uint32_t xb = sb + (copy ? P_R : 8 * wg + hg) * PG;
#pragma unroll
      for (int ks = 0; ks < 4; ks++) {
        if (!TR) {
          const int row = 16 * w + (lane & 15), kc = 2 * ks + (lane >> 4);
          ldsm4(&A[4 * ks], xb + row * 128 + ((kc ^ (row & 7)) << 4));
        } else {
          const int k = 16 * ks + (lane & 7) + 8 * (lane >> 4), pc = 2 * w + ((lane >> 3) & 1);
          ldsm4t(&A[4 * ks], xb + k * 128 + ((pc ^ (k & 7)) << 4));
        }
      }
      float s0 = 0.f, q0 = 0.f, s1 = 0.f, q1 = 0.f;
#pragma unroll
      for (int i = 0; i < 16; i += 2) {
        const float a = bf_lo(A[i]), b = bf_hi(A[i]), c_ = bf_lo(A[i + 1]), d = bf_hi(A[i + 1]);
        s0 += a + b; q0 = fmaf(a, a, q0); q0 = fmaf(b, b, q0);
        s1 += c_ + d; q1 = fmaf(c_, c_, q1); q1 = fmaf(d, d, q1);
      }
#pragma unroll
      for (int o = 1; o <= 2; o <<= 1) {
        s0 += __shfl_xor_sync(~0u, s0, o); q0 += __shfl_xor_sync(~0u, q0, o);
        s1 += __shfl_xor_sync(~0u, s1, o); q1 += __shfl_xor_sync(~0u, q1, o);
      }
      if (t < 2)
        asm volatile("red.relaxed.gpu.global.add.v4.f32 [%0], {%1,%2,%3,%4};" ::"l"(g_rows + layer * LSEQ + blk * 64 + 16 * w + g + 8 * t),
                     "f"(t ? s1 : s0), "f"(t ? q1 : q0), "f"(1.f), "f"(0.f) : "memory");
    }
  }
  if (wg == 1) {
#pragma unroll 1
    for (int c = cut; c < 8; c++) wait_full(c);
    ready = true;
    bar_sync(5, 256);
  }
#pragma unroll 1
  for (int c = cut; c < 8; c++) {
    if (!ready) wait_full(c);
    issue(c, 0);
    if (wg == 1) {
      wg_wait<2>();
      if (leader && c >= cut + 2) mbar_arrive(bar + 8 * (B_DN + 8 + c - 2));
    } else if (c == 7) {
      bar_arrive(5, 256);
    } else {
      ready = peek(c + 1);
      wg_wait<1>();
      if (leader) mbar_arrive(bar + 8 * (B_DN + c - 1));
    }
  }
  mbar_wait(bar + 8 * (B_LN + wg), layer);
  const float4 ln = lds128f(sb + ln_off(wg) + (8 * w + g) * 16);
  mean0 = ln.x; rstd0 = ln.y; mean1 = ln.z; rstd1 = ln.w;
  wg_wait<0>();
  acc_fence<96>(acc);
  if (leader) mbar_arrive(bar + 8 * (B_DN + 8 * wg + 7));
}

__device__ __forceinline__ void attn_phase(const Params& p, uint32_t sb, int layer, int rb, int hg, int wg, int w) {
  const int lane = opaque_tid() & 31;
  const int g = lane >> 2, t = lane & 3;
  const uint32_t bar = sb + SM_BAR;
  const int blk = 16 * wg + rb;
  float acc[96];
  float2 cs[24];
  float mean0, mean1, rstd0, rstd1;
  if (layer) gemm_section<true>(acc, mean0, mean1, rstd0, rstd1, sb, blk, hg, wg, w, lane);
  else gemm_section<false>(acc, mean0, mean1, rstd0, rstd1, sb, blk, hg, wg, w, lane);
  TSW(1);
#pragma unroll
  for (int j = 8; j < 24; j++) cs[j] = lds64f(sb + SM_CS + 4 * (8 * j + 2 * t));
  const uint32_t kvx = sb + (wg ? 22 : 0) * PG;

  uint32_t kb[4][8], vb[4][8], qa[4][4];
  {
    const float nm0 = -mean0 * rstd0, nm1 = -mean1 * rstd1;
    const int st_row = 16 * w + (lane & 7) + 8 * ((lane >> 3) & 1);
    const uint32_t st_base = kvx + st_row * 256;
    const bool sender = (w == 3 && blk < 31);
    uint4* halo = &g_halo[(blk * 8 + hg) * 256 + lane];
    uint32_t r[4][2][4];
#pragma unroll
    for (int h = 0; h < 4; h++) {
#pragma unroll
      for (int kv = 0; kv < 2; kv++) {
#pragma unroll
        for (int dh = 0; dh < 2; dh++) {
          const int j = 8 + kv * 8 + 2 * h + dh;
          const float2 c2 = cs[j];
          const float v0 = fmaf(acc[4 * j + 0], rstd0, nm0 * c2.x), v1 = fmaf(acc[4 * j + 1], rstd0, nm0 * c2.y);
          const float v2 = fmaf(acc[4 * j + 2], rstd1, nm1 * c2.x), v3 = fmaf(acc[4 * j + 3], rstd1, nm1 * c2.y);
          r[h][kv][2 * dh] = packbf(v0, v1);
          r[h][kv][2 * dh + 1] = packbf(v2, v3);
        }
      }
      if (sender) {
        stg128(halo + (2 * h) * 32, make_uint4(r[h][0][0], r[h][0][2], r[h][0][1], r[h][0][3]));
        stg128(halo + (2 * h + 1) * 32, make_uint4(r[h][1][0], r[h][1][1], r[h][1][2], r[h][1][3]));
      }
    }
#pragma unroll
    for (int j = 0; j < 8; j++) cs[j] = lds64f(sb + SM_CS + 4 * (8 * j + 2 * t));
    mbar_wait(bar + 8 * (B_DN + 7), layer);
#pragma unroll
    for (int h = 0; h < 4; h++) {
#pragma unroll
      for (int kv = 0; kv < 2; kv++) {
        const int chunk = 4 * h + 2 * kv + (lane >> 4);
        if (w < 3) stsm4(st_base + (((chunk & 8) | ((chunk ^ st_row) & 7)) << 4), r[h][kv][0], r[h][kv][1], r[h][kv][2], r[h][kv][3]);
      }
      kb[h][4] = r[h][0][0]; kb[h][5] = r[h][0][2]; kb[h][6] = r[h][0][1]; kb[h][7] = r[h][0][3];
      vb[h][4] = movm_t(r[h][1][0]); vb[h][5] = movm_t(r[h][1][1]); vb[h][6] = movm_t(r[h][1][2]); vb[h][7] = movm_t(r[h][1][3]);
    }
#pragma unroll
    for (int h = 0; h < 4; h++) {
#pragma unroll
      for (int dh = 0; dh < 2; dh++) {
        const int j = 2 * h + dh;
        const float2 c2 = cs[j];
        qa[h][2 * dh] = packbf(fmaf(-mean0, c2.x, acc[4 * j + 0]), fmaf(-mean0, c2.y, acc[4 * j + 1]));
        qa[h][2 * dh + 1] = packbf(fmaf(-mean1, c2.x, acc[4 * j + 2]), fmaf(-mean1, c2.y, acc[4 * j + 3]));
      }
    }
  }
  bar_sync(2 + wg, 128);
  TSW(2);
  {
    const uint32_t prev_base = kvx + (16 * w - 16) * 256;
    const int mi = lane >> 3;
    const int r = 8 * (mi >> 1) + (lane & 7), r2 = 8 * (mi & 1) + (lane & 7);
    if (w != 0) {
#pragma unroll
      for (int h = 0; h < 4; h++) {
        const int ch = 4 * h + (mi & 1), ch2 = 4 * h + 2 + (mi >> 1);
        ldsm4(&kb[h][0], prev_base + r * 256 + (((ch & 8) | ((ch ^ r) & 7)) << 4));
        ldsm4t(&vb[h][0], prev_base + r2 * 256 + (((ch2 & 8) | ((ch2 ^ r2) & 7)) << 4));
      }
    } else if (blk > 0) {
      uint4* src = &g_halo[((blk - 1) * 8 + hg) * 256 + lane];
      uint4 hv[8];
      int it = 0;
      bool ok;
      do {
        ok = true;
#pragma unroll
        for (int i = 0; i < 8; i++) hv[i] = ld_tagged(src + i * 32);
#pragma unroll
        for (int i = 0; i < 8; i++) ok = ok && hv[i].x != UNSET;
      } while (!__all_sync(~0u, ok) && ++it < (1 << 20));
      if (layer == 0) {
#pragma unroll
        for (int i = 0; i < 2; i++) stg128(src + i * 128 + (lane >> 1) * 6, make_uint4(UNSET, UNSET, UNSET, UNSET));
      }
#pragma unroll
      for (int h = 0; h < 4; h++) {
        kb[h][0] = hv[2 * h].x; kb[h][1] = hv[2 * h].y; kb[h][2] = hv[2 * h].z; kb[h][3] = hv[2 * h].w;
        vb[h][0] = movm_t(hv[2 * h + 1].x); vb[h][1] = movm_t(hv[2 * h + 1].y);
        vb[h][2] = movm_t(hv[2 * h + 1].z); vb[h][3] = movm_t(hv[2 * h + 1].w);
      }
    } else {
#pragma unroll
      for (int h = 0; h < 4; h++)
#pragma unroll
        for (int k = 0; k < 4; k++) kb[h][k] = vb[h][k] = 0u;
    }
    TSW(3);
  }
  mbar_wait(bar + 8 * (B_DN + 15), layer);
  TSW(4);

  const bool first = (blk == 0 && w == 0);
  const int e = t - (g >> 1);
  const bool par = g & 1, epos = e >= 1;
  const uint32_t pmask = par ? 0xffff0000u : 0x0000ffffu;
  const uint32_t mB0 = epos ? pmask : 0u, mB1 = epos ? 0u : pmask;
  const float cl2 = 0.25f * 1.4426950408889634f;
  const float sc0 = rstd0 * cl2, sc1 = rstd1 * cl2;
  const float NEG = -INFINITY;
  float vA0[4], vB0[4], vA1[4], vB1[4];
#pragma unroll
  for (int h = 0; h < 4; h++) {
    float S[4][4];
#pragma unroll
    for (int j = 0; j < 4; j++) {
      S[j][0] = S[j][1] = S[j][2] = S[j][3] = 0.f;
      mma_bf16(S[j], qa[h], kb[h][2 * j], kb[h][2 * j + 1]);
    }
    vA0[h] = par ? S[1][1] : S[1][0];
    vB0[h] = epos ? (par ? S[0][1] : S[0][0]) : (par ? S[2][1] : S[2][0]);
    vA1[h] = par ? S[2][3] : S[2][2];
    vB1[h] = epos ? (par ? S[1][3] : S[1][2]) : (par ? S[3][3] : S[3][2]);
    if (first) { vA0[h] = NEG; if (epos) { vB0[h] = NEG; vB1[h] = NEG; } }
  }
  float m0[4], m1[4];
#pragma unroll
  for (int h = 0; h < 4; h++) { m0[h] = fmaxf(vA0[h], vB0[h]); m1[h] = fmaxf(vA1[h], vB1[h]); }
#pragma unroll
  for (int o = 1; o <= 2; o <<= 1) {
#pragma unroll
    for (int h = 0; h < 4; h++) {
      m0[h] = fmaxf(m0[h], __shfl_xor_sync(~0u, m0[h], o));
      m1[h] = fmaxf(m1[h], __shfl_xor_sync(~0u, m1[h], o));
    }
  }
  float O0[4][4], O1[4][4], Z[4][4];
#pragma unroll
  for (int h = 0; h < 4; h++) {
    const float mm0 = -m0[h] * sc0, mm1 = -m1[h] * sc1;
    const float pA0 = ex2(fmaf(vA0[h], sc0, mm0)), pB0 = ex2(fmaf(vB0[h], sc0, mm0));
    const float pA1 = ex2(fmaf(vA1[h], sc1, mm1)), pB1 = ex2(fmaf(vB1[h], sc1, mm1));
    const uint32_t hA0 = packbf(pA0, pA0), hB0 = packbf(pB0, pB0), hA1 = packbf(pA1, pA1), hB1 = packbf(pB1, pB1);
    const uint32_t P0[4] = {hB0 & mB0, 0u, hA0 & pmask, hB1 & mB0};
    const uint32_t P1[4] = {hB0 & mB1, hA1 & pmask, 0u, hB1 & mB1};
#pragma unroll
    for (int k = 0; k < 4; k++) O0[h][k] = O1[h][k] = Z[h][k] = 0.f;
    mma_bf16(O0[h], P0, vb[h][0], vb[h][1]); mma_bf16(O1[h], P0, vb[h][2], vb[h][3]); mma_bf16(Z[h], P0, 0x3f803f80u, 0x3f803f80u);
    mma_bf16(O0[h], P1, vb[h][4], vb[h][5]); mma_bf16(O1[h], P1, vb[h][6], vb[h][7]); mma_bf16(Z[h], P1, 0x3f803f80u, 0x3f803f80u);
  }
  if (lane == 0) mbar_arrive(bar + 8 * (B_OST + wg));
  uint4* op = (uint4*)g_O + ((layer * 32 + blk) * 8 + hg) * 512 + 64 * t + 16 * w + g;
#pragma unroll
  for (int h = 0; h < 4; h += 2) {
    const float i0 = rcp_approx(Z[h][0]), i1 = rcp_approx(Z[h][2]), j0 = rcp_approx(Z[h + 1][0]), j1 = rcp_approx(Z[h + 1][2]);
    stg128(op + 128 * h, make_uint4(packbf(O0[h][0] * i0, O0[h][1] * i0), packbf(O1[h][0] * i0, O1[h][1] * i0),
                                   packbf(O0[h + 1][0] * j0, O0[h + 1][1] * j0), packbf(O1[h + 1][0] * j0, O1[h + 1][1] * j0)));
    stg128(op + 128 * h + 8, make_uint4(packbf(O0[h][2] * i1, O0[h][3] * i1), packbf(O1[h][2] * i1, O1[h][3] * i1),
                                            packbf(O0[h + 1][2] * j1, O0[h + 1][3] * j1), packbf(O1[h + 1][2] * j1, O1[h + 1][3] * j1)));
  }
  TSW(5);
  __syncwarp();
  if (lane == 0) red_relaxed(&g_cnt[(C_O + layer * 32 + blk) * 32]);
  TSW(6);
}

__device__ __forceinline__ void proj_phase(const Params& p, uint32_t sb, int layer, int rb, int q, int& rtp) {
  const int lane = opaque_tid() & 31;
  const int wg = __shfl_sync(~0u, opaque_tid() >> 7, 0), w = __shfl_sync(~0u, (opaque_tid() >> 5) & 3, 0);
  const bool TR = layer != 0;
  const int t = lane & 3;
  const uint32_t bar = sb + SM_BAR;
  const uint32_t rbx = sb + (P_R + wg) * PG;
  const uint32_t rsrc = sb + (wg ? 2 : P_R) * PG;
  const int blk = 16 * wg + rb;
  mbar_wait(bar + 8 * (B_RF + wg), layer);
  if (layer) mbar_wait(bar + 8 * B_RS, 0);
  mbar_wait(bar + 8 * B_WOF, layer);
  fence_async_global();
  const uint32_t stg = sb + (wg ? SM_KGT : SM_STG);
  bool clean = false;
#pragma unroll 1
  for (int attempt = 0; attempt < MAX_RETRY; attempt++) {
  uint32_t res[16];
  if (!TR) {
#pragma unroll
    for (int j = 0; j < 8; j += 2) {
      const int mi = lane >> 3;
      const int row = 16 * w + (lane & 7) + 8 * (mi & 1), ch = j + (mi >> 1);
      ldsm4(&res[2 * j], rsrc + row * 128 + ((ch ^ (row & 7)) << 4));
    }
  } else {
#pragma unroll
    for (int j = 0; j < 8; j += 2) {
      const int mi = lane >> 3;
      const int line = 8 * (j + (mi >> 1)) + (lane & 7), pc = 2 * w + (mi & 1);
      ldsm4t(&res[2 * j], rsrc + line * 128 + ((pc ^ (line & 7)) << 4));
    }
  }
  float acc[32];
#pragma unroll
  for (int j = 0; j < 16; j++) { acc[2 * j] = bf_lo(res[j]); acc[2 * j + 1] = bf_hi(res[j]); }
  acc_fence<32>(acc);
  if (wg) mbar_wait(bar + 8 * B_PST, layer);
  const int wg2 = __shfl_sync(~0u, opaque_tid() >> 7, 0);
  const uint64_t da0 = mkdesc(sb, 1024, 128, 0), db0 = mkdesc(sb, 8192, 1024, 1);
#pragma unroll
  for (int c = 0; c < 4; c++) {
    mbar_wait(bar + 8 * (B_OF + 4 * wg + c), layer);
    if (c == 0) TSW(7);
    const uint64_t da = da0 + (uint32_t)(o_page(wg2, c) * 512);
    wg_fence();
#pragma unroll
    for (int ks = 0; ks < 8; ks++) wgmma_ss<64, 0, 1>(acc, da + ks * 128, db0 + wo_page(2 * c + (ks >> 2)) * 512 + (ks & 3) * 128, 1);
    wg_commit();
  }
  if (wg) mbar_wait(bar + 8 * B_KG, 0);
  wg_wait<0>();
  acc_fence<32>(acc);
  TSW(8);
  if (!clean) {
    const float chk = acc[0] + acc[2];
    clean = __all_sync(~0u, chk == chk);
    if (clean && lane == 0) mbar_arrive(bar + 8 * (B_PDONE + wg));
  }
  float s0 = 0.f, q0 = 0.f, s1 = 0.f, q1 = 0.f;
  uint32_t o[16];
#pragma unroll
  for (int j = 0; j < 8; j++) {
    const float a = acc[4 * j], b = acc[4 * j + 1], c = acc[4 * j + 2], d = acc[4 * j + 3];
    o[2 * j] = packbf(a, b);
    o[2 * j + 1] = packbf(c, d);
    s0 += a + b; q0 = fmaf(a, a, q0); q0 = fmaf(b, b, q0);
    s1 += c + d; q1 = fmaf(c, c, q1); q1 = fmaf(d, d, q1);
  }
#pragma unroll
  for (int j = 0; j < 8; j += 2) {
    const int mi = lane >> 3;
    const int line = 8 * (j + (mi >> 1)) + (lane & 7), pc = 2 * w + (mi & 1);
    stsm4t(rbx + line * 128 + ((pc ^ (line & 7)) << 4), o[2 * j], o[2 * j + 1], o[2 * j + 2], o[2 * j + 3]);
  }
#pragma unroll
  for (int o2 = 1; o2 <= 2; o2 <<= 1) {
    s0 += __shfl_xor_sync(~0u, s0, o2); q0 += __shfl_xor_sync(~0u, q0, o2);
    s1 += __shfl_xor_sync(~0u, s1, o2); q1 += __shfl_xor_sync(~0u, q1, o2);
  }
  {
    const int i = 2 * (lane >> 2) + (t & 1), k = (i * 11) >> 5;
    const float v = (t == 0) ? s0 : (t == 1) ? q0 : (t == 2) ? s1 : q1;
    sts32f(stg + k * 128 + (2 * w + (t >> 1)) * 16 + (i - 3 * k) * 4, v);
  }
  TSW(9);
  fence_async_smem();
  if (!bar_or(2 + wg, 128, !clean)) break;
  bool unset = false;
#pragma unroll
  for (int i = 0; i < 4; i++) unset |= lds32(sb + o_page(wg, i) * PG + (32 * w + lane) * 128) == UNSET;
  if (!bar_or(2 + wg, 128, unset)) break;
  if (w == 0 && elect_one()) {
    fence_async_smem();
    mbar_expect(bar + 8 * (B_RT + wg), 9 * PG);
    if (layer == 0) tma_ld(rsrc, &p.mapX, q * 64, blk * 64, bar + 8 * (B_RT + wg));
    else tma_ld(rsrc, &p.mapXT, blk * 64, DM + q * 64, bar + 8 * (B_RT + wg));
#pragma unroll 1
    for (int c = 0; c < 4; c++) bulk_ld(sb + o_page(wg, c) * PG, g_O + ((layer * 32 + blk) * 4 + c) * PG, 2 * PG, bar + 8 * (B_RT + wg));
  }
  mbar_wait(bar + 8 * (B_RT + wg), rtp);
  rtp ^= 1;
  RETRY(0);
  }
  if (!clean && lane == 0) mbar_arrive(bar + 8 * (B_PDONE + wg));
  if (w == 0 && elect_one()) {
    tma_st(&p.mapXT, blk * 64, (2 * layer) * DM + q * 64, rbx);
    bulk_red_add_f32(g_stats + (layer * 32 + blk) * 192, stg, 768);
    bulk_commit();
    red_relaxed(&g_cnt[(C_G + 2 * layer + wg) * 32]);
  }
  TSW(10);
}

__device__ __forceinline__ void conv_load(uint32_t* A, uint32_t pe) {
#pragma unroll
  for (int m = 0; m < 17; m++) {
    A[4 * m + 2] = lds32(pe + 4 * (64 * m - 8));
    A[4 * m + 0] = lds32(pe + 4 * (64 * m));
    A[4 * m + 1] = lds32(pe + 4 * (64 * m + 8));
    asm volatile("mov.b32 %0, %1;" : "=r"(A[4 * m + 3]) : "r"(A[4 * m + 0]));
  }
}
template <int M> __device__ __forceinline__ void conv_tri(float* acc, const uint32_t* A, uint64_t d) {
  if constexpr (M < 16) {
    wgmma_rs<64 - 8 * (M / 2), 0>(acc, A + 4 * M, d + (uint64_t)(64 + 4 * M), M != 0);
    conv_tri<M + 1>(acc, A, d);
  }
}
__device__ __forceinline__ void conv_mma0(float* acc, const uint32_t* A, uint64_t d) {
  wg_fence();
  conv_tri<0>(acc, A, d);
  wg_commit();
}
__device__ __forceinline__ void conv_mma1(float* acc, const uint32_t* A, uint64_t d, uint64_t ds, uint64_t df) {
  wg_fence();
#pragma unroll
  for (int m = 0; m < 17; m++) wgmma_rs<64, 0>(acc, A + 4 * m, d + (uint64_t)(4 * m), m != 0);
  wgmma_ss<64, 1, 0>(acc, ds, df, 1);
  wgmma_ss<64, 1, 0>(acc, ds + 128, df + 128, 1);
  wg_commit();
}
__device__ __forceinline__ void conv_store(float* acc, uint32_t pb, uint32_t over, int w) {
  acc_fence<32>(acc);
  const int l = opaque_tid() & 31, mt = l >> 3;
  int c = 2 * (63 - 8 * (mt >> 1) - (l & 7) + w) + (mt & 1);
  c ^= (c >> 3) & 1;
  const uint32_t a0 = pb + c * 16;
#pragma unroll
  for (int j = 0; j < 8; j += 2)
    stsm4t(j == 0 ? (c < 128 ? a0 : over + (c - 128) * 16) : a0 - 256 * j, packbf(acc[4 * j], acc[4 * j + 1]), packbf(acc[4 * j + 2], acc[4 * j + 3]),
           packbf(acc[4 * j + 4], acc[4 * j + 5]), packbf(acc[4 * j + 6], acc[4 * j + 7]));
}
__device__ __forceinline__ void conv_sums(uint32_t sb, int lc, int ht) {
  const int m = ht - 1;
  uint4 v[2][3];
#pragma unroll
  for (int c = 0; c < 2; c++)
#pragma unroll
    for (int k = 0; k < 3; k++) {
      const int mm = m - 1 + k;
      v[c][k] = lds128(sb + cv_u(lc + c) + (mm >= 0 ? (mm & 1) * CV_UH + (127 - (mm >> 1)) * 16 : 128 * 16));
    }
  const int ce = m + 2, co = m + 1;
#pragma unroll
  for (int c = 0; c < 2; c++) {
    const uint32_t x[8] = {v[c][0].z, v[c][0].w, v[c][1].x, v[c][1].y, v[c][1].z, v[c][1].w, v[c][2].x, v[c][2].y};
    float pv[16];
#pragma unroll
    for (int k = 0; k < 8; k++) { pv[2 * k] = bf_lo(x[k]); pv[2 * k + 1] = bf_hi(x[k]); }
    float t2[15], t4[13], s9[8], s7[8];
#pragma unroll
    for (int i = 0; i < 15; i++) t2[i] = pv[i] + pv[i + 1];
#pragma unroll
    for (int i = 0; i < 13; i++) t4[i] = t2[i] + t2[i + 2];
#pragma unroll
    for (int i = 0; i < 8; i++) {
      s9[i] = (t4[i] + t4[i + 4]) + pv[i + 8];
      s7[i] = (t4[i + 1] + t2[i + 5]) + pv[i + 7];
    }
    const uint4 e4 = make_uint4(packbf(s9[0], s9[1]), packbf(s9[2], s9[3]), packbf(s9[4], s9[5]), packbf(s9[6], s9[7]));
    if (ce < 128) sts128(sb + cv_se(lc + c) + ((ce ^ ((ce >> 3) & 7)) << 4), e4);
    else sts128(sb + cv_se(lc + c), make_uint4(0, 0, 0, 0));
    sts128(sb + cv_so(lc + c) + ((co ^ ((co >> 3) & 7)) << 4),
           make_uint4(packbf(s7[0], s7[1]), packbf(s7[2], s7[3]), packbf(s7[4], s7[5]), packbf(s7[6], s7[7])));
  }
}

template <int HALF, int NCH, int STEP = 1>
__device__ __forceinline__ void conv_epi(uint32_t sb, bf16* out, int lc, int c) {
  uint4 v[NCH][4], xr[NCH];
  const uint32_t sw = (c ^ ((c >> 3) & 1)) * 16;
#pragma unroll
  for (int u = 0; u < NCH; u++) {
#pragma unroll
    for (int k = 0; k < 4; k++) v[u][k] = lds128(sb + (HALF ? cv_pb1(lc + STEP * u, k) : cv_pb0(lc + STEP * u, k)) + sw);
    xr[u] = lds128(sb + cv_x(HALF, lc + STEP * u) + c * 16);
  }
#pragma unroll
  for (int u = 0; u < NCH; u++) {
    uint4 o;
    o.x = hadd2(xr[u].x, hadd2(hadd2(v[u][0].x, v[u][1].x), hadd2(v[u][2].x, v[u][3].x)));
    o.y = hadd2(xr[u].y, hadd2(hadd2(v[u][0].y, v[u][1].y), hadd2(v[u][2].y, v[u][3].y)));
    o.z = hadd2(xr[u].z, hadd2(hadd2(v[u][0].z, v[u][1].z), hadd2(v[u][2].z, v[u][3].z)));
    o.w = hadd2(xr[u].w, hadd2(hadd2(v[u][0].w, v[u][1].w), hadd2(v[u][2].w, v[u][3].w)));
    stg128(out + cv_chan(0, lc + STEP * u) * LSEQ + HALF * 1024 + c * 8, o);
  }
}

__device__ __forceinline__ bool prep_valid(const uint4 (&st)[6], const uint4 (&xr)[4]) {
  const uint32_t n = __float_as_uint(8.f);
  return st[0].w == n && st[1].w == n && st[2].w == n && st[3].w == n && st[4].w == n && (st[5].w | st[5].y | st[5].z) == n &&
         xr[0].x != UNSET && xr[1].x != UNSET && xr[2].x != UNSET && xr[3].x != UNSET;
}
template <int HALF>
__device__ __forceinline__ void conv_prep(uint32_t sb, int layer, int cta, int i) {
  uint4 st[6], xr[4];
  const uint4* sp = (const uint4*)g_stats + (layer * 32 + HALF * 16 + (i >> 3)) * 48 + (i & 7);
  const uint4* xp = (const uint4*)g_xT + (2 * layer * DM + 2 * cta) * (LSEQ / 8) + HALF * 128 + i;
  auto fetch = [&]() {
#pragma unroll
    for (int k = 0; k < 6; k++) st[k] = ld_tagged(sp + 8 * k);
#pragma unroll
    for (int k = 0; k < 4; k++) xr[k] = ld_tagged(xp + cv_chan(0, k) * (LSEQ / 8));
  };
  if (HALF) {
#pragma unroll
    for (int k = 0; k < 6; k++) st[k] = lds128(sb + CV_ST + (i >> 3) * 768 + k * 128 + (i & 7) * 16);
#pragma unroll
    for (int k = 0; k < 4; k++) xr[k] = lds128(sb + cv_x(1, k) + i * 16);
  } else {
    fetch();
  }
  int it = 0;
  while (!__all_sync(~0u, prep_valid(st, xr)) && ++it < MAX_RETRY) { fetch(); RETRY(1); }
  if (!HALF || it) {
#pragma unroll
    for (int k = 0; k < 4; k++) sts128(sb + cv_x(HALF, k) + i * 16, xr[k]);
  }
  const uint32_t v[16] = {st[0].x, st[0].y, st[0].z, st[1].x, st[1].y, st[1].z, st[2].x, st[2].y, st[2].z, st[3].x, st[3].y, st[3].z, st[4].x, st[4].y, st[4].z, st[5].x};
  uint32_t rs[4], nm[4];
#pragma unroll
  for (int k = 0; k < 4; k++) {
    const float m0 = __uint_as_float(v[4 * k]) * (-1.f / DM), m1 = __uint_as_float(v[4 * k + 2]) * (-1.f / DM);
    const float r0 = rsqrt_approx(fmaxf(fmaf(__uint_as_float(v[4 * k + 1]), 1.f / DM, -m0 * m0), 0.f) + 1e-5f);
    const float r1 = rsqrt_approx(fmaxf(fmaf(__uint_as_float(v[4 * k + 3]), 1.f / DM, -m1 * m1), 0.f) + 1e-5f);
    rs[k] = packbf(r0, r1);
    nm[k] = packbf(m0 * bf_lo(rs[k]), m1 * bf_hi(rs[k]));
  }
  const uint32_t ud = sb + (i & 1) * CV_UH + (127 - 64 * HALF - (i >> 1)) * 16;
#pragma unroll
  for (int k = 0; k < 4; k++)
    sts128(ud + cv_u(k), make_uint4(hfma2(xr[k].x, rs[0], nm[0]), hfma2(xr[k].y, rs[1], nm[1]), hfma2(xr[k].z, rs[2], nm[2]), hfma2(xr[k].w, rs[3], nm[3])));
  fence_async_smem();
}

#define AGATE 1
#define PP0 1
__device__ __forceinline__ void conv_phase(const Params& p, uint32_t sb, int layer, int cta) {
  const int tid = opaque_tid();
  const int wg = __shfl_sync(~0u, tid >> 7, 0), w = __shfl_sync(~0u, (tid >> 5) & 3, 0);
  const uint32_t bar = sb + SM_BAR;
  constexpr int CH2 = 4 * PG;
  bf16* xout = g_xT + ((2 * layer + 1) * DM + 2 * cta) * LSEQ;
  uint32_t A0[68], A1[68];
  float acc[32];
  const uint32_t pe = sb + cv_pe(wg) + 4 * (16 + 16 * w + ((tid & 31) >> 2) - 2 * (tid & 3));
  auto staged = [&]() {
    if (w == 0) {
      bulk_wait_read();
      __syncwarp();
      if (elect_one()) mbar_arrive(bar + 8 * (B_PST + wg));
    }
  };
  if (wg == 0) staged();
  mbar_wait(bar + 8 * (B_PDONE + 1), layer);
  mbar_wait(bar + 8 * B_PE, layer);
  conv_load(A0, pe);
  if (wg == 1) staged();
  conv_load(A1, pe + CH2);
  TSW(19);
  const uint64_t d0 = mkdesc(sb + cv_u(wg), CV_UH, 128, 0), d1 = d0 + (CH2 >> 4);
  mbar_wait(bar + 8 * B_U, layer);
  TSW(12);
  if (wg == 1) bar_sync(5, 256);
  conv_mma0(acc, A0, d0);
  if (wg == 0) bar_arrive(5, 256);
  mbar_wait(bar + 8 * (B_PDONE + 1), layer);
  {
    const int l = opaque_tid() & 31;
    if ((l & 15) < 2 * w) sts128(sb + cv_pb0(wg + 2 * (l >> 4), w) + (l & 15) * 16, make_uint4(0, 0, 0, 0));
  }
  wg_wait<0>();
  conv_store(acc, sb + cv_pb0(wg, w), sb + cv_pb1(wg, w), w);
  conv_mma0(acc, A1, d1);
  wg_wait<0>();
  conv_store(acc, sb + cv_pb0(2 + wg, w), sb + cv_pb1(2 + wg, w), w);
  TSW(13);
  bar_sync(2 + wg, 128);
  conv_epi<0, 2, 2>(sb, xout, wg, opaque_tid() & 127);
  TSW(14);
  mbar_arrive(bar + 8 * B_PUB);
  if (wg == 0) mbar_wait(bar + 8 * B_U1, layer);
  else bar_sync(6, 256);
  TSW(15);
  const uint64_t ds = mkdesc(sb + cv_se(wg), 8192, 1024, 1), df = mkdesc(sb + cv_fa(wg), 512, 128, 0);
  conv_mma1(acc, A0, d0, ds, df);
  if (wg == 0) bar_arrive(6, 256);
  wg_wait<0>();
  conv_store(acc, sb + cv_pb1(wg, w), sb + cv_dump(wg), w);
  mbar_arrive(bar + 8 * B_R);
  TSW(16);
  conv_mma1(acc, A1, d1, ds + 512, df + (CH2 >> 4));
  wg_wait<0>();
  conv_store(acc, sb + cv_pb1(2 + wg, w), sb + cv_dump(2 + wg), w);
  TSW(17);
  if (wg == 0) {
    mbar_arrive(bar + 8 * (B_R + 1));
  } else {
    bar_sync(3, 128);
    conv_epi<1, 1>(sb, xout, 3, opaque_tid() & 127);
    mbar_arrive(bar + 8 * (B_PUB + 2));
    TSW(18);
  }
}

__device__ __forceinline__ void final_phase(const Params& p, uint32_t sb, int cta, int wg, int w, int rtp) {
  const int lane = opaque_tid() & 31;
  const uint32_t bar = sb + SM_BAR;
  mbar_wait(bar + 8 * (B_TF + wg), 0);
  if (threadIdx.x == 128) TS(8);
  const uint32_t src = sb + (16 + wg) * PG, dst = src + 2 * PG;
  const int mi = lane >> 3;
#pragma unroll 1
  for (int attempt = 0; attempt < MAX_RETRY; attempt++) {
    uint32_t m = 0;
#pragma unroll
    for (int j = 0; j < 8; j += 2) {
      uint32_t r[4];
      const int line = 8 * (j + (mi >> 1)) + (lane & 7), pc = 2 * w + (mi & 1);
      ldsm4t(r, src + line * 128 + ((pc ^ (line & 7)) << 4));
      const int row = 16 * w + (lane & 7) + 8 * (mi & 1), ch = j + (mi >> 1);
      stsm4(dst + row * 128 + ((ch ^ (row & 7)) << 4), r[0], r[1], r[2], r[3]);
#pragma unroll
      for (int k = 0; k < 4; k++) asm("max.u16x2 %0, %0, %1;" : "+r"(m) : "r"(r[k]));
    }
    fence_async_smem();
    if (!bar_or(2 + wg, 128, m >= 0xffff0000u || (m & 0xffffu) == 0xffffu)) break;
    if (w == 0 && elect_one()) {
      mbar_expect(bar + 8 * (B_RT + wg), PG);
      tma_ld(src, &p.mapXT, (16 * wg + (cta & 15)) * 64, 3 * DM + (cta >> 4) * 64, bar + 8 * (B_RT + wg));
    }
    mbar_wait(bar + 8 * (B_RT + wg), (rtp + attempt) & 1);
    RETRY(2);
  }
  if (w == 0 && elect_one()) {
    tma_st(&p.mapOut, (cta >> 4) * 64, (16 * wg + (cta & 15)) * 64, dst);
    bulk_commit();
    asm volatile("cp.async.bulk.wait_group.read 0;" ::: "memory");
    if (threadIdx.x == 128) TS(9);
    if (threadIdx.x == 128) LTS(1);
  }
}

struct cplx { float r, i; };
__device__ __forceinline__ cplx cmul(cplx a, cplx b) { return {fmaf(a.r, b.r, -a.i * b.i), fmaf(a.r, b.i, a.i * b.r)}; }
__device__ __forceinline__ cplx csqr(cplx a) { return {fmaf(a.r, a.r, -a.i * a.i), (a.r + a.r) * a.i}; }
__device__ __forceinline__ cplx cexp_l(float ar2, float ai, float l) {
  const float m = ex2(ar2 * l);
  const float x = ai * l;
  return {m * __cosf(x), m * __sinf(x)};
}

__device__ __forceinline__ void colsum_cta(const Params& p, uint32_t sb, int j, int tid) {
  const uint32_t bar = sb + SM_BAR;
  auto ld = [&](int i) {
    mbar_expect(bar + 8 * i, 3 * PG);
    tma_ld3(sb + (i & 7) * 3 * PG, &p.mapW3, (2 * j + (i & 1)) * 64, (i >> 1) * 64, 0, bar + 8 * i);
  };
  if (tid == 384) {
#pragma unroll
    for (int i = 0; i < 24; i++) mbar_init(bar + 8 * i, i < 16 ? 1 : 12);
    asm volatile("fence.mbarrier_init.release.cluster;" ::: "memory");
    fence_async_smem();
#pragma unroll 1
    for (int i = 0; i < 8; i++) ld(i);
  }
  const unsigned ep = ld_relaxed(&g_cnt[C_CS * 32]);
  bar_sync(0, NTHREADS);
  if (tid == 384) {
#pragma unroll 1
    for (int i = 8; i < 16; i++) { mbar_wait(bar + 8 * (8 + i), 0); fence_async_smem(); ld(i); }
  }
  if (tid < 384) {
    const int lane = tid & 31, cc = tid & 7, r0 = (tid >> 3) & 15, part = tid >> 7;
    const uint32_t id = ((lane >> 2) == 2 * (lane & 3) ? 0x3f80u : 0u) | ((lane >> 2) == 2 * (lane & 3) + 1 ? 0x3f800000u : 0u);
    const uint32_t src = sb + part * PG + r0 * 128 + ((cc ^ (r0 & 7)) << 4);
    float s[2][2][4];
#pragma unroll
    for (int i = 0; i < 16; i++) s[i >> 3][(i >> 2) & 1][i & 3] = 0.f;
#pragma unroll 1
    for (int i2 = 0; i2 < 16; i2 += 2) {
#pragma unroll
      for (int h = 0; h < 2; h++) {
        const int i = i2 + h;
        mbar_wait(bar + 8 * i, 0);
        uint4 v[4];
#pragma unroll
        for (int k = 0; k < 4; k++) v[k] = lds128(src + (i & 7) * 3 * PG + k * 2048);
#pragma unroll
        for (int k = 0; k < 4; k++) {
          const uint32_t a[4] = {v[k].x, v[k].y, v[k].z, v[k].w};
          mma_bf16(s[h][0], a, id, 0u);
          mma_bf16(s[h][1], a, 0u, id);
        }
        __syncwarp();
        if (i < 8 && lane == 0) mbar_arrive(bar + 8 * (16 + i));
      }
    }
    const uint32_t red = sb + 24 * PG;
#pragma unroll
    for (int h = 0; h < 2; h++)
#pragma unroll
      for (int k = 0; k < 2; k++) sts128f(red + (r0 * 384 + h * 192 + part * 64 + cc * 8 + k * 4) * 4, s[h][k][0], s[h][k][1], s[h][k][2], s[h][k][3]);
    bar_sync(1, 384);
    float tot = 0.f;
#pragma unroll
    for (int k = 0; k < 16; k++) tot += __uint_as_float(lds32(red + (k * 384 + tid) * 4));
    asm volatile("st.relaxed.gpu.global.v2.u32 [%0], {%1,%2};" ::"l"(&g_colsum[j * 384 + tid]), "r"(__float_as_uint(tot)), "r"(ep / NCTA + 1) : "memory");
    const uint4 u = make_uint4(UNSET, UNSET, UNSET, UNSET);
    if (tid < 256) {
#pragma unroll 1
      for (int s = 0; s < 4; s++) {
        const int n = s ? 32 : 16;
        uint4* dst = (s == 1 ? (uint4*)g_O + 131072 : (uint4*)g_xT + (s + !s) * 131072) + j * n * 1024 + (tid >> 1) * 8 + (tid & 1);
#pragma unroll 4
        for (int i = 0; i < n; i++) stg128(dst + i * 1024, u);
        bar_sync(2, 256);
        if (tid == 32 * s) red_release(&g_cnt[(C_R + s) * 32]);
      }
    }
  }
}

#define KW 3
struct ModeIn { uint32_t ar, ai, br, bi, cr, ci; bf16 logdt; };
__device__ __forceinline__ ModeIn load_modes(const Params& p, int d, int m) {
  const int i = d * 64 + m;
  return {((const uint32_t*)p.a_re)[i], ((const uint32_t*)p.a_im)[i], ((const uint32_t*)p.b_re)[i], ((const uint32_t*)p.b_im)[i],
          ((const uint32_t*)p.c_re)[i], ((const uint32_t*)p.c_im)[i], p.log_dt[d]};
}
__device__ __forceinline__ float4 lds128f_nv(uint32_t a) { float4 v; asm("ld.shared.v4.f32 {%0,%1,%2,%3}, [%4];" : "=f"(v.x), "=f"(v.y), "=f"(v.z), "=f"(v.w) : "r"(a)); return v; }
__device__ __forceinline__ void kernel_gen(const Params& p, uint32_t sb, int cta, int ht, ModeIn in, const ModeIn& in1) {
  const uint32_t bst = sb + SM_KGB + ((ht & 63) >> 2) * 144 + (ht & 3) * 4 + (ht >> 6) * 16;
  const uint64_t db = mkdesc(sb + SM_KGB, 144, 2304, 0);
  const float e0 = (float)(8 * (((ht & 32) >> 1) + ((ht & 31) >> 2)));
  float T[20];
#pragma unroll
  for (int i = 0; i < 20; i++) T[i] = 0.f;
  float k0 = (ht & 63) ? 0.f : __bfloat162float(p.dskip[cv_chan(cta, ht >> 6)]);
#pragma unroll 1
  for (int pass = 0; pass < 4; pass++) {
    {
      const int sh = (pass & 1) ? 0 : 16;
      auto val = [&](uint32_t v) { return __uint_as_float((v << sh) & 0xffff0000u); };
      const float dt = __bfloat162float(__float2bfloat16_rn(expf(__bfloat162float(in.logdt))));
      const float ar2 = dt * val(in.ar) * 1.4426950408889634f, ai = dt * val(in.ai);
      const cplx c = cmul({val(in.cr), -val(in.ci)}, {dt * val(in.br), -dt * val(in.bi)});
      k0 += c.r;
      const cplx z1 = cexp_l(ar2, -ai, 1.f), z256 = cexp_l(ar2, -ai, 256.f), z64 = cexp_l(ar2, ai, 64.f);
      const cplx z2 = csqr(z1), z512 = csqr(z256);
      auto put = [&](int j, cplx v) { sts32(bst + (j >> 2) * 2304 + (j & 3) * 32, packbf(v.r, v.i)); };
      sts128f(sb + SM_KGT + ht * 16, ar2, ai, z64.r, z64.i);
      const cplx c1 = cmul(c, z1), c2 = cmul(c, z2), c3 = cmul(c1, z2), c4 = cmul(c2, z2);
      const cplx c5 = cmul(c3, z2), c6 = cmul(c4, z2), c7 = cmul(c5, z2), c8 = cmul(c6, z2);
      put(0, c1); put(1, c2); put(2, c3); put(3, c4); put(4, c5); put(5, c6); put(6, c7); put(7, c8);
      const cplx c260 = cmul(c4, z256), c264 = cmul(c8, z256), c520 = cmul(c8, z512), c776 = cmul(c264, z512);
      put(8, cmul(c2, z256)); put(9, c260); put(10, cmul(c6, z256)); put(11, c264);
      put(12, cmul(c4, z512)); put(13, c520); put(14, cmul(c260, z512)); put(15, c776);
      const cplx c1032 = cmul(c520, z512), c1288 = cmul(c776, z512);
      put(16, c1032); put(17, c1288); put(18, cmul(c1032, z512)); put(19, cmul(c1288, z512));
    }
    fence_async_smem();
    bar_sync(4, 128);
    uint32_t tb = sb + SM_KGT + (ht & 67) * 16;
    asm volatile("mov.u32 %0, %0;" : "+r"(tb) :: "memory");
#pragma unroll
    for (int q = 0; q < 4; q++) {
      uint32_t A[8];
      if (q >= KW) wg_wait<KW - 1>();
#pragma unroll
      for (int s = 0; s < 4; s++) {
        const float4 v = lds128f_nv(tb + (4 * q + s) * 64);
        const cplx lo = cexp_l(v.x, v.y, e0), hi = cmul(lo, {v.z, v.w});
        A[2 * s] = packbf(lo.r, lo.i);
        A[2 * s + 1] = packbf(hi.r, hi.i);
      }
      wg_fence();
      wgmma_rs<40, 0>(T, A, db + 36 * q, (pass & 1) | q);
      wgmma_rs<40, 0>(T, A + 4, db + 36 * q + 18, 1);
      wg_commit();
    }
    wg_wait<0>();
    acc_fence<20>(T);
    if (ht == 0) TS(4 + pass);
    if (pass & 1) {
      const int h2 = opaque_tid() - 256, w = h2 >> 5, lane = h2 & 31, t = lane & 3, chn = h2 >> 6, m = h2 & 63, i0 = 16 * (w & 1) + (lane >> 2);
      const int lc = (pass & 2) + chn;
      const uint32_t kc = sb + kc_off(lc);
      auto put = [&](int idx, float v) {
        sts16(kc + idx * 2, __bfloat16_as_ushort(__float2bfloat16_rn(v)));
      };
#pragma unroll
      for (int hi = 0; hi < 2; hi++) {
        const int i = i0 + 8 * hi;
        float v[5];
#pragma unroll
        for (int j = 0; j < 5; j++) v[j] = chn ? T[4 * j + 2 * hi + 1] : T[4 * j + 2 * hi];
        put(8 * i + 1 + t, v[0]);
        put(8 * i + 5 + t, v[1]);
        put(257 + 4 * i + t, v[2]);
        put(385 + 2 * i + (t & 1) + 64 * (t >> 1), v[3]);
        put(513 + i + 32 * t, v[4]);
      }
#pragma unroll
      for (int o = 16; o > 0; o >>= 1) k0 += __shfl_xor_sync(~0u, k0, o);
      if (lane == 0) sts32f(sb + SM_RED + 4 * w, k0);
      bar_sync(4, 128);
      if (m == 0) put(0, k0 + __uint_as_float(lds32(sb + SM_RED + 4 * w + 4)));
      k0 = m ? 0.f : __bfloat162float(p.dskip[cv_chan(cta, 2 + chn)]);
      in = in1;
    }
  }
}

__device__ __forceinline__ void expand_taps(uint32_t sb, int ht) {
  const int ch = ht >> 5, lane = ht & 31;
  const uint32_t kc = sb + kc_off(ch);
  const uint32_t dst0 = sb + cv_pe(ch);
  auto put = [&](int G, uint32_t v0, uint32_t v1, uint32_t v2, uint32_t v3, uint32_t v4, uint32_t v5, uint32_t v6, uint32_t v7, uint32_t v8) {
    const uint32_t dst = dst0 + G * 32;
    sts128(dst, make_uint4(v1 | (v0 << 16), v2 | (v1 << 16), v3 | (v2 << 16), v4 | (v3 << 16)));
    sts128(dst + 16, make_uint4(v5 | (v4 << 16), v6 | (v5 << 16), v7 | (v6 << 16), v8 | (v7 << 16)));
  };
  {
    const uint4 q = lds128(kc + lane * 16);
    const uint32_t pv = lane ? lds16(kc + lane * 16 - 2) : 0u;
    const uint32_t dst = dst0 + (lane + 2) * 32;
    sts128(dst, make_uint4(__byte_perm(q.x, pv, 0x5410), __byte_perm(q.x, q.x, 0x1032), __byte_perm(q.y, q.x, 0x7610), __byte_perm(q.y, q.y, 0x1032)));
    sts128(dst + 16, make_uint4(__byte_perm(q.z, q.y, 0x7610), __byte_perm(q.z, q.z, 0x1032), __byte_perm(q.w, q.z, 0x7610), __byte_perm(q.w, q.w, 0x1032)));
    if (lane < 4) sts128(dst0 + lane * 16, make_uint4(0, 0, 0, 0));
  }
  uint32_t a[5], b[2][3];
  {
    const uint32_t s1 = kc + 2 * (256 + 4 * lane);
#pragma unroll
    for (int k = 0; k < 5; k++) a[k] = lds16(s1 + 2 * k);
#pragma unroll
    for (int u = 0; u < 2; u++) {
      const uint32_t s2 = kc + 2 * (384 + 2 * (lane + 32 * u));
#pragma unroll
      for (int k = 0; k < 3; k++) b[u][k] = lds16(s2 + 2 * k);
    }
  }
  const uint32_t k255 = lds16(kc + 2 * 255), k1024 = lds16(kc + 2 * 512);
  put(34 + lane, lane == 0 ? k255 : a[0], a[0], a[0], a[1], a[2], a[2], a[2], a[3], a[4]);
#pragma unroll
  for (int u = 0; u < 2; u++) put(66 + lane + 32 * u, b[u][0], b[u][0], b[u][0], b[u][0], b[u][1], b[u][1], b[u][1], b[u][2], b[u][2]);
  if (lane < 10) {
    const uint32_t v = lane == 0 ? k1024 : 0u;
    put(130 + lane, v, v, v, v, v, v, 0u, 0u, 0u);
  }
}
__device__ __forceinline__ void expand_far(uint32_t sb, int ht) {
  const int ch = ht >> 5, lane = ht & 31;
  const uint32_t kc = sb + kc_off(ch) + 2 * (513 + 2 * (63 - lane)), dst = sb + cv_fa(ch) + lane * 16;
#pragma unroll
  for (int ty = 0; ty < 2; ty++) {
    uint32_t v[16];
#pragma unroll
    for (int k = 0; k < 16; k++) v[k] = (k < 8 || 63 - lane - 4 * k >= 0) ? lds16(kc + 2 * (1 - ty) - 16 * k) : 0u;
#pragma unroll
    for (int u = 0; u < 2; u++)
      sts128(dst + ty * 2048 + u * 512, make_uint4(v[8 * u] | (v[8 * u + 1] << 16), v[8 * u + 2] | (v[8 * u + 3] << 16), v[8 * u + 4] | (v[8 * u + 5] << 16), v[8 * u + 6] | (v[8 * u + 7] << 16)));
    sts128(dst + ty * 2048 + 1024, make_uint4(0, 0, 0, 0));
  }
}

#define TMPF 1
#define CONST_SB 1
#define WPRE 1
__host__ __device__ constexpr int bar_count(int i) {
  return i == B_END ? 3 : i == B_LN ? 2 : i < B_OST ? 1 : i < B_PE ? 4 : (i == B_PUB || i == B_PUB + 2 || i == B_R) ? 256 : 128;
}
__host__ __device__ constexpr bool bar_first(int i) { return i < B_WF + 2 && (i & 7) < 2; }

__global__ void __launch_bounds__(NTHREADS, 1) fused_kernel(const __grid_constant__ Params p) {
  extern __shared__ __align__(1024) uint8_t smem[];
  constexpr uint32_t sb = 1024;
  if (s32(smem) != sb) return;
  const int tid = threadIdx.x, lane = tid & 31;
  const int warp = __shfl_sync(~0u, tid >> 5, 0);
  if (tid == 32) {
    asm volatile("prefetch.tensormap [%0];" ::"l"(&p.mapX) : "memory");
    asm volatile("prefetch.tensormap [%0];" ::"l"(&p.mapW3) : "memory");
  }
  const int cta = blockIdx.x - (gridDim.x == NCTA + 4 ? 0 : 4);
  if ((unsigned)cta >= NCTA) {
    if (blockIdx.x < NCTA + 4) colsum_cta(p, sb, blockIdx.x & 3, tid);
    return;
  }
  const int rb = ((cta >> 4) & 3) * 4 + ((cta >> 2) & 3), hg = (cta >> 6) * 4 + (cta & 3);
  const uint32_t bar = sb + SM_BAR;
  auto ld_x0 = [&](int half, int c) {
    const uint32_t b = bar + 8 * (B_XF + 8 * half + c);
    mbar_expect(b, PG);
    tma_ld(sb + x_page(half, c) * PG, &p.mapX, c * 64, (16 * half + rb) * 64, b);
  };
  auto ld_x1 = [&](int half, int c, int b0) {
    const uint32_t b = bar + 8 * b0;
    mbar_expect(b, PG);
    tma_ld(sb + (8 * half + c) * PG, &p.mapXT, (16 * half + rb) * 64, DM + c * 64, b);
  };
  auto ld_w = [&](int c) {
    const uint32_t b = bar + 8 * (B_WF + c);
    mbar_expect(b, 3 * PG);
    tma_ld3(sb + w_page(c) * PG, &p.mapW3, hg * 64, c * 64, 0, b);
  };

  if (tid == 0) TS(0);
  if (tid == 480) LTS(0);
  if (warp == 0 && elect_one()) {
#pragma unroll
    for (int i = 0; i < B_WF + 2; i++)
      if (bar_first(i)) mbar_init(bar + 8 * i, 1);
    asm volatile("fence.mbarrier_init.release.cluster;" ::: "memory");
    fence_async_smem();
    TS(76);
    ld_x0(0, 0);
    TS(77);
    ld_w(0); ld_x0(1, 0);
    ld_x0(0, 1); ld_w(1); ld_x0(1, 1);
    TS(1);
  }
  __syncwarp();
  if (warp >= 1 && warp < 8 && elect_one()) {
    if (warp < 4) {
#pragma unroll
      for (int i = 2; i < 8; i++) mbar_init(bar + 8 * (8 * warp - 8 + i), 1);
    } else {
#pragma unroll
      for (int i = 0; i < 12; i++) mbar_init(bar + 8 * (12 * warp - 24 + i), 1);
    }
    asm volatile("fence.mbarrier_init.release.cluster;" ::: "memory");
  }
  if (warp == 15 && elect_one()) {
#pragma unroll
    for (int i = 72; i < B_COUNT; i++) mbar_init(bar + 8 * i, bar_count(i));
    asm volatile("fence.mbarrier_init.release.cluster;" ::: "memory");
  }

  if (warp < 8) {
    if (tid == 128) TS(78);
    bar_sync(0, NTHREADS);
    if (tid == 128) TS(79);
    asm volatile("setmaxnreg.inc.sync.aligned.u32 %0;" ::"n"(R_CONS));
    const int cw = __shfl_sync(~0u, opaque_tid() >> 5, 0);
    const int wg = cw >> 2, w = cw & 3;
    if (tid == 0) TS(2);
    int rtp = 0;
#pragma unroll 1
    for (int layer = 0; layer < 2; layer++) {
      attn_phase(p, sb, layer, rb, hg, wg, w);
      proj_phase(p, sb, layer, rb, hg, rtp);
      conv_phase(p, sb, layer, cta);
    }
    final_phase(p, sb, cta, wg, w, rtp);
  } else if (warp < 12) {
    asm volatile("setmaxnreg.dec.sync.aligned.u32 %0;" ::"n"(R_HELP));
    const int ht = tid - 256;
    {
      unsigned ep0 = 0;
      if (ht == 0) ep0 = ld_relaxed(&g_cnt[C_CS * 32]);
      const ModeIn in0 = load_modes(p, cv_chan(cta, ht >> 6), ht & 63), in1 = load_modes(p, cv_chan(cta, 2 + (ht >> 6)), ht & 63);
      if (ht < 48) sts128f(sb + SM_STG + ht * 16, 0.f, 0.f, 0.f, 1.f);
      bar_sync(0, NTHREADS);
      if (ht == 0) {
        sts32(sb + SM_EP, ep0 / NCTA);
        mbar_arrive(bar + 8 * B_EP);
      }
      kernel_gen(p, sb, cta, ht, in0, in1);
      if (ht < 48) sts128f(sb + SM_KGT + ht * 16, 0.f, 0.f, 0.f, 1.f);
      fence_async_smem();
      bar_sync(4, 128);
      if (ht == 0) mbar_arrive(bar + 8 * B_KG);
    }
#pragma unroll 1
    for (int layer = 0; layer < 2; layer++) {
      bf16* xout = g_xT + ((2 * layer + 1) * DM + 2 * cta) * LSEQ;
      mbar_wait(bar + 8 * B_PDONE, layer);
      expand_taps(sb, opaque_tid() - 256);
      mbar_arrive(bar + 8 * B_PE);
      TSW(0);
      expand_far(sb, opaque_tid() - 256);
      {
        const int i = opaque_tid() - 256;
        if (i < 32) sts128(sb + cv_u(i >> 3) + ((i >> 2) & 1) * CV_UH + (128 + (i & 3)) * 16, make_uint4(0, 0, 0, 0));
        mbar_wait(bar + 8 * B_RC, layer);
        mbar_wait(bar + 8 * B_GB, layer);
        TSW(13);
        conv_prep<0>(sb, layer, cta, i);
        mbar_arrive(bar + 8 * B_U);
      }
      mbar_wait(bar + 8 * (B_PDONE + 1), layer);
      bar_sync(4, 128);
#pragma unroll 1
      for (int lc = 0; lc < 4; lc += 2) {
        conv_sums(sb, lc, opaque_tid() - 256);
        TSW(1 + lc);
      }
      mbar_wait(bar + 8 * (B_GB + 1), layer);
      conv_prep<1>(sb, layer, cta, opaque_tid() - 256);
      mbar_arrive(bar + 8 * B_U1);
      TSW(4);
      mbar_wait(bar + 8 * B_R, layer);
      conv_epi<1, 2>(sb, xout, 0, opaque_tid() - 256);
      mbar_arrive(bar + 8 * (B_PUB + 1));
      TSW(5);
      mbar_wait(bar + 8 * (B_R + 1), layer);
      conv_epi<1, 1>(sb, xout, 2, opaque_tid() - 256);
      mbar_arrive(bar + 8 * (B_PUB + 2));
      TSW(6);
      if (layer == 0) {
        const int c = __shfl_sync(~0u, (opaque_tid() >> 5) & 3, 0);
#pragma unroll 1
        for (int half = 0; half < 2; half++) {
          const uint32_t a = sb + (8 * half + c) * PG + lane * 128 + (lane & 7) * 16 + (lane >> 3) * 4;
#pragma unroll 1
          for (int it = 0; it < MAX_RETRY; it++) {
            mbar_wait(bar + 8 * (B_XR + 4 * half + c), it & 1);
            const uint32_t v0 = lds32(a), v1 = lds32(a + 4096);
            if (__all_sync(~0u, v0 != UNSET && v1 != UNSET)) break;
            if (elect_one()) { fence_async_smem(); ld_x1(half, c, B_XR + 4 * half + c); }
            __syncwarp();
            RETRY(3);
          }
          if (lane == 0) mbar_arrive(bar + 8 * (B_XF + 8 * half + c));
        }
      }
    }
  } else {
    asm volatile("setmaxnreg.dec.sync.aligned.u32 %0;" ::"n"(R_AGENT));
    bar_sync(0, NTHREADS);
    auto done = [&](int half, int c, int layer) { mbar_wait(bar + 8 * (B_DN + 8 * half + c), layer); };
    auto publish = [&](int layer, int k) {
      mbar_wait(bar + 8 * (B_PUB + k), layer);
      if (layer || k < 2) red_relaxed(&g_cnt[(layer ? C_F + 4 * k + (cta >> 5) : C_C + k) * 32]);
      if (!layer && k != 1) red_release(&g_cnt[(C_C + 3 - (k >> 1)) * 32]);
      TS(16 + layer * 56 + 40 + 7 + k);
    };
    if (warp == 12) {
      if (elect_one()) {
#pragma unroll 1
        for (int layer = 0; layer < 2; layer++) {
          auto ld_xe = [&](int c) {
            const uint32_t b = bar + 8 * (B_XF + c);
            mbar_expect(b, PG);
            if (layer == 0) tma_ld(sb + x_page(0, c) * PG, &p.mapX, c * 64, rb * 64, b);
            else tma_ld(sb + x_page(0, c) * PG, &p.mapXT, rb * 64, DM + c * 64, b);
          };
          if (layer == 0) {
            ld_x0(0, 2); ld_w(2); ld_x0(1, 2);
            if (hg >= 3) {
              mbar_expect(bar + 8 * B_SC, PG);
              tma_ld(sb + P_R * PG, &p.mapX, hg * 64, rb * 64, bar + 8 * B_SC);
            }
            if (rb < 4) tma_prefetch3(&p.mapW3, hg * 64, (4 + rb) * 64, 0);
            ld_x0(0, 3); ld_w(3); ld_x0(1, 3); ld_x0(0, 4); ld_x0(1, 4);
            done(0, 0, 0); done(1, 0, 0);
            ld_w(4);
            ld_x0(1, 5); ld_x0(1, 6); ld_x0(1, 7);
            done(0, 1, 0); done(1, 1, 0);
            ld_w(5);
            if (rb < 8) tma_prefetch5(&p.mapWo, hg * 64, rb * 2);
            done(0, 2, 0);
            fence_async_smem();
            ld_xe(5); ld_xe(6); ld_xe(7);
          } else {
            mbar_wait(bar + 8 * B_PDONE, 0);
            mbar_wait(bar + 8 * (B_PDONE + 1), 0);
            mbar_wait(bar + 8 * (WPRE == 1 ? B_U : B_GB + 1), 0);
            ld_w(0); ld_w(1);
            mbar_wait(bar + 8 * B_U1, 0);
            fence_async_smem();
            ld_w(2);
            mbar_wait(bar + 8 * (B_PUB + 2), 0);
            fence_async_smem();
            ld_w(3);
            spin_until(&g_cnt[(C_C + 3) * 32], (lds32(sb + SM_EP) + 1) * NCTA);
            fence_async_global();
            if (hg >= 3) {
              mbar_expect(bar + 8 * B_SC, PG);
              tma_ld(sb + P_R * PG, &p.mapXT, rb * 64, DM + hg * 64, bar + 8 * B_SC);
            }
            ld_xe(4);
            done(0, 2, 1);
            fence_async_smem();
            ld_xe(5); ld_xe(6); ld_xe(7);
            done(1, 0, 1);
            ld_w(4);
            done(1, 1, 1);
            ld_w(5);
          }
          done(1, 2, layer);
          fence_async_smem();
          ld_w(6); ld_w(7);
          auto ld_res = [&](int half) {
            const uint32_t b = bar + 8 * (B_RF + half);
            mbar_expect(b, PG);
            if (layer == 0) tma_ld(sb + (half ? 2 : P_R) * PG, &p.mapX, hg * 64, (16 * half + rb) * 64, b);
            else tma_ld(sb + (half ? 2 : P_R) * PG, &p.mapXT, (16 * half + rb) * 64, DM + hg * 64, b);
          };
          done(0, 4, layer); done(1, 3, layer);
          fence_async_smem();
          mbar_expect(bar + 8 * B_WOF, 8 * PG);
#pragma unroll 1
          for (int c = 0; c < 8; c++) {
            if (c == 5) { ld_res(0); done(1, 4, layer); }
            tma_ld5(sb + wo_page(c) * PG, &p.mapWo, hg * 64, c * 2, bar + 8 * B_WOF);
          }
          done(0, 7, layer);
          fence_async_global();
          ld_res(1);
        }
      }
    } else if (warp == 13) {
      mbar_wait(bar + 8 * B_EP, 0);
      const unsigned e1 = lds32(sb + SM_EP) + 1;
      auto ld_o = [&](int layer) {
#pragma unroll 1
        for (int half = 0; half < 2; half++) {
          done(1, 7, layer);
          mbar_wait(bar + 8 * B_OST, layer);
          if (half) mbar_wait(bar + 8 * (B_OST + 1), layer);
          fence_async_smem();
#pragma unroll
          for (int c = 0; c < 4; c++) mbar_expect(bar + 8 * (B_OF + 4 * half + c), 2 * PG);
          spin_until(&g_cnt[(C_O + layer * 32 + 16 * half + rb) * 32], e1 * 32);
#pragma unroll
          for (int c = 0; c < 4; c++)
            bulk_ld(sb + o_page(half, c) * PG, g_O + ((layer * 32 + 16 * half + rb) * 4 + c) * PG, 2 * PG, bar + 8 * (B_OF + 4 * half + c));
        }
      };
      if (elect_one()) {
        mbar_wait(bar + 8 * (B_WF + 2), 0);
        asm volatile("prefetch.tensormap [%0];" ::"l"(&p.mapXT) : "memory");
        asm volatile("prefetch.tensormap [%0];" ::"l"(&p.mapOut) : "memory");
        asm volatile("prefetch.tensormap [%0];" ::"l"(&p.mapWo) : "memory");
        spin_until(&g_cnt[C_Z * 32], e1 * NCTA);
        mbar_arrive(bar + 8 * B_ZF);
        TS(3);
        ld_o(0);
#pragma unroll 1
        for (int k = 0; k < 3; k++) {
          mbar_wait(bar + 8 * (B_PUB + k), 0);
          fence_async_smem();
          spin_until(&g_cnt[(C_C + k) * 32], e1 * NCTA);
          TS(10 + k);
          if (k == 2) fence_async_global();
#pragma unroll
          for (int c = 0; c < 4; c++) ld_x1(k != 0, (k & 2) * 2 + c, k < 2 ? B_XR + 4 * k + c : B_XF + 12 + c);
        }
        ld_o(1);
        mbar_wait(bar + 8 * B_PUB, 1);
#pragma unroll 1
        for (int half = 0; half < 2; half++) {
          mbar_expect(bar + 8 * (B_TF + half), PG);
          spin_until(&g_cnt[(C_F + 4 * (half ? 1 + (cta >> 6) : 0) + ((cta >> 4) & 3)) * 32], e1 * 32);
          tma_ld(sb + (16 + half) * PG, &p.mapXT, (16 * half + (cta & 15)) * 64, 3 * DM + (cta >> 4) * 64, bar + 8 * (B_TF + half));
        }
      }
    } else if (warp == 14) {
      mbar_wait(bar + 8 * B_EP, 0);
      const unsigned e1 = lds32(sb + SM_EP) + 1;
      done(0, 1, 0);
      {
        const uint2* cp = g_colsum + (hg * 192 + lane);
        uint2 v[6];
        bool ok;
        int it = 0;
        do {
          ok = true;
#pragma unroll
          for (int i = 0; i < 6; i++) {
            asm volatile("ld.relaxed.gpu.global.v2.u32 {%0,%1}, [%2];" : "=r"(v[i].x), "=r"(v[i].y) : "l"(cp + 32 * i) : "memory");
            ok = ok && v[i].y == e1;
          }
          if (++it > (1 << 22)) __trap();
        } while (!__all_sync(~0u, ok));
#pragma unroll
        for (int i = 0; i < 6; i++) sts32f(sb + SM_CS + 4 * (lane + 32 * i), __uint_as_float(v[i].x));
      }
      __syncwarp();
      if (elect_one()) {
        mbar_wait(bar + 8 * B_ZF, 0);
        mbar_arrive(bar + 8 * B_LN);
        red_relaxed(&g_cnt[C_CS * 32]);
        TS(13);
#pragma unroll 1
        for (int i = 0; i < 4; i++) {
          const int layer = i >> 1;
          mbar_wait(bar + 8 * (B_PST + (i & 1)), layer);
          const uint32_t b = bar + 8 * (B_GB + 1);
          const bf16* xin = g_xT + ((size_t)2 * layer * DM + 2 * cta) * LSEQ + 1024;
          if (i & 1) {
            fence_async_smem();
            mbar_expect(b, 12288 + PG);
          }
          spin_until(&g_cnt[(C_G + i) * 32], e1 * NCTA);
          if (i & 1) {
            bulk_ld(sb + CV_ST, g_stats + (layer * 32 + 16) * 192, 12288, b);
#pragma unroll
            for (int lc = 0; lc < 4; lc++) bulk_ld(sb + cv_x(1, lc), xin + cv_chan(0, lc) * LSEQ, 2048, b);
            TS(14 + layer);
            publish(layer, 1);
          } else {
            mbar_arrive(bar + 8 * B_GB);
          }
        }
      }
    } else {
      const uint4 u = make_uint4(UNSET, UNSET, UNSET, UNSET);
      if (lane < 24) stg128((uint4*)g_stats + cta * 24 + lane, make_uint4(0, 0, 0, 0));
      if (lane < 16) stg128(g_rows + LSEQ + cta * 16 + lane, make_uint4(0, 0, 0, 0));
#pragma unroll 4
      for (int i = 0; i < 16; i++) stg128(g_halo + cta * 512 + 32 * i + lane, u);
#pragma unroll 4
      for (int i = 0; i < 16; i++) stg128(((i & 8) ? (uint4*)g_xT : (uint4*)g_O) + cta * 1024 + (i & 7) * 128 + (lane >> 1) * 8 + (lane & 1), u);
      __syncwarp();
      if (elect_one()) red_release(&g_cnt[C_Z * 32]);
      __syncwarp();
#pragma unroll 1
      for (int layer = 0; layer < 2; layer++) {
        auto reset_done = [&](int s) {
          spin_until(&g_cnt[(C_R + s) * 32], lds32(sb + SM_EP) * 4 + 4);
          mbar_arrive(bar + 8 * (s == 1 ? B_LN : s == 2 ? B_RS : B_RC));
          if (s) TS(16 + 40 + 9 + s);
        };
        if (layer && elect_one()) reset_done(1);
        __syncwarp();
#pragma unroll 1
        for (int half = 0; half < 2; half++) {
          done(half, 2, layer);
          const uint4* src = g_rows + (layer * LSEQ + (16 * half + rb) * 64 + (opaque_tid() & 31));
          uint4 a, b;
          int it = 0;
          do {
            a = ld_tagged(src); b = ld_tagged(src + 32);
          } while (!__all_sync(~0u, (a.z | a.w) == __float_as_uint(8.f) && (b.z | b.w) == __float_as_uint(8.f)) && ++it < (1 << 20));
          float m0 = __uint_as_float(a.x) * (1.f / DM), m1 = __uint_as_float(b.x) * (1.f / DM);
          float r0 = rsqrt_approx(fmaxf(__uint_as_float(a.y) * (1.f / DM) - m0 * m0, 0.f) + 1e-5f);
          float r1 = rsqrt_approx(fmaxf(__uint_as_float(b.y) * (1.f / DM) - m1 * m1, 0.f) + 1e-5f);
          if (half) done(0, 7, layer);
          const uint32_t dst = sb + ln_off(half) + ((lane >> 4) * 8 + (lane & 7)) * 16 + (lane & 8);
          asm volatile("st.shared.v2.f32 [%0], {%1,%2};" ::"r"(dst), "f"(m0), "f"(r0) : "memory");
          asm volatile("st.shared.v2.f32 [%0], {%1,%2};" ::"r"(dst + 256), "f"(m1), "f"(r1) : "memory");
          __syncwarp();
          if (elect_one()) { mbar_arrive(bar + 8 * (B_LN + half)); TS(16 + layer * 56 + 40 + 14 + half); }
        }
        if (layer && lane < 16) stg128(g_rows + cta * 16 + (opaque_tid() & 31), make_uint4(0, 0, 0, 0));
        if (elect_one()) {
          if (layer) reset_done(2);
          reset_done(3 * layer);
          publish(layer, 0);
          publish(layer, 2);
        }
        __syncwarp();
      }
    }
  }
}

typedef CUresult (*EncodeFn)(CUtensorMap*, CUtensorMapDataType, cuuint32_t, void*, const cuuint64_t*, const cuuint64_t*,
                             const cuuint32_t*, const cuuint32_t*, CUtensorMapInterleave, CUtensorMapSwizzle,
                             CUtensorMapL2promotion, CUtensorMapFloatOOBfill);

static void make_map(EncodeFn enc, CUtensorMap* m, void* ptr, uint64_t cols, uint64_t rows, uint32_t box_rows) {
  cuuint64_t dims[2] = {cols, rows};
  cuuint64_t strides[1] = {cols * 2};
  cuuint32_t box[2] = {64, box_rows};
  cuuint32_t es[2] = {1, 1};
  enc(m, CU_TENSOR_MAP_DATA_TYPE_BFLOAT16, 2, ptr, dims, strides, box, es, CU_TENSOR_MAP_INTERLEAVE_NONE,
      CU_TENSOR_MAP_SWIZZLE_128B, CU_TENSOR_MAP_L2_PROMOTION_L2_128B, CU_TENSOR_MAP_FLOAT_OOB_FILL_NONE);
}
static void make_map3(EncodeFn enc, CUtensorMap* m, void* ptr, uint64_t d0, uint64_t cols, uint64_t rows, uint64_t blk_stride,
                      uint64_t nblocks, uint32_t nblk) {
  cuuint64_t dims[3] = {d0, rows, nblocks};
  cuuint64_t strides[2] = {cols * 2, blk_stride * 2};
  cuuint32_t box[3] = {64, 64, nblk};
  cuuint32_t es[3] = {1, 1, 1};
  enc(m, CU_TENSOR_MAP_DATA_TYPE_BFLOAT16, 3, ptr, dims, strides, box, es, CU_TENSOR_MAP_INTERLEAVE_NONE,
      CU_TENSOR_MAP_SWIZZLE_128B, CU_TENSOR_MAP_L2_PROMOTION_L2_128B, CU_TENSOR_MAP_FLOAT_OOB_FILL_NONE);
}

extern "C" void kernel_launch(void* const* d_in, const int* in_sizes, int n_in, void* d_out, int out_size) {
  static Params prm;
  static void* cached[13] = {nullptr};
  static bool attr_done = false;
  static int grid = NCTA + 4;
  bool same = attr_done && cached[12] == d_out;
  for (int i = 0; i < 12 && same; i++) same = cached[i] == d_in[i];
  if (!same) {
    void* fn = nullptr;
    cudaDriverEntryPointQueryResult qr;
    cudaGetDriverEntryPoint("cuTensorMapEncodeTiled", &fn, cudaEnableDefault, &qr);
    EncodeFn enc = (EncodeFn)fn;
    void* pXT;
    cudaGetSymbolAddress(&pXT, g_xT);
    make_map(enc, &prm.mapX, d_in[0], DM, LSEQ, 64);
    make_map(enc, &prm.mapXT, pXT, LSEQ, 4 * DM, 64);
    make_map(enc, &prm.mapOut, d_out, DM, LSEQ, 64);
    {
      cuuint64_t dims[5] = {DM, 2, 4, 4, 16};
      cuuint64_t strides[4] = {DM * 2, 8 * DM * 2, 2 * DM * 2, 32 * DM * 2};
      cuuint32_t box[5] = {64, 2, 4, 4, 2};
      cuuint32_t es[5] = {1, 1, 1, 1, 1};
      enc(&prm.mapWo, CU_TENSOR_MAP_DATA_TYPE_BFLOAT16, 5, d_in[2], dims, strides, box, es, CU_TENSOR_MAP_INTERLEAVE_NONE,
          CU_TENSOR_MAP_SWIZZLE_128B, CU_TENSOR_MAP_L2_PROMOTION_L2_128B, CU_TENSOR_MAP_FLOAT_OOB_FILL_NONE);
    }
    make_map3(enc, &prm.mapW3, d_in[1], DM, 3 * DM, DM, DM, 3, 3);
    prm.wqkv = (const bf16*)d_in[1];
    prm.a_re = (const bf16*)d_in[4]; prm.a_im = (const bf16*)d_in[5];
    prm.b_re = (const bf16*)d_in[6]; prm.b_im = (const bf16*)d_in[7];
    prm.c_re = (const bf16*)d_in[8]; prm.c_im = (const bf16*)d_in[9];
    prm.log_dt = (const bf16*)d_in[10]; prm.dskip = (const bf16*)d_in[11];
    int dev = 0, sms = 0;
    cudaGetDevice(&dev);
    cudaDeviceGetAttribute(&sms, cudaDevAttrMultiProcessorCount, dev);
    grid = sms >= NCTA + 4 ? NCTA + 4 : NCTA + 5;
    cudaFuncSetAttribute(fused_kernel, cudaFuncAttributeMaxDynamicSharedMemorySize, SM_TOTAL);
    for (int i = 0; i < 12; i++) cached[i] = d_in[i];
    cached[12] = d_out;
    attr_done = true;
  }
  fused_kernel<<<grid, NTHREADS, SM_TOTAL>>>(prm);
}
```

```cpp
#include <cuda_runtime.h>
#include <cuda_bf16.h>
#include <cuda.h>
#include <stdint.h>

typedef __nv_bfloat16 bf16;

constexpr int LSEQ = 2048;
constexpr int DM = 512;
constexpr int NCTA = 128;
constexpr int NTHREADS = 512;
#define R_CONS 200
#define R_HELP 88
#define R_AGENT 24
#define TURN0 4
#define TURN1 4

constexpr int PG = 8192;
constexpr int P_R = 25;
__host__ __device__ constexpr int x_page(int half, int c) { return half ? 8 + c : c < 5 ? c : c - 5; }
__host__ __device__ constexpr int w_page(int c) { return (c & 3) < 3 ? 16 + 3 * (c & 3) : c < 4 ? 5 : 8; }
__host__ __device__ constexpr int wo_page(int c) { return c < 5 ? 3 + c : 11 + c; }
__host__ __device__ constexpr int o_page(int half, int pair) { return half ? (pair ? 17 + 2 * pair : 0) : 8 + 2 * pair; }
constexpr int SM_KGB = (P_R + 1) * PG;
constexpr int SM_KC = 27 * PG;
constexpr int KC_STRIDE = 648;
__host__ __device__ constexpr int kc_off(int lc) { return SM_KC + (lc & 1) * 2 * KC_STRIDE + (lc < 2 ? 3328 : 0); }
constexpr int SM_KGT = SM_KC + 3328 + 2592;
constexpr int SM_CS = SM_KGT + 2048;
constexpr int SM_RED = SM_CS + 768;
constexpr int SM_EP = SM_RED + 16;
constexpr int SM_STG = SM_RED + 32;
constexpr int SM_LN = SM_STG + 768;
__host__ __device__ constexpr int ln_off(int half) { return half ? PG + 4096 : SM_LN; }
constexpr int SM_BAR = SM_LN + 512;
constexpr int SM_TS = SM_BAR + 704;
constexpr int SM_TOTAL = SM_TS + 512;
static_assert(SM_TOTAL <= 232448 && SM_STG % 16 == 0 && SM_KGT % 16 == 0, "shared memory");

constexpr int CV_UH = 140 * 16;
__host__ __device__ constexpr int cv_u(int lc) { return (8 + 2 * lc) * PG; }
__host__ __device__ constexpr int cv_pe(int lc) { return cv_u(lc) + 4480; }
__host__ __device__ constexpr int cv_pb1(int lc, int w) { return w ? cv_u(lc) + 8960 + (w - 1) * 2048 : 7 * PG + lc * 2048; }
__host__ __device__ constexpr int cv_fa(int lc) { return cv_pb1(lc, 1) + 128; }
__host__ __device__ constexpr int cv_dump(int lc) { return cv_u(lc) + 16256; }
__host__ __device__ constexpr int cv_pb0(int lc, int w) { return lc * PG + w * 2048; }
__host__ __device__ constexpr int cv_se(int lc) { return 5 * PG + lc * 4096; }
__host__ __device__ constexpr int cv_so(int lc) { return cv_se(lc) + 2048; }
__host__ __device__ constexpr int cv_x(int half, int lc) { return (P_R + half) * PG + lc * 2048; }
constexpr int CV_ST = 22 * PG;
__host__ __device__ constexpr int cv_chan(int cta, int lc) { return 2 * cta + (lc & 1) + 256 * (lc >> 1); }

enum {
  B_XF = 0,
  B_WF = 16,
  B_OF = 24,
  B_DN = 32,
  B_XR = 48,
  B_RF = 56,
  B_PST = 58,
  B_GB = 60,
  B_TF = 62,
  B_RT = 64,
  B_RS = 66,
  B_RC = 67,
  B_WOF = 68,
  B_ZF = 69,
  B_EP = 70,
  B_KG = 71,
  B_SC = 72,
  B_LN = 73,
  B_END = 75,
  B_OST = 76,
  B_PDONE = 78,
  B_PE = 80,
  B_U = 81,
  B_U1 = 82,
  B_PUB = 83,
  B_R = 86,
  B_COUNT = 88
};

enum {
  C_CS = 0,
  C_G = 1,
  C_C = 5,
  C_F = 9,
  C_O = 21,
  C_Z = 85,
  C_R = 86,
  C_COUNT = 90
};

__device__ unsigned g_cnt[C_COUNT * 32];
__device__ __align__(1024) bf16 g_O[2 * LSEQ * DM];
__device__ __align__(1024) bf16 g_xT[4 * DM * LSEQ];
__device__ __align__(1024) float g_stats[2 * 32 * 192];
__device__ __align__(1024) uint2 g_colsum[3 * DM];
__device__ __align__(1024) uint4 g_halo[32 * 8 * 256];
__device__ __align__(1024) uint4 g_rows[2 * LSEQ];
#define TS(i) do { } while (0)
#define TSW(k) do { if ((threadIdx.x & 127) == 0) TS(16 + layer * 56 + (threadIdx.x >> 7) * 20 + (k)); } while (0)
#define TSG(k) do { } while (0)

#define RETRY(i) do { } while (0)
#define LTS(i) do { } while (0)

struct Params {
  CUtensorMap mapX, mapW3, mapXT, mapOut, mapWo;
  const bf16 *wqkv, *a_re, *a_im, *b_re, *b_im, *c_re, *c_im, *log_dt, *dskip;
};

__device__ __forceinline__ uint32_t s32(const void* p) { return (uint32_t)__cvta_generic_to_shared(p); }
__device__ __forceinline__ void mbar_init(uint32_t b, int c) { asm volatile("mbarrier.init.shared::cta.b64 [%0], %1;" ::"r"(b), "r"(c) : "memory"); }
__device__ __forceinline__ void mbar_expect(uint32_t b, int bytes) { asm volatile("mbarrier.arrive.expect_tx.shared::cta.b64 _, [%0], %1;" ::"r"(b), "r"(bytes) : "memory"); }
__device__ __forceinline__ void mbar_arrive(uint32_t b) { asm volatile("mbarrier.arrive.shared::cta.b64 _, [%0];" ::"r"(b) : "memory"); }
__device__ __forceinline__ void mbar_wait(uint32_t b, int parity) {
  asm volatile("{\n.reg .pred p;\nWAIT_LOOP:\nmbarrier.try_wait.parity.shared::cta.b64 p, [%0], %1;\n@p bra WAIT_DONE;\nbra WAIT_LOOP;\nWAIT_DONE:\n}" ::"r"(b), "r"(parity) : "memory");
}
__device__ __forceinline__ bool mbar_test(uint32_t b, int parity) {
  uint32_t ok;
  asm volatile("{\n.reg .pred p;\nmbarrier.test_wait.parity.shared::cta.b64 p, [%1], %2;\nselp.u32 %0, 1, 0, p;\n}" : "=r"(ok) : "r"(b), "r"(parity) : "memory");
  return ok != 0;
}
__device__ __forceinline__ int opaque_tid() { int v; asm volatile("mov.u32 %0, %%tid.x;" : "=r"(v)); return v; }
__device__ __forceinline__ bool elect_one() {
  uint32_t r;
  asm volatile("{\n.reg .pred p;\nelect.sync _|p, 0xffffffff;\nselp.u32 %0, 1, 0, p;\n}" : "=r"(r));
  return r != 0;
}
__device__ __forceinline__ void tma_ld(uint32_t dst, const CUtensorMap* m, int c0, int c1, uint32_t bar) {
  asm volatile("cp.async.bulk.tensor.2d.shared::cluster.global.mbarrier::complete_tx::bytes [%0], [%1, {%3, %4}], [%2];"
               ::"r"(dst), "l"(m), "r"(bar), "r"(c0), "r"(c1) : "memory");
}
__device__ __forceinline__ void tma_ld3(uint32_t dst, const CUtensorMap* m, int c0, int c1, int c2, uint32_t bar) {
  asm volatile("cp.async.bulk.tensor.3d.shared::cluster.global.mbarrier::complete_tx::bytes [%0], [%1, {%3, %4, %5}], [%2];"
               ::"r"(dst), "l"(m), "r"(bar), "r"(c0), "r"(c1), "r"(c2) : "memory");
}
__device__ __forceinline__ void tma_ld5(uint32_t dst, const CUtensorMap* m, int c0, int c4, uint32_t bar) {
  asm volatile("cp.async.bulk.tensor.5d.shared::cluster.global.mbarrier::complete_tx::bytes [%0], [%1, {%3, 0, 0, 0, %4}], [%2];"
               ::"r"(dst), "l"(m), "r"(bar), "r"(c0), "r"(c4) : "memory");
}
__device__ __forceinline__ void tma_prefetch5(const CUtensorMap* m, int c0, int c4) {
  asm volatile("cp.async.bulk.prefetch.tensor.5d.L2.global.tile [%0, {%1, 0, 0, 0, %2}];" ::"l"(m), "r"(c0), "r"(c4) : "memory");
}
__device__ __forceinline__ void tma_prefetch2(const CUtensorMap* m, int c0, int c1) {
  asm volatile("cp.async.bulk.prefetch.tensor.2d.L2.global.tile [%0, {%1, %2}];" ::"l"(m), "r"(c0), "r"(c1) : "memory");
}
__device__ __forceinline__ void tma_prefetch3(const CUtensorMap* m, int c0, int c1, int c2) {
  asm volatile("cp.async.bulk.prefetch.tensor.3d.L2.global.tile [%0, {%1, %2, %3}];" ::"l"(m), "r"(c0), "r"(c1), "r"(c2) : "memory");
}
__device__ __forceinline__ void tma_st(const CUtensorMap* m, int c0, int c1, uint32_t src) {
  asm volatile("cp.async.bulk.tensor.2d.global.shared::cta.bulk_group [%0, {%2, %3}], [%1];" ::"l"(m), "r"(src), "r"(c0), "r"(c1) : "memory");
}
__device__ __forceinline__ void bulk_ld(uint32_t dst, const void* src, int bytes, uint32_t bar) {
  asm volatile("cp.async.bulk.shared::cluster.global.mbarrier::complete_tx::bytes [%0], [%1], %2, [%3];" ::"r"(dst), "l"(src), "r"(bytes), "r"(bar) : "memory");
}
__device__ __forceinline__ void bulk_st(void* dst, uint32_t src, int bytes) {
  asm volatile("cp.async.bulk.global.shared::cta.bulk_group [%0], [%1], %2;" ::"l"(dst), "r"(src), "r"(bytes) : "memory");
}
__device__ __forceinline__ void bulk_red_add_f32(void* dst, uint32_t src, int bytes) {
  asm volatile("cp.reduce.async.bulk.global.shared::cta.bulk_group.add.f32 [%0], [%1], %2;" ::"l"(dst), "r"(src), "r"(bytes) : "memory");
}
__device__ __forceinline__ void bulk_commit() { asm volatile("cp.async.bulk.commit_group;" ::: "memory"); }
__device__ __forceinline__ void bulk_wait_all() { asm volatile("cp.async.bulk.wait_group 0;" ::: "memory"); }
__device__ __forceinline__ void fence_async_smem() { asm volatile("fence.proxy.async.shared::cta;" ::: "memory"); }
__device__ __forceinline__ void fence_async_global() { asm volatile("fence.proxy.async.global;" ::: "memory"); }
__device__ __forceinline__ void bar_sync(int id, int n) { asm volatile("bar.sync %0, %1;" ::"r"(id), "r"(n) : "memory"); }
__device__ __forceinline__ void bar_arrive(int id, int n) { asm volatile("bar.arrive %0, %1;" ::"r"(id), "r"(n) : "memory"); }
__device__ __forceinline__ bool bar_or(int id, int n, bool v) {
  uint32_t r;
  asm volatile("{\n.reg .pred p, q;\nsetp.ne.u32 q, %3, 0;\nbar.red.or.pred p, %1, %2, q;\nselp.u32 %0, 1, 0, p;\n}" : "=r"(r) : "r"(id), "r"(n), "r"((uint32_t)v) : "memory");
  return r != 0;
}
__device__ __forceinline__ void bulk_wait_read() { asm volatile("cp.async.bulk.wait_group.read 0;" ::: "memory"); }
__device__ __forceinline__ void stg128(void* p, uint4 v) { asm volatile("st.relaxed.gpu.global.v4.u32 [%0], {%1,%2,%3,%4};" ::"l"(p), "r"(v.x), "r"(v.y), "r"(v.z), "r"(v.w) : "memory"); }
constexpr uint32_t UNSET = 0xffffffffu;
constexpr int MAX_RETRY = 1 << 16;
__device__ __forceinline__ void wg_fence() { asm volatile("wgmma.fence.sync.aligned;" ::: "memory"); }
__device__ __forceinline__ void wg_commit() { asm volatile("wgmma.commit_group.sync.aligned;" ::: "memory"); }
template <int N> __device__ __forceinline__ void wg_wait() { asm volatile("wgmma.wait_group.sync.aligned %0;" ::"n"(N) : "memory"); }
__device__ __forceinline__ uint64_t mkdesc(uint32_t addr, uint32_t lbo, uint32_t sbo, int sw) {
  return (uint64_t)((addr & 0x3FFFF) >> 4) | ((uint64_t)(lbo >> 4) << 16) | ((uint64_t)(sbo >> 4) << 32) | ((uint64_t)sw << 62);
}
__device__ __forceinline__ void ldsm4(uint32_t* r, uint32_t a) {
  asm volatile("ldmatrix.sync.aligned.m8n8.x4.shared.b16 {%0,%1,%2,%3}, [%4];" : "=r"(r[0]), "=r"(r[1]), "=r"(r[2]), "=r"(r[3]) : "r"(a) : "memory");
}
__device__ __forceinline__ void ldsm4t(uint32_t* r, uint32_t a) {
  asm volatile("ldmatrix.sync.aligned.m8n8.x4.trans.shared.b16 {%0,%1,%2,%3}, [%4];" : "=r"(r[0]), "=r"(r[1]), "=r"(r[2]), "=r"(r[3]) : "r"(a) : "memory");
}
__device__ __forceinline__ void stsm4(uint32_t a, uint32_t r0, uint32_t r1, uint32_t r2, uint32_t r3) {
  asm volatile("stmatrix.sync.aligned.m8n8.x4.shared.b16 [%0], {%1,%2,%3,%4};" ::"r"(a), "r"(r0), "r"(r1), "r"(r2), "r"(r3) : "memory");
}
__device__ __forceinline__ void stsm4t(uint32_t a, uint32_t r0, uint32_t r1, uint32_t r2, uint32_t r3) {
  asm volatile("stmatrix.sync.aligned.m8n8.x4.trans.shared.b16 [%0], {%1,%2,%3,%4};" ::"r"(a), "r"(r0), "r"(r1), "r"(r2), "r"(r3) : "memory");
}
__device__ __forceinline__ uint32_t movm_t(uint32_t a) { uint32_t r; asm volatile("movmatrix.sync.aligned.m8n8.trans.b16 %0, %1;" : "=r"(r) : "r"(a)); return r; }
__device__ __forceinline__ uint32_t lds32(uint32_t a) { uint32_t v; asm volatile("ld.shared.b32 %0, [%1];" : "=r"(v) : "r"(a) : "memory"); return v; }
__device__ __forceinline__ float2 lds64f(uint32_t a) { float2 v; asm volatile("ld.shared.v2.f32 {%0,%1}, [%2];" : "=f"(v.x), "=f"(v.y) : "r"(a) : "memory"); return v; }
__device__ __forceinline__ float4 lds128f(uint32_t a) { float4 v; asm volatile("ld.shared.v4.f32 {%0,%1,%2,%3}, [%4];" : "=f"(v.x), "=f"(v.y), "=f"(v.z), "=f"(v.w) : "r"(a) : "memory"); return v; }
__device__ __forceinline__ uint4 lds128(uint32_t a) { uint4 v; asm volatile("ld.shared.v4.b32 {%0,%1,%2,%3}, [%4];" : "=r"(v.x), "=r"(v.y), "=r"(v.z), "=r"(v.w) : "r"(a) : "memory"); return v; }
__device__ __forceinline__ void sts128(uint32_t a, uint4 v) { asm volatile("st.shared.v4.b32 [%0], {%1,%2,%3,%4};" ::"r"(a), "r"(v.x), "r"(v.y), "r"(v.z), "r"(v.w) : "memory"); }
__device__ __forceinline__ void sts128f(uint32_t a, float x, float y, float z, float w) { asm volatile("st.shared.v4.f32 [%0], {%1,%2,%3,%4};" ::"r"(a), "f"(x), "f"(y), "f"(z), "f"(w) : "memory"); }
__device__ __forceinline__ void sts32f(uint32_t a, float v) { asm volatile("st.shared.f32 [%0], %1;" ::"r"(a), "f"(v) : "memory"); }
__device__ __forceinline__ void sts16(uint32_t a, uint16_t v) { asm volatile("st.shared.u16 [%0], %1;" ::"r"(a), "h"(v) : "memory"); }
__device__ __forceinline__ uint32_t lds16(uint32_t a) { uint16_t v; asm volatile("ld.shared.u16 %0, [%1];" : "=h"(v) : "r"(a) : "memory"); return v; }
__device__ __forceinline__ uint32_t packbf(float lo, float hi) { uint32_t r; asm("cvt.rn.bf16x2.f32 %0, %1, %2;" : "=r"(r) : "f"(hi), "f"(lo)); return r; }
__device__ __forceinline__ float bf_lo(uint32_t v) { return __uint_as_float(v << 16); }
__device__ __forceinline__ float bf_hi(uint32_t v) { return __uint_as_float(v & 0xffff0000u); }
__device__ __forceinline__ float ex2(float x) { float r; asm("ex2.approx.ftz.f32 %0, %1;" : "=f"(r) : "f"(x)); return r; }
__device__ __forceinline__ float rsqrt_approx(float x) { float r; asm("rsqrt.approx.ftz.f32 %0, %1;" : "=f"(r) : "f"(x)); return r; }
__device__ __forceinline__ float rcp_approx(float x) { float r; asm("rcp.approx.ftz.f32 %0, %1;" : "=f"(r) : "f"(x)); return r; }
__device__ __forceinline__ void mma_bf16(float* d, const uint32_t* a, uint32_t b0, uint32_t b1) {
  asm("mma.sync.aligned.m16n8k16.row.col.f32.bf16.bf16.f32 {%0,%1,%2,%3}, {%4,%5,%6,%7}, {%8,%9}, {%0,%1,%2,%3};"
               : "+f"(d[0]), "+f"(d[1]), "+f"(d[2]), "+f"(d[3]) : "r"(a[0]), "r"(a[1]), "r"(a[2]), "r"(a[3]), "r"(b0), "r"(b1));
}
__device__ __forceinline__ void mma_tf32(float* d, float a0, float a1, float a2, float a3, float b0, float b1) {
  asm("mma.sync.aligned.m16n8k8.row.col.f32.tf32.tf32.f32 {%0,%1,%2,%3}, {%4,%5,%6,%7}, {%8,%9}, {%0,%1,%2,%3};"
               : "+f"(d[0]), "+f"(d[1]), "+f"(d[2]), "+f"(d[3])
               : "r"(__float_as_uint(a0)), "r"(__float_as_uint(a1)), "r"(__float_as_uint(a2)), "r"(__float_as_uint(a3)),
                 "r"(__float_as_uint(b0)), "r"(__float_as_uint(b1)));
}
__device__ __forceinline__ void red_release(unsigned* p) { asm volatile("red.release.gpu.global.add.u32 [%0], 1;" ::"l"(p) : "memory"); }
__device__ __forceinline__ void red_relaxed(unsigned* p) { asm volatile("red.relaxed.gpu.global.add.u32 [%0], 1;" ::"l"(p) : "memory"); }
__device__ __forceinline__ unsigned ld_relaxed(const unsigned* p) { unsigned v; asm volatile("ld.relaxed.gpu.global.u32 %0, [%1];" : "=r"(v) : "l"(p) : "memory"); return v; }
__device__ __forceinline__ void spin_until(const unsigned* p, unsigned target) {
  int it = 0;
  while ((int)(ld_relaxed(p) - target) < 0) {
    if (++it > (1 << 23)) __trap();
  }
}
__device__ __forceinline__ uint4 ldcg128(const void* p) { uint4 v; asm volatile("ld.global.cg.v4.b32 {%0,%1,%2,%3}, [%4];" : "=r"(v.x), "=r"(v.y), "=r"(v.z), "=r"(v.w) : "l"(p) : "memory"); return v; }
__device__ __forceinline__ uint4 ld_tagged(const uint4* p) { uint4 v; asm volatile("ld.relaxed.gpu.global.v4.u32 {%0,%1,%2,%3}, [%4];" : "=r"(v.x), "=r"(v.y), "=r"(v.z), "=r"(v.w) : "l"(p) : "memory"); return v; }
__device__ __forceinline__ void st_tagged(uint4* p, uint32_t a, uint32_t b, uint32_t tag) { asm volatile("st.relaxed.gpu.global.v4.u32 [%0], {%1,%2,%3,%2};" ::"l"(p), "r"(a), "r"(tag), "r"(b) : "memory"); }
__device__ __forceinline__ void st_tagged3(uint4* p, uint32_t a, uint32_t b, uint32_t c, uint32_t tag) { asm volatile("st.relaxed.gpu.global.v4.u32 [%0], {%1,%2,%3,%4};" ::"l"(p), "r"(a), "r"(b), "r"(c), "r"(tag) : "memory"); }
__device__ __forceinline__ uint4 poll_tagged(const uint4* p, uint32_t tag) {
  uint4 v = ld_tagged(p);
  int it = 0;
  while (v.y != tag || v.w != tag) {
    if (++it > (1 << 22)) __trap();
    v = ld_tagged(p);
  }
  return v;
}
__device__ __forceinline__ uint32_t hadd2(uint32_t a, uint32_t b) { uint32_t r; asm("add.rn.bf16x2 %0, %1, %2;" : "=r"(r) : "r"(a), "r"(b)); return r; }
__device__ __forceinline__ uint32_t hmul2(uint32_t a, uint32_t b) { uint32_t r; asm("mul.rn.bf16x2 %0, %1, %2;" : "=r"(r) : "r"(a), "r"(b)); return r; }

__device__ __forceinline__ uint32_t hfma2(uint32_t a, uint32_t b, uint32_t c) { uint32_t r; asm("fma.rn.bf16x2 %0, %1, %2, %3;" : "=r"(r) : "r"(a), "r"(b), "r"(c)); return r; }
__device__ __forceinline__ void sts32(uint32_t a, uint32_t v) { asm volatile("st.shared.u32 [%0], %1;" ::"r"(a), "r"(v) : "memory"); }

template <int N> __device__ __forceinline__ void acc_fence(float* a) {
#pragma unroll
  for (int i = 0; i < N; i++) asm volatile("" : "+f"(a[i]) :: "memory");
}

template<int N,int TB> __device__ __forceinline__ void wgmma_rs(float* d, const uint32_t* a, uint64_t db, int sd);
template<int N,int TA,int TB> __device__ __forceinline__ void wgmma_ss(float* d, uint64_t da, uint64_t db, int sd);
template<> __device__ __forceinline__ void wgmma_rs<64,0>(float* d, const uint32_t* a, uint64_t db, int sd) {
  asm volatile("{\n.reg .pred p;\nsetp.ne.b32 p, %37, 0;\nwgmma.mma_async.sync.aligned.m64n64k16.f32.bf16.bf16 {%0,%1,%2,%3,%4,%5,%6,%7,%8,%9,%10,%11,%12,%13,%14,%15,%16,%17,%18,%19,%20,%21,%22,%23,%24,%25,%26,%27,%28,%29,%30,%31}, {%32,%33,%34,%35}, %36, p, 1, 1, 0;\n}\n"
   : "+f"(d[0]),"+f"(d[1]),"+f"(d[2]),"+f"(d[3]),"+f"(d[4]),"+f"(d[5]),"+f"(d[6]),"+f"(d[7]),"+f"(d[8]),"+f"(d[9]),"+f"(d[10]),"+f"(d[11]),"+f"(d[12]),"+f"(d[13]),"+f"(d[14]),"+f"(d[15]),"+f"(d[16]),"+f"(d[17]),"+f"(d[18]),"+f"(d[19]),"+f"(d[20]),"+f"(d[21]),"+f"(d[22]),"+f"(d[23]),"+f"(d[24]),"+f"(d[25]),"+f"(d[26]),"+f"(d[27]),"+f"(d[28]),"+f"(d[29]),"+f"(d[30]),"+f"(d[31])
   : "r"(a[0]), "r"(a[1]), "r"(a[2]), "r"(a[3]), "l"(db), "r"(sd));
}
template<> __device__ __forceinline__ void wgmma_rs<56,0>(float* d, const uint32_t* a, uint64_t db, int sd) {
  asm volatile("{\n.reg .pred p;\nsetp.ne.b32 p, %33, 0;\nwgmma.mma_async.sync.aligned.m64n56k16.f32.bf16.bf16 {%0,%1,%2,%3,%4,%5,%6,%7,%8,%9,%10,%11,%12,%13,%14,%15,%16,%17,%18,%19,%20,%21,%22,%23,%24,%25,%26,%27}, {%28,%29,%30,%31}, %32, p, 1, 1, 0;\n}\n"
   : "+f"(d[0]),"+f"(d[1]),"+f"(d[2]),"+f"(d[3]),"+f"(d[4]),"+f"(d[5]),"+f"(d[6]),"+f"(d[7]),"+f"(d[8]),"+f"(d[9]),"+f"(d[10]),"+f"(d[11]),"+f"(d[12]),"+f"(d[13]),"+f"(d[14]),"+f"(d[15]),"+f"(d[16]),"+f"(d[17]),"+f"(d[18]),"+f"(d[19]),"+f"(d[20]),"+f"(d[21]),"+f"(d[22]),"+f"(d[23]),"+f"(d[24]),"+f"(d[25]),"+f"(d[26]),"+f"(d[27])
   : "r"(a[0]), "r"(a[1]), "r"(a[2]), "r"(a[3]), "l"(db), "r"(sd));
}
template<> __device__ __forceinline__ void wgmma_rs<48,0>(float* d, const uint32_t* a, uint64_t db, int sd) {
  asm volatile("{\n.reg .pred p;\nsetp.ne.b32 p, %29, 0;\nwgmma.mma_async.sync.aligned.m64n48k16.f32.bf16.bf16 {%0,%1,%2,%3,%4,%5,%6,%7,%8,%9,%10,%11,%12,%13,%14,%15,%16,%17,%18,%19,%20,%21,%22,%23}, {%24,%25,%26,%27}, %28, p, 1, 1, 0;\n}\n"
   : "+f"(d[0]),"+f"(d[1]),"+f"(d[2]),"+f"(d[3]),"+f"(d[4]),"+f"(d[5]),"+f"(d[6]),"+f"(d[7]),"+f"(d[8]),"+f"(d[9]),"+f"(d[10]),"+f"(d[11]),"+f"(d[12]),"+f"(d[13]),"+f"(d[14]),"+f"(d[15]),"+f"(d[16]),"+f"(d[17]),"+f"(d[18]),"+f"(d[19]),"+f"(d[20]),"+f"(d[21]),"+f"(d[22]),"+f"(d[23])
   : "r"(a[0]), "r"(a[1]), "r"(a[2]), "r"(a[3]), "l"(db), "r"(sd));
}
template<> __device__ __forceinline__ void wgmma_rs<40,0>(float* d, const uint32_t* a, uint64_t db, int sd) {
  asm volatile("{\n.reg .pred p;\nsetp.ne.b32 p, %25, 0;\nwgmma.mma_async.sync.aligned.m64n40k16.f32.bf16.bf16 {%0,%1,%2,%3,%4,%5,%6,%7,%8,%9,%10,%11,%12,%13,%14,%15,%16,%17,%18,%19}, {%20,%21,%22,%23}, %24, p, 1, 1, 0;\n}\n"
   : "+f"(d[0]),"+f"(d[1]),"+f"(d[2]),"+f"(d[3]),"+f"(d[4]),"+f"(d[5]),"+f"(d[6]),"+f"(d[7]),"+f"(d[8]),"+f"(d[9]),"+f"(d[10]),"+f"(d[11]),"+f"(d[12]),"+f"(d[13]),"+f"(d[14]),"+f"(d[15]),"+f"(d[16]),"+f"(d[17]),"+f"(d[18]),"+f"(d[19])
   : "r"(a[0]), "r"(a[1]), "r"(a[2]), "r"(a[3]), "l"(db), "r"(sd));
}
template<> __device__ __forceinline__ void wgmma_rs<32,0>(float* d, const uint32_t* a, uint64_t db, int sd) {
  asm volatile("{\n.reg .pred p;\nsetp.ne.b32 p, %21, 0;\nwgmma.mma_async.sync.aligned.m64n32k16.f32.bf16.bf16 {%0,%1,%2,%3,%4,%5,%6,%7,%8,%9,%10,%11,%12,%13,%14,%15}, {%16,%17,%18,%19}, %20, p, 1, 1, 0;\n}\n"
   : "+f"(d[0]),"+f"(d[1]),"+f"(d[2]),"+f"(d[3]),"+f"(d[4]),"+f"(d[5]),"+f"(d[6]),"+f"(d[7]),"+f"(d[8]),"+f"(d[9]),"+f"(d[10]),"+f"(d[11]),"+f"(d[12]),"+f"(d[13]),"+f"(d[14]),"+f"(d[15])
   : "r"(a[0]), "r"(a[1]), "r"(a[2]), "r"(a[3]), "l"(db), "r"(sd));
}
template<> __device__ __forceinline__ void wgmma_rs<24,0>(float* d, const uint32_t* a, uint64_t db, int sd) {
  asm volatile("{\n.reg .pred p;\nsetp.ne.b32 p, %17, 0;\nwgmma.mma_async.sync.aligned.m64n24k16.f32.bf16.bf16 {%0,%1,%2,%3,%4,%5,%6,%7,%8,%9,%10,%11}, {%12,%13,%14,%15}, %16, p, 1, 1, 0;\n}\n"
   : "+f"(d[0]),"+f"(d[1]),"+f"(d[2]),"+f"(d[3]),"+f"(d[4]),"+f"(d[5]),"+f"(d[6]),"+f"(d[7]),"+f"(d[8]),"+f"(d[9]),"+f"(d[10]),"+f"(d[11])
   : "r"(a[0]), "r"(a[1]), "r"(a[2]), "r"(a[3]), "l"(db), "r"(sd));
}
template<> __device__ __forceinline__ void wgmma_rs<16,0>(float* d, const uint32_t* a, uint64_t db, int sd) {
  asm volatile("{\n.reg .pred p;\nsetp.ne.b32 p, %13, 0;\nwgmma.mma_async.sync.aligned.m64n16k16.f32.bf16.bf16 {%0,%1,%2,%3,%4,%5,%6,%7}, {%8,%9,%10,%11}, %12, p, 1, 1, 0;\n}\n"
   : "+f"(d[0]),"+f"(d[1]),"+f"(d[2]),"+f"(d[3]),"+f"(d[4]),"+f"(d[5]),"+f"(d[6]),"+f"(d[7])
   : "r"(a[0]), "r"(a[1]), "r"(a[2]), "r"(a[3]), "l"(db), "r"(sd));
}
template<> __device__ __forceinline__ void wgmma_rs<8,0>(float* d, const uint32_t* a, uint64_t db, int sd) {
  asm volatile("{\n.reg .pred p;\nsetp.ne.b32 p, %9, 0;\nwgmma.mma_async.sync.aligned.m64n8k16.f32.bf16.bf16 {%0,%1,%2,%3}, {%4,%5,%6,%7}, %8, p, 1, 1, 0;\n}\n"
   : "+f"(d[0]),"+f"(d[1]),"+f"(d[2]),"+f"(d[3])
   : "r"(a[0]), "r"(a[1]), "r"(a[2]), "r"(a[3]), "l"(db), "r"(sd));
}
template<> __device__ __forceinline__ void wgmma_ss<64,1,0>(float* d, uint64_t da, uint64_t db, int sd) {
  asm volatile("{\n.reg .pred p;\nsetp.ne.b32 p, %34, 0;\nwgmma.mma_async.sync.aligned.m64n64k16.f32.bf16.bf16 {%0,%1,%2,%3,%4,%5,%6,%7,%8,%9,%10,%11,%12,%13,%14,%15,%16,%17,%18,%19,%20,%21,%22,%23,%24,%25,%26,%27,%28,%29,%30,%31}, %32, %33, p, 1, 1, 1, 0;\n}\n"
   : "+f"(d[0]),"+f"(d[1]),"+f"(d[2]),"+f"(d[3]),"+f"(d[4]),"+f"(d[5]),"+f"(d[6]),"+f"(d[7]),"+f"(d[8]),"+f"(d[9]),"+f"(d[10]),"+f"(d[11]),"+f"(d[12]),"+f"(d[13]),"+f"(d[14]),"+f"(d[15]),"+f"(d[16]),"+f"(d[17]),"+f"(d[18]),"+f"(d[19]),"+f"(d[20]),"+f"(d[21]),"+f"(d[22]),"+f"(d[23]),"+f"(d[24]),"+f"(d[25]),"+f"(d[26]),"+f"(d[27]),"+f"(d[28]),"+f"(d[29]),"+f"(d[30]),"+f"(d[31])
   : "l"(da), "l"(db), "r"(sd));
}
template<> __device__ __forceinline__ void wgmma_ss<64,0,1>(float* d, uint64_t da, uint64_t db, int sd) {
  asm volatile("{\n.reg .pred p;\nsetp.ne.b32 p, %34, 0;\nwgmma.mma_async.sync.aligned.m64n64k16.f32.bf16.bf16 {%0,%1,%2,%3,%4,%5,%6,%7,%8,%9,%10,%11,%12,%13,%14,%15,%16,%17,%18,%19,%20,%21,%22,%23,%24,%25,%26,%27,%28,%29,%30,%31}, %32, %33, p, 1, 1, 0, 1;\n}\n"
   : "+f"(d[0]),"+f"(d[1]),"+f"(d[2]),"+f"(d[3]),"+f"(d[4]),"+f"(d[5]),"+f"(d[6]),"+f"(d[7]),"+f"(d[8]),"+f"(d[9]),"+f"(d[10]),"+f"(d[11]),"+f"(d[12]),"+f"(d[13]),"+f"(d[14]),"+f"(d[15]),"+f"(d[16]),"+f"(d[17]),"+f"(d[18]),"+f"(d[19]),"+f"(d[20]),"+f"(d[21]),"+f"(d[22]),"+f"(d[23]),"+f"(d[24]),"+f"(d[25]),"+f"(d[26]),"+f"(d[27]),"+f"(d[28]),"+f"(d[29]),"+f"(d[30]),"+f"(d[31])
   : "l"(da), "l"(db), "r"(sd));
}
template<> __device__ __forceinline__ void wgmma_ss<192,0,1>(float* d, uint64_t da, uint64_t db, int sd) {
  asm volatile("{\n.reg .pred p;\nsetp.ne.b32 p, %98, 0;\nwgmma.mma_async.sync.aligned.m64n192k16.f32.bf16.bf16 {%0,%1,%2,%3,%4,%5,%6,%7,%8,%9,%10,%11,%12,%13,%14,%15,%16,%17,%18,%19,%20,%21,%22,%23,%24,%25,%26,%27,%28,%29,%30,%31,%32,%33,%34,%35,%36,%37,%38,%39,%40,%41,%42,%43,%44,%45,%46,%47,%48,%49,%50,%51,%52,%53,%54,%55,%56,%57,%58,%59,%60,%61,%62,%63,%64,%65,%66,%67,%68,%69,%70,%71,%72,%73,%74,%75,%76,%77,%78,%79,%80,%81,%82,%83,%84,%85,%86,%87,%88,%89,%90,%91,%92,%93,%94,%95}, %96, %97, p, 1, 1, 0, 1;\n}\n"
   : "+f"(d[0]),"+f"(d[1]),"+f"(d[2]),"+f"(d[3]),"+f"(d[4]),"+f"(d[5]),"+f"(d[6]),"+f"(d[7]),"+f"(d[8]),"+f"(d[9]),"+f"(d[10]),"+f"(d[11]),"+f"(d[12]),"+f"(d[13]),"+f"(d[14]),"+f"(d[15]),"+f"(d[16]),"+f"(d[17]),"+f"(d[18]),"+f"(d[19]),"+f"(d[20]),"+f"(d[21]),"+f"(d[22]),"+f"(d[23]),"+f"(d[24]),"+f"(d[25]),"+f"(d[26]),"+f"(d[27]),"+f"(d[28]),"+f"(d[29]),"+f"(d[30]),"+f"(d[31]),"+f"(d[32]),"+f"(d[33]),"+f"(d[34]),"+f"(d[35]),"+f"(d[36]),"+f"(d[37]),"+f"(d[38]),"+f"(d[39]),"+f"(d[40]),"+f"(d[41]),"+f"(d[42]),"+f"(d[43]),"+f"(d[44]),"+f"(d[45]),"+f"(d[46]),"+f"(d[47]),"+f"(d[48]),"+f"(d[49]),"+f"(d[50]),"+f"(d[51]),"+f"(d[52]),"+f"(d[53]),"+f"(d[54]),"+f"(d[55]),"+f"(d[56]),"+f"(d[57]),"+f"(d[58]),"+f"(d[59]),"+f"(d[60]),"+f"(d[61]),"+f"(d[62]),"+f"(d[63]),"+f"(d[64]),"+f"(d[65]),"+f"(d[66]),"+f"(d[67]),"+f"(d[68]),"+f"(d[69]),"+f"(d[70]),"+f"(d[71]),"+f"(d[72]),"+f"(d[73]),"+f"(d[74]),"+f"(d[75]),"+f"(d[76]),"+f"(d[77]),"+f"(d[78]),"+f"(d[79]),"+f"(d[80]),"+f"(d[81]),"+f"(d[82]),"+f"(d[83]),"+f"(d[84]),"+f"(d[85]),"+f"(d[86]),"+f"(d[87]),"+f"(d[88]),"+f"(d[89]),"+f"(d[90]),"+f"(d[91]),"+f"(d[92]),"+f"(d[93]),"+f"(d[94]),"+f"(d[95])
   : "l"(da), "l"(db), "r"(sd));
}
template<> __device__ __forceinline__ void wgmma_ss<192,1,1>(float* d, uint64_t da, uint64_t db, int sd) {
  asm volatile("{\n.reg .pred p;\nsetp.ne.b32 p, %98, 0;\nwgmma.mma_async.sync.aligned.m64n192k16.f32.bf16.bf16 {%0,%1,%2,%3,%4,%5,%6,%7,%8,%9,%10,%11,%12,%13,%14,%15,%16,%17,%18,%19,%20,%21,%22,%23,%24,%25,%26,%27,%28,%29,%30,%31,%32,%33,%34,%35,%36,%37,%38,%39,%40,%41,%42,%43,%44,%45,%46,%47,%48,%49,%50,%51,%52,%53,%54,%55,%56,%57,%58,%59,%60,%61,%62,%63,%64,%65,%66,%67,%68,%69,%70,%71,%72,%73,%74,%75,%76,%77,%78,%79,%80,%81,%82,%83,%84,%85,%86,%87,%88,%89,%90,%91,%92,%93,%94,%95}, %96, %97, p, 1, 1, 1, 1;\n}\n"
   : "+f"(d[0]),"+f"(d[1]),"+f"(d[2]),"+f"(d[3]),"+f"(d[4]),"+f"(d[5]),"+f"(d[6]),"+f"(d[7]),"+f"(d[8]),"+f"(d[9]),"+f"(d[10]),"+f"(d[11]),"+f"(d[12]),"+f"(d[13]),"+f"(d[14]),"+f"(d[15]),"+f"(d[16]),"+f"(d[17]),"+f"(d[18]),"+f"(d[19]),"+f"(d[20]),"+f"(d[21]),"+f"(d[22]),"+f"(d[23]),"+f"(d[24]),"+f"(d[25]),"+f"(d[26]),"+f"(d[27]),"+f"(d[28]),"+f"(d[29]),"+f"(d[30]),"+f"(d[31]),"+f"(d[32]),"+f"(d[33]),"+f"(d[34]),"+f"(d[35]),"+f"(d[36]),"+f"(d[37]),"+f"(d[38]),"+f"(d[39]),"+f"(d[40]),"+f"(d[41]),"+f"(d[42]),"+f"(d[43]),"+f"(d[44]),"+f"(d[45]),"+f"(d[46]),"+f"(d[47]),"+f"(d[48]),"+f"(d[49]),"+f"(d[50]),"+f"(d[51]),"+f"(d[52]),"+f"(d[53]),"+f"(d[54]),"+f"(d[55]),"+f"(d[56]),"+f"(d[57]),"+f"(d[58]),"+f"(d[59]),"+f"(d[60]),"+f"(d[61]),"+f"(d[62]),"+f"(d[63]),"+f"(d[64]),"+f"(d[65]),"+f"(d[66]),"+f"(d[67]),"+f"(d[68]),"+f"(d[69]),"+f"(d[70]),"+f"(d[71]),"+f"(d[72]),"+f"(d[73]),"+f"(d[74]),"+f"(d[75]),"+f"(d[76]),"+f"(d[77]),"+f"(d[78]),"+f"(d[79]),"+f"(d[80]),"+f"(d[81]),"+f"(d[82]),"+f"(d[83]),"+f"(d[84]),"+f"(d[85]),"+f"(d[86]),"+f"(d[87]),"+f"(d[88]),"+f"(d[89]),"+f"(d[90]),"+f"(d[91]),"+f"(d[92]),"+f"(d[93]),"+f"(d[94]),"+f"(d[95])
   : "l"(da), "l"(db), "r"(sd));
}

template <bool TR>
__device__ __forceinline__ void gemm_section(float* acc, float& mean0, float& mean1, float& rstd0, float& rstd1,
                                             uint32_t sb, int blk, int hg, int wg, int w, int lane) {
  constexpr int layer = TR ? 1 : 0;
  constexpr int TURN = TR ? TURN1 : TURN0;
  constexpr int LSTAT = TURN < 4 ? TURN - 1 : 3;
  const uint32_t bar = sb + SM_BAR;
  const int g = lane >> 2, t = lane & 3;
  const bool leader = (w == 0) && (lane == 0);
  const int statpos = hg < 3 ? 1 : wg ? LSTAT : TR ? 3 : 2;
  const bool copy = hg >= 3 && wg == 0;
  const int cut = wg ? TURN : 4;
  auto wait_full = [&](int c) {
    mbar_wait(bar + 8 * (B_XF + 8 * wg + c), layer);
    mbar_wait(bar + 8 * (B_WF + c), layer);
  };
  auto peek = [&](int c) {
    const bool x = mbar_test(bar + 8 * (B_XF + 8 * wg + c), layer), y = mbar_test(bar + 8 * (B_WF + c), layer);
    return x && y;
  };
  const uint64_t da0 = mkdesc(sb, TR ? 8192 : 16, 1024, 1), db0 = mkdesc(sb, 8192, 1024, 1);
  uint32_t xt = wg ? 0xfedcba98u : 0x21043210u;
  uint64_t wt = 0x0816131005161310ull;
  uint64_t da = da0 + ((xt & 15) << 9), db = db0 + (16 << 9);
  auto issue = [&](int c, int first) {
    wg_fence();
#pragma unroll
    for (int ks = 0; ks < 4; ks++) wgmma_ss<192, TR ? 1 : 0, 1>(acc, da + (TR ? ks * 128 : ks * 2), db + ks * 128, !first || ks != 0);
    wg_commit();
    xt >>= 4; wt >>= 8;
    da = da0 + ((xt & 15) << 9); db = db0 + (((uint32_t)wt & 31) << 9);
  };
  wait_full(0);
  bool ready = peek(1);
  issue(0, 1);
  TSW(0);
#pragma unroll 1
  for (int c = 1; c < cut; c++) {
    if (!ready) wait_full(c);
    issue(c, 0);
    ready = peek(c + 1);
    wg_wait<1>();
    if (leader) mbar_arrive(bar + 8 * (B_DN + 8 * wg + c - 1));
    if (wg == 1 && c == cut - 1) {
      wg_wait<0>();
      if (leader) mbar_arrive(bar + 8 * (B_DN + 8 + c));
    }
    if (c == statpos) {
      mbar_wait(bar + 8 * (copy ? B_SC : B_XF + 8 * wg + hg), layer);
      uint32_t A[16];
      const uint32_t xb = sb + (copy ? P_R : 8 * wg + hg) * PG;
#pragma unroll
      for (int ks = 0; ks < 4; ks++) {
        if (!TR) {
          const int row = 16 * w + (lane & 15), kc = 2 * ks + (lane >> 4);
          ldsm4(&A[4 * ks], xb + row * 128 + ((kc ^ (row & 7)) << 4));
        } else {
          const int k = 16 * ks + (lane & 7) + 8 * (lane >> 4), pc = 2 * w + ((lane >> 3) & 1);
          ldsm4t(&A[4 * ks], xb + k * 128 + ((pc ^ (k & 7)) << 4));
        }
      }
      float s0 = 0.f, q0 = 0.f, s1 = 0.f, q1 = 0.f;
#pragma unroll
      for (int i = 0; i < 16; i += 2) {
        const float a = bf_lo(A[i]), b = bf_hi(A[i]), c_ = bf_lo(A[i + 1]), d = bf_hi(A[i + 1]);
        s0 += a + b; q0 = fmaf(a, a, q0); q0 = fmaf(b, b, q0);
        s1 += c_ + d; q1 = fmaf(c_, c_, q1); q1 = fmaf(d, d, q1);
      }
#pragma unroll
      for (int o = 1; o <= 2; o <<= 1) {
        s0 += __shfl_xor_sync(~0u, s0, o); q0 += __shfl_xor_sync(~0u, q0, o);
        s1 += __shfl_xor_sync(~0u, s1, o); q1 += __shfl_xor_sync(~0u, q1, o);
      }
      if (t < 2)
        asm volatile("red.relaxed.gpu.global.add.v4.f32 [%0], {%1,%2,%3,%4};" ::"l"(g_rows + layer * LSEQ + blk * 64 + 16 * w + g + 8 * t),
                     "f"(t ? s1 : s0), "f"(t ? q1 : q0), "f"(1.f), "f"(0.f) : "memory");
    }
  }
  if (wg == 1) {
#pragma unroll 1
    for (int c = cut; c < 8; c++) wait_full(c);
    ready = true;
    bar_sync(5, 256);
  }
#pragma unroll 1
  for (int c = cut; c < 8; c++) {
    if (!ready) wait_full(c);
    issue(c, 0);
    if (wg == 1) {
      wg_wait<2>();
      if (leader && c >= cut + 2) mbar_arrive(bar + 8 * (B_DN + 8 + c - 2));
    } else if (c == 7) {
      bar_arrive(5, 256);
    } else {
      ready = peek(c + 1);
      wg_wait<1>();
      if (leader) mbar_arrive(bar + 8 * (B_DN + c - 1));
    }
  }
  mbar_wait(bar + 8 * (B_LN + wg), layer);
  const float4 ln = lds128f(sb + ln_off(wg) + (8 * w + g) * 16);
  mean0 = ln.x; rstd0 = ln.y; mean1 = ln.z; rstd1 = ln.w;
  wg_wait<0>();
  acc_fence<96>(acc);
  if (leader) mbar_arrive(bar + 8 * (B_DN + 8 * wg + 7));
}

__device__ __forceinline__ void attn_phase(const Params& p, uint32_t sb, int layer, int rb, int hg, int wg, int w) {
  const int lane = opaque_tid() & 31;
  const int g = lane >> 2, t = lane & 3;
  const uint32_t bar = sb + SM_BAR;
  const int blk = 16 * wg + rb;
  float acc[96];
  float2 cs[24];
  float mean0, mean1, rstd0, rstd1;
  if (layer) gemm_section<true>(acc, mean0, mean1, rstd0, rstd1, sb, blk, hg, wg, w, lane);
  else gemm_section<false>(acc, mean0, mean1, rstd0, rstd1, sb, blk, hg, wg, w, lane);
  TSW(1);
#pragma unroll
  for (int j = 8; j < 24; j++) cs[j] = lds64f(sb + SM_CS + 4 * (8 * j + 2 * t));
  const uint32_t kvx = sb + (wg ? 22 : 0) * PG;

  uint32_t kb[4][8], vb[4][8], qa[4][4];
  {
    const float nm0 = -mean0 * rstd0, nm1 = -mean1 * rstd1;
    const int st_row = 16 * w + (lane & 7) + 8 * ((lane >> 3) & 1);
    const uint32_t st_base = kvx + st_row * 256;
    const bool sender = (w == 3 && blk < 31);
    uint4* halo = &g_halo[(blk * 8 + hg) * 256 + lane];
    uint32_t r[4][2][4];
#pragma unroll
    for (int h = 0; h < 4; h++) {
#pragma unroll
      for (int kv = 0; kv < 2; kv++) {
#pragma unroll
        for (int dh = 0; dh < 2; dh++) {
          const int j = 8 + kv * 8 + 2 * h + dh;
          const float2 c2 = cs[j];
          const float v0 = fmaf(acc[4 * j + 0], rstd0, nm0 * c2.x), v1 = fmaf(acc[4 * j + 1], rstd0, nm0 * c2.y);
          const float v2 = fmaf(acc[4 * j + 2], rstd1, nm1 * c2.x), v3 = fmaf(acc[4 * j + 3], rstd1, nm1 * c2.y);
          r[h][kv][2 * dh] = packbf(v0, v1);
          r[h][kv][2 * dh + 1] = packbf(v2, v3);
        }
      }
      if (sender) {
        stg128(halo + (2 * h) * 32, make_uint4(r[h][0][0], r[h][0][2], r[h][0][1], r[h][0][3]));
        stg128(halo + (2 * h + 1) * 32, make_uint4(r[h][1][0], r[h][1][1], r[h][1][2], r[h][1][3]));
      }
    }
#pragma unroll
    for (int j = 0; j < 8; j++) cs[j] = lds64f(sb + SM_CS + 4 * (8 * j + 2 * t));
    mbar_wait(bar + 8 * (B_DN + 7), layer);
#pragma unroll
    for (int h = 0; h < 4; h++) {
#pragma unroll
      for (int kv = 0; kv < 2; kv++) {
        const int chunk = 4 * h + 2 * kv + (lane >> 4);
        if (w < 3) stsm4(st_base + (((chunk & 8) | ((chunk ^ st_row) & 7)) << 4), r[h][kv][0], r[h][kv][1], r[h][kv][2], r[h][kv][3]);
      }
      kb[h][4] = r[h][0][0]; kb[h][5] = r[h][0][2]; kb[h][6] = r[h][0][1]; kb[h][7] = r[h][0][3];
      vb[h][4] = movm_t(r[h][1][0]); vb[h][5] = movm_t(r[h][1][1]); vb[h][6] = movm_t(r[h][1][2]); vb[h][7] = movm_t(r[h][1][3]);
    }
#pragma unroll
    for (int h = 0; h < 4; h++) {
#pragma unroll
      for (int dh = 0; dh < 2; dh++) {
        const int j = 2 * h + dh;
        const float2 c2 = cs[j];
        qa[h][2 * dh] = packbf(fmaf(-mean0, c2.x, acc[4 * j + 0]), fmaf(-mean0, c2.y, acc[4 * j + 1]));
        qa[h][2 * dh + 1] = packbf(fmaf(-mean1, c2.x, acc[4 * j + 2]), fmaf(-mean1, c2.y, acc[4 * j + 3]));
      }
    }
  }
  bar_sync(2 + wg, 128);
  TSW(2);
  {
    const uint32_t prev_base = kvx + (16 * w - 16) * 256;
    const int mi = lane >> 3;
    const int r = 8 * (mi >> 1) + (lane & 7), r2 = 8 * (mi & 1) + (lane & 7);
    if (w != 0) {
#pragma unroll
      for (int h = 0; h < 4; h++) {
        const int ch = 4 * h + (mi & 1), ch2 = 4 * h + 2 + (mi >> 1);
        ldsm4(&kb[h][0], prev_base + r * 256 + (((ch & 8) | ((ch ^ r) & 7)) << 4));
        ldsm4t(&vb[h][0], prev_base + r2 * 256 + (((ch2 & 8) | ((ch2 ^ r2) & 7)) << 4));
      }
    } else if (blk > 0) {
      uint4* src = &g_halo[((blk - 1) * 8 + hg) * 256 + lane];
      uint4 hv[8];
      int it = 0;
      bool ok;
      do {
        ok = true;
#pragma unroll
        for (int i = 0; i < 8; i++) hv[i] = ld_tagged(src + i * 32);
#pragma unroll
        for (int i = 0; i < 8; i++) ok = ok && hv[i].x != UNSET;
      } while (!__all_sync(~0u, ok) && ++it < (1 << 20));
      if (layer == 0) {
#pragma unroll
        for (int i = 0; i < 2; i++) stg128(src + i * 128 + (lane >> 1) * 6, make_uint4(UNSET, UNSET, UNSET, UNSET));
      }
#pragma unroll
      for (int h = 0; h < 4; h++) {
        kb[h][0] = hv[2 * h].x; kb[h][1] = hv[2 * h].y; kb[h][2] = hv[2 * h].z; kb[h][3] = hv[2 * h].w;
        vb[h][0] = movm_t(hv[2 * h + 1].x); vb[h][1] = movm_t(hv[2 * h + 1].y);
        vb[h][2] = movm_t(hv[2 * h + 1].z); vb[h][3] = movm_t(hv[2 * h + 1].w);
      }
    } else {
#pragma unroll
      for (int h = 0; h < 4; h++)
#pragma unroll
        for (int k = 0; k < 4; k++) kb[h][k] = vb[h][k] = 0u;
    }
    TSW(3);
  }
  mbar_wait(bar + 8 * (B_DN + 15), layer);
  TSW(4);

  const bool first = (blk == 0 && w == 0);
  const int e = t - (g >> 1);
  const bool par = g & 1, epos = e >= 1;
  const uint32_t pmask = par ? 0xffff0000u : 0x0000ffffu;
  const uint32_t mB0 = epos ? pmask : 0u, mB1 = epos ? 0u : pmask;
  const float cl2 = 0.25f * 1.4426950408889634f;
  const float sc0 = rstd0 * cl2, sc1 = rstd1 * cl2;
  const float NEG = -INFINITY;
  float vA0[4], vB0[4], vA1[4], vB1[4];
#pragma unroll
  for (int h = 0; h < 4; h++) {
    float S[4][4];
#pragma unroll
    for (int j = 0; j < 4; j++) {
      S[j][0] = S[j][1] = S[j][2] = S[j][3] = 0.f;
      mma_bf16(S[j], qa[h], kb[h][2 * j], kb[h][2 * j + 1]);
    }
    vA0[h] = par ? S[1][1] : S[1][0];
    vB0[h] = epos ? (par ? S[0][1] : S[0][0]) : (par ? S[2][1] : S[2][0]);
    vA1[h] = par ? S[2][3] : S[2][2];
    vB1[h] = epos ? (par ? S[1][3] : S[1][2]) : (par ? S[3][3] : S[3][2]);
    if (first) { vA0[h] = NEG; if (epos) { vB0[h] = NEG; vB1[h] = NEG; } }
  }
  float m0[4], m1[4];
#pragma unroll
  for (int h = 0; h < 4; h++) { m0[h] = fmaxf(vA0[h], vB0[h]); m1[h] = fmaxf(vA1[h], vB1[h]); }
#pragma unroll
  for (int o = 1; o <= 2; o <<= 1) {
#pragma unroll
    for (int h = 0; h < 4; h++) {
      m0[h] = fmaxf(m0[h], __shfl_xor_sync(~0u, m0[h], o));
      m1[h] = fmaxf(m1[h], __shfl_xor_sync(~0u, m1[h], o));
    }
  }
  float O0[4][4], O1[4][4], Z[4][4];
#pragma unroll
  for (int h = 0; h < 4; h++) {
    const float mm0 = -m0[h] * sc0, mm1 = -m1[h] * sc1;
    const float pA0 = ex2(fmaf(vA0[h], sc0, mm0)), pB0 = ex2(fmaf(vB0[h], sc0, mm0));
    const float pA1 = ex2(fmaf(vA1[h], sc1, mm1)), pB1 = ex2(fmaf(vB1[h], sc1, mm1));
    const uint32_t hA0 = packbf(pA0, pA0), hB0 = packbf(pB0, pB0), hA1 = packbf(pA1, pA1), hB1 = packbf(pB1, pB1);
    const uint32_t P0[4] = {hB0 & mB0, 0u, hA0 & pmask, hB1 & mB0};
    const uint32_t P1[4] = {hB0 & mB1, hA1 & pmask, 0u, hB1 & mB1};
#pragma unroll
    for (int k = 0; k < 4; k++) O0[h][k] = O1[h][k] = Z[h][k] = 0.f;
    mma_bf16(O0[h], P0, vb[h][0], vb[h][1]); mma_bf16(O1[h], P0, vb[h][2], vb[h][3]); mma_bf16(Z[h], P0, 0x3f803f80u, 0x3f803f80u);
    mma_bf16(O0[h], P1, vb[h][4], vb[h][5]); mma_bf16(O1[h], P1, vb[h][6], vb[h][7]); mma_bf16(Z[h], P1, 0x3f803f80u, 0x3f803f80u);
  }
  if (lane == 0) mbar_arrive(bar + 8 * (B_OST + wg));
  uint4* op = (uint4*)g_O + ((layer * 32 + blk) * 8 + hg) * 512 + 64 * t + 16 * w + g;
#pragma unroll
  for (int h = 0; h < 4; h += 2) {
    const float i0 = rcp_approx(Z[h][0]), i1 = rcp_approx(Z[h][2]), j0 = rcp_approx(Z[h + 1][0]), j1 = rcp_approx(Z[h + 1][2]);
    stg128(op + 128 * h, make_uint4(packbf(O0[h][0] * i0, O0[h][1] * i0), packbf(O1[h][0] * i0, O1[h][1] * i0),
                                   packbf(O0[h + 1][0] * j0, O0[h + 1][1] * j0), packbf(O1[h + 1][0] * j0, O1[h + 1][1] * j0)));
    stg128(op + 128 * h + 8, make_uint4(packbf(O0[h][2] * i1, O0[h][3] * i1), packbf(O1[h][2] * i1, O1[h][3] * i1),
                                            packbf(O0[h + 1][2] * j1, O0[h + 1][3] * j1), packbf(O1[h + 1][2] * j1, O1[h + 1][3] * j1)));
  }
  TSW(5);
  __syncwarp();
  if (lane == 0) red_relaxed(&g_cnt[(C_O + layer * 32 + blk) * 32]);
  TSW(6);
}

__device__ __forceinline__ void proj_phase(const Params& p, uint32_t sb, int layer, int rb, int q, int& rtp) {
  const int lane = opaque_tid() & 31;
  const int wg = __shfl_sync(~0u, opaque_tid() >> 7, 0), w = __shfl_sync(~0u, (opaque_tid() >> 5) & 3, 0);
  const bool TR = layer != 0;
  const int t = lane & 3;
  const uint32_t bar = sb + SM_BAR;
  const uint32_t rbx = sb + (P_R + wg) * PG;
  const uint32_t rsrc = sb + (wg ? 2 : P_R) * PG;
  const int blk = 16 * wg + rb;
  mbar_wait(bar + 8 * (B_RF + wg), layer);
  if (layer) mbar_wait(bar + 8 * B_RS, 0);
  mbar_wait(bar + 8 * B_WOF, layer);
  fence_async_global();
  const uint32_t stg = sb + (wg ? SM_KGT : SM_STG);
  bool clean = false;
#pragma unroll 1
  for (int attempt = 0; attempt < MAX_RETRY; attempt++) {
  uint32_t res[16];
  if (!TR) {
#pragma unroll
    for (int j = 0; j < 8; j += 2) {
      const int mi = lane >> 3;
      const int row = 16 * w + (lane & 7) + 8 * (mi & 1), ch = j + (mi >> 1);
      ldsm4(&res[2 * j], rsrc + row * 128 + ((ch ^ (row & 7)) << 4));
    }
  } else {
#pragma unroll
    for (int j = 0; j < 8; j += 2) {
      const int mi = lane >> 3;
      const int line = 8 * (j + (mi >> 1)) + (lane & 7), pc = 2 * w + (mi & 1);
      ldsm4t(&res[2 * j], rsrc + line * 128 + ((pc ^ (line & 7)) << 4));
    }
  }
  float acc[32];
#pragma unroll
  for (int j = 0; j < 16; j++) { acc[2 * j] = bf_lo(res[j]); acc[2 * j + 1] = bf_hi(res[j]); }
  acc_fence<32>(acc);
  if (wg) mbar_wait(bar + 8 * B_PST, layer);
  const int wg2 = __shfl_sync(~0u, opaque_tid() >> 7, 0);
  const uint64_t da0 = mkdesc(sb, 1024, 128, 0), db0 = mkdesc(sb, 8192, 1024, 1);
#pragma unroll
  for (int c = 0; c < 4; c++) {
    mbar_wait(bar + 8 * (B_OF + 4 * wg + c), layer);
    if (c == 0) TSW(7);
    const uint64_t da = da0 + (uint32_t)(o_page(wg2, c) * 512);
    wg_fence();
#pragma unroll
    for (int ks = 0; ks < 8; ks++) wgmma_ss<64, 0, 1>(acc, da + ks * 128, db0 + wo_page(2 * c + (ks >> 2)) * 512 + (ks & 3) * 128, 1);
    wg_commit();
  }
  if (wg) mbar_wait(bar + 8 * B_KG, 0);
  wg_wait<0>();
  acc_fence<32>(acc);
  TSW(8);
  if (!clean) {
    const float chk = acc[0] + acc[2];
    clean = __all_sync(~0u, chk == chk);
    if (clean && lane == 0) mbar_arrive(bar + 8 * (B_PDONE + wg));
  }
  float s0 = 0.f, q0 = 0.f, s1 = 0.f, q1 = 0.f;
  uint32_t o[16];
#pragma unroll
  for (int j = 0; j < 8; j++) {
    const float a = acc[4 * j], b = acc[4 * j + 1], c = acc[4 * j + 2], d = acc[4 * j + 3];
    o[2 * j] = packbf(a, b);
    o[2 * j + 1] = packbf(c, d);
    s0 += a + b; q0 = fmaf(a, a, q0); q0 = fmaf(b, b, q0);
    s1 += c + d; q1 = fmaf(c, c, q1); q1 = fmaf(d, d, q1);
  }
#pragma unroll
  for (int j = 0; j < 8; j += 2) {
    const int mi = lane >> 3;
    const int line = 8 * (j + (mi >> 1)) + (lane & 7), pc = 2 * w + (mi & 1);
    stsm4t(rbx + line * 128 + ((pc ^ (line & 7)) << 4), o[2 * j], o[2 * j + 1], o[2 * j + 2], o[2 * j + 3]);
  }
#pragma unroll
  for (int o2 = 1; o2 <= 2; o2 <<= 1) {
    s0 += __shfl_xor_sync(~0u, s0, o2); q0 += __shfl_xor_sync(~0u, q0, o2);
    s1 += __shfl_xor_sync(~0u, s1, o2); q1 += __shfl_xor_sync(~0u, q1, o2);
  }
  {
    const int i = 2 * (lane >> 2) + (t & 1), k = (i * 11) >> 5;
    const float v = (t == 0) ? s0 : (t == 1) ? q0 : (t == 2) ? s1 : q1;
    sts32f(stg + k * 128 + (2 * w + (t >> 1)) * 16 + (i - 3 * k) * 4, v);
  }
  TSW(9);
  fence_async_smem();
  if (!bar_or(2 + wg, 128, !clean)) break;
  bool unset = false;
#pragma unroll
  for (int i = 0; i < 4; i++) unset |= lds32(sb + o_page(wg, i) * PG + (32 * w + lane) * 128) == UNSET;
  if (!bar_or(2 + wg, 128, unset)) break;
  if (w == 0 && elect_one()) {
    fence_async_smem();
    mbar_expect(bar + 8 * (B_RT + wg), 9 * PG);
    if (layer == 0) tma_ld(rsrc, &p.mapX, q * 64, blk * 64, bar + 8 * (B_RT + wg));
    else tma_ld(rsrc, &p.mapXT, blk * 64, DM + q * 64, bar + 8 * (B_RT + wg));
#pragma unroll 1
    for (int c = 0; c < 4; c++) bulk_ld(sb + o_page(wg, c) * PG, g_O + ((layer * 32 + blk) * 4 + c) * PG, 2 * PG, bar + 8 * (B_RT + wg));
  }
  mbar_wait(bar + 8 * (B_RT + wg), rtp);
  rtp ^= 1;
  RETRY(0);
  }
  if (!clean && lane == 0) mbar_arrive(bar + 8 * (B_PDONE + wg));
  if (w == 0 && elect_one()) {
    tma_st(&p.mapXT, blk * 64, (2 * layer) * DM + q * 64, rbx);
    bulk_red_add_f32(g_stats + (layer * 32 + blk) * 192, stg, 768);
    bulk_commit();
    red_relaxed(&g_cnt[(C_G + 2 * layer + wg) * 32]);
  }
  TSW(10);
}

__device__ __forceinline__ void conv_load(uint32_t* A, uint32_t pe) {
#pragma unroll
  for (int m = 0; m < 17; m++) {
    A[4 * m + 2] = lds32(pe + 4 * (64 * m - 8));
    A[4 * m + 0] = lds32(pe + 4 * (64 * m));
    A[4 * m + 1] = lds32(pe + 4 * (64 * m + 8));
    asm volatile("mov.b32 %0, %1;" : "=r"(A[4 * m + 3]) : "r"(A[4 * m + 0]));
  }
}
template <int M> __device__ __forceinline__ void conv_tri(float* acc, const uint32_t* A, uint64_t d) {
  if constexpr (M < 16) {
    wgmma_rs<64 - 8 * (M / 2), 0>(acc, A + 4 * M, d + (uint64_t)(64 + 4 * M), M != 0);
    conv_tri<M + 1>(acc, A, d);
  }
}
__device__ __forceinline__ void conv_mma0(float* acc, const uint32_t* A, uint64_t d) {
  wg_fence();
  conv_tri<0>(acc, A, d);
  wg_commit();
}
__device__ __forceinline__ void conv_mma1(float* acc, const uint32_t* A, uint64_t d, uint64_t ds, uint64_t df) {
  wg_fence();
#pragma unroll
  for (int m = 0; m < 17; m++) wgmma_rs<64, 0>(acc, A + 4 * m, d + (uint64_t)(4 * m), m != 0);
  wgmma_ss<64, 1, 0>(acc, ds, df, 1);
  wgmma_ss<64, 1, 0>(acc, ds + 128, df + 128, 1);
  wg_commit();
}
__device__ __forceinline__ void conv_store(float* acc, uint32_t pb, uint32_t over, int w) {
  acc_fence<32>(acc);
  const int l = opaque_tid() & 31, mt = l >> 3;
  int c = 2 * (63 - 8 * (mt >> 1) - (l & 7) + w) + (mt & 1);
  c ^= (c >> 3) & 1;
  const uint32_t a0 = pb + c * 16;
#pragma unroll
  for (int j = 0; j < 8; j += 2)
    stsm4t(j == 0 ? (c < 128 ? a0 : over + (c - 128) * 16) : a0 - 256 * j, packbf(acc[4 * j], acc[4 * j + 1]), packbf(acc[4 * j + 2], acc[4 * j + 3]),
           packbf(acc[4 * j + 4], acc[4 * j + 5]), packbf(acc[4 * j + 6], acc[4 * j + 7]));
}
__device__ __forceinline__ void conv_sums(uint32_t sb, int lc, int ht) {
  const int m = ht - 1;
  uint4 v[2][3];
#pragma unroll
  for (int c = 0; c < 2; c++)
#pragma unroll
    for (int k = 0; k < 3; k++) {
      const int mm = m - 1 + k;
      v[c][k] = lds128(sb + cv_u(lc + c) + (mm >= 0 ? (mm & 1) * CV_UH + (127 - (mm >> 1)) * 16 : 128 * 16));
    }
  const int ce = m + 2, co = m + 1;
#pragma unroll
  for (int c = 0; c < 2; c++) {
    const uint32_t x[8] = {v[c][0].z, v[c][0].w, v[c][1].x, v[c][1].y, v[c][1].z, v[c][1].w, v[c][2].x, v[c][2].y};
    float pv[16];
#pragma unroll
    for (int k = 0; k < 8; k++) { pv[2 * k] = bf_lo(x[k]); pv[2 * k + 1] = bf_hi(x[k]); }
    float t2[15], t4[13], s9[8], s7[8];
#pragma unroll
    for (int i = 0; i < 15; i++) t2[i] = pv[i] + pv[i + 1];
#pragma unroll
    for (int i = 0; i < 13; i++) t4[i] = t2[i] + t2[i + 2];
#pragma unroll
    for (int i = 0; i < 8; i++) {
      s9[i] = (t4[i] + t4[i + 4]) + pv[i + 8];
      s7[i] = (t4[i + 1] + t2[i + 5]) + pv[i + 7];
    }
    const uint4 e4 = make_uint4(packbf(s9[0], s9[1]), packbf(s9[2], s9[3]), packbf(s9[4], s9[5]), packbf(s9[6], s9[7]));
    if (ce < 128) sts128(sb + cv_se(lc + c) + ((ce ^ ((ce >> 3) & 7)) << 4), e4);
    else sts128(sb + cv_se(lc + c), make_uint4(0, 0, 0, 0));
    sts128(sb + cv_so(lc + c) + ((co ^ ((co >> 3) & 7)) << 4),
           make_uint4(packbf(s7[0], s7[1]), packbf(s7[2], s7[3]), packbf(s7[4], s7[5]), packbf(s7[6], s7[7])));
  }
}

template <int HALF, int NCH, int STEP = 1>
__device__ __forceinline__ void conv_epi(uint32_t sb, bf16* out, int lc, int c) {
  uint4 v[NCH][4], xr[NCH];
  const uint32_t sw = (c ^ ((c >> 3) & 1)) * 16;
#pragma unroll
  for (int u = 0; u < NCH; u++) {
#pragma unroll
    for (int k = 0; k < 4; k++) v[u][k] = lds128(sb + (HALF ? cv_pb1(lc + STEP * u, k) : cv_pb0(lc + STEP * u, k)) + sw);
    xr[u] = lds128(sb + cv_x(HALF, lc + STEP * u) + c * 16);
  }
#pragma unroll
  for (int u = 0; u < NCH; u++) {
    uint4 o;
    o.x = hadd2(xr[u].x, hadd2(hadd2(v[u][0].x, v[u][1].x), hadd2(v[u][2].x, v[u][3].x)));
    o.y = hadd2(xr[u].y, hadd2(hadd2(v[u][0].y, v[u][1].y), hadd2(v[u][2].y, v[u][3].y)));
    o.z = hadd2(xr[u].z, hadd2(hadd2(v[u][0].z, v[u][1].z), hadd2(v[u][2].z, v[u][3].z)));
    o.w = hadd2(xr[u].w, hadd2(hadd2(v[u][0].w, v[u][1].w), hadd2(v[u][2].w, v[u][3].w)));
    stg128(out + cv_chan(0, lc + STEP * u) * LSEQ + HALF * 1024 + c * 8, o);
  }
}

__device__ __forceinline__ bool prep_valid(const uint4 (&st)[6], const uint4 (&xr)[4]) {
  const uint32_t n = __float_as_uint(8.f);
  return st[0].w == n && st[1].w == n && st[2].w == n && st[3].w == n && st[4].w == n && (st[5].w | st[5].y | st[5].z) == n &&
         xr[0].x != UNSET && xr[1].x != UNSET && xr[2].x != UNSET && xr[3].x != UNSET;
}
template <int HALF>
__device__ __forceinline__ void conv_prep(uint32_t sb, int layer, int cta, int i) {
  uint4 st[6], xr[4];
  const uint4* sp = (const uint4*)g_stats + (layer * 32 + HALF * 16 + (i >> 3)) * 48 + (i & 7);
  const uint4* xp = (const uint4*)g_xT + (2 * layer * DM + 2 * cta) * (LSEQ / 8) + HALF * 128 + i;
  auto fetch = [&]() {
#pragma unroll
    for (int k = 0; k < 6; k++) st[k] = ld_tagged(sp + 8 * k);
#pragma unroll
    for (int k = 0; k < 4; k++) xr[k] = ld_tagged(xp + cv_chan(0, k) * (LSEQ / 8));
  };
  if (HALF) {
#pragma unroll
    for (int k = 0; k < 6; k++) st[k] = lds128(sb + CV_ST + (i >> 3) * 768 + k * 128 + (i & 7) * 16);
#pragma unroll
    for (int k = 0; k < 4; k++) xr[k] = lds128(sb + cv_x(1, k) + i * 16);
  } else {
    fetch();
  }
  int it = 0;
  while (!__all_sync(~0u, prep_valid(st, xr)) && ++it < MAX_RETRY) { fetch(); RETRY(1); }
  if (!HALF || it) {
#pragma unroll
    for (int k = 0; k < 4; k++) sts128(sb + cv_x(HALF, k) + i * 16, xr[k]);
  }
  const uint32_t v[16] = {st[0].x, st[0].y, st[0].z, st[1].x, st[1].y, st[1].z, st[2].x, st[2].y, st[2].z, st[3].x, st[3].y, st[3].z, st[4].x, st[4].y, st[4].z, st[5].x};
  uint32_t rs[4], nm[4];
#pragma unroll
  for (int k = 0; k < 4; k++) {
    const float m0 = __uint_as_float(v[4 * k]) * (-1.f / DM), m1 = __uint_as_float(v[4 * k + 2]) * (-1.f / DM);
    const float r0 = rsqrt_approx(fmaxf(fmaf(__uint_as_float(v[4 * k + 1]), 1.f / DM, -m0 * m0), 0.f) + 1e-5f);
    const float r1 = rsqrt_approx(fmaxf(fmaf(__uint_as_float(v[4 * k + 3]), 1.f / DM, -m1 * m1), 0.f) + 1e-5f);
    rs[k] = packbf(r0, r1);
    nm[k] = packbf(m0 * bf_lo(rs[k]), m1 * bf_hi(rs[k]));
  }
  const uint32_t ud = sb + (i & 1) * CV_UH + (127 - 64 * HALF - (i >> 1)) * 16;
#pragma unroll
  for (int k = 0; k < 4; k++)
    sts128(ud + cv_u(k), make_uint4(hfma2(xr[k].x, rs[0], nm[0]), hfma2(xr[k].y, rs[1], nm[1]), hfma2(xr[k].z, rs[2], nm[2]), hfma2(xr[k].w, rs[3], nm[3])));
  fence_async_smem();
}

#define AGATE 1
#define PP0 1
__device__ __forceinline__ void conv_phase(const Params& p, uint32_t sb, int layer, int cta) {
  const int tid = opaque_tid();
  const int wg = __shfl_sync(~0u, tid >> 7, 0), w = __shfl_sync(~0u, (tid >> 5) & 3, 0);
  const uint32_t bar = sb + SM_BAR;
  constexpr int CH2 = 4 * PG;
  bf16* xout = g_xT + ((2 * layer + 1) * DM + 2 * cta) * LSEQ;
  uint32_t A0[68], A1[68];
  float acc[32];
  const uint32_t pe = sb + cv_pe(wg) + 4 * (16 + 16 * w + ((tid & 31) >> 2) - 2 * (tid & 3));
  auto staged = [&]() {
    if (w == 0) {
      bulk_wait_read();
      __syncwarp();
      if (elect_one()) mbar_arrive(bar + 8 * (B_PST + wg));
    }
  };
  if (wg == 0) staged();
  mbar_wait(bar + 8 * (B_PDONE + 1), layer);
  mbar_wait(bar + 8 * B_PE, layer);
  conv_load(A0, pe);
  if (wg == 1) staged();
  conv_load(A1, pe + CH2);
  TSW(19);
  const uint64_t d0 = mkdesc(sb + cv_u(wg), CV_UH, 128, 0), d1 = d0 + (CH2 >> 4);
  mbar_wait(bar + 8 * B_U, layer);
  TSW(12);
  if (wg == 1) bar_sync(5, 256);
  conv_mma0(acc, A0, d0);
  if (wg == 0) bar_arrive(5, 256);
  mbar_wait(bar + 8 * (B_PDONE + 1), layer);
  {
    const int l = opaque_tid() & 31;
    if ((l & 15) < 2 * w) sts128(sb + cv_pb0(wg + 2 * (l >> 4), w) + (l & 15) * 16, make_uint4(0, 0, 0, 0));
  }
  wg_wait<0>();
  conv_store(acc, sb + cv_pb0(wg, w), sb + cv_pb1(wg, w), w);
  conv_mma0(acc, A1, d1);
  wg_wait<0>();
  conv_store(acc, sb + cv_pb0(2 + wg, w), sb + cv_pb1(2 + wg, w), w);
  TSW(13);
  bar_sync(2 + wg, 128);
  conv_epi<0, 2, 2>(sb, xout, wg, opaque_tid() & 127);
  TSW(14);
  mbar_arrive(bar + 8 * B_PUB);
  if (wg == 0) mbar_wait(bar + 8 * B_U1, layer);
  else bar_sync(6, 256);
  TSW(15);
  const uint64_t ds = mkdesc(sb + cv_se(wg), 8192, 1024, 1), df = mkdesc(sb + cv_fa(wg), 512, 128, 0);
  conv_mma1(acc, A0, d0, ds, df);
  if (wg == 0) bar_arrive(6, 256);
  wg_wait<0>();
  conv_store(acc, sb + cv_pb1(wg, w), sb + cv_dump(wg), w);
  mbar_arrive(bar + 8 * B_R);
  TSW(16);
  conv_mma1(acc, A1, d1, ds + 512, df + (CH2 >> 4));
  wg_wait<0>();
  conv_store(acc, sb + cv_pb1(2 + wg, w), sb + cv_dump(2 + wg), w);
  TSW(17);
  if (wg == 0) {
    mbar_arrive(bar + 8 * (B_R + 1));
  } else {
    bar_sync(3, 128);
    conv_epi<1, 1>(sb, xout, 3, opaque_tid() & 127);
    mbar_arrive(bar + 8 * (B_PUB + 2));
    TSW(18);
  }
}

__device__ __forceinline__ void final_phase(const Params& p, uint32_t sb, int cta, int wg, int w, int rtp) {
  const int lane = opaque_tid() & 31;
  const uint32_t bar = sb + SM_BAR;
  mbar_wait(bar + 8 * (B_TF + wg), 0);
  if (threadIdx.x == 128) TS(8);
  const uint32_t src = sb + (16 + wg) * PG, dst = src + 2 * PG;
  const int mi = lane >> 3;
#pragma unroll 1
  for (int attempt = 0; attempt < MAX_RETRY; attempt++) {
    uint32_t m = 0;
#pragma unroll
    for (int j = 0; j < 8; j += 2) {
      uint32_t r[4];
      const int line = 8 * (j + (mi >> 1)) + (lane & 7), pc = 2 * w + (mi & 1);
      ldsm4t(r, src + line * 128 + ((pc ^ (line & 7)) << 4));
      const int row = 16 * w + (lane & 7) + 8 * (mi & 1), ch = j + (mi >> 1);
      stsm4(dst + row * 128 + ((ch ^ (row & 7)) << 4), r[0], r[1], r[2], r[3]);
#pragma unroll
      for (int k = 0; k < 4; k++) asm("max.u16x2 %0, %0, %1;" : "+r"(m) : "r"(r[k]));
    }
    fence_async_smem();
    if (!bar_or(2 + wg, 128, m >= 0xffff0000u || (m & 0xffffu) == 0xffffu)) break;
    if (w == 0 && elect_one()) {
      mbar_expect(bar + 8 * (B_RT + wg), PG);
      tma_ld(src, &p.mapXT, (16 * wg + (cta & 15)) * 64, 3 * DM + (cta >> 4) * 64, bar + 8 * (B_RT + wg));
    }
    mbar_wait(bar + 8 * (B_RT + wg), (rtp + attempt) & 1);
    RETRY(2);
  }
  if (w == 0 && elect_one()) {
    tma_st(&p.mapOut, (cta >> 4) * 64, (16 * wg + (cta & 15)) * 64, dst);
    bulk_commit();
    asm volatile("cp.async.bulk.wait_group.read 0;" ::: "memory");
    if (threadIdx.x == 128) TS(9);
    if (threadIdx.x == 128) LTS(1);
  }
}

struct cplx { float r, i; };
__device__ __forceinline__ cplx cmul(cplx a, cplx b) { return {fmaf(a.r, b.r, -a.i * b.i), fmaf(a.r, b.i, a.i * b.r)}; }
__device__ __forceinline__ cplx csqr(cplx a) { return {fmaf(a.r, a.r, -a.i * a.i), (a.r + a.r) * a.i}; }
__device__ __forceinline__ cplx cexp_l(float ar2, float ai, float l) {
  const float m = ex2(ar2 * l);
  const float x = ai * l;
  return {m * __cosf(x), m * __sinf(x)};
}

__device__ __forceinline__ void colsum_cta(const Params& p, uint32_t sb, int j, int tid) {
  const uint32_t bar = sb + SM_BAR;
  auto ld = [&](int i) {
    mbar_expect(bar + 8 * i, 3 * PG);
    tma_ld3(sb + (i & 7) * 3 * PG, &p.mapW3, (2 * j + (i & 1)) * 64, (i >> 1) * 64, 0, bar + 8 * i);
  };
  if (tid == 384) {
#pragma unroll
    for (int i = 0; i < 24; i++) mbar_init(bar + 8 * i, i < 16 ? 1 : 12);
    asm volatile("fence.mbarrier_init.release.cluster;" ::: "memory");
    fence_async_smem();
#pragma unroll 1
    for (int i = 0; i < 8; i++) ld(i);
  }
  const unsigned ep = ld_relaxed(&g_cnt[C_CS * 32]);
  bar_sync(0, NTHREADS);
  if (tid == 384) {
#pragma unroll 1
    for (int i = 8; i < 16; i++) { mbar_wait(bar + 8 * (8 + i), 0); fence_async_smem(); ld(i); }
  }
  if (tid < 384) {
    const int lane = tid & 31, cc = tid & 7, r0 = (tid >> 3) & 15, part = tid >> 7;
    const uint32_t id = ((lane >> 2) == 2 * (lane & 3) ? 0x3f80u : 0u) | ((lane >> 2) == 2 * (lane & 3) + 1 ? 0x3f800000u : 0u);
    const uint32_t src = sb + part * PG + r0 * 128 + ((cc ^ (r0 & 7)) << 4);
    float s[2][2][4];
#pragma unroll
    for (int i = 0; i < 16; i++) s[i >> 3][(i >> 2) & 1][i & 3] = 0.f;
#pragma unroll 1
    for (int i2 = 0; i2 < 16; i2 += 2) {
#pragma unroll
      for (int h = 0; h < 2; h++) {
        const int i = i2 + h;
        mbar_wait(bar + 8 * i, 0);
        uint4 v[4];
#pragma unroll
        for (int k = 0; k < 4; k++) v[k] = lds128(src + (i & 7) * 3 * PG + k * 2048);
#pragma unroll
        for (int k = 0; k < 4; k++) {
          const uint32_t a[4] = {v[k].x, v[k].y, v[k].z, v[k].w};
          mma_bf16(s[h][0], a, id, 0u);
          mma_bf16(s[h][1], a, 0u, id);
        }
        __syncwarp();
        if (i < 8 && lane == 0) mbar_arrive(bar + 8 * (16 + i));
      }
    }
    const uint32_t red = sb + 24 * PG;
#pragma unroll
    for (int h = 0; h < 2; h++)
#pragma unroll
      for (int k = 0; k < 2; k++) sts128f(red + (r0 * 384 + h * 192 + part * 64 + cc * 8 + k * 4) * 4, s[h][k][0], s[h][k][1], s[h][k][2], s[h][k][3]);
    bar_sync(1, 384);
    float tot = 0.f;
#pragma unroll
    for (int k = 0; k < 16; k++) tot += __uint_as_float(lds32(red + (k * 384 + tid) * 4));
    asm volatile("st.relaxed.gpu.global.v2.u32 [%0], {%1,%2};" ::"l"(&g_colsum[j * 384 + tid]), "r"(__float_as_uint(tot)), "r"(ep / NCTA + 1) : "memory");
    const uint4 u = make_uint4(UNSET, UNSET, UNSET, UNSET);
    if (tid < 256) {
#pragma unroll 1
      for (int s = 0; s < 4; s++) {
        const int n = s ? 32 : 16;
        uint4* dst = (s == 1 ? (uint4*)g_O + 131072 : (uint4*)g_xT + (s + !s) * 131072) + j * n * 1024 + (tid >> 1) * 8 + (tid & 1);
#pragma unroll 4
        for (int i = 0; i < n; i++) stg128(dst + i * 1024, u);
        bar_sync(2, 256);
        if (tid == 32 * s) red_release(&g_cnt[(C_R + s) * 32]);
      }
    }
  }
}

#define KB 4
#define KW 2
struct ModeIn { uint32_t ar, ai, br, bi, cr, ci; bf16 logdt; };
__device__ __forceinline__ ModeIn load_modes(const Params& p, int d, int m) {
  const int i = d * 64 + m;
  return {((const uint32_t*)p.a_re)[i], ((const uint32_t*)p.a_im)[i], ((const uint32_t*)p.b_re)[i], ((const uint32_t*)p.b_im)[i],
          ((const uint32_t*)p.c_re)[i], ((const uint32_t*)p.c_im)[i], p.log_dt[d]};
}
__device__ __forceinline__ float4 lds128f_nv(uint32_t a) { float4 v; asm("ld.shared.v4.f32 {%0,%1,%2,%3}, [%4];" : "=f"(v.x), "=f"(v.y), "=f"(v.z), "=f"(v.w) : "r"(a)); return v; }
__device__ __forceinline__ void kernel_gen(const Params& p, uint32_t sb, int cta, int ht, ModeIn in, const ModeIn& in1) {
  const uint32_t bst = sb + SM_KGB + ((ht & 63) >> 2) * 144 + (ht & 3) * 4 + (ht >> 6) * 16;
  const uint64_t db = mkdesc(sb + SM_KGB, 144, 2304, 0);
  const float e0 = (float)(8 * (((ht & 32) >> 1) + ((ht & 31) >> 2)));
  float T[20];
#pragma unroll
  for (int i = 0; i < 20; i++) T[i] = 0.f;
  float k0 = 0.f;
#pragma unroll 1
  for (int pass = 0; pass < 4; pass++) {
    {
      const int sh = (pass & 1) ? 0 : 16;
      auto val = [&](uint32_t v) { return __uint_as_float((v << sh) & 0xffff0000u); };
      const float dt = __bfloat162float(__float2bfloat16_rn(expf(__bfloat162float(in.logdt))));
      const float ar2 = dt * val(in.ar) * 1.4426950408889634f, ai = dt * val(in.ai);
      const cplx c = cmul({val(in.cr), -val(in.ci)}, {dt * val(in.br), -dt * val(in.bi)});
      k0 += c.r;
      const cplx z1 = cexp_l(ar2, -ai, 1.f), z256 = cexp_l(ar2, -ai, 256.f), z64 = cexp_l(ar2, ai, 64.f);
      const cplx z2 = csqr(z1), z512 = csqr(z256);
      auto put = [&](int j, cplx v) { sts32(bst + (j >> 2) * 2304 + (j & 3) * 32, packbf(v.r, v.i)); };
      sts128f(sb + SM_KGT + ht * 16, ar2, ai, z64.r, z64.i);
      const cplx c1 = cmul(c, z1), c2 = cmul(c, z2), c3 = cmul(c1, z2), c4 = cmul(c2, z2);
      const cplx c5 = cmul(c3, z2), c6 = cmul(c4, z2), c7 = cmul(c5, z2), c8 = cmul(c6, z2);
      put(0, c1); put(1, c2); put(2, c3); put(3, c4); put(4, c5); put(5, c6); put(6, c7); put(7, c8);
      const cplx c260 = cmul(c4, z256), c264 = cmul(c8, z256), c520 = cmul(c8, z512), c776 = cmul(c264, z512);
      put(8, cmul(c2, z256)); put(9, c260); put(10, cmul(c6, z256)); put(11, c264);
      put(12, cmul(c4, z512)); put(13, c520); put(14, cmul(c260, z512)); put(15, c776);
      const cplx c1032 = cmul(c520, z512), c1288 = cmul(c776, z512);
      put(16, c1032); put(17, c1288); put(18, cmul(c1032, z512)); put(19, cmul(c1288, z512));
    }
    fence_async_smem();
    bar_sync(4, 128);
    const uint32_t tb = sb + SM_KGT + (ht & 67) * 16;
    float2 nx[KB];
#pragma unroll
    for (int s = 0; s < KB; s++) nx[s] = lds64f(tb + s * 64);
#pragma unroll
    for (int q = 0; q < 16 / KB; q++) {
      uint32_t A[2 * KB];
      float2 cur[KB], z[KB];
#pragma unroll
      for (int s = 0; s < KB; s++) { cur[s] = nx[s]; z[s] = lds64f(tb + (KB * q + s) * 64 + 8); }
      if (q < 16 / KB - 1) {
#pragma unroll
        for (int s = 0; s < KB; s++) nx[s] = lds64f(tb + (KB * q + KB + s) * 64);
      }
      if (q >= KW) wg_wait<KW - 1>();
#pragma unroll
      for (int s = 0; s < KB; s++) {
        const cplx lo = cexp_l(cur[s].x, cur[s].y, e0), hi = cmul(lo, {z[s].x, z[s].y});
        A[2 * s] = packbf(lo.r, lo.i);
        A[2 * s + 1] = packbf(hi.r, hi.i);
      }
      wg_fence();
#pragma unroll
      for (int k = 0; k < KB / 2; k++) wgmma_rs<40, 0>(T, A + 4 * k, db + 9 * KB * q + 18 * k, (pass & 1) | q | k);
      wg_commit();
    }
    wg_wait<0>();
    acc_fence<20>(T);
    if (ht == 0) TS(4 + pass);
    if (pass & 1) {
      const int h2 = opaque_tid() - 256, w = h2 >> 5, lane = h2 & 31, t = lane & 3, chn = h2 >> 6, m = h2 & 63, i0 = 16 * (w & 1) + (lane >> 2);
      const int lc = (pass & 2) + chn;
      const uint32_t kc = sb + kc_off(lc);
      auto put = [&](int idx, float v) {
        sts16(kc + idx * 2, __bfloat16_as_ushort(__float2bfloat16_rn(v)));
      };
#pragma unroll
      for (int hi = 0; hi < 2; hi++) {
        const int i = i0 + 8 * hi;
        float v[5];
#pragma unroll
        for (int j = 0; j < 5; j++) v[j] = chn ? T[4 * j + 2 * hi + 1] : T[4 * j + 2 * hi];
        put(8 * i + 1 + t, v[0]);
        put(8 * i + 5 + t, v[1]);
        put(257 + 4 * i + t, v[2]);
        put(385 + 2 * i + (t & 1) + 64 * (t >> 1), v[3]);
        put(513 + i + 32 * t, v[4]);
      }
#pragma unroll
      for (int o = 16; o > 0; o >>= 1) k0 += __shfl_xor_sync(~0u, k0, o);
      if (lane == 0) sts32f(sb + SM_RED + 4 * w, k0);
      bar_sync(4, 128);
      if (m == 0) put(0, k0 + __uint_as_float(lds32(sb + SM_RED + 4 * w + 4)) + __uint_as_float(lds16(sb + SM_RED + 24 + 2 * lc) << 16));
      k0 = 0.f;
      in = in1;
    }
  }
}

__device__ __forceinline__ void expand_taps(uint32_t sb, int ht) {
  const int ch = ht >> 5, lane = ht & 31;
  const uint32_t kc = sb + kc_off(ch);
  const uint32_t dst0 = sb + cv_pe(ch);
  auto put = [&](int G, uint32_t v0, uint32_t v1, uint32_t v2, uint32_t v3, uint32_t v4, uint32_t v5, uint32_t v6, uint32_t v7, uint32_t v8) {
    const uint32_t dst = dst0 + G * 32;
    sts128(dst, make_uint4(v1 | (v0 << 16), v2 | (v1 << 16), v3 | (v2 << 16), v4 | (v3 << 16)));
    sts128(dst + 16, make_uint4(v5 | (v4 << 16), v6 | (v5 << 16), v7 | (v6 << 16), v8 | (v7 << 16)));
  };
  {
    const uint4 q = lds128(kc + lane * 16);
    const uint32_t pv = lane ? lds16(kc + lane * 16 - 2) : 0u;
    const uint32_t dst = dst0 + (lane + 2) * 32;
    sts128(dst, make_uint4(__byte_perm(q.x, pv, 0x5410), __byte_perm(q.x, q.x, 0x1032), __byte_perm(q.y, q.x, 0x7610), __byte_perm(q.y, q.y, 0x1032)));
    sts128(dst + 16, make_uint4(__byte_perm(q.z, q.y, 0x7610), __byte_perm(q.z, q.z, 0x1032), __byte_perm(q.w, q.z, 0x7610), __byte_perm(q.w, q.w, 0x1032)));
    if (lane < 4) sts128(dst0 + lane * 16, make_uint4(0, 0, 0, 0));
  }
  uint32_t a[5], b[2][3];
  {
    const uint32_t s1 = kc + 2 * (256 + 4 * lane);
#pragma unroll
    for (int k = 0; k < 5; k++) a[k] = lds16(s1 + 2 * k);
#pragma unroll
    for (int u = 0; u < 2; u++) {
      const uint32_t s2 = kc + 2 * (384 + 2 * (lane + 32 * u));
#pragma unroll
      for (int k = 0; k < 3; k++) b[u][k] = lds16(s2 + 2 * k);
    }
  }
  const uint32_t k255 = lds16(kc + 2 * 255), k1024 = lds16(kc + 2 * 512);
  put(34 + lane, lane == 0 ? k255 : a[0], a[0], a[0], a[1], a[2], a[2], a[2], a[3], a[4]);
#pragma unroll
  for (int u = 0; u < 2; u++) put(66 + lane + 32 * u, b[u][0], b[u][0], b[u][0], b[u][0], b[u][1], b[u][1], b[u][1], b[u][2], b[u][2]);
  if (lane < 10) {
    const uint32_t v = lane == 0 ? k1024 : 0u;
    put(130 + lane, v, v, v, v, v, v, 0u, 0u, 0u);
  }
}
__device__ __forceinline__ void expand_far(uint32_t sb, int ht) {
  const int ch = ht >> 5, lane = ht & 31;
  const uint32_t kc = sb + kc_off(ch) + 2 * (513 + 2 * (63 - lane)), dst = sb + cv_fa(ch) + lane * 16;
#pragma unroll
  for (int ty = 0; ty < 2; ty++) {
    uint32_t v[16];
#pragma unroll
    for (int k = 0; k < 16; k++) v[k] = (k < 8 || 63 - lane - 4 * k >= 0) ? lds16(kc + 2 * (1 - ty) - 16 * k) : 0u;
#pragma unroll
    for (int u = 0; u < 2; u++)
      sts128(dst + ty * 2048 + u * 512, make_uint4(v[8 * u] | (v[8 * u + 1] << 16), v[8 * u + 2] | (v[8 * u + 3] << 16), v[8 * u + 4] | (v[8 * u + 5] << 16), v[8 * u + 6] | (v[8 * u + 7] << 16)));
    sts128(dst + ty * 2048 + 1024, make_uint4(0, 0, 0, 0));
  }
}

#define TMPF 1
#define CONST_SB 1
#define WPRE 1
__host__ __device__ constexpr int bar_count(int i) {
  return i == B_END ? 3 : i == B_LN ? 2 : i < B_OST ? 1 : i < B_PE ? 4 : (i == B_PUB || i == B_PUB + 2 || i == B_R) ? 256 : 128;
}
__host__ __device__ constexpr bool bar_first(int i) { return i < B_WF + 2 && (i & 7) < 2; }

__global__ void __launch_bounds__(NTHREADS, 1) fused_kernel(const __grid_constant__ Params p) {
  extern __shared__ __align__(1024) uint8_t smem[];
  constexpr uint32_t sb = 1024;
  if (s32(smem) != sb) return;
  const int tid = threadIdx.x, lane = tid & 31;
  const int warp = __shfl_sync(~0u, tid >> 5, 0);
  if (tid == 32) {
    asm volatile("prefetch.tensormap [%0];" ::"l"(&p.mapX) : "memory");
    asm volatile("prefetch.tensormap [%0];" ::"l"(&p.mapW3) : "memory");
  }
  const int cta = blockIdx.x - (gridDim.x == NCTA + 4 ? 0 : 4);
  if ((unsigned)cta >= NCTA) {
    if (blockIdx.x < NCTA + 4) colsum_cta(p, sb, blockIdx.x & 3, tid);
    return;
  }
  const int rb = ((cta >> 4) & 3) * 4 + ((cta >> 2) & 3), hg = (cta >> 6) * 4 + (cta & 3);
  const uint32_t bar = sb + SM_BAR;
  auto ld_x0 = [&](int half, int c) {
    const uint32_t b = bar + 8 * (B_XF + 8 * half + c);
    mbar_expect(b, PG);
    tma_ld(sb + x_page(half, c) * PG, &p.mapX, c * 64, (16 * half + rb) * 64, b);
  };
  auto ld_x1 = [&](int half, int c, int b0) {
    const uint32_t b = bar + 8 * b0;
    mbar_expect(b, PG);
    tma_ld(sb + (8 * half + c) * PG, &p.mapXT, (16 * half + rb) * 64, DM + c * 64, b);
  };
  auto ld_w = [&](int c) {
    const uint32_t b = bar + 8 * (B_WF + c);
    mbar_expect(b, 3 * PG);
    tma_ld3(sb + w_page(c) * PG, &p.mapW3, hg * 64, c * 64, 0, b);
  };

  if (tid == 0) TS(0);
  if (tid == 480) LTS(0);
  if (warp == 0 && elect_one()) {
#pragma unroll
    for (int i = 0; i < B_WF + 2; i++)
      if (bar_first(i)) mbar_init(bar + 8 * i, 1);
    asm volatile("fence.mbarrier_init.release.cluster;" ::: "memory");
    fence_async_smem();
    ld_x0(0, 0);
    ld_w(0); ld_x0(1, 0);
    ld_x0(0, 1); ld_w(1); ld_x0(1, 1);
    TS(1);
  }
  __syncwarp();
  if (warp >= 1 && warp < 8 && elect_one()) {
    if (warp < 4) {
#pragma unroll
      for (int i = 2; i < 8; i++) mbar_init(bar + 8 * (8 * warp - 8 + i), 1);
    } else {
#pragma unroll
      for (int i = 0; i < 12; i++) mbar_init(bar + 8 * (12 * warp - 24 + i), 1);
    }
    asm volatile("fence.mbarrier_init.release.cluster;" ::: "memory");
  }
  if (warp == 15 && elect_one()) {
#pragma unroll
    for (int i = 72; i < B_COUNT; i++) mbar_init(bar + 8 * i, bar_count(i));
    asm volatile("fence.mbarrier_init.release.cluster;" ::: "memory");
  }

  if (warp < 8) {
    bar_sync(0, NTHREADS);
    asm volatile("setmaxnreg.inc.sync.aligned.u32 %0;" ::"n"(R_CONS));
    const int cw = __shfl_sync(~0u, opaque_tid() >> 5, 0);
    const int wg = cw >> 2, w = cw & 3;
    if (tid == 0) TS(2);
    int rtp = 0;
#pragma unroll 1
    for (int layer = 0; layer < 2; layer++) {
      attn_phase(p, sb, layer, rb, hg, wg, w);
      proj_phase(p, sb, layer, rb, hg, rtp);
      conv_phase(p, sb, layer, cta);
    }
    final_phase(p, sb, cta, wg, w, rtp);
  } else if (warp < 12) {
    asm volatile("setmaxnreg.dec.sync.aligned.u32 %0;" ::"n"(R_HELP));
    const int ht = tid - 256;
    {
      unsigned ep0 = 0;
      if (ht == 0) ep0 = ld_relaxed(&g_cnt[C_CS * 32]);
      const bf16 dsk = p.dskip[cv_chan(cta, ht & 3)];
      const ModeIn in0 = load_modes(p, cv_chan(cta, ht >> 6), ht & 63), in1 = load_modes(p, cv_chan(cta, 2 + (ht >> 6)), ht & 63);
      if (ht < 48) sts128f(sb + SM_STG + ht * 16, 0.f, 0.f, 0.f, 1.f);
      bar_sync(0, NTHREADS);
      if (ht == 0) {
        sts32(sb + SM_EP, ep0);
        mbar_arrive(bar + 8 * B_EP);
      }
      if (ht >= 124) sts16(sb + SM_RED + 24 + 2 * (ht & 3), __bfloat16_as_ushort(dsk));
      kernel_gen(p, sb, cta, ht, in0, in1);
      if (ht < 48) sts128f(sb + SM_KGT + ht * 16, 0.f, 0.f, 0.f, 1.f);
      fence_async_smem();
      bar_sync(4, 128);
      if (ht == 0) mbar_arrive(bar + 8 * B_KG);
    }
#pragma unroll 1
    for (int layer = 0; layer < 2; layer++) {
      bf16* xout = g_xT + ((2 * layer + 1) * DM + 2 * cta) * LSEQ;
      mbar_wait(bar + 8 * B_PDONE, layer);
      expand_taps(sb, opaque_tid() - 256);
      mbar_arrive(bar + 8 * B_PE);
      TSW(0);
      expand_far(sb, opaque_tid() - 256);
      {
        const int i = opaque_tid() - 256;
        if (i < 32) sts128(sb + cv_u(i >> 3) + ((i >> 2) & 1) * CV_UH + (128 + (i & 3)) * 16, make_uint4(0, 0, 0, 0));
        mbar_wait(bar + 8 * B_RC, layer);
        mbar_wait(bar + 8 * B_GB, layer);
        TSW(13);
        conv_prep<0>(sb, layer, cta, i);
        mbar_arrive(bar + 8 * B_U);
      }
      mbar_wait(bar + 8 * (B_PDONE + 1), layer);
      bar_sync(4, 128);
#pragma unroll 1
      for (int lc = 0; lc < 4; lc += 2) {
        conv_sums(sb, lc, opaque_tid() - 256);
        TSW(1 + lc);
      }
      mbar_wait(bar + 8 * (B_GB + 1), layer);
      conv_prep<1>(sb, layer, cta, opaque_tid() - 256);
      mbar_arrive(bar + 8 * B_U1);
      TSW(4);
      mbar_wait(bar + 8 * B_R, layer);
      conv_epi<1, 2>(sb, xout, 0, opaque_tid() - 256);
      mbar_arrive(bar + 8 * (B_PUB + 1));
      TSW(5);
      mbar_wait(bar + 8 * (B_R + 1), layer);
      conv_epi<1, 1>(sb, xout, 2, opaque_tid() - 256);
      mbar_arrive(bar + 8 * (B_PUB + 2));
      TSW(6);
      if (layer == 0) {
        const int c = __shfl_sync(~0u, (opaque_tid() >> 5) & 3, 0);
#pragma unroll 1
        for (int half = 0; half < 2; half++) {
          const uint32_t a = sb + (8 * half + c) * PG + lane * 128 + (lane & 7) * 16 + (lane >> 3) * 4;
#pragma unroll 1
          for (int it = 0; it < MAX_RETRY; it++) {
            mbar_wait(bar + 8 * (B_XR + 4 * half + c), it & 1);
            const uint32_t v0 = lds32(a), v1 = lds32(a + 4096);
            if (__all_sync(~0u, v0 != UNSET && v1 != UNSET)) break;
            if (elect_one()) { fence_async_smem(); ld_x1(half, c, B_XR + 4 * half + c); }
            __syncwarp();
            RETRY(3);
          }
          if (lane == 0) mbar_arrive(bar + 8 * (B_XF + 8 * half + c));
        }
      }
    }
  } else {
    asm volatile("setmaxnreg.dec.sync.aligned.u32 %0;" ::"n"(R_AGENT));
    bar_sync(0, NTHREADS);
    auto done = [&](int half, int c, int layer) { mbar_wait(bar + 8 * (B_DN + 8 * half + c), layer); };
    auto publish = [&](int layer, int k) {
      mbar_wait(bar + 8 * (B_PUB + k), layer);
      if (layer || k < 2) red_relaxed(&g_cnt[(layer ? C_F + 4 * k + (cta >> 5) : C_C + k) * 32]);
      if (!layer && k != 1) red_release(&g_cnt[(C_C + 3 - (k >> 1)) * 32]);
      TS(16 + layer * 56 + 40 + 7 + k);
    };
    if (warp == 12) {
      if (elect_one()) {
#pragma unroll 1
        for (int layer = 0; layer < 2; layer++) {
          auto ld_xe = [&](int c) {
            const uint32_t b = bar + 8 * (B_XF + c);
            mbar_expect(b, PG);
            if (layer == 0) tma_ld(sb + x_page(0, c) * PG, &p.mapX, c * 64, rb * 64, b);
            else tma_ld(sb + x_page(0, c) * PG, &p.mapXT, rb * 64, DM + c * 64, b);
          };
          if (layer == 0) {
            ld_x0(0, 2); ld_w(2); ld_x0(1, 2);
            if (hg >= 3) {
              mbar_expect(bar + 8 * B_SC, PG);
              tma_ld(sb + P_R * PG, &p.mapX, hg * 64, rb * 64, bar + 8 * B_SC);
            }
            if (rb < 4) tma_prefetch3(&p.mapW3, hg * 64, (4 + rb) * 64, 0);
            ld_x0(0, 3); ld_w(3); ld_x0(1, 3); ld_x0(0, 4); ld_x0(1, 4);
            done(0, 0, 0); done(1, 0, 0);
            ld_w(4);
            ld_x0(1, 5); ld_x0(1, 6); ld_x0(1, 7);
            done(0, 1, 0); done(1, 1, 0);
            ld_w(5);
            if (rb < 8) tma_prefetch5(&p.mapWo, hg * 64, rb * 2);
            done(0, 2, 0);
            fence_async_smem();
            ld_xe(5); ld_xe(6); ld_xe(7);
          } else {
            mbar_wait(bar + 8 * B_PDONE, 0);
            mbar_wait(bar + 8 * (B_PDONE + 1), 0);
            mbar_wait(bar + 8 * (WPRE == 1 ? B_U : B_GB + 1), 0);
            ld_w(0); ld_w(1);
            mbar_wait(bar + 8 * B_U1, 0);
            fence_async_smem();
            ld_w(2);
            mbar_wait(bar + 8 * (B_PUB + 2), 0);
            fence_async_smem();
            ld_w(3);
            spin_until(&g_cnt[(C_C + 3) * 32], ((lds32(sb + SM_EP) / NCTA) + 1) * NCTA);
            fence_async_global();
            if (hg >= 3) {
              mbar_expect(bar + 8 * B_SC, PG);
              tma_ld(sb + P_R * PG, &p.mapXT, rb * 64, DM + hg * 64, bar + 8 * B_SC);
            }
            ld_xe(4);
            done(0, 2, 1);
            fence_async_smem();
            ld_xe(5); ld_xe(6); ld_xe(7);
            done(1, 0, 1);
            ld_w(4);
            done(1, 1, 1);
            ld_w(5);
          }
          done(1, 2, layer);
          fence_async_smem();
          ld_w(6); ld_w(7);
          auto ld_res = [&](int half) {
            const uint32_t b = bar + 8 * (B_RF + half);
            mbar_expect(b, PG);
            if (layer == 0) tma_ld(sb + (half ? 2 : P_R) * PG, &p.mapX, hg * 64, (16 * half + rb) * 64, b);
            else tma_ld(sb + (half ? 2 : P_R) * PG, &p.mapXT, (16 * half + rb) * 64, DM + hg * 64, b);
          };
          done(0, 4, layer); done(1, 3, layer);
          fence_async_smem();
          mbar_expect(bar + 8 * B_WOF, 8 * PG);
#pragma unroll 1
          for (int c = 0; c < 8; c++) {
            if (c == 5) { ld_res(0); done(1, 4, layer); }
            tma_ld5(sb + wo_page(c) * PG, &p.mapWo, hg * 64, c * 2, bar + 8 * B_WOF);
          }
          done(0, 7, layer);
          fence_async_global();
          ld_res(1);
        }
      }
    } else if (warp == 13) {
      mbar_wait(bar + 8 * B_EP, 0);
      const unsigned e1 = (lds32(sb + SM_EP) / NCTA) + 1;
      auto ld_o = [&](int layer) {
#pragma unroll 1
        for (int half = 0; half < 2; half++) {
          done(1, 7, layer);
          mbar_wait(bar + 8 * B_OST, layer);
          if (half) mbar_wait(bar + 8 * (B_OST + 1), layer);
          fence_async_smem();
#pragma unroll
          for (int c = 0; c < 4; c++) mbar_expect(bar + 8 * (B_OF + 4 * half + c), 2 * PG);
          spin_until(&g_cnt[(C_O + layer * 32 + 16 * half + rb) * 32], e1 * 32);
#pragma unroll
          for (int c = 0; c < 4; c++)
            bulk_ld(sb + o_page(half, c) * PG, g_O + ((layer * 32 + 16 * half + rb) * 4 + c) * PG, 2 * PG, bar + 8 * (B_OF + 4 * half + c));
        }
      };
      if (elect_one()) {
        mbar_wait(bar + 8 * (B_WF + 2), 0);
        asm volatile("prefetch.tensormap [%0];" ::"l"(&p.mapXT) : "memory");
        asm volatile("prefetch.tensormap [%0];" ::"l"(&p.mapOut) : "memory");
        asm volatile("prefetch.tensormap [%0];" ::"l"(&p.mapWo) : "memory");
        spin_until(&g_cnt[C_Z * 32], e1 * NCTA);
        mbar_arrive(bar + 8 * B_ZF);
        TS(3);
        ld_o(0);
#pragma unroll 1
        for (int k = 0; k < 3; k++) {
          mbar_wait(bar + 8 * (B_PUB + k), 0);
          fence_async_smem();
          spin_until(&g_cnt[(C_C + k) * 32], e1 * NCTA);
          TS(10 + k);
          if (k == 2) fence_async_global();
#pragma unroll
          for (int c = 0; c < 4; c++) ld_x1(k != 0, (k & 2) * 2 + c, k < 2 ? B_XR + 4 * k + c : B_XF + 12 + c);
        }
        ld_o(1);
        mbar_wait(bar + 8 * B_PUB, 1);
#pragma unroll 1
        for (int half = 0; half < 2; half++) {
          mbar_expect(bar + 8 * (B_TF + half), PG);
          spin_until(&g_cnt[(C_F + 4 * (half ? 1 + (cta >> 6) : 0) + ((cta >> 4) & 3)) * 32], e1 * 32);
          tma_ld(sb + (16 + half) * PG, &p.mapXT, (16 * half + (cta & 15)) * 64, 3 * DM + (cta >> 4) * 64, bar + 8 * (B_TF + half));
        }
      }
    } else if (warp == 14) {
      mbar_wait(bar + 8 * B_EP, 0);
      const unsigned e1 = (lds32(sb + SM_EP) / NCTA) + 1;
      done(0, 1, 0);
      {
        const uint2* cp = g_colsum + (hg * 192 + lane);
        uint2 v[6];
        bool ok;
        int it = 0;
        do {
          ok = true;
#pragma unroll
          for (int i = 0; i < 6; i++) {
            asm volatile("ld.relaxed.gpu.global.v2.u32 {%0,%1}, [%2];" : "=r"(v[i].x), "=r"(v[i].y) : "l"(cp + 32 * i) : "memory");
            ok = ok && v[i].y == e1;
          }
          if (++it > (1 << 22)) __trap();
        } while (!__all_sync(~0u, ok));
#pragma unroll
        for (int i = 0; i < 6; i++) sts32f(sb + SM_CS + 4 * (lane + 32 * i), __uint_as_float(v[i].x));
      }
      __syncwarp();
      if (elect_one()) {
        mbar_wait(bar + 8 * B_ZF, 0);
        mbar_arrive(bar + 8 * B_LN);
        red_relaxed(&g_cnt[C_CS * 32]);
        TS(13);
#pragma unroll 1
        for (int i = 0; i < 4; i++) {
          const int layer = i >> 1;
          mbar_wait(bar + 8 * (B_PST + (i & 1)), layer);
          const uint32_t b = bar + 8 * (B_GB + 1);
          const bf16* xin = g_xT + ((size_t)2 * layer * DM + 2 * cta) * LSEQ + 1024;
          if (i & 1) {
            fence_async_smem();
            mbar_expect(b, 12288 + PG);
          }
          spin_until(&g_cnt[(C_G + i) * 32], e1 * NCTA);
          if (i & 1) {
            bulk_ld(sb + CV_ST, g_stats + (layer * 32 + 16) * 192, 12288, b);
#pragma unroll
            for (int lc = 0; lc < 4; lc++) bulk_ld(sb + cv_x(1, lc), xin + cv_chan(0, lc) * LSEQ, 2048, b);
            TS(14 + layer);
            publish(layer, 1);
          } else {
            mbar_arrive(bar + 8 * B_GB);
          }
        }
      }
    } else {
      const uint4 u = make_uint4(UNSET, UNSET, UNSET, UNSET);
      if (lane < 24) stg128((uint4*)g_stats + cta * 24 + lane, make_uint4(0, 0, 0, 0));
      if (lane < 16) stg128(g_rows + LSEQ + cta * 16 + lane, make_uint4(0, 0, 0, 0));
#pragma unroll 4
      for (int i = 0; i < 16; i++) stg128(g_halo + cta * 512 + 32 * i + lane, u);
#pragma unroll 4
      for (int i = 0; i < 16; i++) stg128(((i & 8) ? (uint4*)g_xT : (uint4*)g_O) + cta * 1024 + (i & 7) * 128 + (lane >> 1) * 8 + (lane & 1), u);
      __syncwarp();
      if (elect_one()) red_release(&g_cnt[C_Z * 32]);
      __syncwarp();
#pragma unroll 1
      for (int layer = 0; layer < 2; layer++) {
        auto reset_done = [&](int s) {
          spin_until(&g_cnt[(C_R + s) * 32], (lds32(sb + SM_EP) / NCTA) * 4 + 4);
          mbar_arrive(bar + 8 * (s == 1 ? B_LN : s == 2 ? B_RS : B_RC));
          if (s) TS(16 + 40 + 9 + s);
        };
        if (layer && elect_one()) reset_done(1);
        __syncwarp();
#pragma unroll 1
        for (int half = 0; half < 2; half++) {
          done(half, 2, layer);
          const uint4* src = g_rows + (layer * LSEQ + (16 * half + rb) * 64 + (opaque_tid() & 31));
          uint4 a, b;
          int it = 0;
          do {
            a = ld_tagged(src); b = ld_tagged(src + 32);
          } while (!__all_sync(~0u, (a.z | a.w) == __float_as_uint(8.f) && (b.z | b.w) == __float_as_uint(8.f)) && ++it < (1 << 20));
          float m0 = __uint_as_float(a.x) * (1.f / DM), m1 = __uint_as_float(b.x) * (1.f / DM);
          float r0 = rsqrt_approx(fmaxf(__uint_as_float(a.y) * (1.f / DM) - m0 * m0, 0.f) + 1e-5f);
          float r1 = rsqrt_approx(fmaxf(__uint_as_float(b.y) * (1.f / DM) - m1 * m1, 0.f) + 1e-5f);
          if (half) done(0, 7, layer);
          const uint32_t dst = sb + ln_off(half) + ((lane >> 4) * 8 + (lane & 7)) * 16 + (lane & 8);
          asm volatile("st.shared.v2.f32 [%0], {%1,%2};" ::"r"(dst), "f"(m0), "f"(r0) : "memory");
          asm volatile("st.shared.v2.f32 [%0], {%1,%2};" ::"r"(dst + 256), "f"(m1), "f"(r1) : "memory");
          __syncwarp();
          if (elect_one()) { mbar_arrive(bar + 8 * (B_LN + half)); TS(16 + layer * 56 + 40 + 14 + half); }
        }
        if (layer && lane < 16) stg128(g_rows + cta * 16 + (opaque_tid() & 31), make_uint4(0, 0, 0, 0));
        if (elect_one()) {
          if (layer) reset_done(2);
          reset_done(3 * layer);
          publish(layer, 0);
          publish(layer, 2);
        }
        __syncwarp();
      }
    }
  }
}

typedef CUresult (*EncodeFn)(CUtensorMap*, CUtensorMapDataType, cuuint32_t, void*, const cuuint64_t*, const cuuint64_t*,
                             const cuuint32_t*, const cuuint32_t*, CUtensorMapInterleave, CUtensorMapSwizzle,
                             CUtensorMapL2promotion, CUtensorMapFloatOOBfill);

static void make_map(EncodeFn enc, CUtensorMap* m, void* ptr, uint64_t cols, uint64_t rows, uint32_t box_rows) {
  cuuint64_t dims[2] = {cols, rows};
  cuuint64_t strides[1] = {cols * 2};
  cuuint32_t box[2] = {64, box_rows};
  cuuint32_t es[2] = {1, 1};
  enc(m, CU_TENSOR_MAP_DATA_TYPE_BFLOAT16, 2, ptr, dims, strides, box, es, CU_TENSOR_MAP_INTERLEAVE_NONE,
      CU_TENSOR_MAP_SWIZZLE_128B, CU_TENSOR_MAP_L2_PROMOTION_L2_128B, CU_TENSOR_MAP_FLOAT_OOB_FILL_NONE);
}
static void make_map3(EncodeFn enc, CUtensorMap* m, void* ptr, uint64_t d0, uint64_t cols, uint64_t rows, uint64_t blk_stride,
                      uint64_t nblocks, uint32_t nblk) {
  cuuint64_t dims[3] = {d0, rows, nblocks};
  cuuint64_t strides[2] = {cols * 2, blk_stride * 2};
  cuuint32_t box[3] = {64, 64, nblk};
  cuuint32_t es[3] = {1, 1, 1};
  enc(m, CU_TENSOR_MAP_DATA_TYPE_BFLOAT16, 3, ptr, dims, strides, box, es, CU_TENSOR_MAP_INTERLEAVE_NONE,
      CU_TENSOR_MAP_SWIZZLE_128B, CU_TENSOR_MAP_L2_PROMOTION_L2_128B, CU_TENSOR_MAP_FLOAT_OOB_FILL_NONE);
}

extern "C" void kernel_launch(void* const* d_in, const int* in_sizes, int n_in, void* d_out, int out_size) {
  static Params prm;
  static void* cached[13] = {nullptr};
  static bool attr_done = false;
  static int grid = NCTA + 4;
  bool same = attr_done && cached[12] == d_out;
  for (int i = 0; i < 12 && same; i++) same = cached[i] == d_in[i];
  if (!same) {
    void* fn = nullptr;
    cudaDriverEntryPointQueryResult qr;
    cudaGetDriverEntryPoint("cuTensorMapEncodeTiled", &fn, cudaEnableDefault, &qr);
    EncodeFn enc = (EncodeFn)fn;
    void* pXT;
    cudaGetSymbolAddress(&pXT, g_xT);
    make_map(enc, &prm.mapX, d_in[0], DM, LSEQ, 64);
    make_map(enc, &prm.mapXT, pXT, LSEQ, 4 * DM, 64);
    make_map(enc, &prm.mapOut, d_out, DM, LSEQ, 64);
    {
      cuuint64_t dims[5] = {DM, 2, 4, 4, 16};
      cuuint64_t strides[4] = {DM * 2, 8 * DM * 2, 2 * DM * 2, 32 * DM * 2};
      cuuint32_t box[5] = {64, 2, 4, 4, 2};
      cuuint32_t es[5] = {1, 1, 1, 1, 1};
      enc(&prm.mapWo, CU_TENSOR_MAP_DATA_TYPE_BFLOAT16, 5, d_in[2], dims, strides, box, es, CU_TENSOR_MAP_INTERLEAVE_NONE,
          CU_TENSOR_MAP_SWIZZLE_128B, CU_TENSOR_MAP_L2_PROMOTION_L2_128B, CU_TENSOR_MAP_FLOAT_OOB_FILL_NONE);
    }
    make_map3(enc, &prm.mapW3, d_in[1], DM, 3 * DM, DM, DM, 3, 3);
    prm.wqkv = (const bf16*)d_in[1];
    prm.a_re = (const bf16*)d_in[4]; prm.a_im = (const bf16*)d_in[5];
    prm.b_re = (const bf16*)d_in[6]; prm.b_im = (const bf16*)d_in[7];
    prm.c_re = (const bf16*)d_in[8]; prm.c_im = (const bf16*)d_in[9];
    prm.log_dt = (const bf16*)d_in[10]; prm.dskip = (const bf16*)d_in[11];
    int dev = 0, sms = 0;
    cudaGetDevice(&dev);
    cudaDeviceGetAttribute(&sms, cudaDevAttrMultiProcessorCount, dev);
    grid = sms >= NCTA + 4 ? NCTA + 4 : NCTA + 5;
    cudaFuncSetAttribute(fused_kernel, cudaFuncAttributeMaxDynamicSharedMemorySize, SM_TOTAL);
    for (int i = 0; i < 12; i++) cached[i] = d_in[i];
    cached[12] = d_out;
    attr_done = true;
  }
  fused_kernel<<<grid, NTHREADS, SM_TOTAL>>>(prm);
}
```

```cpp
#include <cuda_runtime.h>
#include <cuda_bf16.h>
#include <cuda.h>
#include <stdint.h>

typedef __nv_bfloat16 bf16;

constexpr int LSEQ = 2048;
constexpr int DM = 512;
constexpr int NCTA = 128;
constexpr int NTHREADS = 512;
#define R_CONS 200
#define R_HELP 88
#define R_AGENT 24
#define TURN0 4
#define TURN1 4

constexpr int PG = 8192;
constexpr int P_R = 25;
__host__ __device__ constexpr int x_page(int half, int c) { return half ? 8 + c : c < 5 ? c : c - 5; }
__host__ __device__ constexpr int w_page(int c) { return (c & 3) < 3 ? 16 + 3 * (c & 3) : c < 4 ? 5 : 8; }
__host__ __device__ constexpr int wo_page(int c) { return c < 5 ? 3 + c : 11 + c; }
__host__ __device__ constexpr int o_page(int half, int pair) { return half ? (pair ? 17 + 2 * pair : 0) : 8 + 2 * pair; }
constexpr int SM_KGB = (P_R + 1) * PG;
constexpr int SM_KC = 27 * PG;
constexpr int KC_STRIDE = 648;
__host__ __device__ constexpr int kc_off(int lc) { return SM_KC + (lc & 1) * 2 * KC_STRIDE + (lc < 2 ? 3328 : 0); }
constexpr int SM_KGT = SM_KC + 3328 + 2592;
constexpr int SM_CS = SM_KGT + 2048;
constexpr int SM_RED = SM_CS + 768;
constexpr int SM_EP = SM_RED + 16;
constexpr int SM_STG = SM_RED + 32;
constexpr int SM_LN = SM_STG + 768;
__host__ __device__ constexpr int ln_off(int half) { return half ? PG + 4096 : SM_LN; }
constexpr int SM_BAR = SM_LN + 512;
constexpr int SM_TS = SM_BAR + 704;
constexpr int SM_TOTAL = SM_TS + 512;
static_assert(SM_TOTAL <= 232448 && SM_STG % 16 == 0 && SM_KGT % 16 == 0, "shared memory");

constexpr int CV_UH = 140 * 16;
__host__ __device__ constexpr int cv_u(int lc) { return (8 + 2 * lc) * PG; }
__host__ __device__ constexpr int cv_pe(int lc) { return cv_u(lc) + 4480; }
__host__ __device__ constexpr int cv_pb1(int lc, int w) { return w ? cv_u(lc) + 8960 + (w - 1) * 2048 : 7 * PG + lc * 2048; }
__host__ __device__ constexpr int cv_fa(int lc) { return cv_pb1(lc, 1) + 128; }
__host__ __device__ constexpr int cv_dump(int lc) { return cv_u(lc) + 16256; }
__host__ __device__ constexpr int cv_pb0(int lc, int w) { return lc * PG + w * 2048; }
__host__ __device__ constexpr int cv_se(int lc) { return 5 * PG + lc * 4096; }
__host__ __device__ constexpr int cv_so(int lc) { return cv_se(lc) + 2048; }
__host__ __device__ constexpr int cv_x(int half, int lc) { return (P_R + half) * PG + lc * 2048; }
constexpr int CV_ST = 22 * PG;
__host__ __device__ constexpr int cv_chan(int cta, int lc) { return 2 * cta + (lc & 1) + 256 * (lc >> 1); }

enum {
  B_XF = 0,
  B_WF = 16,
  B_OF = 24,
  B_DN = 32,
  B_XR = 48,
  B_RF = 56,
  B_PST = 58,
  B_GB = 60,
  B_TF = 62,
  B_RT = 64,
  B_RS = 66,
  B_RC = 67,
  B_WOF = 68,
  B_ZF = 69,
  B_EP = 70,
  B_KG = 71,
  B_SC = 72,
  B_LN = 73,
  B_END = 75,
  B_OST = 76,
  B_PDONE = 78,
  B_PE = 80,
  B_U = 81,
  B_U1 = 82,
  B_PUB = 83,
  B_COUNT = 86
};

enum {
  C_CS = 0,
  C_G = 1,
  C_C = 5,
  C_F = 9,
  C_O = 21,
  C_Z = 85,
  C_R = 86,
  C_COUNT = 90
};

__device__ unsigned g_cnt[C_COUNT * 32];
__device__ __align__(1024) bf16 g_O[2 * LSEQ * DM];
__device__ __align__(1024) bf16 g_xT[4 * DM * LSEQ];
__device__ __align__(1024) float g_stats[2 * 32 * 192];
__device__ __align__(1024) uint2 g_colsum[3 * DM];
__device__ __align__(1024) uint4 g_halo[32 * 8 * 256];
__device__ __align__(1024) uint4 g_rows[2 * LSEQ];
#define TS(i) do { } while (0)
#define TSW(k) do { if ((threadIdx.x & 127) == 0) TS(16 + layer * 56 + (threadIdx.x >> 7) * 20 + (k)); } while (0)
#define TSG(k) do { } while (0)

#define RETRY(i) do { } while (0)
#define LTS(i) do { } while (0)

struct Params {
  CUtensorMap mapX, mapW3, mapXT, mapOut, mapWo;
  const bf16 *wqkv, *a_re, *a_im, *b_re, *b_im, *c_re, *c_im, *log_dt, *dskip;
};

__device__ __forceinline__ uint32_t s32(const void* p) { return (uint32_t)__cvta_generic_to_shared(p); }
__device__ __forceinline__ void mbar_init(uint32_t b, int c) { asm volatile("mbarrier.init.shared::cta.b64 [%0], %1;" ::"r"(b), "r"(c) : "memory"); }
__device__ __forceinline__ void mbar_expect(uint32_t b, int bytes) { asm volatile("mbarrier.arrive.expect_tx.shared::cta.b64 _, [%0], %1;" ::"r"(b), "r"(bytes) : "memory"); }
__device__ __forceinline__ void mbar_arrive(uint32_t b) { asm volatile("mbarrier.arrive.shared::cta.b64 _, [%0];" ::"r"(b) : "memory"); }
__device__ __forceinline__ void mbar_wait(uint32_t b, int parity) {
  asm volatile("{\n.reg .pred p;\nWAIT_LOOP:\nmbarrier.try_wait.parity.shared::cta.b64 p, [%0], %1;\n@p bra WAIT_DONE;\nbra WAIT_LOOP;\nWAIT_DONE:\n}" ::"r"(b), "r"(parity) : "memory");
}
__device__ __forceinline__ bool mbar_test(uint32_t b, int parity) {
  uint32_t ok;
  asm volatile("{\n.reg .pred p;\nmbarrier.test_wait.parity.shared::cta.b64 p, [%1], %2;\nselp.u32 %0, 1, 0, p;\n}" : "=r"(ok) : "r"(b), "r"(parity) : "memory");
  return ok != 0;
}
__device__ __forceinline__ int opaque_tid() { int v; asm volatile("mov.u32 %0, %%tid.x;" : "=r"(v)); return v; }
__device__ __forceinline__ bool elect_one() {
  uint32_t r;
  asm volatile("{\n.reg .pred p;\nelect.sync _|p, 0xffffffff;\nselp.u32 %0, 1, 0, p;\n}" : "=r"(r));
  return r != 0;
}
__device__ __forceinline__ void tma_ld(uint32_t dst, const CUtensorMap* m, int c0, int c1, uint32_t bar) {
  asm volatile("cp.async.bulk.tensor.2d.shared::cluster.global.mbarrier::complete_tx::bytes [%0], [%1, {%3, %4}], [%2];"
               ::"r"(dst), "l"(m), "r"(bar), "r"(c0), "r"(c1) : "memory");
}
__device__ __forceinline__ void tma_ld3(uint32_t dst, const CUtensorMap* m, int c0, int c1, int c2, uint32_t bar) {
  asm volatile("cp.async.bulk.tensor.3d.shared::cluster.global.mbarrier::complete_tx::bytes [%0], [%1, {%3, %4, %5}], [%2];"
               ::"r"(dst), "l"(m), "r"(bar), "r"(c0), "r"(c1), "r"(c2) : "memory");
}
__device__ __forceinline__ void tma_ld5(uint32_t dst, const CUtensorMap* m, int c0, int c4, uint32_t bar) {
  asm volatile("cp.async.bulk.tensor.5d.shared::cluster.global.mbarrier::complete_tx::bytes [%0], [%1, {%3, 0, 0, 0, %4}], [%2];"
               ::"r"(dst), "l"(m), "r"(bar), "r"(c0), "r"(c4) : "memory");
}
__device__ __forceinline__ void tma_prefetch5(const CUtensorMap* m, int c0, int c4) {
  asm volatile("cp.async.bulk.prefetch.tensor.5d.L2.global.tile [%0, {%1, 0, 0, 0, %2}];" ::"l"(m), "r"(c0), "r"(c4) : "memory");
}
__device__ __forceinline__ void tma_prefetch2(const CUtensorMap* m, int c0, int c1) {
  asm volatile("cp.async.bulk.prefetch.tensor.2d.L2.global.tile [%0, {%1, %2}];" ::"l"(m), "r"(c0), "r"(c1) : "memory");
}
__device__ __forceinline__ void tma_prefetch3(const CUtensorMap* m, int c0, int c1, int c2) {
  asm volatile("cp.async.bulk.prefetch.tensor.3d.L2.global.tile [%0, {%1, %2, %3}];" ::"l"(m), "r"(c0), "r"(c1), "r"(c2) : "memory");
}
__device__ __forceinline__ void tma_st(const CUtensorMap* m, int c0, int c1, uint32_t src) {
  asm volatile("cp.async.bulk.tensor.2d.global.shared::cta.bulk_group [%0, {%2, %3}], [%1];" ::"l"(m), "r"(src), "r"(c0), "r"(c1) : "memory");
}
__device__ __forceinline__ void bulk_ld(uint32_t dst, const void* src, int bytes, uint32_t bar) {
  asm volatile("cp.async.bulk.shared::cluster.global.mbarrier::complete_tx::bytes [%0], [%1], %2, [%3];" ::"r"(dst), "l"(src), "r"(bytes), "r"(bar) : "memory");
}
__device__ __forceinline__ void bulk_st(void* dst, uint32_t src, int bytes) {
  asm volatile("cp.async.bulk.global.shared::cta.bulk_group [%0], [%1], %2;" ::"l"(dst), "r"(src), "r"(bytes) : "memory");
}
__device__ __forceinline__ void bulk_red_add_f32(void* dst, uint32_t src, int bytes) {
  asm volatile("cp.reduce.async.bulk.global.shared::cta.bulk_group.add.f32 [%0], [%1], %2;" ::"l"(dst), "r"(src), "r"(bytes) : "memory");
}
__device__ __forceinline__ void bulk_commit() { asm volatile("cp.async.bulk.commit_group;" ::: "memory"); }
__device__ __forceinline__ void bulk_wait_all() { asm volatile("cp.async.bulk.wait_group 0;" ::: "memory"); }
__device__ __forceinline__ void fence_async_smem() { asm volatile("fence.proxy.async.shared::cta;" ::: "memory"); }
__device__ __forceinline__ void fence_async_global() { asm volatile("fence.proxy.async.global;" ::: "memory"); }
__device__ __forceinline__ void bar_sync(int id, int n) { asm volatile("bar.sync %0, %1;" ::"r"(id), "r"(n) : "memory"); }
__device__ __forceinline__ void bar_arrive(int id, int n) { asm volatile("bar.arrive %0, %1;" ::"r"(id), "r"(n) : "memory"); }
__device__ __forceinline__ bool bar_or(int id, int n, bool v) {
  uint32_t r;
  asm volatile("{\n.reg .pred p, q;\nsetp.ne.u32 q, %3, 0;\nbar.red.or.pred p, %1, %2, q;\nselp.u32 %0, 1, 0, p;\n}" : "=r"(r) : "r"(id), "r"(n), "r"((uint32_t)v) : "memory");
  return r != 0;
}
__device__ __forceinline__ void bulk_wait_read() { asm volatile("cp.async.bulk.wait_group.read 0;" ::: "memory"); }
__device__ __forceinline__ void stg128(void* p, uint4 v) { asm volatile("st.relaxed.gpu.global.v4.u32 [%0], {%1,%2,%3,%4};" ::"l"(p), "r"(v.x), "r"(v.y), "r"(v.z), "r"(v.w) : "memory"); }
constexpr uint32_t UNSET = 0xffffffffu;
constexpr int MAX_RETRY = 1 << 16;
__device__ __forceinline__ void wg_fence() { asm volatile("wgmma.fence.sync.aligned;" ::: "memory"); }
__device__ __forceinline__ void wg_commit() { asm volatile("wgmma.commit_group.sync.aligned;" ::: "memory"); }
template <int N> __device__ __forceinline__ void wg_wait() { asm volatile("wgmma.wait_group.sync.aligned %0;" ::"n"(N) : "memory"); }
__device__ __forceinline__ uint64_t mkdesc(uint32_t addr, uint32_t lbo, uint32_t sbo, int sw) {
  return (uint64_t)((addr & 0x3FFFF) >> 4) | ((uint64_t)(lbo >> 4) << 16) | ((uint64_t)(sbo >> 4) << 32) | ((uint64_t)sw << 62);
}
__device__ __forceinline__ void ldsm4(uint32_t* r, uint32_t a) {
  asm volatile("ldmatrix.sync.aligned.m8n8.x4.shared.b16 {%0,%1,%2,%3}, [%4];" : "=r"(r[0]), "=r"(r[1]), "=r"(r[2]), "=r"(r[3]) : "r"(a) : "memory");
}
__device__ __forceinline__ void ldsm4t(uint32_t* r, uint32_t a) {
  asm volatile("ldmatrix.sync.aligned.m8n8.x4.trans.shared.b16 {%0,%1,%2,%3}, [%4];" : "=r"(r[0]), "=r"(r[1]), "=r"(r[2]), "=r"(r[3]) : "r"(a) : "memory");
}
__device__ __forceinline__ void stsm4(uint32_t a, uint32_t r0, uint32_t r1, uint32_t r2, uint32_t r3) {
  asm volatile("stmatrix.sync.aligned.m8n8.x4.shared.b16 [%0], {%1,%2,%3,%4};" ::"r"(a), "r"(r0), "r"(r1), "r"(r2), "r"(r3) : "memory");
}
__device__ __forceinline__ void stsm4t(uint32_t a, uint32_t r0, uint32_t r1, uint32_t r2, uint32_t r3) {
  asm volatile("stmatrix.sync.aligned.m8n8.x4.trans.shared.b16 [%0], {%1,%2,%3,%4};" ::"r"(a), "r"(r0), "r"(r1), "r"(r2), "r"(r3) : "memory");
}
__device__ __forceinline__ uint32_t movm_t(uint32_t a) { uint32_t r; asm volatile("movmatrix.sync.aligned.m8n8.trans.b16 %0, %1;" : "=r"(r) : "r"(a)); return r; }
__device__ __forceinline__ uint32_t lds32(uint32_t a) { uint32_t v; asm volatile("ld.shared.b32 %0, [%1];" : "=r"(v) : "r"(a) : "memory"); return v; }
__device__ __forceinline__ float2 lds64f(uint32_t a) { float2 v; asm volatile("ld.shared.v2.f32 {%0,%1}, [%2];" : "=f"(v.x), "=f"(v.y) : "r"(a) : "memory"); return v; }
__device__ __forceinline__ float4 lds128f(uint32_t a) { float4 v; asm volatile("ld.shared.v4.f32 {%0,%1,%2,%3}, [%4];" : "=f"(v.x), "=f"(v.y), "=f"(v.z), "=f"(v.w) : "r"(a) : "memory"); return v; }
__device__ __forceinline__ uint4 lds128(uint32_t a) { uint4 v; asm volatile("ld.shared.v4.b32 {%0,%1,%2,%3}, [%4];" : "=r"(v.x), "=r"(v.y), "=r"(v.z), "=r"(v.w) : "r"(a) : "memory"); return v; }
__device__ __forceinline__ void sts128(uint32_t a, uint4 v) { asm volatile("st.shared.v4.b32 [%0], {%1,%2,%3,%4};" ::"r"(a), "r"(v.x), "r"(v.y), "r"(v.z), "r"(v.w) : "memory"); }
__device__ __forceinline__ void sts128f(uint32_t a, float x, float y, float z, float w) { asm volatile("st.shared.v4.f32 [%0], {%1,%2,%3,%4};" ::"r"(a), "f"(x), "f"(y), "f"(z), "f"(w) : "memory"); }
__device__ __forceinline__ void sts32f(uint32_t a, float v) { asm volatile("st.shared.f32 [%0], %1;" ::"r"(a), "f"(v) : "memory"); }
__device__ __forceinline__ void sts16(uint32_t a, uint16_t v) { asm volatile("st.shared.u16 [%0], %1;" ::"r"(a), "h"(v) : "memory"); }
__device__ __forceinline__ uint32_t lds16(uint32_t a) { uint16_t v; asm volatile("ld.shared.u16 %0, [%1];" : "=h"(v) : "r"(a) : "memory"); return v; }
__device__ __forceinline__ uint32_t packbf(float lo, float hi) { uint32_t r; asm("cvt.rn.bf16x2.f32 %0, %1, %2;" : "=r"(r) : "f"(hi), "f"(lo)); return r; }
__device__ __forceinline__ float bf_lo(uint32_t v) { return __uint_as_float(v << 16); }
__device__ __forceinline__ float bf_hi(uint32_t v) { return __uint_as_float(v & 0xffff0000u); }
__device__ __forceinline__ float ex2(float x) { float r; asm("ex2.approx.ftz.f32 %0, %1;" : "=f"(r) : "f"(x)); return r; }
__device__ __forceinline__ float rsqrt_approx(float x) { float r; asm("rsqrt.approx.ftz.f32 %0, %1;" : "=f"(r) : "f"(x)); return r; }
__device__ __forceinline__ float rcp_approx(float x) { float r; asm("rcp.approx.ftz.f32 %0, %1;" : "=f"(r) : "f"(x)); return r; }
__device__ __forceinline__ void mma_bf16(float* d, const uint32_t* a, uint32_t b0, uint32_t b1) {
  asm("mma.sync.aligned.m16n8k16.row.col.f32.bf16.bf16.f32 {%0,%1,%2,%3}, {%4,%5,%6,%7}, {%8,%9}, {%0,%1,%2,%3};"
               : "+f"(d[0]), "+f"(d[1]), "+f"(d[2]), "+f"(d[3]) : "r"(a[0]), "r"(a[1]), "r"(a[2]), "r"(a[3]), "r"(b0), "r"(b1));
}
__device__ __forceinline__ void mma_tf32(float* d, float a0, float a1, float a2, float a3, float b0, float b1) {
  asm("mma.sync.aligned.m16n8k8.row.col.f32.tf32.tf32.f32 {%0,%1,%2,%3}, {%4,%5,%6,%7}, {%8,%9}, {%0,%1,%2,%3};"
               : "+f"(d[0]), "+f"(d[1]), "+f"(d[2]), "+f"(d[3])
               : "r"(__float_as_uint(a0)), "r"(__float_as_uint(a1)), "r"(__float_as_uint(a2)), "r"(__float_as_uint(a3)),
                 "r"(__float_as_uint(b0)), "r"(__float_as_uint(b1)));
}
__device__ __forceinline__ void red_release(unsigned* p) { asm volatile("red.release.gpu.global.add.u32 [%0], 1;" ::"l"(p) : "memory"); }
__device__ __forceinline__ void red_relaxed(unsigned* p) { asm volatile("red.relaxed.gpu.global.add.u32 [%0], 1;" ::"l"(p) : "memory"); }
__device__ __forceinline__ unsigned ld_relaxed(const unsigned* p) { unsigned v; asm volatile("ld.relaxed.gpu.global.u32 %0, [%1];" : "=r"(v) : "l"(p) : "memory"); return v; }
__device__ __forceinline__ void spin_until(const unsigned* p, unsigned target) {
  int it = 0;
  while ((int)(ld_relaxed(p) - target) < 0) {
    if (++it > (1 << 23)) __trap();
  }
}
__device__ __forceinline__ uint4 ldcg128(const void* p) { uint4 v; asm volatile("ld.global.cg.v4.b32 {%0,%1,%2,%3}, [%4];" : "=r"(v.x), "=r"(v.y), "=r"(v.z), "=r"(v.w) : "l"(p) : "memory"); return v; }
__device__ __forceinline__ uint4 ld_tagged(const uint4* p) { uint4 v; asm volatile("ld.relaxed.gpu.global.v4.u32 {%0,%1,%2,%3}, [%4];" : "=r"(v.x), "=r"(v.y), "=r"(v.z), "=r"(v.w) : "l"(p) : "memory"); return v; }
__device__ __forceinline__ void st_tagged(uint4* p, uint32_t a, uint32_t b, uint32_t tag) { asm volatile("st.relaxed.gpu.global.v4.u32 [%0], {%1,%2,%3,%2};" ::"l"(p), "r"(a), "r"(tag), "r"(b) : "memory"); }
__device__ __forceinline__ void st_tagged3(uint4* p, uint32_t a, uint32_t b, uint32_t c, uint32_t tag) { asm volatile("st.relaxed.gpu.global.v4.u32 [%0], {%1,%2,%3,%4};" ::"l"(p), "r"(a), "r"(b), "r"(c), "r"(tag) : "memory"); }
__device__ __forceinline__ uint4 poll_tagged(const uint4* p, uint32_t tag) {
  uint4 v = ld_tagged(p);
  int it = 0;
  while (v.y != tag || v.w != tag) {
    if (++it > (1 << 22)) __trap();
    v = ld_tagged(p);
  }
  return v;
}
__device__ __forceinline__ uint32_t hadd2(uint32_t a, uint32_t b) { uint32_t r; asm("add.rn.bf16x2 %0, %1, %2;" : "=r"(r) : "r"(a), "r"(b)); return r; }
__device__ __forceinline__ uint32_t hmul2(uint32_t a, uint32_t b) { uint32_t r; asm("mul.rn.bf16x2 %0, %1, %2;" : "=r"(r) : "r"(a), "r"(b)); return r; }

__device__ __forceinline__ uint32_t hfma2(uint32_t a, uint32_t b, uint32_t c) { uint32_t r; asm("fma.rn.bf16x2 %0, %1, %2, %3;" : "=r"(r) : "r"(a), "r"(b), "r"(c)); return r; }
__device__ __forceinline__ void sts32(uint32_t a, uint32_t v) { asm volatile("st.shared.u32 [%0], %1;" ::"r"(a), "r"(v) : "memory"); }

template <int N> __device__ __forceinline__ void acc_fence(float* a) {
#pragma unroll
  for (int i = 0; i < N; i++) asm volatile("" : "+f"(a[i]) :: "memory");
}

template<int N,int TB> __device__ __forceinline__ void wgmma_rs(float* d, const uint32_t* a, uint64_t db, int sd);
template<int N,int TA,int TB> __device__ __forceinline__ void wgmma_ss(float* d, uint64_t da, uint64_t db, int sd);
template<> __device__ __forceinline__ void wgmma_rs<64,0>(float* d, const uint32_t* a, uint64_t db, int sd) {
  asm volatile("{\n.reg .pred p;\nsetp.ne.b32 p, %37, 0;\nwgmma.mma_async.sync.aligned.m64n64k16.f32.bf16.bf16 {%0,%1,%2,%3,%4,%5,%6,%7,%8,%9,%10,%11,%12,%13,%14,%15,%16,%17,%18,%19,%20,%21,%22,%23,%24,%25,%26,%27,%28,%29,%30,%31}, {%32,%33,%34,%35}, %36, p, 1, 1, 0;\n}\n"
   : "+f"(d[0]),"+f"(d[1]),"+f"(d[2]),"+f"(d[3]),"+f"(d[4]),"+f"(d[5]),"+f"(d[6]),"+f"(d[7]),"+f"(d[8]),"+f"(d[9]),"+f"(d[10]),"+f"(d[11]),"+f"(d[12]),"+f"(d[13]),"+f"(d[14]),"+f"(d[15]),"+f"(d[16]),"+f"(d[17]),"+f"(d[18]),"+f"(d[19]),"+f"(d[20]),"+f"(d[21]),"+f"(d[22]),"+f"(d[23]),"+f"(d[24]),"+f"(d[25]),"+f"(d[26]),"+f"(d[27]),"+f"(d[28]),"+f"(d[29]),"+f"(d[30]),"+f"(d[31])
   : "r"(a[0]), "r"(a[1]), "r"(a[2]), "r"(a[3]), "l"(db), "r"(sd));
}
template<> __device__ __forceinline__ void wgmma_rs<56,0>(float* d, const uint32_t* a, uint64_t db, int sd) {
  asm volatile("{\n.reg .pred p;\nsetp.ne.b32 p, %33, 0;\nwgmma.mma_async.sync.aligned.m64n56k16.f32.bf16.bf16 {%0,%1,%2,%3,%4,%5,%6,%7,%8,%9,%10,%11,%12,%13,%14,%15,%16,%17,%18,%19,%20,%21,%22,%23,%24,%25,%26,%27}, {%28,%29,%30,%31}, %32, p, 1, 1, 0;\n}\n"
   : "+f"(d[0]),"+f"(d[1]),"+f"(d[2]),"+f"(d[3]),"+f"(d[4]),"+f"(d[5]),"+f"(d[6]),"+f"(d[7]),"+f"(d[8]),"+f"(d[9]),"+f"(d[10]),"+f"(d[11]),"+f"(d[12]),"+f"(d[13]),"+f"(d[14]),"+f"(d[15]),"+f"(d[16]),"+f"(d[17]),"+f"(d[18]),"+f"(d[19]),"+f"(d[20]),"+f"(d[21]),"+f"(d[22]),"+f"(d[23]),"+f"(d[24]),"+f"(d[25]),"+f"(d[26]),"+f"(d[27])
   : "r"(a[0]), "r"(a[1]), "r"(a[2]), "r"(a[3]), "l"(db), "r"(sd));
}
template<> __device__ __forceinline__ void wgmma_rs<48,0>(float* d, const uint32_t* a, uint64_t db, int sd) {
  asm volatile("{\n.reg .pred p;\nsetp.ne.b32 p, %29, 0;\nwgmma.mma_async.sync.aligned.m64n48k16.f32.bf16.bf16 {%0,%1,%2,%3,%4,%5,%6,%7,%8,%9,%10,%11,%12,%13,%14,%15,%16,%17,%18,%19,%20,%21,%22,%23}, {%24,%25,%26,%27}, %28, p, 1, 1, 0;\n}\n"
   : "+f"(d[0]),"+f"(d[1]),"+f"(d[2]),"+f"(d[3]),"+f"(d[4]),"+f"(d[5]),"+f"(d[6]),"+f"(d[7]),"+f"(d[8]),"+f"(d[9]),"+f"(d[10]),"+f"(d[11]),"+f"(d[12]),"+f"(d[13]),"+f"(d[14]),"+f"(d[15]),"+f"(d[16]),"+f"(d[17]),"+f"(d[18]),"+f"(d[19]),"+f"(d[20]),"+f"(d[21]),"+f"(d[22]),"+f"(d[23])
   : "r"(a[0]), "r"(a[1]), "r"(a[2]), "r"(a[3]), "l"(db), "r"(sd));
}
template<> __device__ __forceinline__ void wgmma_rs<40,0>(float* d, const uint32_t* a, uint64_t db, int sd) {
  asm volatile("{\n.reg .pred p;\nsetp.ne.b32 p, %25, 0;\nwgmma.mma_async.sync.aligned.m64n40k16.f32.bf16.bf16 {%0,%1,%2,%3,%4,%5,%6,%7,%8,%9,%10,%11,%12,%13,%14,%15,%16,%17,%18,%19}, {%20,%21,%22,%23}, %24, p, 1, 1, 0;\n}\n"
   : "+f"(d[0]),"+f"(d[1]),"+f"(d[2]),"+f"(d[3]),"+f"(d[4]),"+f"(d[5]),"+f"(d[6]),"+f"(d[7]),"+f"(d[8]),"+f"(d[9]),"+f"(d[10]),"+f"(d[11]),"+f"(d[12]),"+f"(d[13]),"+f"(d[14]),"+f"(d[15]),"+f"(d[16]),"+f"(d[17]),"+f"(d[18]),"+f"(d[19])
   : "r"(a[0]), "r"(a[1]), "r"(a[2]), "r"(a[3]), "l"(db), "r"(sd));
}
template<> __device__ __forceinline__ void wgmma_rs<32,0>(float* d, const uint32_t* a, uint64_t db, int sd) {
  asm volatile("{\n.reg .pred p;\nsetp.ne.b32 p, %21, 0;\nwgmma.mma_async.sync.aligned.m64n32k16.f32.bf16.bf16 {%0,%1,%2,%3,%4,%5,%6,%7,%8,%9,%10,%11,%12,%13,%14,%15}, {%16,%17,%18,%19}, %20, p, 1, 1, 0;\n}\n"
   : "+f"(d[0]),"+f"(d[1]),"+f"(d[2]),"+f"(d[3]),"+f"(d[4]),"+f"(d[5]),"+f"(d[6]),"+f"(d[7]),"+f"(d[8]),"+f"(d[9]),"+f"(d[10]),"+f"(d[11]),"+f"(d[12]),"+f"(d[13]),"+f"(d[14]),"+f"(d[15])
   : "r"(a[0]), "r"(a[1]), "r"(a[2]), "r"(a[3]), "l"(db), "r"(sd));
}
template<> __device__ __forceinline__ void wgmma_rs<24,0>(float* d, const uint32_t* a, uint64_t db, int sd) {
  asm volatile("{\n.reg .pred p;\nsetp.ne.b32 p, %17, 0;\nwgmma.mma_async.sync.aligned.m64n24k16.f32.bf16.bf16 {%0,%1,%2,%3,%4,%5,%6,%7,%8,%9,%10,%11}, {%12,%13,%14,%15}, %16, p, 1, 1, 0;\n}\n"
   : "+f"(d[0]),"+f"(d[1]),"+f"(d[2]),"+f"(d[3]),"+f"(d[4]),"+f"(d[5]),"+f"(d[6]),"+f"(d[7]),"+f"(d[8]),"+f"(d[9]),"+f"(d[10]),"+f"(d[11])
   : "r"(a[0]), "r"(a[1]), "r"(a[2]), "r"(a[3]), "l"(db), "r"(sd));
}
template<> __device__ __forceinline__ void wgmma_rs<16,0>(float* d, const uint32_t* a, uint64_t db, int sd) {
  asm volatile("{\n.reg .pred p;\nsetp.ne.b32 p, %13, 0;\nwgmma.mma_async.sync.aligned.m64n16k16.f32.bf16.bf16 {%0,%1,%2,%3,%4,%5,%6,%7}, {%8,%9,%10,%11}, %12, p, 1, 1, 0;\n}\n"
   : "+f"(d[0]),"+f"(d[1]),"+f"(d[2]),"+f"(d[3]),"+f"(d[4]),"+f"(d[5]),"+f"(d[6]),"+f"(d[7])
   : "r"(a[0]), "r"(a[1]), "r"(a[2]), "r"(a[3]), "l"(db), "r"(sd));
}
template<> __device__ __forceinline__ void wgmma_rs<8,0>(float* d, const uint32_t* a, uint64_t db, int sd) {
  asm volatile("{\n.reg .pred p;\nsetp.ne.b32 p, %9, 0;\nwgmma.mma_async.sync.aligned.m64n8k16.f32.bf16.bf16 {%0,%1,%2,%3}, {%4,%5,%6,%7}, %8, p, 1, 1, 0;\n}\n"
   : "+f"(d[0]),"+f"(d[1]),"+f"(d[2]),"+f"(d[3])
   : "r"(a[0]), "r"(a[1]), "r"(a[2]), "r"(a[3]), "l"(db), "r"(sd));
}
template<> __device__ __forceinline__ void wgmma_ss<64,1,0>(float* d, uint64_t da, uint64_t db, int sd) {
  asm volatile("{\n.reg .pred p;\nsetp.ne.b32 p, %34, 0;\nwgmma.mma_async.sync.aligned.m64n64k16.f32.bf16.bf16 {%0,%1,%2,%3,%4,%5,%6,%7,%8,%9,%10,%11,%12,%13,%14,%15,%16,%17,%18,%19,%20,%21,%22,%23,%24,%25,%26,%27,%28,%29,%30,%31}, %32, %33, p, 1, 1, 1, 0;\n}\n"
   : "+f"(d[0]),"+f"(d[1]),"+f"(d[2]),"+f"(d[3]),"+f"(d[4]),"+f"(d[5]),"+f"(d[6]),"+f"(d[7]),"+f"(d[8]),"+f"(d[9]),"+f"(d[10]),"+f"(d[11]),"+f"(d[12]),"+f"(d[13]),"+f"(d[14]),"+f"(d[15]),"+f"(d[16]),"+f"(d[17]),"+f"(d[18]),"+f"(d[19]),"+f"(d[20]),"+f"(d[21]),"+f"(d[22]),"+f"(d[23]),"+f"(d[24]),"+f"(d[25]),"+f"(d[26]),"+f"(d[27]),"+f"(d[28]),"+f"(d[29]),"+f"(d[30]),"+f"(d[31])
   : "l"(da), "l"(db), "r"(sd));
}
template<> __device__ __forceinline__ void wgmma_ss<64,0,1>(float* d, uint64_t da, uint64_t db, int sd) {
  asm volatile("{\n.reg .pred p;\nsetp.ne.b32 p, %34, 0;\nwgmma.mma_async.sync.aligned.m64n64k16.f32.bf16.bf16 {%0,%1,%2,%3,%4,%5,%6,%7,%8,%9,%10,%11,%12,%13,%14,%15,%16,%17,%18,%19,%20,%21,%22,%23,%24,%25,%26,%27,%28,%29,%30,%31}, %32, %33, p, 1, 1, 0, 1;\n}\n"
   : "+f"(d[0]),"+f"(d[1]),"+f"(d[2]),"+f"(d[3]),"+f"(d[4]),"+f"(d[5]),"+f"(d[6]),"+f"(d[7]),"+f"(d[8]),"+f"(d[9]),"+f"(d[10]),"+f"(d[11]),"+f"(d[12]),"+f"(d[13]),"+f"(d[14]),"+f"(d[15]),"+f"(d[16]),"+f"(d[17]),"+f"(d[18]),"+f"(d[19]),"+f"(d[20]),"+f"(d[21]),"+f"(d[22]),"+f"(d[23]),"+f"(d[24]),"+f"(d[25]),"+f"(d[26]),"+f"(d[27]),"+f"(d[28]),"+f"(d[29]),"+f"(d[30]),"+f"(d[31])
   : "l"(da), "l"(db), "r"(sd));
}
template<> __device__ __forceinline__ void wgmma_ss<192,0,1>(float* d, uint64_t da, uint64_t db, int sd) {
  asm volatile("{\n.reg .pred p;\nsetp.ne.b32 p, %98, 0;\nwgmma.mma_async.sync.aligned.m64n192k16.f32.bf16.bf16 {%0,%1,%2,%3,%4,%5,%6,%7,%8,%9,%10,%11,%12,%13,%14,%15,%16,%17,%18,%19,%20,%21,%22,%23,%24,%25,%26,%27,%28,%29,%30,%31,%32,%33,%34,%35,%36,%37,%38,%39,%40,%41,%42,%43,%44,%45,%46,%47,%48,%49,%50,%51,%52,%53,%54,%55,%56,%57,%58,%59,%60,%61,%62,%63,%64,%65,%66,%67,%68,%69,%70,%71,%72,%73,%74,%75,%76,%77,%78,%79,%80,%81,%82,%83,%84,%85,%86,%87,%88,%89,%90,%91,%92,%93,%94,%95}, %96, %97, p, 1, 1, 0, 1;\n}\n"
   : "+f"(d[0]),"+f"(d[1]),"+f"(d[2]),"+f"(d[3]),"+f"(d[4]),"+f"(d[5]),"+f"(d[6]),"+f"(d[7]),"+f"(d[8]),"+f"(d[9]),"+f"(d[10]),"+f"(d[11]),"+f"(d[12]),"+f"(d[13]),"+f"(d[14]),"+f"(d[15]),"+f"(d[16]),"+f"(d[17]),"+f"(d[18]),"+f"(d[19]),"+f"(d[20]),"+f"(d[21]),"+f"(d[22]),"+f"(d[23]),"+f"(d[24]),"+f"(d[25]),"+f"(d[26]),"+f"(d[27]),"+f"(d[28]),"+f"(d[29]),"+f"(d[30]),"+f"(d[31]),"+f"(d[32]),"+f"(d[33]),"+f"(d[34]),"+f"(d[35]),"+f"(d[36]),"+f"(d[37]),"+f"(d[38]),"+f"(d[39]),"+f"(d[40]),"+f"(d[41]),"+f"(d[42]),"+f"(d[43]),"+f"(d[44]),"+f"(d[45]),"+f"(d[46]),"+f"(d[47]),"+f"(d[48]),"+f"(d[49]),"+f"(d[50]),"+f"(d[51]),"+f"(d[52]),"+f"(d[53]),"+f"(d[54]),"+f"(d[55]),"+f"(d[56]),"+f"(d[57]),"+f"(d[58]),"+f"(d[59]),"+f"(d[60]),"+f"(d[61]),"+f"(d[62]),"+f"(d[63]),"+f"(d[64]),"+f"(d[65]),"+f"(d[66]),"+f"(d[67]),"+f"(d[68]),"+f"(d[69]),"+f"(d[70]),"+f"(d[71]),"+f"(d[72]),"+f"(d[73]),"+f"(d[74]),"+f"(d[75]),"+f"(d[76]),"+f"(d[77]),"+f"(d[78]),"+f"(d[79]),"+f"(d[80]),"+f"(d[81]),"+f"(d[82]),"+f"(d[83]),"+f"(d[84]),"+f"(d[85]),"+f"(d[86]),"+f"(d[87]),"+f"(d[88]),"+f"(d[89]),"+f"(d[90]),"+f"(d[91]),"+f"(d[92]),"+f"(d[93]),"+f"(d[94]),"+f"(d[95])
   : "l"(da), "l"(db), "r"(sd));
}
template<> __device__ __forceinline__ void wgmma_ss<192,1,1>(float* d, uint64_t da, uint64_t db, int sd) {
  asm volatile("{\n.reg .pred p;\nsetp.ne.b32 p, %98, 0;\nwgmma.mma_async.sync.aligned.m64n192k16.f32.bf16.bf16 {%0,%1,%2,%3,%4,%5,%6,%7,%8,%9,%10,%11,%12,%13,%14,%15,%16,%17,%18,%19,%20,%21,%22,%23,%24,%25,%26,%27,%28,%29,%30,%31,%32,%33,%34,%35,%36,%37,%38,%39,%40,%41,%42,%43,%44,%45,%46,%47,%48,%49,%50,%51,%52,%53,%54,%55,%56,%57,%58,%59,%60,%61,%62,%63,%64,%65,%66,%67,%68,%69,%70,%71,%72,%73,%74,%75,%76,%77,%78,%79,%80,%81,%82,%83,%84,%85,%86,%87,%88,%89,%90,%91,%92,%93,%94,%95}, %96, %97, p, 1, 1, 1, 1;\n}\n"
   : "+f"(d[0]),"+f"(d[1]),"+f"(d[2]),"+f"(d[3]),"+f"(d[4]),"+f"(d[5]),"+f"(d[6]),"+f"(d[7]),"+f"(d[8]),"+f"(d[9]),"+f"(d[10]),"+f"(d[11]),"+f"(d[12]),"+f"(d[13]),"+f"(d[14]),"+f"(d[15]),"+f"(d[16]),"+f"(d[17]),"+f"(d[18]),"+f"(d[19]),"+f"(d[20]),"+f"(d[21]),"+f"(d[22]),"+f"(d[23]),"+f"(d[24]),"+f"(d[25]),"+f"(d[26]),"+f"(d[27]),"+f"(d[28]),"+f"(d[29]),"+f"(d[30]),"+f"(d[31]),"+f"(d[32]),"+f"(d[33]),"+f"(d[34]),"+f"(d[35]),"+f"(d[36]),"+f"(d[37]),"+f"(d[38]),"+f"(d[39]),"+f"(d[40]),"+f"(d[41]),"+f"(d[42]),"+f"(d[43]),"+f"(d[44]),"+f"(d[45]),"+f"(d[46]),"+f"(d[47]),"+f"(d[48]),"+f"(d[49]),"+f"(d[50]),"+f"(d[51]),"+f"(d[52]),"+f"(d[53]),"+f"(d[54]),"+f"(d[55]),"+f"(d[56]),"+f"(d[57]),"+f"(d[58]),"+f"(d[59]),"+f"(d[60]),"+f"(d[61]),"+f"(d[62]),"+f"(d[63]),"+f"(d[64]),"+f"(d[65]),"+f"(d[66]),"+f"(d[67]),"+f"(d[68]),"+f"(d[69]),"+f"(d[70]),"+f"(d[71]),"+f"(d[72]),"+f"(d[73]),"+f"(d[74]),"+f"(d[75]),"+f"(d[76]),"+f"(d[77]),"+f"(d[78]),"+f"(d[79]),"+f"(d[80]),"+f"(d[81]),"+f"(d[82]),"+f"(d[83]),"+f"(d[84]),"+f"(d[85]),"+f"(d[86]),"+f"(d[87]),"+f"(d[88]),"+f"(d[89]),"+f"(d[90]),"+f"(d[91]),"+f"(d[92]),"+f"(d[93]),"+f"(d[94]),"+f"(d[95])
   : "l"(da), "l"(db), "r"(sd));
}

template <bool TR>
__device__ __forceinline__ void gemm_section(float* acc, float& mean0, float& mean1, float& rstd0, float& rstd1,
                                             uint32_t sb, int blk, int hg, int wg, int w, int lane) {
  constexpr int layer = TR ? 1 : 0;
  constexpr int TURN = TR ? TURN1 : TURN0;
  constexpr int LSTAT = TURN < 4 ? TURN - 1 : 3;
  const uint32_t bar = sb + SM_BAR;
  const int g = lane >> 2, t = lane & 3;
  const bool leader = (w == 0) && (lane == 0);
  const int statpos = hg < 3 ? 1 : wg ? LSTAT : TR ? 3 : 2;
  const bool copy = hg >= 3 && wg == 0;
  const int cut = wg ? TURN : 4;
  auto wait_full = [&](int c) {
    mbar_wait(bar + 8 * (B_XF + 8 * wg + c), layer);
    mbar_wait(bar + 8 * (B_WF + c), layer);
  };
  auto peek = [&](int c) {
    const bool x = mbar_test(bar + 8 * (B_XF + 8 * wg + c), layer), y = mbar_test(bar + 8 * (B_WF + c), layer);
    return x && y;
  };
  const uint64_t da0 = mkdesc(sb, TR ? 8192 : 16, 1024, 1), db0 = mkdesc(sb, 8192, 1024, 1);
  uint32_t xt = wg ? 0xfedcba98u : 0x21043210u;
  uint64_t wt = 0x0816131005161310ull;
  uint64_t da = da0 + ((xt & 15) << 9), db = db0 + (16 << 9);
  auto issue = [&](int c, int first) {
    wg_fence();
#pragma unroll
    for (int ks = 0; ks < 4; ks++) wgmma_ss<192, TR ? 1 : 0, 1>(acc, da + (TR ? ks * 128 : ks * 2), db + ks * 128, !first || ks != 0);
    wg_commit();
    xt >>= 4; wt >>= 8;
    da = da0 + ((xt & 15) << 9); db = db0 + (((uint32_t)wt & 31) << 9);
  };
  wait_full(0);
  bool ready = peek(1);
  issue(0, 1);
  TSW(0);
#pragma unroll 1
  for (int c = 1; c < cut; c++) {
    if (!ready) wait_full(c);
    issue(c, 0);
    ready = peek(c + 1);
    wg_wait<1>();
    if (leader) mbar_arrive(bar + 8 * (B_DN + 8 * wg + c - 1));
    if (wg == 1 && c == cut - 1) {
      wg_wait<0>();
      if (leader) mbar_arrive(bar + 8 * (B_DN + 8 + c));
    }
    if (c == statpos) {
      mbar_wait(bar + 8 * (copy ? B_SC : B_XF + 8 * wg + hg), layer);
      uint32_t A[16];
      const uint32_t xb = sb + (copy ? P_R : 8 * wg + hg) * PG;
#pragma unroll
      for (int ks = 0; ks < 4; ks++) {
        if (!TR) {
          const int row = 16 * w + (lane & 15), kc = 2 * ks + (lane >> 4);
          ldsm4(&A[4 * ks], xb + row * 128 + ((kc ^ (row & 7)) << 4));
        } else {
          const int k = 16 * ks + (lane & 7) + 8 * (lane >> 4), pc = 2 * w + ((lane >> 3) & 1);
          ldsm4t(&A[4 * ks], xb + k * 128 + ((pc ^ (k & 7)) << 4));
        }
      }
      float s0 = 0.f, q0 = 0.f, s1 = 0.f, q1 = 0.f;
#pragma unroll
      for (int i = 0; i < 16; i += 2) {
        const float a = bf_lo(A[i]), b = bf_hi(A[i]), c_ = bf_lo(A[i + 1]), d = bf_hi(A[i + 1]);
        s0 += a + b; q0 = fmaf(a, a, q0); q0 = fmaf(b, b, q0);
        s1 += c_ + d; q1 = fmaf(c_, c_, q1); q1 = fmaf(d, d, q1);
      }
#pragma unroll
      for (int o = 1; o <= 2; o <<= 1) {
        s0 += __shfl_xor_sync(~0u, s0, o); q0 += __shfl_xor_sync(~0u, q0, o);
        s1 += __shfl_xor_sync(~0u, s1, o); q1 += __shfl_xor_sync(~0u, q1, o);
      }
      if (t < 2)
        asm volatile("red.relaxed.gpu.global.add.v4.f32 [%0], {%1,%2,%3,%4};" ::"l"(g_rows + layer * LSEQ + blk * 64 + 16 * w + g + 8 * t),
                     "f"(t ? s1 : s0), "f"(t ? q1 : q0), "f"(1.f), "f"(0.f) : "memory");
    }
  }
  if (wg == 1) {
#pragma unroll 1
    for (int c = cut; c < 8; c++) wait_full(c);
    ready = true;
    bar_sync(5, 256);
  }
#pragma unroll 1
  for (int c = cut; c < 8; c++) {
    if (!ready) wait_full(c);
    issue(c, 0);
    if (wg == 1) {
      wg_wait<2>();
      if (leader && c >= cut + 2) mbar_arrive(bar + 8 * (B_DN + 8 + c - 2));
    } else if (c == 7) {
      bar_arrive(5, 256);
    } else {
      ready = peek(c + 1);
      wg_wait<1>();
      if (leader) mbar_arrive(bar + 8 * (B_DN + c - 1));
    }
  }
  mbar_wait(bar + 8 * (B_LN + wg), layer);
  const float4 ln = lds128f(sb + ln_off(wg) + (8 * w + g) * 16);
  mean0 = ln.x; rstd0 = ln.y; mean1 = ln.z; rstd1 = ln.w;
  wg_wait<0>();
  acc_fence<96>(acc);
  if (leader) mbar_arrive(bar + 8 * (B_DN + 8 * wg + 7));
}

__device__ __forceinline__ void attn_phase(const Params& p, uint32_t sb, int layer, int rb, int hg, int wg, int w) {
  const int lane = opaque_tid() & 31;
  const int g = lane >> 2, t = lane & 3;
  const uint32_t bar = sb + SM_BAR;
  const int blk = 16 * wg + rb;
  float acc[96];
  float2 cs[24];
  float mean0, mean1, rstd0, rstd1;
  if (layer) gemm_section<true>(acc, mean0, mean1, rstd0, rstd1, sb, blk, hg, wg, w, lane);
  else gemm_section<false>(acc, mean0, mean1, rstd0, rstd1, sb, blk, hg, wg, w, lane);
  TSW(1);
#pragma unroll
  for (int j = 8; j < 24; j++) cs[j] = lds64f(sb + SM_CS + 4 * (8 * j + 2 * t));
  const uint32_t kvx = sb + (wg ? 22 : 0) * PG;

  uint32_t kb[4][8], vb[4][8], qa[4][4];
  {
    const float nm0 = -mean0 * rstd0, nm1 = -mean1 * rstd1;
    const int st_row = 16 * w + (lane & 7) + 8 * ((lane >> 3) & 1);
    const uint32_t st_base = kvx + st_row * 256;
    const bool sender = (w == 3 && blk < 31);
    uint4* halo = &g_halo[(blk * 8 + hg) * 256 + lane];
    uint32_t r[4][2][4];
#pragma unroll
    for (int h = 0; h < 4; h++) {
#pragma unroll
      for (int kv = 0; kv < 2; kv++) {
#pragma unroll
        for (int dh = 0; dh < 2; dh++) {
          const int j = 8 + kv * 8 + 2 * h + dh;
          const float2 c2 = cs[j];
          const float v0 = fmaf(acc[4 * j + 0], rstd0, nm0 * c2.x), v1 = fmaf(acc[4 * j + 1], rstd0, nm0 * c2.y);
          const float v2 = fmaf(acc[4 * j + 2], rstd1, nm1 * c2.x), v3 = fmaf(acc[4 * j + 3], rstd1, nm1 * c2.y);
          r[h][kv][2 * dh] = packbf(v0, v1);
          r[h][kv][2 * dh + 1] = packbf(v2, v3);
        }
      }
      if (sender) {
        stg128(halo + (2 * h) * 32, make_uint4(r[h][0][0], r[h][0][2], r[h][0][1], r[h][0][3]));
        stg128(halo + (2 * h + 1) * 32, make_uint4(r[h][1][0], r[h][1][1], r[h][1][2], r[h][1][3]));
      }
    }
#pragma unroll
    for (int j = 0; j < 8; j++) cs[j] = lds64f(sb + SM_CS + 4 * (8 * j + 2 * t));
    mbar_wait(bar + 8 * (B_DN + 7), layer);
#pragma unroll
    for (int h = 0; h < 4; h++) {
#pragma unroll
      for (int kv = 0; kv < 2; kv++) {
        const int chunk = 4 * h + 2 * kv + (lane >> 4);
        if (w < 3) stsm4(st_base + (((chunk & 8) | ((chunk ^ st_row) & 7)) << 4), r[h][kv][0], r[h][kv][1], r[h][kv][2], r[h][kv][3]);
      }
      kb[h][4] = r[h][0][0]; kb[h][5] = r[h][0][2]; kb[h][6] = r[h][0][1]; kb[h][7] = r[h][0][3];
      vb[h][4] = movm_t(r[h][1][0]); vb[h][5] = movm_t(r[h][1][1]); vb[h][6] = movm_t(r[h][1][2]); vb[h][7] = movm_t(r[h][1][3]);
    }
#pragma unroll
    for (int h = 0; h < 4; h++) {
#pragma unroll
      for (int dh = 0; dh < 2; dh++) {
        const int j = 2 * h + dh;
        const float2 c2 = cs[j];
        qa[h][2 * dh] = packbf(fmaf(-mean0, c2.x, acc[4 * j + 0]), fmaf(-mean0, c2.y, acc[4 * j + 1]));
        qa[h][2 * dh + 1] = packbf(fmaf(-mean1, c2.x, acc[4 * j + 2]), fmaf(-mean1, c2.y, acc[4 * j + 3]));
      }
    }
  }
  bar_sync(2 + wg, 128);
  TSW(2);
  {
    const uint32_t prev_base = kvx + (16 * w - 16) * 256;
    const int mi = lane >> 3;
    const int r = 8 * (mi >> 1) + (lane & 7), r2 = 8 * (mi & 1) + (lane & 7);
    if (w != 0) {
#pragma unroll
      for (int h = 0; h < 4; h++) {
        const int ch = 4 * h + (mi & 1), ch2 = 4 * h + 2 + (mi >> 1);
        ldsm4(&kb[h][0], prev_base + r * 256 + (((ch & 8) | ((ch ^ r) & 7)) << 4));
        ldsm4t(&vb[h][0], prev_base + r2 * 256 + (((ch2 & 8) | ((ch2 ^ r2) & 7)) << 4));
      }
    } else if (blk > 0) {
      uint4* src = &g_halo[((blk - 1) * 8 + hg) * 256 + lane];
      uint4 hv[8];
      int it = 0;
      bool ok;
      do {
        ok = true;
#pragma unroll
        for (int i = 0; i < 8; i++) hv[i] = ld_tagged(src + i * 32);
#pragma unroll
        for (int i = 0; i < 8; i++) ok = ok && hv[i].x != UNSET;
      } while (!__all_sync(~0u, ok) && ++it < (1 << 20));
      if (layer == 0) {
#pragma unroll
        for (int i = 0; i < 2; i++) stg128(src + i * 128 + (lane >> 1) * 6, make_uint4(UNSET, UNSET, UNSET, UNSET));
      }
#pragma unroll
      for (int h = 0; h < 4; h++) {
        kb[h][0] = hv[2 * h].x; kb[h][1] = hv[2 * h].y; kb[h][2] = hv[2 * h].z; kb[h][3] = hv[2 * h].w;
        vb[h][0] = movm_t(hv[2 * h + 1].x); vb[h][1] = movm_t(hv[2 * h + 1].y);
        vb[h][2] = movm_t(hv[2 * h + 1].z); vb[h][3] = movm_t(hv[2 * h + 1].w);
      }
    } else {
#pragma unroll
      for (int h = 0; h < 4; h++)
#pragma unroll
        for (int k = 0; k < 4; k++) kb[h][k] = vb[h][k] = 0u;
    }
    TSW(3);
  }
  mbar_wait(bar + 8 * (B_DN + 15), layer);
  TSW(4);

  const bool first = (blk == 0 && w == 0);
  const int e = t - (g >> 1);
  const bool par = g & 1, epos = e >= 1;
  const uint32_t pmask = par ? 0xffff0000u : 0x0000ffffu;
  const uint32_t mB0 = epos ? pmask : 0u, mB1 = epos ? 0u : pmask;
  const float cl2 = 0.25f * 1.4426950408889634f;
  const float sc0 = rstd0 * cl2, sc1 = rstd1 * cl2;
  const float NEG = -INFINITY;
  float vA0[4], vB0[4], vA1[4], vB1[4];
#pragma unroll
  for (int h = 0; h < 4; h++) {
    float S[4][4];
#pragma unroll
    for (int j = 0; j < 4; j++) {
      S[j][0] = S[j][1] = S[j][2] = S[j][3] = 0.f;
      mma_bf16(S[j], qa[h], kb[h][2 * j], kb[h][2 * j + 1]);
    }
    vA0[h] = par ? S[1][1] : S[1][0];
    vB0[h] = epos ? (par ? S[0][1] : S[0][0]) : (par ? S[2][1] : S[2][0]);
    vA1[h] = par ? S[2][3] : S[2][2];
    vB1[h] = epos ? (par ? S[1][3] : S[1][2]) : (par ? S[3][3] : S[3][2]);
    if (first) { vA0[h] = NEG; if (epos) { vB0[h] = NEG; vB1[h] = NEG; } }
  }
  float m0[4], m1[4];
#pragma unroll
  for (int h = 0; h < 4; h++) { m0[h] = fmaxf(vA0[h], vB0[h]); m1[h] = fmaxf(vA1[h], vB1[h]); }
#pragma unroll
  for (int o = 1; o <= 2; o <<= 1) {
#pragma unroll
    for (int h = 0; h < 4; h++) {
      m0[h] = fmaxf(m0[h], __shfl_xor_sync(~0u, m0[h], o));
      m1[h] = fmaxf(m1[h], __shfl_xor_sync(~0u, m1[h], o));
    }
  }
  float O0[4][4], O1[4][4], Z[4][4];
#pragma unroll
  for (int h = 0; h < 4; h++) {
    const float mm0 = -m0[h] * sc0, mm1 = -m1[h] * sc1;
    const float pA0 = ex2(fmaf(vA0[h], sc0, mm0)), pB0 = ex2(fmaf(vB0[h], sc0, mm0));
    const float pA1 = ex2(fmaf(vA1[h], sc1, mm1)), pB1 = ex2(fmaf(vB1[h], sc1, mm1));
    const uint32_t hA0 = packbf(pA0, pA0), hB0 = packbf(pB0, pB0), hA1 = packbf(pA1, pA1), hB1 = packbf(pB1, pB1);
    const uint32_t P0[4] = {hB0 & mB0, 0u, hA0 & pmask, hB1 & mB0};
    const uint32_t P1[4] = {hB0 & mB1, hA1 & pmask, 0u, hB1 & mB1};
#pragma unroll
    for (int k = 0; k < 4; k++) O0[h][k] = O1[h][k] = Z[h][k] = 0.f;
    mma_bf16(O0[h], P0, vb[h][0], vb[h][1]); mma_bf16(O1[h], P0, vb[h][2], vb[h][3]); mma_bf16(Z[h], P0, 0x3f803f80u, 0x3f803f80u);
    mma_bf16(O0[h], P1, vb[h][4], vb[h][5]); mma_bf16(O1[h], P1, vb[h][6], vb[h][7]); mma_bf16(Z[h], P1, 0x3f803f80u, 0x3f803f80u);
  }
  if (lane == 0) mbar_arrive(bar + 8 * (B_OST + wg));
  uint4* op = (uint4*)g_O + ((layer * 32 + blk) * 8 + hg) * 512 + 64 * t + 16 * w + g;
#pragma unroll
  for (int h = 0; h < 4; h += 2) {
    const float i0 = rcp_approx(Z[h][0]), i1 = rcp_approx(Z[h][2]), j0 = rcp_approx(Z[h + 1][0]), j1 = rcp_approx(Z[h + 1][2]);
    stg128(op + 128 * h, make_uint4(packbf(O0[h][0] * i0, O0[h][1] * i0), packbf(O1[h][0] * i0, O1[h][1] * i0),
                                   packbf(O0[h + 1][0] * j0, O0[h + 1][1] * j0), packbf(O1[h + 1][0] * j0, O1[h + 1][1] * j0)));
    stg128(op + 128 * h + 8, make_uint4(packbf(O0[h][2] * i1, O0[h][3] * i1), packbf(O1[h][2] * i1, O1[h][3] * i1),
                                            packbf(O0[h + 1][2] * j1, O0[h + 1][3] * j1), packbf(O1[h + 1][2] * j1, O1[h + 1][3] * j1)));
  }
  TSW(5);
  __syncwarp();
  if (lane == 0) red_relaxed(&g_cnt[(C_O + layer * 32 + blk) * 32]);
  TSW(6);
}

__device__ __forceinline__ void proj_phase(const Params& p, uint32_t sb, int layer, int rb, int q, int& rtp) {
  const int lane = opaque_tid() & 31;
  const int wg = __shfl_sync(~0u, opaque_tid() >> 7, 0), w = __shfl_sync(~0u, (opaque_tid() >> 5) & 3, 0);
  const bool TR = layer != 0;
  const int t = lane & 3;
  const uint32_t bar = sb + SM_BAR;
  const uint32_t rbx = sb + (P_R + wg) * PG;
  const uint32_t rsrc = sb + (wg ? 2 : P_R) * PG;
  const int blk = 16 * wg + rb;
  mbar_wait(bar + 8 * (B_RF + wg), layer);
  if (layer) mbar_wait(bar + 8 * B_RS, 0);
  mbar_wait(bar + 8 * B_WOF, layer);
  fence_async_global();
  const uint32_t stg = sb + (wg ? SM_KGT : SM_STG);
  bool clean = false;
#pragma unroll 1
  for (int attempt = 0; attempt < MAX_RETRY; attempt++) {
  uint32_t res[16];
  if (!TR) {
#pragma unroll
    for (int j = 0; j < 8; j += 2) {
      const int mi = lane >> 3;
      const int row = 16 * w + (lane & 7) + 8 * (mi & 1), ch = j + (mi >> 1);
      ldsm4(&res[2 * j], rsrc + row * 128 + ((ch ^ (row & 7)) << 4));
    }
  } else {
#pragma unroll
    for (int j = 0; j < 8; j += 2) {
      const int mi = lane >> 3;
      const int line = 8 * (j + (mi >> 1)) + (lane & 7), pc = 2 * w + (mi & 1);
      ldsm4t(&res[2 * j], rsrc + line * 128 + ((pc ^ (line & 7)) << 4));
    }
  }
  float acc[32];
#pragma unroll
  for (int j = 0; j < 16; j++) { acc[2 * j] = bf_lo(res[j]); acc[2 * j + 1] = bf_hi(res[j]); }
  acc_fence<32>(acc);
  if (wg) mbar_wait(bar + 8 * B_PST, layer);
  const int wg2 = __shfl_sync(~0u, opaque_tid() >> 7, 0);
  const uint64_t da0 = mkdesc(sb, 1024, 128, 0), db0 = mkdesc(sb, 8192, 1024, 1);
#pragma unroll
  for (int c = 0; c < 4; c++) {
    mbar_wait(bar + 8 * (B_OF + 4 * wg + c), layer);
    if (c == 0) TSW(7);
    const uint64_t da = da0 + (uint32_t)(o_page(wg2, c) * 512);
    wg_fence();
#pragma unroll
    for (int ks = 0; ks < 8; ks++) wgmma_ss<64, 0, 1>(acc, da + ks * 128, db0 + wo_page(2 * c + (ks >> 2)) * 512 + (ks & 3) * 128, 1);
    wg_commit();
  }
  if (wg) mbar_wait(bar + 8 * B_KG, 0);
  wg_wait<0>();
  acc_fence<32>(acc);
  TSW(8);
  if (!clean) {
    const float chk = acc[0] + acc[2];
    clean = __all_sync(~0u, chk == chk);
    if (clean && lane == 0) mbar_arrive(bar + 8 * (B_PDONE + wg));
  }
  float s0 = 0.f, q0 = 0.f, s1 = 0.f, q1 = 0.f;
  uint32_t o[16];
#pragma unroll
  for (int j = 0; j < 8; j++) {
    const float a = acc[4 * j], b = acc[4 * j + 1], c = acc[4 * j + 2], d = acc[4 * j + 3];
    o[2 * j] = packbf(a, b);
    o[2 * j + 1] = packbf(c, d);
    s0 += a + b; q0 = fmaf(a, a, q0); q0 = fmaf(b, b, q0);
    s1 += c + d; q1 = fmaf(c, c, q1); q1 = fmaf(d, d, q1);
  }
#pragma unroll
  for (int j = 0; j < 8; j += 2) {
    const int mi = lane >> 3;
    const int line = 8 * (j + (mi >> 1)) + (lane & 7), pc = 2 * w + (mi & 1);
    stsm4t(rbx + line * 128 + ((pc ^ (line & 7)) << 4), o[2 * j], o[2 * j + 1], o[2 * j + 2], o[2 * j + 3]);
  }
#pragma unroll
  for (int o2 = 1; o2 <= 2; o2 <<= 1) {
    s0 += __shfl_xor_sync(~0u, s0, o2); q0 += __shfl_xor_sync(~0u, q0, o2);
    s1 += __shfl_xor_sync(~0u, s1, o2); q1 += __shfl_xor_sync(~0u, q1, o2);
  }
  {
    const int i = 2 * (lane >> 2) + (t & 1), k = (i * 11) >> 5;
    const float v = (t == 0) ? s0 : (t == 1) ? q0 : (t == 2) ? s1 : q1;
    sts32f(stg + k * 128 + (2 * w + (t >> 1)) * 16 + (i - 3 * k) * 4, v);
  }
  TSW(9);
  fence_async_smem();
  if (!bar_or(2 + wg, 128, !clean)) break;
  bool unset = false;
#pragma unroll
  for (int i = 0; i < 4; i++) unset |= lds32(sb + o_page(wg, i) * PG + (32 * w + lane) * 128) == UNSET;
  if (!bar_or(2 + wg, 128, unset)) break;
  if (w == 0 && elect_one()) {
    fence_async_smem();
    mbar_expect(bar + 8 * (B_RT + wg), 9 * PG);
    if (layer == 0) tma_ld(rsrc, &p.mapX, q * 64, blk * 64, bar + 8 * (B_RT + wg));
    else tma_ld(rsrc, &p.mapXT, blk * 64, DM + q * 64, bar + 8 * (B_RT + wg));
#pragma unroll 1
    for (int c = 0; c < 4; c++) bulk_ld(sb + o_page(wg, c) * PG, g_O + ((layer * 32 + blk) * 4 + c) * PG, 2 * PG, bar + 8 * (B_RT + wg));
  }
  mbar_wait(bar + 8 * (B_RT + wg), rtp);
  rtp ^= 1;
  RETRY(0);
  }
  if (!clean && lane == 0) mbar_arrive(bar + 8 * (B_PDONE + wg));
  if (w == 0 && elect_one()) {
    tma_st(&p.mapXT, blk * 64, (2 * layer) * DM + q * 64, rbx);
    bulk_red_add_f32(g_stats + (layer * 32 + blk) * 192, stg, 768);
    bulk_commit();
    red_relaxed(&g_cnt[(C_G + 2 * layer + wg) * 32]);
  }
  TSW(10);
}

__device__ __forceinline__ void conv_load(uint32_t* A, uint32_t pe) {
#pragma unroll
  for (int m = 0; m < 17; m++) {
    A[4 * m + 2] = lds32(pe + 4 * (64 * m - 8));
    A[4 * m + 0] = lds32(pe + 4 * (64 * m));
    A[4 * m + 1] = lds32(pe + 4 * (64 * m + 8));
    asm volatile("mov.b32 %0, %1;" : "=r"(A[4 * m + 3]) : "r"(A[4 * m + 0]));
  }
}
template <int M> __device__ __forceinline__ void conv_tri(float* acc, const uint32_t* A, uint64_t d) {
  if constexpr (M < 16) {
    wgmma_rs<64 - 8 * (M / 2), 0>(acc, A + 4 * M, d + (uint64_t)(64 + 4 * M), M != 0);
    conv_tri<M + 1>(acc, A, d);
  }
}
__device__ __forceinline__ void conv_mma0(float* acc, const uint32_t* A, uint64_t d) {
  wg_fence();
  conv_tri<0>(acc, A, d);
  wg_commit();
}
__device__ __forceinline__ void conv_mma1(float* acc, const uint32_t* A, uint64_t d, uint64_t ds, uint64_t df) {
  wg_fence();
#pragma unroll
  for (int m = 0; m < 17; m++) wgmma_rs<64, 0>(acc, A + 4 * m, d + (uint64_t)(4 * m), m != 0);
  wgmma_ss<64, 1, 0>(acc, ds, df, 1);
  wgmma_ss<64, 1, 0>(acc, ds + 128, df + 128, 1);
  wg_commit();
}
__device__ __forceinline__ void conv_store(float* acc, uint32_t pb, uint32_t over, int w) {
  acc_fence<32>(acc);
  const int l = opaque_tid() & 31, mt = l >> 3;
  int c = 2 * (63 - 8 * (mt >> 1) - (l & 7) + w) + (mt & 1);
  c ^= (c >> 3) & 1;
  const uint32_t a0 = pb + c * 16;
#pragma unroll
  for (int j = 0; j < 8; j += 2)
    stsm4t(j == 0 ? (c < 128 ? a0 : over + (c - 128) * 16) : a0 - 256 * j, packbf(acc[4 * j], acc[4 * j + 1]), packbf(acc[4 * j + 2], acc[4 * j + 3]),
           packbf(acc[4 * j + 4], acc[4 * j + 5]), packbf(acc[4 * j + 6], acc[4 * j + 7]));
}
__device__ __forceinline__ void conv_sums(uint32_t sb, int lc, int ht) {
  const int m = ht - 1;
  uint4 v[2][3];
#pragma unroll
  for (int c = 0; c < 2; c++)
#pragma unroll
    for (int k = 0; k < 3; k++) {
      const int mm = m - 1 + k;
      v[c][k] = lds128(sb + cv_u(lc + c) + (mm >= 0 ? (mm & 1) * CV_UH + (127 - (mm >> 1)) * 16 : 128 * 16));
    }
  const int ce = m + 2, co = m + 1;
#pragma unroll
  for (int c = 0; c < 2; c++) {
    const uint32_t x[8] = {v[c][0].z, v[c][0].w, v[c][1].x, v[c][1].y, v[c][1].z, v[c][1].w, v[c][2].x, v[c][2].y};
    float pv[16];
#pragma unroll
    for (int k = 0; k < 8; k++) { pv[2 * k] = bf_lo(x[k]); pv[2 * k + 1] = bf_hi(x[k]); }
    float t2[15], t4[13], s9[8], s7[8];
#pragma unroll
    for (int i = 0; i < 15; i++) t2[i] = pv[i] + pv[i + 1];
#pragma unroll
    for (int i = 0; i < 13; i++) t4[i] = t2[i] + t2[i + 2];
#pragma unroll
    for (int i = 0; i < 8; i++) {
      s9[i] = (t4[i] + t4[i + 4]) + pv[i + 8];
      s7[i] = (t4[i + 1] + t2[i + 5]) + pv[i + 7];
    }
    const uint4 e4 = make_uint4(packbf(s9[0], s9[1]), packbf(s9[2], s9[3]), packbf(s9[4], s9[5]), packbf(s9[6], s9[7]));
    if (ce < 128) sts128(sb + cv_se(lc + c) + ((ce ^ ((ce >> 3) & 7)) << 4), e4);
    else sts128(sb + cv_se(lc + c), make_uint4(0, 0, 0, 0));
    sts128(sb + cv_so(lc + c) + ((co ^ ((co >> 3) & 7)) << 4),
           make_uint4(packbf(s7[0], s7[1]), packbf(s7[2], s7[3]), packbf(s7[4], s7[5]), packbf(s7[6], s7[7])));
  }
}

template <int HALF, int NCH, int STEP = 1>
__device__ __forceinline__ void conv_epi(uint32_t sb, bf16* out, int lc, int c) {
  uint4 v[NCH][4], xr[NCH];
  const uint32_t sw = (c ^ ((c >> 3) & 1)) * 16;
#pragma unroll
  for (int u = 0; u < NCH; u++) {
#pragma unroll
    for (int k = 0; k < 4; k++) v[u][k] = lds128(sb + (HALF ? cv_pb1(lc + STEP * u, k) : cv_pb0(lc + STEP * u, k)) + sw);
    xr[u] = lds128(sb + cv_x(HALF, lc + STEP * u) + c * 16);
  }
#pragma unroll
  for (int u = 0; u < NCH; u++) {
    uint4 o;
    o.x = hadd2(xr[u].x, hadd2(hadd2(v[u][0].x, v[u][1].x), hadd2(v[u][2].x, v[u][3].x)));
    o.y = hadd2(xr[u].y, hadd2(hadd2(v[u][0].y, v[u][1].y), hadd2(v[u][2].y, v[u][3].y)));
    o.z = hadd2(xr[u].z, hadd2(hadd2(v[u][0].z, v[u][1].z), hadd2(v[u][2].z, v[u][3].z)));
    o.w = hadd2(xr[u].w, hadd2(hadd2(v[u][0].w, v[u][1].w), hadd2(v[u][2].w, v[u][3].w)));
    stg128(out + cv_chan(0, lc + STEP * u) * LSEQ + HALF * 1024 + c * 8, o);
  }
}

__device__ __forceinline__ bool prep_valid(const uint4 (&st)[6], const uint4 (&xr)[4]) {
  const uint32_t n = __float_as_uint(8.f);
  return st[0].w == n && st[1].w == n && st[2].w == n && st[3].w == n && st[4].w == n && (st[5].w | st[5].y | st[5].z) == n &&
         xr[0].x != UNSET && xr[1].x != UNSET && xr[2].x != UNSET && xr[3].x != UNSET;
}
template <int HALF>
__device__ __forceinline__ void conv_prep(uint32_t sb, int layer, int cta, int i) {
  uint4 st[6], xr[4];
  const uint4* sp = (const uint4*)g_stats + (layer * 32 + HALF * 16 + (i >> 3)) * 48 + (i & 7);
  const uint4* xp = (const uint4*)g_xT + (2 * layer * DM + 2 * cta) * (LSEQ / 8) + HALF * 128 + i;
  auto fetch = [&]() {
#pragma unroll
    for (int k = 0; k < 6; k++) st[k] = ld_tagged(sp + 8 * k);
#pragma unroll
    for (int k = 0; k < 4; k++) xr[k] = ld_tagged(xp + cv_chan(0, k) * (LSEQ / 8));
  };
  if (HALF) {
#pragma unroll
    for (int k = 0; k < 6; k++) st[k] = lds128(sb + CV_ST + (i >> 3) * 768 + k * 128 + (i & 7) * 16);
#pragma unroll
    for (int k = 0; k < 4; k++) xr[k] = lds128(sb + cv_x(1, k) + i * 16);
  } else {
    fetch();
  }
  int it = 0;
  while (!__all_sync(~0u, prep_valid(st, xr)) && ++it < MAX_RETRY) { fetch(); RETRY(1); }
  if (!HALF || it) {
#pragma unroll
    for (int k = 0; k < 4; k++) sts128(sb + cv_x(HALF, k) + i * 16, xr[k]);
  }
  const uint32_t v[16] = {st[0].x, st[0].y, st[0].z, st[1].x, st[1].y, st[1].z, st[2].x, st[2].y, st[2].z, st[3].x, st[3].y, st[3].z, st[4].x, st[4].y, st[4].z, st[5].x};
  uint32_t rs[4], nm[4];
#pragma unroll
  for (int k = 0; k < 4; k++) {
    const float m0 = __uint_as_float(v[4 * k]) * (-1.f / DM), m1 = __uint_as_float(v[4 * k + 2]) * (-1.f / DM);
    const float r0 = rsqrt_approx(fmaxf(fmaf(__uint_as_float(v[4 * k + 1]), 1.f / DM, -m0 * m0), 0.f) + 1e-5f);
    const float r1 = rsqrt_approx(fmaxf(fmaf(__uint_as_float(v[4 * k + 3]), 1.f / DM, -m1 * m1), 0.f) + 1e-5f);
    rs[k] = packbf(r0, r1);
    nm[k] = packbf(m0 * bf_lo(rs[k]), m1 * bf_hi(rs[k]));
  }
  const uint32_t ud = sb + (i & 1) * CV_UH + (127 - 64 * HALF - (i >> 1)) * 16;
#pragma unroll
  for (int k = 0; k < 4; k++)
    sts128(ud + cv_u(k), make_uint4(hfma2(xr[k].x, rs[0], nm[0]), hfma2(xr[k].y, rs[1], nm[1]), hfma2(xr[k].z, rs[2], nm[2]), hfma2(xr[k].w, rs[3], nm[3])));
  fence_async_smem();
}

#define AGATE 1
#define PP0 1
__device__ __forceinline__ void conv_phase(const Params& p, uint32_t sb, int layer, int cta) {
  const int tid = opaque_tid();
  const int wg = __shfl_sync(~0u, tid >> 7, 0), w = __shfl_sync(~0u, (tid >> 5) & 3, 0);
  const uint32_t bar = sb + SM_BAR;
  constexpr int CH2 = 4 * PG;
  bf16* xout = g_xT + ((2 * layer + 1) * DM + 2 * cta) * LSEQ;
  uint32_t A0[68], A1[68];
  float acc[32];
  const uint32_t pe = sb + cv_pe(wg) + 4 * (16 + 16 * w + ((tid & 31) >> 2) - 2 * (tid & 3));
  auto staged = [&]() {
    if (w == 0) {
      bulk_wait_read();
      __syncwarp();
      if (elect_one()) mbar_arrive(bar + 8 * (B_PST + wg));
    }
  };
  if (wg == 0) staged();
  mbar_wait(bar + 8 * (B_PDONE + 1), layer);
  mbar_wait(bar + 8 * B_PE, layer);
  conv_load(A0, pe);
  if (wg == 1) staged();
  conv_load(A1, pe + CH2);
  TSW(19);
  const uint64_t d0 = mkdesc(sb + cv_u(wg), CV_UH, 128, 0), d1 = d0 + (CH2 >> 4);
  mbar_wait(bar + 8 * B_U, layer);
  TSW(12);
  if (wg == 1) bar_sync(5, 256);
  conv_mma0(acc, A0, d0);
  if (wg == 0) bar_arrive(5, 256);
  mbar_wait(bar + 8 * (B_PDONE + 1), layer);
  {
    const int l = opaque_tid() & 31;
    if ((l & 15) < 2 * w) sts128(sb + cv_pb0(wg + 2 * (l >> 4), w) + (l & 15) * 16, make_uint4(0, 0, 0, 0));
  }
  wg_wait<0>();
  conv_store(acc, sb + cv_pb0(wg, w), sb + cv_pb1(wg, w), w);
  conv_mma0(acc, A1, d1);
  wg_wait<0>();
  conv_store(acc, sb + cv_pb0(2 + wg, w), sb + cv_pb1(2 + wg, w), w);
  TSW(13);
  bar_sync(2 + wg, 128);
  conv_epi<0, 2, 2>(sb, xout, wg, opaque_tid() & 127);
  TSW(14);
  mbar_arrive(bar + 8 * B_PUB);
  if (wg == 0) mbar_wait(bar + 8 * B_U1, layer);
  else bar_sync(6, 256);
  TSW(15);
  const uint64_t ds = mkdesc(sb + cv_se(wg), 8192, 1024, 1), df = mkdesc(sb + cv_fa(wg), 512, 128, 0);
  conv_mma1(acc, A0, d0, ds, df);
  if (wg == 0) bar_arrive(6, 256);
  wg_wait<0>();
  conv_store(acc, sb + cv_pb1(wg, w), sb + cv_dump(wg), w);
  TSW(16);
  bar_sync(2 + wg, 128);
  conv_epi<1, 1>(sb, xout, wg, opaque_tid() & 127);
  mbar_arrive(bar + 8 * (B_PUB + 1));
  conv_mma1(acc, A1, d1, ds + 512, df + (CH2 >> 4));
  wg_wait<0>();
  conv_store(acc, sb + cv_pb1(2 + wg, w), sb + cv_dump(2 + wg), w);
  TSW(17);
  bar_sync(2 + wg, 128);
  conv_epi<1, 1>(sb, xout, 2 + wg, opaque_tid() & 127);
  mbar_arrive(bar + 8 * (B_PUB + 2));
  TSW(18);
}

__device__ __forceinline__ void final_phase(const Params& p, uint32_t sb, int cta, int wg, int w, int rtp) {
  const int lane = opaque_tid() & 31;
  const uint32_t bar = sb + SM_BAR;
  mbar_wait(bar + 8 * (B_TF + wg), 0);
  if (threadIdx.x == 128) TS(8);
  const uint32_t src = sb + (16 + wg) * PG, dst = src + 2 * PG;
  const int mi = lane >> 3;
#pragma unroll 1
  for (int attempt = 0; attempt < MAX_RETRY; attempt++) {
    uint32_t m = 0;
#pragma unroll
    for (int j = 0; j < 8; j += 2) {
      uint32_t r[4];
      const int line = 8 * (j + (mi >> 1)) + (lane & 7), pc = 2 * w + (mi & 1);
      ldsm4t(r, src + line * 128 + ((pc ^ (line & 7)) << 4));
      const int row = 16 * w + (lane & 7) + 8 * (mi & 1), ch = j + (mi >> 1);
      stsm4(dst + row * 128 + ((ch ^ (row & 7)) << 4), r[0], r[1], r[2], r[3]);
#pragma unroll
      for (int k = 0; k < 4; k++) asm("max.u16x2 %0, %0, %1;" : "+r"(m) : "r"(r[k]));
    }
    fence_async_smem();
    if (!bar_or(2 + wg, 128, m >= 0xffff0000u || (m & 0xffffu) == 0xffffu)) break;
    if (w == 0 && elect_one()) {
      mbar_expect(bar + 8 * (B_RT + wg), PG);
      tma_ld(src, &p.mapXT, (16 * wg + (cta & 15)) * 64, 3 * DM + (cta >> 4) * 64, bar + 8 * (B_RT + wg));
    }
    mbar_wait(bar + 8 * (B_RT + wg), (rtp + attempt) & 1);
    RETRY(2);
  }
  if (w == 0 && elect_one()) {
    tma_st(&p.mapOut, (cta >> 4) * 64, (16 * wg + (cta & 15)) * 64, dst);
    bulk_commit();
    asm volatile("cp.async.bulk.wait_group.read 0;" ::: "memory");
    if (threadIdx.x == 128) TS(9);
    if (threadIdx.x == 128) LTS(1);
  }
}

struct cplx { float r, i; };
__device__ __forceinline__ cplx cmul(cplx a, cplx b) { return {fmaf(a.r, b.r, -a.i * b.i), fmaf(a.r, b.i, a.i * b.r)}; }
__device__ __forceinline__ cplx csqr(cplx a) { return {fmaf(a.r, a.r, -a.i * a.i), (a.r + a.r) * a.i}; }
__device__ __forceinline__ cplx cexp_l(float ar2, float ai, float l) {
  const float m = ex2(ar2 * l);
  const float x = ai * l;
  return {m * __cosf(x), m * __sinf(x)};
}

__device__ __forceinline__ void colsum_cta(const Params& p, uint32_t sb, int j, int tid) {
  const uint32_t bar = sb + SM_BAR;
  auto ld = [&](int i) {
    mbar_expect(bar + 8 * i, 3 * PG);
    tma_ld3(sb + (i & 7) * 3 * PG, &p.mapW3, (2 * j + (i & 1)) * 64, (i >> 1) * 64, 0, bar + 8 * i);
  };
  if (tid == 384) {
#pragma unroll
    for (int i = 0; i < 24; i++) mbar_init(bar + 8 * i, i < 16 ? 1 : 12);
    asm volatile("fence.mbarrier_init.release.cluster;" ::: "memory");
    fence_async_smem();
#pragma unroll 1
    for (int i = 0; i < 8; i++) ld(i);
  }
  const unsigned ep = ld_relaxed(&g_cnt[C_CS * 32]);
  bar_sync(0, NTHREADS);
  if (tid == 384) {
#pragma unroll 1
    for (int i = 8; i < 16; i++) { mbar_wait(bar + 8 * (8 + i), 0); fence_async_smem(); ld(i); }
  }
  if (tid < 384) {
    const int lane = tid & 31, cc = tid & 7, r0 = (tid >> 3) & 15, part = tid >> 7;
    const uint32_t id = ((lane >> 2) == 2 * (lane & 3) ? 0x3f80u : 0u) | ((lane >> 2) == 2 * (lane & 3) + 1 ? 0x3f800000u : 0u);
    const uint32_t src = sb + part * PG + r0 * 128 + ((cc ^ (r0 & 7)) << 4);
    float s[2][2][4];
#pragma unroll
    for (int i = 0; i < 16; i++) s[i >> 3][(i >> 2) & 1][i & 3] = 0.f;
#pragma unroll 1
    for (int i2 = 0; i2 < 16; i2 += 2) {
#pragma unroll
      for (int h = 0; h < 2; h++) {
        const int i = i2 + h;
        mbar_wait(bar + 8 * i, 0);
        uint4 v[4];
#pragma unroll
        for (int k = 0; k < 4; k++) v[k] = lds128(src + (i & 7) * 3 * PG + k * 2048);
#pragma unroll
        for (int k = 0; k < 4; k++) {
          const uint32_t a[4] = {v[k].x, v[k].y, v[k].z, v[k].w};
          mma_bf16(s[h][0], a, id, 0u);
          mma_bf16(s[h][1], a, 0u, id);
        }
        __syncwarp();
        if (i < 8 && lane == 0) mbar_arrive(bar + 8 * (16 + i));
      }
    }
    const uint32_t red = sb + 24 * PG;
#pragma unroll
    for (int h = 0; h < 2; h++)
#pragma unroll
      for (int k = 0; k < 2; k++) sts128f(red + (r0 * 384 + h * 192 + part * 64 + cc * 8 + k * 4) * 4, s[h][k][0], s[h][k][1], s[h][k][2], s[h][k][3]);
    bar_sync(1, 384);
    float tot = 0.f;
#pragma unroll
    for (int k = 0; k < 16; k++) tot += __uint_as_float(lds32(red + (k * 384 + tid) * 4));
    asm volatile("st.relaxed.gpu.global.v2.u32 [%0], {%1,%2};" ::"l"(&g_colsum[j * 384 + tid]), "r"(__float_as_uint(tot)), "r"(ep / NCTA + 1) : "memory");
    const uint4 u = make_uint4(UNSET, UNSET, UNSET, UNSET);
    if (tid < 256) {
#pragma unroll 4
      for (int i = 0; i < 8; i++) stg128((uint4*)g_xT + (DM + 256 + j * 64 + i * 8 + (tid >> 5)) * 256 + 128 + ((tid & 31) >> 1) * 8 + (tid & 1), u);
#pragma unroll 1
      for (int s = 0; s < 4; s++) {
        const int n = s ? 32 : 16;
        uint4* dst = (s == 1 ? (uint4*)g_O + 131072 : (uint4*)g_xT + (s + !s) * 131072) + j * n * 1024 + (tid >> 1) * 8 + (tid & 1);
#pragma unroll 4
        for (int i = 0; i < n; i++) stg128(dst + i * 1024, u);
        bar_sync(2, 256);
        if (tid == 32 * s) red_release(&g_cnt[(C_R + s) * 32]);
      }
    }
  }
}

#define KB 4
#define KW 2
struct ModeIn { uint32_t ar, ai, br, bi, cr, ci; bf16 logdt; };
__device__ __forceinline__ ModeIn load_modes(const Params& p, int d, int m) {
  const int i = d * 64 + m;
  return {((const uint32_t*)p.a_re)[i], ((const uint32_t*)p.a_im)[i], ((const uint32_t*)p.b_re)[i], ((const uint32_t*)p.b_im)[i],
          ((const uint32_t*)p.c_re)[i], ((const uint32_t*)p.c_im)[i], p.log_dt[d]};
}
__device__ __forceinline__ float4 lds128f_nv(uint32_t a) { float4 v; asm("ld.shared.v4.f32 {%0,%1,%2,%3}, [%4];" : "=f"(v.x), "=f"(v.y), "=f"(v.z), "=f"(v.w) : "r"(a)); return v; }
__device__ __forceinline__ void kernel_gen(const Params& p, uint32_t sb, int cta, int ht, ModeIn in, const ModeIn& in1) {
  const uint32_t bst = sb + SM_KGB + ((ht & 63) >> 2) * 144 + (ht & 3) * 4 + (ht >> 6) * 16;
  const uint64_t db = mkdesc(sb + SM_KGB, 144, 2304, 0);
  const float e0 = (float)(8 * (((ht & 32) >> 1) + ((ht & 31) >> 2)));
  float T[20];
#pragma unroll
  for (int i = 0; i < 20; i++) T[i] = 0.f;
  float k0 = 0.f;
#pragma unroll 1
  for (int pass = 0; pass < 4; pass++) {
    {
      const int sh = (pass & 1) ? 0 : 16;
      auto val = [&](uint32_t v) { return __uint_as_float((v << sh) & 0xffff0000u); };
      const float dt = __bfloat162float(__float2bfloat16_rn(expf(__bfloat162float(in.logdt))));
      const float ar2 = dt * val(in.ar) * 1.4426950408889634f, ai = dt * val(in.ai);
      const cplx c = cmul({val(in.cr), -val(in.ci)}, {dt * val(in.br), -dt * val(in.bi)});
      k0 += c.r;
      const cplx z1 = cexp_l(ar2, -ai, 1.f), z256 = cexp_l(ar2, -ai, 256.f), z64 = cexp_l(ar2, ai, 64.f);
      const cplx z2 = csqr(z1), z512 = csqr(z256);
      auto put = [&](int j, cplx v) { sts32(bst + (j >> 2) * 2304 + (j & 3) * 32, packbf(v.r, v.i)); };
      sts128f(sb + SM_KGT + ht * 16, ar2, ai, z64.r, z64.i);
      const cplx c1 = cmul(c, z1), c2 = cmul(c, z2), c3 = cmul(c1, z2), c4 = cmul(c2, z2);
      const cplx c5 = cmul(c3, z2), c6 = cmul(c4, z2), c7 = cmul(c5, z2), c8 = cmul(c6, z2);
      put(0, c1); put(1, c2); put(2, c3); put(3, c4); put(4, c5); put(5, c6); put(6, c7); put(7, c8);
      const cplx c260 = cmul(c4, z256), c264 = cmul(c8, z256), c520 = cmul(c8, z512), c776 = cmul(c264, z512);
      put(8, cmul(c2, z256)); put(9, c260); put(10, cmul(c6, z256)); put(11, c264);
      put(12, cmul(c4, z512)); put(13, c520); put(14, cmul(c260, z512)); put(15, c776);
      const cplx c1032 = cmul(c520, z512), c1288 = cmul(c776, z512);
      put(16, c1032); put(17, c1288); put(18, cmul(c1032, z512)); put(19, cmul(c1288, z512));
    }
    fence_async_smem();
    bar_sync(4, 128);
    const uint32_t tb = sb + SM_KGT + (ht & 67) * 16;
    float2 nx[KB];
#pragma unroll
    for (int s = 0; s < KB; s++) nx[s] = lds64f(tb + s * 64);
#pragma unroll
    for (int q = 0; q < 16 / KB; q++) {
      uint32_t A[2 * KB];
      float2 cur[KB], z[KB];
#pragma unroll
      for (int s = 0; s < KB; s++) { cur[s] = nx[s]; z[s] = lds64f(tb + (KB * q + s) * 64 + 8); }
      if (q < 16 / KB - 1) {
#pragma unroll
        for (int s = 0; s < KB; s++) nx[s] = lds64f(tb + (KB * q + KB + s) * 64);
      }
      if (q >= KW) wg_wait<KW - 1>();
#pragma unroll
      for (int s = 0; s < KB; s++) {
        const cplx lo = cexp_l(cur[s].x, cur[s].y, e0), hi = cmul(lo, {z[s].x, z[s].y});
        A[2 * s] = packbf(lo.r, lo.i);
        A[2 * s + 1] = packbf(hi.r, hi.i);
      }
      wg_fence();
#pragma unroll
      for (int k = 0; k < KB / 2; k++) wgmma_rs<40, 0>(T, A + 4 * k, db + 9 * KB * q + 18 * k, (pass & 1) | q | k);
      wg_commit();
    }
    wg_wait<0>();
    acc_fence<20>(T);
    if (ht == 0) TS(4 + pass);
    if (pass & 1) {
      const int h2 = opaque_tid() - 256, w = h2 >> 5, lane = h2 & 31, t = lane & 3, chn = h2 >> 6, m = h2 & 63, i0 = 16 * (w & 1) + (lane >> 2);
      const int lc = (pass & 2) + chn;
      const uint32_t kc = sb + kc_off(lc);
      auto put = [&](int idx, float v) {
        sts16(kc + idx * 2, __bfloat16_as_ushort(__float2bfloat16_rn(v)));
      };
#pragma unroll
      for (int hi = 0; hi < 2; hi++) {
        const int i = i0 + 8 * hi;
        float v[5];
#pragma unroll
        for (int j = 0; j < 5; j++) v[j] = chn ? T[4 * j + 2 * hi + 1] : T[4 * j + 2 * hi];
        put(8 * i + 1 + t, v[0]);
        put(8 * i + 5 + t, v[1]);
        put(257 + 4 * i + t, v[2]);
        put(385 + 2 * i + (t & 1) + 64 * (t >> 1), v[3]);
        put(513 + i + 32 * t, v[4]);
      }
#pragma unroll
      for (int o = 16; o > 0; o >>= 1) k0 += __shfl_xor_sync(~0u, k0, o);
      if (lane == 0) sts32f(sb + SM_RED + 4 * w, k0);
      bar_sync(4, 128);
      if (m == 0) put(0, k0 + __uint_as_float(lds32(sb + SM_RED + 4 * w + 4)) + __uint_as_float(lds16(sb + SM_RED + 24 + 2 * lc) << 16));
      k0 = 0.f;
      in = in1;
    }
  }
}

__device__ __forceinline__ void expand_taps(uint32_t sb, int ht) {
  const int ch = ht >> 5, lane = ht & 31;
  const uint32_t kc = sb + kc_off(ch);
  const uint32_t dst0 = sb + cv_pe(ch);
  auto put = [&](int G, uint32_t v0, uint32_t v1, uint32_t v2, uint32_t v3, uint32_t v4, uint32_t v5, uint32_t v6, uint32_t v7, uint32_t v8) {
    const uint32_t dst = dst0 + G * 32;
    sts128(dst, make_uint4(v1 | (v0 << 16), v2 | (v1 << 16), v3 | (v2 << 16), v4 | (v3 << 16)));
    sts128(dst + 16, make_uint4(v5 | (v4 << 16), v6 | (v5 << 16), v7 | (v6 << 16), v8 | (v7 << 16)));
  };
  {
    const uint4 q = lds128(kc + lane * 16);
    const uint32_t pv = lane ? lds16(kc + lane * 16 - 2) : 0u;
    const uint32_t dst = dst0 + (lane + 2) * 32;
    sts128(dst, make_uint4(__byte_perm(q.x, pv, 0x5410), __byte_perm(q.x, q.x, 0x1032), __byte_perm(q.y, q.x, 0x7610), __byte_perm(q.y, q.y, 0x1032)));
    sts128(dst + 16, make_uint4(__byte_perm(q.z, q.y, 0x7610), __byte_perm(q.z, q.z, 0x1032), __byte_perm(q.w, q.z, 0x7610), __byte_perm(q.w, q.w, 0x1032)));
    if (lane < 4) sts128(dst0 + lane * 16, make_uint4(0, 0, 0, 0));
  }
  uint32_t a[5], b[2][3];
  {
    const uint32_t s1 = kc + 2 * (256 + 4 * lane);
#pragma unroll
    for (int k = 0; k < 5; k++) a[k] = lds16(s1 + 2 * k);
#pragma unroll
    for (int u = 0; u < 2; u++) {
      const uint32_t s2 = kc + 2 * (384 + 2 * (lane + 32 * u));
#pragma unroll
      for (int k = 0; k < 3; k++) b[u][k] = lds16(s2 + 2 * k);
    }
  }
  const uint32_t k255 = lds16(kc + 2 * 255), k1024 = lds16(kc + 2 * 512);
  put(34 + lane, lane == 0 ? k255 : a[0], a[0], a[0], a[1], a[2], a[2], a[2], a[3], a[4]);
#pragma unroll
  for (int u = 0; u < 2; u++) put(66 + lane + 32 * u, b[u][0], b[u][0], b[u][0], b[u][0], b[u][1], b[u][1], b[u][1], b[u][2], b[u][2]);
  if (lane < 10) {
    const uint32_t v = lane == 0 ? k1024 : 0u;
    put(130 + lane, v, v, v, v, v, v, 0u, 0u, 0u);
  }
}
__device__ __forceinline__ void expand_far(uint32_t sb, int ht) {
  const int ch = ht >> 5, lane = ht & 31;
  const uint32_t kc = sb + kc_off(ch) + 2 * (513 + 2 * (63 - lane)), dst = sb + cv_fa(ch) + lane * 16;
#pragma unroll
  for (int ty = 0; ty < 2; ty++) {
    uint32_t v[16];
#pragma unroll
    for (int k = 0; k < 16; k++) v[k] = (k < 8 || 63 - lane - 4 * k >= 0) ? lds16(kc + 2 * (1 - ty) - 16 * k) : 0u;
#pragma unroll
    for (int u = 0; u < 2; u++)
      sts128(dst + ty * 2048 + u * 512, make_uint4(v[8 * u] | (v[8 * u + 1] << 16), v[8 * u + 2] | (v[8 * u + 3] << 16), v[8 * u + 4] | (v[8 * u + 5] << 16), v[8 * u + 6] | (v[8 * u + 7] << 16)));
    sts128(dst + ty * 2048 + 1024, make_uint4(0, 0, 0, 0));
  }
}

#define TMPF 1
#define CONST_SB 1
#define WPRE 1
__host__ __device__ constexpr int bar_count(int i) {
  return i == B_END ? 3 : i == B_LN ? 2 : i < B_OST ? 1 : i < B_PE ? 4 : i >= B_PUB ? 256 : 128;
}
__host__ __device__ constexpr bool bar_first(int i) { return i < B_WF + 2 && (i & 7) < 2; }

__global__ void __launch_bounds__(NTHREADS, 1) fused_kernel(const __grid_constant__ Params p) {
  extern __shared__ __align__(1024) uint8_t smem[];
  constexpr uint32_t sb = 1024;
  if (s32(smem) != sb) return;
  const int tid = threadIdx.x, lane = tid & 31;
  const int warp = __shfl_sync(~0u, tid >> 5, 0);
  if (tid == 32) {
    asm volatile("prefetch.tensormap [%0];" ::"l"(&p.mapX) : "memory");
    asm volatile("prefetch.tensormap [%0];" ::"l"(&p.mapW3) : "memory");
  }
  const int cta = blockIdx.x - (gridDim.x == NCTA + 4 ? 0 : 4);
  if ((unsigned)cta >= NCTA) {
    if (blockIdx.x < NCTA + 4) colsum_cta(p, sb, blockIdx.x & 3, tid);
    return;
  }
  const int rb = ((cta >> 4) & 3) * 4 + ((cta >> 2) & 3), hg = (cta >> 6) * 4 + (cta & 3);
  const uint32_t bar = sb + SM_BAR;
  auto ld_x0 = [&](int half, int c) {
    const uint32_t b = bar + 8 * (B_XF + 8 * half + c);
    mbar_expect(b, PG);
    tma_ld(sb + x_page(half, c) * PG, &p.mapX, c * 64, (16 * half + rb) * 64, b);
  };
  auto ld_x1 = [&](int half, int c, int b0) {
    const uint32_t b = bar + 8 * b0;
    mbar_expect(b, PG);
    tma_ld(sb + (8 * half + c) * PG, &p.mapXT, (16 * half + rb) * 64, DM + c * 64, b);
  };
  auto ld_w = [&](int c) {
    const uint32_t b = bar + 8 * (B_WF + c);
    mbar_expect(b, 3 * PG);
    tma_ld3(sb + w_page(c) * PG, &p.mapW3, hg * 64, c * 64, 0, b);
  };

  if (tid == 0) TS(0);
  if (tid == 480) LTS(0);
  if (warp == 0 && elect_one()) {
#pragma unroll
    for (int i = 0; i < B_WF + 2; i++)
      if (bar_first(i)) mbar_init(bar + 8 * i, 1);
    asm volatile("fence.mbarrier_init.release.cluster;" ::: "memory");
    fence_async_smem();
    ld_x0(0, 0);
    ld_w(0); ld_x0(1, 0);
    ld_x0(0, 1); ld_w(1); ld_x0(1, 1);
    TS(1);
  }
  __syncwarp();
  if (warp >= 1 && warp < 8 && elect_one()) {
    if (warp < 4) {
#pragma unroll
      for (int i = 2; i < 8; i++) mbar_init(bar + 8 * (8 * warp - 8 + i), 1);
    } else {
#pragma unroll
      for (int i = 0; i < 12; i++) mbar_init(bar + 8 * (12 * warp - 24 + i), 1);
    }
    asm volatile("fence.mbarrier_init.release.cluster;" ::: "memory");
  }
  if (warp == 15 && elect_one()) {
#pragma unroll
    for (int i = 72; i < B_COUNT; i++) mbar_init(bar + 8 * i, bar_count(i));
    asm volatile("fence.mbarrier_init.release.cluster;" ::: "memory");
  }

  if (warp < 8) {
    bar_sync(0, NTHREADS);
    asm volatile("setmaxnreg.inc.sync.aligned.u32 %0;" ::"n"(R_CONS));
    const int cw = __shfl_sync(~0u, opaque_tid() >> 5, 0);
    const int wg = cw >> 2, w = cw & 3;
    if (tid == 0) TS(2);
    int rtp = 0;
#pragma unroll 1
    for (int layer = 0; layer < 2; layer++) {
      attn_phase(p, sb, layer, rb, hg, wg, w);
      proj_phase(p, sb, layer, rb, hg, rtp);
      conv_phase(p, sb, layer, cta);
    }
    final_phase(p, sb, cta, wg, w, rtp);
  } else if (warp < 12) {
    asm volatile("setmaxnreg.dec.sync.aligned.u32 %0;" ::"n"(R_HELP));
    const int ht = tid - 256;
    {
      unsigned ep0 = 0;
      if (ht == 0) ep0 = ld_relaxed(&g_cnt[C_CS * 32]);
      const bf16 dsk = p.dskip[cv_chan(cta, ht & 3)];
      const ModeIn in0 = load_modes(p, cv_chan(cta, ht >> 6), ht & 63), in1 = load_modes(p, cv_chan(cta, 2 + (ht >> 6)), ht & 63);
      if (ht < 48) sts128f(sb + SM_STG + ht * 16, 0.f, 0.f, 0.f, 1.f);
      bar_sync(0, NTHREADS);
      if (ht == 0) {
        sts32(sb + SM_EP, ep0);
        mbar_arrive(bar + 8 * B_EP);
      }
      if (ht >= 124) sts16(sb + SM_RED + 24 + 2 * (ht & 3), __bfloat16_as_ushort(dsk));
      kernel_gen(p, sb, cta, ht, in0, in1);
      if (ht < 48) sts128f(sb + SM_KGT + ht * 16, 0.f, 0.f, 0.f, 1.f);
      fence_async_smem();
      bar_sync(4, 128);
      if (ht == 0) mbar_arrive(bar + 8 * B_KG);
    }
#pragma unroll 1
    for (int layer = 0; layer < 2; layer++) {
      mbar_wait(bar + 8 * B_PDONE, layer);
      expand_taps(sb, opaque_tid() - 256);
      mbar_arrive(bar + 8 * B_PE);
      TSW(0);
      expand_far(sb, opaque_tid() - 256);
      {
        const int i = opaque_tid() - 256;
        if (i < 32) sts128(sb + cv_u(i >> 3) + ((i >> 2) & 1) * CV_UH + (128 + (i & 3)) * 16, make_uint4(0, 0, 0, 0));
        mbar_wait(bar + 8 * B_RC, layer);
        mbar_wait(bar + 8 * B_GB, layer);
        TSW(13);
        conv_prep<0>(sb, layer, cta, i);
        mbar_arrive(bar + 8 * B_U);
      }
      mbar_wait(bar + 8 * (B_PDONE + 1), layer);
      bar_sync(4, 128);
#pragma unroll 1
      for (int lc = 0; lc < 4; lc += 2) {
        conv_sums(sb, lc, opaque_tid() - 256);
        TSW(1 + lc);
      }
      mbar_wait(bar + 8 * (B_GB + 1), layer);
      conv_prep<1>(sb, layer, cta, opaque_tid() - 256);
      mbar_arrive(bar + 8 * B_U1);
      TSW(4);
      if (layer == 0) {
        const int c = __shfl_sync(~0u, (opaque_tid() >> 5) & 3, 0);
        int phase = 0;
#pragma unroll 1
        for (int k = 0; k < 3; k++) {
          const int page = (k ? 4 + 4 * k : 0) + c, b = B_XR + 4 * (k & 1) + c;
          const uint32_t a = sb + page * PG + lane * 128 + (lane & 7) * 16 + (lane >> 3) * 4;
          int it = k == 2 ? phase : 0;
#pragma unroll 1
          for (; it < MAX_RETRY; it++) {
            mbar_wait(bar + 8 * b, it & 1);
            const uint32_t v0 = lds32(a), v1 = lds32(a + 4096);
            if (__all_sync(~0u, v0 != UNSET && v1 != UNSET)) break;
            if (elect_one()) { fence_async_smem(); ld_x1(page >> 3, page & 7, b); }
            __syncwarp();
            RETRY(3);
          }
          if (k == 0) phase = it + 1;
          if (lane == 0) mbar_arrive(bar + 8 * (B_XF + page));
        }
      }
    }
  } else {
    asm volatile("setmaxnreg.dec.sync.aligned.u32 %0;" ::"n"(R_AGENT));
    bar_sync(0, NTHREADS);
    auto done = [&](int half, int c, int layer) { mbar_wait(bar + 8 * (B_DN + 8 * half + c), layer); };
    auto publish = [&](int layer, int k) {
      mbar_wait(bar + 8 * (B_PUB + k), layer);
      red_relaxed(&g_cnt[(layer ? C_F + 4 * k + (cta >> 5) : C_C + k) * 32]);
      if (!layer && k == 0) red_release(&g_cnt[(C_C + 3) * 32]);
      TS(16 + layer * 56 + 40 + 7 + k);
    };
    if (warp == 12) {
      if (elect_one()) {
#pragma unroll 1
        for (int layer = 0; layer < 2; layer++) {
          auto ld_xe = [&](int c) {
            const uint32_t b = bar + 8 * (B_XF + c);
            mbar_expect(b, PG);
            if (layer == 0) tma_ld(sb + x_page(0, c) * PG, &p.mapX, c * 64, rb * 64, b);
            else tma_ld(sb + x_page(0, c) * PG, &p.mapXT, rb * 64, DM + c * 64, b);
          };
          if (layer == 0) {
            ld_x0(0, 2); ld_w(2); ld_x0(1, 2);
            if (hg >= 3) {
              mbar_expect(bar + 8 * B_SC, PG);
              tma_ld(sb + P_R * PG, &p.mapX, hg * 64, rb * 64, bar + 8 * B_SC);
            }
            if (rb < 4) tma_prefetch3(&p.mapW3, hg * 64, (4 + rb) * 64, 0);
            ld_x0(0, 3); ld_w(3); ld_x0(1, 3); ld_x0(0, 4); ld_x0(1, 4);
            done(0, 0, 0); done(1, 0, 0);
            ld_w(4);
            ld_x0(1, 5); ld_x0(1, 6); ld_x0(1, 7);
            done(0, 1, 0); done(1, 1, 0);
            ld_w(5);
            if (rb < 8) tma_prefetch5(&p.mapWo, hg * 64, rb * 2);
            done(0, 2, 0);
            fence_async_smem();
            ld_xe(5); ld_xe(6); ld_xe(7);
          } else {
            mbar_wait(bar + 8 * B_PDONE, 0);
            mbar_wait(bar + 8 * (B_PDONE + 1), 0);
            mbar_wait(bar + 8 * (WPRE == 1 ? B_U : B_GB + 1), 0);
            ld_w(0); ld_w(1);
            mbar_wait(bar + 8 * B_U1, 0);
            fence_async_smem();
            ld_w(2);
            mbar_wait(bar + 8 * (B_PUB + 2), 0);
            fence_async_smem();
            ld_w(3);
            spin_until(&g_cnt[(C_C + 3) * 32], ((lds32(sb + SM_EP) / NCTA) + 1) * NCTA);
            fence_async_global();
            if (hg >= 3) {
              mbar_expect(bar + 8 * B_SC, PG);
              tma_ld(sb + P_R * PG, &p.mapXT, rb * 64, DM + hg * 64, bar + 8 * B_SC);
            }
            ld_xe(4);
            done(0, 2, 1);
            fence_async_smem();
            ld_xe(5); ld_xe(6); ld_xe(7);
            done(1, 0, 1);
            ld_w(4);
            done(1, 1, 1);
            ld_w(5);
          }
          done(1, 2, layer);
          fence_async_smem();
          ld_w(6); ld_w(7);
          auto ld_res = [&](int half) {
            const uint32_t b = bar + 8 * (B_RF + half);
            mbar_expect(b, PG);
            if (layer == 0) tma_ld(sb + (half ? 2 : P_R) * PG, &p.mapX, hg * 64, (16 * half + rb) * 64, b);
            else tma_ld(sb + (half ? 2 : P_R) * PG, &p.mapXT, (16 * half + rb) * 64, DM + hg * 64, b);
          };
          done(0, 4, layer); done(1, 3, layer);
          fence_async_smem();
          mbar_expect(bar + 8 * B_WOF, 8 * PG);
#pragma unroll 1
          for (int c = 0; c < 8; c++) {
            if (c == 5) { ld_res(0); done(1, 4, layer); }
            tma_ld5(sb + wo_page(c) * PG, &p.mapWo, hg * 64, c * 2, bar + 8 * B_WOF);
          }
          done(0, 7, layer);
          fence_async_global();
          ld_res(1);
        }
      }
    } else if (warp == 13) {
      mbar_wait(bar + 8 * B_EP, 0);
      const unsigned e1 = (lds32(sb + SM_EP) / NCTA) + 1;
      auto ld_o = [&](int layer) {
#pragma unroll 1
        for (int half = 0; half < 2; half++) {
          done(1, 7, layer);
          mbar_wait(bar + 8 * B_OST, layer);
          if (half) mbar_wait(bar + 8 * (B_OST + 1), layer);
          fence_async_smem();
#pragma unroll
          for (int c = 0; c < 4; c++) mbar_expect(bar + 8 * (B_OF + 4 * half + c), 2 * PG);
          spin_until(&g_cnt[(C_O + layer * 32 + 16 * half + rb) * 32], e1 * 32);
#pragma unroll
          for (int c = 0; c < 4; c++)
            bulk_ld(sb + o_page(half, c) * PG, g_O + ((layer * 32 + 16 * half + rb) * 4 + c) * PG, 2 * PG, bar + 8 * (B_OF + 4 * half + c));
        }
      };
      if (elect_one()) {
        mbar_wait(bar + 8 * (B_WF + 2), 0);
        asm volatile("prefetch.tensormap [%0];" ::"l"(&p.mapXT) : "memory");
        asm volatile("prefetch.tensormap [%0];" ::"l"(&p.mapOut) : "memory");
        asm volatile("prefetch.tensormap [%0];" ::"l"(&p.mapWo) : "memory");
        spin_until(&g_cnt[C_Z * 32], e1 * NCTA);
        mbar_arrive(bar + 8 * B_ZF);
        TS(3);
        ld_o(0);
#pragma unroll 1
        for (int k = 0; k < 3; k++) {
          mbar_wait(bar + 8 * (B_PUB + k), 0);
          if (k == 2) {
#pragma unroll 1
            for (int c = 0; c < 4; c++) mbar_wait(bar + 8 * (B_XF + c), 1);
          }
          fence_async_smem();
          spin_until(&g_cnt[(C_C + k) * 32], e1 * NCTA);
          TS(10 + k);
#pragma unroll
          for (int c = 0; c < 4; c++) ld_x1(k != 0, (k & 2) * 2 + c, B_XR + 4 * (k & 1) + c);
        }
        ld_o(1);
        mbar_wait(bar + 8 * B_PUB, 1);
#pragma unroll 1
        for (int half = 0; half < 2; half++) {
          mbar_expect(bar + 8 * (B_TF + half), PG);
          spin_until(&g_cnt[(C_F + 4 * (half ? 1 + (cta >> 6) : 0) + ((cta >> 4) & 3)) * 32], e1 * 32);
          tma_ld(sb + (16 + half) * PG, &p.mapXT, (16 * half + (cta & 15)) * 64, 3 * DM + (cta >> 4) * 64, bar + 8 * (B_TF + half));
        }
      }
    } else if (warp == 14) {
      mbar_wait(bar + 8 * B_EP, 0);
      const unsigned e1 = (lds32(sb + SM_EP) / NCTA) + 1;
      done(0, 1, 0);
      {
        const uint2* cp = g_colsum + (hg * 192 + lane);
        uint2 v[6];
        bool ok;
        int it = 0;
        do {
          ok = true;
#pragma unroll
          for (int i = 0; i < 6; i++) {
            asm volatile("ld.relaxed.gpu.global.v2.u32 {%0,%1}, [%2];" : "=r"(v[i].x), "=r"(v[i].y) : "l"(cp + 32 * i) : "memory");
            ok = ok && v[i].y == e1;
          }
          if (++it > (1 << 22)) __trap();
        } while (!__all_sync(~0u, ok));
#pragma unroll
        for (int i = 0; i < 6; i++) sts32f(sb + SM_CS + 4 * (lane + 32 * i), __uint_as_float(v[i].x));
      }
      __syncwarp();
      if (elect_one()) {
        mbar_wait(bar + 8 * B_ZF, 0);
        mbar_arrive(bar + 8 * B_LN);
        red_relaxed(&g_cnt[C_CS * 32]);
        TS(13);
#pragma unroll 1
        for (int i = 0; i < 4; i++) {
          const int layer = i >> 1;
          mbar_wait(bar + 8 * (B_PST + (i & 1)), layer);
          const uint32_t b = bar + 8 * (B_GB + 1);
          const bf16* xin = g_xT + ((size_t)2 * layer * DM + 2 * cta) * LSEQ + 1024;
          if (i & 1) {
            fence_async_smem();
            mbar_expect(b, 12288 + PG);
          }
          spin_until(&g_cnt[(C_G + i) * 32], e1 * NCTA);
          if (i & 1) {
            bulk_ld(sb + CV_ST, g_stats + (layer * 32 + 16) * 192, 12288, b);
#pragma unroll
            for (int lc = 0; lc < 4; lc++) bulk_ld(sb + cv_x(1, lc), xin + cv_chan(0, lc) * LSEQ, 2048, b);
            TS(14 + layer);
            publish(layer, 1);
          } else {
            mbar_arrive(bar + 8 * B_GB);
          }
        }
      }
    } else {
      const uint4 u = make_uint4(UNSET, UNSET, UNSET, UNSET);
      if (lane < 24) stg128((uint4*)g_stats + cta * 24 + lane, make_uint4(0, 0, 0, 0));
      if (lane < 16) stg128(g_rows + LSEQ + cta * 16 + lane, make_uint4(0, 0, 0, 0));
#pragma unroll 4
      for (int i = 0; i < 16; i++) stg128(g_halo + cta * 512 + 32 * i + lane, u);
#pragma unroll 4
      for (int i = 0; i < 16; i++) stg128(((i & 8) ? (uint4*)g_xT : (uint4*)g_O) + cta * 1024 + (i & 7) * 128 + (lane >> 1) * 8 + (lane & 1), u);
      __syncwarp();
      if (elect_one()) red_release(&g_cnt[C_Z * 32]);
      __syncwarp();
#pragma unroll 1
      for (int layer = 0; layer < 2; layer++) {
        auto reset_done = [&](int s) {
          spin_until(&g_cnt[(C_R + s) * 32], (lds32(sb + SM_EP) / NCTA) * 4 + 4);
          mbar_arrive(bar + 8 * (s == 1 ? B_LN : s == 2 ? B_RS : B_RC));
          if (s) TS(16 + 40 + 9 + s);
        };
        if (layer && elect_one()) reset_done(1);
        __syncwarp();
#pragma unroll 1
        for (int half = 0; half < 2; half++) {
          done(half, 2, layer);
          const uint4* src = g_rows + (layer * LSEQ + (16 * half + rb) * 64 + (opaque_tid() & 31));
          uint4 a, b;
          int it = 0;
          do {
            a = ld_tagged(src); b = ld_tagged(src + 32);
          } while (!__all_sync(~0u, (a.z | a.w) == __float_as_uint(8.f) && (b.z | b.w) == __float_as_uint(8.f)) && ++it < (1 << 20));
          float m0 = __uint_as_float(a.x) * (1.f / DM), m1 = __uint_as_float(b.x) * (1.f / DM);
          float r0 = rsqrt_approx(fmaxf(__uint_as_float(a.y) * (1.f / DM) - m0 * m0, 0.f) + 1e-5f);
          float r1 = rsqrt_approx(fmaxf(__uint_as_float(b.y) * (1.f / DM) - m1 * m1, 0.f) + 1e-5f);
          if (half) done(0, 7, layer);
          const uint32_t dst = sb + ln_off(half) + ((lane >> 4) * 8 + (lane & 7)) * 16 + (lane & 8);
          asm volatile("st.shared.v2.f32 [%0], {%1,%2};" ::"r"(dst), "f"(m0), "f"(r0) : "memory");
          asm volatile("st.shared.v2.f32 [%0], {%1,%2};" ::"r"(dst + 256), "f"(m1), "f"(r1) : "memory");
          __syncwarp();
          if (elect_one()) { mbar_arrive(bar + 8 * (B_LN + half)); TS(16 + layer * 56 + 40 + 14 + half); }
        }
        if (layer && lane < 16) stg128(g_rows + cta * 16 + (opaque_tid() & 31), make_uint4(0, 0, 0, 0));
        if (elect_one()) {
          if (layer) reset_done(2);
          reset_done(3 * layer);
          publish(layer, 0);
          publish(layer, 2);
        }
        __syncwarp();
      }
    }
  }
}

typedef CUresult (*EncodeFn)(CUtensorMap*, CUtensorMapDataType, cuuint32_t, void*, const cuuint64_t*, const cuuint64_t*,
                             const cuuint32_t*, const cuuint32_t*, CUtensorMapInterleave, CUtensorMapSwizzle,
                             CUtensorMapL2promotion, CUtensorMapFloatOOBfill);

static void make_map(EncodeFn enc, CUtensorMap* m, void* ptr, uint64_t cols, uint64_t rows, uint32_t box_rows) {
  cuuint64_t dims[2] = {cols, rows};
  cuuint64_t strides[1] = {cols * 2};
  cuuint32_t box[2] = {64, box_rows};
  cuuint32_t es[2] = {1, 1};
  enc(m, CU_TENSOR_MAP_DATA_TYPE_BFLOAT16, 2, ptr, dims, strides, box, es, CU_TENSOR_MAP_INTERLEAVE_NONE,
      CU_TENSOR_MAP_SWIZZLE_128B, CU_TENSOR_MAP_L2_PROMOTION_L2_128B, CU_TENSOR_MAP_FLOAT_OOB_FILL_NONE);
}
static void make_map3(EncodeFn enc, CUtensorMap* m, void* ptr, uint64_t d0, uint64_t cols, uint64_t rows, uint64_t blk_stride,
                      uint64_t nblocks, uint32_t nblk) {
  cuuint64_t dims[3] = {d0, rows, nblocks};
  cuuint64_t strides[2] = {cols * 2, blk_stride * 2};
  cuuint32_t box[3] = {64, 64, nblk};
  cuuint32_t es[3] = {1, 1, 1};
  enc(m, CU_TENSOR_MAP_DATA_TYPE_BFLOAT16, 3, ptr, dims, strides, box, es, CU_TENSOR_MAP_INTERLEAVE_NONE,
      CU_TENSOR_MAP_SWIZZLE_128B, CU_TENSOR_MAP_L2_PROMOTION_L2_128B, CU_TENSOR_MAP_FLOAT_OOB_FILL_NONE);
}

extern "C" void kernel_launch(void* const* d_in, const int* in_sizes, int n_in, void* d_out, int out_size) {
  static Params prm;
  static void* cached[13] = {nullptr};
  static bool attr_done = false;
  static int grid = NCTA + 4;
  bool same = attr_done && cached[12] == d_out;
  for (int i = 0; i < 12 && same; i++) same = cached[i] == d_in[i];
  if (!same) {
    void* fn = nullptr;
    cudaDriverEntryPointQueryResult qr;
    cudaGetDriverEntryPoint("cuTensorMapEncodeTiled", &fn, cudaEnableDefault, &qr);
    EncodeFn enc = (EncodeFn)fn;
    void* pXT;
    cudaGetSymbolAddress(&pXT, g_xT);
    make_map(enc, &prm.mapX, d_in[0], DM, LSEQ, 64);
    make_map(enc, &prm.mapXT, pXT, LSEQ, 4 * DM, 64);
    make_map(enc, &prm.mapOut, d_out, DM, LSEQ, 64);
    {
      cuuint64_t dims[5] = {DM, 2, 4, 4, 16};
      cuuint64_t strides[4] = {DM * 2, 8 * DM * 2, 2 * DM * 2, 32 * DM * 2};
      cuuint32_t box[5] = {64, 2, 4, 4, 2};
      cuuint32_t es[5] = {1, 1, 1, 1, 1};
      enc(&prm.mapWo, CU_TENSOR_MAP_DATA_TYPE_BFLOAT16, 5, d_in[2], dims, strides, box, es, CU_TENSOR_MAP_INTERLEAVE_NONE,
          CU_TENSOR_MAP_SWIZZLE_128B, CU_TENSOR_MAP_L2_PROMOTION_L2_128B, CU_TENSOR_MAP_FLOAT_OOB_FILL_NONE);
    }
    make_map3(enc, &prm.mapW3, d_in[1], DM, 3 * DM, DM, DM, 3, 3);
    prm.wqkv = (const bf16*)d_in[1];
    prm.a_re = (const bf16*)d_in[4]; prm.a_im = (const bf16*)d_in[5];
    prm.b_re = (const bf16*)d_in[6]; prm.b_im = (const bf16*)d_in[7];
    prm.c_re = (const bf16*)d_in[8]; prm.c_im = (const bf16*)d_in[9];
    prm.log_dt = (const bf16*)d_in[10]; prm.dskip = (const bf16*)d_in[11];
    int dev = 0, sms = 0;
    cudaGetDevice(&dev);
    cudaDeviceGetAttribute(&sms, cudaDevAttrMultiProcessorCount, dev);
    grid = sms >= NCTA + 4 ? NCTA + 4 : NCTA + 5;
    cudaFuncSetAttribute(fused_kernel, cudaFuncAttributeMaxDynamicSharedMemorySize, SM_TOTAL);
    for (int i = 0; i < 12; i++) cached[i] = d_in[i];
    cached[12] = d_out;
    attr_done = true;
  }
  fused_kernel<<<grid, NTHREADS, SM_TOTAL>>>(prm);
}
```

```cpp
#include <cuda_runtime.h>
#include <cuda_bf16.h>
#include <cuda.h>
#include <stdint.h>

typedef __nv_bfloat16 bf16;

constexpr int LSEQ = 2048;
constexpr int DM = 512;
constexpr int NCTA = 128;
constexpr int NTHREADS = 512;
#define R_CONS 200
#define R_HELP 88
#define R_AGENT 24
#define TURN0 4
#define TURN1 4

constexpr int PG = 8192;
constexpr int P_R = 25;
__host__ __device__ constexpr int x_page(int half, int c) { return half ? 8 + c : c < 5 ? c : c - 5; }
__host__ __device__ constexpr int w_page(int c) { return (c & 3) < 3 ? 16 + 3 * (c & 3) : c < 4 ? 5 : 8; }
__host__ __device__ constexpr int wo_page(int c) { return c < 5 ? 3 + c : 11 + c; }
__host__ __device__ constexpr int o_page(int half, int pair) { return half ? (pair ? 17 + 2 * pair : 0) : 8 + 2 * pair; }
constexpr int SM_KGB = (P_R + 1) * PG;
constexpr int SM_KC = 27 * PG;
constexpr int KC_STRIDE = 648;
__host__ __device__ constexpr int kc_off(int lc) { return SM_KC + (lc & 1) * 2 * KC_STRIDE + (lc < 2 ? 3328 : 0); }
constexpr int SM_KGT = SM_KC + 3328 + 2592;
constexpr int SM_CS = SM_KGT + 2048;
constexpr int SM_RED = SM_CS + 768;
constexpr int SM_EP = SM_RED + 16;
constexpr int SM_STG = SM_RED + 32;
constexpr int SM_LN = SM_STG + 768;
__host__ __device__ constexpr int ln_off(int half) { return half ? PG + 4096 : SM_LN; }
constexpr int SM_BAR = SM_LN + 512;
constexpr int SM_TS = SM_BAR + 704;
constexpr int SM_TOTAL = SM_TS + 512;
static_assert(SM_TOTAL <= 232448 && SM_STG % 16 == 0 && SM_KGT % 16 == 0, "shared memory");

constexpr int CV_UH = 140 * 16;
__host__ __device__ constexpr int cv_u(int lc) { return (8 + 2 * lc) * PG; }
__host__ __device__ constexpr int cv_pe(int lc) { return cv_u(lc) + 4480; }
__host__ __device__ constexpr int cv_pb1(int lc, int w) { return w ? cv_u(lc) + 8960 + (w - 1) * 2048 : 7 * PG + lc * 2048; }
__host__ __device__ constexpr int cv_fa(int lc) { return cv_pb1(lc, 1) + 128; }
__host__ __device__ constexpr int cv_dump(int lc) { return cv_u(lc) + 16256; }
__host__ __device__ constexpr int cv_pb0(int lc, int w) { return lc * PG + w * 2048; }
__host__ __device__ constexpr int cv_se(int lc) { return 5 * PG + lc * 4096; }
__host__ __device__ constexpr int cv_so(int lc) { return cv_se(lc) + 2048; }
__host__ __device__ constexpr int cv_x(int half, int lc) { return (P_R + half) * PG + lc * 2048; }
constexpr int CV_ST = 22 * PG;
__host__ __device__ constexpr int cv_chan(int cta, int lc) { return 2 * cta + (lc & 1) + 256 * (lc >> 1); }

enum {
  B_XF = 0,
  B_WF = 16,
  B_OF = 24,
  B_DN = 32,
  B_XR = 48,
  B_RF = 56,
  B_PST = 58,
  B_GB = 60,
  B_TF = 62,
  B_RT = 64,
  B_RS = 66,
  B_RC = 67,
  B_WOF = 68,
  B_ZF = 69,
  B_EP = 70,
  B_KG = 71,
  B_SC = 72,
  B_LN = 73,
  B_END = 75,
  B_OST = 76,
  B_PDONE = 78,
  B_PE = 80,
  B_U = 81,
  B_U1 = 82,
  B_PUB = 83,
  B_COUNT = 86
};

enum {
  C_CS = 0,
  C_G = 1,
  C_C = 5,
  C_F = 9,
  C_O = 21,
  C_Z = 85,
  C_R = 86,
  C_COUNT = 90
};

__device__ unsigned g_cnt[C_COUNT * 32];
__device__ __align__(1024) bf16 g_O[2 * LSEQ * DM];
__device__ __align__(1024) bf16 g_xT[4 * DM * LSEQ];
__device__ __align__(1024) float g_stats[2 * 32 * 192];
__device__ __align__(1024) uint2 g_colsum[3 * DM];
__device__ __align__(1024) uint4 g_halo[32 * 8 * 256];
__device__ __align__(1024) uint4 g_rows[2 * LSEQ];
#define TS(i) do { } while (0)
#define TSW(k) do { if ((threadIdx.x & 127) == 0) TS(16 + layer * 56 + (threadIdx.x >> 7) * 20 + (k)); } while (0)
#define TSG(k) do { } while (0)

#define RETRY(i) do { } while (0)
#define LTS(i) do { } while (0)

struct Params {
  CUtensorMap mapX, mapW3, mapXT, mapOut, mapWo;
  const bf16 *wqkv, *a_re, *a_im, *b_re, *b_im, *c_re, *c_im, *log_dt, *dskip;
};

__device__ __forceinline__ uint32_t s32(const void* p) { return (uint32_t)__cvta_generic_to_shared(p); }
__device__ __forceinline__ void mbar_init(uint32_t b, int c) { asm volatile("mbarrier.init.shared::cta.b64 [%0], %1;" ::"r"(b), "r"(c) : "memory"); }
__device__ __forceinline__ void mbar_expect(uint32_t b, int bytes) { asm volatile("mbarrier.arrive.expect_tx.shared::cta.b64 _, [%0], %1;" ::"r"(b), "r"(bytes) : "memory"); }
__device__ __forceinline__ void mbar_arrive(uint32_t b) { asm volatile("mbarrier.arrive.shared::cta.b64 _, [%0];" ::"r"(b) : "memory"); }
__device__ __forceinline__ void mbar_wait(uint32_t b, int parity) {
  asm volatile("{\n.reg .pred p;\nWAIT_LOOP:\nmbarrier.try_wait.parity.shared::cta.b64 p, [%0], %1;\n@p bra WAIT_DONE;\nbra WAIT_LOOP;\nWAIT_DONE:\n}" ::"r"(b), "r"(parity) : "memory");
}
__device__ __forceinline__ bool mbar_test(uint32_t b, int parity) {
  uint32_t ok;
  asm volatile("{\n.reg .pred p;\nmbarrier.test_wait.parity.shared::cta.b64 p, [%1], %2;\nselp.u32 %0, 1, 0, p;\n}" : "=r"(ok) : "r"(b), "r"(parity) : "memory");
  return ok != 0;
}
__device__ __forceinline__ int opaque_tid() { int v; asm volatile("mov.u32 %0, %%tid.x;" : "=r"(v)); return v; }
__device__ __forceinline__ bool elect_one() {
  uint32_t r;
  asm volatile("{\n.reg .pred p;\nelect.sync _|p, 0xffffffff;\nselp.u32 %0, 1, 0, p;\n}" : "=r"(r));
  return r != 0;
}
__device__ __forceinline__ void tma_ld(uint32_t dst, const CUtensorMap* m, int c0, int c1, uint32_t bar) {
  asm volatile("cp.async.bulk.tensor.2d.shared::cluster.global.mbarrier::complete_tx::bytes [%0], [%1, {%3, %4}], [%2];"
               ::"r"(dst), "l"(m), "r"(bar), "r"(c0), "r"(c1) : "memory");
}
__device__ __forceinline__ void tma_ld3(uint32_t dst, const CUtensorMap* m, int c0, int c1, int c2, uint32_t bar) {
  asm volatile("cp.async.bulk.tensor.3d.shared::cluster.global.mbarrier::complete_tx::bytes [%0], [%1, {%3, %4, %5}], [%2];"
               ::"r"(dst), "l"(m), "r"(bar), "r"(c0), "r"(c1), "r"(c2) : "memory");
}
__device__ __forceinline__ void tma_ld5(uint32_t dst, const CUtensorMap* m, int c0, int c4, uint32_t bar) {
  asm volatile("cp.async.bulk.tensor.5d.shared::cluster.global.mbarrier::complete_tx::bytes [%0], [%1, {%3, 0, 0, 0, %4}], [%2];"
               ::"r"(dst), "l"(m), "r"(bar), "r"(c0), "r"(c4) : "memory");
}
__device__ __forceinline__ void tma_prefetch5(const CUtensorMap* m, int c0, int c4) {
  asm volatile("cp.async.bulk.prefetch.tensor.5d.L2.global.tile [%0, {%1, 0, 0, 0, %2}];" ::"l"(m), "r"(c0), "r"(c4) : "memory");
}
__device__ __forceinline__ void tma_prefetch2(const CUtensorMap* m, int c0, int c1) {
  asm volatile("cp.async.bulk.prefetch.tensor.2d.L2.global.tile [%0, {%1, %2}];" ::"l"(m), "r"(c0), "r"(c1) : "memory");
}
__device__ __forceinline__ void tma_prefetch3(const CUtensorMap* m, int c0, int c1, int c2) {
  asm volatile("cp.async.bulk.prefetch.tensor.3d.L2.global.tile [%0, {%1, %2, %3}];" ::"l"(m), "r"(c0), "r"(c1), "r"(c2) : "memory");
}
__device__ __forceinline__ void tma_st(const CUtensorMap* m, int c0, int c1, uint32_t src) {
  asm volatile("cp.async.bulk.tensor.2d.global.shared::cta.bulk_group [%0, {%2, %3}], [%1];" ::"l"(m), "r"(src), "r"(c0), "r"(c1) : "memory");
}
__device__ __forceinline__ void bulk_ld(uint32_t dst, const void* src, int bytes, uint32_t bar) {
  asm volatile("cp.async.bulk.shared::cluster.global.mbarrier::complete_tx::bytes [%0], [%1], %2, [%3];" ::"r"(dst), "l"(src), "r"(bytes), "r"(bar) : "memory");
}
__device__ __forceinline__ void bulk_st(void* dst, uint32_t src, int bytes) {
  asm volatile("cp.async.bulk.global.shared::cta.bulk_group [%0], [%1], %2;" ::"l"(dst), "r"(src), "r"(bytes) : "memory");
}
__device__ __forceinline__ void bulk_red_add_f32(void* dst, uint32_t src, int bytes) {
  asm volatile("cp.reduce.async.bulk.global.shared::cta.bulk_group.add.f32 [%0], [%1], %2;" ::"l"(dst), "r"(src), "r"(bytes) : "memory");
}
__device__ __forceinline__ void bulk_commit() { asm volatile("cp.async.bulk.commit_group;" ::: "memory"); }
__device__ __forceinline__ void bulk_wait_all() { asm volatile("cp.async.bulk.wait_group 0;" ::: "memory"); }
__device__ __forceinline__ void fence_async_smem() { asm volatile("fence.proxy.async.shared::cta;" ::: "memory"); }
__device__ __forceinline__ void fence_async_global() { asm volatile("fence.proxy.async.global;" ::: "memory"); }
__device__ __forceinline__ void bar_sync(int id, int n) { asm volatile("bar.sync %0, %1;" ::"r"(id), "r"(n) : "memory"); }
__device__ __forceinline__ void bar_arrive(int id, int n) { asm volatile("bar.arrive %0, %1;" ::"r"(id), "r"(n) : "memory"); }
__device__ __forceinline__ bool bar_or(int id, int n, bool v) {
  uint32_t r;
  asm volatile("{\n.reg .pred p, q;\nsetp.ne.u32 q, %3, 0;\nbar.red.or.pred p, %1, %2, q;\nselp.u32 %0, 1, 0, p;\n}" : "=r"(r) : "r"(id), "r"(n), "r"((uint32_t)v) : "memory");
  return r != 0;
}
__device__ __forceinline__ void bulk_wait_read() { asm volatile("cp.async.bulk.wait_group.read 0;" ::: "memory"); }
__device__ __forceinline__ void stg128(void* p, uint4 v) { asm volatile("st.relaxed.gpu.global.v4.u32 [%0], {%1,%2,%3,%4};" ::"l"(p), "r"(v.x), "r"(v.y), "r"(v.z), "r"(v.w) : "memory"); }
constexpr uint32_t UNSET = 0xffffffffu;
constexpr int MAX_RETRY = 1 << 16;
__device__ __forceinline__ void wg_fence() { asm volatile("wgmma.fence.sync.aligned;" ::: "memory"); }
__device__ __forceinline__ void wg_commit() { asm volatile("wgmma.commit_group.sync.aligned;" ::: "memory"); }
template <int N> __device__ __forceinline__ void wg_wait() { asm volatile("wgmma.wait_group.sync.aligned %0;" ::"n"(N) : "memory"); }
__device__ __forceinline__ uint64_t mkdesc(uint32_t addr, uint32_t lbo, uint32_t sbo, int sw) {
  return (uint64_t)((addr & 0x3FFFF) >> 4) | ((uint64_t)(lbo >> 4) << 16) | ((uint64_t)(sbo >> 4) << 32) | ((uint64_t)sw << 62);
}
__device__ __forceinline__ void ldsm4(uint32_t* r, uint32_t a) {
  asm volatile("ldmatrix.sync.aligned.m8n8.x4.shared.b16 {%0,%1,%2,%3}, [%4];" : "=r"(r[0]), "=r"(r[1]), "=r"(r[2]), "=r"(r[3]) : "r"(a) : "memory");
}
__device__ __forceinline__ void ldsm4t(uint32_t* r, uint32_t a) {
  asm volatile("ldmatrix.sync.aligned.m8n8.x4.trans.shared.b16 {%0,%1,%2,%3}, [%4];" : "=r"(r[0]), "=r"(r[1]), "=r"(r[2]), "=r"(r[3]) : "r"(a) : "memory");
}
__device__ __forceinline__ void stsm4(uint32_t a, uint32_t r0, uint32_t r1, uint32_t r2, uint32_t r3) {
  asm volatile("stmatrix.sync.aligned.m8n8.x4.shared.b16 [%0], {%1,%2,%3,%4};" ::"r"(a), "r"(r0), "r"(r1), "r"(r2), "r"(r3) : "memory");
}
__device__ __forceinline__ void stsm4t(uint32_t a, uint32_t r0, uint32_t r1, uint32_t r2, uint32_t r3) {
  asm volatile("stmatrix.sync.aligned.m8n8.x4.trans.shared.b16 [%0], {%1,%2,%3,%4};" ::"r"(a), "r"(r0), "r"(r1), "r"(r2), "r"(r3) : "memory");
}
__device__ __forceinline__ uint32_t movm_t(uint32_t a) { uint32_t r; asm volatile("movmatrix.sync.aligned.m8n8.trans.b16 %0, %1;" : "=r"(r) : "r"(a)); return r; }
__device__ __forceinline__ uint32_t lds32(uint32_t a) { uint32_t v; asm volatile("ld.shared.b32 %0, [%1];" : "=r"(v) : "r"(a) : "memory"); return v; }
__device__ __forceinline__ float2 lds64f(uint32_t a) { float2 v; asm volatile("ld.shared.v2.f32 {%0,%1}, [%2];" : "=f"(v.x), "=f"(v.y) : "r"(a) : "memory"); return v; }
__device__ __forceinline__ float4 lds128f(uint32_t a) { float4 v; asm volatile("ld.shared.v4.f32 {%0,%1,%2,%3}, [%4];" : "=f"(v.x), "=f"(v.y), "=f"(v.z), "=f"(v.w) : "r"(a) : "memory"); return v; }
__device__ __forceinline__ uint4 lds128(uint32_t a) { uint4 v; asm volatile("ld.shared.v4.b32 {%0,%1,%2,%3}, [%4];" : "=r"(v.x), "=r"(v.y), "=r"(v.z), "=r"(v.w) : "r"(a) : "memory"); return v; }
__device__ __forceinline__ void sts128(uint32_t a, uint4 v) { asm volatile("st.shared.v4.b32 [%0], {%1,%2,%3,%4};" ::"r"(a), "r"(v.x), "r"(v.y), "r"(v.z), "r"(v.w) : "memory"); }
__device__ __forceinline__ void sts128f(uint32_t a, float x, float y, float z, float w) { asm volatile("st.shared.v4.f32 [%0], {%1,%2,%3,%4};" ::"r"(a), "f"(x), "f"(y), "f"(z), "f"(w) : "memory"); }
__device__ __forceinline__ void sts32f(uint32_t a, float v) { asm volatile("st.shared.f32 [%0], %1;" ::"r"(a), "f"(v) : "memory"); }
__device__ __forceinline__ void sts16(uint32_t a, uint16_t v) { asm volatile("st.shared.u16 [%0], %1;" ::"r"(a), "h"(v) : "memory"); }
__device__ __forceinline__ uint32_t lds16(uint32_t a) { uint16_t v; asm volatile("ld.shared.u16 %0, [%1];" : "=h"(v) : "r"(a) : "memory"); return v; }
__device__ __forceinline__ uint32_t packbf(float lo, float hi) { uint32_t r; asm("cvt.rn.bf16x2.f32 %0, %1, %2;" : "=r"(r) : "f"(hi), "f"(lo)); return r; }
__device__ __forceinline__ float bf_lo(uint32_t v) { return __uint_as_float(v << 16); }
__device__ __forceinline__ float bf_hi(uint32_t v) { return __uint_as_float(v & 0xffff0000u); }
__device__ __forceinline__ float ex2(float x) { float r; asm("ex2.approx.ftz.f32 %0, %1;" : "=f"(r) : "f"(x)); return r; }
__device__ __forceinline__ float rsqrt_approx(float x) { float r; asm("rsqrt.approx.ftz.f32 %0, %1;" : "=f"(r) : "f"(x)); return r; }
__device__ __forceinline__ float rcp_approx(float x) { float r; asm("rcp.approx.ftz.f32 %0, %1;" : "=f"(r) : "f"(x)); return r; }
__device__ __forceinline__ void mma_bf16(float* d, const uint32_t* a, uint32_t b0, uint32_t b1) {
  asm("mma.sync.aligned.m16n8k16.row.col.f32.bf16.bf16.f32 {%0,%1,%2,%3}, {%4,%5,%6,%7}, {%8,%9}, {%0,%1,%2,%3};"
               : "+f"(d[0]), "+f"(d[1]), "+f"(d[2]), "+f"(d[3]) : "r"(a[0]), "r"(a[1]), "r"(a[2]), "r"(a[3]), "r"(b0), "r"(b1));
}
__device__ __forceinline__ void mma_tf32(float* d, float a0, float a1, float a2, float a3, float b0, float b1) {
  asm("mma.sync.aligned.m16n8k8.row.col.f32.tf32.tf32.f32 {%0,%1,%2,%3}, {%4,%5,%6,%7}, {%8,%9}, {%0,%1,%2,%3};"
               : "+f"(d[0]), "+f"(d[1]), "+f"(d[2]), "+f"(d[3])
               : "r"(__float_as_uint(a0)), "r"(__float_as_uint(a1)), "r"(__float_as_uint(a2)), "r"(__float_as_uint(a3)),
                 "r"(__float_as_uint(b0)), "r"(__float_as_uint(b1)));
}
__device__ __forceinline__ void red_release(unsigned* p) { asm volatile("red.release.gpu.global.add.u32 [%0], 1;" ::"l"(p) : "memory"); }
__device__ __forceinline__ void red_relaxed(unsigned* p) { asm volatile("red.relaxed.gpu.global.add.u32 [%0], 1;" ::"l"(p) : "memory"); }
__device__ __forceinline__ unsigned ld_relaxed(const unsigned* p) { unsigned v; asm volatile("ld.relaxed.gpu.global.u32 %0, [%1];" : "=r"(v) : "l"(p) : "memory"); return v; }
__device__ __forceinline__ void spin_until(const unsigned* p, unsigned target) {
  int it = 0;
  while ((int)(ld_relaxed(p) - target) < 0) {
    if (++it > (1 << 23)) __trap();
  }
}
__device__ __forceinline__ void spin_hint(const unsigned* p, unsigned target) {
  spin_until(p, target);
}
__device__ __forceinline__ uint4 ldcg128(const void* p) { uint4 v; asm volatile("ld.global.cg.v4.b32 {%0,%1,%2,%3}, [%4];" : "=r"(v.x), "=r"(v.y), "=r"(v.z), "=r"(v.w) : "l"(p) : "memory"); return v; }
__device__ __forceinline__ uint4 ld_tagged(const uint4* p) { uint4 v; asm volatile("ld.relaxed.gpu.global.v4.u32 {%0,%1,%2,%3}, [%4];" : "=r"(v.x), "=r"(v.y), "=r"(v.z), "=r"(v.w) : "l"(p) : "memory"); return v; }
__device__ __forceinline__ void st_tagged(uint4* p, uint32_t a, uint32_t b, uint32_t tag) { asm volatile("st.relaxed.gpu.global.v4.u32 [%0], {%1,%2,%3,%2};" ::"l"(p), "r"(a), "r"(tag), "r"(b) : "memory"); }
__device__ __forceinline__ void st_tagged3(uint4* p, uint32_t a, uint32_t b, uint32_t c, uint32_t tag) { asm volatile("st.relaxed.gpu.global.v4.u32 [%0], {%1,%2,%3,%4};" ::"l"(p), "r"(a), "r"(b), "r"(c), "r"(tag) : "memory"); }
__device__ __forceinline__ uint4 poll_tagged(const uint4* p, uint32_t tag) {
  uint4 v = ld_tagged(p);
  int it = 0;
  while (v.y != tag || v.w != tag) {
    if (++it > (1 << 22)) __trap();
    v = ld_tagged(p);
  }
  return v;
}
__device__ __forceinline__ uint32_t hadd2(uint32_t a, uint32_t b) { uint32_t r; asm("add.rn.bf16x2 %0, %1, %2;" : "=r"(r) : "r"(a), "r"(b)); return r; }
__device__ __forceinline__ uint32_t hmul2(uint32_t a, uint32_t b) { uint32_t r; asm("mul.rn.bf16x2 %0, %1, %2;" : "=r"(r) : "r"(a), "r"(b)); return r; }

__device__ __forceinline__ uint32_t hfma2(uint32_t a, uint32_t b, uint32_t c) { uint32_t r; asm("fma.rn.bf16x2 %0, %1, %2, %3;" : "=r"(r) : "r"(a), "r"(b), "r"(c)); return r; }
__device__ __forceinline__ void sts32(uint32_t a, uint32_t v) { asm volatile("st.shared.u32 [%0], %1;" ::"r"(a), "r"(v) : "memory"); }

template <int N> __device__ __forceinline__ void acc_fence(float* a) {
#pragma unroll
  for (int i = 0; i < N; i++) asm volatile("" : "+f"(a[i]) :: "memory");
}

template<int N,int TB> __device__ __forceinline__ void wgmma_rs(float* d, const uint32_t* a, uint64_t db, int sd);
template<int N,int TA,int TB> __device__ __forceinline__ void wgmma_ss(float* d, uint64_t da, uint64_t db, int sd);
template<> __device__ __forceinline__ void wgmma_rs<64,0>(float* d, const uint32_t* a, uint64_t db, int sd) {
  asm volatile("{\n.reg .pred p;\nsetp.ne.b32 p, %37, 0;\nwgmma.mma_async.sync.aligned.m64n64k16.f32.bf16.bf16 {%0,%1,%2,%3,%4,%5,%6,%7,%8,%9,%10,%11,%12,%13,%14,%15,%16,%17,%18,%19,%20,%21,%22,%23,%24,%25,%26,%27,%28,%29,%30,%31}, {%32,%33,%34,%35}, %36, p, 1, 1, 0;\n}\n"
   : "+f"(d[0]),"+f"(d[1]),"+f"(d[2]),"+f"(d[3]),"+f"(d[4]),"+f"(d[5]),"+f"(d[6]),"+f"(d[7]),"+f"(d[8]),"+f"(d[9]),"+f"(d[10]),"+f"(d[11]),"+f"(d[12]),"+f"(d[13]),"+f"(d[14]),"+f"(d[15]),"+f"(d[16]),"+f"(d[17]),"+f"(d[18]),"+f"(d[19]),"+f"(d[20]),"+f"(d[21]),"+f"(d[22]),"+f"(d[23]),"+f"(d[24]),"+f"(d[25]),"+f"(d[26]),"+f"(d[27]),"+f"(d[28]),"+f"(d[29]),"+f"(d[30]),"+f"(d[31])
   : "r"(a[0]), "r"(a[1]), "r"(a[2]), "r"(a[3]), "l"(db), "r"(sd));
}
template<> __device__ __forceinline__ void wgmma_rs<56,0>(float* d, const uint32_t* a, uint64_t db, int sd) {
  asm volatile("{\n.reg .pred p;\nsetp.ne.b32 p, %33, 0;\nwgmma.mma_async.sync.aligned.m64n56k16.f32.bf16.bf16 {%0,%1,%2,%3,%4,%5,%6,%7,%8,%9,%10,%11,%12,%13,%14,%15,%16,%17,%18,%19,%20,%21,%22,%23,%24,%25,%26,%27}, {%28,%29,%30,%31}, %32, p, 1, 1, 0;\n}\n"
   : "+f"(d[0]),"+f"(d[1]),"+f"(d[2]),"+f"(d[3]),"+f"(d[4]),"+f"(d[5]),"+f"(d[6]),"+f"(d[7]),"+f"(d[8]),"+f"(d[9]),"+f"(d[10]),"+f"(d[11]),"+f"(d[12]),"+f"(d[13]),"+f"(d[14]),"+f"(d[15]),"+f"(d[16]),"+f"(d[17]),"+f"(d[18]),"+f"(d[19]),"+f"(d[20]),"+f"(d[21]),"+f"(d[22]),"+f"(d[23]),"+f"(d[24]),"+f"(d[25]),"+f"(d[26]),"+f"(d[27])
   : "r"(a[0]), "r"(a[1]), "r"(a[2]), "r"(a[3]), "l"(db), "r"(sd));
}
template<> __device__ __forceinline__ void wgmma_rs<48,0>(float* d, const uint32_t* a, uint64_t db, int sd) {
  asm volatile("{\n.reg .pred p;\nsetp.ne.b32 p, %29, 0;\nwgmma.mma_async.sync.aligned.m64n48k16.f32.bf16.bf16 {%0,%1,%2,%3,%4,%5,%6,%7,%8,%9,%10,%11,%12,%13,%14,%15,%16,%17,%18,%19,%20,%21,%22,%23}, {%24,%25,%26,%27}, %28, p, 1, 1, 0;\n}\n"
   : "+f"(d[0]),"+f"(d[1]),"+f"(d[2]),"+f"(d[3]),"+f"(d[4]),"+f"(d[5]),"+f"(d[6]),"+f"(d[7]),"+f"(d[8]),"+f"(d[9]),"+f"(d[10]),"+f"(d[11]),"+f"(d[12]),"+f"(d[13]),"+f"(d[14]),"+f"(d[15]),"+f"(d[16]),"+f"(d[17]),"+f"(d[18]),"+f"(d[19]),"+f"(d[20]),"+f"(d[21]),"+f"(d[22]),"+f"(d[23])
   : "r"(a[0]), "r"(a[1]), "r"(a[2]), "r"(a[3]), "l"(db), "r"(sd));
}
template<> __device__ __forceinline__ void wgmma_rs<40,0>(float* d, const uint32_t* a, uint64_t db, int sd) {
  asm volatile("{\n.reg .pred p;\nsetp.ne.b32 p, %25, 0;\nwgmma.mma_async.sync.aligned.m64n40k16.f32.bf16.bf16 {%0,%1,%2,%3,%4,%5,%6,%7,%8,%9,%10,%11,%12,%13,%14,%15,%16,%17,%18,%19}, {%20,%21,%22,%23}, %24, p, 1, 1, 0;\n}\n"
   : "+f"(d[0]),"+f"(d[1]),"+f"(d[2]),"+f"(d[3]),"+f"(d[4]),"+f"(d[5]),"+f"(d[6]),"+f"(d[7]),"+f"(d[8]),"+f"(d[9]),"+f"(d[10]),"+f"(d[11]),"+f"(d[12]),"+f"(d[13]),"+f"(d[14]),"+f"(d[15]),"+f"(d[16]),"+f"(d[17]),"+f"(d[18]),"+f"(d[19])
   : "r"(a[0]), "r"(a[1]), "r"(a[2]), "r"(a[3]), "l"(db), "r"(sd));
}
template<> __device__ __forceinline__ void wgmma_rs<32,0>(float* d, const uint32_t* a, uint64_t db, int sd) {
  asm volatile("{\n.reg .pred p;\nsetp.ne.b32 p, %21, 0;\nwgmma.mma_async.sync.aligned.m64n32k16.f32.bf16.bf16 {%0,%1,%2,%3,%4,%5,%6,%7,%8,%9,%10,%11,%12,%13,%14,%15}, {%16,%17,%18,%19}, %20, p, 1, 1, 0;\n}\n"
   : "+f"(d[0]),"+f"(d[1]),"+f"(d[2]),"+f"(d[3]),"+f"(d[4]),"+f"(d[5]),"+f"(d[6]),"+f"(d[7]),"+f"(d[8]),"+f"(d[9]),"+f"(d[10]),"+f"(d[11]),"+f"(d[12]),"+f"(d[13]),"+f"(d[14]),"+f"(d[15])
   : "r"(a[0]), "r"(a[1]), "r"(a[2]), "r"(a[3]), "l"(db), "r"(sd));
}
template<> __device__ __forceinline__ void wgmma_rs<24,0>(float* d, const uint32_t* a, uint64_t db, int sd) {
  asm volatile("{\n.reg .pred p;\nsetp.ne.b32 p, %17, 0;\nwgmma.mma_async.sync.aligned.m64n24k16.f32.bf16.bf16 {%0,%1,%2,%3,%4,%5,%6,%7,%8,%9,%10,%11}, {%12,%13,%14,%15}, %16, p, 1, 1, 0;\n}\n"
   : "+f"(d[0]),"+f"(d[1]),"+f"(d[2]),"+f"(d[3]),"+f"(d[4]),"+f"(d[5]),"+f"(d[6]),"+f"(d[7]),"+f"(d[8]),"+f"(d[9]),"+f"(d[10]),"+f"(d[11])
   : "r"(a[0]), "r"(a[1]), "r"(a[2]), "r"(a[3]), "l"(db), "r"(sd));
}
template<> __device__ __forceinline__ void wgmma_rs<16,0>(float* d, const uint32_t* a, uint64_t db, int sd) {
  asm volatile("{\n.reg .pred p;\nsetp.ne.b32 p, %13, 0;\nwgmma.mma_async.sync.aligned.m64n16k16.f32.bf16.bf16 {%0,%1,%2,%3,%4,%5,%6,%7}, {%8,%9,%10,%11}, %12, p, 1, 1, 0;\n}\n"
   : "+f"(d[0]),"+f"(d[1]),"+f"(d[2]),"+f"(d[3]),"+f"(d[4]),"+f"(d[5]),"+f"(d[6]),"+f"(d[7])
   : "r"(a[0]), "r"(a[1]), "r"(a[2]), "r"(a[3]), "l"(db), "r"(sd));
}
template<> __device__ __forceinline__ void wgmma_rs<8,0>(float* d, const uint32_t* a, uint64_t db, int sd) {
  asm volatile("{\n.reg .pred p;\nsetp.ne.b32 p, %9, 0;\nwgmma.mma_async.sync.aligned.m64n8k16.f32.bf16.bf16 {%0,%1,%2,%3}, {%4,%5,%6,%7}, %8, p, 1, 1, 0;\n}\n"
   : "+f"(d[0]),"+f"(d[1]),"+f"(d[2]),"+f"(d[3])
   : "r"(a[0]), "r"(a[1]), "r"(a[2]), "r"(a[3]), "l"(db), "r"(sd));
}
template<> __device__ __forceinline__ void wgmma_ss<64,1,0>(float* d, uint64_t da, uint64_t db, int sd) {
  asm volatile("{\n.reg .pred p;\nsetp.ne.b32 p, %34, 0;\nwgmma.mma_async.sync.aligned.m64n64k16.f32.bf16.bf16 {%0,%1,%2,%3,%4,%5,%6,%7,%8,%9,%10,%11,%12,%13,%14,%15,%16,%17,%18,%19,%20,%21,%22,%23,%24,%25,%26,%27,%28,%29,%30,%31}, %32, %33, p, 1, 1, 1, 0;\n}\n"
   : "+f"(d[0]),"+f"(d[1]),"+f"(d[2]),"+f"(d[3]),"+f"(d[4]),"+f"(d[5]),"+f"(d[6]),"+f"(d[7]),"+f"(d[8]),"+f"(d[9]),"+f"(d[10]),"+f"(d[11]),"+f"(d[12]),"+f"(d[13]),"+f"(d[14]),"+f"(d[15]),"+f"(d[16]),"+f"(d[17]),"+f"(d[18]),"+f"(d[19]),"+f"(d[20]),"+f"(d[21]),"+f"(d[22]),"+f"(d[23]),"+f"(d[24]),"+f"(d[25]),"+f"(d[26]),"+f"(d[27]),"+f"(d[28]),"+f"(d[29]),"+f"(d[30]),"+f"(d[31])
   : "l"(da), "l"(db), "r"(sd));
}
template<> __device__ __forceinline__ void wgmma_ss<64,0,1>(float* d, uint64_t da, uint64_t db, int sd) {
  asm volatile("{\n.reg .pred p;\nsetp.ne.b32 p, %34, 0;\nwgmma.mma_async.sync.aligned.m64n64k16.f32.bf16.bf16 {%0,%1,%2,%3,%4,%5,%6,%7,%8,%9,%10,%11,%12,%13,%14,%15,%16,%17,%18,%19,%20,%21,%22,%23,%24,%25,%26,%27,%28,%29,%30,%31}, %32, %33, p, 1, 1, 0, 1;\n}\n"
   : "+f"(d[0]),"+f"(d[1]),"+f"(d[2]),"+f"(d[3]),"+f"(d[4]),"+f"(d[5]),"+f"(d[6]),"+f"(d[7]),"+f"(d[8]),"+f"(d[9]),"+f"(d[10]),"+f"(d[11]),"+f"(d[12]),"+f"(d[13]),"+f"(d[14]),"+f"(d[15]),"+f"(d[16]),"+f"(d[17]),"+f"(d[18]),"+f"(d[19]),"+f"(d[20]),"+f"(d[21]),"+f"(d[22]),"+f"(d[23]),"+f"(d[24]),"+f"(d[25]),"+f"(d[26]),"+f"(d[27]),"+f"(d[28]),"+f"(d[29]),"+f"(d[30]),"+f"(d[31])
   : "l"(da), "l"(db), "r"(sd));
}
template<> __device__ __forceinline__ void wgmma_ss<192,0,1>(float* d, uint64_t da, uint64_t db, int sd) {
  asm volatile("{\n.reg .pred p;\nsetp.ne.b32 p, %98, 0;\nwgmma.mma_async.sync.aligned.m64n192k16.f32.bf16.bf16 {%0,%1,%2,%3,%4,%5,%6,%7,%8,%9,%10,%11,%12,%13,%14,%15,%16,%17,%18,%19,%20,%21,%22,%23,%24,%25,%26,%27,%28,%29,%30,%31,%32,%33,%34,%35,%36,%37,%38,%39,%40,%41,%42,%43,%44,%45,%46,%47,%48,%49,%50,%51,%52,%53,%54,%55,%56,%57,%58,%59,%60,%61,%62,%63,%64,%65,%66,%67,%68,%69,%70,%71,%72,%73,%74,%75,%76,%77,%78,%79,%80,%81,%82,%83,%84,%85,%86,%87,%88,%89,%90,%91,%92,%93,%94,%95}, %96, %97, p, 1, 1, 0, 1;\n}\n"
   : "+f"(d[0]),"+f"(d[1]),"+f"(d[2]),"+f"(d[3]),"+f"(d[4]),"+f"(d[5]),"+f"(d[6]),"+f"(d[7]),"+f"(d[8]),"+f"(d[9]),"+f"(d[10]),"+f"(d[11]),"+f"(d[12]),"+f"(d[13]),"+f"(d[14]),"+f"(d[15]),"+f"(d[16]),"+f"(d[17]),"+f"(d[18]),"+f"(d[19]),"+f"(d[20]),"+f"(d[21]),"+f"(d[22]),"+f"(d[23]),"+f"(d[24]),"+f"(d[25]),"+f"(d[26]),"+f"(d[27]),"+f"(d[28]),"+f"(d[29]),"+f"(d[30]),"+f"(d[31]),"+f"(d[32]),"+f"(d[33]),"+f"(d[34]),"+f"(d[35]),"+f"(d[36]),"+f"(d[37]),"+f"(d[38]),"+f"(d[39]),"+f"(d[40]),"+f"(d[41]),"+f"(d[42]),"+f"(d[43]),"+f"(d[44]),"+f"(d[45]),"+f"(d[46]),"+f"(d[47]),"+f"(d[48]),"+f"(d[49]),"+f"(d[50]),"+f"(d[51]),"+f"(d[52]),"+f"(d[53]),"+f"(d[54]),"+f"(d[55]),"+f"(d[56]),"+f"(d[57]),"+f"(d[58]),"+f"(d[59]),"+f"(d[60]),"+f"(d[61]),"+f"(d[62]),"+f"(d[63]),"+f"(d[64]),"+f"(d[65]),"+f"(d[66]),"+f"(d[67]),"+f"(d[68]),"+f"(d[69]),"+f"(d[70]),"+f"(d[71]),"+f"(d[72]),"+f"(d[73]),"+f"(d[74]),"+f"(d[75]),"+f"(d[76]),"+f"(d[77]),"+f"(d[78]),"+f"(d[79]),"+f"(d[80]),"+f"(d[81]),"+f"(d[82]),"+f"(d[83]),"+f"(d[84]),"+f"(d[85]),"+f"(d[86]),"+f"(d[87]),"+f"(d[88]),"+f"(d[89]),"+f"(d[90]),"+f"(d[91]),"+f"(d[92]),"+f"(d[93]),"+f"(d[94]),"+f"(d[95])
   : "l"(da), "l"(db), "r"(sd));
}
template<> __device__ __forceinline__ void wgmma_ss<192,1,1>(float* d, uint64_t da, uint64_t db, int sd) {
  asm volatile("{\n.reg .pred p;\nsetp.ne.b32 p, %98, 0;\nwgmma.mma_async.sync.aligned.m64n192k16.f32.bf16.bf16 {%0,%1,%2,%3,%4,%5,%6,%7,%8,%9,%10,%11,%12,%13,%14,%15,%16,%17,%18,%19,%20,%21,%22,%23,%24,%25,%26,%27,%28,%29,%30,%31,%32,%33,%34,%35,%36,%37,%38,%39,%40,%41,%42,%43,%44,%45,%46,%47,%48,%49,%50,%51,%52,%53,%54,%55,%56,%57,%58,%59,%60,%61,%62,%63,%64,%65,%66,%67,%68,%69,%70,%71,%72,%73,%74,%75,%76,%77,%78,%79,%80,%81,%82,%83,%84,%85,%86,%87,%88,%89,%90,%91,%92,%93,%94,%95}, %96, %97, p, 1, 1, 1, 1;\n}\n"
   : "+f"(d[0]),"+f"(d[1]),"+f"(d[2]),"+f"(d[3]),"+f"(d[4]),"+f"(d[5]),"+f"(d[6]),"+f"(d[7]),"+f"(d[8]),"+f"(d[9]),"+f"(d[10]),"+f"(d[11]),"+f"(d[12]),"+f"(d[13]),"+f"(d[14]),"+f"(d[15]),"+f"(d[16]),"+f"(d[17]),"+f"(d[18]),"+f"(d[19]),"+f"(d[20]),"+f"(d[21]),"+f"(d[22]),"+f"(d[23]),"+f"(d[24]),"+f"(d[25]),"+f"(d[26]),"+f"(d[27]),"+f"(d[28]),"+f"(d[29]),"+f"(d[30]),"+f"(d[31]),"+f"(d[32]),"+f"(d[33]),"+f"(d[34]),"+f"(d[35]),"+f"(d[36]),"+f"(d[37]),"+f"(d[38]),"+f"(d[39]),"+f"(d[40]),"+f"(d[41]),"+f"(d[42]),"+f"(d[43]),"+f"(d[44]),"+f"(d[45]),"+f"(d[46]),"+f"(d[47]),"+f"(d[48]),"+f"(d[49]),"+f"(d[50]),"+f"(d[51]),"+f"(d[52]),"+f"(d[53]),"+f"(d[54]),"+f"(d[55]),"+f"(d[56]),"+f"(d[57]),"+f"(d[58]),"+f"(d[59]),"+f"(d[60]),"+f"(d[61]),"+f"(d[62]),"+f"(d[63]),"+f"(d[64]),"+f"(d[65]),"+f"(d[66]),"+f"(d[67]),"+f"(d[68]),"+f"(d[69]),"+f"(d[70]),"+f"(d[71]),"+f"(d[72]),"+f"(d[73]),"+f"(d[74]),"+f"(d[75]),"+f"(d[76]),"+f"(d[77]),"+f"(d[78]),"+f"(d[79]),"+f"(d[80]),"+f"(d[81]),"+f"(d[82]),"+f"(d[83]),"+f"(d[84]),"+f"(d[85]),"+f"(d[86]),"+f"(d[87]),"+f"(d[88]),"+f"(d[89]),"+f"(d[90]),"+f"(d[91]),"+f"(d[92]),"+f"(d[93]),"+f"(d[94]),"+f"(d[95])
   : "l"(da), "l"(db), "r"(sd));
}

template <bool TR>
__device__ __forceinline__ void gemm_section(float* acc, float& mean0, float& mean1, float& rstd0, float& rstd1,
                                             uint32_t sb, int blk, int hg, int wg, int w, int lane) {
  constexpr int layer = TR ? 1 : 0;
  constexpr int TURN = TR ? TURN1 : TURN0;
  constexpr int LSTAT = TURN < 4 ? TURN - 1 : 3;
  const uint32_t bar = sb + SM_BAR;
  const int g = lane >> 2, t = lane & 3;
  const bool leader = (w == 0) && (lane == 0);
  const int statpos = hg < 3 ? 1 : wg ? LSTAT : TR ? 3 : 2;
  const bool copy = hg >= 3 && wg == 0;
  const int cut = wg ? TURN : 4;
  auto wait_full = [&](int c) {
    mbar_wait(bar + 8 * (B_XF + 8 * wg + c), layer);
    mbar_wait(bar + 8 * (B_WF + c), layer);
  };
  auto peek = [&](int c) {
    const bool x = mbar_test(bar + 8 * (B_XF + 8 * wg + c), layer), y = mbar_test(bar + 8 * (B_WF + c), layer);
    return x && y;
  };
  const uint64_t da0 = mkdesc(sb, TR ? 8192 : 16, 1024, 1), db0 = mkdesc(sb, 8192, 1024, 1);
  uint32_t xt = wg ? 0xfedcba98u : 0x21043210u;
  uint64_t wt = 0x0816131005161310ull;
  uint64_t da = da0 + ((xt & 15) << 9), db = db0 + (16 << 9);
  auto issue = [&](int c, int first) {
    wg_fence();
#pragma unroll
    for (int ks = 0; ks < 4; ks++) wgmma_ss<192, TR ? 1 : 0, 1>(acc, da + (TR ? ks * 128 : ks * 2), db + ks * 128, !first || ks != 0);
    wg_commit();
    xt >>= 4; wt >>= 8;
    da = da0 + ((xt & 15) << 9); db = db0 + (((uint32_t)wt & 31) << 9);
  };
  wait_full(0);
  bool ready = peek(1);
  issue(0, 1);
  TSW(0);
#pragma unroll 1
  for (int c = 1; c < cut; c++) {
    if (!ready) wait_full(c);
    issue(c, 0);
    ready = peek(c + 1);
    wg_wait<1>();
    if (leader) mbar_arrive(bar + 8 * (B_DN + 8 * wg + c - 1));
    if (wg == 1 && c == cut - 1) {
      wg_wait<0>();
      if (leader) mbar_arrive(bar + 8 * (B_DN + 8 + c));
    }
    if (c == statpos) {
      mbar_wait(bar + 8 * (copy ? B_SC : B_XF + 8 * wg + hg), layer);
      uint32_t A[16];
      const uint32_t xb = sb + (copy ? P_R : 8 * wg + hg) * PG;
#pragma unroll
      for (int ks = 0; ks < 4; ks++) {
        if (!TR) {
          const int row = 16 * w + (lane & 15), kc = 2 * ks + (lane >> 4);
          ldsm4(&A[4 * ks], xb + row * 128 + ((kc ^ (row & 7)) << 4));
        } else {
          const int k = 16 * ks + (lane & 7) + 8 * (lane >> 4), pc = 2 * w + ((lane >> 3) & 1);
          ldsm4t(&A[4 * ks], xb + k * 128 + ((pc ^ (k & 7)) << 4));
        }
      }
      float s0 = 0.f, q0 = 0.f, s1 = 0.f, q1 = 0.f;
#pragma unroll
      for (int i = 0; i < 16; i += 2) {
        const float a = bf_lo(A[i]), b = bf_hi(A[i]), c_ = bf_lo(A[i + 1]), d = bf_hi(A[i + 1]);
        s0 += a + b; q0 = fmaf(a, a, q0); q0 = fmaf(b, b, q0);
        s1 += c_ + d; q1 = fmaf(c_, c_, q1); q1 = fmaf(d, d, q1);
      }
#pragma unroll
      for (int o = 1; o <= 2; o <<= 1) {
        s0 += __shfl_xor_sync(~0u, s0, o); q0 += __shfl_xor_sync(~0u, q0, o);
        s1 += __shfl_xor_sync(~0u, s1, o); q1 += __shfl_xor_sync(~0u, q1, o);
      }
      if (t < 2)
        asm volatile("red.relaxed.gpu.global.add.v4.f32 [%0], {%1,%2,%3,%4};" ::"l"(g_rows + layer * LSEQ + blk * 64 + 16 * w + g + 8 * t),
                     "f"(t ? s1 : s0), "f"(t ? q1 : q0), "f"(1.f), "f"(0.f) : "memory");
    }
  }
  if (wg == 1) {
#pragma unroll 1
    for (int c = cut; c < 8; c++) wait_full(c);
    ready = true;
    bar_sync(5, 256);
  }
#pragma unroll 1
  for (int c = cut; c < 8; c++) {
    if (!ready) wait_full(c);
    issue(c, 0);
    if (wg == 1) {
      wg_wait<2>();
      if (leader && c >= cut + 2) mbar_arrive(bar + 8 * (B_DN + 8 + c - 2));
    } else if (c == 7) {
      bar_arrive(5, 256);
    } else {
      ready = peek(c + 1);
      wg_wait<1>();
      if (leader) mbar_arrive(bar + 8 * (B_DN + c - 1));
    }
  }
  mbar_wait(bar + 8 * (B_LN + wg), layer);
  const float4 ln = lds128f(sb + ln_off(wg) + (8 * w + g) * 16);
  mean0 = ln.x; rstd0 = ln.y; mean1 = ln.z; rstd1 = ln.w;
  wg_wait<0>();
  acc_fence<96>(acc);
  if (leader) mbar_arrive(bar + 8 * (B_DN + 8 * wg + 7));
}

__device__ __forceinline__ void attn_phase(const Params& p, uint32_t sb, int layer, int rb, int hg, int wg, int w) {
  const int lane = opaque_tid() & 31;
  const int g = lane >> 2, t = lane & 3;
  const uint32_t bar = sb + SM_BAR;
  const int blk = 16 * wg + rb;
  float acc[96];
  float2 cs[24];
  float mean0, mean1, rstd0, rstd1;
  if (layer) gemm_section<true>(acc, mean0, mean1, rstd0, rstd1, sb, blk, hg, wg, w, lane);
  else gemm_section<false>(acc, mean0, mean1, rstd0, rstd1, sb, blk, hg, wg, w, lane);
  TSW(1);
#pragma unroll
  for (int j = 8; j < 24; j++) cs[j] = lds64f(sb + SM_CS + 4 * (8 * j + 2 * t));
  const uint32_t kvx = sb + (wg ? 22 : 0) * PG;

  uint32_t kb[4][8], vb[4][8], qa[4][4];
  {
    const float nm0 = -mean0 * rstd0, nm1 = -mean1 * rstd1;
    const int st_row = 16 * w + (lane & 7) + 8 * ((lane >> 3) & 1);
    const uint32_t st_base = kvx + st_row * 256;
    const bool sender = (w == 3 && blk < 31);
    uint4* halo = &g_halo[(blk * 8 + hg) * 256 + lane];
    uint32_t r[4][2][4];
#pragma unroll
    for (int h = 0; h < 4; h++) {
#pragma unroll
      for (int kv = 0; kv < 2; kv++) {
#pragma unroll
        for (int dh = 0; dh < 2; dh++) {
          const int j = 8 + kv * 8 + 2 * h + dh;
          const float2 c2 = cs[j];
          const float v0 = fmaf(acc[4 * j + 0], rstd0, nm0 * c2.x), v1 = fmaf(acc[4 * j + 1], rstd0, nm0 * c2.y);
          const float v2 = fmaf(acc[4 * j + 2], rstd1, nm1 * c2.x), v3 = fmaf(acc[4 * j + 3], rstd1, nm1 * c2.y);
          r[h][kv][2 * dh] = packbf(v0, v1);
          r[h][kv][2 * dh + 1] = packbf(v2, v3);
        }
      }
      if (sender) {
        stg128(halo + (2 * h) * 32, make_uint4(r[h][0][0], r[h][0][2], r[h][0][1], r[h][0][3]));
        stg128(halo + (2 * h + 1) * 32, make_uint4(r[h][1][0], r[h][1][1], r[h][1][2], r[h][1][3]));
      }
    }
#pragma unroll
    for (int j = 0; j < 8; j++) cs[j] = lds64f(sb + SM_CS + 4 * (8 * j + 2 * t));
    mbar_wait(bar + 8 * (B_DN + 7), layer);
#pragma unroll
    for (int h = 0; h < 4; h++) {
#pragma unroll
      for (int kv = 0; kv < 2; kv++) {
        const int chunk = 4 * h + 2 * kv + (lane >> 4);
        if (w < 3) stsm4(st_base + (((chunk & 8) | ((chunk ^ st_row) & 7)) << 4), r[h][kv][0], r[h][kv][1], r[h][kv][2], r[h][kv][3]);
      }
      kb[h][4] = r[h][0][0]; kb[h][5] = r[h][0][2]; kb[h][6] = r[h][0][1]; kb[h][7] = r[h][0][3];
      vb[h][4] = movm_t(r[h][1][0]); vb[h][5] = movm_t(r[h][1][1]); vb[h][6] = movm_t(r[h][1][2]); vb[h][7] = movm_t(r[h][1][3]);
    }
#pragma unroll
    for (int h = 0; h < 4; h++) {
#pragma unroll
      for (int dh = 0; dh < 2; dh++) {
        const int j = 2 * h + dh;
        const float2 c2 = cs[j];
        qa[h][2 * dh] = packbf(fmaf(-mean0, c2.x, acc[4 * j + 0]), fmaf(-mean0, c2.y, acc[4 * j + 1]));
        qa[h][2 * dh + 1] = packbf(fmaf(-mean1, c2.x, acc[4 * j + 2]), fmaf(-mean1, c2.y, acc[4 * j + 3]));
      }
    }
  }
  bar_sync(2 + wg, 128);
  TSW(2);
  {
    const uint32_t prev_base = kvx + (16 * w - 16) * 256;
    const int mi = lane >> 3;
    const int r = 8 * (mi >> 1) + (lane & 7), r2 = 8 * (mi & 1) + (lane & 7);
    if (w != 0) {
#pragma unroll
      for (int h = 0; h < 4; h++) {
        const int ch = 4 * h + (mi & 1), ch2 = 4 * h + 2 + (mi >> 1);
        ldsm4(&kb[h][0], prev_base + r * 256 + (((ch & 8) | ((ch ^ r) & 7)) << 4));
        ldsm4t(&vb[h][0], prev_base + r2 * 256 + (((ch2 & 8) | ((ch2 ^ r2) & 7)) << 4));
      }
    } else if (blk > 0) {
      uint4* src = &g_halo[((blk - 1) * 8 + hg) * 256 + lane];
      uint4 hv[8];
      int it = 0;
      bool ok;
      do {
        ok = true;
#pragma unroll
        for (int i = 0; i < 8; i++) hv[i] = ld_tagged(src + i * 32);
#pragma unroll
        for (int i = 0; i < 8; i++) ok = ok && hv[i].x != UNSET;
      } while (!__all_sync(~0u, ok) && ++it < (1 << 20));
      if (layer == 0) {
#pragma unroll
        for (int i = 0; i < 2; i++) stg128(src + i * 128 + (lane >> 1) * 6, make_uint4(UNSET, UNSET, UNSET, UNSET));
      }
#pragma unroll
      for (int h = 0; h < 4; h++) {
        kb[h][0] = hv[2 * h].x; kb[h][1] = hv[2 * h].y; kb[h][2] = hv[2 * h].z; kb[h][3] = hv[2 * h].w;
        vb[h][0] = movm_t(hv[2 * h + 1].x); vb[h][1] = movm_t(hv[2 * h + 1].y);
        vb[h][2] = movm_t(hv[2 * h + 1].z); vb[h][3] = movm_t(hv[2 * h + 1].w);
      }
    } else {
#pragma unroll
      for (int h = 0; h < 4; h++)
#pragma unroll
        for (int k = 0; k < 4; k++) kb[h][k] = vb[h][k] = 0u;
    }
    TSW(3);
  }
  mbar_wait(bar + 8 * (B_DN + 15), layer);
  TSW(4);

  const bool first = (blk == 0 && w == 0);
  const int e = t - (g >> 1);
  const bool par = g & 1, epos = e >= 1;
  const uint32_t pmask = par ? 0xffff0000u : 0x0000ffffu;
  const uint32_t mB0 = epos ? pmask : 0u, mB1 = epos ? 0u : pmask;
  const float cl2 = 0.25f * 1.4426950408889634f;
  const float sc0 = rstd0 * cl2, sc1 = rstd1 * cl2;
  const float NEG = -INFINITY;
  float vA0[4], vB0[4], vA1[4], vB1[4];
#pragma unroll
  for (int h = 0; h < 4; h++) {
    float S[4][4];
#pragma unroll
    for (int j = 0; j < 4; j++) {
      S[j][0] = S[j][1] = S[j][2] = S[j][3] = 0.f;
      mma_bf16(S[j], qa[h], kb[h][2 * j], kb[h][2 * j + 1]);
    }
    vA0[h] = par ? S[1][1] : S[1][0];
    vB0[h] = epos ? (par ? S[0][1] : S[0][0]) : (par ? S[2][1] : S[2][0]);
    vA1[h] = par ? S[2][3] : S[2][2];
    vB1[h] = epos ? (par ? S[1][3] : S[1][2]) : (par ? S[3][3] : S[3][2]);
    if (first) { vA0[h] = NEG; if (epos) { vB0[h] = NEG; vB1[h] = NEG; } }
  }
  float m0[4], m1[4];
#pragma unroll
  for (int h = 0; h < 4; h++) { m0[h] = fmaxf(vA0[h], vB0[h]); m1[h] = fmaxf(vA1[h], vB1[h]); }
#pragma unroll
  for (int o = 1; o <= 2; o <<= 1) {
#pragma unroll
    for (int h = 0; h < 4; h++) {
      m0[h] = fmaxf(m0[h], __shfl_xor_sync(~0u, m0[h], o));
      m1[h] = fmaxf(m1[h], __shfl_xor_sync(~0u, m1[h], o));
    }
  }
  float O0[4][4], O1[4][4], Z[4][4];
#pragma unroll
  for (int h = 0; h < 4; h++) {
    const float mm0 = -m0[h] * sc0, mm1 = -m1[h] * sc1;
    const float pA0 = ex2(fmaf(vA0[h], sc0, mm0)), pB0 = ex2(fmaf(vB0[h], sc0, mm0));
    const float pA1 = ex2(fmaf(vA1[h], sc1, mm1)), pB1 = ex2(fmaf(vB1[h], sc1, mm1));
    const uint32_t hA0 = packbf(pA0, pA0), hB0 = packbf(pB0, pB0), hA1 = packbf(pA1, pA1), hB1 = packbf(pB1, pB1);
    const uint32_t P0[4] = {hB0 & mB0, 0u, hA0 & pmask, hB1 & mB0};
    const uint32_t P1[4] = {hB0 & mB1, hA1 & pmask, 0u, hB1 & mB1};
#pragma unroll
    for (int k = 0; k < 4; k++) O0[h][k] = O1[h][k] = Z[h][k] = 0.f;
    mma_bf16(O0[h], P0, vb[h][0], vb[h][1]); mma_bf16(O1[h], P0, vb[h][2], vb[h][3]); mma_bf16(Z[h], P0, 0x3f803f80u, 0x3f803f80u);
    mma_bf16(O0[h], P1, vb[h][4], vb[h][5]); mma_bf16(O1[h], P1, vb[h][6], vb[h][7]); mma_bf16(Z[h], P1, 0x3f803f80u, 0x3f803f80u);
  }
  if (lane == 0) mbar_arrive(bar + 8 * (B_OST + wg));
  uint4* op = (uint4*)g_O + ((layer * 32 + blk) * 8 + hg) * 512 + 64 * t + 16 * w + g;
#pragma unroll
  for (int h = 0; h < 4; h += 2) {
    const float i0 = rcp_approx(Z[h][0]), i1 = rcp_approx(Z[h][2]), j0 = rcp_approx(Z[h + 1][0]), j1 = rcp_approx(Z[h + 1][2]);
    stg128(op + 128 * h, make_uint4(packbf(O0[h][0] * i0, O0[h][1] * i0), packbf(O1[h][0] * i0, O1[h][1] * i0),
                                   packbf(O0[h + 1][0] * j0, O0[h + 1][1] * j0), packbf(O1[h + 1][0] * j0, O1[h + 1][1] * j0)));
    stg128(op + 128 * h + 8, make_uint4(packbf(O0[h][2] * i1, O0[h][3] * i1), packbf(O1[h][2] * i1, O1[h][3] * i1),
                                            packbf(O0[h + 1][2] * j1, O0[h + 1][3] * j1), packbf(O1[h + 1][2] * j1, O1[h + 1][3] * j1)));
  }
  TSW(5);
  __syncwarp();
  if (lane == 0) red_relaxed(&g_cnt[(C_O + layer * 32 + blk) * 32]);
  TSW(6);
}

__device__ __forceinline__ void proj_phase(const Params& p, uint32_t sb, int layer, int rb, int q, int& rtp) {
  const int lane = opaque_tid() & 31;
  const int wg = __shfl_sync(~0u, opaque_tid() >> 7, 0), w = __shfl_sync(~0u, (opaque_tid() >> 5) & 3, 0);
  const bool TR = layer != 0;
  const int t = lane & 3;
  const uint32_t bar = sb + SM_BAR;
  const uint32_t rbx = sb + (P_R + wg) * PG;
  const uint32_t rsrc = sb + (wg ? 2 : P_R) * PG;
  const int blk = 16 * wg + rb;
  mbar_wait(bar + 8 * (B_RF + wg), layer);
  if (layer) mbar_wait(bar + 8 * B_RS, 0);
  mbar_wait(bar + 8 * B_WOF, layer);
  fence_async_global();
  const uint32_t stg = sb + (wg ? SM_KGT : SM_STG);
  bool clean = false;
#pragma unroll 1
  for (int attempt = 0; attempt < MAX_RETRY; attempt++) {
  uint32_t res[16];
  if (!TR) {
#pragma unroll
    for (int j = 0; j < 8; j += 2) {
      const int mi = lane >> 3;
      const int row = 16 * w + (lane & 7) + 8 * (mi & 1), ch = j + (mi >> 1);
      ldsm4(&res[2 * j], rsrc + row * 128 + ((ch ^ (row & 7)) << 4));
    }
  } else {
#pragma unroll
    for (int j = 0; j < 8; j += 2) {
      const int mi = lane >> 3;
      const int line = 8 * (j + (mi >> 1)) + (lane & 7), pc = 2 * w + (mi & 1);
      ldsm4t(&res[2 * j], rsrc + line * 128 + ((pc ^ (line & 7)) << 4));
    }
  }
  float acc[32];
#pragma unroll
  for (int j = 0; j < 16; j++) { acc[2 * j] = bf_lo(res[j]); acc[2 * j + 1] = bf_hi(res[j]); }
  acc_fence<32>(acc);
  if (wg) mbar_wait(bar + 8 * B_PST, layer);
  const int wg2 = __shfl_sync(~0u, opaque_tid() >> 7, 0);
  const uint64_t da0 = mkdesc(sb, 1024, 128, 0), db0 = mkdesc(sb, 8192, 1024, 1);
#pragma unroll
  for (int c = 0; c < 4; c++) {
    mbar_wait(bar + 8 * (B_OF + 4 * wg + c), layer);
    if (c == 0) TSW(7);
    const uint64_t da = da0 + (uint32_t)(o_page(wg2, c) * 512);
    wg_fence();
#pragma unroll
    for (int ks = 0; ks < 8; ks++) wgmma_ss<64, 0, 1>(acc, da + ks * 128, db0 + wo_page(2 * c + (ks >> 2)) * 512 + (ks & 3) * 128, 1);
    wg_commit();
  }
  if (wg) mbar_wait(bar + 8 * B_KG, 0);
  wg_wait<0>();
  acc_fence<32>(acc);
  TSW(8);
  if (!clean) {
    const float chk = acc[0] + acc[2];
    clean = __all_sync(~0u, chk == chk);
    if (clean && lane == 0) mbar_arrive(bar + 8 * (B_PDONE + wg));
  }
  float s0 = 0.f, q0 = 0.f, s1 = 0.f, q1 = 0.f;
  uint32_t o[16];
#pragma unroll
  for (int j = 0; j < 8; j++) {
    const float a = acc[4 * j], b = acc[4 * j + 1], c = acc[4 * j + 2], d = acc[4 * j + 3];
    o[2 * j] = packbf(a, b);
    o[2 * j + 1] = packbf(c, d);
    s0 += a + b; q0 = fmaf(a, a, q0); q0 = fmaf(b, b, q0);
    s1 += c + d; q1 = fmaf(c, c, q1); q1 = fmaf(d, d, q1);
  }
#pragma unroll
  for (int j = 0; j < 8; j += 2) {
    const int mi = lane >> 3;
    const int line = 8 * (j + (mi >> 1)) + (lane & 7), pc = 2 * w + (mi & 1);
    stsm4t(rbx + line * 128 + ((pc ^ (line & 7)) << 4), o[2 * j], o[2 * j + 1], o[2 * j + 2], o[2 * j + 3]);
  }
#pragma unroll
  for (int o2 = 1; o2 <= 2; o2 <<= 1) {
    s0 += __shfl_xor_sync(~0u, s0, o2); q0 += __shfl_xor_sync(~0u, q0, o2);
    s1 += __shfl_xor_sync(~0u, s1, o2); q1 += __shfl_xor_sync(~0u, q1, o2);
  }
  {
    const int i = 2 * (lane >> 2) + (t & 1), k = (i * 11) >> 5;
    const float v = (t == 0) ? s0 : (t == 1) ? q0 : (t == 2) ? s1 : q1;
    sts32f(stg + k * 128 + (2 * w + (t >> 1)) * 16 + (i - 3 * k) * 4, v);
  }
  TSW(9);
  fence_async_smem();
  if (!bar_or(2 + wg, 128, !clean)) break;
  bool unset = false;
#pragma unroll
  for (int i = 0; i < 4; i++) unset |= lds32(sb + o_page(wg, i) * PG + (32 * w + lane) * 128) == UNSET;
  if (!bar_or(2 + wg, 128, unset)) break;
  if (w == 0 && elect_one()) {
    fence_async_smem();
    mbar_expect(bar + 8 * (B_RT + wg), 9 * PG);
    if (layer == 0) tma_ld(rsrc, &p.mapX, q * 64, blk * 64, bar + 8 * (B_RT + wg));
    else tma_ld(rsrc, &p.mapXT, blk * 64, DM + q * 64, bar + 8 * (B_RT + wg));
#pragma unroll 1
    for (int c = 0; c < 4; c++) bulk_ld(sb + o_page(wg, c) * PG, g_O + ((layer * 32 + blk) * 4 + c) * PG, 2 * PG, bar + 8 * (B_RT + wg));
  }
  mbar_wait(bar + 8 * (B_RT + wg), rtp);
  rtp ^= 1;
  RETRY(0);
  }
  if (!clean && lane == 0) mbar_arrive(bar + 8 * (B_PDONE + wg));
  if (w == 0 && elect_one()) {
    tma_st(&p.mapXT, blk * 64, (2 * layer) * DM + q * 64, rbx);
    bulk_red_add_f32(g_stats + (layer * 32 + blk) * 192, stg, 768);
    bulk_commit();
    red_relaxed(&g_cnt[(C_G + 2 * layer + wg) * 32]);
  }
  TSW(10);
}

__device__ __forceinline__ void conv_load(uint32_t* A, uint32_t pe) {
#pragma unroll
  for (int m = 0; m < 17; m++) {
    A[4 * m + 2] = lds32(pe + 4 * (64 * m - 8));
    A[4 * m + 0] = lds32(pe + 4 * (64 * m));
    A[4 * m + 1] = lds32(pe + 4 * (64 * m + 8));
    asm volatile("mov.b32 %0, %1;" : "=r"(A[4 * m + 3]) : "r"(A[4 * m + 0]));
  }
}
template <int M> __device__ __forceinline__ void conv_tri(float* acc, const uint32_t* A, uint64_t d) {
  if constexpr (M < 16) {
    wgmma_rs<64 - 8 * (M / 2), 0>(acc, A + 4 * M, d + (uint64_t)(64 + 4 * M), M != 0);
    conv_tri<M + 1>(acc, A, d);
  }
}
__device__ __forceinline__ void conv_mma0(float* acc, const uint32_t* A, uint64_t d) {
  wg_fence();
  conv_tri<0>(acc, A, d);
  wg_commit();
}
__device__ __forceinline__ void conv_mma1(float* acc, const uint32_t* A, uint64_t d, uint64_t ds, uint64_t df) {
  wg_fence();
#pragma unroll
  for (int m = 0; m < 17; m++) wgmma_rs<64, 0>(acc, A + 4 * m, d + (uint64_t)(4 * m), m != 0);
  wgmma_ss<64, 1, 0>(acc, ds, df, 1);
  wgmma_ss<64, 1, 0>(acc, ds + 128, df + 128, 1);
  wg_commit();
}
__device__ __forceinline__ void conv_store(float* acc, uint32_t pb, uint32_t over, int w) {
  acc_fence<32>(acc);
  const int l = opaque_tid() & 31, mt = l >> 3;
  int c = 2 * (63 - 8 * (mt >> 1) - (l & 7) + w) + (mt & 1);
  c ^= (c >> 3) & 1;
  const uint32_t a0 = pb + c * 16;
#pragma unroll
  for (int j = 0; j < 8; j += 2)
    stsm4t(j == 0 ? (c < 128 ? a0 : over + (c - 128) * 16) : a0 - 256 * j, packbf(acc[4 * j], acc[4 * j + 1]), packbf(acc[4 * j + 2], acc[4 * j + 3]),
           packbf(acc[4 * j + 4], acc[4 * j + 5]), packbf(acc[4 * j + 6], acc[4 * j + 7]));
}
__device__ __forceinline__ void conv_sums(uint32_t sb, int lc, int ht) {
  const int m = ht - 1;
  uint4 v[2][3];
#pragma unroll
  for (int c = 0; c < 2; c++)
#pragma unroll
    for (int k = 0; k < 3; k++) {
      const int mm = m - 1 + k;
      v[c][k] = lds128(sb + cv_u(lc + c) + (mm >= 0 ? (mm & 1) * CV_UH + (127 - (mm >> 1)) * 16 : 128 * 16));
    }
  const int ce = m + 2, co = m + 1;
#pragma unroll
  for (int c = 0; c < 2; c++) {
    const uint32_t x[8] = {v[c][0].z, v[c][0].w, v[c][1].x, v[c][1].y, v[c][1].z, v[c][1].w, v[c][2].x, v[c][2].y};
    float pv[16];
#pragma unroll
    for (int k = 0; k < 8; k++) { pv[2 * k] = bf_lo(x[k]); pv[2 * k + 1] = bf_hi(x[k]); }
    float t2[15], t4[13], s9[8], s7[8];
#pragma unroll
    for (int i = 0; i < 15; i++) t2[i] = pv[i] + pv[i + 1];
#pragma unroll
    for (int i = 0; i < 13; i++) t4[i] = t2[i] + t2[i + 2];
#pragma unroll
    for (int i = 0; i < 8; i++) {
      s9[i] = (t4[i] + t4[i + 4]) + pv[i + 8];
      s7[i] = (t4[i + 1] + t2[i + 5]) + pv[i + 7];
    }
    const uint4 e4 = make_uint4(packbf(s9[0], s9[1]), packbf(s9[2], s9[3]), packbf(s9[4], s9[5]), packbf(s9[6], s9[7]));
    if (ce < 128) sts128(sb + cv_se(lc + c) + ((ce ^ ((ce >> 3) & 7)) << 4), e4);
    else sts128(sb + cv_se(lc + c), make_uint4(0, 0, 0, 0));
    sts128(sb + cv_so(lc + c) + ((co ^ ((co >> 3) & 7)) << 4),
           make_uint4(packbf(s7[0], s7[1]), packbf(s7[2], s7[3]), packbf(s7[4], s7[5]), packbf(s7[6], s7[7])));
  }
}

template <int HALF, int NCH, int STEP = 1>
__device__ __forceinline__ void conv_epi(uint32_t sb, bf16* out, int lc, int c) {
  uint4 v[NCH][4], xr[NCH];
  const uint32_t sw = (c ^ ((c >> 3) & 1)) * 16;
#pragma unroll
  for (int u = 0; u < NCH; u++) {
#pragma unroll
    for (int k = 0; k < 4; k++) v[u][k] = lds128(sb + (HALF ? cv_pb1(lc + STEP * u, k) : cv_pb0(lc + STEP * u, k)) + sw);
    xr[u] = lds128(sb + cv_x(HALF, lc + STEP * u) + c * 16);
  }
#pragma unroll
  for (int u = 0; u < NCH; u++) {
    uint4 o;
    o.x = hadd2(xr[u].x, hadd2(hadd2(v[u][0].x, v[u][1].x), hadd2(v[u][2].x, v[u][3].x)));
    o.y = hadd2(xr[u].y, hadd2(hadd2(v[u][0].y, v[u][1].y), hadd2(v[u][2].y, v[u][3].y)));
    o.z = hadd2(xr[u].z, hadd2(hadd2(v[u][0].z, v[u][1].z), hadd2(v[u][2].z, v[u][3].z)));
    o.w = hadd2(xr[u].w, hadd2(hadd2(v[u][0].w, v[u][1].w), hadd2(v[u][2].w, v[u][3].w)));
    stg128(out + cv_chan(0, lc + STEP * u) * LSEQ + HALF * 1024 + c * 8, o);
  }
}

__device__ __forceinline__ bool prep_valid(const uint4 (&st)[6], const uint4 (&xr)[4]) {
  const uint32_t n = __float_as_uint(8.f);
  return st[0].w == n && st[1].w == n && st[2].w == n && st[3].w == n && st[4].w == n && (st[5].w | st[5].y | st[5].z) == n &&
         xr[0].x != UNSET && xr[1].x != UNSET && xr[2].x != UNSET && xr[3].x != UNSET;
}
template <int HALF>
__device__ __forceinline__ void conv_prep(uint32_t sb, int layer, int cta, int i) {
  uint4 st[6], xr[4];
  const uint4* sp = (const uint4*)g_stats + (layer * 32 + HALF * 16 + (i >> 3)) * 48 + (i & 7);
  const uint4* xp = (const uint4*)g_xT + (2 * layer * DM + 2 * cta) * (LSEQ / 8) + HALF * 128 + i;
  auto fetch = [&]() {
#pragma unroll
    for (int k = 0; k < 6; k++) st[k] = ld_tagged(sp + 8 * k);
#pragma unroll
    for (int k = 0; k < 4; k++) xr[k] = ld_tagged(xp + cv_chan(0, k) * (LSEQ / 8));
  };
  if (HALF) {
#pragma unroll
    for (int k = 0; k < 6; k++) st[k] = lds128(sb + CV_ST + (i >> 3) * 768 + k * 128 + (i & 7) * 16);
#pragma unroll
    for (int k = 0; k < 4; k++) xr[k] = lds128(sb + cv_x(1, k) + i * 16);
  } else {
    fetch();
  }
  int it = 0;
  while (!__all_sync(~0u, prep_valid(st, xr)) && ++it < MAX_RETRY) { fetch(); RETRY(1); }
  if (!HALF || it) {
#pragma unroll
    for (int k = 0; k < 4; k++) sts128(sb + cv_x(HALF, k) + i * 16, xr[k]);
  }
  const uint32_t v[16] = {st[0].x, st[0].y, st[0].z, st[1].x, st[1].y, st[1].z, st[2].x, st[2].y, st[2].z, st[3].x, st[3].y, st[3].z, st[4].x, st[4].y, st[4].z, st[5].x};
  uint32_t rs[4], nm[4];
#pragma unroll
  for (int k = 0; k < 4; k++) {
    const float m0 = __uint_as_float(v[4 * k]) * (-1.f / DM), m1 = __uint_as_float(v[4 * k + 2]) * (-1.f / DM);
    const float r0 = rsqrt_approx(fmaxf(fmaf(__uint_as_float(v[4 * k + 1]), 1.f / DM, -m0 * m0), 0.f) + 1e-5f);
    const float r1 = rsqrt_approx(fmaxf(fmaf(__uint_as_float(v[4 * k + 3]), 1.f / DM, -m1 * m1), 0.f) + 1e-5f);
    rs[k] = packbf(r0, r1);
    nm[k] = packbf(m0 * bf_lo(rs[k]), m1 * bf_hi(rs[k]));
  }
  const uint32_t ud = sb + (i & 1) * CV_UH + (127 - 64 * HALF - (i >> 1)) * 16;
#pragma unroll
  for (int k = 0; k < 4; k++)
    sts128(ud + cv_u(k), make_uint4(hfma2(xr[k].x, rs[0], nm[0]), hfma2(xr[k].y, rs[1], nm[1]), hfma2(xr[k].z, rs[2], nm[2]), hfma2(xr[k].w, rs[3], nm[3])));
  fence_async_smem();
}

#define AGATE 1
#define PP0 1
__device__ __forceinline__ void conv_phase(const Params& p, uint32_t sb, int layer, int cta) {
  const int tid = opaque_tid();
  const int wg = __shfl_sync(~0u, tid >> 7, 0), w = __shfl_sync(~0u, (tid >> 5) & 3, 0);
  const uint32_t bar = sb + SM_BAR;
  constexpr int CH2 = 4 * PG;
  bf16* xout = g_xT + ((2 * layer + 1) * DM + 2 * cta) * LSEQ;
  uint32_t A0[68], A1[68];
  float acc[32];
  const uint32_t pe = sb + cv_pe(wg) + 4 * (16 + 16 * w + ((tid & 31) >> 2) - 2 * (tid & 3));
  auto staged = [&]() {
    if (w == 0) {
      bulk_wait_read();
      __syncwarp();
      if (elect_one()) mbar_arrive(bar + 8 * (B_PST + wg));
    }
  };
  if (wg == 0) staged();
  mbar_wait(bar + 8 * (B_PDONE + 1), layer);
  mbar_wait(bar + 8 * B_PE, layer);
  conv_load(A0, pe);
  if (wg == 1) staged();
  conv_load(A1, pe + CH2);
  TSW(19);
  const uint64_t d0 = mkdesc(sb + cv_u(wg), CV_UH, 128, 0), d1 = d0 + (CH2 >> 4);
  mbar_wait(bar + 8 * B_U, layer);
  TSW(12);
  if (wg == 1) bar_sync(5, 256);
  conv_mma0(acc, A0, d0);
  if (wg == 0) bar_arrive(5, 256);
  mbar_wait(bar + 8 * (B_PDONE + 1), layer);
  {
    const int l = opaque_tid() & 31;
    if ((l & 15) < 2 * w) sts128(sb + cv_pb0(wg + 2 * (l >> 4), w) + (l & 15) * 16, make_uint4(0, 0, 0, 0));
  }
  wg_wait<0>();
  conv_store(acc, sb + cv_pb0(wg, w), sb + cv_pb1(wg, w), w);
  conv_mma0(acc, A1, d1);
  wg_wait<0>();
  conv_store(acc, sb + cv_pb0(2 + wg, w), sb + cv_pb1(2 + wg, w), w);
  TSW(13);
  bar_sync(2 + wg, 128);
  conv_epi<0, 2, 2>(sb, xout, wg, opaque_tid() & 127);
  TSW(14);
  mbar_arrive(bar + 8 * B_PUB);
  if (wg == 0) mbar_wait(bar + 8 * B_U1, layer);
  else bar_sync(6, 256);
  TSW(15);
  const uint64_t ds = mkdesc(sb + cv_se(wg), 8192, 1024, 1), df = mkdesc(sb + cv_fa(wg), 512, 128, 0);
  conv_mma1(acc, A0, d0, ds, df);
  if (wg == 0) bar_arrive(6, 256);
  wg_wait<0>();
  conv_store(acc, sb + cv_pb1(wg, w), sb + cv_dump(wg), w);
  TSW(16);
  bar_sync(2 + wg, 128);
  conv_epi<1, 1>(sb, xout, wg, opaque_tid() & 127);
  mbar_arrive(bar + 8 * (B_PUB + 1));
  conv_mma1(acc, A1, d1, ds + 512, df + (CH2 >> 4));
  wg_wait<0>();
  conv_store(acc, sb + cv_pb1(2 + wg, w), sb + cv_dump(2 + wg), w);
  TSW(17);
  bar_sync(2 + wg, 128);
  conv_epi<1, 1>(sb, xout, 2 + wg, opaque_tid() & 127);
  mbar_arrive(bar + 8 * (B_PUB + 2));
  TSW(18);
}

__device__ __forceinline__ void final_phase(const Params& p, uint32_t sb, int cta, int wg, int w, int rtp) {
  const int lane = opaque_tid() & 31;
  const uint32_t bar = sb + SM_BAR;
  mbar_wait(bar + 8 * (B_TF + wg), 0);
  if (threadIdx.x == 128) TS(8);
  const uint32_t src = sb + (16 + wg) * PG, dst = src + 2 * PG;
  const int mi = lane >> 3;
#pragma unroll 1
  for (int attempt = 0; attempt < MAX_RETRY; attempt++) {
    uint32_t m = 0;
#pragma unroll
    for (int j = 0; j < 8; j += 2) {
      uint32_t r[4];
      const int line = 8 * (j + (mi >> 1)) + (lane & 7), pc = 2 * w + (mi & 1);
      ldsm4t(r, src + line * 128 + ((pc ^ (line & 7)) << 4));
      const int row = 16 * w + (lane & 7) + 8 * (mi & 1), ch = j + (mi >> 1);
      stsm4(dst + row * 128 + ((ch ^ (row & 7)) << 4), r[0], r[1], r[2], r[3]);
#pragma unroll
      for (int k = 0; k < 4; k++) asm("max.u16x2 %0, %0, %1;" : "+r"(m) : "r"(r[k]));
    }
    fence_async_smem();
    if (!bar_or(2 + wg, 128, m >= 0xffff0000u || (m & 0xffffu) == 0xffffu)) break;
    if (w == 0 && elect_one()) {
      mbar_expect(bar + 8 * (B_RT + wg), PG);
      tma_ld(src, &p.mapXT, (16 * wg + (cta & 15)) * 64, 3 * DM + (cta >> 4) * 64, bar + 8 * (B_RT + wg));
    }
    mbar_wait(bar + 8 * (B_RT + wg), (rtp + attempt) & 1);
    RETRY(2);
  }
  if (w == 0 && elect_one()) {
    tma_st(&p.mapOut, (cta >> 4) * 64, (16 * wg + (cta & 15)) * 64, dst);
    bulk_commit();
    asm volatile("cp.async.bulk.wait_group.read 0;" ::: "memory");
    if (threadIdx.x == 128) TS(9);
    if (threadIdx.x == 128) LTS(1);
  }
}

struct cplx { float r, i; };
__device__ __forceinline__ cplx cmul(cplx a, cplx b) { return {fmaf(a.r, b.r, -a.i * b.i), fmaf(a.r, b.i, a.i * b.r)}; }
__device__ __forceinline__ cplx csqr(cplx a) { return {fmaf(a.r, a.r, -a.i * a.i), (a.r + a.r) * a.i}; }
__device__ __forceinline__ cplx cexp_l(float ar2, float ai, float l) {
  const float m = ex2(ar2 * l);
  const float x = ai * l;
  return {m * __cosf(x), m * __sinf(x)};
}

__device__ __forceinline__ void colsum_cta(const Params& p, uint32_t sb, int j, int tid) {
  const uint32_t bar = sb + SM_BAR;
  auto ld = [&](int i) {
    mbar_expect(bar + 8 * i, 3 * PG);
    tma_ld3(sb + (i & 7) * 3 * PG, &p.mapW3, (2 * j + (i & 1)) * 64, (i >> 1) * 64, 0, bar + 8 * i);
  };
  if (tid == 384) {
#pragma unroll
    for (int i = 0; i < 24; i++) mbar_init(bar + 8 * i, i < 16 ? 1 : 12);
    asm volatile("fence.mbarrier_init.release.cluster;" ::: "memory");
    fence_async_smem();
#pragma unroll 1
    for (int i = 0; i < 8; i++) ld(i);
  }
  const unsigned ep = ld_relaxed(&g_cnt[C_CS * 32]);
  bar_sync(0, NTHREADS);
  if (tid == 384) {
#pragma unroll 1
    for (int i = 8; i < 16; i++) { mbar_wait(bar + 8 * (8 + i), 0); fence_async_smem(); ld(i); }
  }
  if (tid < 384) {
    const int lane = tid & 31, cc = tid & 7, r0 = (tid >> 3) & 15, part = tid >> 7;
    const uint32_t id = ((lane >> 2) == 2 * (lane & 3) ? 0x3f80u : 0u) | ((lane >> 2) == 2 * (lane & 3) + 1 ? 0x3f800000u : 0u);
    const uint32_t src = sb + part * PG + r0 * 128 + ((cc ^ (r0 & 7)) << 4);
    float s[2][2][4];
#pragma unroll
    for (int i = 0; i < 16; i++) s[i >> 3][(i >> 2) & 1][i & 3] = 0.f;
#pragma unroll 1
    for (int i2 = 0; i2 < 16; i2 += 2) {
#pragma unroll
      for (int h = 0; h < 2; h++) {
        const int i = i2 + h;
        mbar_wait(bar + 8 * i, 0);
        uint4 v[4];
#pragma unroll
        for (int k = 0; k < 4; k++) v[k] = lds128(src + (i & 7) * 3 * PG + k * 2048);
#pragma unroll
        for (int k = 0; k < 4; k++) {
          const uint32_t a[4] = {v[k].x, v[k].y, v[k].z, v[k].w};
          mma_bf16(s[h][0], a, id, 0u);
          mma_bf16(s[h][1], a, 0u, id);
        }
        __syncwarp();
        if (i < 8 && lane == 0) mbar_arrive(bar + 8 * (16 + i));
      }
    }
    const uint32_t red = sb + 24 * PG;
#pragma unroll
    for (int h = 0; h < 2; h++)
#pragma unroll
      for (int k = 0; k < 2; k++) sts128f(red + (r0 * 384 + h * 192 + part * 64 + cc * 8 + k * 4) * 4, s[h][k][0], s[h][k][1], s[h][k][2], s[h][k][3]);
    bar_sync(1, 384);
    float tot = 0.f;
#pragma unroll
    for (int k = 0; k < 16; k++) tot += __uint_as_float(lds32(red + (k * 384 + tid) * 4));
    asm volatile("st.relaxed.gpu.global.v2.u32 [%0], {%1,%2};" ::"l"(&g_colsum[j * 384 + tid]), "r"(__float_as_uint(tot)), "r"(ep / NCTA + 1) : "memory");
    const uint4 u = make_uint4(UNSET, UNSET, UNSET, UNSET);
    if (tid < 256) {
#pragma unroll 4
      for (int i = 0; i < 8; i++) stg128((uint4*)g_xT + (DM + 256 + j * 64 + i * 8 + (tid >> 5)) * 256 + 128 + ((tid & 31) >> 1) * 8 + (tid & 1), u);
#pragma unroll 1
      for (int s = 0; s < 4; s++) {
        const int n = s ? 32 : 16;
        uint4* dst = (s == 1 ? (uint4*)g_O + 131072 : (uint4*)g_xT + (s + !s) * 131072) + j * n * 1024 + (tid >> 1) * 8 + (tid & 1);
#pragma unroll 4
        for (int i = 0; i < n; i++) stg128(dst + i * 1024, u);
        bar_sync(2, 256);
        if (tid == 32 * s) red_release(&g_cnt[(C_R + s) * 32]);
      }
    }
  }
}

#define KB 4
#define KW 2
struct ModeIn { uint32_t ar, ai, br, bi, cr, ci; bf16 logdt; };
__device__ __forceinline__ ModeIn load_modes(const Params& p, int d, int m) {
  const int i = d * 64 + m;
  return {((const uint32_t*)p.a_re)[i], ((const uint32_t*)p.a_im)[i], ((const uint32_t*)p.b_re)[i], ((const uint32_t*)p.b_im)[i],
          ((const uint32_t*)p.c_re)[i], ((const uint32_t*)p.c_im)[i], p.log_dt[d]};
}
__device__ __forceinline__ float4 lds128f_nv(uint32_t a) { float4 v; asm("ld.shared.v4.f32 {%0,%1,%2,%3}, [%4];" : "=f"(v.x), "=f"(v.y), "=f"(v.z), "=f"(v.w) : "r"(a)); return v; }
__device__ __forceinline__ void kernel_gen(const Params& p, uint32_t sb, int cta, int ht, ModeIn in, const ModeIn& in1) {
  const uint32_t bst = sb + SM_KGB + ((ht & 63) >> 2) * 144 + (ht & 3) * 4 + (ht >> 6) * 16;
  const uint64_t db = mkdesc(sb + SM_KGB, 144, 2304, 0);
  const float e0 = (float)(8 * (((ht & 32) >> 1) + ((ht & 31) >> 2)));
  float T[20];
#pragma unroll
  for (int i = 0; i < 20; i++) T[i] = 0.f;
  float k0 = 0.f;
#pragma unroll 1
  for (int pass = 0; pass < 4; pass++) {
    {
      const int sh = (pass & 1) ? 0 : 16;
      auto val = [&](uint32_t v) { return __uint_as_float((v << sh) & 0xffff0000u); };
      const float dt = __bfloat162float(__float2bfloat16_rn(expf(__bfloat162float(in.logdt))));
      const float ar2 = dt * val(in.ar) * 1.4426950408889634f, ai = dt * val(in.ai);
      const cplx c = cmul({val(in.cr), -val(in.ci)}, {dt * val(in.br), -dt * val(in.bi)});
      k0 += c.r;
      const cplx z1 = cexp_l(ar2, -ai, 1.f), z256 = cexp_l(ar2, -ai, 256.f), z64 = cexp_l(ar2, ai, 64.f);
      const cplx z2 = csqr(z1), z512 = csqr(z256);
      auto put = [&](int j, cplx v) { sts32(bst + (j >> 2) * 2304 + (j & 3) * 32, packbf(v.r, v.i)); };
      sts128f(sb + SM_KGT + ht * 16, ar2, ai, z64.r, z64.i);
      const cplx c1 = cmul(c, z1), c2 = cmul(c, z2), c3 = cmul(c1, z2), c4 = cmul(c2, z2);
      const cplx c5 = cmul(c3, z2), c6 = cmul(c4, z2), c7 = cmul(c5, z2), c8 = cmul(c6, z2);
      put(0, c1); put(1, c2); put(2, c3); put(3, c4); put(4, c5); put(5, c6); put(6, c7); put(7, c8);
      const cplx c260 = cmul(c4, z256), c264 = cmul(c8, z256), c520 = cmul(c8, z512), c776 = cmul(c264, z512);
      put(8, cmul(c2, z256)); put(9, c260); put(10, cmul(c6, z256)); put(11, c264);
      put(12, cmul(c4, z512)); put(13, c520); put(14, cmul(c260, z512)); put(15, c776);
      const cplx c1032 = cmul(c520, z512), c1288 = cmul(c776, z512);
      put(16, c1032); put(17, c1288); put(18, cmul(c1032, z512)); put(19, cmul(c1288, z512));
    }
    fence_async_smem();
    bar_sync(4, 128);
    const uint32_t tb = sb + SM_KGT + (ht & 67) * 16;
    float2 nx[KB];
#pragma unroll
    for (int s = 0; s < KB; s++) nx[s] = lds64f(tb + s * 64);
#pragma unroll
    for (int q = 0; q < 16 / KB; q++) {
      uint32_t A[2 * KB];
      float2 cur[KB], z[KB];
#pragma unroll
      for (int s = 0; s < KB; s++) { cur[s] = nx[s]; z[s] = lds64f(tb + (KB * q + s) * 64 + 8); }
      if (q < 16 / KB - 1) {
#pragma unroll
        for (int s = 0; s < KB; s++) nx[s] = lds64f(tb + (KB * q + KB + s) * 64);
      }
      if (q >= KW) wg_wait<KW - 1>();
#pragma unroll
      for (int s = 0; s < KB; s++) {
        const cplx lo = cexp_l(cur[s].x, cur[s].y, e0), hi = cmul(lo, {z[s].x, z[s].y});
        A[2 * s] = packbf(lo.r, lo.i);
        A[2 * s + 1] = packbf(hi.r, hi.i);
      }
      wg_fence();
#pragma unroll
      for (int k = 0; k < KB / 2; k++) wgmma_rs<40, 0>(T, A + 4 * k, db + 9 * KB * q + 18 * k, (pass & 1) | q | k);
      wg_commit();
    }
    wg_wait<0>();
    acc_fence<20>(T);
    if (ht == 0) TS(4 + pass);
    if (pass & 1) {
      const int h2 = opaque_tid() - 256, w = h2 >> 5, lane = h2 & 31, t = lane & 3, chn = h2 >> 6, m = h2 & 63, i0 = 16 * (w & 1) + (lane >> 2);
      const int lc = (pass & 2) + chn;
      const uint32_t kc = sb + kc_off(lc);
      auto put = [&](int idx, float v) {
        sts16(kc + idx * 2, __bfloat16_as_ushort(__float2bfloat16_rn(v)));
      };
#pragma unroll
      for (int hi = 0; hi < 2; hi++) {
        const int i = i0 + 8 * hi;
        float v[5];
#pragma unroll
        for (int j = 0; j < 5; j++) v[j] = chn ? T[4 * j + 2 * hi + 1] : T[4 * j + 2 * hi];
        put(8 * i + 1 + t, v[0]);
        put(8 * i + 5 + t, v[1]);
        put(257 + 4 * i + t, v[2]);
        put(385 + 2 * i + (t & 1) + 64 * (t >> 1), v[3]);
        put(513 + i + 32 * t, v[4]);
      }
#pragma unroll
      for (int o = 16; o > 0; o >>= 1) k0 += __shfl_xor_sync(~0u, k0, o);
      if (lane == 0) sts32f(sb + SM_RED + 4 * w, k0);
      bar_sync(4, 128);
      if (m == 0) put(0, k0 + __uint_as_float(lds32(sb + SM_RED + 4 * w + 4)) + __uint_as_float(lds16(sb + SM_RED + 24 + 2 * lc) << 16));
      k0 = 0.f;
      in = in1;
    }
  }
}

__device__ __forceinline__ void expand_taps(uint32_t sb, int ht) {
  const int ch = ht >> 5, lane = ht & 31;
  const uint32_t kc = sb + kc_off(ch);
  const uint32_t dst0 = sb + cv_pe(ch);
  auto put = [&](int G, uint32_t v0, uint32_t v1, uint32_t v2, uint32_t v3, uint32_t v4, uint32_t v5, uint32_t v6, uint32_t v7, uint32_t v8) {
    const uint32_t dst = dst0 + G * 32;
    sts128(dst, make_uint4(v1 | (v0 << 16), v2 | (v1 << 16), v3 | (v2 << 16), v4 | (v3 << 16)));
    sts128(dst + 16, make_uint4(v5 | (v4 << 16), v6 | (v5 << 16), v7 | (v6 << 16), v8 | (v7 << 16)));
  };
  {
    const uint4 q = lds128(kc + lane * 16);
    const uint32_t pv = lane ? lds16(kc + lane * 16 - 2) : 0u;
    const uint32_t dst = dst0 + (lane + 2) * 32;
    sts128(dst, make_uint4(__byte_perm(q.x, pv, 0x5410), __byte_perm(q.x, q.x, 0x1032), __byte_perm(q.y, q.x, 0x7610), __byte_perm(q.y, q.y, 0x1032)));
    sts128(dst + 16, make_uint4(__byte_perm(q.z, q.y, 0x7610), __byte_perm(q.z, q.z, 0x1032), __byte_perm(q.w, q.z, 0x7610), __byte_perm(q.w, q.w, 0x1032)));
    if (lane < 4) sts128(dst0 + lane * 16, make_uint4(0, 0, 0, 0));
  }
  uint32_t a[5], b[2][3];
  {
    const uint32_t s1 = kc + 2 * (256 + 4 * lane);
#pragma unroll
    for (int k = 0; k < 5; k++) a[k] = lds16(s1 + 2 * k);
#pragma unroll
    for (int u = 0; u < 2; u++) {
      const uint32_t s2 = kc + 2 * (384 + 2 * (lane + 32 * u));
#pragma unroll
      for (int k = 0; k < 3; k++) b[u][k] = lds16(s2 + 2 * k);
    }
  }
  const uint32_t k255 = lds16(kc + 2 * 255), k1024 = lds16(kc + 2 * 512);
  put(34 + lane, lane == 0 ? k255 : a[0], a[0], a[0], a[1], a[2], a[2], a[2], a[3], a[4]);
#pragma unroll
  for (int u = 0; u < 2; u++) put(66 + lane + 32 * u, b[u][0], b[u][0], b[u][0], b[u][0], b[u][1], b[u][1], b[u][1], b[u][2], b[u][2]);
  if (lane < 10) {
    const uint32_t v = lane == 0 ? k1024 : 0u;
    put(130 + lane, v, v, v, v, v, v, 0u, 0u, 0u);
  }
}
__device__ __forceinline__ void expand_far(uint32_t sb, int ht) {
  const int ch = ht >> 5, lane = ht & 31;
  const uint32_t kc = sb + kc_off(ch) + 2 * (513 + 2 * (63 - lane)), dst = sb + cv_fa(ch) + lane * 16;
#pragma unroll
  for (int ty = 0; ty < 2; ty++) {
    uint32_t v[16];
#pragma unroll
    for (int k = 0; k < 16; k++) v[k] = (k < 8 || 63 - lane - 4 * k >= 0) ? lds16(kc + 2 * (1 - ty) - 16 * k) : 0u;
#pragma unroll
    for (int u = 0; u < 2; u++)
      sts128(dst + ty * 2048 + u * 512, make_uint4(v[8 * u] | (v[8 * u + 1] << 16), v[8 * u + 2] | (v[8 * u + 3] << 16), v[8 * u + 4] | (v[8 * u + 5] << 16), v[8 * u + 6] | (v[8 * u + 7] << 16)));
    sts128(dst + ty * 2048 + 1024, make_uint4(0, 0, 0, 0));
  }
}

#define TMPF 1
#define CONST_SB 1
#define WPRE 1
__host__ __device__ constexpr int bar_count(int i) {
  return i == B_END ? 3 : i == B_LN ? 2 : i < B_OST ? 1 : i < B_PE ? 4 : i >= B_PUB ? 256 : 128;
}
__host__ __device__ constexpr bool bar_first(int i) { return i < B_WF + 2 && (i & 7) < 2; }

__global__ void __launch_bounds__(NTHREADS, 1) fused_kernel(const __grid_constant__ Params p) {
  extern __shared__ __align__(1024) uint8_t smem[];
  constexpr uint32_t sb = 1024;
  if (s32(smem) != sb) return;
  const int tid = threadIdx.x, lane = tid & 31;
  const int warp = __shfl_sync(~0u, tid >> 5, 0);
  if (tid == 32) {
    asm volatile("prefetch.tensormap [%0];" ::"l"(&p.mapX) : "memory");
    asm volatile("prefetch.tensormap [%0];" ::"l"(&p.mapW3) : "memory");
  }
  const int cta = blockIdx.x - (gridDim.x == NCTA + 4 ? 0 : 4);
  if ((unsigned)cta >= NCTA) {
    if (blockIdx.x < NCTA + 4) colsum_cta(p, sb, blockIdx.x & 3, tid);
    return;
  }
  const int rb = ((cta >> 4) & 3) * 4 + ((cta >> 2) & 3), hg = (cta >> 6) * 4 + (cta & 3);
  const uint32_t bar = sb + SM_BAR;
  auto ld_x0 = [&](int half, int c) {
    const uint32_t b = bar + 8 * (B_XF + 8 * half + c);
    mbar_expect(b, PG);
    tma_ld(sb + x_page(half, c) * PG, &p.mapX, c * 64, (16 * half + rb) * 64, b);
  };
  auto ld_x1 = [&](int half, int c, int b0) {
    const uint32_t b = bar + 8 * b0;
    mbar_expect(b, PG);
    tma_ld(sb + (8 * half + c) * PG, &p.mapXT, (16 * half + rb) * 64, DM + c * 64, b);
  };
  auto ld_w = [&](int c) {
    const uint32_t b = bar + 8 * (B_WF + c);
    mbar_expect(b, 3 * PG);
    tma_ld3(sb + w_page(c) * PG, &p.mapW3, hg * 64, c * 64, 0, b);
  };

  if (tid == 0) TS(0);
  if (tid == 480) LTS(0);
  if (warp == 0 && elect_one()) {
#pragma unroll
    for (int i = 0; i < B_WF + 2; i++)
      if (bar_first(i)) mbar_init(bar + 8 * i, 1);
    asm volatile("fence.mbarrier_init.release.cluster;" ::: "memory");
    fence_async_smem();
    ld_x0(0, 0);
    ld_w(0); ld_x0(1, 0);
    ld_x0(0, 1); ld_w(1); ld_x0(1, 1);
    TS(1);
  }
  __syncwarp();
  if (warp >= 1 && warp < 8 && elect_one()) {
    if (warp < 4) {
#pragma unroll
      for (int i = 2; i < 8; i++) mbar_init(bar + 8 * (8 * warp - 8 + i), 1);
    } else {
#pragma unroll
      for (int i = 0; i < 12; i++) mbar_init(bar + 8 * (12 * warp - 24 + i), 1);
    }
    asm volatile("fence.mbarrier_init.release.cluster;" ::: "memory");
  }
  if (warp == 15 && elect_one()) {
#pragma unroll
    for (int i = 72; i < B_COUNT; i++) mbar_init(bar + 8 * i, bar_count(i));
    asm volatile("fence.mbarrier_init.release.cluster;" ::: "memory");
  }

  if (warp < 8) {
    bar_sync(0, NTHREADS);
    asm volatile("setmaxnreg.inc.sync.aligned.u32 %0;" ::"n"(R_CONS));
    const int cw = __shfl_sync(~0u, opaque_tid() >> 5, 0);
    const int wg = cw >> 2, w = cw & 3;
    if (tid == 0) TS(2);
    int rtp = 0;
#pragma unroll 1
    for (int layer = 0; layer < 2; layer++) {
      attn_phase(p, sb, layer, rb, hg, wg, w);
      proj_phase(p, sb, layer, rb, hg, rtp);
      conv_phase(p, sb, layer, cta);
    }
    final_phase(p, sb, cta, wg, w, rtp);
  } else if (warp < 12) {
    asm volatile("setmaxnreg.dec.sync.aligned.u32 %0;" ::"n"(R_HELP));
    const int ht = tid - 256;
    {
      unsigned ep0 = 0;
      if (ht == 0) ep0 = ld_relaxed(&g_cnt[C_CS * 32]);
      const bf16 dsk = p.dskip[cv_chan(cta, ht & 3)];
      const ModeIn in0 = load_modes(p, cv_chan(cta, ht >> 6), ht & 63), in1 = load_modes(p, cv_chan(cta, 2 + (ht >> 6)), ht & 63);
      if (ht < 48) sts128f(sb + SM_STG + ht * 16, 0.f, 0.f, 0.f, 1.f);
      bar_sync(0, NTHREADS);
      if (ht == 0) {
        sts32(sb + SM_EP, ep0);
        mbar_arrive(bar + 8 * B_EP);
      }
      if (ht >= 124) sts16(sb + SM_RED + 24 + 2 * (ht & 3), __bfloat16_as_ushort(dsk));
      kernel_gen(p, sb, cta, ht, in0, in1);
      if (ht < 48) sts128f(sb + SM_KGT + ht * 16, 0.f, 0.f, 0.f, 1.f);
      fence_async_smem();
      bar_sync(4, 128);
      if (ht == 0) mbar_arrive(bar + 8 * B_KG);
    }
#pragma unroll 1
    for (int layer = 0; layer < 2; layer++) {
      mbar_wait(bar + 8 * B_PDONE, layer);
      expand_taps(sb, opaque_tid() - 256);
      mbar_arrive(bar + 8 * B_PE);
      TSW(0);
      expand_far(sb, opaque_tid() - 256);
      {
        const int i = opaque_tid() - 256;
        if (i < 32) sts128(sb + cv_u(i >> 3) + ((i >> 2) & 1) * CV_UH + (128 + (i & 3)) * 16, make_uint4(0, 0, 0, 0));
        mbar_wait(bar + 8 * B_RC, layer);
        mbar_wait(bar + 8 * B_GB, layer);
        TSW(13);
        conv_prep<0>(sb, layer, cta, i);
        mbar_arrive(bar + 8 * B_U);
      }
      mbar_wait(bar + 8 * (B_PDONE + 1), layer);
      bar_sync(4, 128);
#pragma unroll 1
      for (int lc = 0; lc < 4; lc += 2) {
        conv_sums(sb, lc, opaque_tid() - 256);
        TSW(1 + lc);
      }
      mbar_wait(bar + 8 * (B_GB + 1), layer);
      conv_prep<1>(sb, layer, cta, opaque_tid() - 256);
      mbar_arrive(bar + 8 * B_U1);
      TSW(4);
      if (layer == 0) {
        const int c = __shfl_sync(~0u, (opaque_tid() >> 5) & 3, 0);
        int phase = 0;
#pragma unroll 1
        for (int k = 0; k < 3; k++) {
          const int page = (k ? 4 + 4 * k : 0) + c, b = B_XR + 4 * (k & 1) + c;
          const uint32_t a = sb + page * PG + lane * 128 + (lane & 7) * 16 + (lane >> 3) * 4;
          int it = k == 2 ? phase : 0;
#pragma unroll 1
          for (; it < MAX_RETRY; it++) {
            mbar_wait(bar + 8 * b, it & 1);
            const uint32_t v0 = lds32(a), v1 = lds32(a + 4096);
            if (__all_sync(~0u, v0 != UNSET && v1 != UNSET)) break;
            if (elect_one()) { fence_async_smem(); ld_x1(page >> 3, page & 7, b); }
            __syncwarp();
            RETRY(3);
          }
          if (k == 0) phase = it + 1;
          if (lane == 0) mbar_arrive(bar + 8 * (B_XF + page));
        }
      }
    }
  } else {
    asm volatile("setmaxnreg.dec.sync.aligned.u32 %0;" ::"n"(R_AGENT));
    bar_sync(0, NTHREADS);
    auto done = [&](int half, int c, int layer) { mbar_wait(bar + 8 * (B_DN + 8 * half + c), layer); };
    auto publish = [&](int layer, int k) {
      mbar_wait(bar + 8 * (B_PUB + k), layer);
      red_relaxed(&g_cnt[(layer ? C_F + 4 * k + (cta >> 5) : C_C + k) * 32]);
      if (!layer && k == 0) red_release(&g_cnt[(C_C + 3) * 32]);
      TS(16 + layer * 56 + 40 + 7 + k);
    };
    if (warp == 12) {
      if (elect_one()) {
#pragma unroll 1
        for (int layer = 0; layer < 2; layer++) {
          auto ld_xe = [&](int c) {
            const uint32_t b = bar + 8 * (B_XF + c);
            mbar_expect(b, PG);
            if (layer == 0) tma_ld(sb + x_page(0, c) * PG, &p.mapX, c * 64, rb * 64, b);
            else tma_ld(sb + x_page(0, c) * PG, &p.mapXT, rb * 64, DM + c * 64, b);
          };
          if (layer == 0) {
            ld_x0(0, 2); ld_w(2); ld_x0(1, 2);
            if (hg >= 3) {
              mbar_expect(bar + 8 * B_SC, PG);
              tma_ld(sb + P_R * PG, &p.mapX, hg * 64, rb * 64, bar + 8 * B_SC);
            }
            if (rb < 4) tma_prefetch3(&p.mapW3, hg * 64, (4 + rb) * 64, 0);
            ld_x0(0, 3); ld_w(3); ld_x0(1, 3); ld_x0(0, 4); ld_x0(1, 4);
            done(0, 0, 0); done(1, 0, 0);
            ld_w(4);
            ld_x0(1, 5); ld_x0(1, 6); ld_x0(1, 7);
            done(0, 1, 0); done(1, 1, 0);
            ld_w(5);
            if (rb < 8) tma_prefetch5(&p.mapWo, hg * 64, rb * 2);
            done(0, 2, 0);
            fence_async_smem();
            ld_xe(5); ld_xe(6); ld_xe(7);
          } else {
            mbar_wait(bar + 8 * B_PDONE, 0);
            mbar_wait(bar + 8 * (B_PDONE + 1), 0);
            mbar_wait(bar + 8 * (WPRE == 1 ? B_U : B_GB + 1), 0);
            ld_w(0); ld_w(1);
            mbar_wait(bar + 8 * B_U1, 0);
            fence_async_smem();
            ld_w(2);
            mbar_wait(bar + 8 * (B_PUB + 2), 0);
            fence_async_smem();
            ld_w(3);
            spin_until(&g_cnt[(C_C + 3) * 32], ((lds32(sb + SM_EP) / NCTA) + 1) * NCTA);
            fence_async_global();
            if (hg >= 3) {
              mbar_expect(bar + 8 * B_SC, PG);
              tma_ld(sb + P_R * PG, &p.mapXT, rb * 64, DM + hg * 64, bar + 8 * B_SC);
            }
            ld_xe(4);
            done(0, 2, 1);
            fence_async_smem();
            ld_xe(5); ld_xe(6); ld_xe(7);
            done(1, 0, 1);
            ld_w(4);
            done(1, 1, 1);
            ld_w(5);
          }
          done(1, 2, layer);
          fence_async_smem();
          ld_w(6); ld_w(7);
          auto ld_res = [&](int half) {
            const uint32_t b = bar + 8 * (B_RF + half);
            mbar_expect(b, PG);
            if (layer == 0) tma_ld(sb + (half ? 2 : P_R) * PG, &p.mapX, hg * 64, (16 * half + rb) * 64, b);
            else tma_ld(sb + (half ? 2 : P_R) * PG, &p.mapXT, (16 * half + rb) * 64, DM + hg * 64, b);
          };
          done(0, 4, layer); done(1, 3, layer);
          fence_async_smem();
          mbar_expect(bar + 8 * B_WOF, 8 * PG);
#pragma unroll 1
          for (int c = 0; c < 8; c++) {
            if (c == 5) { ld_res(0); done(1, 4, layer); }
            tma_ld5(sb + wo_page(c) * PG, &p.mapWo, hg * 64, c * 2, bar + 8 * B_WOF);
          }
          done(0, 7, layer);
          fence_async_global();
          ld_res(1);
        }
      }
    } else if (warp == 13) {
      mbar_wait(bar + 8 * B_EP, 0);
      const unsigned e1 = (lds32(sb + SM_EP) / NCTA) + 1;
      auto ld_o = [&](int layer) {
#pragma unroll 1
        for (int half = 0; half < 2; half++) {
          done(1, 7, layer);
          mbar_wait(bar + 8 * B_OST, layer);
          if (half) mbar_wait(bar + 8 * (B_OST + 1), layer);
          fence_async_smem();
#pragma unroll
          for (int c = 0; c < 4; c++) mbar_expect(bar + 8 * (B_OF + 4 * half + c), 2 * PG);
          spin_hint(&g_cnt[(C_O + layer * 32 + 16 * half + rb) * 32], e1 * 32);
#pragma unroll
          for (int c = 0; c < 4; c++)
            bulk_ld(sb + o_page(half, c) * PG, g_O + ((layer * 32 + 16 * half + rb) * 4 + c) * PG, 2 * PG, bar + 8 * (B_OF + 4 * half + c));
        }
      };
      if (elect_one()) {
        mbar_wait(bar + 8 * (B_WF + 2), 0);
        asm volatile("prefetch.tensormap [%0];" ::"l"(&p.mapXT) : "memory");
        asm volatile("prefetch.tensormap [%0];" ::"l"(&p.mapOut) : "memory");
        asm volatile("prefetch.tensormap [%0];" ::"l"(&p.mapWo) : "memory");
        spin_until(&g_cnt[C_Z * 32], e1 * NCTA);
        mbar_arrive(bar + 8 * B_ZF);
        TS(3);
        ld_o(0);
#pragma unroll 1
        for (int k = 0; k < 3; k++) {
          mbar_wait(bar + 8 * (B_PUB + k), 0);
          if (k == 2) {
#pragma unroll 1
            for (int c = 0; c < 4; c++) mbar_wait(bar + 8 * (B_XF + c), 1);
          }
          fence_async_smem();
          spin_hint(&g_cnt[(C_C + k) * 32], e1 * NCTA);
          TS(10 + k);
#pragma unroll
          for (int c = 0; c < 4; c++) ld_x1(k != 0, (k & 2) * 2 + c, B_XR + 4 * (k & 1) + c);
        }
        ld_o(1);
        mbar_wait(bar + 8 * B_PUB, 1);
#pragma unroll 1
        for (int half = 0; half < 2; half++) {
          mbar_expect(bar + 8 * (B_TF + half), PG);
          spin_hint(&g_cnt[(C_F + 4 * (half ? 1 + (cta >> 6) : 0) + ((cta >> 4) & 3)) * 32], e1 * 32);
          tma_ld(sb + (16 + half) * PG, &p.mapXT, (16 * half + (cta & 15)) * 64, 3 * DM + (cta >> 4) * 64, bar + 8 * (B_TF + half));
        }
      }
    } else if (warp == 14) {
      mbar_wait(bar + 8 * B_EP, 0);
      const unsigned e1 = (lds32(sb + SM_EP) / NCTA) + 1;
      done(0, 1, 0);
      {
        const uint2* cp = g_colsum + (hg * 192 + lane);
        uint2 v[6];
        bool ok;
        int it = 0;
        do {
          ok = true;
#pragma unroll
          for (int i = 0; i < 6; i++) {
            asm volatile("ld.relaxed.gpu.global.v2.u32 {%0,%1}, [%2];" : "=r"(v[i].x), "=r"(v[i].y) : "l"(cp + 32 * i) : "memory");
            ok = ok && v[i].y == e1;
          }
          if (++it > (1 << 22)) __trap();
        } while (!__all_sync(~0u, ok));
#pragma unroll
        for (int i = 0; i < 6; i++) sts32f(sb + SM_CS + 4 * (lane + 32 * i), __uint_as_float(v[i].x));
      }
      __syncwarp();
      if (elect_one()) {
        mbar_wait(bar + 8 * B_ZF, 0);
        mbar_arrive(bar + 8 * B_LN);
        red_relaxed(&g_cnt[C_CS * 32]);
        TS(13);
#pragma unroll 1
        for (int i = 0; i < 4; i++) {
          const int layer = i >> 1;
          mbar_wait(bar + 8 * (B_PST + (i & 1)), layer);
          const uint32_t b = bar + 8 * (B_GB + 1);
          const bf16* xin = g_xT + ((size_t)2 * layer * DM + 2 * cta) * LSEQ + 1024;
          if (i & 1) {
            fence_async_smem();
            mbar_expect(b, 12288 + PG);
          }
          spin_hint(&g_cnt[(C_G + i) * 32], e1 * NCTA);
          if (i & 1) {
            bulk_ld(sb + CV_ST, g_stats + (layer * 32 + 16) * 192, 12288, b);
#pragma unroll
            for (int lc = 0; lc < 4; lc++) bulk_ld(sb + cv_x(1, lc), xin + cv_chan(0, lc) * LSEQ, 2048, b);
            TS(14 + layer);
            publish(layer, 1);
          } else {
            mbar_arrive(bar + 8 * B_GB);
          }
        }
      }
    } else {
      const uint4 u = make_uint4(UNSET, UNSET, UNSET, UNSET);
      if (lane < 24) stg128((uint4*)g_stats + cta * 24 + lane, make_uint4(0, 0, 0, 0));
      if (lane < 16) stg128(g_rows + LSEQ + cta * 16 + lane, make_uint4(0, 0, 0, 0));
#pragma unroll 4
      for (int i = 0; i < 16; i++) stg128(g_halo + cta * 512 + 32 * i + lane, u);
#pragma unroll 4
      for (int i = 0; i < 16; i++) stg128(((i & 8) ? (uint4*)g_xT : (uint4*)g_O) + cta * 1024 + (i & 7) * 128 + (lane >> 1) * 8 + (lane & 1), u);
      __syncwarp();
      if (elect_one()) red_release(&g_cnt[C_Z * 32]);
      __syncwarp();
#pragma unroll 1
      for (int layer = 0; layer < 2; layer++) {
        auto reset_done = [&](int s) {
          spin_until(&g_cnt[(C_R + s) * 32], (lds32(sb + SM_EP) / NCTA) * 4 + 4);
          mbar_arrive(bar + 8 * (s == 1 ? B_LN : s == 2 ? B_RS : B_RC));
          if (s) TS(16 + 40 + 9 + s);
        };
        if (layer && elect_one()) reset_done(1);
        __syncwarp();
#pragma unroll 1
        for (int half = 0; half < 2; half++) {
          done(half, 2, layer);
          const uint4* src = g_rows + (layer * LSEQ + (16 * half + rb) * 64 + (opaque_tid() & 31));
          uint4 a, b;
          int it = 0;
          do {
            a = ld_tagged(src); b = ld_tagged(src + 32);
          } while (!__all_sync(~0u, (a.z | a.w) == __float_as_uint(8.f) && (b.z | b.w) == __float_as_uint(8.f)) && ++it < (1 << 20));
          float m0 = __uint_as_float(a.x) * (1.f / DM), m1 = __uint_as_float(b.x) * (1.f / DM);
          float r0 = rsqrt_approx(fmaxf(__uint_as_float(a.y) * (1.f / DM) - m0 * m0, 0.f) + 1e-5f);
          float r1 = rsqrt_approx(fmaxf(__uint_as_float(b.y) * (1.f / DM) - m1 * m1, 0.f) + 1e-5f);
          if (half) done(0, 7, layer);
          const uint32_t dst = sb + ln_off(half) + ((lane >> 4) * 8 + (lane & 7)) * 16 + (lane & 8);
          asm volatile("st.shared.v2.f32 [%0], {%1,%2};" ::"r"(dst), "f"(m0), "f"(r0) : "memory");
          asm volatile("st.shared.v2.f32 [%0], {%1,%2};" ::"r"(dst + 256), "f"(m1), "f"(r1) : "memory");
          __syncwarp();
          if (elect_one()) { mbar_arrive(bar + 8 * (B_LN + half)); TS(16 + layer * 56 + 40 + 14 + half); }
        }
        if (layer && lane < 16) stg128(g_rows + cta * 16 + (opaque_tid() & 31), make_uint4(0, 0, 0, 0));
        if (elect_one()) {
          if (layer) reset_done(2);
          reset_done(3 * layer);
          publish(layer, 0);
          publish(layer, 2);
        }
        __syncwarp();
      }
    }
  }
}

typedef CUresult (*EncodeFn)(CUtensorMap*, CUtensorMapDataType, cuuint32_t, void*, const cuuint64_t*, const cuuint64_t*,
                             const cuuint32_t*, const cuuint32_t*, CUtensorMapInterleave, CUtensorMapSwizzle,
                             CUtensorMapL2promotion, CUtensorMapFloatOOBfill);

static void make_map(EncodeFn enc, CUtensorMap* m, void* ptr, uint64_t cols, uint64_t rows, uint32_t box_rows) {
  cuuint64_t dims[2] = {cols, rows};
  cuuint64_t strides[1] = {cols * 2};
  cuuint32_t box[2] = {64, box_rows};
  cuuint32_t es[2] = {1, 1};
  enc(m, CU_TENSOR_MAP_DATA_TYPE_BFLOAT16, 2, ptr, dims, strides, box, es, CU_TENSOR_MAP_INTERLEAVE_NONE,
      CU_TENSOR_MAP_SWIZZLE_128B, CU_TENSOR_MAP_L2_PROMOTION_L2_128B, CU_TENSOR_MAP_FLOAT_OOB_FILL_NONE);
}
static void make_map3(EncodeFn enc, CUtensorMap* m, void* ptr, uint64_t d0, uint64_t cols, uint64_t rows, uint64_t blk_stride,
                      uint64_t nblocks, uint32_t nblk) {
  cuuint64_t dims[3] = {d0, rows, nblocks};
  cuuint64_t strides[2] = {cols * 2, blk_stride * 2};
  cuuint32_t box[3] = {64, 64, nblk};
  cuuint32_t es[3] = {1, 1, 1};
  enc(m, CU_TENSOR_MAP_DATA_TYPE_BFLOAT16, 3, ptr, dims, strides, box, es, CU_TENSOR_MAP_INTERLEAVE_NONE,
      CU_TENSOR_MAP_SWIZZLE_128B, CU_TENSOR_MAP_L2_PROMOTION_L2_128B, CU_TENSOR_MAP_FLOAT_OOB_FILL_NONE);
}

extern "C" void kernel_launch(void* const* d_in, const int* in_sizes, int n_in, void* d_out, int out_size) {
  static Params prm;
  static void* cached[13] = {nullptr};
  static bool attr_done = false;
  static int grid = NCTA + 4;
  bool same = attr_done && cached[12] == d_out;
  for (int i = 0; i < 12 && same; i++) same = cached[i] == d_in[i];
  if (!same) {
    void* fn = nullptr;
    cudaDriverEntryPointQueryResult qr;
    cudaGetDriverEntryPoint("cuTensorMapEncodeTiled", &fn, cudaEnableDefault, &qr);
    EncodeFn enc = (EncodeFn)fn;
    void* pXT;
    cudaGetSymbolAddress(&pXT, g_xT);
    make_map(enc, &prm.mapX, d_in[0], DM, LSEQ, 64);
    make_map(enc, &prm.mapXT, pXT, LSEQ, 4 * DM, 64);
    make_map(enc, &prm.mapOut, d_out, DM, LSEQ, 64);
    {
      cuuint64_t dims[5] = {DM, 2, 4, 4, 16};
      cuuint64_t strides[4] = {DM * 2, 8 * DM * 2, 2 * DM * 2, 32 * DM * 2};
      cuuint32_t box[5] = {64, 2, 4, 4, 2};
      cuuint32_t es[5] = {1, 1, 1, 1, 1};
      enc(&prm.mapWo, CU_TENSOR_MAP_DATA_TYPE_BFLOAT16, 5, d_in[2], dims, strides, box, es, CU_TENSOR_MAP_INTERLEAVE_NONE,
          CU_TENSOR_MAP_SWIZZLE_128B, CU_TENSOR_MAP_L2_PROMOTION_L2_128B, CU_TENSOR_MAP_FLOAT_OOB_FILL_NONE);
    }
    make_map3(enc, &prm.mapW3, d_in[1], DM, 3 * DM, DM, DM, 3, 3);
    prm.wqkv = (const bf16*)d_in[1];
    prm.a_re = (const bf16*)d_in[4]; prm.a_im = (const bf16*)d_in[5];
    prm.b_re = (const bf16*)d_in[6]; prm.b_im = (const bf16*)d_in[7];
    prm.c_re = (const bf16*)d_in[8]; prm.c_im = (const bf16*)d_in[9];
    prm.log_dt = (const bf16*)d_in[10]; prm.dskip = (const bf16*)d_in[11];
    int dev = 0, sms = 0;
    cudaGetDevice(&dev);
    cudaDeviceGetAttribute(&sms, cudaDevAttrMultiProcessorCount, dev);
    grid = sms >= NCTA + 4 ? NCTA + 4 : NCTA + 5;
    cudaFuncSetAttribute(fused_kernel, cudaFuncAttributeMaxDynamicSharedMemorySize, SM_TOTAL);
    for (int i = 0; i < 12; i++) cached[i] = d_in[i];
    cached[12] = d_out;
    attr_done = true;
  }
  fused_kernel<<<grid, NTHREADS, SM_TOTAL>>>(prm);
}
```

```cpp
#include <cuda_runtime.h>
#include <cuda_bf16.h>
#include <cuda.h>
#include <stdint.h>

typedef __nv_bfloat16 bf16;

constexpr int LSEQ = 2048;
constexpr int DM = 512;
constexpr int NCTA = 128;
constexpr int NTHREADS = 512;
#define R_CONS 200
#define R_HELP 88
#define R_AGENT 24
#define TURN0 4
#define TURN1 4

constexpr int PG = 8192;
constexpr int P_R = 25;
__host__ __device__ constexpr int x_page(int half, int c) { return half ? 8 + c : c < 5 ? c : c - 5; }
__host__ __device__ constexpr int w_page(int c) { return (c & 3) < 3 ? 16 + 3 * (c & 3) : c < 4 ? 5 : 8; }
__host__ __device__ constexpr int wo_page(int c) { return c < 5 ? 3 + c : 11 + c; }
__host__ __device__ constexpr int o_page(int half, int pair) { return half ? (pair ? 17 + 2 * pair : 0) : 8 + 2 * pair; }
constexpr int SM_KGB = (P_R + 1) * PG;
constexpr int SM_KC = 27 * PG;
constexpr int KC_STRIDE = 648;
__host__ __device__ constexpr int kc_off(int lc) { return SM_KC + (lc & 1) * 2 * KC_STRIDE + (lc < 2 ? 3328 : 0); }
constexpr int SM_KGT = SM_KC + 3328 + 2592;
constexpr int SM_CS = SM_KGT + 2048;
constexpr int SM_RED = SM_CS + 768;
constexpr int SM_EP = SM_RED + 16;
constexpr int SM_STG = SM_RED + 32;
constexpr int SM_LN = SM_STG + 768;
__host__ __device__ constexpr int ln_off(int half) { return half ? PG + 4096 : SM_LN; }
constexpr int SM_BAR = SM_LN + 512;
constexpr int SM_TS = SM_BAR + 704;
constexpr int SM_TOTAL = SM_TS + 512;
static_assert(SM_TOTAL <= 232448 && SM_STG % 16 == 0 && SM_KGT % 16 == 0, "shared memory");

constexpr int CV_UH = 140 * 16;
__host__ __device__ constexpr int cv_u(int lc) { return (8 + 2 * lc) * PG; }
__host__ __device__ constexpr int cv_pe(int lc) { return cv_u(lc) + 4480; }
__host__ __device__ constexpr int cv_pb1(int lc, int w) { return w ? cv_u(lc) + 8960 + (w - 1) * 2048 : 7 * PG + lc * 2048; }
__host__ __device__ constexpr int cv_fa(int lc) { return cv_pb1(lc, 1) + 128; }
__host__ __device__ constexpr int cv_dump(int lc) { return cv_u(lc) + 16256; }
__host__ __device__ constexpr int cv_pb0(int lc, int w) { return lc * PG + w * 2048; }
__host__ __device__ constexpr int cv_se(int lc) { return 5 * PG + lc * 4096; }
__host__ __device__ constexpr int cv_so(int lc) { return cv_se(lc) + 2048; }
__host__ __device__ constexpr int cv_x(int half, int lc) { return (P_R + half) * PG + lc * 2048; }
constexpr int CV_ST = 22 * PG;
__host__ __device__ constexpr int cv_chan(int cta, int lc) { return 2 * cta + (lc & 1) + 256 * (lc >> 1); }

enum {
  B_XF = 0,
  B_WF = 16,
  B_OF = 24,
  B_DN = 32,
  B_XR = 48,
  B_RF = 56,
  B_PST = 58,
  B_GB = 60,
  B_TF = 62,
  B_RT = 64,
  B_RS = 66,
  B_RC = 67,
  B_WOF = 68,
  B_ZF = 69,
  B_EP = 70,
  B_KG = 71,
  B_SC = 72,
  B_LN = 73,
  B_END = 75,
  B_OST = 76,
  B_PDONE = 78,
  B_PE = 80,
  B_U = 81,
  B_U1 = 82,
  B_PUB = 83,
  B_S = 86,
  B_COUNT = 87
};

enum {
  C_CS = 0,
  C_G = 1,
  C_C = 5,
  C_F = 9,
  C_O = 21,
  C_Z = 85,
  C_R = 86,
  C_COUNT = 90
};

__device__ unsigned g_cnt[C_COUNT * 32];
__device__ __align__(1024) bf16 g_O[2 * LSEQ * DM];
__device__ __align__(1024) bf16 g_xT[4 * DM * LSEQ];
__device__ __align__(1024) float g_stats[2 * 32 * 192];
__device__ __align__(1024) uint2 g_colsum[3 * DM];
__device__ __align__(1024) uint4 g_halo[32 * 8 * 256];
__device__ __align__(1024) uint4 g_rows[2 * LSEQ];
#define TS(i) do { } while (0)
#define TSW(k) do { if ((threadIdx.x & 127) == 0) TS(16 + layer * 56 + (threadIdx.x >> 7) * 20 + (k)); } while (0)
#define TSG(k) do { } while (0)

#define RETRY(i) do { } while (0)
#define LTS(i) do { } while (0)

struct Params {
  CUtensorMap mapX, mapW3, mapXT, mapOut, mapWo;
  const bf16 *wqkv, *a_re, *a_im, *b_re, *b_im, *c_re, *c_im, *log_dt, *dskip;
};

__device__ __forceinline__ uint32_t s32(const void* p) { return (uint32_t)__cvta_generic_to_shared(p); }
__device__ __forceinline__ void mbar_init(uint32_t b, int c) { asm volatile("mbarrier.init.shared::cta.b64 [%0], %1;" ::"r"(b), "r"(c) : "memory"); }
__device__ __forceinline__ void mbar_expect(uint32_t b, int bytes) { asm volatile("mbarrier.arrive.expect_tx.shared::cta.b64 _, [%0], %1;" ::"r"(b), "r"(bytes) : "memory"); }
__device__ __forceinline__ void mbar_arrive(uint32_t b) { asm volatile("mbarrier.arrive.shared::cta.b64 _, [%0];" ::"r"(b) : "memory"); }
__device__ __forceinline__ void mbar_wait(uint32_t b, int parity) {
  asm volatile("{\n.reg .pred p;\nWAIT_LOOP:\nmbarrier.try_wait.parity.shared::cta.b64 p, [%0], %1;\n@p bra WAIT_DONE;\nbra WAIT_LOOP;\nWAIT_DONE:\n}" ::"r"(b), "r"(parity) : "memory");
}
__device__ __forceinline__ bool mbar_test(uint32_t b, int parity) {
  uint32_t ok;
  asm volatile("{\n.reg .pred p;\nmbarrier.test_wait.parity.shared::cta.b64 p, [%1], %2;\nselp.u32 %0, 1, 0, p;\n}" : "=r"(ok) : "r"(b), "r"(parity) : "memory");
  return ok != 0;
}
__device__ __forceinline__ int opaque_tid() { int v; asm volatile("mov.u32 %0, %%tid.x;" : "=r"(v)); return v; }
__device__ __forceinline__ bool elect_one() {
  uint32_t r;
  asm volatile("{\n.reg .pred p;\nelect.sync _|p, 0xffffffff;\nselp.u32 %0, 1, 0, p;\n}" : "=r"(r));
  return r != 0;
}
__device__ __forceinline__ void tma_ld(uint32_t dst, const CUtensorMap* m, int c0, int c1, uint32_t bar) {
  asm volatile("cp.async.bulk.tensor.2d.shared::cluster.global.mbarrier::complete_tx::bytes [%0], [%1, {%3, %4}], [%2];"
               ::"r"(dst), "l"(m), "r"(bar), "r"(c0), "r"(c1) : "memory");
}
__device__ __forceinline__ void tma_ld3(uint32_t dst, const CUtensorMap* m, int c0, int c1, int c2, uint32_t bar) {
  asm volatile("cp.async.bulk.tensor.3d.shared::cluster.global.mbarrier::complete_tx::bytes [%0], [%1, {%3, %4, %5}], [%2];"
               ::"r"(dst), "l"(m), "r"(bar), "r"(c0), "r"(c1), "r"(c2) : "memory");
}
__device__ __forceinline__ void tma_ld5(uint32_t dst, const CUtensorMap* m, int c0, int c4, uint32_t bar) {
  asm volatile("cp.async.bulk.tensor.5d.shared::cluster.global.mbarrier::complete_tx::bytes [%0], [%1, {%3, 0, 0, 0, %4}], [%2];"
               ::"r"(dst), "l"(m), "r"(bar), "r"(c0), "r"(c4) : "memory");
}
__device__ __forceinline__ void tma_prefetch5(const CUtensorMap* m, int c0, int c4) {
  asm volatile("cp.async.bulk.prefetch.tensor.5d.L2.global.tile [%0, {%1, 0, 0, 0, %2}];" ::"l"(m), "r"(c0), "r"(c4) : "memory");
}
__device__ __forceinline__ void tma_prefetch2(const CUtensorMap* m, int c0, int c1) {
  asm volatile("cp.async.bulk.prefetch.tensor.2d.L2.global.tile [%0, {%1, %2}];" ::"l"(m), "r"(c0), "r"(c1) : "memory");
}
__device__ __forceinline__ void tma_prefetch3(const CUtensorMap* m, int c0, int c1, int c2) {
  asm volatile("cp.async.bulk.prefetch.tensor.3d.L2.global.tile [%0, {%1, %2, %3}];" ::"l"(m), "r"(c0), "r"(c1), "r"(c2) : "memory");
}
__device__ __forceinline__ void tma_st(const CUtensorMap* m, int c0, int c1, uint32_t src) {
  asm volatile("cp.async.bulk.tensor.2d.global.shared::cta.bulk_group [%0, {%2, %3}], [%1];" ::"l"(m), "r"(src), "r"(c0), "r"(c1) : "memory");
}
__device__ __forceinline__ void bulk_ld(uint32_t dst, const void* src, int bytes, uint32_t bar) {
  asm volatile("cp.async.bulk.shared::cluster.global.mbarrier::complete_tx::bytes [%0], [%1], %2, [%3];" ::"r"(dst), "l"(src), "r"(bytes), "r"(bar) : "memory");
}
__device__ __forceinline__ void bulk_st(void* dst, uint32_t src, int bytes) {
  asm volatile("cp.async.bulk.global.shared::cta.bulk_group [%0], [%1], %2;" ::"l"(dst), "r"(src), "r"(bytes) : "memory");
}
__device__ __forceinline__ void bulk_red_add_f32(void* dst, uint32_t src, int bytes) {
  asm volatile("cp.reduce.async.bulk.global.shared::cta.bulk_group.add.f32 [%0], [%1], %2;" ::"l"(dst), "r"(src), "r"(bytes) : "memory");
}
__device__ __forceinline__ void bulk_commit() { asm volatile("cp.async.bulk.commit_group;" ::: "memory"); }
__device__ __forceinline__ void bulk_wait_all() { asm volatile("cp.async.bulk.wait_group 0;" ::: "memory"); }
__device__ __forceinline__ void fence_async_smem() { asm volatile("fence.proxy.async.shared::cta;" ::: "memory"); }
__device__ __forceinline__ void fence_async_global() { asm volatile("fence.proxy.async.global;" ::: "memory"); }
__device__ __forceinline__ void bar_sync(int id, int n) { asm volatile("bar.sync %0, %1;" ::"r"(id), "r"(n) : "memory"); }
__device__ __forceinline__ void bar_arrive(int id, int n) { asm volatile("bar.arrive %0, %1;" ::"r"(id), "r"(n) : "memory"); }
__device__ __forceinline__ bool bar_or(int id, int n, bool v) {
  uint32_t r;
  asm volatile("{\n.reg .pred p, q;\nsetp.ne.u32 q, %3, 0;\nbar.red.or.pred p, %1, %2, q;\nselp.u32 %0, 1, 0, p;\n}" : "=r"(r) : "r"(id), "r"(n), "r"((uint32_t)v) : "memory");
  return r != 0;
}
__device__ __forceinline__ void bulk_wait_read() { asm volatile("cp.async.bulk.wait_group.read 0;" ::: "memory"); }
__device__ __forceinline__ void stg128(void* p, uint4 v) { asm volatile("st.relaxed.gpu.global.v4.u32 [%0], {%1,%2,%3,%4};" ::"l"(p), "r"(v.x), "r"(v.y), "r"(v.z), "r"(v.w) : "memory"); }
constexpr uint32_t UNSET = 0xffffffffu;
constexpr int MAX_RETRY = 1 << 16;
__device__ __forceinline__ void wg_fence() { asm volatile("wgmma.fence.sync.aligned;" ::: "memory"); }
__device__ __forceinline__ void wg_commit() { asm volatile("wgmma.commit_group.sync.aligned;" ::: "memory"); }
template <int N> __device__ __forceinline__ void wg_wait() { asm volatile("wgmma.wait_group.sync.aligned %0;" ::"n"(N) : "memory"); }
__device__ __forceinline__ uint64_t mkdesc(uint32_t addr, uint32_t lbo, uint32_t sbo, int sw) {
  return (uint64_t)((addr & 0x3FFFF) >> 4) | ((uint64_t)(lbo >> 4) << 16) | ((uint64_t)(sbo >> 4) << 32) | ((uint64_t)sw << 62);
}
__device__ __forceinline__ void ldsm4(uint32_t* r, uint32_t a) {
  asm volatile("ldmatrix.sync.aligned.m8n8.x4.shared.b16 {%0,%1,%2,%3}, [%4];" : "=r"(r[0]), "=r"(r[1]), "=r"(r[2]), "=r"(r[3]) : "r"(a) : "memory");
}
__device__ __forceinline__ void ldsm4t(uint32_t* r, uint32_t a) {
  asm volatile("ldmatrix.sync.aligned.m8n8.x4.trans.shared.b16 {%0,%1,%2,%3}, [%4];" : "=r"(r[0]), "=r"(r[1]), "=r"(r[2]), "=r"(r[3]) : "r"(a) : "memory");
}
__device__ __forceinline__ void stsm4(uint32_t a, uint32_t r0, uint32_t r1, uint32_t r2, uint32_t r3) {
  asm volatile("stmatrix.sync.aligned.m8n8.x4.shared.b16 [%0], {%1,%2,%3,%4};" ::"r"(a), "r"(r0), "r"(r1), "r"(r2), "r"(r3) : "memory");
}
__device__ __forceinline__ void stsm4t(uint32_t a, uint32_t r0, uint32_t r1, uint32_t r2, uint32_t r3) {
  asm volatile("stmatrix.sync.aligned.m8n8.x4.trans.shared.b16 [%0], {%1,%2,%3,%4};" ::"r"(a), "r"(r0), "r"(r1), "r"(r2), "r"(r3) : "memory");
}
__device__ __forceinline__ uint32_t movm_t(uint32_t a) { uint32_t r; asm volatile("movmatrix.sync.aligned.m8n8.trans.b16 %0, %1;" : "=r"(r) : "r"(a)); return r; }
__device__ __forceinline__ uint32_t lds32(uint32_t a) { uint32_t v; asm volatile("ld.shared.b32 %0, [%1];" : "=r"(v) : "r"(a) : "memory"); return v; }
__device__ __forceinline__ float2 lds64f(uint32_t a) { float2 v; asm volatile("ld.shared.v2.f32 {%0,%1}, [%2];" : "=f"(v.x), "=f"(v.y) : "r"(a) : "memory"); return v; }
__device__ __forceinline__ float4 lds128f(uint32_t a) { float4 v; asm volatile("ld.shared.v4.f32 {%0,%1,%2,%3}, [%4];" : "=f"(v.x), "=f"(v.y), "=f"(v.z), "=f"(v.w) : "r"(a) : "memory"); return v; }
__device__ __forceinline__ uint4 lds128(uint32_t a) { uint4 v; asm volatile("ld.shared.v4.b32 {%0,%1,%2,%3}, [%4];" : "=r"(v.x), "=r"(v.y), "=r"(v.z), "=r"(v.w) : "r"(a) : "memory"); return v; }
__device__ __forceinline__ void sts128(uint32_t a, uint4 v) { asm volatile("st.shared.v4.b32 [%0], {%1,%2,%3,%4};" ::"r"(a), "r"(v.x), "r"(v.y), "r"(v.z), "r"(v.w) : "memory"); }
__device__ __forceinline__ void sts128f(uint32_t a, float x, float y, float z, float w) { asm volatile("st.shared.v4.f32 [%0], {%1,%2,%3,%4};" ::"r"(a), "f"(x), "f"(y), "f"(z), "f"(w) : "memory"); }
__device__ __forceinline__ void sts32f(uint32_t a, float v) { asm volatile("st.shared.f32 [%0], %1;" ::"r"(a), "f"(v) : "memory"); }
__device__ __forceinline__ void sts16(uint32_t a, uint16_t v) { asm volatile("st.shared.u16 [%0], %1;" ::"r"(a), "h"(v) : "memory"); }
__device__ __forceinline__ uint32_t lds16(uint32_t a) { uint16_t v; asm volatile("ld.shared.u16 %0, [%1];" : "=h"(v) : "r"(a) : "memory"); return v; }
__device__ __forceinline__ uint32_t packbf(float lo, float hi) { uint32_t r; asm("cvt.rn.bf16x2.f32 %0, %1, %2;" : "=r"(r) : "f"(hi), "f"(lo)); return r; }
__device__ __forceinline__ float bf_lo(uint32_t v) { return __uint_as_float(v << 16); }
__device__ __forceinline__ float bf_hi(uint32_t v) { return __uint_as_float(v & 0xffff0000u); }
__device__ __forceinline__ float ex2(float x) { float r; asm("ex2.approx.ftz.f32 %0, %1;" : "=f"(r) : "f"(x)); return r; }
__device__ __forceinline__ float rsqrt_approx(float x) { float r; asm("rsqrt.approx.ftz.f32 %0, %1;" : "=f"(r) : "f"(x)); return r; }
__device__ __forceinline__ float rcp_approx(float x) { float r; asm("rcp.approx.ftz.f32 %0, %1;" : "=f"(r) : "f"(x)); return r; }
__device__ __forceinline__ void mma_bf16(float* d, const uint32_t* a, uint32_t b0, uint32_t b1) {
  asm("mma.sync.aligned.m16n8k16.row.col.f32.bf16.bf16.f32 {%0,%1,%2,%3}, {%4,%5,%6,%7}, {%8,%9}, {%0,%1,%2,%3};"
               : "+f"(d[0]), "+f"(d[1]), "+f"(d[2]), "+f"(d[3]) : "r"(a[0]), "r"(a[1]), "r"(a[2]), "r"(a[3]), "r"(b0), "r"(b1));
}
__device__ __forceinline__ void mma_tf32(float* d, float a0, float a1, float a2, float a3, float b0, float b1) {
  asm("mma.sync.aligned.m16n8k8.row.col.f32.tf32.tf32.f32 {%0,%1,%2,%3}, {%4,%5,%6,%7}, {%8,%9}, {%0,%1,%2,%3};"
               : "+f"(d[0]), "+f"(d[1]), "+f"(d[2]), "+f"(d[3])
               : "r"(__float_as_uint(a0)), "r"(__float_as_uint(a1)), "r"(__float_as_uint(a2)), "r"(__float_as_uint(a3)),
                 "r"(__float_as_uint(b0)), "r"(__float_as_uint(b1)));
}
__device__ __forceinline__ void red_release(unsigned* p) { asm volatile("red.release.gpu.global.add.u32 [%0], 1;" ::"l"(p) : "memory"); }
__device__ __forceinline__ void red_relaxed(unsigned* p) { asm volatile("red.relaxed.gpu.global.add.u32 [%0], 1;" ::"l"(p) : "memory"); }
__device__ __forceinline__ unsigned ld_relaxed(const unsigned* p) { unsigned v; asm volatile("ld.relaxed.gpu.global.u32 %0, [%1];" : "=r"(v) : "l"(p) : "memory"); return v; }
__device__ __forceinline__ void spin_until(const unsigned* p, unsigned target) {
  int it = 0;
  while ((int)(ld_relaxed(p) - target) < 0) {
    if (++it > (1 << 23)) __trap();
  }
}
__device__ __forceinline__ void spin_hint(const unsigned* p, unsigned target) {
  spin_until(p, target);
}
__device__ __forceinline__ uint4 ldcg128(const void* p) { uint4 v; asm volatile("ld.global.cg.v4.b32 {%0,%1,%2,%3}, [%4];" : "=r"(v.x), "=r"(v.y), "=r"(v.z), "=r"(v.w) : "l"(p) : "memory"); return v; }
__device__ __forceinline__ uint4 ld_tagged(const uint4* p) { uint4 v; asm volatile("ld.relaxed.gpu.global.v4.u32 {%0,%1,%2,%3}, [%4];" : "=r"(v.x), "=r"(v.y), "=r"(v.z), "=r"(v.w) : "l"(p) : "memory"); return v; }
__device__ __forceinline__ void st_tagged(uint4* p, uint32_t a, uint32_t b, uint32_t tag) { asm volatile("st.relaxed.gpu.global.v4.u32 [%0], {%1,%2,%3,%2};" ::"l"(p), "r"(a), "r"(tag), "r"(b) : "memory"); }
__device__ __forceinline__ void st_tagged3(uint4* p, uint32_t a, uint32_t b, uint32_t c, uint32_t tag) { asm volatile("st.relaxed.gpu.global.v4.u32 [%0], {%1,%2,%3,%4};" ::"l"(p), "r"(a), "r"(b), "r"(c), "r"(tag) : "memory"); }
__device__ __forceinline__ uint4 poll_tagged(const uint4* p, uint32_t tag) {
  uint4 v = ld_tagged(p);
  int it = 0;
  while (v.y != tag || v.w != tag) {
    if (++it > (1 << 22)) __trap();
    v = ld_tagged(p);
  }
  return v;
}
__device__ __forceinline__ uint32_t hadd2(uint32_t a, uint32_t b) { uint32_t r; asm("add.rn.bf16x2 %0, %1, %2;" : "=r"(r) : "r"(a), "r"(b)); return r; }
__device__ __forceinline__ uint32_t hmul2(uint32_t a, uint32_t b) { uint32_t r; asm("mul.rn.bf16x2 %0, %1, %2;" : "=r"(r) : "r"(a), "r"(b)); return r; }

__device__ __forceinline__ uint32_t hfma2(uint32_t a, uint32_t b, uint32_t c) { uint32_t r; asm("fma.rn.bf16x2 %0, %1, %2, %3;" : "=r"(r) : "r"(a), "r"(b), "r"(c)); return r; }
__device__ __forceinline__ void sts32(uint32_t a, uint32_t v) { asm volatile("st.shared.u32 [%0], %1;" ::"r"(a), "r"(v) : "memory"); }

template <int N> __device__ __forceinline__ void acc_fence(float* a) {
#pragma unroll
  for (int i = 0; i < N; i++) asm volatile("" : "+f"(a[i]) :: "memory");
}

template<int N,int TB> __device__ __forceinline__ void wgmma_rs(float* d, const uint32_t* a, uint64_t db, int sd);
template<int N,int TA,int TB> __device__ __forceinline__ void wgmma_ss(float* d, uint64_t da, uint64_t db, int sd);
template<> __device__ __forceinline__ void wgmma_rs<64,0>(float* d, const uint32_t* a, uint64_t db, int sd) {
  asm volatile("{\n.reg .pred p;\nsetp.ne.b32 p, %37, 0;\nwgmma.mma_async.sync.aligned.m64n64k16.f32.bf16.bf16 {%0,%1,%2,%3,%4,%5,%6,%7,%8,%9,%10,%11,%12,%13,%14,%15,%16,%17,%18,%19,%20,%21,%22,%23,%24,%25,%26,%27,%28,%29,%30,%31}, {%32,%33,%34,%35}, %36, p, 1, 1, 0;\n}\n"
   : "+f"(d[0]),"+f"(d[1]),"+f"(d[2]),"+f"(d[3]),"+f"(d[4]),"+f"(d[5]),"+f"(d[6]),"+f"(d[7]),"+f"(d[8]),"+f"(d[9]),"+f"(d[10]),"+f"(d[11]),"+f"(d[12]),"+f"(d[13]),"+f"(d[14]),"+f"(d[15]),"+f"(d[16]),"+f"(d[17]),"+f"(d[18]),"+f"(d[19]),"+f"(d[20]),"+f"(d[21]),"+f"(d[22]),"+f"(d[23]),"+f"(d[24]),"+f"(d[25]),"+f"(d[26]),"+f"(d[27]),"+f"(d[28]),"+f"(d[29]),"+f"(d[30]),"+f"(d[31])
   : "r"(a[0]), "r"(a[1]), "r"(a[2]), "r"(a[3]), "l"(db), "r"(sd));
}
template<> __device__ __forceinline__ void wgmma_rs<56,0>(float* d, const uint32_t* a, uint64_t db, int sd) {
  asm volatile("{\n.reg .pred p;\nsetp.ne.b32 p, %33, 0;\nwgmma.mma_async.sync.aligned.m64n56k16.f32.bf16.bf16 {%0,%1,%2,%3,%4,%5,%6,%7,%8,%9,%10,%11,%12,%13,%14,%15,%16,%17,%18,%19,%20,%21,%22,%23,%24,%25,%26,%27}, {%28,%29,%30,%31}, %32, p, 1, 1, 0;\n}\n"
   : "+f"(d[0]),"+f"(d[1]),"+f"(d[2]),"+f"(d[3]),"+f"(d[4]),"+f"(d[5]),"+f"(d[6]),"+f"(d[7]),"+f"(d[8]),"+f"(d[9]),"+f"(d[10]),"+f"(d[11]),"+f"(d[12]),"+f"(d[13]),"+f"(d[14]),"+f"(d[15]),"+f"(d[16]),"+f"(d[17]),"+f"(d[18]),"+f"(d[19]),"+f"(d[20]),"+f"(d[21]),"+f"(d[22]),"+f"(d[23]),"+f"(d[24]),"+f"(d[25]),"+f"(d[26]),"+f"(d[27])
   : "r"(a[0]), "r"(a[1]), "r"(a[2]), "r"(a[3]), "l"(db), "r"(sd));
}
template<> __device__ __forceinline__ void wgmma_rs<48,0>(float* d, const uint32_t* a, uint64_t db, int sd) {
  asm volatile("{\n.reg .pred p;\nsetp.ne.b32 p, %29, 0;\nwgmma.mma_async.sync.aligned.m64n48k16.f32.bf16.bf16 {%0,%1,%2,%3,%4,%5,%6,%7,%8,%9,%10,%11,%12,%13,%14,%15,%16,%17,%18,%19,%20,%21,%22,%23}, {%24,%25,%26,%27}, %28, p, 1, 1, 0;\n}\n"
   : "+f"(d[0]),"+f"(d[1]),"+f"(d[2]),"+f"(d[3]),"+f"(d[4]),"+f"(d[5]),"+f"(d[6]),"+f"(d[7]),"+f"(d[8]),"+f"(d[9]),"+f"(d[10]),"+f"(d[11]),"+f"(d[12]),"+f"(d[13]),"+f"(d[14]),"+f"(d[15]),"+f"(d[16]),"+f"(d[17]),"+f"(d[18]),"+f"(d[19]),"+f"(d[20]),"+f"(d[21]),"+f"(d[22]),"+f"(d[23])
   : "r"(a[0]), "r"(a[1]), "r"(a[2]), "r"(a[3]), "l"(db), "r"(sd));
}
template<> __device__ __forceinline__ void wgmma_rs<40,0>(float* d, const uint32_t* a, uint64_t db, int sd) {
  asm volatile("{\n.reg .pred p;\nsetp.ne.b32 p, %25, 0;\nwgmma.mma_async.sync.aligned.m64n40k16.f32.bf16.bf16 {%0,%1,%2,%3,%4,%5,%6,%7,%8,%9,%10,%11,%12,%13,%14,%15,%16,%17,%18,%19}, {%20,%21,%22,%23}, %24, p, 1, 1, 0;\n}\n"
   : "+f"(d[0]),"+f"(d[1]),"+f"(d[2]),"+f"(d[3]),"+f"(d[4]),"+f"(d[5]),"+f"(d[6]),"+f"(d[7]),"+f"(d[8]),"+f"(d[9]),"+f"(d[10]),"+f"(d[11]),"+f"(d[12]),"+f"(d[13]),"+f"(d[14]),"+f"(d[15]),"+f"(d[16]),"+f"(d[17]),"+f"(d[18]),"+f"(d[19])
   : "r"(a[0]), "r"(a[1]), "r"(a[2]), "r"(a[3]), "l"(db), "r"(sd));
}
template<> __device__ __forceinline__ void wgmma_rs<32,0>(float* d, const uint32_t* a, uint64_t db, int sd) {
  asm volatile("{\n.reg .pred p;\nsetp.ne.b32 p, %21, 0;\nwgmma.mma_async.sync.aligned.m64n32k16.f32.bf16.bf16 {%0,%1,%2,%3,%4,%5,%6,%7,%8,%9,%10,%11,%12,%13,%14,%15}, {%16,%17,%18,%19}, %20, p, 1, 1, 0;\n}\n"
   : "+f"(d[0]),"+f"(d[1]),"+f"(d[2]),"+f"(d[3]),"+f"(d[4]),"+f"(d[5]),"+f"(d[6]),"+f"(d[7]),"+f"(d[8]),"+f"(d[9]),"+f"(d[10]),"+f"(d[11]),"+f"(d[12]),"+f"(d[13]),"+f"(d[14]),"+f"(d[15])
   : "r"(a[0]), "r"(a[1]), "r"(a[2]), "r"(a[3]), "l"(db), "r"(sd));
}
template<> __device__ __forceinline__ void wgmma_rs<24,0>(float* d, const uint32_t* a, uint64_t db, int sd) {
  asm volatile("{\n.reg .pred p;\nsetp.ne.b32 p, %17, 0;\nwgmma.mma_async.sync.aligned.m64n24k16.f32.bf16.bf16 {%0,%1,%2,%3,%4,%5,%6,%7,%8,%9,%10,%11}, {%12,%13,%14,%15}, %16, p, 1, 1, 0;\n}\n"
   : "+f"(d[0]),"+f"(d[1]),"+f"(d[2]),"+f"(d[3]),"+f"(d[4]),"+f"(d[5]),"+f"(d[6]),"+f"(d[7]),"+f"(d[8]),"+f"(d[9]),"+f"(d[10]),"+f"(d[11])
   : "r"(a[0]), "r"(a[1]), "r"(a[2]), "r"(a[3]), "l"(db), "r"(sd));
}
template<> __device__ __forceinline__ void wgmma_rs<16,0>(float* d, const uint32_t* a, uint64_t db, int sd) {
  asm volatile("{\n.reg .pred p;\nsetp.ne.b32 p, %13, 0;\nwgmma.mma_async.sync.aligned.m64n16k16.f32.bf16.bf16 {%0,%1,%2,%3,%4,%5,%6,%7}, {%8,%9,%10,%11}, %12, p, 1, 1, 0;\n}\n"
   : "+f"(d[0]),"+f"(d[1]),"+f"(d[2]),"+f"(d[3]),"+f"(d[4]),"+f"(d[5]),"+f"(d[6]),"+f"(d[7])
   : "r"(a[0]), "r"(a[1]), "r"(a[2]), "r"(a[3]), "l"(db), "r"(sd));
}
template<> __device__ __forceinline__ void wgmma_rs<8,0>(float* d, const uint32_t* a, uint64_t db, int sd) {
  asm volatile("{\n.reg .pred p;\nsetp.ne.b32 p, %9, 0;\nwgmma.mma_async.sync.aligned.m64n8k16.f32.bf16.bf16 {%0,%1,%2,%3}, {%4,%5,%6,%7}, %8, p, 1, 1, 0;\n}\n"
   : "+f"(d[0]),"+f"(d[1]),"+f"(d[2]),"+f"(d[3])
   : "r"(a[0]), "r"(a[1]), "r"(a[2]), "r"(a[3]), "l"(db), "r"(sd));
}
template<> __device__ __forceinline__ void wgmma_ss<64,1,0>(float* d, uint64_t da, uint64_t db, int sd) {
  asm volatile("{\n.reg .pred p;\nsetp.ne.b32 p, %34, 0;\nwgmma.mma_async.sync.aligned.m64n64k16.f32.bf16.bf16 {%0,%1,%2,%3,%4,%5,%6,%7,%8,%9,%10,%11,%12,%13,%14,%15,%16,%17,%18,%19,%20,%21,%22,%23,%24,%25,%26,%27,%28,%29,%30,%31}, %32, %33, p, 1, 1, 1, 0;\n}\n"
   : "+f"(d[0]),"+f"(d[1]),"+f"(d[2]),"+f"(d[3]),"+f"(d[4]),"+f"(d[5]),"+f"(d[6]),"+f"(d[7]),"+f"(d[8]),"+f"(d[9]),"+f"(d[10]),"+f"(d[11]),"+f"(d[12]),"+f"(d[13]),"+f"(d[14]),"+f"(d[15]),"+f"(d[16]),"+f"(d[17]),"+f"(d[18]),"+f"(d[19]),"+f"(d[20]),"+f"(d[21]),"+f"(d[22]),"+f"(d[23]),"+f"(d[24]),"+f"(d[25]),"+f"(d[26]),"+f"(d[27]),"+f"(d[28]),"+f"(d[29]),"+f"(d[30]),"+f"(d[31])
   : "l"(da), "l"(db), "r"(sd));
}
template<> __device__ __forceinline__ void wgmma_ss<64,0,1>(float* d, uint64_t da, uint64_t db, int sd) {
  asm volatile("{\n.reg .pred p;\nsetp.ne.b32 p, %34, 0;\nwgmma.mma_async.sync.aligned.m64n64k16.f32.bf16.bf16 {%0,%1,%2,%3,%4,%5,%6,%7,%8,%9,%10,%11,%12,%13,%14,%15,%16,%17,%18,%19,%20,%21,%22,%23,%24,%25,%26,%27,%28,%29,%30,%31}, %32, %33, p, 1, 1, 0, 1;\n}\n"
   : "+f"(d[0]),"+f"(d[1]),"+f"(d[2]),"+f"(d[3]),"+f"(d[4]),"+f"(d[5]),"+f"(d[6]),"+f"(d[7]),"+f"(d[8]),"+f"(d[9]),"+f"(d[10]),"+f"(d[11]),"+f"(d[12]),"+f"(d[13]),"+f"(d[14]),"+f"(d[15]),"+f"(d[16]),"+f"(d[17]),"+f"(d[18]),"+f"(d[19]),"+f"(d[20]),"+f"(d[21]),"+f"(d[22]),"+f"(d[23]),"+f"(d[24]),"+f"(d[25]),"+f"(d[26]),"+f"(d[27]),"+f"(d[28]),"+f"(d[29]),"+f"(d[30]),"+f"(d[31])
   : "l"(da), "l"(db), "r"(sd));
}
template<> __device__ __forceinline__ void wgmma_ss<192,0,1>(float* d, uint64_t da, uint64_t db, int sd) {
  asm volatile("{\n.reg .pred p;\nsetp.ne.b32 p, %98, 0;\nwgmma.mma_async.sync.aligned.m64n192k16.f32.bf16.bf16 {%0,%1,%2,%3,%4,%5,%6,%7,%8,%9,%10,%11,%12,%13,%14,%15,%16,%17,%18,%19,%20,%21,%22,%23,%24,%25,%26,%27,%28,%29,%30,%31,%32,%33,%34,%35,%36,%37,%38,%39,%40,%41,%42,%43,%44,%45,%46,%47,%48,%49,%50,%51,%52,%53,%54,%55,%56,%57,%58,%59,%60,%61,%62,%63,%64,%65,%66,%67,%68,%69,%70,%71,%72,%73,%74,%75,%76,%77,%78,%79,%80,%81,%82,%83,%84,%85,%86,%87,%88,%89,%90,%91,%92,%93,%94,%95}, %96, %97, p, 1, 1, 0, 1;\n}\n"
   : "+f"(d[0]),"+f"(d[1]),"+f"(d[2]),"+f"(d[3]),"+f"(d[4]),"+f"(d[5]),"+f"(d[6]),"+f"(d[7]),"+f"(d[8]),"+f"(d[9]),"+f"(d[10]),"+f"(d[11]),"+f"(d[12]),"+f"(d[13]),"+f"(d[14]),"+f"(d[15]),"+f"(d[16]),"+f"(d[17]),"+f"(d[18]),"+f"(d[19]),"+f"(d[20]),"+f"(d[21]),"+f"(d[22]),"+f"(d[23]),"+f"(d[24]),"+f"(d[25]),"+f"(d[26]),"+f"(d[27]),"+f"(d[28]),"+f"(d[29]),"+f"(d[30]),"+f"(d[31]),"+f"(d[32]),"+f"(d[33]),"+f"(d[34]),"+f"(d[35]),"+f"(d[36]),"+f"(d[37]),"+f"(d[38]),"+f"(d[39]),"+f"(d[40]),"+f"(d[41]),"+f"(d[42]),"+f"(d[43]),"+f"(d[44]),"+f"(d[45]),"+f"(d[46]),"+f"(d[47]),"+f"(d[48]),"+f"(d[49]),"+f"(d[50]),"+f"(d[51]),"+f"(d[52]),"+f"(d[53]),"+f"(d[54]),"+f"(d[55]),"+f"(d[56]),"+f"(d[57]),"+f"(d[58]),"+f"(d[59]),"+f"(d[60]),"+f"(d[61]),"+f"(d[62]),"+f"(d[63]),"+f"(d[64]),"+f"(d[65]),"+f"(d[66]),"+f"(d[67]),"+f"(d[68]),"+f"(d[69]),"+f"(d[70]),"+f"(d[71]),"+f"(d[72]),"+f"(d[73]),"+f"(d[74]),"+f"(d[75]),"+f"(d[76]),"+f"(d[77]),"+f"(d[78]),"+f"(d[79]),"+f"(d[80]),"+f"(d[81]),"+f"(d[82]),"+f"(d[83]),"+f"(d[84]),"+f"(d[85]),"+f"(d[86]),"+f"(d[87]),"+f"(d[88]),"+f"(d[89]),"+f"(d[90]),"+f"(d[91]),"+f"(d[92]),"+f"(d[93]),"+f"(d[94]),"+f"(d[95])
   : "l"(da), "l"(db), "r"(sd));
}
template<> __device__ __forceinline__ void wgmma_ss<192,1,1>(float* d, uint64_t da, uint64_t db, int sd) {
  asm volatile("{\n.reg .pred p;\nsetp.ne.b32 p, %98, 0;\nwgmma.mma_async.sync.aligned.m64n192k16.f32.bf16.bf16 {%0,%1,%2,%3,%4,%5,%6,%7,%8,%9,%10,%11,%12,%13,%14,%15,%16,%17,%18,%19,%20,%21,%22,%23,%24,%25,%26,%27,%28,%29,%30,%31,%32,%33,%34,%35,%36,%37,%38,%39,%40,%41,%42,%43,%44,%45,%46,%47,%48,%49,%50,%51,%52,%53,%54,%55,%56,%57,%58,%59,%60,%61,%62,%63,%64,%65,%66,%67,%68,%69,%70,%71,%72,%73,%74,%75,%76,%77,%78,%79,%80,%81,%82,%83,%84,%85,%86,%87,%88,%89,%90,%91,%92,%93,%94,%95}, %96, %97, p, 1, 1, 1, 1;\n}\n"
   : "+f"(d[0]),"+f"(d[1]),"+f"(d[2]),"+f"(d[3]),"+f"(d[4]),"+f"(d[5]),"+f"(d[6]),"+f"(d[7]),"+f"(d[8]),"+f"(d[9]),"+f"(d[10]),"+f"(d[11]),"+f"(d[12]),"+f"(d[13]),"+f"(d[14]),"+f"(d[15]),"+f"(d[16]),"+f"(d[17]),"+f"(d[18]),"+f"(d[19]),"+f"(d[20]),"+f"(d[21]),"+f"(d[22]),"+f"(d[23]),"+f"(d[24]),"+f"(d[25]),"+f"(d[26]),"+f"(d[27]),"+f"(d[28]),"+f"(d[29]),"+f"(d[30]),"+f"(d[31]),"+f"(d[32]),"+f"(d[33]),"+f"(d[34]),"+f"(d[35]),"+f"(d[36]),"+f"(d[37]),"+f"(d[38]),"+f"(d[39]),"+f"(d[40]),"+f"(d[41]),"+f"(d[42]),"+f"(d[43]),"+f"(d[44]),"+f"(d[45]),"+f"(d[46]),"+f"(d[47]),"+f"(d[48]),"+f"(d[49]),"+f"(d[50]),"+f"(d[51]),"+f"(d[52]),"+f"(d[53]),"+f"(d[54]),"+f"(d[55]),"+f"(d[56]),"+f"(d[57]),"+f"(d[58]),"+f"(d[59]),"+f"(d[60]),"+f"(d[61]),"+f"(d[62]),"+f"(d[63]),"+f"(d[64]),"+f"(d[65]),"+f"(d[66]),"+f"(d[67]),"+f"(d[68]),"+f"(d[69]),"+f"(d[70]),"+f"(d[71]),"+f"(d[72]),"+f"(d[73]),"+f"(d[74]),"+f"(d[75]),"+f"(d[76]),"+f"(d[77]),"+f"(d[78]),"+f"(d[79]),"+f"(d[80]),"+f"(d[81]),"+f"(d[82]),"+f"(d[83]),"+f"(d[84]),"+f"(d[85]),"+f"(d[86]),"+f"(d[87]),"+f"(d[88]),"+f"(d[89]),"+f"(d[90]),"+f"(d[91]),"+f"(d[92]),"+f"(d[93]),"+f"(d[94]),"+f"(d[95])
   : "l"(da), "l"(db), "r"(sd));
}

template <bool TR>
__device__ __forceinline__ void gemm_section(float* acc, float& mean0, float& mean1, float& rstd0, float& rstd1,
                                             uint32_t sb, int blk, int hg, int wg, int w, int lane) {
  constexpr int layer = TR ? 1 : 0;
  constexpr int TURN = TR ? TURN1 : TURN0;
  constexpr int LSTAT = TURN < 4 ? TURN - 1 : 3;
  const uint32_t bar = sb + SM_BAR;
  const int g = lane >> 2, t = lane & 3;
  const bool leader = (w == 0) && (lane == 0);
  const int statpos = hg < 3 ? 1 : wg ? LSTAT : TR ? 3 : 2;
  const bool copy = hg >= 3 && wg == 0;
  const int cut = wg ? TURN : 4;
  auto wait_full = [&](int c) {
    mbar_wait(bar + 8 * (B_XF + 8 * wg + c), layer);
    mbar_wait(bar + 8 * (B_WF + c), layer);
  };
  auto peek = [&](int c) {
    const bool x = mbar_test(bar + 8 * (B_XF + 8 * wg + c), layer), y = mbar_test(bar + 8 * (B_WF + c), layer);
    return x && y;
  };
  const uint64_t da0 = mkdesc(sb, TR ? 8192 : 16, 1024, 1), db0 = mkdesc(sb, 8192, 1024, 1);
  uint32_t xt = wg ? 0xfedcba98u : 0x21043210u;
  uint64_t wt = 0x0816131005161310ull;
  uint64_t da = da0 + ((xt & 15) << 9), db = db0 + (16 << 9);
  auto issue = [&](int c, int first) {
    wg_fence();
#pragma unroll
    for (int ks = 0; ks < 4; ks++) wgmma_ss<192, TR ? 1 : 0, 1>(acc, da + (TR ? ks * 128 : ks * 2), db + ks * 128, !first || ks != 0);
    wg_commit();
    xt >>= 4; wt >>= 8;
    da = da0 + ((xt & 15) << 9); db = db0 + (((uint32_t)wt & 31) << 9);
  };
  wait_full(0);
  bool ready = peek(1);
  issue(0, 1);
  TSW(0);
#pragma unroll 1
  for (int c = 1; c < cut; c++) {
    if (!ready) wait_full(c);
    issue(c, 0);
    ready = peek(c + 1);
    wg_wait<1>();
    if (leader) mbar_arrive(bar + 8 * (B_DN + 8 * wg + c - 1));
    if (wg == 1 && c == cut - 1) {
      wg_wait<0>();
      if (leader) mbar_arrive(bar + 8 * (B_DN + 8 + c));
    }
    if (c == statpos) {
      mbar_wait(bar + 8 * (copy ? B_SC : B_XF + 8 * wg + hg), layer);
      uint32_t A[16];
      const uint32_t xb = sb + (copy ? P_R : 8 * wg + hg) * PG;
#pragma unroll
      for (int ks = 0; ks < 4; ks++) {
        if (!TR) {
          const int row = 16 * w + (lane & 15), kc = 2 * ks + (lane >> 4);
          ldsm4(&A[4 * ks], xb + row * 128 + ((kc ^ (row & 7)) << 4));
        } else {
          const int k = 16 * ks + (lane & 7) + 8 * (lane >> 4), pc = 2 * w + ((lane >> 3) & 1);
          ldsm4t(&A[4 * ks], xb + k * 128 + ((pc ^ (k & 7)) << 4));
        }
      }
      float s0 = 0.f, q0 = 0.f, s1 = 0.f, q1 = 0.f;
#pragma unroll
      for (int i = 0; i < 16; i += 2) {
        const float a = bf_lo(A[i]), b = bf_hi(A[i]), c_ = bf_lo(A[i + 1]), d = bf_hi(A[i + 1]);
        s0 += a + b; q0 = fmaf(a, a, q0); q0 = fmaf(b, b, q0);
        s1 += c_ + d; q1 = fmaf(c_, c_, q1); q1 = fmaf(d, d, q1);
      }
#pragma unroll
      for (int o = 1; o <= 2; o <<= 1) {
        s0 += __shfl_xor_sync(~0u, s0, o); q0 += __shfl_xor_sync(~0u, q0, o);
        s1 += __shfl_xor_sync(~0u, s1, o); q1 += __shfl_xor_sync(~0u, q1, o);
      }
      if (t < 2)
        asm volatile("red.relaxed.gpu.global.add.v4.f32 [%0], {%1,%2,%3,%4};" ::"l"(g_rows + layer * LSEQ + blk * 64 + 16 * w + g + 8 * t),
                     "f"(t ? s1 : s0), "f"(t ? q1 : q0), "f"(1.f), "f"(0.f) : "memory");
    }
  }
  if (wg == 1) {
#pragma unroll 1
    for (int c = cut; c < 8; c++) wait_full(c);
    ready = true;
    bar_sync(5, 256);
  }
#pragma unroll 1
  for (int c = cut; c < 8; c++) {
    if (!ready) wait_full(c);
    issue(c, 0);
    if (wg == 1) {
      wg_wait<2>();
      if (leader && c >= cut + 2) mbar_arrive(bar + 8 * (B_DN + 8 + c - 2));
    } else if (c == 7) {
      bar_arrive(5, 256);
    } else {
      ready = peek(c + 1);
      wg_wait<1>();
      if (leader) mbar_arrive(bar + 8 * (B_DN + c - 1));
    }
  }
  mbar_wait(bar + 8 * (B_LN + wg), layer);
  const float4 ln = lds128f(sb + ln_off(wg) + (8 * w + g) * 16);
  mean0 = ln.x; rstd0 = ln.y; mean1 = ln.z; rstd1 = ln.w;
  wg_wait<0>();
  acc_fence<96>(acc);
  if (leader) mbar_arrive(bar + 8 * (B_DN + 8 * wg + 7));
}

__device__ __forceinline__ void attn_phase(const Params& p, uint32_t sb, int layer, int rb, int hg, int wg, int w) {
  const int lane = opaque_tid() & 31;
  const int g = lane >> 2, t = lane & 3;
  const uint32_t bar = sb + SM_BAR;
  const int blk = 16 * wg + rb;
  float acc[96];
  float2 cs[24];
  float mean0, mean1, rstd0, rstd1;
  if (layer) gemm_section<true>(acc, mean0, mean1, rstd0, rstd1, sb, blk, hg, wg, w, lane);
  else gemm_section<false>(acc, mean0, mean1, rstd0, rstd1, sb, blk, hg, wg, w, lane);
  TSW(1);
#pragma unroll
  for (int j = 8; j < 24; j++) cs[j] = lds64f(sb + SM_CS + 4 * (8 * j + 2 * t));
  const uint32_t kvx = sb + (wg ? 22 : 0) * PG;

  uint32_t kb[4][8], vb[4][8], qa[4][4];
  {
    const float nm0 = -mean0 * rstd0, nm1 = -mean1 * rstd1;
    const int st_row = 16 * w + (lane & 7) + 8 * ((lane >> 3) & 1);
    const uint32_t st_base = kvx + st_row * 256;
    const bool sender = (w == 3 && blk < 31);
    uint4* halo = &g_halo[(blk * 8 + hg) * 256 + lane];
    uint32_t r[4][2][4];
#pragma unroll
    for (int h = 0; h < 4; h++) {
#pragma unroll
      for (int kv = 0; kv < 2; kv++) {
#pragma unroll
        for (int dh = 0; dh < 2; dh++) {
          const int j = 8 + kv * 8 + 2 * h + dh;
          const float2 c2 = cs[j];
          const float v0 = fmaf(acc[4 * j + 0], rstd0, nm0 * c2.x), v1 = fmaf(acc[4 * j + 1], rstd0, nm0 * c2.y);
          const float v2 = fmaf(acc[4 * j + 2], rstd1, nm1 * c2.x), v3 = fmaf(acc[4 * j + 3], rstd1, nm1 * c2.y);
          r[h][kv][2 * dh] = packbf(v0, v1);
          r[h][kv][2 * dh + 1] = packbf(v2, v3);
        }
      }
      if (sender) {
        stg128(halo + (2 * h) * 32, make_uint4(r[h][0][0], r[h][0][2], r[h][0][1], r[h][0][3]));
        stg128(halo + (2 * h + 1) * 32, make_uint4(r[h][1][0], r[h][1][1], r[h][1][2], r[h][1][3]));
      }
    }
#pragma unroll
    for (int j = 0; j < 8; j++) cs[j] = lds64f(sb + SM_CS + 4 * (8 * j + 2 * t));
    mbar_wait(bar + 8 * (B_DN + 7), layer);
#pragma unroll
    for (int h = 0; h < 4; h++) {
#pragma unroll
      for (int kv = 0; kv < 2; kv++) {
        const int chunk = 4 * h + 2 * kv + (lane >> 4);
        if (w < 3) stsm4(st_base + (((chunk & 8) | ((chunk ^ st_row) & 7)) << 4), r[h][kv][0], r[h][kv][1], r[h][kv][2], r[h][kv][3]);
      }
      kb[h][4] = r[h][0][0]; kb[h][5] = r[h][0][2]; kb[h][6] = r[h][0][1]; kb[h][7] = r[h][0][3];
      vb[h][4] = movm_t(r[h][1][0]); vb[h][5] = movm_t(r[h][1][1]); vb[h][6] = movm_t(r[h][1][2]); vb[h][7] = movm_t(r[h][1][3]);
    }
#pragma unroll
    for (int h = 0; h < 4; h++) {
#pragma unroll
      for (int dh = 0; dh < 2; dh++) {
        const int j = 2 * h + dh;
        const float2 c2 = cs[j];
        qa[h][2 * dh] = packbf(fmaf(-mean0, c2.x, acc[4 * j + 0]), fmaf(-mean0, c2.y, acc[4 * j + 1]));
        qa[h][2 * dh + 1] = packbf(fmaf(-mean1, c2.x, acc[4 * j + 2]), fmaf(-mean1, c2.y, acc[4 * j + 3]));
      }
    }
  }
  bar_sync(2 + wg, 128);
  TSW(2);
  {
    const uint32_t prev_base = kvx + (16 * w - 16) * 256;
    const int mi = lane >> 3;
    const int r = 8 * (mi >> 1) + (lane & 7), r2 = 8 * (mi & 1) + (lane & 7);
    if (w != 0) {
#pragma unroll
      for (int h = 0; h < 4; h++) {
        const int ch = 4 * h + (mi & 1), ch2 = 4 * h + 2 + (mi >> 1);
        ldsm4(&kb[h][0], prev_base + r * 256 + (((ch & 8) | ((ch ^ r) & 7)) << 4));
        ldsm4t(&vb[h][0], prev_base + r2 * 256 + (((ch2 & 8) | ((ch2 ^ r2) & 7)) << 4));
      }
    } else if (blk > 0) {
      uint4* src = &g_halo[((blk - 1) * 8 + hg) * 256 + lane];
      uint4 hv[8];
      int it = 0;
      bool ok;
      do {
        ok = true;
#pragma unroll
        for (int i = 0; i < 8; i++) hv[i] = ld_tagged(src + i * 32);
#pragma unroll
        for (int i = 0; i < 8; i++) ok = ok && hv[i].x != UNSET;
      } while (!__all_sync(~0u, ok) && ++it < (1 << 20));
      if (layer == 0) {
#pragma unroll
        for (int i = 0; i < 2; i++) stg128(src + i * 128 + (lane >> 1) * 6, make_uint4(UNSET, UNSET, UNSET, UNSET));
      }
#pragma unroll
      for (int h = 0; h < 4; h++) {
        kb[h][0] = hv[2 * h].x; kb[h][1] = hv[2 * h].y; kb[h][2] = hv[2 * h].z; kb[h][3] = hv[2 * h].w;
        vb[h][0] = movm_t(hv[2 * h + 1].x); vb[h][1] = movm_t(hv[2 * h + 1].y);
        vb[h][2] = movm_t(hv[2 * h + 1].z); vb[h][3] = movm_t(hv[2 * h + 1].w);
      }
    } else {
#pragma unroll
      for (int h = 0; h < 4; h++)
#pragma unroll
        for (int k = 0; k < 4; k++) kb[h][k] = vb[h][k] = 0u;
    }
    TSW(3);
  }
  mbar_wait(bar + 8 * (B_DN + 15), layer);
  TSW(4);

  const bool first = (blk == 0 && w == 0);
  const int e = t - (g >> 1);
  const bool par = g & 1, epos = e >= 1;
  const uint32_t pmask = par ? 0xffff0000u : 0x0000ffffu;
  const uint32_t mB0 = epos ? pmask : 0u, mB1 = epos ? 0u : pmask;
  const float cl2 = 0.25f * 1.4426950408889634f;
  const float sc0 = rstd0 * cl2, sc1 = rstd1 * cl2;
  const float NEG = -INFINITY;
  float vA0[4], vB0[4], vA1[4], vB1[4];
#pragma unroll
  for (int h = 0; h < 4; h++) {
    float S[4][4];
#pragma unroll
    for (int j = 0; j < 4; j++) {
      S[j][0] = S[j][1] = S[j][2] = S[j][3] = 0.f;
      mma_bf16(S[j], qa[h], kb[h][2 * j], kb[h][2 * j + 1]);
    }
    vA0[h] = par ? S[1][1] : S[1][0];
    vB0[h] = epos ? (par ? S[0][1] : S[0][0]) : (par ? S[2][1] : S[2][0]);
    vA1[h] = par ? S[2][3] : S[2][2];
    vB1[h] = epos ? (par ? S[1][3] : S[1][2]) : (par ? S[3][3] : S[3][2]);
    if (first) { vA0[h] = NEG; if (epos) { vB0[h] = NEG; vB1[h] = NEG; } }
  }
  float m0[4], m1[4];
#pragma unroll
  for (int h = 0; h < 4; h++) { m0[h] = fmaxf(vA0[h], vB0[h]); m1[h] = fmaxf(vA1[h], vB1[h]); }
#pragma unroll
  for (int o = 1; o <= 2; o <<= 1) {
#pragma unroll
    for (int h = 0; h < 4; h++) {
      m0[h] = fmaxf(m0[h], __shfl_xor_sync(~0u, m0[h], o));
      m1[h] = fmaxf(m1[h], __shfl_xor_sync(~0u, m1[h], o));
    }
  }
  float O0[4][4], O1[4][4], Z[4][4];
#pragma unroll
  for (int h = 0; h < 4; h++) {
    const float mm0 = -m0[h] * sc0, mm1 = -m1[h] * sc1;
    const float pA0 = ex2(fmaf(vA0[h], sc0, mm0)), pB0 = ex2(fmaf(vB0[h], sc0, mm0));
    const float pA1 = ex2(fmaf(vA1[h], sc1, mm1)), pB1 = ex2(fmaf(vB1[h], sc1, mm1));
    const uint32_t hA0 = packbf(pA0, pA0), hB0 = packbf(pB0, pB0), hA1 = packbf(pA1, pA1), hB1 = packbf(pB1, pB1);
    const uint32_t P0[4] = {hB0 & mB0, 0u, hA0 & pmask, hB1 & mB0};
    const uint32_t P1[4] = {hB0 & mB1, hA1 & pmask, 0u, hB1 & mB1};
#pragma unroll
    for (int k = 0; k < 4; k++) O0[h][k] = O1[h][k] = Z[h][k] = 0.f;
    mma_bf16(O0[h], P0, vb[h][0], vb[h][1]); mma_bf16(O1[h], P0, vb[h][2], vb[h][3]); mma_bf16(Z[h], P0, 0x3f803f80u, 0x3f803f80u);
    mma_bf16(O0[h], P1, vb[h][4], vb[h][5]); mma_bf16(O1[h], P1, vb[h][6], vb[h][7]); mma_bf16(Z[h], P1, 0x3f803f80u, 0x3f803f80u);
  }
  if (lane == 0) mbar_arrive(bar + 8 * (B_OST + wg));
  uint4* op = (uint4*)g_O + ((layer * 32 + blk) * 8 + hg) * 512 + 64 * t + 16 * w + g;
#pragma unroll
  for (int h = 0; h < 4; h += 2) {
    const float i0 = rcp_approx(Z[h][0]), i1 = rcp_approx(Z[h][2]), j0 = rcp_approx(Z[h + 1][0]), j1 = rcp_approx(Z[h + 1][2]);
    stg128(op + 128 * h, make_uint4(packbf(O0[h][0] * i0, O0[h][1] * i0), packbf(O1[h][0] * i0, O1[h][1] * i0),
                                   packbf(O0[h + 1][0] * j0, O0[h + 1][1] * j0), packbf(O1[h + 1][0] * j0, O1[h + 1][1] * j0)));
    stg128(op + 128 * h + 8, make_uint4(packbf(O0[h][2] * i1, O0[h][3] * i1), packbf(O1[h][2] * i1, O1[h][3] * i1),
                                            packbf(O0[h + 1][2] * j1, O0[h + 1][3] * j1), packbf(O1[h + 1][2] * j1, O1[h + 1][3] * j1)));
  }
  TSW(5);
  __syncwarp();
  if (lane == 0) red_relaxed(&g_cnt[(C_O + layer * 32 + blk) * 32]);
  TSW(6);
}

__device__ __forceinline__ void proj_phase(const Params& p, uint32_t sb, int layer, int rb, int q, int& rtp) {
  const int lane = opaque_tid() & 31;
  const int wg = __shfl_sync(~0u, opaque_tid() >> 7, 0), w = __shfl_sync(~0u, (opaque_tid() >> 5) & 3, 0);
  const bool TR = layer != 0;
  const int t = lane & 3;
  const uint32_t bar = sb + SM_BAR;
  const uint32_t rbx = sb + (P_R + wg) * PG;
  const uint32_t rsrc = sb + (wg ? 2 : P_R) * PG;
  const int blk = 16 * wg + rb;
  mbar_wait(bar + 8 * (B_RF + wg), layer);
  if (layer) mbar_wait(bar + 8 * B_RS, 0);
  mbar_wait(bar + 8 * B_WOF, layer);
  fence_async_global();
  const uint32_t stg = sb + (wg ? SM_KGT : SM_STG);
  bool clean = false;
#pragma unroll 1
  for (int attempt = 0; attempt < MAX_RETRY; attempt++) {
  uint32_t res[16];
  if (!TR) {
#pragma unroll
    for (int j = 0; j < 8; j += 2) {
      const int mi = lane >> 3;
      const int row = 16 * w + (lane & 7) + 8 * (mi & 1), ch = j + (mi >> 1);
      ldsm4(&res[2 * j], rsrc + row * 128 + ((ch ^ (row & 7)) << 4));
    }
  } else {
#pragma unroll
    for (int j = 0; j < 8; j += 2) {
      const int mi = lane >> 3;
      const int line = 8 * (j + (mi >> 1)) + (lane & 7), pc = 2 * w + (mi & 1);
      ldsm4t(&res[2 * j], rsrc + line * 128 + ((pc ^ (line & 7)) << 4));
    }
  }
  float acc[32];
#pragma unroll
  for (int j = 0; j < 16; j++) { acc[2 * j] = bf_lo(res[j]); acc[2 * j + 1] = bf_hi(res[j]); }
  acc_fence<32>(acc);
  if (wg) mbar_wait(bar + 8 * B_PST, layer);
  const int wg2 = __shfl_sync(~0u, opaque_tid() >> 7, 0);
  const uint64_t da0 = mkdesc(sb, 1024, 128, 0), db0 = mkdesc(sb, 8192, 1024, 1);
#pragma unroll
  for (int c = 0; c < 4; c++) {
    mbar_wait(bar + 8 * (B_OF + 4 * wg + c), layer);
    if (c == 0) TSW(7);
    const uint64_t da = da0 + (uint32_t)(o_page(wg2, c) * 512);
    wg_fence();
#pragma unroll
    for (int ks = 0; ks < 8; ks++) wgmma_ss<64, 0, 1>(acc, da + ks * 128, db0 + wo_page(2 * c + (ks >> 2)) * 512 + (ks & 3) * 128, 1);
    wg_commit();
  }
  if (wg) mbar_wait(bar + 8 * B_KG, 0);
  wg_wait<0>();
  acc_fence<32>(acc);
  TSW(8);
  if (!clean) {
    const float chk = acc[0] + acc[2];
    clean = __all_sync(~0u, chk == chk);
    if (clean && lane == 0) mbar_arrive(bar + 8 * (B_PDONE + wg));
  }
  float s0 = 0.f, q0 = 0.f, s1 = 0.f, q1 = 0.f;
  uint32_t o[16];
#pragma unroll
  for (int j = 0; j < 8; j++) {
    const float a = acc[4 * j], b = acc[4 * j + 1], c = acc[4 * j + 2], d = acc[4 * j + 3];
    o[2 * j] = packbf(a, b);
    o[2 * j + 1] = packbf(c, d);
    s0 += a + b; q0 = fmaf(a, a, q0); q0 = fmaf(b, b, q0);
    s1 += c + d; q1 = fmaf(c, c, q1); q1 = fmaf(d, d, q1);
  }
#pragma unroll
  for (int j = 0; j < 8; j += 2) {
    const int mi = lane >> 3;
    const int line = 8 * (j + (mi >> 1)) + (lane & 7), pc = 2 * w + (mi & 1);
    stsm4t(rbx + line * 128 + ((pc ^ (line & 7)) << 4), o[2 * j], o[2 * j + 1], o[2 * j + 2], o[2 * j + 3]);
  }
#pragma unroll
  for (int o2 = 1; o2 <= 2; o2 <<= 1) {
    s0 += __shfl_xor_sync(~0u, s0, o2); q0 += __shfl_xor_sync(~0u, q0, o2);
    s1 += __shfl_xor_sync(~0u, s1, o2); q1 += __shfl_xor_sync(~0u, q1, o2);
  }
  {
    const int i = 2 * (lane >> 2) + (t & 1), k = (i * 11) >> 5;
    const float v = (t == 0) ? s0 : (t == 1) ? q0 : (t == 2) ? s1 : q1;
    sts32f(stg + k * 128 + (2 * w + (t >> 1)) * 16 + (i - 3 * k) * 4, v);
  }
  TSW(9);
  fence_async_smem();
  if (!bar_or(2 + wg, 128, !clean)) break;
  bool unset = false;
#pragma unroll
  for (int i = 0; i < 4; i++) unset |= lds32(sb + o_page(wg, i) * PG + (32 * w + lane) * 128) == UNSET;
  if (!bar_or(2 + wg, 128, unset)) break;
  if (w == 0 && elect_one()) {
    fence_async_smem();
    mbar_expect(bar + 8 * (B_RT + wg), 9 * PG);
    if (layer == 0) tma_ld(rsrc, &p.mapX, q * 64, blk * 64, bar + 8 * (B_RT + wg));
    else tma_ld(rsrc, &p.mapXT, blk * 64, DM + q * 64, bar + 8 * (B_RT + wg));
#pragma unroll 1
    for (int c = 0; c < 4; c++) bulk_ld(sb + o_page(wg, c) * PG, g_O + ((layer * 32 + blk) * 4 + c) * PG, 2 * PG, bar + 8 * (B_RT + wg));
  }
  mbar_wait(bar + 8 * (B_RT + wg), rtp);
  rtp ^= 1;
  RETRY(0);
  }
  if (!clean && lane == 0) mbar_arrive(bar + 8 * (B_PDONE + wg));
  if (w == 0 && elect_one()) {
    tma_st(&p.mapXT, blk * 64, (2 * layer) * DM + q * 64, rbx);
    bulk_red_add_f32(g_stats + (layer * 32 + blk) * 192, stg, 768);
    bulk_commit();
    red_relaxed(&g_cnt[(C_G + 2 * layer + wg) * 32]);
  }
  TSW(10);
}

__device__ __forceinline__ void conv_load(uint32_t* A, uint32_t pe) {
#pragma unroll
  for (int m = 0; m < 17; m++) {
    A[4 * m + 2] = lds32(pe + 4 * (64 * m - 8));
    A[4 * m + 0] = lds32(pe + 4 * (64 * m));
    A[4 * m + 1] = lds32(pe + 4 * (64 * m + 8));
    asm volatile("mov.b32 %0, %1;" : "=r"(A[4 * m + 3]) : "r"(A[4 * m + 0]));
  }
}
template <int M> __device__ __forceinline__ void conv_tri(float* acc, const uint32_t* A, uint64_t d) {
  if constexpr (M < 16) {
    wgmma_rs<64 - 8 * (M / 2), 0>(acc, A + 4 * M, d + (uint64_t)(64 + 4 * M), M != 0);
    conv_tri<M + 1>(acc, A, d);
  }
}
__device__ __forceinline__ void conv_mma0(float* acc, const uint32_t* A, uint64_t d) {
  wg_fence();
  conv_tri<0>(acc, A, d);
  wg_commit();
}
__device__ __forceinline__ void conv_mma1_early(float* acc, const uint32_t* A, uint64_t d, uint64_t ds, uint64_t df) {
  wg_fence();
  wgmma_rs<64, 0>(acc, A + 64, d + 64, 0);
  wgmma_ss<64, 1, 0>(acc, ds, df, 1);
  wgmma_ss<64, 1, 0>(acc, ds + 128, df + 128, 1);
}
__device__ __forceinline__ void conv_mma1(float* acc, const uint32_t* A, uint64_t d) {
#pragma unroll
  for (int m = 0; m < 16; m++) wgmma_rs<64, 0>(acc, A + 4 * m, d + (uint64_t)(4 * m), 1);
  wg_commit();
}
__device__ __forceinline__ void conv_store(float* acc, uint32_t pb, uint32_t over, int w) {
  acc_fence<32>(acc);
  const int l = opaque_tid() & 31, mt = l >> 3;
  int c = 2 * (63 - 8 * (mt >> 1) - (l & 7) + w) + (mt & 1);
  c ^= (c >> 3) & 1;
  const uint32_t a0 = pb + c * 16;
#pragma unroll
  for (int j = 0; j < 8; j += 2)
    stsm4t(j == 0 ? (c < 128 ? a0 : over + (c - 128) * 16) : a0 - 256 * j, packbf(acc[4 * j], acc[4 * j + 1]), packbf(acc[4 * j + 2], acc[4 * j + 3]),
           packbf(acc[4 * j + 4], acc[4 * j + 5]), packbf(acc[4 * j + 6], acc[4 * j + 7]));
}
__device__ __forceinline__ void conv_sums(uint32_t sb, int lc, int ht) {
  const int m = ht - 1;
  uint4 v[2][3];
#pragma unroll
  for (int c = 0; c < 2; c++)
#pragma unroll
    for (int k = 0; k < 3; k++) {
      const int mm = m - 1 + k;
      v[c][k] = lds128(sb + cv_u(lc + c) + (mm >= 0 ? (mm & 1) * CV_UH + (127 - (mm >> 1)) * 16 : 128 * 16));
    }
  const int ce = m + 2, co = m + 1;
#pragma unroll
  for (int c = 0; c < 2; c++) {
    const uint32_t x[8] = {v[c][0].z, v[c][0].w, v[c][1].x, v[c][1].y, v[c][1].z, v[c][1].w, v[c][2].x, v[c][2].y};
    float pv[16];
#pragma unroll
    for (int k = 0; k < 8; k++) { pv[2 * k] = bf_lo(x[k]); pv[2 * k + 1] = bf_hi(x[k]); }
    float t2[15], t4[13], s9[8], s7[8];
#pragma unroll
    for (int i = 0; i < 15; i++) t2[i] = pv[i] + pv[i + 1];
#pragma unroll
    for (int i = 0; i < 13; i++) t4[i] = t2[i] + t2[i + 2];
#pragma unroll
    for (int i = 0; i < 8; i++) {
      s9[i] = (t4[i] + t4[i + 4]) + pv[i + 8];
      s7[i] = (t4[i + 1] + t2[i + 5]) + pv[i + 7];
    }
    const uint4 e4 = make_uint4(packbf(s9[0], s9[1]), packbf(s9[2], s9[3]), packbf(s9[4], s9[5]), packbf(s9[6], s9[7]));
    if (ce < 128) sts128(sb + cv_se(lc + c) + ((ce ^ ((ce >> 3) & 7)) << 4), e4);
    else sts128(sb + cv_se(lc + c), make_uint4(0, 0, 0, 0));
    sts128(sb + cv_so(lc + c) + ((co ^ ((co >> 3) & 7)) << 4),
           make_uint4(packbf(s7[0], s7[1]), packbf(s7[2], s7[3]), packbf(s7[4], s7[5]), packbf(s7[6], s7[7])));
  }
}

template <int HALF, int NCH, int STEP = 1>
__device__ __forceinline__ void conv_epi(uint32_t sb, bf16* out, int lc, int c) {
  uint4 v[NCH][4], xr[NCH];
  const uint32_t sw = (c ^ ((c >> 3) & 1)) * 16;
#pragma unroll
  for (int u = 0; u < NCH; u++) {
#pragma unroll
    for (int k = 0; k < 4; k++) v[u][k] = lds128(sb + (HALF ? cv_pb1(lc + STEP * u, k) : cv_pb0(lc + STEP * u, k)) + sw);
    xr[u] = lds128(sb + cv_x(HALF, lc + STEP * u) + c * 16);
  }
#pragma unroll
  for (int u = 0; u < NCH; u++) {
    uint4 o;
    o.x = hadd2(xr[u].x, hadd2(hadd2(v[u][0].x, v[u][1].x), hadd2(v[u][2].x, v[u][3].x)));
    o.y = hadd2(xr[u].y, hadd2(hadd2(v[u][0].y, v[u][1].y), hadd2(v[u][2].y, v[u][3].y)));
    o.z = hadd2(xr[u].z, hadd2(hadd2(v[u][0].z, v[u][1].z), hadd2(v[u][2].z, v[u][3].z)));
    o.w = hadd2(xr[u].w, hadd2(hadd2(v[u][0].w, v[u][1].w), hadd2(v[u][2].w, v[u][3].w)));
    stg128(out + cv_chan(0, lc + STEP * u) * LSEQ + HALF * 1024 + c * 8, o);
  }
}

__device__ __forceinline__ bool prep_valid(const uint4 (&st)[6], const uint4 (&xr)[4]) {
  const uint32_t n = __float_as_uint(8.f);
  return st[0].w == n && st[1].w == n && st[2].w == n && st[3].w == n && st[4].w == n && (st[5].w | st[5].y | st[5].z) == n &&
         xr[0].x != UNSET && xr[1].x != UNSET && xr[2].x != UNSET && xr[3].x != UNSET;
}
template <int HALF>
__device__ __forceinline__ void conv_prep(uint32_t sb, int layer, int cta, int i) {
  uint4 st[6], xr[4];
  const uint4* sp = (const uint4*)g_stats + (layer * 32 + HALF * 16 + (i >> 3)) * 48 + (i & 7);
  const uint4* xp = (const uint4*)g_xT + (2 * layer * DM + 2 * cta) * (LSEQ / 8) + HALF * 128 + i;
  auto fetch = [&]() {
#pragma unroll
    for (int k = 0; k < 6; k++) st[k] = ld_tagged(sp + 8 * k);
#pragma unroll
    for (int k = 0; k < 4; k++) xr[k] = ld_tagged(xp + cv_chan(0, k) * (LSEQ / 8));
  };
  if (HALF) {
#pragma unroll
    for (int k = 0; k < 6; k++) st[k] = lds128(sb + CV_ST + (i >> 3) * 768 + k * 128 + (i & 7) * 16);
#pragma unroll
    for (int k = 0; k < 4; k++) xr[k] = lds128(sb + cv_x(1, k) + i * 16);
  } else {
    fetch();
  }
  int it = 0;
  while (!__all_sync(~0u, prep_valid(st, xr)) && ++it < MAX_RETRY) { fetch(); RETRY(1); }
  if (!HALF || it) {
#pragma unroll
    for (int k = 0; k < 4; k++) sts128(sb + cv_x(HALF, k) + i * 16, xr[k]);
  }
  const uint32_t v[16] = {st[0].x, st[0].y, st[0].z, st[1].x, st[1].y, st[1].z, st[2].x, st[2].y, st[2].z, st[3].x, st[3].y, st[3].z, st[4].x, st[4].y, st[4].z, st[5].x};
  uint32_t rs[4], nm[4];
#pragma unroll
  for (int k = 0; k < 4; k++) {
    const float m0 = __uint_as_float(v[4 * k]) * (-1.f / DM), m1 = __uint_as_float(v[4 * k + 2]) * (-1.f / DM);
    const float r0 = rsqrt_approx(fmaxf(fmaf(__uint_as_float(v[4 * k + 1]), 1.f / DM, -m0 * m0), 0.f) + 1e-5f);
    const float r1 = rsqrt_approx(fmaxf(fmaf(__uint_as_float(v[4 * k + 3]), 1.f / DM, -m1 * m1), 0.f) + 1e-5f);
    rs[k] = packbf(r0, r1);
    nm[k] = packbf(m0 * bf_lo(rs[k]), m1 * bf_hi(rs[k]));
  }
  const uint32_t ud = sb + (i & 1) * CV_UH + (127 - 64 * HALF - (i >> 1)) * 16;
#pragma unroll
  for (int k = 0; k < 4; k++)
    sts128(ud + cv_u(k), make_uint4(hfma2(xr[k].x, rs[0], nm[0]), hfma2(xr[k].y, rs[1], nm[1]), hfma2(xr[k].z, rs[2], nm[2]), hfma2(xr[k].w, rs[3], nm[3])));
  fence_async_smem();
}

#define AGATE 1
#define EARLY1 1
#define PP0 1
__device__ __forceinline__ void conv_phase(const Params& p, uint32_t sb, int layer, int cta) {
  const int tid = opaque_tid();
  const int wg = __shfl_sync(~0u, tid >> 7, 0), w = __shfl_sync(~0u, (tid >> 5) & 3, 0);
  const uint32_t bar = sb + SM_BAR;
  constexpr int CH2 = 4 * PG;
  bf16* xout = g_xT + ((2 * layer + 1) * DM + 2 * cta) * LSEQ;
  uint32_t A0[68], A1[68];
  float acc[32];
  const uint32_t pe = sb + cv_pe(wg) + 4 * (16 + 16 * w + ((tid & 31) >> 2) - 2 * (tid & 3));
  auto staged = [&]() {
    if (w == 0) {
      bulk_wait_read();
      __syncwarp();
      if (elect_one()) mbar_arrive(bar + 8 * (B_PST + wg));
    }
  };
  if (wg == 0) staged();
  mbar_wait(bar + 8 * (B_PDONE + 1), layer);
  mbar_wait(bar + 8 * B_PE, layer);
  conv_load(A0, pe);
  if (wg == 1) staged();
  conv_load(A1, pe + CH2);
  TSW(19);
  const uint64_t d0 = mkdesc(sb + cv_u(wg), CV_UH, 128, 0), d1 = d0 + (CH2 >> 4);
  mbar_wait(bar + 8 * B_U, layer);
  TSW(12);
  if (wg == 1) bar_sync(5, 256);
  conv_mma0(acc, A0, d0);
  if (wg == 0) bar_arrive(5, 256);
  mbar_wait(bar + 8 * (B_PDONE + 1), layer);
  {
    const int l = opaque_tid() & 31;
    if ((l & 15) < 2 * w) sts128(sb + cv_pb0(wg + 2 * (l >> 4), w) + (l & 15) * 16, make_uint4(0, 0, 0, 0));
  }
  wg_wait<0>();
  conv_store(acc, sb + cv_pb0(wg, w), sb + cv_pb1(wg, w), w);
  conv_mma0(acc, A1, d1);
  wg_wait<0>();
  conv_store(acc, sb + cv_pb0(2 + wg, w), sb + cv_pb1(2 + wg, w), w);
  TSW(13);
  bar_sync(2 + wg, 128);
  conv_epi<0, 2, 2>(sb, xout, wg, opaque_tid() & 127);
  TSW(14);
  mbar_arrive(bar + 8 * B_PUB);
  const uint64_t ds = mkdesc(sb + cv_se(wg), 8192, 1024, 1), df = mkdesc(sb + cv_fa(wg), 512, 128, 0);
  mbar_wait(bar + 8 * B_S, layer);
  conv_mma1_early(acc, A0, d0, ds, df);
  wg_commit();
  if (wg == 0) mbar_wait(bar + 8 * B_U1, layer);
  else bar_sync(6, 256);
  TSW(15);
  wg_fence();
  conv_mma1(acc, A0, d0);
  if (wg == 0) bar_arrive(6, 256);
  wg_wait<0>();
  conv_store(acc, sb + cv_pb1(wg, w), sb + cv_dump(wg), w);
  TSW(16);
  bar_sync(2 + wg, 128);
  conv_epi<1, 1>(sb, xout, wg, opaque_tid() & 127);
  mbar_arrive(bar + 8 * (B_PUB + 1));
  conv_mma1_early(acc, A1, d1, ds + 512, df + (CH2 >> 4));
  conv_mma1(acc, A1, d1);
  wg_wait<0>();
  conv_store(acc, sb + cv_pb1(2 + wg, w), sb + cv_dump(2 + wg), w);
  TSW(17);
  bar_sync(2 + wg, 128);
  conv_epi<1, 1>(sb, xout, 2 + wg, opaque_tid() & 127);
  mbar_arrive(bar + 8 * (B_PUB + 2));
  TSW(18);
}

__device__ __forceinline__ void final_phase(const Params& p, uint32_t sb, int cta, int wg, int w, int rtp) {
  const int lane = opaque_tid() & 31;
  const uint32_t bar = sb + SM_BAR;
  mbar_wait(bar + 8 * (B_TF + wg), 0);
  if (threadIdx.x == 128) TS(8);
  const uint32_t src = sb + (16 + wg) * PG, dst = src + 2 * PG;
  const int mi = lane >> 3;
#pragma unroll 1
  for (int attempt = 0; attempt < MAX_RETRY; attempt++) {
    uint32_t m = 0;
#pragma unroll
    for (int j = 0; j < 8; j += 2) {
      uint32_t r[4];
      const int line = 8 * (j + (mi >> 1)) + (lane & 7), pc = 2 * w + (mi & 1);
      ldsm4t(r, src + line * 128 + ((pc ^ (line & 7)) << 4));
      const int row = 16 * w + (lane & 7) + 8 * (mi & 1), ch = j + (mi >> 1);
      stsm4(dst + row * 128 + ((ch ^ (row & 7)) << 4), r[0], r[1], r[2], r[3]);
#pragma unroll
      for (int k = 0; k < 4; k++) asm("max.u16x2 %0, %0, %1;" : "+r"(m) : "r"(r[k]));
    }
    fence_async_smem();
    if (!bar_or(2 + wg, 128, m >= 0xffff0000u || (m & 0xffffu) == 0xffffu)) break;
    if (w == 0 && elect_one()) {
      mbar_expect(bar + 8 * (B_RT + wg), PG);
      tma_ld(src, &p.mapXT, (16 * wg + (cta & 15)) * 64, 3 * DM + (cta >> 4) * 64, bar + 8 * (B_RT + wg));
    }
    mbar_wait(bar + 8 * (B_RT + wg), (rtp + attempt) & 1);
    RETRY(2);
  }
  if (w == 0 && elect_one()) {
    tma_st(&p.mapOut, (cta >> 4) * 64, (16 * wg + (cta & 15)) * 64, dst);
    bulk_commit();
    asm volatile("cp.async.bulk.wait_group.read 0;" ::: "memory");
    if (threadIdx.x == 128) TS(9);
    if (threadIdx.x == 128) LTS(1);
  }
}

struct cplx { float r, i; };
__device__ __forceinline__ cplx cmul(cplx a, cplx b) { return {fmaf(a.r, b.r, -a.i * b.i), fmaf(a.r, b.i, a.i * b.r)}; }
__device__ __forceinline__ cplx csqr(cplx a) { return {fmaf(a.r, a.r, -a.i * a.i), (a.r + a.r) * a.i}; }
__device__ __forceinline__ cplx cexp_l(float ar2, float ai, float l) {
  const float m = ex2(ar2 * l);
  const float x = ai * l;
  return {m * __cosf(x), m * __sinf(x)};
}

__device__ __forceinline__ void colsum_cta(const Params& p, uint32_t sb, int j, int tid) {
  const uint32_t bar = sb + SM_BAR;
  auto ld = [&](int i) {
    mbar_expect(bar + 8 * i, 3 * PG);
    tma_ld3(sb + (i & 7) * 3 * PG, &p.mapW3, (2 * j + (i & 1)) * 64, (i >> 1) * 64, 0, bar + 8 * i);
  };
  if (tid == 384) {
#pragma unroll
    for (int i = 0; i < 24; i++) mbar_init(bar + 8 * i, i < 16 ? 1 : 12);
    asm volatile("fence.mbarrier_init.release.cluster;" ::: "memory");
    fence_async_smem();
#pragma unroll 1
    for (int i = 0; i < 8; i++) ld(i);
  }
  const unsigned ep = ld_relaxed(&g_cnt[C_CS * 32]);
  bar_sync(0, NTHREADS);
  if (tid == 384) {
#pragma unroll 1
    for (int i = 8; i < 16; i++) { mbar_wait(bar + 8 * (8 + i), 0); fence_async_smem(); ld(i); }
  }
  if (tid < 384) {
    const int lane = tid & 31, cc = tid & 7, r0 = (tid >> 3) & 15, part = tid >> 7;
    const uint32_t id = ((lane >> 2) == 2 * (lane & 3) ? 0x3f80u : 0u) | ((lane >> 2) == 2 * (lane & 3) + 1 ? 0x3f800000u : 0u);
    const uint32_t src = sb + part * PG + r0 * 128 + ((cc ^ (r0 & 7)) << 4);
    float s[2][2][4];
#pragma unroll
    for (int i = 0; i < 16; i++) s[i >> 3][(i >> 2) & 1][i & 3] = 0.f;
#pragma unroll 1
    for (int i2 = 0; i2 < 16; i2 += 2) {
#pragma unroll
      for (int h = 0; h < 2; h++) {
        const int i = i2 + h;
        mbar_wait(bar + 8 * i, 0);
        uint4 v[4];
#pragma unroll
        for (int k = 0; k < 4; k++) v[k] = lds128(src + (i & 7) * 3 * PG + k * 2048);
#pragma unroll
        for (int k = 0; k < 4; k++) {
          const uint32_t a[4] = {v[k].x, v[k].y, v[k].z, v[k].w};
          mma_bf16(s[h][0], a, id, 0u);
          mma_bf16(s[h][1], a, 0u, id);
        }
        __syncwarp();
        if (i < 8 && lane == 0) mbar_arrive(bar + 8 * (16 + i));
      }
    }
    const uint32_t red = sb + 24 * PG;
#pragma unroll
    for (int h = 0; h < 2; h++)
#pragma unroll
      for (int k = 0; k < 2; k++) sts128f(red + (r0 * 384 + h * 192 + part * 64 + cc * 8 + k * 4) * 4, s[h][k][0], s[h][k][1], s[h][k][2], s[h][k][3]);
    bar_sync(1, 384);
    float tot = 0.f;
#pragma unroll
    for (int k = 0; k < 16; k++) tot += __uint_as_float(lds32(red + (k * 384 + tid) * 4));
    asm volatile("st.relaxed.gpu.global.v2.u32 [%0], {%1,%2};" ::"l"(&g_colsum[j * 384 + tid]), "r"(__float_as_uint(tot)), "r"(ep / NCTA + 1) : "memory");
    const uint4 u = make_uint4(UNSET, UNSET, UNSET, UNSET);
    if (tid < 256) {
#pragma unroll 4
      for (int i = 0; i < 8; i++) stg128((uint4*)g_xT + (DM + 256 + j * 64 + i * 8 + (tid >> 5)) * 256 + 128 + ((tid & 31) >> 1) * 8 + (tid & 1), u);
#pragma unroll 1
      for (int s = 0; s < 4; s++) {
        const int n = s ? 32 : 16;
        uint4* dst = (s == 1 ? (uint4*)g_O + 131072 : (uint4*)g_xT + (s + !s) * 131072) + j * n * 1024 + (tid >> 1) * 8 + (tid & 1);
#pragma unroll 4
        for (int i = 0; i < n; i++) stg128(dst + i * 1024, u);
        bar_sync(2, 256);
        if (tid == 32 * s) red_release(&g_cnt[(C_R + s) * 32]);
      }
    }
  }
}

#define KB 4
#define KW 2
struct ModeIn { uint32_t ar, ai, br, bi, cr, ci; bf16 logdt; };
__device__ __forceinline__ ModeIn load_modes(const Params& p, int d, int m) {
  const int i = d * 64 + m;
  return {((const uint32_t*)p.a_re)[i], ((const uint32_t*)p.a_im)[i], ((const uint32_t*)p.b_re)[i], ((const uint32_t*)p.b_im)[i],
          ((const uint32_t*)p.c_re)[i], ((const uint32_t*)p.c_im)[i], p.log_dt[d]};
}
__device__ __forceinline__ float4 lds128f_nv(uint32_t a) { float4 v; asm("ld.shared.v4.f32 {%0,%1,%2,%3}, [%4];" : "=f"(v.x), "=f"(v.y), "=f"(v.z), "=f"(v.w) : "r"(a)); return v; }
__device__ __forceinline__ void kernel_gen(const Params& p, uint32_t sb, int cta, int ht, ModeIn in, const ModeIn& in1) {
  const uint32_t bst = sb + SM_KGB + ((ht & 63) >> 2) * 144 + (ht & 3) * 4 + (ht >> 6) * 16;
  const uint64_t db = mkdesc(sb + SM_KGB, 144, 2304, 0);
  const float e0 = (float)(8 * (((ht & 32) >> 1) + ((ht & 31) >> 2)));
  float T[20];
#pragma unroll
  for (int i = 0; i < 20; i++) T[i] = 0.f;
  float k0 = 0.f;
#pragma unroll 1
  for (int pass = 0; pass < 4; pass++) {
    {
      const int sh = (pass & 1) ? 0 : 16;
      auto val = [&](uint32_t v) { return __uint_as_float((v << sh) & 0xffff0000u); };
      const float dt = __bfloat162float(__float2bfloat16_rn(expf(__bfloat162float(in.logdt))));
      const float ar2 = dt * val(in.ar) * 1.4426950408889634f, ai = dt * val(in.ai);
      const cplx c = cmul({val(in.cr), -val(in.ci)}, {dt * val(in.br), -dt * val(in.bi)});
      k0 += c.r;
      const cplx z1 = cexp_l(ar2, -ai, 1.f), z256 = cexp_l(ar2, -ai, 256.f), z64 = cexp_l(ar2, ai, 64.f);
      const cplx z2 = csqr(z1), z512 = csqr(z256);
      auto put = [&](int j, cplx v) { sts32(bst + (j >> 2) * 2304 + (j & 3) * 32, packbf(v.r, v.i)); };
      sts128f(sb + SM_KGT + ht * 16, ar2, ai, z64.r, z64.i);
      const cplx c1 = cmul(c, z1), c2 = cmul(c, z2), c3 = cmul(c1, z2), c4 = cmul(c2, z2);
      const cplx c5 = cmul(c3, z2), c6 = cmul(c4, z2), c7 = cmul(c5, z2), c8 = cmul(c6, z2);
      put(0, c1); put(1, c2); put(2, c3); put(3, c4); put(4, c5); put(5, c6); put(6, c7); put(7, c8);
      const cplx c260 = cmul(c4, z256), c264 = cmul(c8, z256), c520 = cmul(c8, z512), c776 = cmul(c264, z512);
      put(8, cmul(c2, z256)); put(9, c260); put(10, cmul(c6, z256)); put(11, c264);
      put(12, cmul(c4, z512)); put(13, c520); put(14, cmul(c260, z512)); put(15, c776);
      const cplx c1032 = cmul(c520, z512), c1288 = cmul(c776, z512);
      put(16, c1032); put(17, c1288); put(18, cmul(c1032, z512)); put(19, cmul(c1288, z512));
    }
    fence_async_smem();
    bar_sync(4, 128);
    const uint32_t tb = sb + SM_KGT + (ht & 67) * 16;
    float2 nx[KB];
#pragma unroll
    for (int s = 0; s < KB; s++) nx[s] = lds64f(tb + s * 64);
#pragma unroll
    for (int q = 0; q < 16 / KB; q++) {
      uint32_t A[2 * KB];
      float2 cur[KB], z[KB];
#pragma unroll
      for (int s = 0; s < KB; s++) { cur[s] = nx[s]; z[s] = lds64f(tb + (KB * q + s) * 64 + 8); }
      if (q < 16 / KB - 1) {
#pragma unroll
        for (int s = 0; s < KB; s++) nx[s] = lds64f(tb + (KB * q + KB + s) * 64);
      }
      if (q >= KW) wg_wait<KW - 1>();
#pragma unroll
      for (int s = 0; s < KB; s++) {
        const cplx lo = cexp_l(cur[s].x, cur[s].y, e0), hi = cmul(lo, {z[s].x, z[s].y});
        A[2 * s] = packbf(lo.r, lo.i);
        A[2 * s + 1] = packbf(hi.r, hi.i);
      }
      wg_fence();
#pragma unroll
      for (int k = 0; k < KB / 2; k++) wgmma_rs<40, 0>(T, A + 4 * k, db + 9 * KB * q + 18 * k, (pass & 1) | q | k);
      wg_commit();
    }
    wg_wait<0>();
    acc_fence<20>(T);
    if (ht == 0) TS(4 + pass);
    if (pass & 1) {
      const int h2 = opaque_tid() - 256, w = h2 >> 5, lane = h2 & 31, t = lane & 3, chn = h2 >> 6, m = h2 & 63, i0 = 16 * (w & 1) + (lane >> 2);
      const int lc = (pass & 2) + chn;
      const uint32_t kc = sb + kc_off(lc);
      auto put = [&](int idx, float v) {
        sts16(kc + idx * 2, __bfloat16_as_ushort(__float2bfloat16_rn(v)));
      };
#pragma unroll
      for (int hi = 0; hi < 2; hi++) {
        const int i = i0 + 8 * hi;
        float v[5];
#pragma unroll
        for (int j = 0; j < 5; j++) v[j] = chn ? T[4 * j + 2 * hi + 1] : T[4 * j + 2 * hi];
        put(8 * i + 1 + t, v[0]);
        put(8 * i + 5 + t, v[1]);
        put(257 + 4 * i + t, v[2]);
        put(385 + 2 * i + (t & 1) + 64 * (t >> 1), v[3]);
        put(513 + i + 32 * t, v[4]);
      }
#pragma unroll
      for (int o = 16; o > 0; o >>= 1) k0 += __shfl_xor_sync(~0u, k0, o);
      if (lane == 0) sts32f(sb + SM_RED + 4 * w, k0);
      bar_sync(4, 128);
      if (m == 0) put(0, k0 + __uint_as_float(lds32(sb + SM_RED + 4 * w + 4)) + __uint_as_float(lds16(sb + SM_RED + 24 + 2 * lc) << 16));
      k0 = 0.f;
      in = in1;
    }
  }
}

__device__ __forceinline__ void expand_taps(uint32_t sb, int ht) {
  const int ch = ht >> 5, lane = ht & 31;
  const uint32_t kc = sb + kc_off(ch);
  const uint32_t dst0 = sb + cv_pe(ch);
  auto put = [&](int G, uint32_t v0, uint32_t v1, uint32_t v2, uint32_t v3, uint32_t v4, uint32_t v5, uint32_t v6, uint32_t v7, uint32_t v8) {
    const uint32_t dst = dst0 + G * 32;
    sts128(dst, make_uint4(v1 | (v0 << 16), v2 | (v1 << 16), v3 | (v2 << 16), v4 | (v3 << 16)));
    sts128(dst + 16, make_uint4(v5 | (v4 << 16), v6 | (v5 << 16), v7 | (v6 << 16), v8 | (v7 << 16)));
  };
  {
    const uint4 q = lds128(kc + lane * 16);
    const uint32_t pv = lane ? lds16(kc + lane * 16 - 2) : 0u;
    const uint32_t dst = dst0 + (lane + 2) * 32;
    sts128(dst, make_uint4(__byte_perm(q.x, pv, 0x5410), __byte_perm(q.x, q.x, 0x1032), __byte_perm(q.y, q.x, 0x7610), __byte_perm(q.y, q.y, 0x1032)));
    sts128(dst + 16, make_uint4(__byte_perm(q.z, q.y, 0x7610), __byte_perm(q.z, q.z, 0x1032), __byte_perm(q.w, q.z, 0x7610), __byte_perm(q.w, q.w, 0x1032)));
    if (lane < 4) sts128(dst0 + lane * 16, make_uint4(0, 0, 0, 0));
  }
  uint32_t a[5], b[2][3];
  {
    const uint32_t s1 = kc + 2 * (256 + 4 * lane);
#pragma unroll
    for (int k = 0; k < 5; k++) a[k] = lds16(s1 + 2 * k);
#pragma unroll
    for (int u = 0; u < 2; u++) {
      const uint32_t s2 = kc + 2 * (384 + 2 * (lane + 32 * u));
#pragma unroll
      for (int k = 0; k < 3; k++) b[u][k] = lds16(s2 + 2 * k);
    }
  }
  const uint32_t k255 = lds16(kc + 2 * 255), k1024 = lds16(kc + 2 * 512);
  put(34 + lane, lane == 0 ? k255 : a[0], a[0], a[0], a[1], a[2], a[2], a[2], a[3], a[4]);
#pragma unroll
  for (int u = 0; u < 2; u++) put(66 + lane + 32 * u, b[u][0], b[u][0], b[u][0], b[u][0], b[u][1], b[u][1], b[u][1], b[u][2], b[u][2]);
  if (lane < 10) {
    const uint32_t v = lane == 0 ? k1024 : 0u;
    put(130 + lane, v, v, v, v, v, v, 0u, 0u, 0u);
  }
}
__device__ __forceinline__ void expand_far(uint32_t sb, int ht) {
  const int ch = ht >> 5, lane = ht & 31;
  const uint32_t kc = sb + kc_off(ch) + 2 * (513 + 2 * (63 - lane)), dst = sb + cv_fa(ch) + lane * 16;
#pragma unroll
  for (int ty = 0; ty < 2; ty++) {
    uint32_t v[16];
#pragma unroll
    for (int k = 0; k < 16; k++) v[k] = (k < 8 || 63 - lane - 4 * k >= 0) ? lds16(kc + 2 * (1 - ty) - 16 * k) : 0u;
#pragma unroll
    for (int u = 0; u < 2; u++)
      sts128(dst + ty * 2048 + u * 512, make_uint4(v[8 * u] | (v[8 * u + 1] << 16), v[8 * u + 2] | (v[8 * u + 3] << 16), v[8 * u + 4] | (v[8 * u + 5] << 16), v[8 * u + 6] | (v[8 * u + 7] << 16)));
    sts128(dst + ty * 2048 + 1024, make_uint4(0, 0, 0, 0));
  }
}

#define TMPF 1
#define CONST_SB 1
#define WPRE 1
__host__ __device__ constexpr int bar_count(int i) {
  return i == B_END ? 3 : i == B_LN ? 2 : i < B_OST ? 1 : i < B_PE ? 4 : (i >= B_PUB && i < B_S) ? 256 : 128;
}
__host__ __device__ constexpr bool bar_first(int i) { return i < B_WF + 2 && (i & 7) < 2; }

__global__ void __launch_bounds__(NTHREADS, 1) fused_kernel(const __grid_constant__ Params p) {
  extern __shared__ __align__(1024) uint8_t smem[];
  constexpr uint32_t sb = 1024;
  if (s32(smem) != sb) return;
  const int tid = threadIdx.x, lane = tid & 31;
  const int warp = __shfl_sync(~0u, tid >> 5, 0);
  if (tid == 32) {
    asm volatile("prefetch.tensormap [%0];" ::"l"(&p.mapX) : "memory");
    asm volatile("prefetch.tensormap [%0];" ::"l"(&p.mapW3) : "memory");
  }
  const int cta = blockIdx.x - (gridDim.x == NCTA + 4 ? 0 : 4);
  if ((unsigned)cta >= NCTA) {
    if (blockIdx.x < NCTA + 4) colsum_cta(p, sb, blockIdx.x & 3, tid);
    return;
  }
  const int rb = ((cta >> 4) & 3) * 4 + ((cta >> 2) & 3), hg = (cta >> 6) * 4 + (cta & 3);
  const uint32_t bar = sb + SM_BAR;
  auto ld_x0 = [&](int half, int c) {
    const uint32_t b = bar + 8 * (B_XF + 8 * half + c);
    mbar_expect(b, PG);
    tma_ld(sb + x_page(half, c) * PG, &p.mapX, c * 64, (16 * half + rb) * 64, b);
  };
  auto ld_x1 = [&](int half, int c, int b0) {
    const uint32_t b = bar + 8 * b0;
    mbar_expect(b, PG);
    tma_ld(sb + (8 * half + c) * PG, &p.mapXT, (16 * half + rb) * 64, DM + c * 64, b);
  };
  auto ld_w = [&](int c) {
    const uint32_t b = bar + 8 * (B_WF + c);
    mbar_expect(b, 3 * PG);
    tma_ld3(sb + w_page(c) * PG, &p.mapW3, hg * 64, c * 64, 0, b);
  };

  if (tid == 0) TS(0);
  if (tid == 480) LTS(0);
  if (warp == 0 && elect_one()) {
#pragma unroll
    for (int i = 0; i < B_WF + 2; i++)
      if (bar_first(i)) mbar_init(bar + 8 * i, 1);
    asm volatile("fence.mbarrier_init.release.cluster;" ::: "memory");
    fence_async_smem();
    ld_x0(0, 0);
    ld_w(0); ld_x0(1, 0);
    ld_x0(0, 1); ld_w(1); ld_x0(1, 1);
    TS(1);
  }
  __syncwarp();
  if (warp >= 1 && warp < 8 && elect_one()) {
    if (warp < 4) {
#pragma unroll
      for (int i = 2; i < 8; i++) mbar_init(bar + 8 * (8 * warp - 8 + i), 1);
    } else {
#pragma unroll
      for (int i = 0; i < 12; i++) mbar_init(bar + 8 * (12 * warp - 24 + i), 1);
    }
    asm volatile("fence.mbarrier_init.release.cluster;" ::: "memory");
  }
  if (warp == 15 && elect_one()) {
#pragma unroll
    for (int i = 72; i < B_COUNT; i++) mbar_init(bar + 8 * i, bar_count(i));
    asm volatile("fence.mbarrier_init.release.cluster;" ::: "memory");
  }

  if (warp < 8) {
    bar_sync(0, NTHREADS);
    asm volatile("setmaxnreg.inc.sync.aligned.u32 %0;" ::"n"(R_CONS));
    const int cw = __shfl_sync(~0u, opaque_tid() >> 5, 0);
    const int wg = cw >> 2, w = cw & 3;
    if (tid == 0) TS(2);
    int rtp = 0;
#pragma unroll 1
    for (int layer = 0; layer < 2; layer++) {
      attn_phase(p, sb, layer, rb, hg, wg, w);
      proj_phase(p, sb, layer, rb, hg, rtp);
      conv_phase(p, sb, layer, cta);
    }
    final_phase(p, sb, cta, wg, w, rtp);
  } else if (warp < 12) {
    asm volatile("setmaxnreg.dec.sync.aligned.u32 %0;" ::"n"(R_HELP));
    const int ht = tid - 256;
    {
      unsigned ep0 = 0;
      if (ht == 0) ep0 = ld_relaxed(&g_cnt[C_CS * 32]);
      const bf16 dsk = p.dskip[cv_chan(cta, ht & 3)];
      const ModeIn in0 = load_modes(p, cv_chan(cta, ht >> 6), ht & 63), in1 = load_modes(p, cv_chan(cta, 2 + (ht >> 6)), ht & 63);
      if (ht < 48) sts128f(sb + SM_STG + ht * 16, 0.f, 0.f, 0.f, 1.f);
      bar_sync(0, NTHREADS);
      if (ht == 0) {
        sts32(sb + SM_EP, ep0);
        mbar_arrive(bar + 8 * B_EP);
      }
      if (ht >= 124) sts16(sb + SM_RED + 24 + 2 * (ht & 3), __bfloat16_as_ushort(dsk));
      kernel_gen(p, sb, cta, ht, in0, in1);
      if (ht < 48) sts128f(sb + SM_KGT + ht * 16, 0.f, 0.f, 0.f, 1.f);
      fence_async_smem();
      bar_sync(4, 128);
      if (ht == 0) mbar_arrive(bar + 8 * B_KG);
    }
#pragma unroll 1
    for (int layer = 0; layer < 2; layer++) {
      mbar_wait(bar + 8 * B_PDONE, layer);
      expand_taps(sb, opaque_tid() - 256);
      mbar_arrive(bar + 8 * B_PE);
      TSW(0);
      expand_far(sb, opaque_tid() - 256);
      {
        const int i = opaque_tid() - 256;
        if (i < 32) sts128(sb + cv_u(i >> 3) + ((i >> 2) & 1) * CV_UH + (128 + (i & 3)) * 16, make_uint4(0, 0, 0, 0));
        mbar_wait(bar + 8 * B_RC, layer);
        mbar_wait(bar + 8 * B_GB, layer);
        TSW(13);
        conv_prep<0>(sb, layer, cta, i);
        mbar_arrive(bar + 8 * B_U);
      }
      mbar_wait(bar + 8 * (B_PDONE + 1), layer);
      bar_sync(4, 128);
#pragma unroll 1
      for (int lc = 0; lc < 4; lc += 2) {
        conv_sums(sb, lc, opaque_tid() - 256);
        TSW(1 + lc);
      }
      fence_async_smem();
      mbar_arrive(bar + 8 * B_S);
      mbar_wait(bar + 8 * (B_GB + 1), layer);
      conv_prep<1>(sb, layer, cta, opaque_tid() - 256);
      mbar_arrive(bar + 8 * B_U1);
      TSW(4);
      if (layer == 0) {
        const int c = __shfl_sync(~0u, (opaque_tid() >> 5) & 3, 0);
        int phase = 0;
#pragma unroll 1
        for (int k = 0; k < 3; k++) {
          const int page = (k ? 4 + 4 * k : 0) + c, b = B_XR + 4 * (k & 1) + c;
          const uint32_t a = sb + page * PG + lane * 128 + (lane & 7) * 16 + (lane >> 3) * 4;
          int it = k == 2 ? phase : 0;
#pragma unroll 1
          for (; it < MAX_RETRY; it++) {
            mbar_wait(bar + 8 * b, it & 1);
            const uint32_t v0 = lds32(a), v1 = lds32(a + 4096);
            if (__all_sync(~0u, v0 != UNSET && v1 != UNSET)) break;
            if (elect_one()) { fence_async_smem(); ld_x1(page >> 3, page & 7, b); }
            __syncwarp();
            RETRY(3);
          }
          if (k == 0) phase = it + 1;
          if (lane == 0) mbar_arrive(bar + 8 * (B_XF + page));
        }
      }
    }
  } else {
    asm volatile("setmaxnreg.dec.sync.aligned.u32 %0;" ::"n"(R_AGENT));
    bar_sync(0, NTHREADS);
    auto done = [&](int half, int c, int layer) { mbar_wait(bar + 8 * (B_DN + 8 * half + c), layer); };
    auto publish = [&](int layer, int k) {
      mbar_wait(bar + 8 * (B_PUB + k), layer);
      red_relaxed(&g_cnt[(layer ? C_F + 4 * k + (cta >> 5) : C_C + k) * 32]);
      if (!layer && k == 0) red_release(&g_cnt[(C_C + 3) * 32]);
      TS(16 + layer * 56 + 40 + 7 + k);
    };
    if (warp == 12) {
      if (elect_one()) {
#pragma unroll 1
        for (int layer = 0; layer < 2; layer++) {
          auto ld_xe = [&](int c) {
            const uint32_t b = bar + 8 * (B_XF + c);
            mbar_expect(b, PG);
            if (layer == 0) tma_ld(sb + x_page(0, c) * PG, &p.mapX, c * 64, rb * 64, b);
            else tma_ld(sb + x_page(0, c) * PG, &p.mapXT, rb * 64, DM + c * 64, b);
          };
          if (layer == 0) {
            ld_x0(0, 2); ld_w(2); ld_x0(1, 2);
            if (hg >= 3) {
              mbar_expect(bar + 8 * B_SC, PG);
              tma_ld(sb + P_R * PG, &p.mapX, hg * 64, rb * 64, bar + 8 * B_SC);
            }
            if (rb < 4) tma_prefetch3(&p.mapW3, hg * 64, (4 + rb) * 64, 0);
            ld_x0(0, 3); ld_w(3); ld_x0(1, 3); ld_x0(0, 4); ld_x0(1, 4);
            done(0, 0, 0); done(1, 0, 0);
            ld_w(4);
            ld_x0(1, 5); ld_x0(1, 6); ld_x0(1, 7);
            done(0, 1, 0); done(1, 1, 0);
            ld_w(5);
            if (rb < 8) tma_prefetch5(&p.mapWo, hg * 64, rb * 2);
            done(0, 2, 0);
            fence_async_smem();
            ld_xe(5); ld_xe(6); ld_xe(7);
          } else {
            mbar_wait(bar + 8 * B_PDONE, 0);
            mbar_wait(bar + 8 * (B_PDONE + 1), 0);
            mbar_wait(bar + 8 * (WPRE == 1 ? B_U : B_GB + 1), 0);
            ld_w(0); ld_w(1);
            mbar_wait(bar + 8 * B_U1, 0);
            fence_async_smem();
            ld_w(2);
            mbar_wait(bar + 8 * (B_PUB + 2), 0);
            fence_async_smem();
            ld_w(3);
            spin_until(&g_cnt[(C_C + 3) * 32], ((lds32(sb + SM_EP) / NCTA) + 1) * NCTA);
            fence_async_global();
            if (hg >= 3) {
              mbar_expect(bar + 8 * B_SC, PG);
              tma_ld(sb + P_R * PG, &p.mapXT, rb * 64, DM + hg * 64, bar + 8 * B_SC);
            }
            ld_xe(4);
            done(0, 2, 1);
            fence_async_smem();
            ld_xe(5); ld_xe(6); ld_xe(7);
            done(1, 0, 1);
            ld_w(4);
            done(1, 1, 1);
            ld_w(5);
          }
          done(1, 2, layer);
          fence_async_smem();
          ld_w(6); ld_w(7);
          auto ld_res = [&](int half) {
            const uint32_t b = bar + 8 * (B_RF + half);
            mbar_expect(b, PG);
            if (layer == 0) tma_ld(sb + (half ? 2 : P_R) * PG, &p.mapX, hg * 64, (16 * half + rb) * 64, b);
            else tma_ld(sb + (half ? 2 : P_R) * PG, &p.mapXT, (16 * half + rb) * 64, DM + hg * 64, b);
          };
          done(0, 4, layer); done(1, 3, layer);
          fence_async_smem();
          mbar_expect(bar + 8 * B_WOF, 8 * PG);
#pragma unroll 1
          for (int c = 0; c < 8; c++) {
            if (c == 5) { ld_res(0); done(1, 4, layer); }
            tma_ld5(sb + wo_page(c) * PG, &p.mapWo, hg * 64, c * 2, bar + 8 * B_WOF);
          }
          done(0, 7, layer);
          fence_async_global();
          ld_res(1);
        }
      }
    } else if (warp == 13) {
      mbar_wait(bar + 8 * B_EP, 0);
      const unsigned e1 = (lds32(sb + SM_EP) / NCTA) + 1;
      auto ld_o = [&](int layer) {
#pragma unroll 1
        for (int half = 0; half < 2; half++) {
          done(1, 7, layer);
          mbar_wait(bar + 8 * B_OST, layer);
          if (half) mbar_wait(bar + 8 * (B_OST + 1), layer);
          fence_async_smem();
#pragma unroll
          for (int c = 0; c < 4; c++) mbar_expect(bar + 8 * (B_OF + 4 * half + c), 2 * PG);
          spin_hint(&g_cnt[(C_O + layer * 32 + 16 * half + rb) * 32], e1 * 32);
#pragma unroll
          for (int c = 0; c < 4; c++)
            bulk_ld(sb + o_page(half, c) * PG, g_O + ((layer * 32 + 16 * half + rb) * 4 + c) * PG, 2 * PG, bar + 8 * (B_OF + 4 * half + c));
        }
      };
      if (elect_one()) {
        mbar_wait(bar + 8 * (B_WF + 2), 0);
        asm volatile("prefetch.tensormap [%0];" ::"l"(&p.mapXT) : "memory");
        asm volatile("prefetch.tensormap [%0];" ::"l"(&p.mapOut) : "memory");
        asm volatile("prefetch.tensormap [%0];" ::"l"(&p.mapWo) : "memory");
        spin_until(&g_cnt[C_Z * 32], e1 * NCTA);
        mbar_arrive(bar + 8 * B_ZF);
        TS(3);
        ld_o(0);
#pragma unroll 1
        for (int k = 0; k < 3; k++) {
          mbar_wait(bar + 8 * (B_PUB + k), 0);
          if (k == 2) {
#pragma unroll 1
            for (int c = 0; c < 4; c++) mbar_wait(bar + 8 * (B_XF + c), 1);
          }
          fence_async_smem();
          spin_hint(&g_cnt[(C_C + k) * 32], e1 * NCTA);
          TS(10 + k);
#pragma unroll
          for (int c = 0; c < 4; c++) ld_x1(k != 0, (k & 2) * 2 + c, B_XR + 4 * (k & 1) + c);
        }
        ld_o(1);
        mbar_wait(bar + 8 * B_PUB, 1);
#pragma unroll 1
        for (int half = 0; half < 2; half++) {
          mbar_expect(bar + 8 * (B_TF + half), PG);
          spin_hint(&g_cnt[(C_F + 4 * (half ? 1 + (cta >> 6) : 0) + ((cta >> 4) & 3)) * 32], e1 * 32);
          tma_ld(sb + (16 + half) * PG, &p.mapXT, (16 * half + (cta & 15)) * 64, 3 * DM + (cta >> 4) * 64, bar + 8 * (B_TF + half));
        }
      }
    } else if (warp == 14) {
      mbar_wait(bar + 8 * B_EP, 0);
      const unsigned e1 = (lds32(sb + SM_EP) / NCTA) + 1;
      done(0, 1, 0);
      {
        const uint2* cp = g_colsum + (hg * 192 + lane);
        uint2 v[6];
        bool ok;
        int it = 0;
        do {
          ok = true;
#pragma unroll
          for (int i = 0; i < 6; i++) {
            asm volatile("ld.relaxed.gpu.global.v2.u32 {%0,%1}, [%2];" : "=r"(v[i].x), "=r"(v[i].y) : "l"(cp + 32 * i) : "memory");
            ok = ok && v[i].y == e1;
          }
          if (++it > (1 << 22)) __trap();
        } while (!__all_sync(~0u, ok));
#pragma unroll
        for (int i = 0; i < 6; i++) sts32f(sb + SM_CS + 4 * (lane + 32 * i), __uint_as_float(v[i].x));
      }
      __syncwarp();
      if (elect_one()) {
        mbar_wait(bar + 8 * B_ZF, 0);
        mbar_arrive(bar + 8 * B_LN);
        red_relaxed(&g_cnt[C_CS * 32]);
        TS(13);
#pragma unroll 1
        for (int i = 0; i < 4; i++) {
          const int layer = i >> 1;
          mbar_wait(bar + 8 * (B_PST + (i & 1)), layer);
          const uint32_t b = bar + 8 * (B_GB + 1);
          const bf16* xin = g_xT + ((size_t)2 * layer * DM + 2 * cta) * LSEQ + 1024;
          if (i & 1) {
            fence_async_smem();
            mbar_expect(b, 12288 + PG);
          }
          spin_hint(&g_cnt[(C_G + i) * 32], e1 * NCTA);
          if (i & 1) {
            bulk_ld(sb + CV_ST, g_stats + (layer * 32 + 16) * 192, 12288, b);
#pragma unroll
            for (int lc = 0; lc < 4; lc++) bulk_ld(sb + cv_x(1, lc), xin + cv_chan(0, lc) * LSEQ, 2048, b);
            TS(14 + layer);
            publish(layer, 1);
          } else {
            mbar_arrive(bar + 8 * B_GB);
          }
        }
      }
    } else {
      const uint4 u = make_uint4(UNSET, UNSET, UNSET, UNSET);
      if (lane < 24) stg128((uint4*)g_stats + cta * 24 + lane, make_uint4(0, 0, 0, 0));
      if (lane < 16) stg128(g_rows + LSEQ + cta * 16 + lane, make_uint4(0, 0, 0, 0));
#pragma unroll 4
      for (int i = 0; i < 16; i++) stg128(g_halo + cta * 512 + 32 * i + lane, u);
#pragma unroll 4
      for (int i = 0; i < 16; i++) stg128(((i & 8) ? (uint4*)g_xT : (uint4*)g_O) + cta * 1024 + (i & 7) * 128 + (lane >> 1) * 8 + (lane & 1), u);
      __syncwarp();
      if (elect_one()) red_release(&g_cnt[C_Z * 32]);
      __syncwarp();
#pragma unroll 1
      for (int layer = 0; layer < 2; layer++) {
        auto reset_done = [&](int s) {
          spin_until(&g_cnt[(C_R + s) * 32], (lds32(sb + SM_EP) / NCTA) * 4 + 4);
          mbar_arrive(bar + 8 * (s == 1 ? B_LN : s == 2 ? B_RS : B_RC));
          if (s) TS(16 + 40 + 9 + s);
        };
        if (layer && elect_one()) reset_done(1);
        __syncwarp();
#pragma unroll 1
        for (int half = 0; half < 2; half++) {
          done(half, 2, layer);
          const uint4* src = g_rows + (layer * LSEQ + (16 * half + rb) * 64 + (opaque_tid() & 31));
          uint4 a, b;
          int it = 0;
          do {
            a = ld_tagged(src); b = ld_tagged(src + 32);
          } while (!__all_sync(~0u, (a.z | a.w) == __float_as_uint(8.f) && (b.z | b.w) == __float_as_uint(8.f)) && ++it < (1 << 20));
          float m0 = __uint_as_float(a.x) * (1.f / DM), m1 = __uint_as_float(b.x) * (1.f / DM);
          float r0 = rsqrt_approx(fmaxf(__uint_as_float(a.y) * (1.f / DM) - m0 * m0, 0.f) + 1e-5f);
          float r1 = rsqrt_approx(fmaxf(__uint_as_float(b.y) * (1.f / DM) - m1 * m1, 0.f) + 1e-5f);
          if (half) done(0, 7, layer);
          const uint32_t dst = sb + ln_off(half) + ((lane >> 4) * 8 + (lane & 7)) * 16 + (lane & 8);
          asm volatile("st.shared.v2.f32 [%0], {%1,%2};" ::"r"(dst), "f"(m0), "f"(r0) : "memory");
          asm volatile("st.shared.v2.f32 [%0], {%1,%2};" ::"r"(dst + 256), "f"(m1), "f"(r1) : "memory");
          __syncwarp();
          if (elect_one()) { mbar_arrive(bar + 8 * (B_LN + half)); TS(16 + layer * 56 + 40 + 14 + half); }
        }
        if (layer && lane < 16) stg128(g_rows + cta * 16 + (opaque_tid() & 31), make_uint4(0, 0, 0, 0));
        if (elect_one()) {
          if (layer) reset_done(2);
          reset_done(3 * layer);
          publish(layer, 0);
          publish(layer, 2);
        }
        __syncwarp();
      }
    }
  }
}

typedef CUresult (*EncodeFn)(CUtensorMap*, CUtensorMapDataType, cuuint32_t, void*, const cuuint64_t*, const cuuint64_t*,
                             const cuuint32_t*, const cuuint32_t*, CUtensorMapInterleave, CUtensorMapSwizzle,
                             CUtensorMapL2promotion, CUtensorMapFloatOOBfill);

static void make_map(EncodeFn enc, CUtensorMap* m, void* ptr, uint64_t cols, uint64_t rows, uint32_t box_rows) {
  cuuint64_t dims[2] = {cols, rows};
  cuuint64_t strides[1] = {cols * 2};
  cuuint32_t box[2] = {64, box_rows};
  cuuint32_t es[2] = {1, 1};
  enc(m, CU_TENSOR_MAP_DATA_TYPE_BFLOAT16, 2, ptr, dims, strides, box, es, CU_TENSOR_MAP_INTERLEAVE_NONE,
      CU_TENSOR_MAP_SWIZZLE_128B, CU_TENSOR_MAP_L2_PROMOTION_L2_128B, CU_TENSOR_MAP_FLOAT_OOB_FILL_NONE);
}
static void make_map3(EncodeFn enc, CUtensorMap* m, void* ptr, uint64_t d0, uint64_t cols, uint64_t rows, uint64_t blk_stride,
                      uint64_t nblocks, uint32_t nblk) {
  cuuint64_t dims[3] = {d0, rows, nblocks};
  cuuint64_t strides[2] = {cols * 2, blk_stride * 2};
  cuuint32_t box[3] = {64, 64, nblk};
  cuuint32_t es[3] = {1, 1, 1};
  enc(m, CU_TENSOR_MAP_DATA_TYPE_BFLOAT16, 3, ptr, dims, strides, box, es, CU_TENSOR_MAP_INTERLEAVE_NONE,
      CU_TENSOR_MAP_SWIZZLE_128B, CU_TENSOR_MAP_L2_PROMOTION_L2_128B, CU_TENSOR_MAP_FLOAT_OOB_FILL_NONE);
}

extern "C" void kernel_launch(void* const* d_in, const int* in_sizes, int n_in, void* d_out, int out_size) {
  static Params prm;
  static void* cached[13] = {nullptr};
  static bool attr_done = false;
  static int grid = NCTA + 4;
  bool same = attr_done && cached[12] == d_out;
  for (int i = 0; i < 12 && same; i++) same = cached[i] == d_in[i];
  if (!same) {
    void* fn = nullptr;
    cudaDriverEntryPointQueryResult qr;
    cudaGetDriverEntryPoint("cuTensorMapEncodeTiled", &fn, cudaEnableDefault, &qr);
    EncodeFn enc = (EncodeFn)fn;
    void* pXT;
    cudaGetSymbolAddress(&pXT, g_xT);
    make_map(enc, &prm.mapX, d_in[0], DM, LSEQ, 64);
    make_map(enc, &prm.mapXT, pXT, LSEQ, 4 * DM, 64);
    make_map(enc, &prm.mapOut, d_out, DM, LSEQ, 64);
    {
      cuuint64_t dims[5] = {DM, 2, 4, 4, 16};
      cuuint64_t strides[4] = {DM * 2, 8 * DM * 2, 2 * DM * 2, 32 * DM * 2};
      cuuint32_t box[5] = {64, 2, 4, 4, 2};
      cuuint32_t es[5] = {1, 1, 1, 1, 1};
      enc(&prm.mapWo, CU_TENSOR_MAP_DATA_TYPE_BFLOAT16, 5, d_in[2], dims, strides, box, es, CU_TENSOR_MAP_INTERLEAVE_NONE,
          CU_TENSOR_MAP_SWIZZLE_128B, CU_TENSOR_MAP_L2_PROMOTION_L2_128B, CU_TENSOR_MAP_FLOAT_OOB_FILL_NONE);
    }
    make_map3(enc, &prm.mapW3, d_in[1], DM, 3 * DM, DM, DM, 3, 3);
    prm.wqkv = (const bf16*)d_in[1];
    prm.a_re = (const bf16*)d_in[4]; prm.a_im = (const bf16*)d_in[5];
    prm.b_re = (const bf16*)d_in[6]; prm.b_im = (const bf16*)d_in[7];
    prm.c_re = (const bf16*)d_in[8]; prm.c_im = (const bf16*)d_in[9];
    prm.log_dt = (const bf16*)d_in[10]; prm.dskip = (const bf16*)d_in[11];
    int dev = 0, sms = 0;
    cudaGetDevice(&dev);
    cudaDeviceGetAttribute(&sms, cudaDevAttrMultiProcessorCount, dev);
    grid = sms >= NCTA + 4 ? NCTA + 4 : NCTA + 5;
    cudaFuncSetAttribute(fused_kernel, cudaFuncAttributeMaxDynamicSharedMemorySize, SM_TOTAL);
    for (int i = 0; i < 12; i++) cached[i] = d_in[i];
    cached[12] = d_out;
    attr_done = true;
  }
  fused_kernel<<<grid, NTHREADS, SM_TOTAL>>>(prm);
}
```

```cpp
#include <cuda_runtime.h>
#include <cuda_bf16.h>
#include <cuda.h>
#include <stdint.h>

typedef __nv_bfloat16 bf16;

constexpr int LSEQ = 2048;
constexpr int DM = 512;
constexpr int NCTA = 128;
constexpr int NTHREADS = 512;
#define R_CONS 200
#define R_HELP 88
#define R_AGENT 24
#define TURN0 4
#define TURN1 4

constexpr int PG = 8192;
constexpr int P_R = 25;
__host__ __device__ constexpr int x_page(int half, int c) { return half ? 8 + c : c < 5 ? c : c - 5; }
__host__ __device__ constexpr int w_page(int c) { return (c & 3) < 3 ? 16 + 3 * (c & 3) : c < 4 ? 5 : 8; }
__host__ __device__ constexpr int wo_page(int c) { return c < 5 ? 3 + c : 11 + c; }
__host__ __device__ constexpr int o_page(int half, int pair) { return half ? (pair ? 25 - 2 * pair : 0) : 8 + 2 * pair; }
constexpr int SM_KGB = (P_R + 1) * PG;
constexpr int SM_KC = 27 * PG;
constexpr int KC_STRIDE = 648;
__host__ __device__ constexpr int kc_off(int lc) { return SM_KC + (lc & 1) * 2 * KC_STRIDE + (lc < 2 ? 3328 : 0); }
constexpr int SM_KGT = SM_KC + 3328 + 2592;
constexpr int SM_CS = SM_KGT + 2048;
constexpr int SM_RED = SM_CS + 768;
constexpr int SM_EP = SM_RED + 16;
constexpr int SM_STG = SM_RED + 32;
constexpr int SM_LN = SM_STG + 768;
__host__ __device__ constexpr int ln_off(int half) { return half ? PG + 4096 : SM_LN; }
constexpr int SM_BAR = SM_LN + 512;
constexpr int SM_TS = SM_BAR + 704;
constexpr int SM_TOTAL = SM_TS + 512;
static_assert(SM_TOTAL <= 232448 && SM_STG % 16 == 0 && SM_KGT % 16 == 0, "shared memory");

constexpr int CV_UH = 140 * 16;
__host__ __device__ constexpr int cv_u(int lc) { return (8 + 2 * lc) * PG; }
__host__ __device__ constexpr int cv_pe(int lc, int early) { return early ? 19 * PG + lc * 4480 : cv_u(lc) + 4480; }
__host__ __device__ constexpr int cv_pb1(int lc, int w) { return w ? cv_u(lc) + 8960 + (w - 1) * 2048 : 7 * PG + lc * 2048; }
__host__ __device__ constexpr int cv_fa(int lc) { return cv_pb1(lc, 1) + 128; }
__host__ __device__ constexpr int cv_dump(int lc) { return cv_u(lc) + 16256; }
__host__ __device__ constexpr int cv_pb0(int lc, int w) { return lc * PG + w * 2048; }
__host__ __device__ constexpr int cv_se(int lc) { return 5 * PG + lc * 4096; }
__host__ __device__ constexpr int cv_so(int lc) { return cv_se(lc) + 2048; }
__host__ __device__ constexpr int cv_x(int half, int lc) { return (P_R + half) * PG + lc * 2048; }
constexpr int CV_ST = 22 * PG;
__host__ __device__ constexpr int cv_chan(int cta, int lc) { return 2 * cta + (lc & 1) + 256 * (lc >> 1); }

enum {
  B_XF = 0,
  B_WF = 16,
  B_OF = 24,
  B_DN = 32,
  B_XR = 48,
  B_RF = 56,
  B_PST = 58,
  B_GB = 60,
  B_TF = 62,
  B_RT = 64,
  B_RS = 66,
  B_RC = 67,
  B_WOF = 68,
  B_ZF = 69,
  B_EP = 70,
  B_KG = 71,
  B_SC = 72,
  B_LN = 73,
  B_END = 75,
  B_OST = 76,
  B_PDONE = 78,
  B_PE = 80,
  B_U = 81,
  B_U1 = 82,
  B_PUB = 83,
  B_S = 86,
  B_AL = 87,
  B_COUNT = 88
};

enum {
  C_CS = 0,
  C_G = 1,
  C_C = 5,
  C_O = 21,
  C_Z = 85,
  C_R = 86,
  C_F = 90,
  C_COUNT = 106
};

__device__ unsigned g_cnt[C_COUNT * 32];
__device__ __align__(1024) bf16 g_O[2 * LSEQ * DM];
__device__ __align__(1024) bf16 g_xT[4 * DM * LSEQ];
__device__ __align__(1024) float g_stats[2 * 32 * 192];
__device__ __align__(1024) uint2 g_colsum[3 * DM];
__device__ __align__(1024) uint4 g_halo[32 * 8 * 256];
__device__ __align__(1024) uint4 g_rows[2 * LSEQ];
#define TS(i) do { } while (0)
#define TSW(k) do { if ((threadIdx.x & 127) == 0) TS(16 + layer * 56 + (threadIdx.x >> 7) * 20 + (k)); } while (0)
#define TSG(k) do { } while (0)

#define RETRY(i) do { } while (0)
#define LTS(i) do { } while (0)
#define LTE() do { } while (0)

struct Params {
  CUtensorMap mapX, mapW3, mapXT, mapWo;
  bf16* out;
  const bf16 *a_re, *a_im, *b_re, *b_im, *c_re, *c_im, *log_dt, *dskip;
};

__device__ __forceinline__ uint32_t s32(const void* p) { return (uint32_t)__cvta_generic_to_shared(p); }
__device__ __forceinline__ void mbar_init(uint32_t b, int c) { asm volatile("mbarrier.init.shared::cta.b64 [%0], %1;" ::"r"(b), "r"(c) : "memory"); }
__device__ __forceinline__ void mbar_expect(uint32_t b, int bytes) { asm volatile("mbarrier.arrive.expect_tx.shared::cta.b64 _, [%0], %1;" ::"r"(b), "r"(bytes) : "memory"); }
__device__ __forceinline__ void mbar_arrive(uint32_t b) { asm volatile("mbarrier.arrive.shared::cta.b64 _, [%0];" ::"r"(b) : "memory"); }
__device__ __forceinline__ void mbar_wait(uint32_t b, int parity) {
  asm volatile("{\n.reg .pred p;\nWAIT_LOOP:\nmbarrier.try_wait.parity.shared::cta.b64 p, [%0], %1;\n@p bra WAIT_DONE;\nbra WAIT_LOOP;\nWAIT_DONE:\n}" ::"r"(b), "r"(parity) : "memory");
}
__device__ __forceinline__ bool mbar_test(uint32_t b, int parity) {
  uint32_t ok;
  asm volatile("{\n.reg .pred p;\nmbarrier.test_wait.parity.shared::cta.b64 p, [%1], %2;\nselp.u32 %0, 1, 0, p;\n}" : "=r"(ok) : "r"(b), "r"(parity) : "memory");
  return ok != 0;
}
__device__ __forceinline__ int opaque_tid() { int v; asm volatile("mov.u32 %0, %%tid.x;" : "=r"(v)); return v; }
__device__ __forceinline__ bool elect_one() {
  uint32_t r;
  asm volatile("{\n.reg .pred p;\nelect.sync _|p, 0xffffffff;\nselp.u32 %0, 1, 0, p;\n}" : "=r"(r));
  return r != 0;
}
__device__ __forceinline__ void tma_ld(uint32_t dst, const CUtensorMap* m, int c0, int c1, uint32_t bar) {
  asm volatile("cp.async.bulk.tensor.2d.shared::cluster.global.mbarrier::complete_tx::bytes [%0], [%1, {%3, %4}], [%2];"
               ::"r"(dst), "l"(m), "r"(bar), "r"(c0), "r"(c1) : "memory");
}
__device__ __forceinline__ void tma_ld3(uint32_t dst, const CUtensorMap* m, int c0, int c1, int c2, uint32_t bar) {
  asm volatile("cp.async.bulk.tensor.3d.shared::cluster.global.mbarrier::complete_tx::bytes [%0], [%1, {%3, %4, %5}], [%2];"
               ::"r"(dst), "l"(m), "r"(bar), "r"(c0), "r"(c1), "r"(c2) : "memory");
}
__device__ __forceinline__ void tma_ld5(uint32_t dst, const CUtensorMap* m, int c0, int c4, uint32_t bar) {
  asm volatile("cp.async.bulk.tensor.5d.shared::cluster.global.mbarrier::complete_tx::bytes [%0], [%1, {%3, 0, 0, 0, %4}], [%2];"
               ::"r"(dst), "l"(m), "r"(bar), "r"(c0), "r"(c4) : "memory");
}
__device__ __forceinline__ void tma_prefetch5(const CUtensorMap* m, int c0, int c4) {
  asm volatile("cp.async.bulk.prefetch.tensor.5d.L2.global.tile [%0, {%1, 0, 0, 0, %2}];" ::"l"(m), "r"(c0), "r"(c4) : "memory");
}
__device__ __forceinline__ void tma_prefetch2(const CUtensorMap* m, int c0, int c1) {
  asm volatile("cp.async.bulk.prefetch.tensor.2d.L2.global.tile [%0, {%1, %2}];" ::"l"(m), "r"(c0), "r"(c1) : "memory");
}
__device__ __forceinline__ void tma_prefetch3(const CUtensorMap* m, int c0, int c1, int c2) {
  asm volatile("cp.async.bulk.prefetch.tensor.3d.L2.global.tile [%0, {%1, %2, %3}];" ::"l"(m), "r"(c0), "r"(c1), "r"(c2) : "memory");
}
__device__ __forceinline__ void tma_st(const CUtensorMap* m, int c0, int c1, uint32_t src) {
  asm volatile("cp.async.bulk.tensor.2d.global.shared::cta.bulk_group [%0, {%2, %3}], [%1];" ::"l"(m), "r"(src), "r"(c0), "r"(c1) : "memory");
}
__device__ __forceinline__ void bulk_ld(uint32_t dst, const void* src, int bytes, uint32_t bar) {
  asm volatile("cp.async.bulk.shared::cluster.global.mbarrier::complete_tx::bytes [%0], [%1], %2, [%3];" ::"r"(dst), "l"(src), "r"(bytes), "r"(bar) : "memory");
}
__device__ __forceinline__ void bulk_st(void* dst, uint32_t src, int bytes) {
  asm volatile("cp.async.bulk.global.shared::cta.bulk_group [%0], [%1], %2;" ::"l"(dst), "r"(src), "r"(bytes) : "memory");
}
__device__ __forceinline__ void bulk_red_add_f32(void* dst, uint32_t src, int bytes) {
  asm volatile("cp.reduce.async.bulk.global.shared::cta.bulk_group.add.f32 [%0], [%1], %2;" ::"l"(dst), "r"(src), "r"(bytes) : "memory");
}
__device__ __forceinline__ void bulk_commit() { asm volatile("cp.async.bulk.commit_group;" ::: "memory"); }
__device__ __forceinline__ void bulk_wait_all() { asm volatile("cp.async.bulk.wait_group 0;" ::: "memory"); }
__device__ __forceinline__ void fence_async_smem() { asm volatile("fence.proxy.async.shared::cta;" ::: "memory"); }
__device__ __forceinline__ void fence_async_global() { asm volatile("fence.proxy.async.global;" ::: "memory"); }
__device__ __forceinline__ void bar_sync(int id, int n) { asm volatile("bar.sync %0, %1;" ::"r"(id), "r"(n) : "memory"); }
__device__ __forceinline__ void bar_arrive(int id, int n) { asm volatile("bar.arrive %0, %1;" ::"r"(id), "r"(n) : "memory"); }
__device__ __forceinline__ bool bar_or(int id, int n, bool v) {
  uint32_t r;
  asm volatile("{\n.reg .pred p, q;\nsetp.ne.u32 q, %3, 0;\nbar.red.or.pred p, %1, %2, q;\nselp.u32 %0, 1, 0, p;\n}" : "=r"(r) : "r"(id), "r"(n), "r"((uint32_t)v) : "memory");
  return r != 0;
}
__device__ __forceinline__ void bulk_wait_read() { asm volatile("cp.async.bulk.wait_group.read 0;" ::: "memory"); }
__device__ __forceinline__ void stg128(void* p, uint4 v) { asm volatile("st.relaxed.gpu.global.v4.u32 [%0], {%1,%2,%3,%4};" ::"l"(p), "r"(v.x), "r"(v.y), "r"(v.z), "r"(v.w) : "memory"); }
constexpr uint32_t UNSET = 0xffffffffu;
constexpr int MAX_RETRY = 1 << 16;
__device__ __forceinline__ void wg_fence() { asm volatile("wgmma.fence.sync.aligned;" ::: "memory"); }
__device__ __forceinline__ void wg_commit() { asm volatile("wgmma.commit_group.sync.aligned;" ::: "memory"); }
template <int N> __device__ __forceinline__ void wg_wait() { asm volatile("wgmma.wait_group.sync.aligned %0;" ::"n"(N) : "memory"); }
__device__ __forceinline__ uint64_t mkdesc(uint32_t addr, uint32_t lbo, uint32_t sbo, int sw) {
  return (uint64_t)((addr & 0x3FFFF) >> 4) | ((uint64_t)(lbo >> 4) << 16) | ((uint64_t)(sbo >> 4) << 32) | ((uint64_t)sw << 62);
}
__device__ __forceinline__ void ldsm4(uint32_t* r, uint32_t a) {
  asm volatile("ldmatrix.sync.aligned.m8n8.x4.shared.b16 {%0,%1,%2,%3}, [%4];" : "=r"(r[0]), "=r"(r[1]), "=r"(r[2]), "=r"(r[3]) : "r"(a) : "memory");
}
__device__ __forceinline__ void ldsm4t(uint32_t* r, uint32_t a) {
  asm volatile("ldmatrix.sync.aligned.m8n8.x4.trans.shared.b16 {%0,%1,%2,%3}, [%4];" : "=r"(r[0]), "=r"(r[1]), "=r"(r[2]), "=r"(r[3]) : "r"(a) : "memory");
}
__device__ __forceinline__ void stsm4(uint32_t a, uint32_t r0, uint32_t r1, uint32_t r2, uint32_t r3) {
  asm volatile("stmatrix.sync.aligned.m8n8.x4.shared.b16 [%0], {%1,%2,%3,%4};" ::"r"(a), "r"(r0), "r"(r1), "r"(r2), "r"(r3) : "memory");
}
__device__ __forceinline__ void stsm4t(uint32_t a, uint32_t r0, uint32_t r1, uint32_t r2, uint32_t r3) {
  asm volatile("stmatrix.sync.aligned.m8n8.x4.trans.shared.b16 [%0], {%1,%2,%3,%4};" ::"r"(a), "r"(r0), "r"(r1), "r"(r2), "r"(r3) : "memory");
}
__device__ __forceinline__ uint32_t movm_t(uint32_t a) { uint32_t r; asm volatile("movmatrix.sync.aligned.m8n8.trans.b16 %0, %1;" : "=r"(r) : "r"(a)); return r; }
__device__ __forceinline__ uint32_t lds32(uint32_t a) { uint32_t v; asm volatile("ld.shared.b32 %0, [%1];" : "=r"(v) : "r"(a) : "memory"); return v; }
__device__ __forceinline__ float2 lds64f(uint32_t a) { float2 v; asm volatile("ld.shared.v2.f32 {%0,%1}, [%2];" : "=f"(v.x), "=f"(v.y) : "r"(a) : "memory"); return v; }
__device__ __forceinline__ float4 lds128f(uint32_t a) { float4 v; asm volatile("ld.shared.v4.f32 {%0,%1,%2,%3}, [%4];" : "=f"(v.x), "=f"(v.y), "=f"(v.z), "=f"(v.w) : "r"(a) : "memory"); return v; }
__device__ __forceinline__ uint4 lds128(uint32_t a) { uint4 v; asm volatile("ld.shared.v4.b32 {%0,%1,%2,%3}, [%4];" : "=r"(v.x), "=r"(v.y), "=r"(v.z), "=r"(v.w) : "r"(a) : "memory"); return v; }
__device__ __forceinline__ void sts128(uint32_t a, uint4 v) { asm volatile("st.shared.v4.b32 [%0], {%1,%2,%3,%4};" ::"r"(a), "r"(v.x), "r"(v.y), "r"(v.z), "r"(v.w) : "memory"); }
__device__ __forceinline__ void sts128f(uint32_t a, float x, float y, float z, float w) { asm volatile("st.shared.v4.f32 [%0], {%1,%2,%3,%4};" ::"r"(a), "f"(x), "f"(y), "f"(z), "f"(w) : "memory"); }
__device__ __forceinline__ void sts32f(uint32_t a, float v) { asm volatile("st.shared.f32 [%0], %1;" ::"r"(a), "f"(v) : "memory"); }
__device__ __forceinline__ void sts16(uint32_t a, uint16_t v) { asm volatile("st.shared.u16 [%0], %1;" ::"r"(a), "h"(v) : "memory"); }
__device__ __forceinline__ uint32_t lds16(uint32_t a) { uint16_t v; asm volatile("ld.shared.u16 %0, [%1];" : "=h"(v) : "r"(a) : "memory"); return v; }
__device__ __forceinline__ uint32_t packbf(float lo, float hi) { uint32_t r; asm("cvt.rn.bf16x2.f32 %0, %1, %2;" : "=r"(r) : "f"(hi), "f"(lo)); return r; }
__device__ __forceinline__ float bf_lo(uint32_t v) { return __uint_as_float(v << 16); }
__device__ __forceinline__ float bf_hi(uint32_t v) { return __uint_as_float(v & 0xffff0000u); }
__device__ __forceinline__ float ex2(float x) { float r; asm("ex2.approx.ftz.f32 %0, %1;" : "=f"(r) : "f"(x)); return r; }
__device__ __forceinline__ float rsqrt_approx(float x) { float r; asm("rsqrt.approx.ftz.f32 %0, %1;" : "=f"(r) : "f"(x)); return r; }
__device__ __forceinline__ float rcp_approx(float x) { float r; asm("rcp.approx.ftz.f32 %0, %1;" : "=f"(r) : "f"(x)); return r; }
__device__ __forceinline__ void mma_bf16(float* d, const uint32_t* a, uint32_t b0, uint32_t b1) {
  asm("mma.sync.aligned.m16n8k16.row.col.f32.bf16.bf16.f32 {%0,%1,%2,%3}, {%4,%5,%6,%7}, {%8,%9}, {%0,%1,%2,%3};"
               : "+f"(d[0]), "+f"(d[1]), "+f"(d[2]), "+f"(d[3]) : "r"(a[0]), "r"(a[1]), "r"(a[2]), "r"(a[3]), "r"(b0), "r"(b1));
}
__device__ __forceinline__ void mma_tf32(float* d, float a0, float a1, float a2, float a3, float b0, float b1) {
  asm("mma.sync.aligned.m16n8k8.row.col.f32.tf32.tf32.f32 {%0,%1,%2,%3}, {%4,%5,%6,%7}, {%8,%9}, {%0,%1,%2,%3};"
               : "+f"(d[0]), "+f"(d[1]), "+f"(d[2]), "+f"(d[3])
               : "r"(__float_as_uint(a0)), "r"(__float_as_uint(a1)), "r"(__float_as_uint(a2)), "r"(__float_as_uint(a3)),
                 "r"(__float_as_uint(b0)), "r"(__float_as_uint(b1)));
}
__device__ __forceinline__ void red_release(unsigned* p) { asm volatile("red.release.gpu.global.add.u32 [%0], 1;" ::"l"(p) : "memory"); }
__device__ __forceinline__ void red_relaxed(unsigned* p) { asm volatile("red.relaxed.gpu.global.add.u32 [%0], 1;" ::"l"(p) : "memory"); }
__device__ __forceinline__ unsigned ld_relaxed(const unsigned* p) { unsigned v; asm volatile("ld.relaxed.gpu.global.u32 %0, [%1];" : "=r"(v) : "l"(p) : "memory"); return v; }
__device__ __forceinline__ void spin_until(const unsigned* p, unsigned target) {
  int it = 0;
  while ((int)(ld_relaxed(p) - target) < 0) {
    if (++it > (1 << 23)) __trap();
  }
}
__device__ __forceinline__ void spin_hint(const unsigned* p, unsigned target) {
  spin_until(p, target);
}
__device__ __forceinline__ uint4 ldcg128(const void* p) { uint4 v; asm volatile("ld.global.cg.v4.b32 {%0,%1,%2,%3}, [%4];" : "=r"(v.x), "=r"(v.y), "=r"(v.z), "=r"(v.w) : "l"(p) : "memory"); return v; }
__device__ __forceinline__ uint4 ld_tagged(const uint4* p) { uint4 v; asm volatile("ld.relaxed.gpu.global.v4.u32 {%0,%1,%2,%3}, [%4];" : "=r"(v.x), "=r"(v.y), "=r"(v.z), "=r"(v.w) : "l"(p) : "memory"); return v; }
__device__ __forceinline__ void st_tagged(uint4* p, uint32_t a, uint32_t b, uint32_t tag) { asm volatile("st.relaxed.gpu.global.v4.u32 [%0], {%1,%2,%3,%2};" ::"l"(p), "r"(a), "r"(tag), "r"(b) : "memory"); }
__device__ __forceinline__ void st_tagged3(uint4* p, uint32_t a, uint32_t b, uint32_t c, uint32_t tag) { asm volatile("st.relaxed.gpu.global.v4.u32 [%0], {%1,%2,%3,%4};" ::"l"(p), "r"(a), "r"(b), "r"(c), "r"(tag) : "memory"); }
__device__ __forceinline__ uint4 poll_tagged(const uint4* p, uint32_t tag) {
  uint4 v = ld_tagged(p);
  int it = 0;
  while (v.y != tag || v.w != tag) {
    if (++it > (1 << 22)) __trap();
    v = ld_tagged(p);
  }
  return v;
}
__device__ __forceinline__ uint32_t hadd2(uint32_t a, uint32_t b) { uint32_t r; asm("add.rn.bf16x2 %0, %1, %2;" : "=r"(r) : "r"(a), "r"(b)); return r; }
__device__ __forceinline__ uint32_t hmul2(uint32_t a, uint32_t b) { uint32_t r; asm("mul.rn.bf16x2 %0, %1, %2;" : "=r"(r) : "r"(a), "r"(b)); return r; }

__device__ __forceinline__ uint32_t hfma2(uint32_t a, uint32_t b, uint32_t c) { uint32_t r; asm("fma.rn.bf16x2 %0, %1, %2, %3;" : "=r"(r) : "r"(a), "r"(b), "r"(c)); return r; }
__device__ __forceinline__ void sts32(uint32_t a, uint32_t v) { asm volatile("st.shared.u32 [%0], %1;" ::"r"(a), "r"(v) : "memory"); }

template <int N> __device__ __forceinline__ void acc_fence(float* a) {
#pragma unroll
  for (int i = 0; i < N; i++) asm volatile("" : "+f"(a[i]) :: "memory");
}

template<int N,int TB> __device__ __forceinline__ void wgmma_rs(float* d, const uint32_t* a, uint64_t db, int sd);
template<int N,int TA,int TB> __device__ __forceinline__ void wgmma_ss(float* d, uint64_t da, uint64_t db, int sd);
template<> __device__ __forceinline__ void wgmma_rs<64,0>(float* d, const uint32_t* a, uint64_t db, int sd) {
  asm volatile("{\n.reg .pred p;\nsetp.ne.b32 p, %37, 0;\nwgmma.mma_async.sync.aligned.m64n64k16.f32.bf16.bf16 {%0,%1,%2,%3,%4,%5,%6,%7,%8,%9,%10,%11,%12,%13,%14,%15,%16,%17,%18,%19,%20,%21,%22,%23,%24,%25,%26,%27,%28,%29,%30,%31}, {%32,%33,%34,%35}, %36, p, 1, 1, 0;\n}\n"
   : "+f"(d[0]),"+f"(d[1]),"+f"(d[2]),"+f"(d[3]),"+f"(d[4]),"+f"(d[5]),"+f"(d[6]),"+f"(d[7]),"+f"(d[8]),"+f"(d[9]),"+f"(d[10]),"+f"(d[11]),"+f"(d[12]),"+f"(d[13]),"+f"(d[14]),"+f"(d[15]),"+f"(d[16]),"+f"(d[17]),"+f"(d[18]),"+f"(d[19]),"+f"(d[20]),"+f"(d[21]),"+f"(d[22]),"+f"(d[23]),"+f"(d[24]),"+f"(d[25]),"+f"(d[26]),"+f"(d[27]),"+f"(d[28]),"+f"(d[29]),"+f"(d[30]),"+f"(d[31])
   : "r"(a[0]), "r"(a[1]), "r"(a[2]), "r"(a[3]), "l"(db), "r"(sd));
}
template<> __device__ __forceinline__ void wgmma_rs<56,0>(float* d, const uint32_t* a, uint64_t db, int sd) {
  asm volatile("{\n.reg .pred p;\nsetp.ne.b32 p, %33, 0;\nwgmma.mma_async.sync.aligned.m64n56k16.f32.bf16.bf16 {%0,%1,%2,%3,%4,%5,%6,%7,%8,%9,%10,%11,%12,%13,%14,%15,%16,%17,%18,%19,%20,%21,%22,%23,%24,%25,%26,%27}, {%28,%29,%30,%31}, %32, p, 1, 1, 0;\n}\n"
   : "+f"(d[0]),"+f"(d[1]),"+f"(d[2]),"+f"(d[3]),"+f"(d[4]),"+f"(d[5]),"+f"(d[6]),"+f"(d[7]),"+f"(d[8]),"+f"(d[9]),"+f"(d[10]),"+f"(d[11]),"+f"(d[12]),"+f"(d[13]),"+f"(d[14]),"+f"(d[15]),"+f"(d[16]),"+f"(d[17]),"+f"(d[18]),"+f"(d[19]),"+f"(d[20]),"+f"(d[21]),"+f"(d[22]),"+f"(d[23]),"+f"(d[24]),"+f"(d[25]),"+f"(d[26]),"+f"(d[27])
   : "r"(a[0]), "r"(a[1]), "r"(a[2]), "r"(a[3]), "l"(db), "r"(sd));
}
template<> __device__ __forceinline__ void wgmma_rs<48,0>(float* d, const uint32_t* a, uint64_t db, int sd) {
  asm volatile("{\n.reg .pred p;\nsetp.ne.b32 p, %29, 0;\nwgmma.mma_async.sync.aligned.m64n48k16.f32.bf16.bf16 {%0,%1,%2,%3,%4,%5,%6,%7,%8,%9,%10,%11,%12,%13,%14,%15,%16,%17,%18,%19,%20,%21,%22,%23}, {%24,%25,%26,%27}, %28, p, 1, 1, 0;\n}\n"
   : "+f"(d[0]),"+f"(d[1]),"+f"(d[2]),"+f"(d[3]),"+f"(d[4]),"+f"(d[5]),"+f"(d[6]),"+f"(d[7]),"+f"(d[8]),"+f"(d[9]),"+f"(d[10]),"+f"(d[11]),"+f"(d[12]),"+f"(d[13]),"+f"(d[14]),"+f"(d[15]),"+f"(d[16]),"+f"(d[17]),"+f"(d[18]),"+f"(d[19]),"+f"(d[20]),"+f"(d[21]),"+f"(d[22]),"+f"(d[23])
   : "r"(a[0]), "r"(a[1]), "r"(a[2]), "r"(a[3]), "l"(db), "r"(sd));
}
template<> __device__ __forceinline__ void wgmma_rs<40,0>(float* d, const uint32_t* a, uint64_t db, int sd) {
  asm volatile("{\n.reg .pred p;\nsetp.ne.b32 p, %25, 0;\nwgmma.mma_async.sync.aligned.m64n40k16.f32.bf16.bf16 {%0,%1,%2,%3,%4,%5,%6,%7,%8,%9,%10,%11,%12,%13,%14,%15,%16,%17,%18,%19}, {%20,%21,%22,%23}, %24, p, 1, 1, 0;\n}\n"
   : "+f"(d[0]),"+f"(d[1]),"+f"(d[2]),"+f"(d[3]),"+f"(d[4]),"+f"(d[5]),"+f"(d[6]),"+f"(d[7]),"+f"(d[8]),"+f"(d[9]),"+f"(d[10]),"+f"(d[11]),"+f"(d[12]),"+f"(d[13]),"+f"(d[14]),"+f"(d[15]),"+f"(d[16]),"+f"(d[17]),"+f"(d[18]),"+f"(d[19])
   : "r"(a[0]), "r"(a[1]), "r"(a[2]), "r"(a[3]), "l"(db), "r"(sd));
}
template<> __device__ __forceinline__ void wgmma_rs<32,0>(float* d, const uint32_t* a, uint64_t db, int sd) {
  asm volatile("{\n.reg .pred p;\nsetp.ne.b32 p, %21, 0;\nwgmma.mma_async.sync.aligned.m64n32k16.f32.bf16.bf16 {%0,%1,%2,%3,%4,%5,%6,%7,%8,%9,%10,%11,%12,%13,%14,%15}, {%16,%17,%18,%19}, %20, p, 1, 1, 0;\n}\n"
   : "+f"(d[0]),"+f"(d[1]),"+f"(d[2]),"+f"(d[3]),"+f"(d[4]),"+f"(d[5]),"+f"(d[6]),"+f"(d[7]),"+f"(d[8]),"+f"(d[9]),"+f"(d[10]),"+f"(d[11]),"+f"(d[12]),"+f"(d[13]),"+f"(d[14]),"+f"(d[15])
   : "r"(a[0]), "r"(a[1]), "r"(a[2]), "r"(a[3]), "l"(db), "r"(sd));
}
template<> __device__ __forceinline__ void wgmma_rs<24,0>(float* d, const uint32_t* a, uint64_t db, int sd) {
  asm volatile("{\n.reg .pred p;\nsetp.ne.b32 p, %17, 0;\nwgmma.mma_async.sync.aligned.m64n24k16.f32.bf16.bf16 {%0,%1,%2,%3,%4,%5,%6,%7,%8,%9,%10,%11}, {%12,%13,%14,%15}, %16, p, 1, 1, 0;\n}\n"
   : "+f"(d[0]),"+f"(d[1]),"+f"(d[2]),"+f"(d[3]),"+f"(d[4]),"+f"(d[5]),"+f"(d[6]),"+f"(d[7]),"+f"(d[8]),"+f"(d[9]),"+f"(d[10]),"+f"(d[11])
   : "r"(a[0]), "r"(a[1]), "r"(a[2]), "r"(a[3]), "l"(db), "r"(sd));
}
template<> __device__ __forceinline__ void wgmma_rs<16,0>(float* d, const uint32_t* a, uint64_t db, int sd) {
  asm volatile("{\n.reg .pred p;\nsetp.ne.b32 p, %13, 0;\nwgmma.mma_async.sync.aligned.m64n16k16.f32.bf16.bf16 {%0,%1,%2,%3,%4,%5,%6,%7}, {%8,%9,%10,%11}, %12, p, 1, 1, 0;\n}\n"
   : "+f"(d[0]),"+f"(d[1]),"+f"(d[2]),"+f"(d[3]),"+f"(d[4]),"+f"(d[5]),"+f"(d[6]),"+f"(d[7])
   : "r"(a[0]), "r"(a[1]), "r"(a[2]), "r"(a[3]), "l"(db), "r"(sd));
}
template<> __device__ __forceinline__ void wgmma_rs<8,0>(float* d, const uint32_t* a, uint64_t db, int sd) {
  asm volatile("{\n.reg .pred p;\nsetp.ne.b32 p, %9, 0;\nwgmma.mma_async.sync.aligned.m64n8k16.f32.bf16.bf16 {%0,%1,%2,%3}, {%4,%5,%6,%7}, %8, p, 1, 1, 0;\n}\n"
   : "+f"(d[0]),"+f"(d[1]),"+f"(d[2]),"+f"(d[3])
   : "r"(a[0]), "r"(a[1]), "r"(a[2]), "r"(a[3]), "l"(db), "r"(sd));
}
template<> __device__ __forceinline__ void wgmma_ss<64,1,0>(float* d, uint64_t da, uint64_t db, int sd) {
  asm volatile("{\n.reg .pred p;\nsetp.ne.b32 p, %34, 0;\nwgmma.mma_async.sync.aligned.m64n64k16.f32.bf16.bf16 {%0,%1,%2,%3,%4,%5,%6,%7,%8,%9,%10,%11,%12,%13,%14,%15,%16,%17,%18,%19,%20,%21,%22,%23,%24,%25,%26,%27,%28,%29,%30,%31}, %32, %33, p, 1, 1, 1, 0;\n}\n"
   : "+f"(d[0]),"+f"(d[1]),"+f"(d[2]),"+f"(d[3]),"+f"(d[4]),"+f"(d[5]),"+f"(d[6]),"+f"(d[7]),"+f"(d[8]),"+f"(d[9]),"+f"(d[10]),"+f"(d[11]),"+f"(d[12]),"+f"(d[13]),"+f"(d[14]),"+f"(d[15]),"+f"(d[16]),"+f"(d[17]),"+f"(d[18]),"+f"(d[19]),"+f"(d[20]),"+f"(d[21]),"+f"(d[22]),"+f"(d[23]),"+f"(d[24]),"+f"(d[25]),"+f"(d[26]),"+f"(d[27]),"+f"(d[28]),"+f"(d[29]),"+f"(d[30]),"+f"(d[31])
   : "l"(da), "l"(db), "r"(sd));
}
template<> __device__ __forceinline__ void wgmma_ss<64,0,1>(float* d, uint64_t da, uint64_t db, int sd) {
  asm volatile("{\n.reg .pred p;\nsetp.ne.b32 p, %34, 0;\nwgmma.mma_async.sync.aligned.m64n64k16.f32.bf16.bf16 {%0,%1,%2,%3,%4,%5,%6,%7,%8,%9,%10,%11,%12,%13,%14,%15,%16,%17,%18,%19,%20,%21,%22,%23,%24,%25,%26,%27,%28,%29,%30,%31}, %32, %33, p, 1, 1, 0, 1;\n}\n"
   : "+f"(d[0]),"+f"(d[1]),"+f"(d[2]),"+f"(d[3]),"+f"(d[4]),"+f"(d[5]),"+f"(d[6]),"+f"(d[7]),"+f"(d[8]),"+f"(d[9]),"+f"(d[10]),"+f"(d[11]),"+f"(d[12]),"+f"(d[13]),"+f"(d[14]),"+f"(d[15]),"+f"(d[16]),"+f"(d[17]),"+f"(d[18]),"+f"(d[19]),"+f"(d[20]),"+f"(d[21]),"+f"(d[22]),"+f"(d[23]),"+f"(d[24]),"+f"(d[25]),"+f"(d[26]),"+f"(d[27]),"+f"(d[28]),"+f"(d[29]),"+f"(d[30]),"+f"(d[31])
   : "l"(da), "l"(db), "r"(sd));
}
template<> __device__ __forceinline__ void wgmma_ss<192,0,1>(float* d, uint64_t da, uint64_t db, int sd) {
  asm volatile("{\n.reg .pred p;\nsetp.ne.b32 p, %98, 0;\nwgmma.mma_async.sync.aligned.m64n192k16.f32.bf16.bf16 {%0,%1,%2,%3,%4,%5,%6,%7,%8,%9,%10,%11,%12,%13,%14,%15,%16,%17,%18,%19,%20,%21,%22,%23,%24,%25,%26,%27,%28,%29,%30,%31,%32,%33,%34,%35,%36,%37,%38,%39,%40,%41,%42,%43,%44,%45,%46,%47,%48,%49,%50,%51,%52,%53,%54,%55,%56,%57,%58,%59,%60,%61,%62,%63,%64,%65,%66,%67,%68,%69,%70,%71,%72,%73,%74,%75,%76,%77,%78,%79,%80,%81,%82,%83,%84,%85,%86,%87,%88,%89,%90,%91,%92,%93,%94,%95}, %96, %97, p, 1, 1, 0, 1;\n}\n"
   : "+f"(d[0]),"+f"(d[1]),"+f"(d[2]),"+f"(d[3]),"+f"(d[4]),"+f"(d[5]),"+f"(d[6]),"+f"(d[7]),"+f"(d[8]),"+f"(d[9]),"+f"(d[10]),"+f"(d[11]),"+f"(d[12]),"+f"(d[13]),"+f"(d[14]),"+f"(d[15]),"+f"(d[16]),"+f"(d[17]),"+f"(d[18]),"+f"(d[19]),"+f"(d[20]),"+f"(d[21]),"+f"(d[22]),"+f"(d[23]),"+f"(d[24]),"+f"(d[25]),"+f"(d[26]),"+f"(d[27]),"+f"(d[28]),"+f"(d[29]),"+f"(d[30]),"+f"(d[31]),"+f"(d[32]),"+f"(d[33]),"+f"(d[34]),"+f"(d[35]),"+f"(d[36]),"+f"(d[37]),"+f"(d[38]),"+f"(d[39]),"+f"(d[40]),"+f"(d[41]),"+f"(d[42]),"+f"(d[43]),"+f"(d[44]),"+f"(d[45]),"+f"(d[46]),"+f"(d[47]),"+f"(d[48]),"+f"(d[49]),"+f"(d[50]),"+f"(d[51]),"+f"(d[52]),"+f"(d[53]),"+f"(d[54]),"+f"(d[55]),"+f"(d[56]),"+f"(d[57]),"+f"(d[58]),"+f"(d[59]),"+f"(d[60]),"+f"(d[61]),"+f"(d[62]),"+f"(d[63]),"+f"(d[64]),"+f"(d[65]),"+f"(d[66]),"+f"(d[67]),"+f"(d[68]),"+f"(d[69]),"+f"(d[70]),"+f"(d[71]),"+f"(d[72]),"+f"(d[73]),"+f"(d[74]),"+f"(d[75]),"+f"(d[76]),"+f"(d[77]),"+f"(d[78]),"+f"(d[79]),"+f"(d[80]),"+f"(d[81]),"+f"(d[82]),"+f"(d[83]),"+f"(d[84]),"+f"(d[85]),"+f"(d[86]),"+f"(d[87]),"+f"(d[88]),"+f"(d[89]),"+f"(d[90]),"+f"(d[91]),"+f"(d[92]),"+f"(d[93]),"+f"(d[94]),"+f"(d[95])
   : "l"(da), "l"(db), "r"(sd));
}
template<> __device__ __forceinline__ void wgmma_ss<192,1,1>(float* d, uint64_t da, uint64_t db, int sd) {
  asm volatile("{\n.reg .pred p;\nsetp.ne.b32 p, %98, 0;\nwgmma.mma_async.sync.aligned.m64n192k16.f32.bf16.bf16 {%0,%1,%2,%3,%4,%5,%6,%7,%8,%9,%10,%11,%12,%13,%14,%15,%16,%17,%18,%19,%20,%21,%22,%23,%24,%25,%26,%27,%28,%29,%30,%31,%32,%33,%34,%35,%36,%37,%38,%39,%40,%41,%42,%43,%44,%45,%46,%47,%48,%49,%50,%51,%52,%53,%54,%55,%56,%57,%58,%59,%60,%61,%62,%63,%64,%65,%66,%67,%68,%69,%70,%71,%72,%73,%74,%75,%76,%77,%78,%79,%80,%81,%82,%83,%84,%85,%86,%87,%88,%89,%90,%91,%92,%93,%94,%95}, %96, %97, p, 1, 1, 1, 1;\n}\n"
   : "+f"(d[0]),"+f"(d[1]),"+f"(d[2]),"+f"(d[3]),"+f"(d[4]),"+f"(d[5]),"+f"(d[6]),"+f"(d[7]),"+f"(d[8]),"+f"(d[9]),"+f"(d[10]),"+f"(d[11]),"+f"(d[12]),"+f"(d[13]),"+f"(d[14]),"+f"(d[15]),"+f"(d[16]),"+f"(d[17]),"+f"(d[18]),"+f"(d[19]),"+f"(d[20]),"+f"(d[21]),"+f"(d[22]),"+f"(d[23]),"+f"(d[24]),"+f"(d[25]),"+f"(d[26]),"+f"(d[27]),"+f"(d[28]),"+f"(d[29]),"+f"(d[30]),"+f"(d[31]),"+f"(d[32]),"+f"(d[33]),"+f"(d[34]),"+f"(d[35]),"+f"(d[36]),"+f"(d[37]),"+f"(d[38]),"+f"(d[39]),"+f"(d[40]),"+f"(d[41]),"+f"(d[42]),"+f"(d[43]),"+f"(d[44]),"+f"(d[45]),"+f"(d[46]),"+f"(d[47]),"+f"(d[48]),"+f"(d[49]),"+f"(d[50]),"+f"(d[51]),"+f"(d[52]),"+f"(d[53]),"+f"(d[54]),"+f"(d[55]),"+f"(d[56]),"+f"(d[57]),"+f"(d[58]),"+f"(d[59]),"+f"(d[60]),"+f"(d[61]),"+f"(d[62]),"+f"(d[63]),"+f"(d[64]),"+f"(d[65]),"+f"(d[66]),"+f"(d[67]),"+f"(d[68]),"+f"(d[69]),"+f"(d[70]),"+f"(d[71]),"+f"(d[72]),"+f"(d[73]),"+f"(d[74]),"+f"(d[75]),"+f"(d[76]),"+f"(d[77]),"+f"(d[78]),"+f"(d[79]),"+f"(d[80]),"+f"(d[81]),"+f"(d[82]),"+f"(d[83]),"+f"(d[84]),"+f"(d[85]),"+f"(d[86]),"+f"(d[87]),"+f"(d[88]),"+f"(d[89]),"+f"(d[90]),"+f"(d[91]),"+f"(d[92]),"+f"(d[93]),"+f"(d[94]),"+f"(d[95])
   : "l"(da), "l"(db), "r"(sd));
}

template <bool TR>
__device__ __forceinline__ void gemm_section(float* acc, float& mean0, float& mean1, float& rstd0, float& rstd1,
                                             uint32_t sb, int blk, int hg, int wg, int w, int lane) {
  constexpr int layer = TR ? 1 : 0;
  constexpr int TURN = TR ? TURN1 : TURN0;
  constexpr int LSTAT = TURN < 4 ? TURN - 1 : 3;
  const uint32_t bar = sb + SM_BAR;
  const int g = lane >> 2, t = lane & 3;
  const bool leader = (w == 0) && (lane == 0);
  const int statpos = hg < 3 ? 1 : wg ? LSTAT : TR ? 3 : 2;
  const bool copy = hg >= 3 && wg == 0;
  const int cut = wg ? TURN : 4;
  auto wait_full = [&](int c) {
    mbar_wait(bar + 8 * (B_XF + 8 * wg + c), layer);
    mbar_wait(bar + 8 * (B_WF + c), layer);
  };
  auto peek = [&](int c) {
    const bool x = mbar_test(bar + 8 * (B_XF + 8 * wg + c), layer), y = mbar_test(bar + 8 * (B_WF + c), layer);
    return x && y;
  };
  const uint64_t da0 = mkdesc(sb, TR ? 8192 : 16, 1024, 1), db0 = mkdesc(sb, 8192, 1024, 1);
  uint32_t xt = wg ? 0xfedcba98u : 0x21043210u;
  uint64_t wt = 0x0816131005161310ull;
  uint64_t da = da0 + ((xt & 15) << 9), db = db0 + (16 << 9);
  auto issue = [&](int c, int first) {
    wg_fence();
#pragma unroll
    for (int ks = 0; ks < 4; ks++) wgmma_ss<192, TR ? 1 : 0, 1>(acc, da + (TR ? ks * 128 : ks * 2), db + ks * 128, !first || ks != 0);
    wg_commit();
    xt >>= 4; wt >>= 8;
    da = da0 + ((xt & 15) << 9); db = db0 + (((uint32_t)wt & 31) << 9);
  };
  wait_full(0);
  bool ready = peek(1);
  issue(0, 1);
  TSW(0);
#pragma unroll 1
  for (int c = 1; c < cut; c++) {
    if (!ready) wait_full(c);
    issue(c, 0);
    ready = peek(c + 1);
    wg_wait<1>();
    if (leader) mbar_arrive(bar + 8 * (B_DN + 8 * wg + c - 1));
    if (wg == 1 && c == cut - 1) {
      wg_wait<0>();
      if (leader) mbar_arrive(bar + 8 * (B_DN + 8 + c));
    }
    if (c == statpos) {
      mbar_wait(bar + 8 * (copy ? B_SC : B_XF + 8 * wg + hg), layer);
      uint32_t A[16];
      const uint32_t xb = sb + (copy ? P_R : 8 * wg + hg) * PG;
#pragma unroll
      for (int ks = 0; ks < 4; ks++) {
        if (!TR) {
          const int row = 16 * w + (lane & 15), kc = 2 * ks + (lane >> 4);
          ldsm4(&A[4 * ks], xb + row * 128 + ((kc ^ (row & 7)) << 4));
        } else {
          const int k = 16 * ks + (lane & 7) + 8 * (lane >> 4), pc = 2 * w + ((lane >> 3) & 1);
          ldsm4t(&A[4 * ks], xb + k * 128 + ((pc ^ (k & 7)) << 4));
        }
      }
      float s0 = 0.f, q0 = 0.f, s1 = 0.f, q1 = 0.f;
#pragma unroll
      for (int i = 0; i < 16; i += 2) {
        const float a = bf_lo(A[i]), b = bf_hi(A[i]), c_ = bf_lo(A[i + 1]), d = bf_hi(A[i + 1]);
        s0 += a + b; q0 = fmaf(a, a, q0); q0 = fmaf(b, b, q0);
        s1 += c_ + d; q1 = fmaf(c_, c_, q1); q1 = fmaf(d, d, q1);
      }
#pragma unroll
      for (int o = 1; o <= 2; o <<= 1) {
        s0 += __shfl_xor_sync(~0u, s0, o); q0 += __shfl_xor_sync(~0u, q0, o);
        s1 += __shfl_xor_sync(~0u, s1, o); q1 += __shfl_xor_sync(~0u, q1, o);
      }
      if (t < 2)
        asm volatile("red.relaxed.gpu.global.add.v4.f32 [%0], {%1,%2,%3,%4};" ::"l"(g_rows + layer * LSEQ + blk * 64 + 16 * w + g + 8 * t),
                     "f"(t ? s1 : s0), "f"(t ? q1 : q0), "f"(1.f), "f"(0.f) : "memory");
    }
  }
  if (wg == 1) {
#pragma unroll 1
    for (int c = cut; c < 8; c++) wait_full(c);
    ready = true;
    bar_sync(5, 256);
  }
#pragma unroll 1
  for (int c = cut; c < 8; c++) {
    if (!ready) wait_full(c);
    issue(c, 0);
    if (wg == 1) {
      wg_wait<2>();
      if (leader && c >= cut + 2) mbar_arrive(bar + 8 * (B_DN + 8 + c - 2));
    } else if (c == 7) {
      bar_arrive(5, 256);
    } else {
      ready = peek(c + 1);
      wg_wait<1>();
      if (leader) mbar_arrive(bar + 8 * (B_DN + c - 1));
    }
  }
  mbar_wait(bar + 8 * (B_LN + wg), layer);
  const float4 ln = lds128f(sb + ln_off(wg) + (8 * w + g) * 16);
  mean0 = ln.x; rstd0 = ln.y; mean1 = ln.z; rstd1 = ln.w;
  wg_wait<0>();
  acc_fence<96>(acc);
  if (leader) mbar_arrive(bar + 8 * (B_DN + 8 * wg + 7));
}

__device__ __forceinline__ void attn_phase(const Params& p, uint32_t sb, int layer, int rb, int hg, int wg, int w) {
  const int lane = opaque_tid() & 31;
  const int g = lane >> 2, t = lane & 3;
  const uint32_t bar = sb + SM_BAR;
  const int blk = 16 * wg + rb;
  float acc[96];
  float2 cs[24];
  float mean0, mean1, rstd0, rstd1;
  if (layer) gemm_section<true>(acc, mean0, mean1, rstd0, rstd1, sb, blk, hg, wg, w, lane);
  else gemm_section<false>(acc, mean0, mean1, rstd0, rstd1, sb, blk, hg, wg, w, lane);
  TSW(1);
#pragma unroll
  for (int j = 8; j < 24; j++) cs[j] = lds64f(sb + SM_CS + 4 * (8 * j + 2 * t));
  const uint32_t kvx = sb + (wg ? 22 : 0) * PG;

  uint32_t kb[4][8], vb[4][8], qa[4][4];
  {
    const float nm0 = -mean0 * rstd0, nm1 = -mean1 * rstd1;
    const int st_row = 16 * w + (lane & 7) + 8 * ((lane >> 3) & 1);
    const uint32_t st_base = kvx + st_row * 256;
    const bool sender = (w == 3 && blk < 31);
    uint4* halo = &g_halo[(blk * 8 + hg) * 256 + lane];
    uint32_t r[4][2][4];
#pragma unroll
    for (int h = 0; h < 4; h++) {
#pragma unroll
      for (int kv = 0; kv < 2; kv++) {
#pragma unroll
        for (int dh = 0; dh < 2; dh++) {
          const int j = 8 + kv * 8 + 2 * h + dh;
          const float2 c2 = cs[j];
          const float v0 = fmaf(acc[4 * j + 0], rstd0, nm0 * c2.x), v1 = fmaf(acc[4 * j + 1], rstd0, nm0 * c2.y);
          const float v2 = fmaf(acc[4 * j + 2], rstd1, nm1 * c2.x), v3 = fmaf(acc[4 * j + 3], rstd1, nm1 * c2.y);
          r[h][kv][2 * dh] = packbf(v0, v1);
          r[h][kv][2 * dh + 1] = packbf(v2, v3);
        }
      }
      if (sender) {
        stg128(halo + (2 * h) * 32, make_uint4(r[h][0][0], r[h][0][2], r[h][0][1], r[h][0][3]));
        stg128(halo + (2 * h + 1) * 32, make_uint4(r[h][1][0], r[h][1][1], r[h][1][2], r[h][1][3]));
      }
    }
#pragma unroll
    for (int j = 0; j < 8; j++) cs[j] = lds64f(sb + SM_CS + 4 * (8 * j + 2 * t));
    mbar_wait(bar + 8 * (B_DN + 7), layer);
#pragma unroll
    for (int h = 0; h < 4; h++) {
#pragma unroll
      for (int kv = 0; kv < 2; kv++) {
        const int chunk = 4 * h + 2 * kv + (lane >> 4);
        if (w < 3) stsm4(st_base + (((chunk & 8) | ((chunk ^ st_row) & 7)) << 4), r[h][kv][0], r[h][kv][1], r[h][kv][2], r[h][kv][3]);
      }
      kb[h][4] = r[h][0][0]; kb[h][5] = r[h][0][2]; kb[h][6] = r[h][0][1]; kb[h][7] = r[h][0][3];
      vb[h][4] = movm_t(r[h][1][0]); vb[h][5] = movm_t(r[h][1][1]); vb[h][6] = movm_t(r[h][1][2]); vb[h][7] = movm_t(r[h][1][3]);
    }
#pragma unroll
    for (int h = 0; h < 4; h++) {
#pragma unroll
      for (int dh = 0; dh < 2; dh++) {
        const int j = 2 * h + dh;
        const float2 c2 = cs[j];
        qa[h][2 * dh] = packbf(fmaf(-mean0, c2.x, acc[4 * j + 0]), fmaf(-mean0, c2.y, acc[4 * j + 1]));
        qa[h][2 * dh + 1] = packbf(fmaf(-mean1, c2.x, acc[4 * j + 2]), fmaf(-mean1, c2.y, acc[4 * j + 3]));
      }
    }
  }
  bar_sync(2 + wg, 128);
  TSW(2);
  {
    const uint32_t prev_base = kvx + (16 * w - 16) * 256;
    const int mi = lane >> 3;
    const int r = 8 * (mi >> 1) + (lane & 7), r2 = 8 * (mi & 1) + (lane & 7);
    if (w != 0) {
#pragma unroll
      for (int h = 0; h < 4; h++) {
        const int ch = 4 * h + (mi & 1), ch2 = 4 * h + 2 + (mi >> 1);
        ldsm4(&kb[h][0], prev_base + r * 256 + (((ch & 8) | ((ch ^ r) & 7)) << 4));
        ldsm4t(&vb[h][0], prev_base + r2 * 256 + (((ch2 & 8) | ((ch2 ^ r2) & 7)) << 4));
      }
    } else if (blk > 0) {
      uint4* src = &g_halo[((blk - 1) * 8 + hg) * 256 + lane];
      uint4 hv[8];
      int it = 0;
      bool ok;
      do {
        ok = true;
#pragma unroll
        for (int i = 0; i < 8; i++) hv[i] = ld_tagged(src + i * 32);
#pragma unroll
        for (int i = 0; i < 8; i++) ok = ok && hv[i].x != UNSET;
      } while (!__all_sync(~0u, ok) && ++it < (1 << 20));
      if (layer == 0) {
#pragma unroll
        for (int i = 0; i < 2; i++) stg128(src + i * 128 + (lane >> 1) * 6, make_uint4(UNSET, UNSET, UNSET, UNSET));
      }
#pragma unroll
      for (int h = 0; h < 4; h++) {
        kb[h][0] = hv[2 * h].x; kb[h][1] = hv[2 * h].y; kb[h][2] = hv[2 * h].z; kb[h][3] = hv[2 * h].w;
        vb[h][0] = movm_t(hv[2 * h + 1].x); vb[h][1] = movm_t(hv[2 * h + 1].y);
        vb[h][2] = movm_t(hv[2 * h + 1].z); vb[h][3] = movm_t(hv[2 * h + 1].w);
      }
    } else {
#pragma unroll
      for (int h = 0; h < 4; h++)
#pragma unroll
        for (int k = 0; k < 4; k++) kb[h][k] = vb[h][k] = 0u;
    }
    TSW(3);
  }
  mbar_wait(bar + 8 * (B_DN + 15), layer);
  TSW(4);

  const bool first = (blk == 0 && w == 0);
  const int e = t - (g >> 1);
  const bool par = g & 1, epos = e >= 1;
  const uint32_t pmask = par ? 0xffff0000u : 0x0000ffffu;
  const uint32_t mB0 = epos ? pmask : 0u, mB1 = epos ? 0u : pmask;
  const float cl2 = 0.25f * 1.4426950408889634f;
  const float sc0 = rstd0 * cl2, sc1 = rstd1 * cl2;
  const float NEG = -INFINITY;
  float vA0[4], vB0[4], vA1[4], vB1[4];
#pragma unroll
  for (int h = 0; h < 4; h++) {
    float S[4][4];
#pragma unroll
    for (int j = 0; j < 4; j++) {
      S[j][0] = S[j][1] = S[j][2] = S[j][3] = 0.f;
      mma_bf16(S[j], qa[h], kb[h][2 * j], kb[h][2 * j + 1]);
    }
    vA0[h] = par ? S[1][1] : S[1][0];
    vB0[h] = epos ? (par ? S[0][1] : S[0][0]) : (par ? S[2][1] : S[2][0]);
    vA1[h] = par ? S[2][3] : S[2][2];
    vB1[h] = epos ? (par ? S[1][3] : S[1][2]) : (par ? S[3][3] : S[3][2]);
    if (first) { vA0[h] = NEG; if (epos) { vB0[h] = NEG; vB1[h] = NEG; } }
  }
  float m0[4], m1[4];
#pragma unroll
  for (int h = 0; h < 4; h++) { m0[h] = fmaxf(vA0[h], vB0[h]); m1[h] = fmaxf(vA1[h], vB1[h]); }
#pragma unroll
  for (int o = 1; o <= 2; o <<= 1) {
#pragma unroll
    for (int h = 0; h < 4; h++) {
      m0[h] = fmaxf(m0[h], __shfl_xor_sync(~0u, m0[h], o));
      m1[h] = fmaxf(m1[h], __shfl_xor_sync(~0u, m1[h], o));
    }
  }
  float O0[4][4], O1[4][4], Z[4][4];
#pragma unroll
  for (int h = 0; h < 4; h++) {
    const float mm0 = -m0[h] * sc0, mm1 = -m1[h] * sc1;
    const float pA0 = ex2(fmaf(vA0[h], sc0, mm0)), pB0 = ex2(fmaf(vB0[h], sc0, mm0));
    const float pA1 = ex2(fmaf(vA1[h], sc1, mm1)), pB1 = ex2(fmaf(vB1[h], sc1, mm1));
    const uint32_t hA0 = packbf(pA0, pA0), hB0 = packbf(pB0, pB0), hA1 = packbf(pA1, pA1), hB1 = packbf(pB1, pB1);
    const uint32_t P0[4] = {hB0 & mB0, 0u, hA0 & pmask, hB1 & mB0};
    const uint32_t P1[4] = {hB0 & mB1, hA1 & pmask, 0u, hB1 & mB1};
#pragma unroll
    for (int k = 0; k < 4; k++) O0[h][k] = O1[h][k] = Z[h][k] = 0.f;
    mma_bf16(O0[h], P0, vb[h][0], vb[h][1]); mma_bf16(O1[h], P0, vb[h][2], vb[h][3]); mma_bf16(Z[h], P0, 0x3f803f80u, 0x3f803f80u);
    mma_bf16(O0[h], P1, vb[h][4], vb[h][5]); mma_bf16(O1[h], P1, vb[h][6], vb[h][7]); mma_bf16(Z[h], P1, 0x3f803f80u, 0x3f803f80u);
  }
  if (lane == 0) mbar_arrive(bar + 8 * (B_OST + wg));
  uint4* op = (uint4*)g_O + ((layer * 32 + blk) * 8 + hg) * 512 + 64 * t + 16 * w + g;
#pragma unroll
  for (int h = 0; h < 4; h += 2) {
    const float i0 = rcp_approx(Z[h][0]), i1 = rcp_approx(Z[h][2]), j0 = rcp_approx(Z[h + 1][0]), j1 = rcp_approx(Z[h + 1][2]);
    stg128(op + 128 * h, make_uint4(packbf(O0[h][0] * i0, O0[h][1] * i0), packbf(O1[h][0] * i0, O1[h][1] * i0),
                                   packbf(O0[h + 1][0] * j0, O0[h + 1][1] * j0), packbf(O1[h + 1][0] * j0, O1[h + 1][1] * j0)));
    stg128(op + 128 * h + 8, make_uint4(packbf(O0[h][2] * i1, O0[h][3] * i1), packbf(O1[h][2] * i1, O1[h][3] * i1),
                                            packbf(O0[h + 1][2] * j1, O0[h + 1][3] * j1), packbf(O1[h + 1][2] * j1, O1[h + 1][3] * j1)));
  }
  TSW(5);
  __syncwarp();
  if (lane == 0) red_relaxed(&g_cnt[(C_O + layer * 32 + blk) * 32]);
  TSW(6);
}

#define LPRE 1
__device__ __forceinline__ void conv_load(uint32_t* A, uint32_t pe);
__device__ __forceinline__ void proj_phase(const Params& p, uint32_t sb, int layer, int rb, int q, int& rtp, uint32_t* A0, uint32_t* A1) {
  const int lane = opaque_tid() & 31;
  const int wg = __shfl_sync(~0u, opaque_tid() >> 7, 0), w = __shfl_sync(~0u, (opaque_tid() >> 5) & 3, 0);
  const bool TR = layer != 0;
  const int t = lane & 3;
  const uint32_t bar = sb + SM_BAR;
  const uint32_t rbx = sb + (P_R + wg) * PG;
  const uint32_t rsrc = sb + (wg ? 2 : P_R) * PG;
  const int blk = 16 * wg + rb;
  mbar_wait(bar + 8 * (B_RF + wg), layer);
  if (layer) mbar_wait(bar + 8 * B_RS, 0);
  mbar_wait(bar + 8 * B_WOF, layer);
  fence_async_global();
  const uint32_t stg = sb + (wg ? SM_KGT : SM_STG);
  if (layer) {
    const uint32_t pe = sb + cv_pe(wg, 1) + 4 * (16 + 16 * w + (lane >> 2) - 2 * t);
    mbar_wait(bar + 8 * B_PE, 1);
    conv_load(A0, pe);
    conv_load(A1, pe + 2 * 4480);
    __syncwarp();
    if (lane == 0) mbar_arrive(bar + 8 * B_AL);
  } else {
#pragma unroll
    for (int i = 0; i < 68; i++) {
      asm volatile("mov.b32 %0, 0;" : "=r"(A0[i]));
      asm volatile("mov.b32 %0, 0;" : "=r"(A1[i]));
    }
  }
  bool clean = false;
#pragma unroll 1
  for (int attempt = 0; attempt < MAX_RETRY; attempt++) {
  uint32_t res[16];
  if (!TR) {
#pragma unroll
    for (int j = 0; j < 8; j += 2) {
      const int mi = lane >> 3;
      const int row = 16 * w + (lane & 7) + 8 * (mi & 1), ch = j + (mi >> 1);
      ldsm4(&res[2 * j], rsrc + row * 128 + ((ch ^ (row & 7)) << 4));
    }
  } else {
#pragma unroll
    for (int j = 0; j < 8; j += 2) {
      const int mi = lane >> 3;
      const int line = 8 * (j + (mi >> 1)) + (lane & 7), pc = 2 * w + (mi & 1);
      ldsm4t(&res[2 * j], rsrc + line * 128 + ((pc ^ (line & 7)) << 4));
    }
  }
  float acc[32];
#pragma unroll
  for (int j = 0; j < 16; j++) { acc[2 * j] = bf_lo(res[j]); acc[2 * j + 1] = bf_hi(res[j]); }
  acc_fence<32>(acc);
  if (wg && attempt == 0) bar_sync(7, 160);
  const int wg2 = __shfl_sync(~0u, opaque_tid() >> 7, 0);
  const uint64_t da0 = mkdesc(sb, 1024, 128, 0), db0 = mkdesc(sb, 8192, 1024, 1);
#pragma unroll
  for (int c = 0; c < 4; c++) {
    mbar_wait(bar + 8 * (B_OF + 4 * wg + c), layer);
    if (c == 0) TSW(7);
    const uint64_t da = da0 + (uint32_t)(o_page(wg2, c) * 512);
    wg_fence();
#pragma unroll
    for (int ks = 0; ks < 8; ks++) wgmma_ss<64, 0, 1>(acc, da + ks * 128, db0 + wo_page(2 * c + (ks >> 2)) * 512 + (ks & 3) * 128, 1);
    wg_commit();
  }
  if (wg) mbar_wait(bar + 8 * B_KG, 0);
  wg_wait<0>();
  acc_fence<32>(acc);
  TSW(8);
  if (!clean) {
    const float chk = acc[0] + acc[2];
    clean = __all_sync(~0u, chk == chk);
    if (clean && lane == 0) mbar_arrive(bar + 8 * (B_PDONE + wg));
  }
  float s0 = 0.f, q0 = 0.f, s1 = 0.f, q1 = 0.f;
  uint32_t o[16];
#pragma unroll
  for (int j = 0; j < 8; j++) {
    const float a = acc[4 * j], b = acc[4 * j + 1], c = acc[4 * j + 2], d = acc[4 * j + 3];
    o[2 * j] = packbf(a, b);
    o[2 * j + 1] = packbf(c, d);
    s0 += a + b; q0 = fmaf(a, a, q0); q0 = fmaf(b, b, q0);
    s1 += c + d; q1 = fmaf(c, c, q1); q1 = fmaf(d, d, q1);
  }
#pragma unroll
  for (int j = 0; j < 8; j += 2) {
    const int mi = lane >> 3;
    const int line = 8 * (j + (mi >> 1)) + (lane & 7), pc = 2 * w + (mi & 1);
    stsm4t(rbx + line * 128 + ((pc ^ (line & 7)) << 4), o[2 * j], o[2 * j + 1], o[2 * j + 2], o[2 * j + 3]);
  }
#pragma unroll
  for (int o2 = 1; o2 <= 2; o2 <<= 1) {
    s0 += __shfl_xor_sync(~0u, s0, o2); q0 += __shfl_xor_sync(~0u, q0, o2);
    s1 += __shfl_xor_sync(~0u, s1, o2); q1 += __shfl_xor_sync(~0u, q1, o2);
  }
  {
    const int i = 2 * (lane >> 2) + (t & 1), k = (i * 11) >> 5;
    const float v = (t == 0) ? s0 : (t == 1) ? q0 : (t == 2) ? s1 : q1;
    sts32f(stg + k * 128 + (2 * w + (t >> 1)) * 16 + (i - 3 * k) * 4, v);
  }
  TSW(9);
  fence_async_smem();
  if (!bar_or(2 + wg, 128, !clean)) break;
  bool unset = false;
#pragma unroll
  for (int i = 0; i < 4; i++) unset |= lds32(sb + o_page(wg, i) * PG + (32 * w + lane) * 128) == UNSET;
  if (!bar_or(2 + wg, 128, unset)) break;
  if (w == 0 && elect_one()) {
    fence_async_smem();
    mbar_expect(bar + 8 * (B_RT + wg), 9 * PG);
    if (layer == 0) tma_ld(rsrc, &p.mapX, q * 64, blk * 64, bar + 8 * (B_RT + wg));
    else tma_ld(rsrc, &p.mapXT, blk * 64, DM + q * 64, bar + 8 * (B_RT + wg));
#pragma unroll 1
    for (int c = 0; c < 4; c++) bulk_ld(sb + o_page(wg, c) * PG, g_O + ((layer * 32 + blk) * 4 + c) * PG, 2 * PG, bar + 8 * (B_RT + wg));
  }
  mbar_wait(bar + 8 * (B_RT + wg), rtp);
  rtp ^= 1;
  RETRY(0);
  }
  if (!clean && lane == 0) mbar_arrive(bar + 8 * (B_PDONE + wg));
  if (w == 0 && elect_one()) {
    tma_st(&p.mapXT, blk * 64, (2 * layer) * DM + q * 64, rbx);
    bulk_red_add_f32(g_stats + (layer * 32 + blk) * 192, stg, 768);
    bulk_commit();
    red_relaxed(&g_cnt[(C_G + 2 * layer + wg) * 32]);
  }
  if (wg == 0 && w == 0) bar_arrive(7, 160);
  TSW(10);
}

__device__ __forceinline__ void conv_load(uint32_t* A, uint32_t pe) {
#pragma unroll
  for (int m = 0; m < 17; m++) {
    A[4 * m + 2] = lds32(pe + 4 * (64 * m - 8));
    A[4 * m + 0] = lds32(pe + 4 * (64 * m));
    A[4 * m + 1] = lds32(pe + 4 * (64 * m + 8));
    asm volatile("mov.b32 %0, %1;" : "=r"(A[4 * m + 3]) : "r"(A[4 * m + 0]));
  }
}
template <int M> __device__ __forceinline__ void conv_tri(float* acc, const uint32_t* A, uint64_t d) {
  if constexpr (M < 16) {
    wgmma_rs<64 - 8 * (M / 2), 0>(acc, A + 4 * M, d + (uint64_t)(64 + 4 * M), M != 0);
    conv_tri<M + 1>(acc, A, d);
  }
}
__device__ __forceinline__ void conv_mma0(float* acc, const uint32_t* A, uint64_t d) {
  wg_fence();
  conv_tri<0>(acc, A, d);
  wg_commit();
}
__device__ __forceinline__ void conv_mma1_early(float* acc, const uint32_t* A, uint64_t d, uint64_t ds, uint64_t df) {
  wg_fence();
  wgmma_rs<64, 0>(acc, A + 64, d + 64, 0);
  wgmma_ss<64, 1, 0>(acc, ds, df, 1);
  wgmma_ss<64, 1, 0>(acc, ds + 128, df + 128, 1);
}
__device__ __forceinline__ void conv_mma1(float* acc, const uint32_t* A, uint64_t d) {
#pragma unroll
  for (int m = 0; m < 16; m++) wgmma_rs<64, 0>(acc, A + 4 * m, d + (uint64_t)(4 * m), 1);
  wg_commit();
}
__device__ __forceinline__ void conv_store(float* acc, uint32_t pb, uint32_t over, int w) {
  acc_fence<32>(acc);
  const int l = opaque_tid() & 31, mt = l >> 3;
  int c = 2 * (63 - 8 * (mt >> 1) - (l & 7) + w) + (mt & 1);
  c ^= (c >> 3) & 1;
  const uint32_t a0 = pb + c * 16;
#pragma unroll
  for (int j = 0; j < 8; j += 2)
    stsm4t(j == 0 ? (c < 128 ? a0 : over + (c - 128) * 16) : a0 - 256 * j, packbf(acc[4 * j], acc[4 * j + 1]), packbf(acc[4 * j + 2], acc[4 * j + 3]),
           packbf(acc[4 * j + 4], acc[4 * j + 5]), packbf(acc[4 * j + 6], acc[4 * j + 7]));
}
__device__ __forceinline__ void conv_sums(uint32_t sb, int lc, int ht) {
  const int m = ht - 1;
  uint4 v[2][3];
#pragma unroll
  for (int c = 0; c < 2; c++)
#pragma unroll
    for (int k = 0; k < 3; k++) {
      const int mm = m - 1 + k;
      v[c][k] = lds128(sb + cv_u(lc + c) + (mm >= 0 ? (mm & 1) * CV_UH + (127 - (mm >> 1)) * 16 : 128 * 16));
    }
  const int ce = m + 2, co = m + 1;
#pragma unroll
  for (int c = 0; c < 2; c++) {
    const uint32_t x[8] = {v[c][0].z, v[c][0].w, v[c][1].x, v[c][1].y, v[c][1].z, v[c][1].w, v[c][2].x, v[c][2].y};
    float pv[16];
#pragma unroll
    for (int k = 0; k < 8; k++) { pv[2 * k] = bf_lo(x[k]); pv[2 * k + 1] = bf_hi(x[k]); }
    float t2[15], t4[13], s9[8], s7[8];
#pragma unroll
    for (int i = 0; i < 15; i++) t2[i] = pv[i] + pv[i + 1];
#pragma unroll
    for (int i = 0; i < 13; i++) t4[i] = t2[i] + t2[i + 2];
#pragma unroll
    for (int i = 0; i < 8; i++) {
      s9[i] = (t4[i] + t4[i + 4]) + pv[i + 8];
      s7[i] = (t4[i + 1] + t2[i + 5]) + pv[i + 7];
    }
    const uint4 e4 = make_uint4(packbf(s9[0], s9[1]), packbf(s9[2], s9[3]), packbf(s9[4], s9[5]), packbf(s9[6], s9[7]));
    if (ce < 128) sts128(sb + cv_se(lc + c) + ((ce ^ ((ce >> 3) & 7)) << 4), e4);
    else sts128(sb + cv_se(lc + c), make_uint4(0, 0, 0, 0));
    sts128(sb + cv_so(lc + c) + ((co ^ ((co >> 3) & 7)) << 4),
           make_uint4(packbf(s7[0], s7[1]), packbf(s7[2], s7[3]), packbf(s7[4], s7[5]), packbf(s7[6], s7[7])));
  }
}

template <int HALF, int NCH, int STEP = 1>
__device__ __forceinline__ void conv_epi(uint32_t sb, bf16* out, int lc, int c) {
  uint4 v[NCH][4], xr[NCH];
  const uint32_t sw = (c ^ ((c >> 3) & 1)) * 16;
#pragma unroll
  for (int u = 0; u < NCH; u++) {
#pragma unroll
    for (int k = 0; k < 4; k++) v[u][k] = lds128(sb + (HALF ? cv_pb1(lc + STEP * u, k) : cv_pb0(lc + STEP * u, k)) + sw);
    xr[u] = lds128(sb + cv_x(HALF, lc + STEP * u) + c * 16);
  }
#pragma unroll
  for (int u = 0; u < NCH; u++) {
    uint4 o;
    o.x = hadd2(xr[u].x, hadd2(hadd2(v[u][0].x, v[u][1].x), hadd2(v[u][2].x, v[u][3].x)));
    o.y = hadd2(xr[u].y, hadd2(hadd2(v[u][0].y, v[u][1].y), hadd2(v[u][2].y, v[u][3].y)));
    o.z = hadd2(xr[u].z, hadd2(hadd2(v[u][0].z, v[u][1].z), hadd2(v[u][2].z, v[u][3].z)));
    o.w = hadd2(xr[u].w, hadd2(hadd2(v[u][0].w, v[u][1].w), hadd2(v[u][2].w, v[u][3].w)));
    stg128(out + cv_chan(0, lc + STEP * u) * LSEQ + HALF * 1024 + c * 8, o);
  }
}

__device__ __forceinline__ bool prep_valid(const uint4 (&st)[6], const uint4 (&xr)[4]) {
  const uint32_t n = __float_as_uint(8.f);
  return st[0].w == n && st[1].w == n && st[2].w == n && st[3].w == n && st[4].w == n && (st[5].w | st[5].y | st[5].z) == n &&
         xr[0].x != UNSET && xr[1].x != UNSET && xr[2].x != UNSET && xr[3].x != UNSET;
}
template <int HALF>
__device__ __forceinline__ void conv_prep(uint32_t sb, int layer, int cta, int i) {
  uint4 st[6], xr[4];
  const uint4* sp = (const uint4*)g_stats + (layer * 32 + HALF * 16 + (i >> 3)) * 48 + (i & 7);
  const uint4* xp = (const uint4*)g_xT + (2 * layer * DM + 2 * cta) * (LSEQ / 8) + HALF * 128 + i;
  auto fetch = [&]() {
#pragma unroll
    for (int k = 0; k < 6; k++) st[k] = ld_tagged(sp + 8 * k);
#pragma unroll
    for (int k = 0; k < 4; k++) xr[k] = ld_tagged(xp + cv_chan(0, k) * (LSEQ / 8));
  };
  if (HALF) {
#pragma unroll
    for (int k = 0; k < 6; k++) st[k] = lds128(sb + CV_ST + (i >> 3) * 768 + k * 128 + (i & 7) * 16);
#pragma unroll
    for (int k = 0; k < 4; k++) xr[k] = lds128(sb + cv_x(1, k) + i * 16);
  } else {
    fetch();
  }
  int it = 0;
  while (!__all_sync(~0u, prep_valid(st, xr)) && ++it < MAX_RETRY) { fetch(); RETRY(1); }
  if (!HALF || it) {
#pragma unroll
    for (int k = 0; k < 4; k++) sts128(sb + cv_x(HALF, k) + i * 16, xr[k]);
  }
  const uint32_t v[16] = {st[0].x, st[0].y, st[0].z, st[1].x, st[1].y, st[1].z, st[2].x, st[2].y, st[2].z, st[3].x, st[3].y, st[3].z, st[4].x, st[4].y, st[4].z, st[5].x};
  uint32_t rs[4], nm[4];
#pragma unroll
  for (int k = 0; k < 4; k++) {
    const float m0 = __uint_as_float(v[4 * k]) * (-1.f / DM), m1 = __uint_as_float(v[4 * k + 2]) * (-1.f / DM);
    const float r0 = rsqrt_approx(fmaxf(fmaf(__uint_as_float(v[4 * k + 1]), 1.f / DM, -m0 * m0), 0.f) + 1e-5f);
    const float r1 = rsqrt_approx(fmaxf(fmaf(__uint_as_float(v[4 * k + 3]), 1.f / DM, -m1 * m1), 0.f) + 1e-5f);
    rs[k] = packbf(r0, r1);
    nm[k] = packbf(m0 * bf_lo(rs[k]), m1 * bf_hi(rs[k]));
  }
  const uint32_t ud = sb + (i & 1) * CV_UH + (127 - 64 * HALF - (i >> 1)) * 16;
#pragma unroll
  for (int k = 0; k < 4; k++)
    sts128(ud + cv_u(k), make_uint4(hfma2(xr[k].x, rs[0], nm[0]), hfma2(xr[k].y, rs[1], nm[1]), hfma2(xr[k].z, rs[2], nm[2]), hfma2(xr[k].w, rs[3], nm[3])));
  fence_async_smem();
}

#define EARLY1 1
#define PP0 1
__device__ __forceinline__ void conv_phase(const Params& p, uint32_t sb, int layer, int cta, uint32_t* A0, uint32_t* A1) {
  const int tid = opaque_tid();
  const int wg = __shfl_sync(~0u, tid >> 7, 0), w = __shfl_sync(~0u, (tid >> 5) & 3, 0);
  const uint32_t bar = sb + SM_BAR;
  constexpr int CH2 = 4 * PG;
  bf16* xout = g_xT + ((2 * layer + 1) * DM + 2 * cta) * LSEQ;
  float acc[32];
  const uint32_t pe = sb + cv_pe(wg, 0) + 4 * (16 + 16 * w + ((tid & 31) >> 2) - 2 * (tid & 3));
  auto staged = [&]() {
    if (w == 0) {
      bulk_wait_read();
      __syncwarp();
      if (elect_one()) mbar_arrive(bar + 8 * (B_PST + wg));
    }
  };
  if (LPRE && layer) {
    staged();
  } else {
    if (wg == 0) staged();
    mbar_wait(bar + 8 * (B_PDONE + 1), layer);
    mbar_wait(bar + 8 * B_PE, layer);
    conv_load(A0, pe);
    if (wg == 1) staged();
    conv_load(A1, pe + CH2);
  }
  TSW(19);
  const uint64_t d0 = mkdesc(sb + cv_u(wg), CV_UH, 128, 0), d1 = d0 + (CH2 >> 4);
  mbar_wait(bar + 8 * B_U, layer);
  TSW(12);
  if (wg == 1) bar_sync(5, 256);
  conv_mma0(acc, A0, d0);
  if (wg == 0) bar_arrive(5, 256);
  mbar_wait(bar + 8 * (B_PDONE + 1), layer);
  {
    const int l = opaque_tid() & 31;
    if ((l & 15) < 2 * w) sts128(sb + cv_pb0(wg + 2 * (l >> 4), w) + (l & 15) * 16, make_uint4(0, 0, 0, 0));
  }
  wg_wait<0>();
  conv_store(acc, sb + cv_pb0(wg, w), sb + cv_pb1(wg, w), w);
  conv_mma0(acc, A1, d1);
  wg_wait<0>();
  conv_store(acc, sb + cv_pb0(2 + wg, w), sb + cv_pb1(2 + wg, w), w);
  TSW(13);
  bar_sync(2 + wg, 128);
  conv_epi<0, 2, 2>(sb, xout, wg, opaque_tid() & 127);
  TSW(14);
  mbar_arrive(bar + 8 * B_PUB);
  const uint64_t ds = mkdesc(sb + cv_se(wg), 8192, 1024, 1), df = mkdesc(sb + cv_fa(wg), 512, 128, 0);
  mbar_wait(bar + 8 * B_S, layer);
  conv_mma1_early(acc, A0, d0, ds, df);
  wg_commit();
  if (wg == 0) mbar_wait(bar + 8 * B_U1, layer);
  else bar_sync(6, 256);
  TSW(15);
  wg_fence();
  conv_mma1(acc, A0, d0);
  if (wg == 0) bar_arrive(6, 256);
  wg_wait<0>();
  conv_store(acc, sb + cv_pb1(wg, w), sb + cv_dump(wg), w);
  TSW(16);
  bar_sync(2 + wg, 128);
  conv_epi<1, 1>(sb, xout, wg, opaque_tid() & 127);
  mbar_arrive(bar + 8 * (B_PUB + 1));
  conv_mma1_early(acc, A1, d1, ds + 512, df + (CH2 >> 4));
  conv_mma1(acc, A1, d1);
  wg_wait<0>();
  conv_store(acc, sb + cv_pb1(2 + wg, w), sb + cv_dump(2 + wg), w);
  TSW(17);
  bar_sync(2 + wg, 128);
  conv_epi<1, 1>(sb, xout, 2 + wg, opaque_tid() & 127);
  mbar_arrive(bar + 8 * (B_PUB + 2));
  TSW(18);
}

__device__ __forceinline__ void final_tile(const Params& p, uint32_t buf, int ch0, int pos0, int barid) {
  const int tid = opaque_tid() & 127, lane = tid & 31, w = tid >> 5;
  const uint4* src = (const uint4*)(g_xT + (3 * DM + ch0 + (tid >> 3)) * LSEQ + pos0) + (tid & 7);
  const int ch = tid >> 3, row = 4 * (ch & 6) + 2 * (ch >> 3) + (ch & 1);
  const uint32_t dst = buf + row * 128;
  const uint32_t ld = buf + lane * 128;
  bf16* out = p.out + (pos0 + 16 * w + (lane >> 2)) * DM + ch0 + 8 * (lane & 3);
  uint4 a, b;
  int it = 0;
  do {
    if (it) RETRY(2);
    a = ld_tagged(src); b = ld_tagged(src + 16 * LSEQ / 8);
  } while (!__all_sync(~0u, a.x != UNSET && b.x != UNSET) && ++it < (1 << 20));
  sts128(dst + (((tid ^ row) & 7) << 4), a);
  sts128(dst + 512 + (((tid ^ row ^ 4) & 7) << 4), b);
  bar_sync(barid, 128);
#pragma unroll
  for (int h = 0; h < 2; h++) {
    uint32_t r[4];
    ldsm4t(r, ld + ((((2 * w + h) ^ lane) & 7) << 4));
    *(uint4*)(out + 8 * h * DM) = make_uint4(r[0], r[1], r[2], r[3]);
  }
}

struct cplx { float r, i; };
__device__ __forceinline__ cplx cmul(cplx a, cplx b) { return {fmaf(a.r, b.r, -a.i * b.i), fmaf(a.r, b.i, a.i * b.r)}; }
__device__ __forceinline__ cplx csqr(cplx a) { return {fmaf(a.r, a.r, -a.i * a.i), (a.r + a.r) * a.i}; }
__device__ __forceinline__ cplx cexp_l(float ar2, float ai, float l) {
  const float m = ex2(ar2 * l);
  const float x = ai * l;
  return {m * __cosf(x), m * __sinf(x)};
}

__device__ __forceinline__ void colsum_cta(const Params& p, uint32_t sb, int j, int tid) {
  const uint32_t bar = sb + SM_BAR;
  auto ld = [&](int i) {
    mbar_expect(bar + 8 * i, 3 * PG);
    tma_ld3(sb + (i & 7) * 3 * PG, &p.mapW3, (2 * j + (i & 1)) * 64, (i >> 1) * 64, 0, bar + 8 * i);
  };
  if (tid == 384) {
#pragma unroll
    for (int i = 0; i < 24; i++) mbar_init(bar + 8 * i, i < 16 ? 1 : 12);
    asm volatile("fence.mbarrier_init.release.cluster;" ::: "memory");
    fence_async_smem();
#pragma unroll 1
    for (int i = 0; i < 8; i++) ld(i);
  }
  const unsigned ep = ld_relaxed(&g_cnt[C_CS * 32]);
  bar_sync(0, NTHREADS);
  if (tid == 384) {
#pragma unroll 1
    for (int i = 8; i < 16; i++) { mbar_wait(bar + 8 * (8 + i), 0); fence_async_smem(); ld(i); }
  }
  if (tid < 384) {
    const int lane = tid & 31, cc = tid & 7, r0 = (tid >> 3) & 15, part = tid >> 7;
    const uint32_t id = ((lane >> 2) == 2 * (lane & 3) ? 0x3f80u : 0u) | ((lane >> 2) == 2 * (lane & 3) + 1 ? 0x3f800000u : 0u);
    const uint32_t src = sb + part * PG + r0 * 128 + ((cc ^ (r0 & 7)) << 4);
    float s[2][2][4];
#pragma unroll
    for (int i = 0; i < 16; i++) s[i >> 3][(i >> 2) & 1][i & 3] = 0.f;
#pragma unroll 1
    for (int i2 = 0; i2 < 16; i2 += 2) {
#pragma unroll
      for (int h = 0; h < 2; h++) {
        const int i = i2 + h;
        mbar_wait(bar + 8 * i, 0);
        uint4 v[4];
#pragma unroll
        for (int k = 0; k < 4; k++) v[k] = lds128(src + (i & 7) * 3 * PG + k * 2048);
#pragma unroll
        for (int k = 0; k < 4; k++) {
          const uint32_t a[4] = {v[k].x, v[k].y, v[k].z, v[k].w};
          mma_bf16(s[h][0], a, id, 0u);
          mma_bf16(s[h][1], a, 0u, id);
        }
        __syncwarp();
        if (i < 8 && lane == 0) mbar_arrive(bar + 8 * (16 + i));
      }
    }
    const uint32_t red = sb + 24 * PG;
#pragma unroll
    for (int h = 0; h < 2; h++)
#pragma unroll
      for (int k = 0; k < 2; k++) sts128f(red + (r0 * 384 + h * 192 + part * 64 + cc * 8 + k * 4) * 4, s[h][k][0], s[h][k][1], s[h][k][2], s[h][k][3]);
    bar_sync(1, 384);
    float tot = 0.f;
#pragma unroll
    for (int k = 0; k < 16; k++) tot += __uint_as_float(lds32(red + (k * 384 + tid) * 4));
    asm volatile("st.relaxed.gpu.global.v2.u32 [%0], {%1,%2};" ::"l"(&g_colsum[j * 384 + tid]), "r"(__float_as_uint(tot)), "r"(ep / NCTA + 1) : "memory");
    const uint4 u = make_uint4(UNSET, UNSET, UNSET, UNSET);
    if (tid < 256) {
#pragma unroll 1
      for (int s = 0; s < 4; s++) {
        const int n = (s == 1 || s == 2) ? 32 : 16;
        uint4* buf = s == 1 ? (uint4*)g_O + 131072 : (uint4*)g_xT + (s + !s) * 131072;
#pragma unroll 4
        for (int i = 0; i < n; i++) stg128(buf + (j * n + i) * 1024 + (tid >> 1) * 8 + (tid & 1), u);
        if (n == 16) {
#pragma unroll 4
          for (int i = 0; i < 8; i++) stg128(buf + (256 + j * 64 + i * 8 + (tid >> 5)) * 256 + (s ? 0 : 128) + ((tid & 31) >> 1) * 8 + (tid & 1), u);
        }
        if (s == 3) {
#pragma unroll 4
          for (int i = 0; i < 32; i++) stg128(buf + (256 + j * 64 + 2 * i + (tid >> 7)) * 256 + 128 + (tid & 127), u);
        }
        bar_sync(2, 256);
        if (tid == 32 * s) red_release(&g_cnt[(C_R + s) * 32]);
      }
    }
  }
}

#define KB 4
#define KW 2
struct ModeIn { uint32_t ar, ai, br, bi, cr, ci; bf16 logdt; };
__device__ __forceinline__ ModeIn load_modes(const Params& p, int d, int m) {
  const int i = d * 64 + m;
  return {((const uint32_t*)p.a_re)[i], ((const uint32_t*)p.a_im)[i], ((const uint32_t*)p.b_re)[i], ((const uint32_t*)p.b_im)[i],
          ((const uint32_t*)p.c_re)[i], ((const uint32_t*)p.c_im)[i], p.log_dt[d]};
}
__device__ __forceinline__ float4 lds128f_nv(uint32_t a) { float4 v; asm("ld.shared.v4.f32 {%0,%1,%2,%3}, [%4];" : "=f"(v.x), "=f"(v.y), "=f"(v.z), "=f"(v.w) : "r"(a)); return v; }
__device__ __forceinline__ void kernel_gen(const Params& p, uint32_t sb, int cta, int ht, ModeIn in, const ModeIn& in1) {
  const uint32_t bst = sb + SM_KGB + ((ht & 63) >> 2) * 144 + (ht & 3) * 4 + (ht >> 6) * 16;
  const uint64_t db = mkdesc(sb + SM_KGB, 144, 2304, 0);
  const float e0 = (float)(8 * (((ht & 32) >> 1) + ((ht & 31) >> 2)));
  float T[20];
#pragma unroll
  for (int i = 0; i < 20; i++) T[i] = 0.f;
  float k0 = 0.f;
#pragma unroll 1
  for (int pass = 0; pass < 4; pass++) {
    {
      const int sh = (pass & 1) ? 0 : 16;
      auto val = [&](uint32_t v) { return __uint_as_float((v << sh) & 0xffff0000u); };
      const float dt = __bfloat162float(__float2bfloat16_rn(expf(__bfloat162float(in.logdt))));
      const float ar2 = dt * val(in.ar) * 1.4426950408889634f, ai = dt * val(in.ai);
      const cplx c = cmul({val(in.cr), -val(in.ci)}, {dt * val(in.br), -dt * val(in.bi)});
      k0 += c.r;
      const cplx z1 = cexp_l(ar2, -ai, 1.f), z256 = cexp_l(ar2, -ai, 256.f), z64 = cexp_l(ar2, ai, 64.f);
      const cplx z2 = csqr(z1), z512 = csqr(z256);
      auto put = [&](int j, cplx v) { sts32(bst + (j >> 2) * 2304 + (j & 3) * 32, packbf(v.r, v.i)); };
      sts128f(sb + SM_KGT + ht * 16, ar2, ai, z64.r, z64.i);
      const cplx c1 = cmul(c, z1), c2 = cmul(c, z2), c3 = cmul(c1, z2), c4 = cmul(c2, z2);
      const cplx c5 = cmul(c3, z2), c6 = cmul(c4, z2), c7 = cmul(c5, z2), c8 = cmul(c6, z2);
      put(0, c1); put(1, c2); put(2, c3); put(3, c4); put(4, c5); put(5, c6); put(6, c7); put(7, c8);
      const cplx c260 = cmul(c4, z256), c264 = cmul(c8, z256), c520 = cmul(c8, z512), c776 = cmul(c264, z512);
      put(8, cmul(c2, z256)); put(9, c260); put(10, cmul(c6, z256)); put(11, c264);
      put(12, cmul(c4, z512)); put(13, c520); put(14, cmul(c260, z512)); put(15, c776);
      const cplx c1032 = cmul(c520, z512), c1288 = cmul(c776, z512);
      put(16, c1032); put(17, c1288); put(18, cmul(c1032, z512)); put(19, cmul(c1288, z512));
    }
    fence_async_smem();
    bar_sync(4, 128);
    const uint32_t tb = sb + SM_KGT + (ht & 67) * 16;
    float2 nx[KB];
#pragma unroll
    for (int s = 0; s < KB; s++) nx[s] = lds64f(tb + s * 64);
#pragma unroll
    for (int q = 0; q < 16 / KB; q++) {
      uint32_t A[2 * KB];
      float2 cur[KB], z[KB];
#pragma unroll
      for (int s = 0; s < KB; s++) { cur[s] = nx[s]; z[s] = lds64f(tb + (KB * q + s) * 64 + 8); }
      if (q < 16 / KB - 1) {
#pragma unroll
        for (int s = 0; s < KB; s++) nx[s] = lds64f(tb + (KB * q + KB + s) * 64);
      }
      if (q >= KW) wg_wait<KW - 1>();
#pragma unroll
      for (int s = 0; s < KB; s++) {
        const cplx lo = cexp_l(cur[s].x, cur[s].y, e0), hi = cmul(lo, {z[s].x, z[s].y});
        A[2 * s] = packbf(lo.r, lo.i);
        A[2 * s + 1] = packbf(hi.r, hi.i);
      }
      wg_fence();
#pragma unroll
      for (int k = 0; k < KB / 2; k++) wgmma_rs<40, 0>(T, A + 4 * k, db + 9 * KB * q + 18 * k, (pass & 1) | q | k);
      wg_commit();
    }
    wg_wait<0>();
    acc_fence<20>(T);
    if (ht == 0) TS(4 + pass);
    if (pass & 1) {
      const int h2 = opaque_tid() - 256, w = h2 >> 5, lane = h2 & 31, t = lane & 3, chn = h2 >> 6, m = h2 & 63, i0 = 16 * (w & 1) + (lane >> 2);
      const int lc = (pass & 2) + chn;
      const uint32_t kc = sb + kc_off(lc);
      auto put = [&](int idx, float v) {
        sts16(kc + idx * 2, __bfloat16_as_ushort(__float2bfloat16_rn(v)));
      };
#pragma unroll
      for (int hi = 0; hi < 2; hi++) {
        const int i = i0 + 8 * hi;
        float v[5];
#pragma unroll
        for (int j = 0; j < 5; j++) v[j] = chn ? T[4 * j + 2 * hi + 1] : T[4 * j + 2 * hi];
        put(8 * i + 1 + t, v[0]);
        put(8 * i + 5 + t, v[1]);
        put(257 + 4 * i + t, v[2]);
        put(385 + 2 * i + (t & 1) + 64 * (t >> 1), v[3]);
        put(513 + i + 32 * t, v[4]);
      }
#pragma unroll
      for (int o = 16; o > 0; o >>= 1) k0 += __shfl_xor_sync(~0u, k0, o);
      if (lane == 0) sts32f(sb + SM_RED + 4 * w, k0);
      bar_sync(4, 128);
      if (m == 0) put(0, k0 + __uint_as_float(lds32(sb + SM_RED + 4 * w + 4)) + __uint_as_float(lds16(sb + SM_RED + 24 + 2 * lc) << 16));
      k0 = 0.f;
      in = in1;
    }
  }
}

__device__ __forceinline__ void expand_taps(uint32_t sb, int ht, int early) {
  const int ch = ht >> 5, lane = ht & 31;
  const uint32_t kc = sb + kc_off(ch);
  const uint32_t dst0 = sb + cv_pe(ch, early);
  auto put = [&](int G, uint32_t v0, uint32_t v1, uint32_t v2, uint32_t v3, uint32_t v4, uint32_t v5, uint32_t v6, uint32_t v7, uint32_t v8) {
    const uint32_t dst = dst0 + G * 32;
    sts128(dst, make_uint4(v1 | (v0 << 16), v2 | (v1 << 16), v3 | (v2 << 16), v4 | (v3 << 16)));
    sts128(dst + 16, make_uint4(v5 | (v4 << 16), v6 | (v5 << 16), v7 | (v6 << 16), v8 | (v7 << 16)));
  };
  {
    const uint4 q = lds128(kc + lane * 16);
    const uint32_t pv = lane ? lds16(kc + lane * 16 - 2) : 0u;
    const uint32_t dst = dst0 + (lane + 2) * 32;
    sts128(dst, make_uint4(__byte_perm(q.x, pv, 0x5410), __byte_perm(q.x, q.x, 0x1032), __byte_perm(q.y, q.x, 0x7610), __byte_perm(q.y, q.y, 0x1032)));
    sts128(dst + 16, make_uint4(__byte_perm(q.z, q.y, 0x7610), __byte_perm(q.z, q.z, 0x1032), __byte_perm(q.w, q.z, 0x7610), __byte_perm(q.w, q.w, 0x1032)));
    if (lane < 4) sts128(dst0 + lane * 16, make_uint4(0, 0, 0, 0));
  }
  uint32_t a[5], b[2][3];
  {
    const uint32_t s1 = kc + 2 * (256 + 4 * lane);
#pragma unroll
    for (int k = 0; k < 5; k++) a[k] = lds16(s1 + 2 * k);
#pragma unroll
    for (int u = 0; u < 2; u++) {
      const uint32_t s2 = kc + 2 * (384 + 2 * (lane + 32 * u));
#pragma unroll
      for (int k = 0; k < 3; k++) b[u][k] = lds16(s2 + 2 * k);
    }
  }
  const uint32_t k255 = lds16(kc + 2 * 255), k1024 = lds16(kc + 2 * 512);
  put(34 + lane, lane == 0 ? k255 : a[0], a[0], a[0], a[1], a[2], a[2], a[2], a[3], a[4]);
#pragma unroll
  for (int u = 0; u < 2; u++) put(66 + lane + 32 * u, b[u][0], b[u][0], b[u][0], b[u][0], b[u][1], b[u][1], b[u][1], b[u][2], b[u][2]);
  if (lane < 10) {
    const uint32_t v = lane == 0 ? k1024 : 0u;
    put(130 + lane, v, v, v, v, v, v, 0u, 0u, 0u);
  }
}
__device__ __forceinline__ void expand_far(uint32_t sb, int ht) {
  const int ch = ht >> 5, lane = ht & 31;
  const uint32_t kc = sb + kc_off(ch) + 2 * (513 + 2 * (63 - lane)), dst = sb + cv_fa(ch) + lane * 16;
#pragma unroll
  for (int ty = 0; ty < 2; ty++) {
    uint32_t v[16];
#pragma unroll
    for (int k = 0; k < 16; k++) v[k] = (k < 8 || 63 - lane - 4 * k >= 0) ? lds16(kc + 2 * (1 - ty) - 16 * k) : 0u;
#pragma unroll
    for (int u = 0; u < 2; u++)
      sts128(dst + ty * 2048 + u * 512, make_uint4(v[8 * u] | (v[8 * u + 1] << 16), v[8 * u + 2] | (v[8 * u + 3] << 16), v[8 * u + 4] | (v[8 * u + 5] << 16), v[8 * u + 6] | (v[8 * u + 7] << 16)));
    sts128(dst + ty * 2048 + 1024, make_uint4(0, 0, 0, 0));
  }
}

#define TMPF 1
#define CONST_SB 1
#define XGATE B_OST
#define WPRE 1
__host__ __device__ constexpr int bar_count(int i) {
  return i == B_END ? 3 : i == B_LN ? 2 : i == B_AL ? 8 : i < B_OST ? 1 : i < B_PE ? 4 : (i >= B_PUB && i < B_S) ? 256 : 128;
}
__host__ __device__ constexpr bool bar_first(int i) { return i < B_WF + 2 && (i & 7) < 2; }

__global__ void __launch_bounds__(NTHREADS, 1) fused_kernel(const __grid_constant__ Params p) {
  extern __shared__ __align__(1024) uint8_t smem[];
  constexpr uint32_t sb = 1024;
  if (s32(smem) != sb) return;
  const int tid = threadIdx.x, lane = tid & 31;
  const int warp = __shfl_sync(~0u, tid >> 5, 0);
  if (tid == 32) {
    asm volatile("prefetch.tensormap [%0];" ::"l"(&p.mapX) : "memory");
    asm volatile("prefetch.tensormap [%0];" ::"l"(&p.mapW3) : "memory");
  }
  const int cta = blockIdx.x - (gridDim.x == NCTA + 4 ? 0 : 4);
  if ((unsigned)cta >= NCTA) {
    if (blockIdx.x < NCTA + 4) colsum_cta(p, sb, blockIdx.x & 3, tid);
    return;
  }
  const int rb = ((cta >> 4) & 3) * 4 + ((cta >> 2) & 3), hg = (cta >> 6) * 4 + (cta & 3);
  const uint32_t bar = sb + SM_BAR;
  auto ld_x0 = [&](int half, int c) {
    const uint32_t b = bar + 8 * (B_XF + 8 * half + c);
    mbar_expect(b, PG);
    tma_ld(sb + x_page(half, c) * PG, &p.mapX, c * 64, (16 * half + rb) * 64, b);
  };
  auto ld_x1 = [&](int half, int c, int b0) {
    const uint32_t b = bar + 8 * b0;
    mbar_expect(b, PG);
    tma_ld(sb + (8 * half + c) * PG, &p.mapXT, (16 * half + rb) * 64, DM + c * 64, b);
  };
  auto ld_w = [&](int c) {
    const uint32_t b = bar + 8 * (B_WF + c);
    mbar_expect(b, 3 * PG);
    tma_ld3(sb + w_page(c) * PG, &p.mapW3, hg * 64, c * 64, 0, b);
  };

  if (tid == 0) TS(0);
  if (tid == 480) LTS(0);
  if (warp == 0 && elect_one()) {
#pragma unroll
    for (int i = 0; i < B_WF + 2; i++)
      if (bar_first(i)) mbar_init(bar + 8 * i, 1);
    asm volatile("fence.mbarrier_init.release.cluster;" ::: "memory");
    fence_async_smem();
    ld_x0(0, 0);
    ld_w(0); ld_x0(1, 0);
    ld_x0(0, 1); ld_w(1); ld_x0(1, 1);
    TS(1);
  }
  __syncwarp();
  if (warp >= 1 && warp < 8 && elect_one()) {
    if (warp < 4) {
#pragma unroll
      for (int i = 2; i < 8; i++) mbar_init(bar + 8 * (8 * warp - 8 + i), 1);
    } else {
#pragma unroll
      for (int i = 0; i < 12; i++) mbar_init(bar + 8 * (12 * warp - 24 + i), 1);
    }
    asm volatile("fence.mbarrier_init.release.cluster;" ::: "memory");
  }
  if (warp == 15 && elect_one()) {
#pragma unroll
    for (int i = 72; i < B_COUNT; i++) mbar_init(bar + 8 * i, bar_count(i));
    asm volatile("fence.mbarrier_init.release.cluster;" ::: "memory");
  }

  if (warp < 8) {
    bar_sync(0, NTHREADS);
    asm volatile("setmaxnreg.inc.sync.aligned.u32 %0;" ::"n"(R_CONS));
    const int cw = __shfl_sync(~0u, opaque_tid() >> 5, 0);
    const int wg = cw >> 2, w = cw & 3;
    if (tid == 0) TS(2);
    int rtp = 0;
#pragma unroll 1
    for (int layer = 0; layer < 2; layer++) {
      attn_phase(p, sb, layer, rb, hg, wg, w);
      uint32_t A0[68], A1[68];
      proj_phase(p, sb, layer, rb, hg, rtp, A0, A1);
      conv_phase(p, sb, layer, cta, A0, A1);
    }
    if (wg == 0) mbar_wait(bar + 8 * (B_TF + 1), 0);
    if (tid == 128) TS(8);
    final_tile(p, sb + (16 + wg) * PG, 256 * wg + 32 * (cta >> 4), 1024 + 64 * (cta & 15), 2 + wg);
    if (tid == 128) TS(9);
    if (tid == 128) LTS(1);
    if (tid == 0) LTE();
  } else if (warp < 12) {
    asm volatile("setmaxnreg.dec.sync.aligned.u32 %0;" ::"n"(R_HELP));
    const int ht = tid - 256;
    {
      unsigned ep0 = 0;
      if (ht == 0) ep0 = ld_relaxed(&g_cnt[C_CS * 32]);
      const bf16 dsk = p.dskip[cv_chan(cta, ht & 3)];
      const ModeIn in0 = load_modes(p, cv_chan(cta, ht >> 6), ht & 63), in1 = load_modes(p, cv_chan(cta, 2 + (ht >> 6)), ht & 63);
      if (ht < 48) sts128f(sb + SM_STG + ht * 16, 0.f, 0.f, 0.f, 1.f);
      bar_sync(0, NTHREADS);
      if (ht == 0) {
        sts32(sb + SM_EP, ep0);
        mbar_arrive(bar + 8 * B_EP);
      }
      if (ht >= 124) sts16(sb + SM_RED + 24 + 2 * (ht & 3), __bfloat16_as_ushort(dsk));
      kernel_gen(p, sb, cta, ht, in0, in1);
      if (ht < 48) sts128f(sb + SM_KGT + ht * 16, 0.f, 0.f, 0.f, 1.f);
      fence_async_smem();
      bar_sync(4, 128);
      if (ht == 0) mbar_arrive(bar + 8 * B_KG);
    }
#pragma unroll 1
    for (int layer = 0; layer < 2; layer++) {
      const int early = LPRE && layer;
      if (early) mbar_wait(bar + 8 * (B_DN + 13), 1);
      mbar_wait(bar + 8 * (early ? XGATE : B_PDONE), layer);
      expand_taps(sb, opaque_tid() - 256, early);
      mbar_arrive(bar + 8 * B_PE);
      TSW(0);
      mbar_wait(bar + 8 * B_PDONE, layer);
      expand_far(sb, opaque_tid() - 256);
      {
        const int i = opaque_tid() - 256;
        if (i < 32) sts128(sb + cv_u(i >> 3) + ((i >> 2) & 1) * CV_UH + (128 + (i & 3)) * 16, make_uint4(0, 0, 0, 0));
        mbar_wait(bar + 8 * B_RC, layer);
        mbar_wait(bar + 8 * B_GB, layer);
        TSW(13);
        conv_prep<0>(sb, layer, cta, i);
        mbar_arrive(bar + 8 * B_U);
      }
      mbar_wait(bar + 8 * (B_PDONE + 1), layer);
      bar_sync(4, 128);
#pragma unroll 1
      for (int lc = 0; lc < 4; lc += 2) {
        conv_sums(sb, lc, opaque_tid() - 256);
        TSW(1 + lc);
      }
      fence_async_smem();
      mbar_arrive(bar + 8 * B_S);
      mbar_wait(bar + 8 * (B_GB + 1), layer);
      conv_prep<1>(sb, layer, cta, opaque_tid() - 256);
      mbar_arrive(bar + 8 * B_U1);
      TSW(4);
      if (layer == 0) {
        const int c = __shfl_sync(~0u, (opaque_tid() >> 5) & 3, 0);
        int phase = 0;
#pragma unroll 1
        for (int k = 0; k < 3; k++) {
          const int page = (k ? 4 + 4 * k : 0) + c, b = B_XR + 4 * (k & 1) + c;
          const uint32_t a = sb + page * PG + lane * 128 + (lane & 7) * 16 + (lane >> 3) * 4;
          int it = k == 2 ? phase : 0;
#pragma unroll 1
          for (; it < MAX_RETRY; it++) {
            mbar_wait(bar + 8 * b, it & 1);
            const uint32_t v0 = lds32(a), v1 = lds32(a + 4096);
            if (__all_sync(~0u, v0 != UNSET && v1 != UNSET)) break;
            if (elect_one()) { fence_async_smem(); ld_x1(page >> 3, page & 7, b); }
            __syncwarp();
            RETRY(3);
          }
          if (k == 0) phase = it + 1;
          if (lane == 0) mbar_arrive(bar + 8 * (B_XF + page));
        }
      }
    }
    mbar_wait(bar + 8 * B_TF, 0);
#pragma unroll 1
    for (int k = 0; k < 2; k++) final_tile(p, sb + 18 * PG + k * 4096, 256 * k + 32 * (cta >> 4), 64 * (cta & 15), 4);
    if (ht == 0) LTE();
  } else {
    asm volatile("setmaxnreg.dec.sync.aligned.u32 %0;" ::"n"(R_AGENT));
    bar_sync(0, NTHREADS);
    auto done = [&](int half, int c, int layer) { mbar_wait(bar + 8 * (B_DN + 8 * half + c), layer); };
    auto publish = [&](int layer, int k) {
      mbar_wait(bar + 8 * (B_PUB + k), layer);
      red_relaxed(&g_cnt[(layer ? C_F + 8 * k + (cta >> 4) : C_C + k) * 32]);
      if (!layer && k == 0) red_release(&g_cnt[(C_C + 3) * 32]);
      TS(16 + layer * 56 + 40 + 7 + k);
    };
    if (warp == 12) {
      if (elect_one()) {
#pragma unroll 1
        for (int layer = 0; layer < 2; layer++) {
          auto ld_xe = [&](int c) {
            const uint32_t b = bar + 8 * (B_XF + c);
            mbar_expect(b, PG);
            if (layer == 0) tma_ld(sb + x_page(0, c) * PG, &p.mapX, c * 64, rb * 64, b);
            else tma_ld(sb + x_page(0, c) * PG, &p.mapXT, rb * 64, DM + c * 64, b);
          };
          if (layer == 0) {
            ld_x0(0, 2); ld_w(2); ld_x0(1, 2);
            if (hg >= 3) {
              mbar_expect(bar + 8 * B_SC, PG);
              tma_ld(sb + P_R * PG, &p.mapX, hg * 64, rb * 64, bar + 8 * B_SC);
            }
            if (rb < 4) tma_prefetch3(&p.mapW3, hg * 64, (4 + rb) * 64, 0);
            ld_x0(0, 3); ld_w(3); ld_x0(1, 3); ld_x0(0, 4); ld_x0(1, 4);
            done(0, 0, 0); done(1, 0, 0);
            ld_w(4);
            ld_x0(1, 5); ld_x0(1, 6); ld_x0(1, 7);
            done(0, 1, 0); done(1, 1, 0);
            ld_w(5);
            if (rb < 8) tma_prefetch5(&p.mapWo, hg * 64, rb * 2);
            done(0, 2, 0);
            fence_async_smem();
            ld_xe(5); ld_xe(6); ld_xe(7);
          } else {
            mbar_wait(bar + 8 * B_PDONE, 0);
            mbar_wait(bar + 8 * (B_PDONE + 1), 0);
            mbar_wait(bar + 8 * (WPRE == 1 ? B_U : B_GB + 1), 0);
            ld_w(0); ld_w(1);
            mbar_wait(bar + 8 * B_U1, 0);
            fence_async_smem();
            ld_w(2);
            mbar_wait(bar + 8 * (B_PUB + 2), 0);
            fence_async_smem();
            ld_w(3);
            spin_until(&g_cnt[(C_C + 3) * 32], ((lds32(sb + SM_EP) / NCTA) + 1) * NCTA);
            fence_async_global();
            if (hg >= 3) {
              mbar_expect(bar + 8 * B_SC, PG);
              tma_ld(sb + P_R * PG, &p.mapXT, rb * 64, DM + hg * 64, bar + 8 * B_SC);
            }
            ld_xe(4);
            done(0, 2, 1);
            fence_async_smem();
            ld_xe(5); ld_xe(6); ld_xe(7);
            done(1, 0, 1);
            ld_w(4);
            done(1, 1, 1);
            ld_w(5);
          }
          done(1, 2, layer);
          fence_async_smem();
          ld_w(6); ld_w(7);
          auto ld_res = [&](int half) {
            const uint32_t b = bar + 8 * (B_RF + half);
            mbar_expect(b, PG);
            if (layer == 0) tma_ld(sb + (half ? 2 : P_R) * PG, &p.mapX, hg * 64, (16 * half + rb) * 64, b);
            else tma_ld(sb + (half ? 2 : P_R) * PG, &p.mapXT, (16 * half + rb) * 64, DM + hg * 64, b);
          };
          done(0, 4, layer); done(1, 3, layer);
          fence_async_smem();
          mbar_expect(bar + 8 * B_WOF, 8 * PG);
#pragma unroll 1
          for (int c = 0; c < 8; c++) {
            if (c == 5) { ld_res(0); done(1, 4, layer); }
            tma_ld5(sb + wo_page(c) * PG, &p.mapWo, hg * 64, c * 2, bar + 8 * B_WOF);
          }
          done(0, 7, layer);
          fence_async_global();
          ld_res(1);
        }
      }
    } else if (warp == 13) {
      mbar_wait(bar + 8 * B_EP, 0);
      const unsigned e1 = (lds32(sb + SM_EP) / NCTA) + 1;
      auto ld_o = [&](int layer) {
#pragma unroll 1
        for (int half = 0; half < 2; half++) {
          done(1, 7, layer);
          mbar_wait(bar + 8 * B_OST, layer);
          if (half) mbar_wait(bar + 8 * (B_OST + 1), layer);
          fence_async_smem();
#pragma unroll
          for (int c = 0; c < 4; c++) mbar_expect(bar + 8 * (B_OF + 4 * half + c), 2 * PG);
          spin_hint(&g_cnt[(C_O + layer * 32 + 16 * half + rb) * 32], e1 * 32);
#pragma unroll
          for (int c = 0; c < 4; c++) {
            if (LPRE && c == 2 && half && layer) { mbar_wait(bar + 8 * B_AL, 0); fence_async_smem(); }
            bulk_ld(sb + o_page(half, c) * PG, g_O + ((layer * 32 + 16 * half + rb) * 4 + c) * PG, 2 * PG, bar + 8 * (B_OF + 4 * half + c));
          }
        }
      };
      if (elect_one()) {
        mbar_wait(bar + 8 * (B_WF + 2), 0);
        asm volatile("prefetch.tensormap [%0];" ::"l"(&p.mapXT) : "memory");
        asm volatile("prefetch.tensormap [%0];" ::"l"(&p.mapWo) : "memory");
        spin_until(&g_cnt[C_Z * 32], e1 * NCTA);
        mbar_arrive(bar + 8 * B_ZF);
        TS(3);
        ld_o(0);
#pragma unroll 1
        for (int k = 0; k < 3; k++) {
          mbar_wait(bar + 8 * (B_PUB + k), 0);
          if (k == 2) {
#pragma unroll 1
            for (int c = 0; c < 4; c++) mbar_wait(bar + 8 * (B_XF + c), 1);
          }
          fence_async_smem();
          spin_hint(&g_cnt[(C_C + k) * 32], e1 * NCTA);
          TS(10 + k);
#pragma unroll
          for (int c = 0; c < 4; c++) ld_x1(k != 0, (k & 2) * 2 + c, B_XR + 4 * (k & 1) + c);
        }
        ld_o(1);
#pragma unroll 1
        for (int k = 0; k < 2; k++) {
          mbar_wait(bar + 8 * (B_PUB + k), 1);
          spin_hint(&g_cnt[(C_F + 8 * k + (cta >> 4)) * 32], e1 * 16);
          mbar_arrive(bar + 8 * (B_TF + k));
        }
      }
    } else if (warp == 14) {
      mbar_wait(bar + 8 * B_EP, 0);
      const unsigned e1 = (lds32(sb + SM_EP) / NCTA) + 1;
      done(0, 1, 0);
      {
        const uint2* cp = g_colsum + (hg * 192 + lane);
        uint2 v[6];
        bool ok;
        int it = 0;
        do {
          ok = true;
#pragma unroll
          for (int i = 0; i < 6; i++) {
            asm volatile("ld.relaxed.gpu.global.v2.u32 {%0,%1}, [%2];" : "=r"(v[i].x), "=r"(v[i].y) : "l"(cp + 32 * i) : "memory");
            ok = ok && v[i].y == e1;
          }
          if (++it > (1 << 22)) __trap();
        } while (!__all_sync(~0u, ok));
#pragma unroll
        for (int i = 0; i < 6; i++) sts32f(sb + SM_CS + 4 * (lane + 32 * i), __uint_as_float(v[i].x));
      }
      __syncwarp();
      if (elect_one()) {
        mbar_wait(bar + 8 * B_ZF, 0);
        mbar_arrive(bar + 8 * B_LN);
        red_relaxed(&g_cnt[C_CS * 32]);
        TS(13);
#pragma unroll 1
        for (int i = 0; i < 4; i++) {
          const int layer = i >> 1;
          mbar_wait(bar + 8 * (B_PST + (i & 1)), layer);
          const uint32_t b = bar + 8 * (B_GB + 1);
          const bf16* xin = g_xT + ((size_t)2 * layer * DM + 2 * cta) * LSEQ + 1024;
          if (i & 1) {
            fence_async_smem();
            mbar_expect(b, 12288 + PG);
          }
          spin_hint(&g_cnt[(C_G + i) * 32], e1 * NCTA);
          if (i & 1) {
            bulk_ld(sb + CV_ST, g_stats + (layer * 32 + 16) * 192, 12288, b);
#pragma unroll
            for (int lc = 0; lc < 4; lc++) bulk_ld(sb + cv_x(1, lc), xin + cv_chan(0, lc) * LSEQ, 2048, b);
            TS(14 + layer);
            publish(layer, 1);
          } else {
            mbar_arrive(bar + 8 * B_GB);
          }
        }
      }
    } else {
      const uint4 u = make_uint4(UNSET, UNSET, UNSET, UNSET);
      if (lane < 24) stg128((uint4*)g_stats + cta * 24 + lane, make_uint4(0, 0, 0, 0));
      if (lane < 16) stg128(g_rows + LSEQ + cta * 16 + lane, make_uint4(0, 0, 0, 0));
#pragma unroll 4
      for (int i = 0; i < 16; i++) stg128(g_halo + cta * 512 + 32 * i + lane, u);
#pragma unroll 4
      for (int i = 0; i < 16; i++) stg128(((i & 8) ? (uint4*)g_xT : (uint4*)g_O) + cta * 1024 + (i & 7) * 128 + (lane >> 1) * 8 + (lane & 1), u);
      __syncwarp();
      if (elect_one()) red_release(&g_cnt[C_Z * 32]);
      __syncwarp();
#pragma unroll 1
      for (int layer = 0; layer < 2; layer++) {
        auto reset_done = [&](int s) {
          spin_until(&g_cnt[(C_R + s) * 32], (lds32(sb + SM_EP) / NCTA) * 4 + 4);
          mbar_arrive(bar + 8 * (s == 1 ? B_LN : s == 2 ? B_RS : B_RC));
          if (s) TS(16 + 40 + 9 + s);
        };
        if (layer && elect_one()) reset_done(1);
        __syncwarp();
#pragma unroll 1
        for (int half = 0; half < 2; half++) {
          done(half, 2, layer);
          const uint4* src = g_rows + (layer * LSEQ + (16 * half + rb) * 64 + (opaque_tid() & 31));
          uint4 a, b;
          int it = 0;
          do {
            a = ld_tagged(src); b = ld_tagged(src + 32);
          } while (!__all_sync(~0u, (a.z | a.w) == __float_as_uint(8.f) && (b.z | b.w) == __float_as_uint(8.f)) && ++it < (1 << 20));
          float m0 = __uint_as_float(a.x) * (1.f / DM), m1 = __uint_as_float(b.x) * (1.f / DM);
          float r0 = rsqrt_approx(fmaxf(__uint_as_float(a.y) * (1.f / DM) - m0 * m0, 0.f) + 1e-5f);
          float r1 = rsqrt_approx(fmaxf(__uint_as_float(b.y) * (1.f / DM) - m1 * m1, 0.f) + 1e-5f);
          if (half) done(0, 7, layer);
          const uint32_t dst = sb + ln_off(half) + ((lane >> 4) * 8 + (lane & 7)) * 16 + (lane & 8);
          asm volatile("st.shared.v2.f32 [%0], {%1,%2};" ::"r"(dst), "f"(m0), "f"(r0) : "memory");
          asm volatile("st.shared.v2.f32 [%0], {%1,%2};" ::"r"(dst + 256), "f"(m1), "f"(r1) : "memory");
          __syncwarp();
          if (elect_one()) { mbar_arrive(bar + 8 * (B_LN + half)); TS(16 + layer * 56 + 40 + 14 + half); }
        }
        if (layer && lane < 16) stg128(g_rows + cta * 16 + (opaque_tid() & 31), make_uint4(0, 0, 0, 0));
        if (elect_one()) {
          if (layer) reset_done(2);
          reset_done(3 * layer);
          publish(layer, 0);
          if (!layer) publish(layer, 2);
        }
        __syncwarp();
      }
    }
  }
}

typedef CUresult (*EncodeFn)(CUtensorMap*, CUtensorMapDataType, cuuint32_t, void*, const cuuint64_t*, const cuuint64_t*,
                             const cuuint32_t*, const cuuint32_t*, CUtensorMapInterleave, CUtensorMapSwizzle,
                             CUtensorMapL2promotion, CUtensorMapFloatOOBfill);

static void make_map(EncodeFn enc, CUtensorMap* m, void* ptr, uint64_t cols, uint64_t rows, uint32_t box_rows) {
  cuuint64_t dims[2] = {cols, rows};
  cuuint64_t strides[1] = {cols * 2};
  cuuint32_t box[2] = {64, box_rows};
  cuuint32_t es[2] = {1, 1};
  enc(m, CU_TENSOR_MAP_DATA_TYPE_BFLOAT16, 2, ptr, dims, strides, box, es, CU_TENSOR_MAP_INTERLEAVE_NONE,
      CU_TENSOR_MAP_SWIZZLE_128B, CU_TENSOR_MAP_L2_PROMOTION_L2_128B, CU_TENSOR_MAP_FLOAT_OOB_FILL_NONE);
}
static void make_map3(EncodeFn enc, CUtensorMap* m, void* ptr, uint64_t d0, uint64_t cols, uint64_t rows, uint64_t blk_stride,
                      uint64_t nblocks, uint32_t nblk) {
  cuuint64_t dims[3] = {d0, rows, nblocks};
  cuuint64_t strides[2] = {cols * 2, blk_stride * 2};
  cuuint32_t box[3] = {64, 64, nblk};
  cuuint32_t es[3] = {1, 1, 1};
  enc(m, CU_TENSOR_MAP_DATA_TYPE_BFLOAT16, 3, ptr, dims, strides, box, es, CU_TENSOR_MAP_INTERLEAVE_NONE,
      CU_TENSOR_MAP_SWIZZLE_128B, CU_TENSOR_MAP_L2_PROMOTION_L2_128B, CU_TENSOR_MAP_FLOAT_OOB_FILL_NONE);
}

extern "C" void kernel_launch(void* const* d_in, const int* in_sizes, int n_in, void* d_out, int out_size) {
  static Params prm;
  static void* cached[13] = {nullptr};
  static bool attr_done = false;
  static int grid = NCTA + 4;
  bool same = attr_done && cached[12] == d_out;
  for (int i = 0; i < 12 && same; i++) same = cached[i] == d_in[i];
  if (!same) {
    void* fn = nullptr;
    cudaDriverEntryPointQueryResult qr;
    cudaGetDriverEntryPoint("cuTensorMapEncodeTiled", &fn, cudaEnableDefault, &qr);
    EncodeFn enc = (EncodeFn)fn;
    void* pXT;
    cudaGetSymbolAddress(&pXT, g_xT);
    make_map(enc, &prm.mapX, d_in[0], DM, LSEQ, 64);
    make_map(enc, &prm.mapXT, pXT, LSEQ, 4 * DM, 64);
    {
      cuuint64_t dims[5] = {DM, 2, 4, 4, 16};
      cuuint64_t strides[4] = {DM * 2, 8 * DM * 2, 2 * DM * 2, 32 * DM * 2};
      cuuint32_t box[5] = {64, 2, 4, 4, 2};
      cuuint32_t es[5] = {1, 1, 1, 1, 1};
      enc(&prm.mapWo, CU_TENSOR_MAP_DATA_TYPE_BFLOAT16, 5, d_in[2], dims, strides, box, es, CU_TENSOR_MAP_INTERLEAVE_NONE,
          CU_TENSOR_MAP_SWIZZLE_128B, CU_TENSOR_MAP_L2_PROMOTION_L2_128B, CU_TENSOR_MAP_FLOAT_OOB_FILL_NONE);
    }
    make_map3(enc, &prm.mapW3, d_in[1], DM, 3 * DM, DM, DM, 3, 3);
    prm.out = (bf16*)d_out;
    prm.a_re = (const bf16*)d_in[4]; prm.a_im = (const bf16*)d_in[5];
    prm.b_re = (const bf16*)d_in[6]; prm.b_im = (const bf16*)d_in[7];
    prm.c_re = (const bf16*)d_in[8]; prm.c_im = (const bf16*)d_in[9];
    prm.log_dt = (const bf16*)d_in[10]; prm.dskip = (const bf16*)d_in[11];
    int dev = 0, sms = 0;
    cudaGetDevice(&dev);
    cudaDeviceGetAttribute(&sms, cudaDevAttrMultiProcessorCount, dev);
    grid = sms >= NCTA + 4 ? NCTA + 4 : NCTA + 5;
    cudaFuncSetAttribute(fused_kernel, cudaFuncAttributeMaxDynamicSharedMemorySize, SM_TOTAL);
    for (int i = 0; i < 12; i++) cached[i] = d_in[i];
    cached[12] = d_out;
    attr_done = true;
  }
  fused_kernel<<<grid, NTHREADS, SM_TOTAL>>>(prm);
}
```

```cpp
#include <cuda_runtime.h>
#include <cuda_bf16.h>
#include <cuda.h>
#include <stdint.h>

typedef __nv_bfloat16 bf16;

constexpr int LSEQ = 2048;
constexpr int DM = 512;
constexpr int NCTA = 128;
constexpr int NTHREADS = 512;
#define R_CONS 200
#define R_HELP 88
#define R_AGENT 24
#define TURN0 4
#define TURN1 4

constexpr int PG = 8192;
constexpr int P_R = 25;
__host__ __device__ constexpr int x_page(int half, int c) { return half ? 8 + c : c < 5 ? c : c - 5; }
__host__ __device__ constexpr int w_page(int c) { return (c & 3) < 3 ? 16 + 3 * (c & 3) : c < 4 ? 5 : 8; }
__host__ __device__ constexpr int wo_page(int c) { return c < 5 ? 3 + c : 11 + c; }
__host__ __device__ constexpr int o_page(int half, int pair) { return half ? (pair ? 25 - 2 * pair : 0) : 8 + 2 * pair; }
constexpr int SM_KGB = (P_R + 1) * PG;
constexpr int SM_KC = 27 * PG;
constexpr int KC_STRIDE = 648;
__host__ __device__ constexpr int kc_off(int lc) { return SM_KC + (lc & 1) * 2 * KC_STRIDE + (lc < 2 ? 3328 : 0); }
constexpr int SM_KGT = SM_KC + 3328 + 2592;
constexpr int SM_CS = SM_KGT + 2048;
constexpr int SM_RED = SM_CS + 768;
constexpr int SM_EP = SM_RED + 16;
constexpr int SM_STG = SM_RED + 32;
constexpr int SM_LN = SM_STG + 768;
__host__ __device__ constexpr int ln_off(int half) { return half ? PG + 4096 : SM_LN; }
constexpr int SM_BAR = SM_LN + 512;
constexpr int SM_TS = SM_BAR + 704;
constexpr int SM_TOTAL = SM_TS + 512;
static_assert(SM_TOTAL <= 232448 && SM_STG % 16 == 0 && SM_KGT % 16 == 0, "shared memory");

constexpr int CV_UH = 140 * 16;
__host__ __device__ constexpr int cv_u(int lc) { return (8 + 2 * lc) * PG; }
__host__ __device__ constexpr int cv_pe(int lc, int early) { return early ? 19 * PG + lc * 4480 : cv_u(lc) + 4480; }
__host__ __device__ constexpr int cv_pb1(int lc, int w) { return w ? cv_u(lc) + 8960 + (w - 1) * 2048 : 7 * PG + lc * 2048; }
__host__ __device__ constexpr int cv_fa(int lc) { return cv_pb1(lc, 1) + 128; }
__host__ __device__ constexpr int cv_dump(int lc) { return cv_u(lc) + 16256; }
__host__ __device__ constexpr int cv_pb0(int lc, int w) { return lc * PG + w * 2048; }
__host__ __device__ constexpr int cv_se(int lc) { return 5 * PG + lc * 4096; }
__host__ __device__ constexpr int cv_so(int lc) { return cv_se(lc) + 2048; }
__host__ __device__ constexpr int cv_x(int half, int lc) { return (P_R + half) * PG + lc * 2048; }
constexpr int CV_ST = 22 * PG;
__host__ __device__ constexpr int cv_chan(int cta, int lc) { return 2 * cta + (lc & 1) + 256 * (lc >> 1); }

enum {
  B_XF = 0,
  B_WF = 16,
  B_OF = 24,
  B_DN = 32,
  B_PG = 46,
  B_XR = 48,
  B_RF = 56,
  B_PST = 58,
  B_GB = 60,
  B_TF = 62,
  B_RT = 64,
  B_RS = 66,
  B_RC = 67,
  B_WOF = 68,
  B_ZF = 69,
  B_EP = 70,
  B_KG = 71,
  B_SC = 37,
  B_LN = 72,
  B_END = 38,
  B_STG = 74,
  B_OST = 76,
  B_PDONE = 78,
  B_PE = 80,
  B_U = 81,
  B_U1 = 82,
  B_PUB = 83,
  B_S = 86,
  B_AL = 87,
  B_COUNT = 88
};

enum {
  C_CS = 0,
  C_G = 1,
  C_C = 5,
  C_O = 21,
  C_Z = 85,
  C_R = 86,
  C_F = 90,
  C_COUNT = 106
};

__device__ unsigned g_cnt[C_COUNT * 32];
__device__ __align__(1024) bf16 g_O[2 * LSEQ * DM];
__device__ __align__(1024) bf16 g_xT[4 * DM * LSEQ];
__device__ __align__(1024) float g_stats[2 * 32 * 192];
__device__ __align__(1024) uint2 g_colsum[3 * DM];
__device__ __align__(1024) uint4 g_halo[32 * 8 * 256];
__device__ __align__(1024) uint4 g_rows[2 * LSEQ];
#define TS(i) do { } while (0)
#define TSW(k) do { if ((threadIdx.x & 127) == 0) TS(16 + layer * 56 + (threadIdx.x >> 7) * 20 + (k)); } while (0)
#define TSG(k) do { } while (0)

#define RETRY(i) do { } while (0)
#define LTS(i) do { } while (0)
#define LTE() do { } while (0)

struct Params {
  CUtensorMap mapX, mapW3, mapXT, mapWo;
  bf16* out;
  const bf16 *a_re, *a_im, *b_re, *b_im, *c_re, *c_im, *log_dt, *dskip;
};

__device__ __forceinline__ uint32_t s32(const void* p) { return (uint32_t)__cvta_generic_to_shared(p); }
__device__ __forceinline__ void mbar_init(uint32_t b, int c) { asm volatile("mbarrier.init.shared::cta.b64 [%0], %1;" ::"r"(b), "r"(c) : "memory"); }
__device__ __forceinline__ void mbar_expect(uint32_t b, int bytes) { asm volatile("mbarrier.arrive.expect_tx.shared::cta.b64 _, [%0], %1;" ::"r"(b), "r"(bytes) : "memory"); }
__device__ __forceinline__ void mbar_arrive(uint32_t b) { asm volatile("mbarrier.arrive.shared::cta.b64 _, [%0];" ::"r"(b) : "memory"); }
__device__ __forceinline__ void mbar_wait(uint32_t b, int parity) {
  asm volatile("{\n.reg .pred p;\nWAIT_LOOP:\nmbarrier.try_wait.parity.shared::cta.b64 p, [%0], %1;\n@p bra WAIT_DONE;\nbra WAIT_LOOP;\nWAIT_DONE:\n}" ::"r"(b), "r"(parity) : "memory");
}
__device__ __forceinline__ bool mbar_test(uint32_t b, int parity) {
  uint32_t ok;
  asm volatile("{\n.reg .pred p;\nmbarrier.test_wait.parity.shared::cta.b64 p, [%1], %2;\nselp.u32 %0, 1, 0, p;\n}" : "=r"(ok) : "r"(b), "r"(parity) : "memory");
  return ok != 0;
}
__device__ __forceinline__ int opaque_tid() { int v; asm volatile("mov.u32 %0, %%tid.x;" : "=r"(v)); return v; }
__device__ __forceinline__ bool elect_one() {
  uint32_t r;
  asm volatile("{\n.reg .pred p;\nelect.sync _|p, 0xffffffff;\nselp.u32 %0, 1, 0, p;\n}" : "=r"(r));
  return r != 0;
}
__device__ __forceinline__ void tma_ld(uint32_t dst, const CUtensorMap* m, int c0, int c1, uint32_t bar) {
  asm volatile("cp.async.bulk.tensor.2d.shared::cluster.global.mbarrier::complete_tx::bytes [%0], [%1, {%3, %4}], [%2];"
               ::"r"(dst), "l"(m), "r"(bar), "r"(c0), "r"(c1) : "memory");
}
__device__ __forceinline__ void tma_ld3(uint32_t dst, const CUtensorMap* m, int c0, int c1, int c2, uint32_t bar) {
  asm volatile("cp.async.bulk.tensor.3d.shared::cluster.global.mbarrier::complete_tx::bytes [%0], [%1, {%3, %4, %5}], [%2];"
               ::"r"(dst), "l"(m), "r"(bar), "r"(c0), "r"(c1), "r"(c2) : "memory");
}
__device__ __forceinline__ void tma_ld5(uint32_t dst, const CUtensorMap* m, int c0, int c4, uint32_t bar) {
  asm volatile("cp.async.bulk.tensor.5d.shared::cluster.global.mbarrier::complete_tx::bytes [%0], [%1, {%3, 0, 0, 0, %4}], [%2];"
               ::"r"(dst), "l"(m), "r"(bar), "r"(c0), "r"(c4) : "memory");
}
__device__ __forceinline__ void tma_prefetch5(const CUtensorMap* m, int c0, int c4) {
  asm volatile("cp.async.bulk.prefetch.tensor.5d.L2.global.tile [%0, {%1, 0, 0, 0, %2}];" ::"l"(m), "r"(c0), "r"(c4) : "memory");
}
__device__ __forceinline__ void tma_prefetch2(const CUtensorMap* m, int c0, int c1) {
  asm volatile("cp.async.bulk.prefetch.tensor.2d.L2.global.tile [%0, {%1, %2}];" ::"l"(m), "r"(c0), "r"(c1) : "memory");
}
__device__ __forceinline__ void tma_prefetch3(const CUtensorMap* m, int c0, int c1, int c2) {
  asm volatile("cp.async.bulk.prefetch.tensor.3d.L2.global.tile [%0, {%1, %2, %3}];" ::"l"(m), "r"(c0), "r"(c1), "r"(c2) : "memory");
}
__device__ __forceinline__ void tma_st(const CUtensorMap* m, int c0, int c1, uint32_t src) {
  asm volatile("cp.async.bulk.tensor.2d.global.shared::cta.bulk_group [%0, {%2, %3}], [%1];" ::"l"(m), "r"(src), "r"(c0), "r"(c1) : "memory");
}
__device__ __forceinline__ void bulk_ld(uint32_t dst, const void* src, int bytes, uint32_t bar) {
  asm volatile("cp.async.bulk.shared::cluster.global.mbarrier::complete_tx::bytes [%0], [%1], %2, [%3];" ::"r"(dst), "l"(src), "r"(bytes), "r"(bar) : "memory");
}
__device__ __forceinline__ void bulk_st(void* dst, uint32_t src, int bytes) {
  asm volatile("cp.async.bulk.global.shared::cta.bulk_group [%0], [%1], %2;" ::"l"(dst), "r"(src), "r"(bytes) : "memory");
}
__device__ __forceinline__ void bulk_red_add_f32(void* dst, uint32_t src, int bytes) {
  asm volatile("cp.reduce.async.bulk.global.shared::cta.bulk_group.add.f32 [%0], [%1], %2;" ::"l"(dst), "r"(src), "r"(bytes) : "memory");
}
__device__ __forceinline__ void bulk_commit() { asm volatile("cp.async.bulk.commit_group;" ::: "memory"); }
__device__ __forceinline__ void bulk_wait_all() { asm volatile("cp.async.bulk.wait_group 0;" ::: "memory"); }
__device__ __forceinline__ void fence_async_smem() { asm volatile("fence.proxy.async.shared::cta;" ::: "memory"); }
__device__ __forceinline__ void fence_async_global() { asm volatile("fence.proxy.async.global;" ::: "memory"); }
__device__ __forceinline__ void bar_sync(int id, int n) { asm volatile("bar.sync %0, %1;" ::"r"(id), "r"(n) : "memory"); }
__device__ __forceinline__ void bar_arrive(int id, int n) { asm volatile("bar.arrive %0, %1;" ::"r"(id), "r"(n) : "memory"); }
__device__ __forceinline__ bool bar_or(int id, int n, bool v) {
  uint32_t r;
  asm volatile("{\n.reg .pred p, q;\nsetp.ne.u32 q, %3, 0;\nbar.red.or.pred p, %1, %2, q;\nselp.u32 %0, 1, 0, p;\n}" : "=r"(r) : "r"(id), "r"(n), "r"((uint32_t)v) : "memory");
  return r != 0;
}
__device__ __forceinline__ void bulk_wait_read() { asm volatile("cp.async.bulk.wait_group.read 0;" ::: "memory"); }
__device__ __forceinline__ void stg128(void* p, uint4 v) { asm volatile("st.relaxed.gpu.global.v4.u32 [%0], {%1,%2,%3,%4};" ::"l"(p), "r"(v.x), "r"(v.y), "r"(v.z), "r"(v.w) : "memory"); }
constexpr uint32_t UNSET = 0xffffffffu;
constexpr int MAX_RETRY = 1 << 16;
__device__ __forceinline__ void wg_fence() { asm volatile("wgmma.fence.sync.aligned;" ::: "memory"); }
__device__ __forceinline__ void wg_commit() { asm volatile("wgmma.commit_group.sync.aligned;" ::: "memory"); }
template <int N> __device__ __forceinline__ void wg_wait() { asm volatile("wgmma.wait_group.sync.aligned %0;" ::"n"(N) : "memory"); }
__device__ __forceinline__ uint64_t mkdesc(uint32_t addr, uint32_t lbo, uint32_t sbo, int sw) {
  return (uint64_t)((addr & 0x3FFFF) >> 4) | ((uint64_t)(lbo >> 4) << 16) | ((uint64_t)(sbo >> 4) << 32) | ((uint64_t)sw << 62);
}
__device__ __forceinline__ void ldsm4(uint32_t* r, uint32_t a) {
  asm volatile("ldmatrix.sync.aligned.m8n8.x4.shared.b16 {%0,%1,%2,%3}, [%4];" : "=r"(r[0]), "=r"(r[1]), "=r"(r[2]), "=r"(r[3]) : "r"(a) : "memory");
}
__device__ __forceinline__ void ldsm4t(uint32_t* r, uint32_t a) {
  asm volatile("ldmatrix.sync.aligned.m8n8.x4.trans.shared.b16 {%0,%1,%2,%3}, [%4];" : "=r"(r[0]), "=r"(r[1]), "=r"(r[2]), "=r"(r[3]) : "r"(a) : "memory");
}
__device__ __forceinline__ void stsm4(uint32_t a, uint32_t r0, uint32_t r1, uint32_t r2, uint32_t r3) {
  asm volatile("stmatrix.sync.aligned.m8n8.x4.shared.b16 [%0], {%1,%2,%3,%4};" ::"r"(a), "r"(r0), "r"(r1), "r"(r2), "r"(r3) : "memory");
}
__device__ __forceinline__ void stsm4t(uint32_t a, uint32_t r0, uint32_t r1, uint32_t r2, uint32_t r3) {
  asm volatile("stmatrix.sync.aligned.m8n8.x4.trans.shared.b16 [%0], {%1,%2,%3,%4};" ::"r"(a), "r"(r0), "r"(r1), "r"(r2), "r"(r3) : "memory");
}
__device__ __forceinline__ uint32_t movm_t(uint32_t a) { uint32_t r; asm volatile("movmatrix.sync.aligned.m8n8.trans.b16 %0, %1;" : "=r"(r) : "r"(a)); return r; }
__device__ __forceinline__ uint32_t lds32(uint32_t a) { uint32_t v; asm volatile("ld.shared.b32 %0, [%1];" : "=r"(v) : "r"(a) : "memory"); return v; }
__device__ __forceinline__ float2 lds64f(uint32_t a) { float2 v; asm volatile("ld.shared.v2.f32 {%0,%1}, [%2];" : "=f"(v.x), "=f"(v.y) : "r"(a) : "memory"); return v; }
__device__ __forceinline__ float4 lds128f(uint32_t a) { float4 v; asm volatile("ld.shared.v4.f32 {%0,%1,%2,%3}, [%4];" : "=f"(v.x), "=f"(v.y), "=f"(v.z), "=f"(v.w) : "r"(a) : "memory"); return v; }
__device__ __forceinline__ uint4 lds128(uint32_t a) { uint4 v; asm volatile("ld.shared.v4.b32 {%0,%1,%2,%3}, [%4];" : "=r"(v.x), "=r"(v.y), "=r"(v.z), "=r"(v.w) : "r"(a) : "memory"); return v; }
__device__ __forceinline__ void sts128(uint32_t a, uint4 v) { asm volatile("st.shared.v4.b32 [%0], {%1,%2,%3,%4};" ::"r"(a), "r"(v.x), "r"(v.y), "r"(v.z), "r"(v.w) : "memory"); }
__device__ __forceinline__ void sts128f(uint32_t a, float x, float y, float z, float w) { asm volatile("st.shared.v4.f32 [%0], {%1,%2,%3,%4};" ::"r"(a), "f"(x), "f"(y), "f"(z), "f"(w) : "memory"); }
__device__ __forceinline__ void sts32f(uint32_t a, float v) { asm volatile("st.shared.f32 [%0], %1;" ::"r"(a), "f"(v) : "memory"); }
__device__ __forceinline__ void sts16(uint32_t a, uint16_t v) { asm volatile("st.shared.u16 [%0], %1;" ::"r"(a), "h"(v) : "memory"); }
__device__ __forceinline__ uint32_t lds16(uint32_t a) { uint16_t v; asm volatile("ld.shared.u16 %0, [%1];" : "=h"(v) : "r"(a) : "memory"); return v; }
__device__ __forceinline__ uint32_t packbf(float lo, float hi) { uint32_t r; asm("cvt.rn.bf16x2.f32 %0, %1, %2;" : "=r"(r) : "f"(hi), "f"(lo)); return r; }
__device__ __forceinline__ float bf_lo(uint32_t v) { return __uint_as_float(v << 16); }
__device__ __forceinline__ float bf_hi(uint32_t v) { return __uint_as_float(v & 0xffff0000u); }
__device__ __forceinline__ float ex2(float x) { float r; asm("ex2.approx.ftz.f32 %0, %1;" : "=f"(r) : "f"(x)); return r; }
__device__ __forceinline__ float rsqrt_approx(float x) { float r; asm("rsqrt.approx.ftz.f32 %0, %1;" : "=f"(r) : "f"(x)); return r; }
__device__ __forceinline__ float rcp_approx(float x) { float r; asm("rcp.approx.ftz.f32 %0, %1;" : "=f"(r) : "f"(x)); return r; }
__device__ __forceinline__ void mma_bf16(float* d, const uint32_t* a, uint32_t b0, uint32_t b1) {
  asm("mma.sync.aligned.m16n8k16.row.col.f32.bf16.bf16.f32 {%0,%1,%2,%3}, {%4,%5,%6,%7}, {%8,%9}, {%0,%1,%2,%3};"
               : "+f"(d[0]), "+f"(d[1]), "+f"(d[2]), "+f"(d[3]) : "r"(a[0]), "r"(a[1]), "r"(a[2]), "r"(a[3]), "r"(b0), "r"(b1));
}
__device__ __forceinline__ void mma_tf32(float* d, float a0, float a1, float a2, float a3, float b0, float b1) {
  asm("mma.sync.aligned.m16n8k8.row.col.f32.tf32.tf32.f32 {%0,%1,%2,%3}, {%4,%5,%6,%7}, {%8,%9}, {%0,%1,%2,%3};"
               : "+f"(d[0]), "+f"(d[1]), "+f"(d[2]), "+f"(d[3])
               : "r"(__float_as_uint(a0)), "r"(__float_as_uint(a1)), "r"(__float_as_uint(a2)), "r"(__float_as_uint(a3)),
                 "r"(__float_as_uint(b0)), "r"(__float_as_uint(b1)));
}
__device__ __forceinline__ void red_release(unsigned* p) { asm volatile("red.release.gpu.global.add.u32 [%0], 1;" ::"l"(p) : "memory"); }
__device__ __forceinline__ void red_relaxed(unsigned* p) { asm volatile("red.relaxed.gpu.global.add.u32 [%0], 1;" ::"l"(p) : "memory"); }
__device__ __forceinline__ unsigned ld_relaxed(const unsigned* p) { unsigned v; asm volatile("ld.relaxed.gpu.global.u32 %0, [%1];" : "=r"(v) : "l"(p) : "memory"); return v; }
__device__ __forceinline__ void spin_until(const unsigned* p, unsigned target) {
  int it = 0;
  while ((int)(ld_relaxed(p) - target) < 0) {
    if (++it > (1 << 23)) __trap();
  }
}
__device__ __forceinline__ void spin_hint(const unsigned* p, unsigned target) {
  spin_until(p, target);
}
__device__ __forceinline__ uint4 ldcg128(const void* p) { uint4 v; asm volatile("ld.global.cg.v4.b32 {%0,%1,%2,%3}, [%4];" : "=r"(v.x), "=r"(v.y), "=r"(v.z), "=r"(v.w) : "l"(p) : "memory"); return v; }
__device__ __forceinline__ uint4 ld_tagged(const uint4* p) { uint4 v; asm volatile("ld.relaxed.gpu.global.v4.u32 {%0,%1,%2,%3}, [%4];" : "=r"(v.x), "=r"(v.y), "=r"(v.z), "=r"(v.w) : "l"(p) : "memory"); return v; }
__device__ __forceinline__ void st_tagged(uint4* p, uint32_t a, uint32_t b, uint32_t tag) { asm volatile("st.relaxed.gpu.global.v4.u32 [%0], {%1,%2,%3,%2};" ::"l"(p), "r"(a), "r"(tag), "r"(b) : "memory"); }
__device__ __forceinline__ void st_tagged3(uint4* p, uint32_t a, uint32_t b, uint32_t c, uint32_t tag) { asm volatile("st.relaxed.gpu.global.v4.u32 [%0], {%1,%2,%3,%4};" ::"l"(p), "r"(a), "r"(b), "r"(c), "r"(tag) : "memory"); }
__device__ __forceinline__ uint4 poll_tagged(const uint4* p, uint32_t tag) {
  uint4 v = ld_tagged(p);
  int it = 0;
  while (v.y != tag || v.w != tag) {
    if (++it > (1 << 22)) __trap();
    v = ld_tagged(p);
  }
  return v;
}
__device__ __forceinline__ uint32_t hadd2(uint32_t a, uint32_t b) { uint32_t r; asm("add.rn.bf16x2 %0, %1, %2;" : "=r"(r) : "r"(a), "r"(b)); return r; }
__device__ __forceinline__ uint32_t hmul2(uint32_t a, uint32_t b) { uint32_t r; asm("mul.rn.bf16x2 %0, %1, %2;" : "=r"(r) : "r"(a), "r"(b)); return r; }

__device__ __forceinline__ uint32_t hfma2(uint32_t a, uint32_t b, uint32_t c) { uint32_t r; asm("fma.rn.bf16x2 %0, %1, %2, %3;" : "=r"(r) : "r"(a), "r"(b), "r"(c)); return r; }
__device__ __forceinline__ void sts32(uint32_t a, uint32_t v) { asm volatile("st.shared.u32 [%0], %1;" ::"r"(a), "r"(v) : "memory"); }

template <int N> __device__ __forceinline__ void acc_fence(float* a) {
#pragma unroll
  for (int i = 0; i < N; i++) asm volatile("" : "+f"(a[i]) :: "memory");
}

template<int N,int TB> __device__ __forceinline__ void wgmma_rs(float* d, const uint32_t* a, uint64_t db, int sd);
template<int N,int TA,int TB> __device__ __forceinline__ void wgmma_ss(float* d, uint64_t da, uint64_t db, int sd);
template<> __device__ __forceinline__ void wgmma_rs<64,0>(float* d, const uint32_t* a, uint64_t db, int sd) {
  asm volatile("{\n.reg .pred p;\nsetp.ne.b32 p, %37, 0;\nwgmma.mma_async.sync.aligned.m64n64k16.f32.bf16.bf16 {%0,%1,%2,%3,%4,%5,%6,%7,%8,%9,%10,%11,%12,%13,%14,%15,%16,%17,%18,%19,%20,%21,%22,%23,%24,%25,%26,%27,%28,%29,%30,%31}, {%32,%33,%34,%35}, %36, p, 1, 1, 0;\n}\n"
   : "+f"(d[0]),"+f"(d[1]),"+f"(d[2]),"+f"(d[3]),"+f"(d[4]),"+f"(d[5]),"+f"(d[6]),"+f"(d[7]),"+f"(d[8]),"+f"(d[9]),"+f"(d[10]),"+f"(d[11]),"+f"(d[12]),"+f"(d[13]),"+f"(d[14]),"+f"(d[15]),"+f"(d[16]),"+f"(d[17]),"+f"(d[18]),"+f"(d[19]),"+f"(d[20]),"+f"(d[21]),"+f"(d[22]),"+f"(d[23]),"+f"(d[24]),"+f"(d[25]),"+f"(d[26]),"+f"(d[27]),"+f"(d[28]),"+f"(d[29]),"+f"(d[30]),"+f"(d[31])
   : "r"(a[0]), "r"(a[1]), "r"(a[2]), "r"(a[3]), "l"(db), "r"(sd));
}
template<> __device__ __forceinline__ void wgmma_rs<56,0>(float* d, const uint32_t* a, uint64_t db, int sd) {
  asm volatile("{\n.reg .pred p;\nsetp.ne.b32 p, %33, 0;\nwgmma.mma_async.sync.aligned.m64n56k16.f32.bf16.bf16 {%0,%1,%2,%3,%4,%5,%6,%7,%8,%9,%10,%11,%12,%13,%14,%15,%16,%17,%18,%19,%20,%21,%22,%23,%24,%25,%26,%27}, {%28,%29,%30,%31}, %32, p, 1, 1, 0;\n}\n"
   : "+f"(d[0]),"+f"(d[1]),"+f"(d[2]),"+f"(d[3]),"+f"(d[4]),"+f"(d[5]),"+f"(d[6]),"+f"(d[7]),"+f"(d[8]),"+f"(d[9]),"+f"(d[10]),"+f"(d[11]),"+f"(d[12]),"+f"(d[13]),"+f"(d[14]),"+f"(d[15]),"+f"(d[16]),"+f"(d[17]),"+f"(d[18]),"+f"(d[19]),"+f"(d[20]),"+f"(d[21]),"+f"(d[22]),"+f"(d[23]),"+f"(d[24]),"+f"(d[25]),"+f"(d[26]),"+f"(d[27])
   : "r"(a[0]), "r"(a[1]), "r"(a[2]), "r"(a[3]), "l"(db), "r"(sd));
}
template<> __device__ __forceinline__ void wgmma_rs<48,0>(float* d, const uint32_t* a, uint64_t db, int sd) {
  asm volatile("{\n.reg .pred p;\nsetp.ne.b32 p, %29, 0;\nwgmma.mma_async.sync.aligned.m64n48k16.f32.bf16.bf16 {%0,%1,%2,%3,%4,%5,%6,%7,%8,%9,%10,%11,%12,%13,%14,%15,%16,%17,%18,%19,%20,%21,%22,%23}, {%24,%25,%26,%27}, %28, p, 1, 1, 0;\n}\n"
   : "+f"(d[0]),"+f"(d[1]),"+f"(d[2]),"+f"(d[3]),"+f"(d[4]),"+f"(d[5]),"+f"(d[6]),"+f"(d[7]),"+f"(d[8]),"+f"(d[9]),"+f"(d[10]),"+f"(d[11]),"+f"(d[12]),"+f"(d[13]),"+f"(d[14]),"+f"(d[15]),"+f"(d[16]),"+f"(d[17]),"+f"(d[18]),"+f"(d[19]),"+f"(d[20]),"+f"(d[21]),"+f"(d[22]),"+f"(d[23])
   : "r"(a[0]), "r"(a[1]), "r"(a[2]), "r"(a[3]), "l"(db), "r"(sd));
}
template<> __device__ __forceinline__ void wgmma_rs<40,0>(float* d, const uint32_t* a, uint64_t db, int sd) {
  asm volatile("{\n.reg .pred p;\nsetp.ne.b32 p, %25, 0;\nwgmma.mma_async.sync.aligned.m64n40k16.f32.bf16.bf16 {%0,%1,%2,%3,%4,%5,%6,%7,%8,%9,%10,%11,%12,%13,%14,%15,%16,%17,%18,%19}, {%20,%21,%22,%23}, %24, p, 1, 1, 0;\n}\n"
   : "+f"(d[0]),"+f"(d[1]),"+f"(d[2]),"+f"(d[3]),"+f"(d[4]),"+f"(d[5]),"+f"(d[6]),"+f"(d[7]),"+f"(d[8]),"+f"(d[9]),"+f"(d[10]),"+f"(d[11]),"+f"(d[12]),"+f"(d[13]),"+f"(d[14]),"+f"(d[15]),"+f"(d[16]),"+f"(d[17]),"+f"(d[18]),"+f"(d[19])
   : "r"(a[0]), "r"(a[1]), "r"(a[2]), "r"(a[3]), "l"(db), "r"(sd));
}
template<> __device__ __forceinline__ void wgmma_rs<32,0>(float* d, const uint32_t* a, uint64_t db, int sd) {
  asm volatile("{\n.reg .pred p;\nsetp.ne.b32 p, %21, 0;\nwgmma.mma_async.sync.aligned.m64n32k16.f32.bf16.bf16 {%0,%1,%2,%3,%4,%5,%6,%7,%8,%9,%10,%11,%12,%13,%14,%15}, {%16,%17,%18,%19}, %20, p, 1, 1, 0;\n}\n"
   : "+f"(d[0]),"+f"(d[1]),"+f"(d[2]),"+f"(d[3]),"+f"(d[4]),"+f"(d[5]),"+f"(d[6]),"+f"(d[7]),"+f"(d[8]),"+f"(d[9]),"+f"(d[10]),"+f"(d[11]),"+f"(d[12]),"+f"(d[13]),"+f"(d[14]),"+f"(d[15])
   : "r"(a[0]), "r"(a[1]), "r"(a[2]), "r"(a[3]), "l"(db), "r"(sd));
}
template<> __device__ __forceinline__ void wgmma_rs<24,0>(float* d, const uint32_t* a, uint64_t db, int sd) {
  asm volatile("{\n.reg .pred p;\nsetp.ne.b32 p, %17, 0;\nwgmma.mma_async.sync.aligned.m64n24k16.f32.bf16.bf16 {%0,%1,%2,%3,%4,%5,%6,%7,%8,%9,%10,%11}, {%12,%13,%14,%15}, %16, p, 1, 1, 0;\n}\n"
   : "+f"(d[0]),"+f"(d[1]),"+f"(d[2]),"+f"(d[3]),"+f"(d[4]),"+f"(d[5]),"+f"(d[6]),"+f"(d[7]),"+f"(d[8]),"+f"(d[9]),"+f"(d[10]),"+f"(d[11])
   : "r"(a[0]), "r"(a[1]), "r"(a[2]), "r"(a[3]), "l"(db), "r"(sd));
}
template<> __device__ __forceinline__ void wgmma_rs<16,0>(float* d, const uint32_t* a, uint64_t db, int sd) {
  asm volatile("{\n.reg .pred p;\nsetp.ne.b32 p, %13, 0;\nwgmma.mma_async.sync.aligned.m64n16k16.f32.bf16.bf16 {%0,%1,%2,%3,%4,%5,%6,%7}, {%8,%9,%10,%11}, %12, p, 1, 1, 0;\n}\n"
   : "+f"(d[0]),"+f"(d[1]),"+f"(d[2]),"+f"(d[3]),"+f"(d[4]),"+f"(d[5]),"+f"(d[6]),"+f"(d[7])
   : "r"(a[0]), "r"(a[1]), "r"(a[2]), "r"(a[3]), "l"(db), "r"(sd));
}
template<> __device__ __forceinline__ void wgmma_rs<8,0>(float* d, const uint32_t* a, uint64_t db, int sd) {
  asm volatile("{\n.reg .pred p;\nsetp.ne.b32 p, %9, 0;\nwgmma.mma_async.sync.aligned.m64n8k16.f32.bf16.bf16 {%0,%1,%2,%3}, {%4,%5,%6,%7}, %8, p, 1, 1, 0;\n}\n"
   : "+f"(d[0]),"+f"(d[1]),"+f"(d[2]),"+f"(d[3])
   : "r"(a[0]), "r"(a[1]), "r"(a[2]), "r"(a[3]), "l"(db), "r"(sd));
}
template<> __device__ __forceinline__ void wgmma_ss<64,1,0>(float* d, uint64_t da, uint64_t db, int sd) {
  asm volatile("{\n.reg .pred p;\nsetp.ne.b32 p, %34, 0;\nwgmma.mma_async.sync.aligned.m64n64k16.f32.bf16.bf16 {%0,%1,%2,%3,%4,%5,%6,%7,%8,%9,%10,%11,%12,%13,%14,%15,%16,%17,%18,%19,%20,%21,%22,%23,%24,%25,%26,%27,%28,%29,%30,%31}, %32, %33, p, 1, 1, 1, 0;\n}\n"
   : "+f"(d[0]),"+f"(d[1]),"+f"(d[2]),"+f"(d[3]),"+f"(d[4]),"+f"(d[5]),"+f"(d[6]),"+f"(d[7]),"+f"(d[8]),"+f"(d[9]),"+f"(d[10]),"+f"(d[11]),"+f"(d[12]),"+f"(d[13]),"+f"(d[14]),"+f"(d[15]),"+f"(d[16]),"+f"(d[17]),"+f"(d[18]),"+f"(d[19]),"+f"(d[20]),"+f"(d[21]),"+f"(d[22]),"+f"(d[23]),"+f"(d[24]),"+f"(d[25]),"+f"(d[26]),"+f"(d[27]),"+f"(d[28]),"+f"(d[29]),"+f"(d[30]),"+f"(d[31])
   : "l"(da), "l"(db), "r"(sd));
}
template<> __device__ __forceinline__ void wgmma_ss<64,0,1>(float* d, uint64_t da, uint64_t db, int sd) {
  asm volatile("{\n.reg .pred p;\nsetp.ne.b32 p, %34, 0;\nwgmma.mma_async.sync.aligned.m64n64k16.f32.bf16.bf16 {%0,%1,%2,%3,%4,%5,%6,%7,%8,%9,%10,%11,%12,%13,%14,%15,%16,%17,%18,%19,%20,%21,%22,%23,%24,%25,%26,%27,%28,%29,%30,%31}, %32, %33, p, 1, 1, 0, 1;\n}\n"
   : "+f"(d[0]),"+f"(d[1]),"+f"(d[2]),"+f"(d[3]),"+f"(d[4]),"+f"(d[5]),"+f"(d[6]),"+f"(d[7]),"+f"(d[8]),"+f"(d[9]),"+f"(d[10]),"+f"(d[11]),"+f"(d[12]),"+f"(d[13]),"+f"(d[14]),"+f"(d[15]),"+f"(d[16]),"+f"(d[17]),"+f"(d[18]),"+f"(d[19]),"+f"(d[20]),"+f"(d[21]),"+f"(d[22]),"+f"(d[23]),"+f"(d[24]),"+f"(d[25]),"+f"(d[26]),"+f"(d[27]),"+f"(d[28]),"+f"(d[29]),"+f"(d[30]),"+f"(d[31])
   : "l"(da), "l"(db), "r"(sd));
}
template<> __device__ __forceinline__ void wgmma_ss<192,0,1>(float* d, uint64_t da, uint64_t db, int sd) {
  asm volatile("{\n.reg .pred p;\nsetp.ne.b32 p, %98, 0;\nwgmma.mma_async.sync.aligned.m64n192k16.f32.bf16.bf16 {%0,%1,%2,%3,%4,%5,%6,%7,%8,%9,%10,%11,%12,%13,%14,%15,%16,%17,%18,%19,%20,%21,%22,%23,%24,%25,%26,%27,%28,%29,%30,%31,%32,%33,%34,%35,%36,%37,%38,%39,%40,%41,%42,%43,%44,%45,%46,%47,%48,%49,%50,%51,%52,%53,%54,%55,%56,%57,%58,%59,%60,%61,%62,%63,%64,%65,%66,%67,%68,%69,%70,%71,%72,%73,%74,%75,%76,%77,%78,%79,%80,%81,%82,%83,%84,%85,%86,%87,%88,%89,%90,%91,%92,%93,%94,%95}, %96, %97, p, 1, 1, 0, 1;\n}\n"
   : "+f"(d[0]),"+f"(d[1]),"+f"(d[2]),"+f"(d[3]),"+f"(d[4]),"+f"(d[5]),"+f"(d[6]),"+f"(d[7]),"+f"(d[8]),"+f"(d[9]),"+f"(d[10]),"+f"(d[11]),"+f"(d[12]),"+f"(d[13]),"+f"(d[14]),"+f"(d[15]),"+f"(d[16]),"+f"(d[17]),"+f"(d[18]),"+f"(d[19]),"+f"(d[20]),"+f"(d[21]),"+f"(d[22]),"+f"(d[23]),"+f"(d[24]),"+f"(d[25]),"+f"(d[26]),"+f"(d[27]),"+f"(d[28]),"+f"(d[29]),"+f"(d[30]),"+f"(d[31]),"+f"(d[32]),"+f"(d[33]),"+f"(d[34]),"+f"(d[35]),"+f"(d[36]),"+f"(d[37]),"+f"(d[38]),"+f"(d[39]),"+f"(d[40]),"+f"(d[41]),"+f"(d[42]),"+f"(d[43]),"+f"(d[44]),"+f"(d[45]),"+f"(d[46]),"+f"(d[47]),"+f"(d[48]),"+f"(d[49]),"+f"(d[50]),"+f"(d[51]),"+f"(d[52]),"+f"(d[53]),"+f"(d[54]),"+f"(d[55]),"+f"(d[56]),"+f"(d[57]),"+f"(d[58]),"+f"(d[59]),"+f"(d[60]),"+f"(d[61]),"+f"(d[62]),"+f"(d[63]),"+f"(d[64]),"+f"(d[65]),"+f"(d[66]),"+f"(d[67]),"+f"(d[68]),"+f"(d[69]),"+f"(d[70]),"+f"(d[71]),"+f"(d[72]),"+f"(d[73]),"+f"(d[74]),"+f"(d[75]),"+f"(d[76]),"+f"(d[77]),"+f"(d[78]),"+f"(d[79]),"+f"(d[80]),"+f"(d[81]),"+f"(d[82]),"+f"(d[83]),"+f"(d[84]),"+f"(d[85]),"+f"(d[86]),"+f"(d[87]),"+f"(d[88]),"+f"(d[89]),"+f"(d[90]),"+f"(d[91]),"+f"(d[92]),"+f"(d[93]),"+f"(d[94]),"+f"(d[95])
   : "l"(da), "l"(db), "r"(sd));
}
template<> __device__ __forceinline__ void wgmma_ss<192,1,1>(float* d, uint64_t da, uint64_t db, int sd) {
  asm volatile("{\n.reg .pred p;\nsetp.ne.b32 p, %98, 0;\nwgmma.mma_async.sync.aligned.m64n192k16.f32.bf16.bf16 {%0,%1,%2,%3,%4,%5,%6,%7,%8,%9,%10,%11,%12,%13,%14,%15,%16,%17,%18,%19,%20,%21,%22,%23,%24,%25,%26,%27,%28,%29,%30,%31,%32,%33,%34,%35,%36,%37,%38,%39,%40,%41,%42,%43,%44,%45,%46,%47,%48,%49,%50,%51,%52,%53,%54,%55,%56,%57,%58,%59,%60,%61,%62,%63,%64,%65,%66,%67,%68,%69,%70,%71,%72,%73,%74,%75,%76,%77,%78,%79,%80,%81,%82,%83,%84,%85,%86,%87,%88,%89,%90,%91,%92,%93,%94,%95}, %96, %97, p, 1, 1, 1, 1;\n}\n"
   : "+f"(d[0]),"+f"(d[1]),"+f"(d[2]),"+f"(d[3]),"+f"(d[4]),"+f"(d[5]),"+f"(d[6]),"+f"(d[7]),"+f"(d[8]),"+f"(d[9]),"+f"(d[10]),"+f"(d[11]),"+f"(d[12]),"+f"(d[13]),"+f"(d[14]),"+f"(d[15]),"+f"(d[16]),"+f"(d[17]),"+f"(d[18]),"+f"(d[19]),"+f"(d[20]),"+f"(d[21]),"+f"(d[22]),"+f"(d[23]),"+f"(d[24]),"+f"(d[25]),"+f"(d[26]),"+f"(d[27]),"+f"(d[28]),"+f"(d[29]),"+f"(d[30]),"+f"(d[31]),"+f"(d[32]),"+f"(d[33]),"+f"(d[34]),"+f"(d[35]),"+f"(d[36]),"+f"(d[37]),"+f"(d[38]),"+f"(d[39]),"+f"(d[40]),"+f"(d[41]),"+f"(d[42]),"+f"(d[43]),"+f"(d[44]),"+f"(d[45]),"+f"(d[46]),"+f"(d[47]),"+f"(d[48]),"+f"(d[49]),"+f"(d[50]),"+f"(d[51]),"+f"(d[52]),"+f"(d[53]),"+f"(d[54]),"+f"(d[55]),"+f"(d[56]),"+f"(d[57]),"+f"(d[58]),"+f"(d[59]),"+f"(d[60]),"+f"(d[61]),"+f"(d[62]),"+f"(d[63]),"+f"(d[64]),"+f"(d[65]),"+f"(d[66]),"+f"(d[67]),"+f"(d[68]),"+f"(d[69]),"+f"(d[70]),"+f"(d[71]),"+f"(d[72]),"+f"(d[73]),"+f"(d[74]),"+f"(d[75]),"+f"(d[76]),"+f"(d[77]),"+f"(d[78]),"+f"(d[79]),"+f"(d[80]),"+f"(d[81]),"+f"(d[82]),"+f"(d[83]),"+f"(d[84]),"+f"(d[85]),"+f"(d[86]),"+f"(d[87]),"+f"(d[88]),"+f"(d[89]),"+f"(d[90]),"+f"(d[91]),"+f"(d[92]),"+f"(d[93]),"+f"(d[94]),"+f"(d[95])
   : "l"(da), "l"(db), "r"(sd));
}

template <bool TR>
__device__ __forceinline__ void gemm_section(float* acc, float& mean0, float& mean1, float& rstd0, float& rstd1,
                                             uint32_t sb, int blk, int hg, int wg, int w, int lane) {
  constexpr int layer = TR ? 1 : 0;
  constexpr int TURN = TR ? TURN1 : TURN0;
  constexpr int LSTAT = TURN < 4 ? TURN - 1 : 3;
  const uint32_t bar = sb + SM_BAR;
  const int g = lane >> 2, t = lane & 3;
  const bool leader = (w == 0) && (lane == 0);
  const int statpos = hg < 3 ? 1 : wg ? LSTAT : TR ? 3 : 2;
  const bool copy = hg >= 3 && wg == 0;
  const int cut = wg ? TURN : 4;
  auto wait_full = [&](int c) {
    mbar_wait(bar + 8 * (B_XF + 8 * wg + c), layer);
    mbar_wait(bar + 8 * (B_WF + c), layer);
  };
  auto peek = [&](int c) {
    const bool x = mbar_test(bar + 8 * (B_XF + 8 * wg + c), layer), y = mbar_test(bar + 8 * (B_WF + c), layer);
    return x && y;
  };
  const uint64_t da0 = mkdesc(sb, TR ? 8192 : 16, 1024, 1), db0 = mkdesc(sb, 8192, 1024, 1);
  uint32_t xt = wg ? 0xfedcba98u : 0x21043210u;
  uint64_t wt = 0x0816131005161310ull;
  uint64_t da = da0 + ((xt & 15) << 9), db = db0 + (16 << 9);
  auto issue = [&](int c, int first) {
    wg_fence();
#pragma unroll
    for (int ks = 0; ks < 4; ks++) wgmma_ss<192, TR ? 1 : 0, 1>(acc, da + (TR ? ks * 128 : ks * 2), db + ks * 128, !first || ks != 0);
    wg_commit();
    xt >>= 4; wt >>= 8;
    da = da0 + ((xt & 15) << 9); db = db0 + (((uint32_t)wt & 31) << 9);
  };
  wait_full(0);
  bool ready = peek(1);
  issue(0, 1);
  TSW(0);
#pragma unroll 1
  for (int c = 1; c < cut; c++) {
    if (!ready) wait_full(c);
    issue(c, 0);
    ready = peek(c + 1);
    wg_wait<1>();
    if (leader) mbar_arrive(bar + 8 * (B_DN + 8 * wg + c - 1));
    if (wg == 1 && c == cut - 1) {
      wg_wait<0>();
      if (leader) mbar_arrive(bar + 8 * (B_DN + 8 + c));
    }
    if (c == statpos) {
      mbar_wait(bar + 8 * (copy ? B_SC : B_XF + 8 * wg + hg), layer);
      uint32_t A[16];
      const uint32_t xb = sb + (copy ? P_R : 8 * wg + hg) * PG;
#pragma unroll
      for (int ks = 0; ks < 4; ks++) {
        if (!TR) {
          const int row = 16 * w + (lane & 15), kc = 2 * ks + (lane >> 4);
          ldsm4(&A[4 * ks], xb + row * 128 + ((kc ^ (row & 7)) << 4));
        } else {
          const int k = 16 * ks + (lane & 7) + 8 * (lane >> 4), pc = 2 * w + ((lane >> 3) & 1);
          ldsm4t(&A[4 * ks], xb + k * 128 + ((pc ^ (k & 7)) << 4));
        }
      }
      float s0 = 0.f, q0 = 0.f, s1 = 0.f, q1 = 0.f;
#pragma unroll
      for (int i = 0; i < 16; i += 2) {
        const float a = bf_lo(A[i]), b = bf_hi(A[i]), c_ = bf_lo(A[i + 1]), d = bf_hi(A[i + 1]);
        s0 += a + b; q0 = fmaf(a, a, q0); q0 = fmaf(b, b, q0);
        s1 += c_ + d; q1 = fmaf(c_, c_, q1); q1 = fmaf(d, d, q1);
      }
#pragma unroll
      for (int o = 1; o <= 2; o <<= 1) {
        s0 += __shfl_xor_sync(~0u, s0, o); q0 += __shfl_xor_sync(~0u, q0, o);
        s1 += __shfl_xor_sync(~0u, s1, o); q1 += __shfl_xor_sync(~0u, q1, o);
      }
      if (t < 2)
        asm volatile("red.relaxed.gpu.global.add.v4.f32 [%0], {%1,%2,%3,%4};" ::"l"(g_rows + layer * LSEQ + blk * 64 + 16 * w + g + 8 * t),
                     "f"(t ? s1 : s0), "f"(t ? q1 : q0), "f"(1.f), "f"(0.f) : "memory");
    }
  }
  if (wg == 1) {
#pragma unroll 1
    for (int c = cut; c < 8; c++) wait_full(c);
    ready = true;
    bar_sync(5, 256);
  }
#pragma unroll 1
  for (int c = cut; c < 8; c++) {
    if (!ready) wait_full(c);
    issue(c, 0);
    if (wg == 1) {
      wg_wait<2>();
      if (leader && c >= cut + 2) mbar_arrive(bar + 8 * (B_DN + 8 + c - 2));
    } else if (c == 7) {
      bar_arrive(5, 256);
    } else {
      ready = peek(c + 1);
      wg_wait<1>();
      if (leader && c < 6) mbar_arrive(bar + 8 * (B_DN + c - 1));
    }
  }
  mbar_wait(bar + 8 * (B_LN + wg), layer);
  const float4 ln = lds128f(sb + ln_off(wg) + (8 * w + g) * 16);
  mean0 = ln.x; rstd0 = ln.y; mean1 = ln.z; rstd1 = ln.w;
  wg_wait<0>();
  acc_fence<96>(acc);
  if (leader) mbar_arrive(bar + 8 * (B_DN + 8 * wg + 7));
}

__device__ __forceinline__ void attn_phase(const Params& p, uint32_t sb, int layer, int rb, int hg, int wg, int w) {
  const int lane = opaque_tid() & 31;
  const int g = lane >> 2, t = lane & 3;
  const uint32_t bar = sb + SM_BAR;
  const int blk = 16 * wg + rb;
  float acc[96];
  float2 cs[24];
  float mean0, mean1, rstd0, rstd1;
  if (layer) gemm_section<true>(acc, mean0, mean1, rstd0, rstd1, sb, blk, hg, wg, w, lane);
  else gemm_section<false>(acc, mean0, mean1, rstd0, rstd1, sb, blk, hg, wg, w, lane);
  TSW(1);
#pragma unroll
  for (int j = 8; j < 24; j++) cs[j] = lds64f(sb + SM_CS + 4 * (8 * j + 2 * t));
  const uint32_t kvx = sb + (wg ? 22 : 0) * PG;

  uint32_t kb[4][8], vb[4][8], qa[4][4];
  {
    const float nm0 = -mean0 * rstd0, nm1 = -mean1 * rstd1;
    const int st_row = 16 * w + (lane & 7) + 8 * ((lane >> 3) & 1);
    const uint32_t st_base = kvx + st_row * 256;
    const bool sender = (w == 3 && blk < 31);
    uint4* halo = &g_halo[(blk * 8 + hg) * 256 + lane];
    uint32_t r[4][2][4];
#pragma unroll
    for (int h = 0; h < 4; h++) {
#pragma unroll
      for (int kv = 0; kv < 2; kv++) {
#pragma unroll
        for (int dh = 0; dh < 2; dh++) {
          const int j = 8 + kv * 8 + 2 * h + dh;
          const float2 c2 = cs[j];
          const float v0 = fmaf(acc[4 * j + 0], rstd0, nm0 * c2.x), v1 = fmaf(acc[4 * j + 1], rstd0, nm0 * c2.y);
          const float v2 = fmaf(acc[4 * j + 2], rstd1, nm1 * c2.x), v3 = fmaf(acc[4 * j + 3], rstd1, nm1 * c2.y);
          r[h][kv][2 * dh] = packbf(v0, v1);
          r[h][kv][2 * dh + 1] = packbf(v2, v3);
        }
      }
      if (sender) {
        stg128(halo + (2 * h) * 32, make_uint4(r[h][0][0], r[h][0][2], r[h][0][1], r[h][0][3]));
        stg128(halo + (2 * h + 1) * 32, make_uint4(r[h][1][0], r[h][1][1], r[h][1][2], r[h][1][3]));
      }
    }
#pragma unroll
    for (int j = 0; j < 8; j++) cs[j] = lds64f(sb + SM_CS + 4 * (8 * j + 2 * t));
    mbar_wait(bar + 8 * (B_DN + 7), layer);
#pragma unroll
    for (int h = 0; h < 4; h++) {
#pragma unroll
      for (int kv = 0; kv < 2; kv++) {
        const int chunk = 4 * h + 2 * kv + (lane >> 4);
        if (w < 3) stsm4(st_base + (((chunk & 8) | ((chunk ^ st_row) & 7)) << 4), r[h][kv][0], r[h][kv][1], r[h][kv][2], r[h][kv][3]);
      }
      kb[h][4] = r[h][0][0]; kb[h][5] = r[h][0][2]; kb[h][6] = r[h][0][1]; kb[h][7] = r[h][0][3];
      vb[h][4] = movm_t(r[h][1][0]); vb[h][5] = movm_t(r[h][1][1]); vb[h][6] = movm_t(r[h][1][2]); vb[h][7] = movm_t(r[h][1][3]);
    }
#pragma unroll
    for (int h = 0; h < 4; h++) {
#pragma unroll
      for (int dh = 0; dh < 2; dh++) {
        const int j = 2 * h + dh;
        const float2 c2 = cs[j];
        qa[h][2 * dh] = packbf(fmaf(-mean0, c2.x, acc[4 * j + 0]), fmaf(-mean0, c2.y, acc[4 * j + 1]));
        qa[h][2 * dh + 1] = packbf(fmaf(-mean1, c2.x, acc[4 * j + 2]), fmaf(-mean1, c2.y, acc[4 * j + 3]));
      }
    }
  }
  bar_sync(2 + wg, 128);
  TSW(2);
  {
    const uint32_t prev_base = kvx + (16 * w - 16) * 256;
    const int mi = lane >> 3;
    const int r = 8 * (mi >> 1) + (lane & 7), r2 = 8 * (mi & 1) + (lane & 7);
    if (w != 0) {
#pragma unroll
      for (int h = 0; h < 4; h++) {
        const int ch = 4 * h + (mi & 1), ch2 = 4 * h + 2 + (mi >> 1);
        ldsm4(&kb[h][0], prev_base + r * 256 + (((ch & 8) | ((ch ^ r) & 7)) << 4));
        ldsm4t(&vb[h][0], prev_base + r2 * 256 + (((ch2 & 8) | ((ch2 ^ r2) & 7)) << 4));
      }
    } else if (blk > 0) {
      uint4* src = &g_halo[((blk - 1) * 8 + hg) * 256 + lane];
      uint4 hv[8];
      int it = 0;
      bool ok;
      do {
        ok = true;
#pragma unroll
        for (int i = 0; i < 8; i++) hv[i] = ld_tagged(src + i * 32);
#pragma unroll
        for (int i = 0; i < 8; i++) ok = ok && hv[i].x != UNSET;
      } while (!__all_sync(~0u, ok) && ++it < (1 << 20));
      if (layer == 0) {
#pragma unroll
        for (int i = 0; i < 2; i++) stg128(src + i * 128 + (lane >> 1) * 6, make_uint4(UNSET, UNSET, UNSET, UNSET));
      }
#pragma unroll
      for (int h = 0; h < 4; h++) {
        kb[h][0] = hv[2 * h].x; kb[h][1] = hv[2 * h].y; kb[h][2] = hv[2 * h].z; kb[h][3] = hv[2 * h].w;
        vb[h][0] = movm_t(hv[2 * h + 1].x); vb[h][1] = movm_t(hv[2 * h + 1].y);
        vb[h][2] = movm_t(hv[2 * h + 1].z); vb[h][3] = movm_t(hv[2 * h + 1].w);
      }
    } else {
#pragma unroll
      for (int h = 0; h < 4; h++)
#pragma unroll
        for (int k = 0; k < 4; k++) kb[h][k] = vb[h][k] = 0u;
    }
    TSW(3);
  }
  mbar_wait(bar + 8 * (B_DN + 15), layer);
  TSW(4);

  const bool first = (blk == 0 && w == 0);
  const int e = t - (g >> 1);
  const bool par = g & 1, epos = e >= 1;
  const uint32_t pmask = par ? 0xffff0000u : 0x0000ffffu;
  const uint32_t mB0 = epos ? pmask : 0u, mB1 = epos ? 0u : pmask;
  const float cl2 = 0.25f * 1.4426950408889634f;
  const float sc0 = rstd0 * cl2, sc1 = rstd1 * cl2;
  const float NEG = -INFINITY;
  float vA0[4], vB0[4], vA1[4], vB1[4];
#pragma unroll
  for (int h = 0; h < 4; h++) {
    float S[4][4];
#pragma unroll
    for (int j = 0; j < 4; j++) {
      S[j][0] = S[j][1] = S[j][2] = S[j][3] = 0.f;
      mma_bf16(S[j], qa[h], kb[h][2 * j], kb[h][2 * j + 1]);
    }
    vA0[h] = par ? S[1][1] : S[1][0];
    vB0[h] = epos ? (par ? S[0][1] : S[0][0]) : (par ? S[2][1] : S[2][0]);
    vA1[h] = par ? S[2][3] : S[2][2];
    vB1[h] = epos ? (par ? S[1][3] : S[1][2]) : (par ? S[3][3] : S[3][2]);
    if (first) { vA0[h] = NEG; if (epos) { vB0[h] = NEG; vB1[h] = NEG; } }
  }
  float m0[4], m1[4];
#pragma unroll
  for (int h = 0; h < 4; h++) { m0[h] = fmaxf(vA0[h], vB0[h]); m1[h] = fmaxf(vA1[h], vB1[h]); }
#pragma unroll
  for (int o = 1; o <= 2; o <<= 1) {
#pragma unroll
    for (int h = 0; h < 4; h++) {
      m0[h] = fmaxf(m0[h], __shfl_xor_sync(~0u, m0[h], o));
      m1[h] = fmaxf(m1[h], __shfl_xor_sync(~0u, m1[h], o));
    }
  }
  float O0[4][4], O1[4][4], Z[4][4];
#pragma unroll
  for (int h = 0; h < 4; h++) {
    const float mm0 = -m0[h] * sc0, mm1 = -m1[h] * sc1;
    const float pA0 = ex2(fmaf(vA0[h], sc0, mm0)), pB0 = ex2(fmaf(vB0[h], sc0, mm0));
    const float pA1 = ex2(fmaf(vA1[h], sc1, mm1)), pB1 = ex2(fmaf(vB1[h], sc1, mm1));
    const uint32_t hA0 = packbf(pA0, pA0), hB0 = packbf(pB0, pB0), hA1 = packbf(pA1, pA1), hB1 = packbf(pB1, pB1);
    const uint32_t P0[4] = {hB0 & mB0, 0u, hA0 & pmask, hB1 & mB0};
    const uint32_t P1[4] = {hB0 & mB1, hA1 & pmask, 0u, hB1 & mB1};
#pragma unroll
    for (int k = 0; k < 4; k++) O0[h][k] = O1[h][k] = Z[h][k] = 0.f;
    mma_bf16(O0[h], P0, vb[h][0], vb[h][1]); mma_bf16(O1[h], P0, vb[h][2], vb[h][3]); mma_bf16(Z[h], P0, 0x3f803f80u, 0x3f803f80u);
    mma_bf16(O0[h], P1, vb[h][4], vb[h][5]); mma_bf16(O1[h], P1, vb[h][6], vb[h][7]); mma_bf16(Z[h], P1, 0x3f803f80u, 0x3f803f80u);
  }
  if (lane == 0) mbar_arrive(bar + 8 * (B_OST + wg));
  uint4* op = (uint4*)g_O + ((layer * 32 + blk) * 8 + hg) * 512 + 64 * t + 16 * w + g;
#pragma unroll
  for (int h = 0; h < 4; h += 2) {
    const float i0 = rcp_approx(Z[h][0]), i1 = rcp_approx(Z[h][2]), j0 = rcp_approx(Z[h + 1][0]), j1 = rcp_approx(Z[h + 1][2]);
    stg128(op + 128 * h, make_uint4(packbf(O0[h][0] * i0, O0[h][1] * i0), packbf(O1[h][0] * i0, O1[h][1] * i0),
                                   packbf(O0[h + 1][0] * j0, O0[h + 1][1] * j0), packbf(O1[h + 1][0] * j0, O1[h + 1][1] * j0)));
    stg128(op + 128 * h + 8, make_uint4(packbf(O0[h][2] * i1, O0[h][3] * i1), packbf(O1[h][2] * i1, O1[h][3] * i1),
                                            packbf(O0[h + 1][2] * j1, O0[h + 1][3] * j1), packbf(O1[h + 1][2] * j1, O1[h + 1][3] * j1)));
  }
  TSW(5);
  __syncwarp();
  if (lane == 0) red_relaxed(&g_cnt[(C_O + layer * 32 + blk) * 32]);
  TSW(6);
}

#define LPRE 1
__device__ __forceinline__ void conv_load(uint32_t* A, uint32_t pe);
__device__ __forceinline__ void proj_phase(const Params& p, uint32_t sb, int layer, int rb, int q, int& rtp, uint32_t* A0, uint32_t* A1) {
  const int lane = opaque_tid() & 31;
  const int wg = __shfl_sync(~0u, opaque_tid() >> 7, 0), w = __shfl_sync(~0u, (opaque_tid() >> 5) & 3, 0);
  const bool TR = layer != 0;
  const int t = lane & 3;
  const uint32_t bar = sb + SM_BAR;
  const uint32_t rbx = sb + (P_R + wg) * PG;
  const uint32_t rsrc = sb + (wg ? 2 : P_R) * PG;
  const int blk = 16 * wg + rb;
  mbar_wait(bar + 8 * (B_RF + wg), layer);
  mbar_wait(bar + 8 * B_WOF, layer);
  const uint32_t stg = sb + (wg ? SM_KGT : SM_STG);
  if (layer) {
    const uint32_t pe = sb + cv_pe(wg, 1) + 4 * (16 + 16 * w + (lane >> 2) - 2 * t);
    mbar_wait(bar + 8 * B_PE, 1);
    conv_load(A0, pe);
    conv_load(A1, pe + 2 * 4480);
    __syncwarp();
    if (lane == 0) mbar_arrive(bar + 8 * B_AL);
  } else {
#pragma unroll
    for (int i = 0; i < 68; i++) {
      asm volatile("mov.b32 %0, 0;" : "=r"(A0[i]));
      asm volatile("mov.b32 %0, 0;" : "=r"(A1[i]));
    }
  }
  bool clean = false, staged = false;
#pragma unroll 1
  for (int attempt = 0; attempt < MAX_RETRY; attempt++) {
  uint32_t res[16];
  if (!TR) {
#pragma unroll
    for (int j = 0; j < 8; j += 2) {
      const int mi = lane >> 3;
      const int row = 16 * w + (lane & 7) + 8 * (mi & 1), ch = j + (mi >> 1);
      ldsm4(&res[2 * j], rsrc + row * 128 + ((ch ^ (row & 7)) << 4));
    }
  } else {
#pragma unroll
    for (int j = 0; j < 8; j += 2) {
      const int mi = lane >> 3;
      const int line = 8 * (j + (mi >> 1)) + (lane & 7), pc = 2 * w + (mi & 1);
      ldsm4t(&res[2 * j], rsrc + line * 128 + ((pc ^ (line & 7)) << 4));
    }
  }
  float acc[32];
#pragma unroll
  for (int j = 0; j < 16; j++) { acc[2 * j] = bf_lo(res[j]); acc[2 * j + 1] = bf_hi(res[j]); }
  acc_fence<32>(acc);
  if (wg) mbar_wait(bar + 8 * B_PG, layer);
  const int wg2 = __shfl_sync(~0u, opaque_tid() >> 7, 0);
  const uint64_t da0 = mkdesc(sb, 1024, 128, 0), db0 = mkdesc(sb, 8192, 1024, 1);
#pragma unroll
  for (int c = 0; c < 4; c++) {
    mbar_wait(bar + 8 * (B_OF + 4 * wg + c), layer);
    if (c == 0) TSW(7);
    const uint64_t da = da0 + (uint32_t)(o_page(wg2, c) * 512);
    wg_fence();
#pragma unroll
    for (int ks = 0; ks < 8; ks++) wgmma_ss<64, 0, 1>(acc, da + ks * 128, db0 + wo_page(2 * c + (ks >> 2)) * 512 + (ks & 3) * 128, 1);
    wg_commit();
  }
  if (wg) mbar_wait(bar + 8 * B_KG, 0);
  wg_wait<0>();
  acc_fence<32>(acc);
  TSW(8);
  if (!clean) {
    const float chk = acc[0] + acc[2];
    clean = __all_sync(~0u, chk == chk);
    if (clean && lane == 0) mbar_arrive(bar + 8 * (B_PDONE + wg));
  }
  float s0 = 0.f, q0 = 0.f, s1 = 0.f, q1 = 0.f;
  uint32_t o[16];
#pragma unroll
  for (int j = 0; j < 8; j++) {
    const float a = acc[4 * j], b = acc[4 * j + 1], c = acc[4 * j + 2], d = acc[4 * j + 3];
    o[2 * j] = packbf(a, b);
    o[2 * j + 1] = packbf(c, d);
    s0 += a + b; q0 = fmaf(a, a, q0); q0 = fmaf(b, b, q0);
    s1 += c + d; q1 = fmaf(c, c, q1); q1 = fmaf(d, d, q1);
  }
#pragma unroll
  for (int j = 0; j < 8; j += 2) {
    const int mi = lane >> 3;
    const int line = 8 * (j + (mi >> 1)) + (lane & 7), pc = 2 * w + (mi & 1);
    stsm4t(rbx + line * 128 + ((pc ^ (line & 7)) << 4), o[2 * j], o[2 * j + 1], o[2 * j + 2], o[2 * j + 3]);
  }
#pragma unroll
  for (int o2 = 1; o2 <= 2; o2 <<= 1) {
    s0 += __shfl_xor_sync(~0u, s0, o2); q0 += __shfl_xor_sync(~0u, q0, o2);
    s1 += __shfl_xor_sync(~0u, s1, o2); q1 += __shfl_xor_sync(~0u, q1, o2);
  }
  {
    const int i = 2 * (lane >> 2) + (t & 1), k = (i * 11) >> 5;
    const float v = (t == 0) ? s0 : (t == 1) ? q0 : (t == 2) ? s1 : q1;
    sts32f(stg + k * 128 + (2 * w + (t >> 1)) * 16 + (i - 3 * k) * 4, v);
  }
  TSW(9);
  fence_async_smem();
  if (attempt == 0 && clean) {
    staged = true;
    __syncwarp();
    if (lane == 0) mbar_arrive(bar + 8 * (B_STG + wg));
  }
  if (!bar_or(2 + wg, 128, !clean)) break;
  bool unset = false;
#pragma unroll
  for (int i = 0; i < 4; i++) unset |= lds32(sb + o_page(wg, i) * PG + (32 * w + lane) * 128) == UNSET;
  if (!bar_or(2 + wg, 128, unset)) break;
  if (w == 0 && elect_one()) {
    fence_async_smem();
    mbar_expect(bar + 8 * (B_RT + wg), 9 * PG);
    if (layer == 0) tma_ld(rsrc, &p.mapX, q * 64, blk * 64, bar + 8 * (B_RT + wg));
    else tma_ld(rsrc, &p.mapXT, blk * 64, DM + q * 64, bar + 8 * (B_RT + wg));
#pragma unroll 1
    for (int c = 0; c < 4; c++) bulk_ld(sb + o_page(wg, c) * PG, g_O + ((layer * 32 + blk) * 4 + c) * PG, 2 * PG, bar + 8 * (B_RT + wg));
  }
  mbar_wait(bar + 8 * (B_RT + wg), rtp);
  rtp ^= 1;
  RETRY(0);
  }
  if (!clean && lane == 0) mbar_arrive(bar + 8 * (B_PDONE + wg));
  if (!staged && lane == 0) mbar_arrive(bar + 8 * (B_STG + wg));
  TSW(10);
}

__device__ __forceinline__ void conv_load(uint32_t* A, uint32_t pe) {
#pragma unroll
  for (int m = 0; m < 17; m++) {
    A[4 * m + 2] = lds32(pe + 4 * (64 * m - 8));
    A[4 * m + 0] = lds32(pe + 4 * (64 * m));
    A[4 * m + 1] = lds32(pe + 4 * (64 * m + 8));
    asm volatile("mov.b32 %0, %1;" : "=r"(A[4 * m + 3]) : "r"(A[4 * m + 0]));
  }
}
template <int M> __device__ __forceinline__ void conv_tri(float* acc, const uint32_t* A, uint64_t d) {
  if constexpr (M < 16) {
    wgmma_rs<64 - 8 * (M / 2), 0>(acc, A + 4 * M, d + (uint64_t)(64 + 4 * M), M != 0);
    conv_tri<M + 1>(acc, A, d);
  }
}
__device__ __forceinline__ void conv_mma0(float* acc, const uint32_t* A, uint64_t d) {
  wg_fence();
  conv_tri<0>(acc, A, d);
  wg_commit();
}
__device__ __forceinline__ void conv_mma1_early(float* acc, const uint32_t* A, uint64_t d, uint64_t ds, uint64_t df) {
  wg_fence();
  wgmma_rs<64, 0>(acc, A + 64, d + 64, 0);
  wgmma_ss<64, 1, 0>(acc, ds, df, 1);
  wgmma_ss<64, 1, 0>(acc, ds + 128, df + 128, 1);
}
__device__ __forceinline__ void conv_mma1(float* acc, const uint32_t* A, uint64_t d) {
#pragma unroll
  for (int m = 0; m < 16; m++) wgmma_rs<64, 0>(acc, A + 4 * m, d + (uint64_t)(4 * m), 1);
  wg_commit();
}
__device__ __forceinline__ void conv_store(float* acc, uint32_t pb, uint32_t over, int w) {
  acc_fence<32>(acc);
  const int l = opaque_tid() & 31, mt = l >> 3;
  int c = 2 * (63 - 8 * (mt >> 1) - (l & 7) + w) + (mt & 1);
  c ^= (c >> 3) & 1;
  const uint32_t a0 = pb + c * 16;
#pragma unroll
  for (int j = 0; j < 8; j += 2)
    stsm4t(j == 0 ? (c < 128 ? a0 : over + (c - 128) * 16) : a0 - 256 * j, packbf(acc[4 * j], acc[4 * j + 1]), packbf(acc[4 * j + 2], acc[4 * j + 3]),
           packbf(acc[4 * j + 4], acc[4 * j + 5]), packbf(acc[4 * j + 6], acc[4 * j + 7]));
}
__device__ __forceinline__ void conv_sums(uint32_t sb, int lc, int ht) {
  const int m = ht - 1;
  uint4 v[2][3];
#pragma unroll
  for (int c = 0; c < 2; c++)
#pragma unroll
    for (int k = 0; k < 3; k++) {
      const int mm = m - 1 + k;
      v[c][k] = lds128(sb + cv_u(lc + c) + (mm >= 0 ? (mm & 1) * CV_UH + (127 - (mm >> 1)) * 16 : 128 * 16));
    }
  const int ce = m + 2, co = m + 1;
#pragma unroll
  for (int c = 0; c < 2; c++) {
    const uint32_t x[8] = {v[c][0].z, v[c][0].w, v[c][1].x, v[c][1].y, v[c][1].z, v[c][1].w, v[c][2].x, v[c][2].y};
    float pv[16];
#pragma unroll
    for (int k = 0; k < 8; k++) { pv[2 * k] = bf_lo(x[k]); pv[2 * k + 1] = bf_hi(x[k]); }
    float t2[15], t4[13], s9[8], s7[8];
#pragma unroll
    for (int i = 0; i < 15; i++) t2[i] = pv[i] + pv[i + 1];
#pragma unroll
    for (int i = 0; i < 13; i++) t4[i] = t2[i] + t2[i + 2];
#pragma unroll
    for (int i = 0; i < 8; i++) {
      s9[i] = (t4[i] + t4[i + 4]) + pv[i + 8];
      s7[i] = (t4[i + 1] + t2[i + 5]) + pv[i + 7];
    }
    const uint4 e4 = make_uint4(packbf(s9[0], s9[1]), packbf(s9[2], s9[3]), packbf(s9[4], s9[5]), packbf(s9[6], s9[7]));
    if (ce < 128) sts128(sb + cv_se(lc + c) + ((ce ^ ((ce >> 3) & 7)) << 4), e4);
    else sts128(sb + cv_se(lc + c), make_uint4(0, 0, 0, 0));
    sts128(sb + cv_so(lc + c) + ((co ^ ((co >> 3) & 7)) << 4),
           make_uint4(packbf(s7[0], s7[1]), packbf(s7[2], s7[3]), packbf(s7[4], s7[5]), packbf(s7[6], s7[7])));
  }
}

template <int HALF, int NCH, int STEP = 1>
__device__ __forceinline__ void conv_epi(uint32_t sb, bf16* out, int lc, int c) {
  uint4 v[NCH][4], xr[NCH];
  const uint32_t sw = (c ^ ((c >> 3) & 1)) * 16;
#pragma unroll
  for (int u = 0; u < NCH; u++) {
#pragma unroll
    for (int k = 0; k < 4; k++) v[u][k] = lds128(sb + (HALF ? cv_pb1(lc + STEP * u, k) : cv_pb0(lc + STEP * u, k)) + sw);
    xr[u] = lds128(sb + cv_x(HALF, lc + STEP * u) + c * 16);
  }
#pragma unroll
  for (int u = 0; u < NCH; u++) {
    uint4 o;
    o.x = hadd2(xr[u].x, hadd2(hadd2(v[u][0].x, v[u][1].x), hadd2(v[u][2].x, v[u][3].x)));
    o.y = hadd2(xr[u].y, hadd2(hadd2(v[u][0].y, v[u][1].y), hadd2(v[u][2].y, v[u][3].y)));
    o.z = hadd2(xr[u].z, hadd2(hadd2(v[u][0].z, v[u][1].z), hadd2(v[u][2].z, v[u][3].z)));
    o.w = hadd2(xr[u].w, hadd2(hadd2(v[u][0].w, v[u][1].w), hadd2(v[u][2].w, v[u][3].w)));
    stg128(out + cv_chan(0, lc + STEP * u) * LSEQ + HALF * 1024 + c * 8, o);
  }
}

__device__ __forceinline__ bool prep_valid(const uint4 (&st)[6], const uint4 (&xr)[4]) {
  const uint32_t n = __float_as_uint(8.f);
  return st[0].w == n && st[1].w == n && st[2].w == n && st[3].w == n && st[4].w == n && (st[5].w | st[5].y | st[5].z) == n &&
         xr[0].x != UNSET && xr[1].x != UNSET && xr[2].x != UNSET && xr[3].x != UNSET;
}
template <int HALF>
__device__ __forceinline__ void conv_prep(uint32_t sb, int layer, int cta, int i) {
  uint4 st[6], xr[4];
  const uint4* sp = (const uint4*)g_stats + (layer * 32 + HALF * 16 + (i >> 3)) * 48 + (i & 7);
  const uint4* xp = (const uint4*)g_xT + (2 * layer * DM + 2 * cta) * (LSEQ / 8) + HALF * 128 + i;
  auto fetch = [&]() {
#pragma unroll
    for (int k = 0; k < 6; k++) st[k] = ld_tagged(sp + 8 * k);
#pragma unroll
    for (int k = 0; k < 4; k++) xr[k] = ld_tagged(xp + cv_chan(0, k) * (LSEQ / 8));
  };
  if (HALF) {
#pragma unroll
    for (int k = 0; k < 6; k++) st[k] = lds128(sb + CV_ST + (i >> 3) * 768 + k * 128 + (i & 7) * 16);
#pragma unroll
    for (int k = 0; k < 4; k++) xr[k] = lds128(sb + cv_x(1, k) + i * 16);
  } else {
    fetch();
  }
  int it = 0;
  while (!__all_sync(~0u, prep_valid(st, xr)) && ++it < MAX_RETRY) { fetch(); RETRY(1); }
  if (!HALF || it) {
#pragma unroll
    for (int k = 0; k < 4; k++) sts128(sb + cv_x(HALF, k) + i * 16, xr[k]);
  }
  const uint32_t v[16] = {st[0].x, st[0].y, st[0].z, st[1].x, st[1].y, st[1].z, st[2].x, st[2].y, st[2].z, st[3].x, st[3].y, st[3].z, st[4].x, st[4].y, st[4].z, st[5].x};
  uint32_t rs[4], nm[4];
#pragma unroll
  for (int k = 0; k < 4; k++) {
    const float m0 = __uint_as_float(v[4 * k]) * (-1.f / DM), m1 = __uint_as_float(v[4 * k + 2]) * (-1.f / DM);
    const float r0 = rsqrt_approx(fmaxf(fmaf(__uint_as_float(v[4 * k + 1]), 1.f / DM, -m0 * m0), 0.f) + 1e-5f);
    const float r1 = rsqrt_approx(fmaxf(fmaf(__uint_as_float(v[4 * k + 3]), 1.f / DM, -m1 * m1), 0.f) + 1e-5f);
    rs[k] = packbf(r0, r1);
    nm[k] = packbf(m0 * bf_lo(rs[k]), m1 * bf_hi(rs[k]));
  }
  const uint32_t ud = sb + (i & 1) * CV_UH + (127 - 64 * HALF - (i >> 1)) * 16;
#pragma unroll
  for (int k = 0; k < 4; k++)
    sts128(ud + cv_u(k), make_uint4(hfma2(xr[k].x, rs[0], nm[0]), hfma2(xr[k].y, rs[1], nm[1]), hfma2(xr[k].z, rs[2], nm[2]), hfma2(xr[k].w, rs[3], nm[3])));
  fence_async_smem();
}

#define EARLY1 1
#define PP0 1
__device__ __forceinline__ void conv_phase(const Params& p, uint32_t sb, int layer, int cta, uint32_t* A0, uint32_t* A1) {
  const int tid = opaque_tid();
  const int wg = __shfl_sync(~0u, tid >> 7, 0), w = __shfl_sync(~0u, (tid >> 5) & 3, 0);
  const uint32_t bar = sb + SM_BAR;
  constexpr int CH2 = 4 * PG;
  bf16* xout = g_xT + ((2 * layer + 1) * DM + 2 * cta) * LSEQ;
  float acc[32];
  const uint32_t pe = sb + cv_pe(wg, 0) + 4 * (16 + 16 * w + ((tid & 31) >> 2) - 2 * (tid & 3));
  if (!(LPRE && layer)) {
    mbar_wait(bar + 8 * (B_PDONE + 1), layer);
    mbar_wait(bar + 8 * B_PE, layer);
    conv_load(A0, pe);
    conv_load(A1, pe + CH2);
  }
  TSW(19);
  const uint64_t d0 = mkdesc(sb + cv_u(wg), CV_UH, 128, 0), d1 = d0 + (CH2 >> 4);
  mbar_wait(bar + 8 * B_U, layer);
  TSW(12);
  if (wg == 1) bar_sync(5, 256);
  conv_mma0(acc, A0, d0);
  if (wg == 0) bar_arrive(5, 256);
  mbar_wait(bar + 8 * (B_PDONE + 1), layer);
  {
    const int l = opaque_tid() & 31;
    if ((l & 15) < 2 * w) sts128(sb + cv_pb0(wg + 2 * (l >> 4), w) + (l & 15) * 16, make_uint4(0, 0, 0, 0));
  }
  wg_wait<0>();
  conv_store(acc, sb + cv_pb0(wg, w), sb + cv_pb1(wg, w), w);
  conv_mma0(acc, A1, d1);
  wg_wait<0>();
  conv_store(acc, sb + cv_pb0(2 + wg, w), sb + cv_pb1(2 + wg, w), w);
  TSW(13);
  bar_sync(2 + wg, 128);
  conv_epi<0, 2, 2>(sb, xout, wg, opaque_tid() & 127);
  TSW(14);
  mbar_arrive(bar + 8 * B_PUB);
  const uint64_t ds = mkdesc(sb + cv_se(wg), 8192, 1024, 1), df = mkdesc(sb + cv_fa(wg), 512, 128, 0);
  mbar_wait(bar + 8 * B_S, layer);
  conv_mma1_early(acc, A0, d0, ds, df);
  wg_commit();
  if (wg == 0) mbar_wait(bar + 8 * B_U1, layer);
  else bar_sync(6, 256);
  TSW(15);
  wg_fence();
  conv_mma1(acc, A0, d0);
  if (wg == 0) bar_arrive(6, 256);
  wg_wait<0>();
  conv_store(acc, sb + cv_pb1(wg, w), sb + cv_dump(wg), w);
  TSW(16);
  bar_sync(2 + wg, 128);
  conv_epi<1, 1>(sb, xout, wg, opaque_tid() & 127);
  mbar_arrive(bar + 8 * (B_PUB + 1));
  conv_mma1_early(acc, A1, d1, ds + 512, df + (CH2 >> 4));
  conv_mma1(acc, A1, d1);
  wg_wait<0>();
  conv_store(acc, sb + cv_pb1(2 + wg, w), sb + cv_dump(2 + wg), w);
  TSW(17);
  bar_sync(2 + wg, 128);
  conv_epi<1, 1>(sb, xout, 2 + wg, opaque_tid() & 127);
  mbar_arrive(bar + 8 * (B_PUB + 2));
  TSW(18);
}

__device__ __forceinline__ void final_tile(const Params& p, uint32_t buf, int ch0, int pos0, int barid) {
  const int tid = opaque_tid() & 127, lane = tid & 31, w = tid >> 5;
  const uint4* src = (const uint4*)(g_xT + (3 * DM + ch0 + (tid >> 3)) * LSEQ + pos0) + (tid & 7);
  const int ch = tid >> 3, row = 4 * (ch & 6) + 2 * (ch >> 3) + (ch & 1);
  const uint32_t dst = buf + row * 128;
  const uint32_t ld = buf + lane * 128;
  bf16* out = p.out + (pos0 + 16 * w + (lane >> 2)) * DM + ch0 + 8 * (lane & 3);
  uint4 a, b;
  int it = 0;
  do {
    if (it) RETRY(2);
    a = ld_tagged(src); b = ld_tagged(src + 16 * LSEQ / 8);
  } while (!__all_sync(~0u, a.x != UNSET && b.x != UNSET) && ++it < (1 << 20));
  sts128(dst + (((tid ^ row) & 7) << 4), a);
  sts128(dst + 512 + (((tid ^ row ^ 4) & 7) << 4), b);
  bar_sync(barid, 128);
#pragma unroll
  for (int h = 0; h < 2; h++) {
    uint32_t r[4];
    ldsm4t(r, ld + ((((2 * w + h) ^ lane) & 7) << 4));
    *(uint4*)(out + 8 * h * DM) = make_uint4(r[0], r[1], r[2], r[3]);
  }
}

struct cplx { float r, i; };
__device__ __forceinline__ cplx cmul(cplx a, cplx b) { return {fmaf(a.r, b.r, -a.i * b.i), fmaf(a.r, b.i, a.i * b.r)}; }
__device__ __forceinline__ cplx csqr(cplx a) { return {fmaf(a.r, a.r, -a.i * a.i), (a.r + a.r) * a.i}; }
__device__ __forceinline__ cplx cexp_l(float ar2, float ai, float l) {
  const float m = ex2(ar2 * l);
  const float x = ai * l;
  return {m * __cosf(x), m * __sinf(x)};
}

__device__ __forceinline__ void colsum_cta(const Params& p, uint32_t sb, int j, int tid) {
  const uint32_t bar = sb + SM_BAR;
  auto ld = [&](int i) {
    mbar_expect(bar + 8 * i, 3 * PG);
    tma_ld3(sb + (i & 7) * 3 * PG, &p.mapW3, (2 * j + (i & 1)) * 64, (i >> 1) * 64, 0, bar + 8 * i);
  };
  if (tid == 384) {
#pragma unroll
    for (int i = 0; i < 24; i++) mbar_init(bar + 8 * i, i < 16 ? 1 : 12);
    asm volatile("fence.mbarrier_init.release.cluster;" ::: "memory");
    fence_async_smem();
#pragma unroll 1
    for (int i = 0; i < 8; i++) ld(i);
  }
  const unsigned ep = ld_relaxed(&g_cnt[C_CS * 32]);
  bar_sync(0, NTHREADS);
  if (tid == 384) {
#pragma unroll 1
    for (int i = 8; i < 16; i++) { mbar_wait(bar + 8 * (8 + i), 0); fence_async_smem(); ld(i); }
  }
  if (tid < 384) {
    const int lane = tid & 31, cc = tid & 7, r0 = (tid >> 3) & 15, part = tid >> 7;
    const uint32_t id = ((lane >> 2) == 2 * (lane & 3) ? 0x3f80u : 0u) | ((lane >> 2) == 2 * (lane & 3) + 1 ? 0x3f800000u : 0u);
    const uint32_t src = sb + part * PG + r0 * 128 + ((cc ^ (r0 & 7)) << 4);
    float s[2][2][4];
#pragma unroll
    for (int i = 0; i < 16; i++) s[i >> 3][(i >> 2) & 1][i & 3] = 0.f;
#pragma unroll 1
    for (int i2 = 0; i2 < 16; i2 += 2) {
#pragma unroll
      for (int h = 0; h < 2; h++) {
        const int i = i2 + h;
        mbar_wait(bar + 8 * i, 0);
        uint4 v[4];
#pragma unroll
        for (int k = 0; k < 4; k++) v[k] = lds128(src + (i & 7) * 3 * PG + k * 2048);
#pragma unroll
        for (int k = 0; k < 4; k++) {
          const uint32_t a[4] = {v[k].x, v[k].y, v[k].z, v[k].w};
          mma_bf16(s[h][0], a, id, 0u);
          mma_bf16(s[h][1], a, 0u, id);
        }
        __syncwarp();
        if (i < 8 && lane == 0) mbar_arrive(bar + 8 * (16 + i));
      }
    }
    const uint32_t red = sb + 24 * PG;
#pragma unroll
    for (int h = 0; h < 2; h++)
#pragma unroll
      for (int k = 0; k < 2; k++) sts128f(red + (r0 * 384 + h * 192 + part * 64 + cc * 8 + k * 4) * 4, s[h][k][0], s[h][k][1], s[h][k][2], s[h][k][3]);
    bar_sync(1, 384);
    float tot = 0.f;
#pragma unroll
    for (int k = 0; k < 16; k++) tot += __uint_as_float(lds32(red + (k * 384 + tid) * 4));
    asm volatile("st.relaxed.gpu.global.v2.u32 [%0], {%1,%2};" ::"l"(&g_colsum[j * 384 + tid]), "r"(__float_as_uint(tot)), "r"(ep / NCTA + 1) : "memory");
    const uint4 u = make_uint4(UNSET, UNSET, UNSET, UNSET);
    if (tid < 256) {
#pragma unroll 1
      for (int s = 0; s < 4; s++) {
        const int n = (s == 1 || s == 2) ? 32 : 16;
        uint4* buf = s == 1 ? (uint4*)g_O + 131072 : (uint4*)g_xT + (s + !s) * 131072;
#pragma unroll 4
        for (int i = 0; i < n; i++) stg128(buf + (j * n + i) * 1024 + (tid >> 1) * 8 + (tid & 1), u);
        if (n == 16) {
#pragma unroll 4
          for (int i = 0; i < 8; i++) stg128(buf + (256 + j * 64 + i * 8 + (tid >> 5)) * 256 + (s ? 0 : 128) + ((tid & 31) >> 1) * 8 + (tid & 1), u);
        }
        if (s == 3) {
#pragma unroll 4
          for (int i = 0; i < 32; i++) stg128(buf + (256 + j * 64 + 2 * i + (tid >> 7)) * 256 + 128 + (tid & 127), u);
        }
        bar_sync(2, 256);
        if (tid == 32 * s) red_release(&g_cnt[(C_R + s) * 32]);
      }
    }
  }
}

#define KB 4
#define KW 2
struct ModeIn { uint32_t ar, ai, br, bi, cr, ci; bf16 logdt; };
__device__ __forceinline__ ModeIn load_modes(const Params& p, int d, int m) {
  const int i = d * 64 + m;
  return {((const uint32_t*)p.a_re)[i], ((const uint32_t*)p.a_im)[i], ((const uint32_t*)p.b_re)[i], ((const uint32_t*)p.b_im)[i],
          ((const uint32_t*)p.c_re)[i], ((const uint32_t*)p.c_im)[i], p.log_dt[d]};
}
__device__ __forceinline__ float4 lds128f_nv(uint32_t a) { float4 v; asm("ld.shared.v4.f32 {%0,%1,%2,%3}, [%4];" : "=f"(v.x), "=f"(v.y), "=f"(v.z), "=f"(v.w) : "r"(a)); return v; }
__device__ __forceinline__ void kernel_gen(const Params& p, uint32_t sb, int cta, int ht, ModeIn in, const ModeIn& in1) {
  const uint32_t bst = sb + SM_KGB + ((ht & 63) >> 2) * 144 + (ht & 3) * 4 + (ht >> 6) * 16;
  const uint64_t db = mkdesc(sb + SM_KGB, 144, 2304, 0);
  const float e0 = (float)(8 * (((ht & 32) >> 1) + ((ht & 31) >> 2)));
  float T[20];
#pragma unroll
  for (int i = 0; i < 20; i++) T[i] = 0.f;
  float k0 = 0.f;
#pragma unroll 1
  for (int pass = 0; pass < 4; pass++) {
    {
      const int sh = (pass & 1) ? 0 : 16;
      auto val = [&](uint32_t v) { return __uint_as_float((v << sh) & 0xffff0000u); };
      const float dt = __bfloat162float(__float2bfloat16_rn(expf(__bfloat162float(in.logdt))));
      const float ar2 = dt * val(in.ar) * 1.4426950408889634f, ai = dt * val(in.ai);
      const cplx c = cmul({val(in.cr), -val(in.ci)}, {dt * val(in.br), -dt * val(in.bi)});
      k0 += c.r;
      const cplx z1 = cexp_l(ar2, -ai, 1.f), z256 = cexp_l(ar2, -ai, 256.f), z64 = cexp_l(ar2, ai, 64.f);
      const cplx z2 = csqr(z1), z512 = csqr(z256);
      auto put = [&](int j, cplx v) { sts32(bst + (j >> 2) * 2304 + (j & 3) * 32, packbf(v.r, v.i)); };
      sts128f(sb + SM_KGT + ht * 16, ar2, ai, z64.r, z64.i);
      const cplx c1 = cmul(c, z1), c2 = cmul(c, z2), c3 = cmul(c1, z2), c4 = cmul(c2, z2);
      const cplx c5 = cmul(c3, z2), c6 = cmul(c4, z2), c7 = cmul(c5, z2), c8 = cmul(c6, z2);
      put(0, c1); put(1, c2); put(2, c3); put(3, c4); put(4, c5); put(5, c6); put(6, c7); put(7, c8);
      const cplx c260 = cmul(c4, z256), c264 = cmul(c8, z256), c520 = cmul(c8, z512), c776 = cmul(c264, z512);
      put(8, cmul(c2, z256)); put(9, c260); put(10, cmul(c6, z256)); put(11, c264);
      put(12, cmul(c4, z512)); put(13, c520); put(14, cmul(c260, z512)); put(15, c776);
      const cplx c1032 = cmul(c520, z512), c1288 = cmul(c776, z512);
      put(16, c1032); put(17, c1288); put(18, cmul(c1032, z512)); put(19, cmul(c1288, z512));
    }
    fence_async_smem();
    bar_sync(4, 128);
    const uint32_t tb = sb + SM_KGT + (ht & 67) * 16;
    float2 nx[KB];
#pragma unroll
    for (int s = 0; s < KB; s++) nx[s] = lds64f(tb + s * 64);
#pragma unroll
    for (int q = 0; q < 16 / KB; q++) {
      uint32_t A[2 * KB];
      float2 cur[KB], z[KB];
#pragma unroll
      for (int s = 0; s < KB; s++) { cur[s] = nx[s]; z[s] = lds64f(tb + (KB * q + s) * 64 + 8); }
      if (q < 16 / KB - 1) {
#pragma unroll
        for (int s = 0; s < KB; s++) nx[s] = lds64f(tb + (KB * q + KB + s) * 64);
      }
      if (q >= KW) wg_wait<KW - 1>();
#pragma unroll
      for (int s = 0; s < KB; s++) {
        const cplx lo = cexp_l(cur[s].x, cur[s].y, e0), hi = cmul(lo, {z[s].x, z[s].y});
        A[2 * s] = packbf(lo.r, lo.i);
        A[2 * s + 1] = packbf(hi.r, hi.i);
      }
      wg_fence();
#pragma unroll
      for (int k = 0; k < KB / 2; k++) wgmma_rs<40, 0>(T, A + 4 * k, db + 9 * KB * q + 18 * k, (pass & 1) | q | k);
      wg_commit();
    }
    wg_wait<0>();
    acc_fence<20>(T);
    if (ht == 0) TS(4 + pass);
    if (pass & 1) {
      const int h2 = opaque_tid() - 256, w = h2 >> 5, lane = h2 & 31, t = lane & 3, chn = h2 >> 6, m = h2 & 63, i0 = 16 * (w & 1) + (lane >> 2);
      const int lc = (pass & 2) + chn;
      const uint32_t kc = sb + kc_off(lc);
      auto put = [&](int idx, float v) {
        sts16(kc + idx * 2, __bfloat16_as_ushort(__float2bfloat16_rn(v)));
      };
#pragma unroll
      for (int hi = 0; hi < 2; hi++) {
        const int i = i0 + 8 * hi;
        float v[5];
#pragma unroll
        for (int j = 0; j < 5; j++) v[j] = chn ? T[4 * j + 2 * hi + 1] : T[4 * j + 2 * hi];
        put(8 * i + 1 + t, v[0]);
        put(8 * i + 5 + t, v[1]);
        put(257 + 4 * i + t, v[2]);
        put(385 + 2 * i + (t & 1) + 64 * (t >> 1), v[3]);
        put(513 + i + 32 * t, v[4]);
      }
#pragma unroll
      for (int o = 16; o > 0; o >>= 1) k0 += __shfl_xor_sync(~0u, k0, o);
      if (lane == 0) sts32f(sb + SM_RED + 4 * w, k0);
      bar_sync(4, 128);
      if (m == 0) put(0, k0 + __uint_as_float(lds32(sb + SM_RED + 4 * w + 4)) + __uint_as_float(lds16(sb + SM_RED + 24 + 2 * lc) << 16));
      k0 = 0.f;
      in = in1;
    }
  }
}

__device__ __forceinline__ void expand_taps(uint32_t sb, int ht, int early) {
  const int ch = ht >> 5, lane = ht & 31;
  const uint32_t kc = sb + kc_off(ch);
  const uint32_t dst0 = sb + cv_pe(ch, early);
  auto put = [&](int G, uint32_t v0, uint32_t v1, uint32_t v2, uint32_t v3, uint32_t v4, uint32_t v5, uint32_t v6, uint32_t v7, uint32_t v8) {
    const uint32_t dst = dst0 + G * 32;
    sts128(dst, make_uint4(v1 | (v0 << 16), v2 | (v1 << 16), v3 | (v2 << 16), v4 | (v3 << 16)));
    sts128(dst + 16, make_uint4(v5 | (v4 << 16), v6 | (v5 << 16), v7 | (v6 << 16), v8 | (v7 << 16)));
  };
  {
    const uint4 q = lds128(kc + lane * 16);
    const uint32_t pv = lane ? lds16(kc + lane * 16 - 2) : 0u;
    const uint32_t dst = dst0 + (lane + 2) * 32;
    sts128(dst, make_uint4(__byte_perm(q.x, pv, 0x5410), __byte_perm(q.x, q.x, 0x1032), __byte_perm(q.y, q.x, 0x7610), __byte_perm(q.y, q.y, 0x1032)));
    sts128(dst + 16, make_uint4(__byte_perm(q.z, q.y, 0x7610), __byte_perm(q.z, q.z, 0x1032), __byte_perm(q.w, q.z, 0x7610), __byte_perm(q.w, q.w, 0x1032)));
    if (lane < 4) sts128(dst0 + lane * 16, make_uint4(0, 0, 0, 0));
  }
  uint32_t a[5], b[2][3];
  {
    const uint32_t s1 = kc + 2 * (256 + 4 * lane);
#pragma unroll
    for (int k = 0; k < 5; k++) a[k] = lds16(s1 + 2 * k);
#pragma unroll
    for (int u = 0; u < 2; u++) {
      const uint32_t s2 = kc + 2 * (384 + 2 * (lane + 32 * u));
#pragma unroll
      for (int k = 0; k < 3; k++) b[u][k] = lds16(s2 + 2 * k);
    }
  }
  const uint32_t k255 = lds16(kc + 2 * 255), k1024 = lds16(kc + 2 * 512);
  put(34 + lane, lane == 0 ? k255 : a[0], a[0], a[0], a[1], a[2], a[2], a[2], a[3], a[4]);
#pragma unroll
  for (int u = 0; u < 2; u++) put(66 + lane + 32 * u, b[u][0], b[u][0], b[u][0], b[u][0], b[u][1], b[u][1], b[u][1], b[u][2], b[u][2]);
  if (lane < 10) {
    const uint32_t v = lane == 0 ? k1024 : 0u;
    put(130 + lane, v, v, v, v, v, v, 0u, 0u, 0u);
  }
}
__device__ __forceinline__ void expand_far(uint32_t sb, int ht) {
  const int ch = ht >> 5, lane = ht & 31;
  const uint32_t kc = sb + kc_off(ch) + 2 * (513 + 2 * (63 - lane)), dst = sb + cv_fa(ch) + lane * 16;
#pragma unroll
  for (int ty = 0; ty < 2; ty++) {
    uint32_t v[16];
#pragma unroll
    for (int k = 0; k < 16; k++) v[k] = (k < 8 || 63 - lane - 4 * k >= 0) ? lds16(kc + 2 * (1 - ty) - 16 * k) : 0u;
#pragma unroll
    for (int u = 0; u < 2; u++)
      sts128(dst + ty * 2048 + u * 512, make_uint4(v[8 * u] | (v[8 * u + 1] << 16), v[8 * u + 2] | (v[8 * u + 3] << 16), v[8 * u + 4] | (v[8 * u + 5] << 16), v[8 * u + 6] | (v[8 * u + 7] << 16)));
    sts128(dst + ty * 2048 + 1024, make_uint4(0, 0, 0, 0));
  }
}

#define TMPF 1
#define CONST_SB 1
#define XGATE B_OST
#define WPRE 1
__host__ __device__ constexpr int bar_count(int i) {
  return i == B_LN ? 2 : i == B_AL ? 8 : i < B_STG ? 1 : i < B_PE ? 4 : (i >= B_PUB && i < B_S) ? 256 : 128;
}
__host__ __device__ constexpr bool bar_first(int i) { return i < B_WF + 2 && (i & 7) < 2; }

__global__ void __launch_bounds__(NTHREADS, 1) fused_kernel(const __grid_constant__ Params p) {
  extern __shared__ __align__(1024) uint8_t smem[];
  constexpr uint32_t sb = 1024;
  if (s32(smem) != sb) return;
  const int tid = threadIdx.x, lane = tid & 31;
  const int warp = __shfl_sync(~0u, tid >> 5, 0);
  if (tid == 32) {
    asm volatile("prefetch.tensormap [%0];" ::"l"(&p.mapX) : "memory");
    asm volatile("prefetch.tensormap [%0];" ::"l"(&p.mapW3) : "memory");
  }
  const int cta = blockIdx.x - (gridDim.x == NCTA + 4 ? 0 : 4);
  if ((unsigned)cta >= NCTA) {
    if (blockIdx.x < NCTA + 4) colsum_cta(p, sb, blockIdx.x & 3, tid);
    return;
  }
  const int rb = ((cta >> 4) & 3) * 4 + ((cta >> 2) & 3), hg = (cta >> 6) * 4 + (cta & 3);
  const uint32_t bar = sb + SM_BAR;
  auto ld_x0 = [&](int half, int c) {
    const uint32_t b = bar + 8 * (B_XF + 8 * half + c);
    mbar_expect(b, PG);
    tma_ld(sb + x_page(half, c) * PG, &p.mapX, c * 64, (16 * half + rb) * 64, b);
  };
  auto ld_x1 = [&](int half, int c, int b0) {
    const uint32_t b = bar + 8 * b0;
    mbar_expect(b, PG);
    tma_ld(sb + (8 * half + c) * PG, &p.mapXT, (16 * half + rb) * 64, DM + c * 64, b);
  };
  auto ld_w = [&](int c) {
    const uint32_t b = bar + 8 * (B_WF + c);
    mbar_expect(b, 3 * PG);
    tma_ld3(sb + w_page(c) * PG, &p.mapW3, hg * 64, c * 64, 0, b);
  };

  if (tid == 0) TS(0);
  if (tid == 480) LTS(0);
  if (warp == 0 && elect_one()) {
#pragma unroll
    for (int i = 0; i < B_WF + 2; i++)
      if (bar_first(i)) mbar_init(bar + 8 * i, 1);
    asm volatile("fence.mbarrier_init.release.cluster;" ::: "memory");
    fence_async_smem();
    ld_x0(0, 0);
    ld_w(0); ld_x0(1, 0);
    ld_x0(0, 1); ld_w(1); ld_x0(1, 1);
    TS(1);
  }
  __syncwarp();
  if (warp >= 1 && warp < 8 && elect_one()) {
    if (warp < 4) {
#pragma unroll
      for (int i = 2; i < 8; i++) mbar_init(bar + 8 * (8 * warp - 8 + i), 1);
    } else {
#pragma unroll
      for (int i = 0; i < 12; i++) mbar_init(bar + 8 * (12 * warp - 24 + i), 1);
    }
    asm volatile("fence.mbarrier_init.release.cluster;" ::: "memory");
  }
  if (warp == 15 && elect_one()) {
#pragma unroll
    for (int i = 72; i < B_COUNT; i++) mbar_init(bar + 8 * i, bar_count(i));
    asm volatile("fence.mbarrier_init.release.cluster;" ::: "memory");
  }

  if (warp < 8) {
    bar_sync(0, NTHREADS);
    asm volatile("setmaxnreg.inc.sync.aligned.u32 %0;" ::"n"(R_CONS));
    const int cw = __shfl_sync(~0u, opaque_tid() >> 5, 0);
    const int wg = cw >> 2, w = cw & 3;
    if (tid == 0) TS(2);
    int rtp = 0;
#pragma unroll 1
    for (int layer = 0; layer < 2; layer++) {
      attn_phase(p, sb, layer, rb, hg, wg, w);
      uint32_t A0[68], A1[68];
      proj_phase(p, sb, layer, rb, hg, rtp, A0, A1);
      conv_phase(p, sb, layer, cta, A0, A1);
    }
    if (wg == 0) mbar_wait(bar + 8 * (B_TF + 1), 0);
    if (tid == 128) TS(8);
    final_tile(p, sb + (16 + wg) * PG, 256 * wg + 32 * (cta >> 4), 1024 + 64 * (cta & 15), 2 + wg);
    if (tid == 128) TS(9);
    if (tid == 128) LTS(1);
    if (tid == 0) LTE();
  } else if (warp < 12) {
    asm volatile("setmaxnreg.dec.sync.aligned.u32 %0;" ::"n"(R_HELP));
    const int ht = tid - 256;
    {
      unsigned ep0 = 0;
      if (ht == 0) ep0 = ld_relaxed(&g_cnt[C_CS * 32]);
      const bf16 dsk = p.dskip[cv_chan(cta, ht & 3)];
      const ModeIn in0 = load_modes(p, cv_chan(cta, ht >> 6), ht & 63), in1 = load_modes(p, cv_chan(cta, 2 + (ht >> 6)), ht & 63);
      if (ht < 48) sts128f(sb + SM_STG + ht * 16, 0.f, 0.f, 0.f, 1.f);
      bar_sync(0, NTHREADS);
      if (ht == 0) {
        sts32(sb + SM_EP, ep0);
        mbar_arrive(bar + 8 * B_EP);
      }
      if (ht >= 124) sts16(sb + SM_RED + 24 + 2 * (ht & 3), __bfloat16_as_ushort(dsk));
      kernel_gen(p, sb, cta, ht, in0, in1);
      if (ht < 48) sts128f(sb + SM_KGT + ht * 16, 0.f, 0.f, 0.f, 1.f);
      fence_async_smem();
      bar_sync(4, 128);
      if (ht == 0) mbar_arrive(bar + 8 * B_KG);
    }
#pragma unroll 1
    for (int layer = 0; layer < 2; layer++) {
      const int early = LPRE && layer;
      if (early) mbar_wait(bar + 8 * (B_DN + 13), 1);
      mbar_wait(bar + 8 * (early ? XGATE : B_PDONE), layer);
      expand_taps(sb, opaque_tid() - 256, early);
      mbar_arrive(bar + 8 * B_PE);
      TSW(0);
      mbar_wait(bar + 8 * B_PDONE, layer);
      expand_far(sb, opaque_tid() - 256);
      {
        const int i = opaque_tid() - 256;
        if (i < 32) sts128(sb + cv_u(i >> 3) + ((i >> 2) & 1) * CV_UH + (128 + (i & 3)) * 16, make_uint4(0, 0, 0, 0));
        mbar_wait(bar + 8 * B_RC, layer);
        mbar_wait(bar + 8 * B_GB, layer);
        TSW(13);
        conv_prep<0>(sb, layer, cta, i);
        mbar_arrive(bar + 8 * B_U);
      }
      mbar_wait(bar + 8 * (B_PDONE + 1), layer);
      bar_sync(4, 128);
#pragma unroll 1
      for (int lc = 0; lc < 4; lc += 2) {
        conv_sums(sb, lc, opaque_tid() - 256);
        TSW(1 + lc);
      }
      fence_async_smem();
      mbar_arrive(bar + 8 * B_S);
      mbar_wait(bar + 8 * (B_GB + 1), layer);
      conv_prep<1>(sb, layer, cta, opaque_tid() - 256);
      mbar_arrive(bar + 8 * B_U1);
      TSW(4);
      if (layer == 0) {
        const int c = __shfl_sync(~0u, (opaque_tid() >> 5) & 3, 0);
        int phase = 0;
#pragma unroll 1
        for (int k = 0; k < 3; k++) {
          const int page = (k ? 4 + 4 * k : 0) + c, b = B_XR + 4 * (k & 1) + c;
          const uint32_t a = sb + page * PG + lane * 128 + (lane & 7) * 16 + (lane >> 3) * 4;
          int it = k == 2 ? phase : 0;
#pragma unroll 1
          for (; it < MAX_RETRY; it++) {
            mbar_wait(bar + 8 * b, it & 1);
            const uint32_t v0 = lds32(a), v1 = lds32(a + 4096);
            if (__all_sync(~0u, v0 != UNSET && v1 != UNSET)) break;
            if (elect_one()) { fence_async_smem(); ld_x1(page >> 3, page & 7, b); }
            __syncwarp();
            RETRY(3);
          }
          if (k == 0) phase = it + 1;
          if (lane == 0) mbar_arrive(bar + 8 * (B_XF + page));
        }
      }
    }
    mbar_wait(bar + 8 * B_TF, 0);
#pragma unroll 1
    for (int k = 0; k < 2; k++) final_tile(p, sb + 18 * PG + k * 4096, 256 * k + 32 * (cta >> 4), 64 * (cta & 15), 4);
    if (ht == 0) LTE();
  } else {
    asm volatile("setmaxnreg.dec.sync.aligned.u32 %0;" ::"n"(R_AGENT));
    bar_sync(0, NTHREADS);
    auto done = [&](int half, int c, int layer) { mbar_wait(bar + 8 * (B_DN + 8 * half + c), layer); };
    auto publish = [&](int layer, int k) {
      mbar_wait(bar + 8 * (B_PUB + k), layer);
      red_relaxed(&g_cnt[(layer ? C_F + 8 * k + (cta >> 4) : C_C + k) * 32]);
      if (!layer && k == 0) red_release(&g_cnt[(C_C + 3) * 32]);
      TS(16 + layer * 56 + 40 + 7 + k);
    };
    if (warp == 12) {
      if (elect_one()) {
#pragma unroll 1
        for (int layer = 0; layer < 2; layer++) {
          auto ld_xe = [&](int c) {
            const uint32_t b = bar + 8 * (B_XF + c);
            mbar_expect(b, PG);
            if (layer == 0) tma_ld(sb + x_page(0, c) * PG, &p.mapX, c * 64, rb * 64, b);
            else tma_ld(sb + x_page(0, c) * PG, &p.mapXT, rb * 64, DM + c * 64, b);
          };
          if (layer == 0) {
            ld_x0(0, 2); ld_w(2); ld_x0(1, 2);
            if (hg >= 3) {
              mbar_expect(bar + 8 * B_SC, PG);
              tma_ld(sb + P_R * PG, &p.mapX, hg * 64, rb * 64, bar + 8 * B_SC);
            }
            if (rb < 4) tma_prefetch3(&p.mapW3, hg * 64, (4 + rb) * 64, 0);
            ld_x0(0, 3); ld_w(3); ld_x0(1, 3); ld_x0(0, 4); ld_x0(1, 4);
            done(0, 0, 0); done(1, 0, 0);
            ld_w(4);
            ld_x0(1, 5); ld_x0(1, 6); ld_x0(1, 7);
            done(0, 1, 0); done(1, 1, 0);
            ld_w(5);
            if (rb < 8) tma_prefetch5(&p.mapWo, hg * 64, rb * 2);
            done(0, 2, 0);
            fence_async_smem();
            ld_xe(5); ld_xe(6); ld_xe(7);
          } else {
            mbar_wait(bar + 8 * B_PDONE, 0);
            mbar_wait(bar + 8 * (B_PDONE + 1), 0);
            mbar_wait(bar + 8 * (WPRE == 1 ? B_U : B_GB + 1), 0);
            ld_w(0); ld_w(1);
            mbar_wait(bar + 8 * B_U1, 0);
            fence_async_smem();
            ld_w(2);
            mbar_wait(bar + 8 * (B_PUB + 2), 0);
            fence_async_smem();
            ld_w(3);
            spin_until(&g_cnt[(C_C + 3) * 32], ((lds32(sb + SM_EP) / NCTA) + 1) * NCTA);
            fence_async_global();
            if (hg >= 3) {
              mbar_expect(bar + 8 * B_SC, PG);
              tma_ld(sb + P_R * PG, &p.mapXT, rb * 64, DM + hg * 64, bar + 8 * B_SC);
            }
            ld_xe(4);
            done(0, 2, 1);
            fence_async_smem();
            ld_xe(5); ld_xe(6); ld_xe(7);
            done(1, 0, 1);
            ld_w(4);
            done(1, 1, 1);
            ld_w(5);
          }
          done(1, 2, layer);
          fence_async_smem();
          ld_w(6); ld_w(7);
          auto ld_res = [&](int half) {
            const uint32_t b = bar + 8 * (B_RF + half);
            mbar_expect(b, PG);
            if (layer == 0) tma_ld(sb + (half ? 2 : P_R) * PG, &p.mapX, hg * 64, (16 * half + rb) * 64, b);
            else tma_ld(sb + (half ? 2 : P_R) * PG, &p.mapXT, (16 * half + rb) * 64, DM + hg * 64, b);
          };
          done(0, 4, layer); done(1, 3, layer);
          fence_async_smem();
          mbar_expect(bar + 8 * B_WOF, 8 * PG);
#pragma unroll 1
          for (int c = 0; c < 8; c++) {
            if (c == 5) { ld_res(0); done(1, 4, layer); }
            tma_ld5(sb + wo_page(c) * PG, &p.mapWo, hg * 64, c * 2, bar + 8 * B_WOF);
          }
          done(0, 7, layer);
          fence_async_global();
          ld_res(1);
          if (layer) mbar_wait(bar + 8 * B_RS, 0);
          fence_async_global();
#pragma unroll
          for (int half = 0; half < 2; half++) {
            float* stats = g_stats + (layer * 32 + 16 * half + rb) * 192;
            unsigned* cnt = &g_cnt[(C_G + 2 * layer + half) * 32];
            mbar_wait(bar + 8 * (B_STG + half), layer);
            tma_st(&p.mapXT, (16 * half + rb) * 64, 2 * layer * DM + hg * 64, sb + (P_R + half) * PG);
            bulk_red_add_f32(stats, sb + (half ? SM_KGT : SM_STG), 768);
            bulk_commit();
            red_relaxed(cnt);
            if (half == 0) mbar_arrive(bar + 8 * B_PG);
            bulk_wait_read();
            mbar_arrive(bar + 8 * (B_PST + half));
          }
        }
      }
    } else if (warp == 13) {
      mbar_wait(bar + 8 * B_EP, 0);
      const unsigned e1 = (lds32(sb + SM_EP) / NCTA) + 1;
      auto ld_o = [&](int layer) {
#pragma unroll 1
        for (int half = 0; half < 2; half++) {
          done(1, 7, layer);
          mbar_wait(bar + 8 * B_OST, layer);
          if (half) mbar_wait(bar + 8 * (B_OST + 1), layer);
          fence_async_smem();
#pragma unroll
          for (int c = 0; c < 4; c++) mbar_expect(bar + 8 * (B_OF + 4 * half + c), 2 * PG);
          spin_hint(&g_cnt[(C_O + layer * 32 + 16 * half + rb) * 32], e1 * 32);
#pragma unroll
          for (int c = 0; c < 4; c++) {
            if (LPRE && c == 2 && half && layer) { mbar_wait(bar + 8 * B_AL, 0); fence_async_smem(); }
            bulk_ld(sb + o_page(half, c) * PG, g_O + ((layer * 32 + 16 * half + rb) * 4 + c) * PG, 2 * PG, bar + 8 * (B_OF + 4 * half + c));
          }
        }
      };
      if (elect_one()) {
        mbar_wait(bar + 8 * (B_WF + 2), 0);
        asm volatile("prefetch.tensormap [%0];" ::"l"(&p.mapXT) : "memory");
        asm volatile("prefetch.tensormap [%0];" ::"l"(&p.mapWo) : "memory");
        spin_until(&g_cnt[C_Z * 32], e1 * NCTA);
        mbar_arrive(bar + 8 * B_ZF);
        TS(3);
        ld_o(0);
#pragma unroll 1
        for (int k = 0; k < 3; k++) {
          mbar_wait(bar + 8 * (B_PUB + k), 0);
          if (k == 2) {
#pragma unroll 1
            for (int c = 0; c < 4; c++) mbar_wait(bar + 8 * (B_XF + c), 1);
          }
          fence_async_smem();
          spin_hint(&g_cnt[(C_C + k) * 32], e1 * NCTA);
          TS(10 + k);
#pragma unroll
          for (int c = 0; c < 4; c++) ld_x1(k != 0, (k & 2) * 2 + c, B_XR + 4 * (k & 1) + c);
        }
        ld_o(1);
#pragma unroll 1
        for (int k = 0; k < 2; k++) {
          mbar_wait(bar + 8 * (B_PUB + k), 1);
          spin_hint(&g_cnt[(C_F + 8 * k + (cta >> 4)) * 32], e1 * 16);
          mbar_arrive(bar + 8 * (B_TF + k));
        }
      }
    } else if (warp == 14) {
      mbar_wait(bar + 8 * B_EP, 0);
      const unsigned e1 = (lds32(sb + SM_EP) / NCTA) + 1;
      done(0, 1, 0);
      {
        const uint2* cp = g_colsum + (hg * 192 + lane);
        uint2 v[6];
        bool ok;
        int it = 0;
        do {
          ok = true;
#pragma unroll
          for (int i = 0; i < 6; i++) {
            asm volatile("ld.relaxed.gpu.global.v2.u32 {%0,%1}, [%2];" : "=r"(v[i].x), "=r"(v[i].y) : "l"(cp + 32 * i) : "memory");
            ok = ok && v[i].y == e1;
          }
          if (++it > (1 << 22)) __trap();
        } while (!__all_sync(~0u, ok));
#pragma unroll
        for (int i = 0; i < 6; i++) sts32f(sb + SM_CS + 4 * (lane + 32 * i), __uint_as_float(v[i].x));
      }
      __syncwarp();
      if (elect_one()) {
        mbar_wait(bar + 8 * B_ZF, 0);
        mbar_arrive(bar + 8 * B_LN);
        red_relaxed(&g_cnt[C_CS * 32]);
        TS(13);
#pragma unroll 1
        for (int i = 0; i < 4; i++) {
          const int layer = i >> 1;
          mbar_wait(bar + 8 * (B_PST + (i & 1)), layer);
          const uint32_t b = bar + 8 * (B_GB + 1);
          const bf16* xin = g_xT + ((size_t)2 * layer * DM + 2 * cta) * LSEQ + 1024;
          if (i & 1) {
            fence_async_smem();
            mbar_expect(b, 12288 + PG);
          }
          spin_hint(&g_cnt[(C_G + i) * 32], e1 * NCTA);
          if (i & 1) {
            bulk_ld(sb + CV_ST, g_stats + (layer * 32 + 16) * 192, 12288, b);
#pragma unroll
            for (int lc = 0; lc < 4; lc++) bulk_ld(sb + cv_x(1, lc), xin + cv_chan(0, lc) * LSEQ, 2048, b);
            TS(14 + layer);
            publish(layer, 1);
          } else {
            mbar_arrive(bar + 8 * B_GB);
          }
        }
      }
    } else {
      const uint4 u = make_uint4(UNSET, UNSET, UNSET, UNSET);
      if (lane < 24) stg128((uint4*)g_stats + cta * 24 + lane, make_uint4(0, 0, 0, 0));
      if (lane < 16) stg128(g_rows + LSEQ + cta * 16 + lane, make_uint4(0, 0, 0, 0));
#pragma unroll 4
      for (int i = 0; i < 16; i++) stg128(g_halo + cta * 512 + 32 * i + lane, u);
#pragma unroll 4
      for (int i = 0; i < 16; i++) stg128(((i & 8) ? (uint4*)g_xT : (uint4*)g_O) + cta * 1024 + (i & 7) * 128 + (lane >> 1) * 8 + (lane & 1), u);
      __syncwarp();
      if (elect_one()) red_release(&g_cnt[C_Z * 32]);
      __syncwarp();
#pragma unroll 1
      for (int layer = 0; layer < 2; layer++) {
        auto reset_done = [&](int s) {
          spin_until(&g_cnt[(C_R + s) * 32], (lds32(sb + SM_EP) / NCTA) * 4 + 4);
          mbar_arrive(bar + 8 * (s == 1 ? B_LN : s == 2 ? B_RS : B_RC));
          if (s) TS(16 + 40 + 9 + s);
        };
        if (layer && elect_one()) reset_done(1);
        __syncwarp();
#pragma unroll 1
        for (int half = 0; half < 2; half++) {
          done(half, 2, layer);
          const uint4* src = g_rows + (layer * LSEQ + (16 * half + rb) * 64 + (opaque_tid() & 31));
          uint4 a, b;
          int it = 0;
          do {
            a = ld_tagged(src); b = ld_tagged(src + 32);
          } while (!__all_sync(~0u, (a.z | a.w) == __float_as_uint(8.f) && (b.z | b.w) == __float_as_uint(8.f)) && ++it < (1 << 20));
          float m0 = __uint_as_float(a.x) * (1.f / DM), m1 = __uint_as_float(b.x) * (1.f / DM);
          float r0 = rsqrt_approx(fmaxf(__uint_as_float(a.y) * (1.f / DM) - m0 * m0, 0.f) + 1e-5f);
          float r1 = rsqrt_approx(fmaxf(__uint_as_float(b.y) * (1.f / DM) - m1 * m1, 0.f) + 1e-5f);
          if (half) done(0, 7, layer);
          const uint32_t dst = sb + ln_off(half) + ((lane >> 4) * 8 + (lane & 7)) * 16 + (lane & 8);
          asm volatile("st.shared.v2.f32 [%0], {%1,%2};" ::"r"(dst), "f"(m0), "f"(r0) : "memory");
          asm volatile("st.shared.v2.f32 [%0], {%1,%2};" ::"r"(dst + 256), "f"(m1), "f"(r1) : "memory");
          __syncwarp();
          if (elect_one()) { mbar_arrive(bar + 8 * (B_LN + half)); TS(16 + layer * 56 + 40 + 14 + half); }
        }
        if (layer && lane < 16) stg128(g_rows + cta * 16 + (opaque_tid() & 31), make_uint4(0, 0, 0, 0));
        if (elect_one()) {
          if (layer) reset_done(2);
          reset_done(3 * layer);
          publish(layer, 0);
          if (!layer) publish(layer, 2);
        }
        __syncwarp();
      }
    }
  }
}

typedef CUresult (*EncodeFn)(CUtensorMap*, CUtensorMapDataType, cuuint32_t, void*, const cuuint64_t*, const cuuint64_t*,
                             const cuuint32_t*, const cuuint32_t*, CUtensorMapInterleave, CUtensorMapSwizzle,
                             CUtensorMapL2promotion, CUtensorMapFloatOOBfill);

static void make_map(EncodeFn enc, CUtensorMap* m, void* ptr, uint64_t cols, uint64_t rows, uint32_t box_rows) {
  cuuint64_t dims[2] = {cols, rows};
  cuuint64_t strides[1] = {cols * 2};
  cuuint32_t box[2] = {64, box_rows};
  cuuint32_t es[2] = {1, 1};
  enc(m, CU_TENSOR_MAP_DATA_TYPE_BFLOAT16, 2, ptr, dims, strides, box, es, CU_TENSOR_MAP_INTERLEAVE_NONE,
      CU_TENSOR_MAP_SWIZZLE_128B, CU_TENSOR_MAP_L2_PROMOTION_L2_128B, CU_TENSOR_MAP_FLOAT_OOB_FILL_NONE);
}
static void make_map3(EncodeFn enc, CUtensorMap* m, void* ptr, uint64_t d0, uint64_t cols, uint64_t rows, uint64_t blk_stride,
                      uint64_t nblocks, uint32_t nblk) {
  cuuint64_t dims[3] = {d0, rows, nblocks};
  cuuint64_t strides[2] = {cols * 2, blk_stride * 2};
  cuuint32_t box[3] = {64, 64, nblk};
  cuuint32_t es[3] = {1, 1, 1};
  enc(m, CU_TENSOR_MAP_DATA_TYPE_BFLOAT16, 3, ptr, dims, strides, box, es, CU_TENSOR_MAP_INTERLEAVE_NONE,
      CU_TENSOR_MAP_SWIZZLE_128B, CU_TENSOR_MAP_L2_PROMOTION_L2_128B, CU_TENSOR_MAP_FLOAT_OOB_FILL_NONE);
}

extern "C" void kernel_launch(void* const* d_in, const int* in_sizes, int n_in, void* d_out, int out_size) {
  static Params prm;
  static void* cached[13] = {nullptr};
  static bool attr_done = false;
  static int grid = NCTA + 4;
  bool same = attr_done && cached[12] == d_out;
  for (int i = 0; i < 12 && same; i++) same = cached[i] == d_in[i];
  if (!same) {
    void* fn = nullptr;
    cudaDriverEntryPointQueryResult qr;
    cudaGetDriverEntryPoint("cuTensorMapEncodeTiled", &fn, cudaEnableDefault, &qr);
    EncodeFn enc = (EncodeFn)fn;
    void* pXT;
    cudaGetSymbolAddress(&pXT, g_xT);
    make_map(enc, &prm.mapX, d_in[0], DM, LSEQ, 64);
    make_map(enc, &prm.mapXT, pXT, LSEQ, 4 * DM, 64);
    {
      cuuint64_t dims[5] = {DM, 2, 4, 4, 16};
      cuuint64_t strides[4] = {DM * 2, 8 * DM * 2, 2 * DM * 2, 32 * DM * 2};
      cuuint32_t box[5] = {64, 2, 4, 4, 2};
      cuuint32_t es[5] = {1, 1, 1, 1, 1};
      enc(&prm.mapWo, CU_TENSOR_MAP_DATA_TYPE_BFLOAT16, 5, d_in[2], dims, strides, box, es, CU_TENSOR_MAP_INTERLEAVE_NONE,
          CU_TENSOR_MAP_SWIZZLE_128B, CU_TENSOR_MAP_L2_PROMOTION_L2_128B, CU_TENSOR_MAP_FLOAT_OOB_FILL_NONE);
    }
    make_map3(enc, &prm.mapW3, d_in[1], DM, 3 * DM, DM, DM, 3, 3);
    prm.out = (bf16*)d_out;
    prm.a_re = (const bf16*)d_in[4]; prm.a_im = (const bf16*)d_in[5];
    prm.b_re = (const bf16*)d_in[6]; prm.b_im = (const bf16*)d_in[7];
    prm.c_re = (const bf16*)d_in[8]; prm.c_im = (const bf16*)d_in[9];
    prm.log_dt = (const bf16*)d_in[10]; prm.dskip = (const bf16*)d_in[11];
    int dev = 0, sms = 0;
    cudaGetDevice(&dev);
    cudaDeviceGetAttribute(&sms, cudaDevAttrMultiProcessorCount, dev);
    grid = sms >= NCTA + 4 ? NCTA + 4 : NCTA + 5;
    cudaFuncSetAttribute(fused_kernel, cudaFuncAttributeMaxDynamicSharedMemorySize, SM_TOTAL);
    for (int i = 0; i < 12; i++) cached[i] = d_in[i];
    cached[12] = d_out;
    attr_done = true;
  }
  fused_kernel<<<grid, NTHREADS, SM_TOTAL>>>(prm);
}
```

```cpp
#include <cuda_runtime.h>
#include <cuda_bf16.h>
#include <cuda.h>
#include <stdint.h>

typedef __nv_bfloat16 bf16;

constexpr int LSEQ = 2048;
constexpr int DM = 512;
constexpr int NCTA = 128;
constexpr int NTHREADS = 512;
#define R_CONS 200
#define R_HELP 88
#define R_AGENT 24
#define TURN0 4
#define TURN1 4

constexpr int PG = 8192;
constexpr int P_R = 25;
__host__ __device__ constexpr int x_page(int half, int c) { return half ? 8 + c : c < 5 ? c : c - 5; }
__host__ __device__ constexpr int w_page(int c) { return (c & 3) < 3 ? 16 + 3 * (c & 3) : c < 4 ? 5 : 8; }
__host__ __device__ constexpr int wo_page(int c) { return c < 5 ? 3 + c : 11 + c; }
__host__ __device__ constexpr int o_page(int half, int pair) { return half ? (pair ? 25 - 2 * pair : 0) : 8 + 2 * pair; }
constexpr int SM_KGB = (P_R + 1) * PG;
constexpr int SM_KC = 27 * PG;
constexpr int KC_STRIDE = 648;
__host__ __device__ constexpr int kc_off(int lc) { return SM_KC + (lc & 1) * 2 * KC_STRIDE + (lc < 2 ? 3328 : 0); }
constexpr int SM_KGT = SM_KC + 3328 + 2592;
constexpr int SM_CS = SM_KGT + 2048;
constexpr int SM_RED = SM_CS + 768;
constexpr int SM_EP = SM_RED + 16;
constexpr int SM_STG = SM_RED + 32;
constexpr int SM_LN = SM_STG + 768;
__host__ __device__ constexpr int ln_off(int half) { return half ? PG + 4096 : SM_LN; }
constexpr int SM_BAR = SM_LN + 512;
constexpr int SM_TS = SM_BAR + 704;
constexpr int SM_TOTAL = SM_TS + 512;
static_assert(SM_TOTAL <= 232448 && SM_STG % 16 == 0 && SM_KGT % 16 == 0, "shared memory");

constexpr int CV_UH = 140 * 16;
__host__ __device__ constexpr int cv_u(int lc) { return (8 + 2 * lc) * PG; }
__host__ __device__ constexpr int cv_pe(int lc, int early) { return early ? 19 * PG + lc * 4480 : cv_u(lc) + 4480; }
__host__ __device__ constexpr int cv_pb1(int lc, int w) { return w ? cv_u(lc) + 8960 + (w - 1) * 2048 : 7 * PG + lc * 2048; }
__host__ __device__ constexpr int cv_fa(int lc) { return cv_pb1(lc, 1) + 128; }
__host__ __device__ constexpr int cv_dump(int lc) { return cv_u(lc) + 16256; }
__host__ __device__ constexpr int cv_pb0(int lc, int w) { return lc * PG + w * 2048; }
__host__ __device__ constexpr int cv_se(int lc) { return 5 * PG + lc * 4096; }
__host__ __device__ constexpr int cv_so(int lc) { return cv_se(lc) + 2048; }
__host__ __device__ constexpr int cv_x(int half, int lc) { return (P_R + half) * PG + lc * 2048; }
constexpr int CV_ST = 22 * PG;
__host__ __device__ constexpr int cv_chan(int cta, int lc) { return 2 * cta + (lc & 1) + 256 * (lc >> 1); }

enum {
  B_XF = 0,
  B_WF = 16,
  B_OF = 24,
  B_DN = 32,
  B_PG = 46,
  B_XR = 48,
  B_RF = 56,
  B_PST = 58,
  B_GB = 60,
  B_TF = 62,
  B_RT = 64,
  B_RS = 66,
  B_RC = 67,
  B_WOF = 68,
  B_ZF = 69,
  B_EP = 70,
  B_KG = 71,
  B_SC = 37,
  B_LN = 72,
  B_END = 38,
  B_STG = 74,
  B_OST = 76,
  B_PDONE = 78,
  B_PE = 80,
  B_U = 81,
  B_U1 = 82,
  B_PUB = 83,
  B_S = 86,
  B_AL = 87,
  B_COUNT = 88
};

enum {
  C_CS = 0,
  C_G = 1,
  C_C = 5,
  C_O = 21,
  C_Z = 85,
  C_R = 86,
  C_F = 90,
  C_COUNT = 106
};

__device__ unsigned g_cnt[C_COUNT * 32];
__device__ __align__(1024) bf16 g_O[2 * LSEQ * DM];
__device__ __align__(1024) bf16 g_xT[4 * DM * LSEQ];
__device__ __align__(1024) float g_stats[2 * 32 * 192];
__device__ __align__(1024) uint2 g_colsum[3 * DM];
__device__ __align__(1024) uint4 g_halo[32 * 8 * 256];
__device__ __align__(1024) uint4 g_rows[2 * LSEQ];
#define TS(i) do { } while (0)
#define TSW(k) do { if ((threadIdx.x & 127) == 0) TS(16 + layer * 56 + (threadIdx.x >> 7) * 20 + (k)); } while (0)
#define TSG(k) do { } while (0)

#define RETRY(i) do { } while (0)
#define LTS(i) do { } while (0)
#define LTE() do { } while (0)

struct Params {
  CUtensorMap mapX, mapW3, mapXT, mapWo;
  bf16* out;
  const bf16 *a_re, *a_im, *b_re, *b_im, *c_re, *c_im, *log_dt, *dskip;
};

__device__ __forceinline__ uint32_t s32(const void* p) { return (uint32_t)__cvta_generic_to_shared(p); }
__device__ __forceinline__ void mbar_init(uint32_t b, int c) { asm volatile("mbarrier.init.shared::cta.b64 [%0], %1;" ::"r"(b), "r"(c) : "memory"); }
__device__ __forceinline__ void mbar_expect(uint32_t b, int bytes) { asm volatile("mbarrier.arrive.expect_tx.shared::cta.b64 _, [%0], %1;" ::"r"(b), "r"(bytes) : "memory"); }
__device__ __forceinline__ void mbar_arrive(uint32_t b) { asm volatile("mbarrier.arrive.shared::cta.b64 _, [%0];" ::"r"(b) : "memory"); }
__device__ __forceinline__ void mbar_wait(uint32_t b, int parity) {
  asm volatile("{\n.reg .pred p;\nWAIT_LOOP:\nmbarrier.try_wait.parity.shared::cta.b64 p, [%0], %1;\n@p bra WAIT_DONE;\nbra WAIT_LOOP;\nWAIT_DONE:\n}" ::"r"(b), "r"(parity) : "memory");
}
__device__ __forceinline__ bool mbar_test(uint32_t b, int parity) {
  uint32_t ok;
  asm volatile("{\n.reg .pred p;\nmbarrier.test_wait.parity.shared::cta.b64 p, [%1], %2;\nselp.u32 %0, 1, 0, p;\n}" : "=r"(ok) : "r"(b), "r"(parity) : "memory");
  return ok != 0;
}
__device__ __forceinline__ int opaque_tid() { int v; asm volatile("mov.u32 %0, %%tid.x;" : "=r"(v)); return v; }
__device__ __forceinline__ bool elect_one() {
  uint32_t r;
  asm volatile("{\n.reg .pred p;\nelect.sync _|p, 0xffffffff;\nselp.u32 %0, 1, 0, p;\n}" : "=r"(r));
  return r != 0;
}
__device__ __forceinline__ void tma_ld(uint32_t dst, const CUtensorMap* m, int c0, int c1, uint32_t bar) {
  asm volatile("cp.async.bulk.tensor.2d.shared::cluster.global.mbarrier::complete_tx::bytes [%0], [%1, {%3, %4}], [%2];"
               ::"r"(dst), "l"(m), "r"(bar), "r"(c0), "r"(c1) : "memory");
}
__device__ __forceinline__ void tma_ld3(uint32_t dst, const CUtensorMap* m, int c0, int c1, int c2, uint32_t bar) {
  asm volatile("cp.async.bulk.tensor.3d.shared::cluster.global.mbarrier::complete_tx::bytes [%0], [%1, {%3, %4, %5}], [%2];"
               ::"r"(dst), "l"(m), "r"(bar), "r"(c0), "r"(c1), "r"(c2) : "memory");
}
__device__ __forceinline__ void tma_ld5(uint32_t dst, const CUtensorMap* m, int c0, int c4, uint32_t bar) {
  asm volatile("cp.async.bulk.tensor.5d.shared::cluster.global.mbarrier::complete_tx::bytes [%0], [%1, {%3, 0, 0, 0, %4}], [%2];"
               ::"r"(dst), "l"(m), "r"(bar), "r"(c0), "r"(c4) : "memory");
}
__device__ __forceinline__ void tma_prefetch5(const CUtensorMap* m, int c0, int c4) {
  asm volatile("cp.async.bulk.prefetch.tensor.5d.L2.global.tile [%0, {%1, 0, 0, 0, %2}];" ::"l"(m), "r"(c0), "r"(c4) : "memory");
}
__device__ __forceinline__ void tma_prefetch2(const CUtensorMap* m, int c0, int c1) {
  asm volatile("cp.async.bulk.prefetch.tensor.2d.L2.global.tile [%0, {%1, %2}];" ::"l"(m), "r"(c0), "r"(c1) : "memory");
}
__device__ __forceinline__ void tma_prefetch3(const CUtensorMap* m, int c0, int c1, int c2) {
  asm volatile("cp.async.bulk.prefetch.tensor.3d.L2.global.tile [%0, {%1, %2, %3}];" ::"l"(m), "r"(c0), "r"(c1), "r"(c2) : "memory");
}
__device__ __forceinline__ void tma_st(const CUtensorMap* m, int c0, int c1, uint32_t src) {
  asm volatile("cp.async.bulk.tensor.2d.global.shared::cta.bulk_group [%0, {%2, %3}], [%1];" ::"l"(m), "r"(src), "r"(c0), "r"(c1) : "memory");
}
__device__ __forceinline__ void bulk_ld(uint32_t dst, const void* src, int bytes, uint32_t bar) {
  asm volatile("cp.async.bulk.shared::cluster.global.mbarrier::complete_tx::bytes [%0], [%1], %2, [%3];" ::"r"(dst), "l"(src), "r"(bytes), "r"(bar) : "memory");
}
__device__ __forceinline__ void bulk_st(void* dst, uint32_t src, int bytes) {
  asm volatile("cp.async.bulk.global.shared::cta.bulk_group [%0], [%1], %2;" ::"l"(dst), "r"(src), "r"(bytes) : "memory");
}
__device__ __forceinline__ void bulk_red_add_f32(void* dst, uint32_t src, int bytes) {
  asm volatile("cp.reduce.async.bulk.global.shared::cta.bulk_group.add.f32 [%0], [%1], %2;" ::"l"(dst), "r"(src), "r"(bytes) : "memory");
}
__device__ __forceinline__ void bulk_commit() { asm volatile("cp.async.bulk.commit_group;" ::: "memory"); }
__device__ __forceinline__ void bulk_wait_all() { asm volatile("cp.async.bulk.wait_group 0;" ::: "memory"); }
__device__ __forceinline__ void fence_async_smem() { asm volatile("fence.proxy.async.shared::cta;" ::: "memory"); }
__device__ __forceinline__ void fence_async_global() { asm volatile("fence.proxy.async.global;" ::: "memory"); }
__device__ __forceinline__ void bar_sync(int id, int n) { asm volatile("bar.sync %0, %1;" ::"r"(id), "r"(n) : "memory"); }
__device__ __forceinline__ void bar_arrive(int id, int n) { asm volatile("bar.arrive %0, %1;" ::"r"(id), "r"(n) : "memory"); }
__device__ __forceinline__ bool bar_or(int id, int n, bool v) {
  uint32_t r;
  asm volatile("{\n.reg .pred p, q;\nsetp.ne.u32 q, %3, 0;\nbar.red.or.pred p, %1, %2, q;\nselp.u32 %0, 1, 0, p;\n}" : "=r"(r) : "r"(id), "r"(n), "r"((uint32_t)v) : "memory");
  return r != 0;
}
__device__ __forceinline__ void bulk_wait_read() { asm volatile("cp.async.bulk.wait_group.read 0;" ::: "memory"); }
__device__ __forceinline__ void stg128(void* p, uint4 v) { asm volatile("st.relaxed.gpu.global.v4.u32 [%0], {%1,%2,%3,%4};" ::"l"(p), "r"(v.x), "r"(v.y), "r"(v.z), "r"(v.w) : "memory"); }
constexpr uint32_t UNSET = 0xffffffffu;
constexpr int MAX_RETRY = 1 << 16;
__device__ __forceinline__ void wg_fence() { asm volatile("wgmma.fence.sync.aligned;" ::: "memory"); }
__device__ __forceinline__ void wg_commit() { asm volatile("wgmma.commit_group.sync.aligned;" ::: "memory"); }
template <int N> __device__ __forceinline__ void wg_wait() { asm volatile("wgmma.wait_group.sync.aligned %0;" ::"n"(N) : "memory"); }
__device__ __forceinline__ uint64_t mkdesc(uint32_t addr, uint32_t lbo, uint32_t sbo, int sw) {
  return (uint64_t)((addr & 0x3FFFF) >> 4) | ((uint64_t)(lbo >> 4) << 16) | ((uint64_t)(sbo >> 4) << 32) | ((uint64_t)sw << 62);
}
__device__ __forceinline__ void ldsm4(uint32_t* r, uint32_t a) {
  asm volatile("ldmatrix.sync.aligned.m8n8.x4.shared.b16 {%0,%1,%2,%3}, [%4];" : "=r"(r[0]), "=r"(r[1]), "=r"(r[2]), "=r"(r[3]) : "r"(a) : "memory");
}
__device__ __forceinline__ void ldsm4t(uint32_t* r, uint32_t a) {
  asm volatile("ldmatrix.sync.aligned.m8n8.x4.trans.shared.b16 {%0,%1,%2,%3}, [%4];" : "=r"(r[0]), "=r"(r[1]), "=r"(r[2]), "=r"(r[3]) : "r"(a) : "memory");
}
__device__ __forceinline__ void stsm4(uint32_t a, uint32_t r0, uint32_t r1, uint32_t r2, uint32_t r3) {
  asm volatile("stmatrix.sync.aligned.m8n8.x4.shared.b16 [%0], {%1,%2,%3,%4};" ::"r"(a), "r"(r0), "r"(r1), "r"(r2), "r"(r3) : "memory");
}
__device__ __forceinline__ void stsm4t(uint32_t a, uint32_t r0, uint32_t r1, uint32_t r2, uint32_t r3) {
  asm volatile("stmatrix.sync.aligned.m8n8.x4.trans.shared.b16 [%0], {%1,%2,%3,%4};" ::"r"(a), "r"(r0), "r"(r1), "r"(r2), "r"(r3) : "memory");
}
__device__ __forceinline__ uint32_t movm_t(uint32_t a) { uint32_t r; asm volatile("movmatrix.sync.aligned.m8n8.trans.b16 %0, %1;" : "=r"(r) : "r"(a)); return r; }
__device__ __forceinline__ uint32_t lds32(uint32_t a) { uint32_t v; asm volatile("ld.shared.b32 %0, [%1];" : "=r"(v) : "r"(a) : "memory"); return v; }
__device__ __forceinline__ float2 lds64f(uint32_t a) { float2 v; asm volatile("ld.shared.v2.f32 {%0,%1}, [%2];" : "=f"(v.x), "=f"(v.y) : "r"(a) : "memory"); return v; }
__device__ __forceinline__ float4 lds128f(uint32_t a) { float4 v; asm volatile("ld.shared.v4.f32 {%0,%1,%2,%3}, [%4];" : "=f"(v.x), "=f"(v.y), "=f"(v.z), "=f"(v.w) : "r"(a) : "memory"); return v; }
__device__ __forceinline__ uint4 lds128(uint32_t a) { uint4 v; asm volatile("ld.shared.v4.b32 {%0,%1,%2,%3}, [%4];" : "=r"(v.x), "=r"(v.y), "=r"(v.z), "=r"(v.w) : "r"(a) : "memory"); return v; }
__device__ __forceinline__ void sts128(uint32_t a, uint4 v) { asm volatile("st.shared.v4.b32 [%0], {%1,%2,%3,%4};" ::"r"(a), "r"(v.x), "r"(v.y), "r"(v.z), "r"(v.w) : "memory"); }
__device__ __forceinline__ void sts128f(uint32_t a, float x, float y, float z, float w) { asm volatile("st.shared.v4.f32 [%0], {%1,%2,%3,%4};" ::"r"(a), "f"(x), "f"(y), "f"(z), "f"(w) : "memory"); }
__device__ __forceinline__ void sts32f(uint32_t a, float v) { asm volatile("st.shared.f32 [%0], %1;" ::"r"(a), "f"(v) : "memory"); }
__device__ __forceinline__ void sts16(uint32_t a, uint16_t v) { asm volatile("st.shared.u16 [%0], %1;" ::"r"(a), "h"(v) : "memory"); }
__device__ __forceinline__ uint32_t lds16(uint32_t a) { uint16_t v; asm volatile("ld.shared.u16 %0, [%1];" : "=h"(v) : "r"(a) : "memory"); return v; }
__device__ __forceinline__ uint32_t packbf(float lo, float hi) { uint32_t r; asm("cvt.rn.bf16x2.f32 %0, %1, %2;" : "=r"(r) : "f"(hi), "f"(lo)); return r; }
__device__ __forceinline__ float bf_lo(uint32_t v) { return __uint_as_float(v << 16); }
__device__ __forceinline__ float bf_hi(uint32_t v) { return __uint_as_float(v & 0xffff0000u); }
__device__ __forceinline__ float ex2(float x) { float r; asm("ex2.approx.ftz.f32 %0, %1;" : "=f"(r) : "f"(x)); return r; }
__device__ __forceinline__ float rsqrt_approx(float x) { float r; asm("rsqrt.approx.ftz.f32 %0, %1;" : "=f"(r) : "f"(x)); return r; }
__device__ __forceinline__ float rcp_approx(float x) { float r; asm("rcp.approx.ftz.f32 %0, %1;" : "=f"(r) : "f"(x)); return r; }
__device__ __forceinline__ void mma_bf16(float* d, const uint32_t* a, uint32_t b0, uint32_t b1) {
  asm("mma.sync.aligned.m16n8k16.row.col.f32.bf16.bf16.f32 {%0,%1,%2,%3}, {%4,%5,%6,%7}, {%8,%9}, {%0,%1,%2,%3};"
               : "+f"(d[0]), "+f"(d[1]), "+f"(d[2]), "+f"(d[3]) : "r"(a[0]), "r"(a[1]), "r"(a[2]), "r"(a[3]), "r"(b0), "r"(b1));
}
__device__ __forceinline__ void mma_tf32(float* d, float a0, float a1, float a2, float a3, float b0, float b1) {
  asm("mma.sync.aligned.m16n8k8.row.col.f32.tf32.tf32.f32 {%0,%1,%2,%3}, {%4,%5,%6,%7}, {%8,%9}, {%0,%1,%2,%3};"
               : "+f"(d[0]), "+f"(d[1]), "+f"(d[2]), "+f"(d[3])
               : "r"(__float_as_uint(a0)), "r"(__float_as_uint(a1)), "r"(__float_as_uint(a2)), "r"(__float_as_uint(a3)),
                 "r"(__float_as_uint(b0)), "r"(__float_as_uint(b1)));
}
__device__ __forceinline__ void red_release(unsigned* p) { asm volatile("red.release.gpu.global.add.u32 [%0], 1;" ::"l"(p) : "memory"); }
__device__ __forceinline__ void red_relaxed(unsigned* p) { asm volatile("red.relaxed.gpu.global.add.u32 [%0], 1;" ::"l"(p) : "memory"); }
__device__ __forceinline__ unsigned ld_relaxed(const unsigned* p) { unsigned v; asm volatile("ld.relaxed.gpu.global.u32 %0, [%1];" : "=r"(v) : "l"(p) : "memory"); return v; }
__device__ __forceinline__ void spin_until(const unsigned* p, unsigned target) {
  int it = 0;
  while ((int)(ld_relaxed(p) - target) < 0) {
    if (++it > (1 << 23)) __trap();
  }
}
__device__ __forceinline__ void spin_hint(const unsigned* p, unsigned target) {
  spin_until(p, target);
}
__device__ __forceinline__ uint4 ldcg128(const void* p) { uint4 v; asm volatile("ld.global.cg.v4.b32 {%0,%1,%2,%3}, [%4];" : "=r"(v.x), "=r"(v.y), "=r"(v.z), "=r"(v.w) : "l"(p) : "memory"); return v; }
__device__ __forceinline__ uint4 ld_tagged(const uint4* p) { uint4 v; asm volatile("ld.relaxed.gpu.global.v4.u32 {%0,%1,%2,%3}, [%4];" : "=r"(v.x), "=r"(v.y), "=r"(v.z), "=r"(v.w) : "l"(p) : "memory"); return v; }
__device__ __forceinline__ void st_tagged(uint4* p, uint32_t a, uint32_t b, uint32_t tag) { asm volatile("st.relaxed.gpu.global.v4.u32 [%0], {%1,%2,%3,%2};" ::"l"(p), "r"(a), "r"(tag), "r"(b) : "memory"); }
__device__ __forceinline__ void st_tagged3(uint4* p, uint32_t a, uint32_t b, uint32_t c, uint32_t tag) { asm volatile("st.relaxed.gpu.global.v4.u32 [%0], {%1,%2,%3,%4};" ::"l"(p), "r"(a), "r"(b), "r"(c), "r"(tag) : "memory"); }
__device__ __forceinline__ uint4 poll_tagged(const uint4* p, uint32_t tag) {
  uint4 v = ld_tagged(p);
  int it = 0;
  while (v.y != tag || v.w != tag) {
    if (++it > (1 << 22)) __trap();
    v = ld_tagged(p);
  }
  return v;
}
__device__ __forceinline__ uint32_t hadd2(uint32_t a, uint32_t b) { uint32_t r; asm("add.rn.bf16x2 %0, %1, %2;" : "=r"(r) : "r"(a), "r"(b)); return r; }
__device__ __forceinline__ uint32_t hmul2(uint32_t a, uint32_t b) { uint32_t r; asm("mul.rn.bf16x2 %0, %1, %2;" : "=r"(r) : "r"(a), "r"(b)); return r; }

__device__ __forceinline__ uint32_t hfma2(uint32_t a, uint32_t b, uint32_t c) { uint32_t r; asm("fma.rn.bf16x2 %0, %1, %2, %3;" : "=r"(r) : "r"(a), "r"(b), "r"(c)); return r; }
__device__ __forceinline__ void sts32(uint32_t a, uint32_t v) { asm volatile("st.shared.u32 [%0], %1;" ::"r"(a), "r"(v) : "memory"); }

template <int N> __device__ __forceinline__ void acc_fence(float* a) {
#pragma unroll
  for (int i = 0; i < N; i++) asm volatile("" : "+f"(a[i]) :: "memory");
}

template<int N,int TB> __device__ __forceinline__ void wgmma_rs(float* d, const uint32_t* a, uint64_t db, int sd);
template<int N,int TA,int TB> __device__ __forceinline__ void wgmma_ss(float* d, uint64_t da, uint64_t db, int sd);
template<> __device__ __forceinline__ void wgmma_rs<64,0>(float* d, const uint32_t* a, uint64_t db, int sd) {
  asm volatile("{\n.reg .pred p;\nsetp.ne.b32 p, %37, 0;\nwgmma.mma_async.sync.aligned.m64n64k16.f32.bf16.bf16 {%0,%1,%2,%3,%4,%5,%6,%7,%8,%9,%10,%11,%12,%13,%14,%15,%16,%17,%18,%19,%20,%21,%22,%23,%24,%25,%26,%27,%28,%29,%30,%31}, {%32,%33,%34,%35}, %36, p, 1, 1, 0;\n}\n"
   : "+f"(d[0]),"+f"(d[1]),"+f"(d[2]),"+f"(d[3]),"+f"(d[4]),"+f"(d[5]),"+f"(d[6]),"+f"(d[7]),"+f"(d[8]),"+f"(d[9]),"+f"(d[10]),"+f"(d[11]),"+f"(d[12]),"+f"(d[13]),"+f"(d[14]),"+f"(d[15]),"+f"(d[16]),"+f"(d[17]),"+f"(d[18]),"+f"(d[19]),"+f"(d[20]),"+f"(d[21]),"+f"(d[22]),"+f"(d[23]),"+f"(d[24]),"+f"(d[25]),"+f"(d[26]),"+f"(d[27]),"+f"(d[28]),"+f"(d[29]),"+f"(d[30]),"+f"(d[31])
   : "r"(a[0]), "r"(a[1]), "r"(a[2]), "r"(a[3]), "l"(db), "r"(sd));
}
template<> __device__ __forceinline__ void wgmma_rs<56,0>(float* d, const uint32_t* a, uint64_t db, int sd) {
  asm volatile("{\n.reg .pred p;\nsetp.ne.b32 p, %33, 0;\nwgmma.mma_async.sync.aligned.m64n56k16.f32.bf16.bf16 {%0,%1,%2,%3,%4,%5,%6,%7,%8,%9,%10,%11,%12,%13,%14,%15,%16,%17,%18,%19,%20,%21,%22,%23,%24,%25,%26,%27}, {%28,%29,%30,%31}, %32, p, 1, 1, 0;\n}\n"
   : "+f"(d[0]),"+f"(d[1]),"+f"(d[2]),"+f"(d[3]),"+f"(d[4]),"+f"(d[5]),"+f"(d[6]),"+f"(d[7]),"+f"(d[8]),"+f"(d[9]),"+f"(d[10]),"+f"(d[11]),"+f"(d[12]),"+f"(d[13]),"+f"(d[14]),"+f"(d[15]),"+f"(d[16]),"+f"(d[17]),"+f"(d[18]),"+f"(d[19]),"+f"(d[20]),"+f"(d[21]),"+f"(d[22]),"+f"(d[23]),"+f"(d[24]),"+f"(d[25]),"+f"(d[26]),"+f"(d[27])
   : "r"(a[0]), "r"(a[1]), "r"(a[2]), "r"(a[3]), "l"(db), "r"(sd));
}
template<> __device__ __forceinline__ void wgmma_rs<48,0>(float* d, const uint32_t* a, uint64_t db, int sd) {
  asm volatile("{\n.reg .pred p;\nsetp.ne.b32 p, %29, 0;\nwgmma.mma_async.sync.aligned.m64n48k16.f32.bf16.bf16 {%0,%1,%2,%3,%4,%5,%6,%7,%8,%9,%10,%11,%12,%13,%14,%15,%16,%17,%18,%19,%20,%21,%22,%23}, {%24,%25,%26,%27}, %28, p, 1, 1, 0;\n}\n"
   : "+f"(d[0]),"+f"(d[1]),"+f"(d[2]),"+f"(d[3]),"+f"(d[4]),"+f"(d[5]),"+f"(d[6]),"+f"(d[7]),"+f"(d[8]),"+f"(d[9]),"+f"(d[10]),"+f"(d[11]),"+f"(d[12]),"+f"(d[13]),"+f"(d[14]),"+f"(d[15]),"+f"(d[16]),"+f"(d[17]),"+f"(d[18]),"+f"(d[19]),"+f"(d[20]),"+f"(d[21]),"+f"(d[22]),"+f"(d[23])
   : "r"(a[0]), "r"(a[1]), "r"(a[2]), "r"(a[3]), "l"(db), "r"(sd));
}
template<> __device__ __forceinline__ void wgmma_rs<40,0>(float* d, const uint32_t* a, uint64_t db, int sd) {
  asm volatile("{\n.reg .pred p;\nsetp.ne.b32 p, %25, 0;\nwgmma.mma_async.sync.aligned.m64n40k16.f32.bf16.bf16 {%0,%1,%2,%3,%4,%5,%6,%7,%8,%9,%10,%11,%12,%13,%14,%15,%16,%17,%18,%19}, {%20,%21,%22,%23}, %24, p, 1, 1, 0;\n}\n"
   : "+f"(d[0]),"+f"(d[1]),"+f"(d[2]),"+f"(d[3]),"+f"(d[4]),"+f"(d[5]),"+f"(d[6]),"+f"(d[7]),"+f"(d[8]),"+f"(d[9]),"+f"(d[10]),"+f"(d[11]),"+f"(d[12]),"+f"(d[13]),"+f"(d[14]),"+f"(d[15]),"+f"(d[16]),"+f"(d[17]),"+f"(d[18]),"+f"(d[19])
   : "r"(a[0]), "r"(a[1]), "r"(a[2]), "r"(a[3]), "l"(db), "r"(sd));
}
template<> __device__ __forceinline__ void wgmma_rs<32,0>(float* d, const uint32_t* a, uint64_t db, int sd) {
  asm volatile("{\n.reg .pred p;\nsetp.ne.b32 p, %21, 0;\nwgmma.mma_async.sync.aligned.m64n32k16.f32.bf16.bf16 {%0,%1,%2,%3,%4,%5,%6,%7,%8,%9,%10,%11,%12,%13,%14,%15}, {%16,%17,%18,%19}, %20, p, 1, 1, 0;\n}\n"
   : "+f"(d[0]),"+f"(d[1]),"+f"(d[2]),"+f"(d[3]),"+f"(d[4]),"+f"(d[5]),"+f"(d[6]),"+f"(d[7]),"+f"(d[8]),"+f"(d[9]),"+f"(d[10]),"+f"(d[11]),"+f"(d[12]),"+f"(d[13]),"+f"(d[14]),"+f"(d[15])
   : "r"(a[0]), "r"(a[1]), "r"(a[2]), "r"(a[3]), "l"(db), "r"(sd));
}
template<> __device__ __forceinline__ void wgmma_rs<24,0>(float* d, const uint32_t* a, uint64_t db, int sd) {
  asm volatile("{\n.reg .pred p;\nsetp.ne.b32 p, %17, 0;\nwgmma.mma_async.sync.aligned.m64n24k16.f32.bf16.bf16 {%0,%1,%2,%3,%4,%5,%6,%7,%8,%9,%10,%11}, {%12,%13,%14,%15}, %16, p, 1, 1, 0;\n}\n"
   : "+f"(d[0]),"+f"(d[1]),"+f"(d[2]),"+f"(d[3]),"+f"(d[4]),"+f"(d[5]),"+f"(d[6]),"+f"(d[7]),"+f"(d[8]),"+f"(d[9]),"+f"(d[10]),"+f"(d[11])
   : "r"(a[0]), "r"(a[1]), "r"(a[2]), "r"(a[3]), "l"(db), "r"(sd));
}
template<> __device__ __forceinline__ void wgmma_rs<16,0>(float* d, const uint32_t* a, uint64_t db, int sd) {
  asm volatile("{\n.reg .pred p;\nsetp.ne.b32 p, %13, 0;\nwgmma.mma_async.sync.aligned.m64n16k16.f32.bf16.bf16 {%0,%1,%2,%3,%4,%5,%6,%7}, {%8,%9,%10,%11}, %12, p, 1, 1, 0;\n}\n"
   : "+f"(d[0]),"+f"(d[1]),"+f"(d[2]),"+f"(d[3]),"+f"(d[4]),"+f"(d[5]),"+f"(d[6]),"+f"(d[7])
   : "r"(a[0]), "r"(a[1]), "r"(a[2]), "r"(a[3]), "l"(db), "r"(sd));
}
template<> __device__ __forceinline__ void wgmma_rs<8,0>(float* d, const uint32_t* a, uint64_t db, int sd) {
  asm volatile("{\n.reg .pred p;\nsetp.ne.b32 p, %9, 0;\nwgmma.mma_async.sync.aligned.m64n8k16.f32.bf16.bf16 {%0,%1,%2,%3}, {%4,%5,%6,%7}, %8, p, 1, 1, 0;\n}\n"
   : "+f"(d[0]),"+f"(d[1]),"+f"(d[2]),"+f"(d[3])
   : "r"(a[0]), "r"(a[1]), "r"(a[2]), "r"(a[3]), "l"(db), "r"(sd));
}
template<> __device__ __forceinline__ void wgmma_ss<64,1,0>(float* d, uint64_t da, uint64_t db, int sd) {
  asm volatile("{\n.reg .pred p;\nsetp.ne.b32 p, %34, 0;\nwgmma.mma_async.sync.aligned.m64n64k16.f32.bf16.bf16 {%0,%1,%2,%3,%4,%5,%6,%7,%8,%9,%10,%11,%12,%13,%14,%15,%16,%17,%18,%19,%20,%21,%22,%23,%24,%25,%26,%27,%28,%29,%30,%31}, %32, %33, p, 1, 1, 1, 0;\n}\n"
   : "+f"(d[0]),"+f"(d[1]),"+f"(d[2]),"+f"(d[3]),"+f"(d[4]),"+f"(d[5]),"+f"(d[6]),"+f"(d[7]),"+f"(d[8]),"+f"(d[9]),"+f"(d[10]),"+f"(d[11]),"+f"(d[12]),"+f"(d[13]),"+f"(d[14]),"+f"(d[15]),"+f"(d[16]),"+f"(d[17]),"+f"(d[18]),"+f"(d[19]),"+f"(d[20]),"+f"(d[21]),"+f"(d[22]),"+f"(d[23]),"+f"(d[24]),"+f"(d[25]),"+f"(d[26]),"+f"(d[27]),"+f"(d[28]),"+f"(d[29]),"+f"(d[30]),"+f"(d[31])
   : "l"(da), "l"(db), "r"(sd));
}
template<> __device__ __forceinline__ void wgmma_ss<64,0,1>(float* d, uint64_t da, uint64_t db, int sd) {
  asm volatile("{\n.reg .pred p;\nsetp.ne.b32 p, %34, 0;\nwgmma.mma_async.sync.aligned.m64n64k16.f32.bf16.bf16 {%0,%1,%2,%3,%4,%5,%6,%7,%8,%9,%10,%11,%12,%13,%14,%15,%16,%17,%18,%19,%20,%21,%22,%23,%24,%25,%26,%27,%28,%29,%30,%31}, %32, %33, p, 1, 1, 0, 1;\n}\n"
   : "+f"(d[0]),"+f"(d[1]),"+f"(d[2]),"+f"(d[3]),"+f"(d[4]),"+f"(d[5]),"+f"(d[6]),"+f"(d[7]),"+f"(d[8]),"+f"(d[9]),"+f"(d[10]),"+f"(d[11]),"+f"(d[12]),"+f"(d[13]),"+f"(d[14]),"+f"(d[15]),"+f"(d[16]),"+f"(d[17]),"+f"(d[18]),"+f"(d[19]),"+f"(d[20]),"+f"(d[21]),"+f"(d[22]),"+f"(d[23]),"+f"(d[24]),"+f"(d[25]),"+f"(d[26]),"+f"(d[27]),"+f"(d[28]),"+f"(d[29]),"+f"(d[30]),"+f"(d[31])
   : "l"(da), "l"(db), "r"(sd));
}
template<> __device__ __forceinline__ void wgmma_ss<192,0,1>(float* d, uint64_t da, uint64_t db, int sd) {
  asm volatile("{\n.reg .pred p;\nsetp.ne.b32 p, %98, 0;\nwgmma.mma_async.sync.aligned.m64n192k16.f32.bf16.bf16 {%0,%1,%2,%3,%4,%5,%6,%7,%8,%9,%10,%11,%12,%13,%14,%15,%16,%17,%18,%19,%20,%21,%22,%23,%24,%25,%26,%27,%28,%29,%30,%31,%32,%33,%34,%35,%36,%37,%38,%39,%40,%41,%42,%43,%44,%45,%46,%47,%48,%49,%50,%51,%52,%53,%54,%55,%56,%57,%58,%59,%60,%61,%62,%63,%64,%65,%66,%67,%68,%69,%70,%71,%72,%73,%74,%75,%76,%77,%78,%79,%80,%81,%82,%83,%84,%85,%86,%87,%88,%89,%90,%91,%92,%93,%94,%95}, %96, %97, p, 1, 1, 0, 1;\n}\n"
   : "+f"(d[0]),"+f"(d[1]),"+f"(d[2]),"+f"(d[3]),"+f"(d[4]),"+f"(d[5]),"+f"(d[6]),"+f"(d[7]),"+f"(d[8]),"+f"(d[9]),"+f"(d[10]),"+f"(d[11]),"+f"(d[12]),"+f"(d[13]),"+f"(d[14]),"+f"(d[15]),"+f"(d[16]),"+f"(d[17]),"+f"(d[18]),"+f"(d[19]),"+f"(d[20]),"+f"(d[21]),"+f"(d[22]),"+f"(d[23]),"+f"(d[24]),"+f"(d[25]),"+f"(d[26]),"+f"(d[27]),"+f"(d[28]),"+f"(d[29]),"+f"(d[30]),"+f"(d[31]),"+f"(d[32]),"+f"(d[33]),"+f"(d[34]),"+f"(d[35]),"+f"(d[36]),"+f"(d[37]),"+f"(d[38]),"+f"(d[39]),"+f"(d[40]),"+f"(d[41]),"+f"(d[42]),"+f"(d[43]),"+f"(d[44]),"+f"(d[45]),"+f"(d[46]),"+f"(d[47]),"+f"(d[48]),"+f"(d[49]),"+f"(d[50]),"+f"(d[51]),"+f"(d[52]),"+f"(d[53]),"+f"(d[54]),"+f"(d[55]),"+f"(d[56]),"+f"(d[57]),"+f"(d[58]),"+f"(d[59]),"+f"(d[60]),"+f"(d[61]),"+f"(d[62]),"+f"(d[63]),"+f"(d[64]),"+f"(d[65]),"+f"(d[66]),"+f"(d[67]),"+f"(d[68]),"+f"(d[69]),"+f"(d[70]),"+f"(d[71]),"+f"(d[72]),"+f"(d[73]),"+f"(d[74]),"+f"(d[75]),"+f"(d[76]),"+f"(d[77]),"+f"(d[78]),"+f"(d[79]),"+f"(d[80]),"+f"(d[81]),"+f"(d[82]),"+f"(d[83]),"+f"(d[84]),"+f"(d[85]),"+f"(d[86]),"+f"(d[87]),"+f"(d[88]),"+f"(d[89]),"+f"(d[90]),"+f"(d[91]),"+f"(d[92]),"+f"(d[93]),"+f"(d[94]),"+f"(d[95])
   : "l"(da), "l"(db), "r"(sd));
}
template<> __device__ __forceinline__ void wgmma_ss<192,1,1>(float* d, uint64_t da, uint64_t db, int sd) {
  asm volatile("{\n.reg .pred p;\nsetp.ne.b32 p, %98, 0;\nwgmma.mma_async.sync.aligned.m64n192k16.f32.bf16.bf16 {%0,%1,%2,%3,%4,%5,%6,%7,%8,%9,%10,%11,%12,%13,%14,%15,%16,%17,%18,%19,%20,%21,%22,%23,%24,%25,%26,%27,%28,%29,%30,%31,%32,%33,%34,%35,%36,%37,%38,%39,%40,%41,%42,%43,%44,%45,%46,%47,%48,%49,%50,%51,%52,%53,%54,%55,%56,%57,%58,%59,%60,%61,%62,%63,%64,%65,%66,%67,%68,%69,%70,%71,%72,%73,%74,%75,%76,%77,%78,%79,%80,%81,%82,%83,%84,%85,%86,%87,%88,%89,%90,%91,%92,%93,%94,%95}, %96, %97, p, 1, 1, 1, 1;\n}\n"
   : "+f"(d[0]),"+f"(d[1]),"+f"(d[2]),"+f"(d[3]),"+f"(d[4]),"+f"(d[5]),"+f"(d[6]),"+f"(d[7]),"+f"(d[8]),"+f"(d[9]),"+f"(d[10]),"+f"(d[11]),"+f"(d[12]),"+f"(d[13]),"+f"(d[14]),"+f"(d[15]),"+f"(d[16]),"+f"(d[17]),"+f"(d[18]),"+f"(d[19]),"+f"(d[20]),"+f"(d[21]),"+f"(d[22]),"+f"(d[23]),"+f"(d[24]),"+f"(d[25]),"+f"(d[26]),"+f"(d[27]),"+f"(d[28]),"+f"(d[29]),"+f"(d[30]),"+f"(d[31]),"+f"(d[32]),"+f"(d[33]),"+f"(d[34]),"+f"(d[35]),"+f"(d[36]),"+f"(d[37]),"+f"(d[38]),"+f"(d[39]),"+f"(d[40]),"+f"(d[41]),"+f"(d[42]),"+f"(d[43]),"+f"(d[44]),"+f"(d[45]),"+f"(d[46]),"+f"(d[47]),"+f"(d[48]),"+f"(d[49]),"+f"(d[50]),"+f"(d[51]),"+f"(d[52]),"+f"(d[53]),"+f"(d[54]),"+f"(d[55]),"+f"(d[56]),"+f"(d[57]),"+f"(d[58]),"+f"(d[59]),"+f"(d[60]),"+f"(d[61]),"+f"(d[62]),"+f"(d[63]),"+f"(d[64]),"+f"(d[65]),"+f"(d[66]),"+f"(d[67]),"+f"(d[68]),"+f"(d[69]),"+f"(d[70]),"+f"(d[71]),"+f"(d[72]),"+f"(d[73]),"+f"(d[74]),"+f"(d[75]),"+f"(d[76]),"+f"(d[77]),"+f"(d[78]),"+f"(d[79]),"+f"(d[80]),"+f"(d[81]),"+f"(d[82]),"+f"(d[83]),"+f"(d[84]),"+f"(d[85]),"+f"(d[86]),"+f"(d[87]),"+f"(d[88]),"+f"(d[89]),"+f"(d[90]),"+f"(d[91]),"+f"(d[92]),"+f"(d[93]),"+f"(d[94]),"+f"(d[95])
   : "l"(da), "l"(db), "r"(sd));
}

template <bool TR>
__device__ __forceinline__ void gemm_section(float* acc, float& mean0, float& mean1, float& rstd0, float& rstd1,
                                             uint32_t sb, int blk, int hg, int wg, int w, int lane) {
  constexpr int layer = TR ? 1 : 0;
  constexpr int TURN = TR ? TURN1 : TURN0;
  constexpr int LSTAT = TURN < 4 ? TURN - 1 : 3;
  const uint32_t bar = sb + SM_BAR;
  const int g = lane >> 2, t = lane & 3;
  const bool leader = (w == 0) && (lane == 0);
  const int statpos = hg < 3 ? 1 : wg ? LSTAT : TR ? 3 : 2;
  const bool copy = hg >= 3 && wg == 0;
  const int cut = wg ? TURN : 4;
  auto wait_full = [&](int c) {
    mbar_wait(bar + 8 * (B_XF + 8 * wg + c), layer);
    mbar_wait(bar + 8 * (B_WF + c), layer);
  };
  auto peek = [&](int c) {
    const bool x = mbar_test(bar + 8 * (B_XF + 8 * wg + c), layer), y = mbar_test(bar + 8 * (B_WF + c), layer);
    return x && y;
  };
  const uint64_t da0 = mkdesc(sb, TR ? 8192 : 16, 1024, 1), db0 = mkdesc(sb, 8192, 1024, 1);
  uint32_t xt = wg ? 0xfedcba98u : 0x21043210u;
  uint64_t wt = 0x0816131005161310ull;
  uint64_t da = da0 + ((xt & 15) << 9), db = db0 + (16 << 9);
  auto issue = [&](int c, int first) {
    wg_fence();
#pragma unroll
    for (int ks = 0; ks < 4; ks++) wgmma_ss<192, TR ? 1 : 0, 1>(acc, da + (TR ? ks * 128 : ks * 2), db + ks * 128, !first || ks != 0);
    wg_commit();
    xt >>= 4; wt >>= 8;
    da = da0 + ((xt & 15) << 9); db = db0 + (((uint32_t)wt & 31) << 9);
  };
  wait_full(0);
  bool ready = peek(1);
  issue(0, 1);
  TSW(0);
#pragma unroll 1
  for (int c = 1; c < cut; c++) {
    if (!ready) wait_full(c);
    issue(c, 0);
    ready = peek(c + 1);
    wg_wait<1>();
    if (leader) mbar_arrive(bar + 8 * (B_DN + 8 * wg + c - 1));
    if (wg == 1 && c == cut - 1) {
      wg_wait<0>();
      if (leader) mbar_arrive(bar + 8 * (B_DN + 8 + c));
    }
    if (c == statpos) {
      mbar_wait(bar + 8 * (copy ? B_SC : B_XF + 8 * wg + hg), layer);
      uint32_t A[16];
      const uint32_t xb = sb + (copy ? P_R : 8 * wg + hg) * PG;
#pragma unroll
      for (int ks = 0; ks < 4; ks++) {
        if (!TR) {
          const int row = 16 * w + (lane & 15), kc = 2 * ks + (lane >> 4);
          ldsm4(&A[4 * ks], xb + row * 128 + ((kc ^ (row & 7)) << 4));
        } else {
          const int k = 16 * ks + (lane & 7) + 8 * (lane >> 4), pc = 2 * w + ((lane >> 3) & 1);
          ldsm4t(&A[4 * ks], xb + k * 128 + ((pc ^ (k & 7)) << 4));
        }
      }
      float s0 = 0.f, q0 = 0.f, s1 = 0.f, q1 = 0.f;
#pragma unroll
      for (int i = 0; i < 16; i += 2) {
        const float a = bf_lo(A[i]), b = bf_hi(A[i]), c_ = bf_lo(A[i + 1]), d = bf_hi(A[i + 1]);
        s0 += a + b; q0 = fmaf(a, a, q0); q0 = fmaf(b, b, q0);
        s1 += c_ + d; q1 = fmaf(c_, c_, q1); q1 = fmaf(d, d, q1);
      }
#pragma unroll
      for (int o = 1; o <= 2; o <<= 1) {
        s0 += __shfl_xor_sync(~0u, s0, o); q0 += __shfl_xor_sync(~0u, q0, o);
        s1 += __shfl_xor_sync(~0u, s1, o); q1 += __shfl_xor_sync(~0u, q1, o);
      }
      if (t < 2)
        asm volatile("red.relaxed.gpu.global.add.v4.f32 [%0], {%1,%2,%3,%4};" ::"l"(g_rows + layer * LSEQ + blk * 64 + 16 * w + g + 8 * t),
                     "f"(t ? s1 : s0), "f"(t ? q1 : q0), "f"(1.f), "f"(0.f) : "memory");
    }
  }
  if (wg == 1) {
#pragma unroll 1
    for (int c = cut; c < 8; c++) wait_full(c);
    ready = true;
    bar_sync(5, 256);
  }
#pragma unroll 1
  for (int c = cut; c < 8; c++) {
    if (!ready) wait_full(c);
    issue(c, 0);
    if (wg == 1) {
      wg_wait<2>();
      if (leader && c >= cut + 2) mbar_arrive(bar + 8 * (B_DN + 8 + c - 2));
    } else if (c == 7) {
      bar_arrive(5, 256);
    } else {
      ready = peek(c + 1);
      wg_wait<1>();
      if (leader && c < 6) mbar_arrive(bar + 8 * (B_DN + c - 1));
    }
  }
  mbar_wait(bar + 8 * (B_LN + wg), layer);
  const float4 ln = lds128f(sb + ln_off(wg) + (8 * w + g) * 16);
  mean0 = ln.x; rstd0 = ln.y; mean1 = ln.z; rstd1 = ln.w;
  wg_wait<0>();
  acc_fence<96>(acc);
  if (leader) mbar_arrive(bar + 8 * (B_DN + 8 * wg + 7));
}

__device__ __forceinline__ void attn_phase(const Params& p, uint32_t sb, int layer, int rb, int hg, int wg, int w) {
  const int lane = opaque_tid() & 31;
  const int g = lane >> 2, t = lane & 3;
  const uint32_t bar = sb + SM_BAR;
  const int blk = 16 * wg + rb;
  float acc[96];
  float2 cs[24];
  float mean0, mean1, rstd0, rstd1;
  if (layer) gemm_section<true>(acc, mean0, mean1, rstd0, rstd1, sb, blk, hg, wg, w, lane);
  else gemm_section<false>(acc, mean0, mean1, rstd0, rstd1, sb, blk, hg, wg, w, lane);
  TSW(1);
#pragma unroll
  for (int j = 8; j < 24; j++) cs[j] = lds64f(sb + SM_CS + 4 * (8 * j + 2 * t));
  const uint32_t kvx = sb + (wg ? 22 : 0) * PG;

  uint32_t kb[4][8], vb[4][8], qa[4][4];
  {
    const float nm0 = -mean0 * rstd0, nm1 = -mean1 * rstd1;
    const int st_row = 16 * w + (lane & 7) + 8 * ((lane >> 3) & 1);
    const uint32_t st_base = kvx + st_row * 256;
    const bool sender = (w == 3 && blk < 31);
    uint4* halo = &g_halo[(blk * 8 + hg) * 256 + lane];
    uint32_t r[4][2][4];
#pragma unroll
    for (int h = 0; h < 4; h++) {
#pragma unroll
      for (int kv = 0; kv < 2; kv++) {
#pragma unroll
        for (int dh = 0; dh < 2; dh++) {
          const int j = 8 + kv * 8 + 2 * h + dh;
          const float2 c2 = cs[j];
          const float v0 = fmaf(acc[4 * j + 0], rstd0, nm0 * c2.x), v1 = fmaf(acc[4 * j + 1], rstd0, nm0 * c2.y);
          const float v2 = fmaf(acc[4 * j + 2], rstd1, nm1 * c2.x), v3 = fmaf(acc[4 * j + 3], rstd1, nm1 * c2.y);
          r[h][kv][2 * dh] = packbf(v0, v1);
          r[h][kv][2 * dh + 1] = packbf(v2, v3);
        }
      }
      if (sender) {
        stg128(halo + (2 * h) * 32, make_uint4(r[h][0][0], r[h][0][2], r[h][0][1], r[h][0][3]));
        stg128(halo + (2 * h + 1) * 32, make_uint4(r[h][1][0], r[h][1][1], r[h][1][2], r[h][1][3]));
      }
    }
#pragma unroll
    for (int j = 0; j < 8; j++) cs[j] = lds64f(sb + SM_CS + 4 * (8 * j + 2 * t));
    mbar_wait(bar + 8 * (B_DN + 7), layer);
#pragma unroll
    for (int h = 0; h < 4; h++) {
#pragma unroll
      for (int kv = 0; kv < 2; kv++) {
        const int chunk = 4 * h + 2 * kv + (lane >> 4);
        if (w < 3) stsm4(st_base + (((chunk & 8) | ((chunk ^ st_row) & 7)) << 4), r[h][kv][0], r[h][kv][1], r[h][kv][2], r[h][kv][3]);
      }
      kb[h][4] = r[h][0][0]; kb[h][5] = r[h][0][2]; kb[h][6] = r[h][0][1]; kb[h][7] = r[h][0][3];
      vb[h][4] = movm_t(r[h][1][0]); vb[h][5] = movm_t(r[h][1][1]); vb[h][6] = movm_t(r[h][1][2]); vb[h][7] = movm_t(r[h][1][3]);
    }
#pragma unroll
    for (int h = 0; h < 4; h++) {
#pragma unroll
      for (int dh = 0; dh < 2; dh++) {
        const int j = 2 * h + dh;
        const float2 c2 = cs[j];
        qa[h][2 * dh] = packbf(fmaf(-mean0, c2.x, acc[4 * j + 0]), fmaf(-mean0, c2.y, acc[4 * j + 1]));
        qa[h][2 * dh + 1] = packbf(fmaf(-mean1, c2.x, acc[4 * j + 2]), fmaf(-mean1, c2.y, acc[4 * j + 3]));
      }
    }
  }
  bar_sync(2 + wg, 128);
  TSW(2);
  {
    const uint32_t prev_base = kvx + (16 * w - 16) * 256;
    const int mi = lane >> 3;
    const int r = 8 * (mi >> 1) + (lane & 7), r2 = 8 * (mi & 1) + (lane & 7);
    if (w != 0) {
#pragma unroll
      for (int h = 0; h < 4; h++) {
        const int ch = 4 * h + (mi & 1), ch2 = 4 * h + 2 + (mi >> 1);
        ldsm4(&kb[h][0], prev_base + r * 256 + (((ch & 8) | ((ch ^ r) & 7)) << 4));
        ldsm4t(&vb[h][0], prev_base + r2 * 256 + (((ch2 & 8) | ((ch2 ^ r2) & 7)) << 4));
      }
    } else if (blk > 0) {
      uint4* src = &g_halo[((blk - 1) * 8 + hg) * 256 + lane];
      uint4 hv[8];
      int it = 0;
      bool ok;
      do {
        ok = true;
#pragma unroll
        for (int i = 0; i < 8; i++) hv[i] = ld_tagged(src + i * 32);
#pragma unroll
        for (int i = 0; i < 8; i++) ok = ok && hv[i].x != UNSET;
      } while (!__all_sync(~0u, ok) && ++it < (1 << 20));
      if (layer == 0) {
#pragma unroll
        for (int i = 0; i < 2; i++) stg128(src + i * 128 + (lane >> 1) * 6, make_uint4(UNSET, UNSET, UNSET, UNSET));
      }
#pragma unroll
      for (int h = 0; h < 4; h++) {
        kb[h][0] = hv[2 * h].x; kb[h][1] = hv[2 * h].y; kb[h][2] = hv[2 * h].z; kb[h][3] = hv[2 * h].w;
        vb[h][0] = movm_t(hv[2 * h + 1].x); vb[h][1] = movm_t(hv[2 * h + 1].y);
        vb[h][2] = movm_t(hv[2 * h + 1].z); vb[h][3] = movm_t(hv[2 * h + 1].w);
      }
    } else {
#pragma unroll
      for (int h = 0; h < 4; h++)
#pragma unroll
        for (int k = 0; k < 4; k++) kb[h][k] = vb[h][k] = 0u;
    }
    TSW(3);
  }
  mbar_wait(bar + 8 * (B_DN + 15), layer);
  TSW(4);

  const bool first = (blk == 0 && w == 0);
  const int e = t - (g >> 1);
  const bool par = g & 1, epos = e >= 1;
  const uint32_t pmask = par ? 0xffff0000u : 0x0000ffffu;
  const uint32_t mB0 = epos ? pmask : 0u, mB1 = epos ? 0u : pmask;
  const float cl2 = 0.25f * 1.4426950408889634f;
  const float sc0 = rstd0 * cl2, sc1 = rstd1 * cl2;
  const float NEG = -INFINITY;
  float vA0[4], vB0[4], vA1[4], vB1[4];
#pragma unroll
  for (int h = 0; h < 4; h++) {
    float S[4][4];
#pragma unroll
    for (int j = 0; j < 4; j++) {
      S[j][0] = S[j][1] = S[j][2] = S[j][3] = 0.f;
      mma_bf16(S[j], qa[h], kb[h][2 * j], kb[h][2 * j + 1]);
    }
    vA0[h] = par ? S[1][1] : S[1][0];
    vB0[h] = epos ? (par ? S[0][1] : S[0][0]) : (par ? S[2][1] : S[2][0]);
    vA1[h] = par ? S[2][3] : S[2][2];
    vB1[h] = epos ? (par ? S[1][3] : S[1][2]) : (par ? S[3][3] : S[3][2]);
    if (first) { vA0[h] = NEG; if (epos) { vB0[h] = NEG; vB1[h] = NEG; } }
  }
  float m0[4], m1[4];
#pragma unroll
  for (int h = 0; h < 4; h++) { m0[h] = fmaxf(vA0[h], vB0[h]); m1[h] = fmaxf(vA1[h], vB1[h]); }
#pragma unroll
  for (int o = 1; o <= 2; o <<= 1) {
#pragma unroll
    for (int h = 0; h < 4; h++) {
      m0[h] = fmaxf(m0[h], __shfl_xor_sync(~0u, m0[h], o));
      m1[h] = fmaxf(m1[h], __shfl_xor_sync(~0u, m1[h], o));
    }
  }
  float O0[4][4], O1[4][4], Z[4][4];
#pragma unroll
  for (int h = 0; h < 4; h++) {
    const float mm0 = -m0[h] * sc0, mm1 = -m1[h] * sc1;
    const float pA0 = ex2(fmaf(vA0[h], sc0, mm0)), pB0 = ex2(fmaf(vB0[h], sc0, mm0));
    const float pA1 = ex2(fmaf(vA1[h], sc1, mm1)), pB1 = ex2(fmaf(vB1[h], sc1, mm1));
    const uint32_t hA0 = packbf(pA0, pA0), hB0 = packbf(pB0, pB0), hA1 = packbf(pA1, pA1), hB1 = packbf(pB1, pB1);
    const uint32_t P0[4] = {hB0 & mB0, 0u, hA0 & pmask, hB1 & mB0};
    const uint32_t P1[4] = {hB0 & mB1, hA1 & pmask, 0u, hB1 & mB1};
#pragma unroll
    for (int k = 0; k < 4; k++) O0[h][k] = O1[h][k] = Z[h][k] = 0.f;
    mma_bf16(O0[h], P0, vb[h][0], vb[h][1]); mma_bf16(O1[h], P0, vb[h][2], vb[h][3]); mma_bf16(Z[h], P0, 0x3f803f80u, 0x3f803f80u);
    mma_bf16(O0[h], P1, vb[h][4], vb[h][5]); mma_bf16(O1[h], P1, vb[h][6], vb[h][7]); mma_bf16(Z[h], P1, 0x3f803f80u, 0x3f803f80u);
  }
  if (lane == 0) mbar_arrive(bar + 8 * (B_OST + wg));
  uint4* op = (uint4*)g_O + ((layer * 32 + blk) * 8 + hg) * 512 + 64 * t + 16 * w + g;
#pragma unroll
  for (int h = 0; h < 4; h += 2) {
    const float i0 = rcp_approx(Z[h][0]), i1 = rcp_approx(Z[h][2]), j0 = rcp_approx(Z[h + 1][0]), j1 = rcp_approx(Z[h + 1][2]);
    stg128(op + 128 * h, make_uint4(packbf(O0[h][0] * i0, O0[h][1] * i0), packbf(O1[h][0] * i0, O1[h][1] * i0),
                                   packbf(O0[h + 1][0] * j0, O0[h + 1][1] * j0), packbf(O1[h + 1][0] * j0, O1[h + 1][1] * j0)));
    stg128(op + 128 * h + 8, make_uint4(packbf(O0[h][2] * i1, O0[h][3] * i1), packbf(O1[h][2] * i1, O1[h][3] * i1),
                                            packbf(O0[h + 1][2] * j1, O0[h + 1][3] * j1), packbf(O1[h + 1][2] * j1, O1[h + 1][3] * j1)));
  }
  TSW(5);
  __syncwarp();
  if (lane == 0) red_relaxed(&g_cnt[(C_O + layer * 32 + blk) * 32]);
  TSW(6);
}

#define PTH 0
#define PTG 4
#define PGB B_PG
#define LPRE 1
__device__ __forceinline__ void conv_load(uint32_t* A, uint32_t pe);
__device__ __forceinline__ void proj_phase(const Params& p, uint32_t sb, int layer, int rb, int q, uint32_t* A0, uint32_t* A1) {
  const int lane = opaque_tid() & 31;
  const int wg = __shfl_sync(~0u, opaque_tid() >> 7, 0), w = __shfl_sync(~0u, (opaque_tid() >> 5) & 3, 0);
  const bool TR = layer != 0;
  const int t = lane & 3;
  const uint32_t bar = sb + SM_BAR;
  const uint32_t rbx = sb + (P_R + wg) * PG;
  const uint32_t rsrc = sb + (wg ? 2 : P_R) * PG;
  const int blk = 16 * wg + rb;
  mbar_wait(bar + 8 * (B_RF + wg), layer);
  mbar_wait(bar + 8 * B_WOF, layer);
  const uint32_t stg = sb + (wg ? SM_KGT : SM_STG);
  if (layer) {
    const uint32_t pe = sb + cv_pe(wg, 1) + 4 * (16 + 16 * w + (lane >> 2) - 2 * t);
    mbar_wait(bar + 8 * B_PE, 1);
    conv_load(A0, pe);
    conv_load(A1, pe + 2 * 4480);
    __syncwarp();
    if (lane == 0) mbar_arrive(bar + 8 * B_AL);
  } else {
#pragma unroll
    for (int i = 0; i < 68; i++) {
      asm volatile("mov.b32 %0, 0;" : "=r"(A0[i]));
      asm volatile("mov.b32 %0, 0;" : "=r"(A1[i]));
    }
  }
  bool clean = false, staged = false;
#pragma unroll 1
  for (int attempt = 0; attempt < MAX_RETRY; attempt++) {
  uint32_t res[16];
  if (!TR) {
#pragma unroll
    for (int j = 0; j < 8; j += 2) {
      const int mi = lane >> 3;
      const int row = 16 * w + (lane & 7) + 8 * (mi & 1), ch = j + (mi >> 1);
      ldsm4(&res[2 * j], rsrc + row * 128 + ((ch ^ (row & 7)) << 4));
    }
  } else {
#pragma unroll
    for (int j = 0; j < 8; j += 2) {
      const int mi = lane >> 3;
      const int line = 8 * (j + (mi >> 1)) + (lane & 7), pc = 2 * w + (mi & 1);
      ldsm4t(&res[2 * j], rsrc + line * 128 + ((pc ^ (line & 7)) << 4));
    }
  }
  float acc[32];
#pragma unroll
  for (int j = 0; j < 16; j++) { acc[2 * j] = bf_lo(res[j]); acc[2 * j + 1] = bf_hi(res[j]); }
  acc_fence<32>(acc);
  if (wg) mbar_wait(bar + 8 * (PGB), layer);
  const int wg2 = __shfl_sync(~0u, opaque_tid() >> 7, 0);
  const uint64_t da0 = mkdesc(sb, 1024, 128, 0), db0 = mkdesc(sb, 8192, 1024, 1);
#pragma unroll
  for (int c = 0; c < 4; c++) {
    mbar_wait(bar + 8 * (B_OF + 4 * wg + c), layer);
    if (c == 0) TSW(7);
    const uint64_t da = da0 + (uint32_t)(o_page(wg2, c) * 512);
    wg_fence();
#pragma unroll
    for (int ks = 0; ks < 8; ks++) {
      if (c >= PTH && ks % PTG == 0) { if (ks) wg_commit(); if (wg2) wg_wait<0>(); wg_fence(); }
      wgmma_ss<64, 0, 1>(acc, da + ks * 128, db0 + wo_page(2 * c + (ks >> 2)) * 512 + (ks & 3) * 128, 1);
    }
    wg_commit();
  }
  if (wg) mbar_wait(bar + 8 * B_KG, 0);
  wg_wait<0>();
  acc_fence<32>(acc);
  TSW(8);
  if (!clean) {
    const float chk = acc[0] + acc[2];
    clean = __all_sync(~0u, chk == chk);
    if (clean && lane == 0) mbar_arrive(bar + 8 * (B_PDONE + wg));
  }
  float s0 = 0.f, q0 = 0.f, s1 = 0.f, q1 = 0.f;
  uint32_t o[16];
#pragma unroll
  for (int j = 0; j < 8; j++) {
    const float a = acc[4 * j], b = acc[4 * j + 1], c = acc[4 * j + 2], d = acc[4 * j + 3];
    o[2 * j] = packbf(a, b);
    o[2 * j + 1] = packbf(c, d);
    s0 += a + b; q0 = fmaf(a, a, q0); q0 = fmaf(b, b, q0);
    s1 += c + d; q1 = fmaf(c, c, q1); q1 = fmaf(d, d, q1);
  }
#pragma unroll
  for (int j = 0; j < 8; j += 2) {
    const int mi = lane >> 3;
    const int line = 8 * (j + (mi >> 1)) + (lane & 7), pc = 2 * w + (mi & 1);
    stsm4t(rbx + line * 128 + ((pc ^ (line & 7)) << 4), o[2 * j], o[2 * j + 1], o[2 * j + 2], o[2 * j + 3]);
  }
#pragma unroll
  for (int o2 = 1; o2 <= 2; o2 <<= 1) {
    s0 += __shfl_xor_sync(~0u, s0, o2); q0 += __shfl_xor_sync(~0u, q0, o2);
    s1 += __shfl_xor_sync(~0u, s1, o2); q1 += __shfl_xor_sync(~0u, q1, o2);
  }
  {
    const int i = 2 * (lane >> 2) + (t & 1), k = (i * 11) >> 5;
    const float v = (t == 0) ? s0 : (t == 1) ? q0 : (t == 2) ? s1 : q1;
    sts32f(stg + k * 128 + (2 * w + (t >> 1)) * 16 + (i - 3 * k) * 4, v);
  }
  TSW(9);
  fence_async_smem();
  if (attempt == 0 && clean) {
    staged = true;
    __syncwarp();
    if (lane == 0) mbar_arrive(bar + 8 * (B_STG + wg));
  }
  if (!bar_or(2 + wg, 128, !clean)) break;
  const int rtp = mbar_test(bar + 8 * (B_RT + wg), 0);
  bool unset = false;
#pragma unroll
  for (int i = 0; i < 4; i++) unset |= lds32(sb + o_page(wg, i) * PG + (32 * w + lane) * 128) == UNSET;
  if (!bar_or(2 + wg, 128, unset)) break;
  if (w == 0 && elect_one()) {
    fence_async_smem();
    mbar_expect(bar + 8 * (B_RT + wg), 9 * PG);
    if (layer == 0) tma_ld(rsrc, &p.mapX, q * 64, blk * 64, bar + 8 * (B_RT + wg));
    else tma_ld(rsrc, &p.mapXT, blk * 64, DM + q * 64, bar + 8 * (B_RT + wg));
#pragma unroll 1
    for (int c = 0; c < 4; c++) bulk_ld(sb + o_page(wg, c) * PG, g_O + ((layer * 32 + blk) * 4 + c) * PG, 2 * PG, bar + 8 * (B_RT + wg));
  }
  mbar_wait(bar + 8 * (B_RT + wg), rtp);
  RETRY(0);
  }
  if (!clean && lane == 0) mbar_arrive(bar + 8 * (B_PDONE + wg));
  if (!staged && lane == 0) mbar_arrive(bar + 8 * (B_STG + wg));
  TSW(10);
}

__device__ __forceinline__ void conv_load(uint32_t* A, uint32_t pe) {
#pragma unroll
  for (int m = 0; m < 17; m++) {
    A[4 * m + 2] = lds32(pe + 4 * (64 * m - 8));
    A[4 * m + 0] = lds32(pe + 4 * (64 * m));
    A[4 * m + 1] = lds32(pe + 4 * (64 * m + 8));
    asm volatile("mov.b32 %0, %1;" : "=r"(A[4 * m + 3]) : "r"(A[4 * m + 0]));
  }
}
template <int M> __device__ __forceinline__ void conv_tri(float* acc, const uint32_t* A, uint64_t d) {
  if constexpr (M < 16) {
    wgmma_rs<64 - 8 * (M / 2), 0>(acc, A + 4 * M, d + (uint64_t)(64 + 4 * M), M != 0);
    conv_tri<M + 1>(acc, A, d);
  }
}
__device__ __forceinline__ void conv_mma0(float* acc, const uint32_t* A, uint64_t d) {
  wg_fence();
  conv_tri<0>(acc, A, d);
  wg_commit();
}
__device__ __forceinline__ void conv_mma1_early(float* acc, const uint32_t* A, uint64_t d, uint64_t ds, uint64_t df) {
  wg_fence();
  wgmma_rs<64, 0>(acc, A + 64, d + 64, 0);
  wgmma_ss<64, 1, 0>(acc, ds, df, 1);
  wgmma_ss<64, 1, 0>(acc, ds + 128, df + 128, 1);
}
__device__ __forceinline__ void conv_mma1(float* acc, const uint32_t* A, uint64_t d) {
#pragma unroll
  for (int m = 0; m < 16; m++) wgmma_rs<64, 0>(acc, A + 4 * m, d + (uint64_t)(4 * m), 1);
  wg_commit();
}
__device__ __forceinline__ void conv_store(float* acc, uint32_t pb, uint32_t over, int w) {
  acc_fence<32>(acc);
  const int l = opaque_tid() & 31, mt = l >> 3;
  int c = 2 * (63 - 8 * (mt >> 1) - (l & 7) + w) + (mt & 1);
  c ^= (c >> 3) & 1;
  const uint32_t a0 = pb + c * 16;
#pragma unroll
  for (int j = 0; j < 8; j += 2)
    stsm4t(j == 0 ? (c < 128 ? a0 : over + (c - 128) * 16) : a0 - 256 * j, packbf(acc[4 * j], acc[4 * j + 1]), packbf(acc[4 * j + 2], acc[4 * j + 3]),
           packbf(acc[4 * j + 4], acc[4 * j + 5]), packbf(acc[4 * j + 6], acc[4 * j + 7]));
}
__device__ __forceinline__ void conv_sums(uint32_t sb, int lc, int ht) {
  const int m = ht - 1;
  uint4 v[2][3];
#pragma unroll
  for (int c = 0; c < 2; c++)
#pragma unroll
    for (int k = 0; k < 3; k++) {
      const int mm = m - 1 + k;
      v[c][k] = lds128(sb + cv_u(lc + c) + (mm >= 0 ? (mm & 1) * CV_UH + (127 - (mm >> 1)) * 16 : 128 * 16));
    }
  const int ce = m + 2, co = m + 1;
#pragma unroll
  for (int c = 0; c < 2; c++) {
    const uint32_t x[8] = {v[c][0].z, v[c][0].w, v[c][1].x, v[c][1].y, v[c][1].z, v[c][1].w, v[c][2].x, v[c][2].y};
    float pv[16];
#pragma unroll
    for (int k = 0; k < 8; k++) { pv[2 * k] = bf_lo(x[k]); pv[2 * k + 1] = bf_hi(x[k]); }
    float t2[15], t4[13], s9[8], s7[8];
#pragma unroll
    for (int i = 0; i < 15; i++) t2[i] = pv[i] + pv[i + 1];
#pragma unroll
    for (int i = 0; i < 13; i++) t4[i] = t2[i] + t2[i + 2];
#pragma unroll
    for (int i = 0; i < 8; i++) {
      s9[i] = (t4[i] + t4[i + 4]) + pv[i + 8];
      s7[i] = (t4[i + 1] + t2[i + 5]) + pv[i + 7];
    }
    const uint4 e4 = make_uint4(packbf(s9[0], s9[1]), packbf(s9[2], s9[3]), packbf(s9[4], s9[5]), packbf(s9[6], s9[7]));
    if (ce < 128) sts128(sb + cv_se(lc + c) + ((ce ^ ((ce >> 3) & 7)) << 4), e4);
    else sts128(sb + cv_se(lc + c), make_uint4(0, 0, 0, 0));
    sts128(sb + cv_so(lc + c) + ((co ^ ((co >> 3) & 7)) << 4),
           make_uint4(packbf(s7[0], s7[1]), packbf(s7[2], s7[3]), packbf(s7[4], s7[5]), packbf(s7[6], s7[7])));
  }
}

template <int HALF, int NCH, int STEP = 1>
__device__ __forceinline__ void conv_epi(uint32_t sb, bf16* out, int lc, int c) {
  uint4 v[NCH][4], xr[NCH];
  const uint32_t sw = (c ^ ((c >> 3) & 1)) * 16;
#pragma unroll
  for (int u = 0; u < NCH; u++) {
#pragma unroll
    for (int k = 0; k < 4; k++) v[u][k] = lds128(sb + (HALF ? cv_pb1(lc + STEP * u, k) : cv_pb0(lc + STEP * u, k)) + sw);
    xr[u] = lds128(sb + cv_x(HALF, lc + STEP * u) + c * 16);
  }
#pragma unroll
  for (int u = 0; u < NCH; u++) {
    uint4 o;
    o.x = hadd2(xr[u].x, hadd2(hadd2(v[u][0].x, v[u][1].x), hadd2(v[u][2].x, v[u][3].x)));
    o.y = hadd2(xr[u].y, hadd2(hadd2(v[u][0].y, v[u][1].y), hadd2(v[u][2].y, v[u][3].y)));
    o.z = hadd2(xr[u].z, hadd2(hadd2(v[u][0].z, v[u][1].z), hadd2(v[u][2].z, v[u][3].z)));
    o.w = hadd2(xr[u].w, hadd2(hadd2(v[u][0].w, v[u][1].w), hadd2(v[u][2].w, v[u][3].w)));
    stg128(out + cv_chan(0, lc + STEP * u) * LSEQ + HALF * 1024 + c * 8, o);
  }
}

__device__ __forceinline__ bool prep_valid(const uint4 (&st)[6], const uint4 (&xr)[4]) {
  const uint32_t n = __float_as_uint(8.f);
  return st[0].w == n && st[1].w == n && st[2].w == n && st[3].w == n && st[4].w == n && (st[5].w | st[5].y | st[5].z) == n &&
         xr[0].x != UNSET && xr[1].x != UNSET && xr[2].x != UNSET && xr[3].x != UNSET;
}
template <int HALF>
__device__ __forceinline__ void conv_prep(uint32_t sb, int layer, int cta, int i) {
  uint4 st[6], xr[4];
  const uint4* sp = (const uint4*)g_stats + (layer * 32 + HALF * 16 + (i >> 3)) * 48 + (i & 7);
  const uint4* xp = (const uint4*)g_xT + (2 * layer * DM + 2 * cta) * (LSEQ / 8) + HALF * 128 + i;
  auto fetch = [&]() {
#pragma unroll
    for (int k = 0; k < 6; k++) st[k] = ld_tagged(sp + 8 * k);
#pragma unroll
    for (int k = 0; k < 4; k++) xr[k] = ld_tagged(xp + cv_chan(0, k) * (LSEQ / 8));
  };
  if (HALF) {
#pragma unroll
    for (int k = 0; k < 6; k++) st[k] = lds128(sb + CV_ST + (i >> 3) * 768 + k * 128 + (i & 7) * 16);
#pragma unroll
    for (int k = 0; k < 4; k++) xr[k] = lds128(sb + cv_x(1, k) + i * 16);
  } else {
    fetch();
  }
  int it = 0;
  while (!__all_sync(~0u, prep_valid(st, xr)) && ++it < MAX_RETRY) { fetch(); RETRY(1); }
  if (!HALF || it) {
#pragma unroll
    for (int k = 0; k < 4; k++) sts128(sb + cv_x(HALF, k) + i * 16, xr[k]);
  }
  const uint32_t v[16] = {st[0].x, st[0].y, st[0].z, st[1].x, st[1].y, st[1].z, st[2].x, st[2].y, st[2].z, st[3].x, st[3].y, st[3].z, st[4].x, st[4].y, st[4].z, st[5].x};
  uint32_t rs[4], nm[4];
#pragma unroll
  for (int k = 0; k < 4; k++) {
    const float m0 = __uint_as_float(v[4 * k]) * (-1.f / DM), m1 = __uint_as_float(v[4 * k + 2]) * (-1.f / DM);
    const float r0 = rsqrt_approx(fmaxf(fmaf(__uint_as_float(v[4 * k + 1]), 1.f / DM, -m0 * m0), 0.f) + 1e-5f);
    const float r1 = rsqrt_approx(fmaxf(fmaf(__uint_as_float(v[4 * k + 3]), 1.f / DM, -m1 * m1), 0.f) + 1e-5f);
    rs[k] = packbf(r0, r1);
    nm[k] = packbf(m0 * bf_lo(rs[k]), m1 * bf_hi(rs[k]));
  }
  const uint32_t ud = sb + (i & 1) * CV_UH + (127 - 64 * HALF - (i >> 1)) * 16;
#pragma unroll
  for (int k = 0; k < 4; k++)
    sts128(ud + cv_u(k), make_uint4(hfma2(xr[k].x, rs[0], nm[0]), hfma2(xr[k].y, rs[1], nm[1]), hfma2(xr[k].z, rs[2], nm[2]), hfma2(xr[k].w, rs[3], nm[3])));
  fence_async_smem();
}

#define EARLY1 1
#define PP0 1
__device__ __forceinline__ void conv_phase(const Params& p, uint32_t sb, int layer, int cta, uint32_t* A0, uint32_t* A1) {
  const int tid = opaque_tid();
  const int wg = __shfl_sync(~0u, tid >> 7, 0), w = __shfl_sync(~0u, (tid >> 5) & 3, 0);
  const uint32_t bar = sb + SM_BAR;
  constexpr int CH2 = 4 * PG;
  bf16* xout = g_xT + ((2 * layer + 1) * DM + 2 * cta) * LSEQ;
  float acc[32];
  const uint32_t pe = sb + cv_pe(wg, 0) + 4 * (16 + 16 * w + ((tid & 31) >> 2) - 2 * (tid & 3));
  if (!(LPRE && layer)) {
    mbar_wait(bar + 8 * (B_PDONE + 1), layer);
    mbar_wait(bar + 8 * B_PE, layer);
    conv_load(A0, pe);
    conv_load(A1, pe + CH2);
  }
  TSW(19);
  const uint64_t d0 = mkdesc(sb + cv_u(wg), CV_UH, 128, 0), d1 = d0 + (CH2 >> 4);
  mbar_wait(bar + 8 * B_U, layer);
  TSW(12);
  if (wg == 1) bar_sync(5, 256);
  conv_mma0(acc, A0, d0);
  if (wg == 0) bar_arrive(5, 256);
  mbar_wait(bar + 8 * (B_PDONE + 1), layer);
  {
    const int l = opaque_tid() & 31;
    if ((l & 15) < 2 * w) sts128(sb + cv_pb0(wg + 2 * (l >> 4), w) + (l & 15) * 16, make_uint4(0, 0, 0, 0));
  }
  wg_wait<0>();
  conv_store(acc, sb + cv_pb0(wg, w), sb + cv_pb1(wg, w), w);
  conv_mma0(acc, A1, d1);
  wg_wait<0>();
  conv_store(acc, sb + cv_pb0(2 + wg, w), sb + cv_pb1(2 + wg, w), w);
  TSW(13);
  bar_sync(2 + wg, 128);
  conv_epi<0, 2, 2>(sb, xout, wg, opaque_tid() & 127);
  TSW(14);
  mbar_arrive(bar + 8 * B_PUB);
  const uint64_t ds = mkdesc(sb + cv_se(wg), 8192, 1024, 1), df = mkdesc(sb + cv_fa(wg), 512, 128, 0);
  mbar_wait(bar + 8 * B_S, layer);
  conv_mma1_early(acc, A0, d0, ds, df);
  wg_commit();
  if (wg == 0) mbar_wait(bar + 8 * B_U1, layer);
  else bar_sync(6, 256);
  TSW(15);
  wg_fence();
  conv_mma1(acc, A0, d0);
  if (wg == 0) bar_arrive(6, 256);
  wg_wait<0>();
  conv_store(acc, sb + cv_pb1(wg, w), sb + cv_dump(wg), w);
  TSW(16);
  bar_sync(2 + wg, 128);
  conv_epi<1, 1>(sb, xout, wg, opaque_tid() & 127);
  mbar_arrive(bar + 8 * (B_PUB + 1));
  conv_mma1_early(acc, A1, d1, ds + 512, df + (CH2 >> 4));
  conv_mma1(acc, A1, d1);
  wg_wait<0>();
  conv_store(acc, sb + cv_pb1(2 + wg, w), sb + cv_dump(2 + wg), w);
  TSW(17);
  bar_sync(2 + wg, 128);
  conv_epi<1, 1>(sb, xout, 2 + wg, opaque_tid() & 127);
  mbar_arrive(bar + 8 * (B_PUB + 2));
  TSW(18);
}

__device__ __forceinline__ void final_tile(const Params& p, uint32_t buf, int ch0, int pos0, int barid) {
  const int tid = opaque_tid() & 127, lane = tid & 31, w = tid >> 5;
  const uint4* src = (const uint4*)(g_xT + (3 * DM + ch0 + (tid >> 3)) * LSEQ + pos0) + (tid & 7);
  const int ch = tid >> 3, row = 4 * (ch & 6) + 2 * (ch >> 3) + (ch & 1);
  const uint32_t dst = buf + row * 128;
  const uint32_t ld = buf + lane * 128;
  bf16* out = p.out + (pos0 + 16 * w + (lane >> 2)) * DM + ch0 + 8 * (lane & 3);
  uint4 a, b;
  int it = 0;
  do {
    if (it) RETRY(2);
    a = ld_tagged(src); b = ld_tagged(src + 16 * LSEQ / 8);
  } while (!__all_sync(~0u, a.x != UNSET && b.x != UNSET) && ++it < (1 << 20));
  sts128(dst + (((tid ^ row) & 7) << 4), a);
  sts128(dst + 512 + (((tid ^ row ^ 4) & 7) << 4), b);
  bar_sync(barid, 128);
#pragma unroll
  for (int h = 0; h < 2; h++) {
    uint32_t r[4];
    ldsm4t(r, ld + ((((2 * w + h) ^ lane) & 7) << 4));
    *(uint4*)(out + 8 * h * DM) = make_uint4(r[0], r[1], r[2], r[3]);
  }
}

struct cplx { float r, i; };
__device__ __forceinline__ cplx cmul(cplx a, cplx b) { return {fmaf(a.r, b.r, -a.i * b.i), fmaf(a.r, b.i, a.i * b.r)}; }
__device__ __forceinline__ cplx csqr(cplx a) { return {fmaf(a.r, a.r, -a.i * a.i), (a.r + a.r) * a.i}; }
__device__ __forceinline__ cplx cexp_l(float ar2, float ai, float l) {
  const float m = ex2(ar2 * l);
  const float x = ai * l;
  return {m * __cosf(x), m * __sinf(x)};
}

__device__ __forceinline__ void colsum_cta(const Params& p, uint32_t sb, int j, int tid) {
  const uint32_t bar = sb + SM_BAR;
  auto ld = [&](int i) {
    mbar_expect(bar + 8 * i, 3 * PG);
    tma_ld3(sb + (i & 7) * 3 * PG, &p.mapW3, (2 * j + (i & 1)) * 64, (i >> 1) * 64, 0, bar + 8 * i);
  };
  if (tid == 384) {
#pragma unroll
    for (int i = 0; i < 24; i++) mbar_init(bar + 8 * i, i < 16 ? 1 : 12);
    asm volatile("fence.mbarrier_init.release.cluster;" ::: "memory");
    fence_async_smem();
#pragma unroll 1
    for (int i = 0; i < 8; i++) ld(i);
  }
  const unsigned ep = ld_relaxed(&g_cnt[C_CS * 32]);
  bar_sync(0, NTHREADS);
  if (tid == 384) {
#pragma unroll 1
    for (int i = 8; i < 16; i++) { mbar_wait(bar + 8 * (8 + i), 0); fence_async_smem(); ld(i); }
  }
  if (tid < 384) {
    const int lane = tid & 31, cc = tid & 7, r0 = (tid >> 3) & 15, part = tid >> 7;
    const uint32_t id = ((lane >> 2) == 2 * (lane & 3) ? 0x3f80u : 0u) | ((lane >> 2) == 2 * (lane & 3) + 1 ? 0x3f800000u : 0u);
    const uint32_t src = sb + part * PG + r0 * 128 + ((cc ^ (r0 & 7)) << 4);
    float s[2][2][4];
#pragma unroll
    for (int i = 0; i < 16; i++) s[i >> 3][(i >> 2) & 1][i & 3] = 0.f;
#pragma unroll 1
    for (int i2 = 0; i2 < 16; i2 += 2) {
#pragma unroll
      for (int h = 0; h < 2; h++) {
        const int i = i2 + h;
        mbar_wait(bar + 8 * i, 0);
        uint4 v[4];
#pragma unroll
        for (int k = 0; k < 4; k++) v[k] = lds128(src + (i & 7) * 3 * PG + k * 2048);
#pragma unroll
        for (int k = 0; k < 4; k++) {
          const uint32_t a[4] = {v[k].x, v[k].y, v[k].z, v[k].w};
          mma_bf16(s[h][0], a, id, 0u);
          mma_bf16(s[h][1], a, 0u, id);
        }
        __syncwarp();
        if (i < 8 && lane == 0) mbar_arrive(bar + 8 * (16 + i));
      }
    }
    const uint32_t red = sb + 24 * PG;
#pragma unroll
    for (int h = 0; h < 2; h++)
#pragma unroll
      for (int k = 0; k < 2; k++) sts128f(red + (r0 * 384 + h * 192 + part * 64 + cc * 8 + k * 4) * 4, s[h][k][0], s[h][k][1], s[h][k][2], s[h][k][3]);
    bar_sync(1, 384);
    float tot = 0.f;
#pragma unroll
    for (int k = 0; k < 16; k++) tot += __uint_as_float(lds32(red + (k * 384 + tid) * 4));
    asm volatile("st.relaxed.gpu.global.v2.u32 [%0], {%1,%2};" ::"l"(&g_colsum[j * 384 + tid]), "r"(__float_as_uint(tot)), "r"(ep / NCTA + 1) : "memory");
    const uint4 u = make_uint4(UNSET, UNSET, UNSET, UNSET);
    if (tid < 256) {
#pragma unroll 1
      for (int s = 0; s < 4; s++) {
        const int n = (s == 1 || s == 2) ? 32 : 16;
        uint4* buf = s == 1 ? (uint4*)g_O + 131072 : (uint4*)g_xT + (s + !s) * 131072;
#pragma unroll 4
        for (int i = 0; i < n; i++) stg128(buf + (j * n + i) * 1024 + (tid >> 1) * 8 + (tid & 1), u);
        if (n == 16) {
#pragma unroll 4
          for (int i = 0; i < 8; i++) stg128(buf + (256 + j * 64 + i * 8 + (tid >> 5)) * 256 + (s ? 0 : 128) + ((tid & 31) >> 1) * 8 + (tid & 1), u);
        }
        if (s == 3) {
#pragma unroll 4
          for (int i = 0; i < 32; i++) stg128(buf + (256 + j * 64 + 2 * i + (tid >> 7)) * 256 + 128 + (tid & 127), u);
        }
        bar_sync(2, 256);
        if (tid == 32 * s) red_release(&g_cnt[(C_R + s) * 32]);
      }
    }
  }
}

#define KB 4
#define KW 2
struct ModeIn { uint32_t ar, ai, br, bi, cr, ci; bf16 logdt; };
__device__ __forceinline__ ModeIn load_modes(const Params& p, int d, int m) {
  const int i = d * 64 + m;
  return {((const uint32_t*)p.a_re)[i], ((const uint32_t*)p.a_im)[i], ((const uint32_t*)p.b_re)[i], ((const uint32_t*)p.b_im)[i],
          ((const uint32_t*)p.c_re)[i], ((const uint32_t*)p.c_im)[i], p.log_dt[d]};
}
__device__ __forceinline__ float4 lds128f_nv(uint32_t a) { float4 v; asm("ld.shared.v4.f32 {%0,%1,%2,%3}, [%4];" : "=f"(v.x), "=f"(v.y), "=f"(v.z), "=f"(v.w) : "r"(a)); return v; }
__device__ __forceinline__ void kernel_gen(const Params& p, uint32_t sb, int cta, int ht, ModeIn in, const ModeIn& in1) {
  const uint32_t bst = sb + SM_KGB + ((ht & 63) >> 2) * 144 + (ht & 3) * 4 + (ht >> 6) * 16;
  const uint64_t db = mkdesc(sb + SM_KGB, 144, 2304, 0);
  const float e0 = (float)(8 * (((ht & 32) >> 1) + ((ht & 31) >> 2)));
  float T[20];
#pragma unroll
  for (int i = 0; i < 20; i++) T[i] = 0.f;
  float k0 = 0.f;
#pragma unroll 1
  for (int pass = 0; pass < 4; pass++) {
    {
      const int sh = (pass & 1) ? 0 : 16;
      auto val = [&](uint32_t v) { return __uint_as_float((v << sh) & 0xffff0000u); };
      const float dt = __bfloat162float(__float2bfloat16_rn(expf(__bfloat162float(in.logdt))));
      const float ar2 = dt * val(in.ar) * 1.4426950408889634f, ai = dt * val(in.ai);
      const cplx c = cmul({val(in.cr), -val(in.ci)}, {dt * val(in.br), -dt * val(in.bi)});
      k0 += c.r;
      const cplx z1 = cexp_l(ar2, -ai, 1.f), z256 = cexp_l(ar2, -ai, 256.f), z64 = cexp_l(ar2, ai, 64.f);
      const cplx z2 = csqr(z1), z512 = csqr(z256);
      auto put = [&](int j, cplx v) { sts32(bst + (j >> 2) * 2304 + (j & 3) * 32, packbf(v.r, v.i)); };
      sts128f(sb + SM_KGT + ht * 16, ar2, ai, z64.r, z64.i);
      const cplx c1 = cmul(c, z1), c2 = cmul(c, z2), c3 = cmul(c1, z2), c4 = cmul(c2, z2);
      const cplx c5 = cmul(c3, z2), c6 = cmul(c4, z2), c7 = cmul(c5, z2), c8 = cmul(c6, z2);
      put(0, c1); put(1, c2); put(2, c3); put(3, c4); put(4, c5); put(5, c6); put(6, c7); put(7, c8);
      const cplx c260 = cmul(c4, z256), c264 = cmul(c8, z256), c520 = cmul(c8, z512), c776 = cmul(c264, z512);
      put(8, cmul(c2, z256)); put(9, c260); put(10, cmul(c6, z256)); put(11, c264);
      put(12, cmul(c4, z512)); put(13, c520); put(14, cmul(c260, z512)); put(15, c776);
      const cplx c1032 = cmul(c520, z512), c1288 = cmul(c776, z512);
      put(16, c1032); put(17, c1288); put(18, cmul(c1032, z512)); put(19, cmul(c1288, z512));
    }
    fence_async_smem();
    bar_sync(4, 128);
    const uint32_t tb = sb + SM_KGT + (ht & 67) * 16;
    float2 nx[KB];
#pragma unroll
    for (int s = 0; s < KB; s++) nx[s] = lds64f(tb + s * 64);
#pragma unroll
    for (int q = 0; q < 16 / KB; q++) {
      uint32_t A[2 * KB];
      float2 cur[KB], z[KB];
#pragma unroll
      for (int s = 0; s < KB; s++) { cur[s] = nx[s]; z[s] = lds64f(tb + (KB * q + s) * 64 + 8); }
      if (q < 16 / KB - 1) {
#pragma unroll
        for (int s = 0; s < KB; s++) nx[s] = lds64f(tb + (KB * q + KB + s) * 64);
      }
      if (q >= KW) wg_wait<KW - 1>();
#pragma unroll
      for (int s = 0; s < KB; s++) {
        const cplx lo = cexp_l(cur[s].x, cur[s].y, e0), hi = cmul(lo, {z[s].x, z[s].y});
        A[2 * s] = packbf(lo.r, lo.i);
        A[2 * s + 1] = packbf(hi.r, hi.i);
      }
      wg_fence();
#pragma unroll
      for (int k = 0; k < KB / 2; k++) wgmma_rs<40, 0>(T, A + 4 * k, db + 9 * KB * q + 18 * k, (pass & 1) | q | k);
      wg_commit();
    }
    wg_wait<0>();
    acc_fence<20>(T);
    if (ht == 0) TS(4 + pass);
    if (pass & 1) {
      const int h2 = opaque_tid() - 256, w = h2 >> 5, lane = h2 & 31, t = lane & 3, chn = h2 >> 6, m = h2 & 63, i0 = 16 * (w & 1) + (lane >> 2);
      const int lc = (pass & 2) + chn;
      const uint32_t kc = sb + kc_off(lc);
      auto put = [&](int idx, float v) {
        sts16(kc + idx * 2, __bfloat16_as_ushort(__float2bfloat16_rn(v)));
      };
#pragma unroll
      for (int hi = 0; hi < 2; hi++) {
        const int i = i0 + 8 * hi;
        float v[5];
#pragma unroll
        for (int j = 0; j < 5; j++) v[j] = chn ? T[4 * j + 2 * hi + 1] : T[4 * j + 2 * hi];
        put(8 * i + 1 + t, v[0]);
        put(8 * i + 5 + t, v[1]);
        put(257 + 4 * i + t, v[2]);
        put(385 + 2 * i + (t & 1) + 64 * (t >> 1), v[3]);
        put(513 + i + 32 * t, v[4]);
      }
#pragma unroll
      for (int o = 16; o > 0; o >>= 1) k0 += __shfl_xor_sync(~0u, k0, o);
      if (lane == 0) sts32f(sb + SM_RED + 4 * w, k0);
      bar_sync(4, 128);
      if (m == 0) put(0, k0 + __uint_as_float(lds32(sb + SM_RED + 4 * w + 4)) + __uint_as_float(lds16(sb + SM_RED + 24 + 2 * lc) << 16));
      k0 = 0.f;
      in = in1;
    }
  }
}

__device__ __forceinline__ void expand_taps(uint32_t sb, int ht, int early) {
  const int ch = ht >> 5, lane = ht & 31;
  const uint32_t kc = sb + kc_off(ch);
  const uint32_t dst0 = sb + cv_pe(ch, early);
  auto put = [&](int G, uint32_t v0, uint32_t v1, uint32_t v2, uint32_t v3, uint32_t v4, uint32_t v5, uint32_t v6, uint32_t v7, uint32_t v8) {
    const uint32_t dst = dst0 + G * 32;
    sts128(dst, make_uint4(v1 | (v0 << 16), v2 | (v1 << 16), v3 | (v2 << 16), v4 | (v3 << 16)));
    sts128(dst + 16, make_uint4(v5 | (v4 << 16), v6 | (v5 << 16), v7 | (v6 << 16), v8 | (v7 << 16)));
  };
  {
    const uint4 q = lds128(kc + lane * 16);
    const uint32_t pv = lane ? lds16(kc + lane * 16 - 2) : 0u;
    const uint32_t dst = dst0 + (lane + 2) * 32;
    sts128(dst, make_uint4(__byte_perm(q.x, pv, 0x5410), __byte_perm(q.x, q.x, 0x1032), __byte_perm(q.y, q.x, 0x7610), __byte_perm(q.y, q.y, 0x1032)));
    sts128(dst + 16, make_uint4(__byte_perm(q.z, q.y, 0x7610), __byte_perm(q.z, q.z, 0x1032), __byte_perm(q.w, q.z, 0x7610), __byte_perm(q.w, q.w, 0x1032)));
    if (lane < 4) sts128(dst0 + lane * 16, make_uint4(0, 0, 0, 0));
  }
  uint32_t a[5], b[2][3];
  {
    const uint32_t s1 = kc + 2 * (256 + 4 * lane);
#pragma unroll
    for (int k = 0; k < 5; k++) a[k] = lds16(s1 + 2 * k);
#pragma unroll
    for (int u = 0; u < 2; u++) {
      const uint32_t s2 = kc + 2 * (384 + 2 * (lane + 32 * u));
#pragma unroll
      for (int k = 0; k < 3; k++) b[u][k] = lds16(s2 + 2 * k);
    }
  }
  const uint32_t k255 = lds16(kc + 2 * 255), k1024 = lds16(kc + 2 * 512);
  put(34 + lane, lane == 0 ? k255 : a[0], a[0], a[0], a[1], a[2], a[2], a[2], a[3], a[4]);
#pragma unroll
  for (int u = 0; u < 2; u++) put(66 + lane + 32 * u, b[u][0], b[u][0], b[u][0], b[u][0], b[u][1], b[u][1], b[u][1], b[u][2], b[u][2]);
  if (lane < 10) {
    const uint32_t v = lane == 0 ? k1024 : 0u;
    put(130 + lane, v, v, v, v, v, v, 0u, 0u, 0u);
  }
}
__device__ __forceinline__ void expand_far(uint32_t sb, int ht) {
  const int ch = ht >> 5, lane = ht & 31;
  const uint32_t kc = sb + kc_off(ch) + 2 * (513 + 2 * (63 - lane)), dst = sb + cv_fa(ch) + lane * 16;
#pragma unroll
  for (int ty = 0; ty < 2; ty++) {
    uint32_t v[16];
#pragma unroll
    for (int k = 0; k < 16; k++) v[k] = (k < 8 || 63 - lane - 4 * k >= 0) ? lds16(kc + 2 * (1 - ty) - 16 * k) : 0u;
#pragma unroll
    for (int u = 0; u < 2; u++)
      sts128(dst + ty * 2048 + u * 512, make_uint4(v[8 * u] | (v[8 * u + 1] << 16), v[8 * u + 2] | (v[8 * u + 3] << 16), v[8 * u + 4] | (v[8 * u + 5] << 16), v[8 * u + 6] | (v[8 * u + 7] << 16)));
    sts128(dst + ty * 2048 + 1024, make_uint4(0, 0, 0, 0));
  }
}

#define TMPF 1
#define CONST_SB 1
#define XGATE B_OST
#define WPRE 1
__host__ __device__ constexpr int bar_count(int i) {
  return i == B_LN ? 2 : i == B_AL ? 8 : i < B_STG ? 1 : i < B_PE ? 4 : (i >= B_PUB && i < B_S) ? 256 : 128;
}
__host__ __device__ constexpr bool bar_first(int i) { return i < B_WF + 2 && (i & 7) < 2; }

__global__ void __launch_bounds__(NTHREADS, 1) fused_kernel(const __grid_constant__ Params p) {
  extern __shared__ __align__(1024) uint8_t smem[];
  constexpr uint32_t sb = 1024;
  if (s32(smem) != sb) return;
  const int tid = threadIdx.x, lane = tid & 31;
  const int warp = __shfl_sync(~0u, tid >> 5, 0);
  if (tid == 32) {
    asm volatile("prefetch.tensormap [%0];" ::"l"(&p.mapX) : "memory");
    asm volatile("prefetch.tensormap [%0];" ::"l"(&p.mapW3) : "memory");
  }
  const int cta = blockIdx.x - (gridDim.x == NCTA + 4 ? 0 : 4);
  if ((unsigned)cta >= NCTA) {
    if (blockIdx.x < NCTA + 4) colsum_cta(p, sb, blockIdx.x & 3, tid);
    return;
  }
  const int rb = ((cta >> 4) & 3) * 4 + ((cta >> 2) & 3), hg = (cta >> 6) * 4 + (cta & 3);
  const uint32_t bar = sb + SM_BAR;
  auto ld_x0 = [&](int half, int c) {
    const uint32_t b = bar + 8 * (B_XF + 8 * half + c);
    mbar_expect(b, PG);
    tma_ld(sb + x_page(half, c) * PG, &p.mapX, c * 64, (16 * half + rb) * 64, b);
  };
  auto ld_x1 = [&](int half, int c, int b0) {
    const uint32_t b = bar + 8 * b0;
    mbar_expect(b, PG);
    tma_ld(sb + (8 * half + c) * PG, &p.mapXT, (16 * half + rb) * 64, DM + c * 64, b);
  };
  auto ld_w = [&](int c) {
    const uint32_t b = bar + 8 * (B_WF + c);
    mbar_expect(b, 3 * PG);
    tma_ld3(sb + w_page(c) * PG, &p.mapW3, hg * 64, c * 64, 0, b);
  };

  if (tid == 0) TS(0);
  if (tid == 480) LTS(0);
  if (warp == 0 && elect_one()) {
#pragma unroll
    for (int i = 0; i < B_WF + 2; i++)
      if (bar_first(i)) mbar_init(bar + 8 * i, 1);
    asm volatile("fence.mbarrier_init.release.cluster;" ::: "memory");
    fence_async_smem();
    ld_x0(0, 0);
    ld_w(0); ld_x0(1, 0);
    ld_x0(0, 1); ld_w(1); ld_x0(1, 1);
    TS(1);
  }
  __syncwarp();
  if (warp >= 1 && warp < 8 && elect_one()) {
    if (warp < 4) {
#pragma unroll
      for (int i = 2; i < 8; i++) mbar_init(bar + 8 * (8 * warp - 8 + i), 1);
    } else {
#pragma unroll
      for (int i = 0; i < 12; i++) mbar_init(bar + 8 * (12 * warp - 24 + i), 1);
    }
    asm volatile("fence.mbarrier_init.release.cluster;" ::: "memory");
  }
  if (warp == 15 && elect_one()) {
#pragma unroll
    for (int i = 72; i < B_COUNT; i++) mbar_init(bar + 8 * i, bar_count(i));
    asm volatile("fence.mbarrier_init.release.cluster;" ::: "memory");
  }

  if (warp < 8) {
    bar_sync(0, NTHREADS);
    asm volatile("setmaxnreg.inc.sync.aligned.u32 %0;" ::"n"(R_CONS));
    const int cw = __shfl_sync(~0u, opaque_tid() >> 5, 0);
    const int wg = cw >> 2, w = cw & 3;
    if (tid == 0) TS(2);
#pragma unroll 1
    for (int layer = 0; layer < 2; layer++) {
      attn_phase(p, sb, layer, rb, hg, wg, w);
      uint32_t A0[68], A1[68];
      proj_phase(p, sb, layer, rb, hg, A0, A1);
      conv_phase(p, sb, layer, cta, A0, A1);
    }
    if (wg == 0) mbar_wait(bar + 8 * (B_TF + 1), 0);
    if (tid == 128) TS(8);
    final_tile(p, sb + (16 + wg) * PG, 256 * wg + 32 * (cta >> 4), 1024 + 64 * (cta & 15), 2 + wg);
    if (tid == 128) TS(9);
    if (tid == 128) LTS(1);
    if (tid == 0) LTE();
  } else if (warp < 12) {
    asm volatile("setmaxnreg.dec.sync.aligned.u32 %0;" ::"n"(R_HELP));
    const int ht = tid - 256;
    {
      unsigned ep0 = 0;
      if (ht == 0) ep0 = ld_relaxed(&g_cnt[C_CS * 32]);
      const bf16 dsk = p.dskip[cv_chan(cta, ht & 3)];
      const ModeIn in0 = load_modes(p, cv_chan(cta, ht >> 6), ht & 63), in1 = load_modes(p, cv_chan(cta, 2 + (ht >> 6)), ht & 63);
      if (ht < 48) sts128f(sb + SM_STG + ht * 16, 0.f, 0.f, 0.f, 1.f);
      bar_sync(0, NTHREADS);
      if (ht == 0) {
        sts32(sb + SM_EP, ep0);
        mbar_arrive(bar + 8 * B_EP);
      }
      if (ht >= 124) sts16(sb + SM_RED + 24 + 2 * (ht & 3), __bfloat16_as_ushort(dsk));
      kernel_gen(p, sb, cta, ht, in0, in1);
      if (ht < 48) sts128f(sb + SM_KGT + ht * 16, 0.f, 0.f, 0.f, 1.f);
      fence_async_smem();
      bar_sync(4, 128);
      if (ht == 0) mbar_arrive(bar + 8 * B_KG);
    }
#pragma unroll 1
    for (int layer = 0; layer < 2; layer++) {
      const int early = LPRE && layer;
      if (early) mbar_wait(bar + 8 * (B_DN + 13), 1);
      mbar_wait(bar + 8 * (early ? XGATE : B_PDONE), layer);
      expand_taps(sb, opaque_tid() - 256, early);
      mbar_arrive(bar + 8 * B_PE);
      TSW(0);
      mbar_wait(bar + 8 * B_PDONE, layer);
      expand_far(sb, opaque_tid() - 256);
      {
        const int i = opaque_tid() - 256;
        if (i < 32) sts128(sb + cv_u(i >> 3) + ((i >> 2) & 1) * CV_UH + (128 + (i & 3)) * 16, make_uint4(0, 0, 0, 0));
        mbar_wait(bar + 8 * B_RC, layer);
        mbar_wait(bar + 8 * B_GB, layer);
        TSW(13);
        conv_prep<0>(sb, layer, cta, i);
        mbar_arrive(bar + 8 * B_U);
      }
      mbar_wait(bar + 8 * (B_PDONE + 1), layer);
      bar_sync(4, 128);
#pragma unroll 1
      for (int lc = 0; lc < 4; lc += 2) {
        conv_sums(sb, lc, opaque_tid() - 256);
        TSW(1 + lc);
      }
      fence_async_smem();
      mbar_arrive(bar + 8 * B_S);
      mbar_wait(bar + 8 * (B_GB + 1), layer);
      conv_prep<1>(sb, layer, cta, opaque_tid() - 256);
      mbar_arrive(bar + 8 * B_U1);
      TSW(4);
      if (layer == 0) {
        const int c = __shfl_sync(~0u, (opaque_tid() >> 5) & 3, 0);
        int phase = 0;
#pragma unroll 1
        for (int k = 0; k < 3; k++) {
          const int page = (k ? 4 + 4 * k : 0) + c, b = B_XR + 4 * (k & 1) + c;
          const uint32_t a = sb + page * PG + lane * 128 + (lane & 7) * 16 + (lane >> 3) * 4;
          int it = k == 2 ? phase : 0;
#pragma unroll 1
          for (; it < MAX_RETRY; it++) {
            mbar_wait(bar + 8 * b, it & 1);
            const uint32_t v0 = lds32(a), v1 = lds32(a + 4096);
            if (__all_sync(~0u, v0 != UNSET && v1 != UNSET)) break;
            if (elect_one()) { fence_async_smem(); ld_x1(page >> 3, page & 7, b); }
            __syncwarp();
            RETRY(3);
          }
          if (k == 0) phase = it + 1;
          if (lane == 0) mbar_arrive(bar + 8 * (B_XF + page));
        }
      }
    }
    mbar_wait(bar + 8 * B_TF, 0);
#pragma unroll 1
    for (int k = 0; k < 2; k++) final_tile(p, sb + 18 * PG + k * 4096, 256 * k + 32 * (cta >> 4), 64 * (cta & 15), 4);
    if (ht == 0) LTE();
  } else {
    asm volatile("setmaxnreg.dec.sync.aligned.u32 %0;" ::"n"(R_AGENT));
    bar_sync(0, NTHREADS);
    auto done = [&](int half, int c, int layer) { mbar_wait(bar + 8 * (B_DN + 8 * half + c), layer); };
    auto publish = [&](int layer, int k) {
      mbar_wait(bar + 8 * (B_PUB + k), layer);
      red_relaxed(&g_cnt[(layer ? C_F + 8 * k + (cta >> 4) : C_C + k) * 32]);
      if (!layer && k == 0) red_release(&g_cnt[(C_C + 3) * 32]);
      TS(16 + layer * 56 + 40 + 7 + k);
    };
    if (warp == 12) {
      if (elect_one()) {
#pragma unroll 1
        for (int layer = 0; layer < 2; layer++) {
          auto ld_xe = [&](int c) {
            const uint32_t b = bar + 8 * (B_XF + c);
            mbar_expect(b, PG);
            if (layer == 0) tma_ld(sb + x_page(0, c) * PG, &p.mapX, c * 64, rb * 64, b);
            else tma_ld(sb + x_page(0, c) * PG, &p.mapXT, rb * 64, DM + c * 64, b);
          };
          if (layer == 0) {
            ld_x0(0, 2); ld_w(2); ld_x0(1, 2);
            if (hg >= 3) {
              mbar_expect(bar + 8 * B_SC, PG);
              tma_ld(sb + P_R * PG, &p.mapX, hg * 64, rb * 64, bar + 8 * B_SC);
            }
            if (rb < 4) tma_prefetch3(&p.mapW3, hg * 64, (4 + rb) * 64, 0);
            ld_x0(0, 3); ld_w(3); ld_x0(1, 3); ld_x0(0, 4); ld_x0(1, 4);
            done(0, 0, 0); done(1, 0, 0);
            ld_w(4);
            ld_x0(1, 5); ld_x0(1, 6); ld_x0(1, 7);
            done(0, 1, 0); done(1, 1, 0);
            ld_w(5);
            if (rb < 8) tma_prefetch5(&p.mapWo, hg * 64, rb * 2);
            done(0, 2, 0);
            fence_async_smem();
            ld_xe(5); ld_xe(6); ld_xe(7);
          } else {
            mbar_wait(bar + 8 * B_PDONE, 0);
            mbar_wait(bar + 8 * (B_PDONE + 1), 0);
            mbar_wait(bar + 8 * (WPRE == 1 ? B_U : B_GB + 1), 0);
            ld_w(0); ld_w(1);
            mbar_wait(bar + 8 * B_U1, 0);
            fence_async_smem();
            ld_w(2);
            mbar_wait(bar + 8 * (B_PUB + 2), 0);
            fence_async_smem();
            ld_w(3);
            spin_until(&g_cnt[(C_C + 3) * 32], ((lds32(sb + SM_EP) / NCTA) + 1) * NCTA);
            fence_async_global();
            if (hg >= 3) {
              mbar_expect(bar + 8 * B_SC, PG);
              tma_ld(sb + P_R * PG, &p.mapXT, rb * 64, DM + hg * 64, bar + 8 * B_SC);
            }
            ld_xe(4);
            done(0, 2, 1);
            fence_async_smem();
            ld_xe(5); ld_xe(6); ld_xe(7);
            done(1, 0, 1);
            ld_w(4);
            done(1, 1, 1);
            ld_w(5);
          }
          done(1, 2, layer);
          fence_async_smem();
          ld_w(6); ld_w(7);
          auto ld_res = [&](int half) {
            const uint32_t b = bar + 8 * (B_RF + half);
            mbar_expect(b, PG);
            if (layer == 0) tma_ld(sb + (half ? 2 : P_R) * PG, &p.mapX, hg * 64, (16 * half + rb) * 64, b);
            else tma_ld(sb + (half ? 2 : P_R) * PG, &p.mapXT, (16 * half + rb) * 64, DM + hg * 64, b);
          };
          done(0, 4, layer); done(1, 3, layer);
          fence_async_smem();
          mbar_expect(bar + 8 * B_WOF, 8 * PG);
#pragma unroll 1
          for (int c = 0; c < 8; c++) {
            if (c == 5) { ld_res(0); done(1, 4, layer); }
            tma_ld5(sb + wo_page(c) * PG, &p.mapWo, hg * 64, c * 2, bar + 8 * B_WOF);
          }
          done(0, 7, layer);
          fence_async_global();
          ld_res(1);
          if (layer) mbar_wait(bar + 8 * B_RS, 0);
          fence_async_global();
#pragma unroll
          for (int half = 0; half < 2; half++) {
            float* stats = g_stats + (layer * 32 + 16 * half + rb) * 192;
            unsigned* cnt = &g_cnt[(C_G + 2 * layer + half) * 32];
            mbar_wait(bar + 8 * (B_STG + half), layer);
            tma_st(&p.mapXT, (16 * half + rb) * 64, 2 * layer * DM + hg * 64, sb + (P_R + half) * PG);
            bulk_red_add_f32(stats, sb + (half ? SM_KGT : SM_STG), 768);
            bulk_commit();
            red_relaxed(cnt);
            if (half == 0) mbar_arrive(bar + 8 * B_PG);
            bulk_wait_read();
            mbar_arrive(bar + 8 * (B_PST + half));
          }
        }
      }
    } else if (warp == 13) {
      mbar_wait(bar + 8 * B_EP, 0);
      const unsigned e1 = (lds32(sb + SM_EP) / NCTA) + 1;
      auto ld_o = [&](int layer) {
#pragma unroll 1
        for (int half = 0; half < 2; half++) {
          done(1, 7, layer);
          mbar_wait(bar + 8 * B_OST, layer);
          if (half) mbar_wait(bar + 8 * (B_OST + 1), layer);
          fence_async_smem();
#pragma unroll
          for (int c = 0; c < 4; c++) mbar_expect(bar + 8 * (B_OF + 4 * half + c), 2 * PG);
          spin_hint(&g_cnt[(C_O + layer * 32 + 16 * half + rb) * 32], e1 * 32);
#pragma unroll
          for (int c = 0; c < 4; c++) {
            if (LPRE && c == 2 && half && layer) { mbar_wait(bar + 8 * B_AL, 0); fence_async_smem(); }
            bulk_ld(sb + o_page(half, c) * PG, g_O + ((layer * 32 + 16 * half + rb) * 4 + c) * PG, 2 * PG, bar + 8 * (B_OF + 4 * half + c));
          }
        }
      };
      if (elect_one()) {
        mbar_wait(bar + 8 * (B_WF + 2), 0);
        asm volatile("prefetch.tensormap [%0];" ::"l"(&p.mapXT) : "memory");
        asm volatile("prefetch.tensormap [%0];" ::"l"(&p.mapWo) : "memory");
        spin_until(&g_cnt[C_Z * 32], e1 * NCTA);
        mbar_arrive(bar + 8 * B_ZF);
        TS(3);
        ld_o(0);
#pragma unroll 1
        for (int k = 0; k < 3; k++) {
          mbar_wait(bar + 8 * (B_PUB + k), 0);
          if (k == 2) {
#pragma unroll 1
            for (int c = 0; c < 4; c++) mbar_wait(bar + 8 * (B_XF + c), 1);
          }
          fence_async_smem();
          spin_hint(&g_cnt[(C_C + k) * 32], e1 * NCTA);
          TS(10 + k);
#pragma unroll
          for (int c = 0; c < 4; c++) ld_x1(k != 0, (k & 2) * 2 + c, B_XR + 4 * (k & 1) + c);
        }
        ld_o(1);
#pragma unroll 1
        for (int k = 0; k < 2; k++) {
          mbar_wait(bar + 8 * (B_PUB + k), 1);
          spin_hint(&g_cnt[(C_F + 8 * k + (cta >> 4)) * 32], e1 * 16);
          mbar_arrive(bar + 8 * (B_TF + k));
        }
      }
    } else if (warp == 14) {
      mbar_wait(bar + 8 * B_EP, 0);
      const unsigned e1 = (lds32(sb + SM_EP) / NCTA) + 1;
      done(0, 1, 0);
      {
        const uint2* cp = g_colsum + (hg * 192 + lane);
        uint2 v[6];
        bool ok;
        int it = 0;
        do {
          ok = true;
#pragma unroll
          for (int i = 0; i < 6; i++) {
            asm volatile("ld.relaxed.gpu.global.v2.u32 {%0,%1}, [%2];" : "=r"(v[i].x), "=r"(v[i].y) : "l"(cp + 32 * i) : "memory");
            ok = ok && v[i].y == e1;
          }
          if (++it > (1 << 22)) __trap();
        } while (!__all_sync(~0u, ok));
#pragma unroll
        for (int i = 0; i < 6; i++) sts32f(sb + SM_CS + 4 * (lane + 32 * i), __uint_as_float(v[i].x));
      }
      __syncwarp();
      if (elect_one()) {
        mbar_wait(bar + 8 * B_ZF, 0);
        mbar_arrive(bar + 8 * B_LN);
        red_relaxed(&g_cnt[C_CS * 32]);
        TS(13);
#pragma unroll 1
        for (int i = 0; i < 4; i++) {
          const int layer = i >> 1;
          mbar_wait(bar + 8 * (B_PST + (i & 1)), layer);
          const uint32_t b = bar + 8 * (B_GB + 1);
          const bf16* xin = g_xT + ((size_t)2 * layer * DM + 2 * cta) * LSEQ + 1024;
          if (i & 1) {
            fence_async_smem();
            mbar_expect(b, 12288 + PG);
          }
          spin_hint(&g_cnt[(C_G + i) * 32], e1 * NCTA);
          if (i & 1) {
            bulk_ld(sb + CV_ST, g_stats + (layer * 32 + 16) * 192, 12288, b);
#pragma unroll
            for (int lc = 0; lc < 4; lc++) bulk_ld(sb + cv_x(1, lc), xin + cv_chan(0, lc) * LSEQ, 2048, b);
            TS(14 + layer);
            publish(layer, 1);
          } else {
            mbar_arrive(bar + 8 * B_GB);
          }
        }
      }
    } else {
      const uint4 u = make_uint4(UNSET, UNSET, UNSET, UNSET);
      if (lane < 24) stg128((uint4*)g_stats + cta * 24 + lane, make_uint4(0, 0, 0, 0));
      if (lane < 16) stg128(g_rows + LSEQ + cta * 16 + lane, make_uint4(0, 0, 0, 0));
#pragma unroll 4
      for (int i = 0; i < 16; i++) stg128(g_halo + cta * 512 + 32 * i + lane, u);
#pragma unroll 4
      for (int i = 0; i < 16; i++) stg128(((i & 8) ? (uint4*)g_xT : (uint4*)g_O) + cta * 1024 + (i & 7) * 128 + (lane >> 1) * 8 + (lane & 1), u);
      __syncwarp();
      if (elect_one()) red_release(&g_cnt[C_Z * 32]);
      __syncwarp();
#pragma unroll 1
      for (int layer = 0; layer < 2; layer++) {
        auto reset_done = [&](int s) {
          spin_until(&g_cnt[(C_R + s) * 32], (lds32(sb + SM_EP) / NCTA) * 4 + 4);
          mbar_arrive(bar + 8 * (s == 1 ? B_LN : s == 2 ? B_RS : B_RC));
          if (s) TS(16 + 40 + 9 + s);
        };
        if (layer && elect_one()) reset_done(1);
        __syncwarp();
#pragma unroll 1
        for (int half = 0; half < 2; half++) {
          done(half, 2, layer);
          const uint4* src = g_rows + (layer * LSEQ + (16 * half + rb) * 64 + (opaque_tid() & 31));
          uint4 a, b;
          int it = 0;
          do {
            a = ld_tagged(src); b = ld_tagged(src + 32);
          } while (!__all_sync(~0u, (a.z | a.w) == __float_as_uint(8.f) && (b.z | b.w) == __float_as_uint(8.f)) && ++it < (1 << 20));
          float m0 = __uint_as_float(a.x) * (1.f / DM), m1 = __uint_as_float(b.x) * (1.f / DM);
          float r0 = rsqrt_approx(fmaxf(__uint_as_float(a.y) * (1.f / DM) - m0 * m0, 0.f) + 1e-5f);
          float r1 = rsqrt_approx(fmaxf(__uint_as_float(b.y) * (1.f / DM) - m1 * m1, 0.f) + 1e-5f);
          if (half) done(0, 7, layer);
          const uint32_t dst = sb + ln_off(half) + ((lane >> 4) * 8 + (lane & 7)) * 16 + (lane & 8);
          asm volatile("st.shared.v2.f32 [%0], {%1,%2};" ::"r"(dst), "f"(m0), "f"(r0) : "memory");
          asm volatile("st.shared.v2.f32 [%0], {%1,%2};" ::"r"(dst + 256), "f"(m1), "f"(r1) : "memory");
          __syncwarp();
          if (elect_one()) { mbar_arrive(bar + 8 * (B_LN + half)); TS(16 + layer * 56 + 40 + 14 + half); }
        }
        if (layer && lane < 16) stg128(g_rows + cta * 16 + (opaque_tid() & 31), make_uint4(0, 0, 0, 0));
        if (elect_one()) {
          if (layer) reset_done(2);
          reset_done(3 * layer);
          publish(layer, 0);
          if (!layer) publish(layer, 2);
        }
        __syncwarp();
      }
    }
  }
}

typedef CUresult (*EncodeFn)(CUtensorMap*, CUtensorMapDataType, cuuint32_t, void*, const cuuint64_t*, const cuuint64_t*,
                             const cuuint32_t*, const cuuint32_t*, CUtensorMapInterleave, CUtensorMapSwizzle,
                             CUtensorMapL2promotion, CUtensorMapFloatOOBfill);

static void make_map(EncodeFn enc, CUtensorMap* m, void* ptr, uint64_t cols, uint64_t rows, uint32_t box_rows) {
  cuuint64_t dims[2] = {cols, rows};
  cuuint64_t strides[1] = {cols * 2};
  cuuint32_t box[2] = {64, box_rows};
  cuuint32_t es[2] = {1, 1};
  enc(m, CU_TENSOR_MAP_DATA_TYPE_BFLOAT16, 2, ptr, dims, strides, box, es, CU_TENSOR_MAP_INTERLEAVE_NONE,
      CU_TENSOR_MAP_SWIZZLE_128B, CU_TENSOR_MAP_L2_PROMOTION_L2_128B, CU_TENSOR_MAP_FLOAT_OOB_FILL_NONE);
}
static void make_map3(EncodeFn enc, CUtensorMap* m, void* ptr, uint64_t d0, uint64_t cols, uint64_t rows, uint64_t blk_stride,
                      uint64_t nblocks, uint32_t nblk) {
  cuuint64_t dims[3] = {d0, rows, nblocks};
  cuuint64_t strides[2] = {cols * 2, blk_stride * 2};
  cuuint32_t box[3] = {64, 64, nblk};
  cuuint32_t es[3] = {1, 1, 1};
  enc(m, CU_TENSOR_MAP_DATA_TYPE_BFLOAT16, 3, ptr, dims, strides, box, es, CU_TENSOR_MAP_INTERLEAVE_NONE,
      CU_TENSOR_MAP_SWIZZLE_128B, CU_TENSOR_MAP_L2_PROMOTION_L2_128B, CU_TENSOR_MAP_FLOAT_OOB_FILL_NONE);
}

extern "C" void kernel_launch(void* const* d_in, const int* in_sizes, int n_in, void* d_out, int out_size) {
  static Params prm;
  static void* cached[13] = {nullptr};
  static bool attr_done = false;
  static int grid = NCTA + 4;
  bool same = attr_done && cached[12] == d_out;
  for (int i = 0; i < 12 && same; i++) same = cached[i] == d_in[i];
  if (!same) {
    void* fn = nullptr;
    cudaDriverEntryPointQueryResult qr;
    cudaGetDriverEntryPoint("cuTensorMapEncodeTiled", &fn, cudaEnableDefault, &qr);
    EncodeFn enc = (EncodeFn)fn;
    void* pXT;
    cudaGetSymbolAddress(&pXT, g_xT);
    make_map(enc, &prm.mapX, d_in[0], DM, LSEQ, 64);
    make_map(enc, &prm.mapXT, pXT, LSEQ, 4 * DM, 64);
    {
      cuuint64_t dims[5] = {DM, 2, 4, 4, 16};
      cuuint64_t strides[4] = {DM * 2, 8 * DM * 2, 2 * DM * 2, 32 * DM * 2};
      cuuint32_t box[5] = {64, 2, 4, 4, 2};
      cuuint32_t es[5] = {1, 1, 1, 1, 1};
      enc(&prm.mapWo, CU_TENSOR_MAP_DATA_TYPE_BFLOAT16, 5, d_in[2], dims, strides, box, es, CU_TENSOR_MAP_INTERLEAVE_NONE,
          CU_TENSOR_MAP_SWIZZLE_128B, CU_TENSOR_MAP_L2_PROMOTION_L2_128B, CU_TENSOR_MAP_FLOAT_OOB_FILL_NONE);
    }
    make_map3(enc, &prm.mapW3, d_in[1], DM, 3 * DM, DM, DM, 3, 3);
    prm.out = (bf16*)d_out;
    prm.a_re = (const bf16*)d_in[4]; prm.a_im = (const bf16*)d_in[5];
    prm.b_re = (const bf16*)d_in[6]; prm.b_im = (const bf16*)d_in[7];
    prm.c_re = (const bf16*)d_in[8]; prm.c_im = (const bf16*)d_in[9];
    prm.log_dt = (const bf16*)d_in[10]; prm.dskip = (const bf16*)d_in[11];
    int dev = 0, sms = 0;
    cudaGetDevice(&dev);
    cudaDeviceGetAttribute(&sms, cudaDevAttrMultiProcessorCount, dev);
    grid = sms >= NCTA + 4 ? NCTA + 4 : NCTA + 5;
    cudaFuncSetAttribute(fused_kernel, cudaFuncAttributeMaxDynamicSharedMemorySize, SM_TOTAL);
    for (int i = 0; i < 12; i++) cached[i] = d_in[i];
    cached[12] = d_out;
    attr_done = true;
  }
  fused_kernel<<<grid, NTHREADS, SM_TOTAL>>>(prm);
}
```

```cpp
#include <cuda_runtime.h>
#include <cuda_bf16.h>
#include <cuda.h>
#include <stdint.h>

typedef __nv_bfloat16 bf16;

constexpr int LSEQ = 2048;
constexpr int DM = 512;
constexpr int NCTA = 128;
constexpr int NTHREADS = 512;
#define R_CONS 200
#define R_HELP 88
#define R_AGENT 24
#define TURN0 4
#define TURN1 4

constexpr int PG = 8192;
constexpr int P_R = 25;
__host__ __device__ constexpr int x_page(int half, int c) { return half ? 8 + c : c < 5 ? c : c - 5; }
__host__ __device__ constexpr int w_page(int c) { return (c & 3) < 3 ? 16 + 3 * (c & 3) : c < 4 ? 5 : 8; }
__host__ __device__ constexpr int wo_page(int c) { return c < 5 ? 3 + c : 11 + c; }
__host__ __device__ constexpr int o_page(int half, int pair) { return half ? (pair ? 25 - 2 * pair : 0) : 8 + 2 * pair; }
constexpr int SM_KGB = (P_R + 1) * PG;
constexpr int SM_KC = 27 * PG;
constexpr int KC_STRIDE = 648;
__host__ __device__ constexpr int kc_off(int lc) { return SM_KC + (lc & 1) * 2 * KC_STRIDE + (lc < 2 ? 3328 : 0); }
constexpr int SM_KGT = SM_KC + 3328 + 2592;
constexpr int SM_CS = SM_KGT + 2048;
constexpr int SM_RED = SM_CS + 768;
constexpr int SM_EP = SM_RED + 16;
constexpr int SM_STG = SM_RED + 32;
constexpr int SM_LN = SM_STG + 768;
__host__ __device__ constexpr int ln_off(int half) { return half ? PG + 4096 : SM_LN; }
constexpr int SM_BAR = SM_LN + 512;
constexpr int SM_TS = SM_BAR + 704;
constexpr int SM_TOTAL = SM_TS + 512;
static_assert(SM_TOTAL <= 232448 && SM_STG % 16 == 0 && SM_KGT % 16 == 0, "shared memory");

constexpr int CV_UH = 140 * 16;
__host__ __device__ constexpr int cv_u(int lc) { return (8 + 2 * lc) * PG; }
__host__ __device__ constexpr int cv_pe(int lc, int early) { return early ? 19 * PG + lc * 4480 : cv_u(lc) + 4480; }
__host__ __device__ constexpr int cv_pb1(int lc, int w) { return w ? cv_u(lc) + 8960 + (w - 1) * 2048 : 7 * PG + lc * 2048; }
__host__ __device__ constexpr int cv_fa(int lc) { return cv_pb1(lc, 1) + 128; }
__host__ __device__ constexpr int cv_dump(int lc) { return cv_u(lc) + 16256; }
__host__ __device__ constexpr int cv_pb0(int lc, int w) { return lc * PG + w * 2048; }
__host__ __device__ constexpr int cv_se(int lc) { return 5 * PG + lc * 4096; }
__host__ __device__ constexpr int cv_so(int lc) { return cv_se(lc) + 2048; }
__host__ __device__ constexpr int cv_x(int half, int lc) { return (P_R + half) * PG + lc * 2048; }
constexpr int CV_ST = 22 * PG;
__host__ __device__ constexpr int cv_chan(int cta, int lc) { return 2 * cta + (lc & 1) + 256 * (lc >> 1); }

enum {
  B_XF = 0,
  B_WF = 16,
  B_OF = 24,
  B_DN = 32,
  B_PG = 46,
  B_XR = 48,
  B_RF = 56,
  B_PST = 58,
  B_GB = 60,
  B_TF = 62,
  B_RT = 64,
  B_RS = 66,
  B_RC = 67,
  B_WOF = 68,
  B_ZF = 69,
  B_EP = 70,
  B_KG = 71,
  B_SC = 37,
  B_LN = 72,
  B_END = 38,
  B_STG = 74,
  B_OST = 76,
  B_PDONE = 78,
  B_PE = 80,
  B_U = 81,
  B_U1 = 82,
  B_PUB = 83,
  B_AL = 86,
  B_COUNT = 87
};

enum {
  C_CS = 0,
  C_G = 1,
  C_C = 5,
  C_O = 21,
  C_Z = 85,
  C_R = 86,
  C_F = 90,
  C_COUNT = 106
};

__device__ unsigned g_cnt[C_COUNT * 32];
__device__ __align__(1024) bf16 g_O[2 * LSEQ * DM];
__device__ __align__(1024) bf16 g_xT[4 * DM * LSEQ];
__device__ __align__(1024) float g_stats[2 * 32 * 192];
__device__ __align__(1024) uint2 g_colsum[3 * DM];
__device__ __align__(1024) uint4 g_halo[32 * 8 * 256];
__device__ __align__(1024) uint4 g_rows[2 * LSEQ];
#define TS(i) do { } while (0)
#define TSW(k) do { if ((threadIdx.x & 127) == 0) TS(16 + layer * 56 + (threadIdx.x >> 7) * 20 + (k)); } while (0)
#define TSG(k) do { } while (0)

#define RETRY(i) do { } while (0)
#define LTS(i) do { } while (0)
#define LTE() do { } while (0)

struct Params {
  CUtensorMap mapX, mapW3, mapXT, mapWo;
  bf16* out;
  const bf16 *a_re, *a_im, *b_re, *b_im, *c_re, *c_im, *log_dt, *dskip;
};

__device__ __forceinline__ uint32_t s32(const void* p) { return (uint32_t)__cvta_generic_to_shared(p); }
__device__ __forceinline__ void mbar_init(uint32_t b, int c) { asm volatile("mbarrier.init.shared::cta.b64 [%0], %1;" ::"r"(b), "r"(c) : "memory"); }
__device__ __forceinline__ void mbar_expect(uint32_t b, int bytes) { asm volatile("mbarrier.arrive.expect_tx.shared::cta.b64 _, [%0], %1;" ::"r"(b), "r"(bytes) : "memory"); }
__device__ __forceinline__ void mbar_arrive(uint32_t b) { asm volatile("mbarrier.arrive.shared::cta.b64 _, [%0];" ::"r"(b) : "memory"); }
__device__ __forceinline__ void mbar_wait(uint32_t b, int parity) {
  asm volatile("{\n.reg .pred p;\nWAIT_LOOP:\nmbarrier.try_wait.parity.shared::cta.b64 p, [%0], %1;\n@p bra WAIT_DONE;\nbra WAIT_LOOP;\nWAIT_DONE:\n}" ::"r"(b), "r"(parity) : "memory");
}
__device__ __forceinline__ bool mbar_test(uint32_t b, int parity) {
  uint32_t ok;
  asm volatile("{\n.reg .pred p;\nmbarrier.test_wait.parity.shared::cta.b64 p, [%1], %2;\nselp.u32 %0, 1, 0, p;\n}" : "=r"(ok) : "r"(b), "r"(parity) : "memory");
  return ok != 0;
}
__device__ __forceinline__ int opaque_tid() { int v; asm volatile("mov.u32 %0, %%tid.x;" : "=r"(v)); return v; }
__device__ __forceinline__ bool elect_one() {
  uint32_t r;
  asm volatile("{\n.reg .pred p;\nelect.sync _|p, 0xffffffff;\nselp.u32 %0, 1, 0, p;\n}" : "=r"(r));
  return r != 0;
}
__device__ __forceinline__ void tma_ld(uint32_t dst, const CUtensorMap* m, int c0, int c1, uint32_t bar) {
  asm volatile("cp.async.bulk.tensor.2d.shared::cluster.global.mbarrier::complete_tx::bytes [%0], [%1, {%3, %4}], [%2];"
               ::"r"(dst), "l"(m), "r"(bar), "r"(c0), "r"(c1) : "memory");
}
__device__ __forceinline__ void tma_ld3(uint32_t dst, const CUtensorMap* m, int c0, int c1, int c2, uint32_t bar) {
  asm volatile("cp.async.bulk.tensor.3d.shared::cluster.global.mbarrier::complete_tx::bytes [%0], [%1, {%3, %4, %5}], [%2];"
               ::"r"(dst), "l"(m), "r"(bar), "r"(c0), "r"(c1), "r"(c2) : "memory");
}
__device__ __forceinline__ void tma_ld5(uint32_t dst, const CUtensorMap* m, int c0, int c4, uint32_t bar) {
  asm volatile("cp.async.bulk.tensor.5d.shared::cluster.global.mbarrier::complete_tx::bytes [%0], [%1, {%3, 0, 0, 0, %4}], [%2];"
               ::"r"(dst), "l"(m), "r"(bar), "r"(c0), "r"(c4) : "memory");
}
__device__ __forceinline__ void tma_prefetch5(const CUtensorMap* m, int c0, int c4) {
  asm volatile("cp.async.bulk.prefetch.tensor.5d.L2.global.tile [%0, {%1, 0, 0, 0, %2}];" ::"l"(m), "r"(c0), "r"(c4) : "memory");
}
__device__ __forceinline__ void tma_prefetch2(const CUtensorMap* m, int c0, int c1) {
  asm volatile("cp.async.bulk.prefetch.tensor.2d.L2.global.tile [%0, {%1, %2}];" ::"l"(m), "r"(c0), "r"(c1) : "memory");
}
__device__ __forceinline__ void tma_prefetch3(const CUtensorMap* m, int c0, int c1, int c2) {
  asm volatile("cp.async.bulk.prefetch.tensor.3d.L2.global.tile [%0, {%1, %2, %3}];" ::"l"(m), "r"(c0), "r"(c1), "r"(c2) : "memory");
}
__device__ __forceinline__ void tma_st(const CUtensorMap* m, int c0, int c1, uint32_t src) {
  asm volatile("cp.async.bulk.tensor.2d.global.shared::cta.bulk_group [%0, {%2, %3}], [%1];" ::"l"(m), "r"(src), "r"(c0), "r"(c1) : "memory");
}
__device__ __forceinline__ void bulk_ld(uint32_t dst, const void* src, int bytes, uint32_t bar) {
  asm volatile("cp.async.bulk.shared::cluster.global.mbarrier::complete_tx::bytes [%0], [%1], %2, [%3];" ::"r"(dst), "l"(src), "r"(bytes), "r"(bar) : "memory");
}
__device__ __forceinline__ void bulk_st(void* dst, uint32_t src, int bytes) {
  asm volatile("cp.async.bulk.global.shared::cta.bulk_group [%0], [%1], %2;" ::"l"(dst), "r"(src), "r"(bytes) : "memory");
}
__device__ __forceinline__ void bulk_red_add_f32(void* dst, uint32_t src, int bytes) {
  asm volatile("cp.reduce.async.bulk.global.shared::cta.bulk_group.add.f32 [%0], [%1], %2;" ::"l"(dst), "r"(src), "r"(bytes) : "memory");
}
__device__ __forceinline__ void bulk_commit() { asm volatile("cp.async.bulk.commit_group;" ::: "memory"); }
__device__ __forceinline__ void bulk_wait_all() { asm volatile("cp.async.bulk.wait_group 0;" ::: "memory"); }
__device__ __forceinline__ void fence_async_smem() { asm volatile("fence.proxy.async.shared::cta;" ::: "memory"); }
__device__ __forceinline__ void fence_async_global() { asm volatile("fence.proxy.async.global;" ::: "memory"); }
__device__ __forceinline__ void bar_sync(int id, int n) { asm volatile("bar.sync %0, %1;" ::"r"(id), "r"(n) : "memory"); }
__device__ __forceinline__ void bar_arrive(int id, int n) { asm volatile("bar.arrive %0, %1;" ::"r"(id), "r"(n) : "memory"); }
__device__ __forceinline__ bool bar_or(int id, int n, bool v) {
  uint32_t r;
  asm volatile("{\n.reg .pred p, q;\nsetp.ne.u32 q, %3, 0;\nbar.red.or.pred p, %1, %2, q;\nselp.u32 %0, 1, 0, p;\n}" : "=r"(r) : "r"(id), "r"(n), "r"((uint32_t)v) : "memory");
  return r != 0;
}
__device__ __forceinline__ void bulk_wait_read() { asm volatile("cp.async.bulk.wait_group.read 0;" ::: "memory"); }
__device__ __forceinline__ void stg128(void* p, uint4 v) { asm volatile("st.relaxed.gpu.global.v4.u32 [%0], {%1,%2,%3,%4};" ::"l"(p), "r"(v.x), "r"(v.y), "r"(v.z), "r"(v.w) : "memory"); }
constexpr uint32_t UNSET = 0xffffffffu;
constexpr int MAX_RETRY = 1 << 16;
__device__ __forceinline__ void wg_fence() { asm volatile("wgmma.fence.sync.aligned;" ::: "memory"); }
__device__ __forceinline__ void wg_commit() { asm volatile("wgmma.commit_group.sync.aligned;" ::: "memory"); }
template <int N> __device__ __forceinline__ void wg_wait() { asm volatile("wgmma.wait_group.sync.aligned %0;" ::"n"(N) : "memory"); }
__device__ __forceinline__ uint64_t mkdesc(uint32_t addr, uint32_t lbo, uint32_t sbo, int sw) {
  return (uint64_t)((addr & 0x3FFFF) >> 4) | ((uint64_t)(lbo >> 4) << 16) | ((uint64_t)(sbo >> 4) << 32) | ((uint64_t)sw << 62);
}
__device__ __forceinline__ void ldsm4(uint32_t* r, uint32_t a) {
  asm volatile("ldmatrix.sync.aligned.m8n8.x4.shared.b16 {%0,%1,%2,%3}, [%4];" : "=r"(r[0]), "=r"(r[1]), "=r"(r[2]), "=r"(r[3]) : "r"(a) : "memory");
}
__device__ __forceinline__ void ldsm4t(uint32_t* r, uint32_t a) {
  asm volatile("ldmatrix.sync.aligned.m8n8.x4.trans.shared.b16 {%0,%1,%2,%3}, [%4];" : "=r"(r[0]), "=r"(r[1]), "=r"(r[2]), "=r"(r[3]) : "r"(a) : "memory");
}
__device__ __forceinline__ void stsm4(uint32_t a, uint32_t r0, uint32_t r1, uint32_t r2, uint32_t r3) {
  asm volatile("stmatrix.sync.aligned.m8n8.x4.shared.b16 [%0], {%1,%2,%3,%4};" ::"r"(a), "r"(r0), "r"(r1), "r"(r2), "r"(r3) : "memory");
}
__device__ __forceinline__ void stsm4t(uint32_t a, uint32_t r0, uint32_t r1, uint32_t r2, uint32_t r3) {
  asm volatile("stmatrix.sync.aligned.m8n8.x4.trans.shared.b16 [%0], {%1,%2,%3,%4};" ::"r"(a), "r"(r0), "r"(r1), "r"(r2), "r"(r3) : "memory");
}
__device__ __forceinline__ uint32_t movm_t(uint32_t a) { uint32_t r; asm volatile("movmatrix.sync.aligned.m8n8.trans.b16 %0, %1;" : "=r"(r) : "r"(a)); return r; }
__device__ __forceinline__ uint32_t lds32(uint32_t a) { uint32_t v; asm volatile("ld.shared.b32 %0, [%1];" : "=r"(v) : "r"(a) : "memory"); return v; }
__device__ __forceinline__ float2 lds64f(uint32_t a) { float2 v; asm volatile("ld.shared.v2.f32 {%0,%1}, [%2];" : "=f"(v.x), "=f"(v.y) : "r"(a) : "memory"); return v; }
__device__ __forceinline__ float4 lds128f(uint32_t a) { float4 v; asm volatile("ld.shared.v4.f32 {%0,%1,%2,%3}, [%4];" : "=f"(v.x), "=f"(v.y), "=f"(v.z), "=f"(v.w) : "r"(a) : "memory"); return v; }
__device__ __forceinline__ uint4 lds128(uint32_t a) { uint4 v; asm volatile("ld.shared.v4.b32 {%0,%1,%2,%3}, [%4];" : "=r"(v.x), "=r"(v.y), "=r"(v.z), "=r"(v.w) : "r"(a) : "memory"); return v; }
__device__ __forceinline__ void sts128(uint32_t a, uint4 v) { asm volatile("st.shared.v4.b32 [%0], {%1,%2,%3,%4};" ::"r"(a), "r"(v.x), "r"(v.y), "r"(v.z), "r"(v.w) : "memory"); }
__device__ __forceinline__ void sts128f(uint32_t a, float x, float y, float z, float w) { asm volatile("st.shared.v4.f32 [%0], {%1,%2,%3,%4};" ::"r"(a), "f"(x), "f"(y), "f"(z), "f"(w) : "memory"); }
__device__ __forceinline__ void sts32f(uint32_t a, float v) { asm volatile("st.shared.f32 [%0], %1;" ::"r"(a), "f"(v) : "memory"); }
__device__ __forceinline__ void sts16(uint32_t a, uint16_t v) { asm volatile("st.shared.u16 [%0], %1;" ::"r"(a), "h"(v) : "memory"); }
__device__ __forceinline__ uint32_t lds16(uint32_t a) { uint16_t v; asm volatile("ld.shared.u16 %0, [%1];" : "=h"(v) : "r"(a) : "memory"); return v; }
__device__ __forceinline__ uint32_t packbf(float lo, float hi) { uint32_t r; asm("cvt.rn.bf16x2.f32 %0, %1, %2;" : "=r"(r) : "f"(hi), "f"(lo)); return r; }
__device__ __forceinline__ float bf_lo(uint32_t v) { return __uint_as_float(v << 16); }
__device__ __forceinline__ float bf_hi(uint32_t v) { return __uint_as_float(v & 0xffff0000u); }
__device__ __forceinline__ float ex2(float x) { float r; asm("ex2.approx.ftz.f32 %0, %1;" : "=f"(r) : "f"(x)); return r; }
__device__ __forceinline__ float rsqrt_approx(float x) { float r; asm("rsqrt.approx.ftz.f32 %0, %1;" : "=f"(r) : "f"(x)); return r; }
__device__ __forceinline__ float rcp_approx(float x) { float r; asm("rcp.approx.ftz.f32 %0, %1;" : "=f"(r) : "f"(x)); return r; }
__device__ __forceinline__ void mma_bf16(float* d, const uint32_t* a, uint32_t b0, uint32_t b1) {
  asm("mma.sync.aligned.m16n8k16.row.col.f32.bf16.bf16.f32 {%0,%1,%2,%3}, {%4,%5,%6,%7}, {%8,%9}, {%0,%1,%2,%3};"
               : "+f"(d[0]), "+f"(d[1]), "+f"(d[2]), "+f"(d[3]) : "r"(a[0]), "r"(a[1]), "r"(a[2]), "r"(a[3]), "r"(b0), "r"(b1));
}
__device__ __forceinline__ void mma_tf32(float* d, float a0, float a1, float a2, float a3, float b0, float b1) {
  asm("mma.sync.aligned.m16n8k8.row.col.f32.tf32.tf32.f32 {%0,%1,%2,%3}, {%4,%5,%6,%7}, {%8,%9}, {%0,%1,%2,%3};"
               : "+f"(d[0]), "+f"(d[1]), "+f"(d[2]), "+f"(d[3])
               : "r"(__float_as_uint(a0)), "r"(__float_as_uint(a1)), "r"(__float_as_uint(a2)), "r"(__float_as_uint(a3)),
                 "r"(__float_as_uint(b0)), "r"(__float_as_uint(b1)));
}
__device__ __forceinline__ void red_release(unsigned* p) { asm volatile("red.release.gpu.global.add.u32 [%0], 1;" ::"l"(p) : "memory"); }
__device__ __forceinline__ void red_relaxed(unsigned* p) { asm volatile("red.relaxed.gpu.global.add.u32 [%0], 1;" ::"l"(p) : "memory"); }
__device__ __forceinline__ unsigned ld_relaxed(const unsigned* p) { unsigned v; asm volatile("ld.relaxed.gpu.global.u32 %0, [%1];" : "=r"(v) : "l"(p) : "memory"); return v; }
__device__ __forceinline__ void spin_until(const unsigned* p, unsigned target) {
  int it = 0;
  while ((int)(ld_relaxed(p) - target) < 0) {
    if (++it > (1 << 23)) __trap();
  }
}
__device__ __forceinline__ void spin_hint(const unsigned* p, unsigned target) {
  spin_until(p, target);
}
__device__ __forceinline__ uint4 ldcg128(const void* p) { uint4 v; asm volatile("ld.global.cg.v4.b32 {%0,%1,%2,%3}, [%4];" : "=r"(v.x), "=r"(v.y), "=r"(v.z), "=r"(v.w) : "l"(p) : "memory"); return v; }
__device__ __forceinline__ uint4 ld_tagged(const uint4* p) { uint4 v; asm volatile("ld.relaxed.gpu.global.v4.u32 {%0,%1,%2,%3}, [%4];" : "=r"(v.x), "=r"(v.y), "=r"(v.z), "=r"(v.w) : "l"(p) : "memory"); return v; }
__device__ __forceinline__ void st_tagged(uint4* p, uint32_t a, uint32_t b, uint32_t tag) { asm volatile("st.relaxed.gpu.global.v4.u32 [%0], {%1,%2,%3,%2};" ::"l"(p), "r"(a), "r"(tag), "r"(b) : "memory"); }
__device__ __forceinline__ void st_tagged3(uint4* p, uint32_t a, uint32_t b, uint32_t c, uint32_t tag) { asm volatile("st.relaxed.gpu.global.v4.u32 [%0], {%1,%2,%3,%4};" ::"l"(p), "r"(a), "r"(b), "r"(c), "r"(tag) : "memory"); }
__device__ __forceinline__ uint4 poll_tagged(const uint4* p, uint32_t tag) {
  uint4 v = ld_tagged(p);
  int it = 0;
  while (v.y != tag || v.w != tag) {
    if (++it > (1 << 22)) __trap();
    v = ld_tagged(p);
  }
  return v;
}
__device__ __forceinline__ uint32_t hadd2(uint32_t a, uint32_t b) { uint32_t r; asm("add.rn.bf16x2 %0, %1, %2;" : "=r"(r) : "r"(a), "r"(b)); return r; }
__device__ __forceinline__ uint32_t hmul2(uint32_t a, uint32_t b) { uint32_t r; asm("mul.rn.bf16x2 %0, %1, %2;" : "=r"(r) : "r"(a), "r"(b)); return r; }

__device__ __forceinline__ uint32_t hfma2(uint32_t a, uint32_t b, uint32_t c) { uint32_t r; asm("fma.rn.bf16x2 %0, %1, %2, %3;" : "=r"(r) : "r"(a), "r"(b), "r"(c)); return r; }
__device__ __forceinline__ void sts32(uint32_t a, uint32_t v) { asm volatile("st.shared.u32 [%0], %1;" ::"r"(a), "r"(v) : "memory"); }

template <int N> __device__ __forceinline__ void acc_fence(float* a) {
#pragma unroll
  for (int i = 0; i < N; i++) asm volatile("" : "+f"(a[i]) :: "memory");
}

template<int N,int TB> __device__ __forceinline__ void wgmma_rs(float* d, const uint32_t* a, uint64_t db, int sd);
template<int N,int TA,int TB> __device__ __forceinline__ void wgmma_ss(float* d, uint64_t da, uint64_t db, int sd);
template<> __device__ __forceinline__ void wgmma_rs<64,0>(float* d, const uint32_t* a, uint64_t db, int sd) {
  asm volatile("{\n.reg .pred p;\nsetp.ne.b32 p, %37, 0;\nwgmma.mma_async.sync.aligned.m64n64k16.f32.bf16.bf16 {%0,%1,%2,%3,%4,%5,%6,%7,%8,%9,%10,%11,%12,%13,%14,%15,%16,%17,%18,%19,%20,%21,%22,%23,%24,%25,%26,%27,%28,%29,%30,%31}, {%32,%33,%34,%35}, %36, p, 1, 1, 0;\n}\n"
   : "+f"(d[0]),"+f"(d[1]),"+f"(d[2]),"+f"(d[3]),"+f"(d[4]),"+f"(d[5]),"+f"(d[6]),"+f"(d[7]),"+f"(d[8]),"+f"(d[9]),"+f"(d[10]),"+f"(d[11]),"+f"(d[12]),"+f"(d[13]),"+f"(d[14]),"+f"(d[15]),"+f"(d[16]),"+f"(d[17]),"+f"(d[18]),"+f"(d[19]),"+f"(d[20]),"+f"(d[21]),"+f"(d[22]),"+f"(d[23]),"+f"(d[24]),"+f"(d[25]),"+f"(d[26]),"+f"(d[27]),"+f"(d[28]),"+f"(d[29]),"+f"(d[30]),"+f"(d[31])
   : "r"(a[0]), "r"(a[1]), "r"(a[2]), "r"(a[3]), "l"(db), "r"(sd));
}
template<> __device__ __forceinline__ void wgmma_rs<56,0>(float* d, const uint32_t* a, uint64_t db, int sd) {
  asm volatile("{\n.reg .pred p;\nsetp.ne.b32 p, %33, 0;\nwgmma.mma_async.sync.aligned.m64n56k16.f32.bf16.bf16 {%0,%1,%2,%3,%4,%5,%6,%7,%8,%9,%10,%11,%12,%13,%14,%15,%16,%17,%18,%19,%20,%21,%22,%23,%24,%25,%26,%27}, {%28,%29,%30,%31}, %32, p, 1, 1, 0;\n}\n"
   : "+f"(d[0]),"+f"(d[1]),"+f"(d[2]),"+f"(d[3]),"+f"(d[4]),"+f"(d[5]),"+f"(d[6]),"+f"(d[7]),"+f"(d[8]),"+f"(d[9]),"+f"(d[10]),"+f"(d[11]),"+f"(d[12]),"+f"(d[13]),"+f"(d[14]),"+f"(d[15]),"+f"(d[16]),"+f"(d[17]),"+f"(d[18]),"+f"(d[19]),"+f"(d[20]),"+f"(d[21]),"+f"(d[22]),"+f"(d[23]),"+f"(d[24]),"+f"(d[25]),"+f"(d[26]),"+f"(d[27])
   : "r"(a[0]), "r"(a[1]), "r"(a[2]), "r"(a[3]), "l"(db), "r"(sd));
}
template<> __device__ __forceinline__ void wgmma_rs<48,0>(float* d, const uint32_t* a, uint64_t db, int sd) {
  asm volatile("{\n.reg .pred p;\nsetp.ne.b32 p, %29, 0;\nwgmma.mma_async.sync.aligned.m64n48k16.f32.bf16.bf16 {%0,%1,%2,%3,%4,%5,%6,%7,%8,%9,%10,%11,%12,%13,%14,%15,%16,%17,%18,%19,%20,%21,%22,%23}, {%24,%25,%26,%27}, %28, p, 1, 1, 0;\n}\n"
   : "+f"(d[0]),"+f"(d[1]),"+f"(d[2]),"+f"(d[3]),"+f"(d[4]),"+f"(d[5]),"+f"(d[6]),"+f"(d[7]),"+f"(d[8]),"+f"(d[9]),"+f"(d[10]),"+f"(d[11]),"+f"(d[12]),"+f"(d[13]),"+f"(d[14]),"+f"(d[15]),"+f"(d[16]),"+f"(d[17]),"+f"(d[18]),"+f"(d[19]),"+f"(d[20]),"+f"(d[21]),"+f"(d[22]),"+f"(d[23])
   : "r"(a[0]), "r"(a[1]), "r"(a[2]), "r"(a[3]), "l"(db), "r"(sd));
}
template<> __device__ __forceinline__ void wgmma_rs<40,0>(float* d, const uint32_t* a, uint64_t db, int sd) {
  asm volatile("{\n.reg .pred p;\nsetp.ne.b32 p, %25, 0;\nwgmma.mma_async.sync.aligned.m64n40k16.f32.bf16.bf16 {%0,%1,%2,%3,%4,%5,%6,%7,%8,%9,%10,%11,%12,%13,%14,%15,%16,%17,%18,%19}, {%20,%21,%22,%23}, %24, p, 1, 1, 0;\n}\n"
   : "+f"(d[0]),"+f"(d[1]),"+f"(d[2]),"+f"(d[3]),"+f"(d[4]),"+f"(d[5]),"+f"(d[6]),"+f"(d[7]),"+f"(d[8]),"+f"(d[9]),"+f"(d[10]),"+f"(d[11]),"+f"(d[12]),"+f"(d[13]),"+f"(d[14]),"+f"(d[15]),"+f"(d[16]),"+f"(d[17]),"+f"(d[18]),"+f"(d[19])
   : "r"(a[0]), "r"(a[1]), "r"(a[2]), "r"(a[3]), "l"(db), "r"(sd));
}
template<> __device__ __forceinline__ void wgmma_rs<32,0>(float* d, const uint32_t* a, uint64_t db, int sd) {
  asm volatile("{\n.reg .pred p;\nsetp.ne.b32 p, %21, 0;\nwgmma.mma_async.sync.aligned.m64n32k16.f32.bf16.bf16 {%0,%1,%2,%3,%4,%5,%6,%7,%8,%9,%10,%11,%12,%13,%14,%15}, {%16,%17,%18,%19}, %20, p, 1, 1, 0;\n}\n"
   : "+f"(d[0]),"+f"(d[1]),"+f"(d[2]),"+f"(d[3]),"+f"(d[4]),"+f"(d[5]),"+f"(d[6]),"+f"(d[7]),"+f"(d[8]),"+f"(d[9]),"+f"(d[10]),"+f"(d[11]),"+f"(d[12]),"+f"(d[13]),"+f"(d[14]),"+f"(d[15])
   : "r"(a[0]), "r"(a[1]), "r"(a[2]), "r"(a[3]), "l"(db), "r"(sd));
}
template<> __device__ __forceinline__ void wgmma_rs<24,0>(float* d, const uint32_t* a, uint64_t db, int sd) {
  asm volatile("{\n.reg .pred p;\nsetp.ne.b32 p, %17, 0;\nwgmma.mma_async.sync.aligned.m64n24k16.f32.bf16.bf16 {%0,%1,%2,%3,%4,%5,%6,%7,%8,%9,%10,%11}, {%12,%13,%14,%15}, %16, p, 1, 1, 0;\n}\n"
   : "+f"(d[0]),"+f"(d[1]),"+f"(d[2]),"+f"(d[3]),"+f"(d[4]),"+f"(d[5]),"+f"(d[6]),"+f"(d[7]),"+f"(d[8]),"+f"(d[9]),"+f"(d[10]),"+f"(d[11])
   : "r"(a[0]), "r"(a[1]), "r"(a[2]), "r"(a[3]), "l"(db), "r"(sd));
}
template<> __device__ __forceinline__ void wgmma_rs<16,0>(float* d, const uint32_t* a, uint64_t db, int sd) {
  asm volatile("{\n.reg .pred p;\nsetp.ne.b32 p, %13, 0;\nwgmma.mma_async.sync.aligned.m64n16k16.f32.bf16.bf16 {%0,%1,%2,%3,%4,%5,%6,%7}, {%8,%9,%10,%11}, %12, p, 1, 1, 0;\n}\n"
   : "+f"(d[0]),"+f"(d[1]),"+f"(d[2]),"+f"(d[3]),"+f"(d[4]),"+f"(d[5]),"+f"(d[6]),"+f"(d[7])
   : "r"(a[0]), "r"(a[1]), "r"(a[2]), "r"(a[3]), "l"(db), "r"(sd));
}
template<> __device__ __forceinline__ void wgmma_rs<8,0>(float* d, const uint32_t* a, uint64_t db, int sd) {
  asm volatile("{\n.reg .pred p;\nsetp.ne.b32 p, %9, 0;\nwgmma.mma_async.sync.aligned.m64n8k16.f32.bf16.bf16 {%0,%1,%2,%3}, {%4,%5,%6,%7}, %8, p, 1, 1, 0;\n}\n"
   : "+f"(d[0]),"+f"(d[1]),"+f"(d[2]),"+f"(d[3])
   : "r"(a[0]), "r"(a[1]), "r"(a[2]), "r"(a[3]), "l"(db), "r"(sd));
}
template<> __device__ __forceinline__ void wgmma_ss<64,1,0>(float* d, uint64_t da, uint64_t db, int sd) {
  asm volatile("{\n.reg .pred p;\nsetp.ne.b32 p, %34, 0;\nwgmma.mma_async.sync.aligned.m64n64k16.f32.bf16.bf16 {%0,%1,%2,%3,%4,%5,%6,%7,%8,%9,%10,%11,%12,%13,%14,%15,%16,%17,%18,%19,%20,%21,%22,%23,%24,%25,%26,%27,%28,%29,%30,%31}, %32, %33, p, 1, 1, 1, 0;\n}\n"
   : "+f"(d[0]),"+f"(d[1]),"+f"(d[2]),"+f"(d[3]),"+f"(d[4]),"+f"(d[5]),"+f"(d[6]),"+f"(d[7]),"+f"(d[8]),"+f"(d[9]),"+f"(d[10]),"+f"(d[11]),"+f"(d[12]),"+f"(d[13]),"+f"(d[14]),"+f"(d[15]),"+f"(d[16]),"+f"(d[17]),"+f"(d[18]),"+f"(d[19]),"+f"(d[20]),"+f"(d[21]),"+f"(d[22]),"+f"(d[23]),"+f"(d[24]),"+f"(d[25]),"+f"(d[26]),"+f"(d[27]),"+f"(d[28]),"+f"(d[29]),"+f"(d[30]),"+f"(d[31])
   : "l"(da), "l"(db), "r"(sd));
}
template<> __device__ __forceinline__ void wgmma_ss<64,0,1>(float* d, uint64_t da, uint64_t db, int sd) {
  asm volatile("{\n.reg .pred p;\nsetp.ne.b32 p, %34, 0;\nwgmma.mma_async.sync.aligned.m64n64k16.f32.bf16.bf16 {%0,%1,%2,%3,%4,%5,%6,%7,%8,%9,%10,%11,%12,%13,%14,%15,%16,%17,%18,%19,%20,%21,%22,%23,%24,%25,%26,%27,%28,%29,%30,%31}, %32, %33, p, 1, 1, 0, 1;\n}\n"
   : "+f"(d[0]),"+f"(d[1]),"+f"(d[2]),"+f"(d[3]),"+f"(d[4]),"+f"(d[5]),"+f"(d[6]),"+f"(d[7]),"+f"(d[8]),"+f"(d[9]),"+f"(d[10]),"+f"(d[11]),"+f"(d[12]),"+f"(d[13]),"+f"(d[14]),"+f"(d[15]),"+f"(d[16]),"+f"(d[17]),"+f"(d[18]),"+f"(d[19]),"+f"(d[20]),"+f"(d[21]),"+f"(d[22]),"+f"(d[23]),"+f"(d[24]),"+f"(d[25]),"+f"(d[26]),"+f"(d[27]),"+f"(d[28]),"+f"(d[29]),"+f"(d[30]),"+f"(d[31])
   : "l"(da), "l"(db), "r"(sd));
}
template<> __device__ __forceinline__ void wgmma_ss<192,0,1>(float* d, uint64_t da, uint64_t db, int sd) {
  asm volatile("{\n.reg .pred p;\nsetp.ne.b32 p, %98, 0;\nwgmma.mma_async.sync.aligned.m64n192k16.f32.bf16.bf16 {%0,%1,%2,%3,%4,%5,%6,%7,%8,%9,%10,%11,%12,%13,%14,%15,%16,%17,%18,%19,%20,%21,%22,%23,%24,%25,%26,%27,%28,%29,%30,%31,%32,%33,%34,%35,%36,%37,%38,%39,%40,%41,%42,%43,%44,%45,%46,%47,%48,%49,%50,%51,%52,%53,%54,%55,%56,%57,%58,%59,%60,%61,%62,%63,%64,%65,%66,%67,%68,%69,%70,%71,%72,%73,%74,%75,%76,%77,%78,%79,%80,%81,%82,%83,%84,%85,%86,%87,%88,%89,%90,%91,%92,%93,%94,%95}, %96, %97, p, 1, 1, 0, 1;\n}\n"
   : "+f"(d[0]),"+f"(d[1]),"+f"(d[2]),"+f"(d[3]),"+f"(d[4]),"+f"(d[5]),"+f"(d[6]),"+f"(d[7]),"+f"(d[8]),"+f"(d[9]),"+f"(d[10]),"+f"(d[11]),"+f"(d[12]),"+f"(d[13]),"+f"(d[14]),"+f"(d[15]),"+f"(d[16]),"+f"(d[17]),"+f"(d[18]),"+f"(d[19]),"+f"(d[20]),"+f"(d[21]),"+f"(d[22]),"+f"(d[23]),"+f"(d[24]),"+f"(d[25]),"+f"(d[26]),"+f"(d[27]),"+f"(d[28]),"+f"(d[29]),"+f"(d[30]),"+f"(d[31]),"+f"(d[32]),"+f"(d[33]),"+f"(d[34]),"+f"(d[35]),"+f"(d[36]),"+f"(d[37]),"+f"(d[38]),"+f"(d[39]),"+f"(d[40]),"+f"(d[41]),"+f"(d[42]),"+f"(d[43]),"+f"(d[44]),"+f"(d[45]),"+f"(d[46]),"+f"(d[47]),"+f"(d[48]),"+f"(d[49]),"+f"(d[50]),"+f"(d[51]),"+f"(d[52]),"+f"(d[53]),"+f"(d[54]),"+f"(d[55]),"+f"(d[56]),"+f"(d[57]),"+f"(d[58]),"+f"(d[59]),"+f"(d[60]),"+f"(d[61]),"+f"(d[62]),"+f"(d[63]),"+f"(d[64]),"+f"(d[65]),"+f"(d[66]),"+f"(d[67]),"+f"(d[68]),"+f"(d[69]),"+f"(d[70]),"+f"(d[71]),"+f"(d[72]),"+f"(d[73]),"+f"(d[74]),"+f"(d[75]),"+f"(d[76]),"+f"(d[77]),"+f"(d[78]),"+f"(d[79]),"+f"(d[80]),"+f"(d[81]),"+f"(d[82]),"+f"(d[83]),"+f"(d[84]),"+f"(d[85]),"+f"(d[86]),"+f"(d[87]),"+f"(d[88]),"+f"(d[89]),"+f"(d[90]),"+f"(d[91]),"+f"(d[92]),"+f"(d[93]),"+f"(d[94]),"+f"(d[95])
   : "l"(da), "l"(db), "r"(sd));
}
template<> __device__ __forceinline__ void wgmma_ss<192,1,1>(float* d, uint64_t da, uint64_t db, int sd) {
  asm volatile("{\n.reg .pred p;\nsetp.ne.b32 p, %98, 0;\nwgmma.mma_async.sync.aligned.m64n192k16.f32.bf16.bf16 {%0,%1,%2,%3,%4,%5,%6,%7,%8,%9,%10,%11,%12,%13,%14,%15,%16,%17,%18,%19,%20,%21,%22,%23,%24,%25,%26,%27,%28,%29,%30,%31,%32,%33,%34,%35,%36,%37,%38,%39,%40,%41,%42,%43,%44,%45,%46,%47,%48,%49,%50,%51,%52,%53,%54,%55,%56,%57,%58,%59,%60,%61,%62,%63,%64,%65,%66,%67,%68,%69,%70,%71,%72,%73,%74,%75,%76,%77,%78,%79,%80,%81,%82,%83,%84,%85,%86,%87,%88,%89,%90,%91,%92,%93,%94,%95}, %96, %97, p, 1, 1, 1, 1;\n}\n"
   : "+f"(d[0]),"+f"(d[1]),"+f"(d[2]),"+f"(d[3]),"+f"(d[4]),"+f"(d[5]),"+f"(d[6]),"+f"(d[7]),"+f"(d[8]),"+f"(d[9]),"+f"(d[10]),"+f"(d[11]),"+f"(d[12]),"+f"(d[13]),"+f"(d[14]),"+f"(d[15]),"+f"(d[16]),"+f"(d[17]),"+f"(d[18]),"+f"(d[19]),"+f"(d[20]),"+f"(d[21]),"+f"(d[22]),"+f"(d[23]),"+f"(d[24]),"+f"(d[25]),"+f"(d[26]),"+f"(d[27]),"+f"(d[28]),"+f"(d[29]),"+f"(d[30]),"+f"(d[31]),"+f"(d[32]),"+f"(d[33]),"+f"(d[34]),"+f"(d[35]),"+f"(d[36]),"+f"(d[37]),"+f"(d[38]),"+f"(d[39]),"+f"(d[40]),"+f"(d[41]),"+f"(d[42]),"+f"(d[43]),"+f"(d[44]),"+f"(d[45]),"+f"(d[46]),"+f"(d[47]),"+f"(d[48]),"+f"(d[49]),"+f"(d[50]),"+f"(d[51]),"+f"(d[52]),"+f"(d[53]),"+f"(d[54]),"+f"(d[55]),"+f"(d[56]),"+f"(d[57]),"+f"(d[58]),"+f"(d[59]),"+f"(d[60]),"+f"(d[61]),"+f"(d[62]),"+f"(d[63]),"+f"(d[64]),"+f"(d[65]),"+f"(d[66]),"+f"(d[67]),"+f"(d[68]),"+f"(d[69]),"+f"(d[70]),"+f"(d[71]),"+f"(d[72]),"+f"(d[73]),"+f"(d[74]),"+f"(d[75]),"+f"(d[76]),"+f"(d[77]),"+f"(d[78]),"+f"(d[79]),"+f"(d[80]),"+f"(d[81]),"+f"(d[82]),"+f"(d[83]),"+f"(d[84]),"+f"(d[85]),"+f"(d[86]),"+f"(d[87]),"+f"(d[88]),"+f"(d[89]),"+f"(d[90]),"+f"(d[91]),"+f"(d[92]),"+f"(d[93]),"+f"(d[94]),"+f"(d[95])
   : "l"(da), "l"(db), "r"(sd));
}

template <bool TR>
__device__ __forceinline__ void gemm_section(float* acc, float& mean0, float& mean1, float& rstd0, float& rstd1,
                                             uint32_t sb, int blk, int hg, int wg, int w, int lane) {
  constexpr int layer = TR ? 1 : 0;
  constexpr int TURN = TR ? TURN1 : TURN0;
  constexpr int LSTAT = TURN < 4 ? TURN - 1 : 3;
  const uint32_t bar = sb + SM_BAR;
  const int g = lane >> 2, t = lane & 3;
  const bool leader = (w == 0) && (lane == 0);
  const int statpos = hg < 3 ? 1 : wg ? LSTAT : TR ? 3 : 2;
  const bool copy = hg >= 3 && wg == 0;
  const int cut = wg ? TURN : 4;
  auto wait_full = [&](int c) {
    mbar_wait(bar + 8 * (B_XF + 8 * wg + c), layer);
    mbar_wait(bar + 8 * (B_WF + c), layer);
  };
  auto peek = [&](int c) {
    const bool x = mbar_test(bar + 8 * (B_XF + 8 * wg + c), layer), y = mbar_test(bar + 8 * (B_WF + c), layer);
    return x && y;
  };
  const uint64_t da0 = mkdesc(sb, TR ? 8192 : 16, 1024, 1), db0 = mkdesc(sb, 8192, 1024, 1);
  uint32_t xt = wg ? 0xfedcba98u : 0x21043210u;
  uint64_t wt = 0x0816131005161310ull;
  uint64_t da = da0 + ((xt & 15) << 9), db = db0 + (16 << 9);
  auto issue = [&](int c, int first) {
    wg_fence();
#pragma unroll
    for (int ks = 0; ks < 4; ks++) wgmma_ss<192, TR ? 1 : 0, 1>(acc, da + (TR ? ks * 128 : ks * 2), db + ks * 128, !first || ks != 0);
    wg_commit();
    xt >>= 4; wt >>= 8;
    da = da0 + ((xt & 15) << 9); db = db0 + (((uint32_t)wt & 31) << 9);
  };
  wait_full(0);
  bool ready = peek(1);
  issue(0, 1);
  TSW(0);
#pragma unroll 1
  for (int c = 1; c < cut; c++) {
    if (!ready) wait_full(c);
    issue(c, 0);
    ready = peek(c + 1);
    wg_wait<1>();
    if (leader) mbar_arrive(bar + 8 * (B_DN + 8 * wg + c - 1));
    if (wg == 1 && c == cut - 1) {
      wg_wait<0>();
      if (leader) mbar_arrive(bar + 8 * (B_DN + 8 + c));
    }
    if (c == statpos) {
      mbar_wait(bar + 8 * (copy ? B_SC : B_XF + 8 * wg + hg), layer);
      uint32_t A[16];
      const uint32_t xb = sb + (copy ? P_R : 8 * wg + hg) * PG;
#pragma unroll
      for (int ks = 0; ks < 4; ks++) {
        if (!TR) {
          const int row = 16 * w + (lane & 15), kc = 2 * ks + (lane >> 4);
          ldsm4(&A[4 * ks], xb + row * 128 + ((kc ^ (row & 7)) << 4));
        } else {
          const int k = 16 * ks + (lane & 7) + 8 * (lane >> 4), pc = 2 * w + ((lane >> 3) & 1);
          ldsm4t(&A[4 * ks], xb + k * 128 + ((pc ^ (k & 7)) << 4));
        }
      }
      float s0 = 0.f, q0 = 0.f, s1 = 0.f, q1 = 0.f;
#pragma unroll
      for (int i = 0; i < 16; i += 2) {
        const float a = bf_lo(A[i]), b = bf_hi(A[i]), c_ = bf_lo(A[i + 1]), d = bf_hi(A[i + 1]);
        s0 += a + b; q0 = fmaf(a, a, q0); q0 = fmaf(b, b, q0);
        s1 += c_ + d; q1 = fmaf(c_, c_, q1); q1 = fmaf(d, d, q1);
      }
#pragma unroll
      for (int o = 1; o <= 2; o <<= 1) {
        s0 += __shfl_xor_sync(~0u, s0, o); q0 += __shfl_xor_sync(~0u, q0, o);
        s1 += __shfl_xor_sync(~0u, s1, o); q1 += __shfl_xor_sync(~0u, q1, o);
      }
      if (t < 2)
        asm volatile("red.relaxed.gpu.global.add.v4.f32 [%0], {%1,%2,%3,%4};" ::"l"(g_rows + layer * LSEQ + blk * 64 + 16 * w + g + 8 * t),
                     "f"(t ? s1 : s0), "f"(t ? q1 : q0), "f"(1.f), "f"(0.f) : "memory");
    }
  }
  if (wg == 1) {
#pragma unroll 1
    for (int c = cut; c < 8; c++) wait_full(c);
    ready = true;
    bar_sync(5, 256);
  }
#pragma unroll 1
  for (int c = cut; c < 8; c++) {
    if (!ready) wait_full(c);
    issue(c, 0);
    if (wg == 1) {
      wg_wait<2>();
      if (leader && c >= cut + 2) mbar_arrive(bar + 8 * (B_DN + 8 + c - 2));
    } else if (c == 7) {
      bar_arrive(5, 256);
    } else {
      ready = peek(c + 1);
      wg_wait<1>();
      if (leader && c < 6) mbar_arrive(bar + 8 * (B_DN + c - 1));
    }
  }
  mbar_wait(bar + 8 * (B_LN + wg), layer);
  const float4 ln = lds128f(sb + ln_off(wg) + (8 * w + g) * 16);
  mean0 = ln.x; rstd0 = ln.y; mean1 = ln.z; rstd1 = ln.w;
  wg_wait<0>();
  acc_fence<96>(acc);
  if (leader) mbar_arrive(bar + 8 * (B_DN + 8 * wg + 7));
}

__device__ __forceinline__ void attn_phase(const Params& p, uint32_t sb, int layer, int rb, int hg, int wg, int w) {
  const int lane = opaque_tid() & 31;
  const int g = lane >> 2, t = lane & 3;
  const uint32_t bar = sb + SM_BAR;
  const int blk = 16 * wg + rb;
  float acc[96];
  float2 cs[24];
  float mean0, mean1, rstd0, rstd1;
  if (layer) gemm_section<true>(acc, mean0, mean1, rstd0, rstd1, sb, blk, hg, wg, w, lane);
  else gemm_section<false>(acc, mean0, mean1, rstd0, rstd1, sb, blk, hg, wg, w, lane);
  TSW(1);
#pragma unroll
  for (int j = 8; j < 24; j++) cs[j] = lds64f(sb + SM_CS + 4 * (8 * j + 2 * t));
  const uint32_t kvx = sb + (wg ? 22 : 0) * PG;

  uint32_t kb[4][8], vb[4][8], qa[4][4];
  {
    const float nm0 = -mean0 * rstd0, nm1 = -mean1 * rstd1;
    const int st_row = 16 * w + (lane & 7) + 8 * ((lane >> 3) & 1);
    const uint32_t st_base = kvx + st_row * 256;
    const bool sender = (w == 3 && blk < 31);
    uint4* halo = &g_halo[(blk * 8 + hg) * 256 + lane];
    uint32_t r[4][2][4];
#pragma unroll
    for (int h = 0; h < 4; h++) {
#pragma unroll
      for (int kv = 0; kv < 2; kv++) {
#pragma unroll
        for (int dh = 0; dh < 2; dh++) {
          const int j = 8 + kv * 8 + 2 * h + dh;
          const float2 c2 = cs[j];
          const float v0 = fmaf(acc[4 * j + 0], rstd0, nm0 * c2.x), v1 = fmaf(acc[4 * j + 1], rstd0, nm0 * c2.y);
          const float v2 = fmaf(acc[4 * j + 2], rstd1, nm1 * c2.x), v3 = fmaf(acc[4 * j + 3], rstd1, nm1 * c2.y);
          r[h][kv][2 * dh] = packbf(v0, v1);
          r[h][kv][2 * dh + 1] = packbf(v2, v3);
        }
      }
      if (sender) {
        stg128(halo + (2 * h) * 32, make_uint4(r[h][0][0], r[h][0][2], r[h][0][1], r[h][0][3]));
        stg128(halo + (2 * h + 1) * 32, make_uint4(r[h][1][0], r[h][1][1], r[h][1][2], r[h][1][3]));
      }
    }
#pragma unroll
    for (int j = 0; j < 8; j++) cs[j] = lds64f(sb + SM_CS + 4 * (8 * j + 2 * t));
    mbar_wait(bar + 8 * (B_DN + 7), layer);
#pragma unroll
    for (int h = 0; h < 4; h++) {
#pragma unroll
      for (int kv = 0; kv < 2; kv++) {
        const int chunk = 4 * h + 2 * kv + (lane >> 4);
        if (w < 3) stsm4(st_base + (((chunk & 8) | ((chunk ^ st_row) & 7)) << 4), r[h][kv][0], r[h][kv][1], r[h][kv][2], r[h][kv][3]);
      }
      kb[h][4] = r[h][0][0]; kb[h][5] = r[h][0][2]; kb[h][6] = r[h][0][1]; kb[h][7] = r[h][0][3];
      vb[h][4] = movm_t(r[h][1][0]); vb[h][5] = movm_t(r[h][1][1]); vb[h][6] = movm_t(r[h][1][2]); vb[h][7] = movm_t(r[h][1][3]);
    }
#pragma unroll
    for (int h = 0; h < 4; h++) {
#pragma unroll
      for (int dh = 0; dh < 2; dh++) {
        const int j = 2 * h + dh;
        const float2 c2 = cs[j];
        qa[h][2 * dh] = packbf(fmaf(-mean0, c2.x, acc[4 * j + 0]), fmaf(-mean0, c2.y, acc[4 * j + 1]));
        qa[h][2 * dh + 1] = packbf(fmaf(-mean1, c2.x, acc[4 * j + 2]), fmaf(-mean1, c2.y, acc[4 * j + 3]));
      }
    }
  }
  bar_sync(2 + wg, 128);
  TSW(2);
  {
    const uint32_t prev_base = kvx + (16 * w - 16) * 256;
    const int mi = lane >> 3;
    const int r = 8 * (mi >> 1) + (lane & 7), r2 = 8 * (mi & 1) + (lane & 7);
    if (w != 0) {
#pragma unroll
      for (int h = 0; h < 4; h++) {
        const int ch = 4 * h + (mi & 1), ch2 = 4 * h + 2 + (mi >> 1);
        ldsm4(&kb[h][0], prev_base + r * 256 + (((ch & 8) | ((ch ^ r) & 7)) << 4));
        ldsm4t(&vb[h][0], prev_base + r2 * 256 + (((ch2 & 8) | ((ch2 ^ r2) & 7)) << 4));
      }
    } else if (blk > 0) {
      uint4* src = &g_halo[((blk - 1) * 8 + hg) * 256 + lane];
      uint4 hv[8];
      int it = 0;
      bool ok;
      do {
        ok = true;
#pragma unroll
        for (int i = 0; i < 8; i++) hv[i] = ld_tagged(src + i * 32);
#pragma unroll
        for (int i = 0; i < 8; i++) ok = ok && hv[i].x != UNSET;
      } while (!__all_sync(~0u, ok) && ++it < (1 << 20));
      if (layer == 0) {
#pragma unroll
        for (int i = 0; i < 2; i++) stg128(src + i * 128 + (lane >> 1) * 6, make_uint4(UNSET, UNSET, UNSET, UNSET));
      }
#pragma unroll
      for (int h = 0; h < 4; h++) {
        kb[h][0] = hv[2 * h].x; kb[h][1] = hv[2 * h].y; kb[h][2] = hv[2 * h].z; kb[h][3] = hv[2 * h].w;
        vb[h][0] = movm_t(hv[2 * h + 1].x); vb[h][1] = movm_t(hv[2 * h + 1].y);
        vb[h][2] = movm_t(hv[2 * h + 1].z); vb[h][3] = movm_t(hv[2 * h + 1].w);
      }
    } else {
#pragma unroll
      for (int h = 0; h < 4; h++)
#pragma unroll
        for (int k = 0; k < 4; k++) kb[h][k] = vb[h][k] = 0u;
    }
    TSW(3);
  }
  mbar_wait(bar + 8 * (B_DN + 15), layer);
  TSW(4);

  const bool first = (blk == 0 && w == 0);
  const int e = t - (g >> 1);
  const bool par = g & 1, epos = e >= 1;
  const uint32_t pmask = par ? 0xffff0000u : 0x0000ffffu;
  const uint32_t mB0 = epos ? pmask : 0u, mB1 = epos ? 0u : pmask;
  const float cl2 = 0.25f * 1.4426950408889634f;
  const float sc0 = rstd0 * cl2, sc1 = rstd1 * cl2;
  const float NEG = -INFINITY;
  float vA0[4], vB0[4], vA1[4], vB1[4];
#pragma unroll
  for (int h = 0; h < 4; h++) {
    float S[4][4];
#pragma unroll
    for (int j = 0; j < 4; j++) {
      S[j][0] = S[j][1] = S[j][2] = S[j][3] = 0.f;
      mma_bf16(S[j], qa[h], kb[h][2 * j], kb[h][2 * j + 1]);
    }
    vA0[h] = par ? S[1][1] : S[1][0];
    vB0[h] = epos ? (par ? S[0][1] : S[0][0]) : (par ? S[2][1] : S[2][0]);
    vA1[h] = par ? S[2][3] : S[2][2];
    vB1[h] = epos ? (par ? S[1][3] : S[1][2]) : (par ? S[3][3] : S[3][2]);
    if (first) { vA0[h] = NEG; if (epos) { vB0[h] = NEG; vB1[h] = NEG; } }
  }
  float m0[4], m1[4];
#pragma unroll
  for (int h = 0; h < 4; h++) { m0[h] = fmaxf(vA0[h], vB0[h]); m1[h] = fmaxf(vA1[h], vB1[h]); }
#pragma unroll
  for (int o = 1; o <= 2; o <<= 1) {
#pragma unroll
    for (int h = 0; h < 4; h++) {
      m0[h] = fmaxf(m0[h], __shfl_xor_sync(~0u, m0[h], o));
      m1[h] = fmaxf(m1[h], __shfl_xor_sync(~0u, m1[h], o));
    }
  }
  float O0[4][4], O1[4][4], Z[4][4];
#pragma unroll
  for (int h = 0; h < 4; h++) {
    const float mm0 = -m0[h] * sc0, mm1 = -m1[h] * sc1;
    const float pA0 = ex2(fmaf(vA0[h], sc0, mm0)), pB0 = ex2(fmaf(vB0[h], sc0, mm0));
    const float pA1 = ex2(fmaf(vA1[h], sc1, mm1)), pB1 = ex2(fmaf(vB1[h], sc1, mm1));
    const uint32_t hA0 = packbf(pA0, pA0), hB0 = packbf(pB0, pB0), hA1 = packbf(pA1, pA1), hB1 = packbf(pB1, pB1);
    const uint32_t P0[4] = {hB0 & mB0, 0u, hA0 & pmask, hB1 & mB0};
    const uint32_t P1[4] = {hB0 & mB1, hA1 & pmask, 0u, hB1 & mB1};
#pragma unroll
    for (int k = 0; k < 4; k++) O0[h][k] = O1[h][k] = Z[h][k] = 0.f;
    mma_bf16(O0[h], P0, vb[h][0], vb[h][1]); mma_bf16(O1[h], P0, vb[h][2], vb[h][3]); mma_bf16(Z[h], P0, 0x3f803f80u, 0x3f803f80u);
    mma_bf16(O0[h], P1, vb[h][4], vb[h][5]); mma_bf16(O1[h], P1, vb[h][6], vb[h][7]); mma_bf16(Z[h], P1, 0x3f803f80u, 0x3f803f80u);
  }
  if (lane == 0) mbar_arrive(bar + 8 * (B_OST + wg));
  uint4* op = (uint4*)g_O + ((layer * 32 + blk) * 8 + hg) * 512 + 64 * t + 16 * w + g;
#pragma unroll
  for (int h = 0; h < 4; h += 2) {
    const float i0 = rcp_approx(Z[h][0]), i1 = rcp_approx(Z[h][2]), j0 = rcp_approx(Z[h + 1][0]), j1 = rcp_approx(Z[h + 1][2]);
    stg128(op + 128 * h, make_uint4(packbf(O0[h][0] * i0, O0[h][1] * i0), packbf(O1[h][0] * i0, O1[h][1] * i0),
                                   packbf(O0[h + 1][0] * j0, O0[h + 1][1] * j0), packbf(O1[h + 1][0] * j0, O1[h + 1][1] * j0)));
    stg128(op + 128 * h + 8, make_uint4(packbf(O0[h][2] * i1, O0[h][3] * i1), packbf(O1[h][2] * i1, O1[h][3] * i1),
                                            packbf(O0[h + 1][2] * j1, O0[h + 1][3] * j1), packbf(O1[h + 1][2] * j1, O1[h + 1][3] * j1)));
  }
  TSW(5);
  __syncwarp();
  if (lane == 0) red_relaxed(&g_cnt[(C_O + layer * 32 + blk) * 32]);
  TSW(6);
}

#define PTH 0
#define PTG 4
#define PGB B_PG
#define LPRE 1
__device__ __forceinline__ void conv_load(uint32_t* A, uint32_t pe);
__device__ __forceinline__ void proj_phase(const Params& p, uint32_t sb, int layer, int rb, int q, uint32_t* A0, uint32_t* A1) {
  const int lane = opaque_tid() & 31;
  const int wg = __shfl_sync(~0u, opaque_tid() >> 7, 0), w = __shfl_sync(~0u, (opaque_tid() >> 5) & 3, 0);
  const bool TR = layer != 0;
  const int t = lane & 3;
  const uint32_t bar = sb + SM_BAR;
  const uint32_t rbx = sb + (P_R + wg) * PG;
  const uint32_t rsrc = sb + (wg ? 2 : P_R) * PG;
  const int blk = 16 * wg + rb;
  mbar_wait(bar + 8 * (B_RF + wg), layer);
  mbar_wait(bar + 8 * B_WOF, layer);
  const uint32_t stg = sb + (wg ? SM_KGT : SM_STG);
  if (layer) {
    const uint32_t pe = sb + cv_pe(wg, 1) + 4 * (16 + 16 * w + (lane >> 2) - 2 * t);
    mbar_wait(bar + 8 * B_PE, 1);
    conv_load(A0, pe);
    conv_load(A1, pe + 2 * 4480);
    __syncwarp();
    if (lane == 0) mbar_arrive(bar + 8 * B_AL);
  } else {
#pragma unroll
    for (int i = 0; i < 68; i++) {
      asm volatile("mov.b32 %0, 0;" : "=r"(A0[i]));
      asm volatile("mov.b32 %0, 0;" : "=r"(A1[i]));
    }
  }
  bool clean = false, staged = false;
#pragma unroll 1
  for (int attempt = 0; attempt < MAX_RETRY; attempt++) {
  uint32_t res[16];
  if (!TR) {
#pragma unroll
    for (int j = 0; j < 8; j += 2) {
      const int mi = lane >> 3;
      const int row = 16 * w + (lane & 7) + 8 * (mi & 1), ch = j + (mi >> 1);
      ldsm4(&res[2 * j], rsrc + row * 128 + ((ch ^ (row & 7)) << 4));
    }
  } else {
#pragma unroll
    for (int j = 0; j < 8; j += 2) {
      const int mi = lane >> 3;
      const int line = 8 * (j + (mi >> 1)) + (lane & 7), pc = 2 * w + (mi & 1);
      ldsm4t(&res[2 * j], rsrc + line * 128 + ((pc ^ (line & 7)) << 4));
    }
  }
  float acc[32];
#pragma unroll
  for (int j = 0; j < 16; j++) { acc[2 * j] = bf_lo(res[j]); acc[2 * j + 1] = bf_hi(res[j]); }
  acc_fence<32>(acc);
  if (wg) mbar_wait(bar + 8 * (PGB), layer);
  const int wg2 = __shfl_sync(~0u, opaque_tid() >> 7, 0);
  const uint64_t da0 = mkdesc(sb, 1024, 128, 0), db0 = mkdesc(sb, 8192, 1024, 1);
#pragma unroll
  for (int c = 0; c < 4; c++) {
    mbar_wait(bar + 8 * (B_OF + 4 * wg + c), layer);
    if (c == 0) TSW(7);
    const uint64_t da = da0 + (uint32_t)(o_page(wg2, c) * 512);
    wg_fence();
#pragma unroll
    for (int ks = 0; ks < 8; ks++) {
      if (c >= PTH && ks % PTG == 0) { if (ks) wg_commit(); if (wg2) wg_wait<0>(); wg_fence(); }
      wgmma_ss<64, 0, 1>(acc, da + ks * 128, db0 + wo_page(2 * c + (ks >> 2)) * 512 + (ks & 3) * 128, 1);
    }
    wg_commit();
  }
  if (wg) mbar_wait(bar + 8 * B_KG, 0);
  wg_wait<0>();
  acc_fence<32>(acc);
  TSW(8);
  if (!clean) {
    const float chk = acc[0] + acc[2];
    clean = __all_sync(~0u, chk == chk);
    if (clean && lane == 0) mbar_arrive(bar + 8 * (B_PDONE + wg));
  }
  float s0 = 0.f, q0 = 0.f, s1 = 0.f, q1 = 0.f;
  uint32_t o[16];
#pragma unroll
  for (int j = 0; j < 8; j++) {
    const float a = acc[4 * j], b = acc[4 * j + 1], c = acc[4 * j + 2], d = acc[4 * j + 3];
    o[2 * j] = packbf(a, b);
    o[2 * j + 1] = packbf(c, d);
    s0 += a + b; q0 = fmaf(a, a, q0); q0 = fmaf(b, b, q0);
    s1 += c + d; q1 = fmaf(c, c, q1); q1 = fmaf(d, d, q1);
  }
#pragma unroll
  for (int j = 0; j < 8; j += 2) {
    const int mi = lane >> 3;
    const int line = 8 * (j + (mi >> 1)) + (lane & 7), pc = 2 * w + (mi & 1);
    stsm4t(rbx + line * 128 + ((pc ^ (line & 7)) << 4), o[2 * j], o[2 * j + 1], o[2 * j + 2], o[2 * j + 3]);
  }
#pragma unroll
  for (int o2 = 1; o2 <= 2; o2 <<= 1) {
    s0 += __shfl_xor_sync(~0u, s0, o2); q0 += __shfl_xor_sync(~0u, q0, o2);
    s1 += __shfl_xor_sync(~0u, s1, o2); q1 += __shfl_xor_sync(~0u, q1, o2);
  }
  {
    const int i = 2 * (lane >> 2) + (t & 1), k = (i * 11) >> 5;
    const float v = (t == 0) ? s0 : (t == 1) ? q0 : (t == 2) ? s1 : q1;
    sts32f(stg + k * 128 + (2 * w + (t >> 1)) * 16 + (i - 3 * k) * 4, v);
  }
  TSW(9);
  fence_async_smem();
  if (attempt == 0 && clean) {
    staged = true;
    __syncwarp();
    if (lane == 0) mbar_arrive(bar + 8 * (B_STG + wg));
  }
  if (!bar_or(2 + wg, 128, !clean)) break;
  const int rtp = mbar_test(bar + 8 * (B_RT + wg), 0);
  bool unset = false;
#pragma unroll
  for (int i = 0; i < 4; i++) unset |= lds32(sb + o_page(wg, i) * PG + (32 * w + lane) * 128) == UNSET;
  if (!bar_or(2 + wg, 128, unset)) break;
  if (w == 0 && elect_one()) {
    fence_async_smem();
    mbar_expect(bar + 8 * (B_RT + wg), 9 * PG);
    if (layer == 0) tma_ld(rsrc, &p.mapX, q * 64, blk * 64, bar + 8 * (B_RT + wg));
    else tma_ld(rsrc, &p.mapXT, blk * 64, DM + q * 64, bar + 8 * (B_RT + wg));
#pragma unroll 1
    for (int c = 0; c < 4; c++) bulk_ld(sb + o_page(wg, c) * PG, g_O + ((layer * 32 + blk) * 4 + c) * PG, 2 * PG, bar + 8 * (B_RT + wg));
  }
  mbar_wait(bar + 8 * (B_RT + wg), rtp);
  RETRY(0);
  }
  if (!clean && lane == 0) mbar_arrive(bar + 8 * (B_PDONE + wg));
  if (!staged && lane == 0) mbar_arrive(bar + 8 * (B_STG + wg));
  TSW(10);
}

__device__ __forceinline__ void conv_load(uint32_t* A, uint32_t pe) {
#pragma unroll
  for (int m = 0; m < 17; m++) {
    A[4 * m + 2] = lds32(pe + 4 * (64 * m - 8));
    A[4 * m + 0] = lds32(pe + 4 * (64 * m));
    A[4 * m + 1] = lds32(pe + 4 * (64 * m + 8));
    asm volatile("mov.b32 %0, %1;" : "=r"(A[4 * m + 3]) : "r"(A[4 * m + 0]));
  }
}
template <int M> __device__ __forceinline__ void conv_tri(float* acc, const uint32_t* A, uint64_t d) {
  if constexpr (M < 16) {
    wgmma_rs<64 - 8 * (M / 2), 0>(acc, A + 4 * M, d + (uint64_t)(64 + 4 * M), M != 0);
    conv_tri<M + 1>(acc, A, d);
  }
}
__device__ __forceinline__ void conv_mma0(float* acc, const uint32_t* A, uint64_t d) {
  wg_fence();
  conv_tri<0>(acc, A, d);
  wg_commit();
}
__device__ __forceinline__ void conv_mma1(float* acc, const uint32_t* A, uint64_t d, uint64_t ds, uint64_t df) {
  wg_fence();
#pragma unroll
  for (int m = 0; m < 17; m++) wgmma_rs<64, 0>(acc, A + 4 * m, d + (uint64_t)(4 * m), m != 0);
  wgmma_ss<64, 1, 0>(acc, ds, df, 1);
  wgmma_ss<64, 1, 0>(acc, ds + 128, df + 128, 1);
  wg_commit();
}
__device__ __forceinline__ void conv_store(float* acc, uint32_t pb, uint32_t over, int w) {
  acc_fence<32>(acc);
  const int l = opaque_tid() & 31, mt = l >> 3;
  int c = 2 * (63 - 8 * (mt >> 1) - (l & 7) + w) + (mt & 1);
  c ^= (c >> 3) & 1;
  const uint32_t a0 = pb + c * 16;
#pragma unroll
  for (int j = 0; j < 8; j += 2)
    stsm4t(j == 0 ? (c < 128 ? a0 : over + (c - 128) * 16) : a0 - 256 * j, packbf(acc[4 * j], acc[4 * j + 1]), packbf(acc[4 * j + 2], acc[4 * j + 3]),
           packbf(acc[4 * j + 4], acc[4 * j + 5]), packbf(acc[4 * j + 6], acc[4 * j + 7]));
}
__device__ __forceinline__ void conv_sums(uint32_t sb, int lc, int ht) {
  const int m = ht - 1;
  uint4 v[2][3];
#pragma unroll
  for (int c = 0; c < 2; c++)
#pragma unroll
    for (int k = 0; k < 3; k++) {
      const int mm = m - 1 + k;
      v[c][k] = lds128(sb + cv_u(lc + c) + (mm >= 0 ? (mm & 1) * CV_UH + (127 - (mm >> 1)) * 16 : 128 * 16));
    }
  const int ce = m + 2, co = m + 1;
#pragma unroll
  for (int c = 0; c < 2; c++) {
    const uint32_t x[8] = {v[c][0].z, v[c][0].w, v[c][1].x, v[c][1].y, v[c][1].z, v[c][1].w, v[c][2].x, v[c][2].y};
    float pv[16];
#pragma unroll
    for (int k = 0; k < 8; k++) { pv[2 * k] = bf_lo(x[k]); pv[2 * k + 1] = bf_hi(x[k]); }
    float t2[15], t4[13], s9[8], s7[8];
#pragma unroll
    for (int i = 0; i < 15; i++) t2[i] = pv[i] + pv[i + 1];
#pragma unroll
    for (int i = 0; i < 13; i++) t4[i] = t2[i] + t2[i + 2];
#pragma unroll
    for (int i = 0; i < 8; i++) {
      s9[i] = (t4[i] + t4[i + 4]) + pv[i + 8];
      s7[i] = (t4[i + 1] + t2[i + 5]) + pv[i + 7];
    }
    const uint4 e4 = make_uint4(packbf(s9[0], s9[1]), packbf(s9[2], s9[3]), packbf(s9[4], s9[5]), packbf(s9[6], s9[7]));
    if (ce < 128) sts128(sb + cv_se(lc + c) + ((ce ^ ((ce >> 3) & 7)) << 4), e4);
    else sts128(sb + cv_se(lc + c), make_uint4(0, 0, 0, 0));
    sts128(sb + cv_so(lc + c) + ((co ^ ((co >> 3) & 7)) << 4),
           make_uint4(packbf(s7[0], s7[1]), packbf(s7[2], s7[3]), packbf(s7[4], s7[5]), packbf(s7[6], s7[7])));
  }
}

template <int HALF, int NCH, int STEP = 1>
__device__ __forceinline__ void conv_epi(uint32_t sb, bf16* out, int lc, int c) {
  uint4 v[NCH][4], xr[NCH];
  const uint32_t sw = (c ^ ((c >> 3) & 1)) * 16;
#pragma unroll
  for (int u = 0; u < NCH; u++) {
#pragma unroll
    for (int k = 0; k < 4; k++) v[u][k] = lds128(sb + (HALF ? cv_pb1(lc + STEP * u, k) : cv_pb0(lc + STEP * u, k)) + sw);
    xr[u] = lds128(sb + cv_x(HALF, lc + STEP * u) + c * 16);
  }
#pragma unroll
  for (int u = 0; u < NCH; u++) {
    uint4 o;
    o.x = hadd2(xr[u].x, hadd2(hadd2(v[u][0].x, v[u][1].x), hadd2(v[u][2].x, v[u][3].x)));
    o.y = hadd2(xr[u].y, hadd2(hadd2(v[u][0].y, v[u][1].y), hadd2(v[u][2].y, v[u][3].y)));
    o.z = hadd2(xr[u].z, hadd2(hadd2(v[u][0].z, v[u][1].z), hadd2(v[u][2].z, v[u][3].z)));
    o.w = hadd2(xr[u].w, hadd2(hadd2(v[u][0].w, v[u][1].w), hadd2(v[u][2].w, v[u][3].w)));
    stg128(out + cv_chan(0, lc + STEP * u) * LSEQ + HALF * 1024 + c * 8, o);
  }
}

__device__ __forceinline__ bool prep_valid(const uint4 (&st)[6], const uint4 (&xr)[4]) {
  const uint32_t n = __float_as_uint(8.f);
  return st[0].w == n && st[1].w == n && st[2].w == n && st[3].w == n && st[4].w == n && (st[5].w | st[5].y | st[5].z) == n &&
         xr[0].x != UNSET && xr[1].x != UNSET && xr[2].x != UNSET && xr[3].x != UNSET;
}
template <int HALF>
__device__ __forceinline__ void conv_prep(uint32_t sb, int layer, int cta, int i) {
  uint4 st[6], xr[4];
  const uint4* sp = (const uint4*)g_stats + (layer * 32 + HALF * 16 + (i >> 3)) * 48 + (i & 7);
  const uint4* xp = (const uint4*)g_xT + (2 * layer * DM + 2 * cta) * (LSEQ / 8) + HALF * 128 + i;
  auto fetch = [&]() {
#pragma unroll
    for (int k = 0; k < 6; k++) st[k] = ld_tagged(sp + 8 * k);
#pragma unroll
    for (int k = 0; k < 4; k++) xr[k] = ld_tagged(xp + cv_chan(0, k) * (LSEQ / 8));
  };
  if (HALF) {
#pragma unroll
    for (int k = 0; k < 6; k++) st[k] = lds128(sb + CV_ST + (i >> 3) * 768 + k * 128 + (i & 7) * 16);
#pragma unroll
    for (int k = 0; k < 4; k++) xr[k] = lds128(sb + cv_x(1, k) + i * 16);
  } else {
    fetch();
  }
  int it = 0;
  while (!__all_sync(~0u, prep_valid(st, xr)) && ++it < MAX_RETRY) { fetch(); RETRY(1); }
  if (!HALF || it) {
#pragma unroll
    for (int k = 0; k < 4; k++) sts128(sb + cv_x(HALF, k) + i * 16, xr[k]);
  }
  const uint32_t v[16] = {st[0].x, st[0].y, st[0].z, st[1].x, st[1].y, st[1].z, st[2].x, st[2].y, st[2].z, st[3].x, st[3].y, st[3].z, st[4].x, st[4].y, st[4].z, st[5].x};
  uint32_t rs[4], nm[4];
#pragma unroll
  for (int k = 0; k < 4; k++) {
    const float m0 = __uint_as_float(v[4 * k]) * (-1.f / DM), m1 = __uint_as_float(v[4 * k + 2]) * (-1.f / DM);
    const float r0 = rsqrt_approx(fmaxf(fmaf(__uint_as_float(v[4 * k + 1]), 1.f / DM, -m0 * m0), 0.f) + 1e-5f);
    const float r1 = rsqrt_approx(fmaxf(fmaf(__uint_as_float(v[4 * k + 3]), 1.f / DM, -m1 * m1), 0.f) + 1e-5f);
    rs[k] = packbf(r0, r1);
    nm[k] = packbf(m0 * bf_lo(rs[k]), m1 * bf_hi(rs[k]));
  }
  const uint32_t ud = sb + (i & 1) * CV_UH + (127 - 64 * HALF - (i >> 1)) * 16;
#pragma unroll
  for (int k = 0; k < 4; k++)
    sts128(ud + cv_u(k), make_uint4(hfma2(xr[k].x, rs[0], nm[0]), hfma2(xr[k].y, rs[1], nm[1]), hfma2(xr[k].z, rs[2], nm[2]), hfma2(xr[k].w, rs[3], nm[3])));
  fence_async_smem();
}

#define PP0 1
__device__ __forceinline__ void conv_phase(const Params& p, uint32_t sb, int layer, int cta, uint32_t* A0, uint32_t* A1) {
  const int tid = opaque_tid();
  const int wg = __shfl_sync(~0u, tid >> 7, 0), w = __shfl_sync(~0u, (tid >> 5) & 3, 0);
  const uint32_t bar = sb + SM_BAR;
  constexpr int CH2 = 4 * PG;
  bf16* xout = g_xT + ((2 * layer + 1) * DM + 2 * cta) * LSEQ;
  float acc[32];
  const uint32_t pe = sb + cv_pe(wg, 0) + 4 * (16 + 16 * w + ((tid & 31) >> 2) - 2 * (tid & 3));
  if (!(LPRE && layer)) {
    mbar_wait(bar + 8 * (B_PDONE + 1), layer);
    mbar_wait(bar + 8 * B_PE, layer);
    conv_load(A0, pe);
    conv_load(A1, pe + CH2);
  }
  TSW(19);
  const uint64_t d0 = mkdesc(sb + cv_u(wg), CV_UH, 128, 0), d1 = d0 + (CH2 >> 4);
  mbar_wait(bar + 8 * B_U, layer);
  TSW(12);
  if (wg == 1) bar_sync(5, 256);
  conv_mma0(acc, A0, d0);
  if (wg == 0) bar_arrive(5, 256);
  mbar_wait(bar + 8 * (B_PDONE + 1), layer);
  {
    const int l = opaque_tid() & 31;
    if ((l & 15) < 2 * w) sts128(sb + cv_pb0(wg + 2 * (l >> 4), w) + (l & 15) * 16, make_uint4(0, 0, 0, 0));
  }
  wg_wait<0>();
  conv_store(acc, sb + cv_pb0(wg, w), sb + cv_pb1(wg, w), w);
  conv_mma0(acc, A1, d1);
  wg_wait<0>();
  conv_store(acc, sb + cv_pb0(2 + wg, w), sb + cv_pb1(2 + wg, w), w);
  TSW(13);
  bar_sync(2 + wg, 128);
  conv_epi<0, 2, 2>(sb, xout, wg, opaque_tid() & 127);
  TSW(14);
  mbar_arrive(bar + 8 * B_PUB);
  const uint64_t ds = mkdesc(sb + cv_se(wg), 8192, 1024, 1), df = mkdesc(sb + cv_fa(wg), 512, 128, 0);
  if (wg == 0) mbar_wait(bar + 8 * B_U1, layer);
  else bar_sync(6, 256);
  TSW(15);
  conv_mma1(acc, A0, d0, ds, df);
  if (wg == 0) bar_arrive(6, 256);
  wg_wait<0>();
  conv_store(acc, sb + cv_pb1(wg, w), sb + cv_dump(wg), w);
  TSW(16);
  bar_sync(2 + wg, 128);
  conv_epi<1, 1>(sb, xout, wg, opaque_tid() & 127);
  mbar_arrive(bar + 8 * (B_PUB + 1));
  conv_mma1(acc, A1, d1, ds + 512, df + (CH2 >> 4));
  wg_wait<0>();
  conv_store(acc, sb + cv_pb1(2 + wg, w), sb + cv_dump(2 + wg), w);
  TSW(17);
  bar_sync(2 + wg, 128);
  conv_epi<1, 1>(sb, xout, 2 + wg, opaque_tid() & 127);
  mbar_arrive(bar + 8 * (B_PUB + 2));
  TSW(18);
}

__device__ __forceinline__ void final_tile(const Params& p, uint32_t buf, int ch0, int pos0, int barid) {
  const int tid = opaque_tid() & 127, lane = tid & 31, w = tid >> 5;
  const uint4* src = (const uint4*)(g_xT + (3 * DM + ch0 + (tid >> 3)) * LSEQ + pos0) + (tid & 7);
  const int ch = tid >> 3, row = 4 * (ch & 6) + 2 * (ch >> 3) + (ch & 1);
  const uint32_t dst = buf + row * 128;
  const uint32_t ld = buf + lane * 128;
  bf16* out = p.out + (pos0 + 16 * w + (lane >> 2)) * DM + ch0 + 8 * (lane & 3);
  uint4 a, b;
  int it = 0;
  do {
    if (it) RETRY(2);
    a = ld_tagged(src); b = ld_tagged(src + 16 * LSEQ / 8);
  } while (!__all_sync(~0u, a.x != UNSET && b.x != UNSET) && ++it < (1 << 20));
  sts128(dst + (((tid ^ row) & 7) << 4), a);
  sts128(dst + 512 + (((tid ^ row ^ 4) & 7) << 4), b);
  bar_sync(barid, 128);
#pragma unroll
  for (int h = 0; h < 2; h++) {
    uint32_t r[4];
    ldsm4t(r, ld + ((((2 * w + h) ^ lane) & 7) << 4));
    *(uint4*)(out + 8 * h * DM) = make_uint4(r[0], r[1], r[2], r[3]);
  }
}

struct cplx { float r, i; };
__device__ __forceinline__ cplx cmul(cplx a, cplx b) { return {fmaf(a.r, b.r, -a.i * b.i), fmaf(a.r, b.i, a.i * b.r)}; }
__device__ __forceinline__ cplx csqr(cplx a) { return {fmaf(a.r, a.r, -a.i * a.i), (a.r + a.r) * a.i}; }
__device__ __forceinline__ cplx cexp_l(float ar2, float ai, float l) {
  const float m = ex2(ar2 * l);
  const float x = ai * l;
  return {m * __cosf(x), m * __sinf(x)};
}

__device__ __forceinline__ void colsum_cta(const Params& p, uint32_t sb, int j, int tid) {
  const uint32_t bar = sb + SM_BAR;
  auto ld = [&](int i) {
    mbar_expect(bar + 8 * i, 3 * PG);
    tma_ld3(sb + (i & 7) * 3 * PG, &p.mapW3, (2 * j + (i & 1)) * 64, (i >> 1) * 64, 0, bar + 8 * i);
  };
  if (tid == 384) {
#pragma unroll
    for (int i = 0; i < 24; i++) mbar_init(bar + 8 * i, i < 16 ? 1 : 12);
    asm volatile("fence.mbarrier_init.release.cluster;" ::: "memory");
    fence_async_smem();
#pragma unroll 1
    for (int i = 0; i < 8; i++) ld(i);
  }
  const unsigned ep = ld_relaxed(&g_cnt[C_CS * 32]);
  bar_sync(0, NTHREADS);
  if (tid == 384) {
#pragma unroll 1
    for (int i = 8; i < 16; i++) { mbar_wait(bar + 8 * (8 + i), 0); fence_async_smem(); ld(i); }
  }
  if (tid < 384) {
    const int lane = tid & 31, cc = tid & 7, r0 = (tid >> 3) & 15, part = tid >> 7;
    const uint32_t id = ((lane >> 2) == 2 * (lane & 3) ? 0x3f80u : 0u) | ((lane >> 2) == 2 * (lane & 3) + 1 ? 0x3f800000u : 0u);
    const uint32_t src = sb + part * PG + r0 * 128 + ((cc ^ (r0 & 7)) << 4);
    float s[2][2][4];
#pragma unroll
    for (int i = 0; i < 16; i++) s[i >> 3][(i >> 2) & 1][i & 3] = 0.f;
#pragma unroll 1
    for (int i2 = 0; i2 < 16; i2 += 2) {
#pragma unroll
      for (int h = 0; h < 2; h++) {
        const int i = i2 + h;
        mbar_wait(bar + 8 * i, 0);
        uint4 v[4];
#pragma unroll
        for (int k = 0; k < 4; k++) v[k] = lds128(src + (i & 7) * 3 * PG + k * 2048);
#pragma unroll
        for (int k = 0; k < 4; k++) {
          const uint32_t a[4] = {v[k].x, v[k].y, v[k].z, v[k].w};
          mma_bf16(s[h][0], a, id, 0u);
          mma_bf16(s[h][1], a, 0u, id);
        }
        __syncwarp();
        if (i < 8 && lane == 0) mbar_arrive(bar + 8 * (16 + i));
      }
    }
    const uint32_t red = sb + 24 * PG;
#pragma unroll
    for (int h = 0; h < 2; h++)
#pragma unroll
      for (int k = 0; k < 2; k++) sts128f(red + (r0 * 384 + h * 192 + part * 64 + cc * 8 + k * 4) * 4, s[h][k][0], s[h][k][1], s[h][k][2], s[h][k][3]);
    bar_sync(1, 384);
    float tot = 0.f;
#pragma unroll
    for (int k = 0; k < 16; k++) tot += __uint_as_float(lds32(red + (k * 384 + tid) * 4));
    asm volatile("st.relaxed.gpu.global.v2.u32 [%0], {%1,%2};" ::"l"(&g_colsum[j * 384 + tid]), "r"(__float_as_uint(tot)), "r"(ep / NCTA + 1) : "memory");
    const uint4 u = make_uint4(UNSET, UNSET, UNSET, UNSET);
    if (tid < 256) {
#pragma unroll 1
      for (int s = 0; s < 4; s++) {
        const int n = (s == 1 || s == 2) ? 32 : 16;
        uint4* buf = s == 1 ? (uint4*)g_O + 131072 : (uint4*)g_xT + (s + !s) * 131072;
#pragma unroll 4
        for (int i = 0; i < n; i++) stg128(buf + (j * n + i) * 1024 + (tid >> 1) * 8 + (tid & 1), u);
        if (n == 16) {
#pragma unroll 4
          for (int i = 0; i < 8; i++) stg128(buf + (256 + j * 64 + i * 8 + (tid >> 5)) * 256 + (s ? 0 : 128) + ((tid & 31) >> 1) * 8 + (tid & 1), u);
        }
        if (s == 3) {
#pragma unroll 4
          for (int i = 0; i < 32; i++) stg128(buf + (256 + j * 64 + 2 * i + (tid >> 7)) * 256 + 128 + (tid & 127), u);
        }
        bar_sync(2, 256);
        if (tid == 32 * s) red_release(&g_cnt[(C_R + s) * 32]);
      }
    }
  }
}

#define KB 4
#define KW 2
struct ModeIn { uint32_t ar, ai, br, bi, cr, ci; bf16 logdt; };
__device__ __forceinline__ ModeIn load_modes(const Params& p, int d, int m) {
  const int i = d * 64 + m;
  return {((const uint32_t*)p.a_re)[i], ((const uint32_t*)p.a_im)[i], ((const uint32_t*)p.b_re)[i], ((const uint32_t*)p.b_im)[i],
          ((const uint32_t*)p.c_re)[i], ((const uint32_t*)p.c_im)[i], p.log_dt[d]};
}
__device__ __forceinline__ float4 lds128f_nv(uint32_t a) { float4 v; asm("ld.shared.v4.f32 {%0,%1,%2,%3}, [%4];" : "=f"(v.x), "=f"(v.y), "=f"(v.z), "=f"(v.w) : "r"(a)); return v; }
__device__ __forceinline__ void kernel_gen(const Params& p, uint32_t sb, int cta, int ht, ModeIn in, const ModeIn& in1) {
  const uint32_t bst = sb + SM_KGB + ((ht & 63) >> 2) * 144 + (ht & 3) * 4 + (ht >> 6) * 16;
  const uint64_t db = mkdesc(sb + SM_KGB, 144, 2304, 0);
  const float e0 = (float)(8 * (((ht & 32) >> 1) + ((ht & 31) >> 2)));
  float T[20];
#pragma unroll
  for (int i = 0; i < 20; i++) T[i] = 0.f;
  float k0 = 0.f;
#pragma unroll 1
  for (int pass = 0; pass < 4; pass++) {
    {
      const int sh = (pass & 1) ? 0 : 16;
      auto val = [&](uint32_t v) { return __uint_as_float((v << sh) & 0xffff0000u); };
      const float dt = __bfloat162float(__float2bfloat16_rn(expf(__bfloat162float(in.logdt))));
      const float ar2 = dt * val(in.ar) * 1.4426950408889634f, ai = dt * val(in.ai);
      const cplx c = cmul({val(in.cr), -val(in.ci)}, {dt * val(in.br), -dt * val(in.bi)});
      k0 += c.r;
      const cplx z1 = cexp_l(ar2, -ai, 1.f), z256 = cexp_l(ar2, -ai, 256.f), z64 = cexp_l(ar2, ai, 64.f);
      const cplx z2 = csqr(z1), z512 = csqr(z256);
      auto put = [&](int j, cplx v) { sts32(bst + (j >> 2) * 2304 + (j & 3) * 32, packbf(v.r, v.i)); };
      sts128f(sb + SM_KGT + ht * 16, ar2, ai, z64.r, z64.i);
      const cplx c1 = cmul(c, z1), c2 = cmul(c, z2), c3 = cmul(c1, z2), c4 = cmul(c2, z2);
      const cplx c5 = cmul(c3, z2), c6 = cmul(c4, z2), c7 = cmul(c5, z2), c8 = cmul(c6, z2);
      put(0, c1); put(1, c2); put(2, c3); put(3, c4); put(4, c5); put(5, c6); put(6, c7); put(7, c8);
      const cplx c260 = cmul(c4, z256), c264 = cmul(c8, z256), c520 = cmul(c8, z512), c776 = cmul(c264, z512);
      put(8, cmul(c2, z256)); put(9, c260); put(10, cmul(c6, z256)); put(11, c264);
      put(12, cmul(c4, z512)); put(13, c520); put(14, cmul(c260, z512)); put(15, c776);
      const cplx c1032 = cmul(c520, z512), c1288 = cmul(c776, z512);
      put(16, c1032); put(17, c1288); put(18, cmul(c1032, z512)); put(19, cmul(c1288, z512));
    }
    fence_async_smem();
    bar_sync(4, 128);
    const uint32_t tb = sb + SM_KGT + (ht & 67) * 16;
    float2 nx[KB];
#pragma unroll
    for (int s = 0; s < KB; s++) nx[s] = lds64f(tb + s * 64);
#pragma unroll
    for (int q = 0; q < 16 / KB; q++) {
      uint32_t A[2 * KB];
      float2 cur[KB], z[KB];
#pragma unroll
      for (int s = 0; s < KB; s++) { cur[s] = nx[s]; z[s] = lds64f(tb + (KB * q + s) * 64 + 8); }
      if (q < 16 / KB - 1) {
#pragma unroll
        for (int s = 0; s < KB; s++) nx[s] = lds64f(tb + (KB * q + KB + s) * 64);
      }
      if (q >= KW) wg_wait<KW - 1>();
#pragma unroll
      for (int s = 0; s < KB; s++) {
        const cplx lo = cexp_l(cur[s].x, cur[s].y, e0), hi = cmul(lo, {z[s].x, z[s].y});
        A[2 * s] = packbf(lo.r, lo.i);
        A[2 * s + 1] = packbf(hi.r, hi.i);
      }
      wg_fence();
#pragma unroll
      for (int k = 0; k < KB / 2; k++) wgmma_rs<40, 0>(T, A + 4 * k, db + 9 * KB * q + 18 * k, (pass & 1) | q | k);
      wg_commit();
    }
    wg_wait<0>();
    acc_fence<20>(T);
    if (ht == 0) TS(4 + pass);
    if (pass & 1) {
      const int h2 = opaque_tid() - 256, w = h2 >> 5, lane = h2 & 31, t = lane & 3, chn = h2 >> 6, m = h2 & 63, i0 = 16 * (w & 1) + (lane >> 2);
      const int lc = (pass & 2) + chn;
      const uint32_t kc = sb + kc_off(lc);
      auto put = [&](int idx, float v) {
        sts16(kc + idx * 2, __bfloat16_as_ushort(__float2bfloat16_rn(v)));
      };
#pragma unroll
      for (int hi = 0; hi < 2; hi++) {
        const int i = i0 + 8 * hi;
        float v[5];
#pragma unroll
        for (int j = 0; j < 5; j++) v[j] = chn ? T[4 * j + 2 * hi + 1] : T[4 * j + 2 * hi];
        put(8 * i + 1 + t, v[0]);
        put(8 * i + 5 + t, v[1]);
        put(257 + 4 * i + t, v[2]);
        put(385 + 2 * i + (t & 1) + 64 * (t >> 1), v[3]);
        put(513 + i + 32 * t, v[4]);
      }
#pragma unroll
      for (int o = 16; o > 0; o >>= 1) k0 += __shfl_xor_sync(~0u, k0, o);
      if (lane == 0) sts32f(sb + SM_RED + 4 * w, k0);
      bar_sync(4, 128);
      if (m == 0) put(0, k0 + __uint_as_float(lds32(sb + SM_RED + 4 * w + 4)) + __uint_as_float(lds16(sb + SM_RED + 24 + 2 * lc) << 16));
      k0 = 0.f;
      in = in1;
    }
  }
}

__device__ __forceinline__ void expand_taps(uint32_t sb, int ht, int early) {
  const int ch = ht >> 5, lane = ht & 31;
  const uint32_t kc = sb + kc_off(ch);
  const uint32_t dst0 = sb + cv_pe(ch, early);
  auto put = [&](int G, uint32_t v0, uint32_t v1, uint32_t v2, uint32_t v3, uint32_t v4, uint32_t v5, uint32_t v6, uint32_t v7, uint32_t v8) {
    const uint32_t dst = dst0 + G * 32;
    sts128(dst, make_uint4(v1 | (v0 << 16), v2 | (v1 << 16), v3 | (v2 << 16), v4 | (v3 << 16)));
    sts128(dst + 16, make_uint4(v5 | (v4 << 16), v6 | (v5 << 16), v7 | (v6 << 16), v8 | (v7 << 16)));
  };
  {
    const uint4 q = lds128(kc + lane * 16);
    const uint32_t pv = lane ? lds16(kc + lane * 16 - 2) : 0u;
    const uint32_t dst = dst0 + (lane + 2) * 32;
    sts128(dst, make_uint4(__byte_perm(q.x, pv, 0x5410), __byte_perm(q.x, q.x, 0x1032), __byte_perm(q.y, q.x, 0x7610), __byte_perm(q.y, q.y, 0x1032)));
    sts128(dst + 16, make_uint4(__byte_perm(q.z, q.y, 0x7610), __byte_perm(q.z, q.z, 0x1032), __byte_perm(q.w, q.z, 0x7610), __byte_perm(q.w, q.w, 0x1032)));
    if (lane < 4) sts128(dst0 + lane * 16, make_uint4(0, 0, 0, 0));
  }
  uint32_t a[5], b[2][3];
  {
    const uint32_t s1 = kc + 2 * (256 + 4 * lane);
#pragma unroll
    for (int k = 0; k < 5; k++) a[k] = lds16(s1 + 2 * k);
#pragma unroll
    for (int u = 0; u < 2; u++) {
      const uint32_t s2 = kc + 2 * (384 + 2 * (lane + 32 * u));
#pragma unroll
      for (int k = 0; k < 3; k++) b[u][k] = lds16(s2 + 2 * k);
    }
  }
  const uint32_t k255 = lds16(kc + 2 * 255), k1024 = lds16(kc + 2 * 512);
  put(34 + lane, lane == 0 ? k255 : a[0], a[0], a[0], a[1], a[2], a[2], a[2], a[3], a[4]);
#pragma unroll
  for (int u = 0; u < 2; u++) put(66 + lane + 32 * u, b[u][0], b[u][0], b[u][0], b[u][0], b[u][1], b[u][1], b[u][1], b[u][2], b[u][2]);
  if (lane < 10) {
    const uint32_t v = lane == 0 ? k1024 : 0u;
    put(130 + lane, v, v, v, v, v, v, 0u, 0u, 0u);
  }
}
__device__ __forceinline__ void expand_far(uint32_t sb, int ht) {
  const int ch = ht >> 5, lane = ht & 31;
  const uint32_t kc = sb + kc_off(ch) + 2 * (513 + 2 * (63 - lane)), dst = sb + cv_fa(ch) + lane * 16;
#pragma unroll
  for (int ty = 0; ty < 2; ty++) {
    uint32_t v[16];
#pragma unroll
    for (int k = 0; k < 16; k++) v[k] = (k < 8 || 63 - lane - 4 * k >= 0) ? lds16(kc + 2 * (1 - ty) - 16 * k) : 0u;
#pragma unroll
    for (int u = 0; u < 2; u++)
      sts128(dst + ty * 2048 + u * 512, make_uint4(v[8 * u] | (v[8 * u + 1] << 16), v[8 * u + 2] | (v[8 * u + 3] << 16), v[8 * u + 4] | (v[8 * u + 5] << 16), v[8 * u + 6] | (v[8 * u + 7] << 16)));
    sts128(dst + ty * 2048 + 1024, make_uint4(0, 0, 0, 0));
  }
}

#define TMPF 1
#define CONST_SB 1
#define XGATE B_OST
#define WPRE 1
__host__ __device__ constexpr int bar_count(int i) {
  return i == B_LN ? 2 : i == B_AL ? 8 : i < B_STG ? 1 : i < B_PE ? 4 : i >= B_PUB ? 256 : 128;
}
__host__ __device__ constexpr bool bar_first(int i) { return i < B_WF + 2 && (i & 7) < 2; }

__global__ void __launch_bounds__(NTHREADS, 1) fused_kernel(const __grid_constant__ Params p) {
  extern __shared__ __align__(1024) uint8_t smem[];
  constexpr uint32_t sb = 1024;
  if (s32(smem) != sb) return;
  const int tid = threadIdx.x, lane = tid & 31;
  const int warp = __shfl_sync(~0u, tid >> 5, 0);
  if (tid == 32) {
    asm volatile("prefetch.tensormap [%0];" ::"l"(&p.mapX) : "memory");
    asm volatile("prefetch.tensormap [%0];" ::"l"(&p.mapW3) : "memory");
  }
  const int cta = blockIdx.x - (gridDim.x == NCTA + 4 ? 0 : 4);
  if ((unsigned)cta >= NCTA) {
    if (blockIdx.x < NCTA + 4) colsum_cta(p, sb, blockIdx.x & 3, tid);
    return;
  }
  const int rb = ((cta >> 4) & 3) * 4 + ((cta >> 2) & 3), hg = (cta >> 6) * 4 + (cta & 3);
  const uint32_t bar = sb + SM_BAR;
  auto ld_x0 = [&](int half, int c) {
    const uint32_t b = bar + 8 * (B_XF + 8 * half + c);
    mbar_expect(b, PG);
    tma_ld(sb + x_page(half, c) * PG, &p.mapX, c * 64, (16 * half + rb) * 64, b);
  };
  auto ld_x1 = [&](int half, int c, int b0) {
    const uint32_t b = bar + 8 * b0;
    mbar_expect(b, PG);
    tma_ld(sb + (8 * half + c) * PG, &p.mapXT, (16 * half + rb) * 64, DM + c * 64, b);
  };
  auto ld_w = [&](int c) {
    const uint32_t b = bar + 8 * (B_WF + c);
    mbar_expect(b, 3 * PG);
    tma_ld3(sb + w_page(c) * PG, &p.mapW3, hg * 64, c * 64, 0, b);
  };

  if (tid == 0) TS(0);
  if (tid == 480) LTS(0);
  if (warp == 0 && elect_one()) {
#pragma unroll
    for (int i = 0; i < B_WF + 2; i++)
      if (bar_first(i)) mbar_init(bar + 8 * i, 1);
    asm volatile("fence.mbarrier_init.release.cluster;" ::: "memory");
    fence_async_smem();
    ld_x0(0, 0);
    ld_w(0); ld_x0(1, 0);
    ld_x0(0, 1); ld_w(1); ld_x0(1, 1);
    TS(1);
  }
  __syncwarp();
  if (warp >= 1 && warp < 8 && elect_one()) {
    if (warp < 4) {
#pragma unroll
      for (int i = 2; i < 8; i++) mbar_init(bar + 8 * (8 * warp - 8 + i), 1);
    } else {
#pragma unroll
      for (int i = 0; i < 12; i++) mbar_init(bar + 8 * (12 * warp - 24 + i), 1);
    }
    asm volatile("fence.mbarrier_init.release.cluster;" ::: "memory");
  }
  if (warp == 15 && elect_one()) {
#pragma unroll
    for (int i = 72; i < B_COUNT; i++) mbar_init(bar + 8 * i, bar_count(i));
    asm volatile("fence.mbarrier_init.release.cluster;" ::: "memory");
  }

  if (warp < 8) {
    bar_sync(0, NTHREADS);
    asm volatile("setmaxnreg.inc.sync.aligned.u32 %0;" ::"n"(R_CONS));
    const int cw = __shfl_sync(~0u, opaque_tid() >> 5, 0);
    const int wg = cw >> 2, w = cw & 3;
    if (tid == 0) TS(2);
#pragma unroll 1
    for (int layer = 0; layer < 2; layer++) {
      attn_phase(p, sb, layer, rb, hg, wg, w);
      uint32_t A0[68], A1[68];
      proj_phase(p, sb, layer, rb, hg, A0, A1);
      conv_phase(p, sb, layer, cta, A0, A1);
    }
    if (wg == 0) mbar_wait(bar + 8 * (B_TF + 1), 0);
    if (tid == 128) TS(8);
    final_tile(p, sb + (16 + wg) * PG, 256 * wg + 32 * (cta >> 4), 1024 + 64 * (cta & 15), 2 + wg);
    if (tid == 128) TS(9);
    if (tid == 128) LTS(1);
    if (tid == 0) LTE();
  } else if (warp < 12) {
    asm volatile("setmaxnreg.dec.sync.aligned.u32 %0;" ::"n"(R_HELP));
    const int ht = tid - 256;
    {
      unsigned ep0 = 0;
      if (ht == 0) ep0 = ld_relaxed(&g_cnt[C_CS * 32]);
      const bf16 dsk = p.dskip[cv_chan(cta, ht & 3)];
      const ModeIn in0 = load_modes(p, cv_chan(cta, ht >> 6), ht & 63), in1 = load_modes(p, cv_chan(cta, 2 + (ht >> 6)), ht & 63);
      if (ht < 48) sts128f(sb + SM_STG + ht * 16, 0.f, 0.f, 0.f, 1.f);
      bar_sync(0, NTHREADS);
      if (ht == 0) {
        sts32(sb + SM_EP, ep0);
        mbar_arrive(bar + 8 * B_EP);
      }
      if (ht >= 124) sts16(sb + SM_RED + 24 + 2 * (ht & 3), __bfloat16_as_ushort(dsk));
      kernel_gen(p, sb, cta, ht, in0, in1);
      if (ht < 48) sts128f(sb + SM_KGT + ht * 16, 0.f, 0.f, 0.f, 1.f);
      fence_async_smem();
      bar_sync(4, 128);
      if (ht == 0) mbar_arrive(bar + 8 * B_KG);
    }
#pragma unroll 1
    for (int layer = 0; layer < 2; layer++) {
      const int early = LPRE && layer;
      if (early) mbar_wait(bar + 8 * (B_DN + 13), 1);
      mbar_wait(bar + 8 * (early ? XGATE : B_PDONE), layer);
      expand_taps(sb, opaque_tid() - 256, early);
      mbar_arrive(bar + 8 * B_PE);
      TSW(0);
      mbar_wait(bar + 8 * B_PDONE, layer);
      expand_far(sb, opaque_tid() - 256);
      {
        const int i = opaque_tid() - 256;
        if (i < 32) sts128(sb + cv_u(i >> 3) + ((i >> 2) & 1) * CV_UH + (128 + (i & 3)) * 16, make_uint4(0, 0, 0, 0));
        mbar_wait(bar + 8 * B_RC, layer);
        mbar_wait(bar + 8 * B_GB, layer);
        TSW(13);
        conv_prep<0>(sb, layer, cta, i);
        mbar_arrive(bar + 8 * B_U);
      }
      mbar_wait(bar + 8 * (B_PDONE + 1), layer);
      bar_sync(4, 128);
#pragma unroll 1
      for (int lc = 0; lc < 4; lc += 2) {
        conv_sums(sb, lc, opaque_tid() - 256);
        TSW(1 + lc);
      }
      mbar_wait(bar + 8 * (B_GB + 1), layer);
      conv_prep<1>(sb, layer, cta, opaque_tid() - 256);
      mbar_arrive(bar + 8 * B_U1);
      TSW(4);
      if (layer == 0) {
        const int c = __shfl_sync(~0u, (opaque_tid() >> 5) & 3, 0);
        int phase = 0;
#pragma unroll 1
        for (int k = 0; k < 3; k++) {
          const int page = (k ? 4 + 4 * k : 0) + c, b = B_XR + 4 * (k & 1) + c;
          const uint32_t a = sb + page * PG + lane * 128 + (lane & 7) * 16 + (lane >> 3) * 4;
          int it = k == 2 ? phase : 0;
#pragma unroll 1
          for (; it < MAX_RETRY; it++) {
            mbar_wait(bar + 8 * b, it & 1);
            const uint32_t v0 = lds32(a), v1 = lds32(a + 4096);
            if (__all_sync(~0u, v0 != UNSET && v1 != UNSET)) break;
            if (elect_one()) { fence_async_smem(); ld_x1(page >> 3, page & 7, b); }
            __syncwarp();
            RETRY(3);
          }
          if (k == 0) phase = it + 1;
          if (lane == 0) mbar_arrive(bar + 8 * (B_XF + page));
        }
      }
    }
    mbar_wait(bar + 8 * B_TF, 0);
#pragma unroll 1
    for (int k = 0; k < 2; k++) final_tile(p, sb + 18 * PG + k * 4096, 256 * k + 32 * (cta >> 4), 64 * (cta & 15), 4);
    if (ht == 0) LTE();
  } else {
    asm volatile("setmaxnreg.dec.sync.aligned.u32 %0;" ::"n"(R_AGENT));
    bar_sync(0, NTHREADS);
    auto done = [&](int half, int c, int layer) { mbar_wait(bar + 8 * (B_DN + 8 * half + c), layer); };
    auto publish = [&](int layer, int k) {
      mbar_wait(bar + 8 * (B_PUB + k), layer);
      red_relaxed(&g_cnt[(layer ? C_F + 8 * k + (cta >> 4) : C_C + k) * 32]);
      if (!layer && k == 0) red_release(&g_cnt[(C_C + 3) * 32]);
      TS(16 + layer * 56 + 40 + 7 + k);
    };
    if (warp == 12) {
      if (elect_one()) {
#pragma unroll 1
        for (int layer = 0; layer < 2; layer++) {
          auto ld_xe = [&](int c) {
            const uint32_t b = bar + 8 * (B_XF + c);
            mbar_expect(b, PG);
            if (layer == 0) tma_ld(sb + x_page(0, c) * PG, &p.mapX, c * 64, rb * 64, b);
            else tma_ld(sb + x_page(0, c) * PG, &p.mapXT, rb * 64, DM + c * 64, b);
          };
          if (layer == 0) {
            ld_x0(0, 2); ld_w(2); ld_x0(1, 2);
            if (hg >= 3) {
              mbar_expect(bar + 8 * B_SC, PG);
              tma_ld(sb + P_R * PG, &p.mapX, hg * 64, rb * 64, bar + 8 * B_SC);
            }
            if (rb < 4) tma_prefetch3(&p.mapW3, hg * 64, (4 + rb) * 64, 0);
            ld_x0(0, 3); ld_w(3); ld_x0(1, 3); ld_x0(0, 4); ld_x0(1, 4);
            done(0, 0, 0); done(1, 0, 0);
            ld_w(4);
            ld_x0(1, 5); ld_x0(1, 6); ld_x0(1, 7);
            done(0, 1, 0); done(1, 1, 0);
            ld_w(5);
            if (rb < 8) tma_prefetch5(&p.mapWo, hg * 64, rb * 2);
            done(0, 2, 0);
            fence_async_smem();
            ld_xe(5); ld_xe(6); ld_xe(7);
          } else {
            mbar_wait(bar + 8 * B_PDONE, 0);
            mbar_wait(bar + 8 * (B_PDONE + 1), 0);
            mbar_wait(bar + 8 * (WPRE == 1 ? B_U : B_GB + 1), 0);
            ld_w(0); ld_w(1);
            mbar_wait(bar + 8 * B_U1, 0);
            fence_async_smem();
            ld_w(2);
            mbar_wait(bar + 8 * (B_PUB + 2), 0);
            fence_async_smem();
            ld_w(3);
            spin_until(&g_cnt[(C_C + 3) * 32], ((lds32(sb + SM_EP) / NCTA) + 1) * NCTA);
            fence_async_global();
            if (hg >= 3) {
              mbar_expect(bar + 8 * B_SC, PG);
              tma_ld(sb + P_R * PG, &p.mapXT, rb * 64, DM + hg * 64, bar + 8 * B_SC);
            }
            ld_xe(4);
            done(0, 2, 1);
            fence_async_smem();
            ld_xe(5); ld_xe(6); ld_xe(7);
            done(1, 0, 1);
            ld_w(4);
            done(1, 1, 1);
            ld_w(5);
          }
          done(1, 2, layer);
          fence_async_smem();
          ld_w(6); ld_w(7);
          auto ld_res = [&](int half) {
            const uint32_t b = bar + 8 * (B_RF + half);
            mbar_expect(b, PG);
            if (layer == 0) tma_ld(sb + (half ? 2 : P_R) * PG, &p.mapX, hg * 64, (16 * half + rb) * 64, b);
            else tma_ld(sb + (half ? 2 : P_R) * PG, &p.mapXT, (16 * half + rb) * 64, DM + hg * 64, b);
          };
          done(0, 4, layer); done(1, 3, layer);
          fence_async_smem();
          mbar_expect(bar + 8 * B_WOF, 8 * PG);
#pragma unroll 1
          for (int c = 0; c < 8; c++) {
            if (c == 5) { ld_res(0); done(1, 4, layer); }
            tma_ld5(sb + wo_page(c) * PG, &p.mapWo, hg * 64, c * 2, bar + 8 * B_WOF);
          }
          done(0, 7, layer);
          fence_async_global();
          ld_res(1);
          if (layer) mbar_wait(bar + 8 * B_RS, 0);
          fence_async_global();
#pragma unroll
          for (int half = 0; half < 2; half++) {
            float* stats = g_stats + (layer * 32 + 16 * half + rb) * 192;
            unsigned* cnt = &g_cnt[(C_G + 2 * layer + half) * 32];
            mbar_wait(bar + 8 * (B_STG + half), layer);
            tma_st(&p.mapXT, (16 * half + rb) * 64, 2 * layer * DM + hg * 64, sb + (P_R + half) * PG);
            bulk_red_add_f32(stats, sb + (half ? SM_KGT : SM_STG), 768);
            bulk_commit();
            red_relaxed(cnt);
            if (half == 0) mbar_arrive(bar + 8 * B_PG);
            bulk_wait_read();
            mbar_arrive(bar + 8 * (B_PST + half));
          }
        }
      }
    } else if (warp == 13) {
      mbar_wait(bar + 8 * B_EP, 0);
      const unsigned e1 = (lds32(sb + SM_EP) / NCTA) + 1;
      auto ld_o = [&](int layer) {
#pragma unroll 1
        for (int half = 0; half < 2; half++) {
          done(1, 7, layer);
          mbar_wait(bar + 8 * B_OST, layer);
          if (half) mbar_wait(bar + 8 * (B_OST + 1), layer);
          fence_async_smem();
#pragma unroll
          for (int c = 0; c < 4; c++) mbar_expect(bar + 8 * (B_OF + 4 * half + c), 2 * PG);
          spin_hint(&g_cnt[(C_O + layer * 32 + 16 * half + rb) * 32], e1 * 32);
#pragma unroll
          for (int c = 0; c < 4; c++) {
            if (LPRE && c == 2 && half && layer) { mbar_wait(bar + 8 * B_AL, 0); fence_async_smem(); }
            bulk_ld(sb + o_page(half, c) * PG, g_O + ((layer * 32 + 16 * half + rb) * 4 + c) * PG, 2 * PG, bar + 8 * (B_OF + 4 * half + c));
          }
        }
      };
      if (elect_one()) {
        mbar_wait(bar + 8 * (B_WF + 2), 0);
        asm volatile("prefetch.tensormap [%0];" ::"l"(&p.mapXT) : "memory");
        asm volatile("prefetch.tensormap [%0];" ::"l"(&p.mapWo) : "memory");
        spin_until(&g_cnt[C_Z * 32], e1 * NCTA);
        mbar_arrive(bar + 8 * B_ZF);
        TS(3);
        ld_o(0);
#pragma unroll 1
        for (int k = 0; k < 3; k++) {
          mbar_wait(bar + 8 * (B_PUB + k), 0);
          if (k == 2) {
#pragma unroll 1
            for (int c = 0; c < 4; c++) mbar_wait(bar + 8 * (B_XF + c), 1);
          }
          fence_async_smem();
          spin_hint(&g_cnt[(C_C + k) * 32], e1 * NCTA);
          TS(10 + k);
#pragma unroll
          for (int c = 0; c < 4; c++) ld_x1(k != 0, (k & 2) * 2 + c, B_XR + 4 * (k & 1) + c);
        }
        ld_o(1);
#pragma unroll 1
        for (int k = 0; k < 2; k++) {
          mbar_wait(bar + 8 * (B_PUB + k), 1);
          spin_hint(&g_cnt[(C_F + 8 * k + (cta >> 4)) * 32], e1 * 16);
          mbar_arrive(bar + 8 * (B_TF + k));
        }
      }
    } else if (warp == 14) {
      mbar_wait(bar + 8 * B_EP, 0);
      const unsigned e1 = (lds32(sb + SM_EP) / NCTA) + 1;
      done(0, 1, 0);
      {
        const uint2* cp = g_colsum + (hg * 192 + lane);
        uint2 v[6];
        bool ok;
        int it = 0;
        do {
          ok = true;
#pragma unroll
          for (int i = 0; i < 6; i++) {
            asm volatile("ld.relaxed.gpu.global.v2.u32 {%0,%1}, [%2];" : "=r"(v[i].x), "=r"(v[i].y) : "l"(cp + 32 * i) : "memory");
            ok = ok && v[i].y == e1;
          }
          if (++it > (1 << 22)) __trap();
        } while (!__all_sync(~0u, ok));
#pragma unroll
        for (int i = 0; i < 6; i++) sts32f(sb + SM_CS + 4 * (lane + 32 * i), __uint_as_float(v[i].x));
      }
      __syncwarp();
      if (elect_one()) {
        mbar_wait(bar + 8 * B_ZF, 0);
        mbar_arrive(bar + 8 * B_LN);
        red_relaxed(&g_cnt[C_CS * 32]);
        TS(13);
#pragma unroll 1
        for (int i = 0; i < 4; i++) {
          const int layer = i >> 1;
          mbar_wait(bar + 8 * (B_PST + (i & 1)), layer);
          const uint32_t b = bar + 8 * (B_GB + 1);
          const bf16* xin = g_xT + ((size_t)2 * layer * DM + 2 * cta) * LSEQ + 1024;
          if (i & 1) {
            fence_async_smem();
            mbar_expect(b, 12288 + PG);
          }
          spin_hint(&g_cnt[(C_G + i) * 32], e1 * NCTA);
          if (i & 1) {
            bulk_ld(sb + CV_ST, g_stats + (layer * 32 + 16) * 192, 12288, b);
#pragma unroll
            for (int lc = 0; lc < 4; lc++) bulk_ld(sb + cv_x(1, lc), xin + cv_chan(0, lc) * LSEQ, 2048, b);
            TS(14 + layer);
            publish(layer, 1);
          } else {
            mbar_arrive(bar + 8 * B_GB);
          }
        }
      }
    } else {
      const uint4 u = make_uint4(UNSET, UNSET, UNSET, UNSET);
      if (lane < 24) stg128((uint4*)g_stats + cta * 24 + lane, make_uint4(0, 0, 0, 0));
      if (lane < 16) stg128(g_rows + LSEQ + cta * 16 + lane, make_uint4(0, 0, 0, 0));
#pragma unroll 4
      for (int i = 0; i < 16; i++) stg128(g_halo + cta * 512 + 32 * i + lane, u);
#pragma unroll 4
      for (int i = 0; i < 16; i++) stg128(((i & 8) ? (uint4*)g_xT : (uint4*)g_O) + cta * 1024 + (i & 7) * 128 + (lane >> 1) * 8 + (lane & 1), u);
      __syncwarp();
      if (elect_one()) red_release(&g_cnt[C_Z * 32]);
      __syncwarp();
#pragma unroll 1
      for (int layer = 0; layer < 2; layer++) {
        auto reset_done = [&](int s) {
          spin_until(&g_cnt[(C_R + s) * 32], (lds32(sb + SM_EP) / NCTA) * 4 + 4);
          mbar_arrive(bar + 8 * (s == 1 ? B_LN : s == 2 ? B_RS : B_RC));
          if (s) TS(16 + 40 + 9 + s);
        };
        if (layer && elect_one()) reset_done(1);
        __syncwarp();
#pragma unroll 1
        for (int half = 0; half < 2; half++) {
          done(half, 2, layer);
          const uint4* src = g_rows + (layer * LSEQ + (16 * half + rb) * 64 + (opaque_tid() & 31));
          uint4 a, b;
          int it = 0;
          do {
            a = ld_tagged(src); b = ld_tagged(src + 32);
          } while (!__all_sync(~0u, (a.z | a.w) == __float_as_uint(8.f) && (b.z | b.w) == __float_as_uint(8.f)) && ++it < (1 << 20));
          float m0 = __uint_as_float(a.x) * (1.f / DM), m1 = __uint_as_float(b.x) * (1.f / DM);
          float r0 = rsqrt_approx(fmaxf(__uint_as_float(a.y) * (1.f / DM) - m0 * m0, 0.f) + 1e-5f);
          float r1 = rsqrt_approx(fmaxf(__uint_as_float(b.y) * (1.f / DM) - m1 * m1, 0.f) + 1e-5f);
          if (half) done(0, 7, layer);
          const uint32_t dst = sb + ln_off(half) + ((lane >> 4) * 8 + (lane & 7)) * 16 + (lane & 8);
          asm volatile("st.shared.v2.f32 [%0], {%1,%2};" ::"r"(dst), "f"(m0), "f"(r0) : "memory");
          asm volatile("st.shared.v2.f32 [%0], {%1,%2};" ::"r"(dst + 256), "f"(m1), "f"(r1) : "memory");
          __syncwarp();
          if (elect_one()) { mbar_arrive(bar + 8 * (B_LN + half)); TS(16 + layer * 56 + 40 + 14 + half); }
        }
        if (layer && lane < 16) stg128(g_rows + cta * 16 + (opaque_tid() & 31), make_uint4(0, 0, 0, 0));
        if (elect_one()) {
          if (layer) reset_done(2);
          reset_done(3 * layer);
          publish(layer, 0);
          if (!layer) publish(layer, 2);
        }
        __syncwarp();
      }
    }
  }
}

typedef CUresult (*EncodeFn)(CUtensorMap*, CUtensorMapDataType, cuuint32_t, void*, const cuuint64_t*, const cuuint64_t*,
                             const cuuint32_t*, const cuuint32_t*, CUtensorMapInterleave, CUtensorMapSwizzle,
                             CUtensorMapL2promotion, CUtensorMapFloatOOBfill);

static void make_map(EncodeFn enc, CUtensorMap* m, void* ptr, uint64_t cols, uint64_t rows, uint32_t box_rows) {
  cuuint64_t dims[2] = {cols, rows};
  cuuint64_t strides[1] = {cols * 2};
  cuuint32_t box[2] = {64, box_rows};
  cuuint32_t es[2] = {1, 1};
  enc(m, CU_TENSOR_MAP_DATA_TYPE_BFLOAT16, 2, ptr, dims, strides, box, es, CU_TENSOR_MAP_INTERLEAVE_NONE,
      CU_TENSOR_MAP_SWIZZLE_128B, CU_TENSOR_MAP_L2_PROMOTION_L2_128B, CU_TENSOR_MAP_FLOAT_OOB_FILL_NONE);
}
static void make_map3(EncodeFn enc, CUtensorMap* m, void* ptr, uint64_t d0, uint64_t cols, uint64_t rows, uint64_t blk_stride,
                      uint64_t nblocks, uint32_t nblk) {
  cuuint64_t dims[3] = {d0, rows, nblocks};
  cuuint64_t strides[2] = {cols * 2, blk_stride * 2};
  cuuint32_t box[3] = {64, 64, nblk};
  cuuint32_t es[3] = {1, 1, 1};
  enc(m, CU_TENSOR_MAP_DATA_TYPE_BFLOAT16, 3, ptr, dims, strides, box, es, CU_TENSOR_MAP_INTERLEAVE_NONE,
      CU_TENSOR_MAP_SWIZZLE_128B, CU_TENSOR_MAP_L2_PROMOTION_L2_128B, CU_TENSOR_MAP_FLOAT_OOB_FILL_NONE);
}

extern "C" void kernel_launch(void* const* d_in, const int* in_sizes, int n_in, void* d_out, int out_size) {
  static Params prm;
  static void* cached[13] = {nullptr};
  static bool attr_done = false;
  static int grid = NCTA + 4;
  bool same = attr_done && cached[12] == d_out;
  for (int i = 0; i < 12 && same; i++) same = cached[i] == d_in[i];
  if (!same) {
    void* fn = nullptr;
    cudaDriverEntryPointQueryResult qr;
    cudaGetDriverEntryPoint("cuTensorMapEncodeTiled", &fn, cudaEnableDefault, &qr);
    EncodeFn enc = (EncodeFn)fn;
    void* pXT;
    cudaGetSymbolAddress(&pXT, g_xT);
    make_map(enc, &prm.mapX, d_in[0], DM, LSEQ, 64);
    make_map(enc, &prm.mapXT, pXT, LSEQ, 4 * DM, 64);
    {
      cuuint64_t dims[5] = {DM, 2, 4, 4, 16};
      cuuint64_t strides[4] = {DM * 2, 8 * DM * 2, 2 * DM * 2, 32 * DM * 2};
      cuuint32_t box[5] = {64, 2, 4, 4, 2};
      cuuint32_t es[5] = {1, 1, 1, 1, 1};
      enc(&prm.mapWo, CU_TENSOR_MAP_DATA_TYPE_BFLOAT16, 5, d_in[2], dims, strides, box, es, CU_TENSOR_MAP_INTERLEAVE_NONE,
          CU_TENSOR_MAP_SWIZZLE_128B, CU_TENSOR_MAP_L2_PROMOTION_L2_128B, CU_TENSOR_MAP_FLOAT_OOB_FILL_NONE);
    }
    make_map3(enc, &prm.mapW3, d_in[1], DM, 3 * DM, DM, DM, 3, 3);
    prm.out = (bf16*)d_out;
    prm.a_re = (const bf16*)d_in[4]; prm.a_im = (const bf16*)d_in[5];
    prm.b_re = (const bf16*)d_in[6]; prm.b_im = (const bf16*)d_in[7];
    prm.c_re = (const bf16*)d_in[8]; prm.c_im = (const bf16*)d_in[9];
    prm.log_dt = (const bf16*)d_in[10]; prm.dskip = (const bf16*)d_in[11];
    int dev = 0, sms = 0;
    cudaGetDevice(&dev);
    cudaDeviceGetAttribute(&sms, cudaDevAttrMultiProcessorCount, dev);
    grid = sms >= NCTA + 4 ? NCTA + 4 : NCTA + 5;
    cudaFuncSetAttribute(fused_kernel, cudaFuncAttributeMaxDynamicSharedMemorySize, SM_TOTAL);
    for (int i = 0; i < 12; i++) cached[i] = d_in[i];
    cached[12] = d_out;
    attr_done = true;
  }
  fused_kernel<<<grid, NTHREADS, SM_TOTAL>>>(prm);
}
```

```cpp
#include <cuda_runtime.h>
#include <cuda_bf16.h>
#include <cuda.h>
#include <stdint.h>

typedef __nv_bfloat16 bf16;

constexpr int LSEQ = 2048;
constexpr int DM = 512;
constexpr int NCTA = 128;
constexpr int NTHREADS = 512;
#define R_CONS 200
#define R_HELP 88
#define R_AGENT 24
#define TURN0 4
#define TURN1 4

constexpr int PG = 8192;
constexpr int P_R = 25;
__host__ __device__ constexpr int x_page(int half, int c) { return half ? 8 + c : c < 5 ? c : c - 5; }
__host__ __device__ constexpr int w_page(int c) { return (c & 3) < 3 ? 16 + 3 * (c & 3) : c < 4 ? 5 : 8; }
__host__ __device__ constexpr int wo_page(int c) { return c < 5 ? 3 + c : 11 + c; }
__host__ __device__ constexpr int o_page(int half, int pair) { return half ? (pair ? 25 - 2 * pair : 0) : 8 + 2 * pair; }
constexpr int SM_KGB = (P_R + 1) * PG;
constexpr int SM_KC = 27 * PG;
constexpr int KC_STRIDE = 648;
__host__ __device__ constexpr int kc_off(int lc) { return SM_KC + (lc & 1) * 2 * KC_STRIDE + (lc < 2 ? 3328 : 0); }
constexpr int SM_KGT = SM_KC + 3328 + 2592;
constexpr int SM_CS = SM_KGT + 2048;
constexpr int SM_RED = SM_CS + 768;
constexpr int SM_EP = SM_RED + 16;
constexpr int SM_STG = SM_RED + 32;
constexpr int SM_LN = SM_STG + 768;
__host__ __device__ constexpr int ln_off(int half) { return half ? PG + 4096 : SM_LN; }
constexpr int SM_BAR = SM_LN + 512;
constexpr int SM_TS = SM_BAR + 704;
constexpr int SM_TOTAL = SM_TS + 512;
static_assert(SM_TOTAL <= 232448 && SM_STG % 16 == 0 && SM_KGT % 16 == 0, "shared memory");

constexpr int CV_UH = 140 * 16;
__host__ __device__ constexpr int cv_u(int lc) { return (8 + 2 * lc) * PG; }
__host__ __device__ constexpr int cv_pe(int lc, int early) { return early ? 19 * PG + lc * 4480 : cv_u(lc) + 4480; }
__host__ __device__ constexpr int cv_pb1(int lc, int w) { return w ? cv_u(lc) + 8960 + (w - 1) * 2048 : 7 * PG + lc * 2048; }
__host__ __device__ constexpr int cv_fa(int lc) { return cv_pb1(lc, 1) + 128; }
__host__ __device__ constexpr int cv_dump(int lc) { return cv_u(lc) + 16256; }
__host__ __device__ constexpr int cv_pb0(int lc, int w) { return lc * PG + w * 2048; }
__host__ __device__ constexpr int cv_se(int lc) { return 5 * PG + lc * 4096; }
__host__ __device__ constexpr int cv_so(int lc) { return cv_se(lc) + 2048; }
__host__ __device__ constexpr int cv_x(int half, int lc) { return (P_R + half) * PG + lc * 2048; }
constexpr int CV_ST = 22 * PG;
__host__ __device__ constexpr int cv_chan(int cta, int lc) { return 2 * cta + (lc & 1) + 256 * (lc >> 1); }

enum {
  B_XF = 0,
  B_WF = 16,
  B_OF = 24,
  B_DN = 32,
  B_PG = 46,
  B_XR = 48,
  B_RF = 56,
  B_PST = 58,
  B_GB = 60,
  B_TF = 62,
  B_RT = 64,
  B_RS = 66,
  B_RC = 67,
  B_WOF = 68,
  B_ZF = 69,
  B_EP = 70,
  B_KG = 71,
  B_SC = 37,
  B_LN = 72,
  B_END = 38,
  B_STG = 74,
  B_OST = 76,
  B_PDONE = 78,
  B_PE = 80,
  B_U = 81,
  B_U1 = 82,
  B_PUB = 83,
  B_AL = 86,
  B_COUNT = 87
};

enum {
  C_CS = 0,
  C_G = 1,
  C_C = 5,
  C_O = 21,
  C_Z = 85,
  C_R = 86,
  C_F = 90,
  C_COUNT = 106
};

__device__ unsigned g_cnt[C_COUNT * 32];
__device__ __align__(1024) bf16 g_O[2 * LSEQ * DM];
__device__ __align__(1024) bf16 g_xT[4 * DM * LSEQ];
__device__ __align__(1024) float g_stats[2 * 32 * 192];
__device__ __align__(1024) uint2 g_colsum[3 * DM];
__device__ __align__(1024) uint4 g_halo[32 * 8 * 256];
__device__ __align__(1024) uint4 g_rows[2 * LSEQ];
#define TS(i) do { } while (0)
#define TSW(k) do { if ((threadIdx.x & 127) == 0) TS(16 + layer * 56 + (threadIdx.x >> 7) * 20 + (k)); } while (0)
#define TSG(k) do { } while (0)

#define RETRY(i) do { } while (0)
#define LTS(i) do { } while (0)
#define LTE() do { } while (0)

struct Params {
  CUtensorMap mapX, mapW3, mapXT, mapWo;
  bf16* out;
  const bf16 *a_re, *a_im, *b_re, *b_im, *c_re, *c_im, *log_dt, *dskip;
};

__device__ __forceinline__ uint32_t s32(const void* p) { return (uint32_t)__cvta_generic_to_shared(p); }
__device__ __forceinline__ void mbar_init(uint32_t b, int c) { asm volatile("mbarrier.init.shared::cta.b64 [%0], %1;" ::"r"(b), "r"(c) : "memory"); }
__device__ __forceinline__ void mbar_expect(uint32_t b, int bytes) { asm volatile("mbarrier.arrive.expect_tx.shared::cta.b64 _, [%0], %1;" ::"r"(b), "r"(bytes) : "memory"); }
__device__ __forceinline__ void mbar_arrive(uint32_t b) { asm volatile("mbarrier.arrive.shared::cta.b64 _, [%0];" ::"r"(b) : "memory"); }
__device__ __forceinline__ void mbar_wait(uint32_t b, int parity) {
  asm volatile("{\n.reg .pred p;\nWAIT_LOOP:\nmbarrier.try_wait.parity.shared::cta.b64 p, [%0], %1;\n@p bra WAIT_DONE;\nbra WAIT_LOOP;\nWAIT_DONE:\n}" ::"r"(b), "r"(parity) : "memory");
}
__device__ __forceinline__ bool mbar_test(uint32_t b, int parity) {
  uint32_t ok;
  asm volatile("{\n.reg .pred p;\nmbarrier.test_wait.parity.shared::cta.b64 p, [%1], %2;\nselp.u32 %0, 1, 0, p;\n}" : "=r"(ok) : "r"(b), "r"(parity) : "memory");
  return ok != 0;
}
__device__ __forceinline__ int opaque_tid() { int v; asm volatile("mov.u32 %0, %%tid.x;" : "=r"(v)); return v; }
__device__ __forceinline__ bool elect_one() {
  uint32_t r;
  asm volatile("{\n.reg .pred p;\nelect.sync _|p, 0xffffffff;\nselp.u32 %0, 1, 0, p;\n}" : "=r"(r));
  return r != 0;
}
__device__ __forceinline__ void tma_ld(uint32_t dst, const CUtensorMap* m, int c0, int c1, uint32_t bar) {
  asm volatile("cp.async.bulk.tensor.2d.shared::cluster.global.mbarrier::complete_tx::bytes [%0], [%1, {%3, %4}], [%2];"
               ::"r"(dst), "l"(m), "r"(bar), "r"(c0), "r"(c1) : "memory");
}
__device__ __forceinline__ void tma_ld3(uint32_t dst, const CUtensorMap* m, int c0, int c1, int c2, uint32_t bar) {
  asm volatile("cp.async.bulk.tensor.3d.shared::cluster.global.mbarrier::complete_tx::bytes [%0], [%1, {%3, %4, %5}], [%2];"
               ::"r"(dst), "l"(m), "r"(bar), "r"(c0), "r"(c1), "r"(c2) : "memory");
}
__device__ __forceinline__ void tma_ld5(uint32_t dst, const CUtensorMap* m, int c0, int c4, uint32_t bar) {
  asm volatile("cp.async.bulk.tensor.5d.shared::cluster.global.mbarrier::complete_tx::bytes [%0], [%1, {%3, 0, 0, 0, %4}], [%2];"
               ::"r"(dst), "l"(m), "r"(bar), "r"(c0), "r"(c4) : "memory");
}
__device__ __forceinline__ void tma_prefetch5(const CUtensorMap* m, int c0, int c4) {
  asm volatile("cp.async.bulk.prefetch.tensor.5d.L2.global.tile [%0, {%1, 0, 0, 0, %2}];" ::"l"(m), "r"(c0), "r"(c4) : "memory");
}
__device__ __forceinline__ void tma_prefetch3(const CUtensorMap* m, int c0, int c1, int c2) {
  asm volatile("cp.async.bulk.prefetch.tensor.3d.L2.global.tile [%0, {%1, %2, %3}];" ::"l"(m), "r"(c0), "r"(c1), "r"(c2) : "memory");
}
__device__ __forceinline__ void tma_st(const CUtensorMap* m, int c0, int c1, uint32_t src) {
  asm volatile("cp.async.bulk.tensor.2d.global.shared::cta.bulk_group [%0, {%2, %3}], [%1];" ::"l"(m), "r"(src), "r"(c0), "r"(c1) : "memory");
}
__device__ __forceinline__ void bulk_ld(uint32_t dst, const void* src, int bytes, uint32_t bar) {
  asm volatile("cp.async.bulk.shared::cluster.global.mbarrier::complete_tx::bytes [%0], [%1], %2, [%3];" ::"r"(dst), "l"(src), "r"(bytes), "r"(bar) : "memory");
}
__device__ __forceinline__ void bulk_red_add_f32(void* dst, uint32_t src, int bytes) {
  asm volatile("cp.reduce.async.bulk.global.shared::cta.bulk_group.add.f32 [%0], [%1], %2;" ::"l"(dst), "r"(src), "r"(bytes) : "memory");
}
__device__ __forceinline__ void bulk_commit() { asm volatile("cp.async.bulk.commit_group;" ::: "memory"); }
__device__ __forceinline__ void fence_async_smem() { asm volatile("fence.proxy.async.shared::cta;" ::: "memory"); }
__device__ __forceinline__ void fence_async_global() { asm volatile("fence.proxy.async.global;" ::: "memory"); }
__device__ __forceinline__ void bar_sync(int id, int n) { asm volatile("bar.sync %0, %1;" ::"r"(id), "r"(n) : "memory"); }
__device__ __forceinline__ void bar_arrive(int id, int n) { asm volatile("bar.arrive %0, %1;" ::"r"(id), "r"(n) : "memory"); }
__device__ __forceinline__ bool bar_or(int id, int n, bool v) {
  uint32_t r;
  asm volatile("{\n.reg .pred p, q;\nsetp.ne.u32 q, %3, 0;\nbar.red.or.pred p, %1, %2, q;\nselp.u32 %0, 1, 0, p;\n}" : "=r"(r) : "r"(id), "r"(n), "r"((uint32_t)v) : "memory");
  return r != 0;
}
__device__ __forceinline__ void bulk_wait_read() { asm volatile("cp.async.bulk.wait_group.read 0;" ::: "memory"); }
__device__ __forceinline__ void stg128(void* p, uint4 v) { asm volatile("st.relaxed.gpu.global.v4.u32 [%0], {%1,%2,%3,%4};" ::"l"(p), "r"(v.x), "r"(v.y), "r"(v.z), "r"(v.w) : "memory"); }
constexpr uint32_t UNSET = 0xffffffffu;
constexpr int MAX_RETRY = 1 << 16;
__device__ __forceinline__ void wg_fence() { asm volatile("wgmma.fence.sync.aligned;" ::: "memory"); }
__device__ __forceinline__ void wg_commit() { asm volatile("wgmma.commit_group.sync.aligned;" ::: "memory"); }
template <int N> __device__ __forceinline__ void wg_wait() { asm volatile("wgmma.wait_group.sync.aligned %0;" ::"n"(N) : "memory"); }
__device__ __forceinline__ uint64_t mkdesc(uint32_t addr, uint32_t lbo, uint32_t sbo, int sw) {
  return (uint64_t)((addr & 0x3FFFF) >> 4) | ((uint64_t)(lbo >> 4) << 16) | ((uint64_t)(sbo >> 4) << 32) | ((uint64_t)sw << 62);
}
__device__ __forceinline__ void ldsm4(uint32_t* r, uint32_t a) {
  asm volatile("ldmatrix.sync.aligned.m8n8.x4.shared.b16 {%0,%1,%2,%3}, [%4];" : "=r"(r[0]), "=r"(r[1]), "=r"(r[2]), "=r"(r[3]) : "r"(a) : "memory");
}
__device__ __forceinline__ void ldsm4t(uint32_t* r, uint32_t a) {
  asm volatile("ldmatrix.sync.aligned.m8n8.x4.trans.shared.b16 {%0,%1,%2,%3}, [%4];" : "=r"(r[0]), "=r"(r[1]), "=r"(r[2]), "=r"(r[3]) : "r"(a) : "memory");
}
__device__ __forceinline__ void stsm4(uint32_t a, uint32_t r0, uint32_t r1, uint32_t r2, uint32_t r3) {
  asm volatile("stmatrix.sync.aligned.m8n8.x4.shared.b16 [%0], {%1,%2,%3,%4};" ::"r"(a), "r"(r0), "r"(r1), "r"(r2), "r"(r3) : "memory");
}
__device__ __forceinline__ void stsm4t(uint32_t a, uint32_t r0, uint32_t r1, uint32_t r2, uint32_t r3) {
  asm volatile("stmatrix.sync.aligned.m8n8.x4.trans.shared.b16 [%0], {%1,%2,%3,%4};" ::"r"(a), "r"(r0), "r"(r1), "r"(r2), "r"(r3) : "memory");
}
__device__ __forceinline__ uint32_t movm_t(uint32_t a) { uint32_t r; asm volatile("movmatrix.sync.aligned.m8n8.trans.b16 %0, %1;" : "=r"(r) : "r"(a)); return r; }
__device__ __forceinline__ uint32_t lds32(uint32_t a) { uint32_t v; asm volatile("ld.shared.b32 %0, [%1];" : "=r"(v) : "r"(a) : "memory"); return v; }
__device__ __forceinline__ float2 lds64f(uint32_t a) { float2 v; asm volatile("ld.shared.v2.f32 {%0,%1}, [%2];" : "=f"(v.x), "=f"(v.y) : "r"(a) : "memory"); return v; }
__device__ __forceinline__ float4 lds128f(uint32_t a) { float4 v; asm volatile("ld.shared.v4.f32 {%0,%1,%2,%3}, [%4];" : "=f"(v.x), "=f"(v.y), "=f"(v.z), "=f"(v.w) : "r"(a) : "memory"); return v; }
__device__ __forceinline__ uint4 lds128(uint32_t a) { uint4 v; asm volatile("ld.shared.v4.b32 {%0,%1,%2,%3}, [%4];" : "=r"(v.x), "=r"(v.y), "=r"(v.z), "=r"(v.w) : "r"(a) : "memory"); return v; }
__device__ __forceinline__ void sts128(uint32_t a, uint4 v) { asm volatile("st.shared.v4.b32 [%0], {%1,%2,%3,%4};" ::"r"(a), "r"(v.x), "r"(v.y), "r"(v.z), "r"(v.w) : "memory"); }
__device__ __forceinline__ void sts128f(uint32_t a, float x, float y, float z, float w) { asm volatile("st.shared.v4.f32 [%0], {%1,%2,%3,%4};" ::"r"(a), "f"(x), "f"(y), "f"(z), "f"(w) : "memory"); }
__device__ __forceinline__ void sts32f(uint32_t a, float v) { asm volatile("st.shared.f32 [%0], %1;" ::"r"(a), "f"(v) : "memory"); }
__device__ __forceinline__ void sts16(uint32_t a, uint16_t v) { asm volatile("st.shared.u16 [%0], %1;" ::"r"(a), "h"(v) : "memory"); }
__device__ __forceinline__ uint32_t lds16(uint32_t a) { uint16_t v; asm volatile("ld.shared.u16 %0, [%1];" : "=h"(v) : "r"(a) : "memory"); return v; }
__device__ __forceinline__ uint32_t packbf(float lo, float hi) { uint32_t r; asm("cvt.rn.bf16x2.f32 %0, %1, %2;" : "=r"(r) : "f"(hi), "f"(lo)); return r; }
__device__ __forceinline__ float bf_lo(uint32_t v) { return __uint_as_float(v << 16); }
__device__ __forceinline__ float bf_hi(uint32_t v) { return __uint_as_float(v & 0xffff0000u); }
__device__ __forceinline__ float ex2(float x) { float r; asm("ex2.approx.ftz.f32 %0, %1;" : "=f"(r) : "f"(x)); return r; }
__device__ __forceinline__ float rsqrt_approx(float x) { float r; asm("rsqrt.approx.ftz.f32 %0, %1;" : "=f"(r) : "f"(x)); return r; }
__device__ __forceinline__ float rcp_approx(float x) { float r; asm("rcp.approx.ftz.f32 %0, %1;" : "=f"(r) : "f"(x)); return r; }
__device__ __forceinline__ void mma_bf16(float* d, const uint32_t* a, uint32_t b0, uint32_t b1) {
  asm("mma.sync.aligned.m16n8k16.row.col.f32.bf16.bf16.f32 {%0,%1,%2,%3}, {%4,%5,%6,%7}, {%8,%9}, {%0,%1,%2,%3};"
               : "+f"(d[0]), "+f"(d[1]), "+f"(d[2]), "+f"(d[3]) : "r"(a[0]), "r"(a[1]), "r"(a[2]), "r"(a[3]), "r"(b0), "r"(b1));
}
__device__ __forceinline__ void red_release(unsigned* p) { asm volatile("red.release.gpu.global.add.u32 [%0], 1;" ::"l"(p) : "memory"); }
__device__ __forceinline__ void red_relaxed(unsigned* p) { asm volatile("red.relaxed.gpu.global.add.u32 [%0], 1;" ::"l"(p) : "memory"); }
__device__ __forceinline__ unsigned ld_relaxed(const unsigned* p) { unsigned v; asm volatile("ld.relaxed.gpu.global.u32 %0, [%1];" : "=r"(v) : "l"(p) : "memory"); return v; }
__device__ __forceinline__ void spin_until(const unsigned* p, unsigned target) {
  int it = 0;
  while ((int)(ld_relaxed(p) - target) < 0) {
    if (++it > (1 << 23)) __trap();
  }
}
__device__ __forceinline__ void spin_hint(const unsigned* p, unsigned target) {
  spin_until(p, target);
}
__device__ __forceinline__ uint4 ld_tagged(const uint4* p) { uint4 v; asm volatile("ld.relaxed.gpu.global.v4.u32 {%0,%1,%2,%3}, [%4];" : "=r"(v.x), "=r"(v.y), "=r"(v.z), "=r"(v.w) : "l"(p) : "memory"); return v; }
__device__ __forceinline__ uint32_t hadd2(uint32_t a, uint32_t b) { uint32_t r; asm("add.rn.bf16x2 %0, %1, %2;" : "=r"(r) : "r"(a), "r"(b)); return r; }

__device__ __forceinline__ uint32_t hfma2(uint32_t a, uint32_t b, uint32_t c) { uint32_t r; asm("fma.rn.bf16x2 %0, %1, %2, %3;" : "=r"(r) : "r"(a), "r"(b), "r"(c)); return r; }
__device__ __forceinline__ void sts32(uint32_t a, uint32_t v) { asm volatile("st.shared.u32 [%0], %1;" ::"r"(a), "r"(v) : "memory"); }

template <int N> __device__ __forceinline__ void acc_fence(float* a) {
#pragma unroll
  for (int i = 0; i < N; i++) asm volatile("" : "+f"(a[i]) :: "memory");
}

template<int N,int TB> __device__ __forceinline__ void wgmma_rs(float* d, const uint32_t* a, uint64_t db, int sd);
template<int N,int TA,int TB> __device__ __forceinline__ void wgmma_ss(float* d, uint64_t da, uint64_t db, int sd);
template<> __device__ __forceinline__ void wgmma_rs<64,0>(float* d, const uint32_t* a, uint64_t db, int sd) {
  asm volatile("{\n.reg .pred p;\nsetp.ne.b32 p, %37, 0;\nwgmma.mma_async.sync.aligned.m64n64k16.f32.bf16.bf16 {%0,%1,%2,%3,%4,%5,%6,%7,%8,%9,%10,%11,%12,%13,%14,%15,%16,%17,%18,%19,%20,%21,%22,%23,%24,%25,%26,%27,%28,%29,%30,%31}, {%32,%33,%34,%35}, %36, p, 1, 1, 0;\n}\n"
   : "+f"(d[0]),"+f"(d[1]),"+f"(d[2]),"+f"(d[3]),"+f"(d[4]),"+f"(d[5]),"+f"(d[6]),"+f"(d[7]),"+f"(d[8]),"+f"(d[9]),"+f"(d[10]),"+f"(d[11]),"+f"(d[12]),"+f"(d[13]),"+f"(d[14]),"+f"(d[15]),"+f"(d[16]),"+f"(d[17]),"+f"(d[18]),"+f"(d[19]),"+f"(d[20]),"+f"(d[21]),"+f"(d[22]),"+f"(d[23]),"+f"(d[24]),"+f"(d[25]),"+f"(d[26]),"+f"(d[27]),"+f"(d[28]),"+f"(d[29]),"+f"(d[30]),"+f"(d[31])
   : "r"(a[0]), "r"(a[1]), "r"(a[2]), "r"(a[3]), "l"(db), "r"(sd));
}
template<> __device__ __forceinline__ void wgmma_rs<56,0>(float* d, const uint32_t* a, uint64_t db, int sd) {
  asm volatile("{\n.reg .pred p;\nsetp.ne.b32 p, %33, 0;\nwgmma.mma_async.sync.aligned.m64n56k16.f32.bf16.bf16 {%0,%1,%2,%3,%4,%5,%6,%7,%8,%9,%10,%11,%12,%13,%14,%15,%16,%17,%18,%19,%20,%21,%22,%23,%24,%25,%26,%27}, {%28,%29,%30,%31}, %32, p, 1, 1, 0;\n}\n"
   : "+f"(d[0]),"+f"(d[1]),"+f"(d[2]),"+f"(d[3]),"+f"(d[4]),"+f"(d[5]),"+f"(d[6]),"+f"(d[7]),"+f"(d[8]),"+f"(d[9]),"+f"(d[10]),"+f"(d[11]),"+f"(d[12]),"+f"(d[13]),"+f"(d[14]),"+f"(d[15]),"+f"(d[16]),"+f"(d[17]),"+f"(d[18]),"+f"(d[19]),"+f"(d[20]),"+f"(d[21]),"+f"(d[22]),"+f"(d[23]),"+f"(d[24]),"+f"(d[25]),"+f"(d[26]),"+f"(d[27])
   : "r"(a[0]), "r"(a[1]), "r"(a[2]), "r"(a[3]), "l"(db), "r"(sd));
}
template<> __device__ __forceinline__ void wgmma_rs<48,0>(float* d, const uint32_t* a, uint64_t db, int sd) {
  asm volatile("{\n.reg .pred p;\nsetp.ne.b32 p, %29, 0;\nwgmma.mma_async.sync.aligned.m64n48k16.f32.bf16.bf16 {%0,%1,%2,%3,%4,%5,%6,%7,%8,%9,%10,%11,%12,%13,%14,%15,%16,%17,%18,%19,%20,%21,%22,%23}, {%24,%25,%26,%27}, %28, p, 1, 1, 0;\n}\n"
   : "+f"(d[0]),"+f"(d[1]),"+f"(d[2]),"+f"(d[3]),"+f"(d[4]),"+f"(d[5]),"+f"(d[6]),"+f"(d[7]),"+f"(d[8]),"+f"(d[9]),"+f"(d[10]),"+f"(d[11]),"+f"(d[12]),"+f"(d[13]),"+f"(d[14]),"+f"(d[15]),"+f"(d[16]),"+f"(d[17]),"+f"(d[18]),"+f"(d[19]),"+f"(d[20]),"+f"(d[21]),"+f"(d[22]),"+f"(d[23])
   : "r"(a[0]), "r"(a[1]), "r"(a[2]), "r"(a[3]), "l"(db), "r"(sd));
}
template<> __device__ __forceinline__ void wgmma_rs<40,0>(float* d, const uint32_t* a, uint64_t db, int sd) {
  asm volatile("{\n.reg .pred p;\nsetp.ne.b32 p, %25, 0;\nwgmma.mma_async.sync.aligned.m64n40k16.f32.bf16.bf16 {%0,%1,%2,%3,%4,%5,%6,%7,%8,%9,%10,%11,%12,%13,%14,%15,%16,%17,%18,%19}, {%20,%21,%22,%23}, %24, p, 1, 1, 0;\n}\n"
   : "+f"(d[0]),"+f"(d[1]),"+f"(d[2]),"+f"(d[3]),"+f"(d[4]),"+f"(d[5]),"+f"(d[6]),"+f"(d[7]),"+f"(d[8]),"+f"(d[9]),"+f"(d[10]),"+f"(d[11]),"+f"(d[12]),"+f"(d[13]),"+f"(d[14]),"+f"(d[15]),"+f"(d[16]),"+f"(d[17]),"+f"(d[18]),"+f"(d[19])
   : "r"(a[0]), "r"(a[1]), "r"(a[2]), "r"(a[3]), "l"(db), "r"(sd));
}
template<> __device__ __forceinline__ void wgmma_rs<32,0>(float* d, const uint32_t* a, uint64_t db, int sd) {
  asm volatile("{\n.reg .pred p;\nsetp.ne.b32 p, %21, 0;\nwgmma.mma_async.sync.aligned.m64n32k16.f32.bf16.bf16 {%0,%1,%2,%3,%4,%5,%6,%7,%8,%9,%10,%11,%12,%13,%14,%15}, {%16,%17,%18,%19}, %20, p, 1, 1, 0;\n}\n"
   : "+f"(d[0]),"+f"(d[1]),"+f"(d[2]),"+f"(d[3]),"+f"(d[4]),"+f"(d[5]),"+f"(d[6]),"+f"(d[7]),"+f"(d[8]),"+f"(d[9]),"+f"(d[10]),"+f"(d[11]),"+f"(d[12]),"+f"(d[13]),"+f"(d[14]),"+f"(d[15])
   : "r"(a[0]), "r"(a[1]), "r"(a[2]), "r"(a[3]), "l"(db), "r"(sd));
}
template<> __device__ __forceinline__ void wgmma_rs<24,0>(float* d, const uint32_t* a, uint64_t db, int sd) {
  asm volatile("{\n.reg .pred p;\nsetp.ne.b32 p, %17, 0;\nwgmma.mma_async.sync.aligned.m64n24k16.f32.bf16.bf16 {%0,%1,%2,%3,%4,%5,%6,%7,%8,%9,%10,%11}, {%12,%13,%14,%15}, %16, p, 1, 1, 0;\n}\n"
   : "+f"(d[0]),"+f"(d[1]),"+f"(d[2]),"+f"(d[3]),"+f"(d[4]),"+f"(d[5]),"+f"(d[6]),"+f"(d[7]),"+f"(d[8]),"+f"(d[9]),"+f"(d[10]),"+f"(d[11])
   : "r"(a[0]), "r"(a[1]), "r"(a[2]), "r"(a[3]), "l"(db), "r"(sd));
}
template<> __device__ __forceinline__ void wgmma_rs<16,0>(float* d, const uint32_t* a, uint64_t db, int sd) {
  asm volatile("{\n.reg .pred p;\nsetp.ne.b32 p, %13, 0;\nwgmma.mma_async.sync.aligned.m64n16k16.f32.bf16.bf16 {%0,%1,%2,%3,%4,%5,%6,%7}, {%8,%9,%10,%11}, %12, p, 1, 1, 0;\n}\n"
   : "+f"(d[0]),"+f"(d[1]),"+f"(d[2]),"+f"(d[3]),"+f"(d[4]),"+f"(d[5]),"+f"(d[6]),"+f"(d[7])
   : "r"(a[0]), "r"(a[1]), "r"(a[2]), "r"(a[3]), "l"(db), "r"(sd));
}
template<> __device__ __forceinline__ void wgmma_rs<8,0>(float* d, const uint32_t* a, uint64_t db, int sd) {
  asm volatile("{\n.reg .pred p;\nsetp.ne.b32 p, %9, 0;\nwgmma.mma_async.sync.aligned.m64n8k16.f32.bf16.bf16 {%0,%1,%2,%3}, {%4,%5,%6,%7}, %8, p, 1, 1, 0;\n}\n"
   : "+f"(d[0]),"+f"(d[1]),"+f"(d[2]),"+f"(d[3])
   : "r"(a[0]), "r"(a[1]), "r"(a[2]), "r"(a[3]), "l"(db), "r"(sd));
}
template<> __device__ __forceinline__ void wgmma_ss<64,1,0>(float* d, uint64_t da, uint64_t db, int sd) {
  asm volatile("{\n.reg .pred p;\nsetp.ne.b32 p, %34, 0;\nwgmma.mma_async.sync.aligned.m64n64k16.f32.bf16.bf16 {%0,%1,%2,%3,%4,%5,%6,%7,%8,%9,%10,%11,%12,%13,%14,%15,%16,%17,%18,%19,%20,%21,%22,%23,%24,%25,%26,%27,%28,%29,%30,%31}, %32, %33, p, 1, 1, 1, 0;\n}\n"
   : "+f"(d[0]),"+f"(d[1]),"+f"(d[2]),"+f"(d[3]),"+f"(d[4]),"+f"(d[5]),"+f"(d[6]),"+f"(d[7]),"+f"(d[8]),"+f"(d[9]),"+f"(d[10]),"+f"(d[11]),"+f"(d[12]),"+f"(d[13]),"+f"(d[14]),"+f"(d[15]),"+f"(d[16]),"+f"(d[17]),"+f"(d[18]),"+f"(d[19]),"+f"(d[20]),"+f"(d[21]),"+f"(d[22]),"+f"(d[23]),"+f"(d[24]),"+f"(d[25]),"+f"(d[26]),"+f"(d[27]),"+f"(d[28]),"+f"(d[29]),"+f"(d[30]),"+f"(d[31])
   : "l"(da), "l"(db), "r"(sd));
}
template<> __device__ __forceinline__ void wgmma_ss<64,0,1>(float* d, uint64_t da, uint64_t db, int sd) {
  asm volatile("{\n.reg .pred p;\nsetp.ne.b32 p, %34, 0;\nwgmma.mma_async.sync.aligned.m64n64k16.f32.bf16.bf16 {%0,%1,%2,%3,%4,%5,%6,%7,%8,%9,%10,%11,%12,%13,%14,%15,%16,%17,%18,%19,%20,%21,%22,%23,%24,%25,%26,%27,%28,%29,%30,%31}, %32, %33, p, 1, 1, 0, 1;\n}\n"
   : "+f"(d[0]),"+f"(d[1]),"+f"(d[2]),"+f"(d[3]),"+f"(d[4]),"+f"(d[5]),"+f"(d[6]),"+f"(d[7]),"+f"(d[8]),"+f"(d[9]),"+f"(d[10]),"+f"(d[11]),"+f"(d[12]),"+f"(d[13]),"+f"(d[14]),"+f"(d[15]),"+f"(d[16]),"+f"(d[17]),"+f"(d[18]),"+f"(d[19]),"+f"(d[20]),"+f"(d[21]),"+f"(d[22]),"+f"(d[23]),"+f"(d[24]),"+f"(d[25]),"+f"(d[26]),"+f"(d[27]),"+f"(d[28]),"+f"(d[29]),"+f"(d[30]),"+f"(d[31])
   : "l"(da), "l"(db), "r"(sd));
}
template<> __device__ __forceinline__ void wgmma_ss<192,0,1>(float* d, uint64_t da, uint64_t db, int sd) {
  asm volatile("{\n.reg .pred p;\nsetp.ne.b32 p, %98, 0;\nwgmma.mma_async.sync.aligned.m64n192k16.f32.bf16.bf16 {%0,%1,%2,%3,%4,%5,%6,%7,%8,%9,%10,%11,%12,%13,%14,%15,%16,%17,%18,%19,%20,%21,%22,%23,%24,%25,%26,%27,%28,%29,%30,%31,%32,%33,%34,%35,%36,%37,%38,%39,%40,%41,%42,%43,%44,%45,%46,%47,%48,%49,%50,%51,%52,%53,%54,%55,%56,%57,%58,%59,%60,%61,%62,%63,%64,%65,%66,%67,%68,%69,%70,%71,%72,%73,%74,%75,%76,%77,%78,%79,%80,%81,%82,%83,%84,%85,%86,%87,%88,%89,%90,%91,%92,%93,%94,%95}, %96, %97, p, 1, 1, 0, 1;\n}\n"
   : "+f"(d[0]),"+f"(d[1]),"+f"(d[2]),"+f"(d[3]),"+f"(d[4]),"+f"(d[5]),"+f"(d[6]),"+f"(d[7]),"+f"(d[8]),"+f"(d[9]),"+f"(d[10]),"+f"(d[11]),"+f"(d[12]),"+f"(d[13]),"+f"(d[14]),"+f"(d[15]),"+f"(d[16]),"+f"(d[17]),"+f"(d[18]),"+f"(d[19]),"+f"(d[20]),"+f"(d[21]),"+f"(d[22]),"+f"(d[23]),"+f"(d[24]),"+f"(d[25]),"+f"(d[26]),"+f"(d[27]),"+f"(d[28]),"+f"(d[29]),"+f"(d[30]),"+f"(d[31]),"+f"(d[32]),"+f"(d[33]),"+f"(d[34]),"+f"(d[35]),"+f"(d[36]),"+f"(d[37]),"+f"(d[38]),"+f"(d[39]),"+f"(d[40]),"+f"(d[41]),"+f"(d[42]),"+f"(d[43]),"+f"(d[44]),"+f"(d[45]),"+f"(d[46]),"+f"(d[47]),"+f"(d[48]),"+f"(d[49]),"+f"(d[50]),"+f"(d[51]),"+f"(d[52]),"+f"(d[53]),"+f"(d[54]),"+f"(d[55]),"+f"(d[56]),"+f"(d[57]),"+f"(d[58]),"+f"(d[59]),"+f"(d[60]),"+f"(d[61]),"+f"(d[62]),"+f"(d[63]),"+f"(d[64]),"+f"(d[65]),"+f"(d[66]),"+f"(d[67]),"+f"(d[68]),"+f"(d[69]),"+f"(d[70]),"+f"(d[71]),"+f"(d[72]),"+f"(d[73]),"+f"(d[74]),"+f"(d[75]),"+f"(d[76]),"+f"(d[77]),"+f"(d[78]),"+f"(d[79]),"+f"(d[80]),"+f"(d[81]),"+f"(d[82]),"+f"(d[83]),"+f"(d[84]),"+f"(d[85]),"+f"(d[86]),"+f"(d[87]),"+f"(d[88]),"+f"(d[89]),"+f"(d[90]),"+f"(d[91]),"+f"(d[92]),"+f"(d[93]),"+f"(d[94]),"+f"(d[95])
   : "l"(da), "l"(db), "r"(sd));
}
template<> __device__ __forceinline__ void wgmma_ss<192,1,1>(float* d, uint64_t da, uint64_t db, int sd) {
  asm volatile("{\n.reg .pred p;\nsetp.ne.b32 p, %98, 0;\nwgmma.mma_async.sync.aligned.m64n192k16.f32.bf16.bf16 {%0,%1,%2,%3,%4,%5,%6,%7,%8,%9,%10,%11,%12,%13,%14,%15,%16,%17,%18,%19,%20,%21,%22,%23,%24,%25,%26,%27,%28,%29,%30,%31,%32,%33,%34,%35,%36,%37,%38,%39,%40,%41,%42,%43,%44,%45,%46,%47,%48,%49,%50,%51,%52,%53,%54,%55,%56,%57,%58,%59,%60,%61,%62,%63,%64,%65,%66,%67,%68,%69,%70,%71,%72,%73,%74,%75,%76,%77,%78,%79,%80,%81,%82,%83,%84,%85,%86,%87,%88,%89,%90,%91,%92,%93,%94,%95}, %96, %97, p, 1, 1, 1, 1;\n}\n"
   : "+f"(d[0]),"+f"(d[1]),"+f"(d[2]),"+f"(d[3]),"+f"(d[4]),"+f"(d[5]),"+f"(d[6]),"+f"(d[7]),"+f"(d[8]),"+f"(d[9]),"+f"(d[10]),"+f"(d[11]),"+f"(d[12]),"+f"(d[13]),"+f"(d[14]),"+f"(d[15]),"+f"(d[16]),"+f"(d[17]),"+f"(d[18]),"+f"(d[19]),"+f"(d[20]),"+f"(d[21]),"+f"(d[22]),"+f"(d[23]),"+f"(d[24]),"+f"(d[25]),"+f"(d[26]),"+f"(d[27]),"+f"(d[28]),"+f"(d[29]),"+f"(d[30]),"+f"(d[31]),"+f"(d[32]),"+f"(d[33]),"+f"(d[34]),"+f"(d[35]),"+f"(d[36]),"+f"(d[37]),"+f"(d[38]),"+f"(d[39]),"+f"(d[40]),"+f"(d[41]),"+f"(d[42]),"+f"(d[43]),"+f"(d[44]),"+f"(d[45]),"+f"(d[46]),"+f"(d[47]),"+f"(d[48]),"+f"(d[49]),"+f"(d[50]),"+f"(d[51]),"+f"(d[52]),"+f"(d[53]),"+f"(d[54]),"+f"(d[55]),"+f"(d[56]),"+f"(d[57]),"+f"(d[58]),"+f"(d[59]),"+f"(d[60]),"+f"(d[61]),"+f"(d[62]),"+f"(d[63]),"+f"(d[64]),"+f"(d[65]),"+f"(d[66]),"+f"(d[67]),"+f"(d[68]),"+f"(d[69]),"+f"(d[70]),"+f"(d[71]),"+f"(d[72]),"+f"(d[73]),"+f"(d[74]),"+f"(d[75]),"+f"(d[76]),"+f"(d[77]),"+f"(d[78]),"+f"(d[79]),"+f"(d[80]),"+f"(d[81]),"+f"(d[82]),"+f"(d[83]),"+f"(d[84]),"+f"(d[85]),"+f"(d[86]),"+f"(d[87]),"+f"(d[88]),"+f"(d[89]),"+f"(d[90]),"+f"(d[91]),"+f"(d[92]),"+f"(d[93]),"+f"(d[94]),"+f"(d[95])
   : "l"(da), "l"(db), "r"(sd));
}

template <bool TR>
__device__ __forceinline__ void gemm_section(float* acc, float& mean0, float& mean1, float& rstd0, float& rstd1,
                                             uint32_t sb, int blk, int hg, int wg, int w, int lane) {
  constexpr int layer = TR ? 1 : 0;
  constexpr int TURN = TR ? TURN1 : TURN0;
  constexpr int LSTAT = TURN < 4 ? TURN - 1 : 3;
  const uint32_t bar = sb + SM_BAR;
  const int g = lane >> 2, t = lane & 3;
  const bool leader = (w == 0) && (lane == 0);
  const int statpos = hg < 3 ? 1 : wg ? LSTAT : TR ? 3 : 2;
  const bool copy = hg >= 3 && wg == 0;
  const int cut = wg ? TURN : 4;
  auto wait_full = [&](int c) {
    mbar_wait(bar + 8 * (B_XF + 8 * wg + c), layer);
    mbar_wait(bar + 8 * (B_WF + c), layer);
  };
  auto peek = [&](int c) {
    const bool x = mbar_test(bar + 8 * (B_XF + 8 * wg + c), layer), y = mbar_test(bar + 8 * (B_WF + c), layer);
    return x && y;
  };
  const uint64_t da0 = mkdesc(sb, TR ? 8192 : 16, 1024, 1), db0 = mkdesc(sb, 8192, 1024, 1);
  uint32_t xt = wg ? 0xfedcba98u : 0x21043210u;
  uint64_t wt = 0x0816131005161310ull;
  uint64_t da = da0 + ((xt & 15) << 9), db = db0 + (16 << 9);
  auto issue = [&](int c, int first) {
    wg_fence();
#pragma unroll
    for (int ks = 0; ks < 4; ks++) wgmma_ss<192, TR ? 1 : 0, 1>(acc, da + (TR ? ks * 128 : ks * 2), db + ks * 128, !first || ks != 0);
    wg_commit();
    xt >>= 4; wt >>= 8;
    da = da0 + ((xt & 15) << 9); db = db0 + (((uint32_t)wt & 31) << 9);
  };
  wait_full(0);
  bool ready = peek(1);
  issue(0, 1);
  TSW(0);
#pragma unroll 1
  for (int c = 1; c < cut; c++) {
    if (!ready) wait_full(c);
    issue(c, 0);
    ready = peek(c + 1);
    wg_wait<1>();
    if (leader) mbar_arrive(bar + 8 * (B_DN + 8 * wg + c - 1));
    if (wg == 1 && c == cut - 1) {
      wg_wait<0>();
      if (leader) mbar_arrive(bar + 8 * (B_DN + 8 + c));
    }
    if (c == statpos) {
      mbar_wait(bar + 8 * (copy ? B_SC : B_XF + 8 * wg + hg), layer);
      uint32_t A[16];
      const uint32_t xb = sb + (copy ? P_R : 8 * wg + hg) * PG;
#pragma unroll
      for (int ks = 0; ks < 4; ks++) {
        if (!TR) {
          const int row = 16 * w + (lane & 15), kc = 2 * ks + (lane >> 4);
          ldsm4(&A[4 * ks], xb + row * 128 + ((kc ^ (row & 7)) << 4));
        } else {
          const int k = 16 * ks + (lane & 7) + 8 * (lane >> 4), pc = 2 * w + ((lane >> 3) & 1);
          ldsm4t(&A[4 * ks], xb + k * 128 + ((pc ^ (k & 7)) << 4));
        }
      }
      float s0 = 0.f, q0 = 0.f, s1 = 0.f, q1 = 0.f;
#pragma unroll
      for (int i = 0; i < 16; i += 2) {
        const float a = bf_lo(A[i]), b = bf_hi(A[i]), c_ = bf_lo(A[i + 1]), d = bf_hi(A[i + 1]);
        s0 += a + b; q0 = fmaf(a, a, q0); q0 = fmaf(b, b, q0);
        s1 += c_ + d; q1 = fmaf(c_, c_, q1); q1 = fmaf(d, d, q1);
      }
#pragma unroll
      for (int o = 1; o <= 2; o <<= 1) {
        s0 += __shfl_xor_sync(~0u, s0, o); q0 += __shfl_xor_sync(~0u, q0, o);
        s1 += __shfl_xor_sync(~0u, s1, o); q1 += __shfl_xor_sync(~0u, q1, o);
      }
      if (t < 2)
        asm volatile("red.relaxed.gpu.global.add.v4.f32 [%0], {%1,%2,%3,%4};" ::"l"(g_rows + layer * LSEQ + blk * 64 + 16 * w + g + 8 * t),
                     "f"(t ? s1 : s0), "f"(t ? q1 : q0), "f"(1.f), "f"(0.f) : "memory");
    }
  }
  if (wg == 1) {
#pragma unroll 1
    for (int c = cut; c < 8; c++) wait_full(c);
    ready = true;
    bar_sync(5, 256);
  }
#pragma unroll 1
  for (int c = cut; c < 8; c++) {
    if (!ready) wait_full(c);
    issue(c, 0);
    if (wg == 1) {
      wg_wait<2>();
      if (leader && c >= cut + 2) mbar_arrive(bar + 8 * (B_DN + 8 + c - 2));
    } else if (c == 7) {
      bar_arrive(5, 256);
    } else {
      ready = peek(c + 1);
      wg_wait<1>();
      if (leader && c < 6) mbar_arrive(bar + 8 * (B_DN + c - 1));
    }
  }
  mbar_wait(bar + 8 * (B_LN + wg), layer);
  const float4 ln = lds128f(sb + ln_off(wg) + (8 * w + g) * 16);
  mean0 = ln.x; rstd0 = ln.y; mean1 = ln.z; rstd1 = ln.w;
  wg_wait<0>();
  acc_fence<96>(acc);
  if (leader) mbar_arrive(bar + 8 * (B_DN + 8 * wg + 7));
}

__device__ __forceinline__ void attn_phase(const Params& p, uint32_t sb, int layer, int rb, int hg, int wg, int w) {
  const int lane = opaque_tid() & 31;
  const int g = lane >> 2, t = lane & 3;
  const uint32_t bar = sb + SM_BAR;
  const int blk = 16 * wg + rb;
  float acc[96];
  float2 cs[24];
  float mean0, mean1, rstd0, rstd1;
  if (layer) gemm_section<true>(acc, mean0, mean1, rstd0, rstd1, sb, blk, hg, wg, w, lane);
  else gemm_section<false>(acc, mean0, mean1, rstd0, rstd1, sb, blk, hg, wg, w, lane);
  TSW(1);
#pragma unroll
  for (int j = 8; j < 24; j++) cs[j] = lds64f(sb + SM_CS + 4 * (8 * j + 2 * t));
  const uint32_t kvx = sb + (wg ? 22 : 0) * PG;

  uint32_t kb[4][8], vb[4][8], qa[4][4];
  {
    const float nm0 = -mean0 * rstd0, nm1 = -mean1 * rstd1;
    const int st_row = 16 * w + (lane & 7) + 8 * ((lane >> 3) & 1);
    const uint32_t st_base = kvx + st_row * 256;
    const bool sender = (w == 3 && blk < 31);
    uint4* halo = &g_halo[(blk * 8 + hg) * 256 + lane];
    uint32_t r[4][2][4];
#pragma unroll
    for (int h = 0; h < 4; h++) {
#pragma unroll
      for (int kv = 0; kv < 2; kv++) {
#pragma unroll
        for (int dh = 0; dh < 2; dh++) {
          const int j = 8 + kv * 8 + 2 * h + dh;
          const float2 c2 = cs[j];
          const float v0 = fmaf(acc[4 * j + 0], rstd0, nm0 * c2.x), v1 = fmaf(acc[4 * j + 1], rstd0, nm0 * c2.y);
          const float v2 = fmaf(acc[4 * j + 2], rstd1, nm1 * c2.x), v3 = fmaf(acc[4 * j + 3], rstd1, nm1 * c2.y);
          r[h][kv][2 * dh] = packbf(v0, v1);
          r[h][kv][2 * dh + 1] = packbf(v2, v3);
        }
      }
      if (sender) {
        stg128(halo + (2 * h) * 32, make_uint4(r[h][0][0], r[h][0][2], r[h][0][1], r[h][0][3]));
        stg128(halo + (2 * h + 1) * 32, make_uint4(r[h][1][0], r[h][1][1], r[h][1][2], r[h][1][3]));
      }
    }
#pragma unroll
    for (int j = 0; j < 8; j++) cs[j] = lds64f(sb + SM_CS + 4 * (8 * j + 2 * t));
    mbar_wait(bar + 8 * (B_DN + 7), layer);
#pragma unroll
    for (int h = 0; h < 4; h++) {
#pragma unroll
      for (int kv = 0; kv < 2; kv++) {
        const int chunk = 4 * h + 2 * kv + (lane >> 4);
        if (w < 3) stsm4(st_base + (((chunk & 8) | ((chunk ^ st_row) & 7)) << 4), r[h][kv][0], r[h][kv][1], r[h][kv][2], r[h][kv][3]);
      }
      kb[h][4] = r[h][0][0]; kb[h][5] = r[h][0][2]; kb[h][6] = r[h][0][1]; kb[h][7] = r[h][0][3];
      vb[h][4] = movm_t(r[h][1][0]); vb[h][5] = movm_t(r[h][1][1]); vb[h][6] = movm_t(r[h][1][2]); vb[h][7] = movm_t(r[h][1][3]);
    }
#pragma unroll
    for (int h = 0; h < 4; h++) {
#pragma unroll
      for (int dh = 0; dh < 2; dh++) {
        const int j = 2 * h + dh;
        const float2 c2 = cs[j];
        qa[h][2 * dh] = packbf(fmaf(-mean0, c2.x, acc[4 * j + 0]), fmaf(-mean0, c2.y, acc[4 * j + 1]));
        qa[h][2 * dh + 1] = packbf(fmaf(-mean1, c2.x, acc[4 * j + 2]), fmaf(-mean1, c2.y, acc[4 * j + 3]));
      }
    }
  }
  bar_sync(2 + wg, 128);
  TSW(2);
  {
    const uint32_t prev_base = kvx + (16 * w - 16) * 256;
    const int mi = lane >> 3;
    const int r = 8 * (mi >> 1) + (lane & 7), r2 = 8 * (mi & 1) + (lane & 7);
    if (w != 0) {
#pragma unroll
      for (int h = 0; h < 4; h++) {
        const int ch = 4 * h + (mi & 1), ch2 = 4 * h + 2 + (mi >> 1);
        ldsm4(&kb[h][0], prev_base + r * 256 + (((ch & 8) | ((ch ^ r) & 7)) << 4));
        ldsm4t(&vb[h][0], prev_base + r2 * 256 + (((ch2 & 8) | ((ch2 ^ r2) & 7)) << 4));
      }
    } else if (blk > 0) {
      uint4* src = &g_halo[((blk - 1) * 8 + hg) * 256 + lane];
      uint4 hv[8];
      int it = 0;
      bool ok;
      do {
        ok = true;
#pragma unroll
        for (int i = 0; i < 8; i++) hv[i] = ld_tagged(src + i * 32);
#pragma unroll
        for (int i = 0; i < 8; i++) ok = ok && hv[i].x != UNSET;
      } while (!__all_sync(~0u, ok) && ++it < (1 << 20));
      if (layer == 0) {
#pragma unroll
        for (int i = 0; i < 2; i++) stg128(src + i * 128 + (lane >> 1) * 6, make_uint4(UNSET, UNSET, UNSET, UNSET));
      }
#pragma unroll
      for (int h = 0; h < 4; h++) {
        kb[h][0] = hv[2 * h].x; kb[h][1] = hv[2 * h].y; kb[h][2] = hv[2 * h].z; kb[h][3] = hv[2 * h].w;
        vb[h][0] = movm_t(hv[2 * h + 1].x); vb[h][1] = movm_t(hv[2 * h + 1].y);
        vb[h][2] = movm_t(hv[2 * h + 1].z); vb[h][3] = movm_t(hv[2 * h + 1].w);
      }
    } else {
#pragma unroll
      for (int h = 0; h < 4; h++)
#pragma unroll
        for (int k = 0; k < 4; k++) kb[h][k] = vb[h][k] = 0u;
    }
    TSW(3);
  }
  mbar_wait(bar + 8 * (B_DN + 15), layer);
  TSW(4);

  const bool first = (blk == 0 && w == 0);
  const int e = t - (g >> 1);
  const bool par = g & 1, epos = e >= 1;
  const uint32_t pmask = par ? 0xffff0000u : 0x0000ffffu;
  const uint32_t mB0 = epos ? pmask : 0u, mB1 = epos ? 0u : pmask;
  const float cl2 = 0.25f * 1.4426950408889634f;
  const float sc0 = rstd0 * cl2, sc1 = rstd1 * cl2;
  const float NEG = -INFINITY;
  float vA0[4], vB0[4], vA1[4], vB1[4];
#pragma unroll
  for (int h = 0; h < 4; h++) {
    float S[4][4];
#pragma unroll
    for (int j = 0; j < 4; j++) {
      S[j][0] = S[j][1] = S[j][2] = S[j][3] = 0.f;
      mma_bf16(S[j], qa[h], kb[h][2 * j], kb[h][2 * j + 1]);
    }
    vA0[h] = par ? S[1][1] : S[1][0];
    vB0[h] = epos ? (par ? S[0][1] : S[0][0]) : (par ? S[2][1] : S[2][0]);
    vA1[h] = par ? S[2][3] : S[2][2];
    vB1[h] = epos ? (par ? S[1][3] : S[1][2]) : (par ? S[3][3] : S[3][2]);
    if (first) { vA0[h] = NEG; if (epos) { vB0[h] = NEG; vB1[h] = NEG; } }
  }
  float m0[4], m1[4];
#pragma unroll
  for (int h = 0; h < 4; h++) { m0[h] = fmaxf(vA0[h], vB0[h]); m1[h] = fmaxf(vA1[h], vB1[h]); }
#pragma unroll
  for (int o = 1; o <= 2; o <<= 1) {
#pragma unroll
    for (int h = 0; h < 4; h++) {
      m0[h] = fmaxf(m0[h], __shfl_xor_sync(~0u, m0[h], o));
      m1[h] = fmaxf(m1[h], __shfl_xor_sync(~0u, m1[h], o));
    }
  }
  float O0[4][4], O1[4][4], Z[4][4];
#pragma unroll
  for (int h = 0; h < 4; h++) {
    const float mm0 = -m0[h] * sc0, mm1 = -m1[h] * sc1;
    const float pA0 = ex2(fmaf(vA0[h], sc0, mm0)), pB0 = ex2(fmaf(vB0[h], sc0, mm0));
    const float pA1 = ex2(fmaf(vA1[h], sc1, mm1)), pB1 = ex2(fmaf(vB1[h], sc1, mm1));
    const uint32_t hA0 = packbf(pA0, pA0), hB0 = packbf(pB0, pB0), hA1 = packbf(pA1, pA1), hB1 = packbf(pB1, pB1);
    const uint32_t P0[4] = {hB0 & mB0, 0u, hA0 & pmask, hB1 & mB0};
    const uint32_t P1[4] = {hB0 & mB1, hA1 & pmask, 0u, hB1 & mB1};
#pragma unroll
    for (int k = 0; k < 4; k++) O0[h][k] = O1[h][k] = Z[h][k] = 0.f;
    mma_bf16(O0[h], P0, vb[h][0], vb[h][1]); mma_bf16(O1[h], P0, vb[h][2], vb[h][3]); mma_bf16(Z[h], P0, 0x3f803f80u, 0x3f803f80u);
    mma_bf16(O0[h], P1, vb[h][4], vb[h][5]); mma_bf16(O1[h], P1, vb[h][6], vb[h][7]); mma_bf16(Z[h], P1, 0x3f803f80u, 0x3f803f80u);
  }
  if (lane == 0) mbar_arrive(bar + 8 * (B_OST + wg));
  uint4* op = (uint4*)g_O + ((layer * 32 + blk) * 8 + hg) * 512 + 64 * t + 16 * w + g;
#pragma unroll
  for (int h = 0; h < 4; h += 2) {
    const float i0 = rcp_approx(Z[h][0]), i1 = rcp_approx(Z[h][2]), j0 = rcp_approx(Z[h + 1][0]), j1 = rcp_approx(Z[h + 1][2]);
    stg128(op + 128 * h, make_uint4(packbf(O0[h][0] * i0, O0[h][1] * i0), packbf(O1[h][0] * i0, O1[h][1] * i0),
                                   packbf(O0[h + 1][0] * j0, O0[h + 1][1] * j0), packbf(O1[h + 1][0] * j0, O1[h + 1][1] * j0)));
    stg128(op + 128 * h + 8, make_uint4(packbf(O0[h][2] * i1, O0[h][3] * i1), packbf(O1[h][2] * i1, O1[h][3] * i1),
                                            packbf(O0[h + 1][2] * j1, O0[h + 1][3] * j1), packbf(O1[h + 1][2] * j1, O1[h + 1][3] * j1)));
  }
  TSW(5);
  __syncwarp();
  if (lane == 0) red_relaxed(&g_cnt[(C_O + layer * 32 + blk) * 32]);
  TSW(6);
}

__device__ __forceinline__ void conv_load(uint32_t* A, uint32_t pe);
__device__ __forceinline__ void proj_phase(const Params& p, uint32_t sb, int layer, int rb, int q, uint32_t* A0, uint32_t* A1) {
  const int lane = opaque_tid() & 31;
  const int wg = __shfl_sync(~0u, opaque_tid() >> 7, 0), w = __shfl_sync(~0u, (opaque_tid() >> 5) & 3, 0);
  const bool TR = layer != 0;
  const int t = lane & 3;
  const uint32_t bar = sb + SM_BAR;
  const uint32_t rbx = sb + (P_R + wg) * PG;
  const uint32_t rsrc = sb + (wg ? 2 : P_R) * PG;
  const int blk = 16 * wg + rb;
  mbar_wait(bar + 8 * (B_RF + wg), layer);
  mbar_wait(bar + 8 * B_WOF, layer);
  const uint32_t stg = sb + (wg ? SM_KGT : SM_STG);
  if (layer) {
    const uint32_t pe = sb + cv_pe(wg, 1) + 4 * (16 + 16 * w + (lane >> 2) - 2 * t);
    mbar_wait(bar + 8 * B_PE, 1);
    conv_load(A0, pe);
    conv_load(A1, pe + 2 * 4480);
    __syncwarp();
    if (lane == 0) mbar_arrive(bar + 8 * B_AL);
  } else {
#pragma unroll
    for (int i = 0; i < 68; i++) {
      asm volatile("mov.b32 %0, 0;" : "=r"(A0[i]));
      asm volatile("mov.b32 %0, 0;" : "=r"(A1[i]));
    }
  }
  bool clean = false, staged = false;
#pragma unroll 1
  for (int attempt = 0; attempt < MAX_RETRY; attempt++) {
  uint32_t res[16];
  if (!TR) {
#pragma unroll
    for (int j = 0; j < 8; j += 2) {
      const int mi = lane >> 3;
      const int row = 16 * w + (lane & 7) + 8 * (mi & 1), ch = j + (mi >> 1);
      ldsm4(&res[2 * j], rsrc + row * 128 + ((ch ^ (row & 7)) << 4));
    }
  } else {
#pragma unroll
    for (int j = 0; j < 8; j += 2) {
      const int mi = lane >> 3;
      const int line = 8 * (j + (mi >> 1)) + (lane & 7), pc = 2 * w + (mi & 1);
      ldsm4t(&res[2 * j], rsrc + line * 128 + ((pc ^ (line & 7)) << 4));
    }
  }
  float acc[32];
#pragma unroll
  for (int j = 0; j < 16; j++) { acc[2 * j] = bf_lo(res[j]); acc[2 * j + 1] = bf_hi(res[j]); }
  acc_fence<32>(acc);
  if (wg) mbar_wait(bar + 8 * B_PG, layer);
  const int wg2 = __shfl_sync(~0u, opaque_tid() >> 7, 0);
  const uint64_t da0 = mkdesc(sb, 1024, 128, 0), db0 = mkdesc(sb, 8192, 1024, 1);
#pragma unroll
  for (int c = 0; c < 4; c++) {
    mbar_wait(bar + 8 * (B_OF + 4 * wg + c), layer);
    if (c == 0) TSW(7);
    const uint64_t da = da0 + (uint32_t)(o_page(wg2, c) * 512);
#pragma unroll
    for (int ks = 0; ks < 8; ks++) {
      if (ks % 4 == 0) { if (ks) wg_commit(); if (wg2) wg_wait<0>(); wg_fence(); }
      wgmma_ss<64, 0, 1>(acc, da + ks * 128, db0 + wo_page(2 * c + (ks >> 2)) * 512 + (ks & 3) * 128, 1);
    }
    wg_commit();
  }
  if (wg) mbar_wait(bar + 8 * B_KG, 0);
  wg_wait<0>();
  acc_fence<32>(acc);
  TSW(8);
  if (!clean) {
    const float chk = acc[0] + acc[2];
    clean = __all_sync(~0u, chk == chk);
    if (clean && lane == 0) mbar_arrive(bar + 8 * (B_PDONE + wg));
  }
  float s0 = 0.f, q0 = 0.f, s1 = 0.f, q1 = 0.f;
  uint32_t o[16];
#pragma unroll
  for (int j = 0; j < 8; j++) {
    const float a = acc[4 * j], b = acc[4 * j + 1], c = acc[4 * j + 2], d = acc[4 * j + 3];
    o[2 * j] = packbf(a, b);
    o[2 * j + 1] = packbf(c, d);
    s0 += a + b; q0 = fmaf(a, a, q0); q0 = fmaf(b, b, q0);
    s1 += c + d; q1 = fmaf(c, c, q1); q1 = fmaf(d, d, q1);
  }
#pragma unroll
  for (int j = 0; j < 8; j += 2) {
    const int mi = lane >> 3;
    const int line = 8 * (j + (mi >> 1)) + (lane & 7), pc = 2 * w + (mi & 1);
    stsm4t(rbx + line * 128 + ((pc ^ (line & 7)) << 4), o[2 * j], o[2 * j + 1], o[2 * j + 2], o[2 * j + 3]);
  }
#pragma unroll
  for (int o2 = 1; o2 <= 2; o2 <<= 1) {
    s0 += __shfl_xor_sync(~0u, s0, o2); q0 += __shfl_xor_sync(~0u, q0, o2);
    s1 += __shfl_xor_sync(~0u, s1, o2); q1 += __shfl_xor_sync(~0u, q1, o2);
  }
  {
    const int i = 2 * (lane >> 2) + (t & 1), k = (i * 11) >> 5;
    const float v = (t == 0) ? s0 : (t == 1) ? q0 : (t == 2) ? s1 : q1;
    sts32f(stg + k * 128 + (2 * w + (t >> 1)) * 16 + (i - 3 * k) * 4, v);
  }
  TSW(9);
  fence_async_smem();
  if (attempt == 0 && clean) {
    staged = true;
    __syncwarp();
    if (lane == 0) mbar_arrive(bar + 8 * (B_STG + wg));
  }
  if (!bar_or(2 + wg, 128, !clean)) break;
  const int rtp = mbar_test(bar + 8 * (B_RT + wg), 0);
  bool unset = false;
#pragma unroll
  for (int i = 0; i < 4; i++) unset |= lds32(sb + o_page(wg, i) * PG + (32 * w + lane) * 128) == UNSET;
  if (!bar_or(2 + wg, 128, unset)) break;
  if (w == 0 && elect_one()) {
    fence_async_smem();
    mbar_expect(bar + 8 * (B_RT + wg), 9 * PG);
    if (layer == 0) tma_ld(rsrc, &p.mapX, q * 64, blk * 64, bar + 8 * (B_RT + wg));
    else tma_ld(rsrc, &p.mapXT, blk * 64, DM + q * 64, bar + 8 * (B_RT + wg));
#pragma unroll 1
    for (int c = 0; c < 4; c++) bulk_ld(sb + o_page(wg, c) * PG, g_O + ((layer * 32 + blk) * 4 + c) * PG, 2 * PG, bar + 8 * (B_RT + wg));
  }
  mbar_wait(bar + 8 * (B_RT + wg), rtp);
  RETRY(0);
  }
  if (!clean && lane == 0) mbar_arrive(bar + 8 * (B_PDONE + wg));
  if (!staged && lane == 0) mbar_arrive(bar + 8 * (B_STG + wg));
  TSW(10);
}

__device__ __forceinline__ void conv_load(uint32_t* A, uint32_t pe) {
#pragma unroll
  for (int m = 0; m < 17; m++) {
    A[4 * m + 2] = lds32(pe + 4 * (64 * m - 8));
    A[4 * m + 0] = lds32(pe + 4 * (64 * m));
    A[4 * m + 1] = lds32(pe + 4 * (64 * m + 8));
    asm volatile("mov.b32 %0, %1;" : "=r"(A[4 * m + 3]) : "r"(A[4 * m + 0]));
  }
}
template <int M> __device__ __forceinline__ void conv_tri(float* acc, const uint32_t* A, uint64_t d) {
  if constexpr (M < 16) {
    wgmma_rs<64 - 8 * (M / 2), 0>(acc, A + 4 * M, d + (uint64_t)(64 + 4 * M), M != 0);
    conv_tri<M + 1>(acc, A, d);
  }
}
__device__ __forceinline__ void conv_mma0(float* acc, const uint32_t* A, uint64_t d) {
  wg_fence();
  conv_tri<0>(acc, A, d);
  wg_commit();
}
__device__ __forceinline__ void conv_mma1(float* acc, const uint32_t* A, uint64_t d, uint64_t ds, uint64_t df) {
  wg_fence();
#pragma unroll
  for (int m = 0; m < 17; m++) wgmma_rs<64, 0>(acc, A + 4 * m, d + (uint64_t)(4 * m), m != 0);
  wgmma_ss<64, 1, 0>(acc, ds, df, 1);
  wgmma_ss<64, 1, 0>(acc, ds + 128, df + 128, 1);
  wg_commit();
}
__device__ __forceinline__ void conv_store(float* acc, uint32_t pb, uint32_t over, int w) {
  acc_fence<32>(acc);
  const int l = opaque_tid() & 31, mt = l >> 3;
  int c = 2 * (63 - 8 * (mt >> 1) - (l & 7) + w) + (mt & 1);
  c ^= (c >> 3) & 1;
  const uint32_t a0 = pb + c * 16;
#pragma unroll
  for (int j = 0; j < 8; j += 2)
    stsm4t(j == 0 ? (c < 128 ? a0 : over + (c - 128) * 16) : a0 - 256 * j, packbf(acc[4 * j], acc[4 * j + 1]), packbf(acc[4 * j + 2], acc[4 * j + 3]),
           packbf(acc[4 * j + 4], acc[4 * j + 5]), packbf(acc[4 * j + 6], acc[4 * j + 7]));
}
__device__ __forceinline__ void conv_sums(uint32_t sb, int lc, int ht) {
  const int m = ht - 1;
  uint4 v[2][3];
#pragma unroll
  for (int c = 0; c < 2; c++)
#pragma unroll
    for (int k = 0; k < 3; k++) {
      const int mm = m - 1 + k;
      v[c][k] = lds128(sb + cv_u(lc + c) + (mm >= 0 ? (mm & 1) * CV_UH + (127 - (mm >> 1)) * 16 : 128 * 16));
    }
  const int ce = m + 2, co = m + 1;
#pragma unroll
  for (int c = 0; c < 2; c++) {
    const uint32_t x[8] = {v[c][0].z, v[c][0].w, v[c][1].x, v[c][1].y, v[c][1].z, v[c][1].w, v[c][2].x, v[c][2].y};
    float pv[16];
#pragma unroll
    for (int k = 0; k < 8; k++) { pv[2 * k] = bf_lo(x[k]); pv[2 * k + 1] = bf_hi(x[k]); }
    float t2[15], t4[13], s9[8], s7[8];
#pragma unroll
    for (int i = 0; i < 15; i++) t2[i] = pv[i] + pv[i + 1];
#pragma unroll
    for (int i = 0; i < 13; i++) t4[i] = t2[i] + t2[i + 2];
#pragma unroll
    for (int i = 0; i < 8; i++) {
      s9[i] = (t4[i] + t4[i + 4]) + pv[i + 8];
      s7[i] = (t4[i + 1] + t2[i + 5]) + pv[i + 7];
    }
    const uint4 e4 = make_uint4(packbf(s9[0], s9[1]), packbf(s9[2], s9[3]), packbf(s9[4], s9[5]), packbf(s9[6], s9[7]));
    if (ce < 128) sts128(sb + cv_se(lc + c) + ((ce ^ ((ce >> 3) & 7)) << 4), e4);
    else sts128(sb + cv_se(lc + c), make_uint4(0, 0, 0, 0));
    sts128(sb + cv_so(lc + c) + ((co ^ ((co >> 3) & 7)) << 4),
           make_uint4(packbf(s7[0], s7[1]), packbf(s7[2], s7[3]), packbf(s7[4], s7[5]), packbf(s7[6], s7[7])));
  }
}

template <int HALF, int NCH, int STEP = 1>
__device__ __forceinline__ void conv_epi(uint32_t sb, bf16* out, int lc, int c) {
  uint4 v[NCH][4], xr[NCH];
  const uint32_t sw = (c ^ ((c >> 3) & 1)) * 16;
#pragma unroll
  for (int u = 0; u < NCH; u++) {
#pragma unroll
    for (int k = 0; k < 4; k++) v[u][k] = lds128(sb + (HALF ? cv_pb1(lc + STEP * u, k) : cv_pb0(lc + STEP * u, k)) + sw);
    xr[u] = lds128(sb + cv_x(HALF, lc + STEP * u) + c * 16);
  }
#pragma unroll
  for (int u = 0; u < NCH; u++) {
    uint4 o;
    o.x = hadd2(xr[u].x, hadd2(hadd2(v[u][0].x, v[u][1].x), hadd2(v[u][2].x, v[u][3].x)));
    o.y = hadd2(xr[u].y, hadd2(hadd2(v[u][0].y, v[u][1].y), hadd2(v[u][2].y, v[u][3].y)));
    o.z = hadd2(xr[u].z, hadd2(hadd2(v[u][0].z, v[u][1].z), hadd2(v[u][2].z, v[u][3].z)));
    o.w = hadd2(xr[u].w, hadd2(hadd2(v[u][0].w, v[u][1].w), hadd2(v[u][2].w, v[u][3].w)));
    stg128(out + cv_chan(0, lc + STEP * u) * LSEQ + HALF * 1024 + c * 8, o);
  }
}

__device__ __forceinline__ bool prep_valid(const uint4 (&st)[6], const uint4 (&xr)[4]) {
  const uint32_t n = __float_as_uint(8.f);
  return st[0].w == n && st[1].w == n && st[2].w == n && st[3].w == n && st[4].w == n && (st[5].w | st[5].y | st[5].z) == n &&
         xr[0].x != UNSET && xr[1].x != UNSET && xr[2].x != UNSET && xr[3].x != UNSET;
}
template <int HALF>
__device__ __forceinline__ void conv_prep(uint32_t sb, int layer, int cta, int i) {
  uint4 st[6], xr[4];
  const uint4* sp = (const uint4*)g_stats + (layer * 32 + HALF * 16 + (i >> 3)) * 48 + (i & 7);
  const uint4* xp = (const uint4*)g_xT + (2 * layer * DM + 2 * cta) * (LSEQ / 8) + HALF * 128 + i;
  auto fetch = [&]() {
#pragma unroll
    for (int k = 0; k < 6; k++) st[k] = ld_tagged(sp + 8 * k);
#pragma unroll
    for (int k = 0; k < 4; k++) xr[k] = ld_tagged(xp + cv_chan(0, k) * (LSEQ / 8));
  };
  if (HALF) {
#pragma unroll
    for (int k = 0; k < 6; k++) st[k] = lds128(sb + CV_ST + (i >> 3) * 768 + k * 128 + (i & 7) * 16);
#pragma unroll
    for (int k = 0; k < 4; k++) xr[k] = lds128(sb + cv_x(1, k) + i * 16);
  } else {
    fetch();
  }
  int it = 0;
  while (!__all_sync(~0u, prep_valid(st, xr)) && ++it < MAX_RETRY) { fetch(); RETRY(1); }
  if (!HALF || it) {
#pragma unroll
    for (int k = 0; k < 4; k++) sts128(sb + cv_x(HALF, k) + i * 16, xr[k]);
  }
  const uint32_t v[16] = {st[0].x, st[0].y, st[0].z, st[1].x, st[1].y, st[1].z, st[2].x, st[2].y, st[2].z, st[3].x, st[3].y, st[3].z, st[4].x, st[4].y, st[4].z, st[5].x};
  uint32_t rs[4], nm[4];
#pragma unroll
  for (int k = 0; k < 4; k++) {
    const float m0 = __uint_as_float(v[4 * k]) * (-1.f / DM), m1 = __uint_as_float(v[4 * k + 2]) * (-1.f / DM);
    const float r0 = rsqrt_approx(fmaxf(fmaf(__uint_as_float(v[4 * k + 1]), 1.f / DM, -m0 * m0), 0.f) + 1e-5f);
    const float r1 = rsqrt_approx(fmaxf(fmaf(__uint_as_float(v[4 * k + 3]), 1.f / DM, -m1 * m1), 0.f) + 1e-5f);
    rs[k] = packbf(r0, r1);
    nm[k] = packbf(m0 * bf_lo(rs[k]), m1 * bf_hi(rs[k]));
  }
  const uint32_t ud = sb + (i & 1) * CV_UH + (127 - 64 * HALF - (i >> 1)) * 16;
#pragma unroll
  for (int k = 0; k < 4; k++)
    sts128(ud + cv_u(k), make_uint4(hfma2(xr[k].x, rs[0], nm[0]), hfma2(xr[k].y, rs[1], nm[1]), hfma2(xr[k].z, rs[2], nm[2]), hfma2(xr[k].w, rs[3], nm[3])));
  fence_async_smem();
}

__device__ __forceinline__ void conv_phase(const Params& p, uint32_t sb, int layer, int cta, uint32_t* A0, uint32_t* A1) {
  const int tid = opaque_tid();
  const int wg = __shfl_sync(~0u, tid >> 7, 0), w = __shfl_sync(~0u, (tid >> 5) & 3, 0);
  const uint32_t bar = sb + SM_BAR;
  constexpr int CH2 = 4 * PG;
  bf16* xout = g_xT + ((2 * layer + 1) * DM + 2 * cta) * LSEQ;
  float acc[32];
  const uint32_t pe = sb + cv_pe(wg, 0) + 4 * (16 + 16 * w + ((tid & 31) >> 2) - 2 * (tid & 3));
  if (layer == 0) {
    mbar_wait(bar + 8 * (B_PDONE + 1), layer);
    mbar_wait(bar + 8 * B_PE, layer);
    conv_load(A0, pe);
    conv_load(A1, pe + CH2);
  }
  TSW(19);
  const uint64_t d0 = mkdesc(sb + cv_u(wg), CV_UH, 128, 0), d1 = d0 + (CH2 >> 4);
  mbar_wait(bar + 8 * B_U, layer);
  TSW(12);
  if (wg == 1) bar_sync(5, 256);
  conv_mma0(acc, A0, d0);
  if (wg == 0) bar_arrive(5, 256);
  mbar_wait(bar + 8 * (B_PDONE + 1), layer);
  {
    const int l = opaque_tid() & 31;
    if ((l & 15) < 2 * w) sts128(sb + cv_pb0(wg + 2 * (l >> 4), w) + (l & 15) * 16, make_uint4(0, 0, 0, 0));
  }
  wg_wait<0>();
  conv_store(acc, sb + cv_pb0(wg, w), sb + cv_pb1(wg, w), w);
  conv_mma0(acc, A1, d1);
  wg_wait<0>();
  conv_store(acc, sb + cv_pb0(2 + wg, w), sb + cv_pb1(2 + wg, w), w);
  TSW(13);
  bar_sync(2 + wg, 128);
  conv_epi<0, 2, 2>(sb, xout, wg, opaque_tid() & 127);
  TSW(14);
  mbar_arrive(bar + 8 * B_PUB);
  const uint64_t ds = mkdesc(sb + cv_se(wg), 8192, 1024, 1), df = mkdesc(sb + cv_fa(wg), 512, 128, 0);
  if (wg == 0) mbar_wait(bar + 8 * B_U1, layer);
  else bar_sync(6, 256);
  TSW(15);
  conv_mma1(acc, A0, d0, ds, df);
  if (wg == 0) bar_arrive(6, 256);
  wg_wait<0>();
  conv_store(acc, sb + cv_pb1(wg, w), sb + cv_dump(wg), w);
  TSW(16);
  bar_sync(2 + wg, 128);
  conv_epi<1, 1>(sb, xout, wg, opaque_tid() & 127);
  mbar_arrive(bar + 8 * (B_PUB + 1));
  conv_mma1(acc, A1, d1, ds + 512, df + (CH2 >> 4));
  wg_wait<0>();
  conv_store(acc, sb + cv_pb1(2 + wg, w), sb + cv_dump(2 + wg), w);
  TSW(17);
  bar_sync(2 + wg, 128);
  conv_epi<1, 1>(sb, xout, 2 + wg, opaque_tid() & 127);
  mbar_arrive(bar + 8 * (B_PUB + 2));
  TSW(18);
}

__device__ __forceinline__ void final_tile(const Params& p, uint32_t buf, int ch0, int pos0, int barid) {
  const int tid = opaque_tid() & 127, lane = tid & 31, w = tid >> 5;
  const uint4* src = (const uint4*)(g_xT + (3 * DM + ch0 + (tid >> 3)) * LSEQ + pos0) + (tid & 7);
  const int ch = tid >> 3, row = 4 * (ch & 6) + 2 * (ch >> 3) + (ch & 1);
  const uint32_t dst = buf + row * 128;
  const uint32_t ld = buf + lane * 128;
  bf16* out = p.out + (pos0 + 16 * w + (lane >> 2)) * DM + ch0 + 8 * (lane & 3);
  uint4 a, b;
  int it = 0;
  do {
    if (it) RETRY(2);
    a = ld_tagged(src); b = ld_tagged(src + 16 * LSEQ / 8);
  } while (!__all_sync(~0u, a.x != UNSET && b.x != UNSET) && ++it < (1 << 20));
  sts128(dst + (((tid ^ row) & 7) << 4), a);
  sts128(dst + 512 + (((tid ^ row ^ 4) & 7) << 4), b);
  bar_sync(barid, 128);
#pragma unroll
  for (int h = 0; h < 2; h++) {
    uint32_t r[4];
    ldsm4t(r, ld + ((((2 * w + h) ^ lane) & 7) << 4));
    *(uint4*)(out + 8 * h * DM) = make_uint4(r[0], r[1], r[2], r[3]);
  }
}

struct cplx { float r, i; };
__device__ __forceinline__ cplx cmul(cplx a, cplx b) { return {fmaf(a.r, b.r, -a.i * b.i), fmaf(a.r, b.i, a.i * b.r)}; }
__device__ __forceinline__ cplx csqr(cplx a) { return {fmaf(a.r, a.r, -a.i * a.i), (a.r + a.r) * a.i}; }
__device__ __forceinline__ cplx cexp_l(float ar2, float ai, float l) {
  const float m = ex2(ar2 * l);
  const float x = ai * l;
  return {m * __cosf(x), m * __sinf(x)};
}

__device__ __forceinline__ void colsum_cta(const Params& p, uint32_t sb, int j, int tid) {
  const uint32_t bar = sb + SM_BAR;
  auto ld = [&](int i) {
    mbar_expect(bar + 8 * i, 3 * PG);
    tma_ld3(sb + (i & 7) * 3 * PG, &p.mapW3, (2 * j + (i & 1)) * 64, (i >> 1) * 64, 0, bar + 8 * i);
  };
  if (tid == 384) {
#pragma unroll
    for (int i = 0; i < 24; i++) mbar_init(bar + 8 * i, i < 16 ? 1 : 12);
    asm volatile("fence.mbarrier_init.release.cluster;" ::: "memory");
    fence_async_smem();
#pragma unroll 1
    for (int i = 0; i < 8; i++) ld(i);
  }
  const unsigned ep = ld_relaxed(&g_cnt[C_CS * 32]);
  bar_sync(0, NTHREADS);
  if (tid == 384) {
#pragma unroll 1
    for (int i = 8; i < 16; i++) { mbar_wait(bar + 8 * (8 + i), 0); fence_async_smem(); ld(i); }
  }
  if (tid < 384) {
    const int lane = tid & 31, cc = tid & 7, r0 = (tid >> 3) & 15, part = tid >> 7;
    const uint32_t id = ((lane >> 2) == 2 * (lane & 3) ? 0x3f80u : 0u) | ((lane >> 2) == 2 * (lane & 3) + 1 ? 0x3f800000u : 0u);
    const uint32_t src = sb + part * PG + r0 * 128 + ((cc ^ (r0 & 7)) << 4);
    float s[2][2][4];
#pragma unroll
    for (int i = 0; i < 16; i++) s[i >> 3][(i >> 2) & 1][i & 3] = 0.f;
#pragma unroll 1
    for (int i2 = 0; i2 < 16; i2 += 2) {
#pragma unroll
      for (int h = 0; h < 2; h++) {
        const int i = i2 + h;
        mbar_wait(bar + 8 * i, 0);
        uint4 v[4];
#pragma unroll
        for (int k = 0; k < 4; k++) v[k] = lds128(src + (i & 7) * 3 * PG + k * 2048);
#pragma unroll
        for (int k = 0; k < 4; k++) {
          const uint32_t a[4] = {v[k].x, v[k].y, v[k].z, v[k].w};
          mma_bf16(s[h][0], a, id, 0u);
          mma_bf16(s[h][1], a, 0u, id);
        }
        __syncwarp();
        if (i < 8 && lane == 0) mbar_arrive(bar + 8 * (16 + i));
      }
    }
    const uint32_t red = sb + 24 * PG;
#pragma unroll
    for (int h = 0; h < 2; h++)
#pragma unroll
      for (int k = 0; k < 2; k++) sts128f(red + (r0 * 384 + h * 192 + part * 64 + cc * 8 + k * 4) * 4, s[h][k][0], s[h][k][1], s[h][k][2], s[h][k][3]);
    bar_sync(1, 384);
    float tot = 0.f;
#pragma unroll
    for (int k = 0; k < 16; k++) tot += __uint_as_float(lds32(red + (k * 384 + tid) * 4));
    asm volatile("st.relaxed.gpu.global.v2.u32 [%0], {%1,%2};" ::"l"(&g_colsum[j * 384 + tid]), "r"(__float_as_uint(tot)), "r"(ep / NCTA + 1) : "memory");
    const uint4 u = make_uint4(UNSET, UNSET, UNSET, UNSET);
    if (tid < 256) {
#pragma unroll 1
      for (int s = 0; s < 4; s++) {
        const int n = (s == 1 || s == 2) ? 32 : 16;
        uint4* buf = s == 1 ? (uint4*)g_O + 131072 : (uint4*)g_xT + (s + !s) * 131072;
#pragma unroll 4
        for (int i = 0; i < n; i++) stg128(buf + (j * n + i) * 1024 + (tid >> 1) * 8 + (tid & 1), u);
        if (n == 16) {
#pragma unroll 4
          for (int i = 0; i < 8; i++) stg128(buf + (256 + j * 64 + i * 8 + (tid >> 5)) * 256 + (s ? 0 : 128) + ((tid & 31) >> 1) * 8 + (tid & 1), u);
        }
        if (s == 3) {
#pragma unroll 4
          for (int i = 0; i < 32; i++) stg128(buf + (256 + j * 64 + 2 * i + (tid >> 7)) * 256 + 128 + (tid & 127), u);
        }
        bar_sync(2, 256);
        if (tid == 32 * s) red_release(&g_cnt[(C_R + s) * 32]);
      }
    }
  }
}

constexpr int KB = 4, KW = 2;
struct ModeIn { uint32_t ar, ai, br, bi, cr, ci; bf16 logdt; };
__device__ __forceinline__ ModeIn load_modes(const Params& p, int d, int m) {
  const int i = d * 64 + m;
  return {((const uint32_t*)p.a_re)[i], ((const uint32_t*)p.a_im)[i], ((const uint32_t*)p.b_re)[i], ((const uint32_t*)p.b_im)[i],
          ((const uint32_t*)p.c_re)[i], ((const uint32_t*)p.c_im)[i], p.log_dt[d]};
}
__device__ __forceinline__ void kernel_gen(uint32_t sb, int cta, int ht, ModeIn in, const ModeIn& in1) {
  const uint32_t bst = sb + SM_KGB + ((ht & 63) >> 2) * 144 + (ht & 3) * 4 + (ht >> 6) * 16;
  const uint64_t db = mkdesc(sb + SM_KGB, 144, 2304, 0);
  const float e0 = (float)(8 * (((ht & 32) >> 1) + ((ht & 31) >> 2)));
  float T[20];
#pragma unroll
  for (int i = 0; i < 20; i++) T[i] = 0.f;
  float k0 = 0.f;
#pragma unroll 1
  for (int pass = 0; pass < 4; pass++) {
    {
      const int sh = (pass & 1) ? 0 : 16;
      auto val = [&](uint32_t v) { return __uint_as_float((v << sh) & 0xffff0000u); };
      const float dt = __bfloat162float(__float2bfloat16_rn(expf(__bfloat162float(in.logdt))));
      const float ar2 = dt * val(in.ar) * 1.4426950408889634f, ai = dt * val(in.ai);
      const cplx c = cmul({val(in.cr), -val(in.ci)}, {dt * val(in.br), -dt * val(in.bi)});
      k0 += c.r;
      const cplx z1 = cexp_l(ar2, -ai, 1.f), z256 = cexp_l(ar2, -ai, 256.f), z64 = cexp_l(ar2, ai, 64.f);
      const cplx z2 = csqr(z1), z512 = csqr(z256);
      auto put = [&](int j, cplx v) { sts32(bst + (j >> 2) * 2304 + (j & 3) * 32, packbf(v.r, v.i)); };
      sts128f(sb + SM_KGT + ht * 16, ar2, ai, z64.r, z64.i);
      const cplx c1 = cmul(c, z1), c2 = cmul(c, z2), c3 = cmul(c1, z2), c4 = cmul(c2, z2);
      const cplx c5 = cmul(c3, z2), c6 = cmul(c4, z2), c7 = cmul(c5, z2), c8 = cmul(c6, z2);
      put(0, c1); put(1, c2); put(2, c3); put(3, c4); put(4, c5); put(5, c6); put(6, c7); put(7, c8);
      const cplx c260 = cmul(c4, z256), c264 = cmul(c8, z256), c520 = cmul(c8, z512), c776 = cmul(c264, z512);
      put(8, cmul(c2, z256)); put(9, c260); put(10, cmul(c6, z256)); put(11, c264);
      put(12, cmul(c4, z512)); put(13, c520); put(14, cmul(c260, z512)); put(15, c776);
      const cplx c1032 = cmul(c520, z512), c1288 = cmul(c776, z512);
      put(16, c1032); put(17, c1288); put(18, cmul(c1032, z512)); put(19, cmul(c1288, z512));
    }
    fence_async_smem();
    bar_sync(4, 128);
    const uint32_t tb = sb + SM_KGT + (ht & 67) * 16;
    float2 nx[KB];
#pragma unroll
    for (int s = 0; s < KB; s++) nx[s] = lds64f(tb + s * 64);
#pragma unroll
    for (int q = 0; q < 16 / KB; q++) {
      uint32_t A[2 * KB];
      float2 cur[KB], z[KB];
#pragma unroll
      for (int s = 0; s < KB; s++) { cur[s] = nx[s]; z[s] = lds64f(tb + (KB * q + s) * 64 + 8); }
      if (q < 16 / KB - 1) {
#pragma unroll
        for (int s = 0; s < KB; s++) nx[s] = lds64f(tb + (KB * q + KB + s) * 64);
      }
      if (q >= KW) wg_wait<KW - 1>();
#pragma unroll
      for (int s = 0; s < KB; s++) {
        const cplx lo = cexp_l(cur[s].x, cur[s].y, e0), hi = cmul(lo, {z[s].x, z[s].y});
        A[2 * s] = packbf(lo.r, lo.i);
        A[2 * s + 1] = packbf(hi.r, hi.i);
      }
      wg_fence();
#pragma unroll
      for (int k = 0; k < KB / 2; k++) wgmma_rs<40, 0>(T, A + 4 * k, db + 9 * KB * q + 18 * k, (pass & 1) | q | k);
      wg_commit();
    }
    wg_wait<0>();
    acc_fence<20>(T);
    if (ht == 0) TS(4 + pass);
    if (pass & 1) {
      const int h2 = opaque_tid() - 256, w = h2 >> 5, lane = h2 & 31, t = lane & 3, chn = h2 >> 6, m = h2 & 63, i0 = 16 * (w & 1) + (lane >> 2);
      const int lc = (pass & 2) + chn;
      const uint32_t kc = sb + kc_off(lc);
      auto put = [&](int idx, float v) {
        sts16(kc + idx * 2, __bfloat16_as_ushort(__float2bfloat16_rn(v)));
      };
#pragma unroll
      for (int hi = 0; hi < 2; hi++) {
        const int i = i0 + 8 * hi;
        float v[5];
#pragma unroll
        for (int j = 0; j < 5; j++) v[j] = chn ? T[4 * j + 2 * hi + 1] : T[4 * j + 2 * hi];
        put(8 * i + 1 + t, v[0]);
        put(8 * i + 5 + t, v[1]);
        put(257 + 4 * i + t, v[2]);
        put(385 + 2 * i + (t & 1) + 64 * (t >> 1), v[3]);
        put(513 + i + 32 * t, v[4]);
      }
#pragma unroll
      for (int o = 16; o > 0; o >>= 1) k0 += __shfl_xor_sync(~0u, k0, o);
      if (lane == 0) sts32f(sb + SM_RED + 4 * w, k0);
      bar_sync(4, 128);
      if (m == 0) put(0, k0 + __uint_as_float(lds32(sb + SM_RED + 4 * w + 4)) + __uint_as_float(lds16(sb + SM_RED + 24 + 2 * lc) << 16));
      k0 = 0.f;
      in = in1;
    }
  }
}

__device__ __forceinline__ void expand_taps(uint32_t sb, int ht, int early) {
  const int ch = ht >> 5, lane = ht & 31;
  const uint32_t kc = sb + kc_off(ch);
  const uint32_t dst0 = sb + cv_pe(ch, early);
  auto put = [&](int G, uint32_t v0, uint32_t v1, uint32_t v2, uint32_t v3, uint32_t v4, uint32_t v5, uint32_t v6, uint32_t v7, uint32_t v8) {
    const uint32_t dst = dst0 + G * 32;
    sts128(dst, make_uint4(v1 | (v0 << 16), v2 | (v1 << 16), v3 | (v2 << 16), v4 | (v3 << 16)));
    sts128(dst + 16, make_uint4(v5 | (v4 << 16), v6 | (v5 << 16), v7 | (v6 << 16), v8 | (v7 << 16)));
  };
  {
    const uint4 q = lds128(kc + lane * 16);
    const uint32_t pv = lane ? lds16(kc + lane * 16 - 2) : 0u;
    const uint32_t dst = dst0 + (lane + 2) * 32;
    sts128(dst, make_uint4(__byte_perm(q.x, pv, 0x5410), __byte_perm(q.x, q.x, 0x1032), __byte_perm(q.y, q.x, 0x7610), __byte_perm(q.y, q.y, 0x1032)));
    sts128(dst + 16, make_uint4(__byte_perm(q.z, q.y, 0x7610), __byte_perm(q.z, q.z, 0x1032), __byte_perm(q.w, q.z, 0x7610), __byte_perm(q.w, q.w, 0x1032)));
    if (lane < 4) sts128(dst0 + lane * 16, make_uint4(0, 0, 0, 0));
  }
  uint32_t a[5], b[2][3];
  {
    const uint32_t s1 = kc + 2 * (256 + 4 * lane);
#pragma unroll
    for (int k = 0; k < 5; k++) a[k] = lds16(s1 + 2 * k);
#pragma unroll
    for (int u = 0; u < 2; u++) {
      const uint32_t s2 = kc + 2 * (384 + 2 * (lane + 32 * u));
#pragma unroll
      for (int k = 0; k < 3; k++) b[u][k] = lds16(s2 + 2 * k);
    }
  }
  const uint32_t k255 = lds16(kc + 2 * 255), k1024 = lds16(kc + 2 * 512);
  put(34 + lane, lane == 0 ? k255 : a[0], a[0], a[0], a[1], a[2], a[2], a[2], a[3], a[4]);
#pragma unroll
  for (int u = 0; u < 2; u++) put(66 + lane + 32 * u, b[u][0], b[u][0], b[u][0], b[u][0], b[u][1], b[u][1], b[u][1], b[u][2], b[u][2]);
  if (lane < 10) {
    const uint32_t v = lane == 0 ? k1024 : 0u;
    put(130 + lane, v, v, v, v, v, v, 0u, 0u, 0u);
  }
}
__device__ __forceinline__ void expand_far(uint32_t sb, int ht) {
  const int ch = ht >> 5, lane = ht & 31;
  const uint32_t kc = sb + kc_off(ch) + 2 * (513 + 2 * (63 - lane)), dst = sb + cv_fa(ch) + lane * 16;
#pragma unroll
  for (int ty = 0; ty < 2; ty++) {
    uint32_t v[16];
#pragma unroll
    for (int k = 0; k < 16; k++) v[k] = (k < 8 || 63 - lane - 4 * k >= 0) ? lds16(kc + 2 * (1 - ty) - 16 * k) : 0u;
#pragma unroll
    for (int u = 0; u < 2; u++)
      sts128(dst + ty * 2048 + u * 512, make_uint4(v[8 * u] | (v[8 * u + 1] << 16), v[8 * u + 2] | (v[8 * u + 3] << 16), v[8 * u + 4] | (v[8 * u + 5] << 16), v[8 * u + 6] | (v[8 * u + 7] << 16)));
    sts128(dst + ty * 2048 + 1024, make_uint4(0, 0, 0, 0));
  }
}

__host__ __device__ constexpr int bar_count(int i) {
  return i == B_LN ? 2 : i == B_AL ? 8 : i < B_STG ? 1 : i < B_PE ? 4 : i >= B_PUB ? 256 : 128;
}
__host__ __device__ constexpr bool bar_first(int i) { return i < B_WF + 2 && (i & 7) < 2; }

__global__ void __launch_bounds__(NTHREADS, 1) fused_kernel(const __grid_constant__ Params p) {
  extern __shared__ __align__(1024) uint8_t smem[];
  constexpr uint32_t sb = 1024;
  if (s32(smem) != sb) return;
  const int tid = threadIdx.x, lane = tid & 31;
  const int warp = __shfl_sync(~0u, tid >> 5, 0);
  if (tid == 32) {
    asm volatile("prefetch.tensormap [%0];" ::"l"(&p.mapX) : "memory");
    asm volatile("prefetch.tensormap [%0];" ::"l"(&p.mapW3) : "memory");
  }
  const int cta = blockIdx.x - (gridDim.x == NCTA + 4 ? 0 : 4);
  if ((unsigned)cta >= NCTA) {
    if (blockIdx.x < NCTA + 4) colsum_cta(p, sb, blockIdx.x & 3, tid);
    return;
  }
  const int rb = ((cta >> 4) & 3) * 4 + ((cta >> 2) & 3), hg = (cta >> 6) * 4 + (cta & 3);
  const uint32_t bar = sb + SM_BAR;
  auto ld_x0 = [&](int half, int c) {
    const uint32_t b = bar + 8 * (B_XF + 8 * half + c);
    mbar_expect(b, PG);
    tma_ld(sb + x_page(half, c) * PG, &p.mapX, c * 64, (16 * half + rb) * 64, b);
  };
  auto ld_x1 = [&](int half, int c, int b0) {
    const uint32_t b = bar + 8 * b0;
    mbar_expect(b, PG);
    tma_ld(sb + (8 * half + c) * PG, &p.mapXT, (16 * half + rb) * 64, DM + c * 64, b);
  };
  auto ld_w = [&](int c) {
    const uint32_t b = bar + 8 * (B_WF + c);
    mbar_expect(b, 3 * PG);
    tma_ld3(sb + w_page(c) * PG, &p.mapW3, hg * 64, c * 64, 0, b);
  };

  if (tid == 0) TS(0);
  if (tid == 480) LTS(0);
  if (warp == 0 && elect_one()) {
#pragma unroll
    for (int i = 0; i < B_WF + 2; i++)
      if (bar_first(i)) mbar_init(bar + 8 * i, 1);
    asm volatile("fence.mbarrier_init.release.cluster;" ::: "memory");
    fence_async_smem();
    ld_x0(0, 0);
    ld_w(0); ld_x0(1, 0);
    ld_x0(0, 1); ld_w(1); ld_x0(1, 1);
    TS(1);
  }
  __syncwarp();
  if (warp >= 1 && warp < 8 && elect_one()) {
    if (warp < 4) {
#pragma unroll
      for (int i = 2; i < 8; i++) mbar_init(bar + 8 * (8 * warp - 8 + i), 1);
    } else {
#pragma unroll
      for (int i = 0; i < 12; i++) mbar_init(bar + 8 * (12 * warp - 24 + i), 1);
    }
    asm volatile("fence.mbarrier_init.release.cluster;" ::: "memory");
  }
  if (warp == 15 && elect_one()) {
#pragma unroll
    for (int i = 72; i < B_COUNT; i++) mbar_init(bar + 8 * i, bar_count(i));
    asm volatile("fence.mbarrier_init.release.cluster;" ::: "memory");
  }

  if (warp < 8) {
    bar_sync(0, NTHREADS);
    asm volatile("setmaxnreg.inc.sync.aligned.u32 %0;" ::"n"(R_CONS));
    const int cw = __shfl_sync(~0u, opaque_tid() >> 5, 0);
    const int wg = cw >> 2, w = cw & 3;
    if (tid == 0) TS(2);
#pragma unroll 1
    for (int layer = 0; layer < 2; layer++) {
      attn_phase(p, sb, layer, rb, hg, wg, w);
      uint32_t A0[68], A1[68];
      proj_phase(p, sb, layer, rb, hg, A0, A1);
      conv_phase(p, sb, layer, cta, A0, A1);
    }
    if (wg == 0) mbar_wait(bar + 8 * (B_TF + 1), 0);
    if (tid == 128) TS(8);
    final_tile(p, sb + (16 + wg) * PG, 256 * wg + 32 * (cta >> 4), 1024 + 64 * (cta & 15), 2 + wg);
    if (tid == 128) TS(9);
    if (tid == 128) LTS(1);
    if (tid == 0) LTE();
  } else if (warp < 12) {
    asm volatile("setmaxnreg.dec.sync.aligned.u32 %0;" ::"n"(R_HELP));
    const int ht = tid - 256;
    {
      unsigned ep0 = 0;
      if (ht == 0) ep0 = ld_relaxed(&g_cnt[C_CS * 32]);
      const bf16 dsk = p.dskip[cv_chan(cta, ht & 3)];
      const ModeIn in0 = load_modes(p, cv_chan(cta, ht >> 6), ht & 63), in1 = load_modes(p, cv_chan(cta, 2 + (ht >> 6)), ht & 63);
      if (ht < 48) sts128f(sb + SM_STG + ht * 16, 0.f, 0.f, 0.f, 1.f);
      bar_sync(0, NTHREADS);
      if (ht == 0) {
        sts32(sb + SM_EP, ep0);
        mbar_arrive(bar + 8 * B_EP);
      }
      if (ht >= 124) sts16(sb + SM_RED + 24 + 2 * (ht & 3), __bfloat16_as_ushort(dsk));
      kernel_gen(sb, cta, ht, in0, in1);
      if (ht < 48) sts128f(sb + SM_KGT + ht * 16, 0.f, 0.f, 0.f, 1.f);
      fence_async_smem();
      bar_sync(4, 128);
      if (ht == 0) mbar_arrive(bar + 8 * B_KG);
    }
#pragma unroll 1
    for (int layer = 0; layer < 2; layer++) {
      const int early = layer;
      if (early) mbar_wait(bar + 8 * (B_DN + 13), 1);
      mbar_wait(bar + 8 * (early ? B_OST : B_PDONE), layer);
      expand_taps(sb, opaque_tid() - 256, early);
      mbar_arrive(bar + 8 * B_PE);
      TSW(0);
      mbar_wait(bar + 8 * B_PDONE, layer);
      expand_far(sb, opaque_tid() - 256);
      {
        const int i = opaque_tid() - 256;
        if (i < 32) sts128(sb + cv_u(i >> 3) + ((i >> 2) & 1) * CV_UH + (128 + (i & 3)) * 16, make_uint4(0, 0, 0, 0));
        mbar_wait(bar + 8 * B_RC, layer);
        mbar_wait(bar + 8 * B_GB, layer);
        TSW(13);
        conv_prep<0>(sb, layer, cta, i);
        mbar_arrive(bar + 8 * B_U);
      }
      mbar_wait(bar + 8 * (B_PDONE + 1), layer);
      bar_sync(4, 128);
#pragma unroll 1
      for (int lc = 0; lc < 4; lc += 2) {
        conv_sums(sb, lc, opaque_tid() - 256);
        TSW(1 + lc);
      }
      mbar_wait(bar + 8 * (B_GB + 1), layer);
      conv_prep<1>(sb, layer, cta, opaque_tid() - 256);
      mbar_arrive(bar + 8 * B_U1);
      TSW(4);
      if (layer == 0) {
        const int c = __shfl_sync(~0u, (opaque_tid() >> 5) & 3, 0);
        int phase = 0;
#pragma unroll 1
        for (int k = 0; k < 3; k++) {
          const int page = (k ? 4 + 4 * k : 0) + c, b = B_XR + 4 * (k & 1) + c;
          const uint32_t a = sb + page * PG + lane * 128 + (lane & 7) * 16 + (lane >> 3) * 4;
          int it = k == 2 ? phase : 0;
#pragma unroll 1
          for (; it < MAX_RETRY; it++) {
            mbar_wait(bar + 8 * b, it & 1);
            const uint32_t v0 = lds32(a), v1 = lds32(a + 4096);
            if (__all_sync(~0u, v0 != UNSET && v1 != UNSET)) break;
            if (elect_one()) { fence_async_smem(); ld_x1(page >> 3, page & 7, b); }
            __syncwarp();
            RETRY(3);
          }
          if (k == 0) phase = it + 1;
          if (lane == 0) mbar_arrive(bar + 8 * (B_XF + page));
        }
      }
    }
    mbar_wait(bar + 8 * B_TF, 0);
#pragma unroll 1
    for (int k = 0; k < 2; k++) final_tile(p, sb + 18 * PG + k * 4096, 256 * k + 32 * (cta >> 4), 64 * (cta & 15), 4);
    if (ht == 0) LTE();
  } else {
    asm volatile("setmaxnreg.dec.sync.aligned.u32 %0;" ::"n"(R_AGENT));
    bar_sync(0, NTHREADS);
    auto done = [&](int half, int c, int layer) { mbar_wait(bar + 8 * (B_DN + 8 * half + c), layer); };
    auto publish = [&](int layer, int k) {
      mbar_wait(bar + 8 * (B_PUB + k), layer);
      red_relaxed(&g_cnt[(layer ? C_F + 8 * k + (cta >> 4) : C_C + k) * 32]);
      if (!layer && k == 0) red_release(&g_cnt[(C_C + 3) * 32]);
      TS(16 + layer * 56 + 40 + 7 + k);
    };
    if (warp == 12) {
      if (elect_one()) {
#pragma unroll 1
        for (int layer = 0; layer < 2; layer++) {
          auto ld_xe = [&](int c) {
            const uint32_t b = bar + 8 * (B_XF + c);
            mbar_expect(b, PG);
            if (layer == 0) tma_ld(sb + x_page(0, c) * PG, &p.mapX, c * 64, rb * 64, b);
            else tma_ld(sb + x_page(0, c) * PG, &p.mapXT, rb * 64, DM + c * 64, b);
          };
          if (layer == 0) {
            ld_x0(0, 2); ld_w(2); ld_x0(1, 2);
            if (hg >= 3) {
              mbar_expect(bar + 8 * B_SC, PG);
              tma_ld(sb + P_R * PG, &p.mapX, hg * 64, rb * 64, bar + 8 * B_SC);
            }
            if (rb < 4) tma_prefetch3(&p.mapW3, hg * 64, (4 + rb) * 64, 0);
            ld_x0(0, 3); ld_w(3); ld_x0(1, 3); ld_x0(0, 4); ld_x0(1, 4);
            done(0, 0, 0); done(1, 0, 0);
            ld_w(4);
            ld_x0(1, 5); ld_x0(1, 6); ld_x0(1, 7);
            done(0, 1, 0); done(1, 1, 0);
            ld_w(5);
            if (rb < 8) tma_prefetch5(&p.mapWo, hg * 64, rb * 2);
            done(0, 2, 0);
            fence_async_smem();
            ld_xe(5); ld_xe(6); ld_xe(7);
          } else {
            mbar_wait(bar + 8 * B_PDONE, 0);
            mbar_wait(bar + 8 * (B_PDONE + 1), 0);
            mbar_wait(bar + 8 * B_U, 0);
            ld_w(0); ld_w(1);
            mbar_wait(bar + 8 * B_U1, 0);
            fence_async_smem();
            ld_w(2);
            mbar_wait(bar + 8 * (B_PUB + 2), 0);
            fence_async_smem();
            ld_w(3);
            spin_until(&g_cnt[(C_C + 3) * 32], ((lds32(sb + SM_EP) / NCTA) + 1) * NCTA);
            fence_async_global();
            if (hg >= 3) {
              mbar_expect(bar + 8 * B_SC, PG);
              tma_ld(sb + P_R * PG, &p.mapXT, rb * 64, DM + hg * 64, bar + 8 * B_SC);
            }
            ld_xe(4);
            done(0, 2, 1);
            fence_async_smem();
            ld_xe(5); ld_xe(6); ld_xe(7);
            done(1, 0, 1);
            ld_w(4);
            done(1, 1, 1);
            ld_w(5);
          }
          done(1, 2, layer);
          fence_async_smem();
          ld_w(6); ld_w(7);
          auto ld_res = [&](int half) {
            const uint32_t b = bar + 8 * (B_RF + half);
            mbar_expect(b, PG);
            if (layer == 0) tma_ld(sb + (half ? 2 : P_R) * PG, &p.mapX, hg * 64, (16 * half + rb) * 64, b);
            else tma_ld(sb + (half ? 2 : P_R) * PG, &p.mapXT, (16 * half + rb) * 64, DM + hg * 64, b);
          };
          done(0, 4, layer); done(1, 3, layer);
          fence_async_smem();
          mbar_expect(bar + 8 * B_WOF, 8 * PG);
#pragma unroll 1
          for (int c = 0; c < 8; c++) {
            if (c == 5) { ld_res(0); done(1, 4, layer); }
            tma_ld5(sb + wo_page(c) * PG, &p.mapWo, hg * 64, c * 2, bar + 8 * B_WOF);
          }
          done(0, 7, layer);
          fence_async_global();
          ld_res(1);
          if (layer) mbar_wait(bar + 8 * B_RS, 0);
          fence_async_global();
#pragma unroll
          for (int half = 0; half < 2; half++) {
            float* stats = g_stats + (layer * 32 + 16 * half + rb) * 192;
            unsigned* cnt = &g_cnt[(C_G + 2 * layer + half) * 32];
            mbar_wait(bar + 8 * (B_STG + half), layer);
            tma_st(&p.mapXT, (16 * half + rb) * 64, 2 * layer * DM + hg * 64, sb + (P_R + half) * PG);
            bulk_red_add_f32(stats, sb + (half ? SM_KGT : SM_STG), 768);
            bulk_commit();
            red_relaxed(cnt);
            if (half == 0) mbar_arrive(bar + 8 * B_PG);
            bulk_wait_read();
            mbar_arrive(bar + 8 * (B_PST + half));
          }
        }
      }
    } else if (warp == 13) {
      mbar_wait(bar + 8 * B_EP, 0);
      const unsigned e1 = (lds32(sb + SM_EP) / NCTA) + 1;
      auto ld_o = [&](int layer) {
#pragma unroll 1
        for (int half = 0; half < 2; half++) {
          done(1, 7, layer);
          mbar_wait(bar + 8 * B_OST, layer);
          if (half) mbar_wait(bar + 8 * (B_OST + 1), layer);
          fence_async_smem();
#pragma unroll
          for (int c = 0; c < 4; c++) mbar_expect(bar + 8 * (B_OF + 4 * half + c), 2 * PG);
          spin_hint(&g_cnt[(C_O + layer * 32 + 16 * half + rb) * 32], e1 * 32);
#pragma unroll
          for (int c = 0; c < 4; c++) {
            if (c == 2 && half && layer) { mbar_wait(bar + 8 * B_AL, 0); fence_async_smem(); }
            bulk_ld(sb + o_page(half, c) * PG, g_O + ((layer * 32 + 16 * half + rb) * 4 + c) * PG, 2 * PG, bar + 8 * (B_OF + 4 * half + c));
          }
        }
      };
      if (elect_one()) {
        mbar_wait(bar + 8 * (B_WF + 2), 0);
        asm volatile("prefetch.tensormap [%0];" ::"l"(&p.mapXT) : "memory");
        asm volatile("prefetch.tensormap [%0];" ::"l"(&p.mapWo) : "memory");
        spin_until(&g_cnt[C_Z * 32], e1 * NCTA);
        mbar_arrive(bar + 8 * B_ZF);
        TS(3);
        ld_o(0);
#pragma unroll 1
        for (int k = 0; k < 3; k++) {
          mbar_wait(bar + 8 * (B_PUB + k), 0);
          if (k == 2) {
#pragma unroll 1
            for (int c = 0; c < 4; c++) mbar_wait(bar + 8 * (B_XF + c), 1);
          }
          fence_async_smem();
          spin_hint(&g_cnt[(C_C + k) * 32], e1 * NCTA);
          TS(10 + k);
#pragma unroll
          for (int c = 0; c < 4; c++) ld_x1(k != 0, (k & 2) * 2 + c, B_XR + 4 * (k & 1) + c);
        }
        ld_o(1);
#pragma unroll 1
        for (int k = 0; k < 2; k++) {
          mbar_wait(bar + 8 * (B_PUB + k), 1);
          spin_hint(&g_cnt[(C_F + 8 * k + (cta >> 4)) * 32], e1 * 16);
          mbar_arrive(bar + 8 * (B_TF + k));
        }
      }
    } else if (warp == 14) {
      mbar_wait(bar + 8 * B_EP, 0);
      const unsigned e1 = (lds32(sb + SM_EP) / NCTA) + 1;
      done(0, 1, 0);
      {
        const uint2* cp = g_colsum + (hg * 192 + lane);
        uint2 v[6];
        bool ok;
        int it = 0;
        do {
          ok = true;
#pragma unroll
          for (int i = 0; i < 6; i++) {
            asm volatile("ld.relaxed.gpu.global.v2.u32 {%0,%1}, [%2];" : "=r"(v[i].x), "=r"(v[i].y) : "l"(cp + 32 * i) : "memory");
            ok = ok && v[i].y == e1;
          }
          if (++it > (1 << 22)) __trap();
        } while (!__all_sync(~0u, ok));
#pragma unroll
        for (int i = 0; i < 6; i++) sts32f(sb + SM_CS + 4 * (lane + 32 * i), __uint_as_float(v[i].x));
      }
      __syncwarp();
      if (elect_one()) {
        mbar_wait(bar + 8 * B_ZF, 0);
        mbar_arrive(bar + 8 * B_LN);
        red_relaxed(&g_cnt[C_CS * 32]);
        TS(13);
#pragma unroll 1
        for (int i = 0; i < 4; i++) {
          const int layer = i >> 1;
          mbar_wait(bar + 8 * (B_PST + (i & 1)), layer);
          const uint32_t b = bar + 8 * (B_GB + 1);
          const bf16* xin = g_xT + ((size_t)2 * layer * DM + 2 * cta) * LSEQ + 1024;
          if (i & 1) {
            fence_async_smem();
            mbar_expect(b, 12288 + PG);
          }
          spin_hint(&g_cnt[(C_G + i) * 32], e1 * NCTA);
          if (i & 1) {
            bulk_ld(sb + CV_ST, g_stats + (layer * 32 + 16) * 192, 12288, b);
#pragma unroll
            for (int lc = 0; lc < 4; lc++) bulk_ld(sb + cv_x(1, lc), xin + cv_chan(0, lc) * LSEQ, 2048, b);
            TS(14 + layer);
            publish(layer, 1);
          } else {
            mbar_arrive(bar + 8 * B_GB);
          }
        }
      }
    } else {
      const uint4 u = make_uint4(UNSET, UNSET, UNSET, UNSET);
      if (lane < 24) stg128((uint4*)g_stats + cta * 24 + lane, make_uint4(0, 0, 0, 0));
      if (lane < 16) stg128(g_rows + LSEQ + cta * 16 + lane, make_uint4(0, 0, 0, 0));
#pragma unroll 4
      for (int i = 0; i < 16; i++) stg128(g_halo + cta * 512 + 32 * i + lane, u);
#pragma unroll 4
      for (int i = 0; i < 16; i++) stg128(((i & 8) ? (uint4*)g_xT : (uint4*)g_O) + cta * 1024 + (i & 7) * 128 + (lane >> 1) * 8 + (lane & 1), u);
      __syncwarp();
      if (elect_one()) red_release(&g_cnt[C_Z * 32]);
      __syncwarp();
#pragma unroll 1
      for (int layer = 0; layer < 2; layer++) {
        auto reset_done = [&](int s) {
          spin_until(&g_cnt[(C_R + s) * 32], (lds32(sb + SM_EP) / NCTA) * 4 + 4);
          mbar_arrive(bar + 8 * (s == 1 ? B_LN : s == 2 ? B_RS : B_RC));
          if (s) TS(16 + 40 + 9 + s);
        };
        if (layer && elect_one()) reset_done(1);
        __syncwarp();
#pragma unroll 1
        for (int half = 0; half < 2; half++) {
          done(half, 2, layer);
          const uint4* src = g_rows + (layer * LSEQ + (16 * half + rb) * 64 + (opaque_tid() & 31));
          uint4 a, b;
          int it = 0;
          do {
            a = ld_tagged(src); b = ld_tagged(src + 32);
          } while (!__all_sync(~0u, (a.z | a.w) == __float_as_uint(8.f) && (b.z | b.w) == __float_as_uint(8.f)) && ++it < (1 << 20));
          float m0 = __uint_as_float(a.x) * (1.f / DM), m1 = __uint_as_float(b.x) * (1.f / DM);
          float r0 = rsqrt_approx(fmaxf(__uint_as_float(a.y) * (1.f / DM) - m0 * m0, 0.f) + 1e-5f);
          float r1 = rsqrt_approx(fmaxf(__uint_as_float(b.y) * (1.f / DM) - m1 * m1, 0.f) + 1e-5f);
          if (half) done(0, 7, layer);
          const uint32_t dst = sb + ln_off(half) + ((lane >> 4) * 8 + (lane & 7)) * 16 + (lane & 8);
          asm volatile("st.shared.v2.f32 [%0], {%1,%2};" ::"r"(dst), "f"(m0), "f"(r0) : "memory");
          asm volatile("st.shared.v2.f32 [%0], {%1,%2};" ::"r"(dst + 256), "f"(m1), "f"(r1) : "memory");
          __syncwarp();
          if (elect_one()) { mbar_arrive(bar + 8 * (B_LN + half)); TS(16 + layer * 56 + 40 + 14 + half); }
        }
        if (layer && lane < 16) stg128(g_rows + cta * 16 + (opaque_tid() & 31), make_uint4(0, 0, 0, 0));
        if (elect_one()) {
          if (layer) reset_done(2);
          reset_done(3 * layer);
          publish(layer, 0);
          if (!layer) publish(layer, 2);
        }
        __syncwarp();
      }
    }
  }
}

typedef CUresult (*EncodeFn)(CUtensorMap*, CUtensorMapDataType, cuuint32_t, void*, const cuuint64_t*, const cuuint64_t*,
                             const cuuint32_t*, const cuuint32_t*, CUtensorMapInterleave, CUtensorMapSwizzle,
                             CUtensorMapL2promotion, CUtensorMapFloatOOBfill);

static void make_map(EncodeFn enc, CUtensorMap* m, void* ptr, uint64_t cols, uint64_t rows, uint32_t box_rows) {
  cuuint64_t dims[2] = {cols, rows};
  cuuint64_t strides[1] = {cols * 2};
  cuuint32_t box[2] = {64, box_rows};
  cuuint32_t es[2] = {1, 1};
  enc(m, CU_TENSOR_MAP_DATA_TYPE_BFLOAT16, 2, ptr, dims, strides, box, es, CU_TENSOR_MAP_INTERLEAVE_NONE,
      CU_TENSOR_MAP_SWIZZLE_128B, CU_TENSOR_MAP_L2_PROMOTION_L2_128B, CU_TENSOR_MAP_FLOAT_OOB_FILL_NONE);
}
static void make_map3(EncodeFn enc, CUtensorMap* m, void* ptr, uint64_t d0, uint64_t cols, uint64_t rows, uint64_t blk_stride,
                      uint64_t nblocks, uint32_t nblk) {
  cuuint64_t dims[3] = {d0, rows, nblocks};
  cuuint64_t strides[2] = {cols * 2, blk_stride * 2};
  cuuint32_t box[3] = {64, 64, nblk};
  cuuint32_t es[3] = {1, 1, 1};
  enc(m, CU_TENSOR_MAP_DATA_TYPE_BFLOAT16, 3, ptr, dims, strides, box, es, CU_TENSOR_MAP_INTERLEAVE_NONE,
      CU_TENSOR_MAP_SWIZZLE_128B, CU_TENSOR_MAP_L2_PROMOTION_L2_128B, CU_TENSOR_MAP_FLOAT_OOB_FILL_NONE);
}

extern "C" void kernel_launch(void* const* d_in, const int* in_sizes, int n_in, void* d_out, int out_size) {
  static Params prm;
  static void* cached[13] = {nullptr};
  static bool attr_done = false;
  static int grid = NCTA + 4;
  bool same = attr_done && cached[12] == d_out;
  for (int i = 0; i < 12 && same; i++) same = cached[i] == d_in[i];
  if (!same) {
    void* fn = nullptr;
    cudaDriverEntryPointQueryResult qr;
    cudaGetDriverEntryPoint("cuTensorMapEncodeTiled", &fn, cudaEnableDefault, &qr);
    EncodeFn enc = (EncodeFn)fn;
    void* pXT;
    cudaGetSymbolAddress(&pXT, g_xT);
    make_map(enc, &prm.mapX, d_in[0], DM, LSEQ, 64);
    make_map(enc, &prm.mapXT, pXT, LSEQ, 4 * DM, 64);
    {
      cuuint64_t dims[5] = {DM, 2, 4, 4, 16};
      cuuint64_t strides[4] = {DM * 2, 8 * DM * 2, 2 * DM * 2, 32 * DM * 2};
      cuuint32_t box[5] = {64, 2, 4, 4, 2};
      cuuint32_t es[5] = {1, 1, 1, 1, 1};
      enc(&prm.mapWo, CU_TENSOR_MAP_DATA_TYPE_BFLOAT16, 5, d_in[2], dims, strides, box, es, CU_TENSOR_MAP_INTERLEAVE_NONE,
          CU_TENSOR_MAP_SWIZZLE_128B, CU_TENSOR_MAP_L2_PROMOTION_L2_128B, CU_TENSOR_MAP_FLOAT_OOB_FILL_NONE);
    }
    make_map3(enc, &prm.mapW3, d_in[1], DM, 3 * DM, DM, DM, 3, 3);
    prm.out = (bf16*)d_out;
    prm.a_re = (const bf16*)d_in[4]; prm.a_im = (const bf16*)d_in[5];
    prm.b_re = (const bf16*)d_in[6]; prm.b_im = (const bf16*)d_in[7];
    prm.c_re = (const bf16*)d_in[8]; prm.c_im = (const bf16*)d_in[9];
    prm.log_dt = (const bf16*)d_in[10]; prm.dskip = (const bf16*)d_in[11];
    int dev = 0, sms = 0;
    cudaGetDevice(&dev);
    cudaDeviceGetAttribute(&sms, cudaDevAttrMultiProcessorCount, dev);
    grid = sms >= NCTA + 4 ? NCTA + 4 : NCTA + 5;
    cudaFuncSetAttribute(fused_kernel, cudaFuncAttributeMaxDynamicSharedMemorySize, SM_TOTAL);
    for (int i = 0; i < 12; i++) cached[i] = d_in[i];
    cached[12] = d_out;
    attr_done = true;
  }
  fused_kernel<<<grid, NTHREADS, SM_TOTAL>>>(prm);
}
```

```cpp
#include <cuda_runtime.h>
#include <cuda_bf16.h>
#include <cuda.h>
#include <stdint.h>

typedef __nv_bfloat16 bf16;

constexpr int LSEQ = 2048;
constexpr int DM = 512;
constexpr int NCTA = 128;
constexpr int NTHREADS = 512;
#define R_CONS 200
#define R_HELP 88
#define R_AGENT 24
#define TURN0 4
#define TURN1 4

constexpr int PG = 8192;
constexpr int P_R = 25;
__host__ __device__ constexpr int x_page(int half, int c) { return half ? 8 + c : c < 5 ? c : c - 5; }
__host__ __device__ constexpr int w_page(int c) { return (c & 3) < 3 ? 16 + 3 * (c & 3) : c < 4 ? 5 : 8; }
__host__ __device__ constexpr int wo_page(int c) { return c < 5 ? 3 + c : 11 + c; }
__host__ __device__ constexpr int o_page(int half, int pair) { return half ? (pair ? 25 - 2 * pair : 0) : 8 + 2 * pair; }
constexpr int SM_KGB = (P_R + 1) * PG;
constexpr int SM_KC = 27 * PG;
constexpr int KC_STRIDE = 648;
__host__ __device__ constexpr int kc_off(int lc) { return SM_KC + (lc & 1) * 2 * KC_STRIDE + (lc < 2 ? 3328 : 0); }
constexpr int SM_KGT = SM_KC + 3328 + 2592;
constexpr int SM_CS = SM_KGT + 2048;
constexpr int SM_RED = SM_CS + 768;
constexpr int SM_EP = SM_RED + 16;
constexpr int SM_STG = SM_RED + 32;
constexpr int SM_LN = SM_STG + 768;
__host__ __device__ constexpr int ln_off(int half) { return half ? PG + 4096 : SM_LN; }
constexpr int SM_BAR = SM_LN + 512;
constexpr int SM_TS = SM_BAR + 704;
constexpr int SM_TOTAL = SM_TS + 512;
static_assert(SM_TOTAL <= 232448 && SM_STG % 16 == 0 && SM_KGT % 16 == 0, "shared memory");

constexpr int CV_UH = 140 * 16;
__host__ __device__ constexpr int cv_u(int lc) { return (8 + 2 * lc) * PG; }
__host__ __device__ constexpr int cv_pe(int lc, int early) { return early ? 19 * PG + lc * 4480 : cv_u(lc) + 4480; }
__host__ __device__ constexpr int cv_pb1(int lc, int w) { return w ? cv_u(lc) + 8960 + (w - 1) * 2048 : 7 * PG + lc * 2048; }
__host__ __device__ constexpr int cv_fa(int lc) { return cv_pb1(lc, 1) + 128; }
__host__ __device__ constexpr int cv_dump(int lc) { return cv_u(lc) + 16256; }
__host__ __device__ constexpr int cv_pb0(int lc, int w) { return lc * PG + w * 2048; }
__host__ __device__ constexpr int cv_se(int lc) { return 5 * PG + lc * 4096; }
__host__ __device__ constexpr int cv_so(int lc) { return cv_se(lc) + 2048; }
__host__ __device__ constexpr int cv_x(int half, int lc) { return (P_R + half) * PG + lc * 2048; }
constexpr int CV_ST = 22 * PG;
__host__ __device__ constexpr int cv_chan(int cta, int lc) { return 2 * cta + (lc & 1) + 256 * (lc >> 1); }

enum {
  B_XF = 0,
  B_WF = 16,
  B_OF = 24,
  B_DN = 32,
  B_PG = 46,
  B_XR = 48,
  B_RF = 56,
  B_PST = 58,
  B_GB = 60,
  B_TF = 62,
  B_RT = 64,
  B_RS = 66,
  B_RC = 67,
  B_WOF = 68,
  B_ZF = 69,
  B_EP = 70,
  B_KG = 71,
  B_SC = 37,
  B_LN = 72,
  B_END = 38,
  B_STG = 74,
  B_OST = 76,
  B_PDONE = 78,
  B_PE = 80,
  B_U = 81,
  B_U1 = 82,
  B_PUB = 83,
  B_AL = 86,
  B_COUNT = 87
};

enum {
  C_CS = 0,
  C_G = 1,
  C_C = 5,
  C_O = 21,
  C_Z = 85,
  C_R = 86,
  C_F = 90,
  C_COUNT = 106
};

__device__ unsigned g_cnt[C_COUNT * 32];
__device__ __align__(1024) bf16 g_O[2 * LSEQ * DM];
__device__ __align__(1024) bf16 g_xT[4 * DM * LSEQ];
__device__ __align__(1024) float g_stats[2 * 32 * 192];
__device__ __align__(1024) uint2 g_colsum[3 * DM];
__device__ __align__(1024) uint4 g_halo[32 * 8 * 256];
__device__ __align__(1024) uint4 g_rows[2 * LSEQ];
#define TS(i) do { } while (0)
#define TSW(k) do { if ((threadIdx.x & 127) == 0) TS(16 + layer * 56 + (threadIdx.x >> 7) * 20 + (k)); } while (0)
#define TSG(k) do { } while (0)

#define RETRY(i) do { } while (0)
#define LTS(i) do { } while (0)
#define LTE() do { } while (0)

struct Params {
  CUtensorMap mapX, mapW3, mapXT, mapWo;
  bf16* out;
  const bf16 *a_re, *a_im, *b_re, *b_im, *c_re, *c_im, *log_dt, *dskip;
};

__device__ __forceinline__ uint32_t s32(const void* p) { return (uint32_t)__cvta_generic_to_shared(p); }
__device__ __forceinline__ void mbar_init(uint32_t b, int c) { asm volatile("mbarrier.init.shared::cta.b64 [%0], %1;" ::"r"(b), "r"(c) : "memory"); }
__device__ __forceinline__ void mbar_expect(uint32_t b, int bytes) { asm volatile("mbarrier.arrive.expect_tx.shared::cta.b64 _, [%0], %1;" ::"r"(b), "r"(bytes) : "memory"); }
__device__ __forceinline__ void mbar_arrive(uint32_t b) { asm volatile("mbarrier.arrive.shared::cta.b64 _, [%0];" ::"r"(b) : "memory"); }
__device__ __forceinline__ void mbar_wait(uint32_t b, int parity) {
  asm volatile("{\n.reg .pred p;\nWAIT_LOOP:\nmbarrier.try_wait.parity.shared::cta.b64 p, [%0], %1;\n@p bra WAIT_DONE;\nbra WAIT_LOOP;\nWAIT_DONE:\n}" ::"r"(b), "r"(parity) : "memory");
}
__device__ __forceinline__ bool mbar_test(uint32_t b, int parity) {
  uint32_t ok;
  asm volatile("{\n.reg .pred p;\nmbarrier.test_wait.parity.shared::cta.b64 p, [%1], %2;\nselp.u32 %0, 1, 0, p;\n}" : "=r"(ok) : "r"(b), "r"(parity) : "memory");
  return ok != 0;
}
__device__ __forceinline__ int opaque_tid() { int v; asm volatile("mov.u32 %0, %%tid.x;" : "=r"(v)); return v; }
__device__ __forceinline__ bool elect_one() {
  uint32_t r;
  asm volatile("{\n.reg .pred p;\nelect.sync _|p, 0xffffffff;\nselp.u32 %0, 1, 0, p;\n}" : "=r"(r));
  return r != 0;
}
__device__ __forceinline__ void tma_ld(uint32_t dst, const CUtensorMap* m, int c0, int c1, uint32_t bar) {
  asm volatile("cp.async.bulk.tensor.2d.shared::cluster.global.mbarrier::complete_tx::bytes [%0], [%1, {%3, %4}], [%2];"
               ::"r"(dst), "l"(m), "r"(bar), "r"(c0), "r"(c1) : "memory");
}
__device__ __forceinline__ void tma_ld3(uint32_t dst, const CUtensorMap* m, int c0, int c1, int c2, uint32_t bar) {
  asm volatile("cp.async.bulk.tensor.3d.shared::cluster.global.mbarrier::complete_tx::bytes [%0], [%1, {%3, %4, %5}], [%2];"
               ::"r"(dst), "l"(m), "r"(bar), "r"(c0), "r"(c1), "r"(c2) : "memory");
}
__device__ __forceinline__ void tma_ld5(uint32_t dst, const CUtensorMap* m, int c0, int c4, uint32_t bar) {
  asm volatile("cp.async.bulk.tensor.5d.shared::cluster.global.mbarrier::complete_tx::bytes [%0], [%1, {%3, 0, 0, 0, %4}], [%2];"
               ::"r"(dst), "l"(m), "r"(bar), "r"(c0), "r"(c4) : "memory");
}
__device__ __forceinline__ void tma_prefetch5(const CUtensorMap* m, int c0, int c4) {
  asm volatile("cp.async.bulk.prefetch.tensor.5d.L2.global.tile [%0, {%1, 0, 0, 0, %2}];" ::"l"(m), "r"(c0), "r"(c4) : "memory");
}
__device__ __forceinline__ void tma_prefetch3(const CUtensorMap* m, int c0, int c1, int c2) {
  asm volatile("cp.async.bulk.prefetch.tensor.3d.L2.global.tile [%0, {%1, %2, %3}];" ::"l"(m), "r"(c0), "r"(c1), "r"(c2) : "memory");
}
__device__ __forceinline__ void tma_st(const CUtensorMap* m, int c0, int c1, uint32_t src) {
  asm volatile("cp.async.bulk.tensor.2d.global.shared::cta.bulk_group [%0, {%2, %3}], [%1];" ::"l"(m), "r"(src), "r"(c0), "r"(c1) : "memory");
}
__device__ __forceinline__ void bulk_ld(uint32_t dst, const void* src, int bytes, uint32_t bar) {
  asm volatile("cp.async.bulk.shared::cluster.global.mbarrier::complete_tx::bytes [%0], [%1], %2, [%3];" ::"r"(dst), "l"(src), "r"(bytes), "r"(bar) : "memory");
}
__device__ __forceinline__ void bulk_red_add_f32(void* dst, uint32_t src, int bytes) {
  asm volatile("cp.reduce.async.bulk.global.shared::cta.bulk_group.add.f32 [%0], [%1], %2;" ::"l"(dst), "r"(src), "r"(bytes) : "memory");
}
__device__ __forceinline__ void bulk_commit() { asm volatile("cp.async.bulk.commit_group;" ::: "memory"); }
__device__ __forceinline__ void fence_async_smem() { asm volatile("fence.proxy.async.shared::cta;" ::: "memory"); }
__device__ __forceinline__ void fence_async_global() { asm volatile("fence.proxy.async.global;" ::: "memory"); }
__device__ __forceinline__ void bar_sync(int id, int n) { asm volatile("bar.sync %0, %1;" ::"r"(id), "r"(n) : "memory"); }
__device__ __forceinline__ void bar_arrive(int id, int n) { asm volatile("bar.arrive %0, %1;" ::"r"(id), "r"(n) : "memory"); }
__device__ __forceinline__ bool bar_or(int id, int n, bool v) {
  uint32_t r;
  asm volatile("{\n.reg .pred p, q;\nsetp.ne.u32 q, %3, 0;\nbar.red.or.pred p, %1, %2, q;\nselp.u32 %0, 1, 0, p;\n}" : "=r"(r) : "r"(id), "r"(n), "r"((uint32_t)v) : "memory");
  return r != 0;
}
__device__ __forceinline__ void bulk_wait_read() { asm volatile("cp.async.bulk.wait_group.read 0;" ::: "memory"); }
__device__ __forceinline__ void stg128(void* p, uint4 v) { asm volatile("st.relaxed.gpu.global.v4.u32 [%0], {%1,%2,%3,%4};" ::"l"(p), "r"(v.x), "r"(v.y), "r"(v.z), "r"(v.w) : "memory"); }
constexpr uint32_t UNSET = 0xffffffffu;
constexpr int MAX_RETRY = 1 << 16;
__device__ __forceinline__ void wg_fence() { asm volatile("wgmma.fence.sync.aligned;" ::: "memory"); }
__device__ __forceinline__ void wg_commit() { asm volatile("wgmma.commit_group.sync.aligned;" ::: "memory"); }
template <int N> __device__ __forceinline__ void wg_wait() { asm volatile("wgmma.wait_group.sync.aligned %0;" ::"n"(N) : "memory"); }
__device__ __forceinline__ uint64_t mkdesc(uint32_t addr, uint32_t lbo, uint32_t sbo, int sw) {
  return (uint64_t)((addr & 0x3FFFF) >> 4) | ((uint64_t)(lbo >> 4) << 16) | ((uint64_t)(sbo >> 4) << 32) | ((uint64_t)sw << 62);
}
__device__ __forceinline__ void ldsm4(uint32_t* r, uint32_t a) {
  asm volatile("ldmatrix.sync.aligned.m8n8.x4.shared.b16 {%0,%1,%2,%3}, [%4];" : "=r"(r[0]), "=r"(r[1]), "=r"(r[2]), "=r"(r[3]) : "r"(a) : "memory");
}
__device__ __forceinline__ void ldsm4t(uint32_t* r, uint32_t a) {
  asm volatile("ldmatrix.sync.aligned.m8n8.x4.trans.shared.b16 {%0,%1,%2,%3}, [%4];" : "=r"(r[0]), "=r"(r[1]), "=r"(r[2]), "=r"(r[3]) : "r"(a) : "memory");
}
__device__ __forceinline__ void stsm4(uint32_t a, uint32_t r0, uint32_t r1, uint32_t r2, uint32_t r3) {
  asm volatile("stmatrix.sync.aligned.m8n8.x4.shared.b16 [%0], {%1,%2,%3,%4};" ::"r"(a), "r"(r0), "r"(r1), "r"(r2), "r"(r3) : "memory");
}
__device__ __forceinline__ void stsm4t(uint32_t a, uint32_t r0, uint32_t r1, uint32_t r2, uint32_t r3) {
  asm volatile("stmatrix.sync.aligned.m8n8.x4.trans.shared.b16 [%0], {%1,%2,%3,%4};" ::"r"(a), "r"(r0), "r"(r1), "r"(r2), "r"(r3) : "memory");
}
__device__ __forceinline__ uint32_t movm_t(uint32_t a) { uint32_t r; asm volatile("movmatrix.sync.aligned.m8n8.trans.b16 %0, %1;" : "=r"(r) : "r"(a)); return r; }
__device__ __forceinline__ uint32_t lds32(uint32_t a) { uint32_t v; asm volatile("ld.shared.b32 %0, [%1];" : "=r"(v) : "r"(a) : "memory"); return v; }
__device__ __forceinline__ float2 lds64f(uint32_t a) { float2 v; asm volatile("ld.shared.v2.f32 {%0,%1}, [%2];" : "=f"(v.x), "=f"(v.y) : "r"(a) : "memory"); return v; }
__device__ __forceinline__ float4 lds128f(uint32_t a) { float4 v; asm volatile("ld.shared.v4.f32 {%0,%1,%2,%3}, [%4];" : "=f"(v.x), "=f"(v.y), "=f"(v.z), "=f"(v.w) : "r"(a) : "memory"); return v; }
__device__ __forceinline__ uint4 lds128(uint32_t a) { uint4 v; asm volatile("ld.shared.v4.b32 {%0,%1,%2,%3}, [%4];" : "=r"(v.x), "=r"(v.y), "=r"(v.z), "=r"(v.w) : "r"(a) : "memory"); return v; }
__device__ __forceinline__ void sts128(uint32_t a, uint4 v) { asm volatile("st.shared.v4.b32 [%0], {%1,%2,%3,%4};" ::"r"(a), "r"(v.x), "r"(v.y), "r"(v.z), "r"(v.w) : "memory"); }
__device__ __forceinline__ void sts128f(uint32_t a, float x, float y, float z, float w) { asm volatile("st.shared.v4.f32 [%0], {%1,%2,%3,%4};" ::"r"(a), "f"(x), "f"(y), "f"(z), "f"(w) : "memory"); }
__device__ __forceinline__ void sts32f(uint32_t a, float v) { asm volatile("st.shared.f32 [%0], %1;" ::"r"(a), "f"(v) : "memory"); }
__device__ __forceinline__ void sts16(uint32_t a, uint16_t v) { asm volatile("st.shared.u16 [%0], %1;" ::"r"(a), "h"(v) : "memory"); }
__device__ __forceinline__ uint32_t lds16(uint32_t a) { uint16_t v; asm volatile("ld.shared.u16 %0, [%1];" : "=h"(v) : "r"(a) : "memory"); return v; }
__device__ __forceinline__ uint32_t packbf(float lo, float hi) { uint32_t r; asm("cvt.rn.bf16x2.f32 %0, %1, %2;" : "=r"(r) : "f"(hi), "f"(lo)); return r; }
__device__ __forceinline__ float bf_lo(uint32_t v) { return __uint_as_float(v << 16); }
__device__ __forceinline__ float bf_hi(uint32_t v) { return __uint_as_float(v & 0xffff0000u); }
__device__ __forceinline__ float ex2(float x) { float r; asm("ex2.approx.ftz.f32 %0, %1;" : "=f"(r) : "f"(x)); return r; }
__device__ __forceinline__ float rsqrt_approx(float x) { float r; asm("rsqrt.approx.ftz.f32 %0, %1;" : "=f"(r) : "f"(x)); return r; }
__device__ __forceinline__ float rcp_approx(float x) { float r; asm("rcp.approx.ftz.f32 %0, %1;" : "=f"(r) : "f"(x)); return r; }
__device__ __forceinline__ void mma_bf16(float* d, const uint32_t* a, uint32_t b0, uint32_t b1) {
  asm("mma.sync.aligned.m16n8k16.row.col.f32.bf16.bf16.f32 {%0,%1,%2,%3}, {%4,%5,%6,%7}, {%8,%9}, {%0,%1,%2,%3};"
               : "+f"(d[0]), "+f"(d[1]), "+f"(d[2]), "+f"(d[3]) : "r"(a[0]), "r"(a[1]), "r"(a[2]), "r"(a[3]), "r"(b0), "r"(b1));
}
__device__ __forceinline__ void red_release(unsigned* p) { asm volatile("red.release.gpu.global.add.u32 [%0], 1;" ::"l"(p) : "memory"); }
__device__ __forceinline__ void red_relaxed(unsigned* p) { asm volatile("red.relaxed.gpu.global.add.u32 [%0], 1;" ::"l"(p) : "memory"); }
__device__ __forceinline__ unsigned ld_relaxed(const unsigned* p) { unsigned v; asm volatile("ld.relaxed.gpu.global.u32 %0, [%1];" : "=r"(v) : "l"(p) : "memory"); return v; }
__device__ __forceinline__ void spin_until(const unsigned* p, unsigned target) {
  int it = 0;
  while ((int)(ld_relaxed(p) - target) < 0) {
    if (++it > (1 << 23)) __trap();
  }
}
__device__ __forceinline__ void delay(uint32_t cycles) {
  const uint32_t t0 = (uint32_t)clock();
  while ((uint32_t)clock() - t0 < cycles);
}
__device__ __forceinline__ void spin_hint(const unsigned* p, unsigned target) {
  spin_until(p, target);
}
__device__ __forceinline__ uint4 ld_tagged(const uint4* p) { uint4 v; asm volatile("ld.relaxed.gpu.global.v4.u32 {%0,%1,%2,%3}, [%4];" : "=r"(v.x), "=r"(v.y), "=r"(v.z), "=r"(v.w) : "l"(p) : "memory"); return v; }
__device__ __forceinline__ uint32_t hadd2(uint32_t a, uint32_t b) { uint32_t r; asm("add.rn.bf16x2 %0, %1, %2;" : "=r"(r) : "r"(a), "r"(b)); return r; }

__device__ __forceinline__ uint32_t hfma2(uint32_t a, uint32_t b, uint32_t c) { uint32_t r; asm("fma.rn.bf16x2 %0, %1, %2, %3;" : "=r"(r) : "r"(a), "r"(b), "r"(c)); return r; }
__device__ __forceinline__ void sts32(uint32_t a, uint32_t v) { asm volatile("st.shared.u32 [%0], %1;" ::"r"(a), "r"(v) : "memory"); }

template <int N> __device__ __forceinline__ void acc_fence(float* a) {
#pragma unroll
  for (int i = 0; i < N; i++) asm volatile("" : "+f"(a[i]) :: "memory");
}

template<int N,int TB> __device__ __forceinline__ void wgmma_rs(float* d, const uint32_t* a, uint64_t db, int sd);
template<int N,int TA,int TB> __device__ __forceinline__ void wgmma_ss(float* d, uint64_t da, uint64_t db, int sd);
template<> __device__ __forceinline__ void wgmma_rs<64,0>(float* d, const uint32_t* a, uint64_t db, int sd) {
  asm volatile("{\n.reg .pred p;\nsetp.ne.b32 p, %37, 0;\nwgmma.mma_async.sync.aligned.m64n64k16.f32.bf16.bf16 {%0,%1,%2,%3,%4,%5,%6,%7,%8,%9,%10,%11,%12,%13,%14,%15,%16,%17,%18,%19,%20,%21,%22,%23,%24,%25,%26,%27,%28,%29,%30,%31}, {%32,%33,%34,%35}, %36, p, 1, 1, 0;\n}\n"
   : "+f"(d[0]),"+f"(d[1]),"+f"(d[2]),"+f"(d[3]),"+f"(d[4]),"+f"(d[5]),"+f"(d[6]),"+f"(d[7]),"+f"(d[8]),"+f"(d[9]),"+f"(d[10]),"+f"(d[11]),"+f"(d[12]),"+f"(d[13]),"+f"(d[14]),"+f"(d[15]),"+f"(d[16]),"+f"(d[17]),"+f"(d[18]),"+f"(d[19]),"+f"(d[20]),"+f"(d[21]),"+f"(d[22]),"+f"(d[23]),"+f"(d[24]),"+f"(d[25]),"+f"(d[26]),"+f"(d[27]),"+f"(d[28]),"+f"(d[29]),"+f"(d[30]),"+f"(d[31])
   : "r"(a[0]), "r"(a[1]), "r"(a[2]), "r"(a[3]), "l"(db), "r"(sd));
}
template<> __device__ __forceinline__ void wgmma_rs<56,0>(float* d, const uint32_t* a, uint64_t db, int sd) {
  asm volatile("{\n.reg .pred p;\nsetp.ne.b32 p, %33, 0;\nwgmma.mma_async.sync.aligned.m64n56k16.f32.bf16.bf16 {%0,%1,%2,%3,%4,%5,%6,%7,%8,%9,%10,%11,%12,%13,%14,%15,%16,%17,%18,%19,%20,%21,%22,%23,%24,%25,%26,%27}, {%28,%29,%30,%31}, %32, p, 1, 1, 0;\n}\n"
   : "+f"(d[0]),"+f"(d[1]),"+f"(d[2]),"+f"(d[3]),"+f"(d[4]),"+f"(d[5]),"+f"(d[6]),"+f"(d[7]),"+f"(d[8]),"+f"(d[9]),"+f"(d[10]),"+f"(d[11]),"+f"(d[12]),"+f"(d[13]),"+f"(d[14]),"+f"(d[15]),"+f"(d[16]),"+f"(d[17]),"+f"(d[18]),"+f"(d[19]),"+f"(d[20]),"+f"(d[21]),"+f"(d[22]),"+f"(d[23]),"+f"(d[24]),"+f"(d[25]),"+f"(d[26]),"+f"(d[27])
   : "r"(a[0]), "r"(a[1]), "r"(a[2]), "r"(a[3]), "l"(db), "r"(sd));
}
template<> __device__ __forceinline__ void wgmma_rs<48,0>(float* d, const uint32_t* a, uint64_t db, int sd) {
  asm volatile("{\n.reg .pred p;\nsetp.ne.b32 p, %29, 0;\nwgmma.mma_async.sync.aligned.m64n48k16.f32.bf16.bf16 {%0,%1,%2,%3,%4,%5,%6,%7,%8,%9,%10,%11,%12,%13,%14,%15,%16,%17,%18,%19,%20,%21,%22,%23}, {%24,%25,%26,%27}, %28, p, 1, 1, 0;\n}\n"
   : "+f"(d[0]),"+f"(d[1]),"+f"(d[2]),"+f"(d[3]),"+f"(d[4]),"+f"(d[5]),"+f"(d[6]),"+f"(d[7]),"+f"(d[8]),"+f"(d[9]),"+f"(d[10]),"+f"(d[11]),"+f"(d[12]),"+f"(d[13]),"+f"(d[14]),"+f"(d[15]),"+f"(d[16]),"+f"(d[17]),"+f"(d[18]),"+f"(d[19]),"+f"(d[20]),"+f"(d[21]),"+f"(d[22]),"+f"(d[23])
   : "r"(a[0]), "r"(a[1]), "r"(a[2]), "r"(a[3]), "l"(db), "r"(sd));
}
template<> __device__ __forceinline__ void wgmma_rs<40,0>(float* d, const uint32_t* a, uint64_t db, int sd) {
  asm volatile("{\n.reg .pred p;\nsetp.ne.b32 p, %25, 0;\nwgmma.mma_async.sync.aligned.m64n40k16.f32.bf16.bf16 {%0,%1,%2,%3,%4,%5,%6,%7,%8,%9,%10,%11,%12,%13,%14,%15,%16,%17,%18,%19}, {%20,%21,%22,%23}, %24, p, 1, 1, 0;\n}\n"
   : "+f"(d[0]),"+f"(d[1]),"+f"(d[2]),"+f"(d[3]),"+f"(d[4]),"+f"(d[5]),"+f"(d[6]),"+f"(d[7]),"+f"(d[8]),"+f"(d[9]),"+f"(d[10]),"+f"(d[11]),"+f"(d[12]),"+f"(d[13]),"+f"(d[14]),"+f"(d[15]),"+f"(d[16]),"+f"(d[17]),"+f"(d[18]),"+f"(d[19])
   : "r"(a[0]), "r"(a[1]), "r"(a[2]), "r"(a[3]), "l"(db), "r"(sd));
}
template<> __device__ __forceinline__ void wgmma_rs<32,0>(float* d, const uint32_t* a, uint64_t db, int sd) {
  asm volatile("{\n.reg .pred p;\nsetp.ne.b32 p, %21, 0;\nwgmma.mma_async.sync.aligned.m64n32k16.f32.bf16.bf16 {%0,%1,%2,%3,%4,%5,%6,%7,%8,%9,%10,%11,%12,%13,%14,%15}, {%16,%17,%18,%19}, %20, p, 1, 1, 0;\n}\n"
   : "+f"(d[0]),"+f"(d[1]),"+f"(d[2]),"+f"(d[3]),"+f"(d[4]),"+f"(d[5]),"+f"(d[6]),"+f"(d[7]),"+f"(d[8]),"+f"(d[9]),"+f"(d[10]),"+f"(d[11]),"+f"(d[12]),"+f"(d[13]),"+f"(d[14]),"+f"(d[15])
   : "r"(a[0]), "r"(a[1]), "r"(a[2]), "r"(a[3]), "l"(db), "r"(sd));
}
template<> __device__ __forceinline__ void wgmma_rs<24,0>(float* d, const uint32_t* a, uint64_t db, int sd) {
  asm volatile("{\n.reg .pred p;\nsetp.ne.b32 p, %17, 0;\nwgmma.mma_async.sync.aligned.m64n24k16.f32.bf16.bf16 {%0,%1,%2,%3,%4,%5,%6,%7,%8,%9,%10,%11}, {%12,%13,%14,%15}, %16, p, 1, 1, 0;\n}\n"
   : "+f"(d[0]),"+f"(d[1]),"+f"(d[2]),"+f"(d[3]),"+f"(d[4]),"+f"(d[5]),"+f"(d[6]),"+f"(d[7]),"+f"(d[8]),"+f"(d[9]),"+f"(d[10]),"+f"(d[11])
   : "r"(a[0]), "r"(a[1]), "r"(a[2]), "r"(a[3]), "l"(db), "r"(sd));
}
template<> __device__ __forceinline__ void wgmma_rs<16,0>(float* d, const uint32_t* a, uint64_t db, int sd) {
  asm volatile("{\n.reg .pred p;\nsetp.ne.b32 p, %13, 0;\nwgmma.mma_async.sync.aligned.m64n16k16.f32.bf16.bf16 {%0,%1,%2,%3,%4,%5,%6,%7}, {%8,%9,%10,%11}, %12, p, 1, 1, 0;\n}\n"
   : "+f"(d[0]),"+f"(d[1]),"+f"(d[2]),"+f"(d[3]),"+f"(d[4]),"+f"(d[5]),"+f"(d[6]),"+f"(d[7])
   : "r"(a[0]), "r"(a[1]), "r"(a[2]), "r"(a[3]), "l"(db), "r"(sd));
}
template<> __device__ __forceinline__ void wgmma_rs<8,0>(float* d, const uint32_t* a, uint64_t db, int sd) {
  asm volatile("{\n.reg .pred p;\nsetp.ne.b32 p, %9, 0;\nwgmma.mma_async.sync.aligned.m64n8k16.f32.bf16.bf16 {%0,%1,%2,%3}, {%4,%5,%6,%7}, %8, p, 1, 1, 0;\n}\n"
   : "+f"(d[0]),"+f"(d[1]),"+f"(d[2]),"+f"(d[3])
   : "r"(a[0]), "r"(a[1]), "r"(a[2]), "r"(a[3]), "l"(db), "r"(sd));
}
template<> __device__ __forceinline__ void wgmma_ss<64,1,0>(float* d, uint64_t da, uint64_t db, int sd) {
  asm volatile("{\n.reg .pred p;\nsetp.ne.b32 p, %34, 0;\nwgmma.mma_async.sync.aligned.m64n64k16.f32.bf16.bf16 {%0,%1,%2,%3,%4,%5,%6,%7,%8,%9,%10,%11,%12,%13,%14,%15,%16,%17,%18,%19,%20,%21,%22,%23,%24,%25,%26,%27,%28,%29,%30,%31}, %32, %33, p, 1, 1, 1, 0;\n}\n"
   : "+f"(d[0]),"+f"(d[1]),"+f"(d[2]),"+f"(d[3]),"+f"(d[4]),"+f"(d[5]),"+f"(d[6]),"+f"(d[7]),"+f"(d[8]),"+f"(d[9]),"+f"(d[10]),"+f"(d[11]),"+f"(d[12]),"+f"(d[13]),"+f"(d[14]),"+f"(d[15]),"+f"(d[16]),"+f"(d[17]),"+f"(d[18]),"+f"(d[19]),"+f"(d[20]),"+f"(d[21]),"+f"(d[22]),"+f"(d[23]),"+f"(d[24]),"+f"(d[25]),"+f"(d[26]),"+f"(d[27]),"+f"(d[28]),"+f"(d[29]),"+f"(d[30]),"+f"(d[31])
   : "l"(da), "l"(db), "r"(sd));
}
template<> __device__ __forceinline__ void wgmma_ss<64,0,1>(float* d, uint64_t da, uint64_t db, int sd) {
  asm volatile("{\n.reg .pred p;\nsetp.ne.b32 p, %34, 0;\nwgmma.mma_async.sync.aligned.m64n64k16.f32.bf16.bf16 {%0,%1,%2,%3,%4,%5,%6,%7,%8,%9,%10,%11,%12,%13,%14,%15,%16,%17,%18,%19,%20,%21,%22,%23,%24,%25,%26,%27,%28,%29,%30,%31}, %32, %33, p, 1, 1, 0, 1;\n}\n"
   : "+f"(d[0]),"+f"(d[1]),"+f"(d[2]),"+f"(d[3]),"+f"(d[4]),"+f"(d[5]),"+f"(d[6]),"+f"(d[7]),"+f"(d[8]),"+f"(d[9]),"+f"(d[10]),"+f"(d[11]),"+f"(d[12]),"+f"(d[13]),"+f"(d[14]),"+f"(d[15]),"+f"(d[16]),"+f"(d[17]),"+f"(d[18]),"+f"(d[19]),"+f"(d[20]),"+f"(d[21]),"+f"(d[22]),"+f"(d[23]),"+f"(d[24]),"+f"(d[25]),"+f"(d[26]),"+f"(d[27]),"+f"(d[28]),"+f"(d[29]),"+f"(d[30]),"+f"(d[31])
   : "l"(da), "l"(db), "r"(sd));
}
template<> __device__ __forceinline__ void wgmma_ss<192,0,1>(float* d, uint64_t da, uint64_t db, int sd) {
  asm volatile("{\n.reg .pred p;\nsetp.ne.b32 p, %98, 0;\nwgmma.mma_async.sync.aligned.m64n192k16.f32.bf16.bf16 {%0,%1,%2,%3,%4,%5,%6,%7,%8,%9,%10,%11,%12,%13,%14,%15,%16,%17,%18,%19,%20,%21,%22,%23,%24,%25,%26,%27,%28,%29,%30,%31,%32,%33,%34,%35,%36,%37,%38,%39,%40,%41,%42,%43,%44,%45,%46,%47,%48,%49,%50,%51,%52,%53,%54,%55,%56,%57,%58,%59,%60,%61,%62,%63,%64,%65,%66,%67,%68,%69,%70,%71,%72,%73,%74,%75,%76,%77,%78,%79,%80,%81,%82,%83,%84,%85,%86,%87,%88,%89,%90,%91,%92,%93,%94,%95}, %96, %97, p, 1, 1, 0, 1;\n}\n"
   : "+f"(d[0]),"+f"(d[1]),"+f"(d[2]),"+f"(d[3]),"+f"(d[4]),"+f"(d[5]),"+f"(d[6]),"+f"(d[7]),"+f"(d[8]),"+f"(d[9]),"+f"(d[10]),"+f"(d[11]),"+f"(d[12]),"+f"(d[13]),"+f"(d[14]),"+f"(d[15]),"+f"(d[16]),"+f"(d[17]),"+f"(d[18]),"+f"(d[19]),"+f"(d[20]),"+f"(d[21]),"+f"(d[22]),"+f"(d[23]),"+f"(d[24]),"+f"(d[25]),"+f"(d[26]),"+f"(d[27]),"+f"(d[28]),"+f"(d[29]),"+f"(d[30]),"+f"(d[31]),"+f"(d[32]),"+f"(d[33]),"+f"(d[34]),"+f"(d[35]),"+f"(d[36]),"+f"(d[37]),"+f"(d[38]),"+f"(d[39]),"+f"(d[40]),"+f"(d[41]),"+f"(d[42]),"+f"(d[43]),"+f"(d[44]),"+f"(d[45]),"+f"(d[46]),"+f"(d[47]),"+f"(d[48]),"+f"(d[49]),"+f"(d[50]),"+f"(d[51]),"+f"(d[52]),"+f"(d[53]),"+f"(d[54]),"+f"(d[55]),"+f"(d[56]),"+f"(d[57]),"+f"(d[58]),"+f"(d[59]),"+f"(d[60]),"+f"(d[61]),"+f"(d[62]),"+f"(d[63]),"+f"(d[64]),"+f"(d[65]),"+f"(d[66]),"+f"(d[67]),"+f"(d[68]),"+f"(d[69]),"+f"(d[70]),"+f"(d[71]),"+f"(d[72]),"+f"(d[73]),"+f"(d[74]),"+f"(d[75]),"+f"(d[76]),"+f"(d[77]),"+f"(d[78]),"+f"(d[79]),"+f"(d[80]),"+f"(d[81]),"+f"(d[82]),"+f"(d[83]),"+f"(d[84]),"+f"(d[85]),"+f"(d[86]),"+f"(d[87]),"+f"(d[88]),"+f"(d[89]),"+f"(d[90]),"+f"(d[91]),"+f"(d[92]),"+f"(d[93]),"+f"(d[94]),"+f"(d[95])
   : "l"(da), "l"(db), "r"(sd));
}
template<> __device__ __forceinline__ void wgmma_ss<192,1,1>(float* d, uint64_t da, uint64_t db, int sd) {
  asm volatile("{\n.reg .pred p;\nsetp.ne.b32 p, %98, 0;\nwgmma.mma_async.sync.aligned.m64n192k16.f32.bf16.bf16 {%0,%1,%2,%3,%4,%5,%6,%7,%8,%9,%10,%11,%12,%13,%14,%15,%16,%17,%18,%19,%20,%21,%22,%23,%24,%25,%26,%27,%28,%29,%30,%31,%32,%33,%34,%35,%36,%37,%38,%39,%40,%41,%42,%43,%44,%45,%46,%47,%48,%49,%50,%51,%52,%53,%54,%55,%56,%57,%58,%59,%60,%61,%62,%63,%64,%65,%66,%67,%68,%69,%70,%71,%72,%73,%74,%75,%76,%77,%78,%79,%80,%81,%82,%83,%84,%85,%86,%87,%88,%89,%90,%91,%92,%93,%94,%95}, %96, %97, p, 1, 1, 1, 1;\n}\n"
   : "+f"(d[0]),"+f"(d[1]),"+f"(d[2]),"+f"(d[3]),"+f"(d[4]),"+f"(d[5]),"+f"(d[6]),"+f"(d[7]),"+f"(d[8]),"+f"(d[9]),"+f"(d[10]),"+f"(d[11]),"+f"(d[12]),"+f"(d[13]),"+f"(d[14]),"+f"(d[15]),"+f"(d[16]),"+f"(d[17]),"+f"(d[18]),"+f"(d[19]),"+f"(d[20]),"+f"(d[21]),"+f"(d[22]),"+f"(d[23]),"+f"(d[24]),"+f"(d[25]),"+f"(d[26]),"+f"(d[27]),"+f"(d[28]),"+f"(d[29]),"+f"(d[30]),"+f"(d[31]),"+f"(d[32]),"+f"(d[33]),"+f"(d[34]),"+f"(d[35]),"+f"(d[36]),"+f"(d[37]),"+f"(d[38]),"+f"(d[39]),"+f"(d[40]),"+f"(d[41]),"+f"(d[42]),"+f"(d[43]),"+f"(d[44]),"+f"(d[45]),"+f"(d[46]),"+f"(d[47]),"+f"(d[48]),"+f"(d[49]),"+f"(d[50]),"+f"(d[51]),"+f"(d[52]),"+f"(d[53]),"+f"(d[54]),"+f"(d[55]),"+f"(d[56]),"+f"(d[57]),"+f"(d[58]),"+f"(d[59]),"+f"(d[60]),"+f"(d[61]),"+f"(d[62]),"+f"(d[63]),"+f"(d[64]),"+f"(d[65]),"+f"(d[66]),"+f"(d[67]),"+f"(d[68]),"+f"(d[69]),"+f"(d[70]),"+f"(d[71]),"+f"(d[72]),"+f"(d[73]),"+f"(d[74]),"+f"(d[75]),"+f"(d[76]),"+f"(d[77]),"+f"(d[78]),"+f"(d[79]),"+f"(d[80]),"+f"(d[81]),"+f"(d[82]),"+f"(d[83]),"+f"(d[84]),"+f"(d[85]),"+f"(d[86]),"+f"(d[87]),"+f"(d[88]),"+f"(d[89]),"+f"(d[90]),"+f"(d[91]),"+f"(d[92]),"+f"(d[93]),"+f"(d[94]),"+f"(d[95])
   : "l"(da), "l"(db), "r"(sd));
}

template <bool TR>
__device__ __forceinline__ void gemm_section(float* acc, float& mean0, float& mean1, float& rstd0, float& rstd1,
                                             uint32_t sb, int blk, int hg, int wg, int w, int lane) {
  constexpr int layer = TR ? 1 : 0;
  constexpr int TURN = TR ? TURN1 : TURN0;
  constexpr int LSTAT = TURN < 4 ? TURN - 1 : 3;
  const uint32_t bar = sb + SM_BAR;
  const int g = lane >> 2, t = lane & 3;
  const bool leader = (w == 0) && (lane == 0);
  const int statpos = hg < 3 ? 1 : wg ? LSTAT : TR ? 3 : 2;
  const bool copy = hg >= 3 && wg == 0;
  const int cut = wg ? TURN : 4;
  auto wait_full = [&](int c) {
    mbar_wait(bar + 8 * (B_XF + 8 * wg + c), layer);
    mbar_wait(bar + 8 * (B_WF + c), layer);
  };
  auto peek = [&](int c) {
    const bool x = mbar_test(bar + 8 * (B_XF + 8 * wg + c), layer), y = mbar_test(bar + 8 * (B_WF + c), layer);
    return x && y;
  };
  const uint64_t da0 = mkdesc(sb, TR ? 8192 : 16, 1024, 1), db0 = mkdesc(sb, 8192, 1024, 1);
  uint32_t xt = wg ? 0xfedcba98u : 0x21043210u;
  uint64_t wt = 0x0816131005161310ull;
  uint64_t da = da0 + ((xt & 15) << 9), db = db0 + (16 << 9);
  auto issue = [&](int c, int first) {
    wg_fence();
#pragma unroll
    for (int ks = 0; ks < 4; ks++) wgmma_ss<192, TR ? 1 : 0, 1>(acc, da + (TR ? ks * 128 : ks * 2), db + ks * 128, !first || ks != 0);
    wg_commit();
    xt >>= 4; wt >>= 8;
    da = da0 + ((xt & 15) << 9); db = db0 + (((uint32_t)wt & 31) << 9);
  };
  wait_full(0);
  bool ready = peek(1);
  issue(0, 1);
  TSW(0);
#pragma unroll 1
  for (int c = 1; c < cut; c++) {
    if (!ready) wait_full(c);
    issue(c, 0);
    ready = peek(c + 1);
    wg_wait<1>();
    if (leader) mbar_arrive(bar + 8 * (B_DN + 8 * wg + c - 1));
    if (wg == 1 && c == cut - 1) {
      wg_wait<0>();
      if (leader) mbar_arrive(bar + 8 * (B_DN + 8 + c));
    }
    if (c == statpos) {
      mbar_wait(bar + 8 * (copy ? B_SC : B_XF + 8 * wg + hg), layer);
      uint32_t A[16];
      const uint32_t xb = sb + (copy ? P_R : 8 * wg + hg) * PG;
#pragma unroll
      for (int ks = 0; ks < 4; ks++) {
        if (!TR) {
          const int row = 16 * w + (lane & 15), kc = 2 * ks + (lane >> 4);
          ldsm4(&A[4 * ks], xb + row * 128 + ((kc ^ (row & 7)) << 4));
        } else {
          const int k = 16 * ks + (lane & 7) + 8 * (lane >> 4), pc = 2 * w + ((lane >> 3) & 1);
          ldsm4t(&A[4 * ks], xb + k * 128 + ((pc ^ (k & 7)) << 4));
        }
      }
      float s0 = 0.f, q0 = 0.f, s1 = 0.f, q1 = 0.f;
#pragma unroll
      for (int i = 0; i < 16; i += 2) {
        const float a = bf_lo(A[i]), b = bf_hi(A[i]), c_ = bf_lo(A[i + 1]), d = bf_hi(A[i + 1]);
        s0 += a + b; q0 = fmaf(a, a, q0); q0 = fmaf(b, b, q0);
        s1 += c_ + d; q1 = fmaf(c_, c_, q1); q1 = fmaf(d, d, q1);
      }
#pragma unroll
      for (int o = 1; o <= 2; o <<= 1) {
        s0 += __shfl_xor_sync(~0u, s0, o); q0 += __shfl_xor_sync(~0u, q0, o);
        s1 += __shfl_xor_sync(~0u, s1, o); q1 += __shfl_xor_sync(~0u, q1, o);
      }
      if (t < 2)
        asm volatile("red.relaxed.gpu.global.add.v4.f32 [%0], {%1,%2,%3,%4};" ::"l"(g_rows + layer * LSEQ + blk * 64 + 16 * w + g + 8 * t),
                     "f"(t ? s1 : s0), "f"(t ? q1 : q0), "f"(1.f), "f"(0.f) : "memory");
    }
  }
  if (wg == 1) {
#pragma unroll 1
    for (int c = cut; c < 8; c++) wait_full(c);
    ready = true;
    bar_sync(5, 256);
  }
#pragma unroll 1
  for (int c = cut; c < 8; c++) {
    if (!ready) wait_full(c);
    issue(c, 0);
    if (wg == 1) {
      wg_wait<2>();
      if (leader && c >= cut + 2) mbar_arrive(bar + 8 * (B_DN + 8 + c - 2));
    } else if (c == 7) {
      bar_arrive(5, 256);
    } else {
      ready = peek(c + 1);
      wg_wait<1>();
      if (leader && c < 6) mbar_arrive(bar + 8 * (B_DN + c - 1));
    }
  }
  mbar_wait(bar + 8 * (B_LN + wg), layer);
  const float4 ln = lds128f(sb + ln_off(wg) + (8 * w + g) * 16);
  mean0 = ln.x; rstd0 = ln.y; mean1 = ln.z; rstd1 = ln.w;
  wg_wait<0>();
  acc_fence<96>(acc);
  if (leader) mbar_arrive(bar + 8 * (B_DN + 8 * wg + 7));
}

__device__ __forceinline__ void attn_phase(const Params& p, uint32_t sb, int layer, int rb, int hg, int wg, int w) {
  const int lane = opaque_tid() & 31;
  const int g = lane >> 2, t = lane & 3;
  const uint32_t bar = sb + SM_BAR;
  const int blk = 16 * wg + rb;
  float acc[96];
  float2 cs[24];
  float mean0, mean1, rstd0, rstd1;
  if (layer) gemm_section<true>(acc, mean0, mean1, rstd0, rstd1, sb, blk, hg, wg, w, lane);
  else gemm_section<false>(acc, mean0, mean1, rstd0, rstd1, sb, blk, hg, wg, w, lane);
  TSW(1);
#pragma unroll
  for (int j = 8; j < 24; j++) cs[j] = lds64f(sb + SM_CS + 4 * (8 * j + 2 * t));
  const uint32_t kvx = sb + (wg ? 22 : 0) * PG;

  uint32_t kb[4][8], vb[4][8], qa[4][4];
  {
    const float nm0 = -mean0 * rstd0, nm1 = -mean1 * rstd1;
    const int st_row = 16 * w + (lane & 7) + 8 * ((lane >> 3) & 1);
    const uint32_t st_base = kvx + st_row * 256;
    const bool sender = (w == 3 && blk < 31);
    uint4* halo = &g_halo[(blk * 8 + hg) * 256 + lane];
    uint32_t r[4][2][4];
#pragma unroll
    for (int h = 0; h < 4; h++) {
#pragma unroll
      for (int kv = 0; kv < 2; kv++) {
#pragma unroll
        for (int dh = 0; dh < 2; dh++) {
          const int j = 8 + kv * 8 + 2 * h + dh;
          const float2 c2 = cs[j];
          const float v0 = fmaf(acc[4 * j + 0], rstd0, nm0 * c2.x), v1 = fmaf(acc[4 * j + 1], rstd0, nm0 * c2.y);
          const float v2 = fmaf(acc[4 * j + 2], rstd1, nm1 * c2.x), v3 = fmaf(acc[4 * j + 3], rstd1, nm1 * c2.y);
          r[h][kv][2 * dh] = packbf(v0, v1);
          r[h][kv][2 * dh + 1] = packbf(v2, v3);
        }
      }
      if (sender) {
        stg128(halo + (2 * h) * 32, make_uint4(r[h][0][0], r[h][0][2], r[h][0][1], r[h][0][3]));
        stg128(halo + (2 * h + 1) * 32, make_uint4(r[h][1][0], r[h][1][1], r[h][1][2], r[h][1][3]));
      }
    }
#pragma unroll
    for (int j = 0; j < 8; j++) cs[j] = lds64f(sb + SM_CS + 4 * (8 * j + 2 * t));
    mbar_wait(bar + 8 * (B_DN + 7), layer);
#pragma unroll
    for (int h = 0; h < 4; h++) {
#pragma unroll
      for (int kv = 0; kv < 2; kv++) {
        const int chunk = 4 * h + 2 * kv + (lane >> 4);
        if (w < 3) stsm4(st_base + (((chunk & 8) | ((chunk ^ st_row) & 7)) << 4), r[h][kv][0], r[h][kv][1], r[h][kv][2], r[h][kv][3]);
      }
      kb[h][4] = r[h][0][0]; kb[h][5] = r[h][0][2]; kb[h][6] = r[h][0][1]; kb[h][7] = r[h][0][3];
      vb[h][4] = movm_t(r[h][1][0]); vb[h][5] = movm_t(r[h][1][1]); vb[h][6] = movm_t(r[h][1][2]); vb[h][7] = movm_t(r[h][1][3]);
    }
#pragma unroll
    for (int h = 0; h < 4; h++) {
#pragma unroll
      for (int dh = 0; dh < 2; dh++) {
        const int j = 2 * h + dh;
        const float2 c2 = cs[j];
        qa[h][2 * dh] = packbf(fmaf(-mean0, c2.x, acc[4 * j + 0]), fmaf(-mean0, c2.y, acc[4 * j + 1]));
        qa[h][2 * dh + 1] = packbf(fmaf(-mean1, c2.x, acc[4 * j + 2]), fmaf(-mean1, c2.y, acc[4 * j + 3]));
      }
    }
  }
  bar_sync(2 + wg, 128);
  TSW(2);
  {
    const uint32_t prev_base = kvx + (16 * w - 16) * 256;
    const int mi = lane >> 3;
    const int r = 8 * (mi >> 1) + (lane & 7), r2 = 8 * (mi & 1) + (lane & 7);
    if (w != 0) {
#pragma unroll
      for (int h = 0; h < 4; h++) {
        const int ch = 4 * h + (mi & 1), ch2 = 4 * h + 2 + (mi >> 1);
        ldsm4(&kb[h][0], prev_base + r * 256 + (((ch & 8) | ((ch ^ r) & 7)) << 4));
        ldsm4t(&vb[h][0], prev_base + r2 * 256 + (((ch2 & 8) | ((ch2 ^ r2) & 7)) << 4));
      }
    } else if (blk > 0) {
      uint4* src = &g_halo[((blk - 1) * 8 + hg) * 256 + lane];
      uint4 hv[8];
      int it = 0;
      bool ok;
      do {
        ok = true;
#pragma unroll
        for (int i = 0; i < 8; i++) hv[i] = ld_tagged(src + i * 32);
#pragma unroll
        for (int i = 0; i < 8; i++) ok = ok && hv[i].x != UNSET;
      } while (!__all_sync(~0u, ok) && ++it < (1 << 20));
      if (layer == 0) {
#pragma unroll
        for (int i = 0; i < 2; i++) stg128(src + i * 128 + (lane >> 1) * 6, make_uint4(UNSET, UNSET, UNSET, UNSET));
      }
#pragma unroll
      for (int h = 0; h < 4; h++) {
        kb[h][0] = hv[2 * h].x; kb[h][1] = hv[2 * h].y; kb[h][2] = hv[2 * h].z; kb[h][3] = hv[2 * h].w;
        vb[h][0] = movm_t(hv[2 * h + 1].x); vb[h][1] = movm_t(hv[2 * h + 1].y);
        vb[h][2] = movm_t(hv[2 * h + 1].z); vb[h][3] = movm_t(hv[2 * h + 1].w);
      }
    } else {
#pragma unroll
      for (int h = 0; h < 4; h++)
#pragma unroll
        for (int k = 0; k < 4; k++) kb[h][k] = vb[h][k] = 0u;
    }
    TSW(3);
  }
  mbar_wait(bar + 8 * (B_DN + 15), layer);
  TSW(4);

  const bool first = (blk == 0 && w == 0);
  const int e = t - (g >> 1);
  const bool par = g & 1, epos = e >= 1;
  const uint32_t pmask = par ? 0xffff0000u : 0x0000ffffu;
  const uint32_t mB0 = epos ? pmask : 0u, mB1 = epos ? 0u : pmask;
  const float cl2 = 0.25f * 1.4426950408889634f;
  const float sc0 = rstd0 * cl2, sc1 = rstd1 * cl2;
  const float NEG = -INFINITY;
  float vA0[4], vB0[4], vA1[4], vB1[4];
#pragma unroll
  for (int h = 0; h < 4; h++) {
    float S[4][4];
#pragma unroll
    for (int j = 0; j < 4; j++) {
      S[j][0] = S[j][1] = S[j][2] = S[j][3] = 0.f;
      mma_bf16(S[j], qa[h], kb[h][2 * j], kb[h][2 * j + 1]);
    }
    vA0[h] = par ? S[1][1] : S[1][0];
    vB0[h] = epos ? (par ? S[0][1] : S[0][0]) : (par ? S[2][1] : S[2][0]);
    vA1[h] = par ? S[2][3] : S[2][2];
    vB1[h] = epos ? (par ? S[1][3] : S[1][2]) : (par ? S[3][3] : S[3][2]);
    if (first) { vA0[h] = NEG; if (epos) { vB0[h] = NEG; vB1[h] = NEG; } }
  }
  float m0[4], m1[4];
#pragma unroll
  for (int h = 0; h < 4; h++) { m0[h] = fmaxf(vA0[h], vB0[h]); m1[h] = fmaxf(vA1[h], vB1[h]); }
#pragma unroll
  for (int o = 1; o <= 2; o <<= 1) {
#pragma unroll
    for (int h = 0; h < 4; h++) {
      m0[h] = fmaxf(m0[h], __shfl_xor_sync(~0u, m0[h], o));
      m1[h] = fmaxf(m1[h], __shfl_xor_sync(~0u, m1[h], o));
    }
  }
  float O0[4][4], O1[4][4], Z[4][4];
#pragma unroll
  for (int h = 0; h < 4; h++) {
    const float mm0 = -m0[h] * sc0, mm1 = -m1[h] * sc1;
    const float pA0 = ex2(fmaf(vA0[h], sc0, mm0)), pB0 = ex2(fmaf(vB0[h], sc0, mm0));
    const float pA1 = ex2(fmaf(vA1[h], sc1, mm1)), pB1 = ex2(fmaf(vB1[h], sc1, mm1));
    const uint32_t hA0 = packbf(pA0, pA0), hB0 = packbf(pB0, pB0), hA1 = packbf(pA1, pA1), hB1 = packbf(pB1, pB1);
    const uint32_t P0[4] = {hB0 & mB0, 0u, hA0 & pmask, hB1 & mB0};
    const uint32_t P1[4] = {hB0 & mB1, hA1 & pmask, 0u, hB1 & mB1};
#pragma unroll
    for (int k = 0; k < 4; k++) O0[h][k] = O1[h][k] = Z[h][k] = 0.f;
    mma_bf16(O0[h], P0, vb[h][0], vb[h][1]); mma_bf16(O1[h], P0, vb[h][2], vb[h][3]); mma_bf16(Z[h], P0, 0x3f803f80u, 0x3f803f80u);
    mma_bf16(O0[h], P1, vb[h][4], vb[h][5]); mma_bf16(O1[h], P1, vb[h][6], vb[h][7]); mma_bf16(Z[h], P1, 0x3f803f80u, 0x3f803f80u);
  }
  if (lane == 0) mbar_arrive(bar + 8 * (B_OST + wg));
  uint4* op = (uint4*)g_O + ((layer * 32 + blk) * 8 + hg) * 512 + 64 * t + 16 * w + g;
#pragma unroll
  for (int h = 0; h < 4; h += 2) {
    const float i0 = rcp_approx(Z[h][0]), i1 = rcp_approx(Z[h][2]), j0 = rcp_approx(Z[h + 1][0]), j1 = rcp_approx(Z[h + 1][2]);
    stg128(op + 128 * h, make_uint4(packbf(O0[h][0] * i0, O0[h][1] * i0), packbf(O1[h][0] * i0, O1[h][1] * i0),
                                   packbf(O0[h + 1][0] * j0, O0[h + 1][1] * j0), packbf(O1[h + 1][0] * j0, O1[h + 1][1] * j0)));
    stg128(op + 128 * h + 8, make_uint4(packbf(O0[h][2] * i1, O0[h][3] * i1), packbf(O1[h][2] * i1, O1[h][3] * i1),
                                            packbf(O0[h + 1][2] * j1, O0[h + 1][3] * j1), packbf(O1[h + 1][2] * j1, O1[h + 1][3] * j1)));
  }
  TSW(5);
  __syncwarp();
  if (lane == 0) red_relaxed(&g_cnt[(C_O + layer * 32 + blk) * 32]);
  TSW(6);
}

__device__ __forceinline__ void conv_load(uint32_t* A, uint32_t pe);
__device__ __forceinline__ void proj_phase(const Params& p, uint32_t sb, int layer, int rb, int q, uint32_t* A0, uint32_t* A1) {
  const int lane = opaque_tid() & 31;
  const int wg = __shfl_sync(~0u, opaque_tid() >> 7, 0), w = __shfl_sync(~0u, (opaque_tid() >> 5) & 3, 0);
  const bool TR = layer != 0;
  const int t = lane & 3;
  const uint32_t bar = sb + SM_BAR;
  const uint32_t rbx = sb + (P_R + wg) * PG;
  const uint32_t rsrc = sb + (wg ? 2 : P_R) * PG;
  const int blk = 16 * wg + rb;
  mbar_wait(bar + 8 * (B_RF + wg), layer);
  mbar_wait(bar + 8 * B_WOF, layer);
  const uint32_t stg = sb + (wg ? SM_KGT : SM_STG);
  if (layer) {
    const uint32_t pe = sb + cv_pe(wg, 1) + 4 * (16 + 16 * w + (lane >> 2) - 2 * t);
    mbar_wait(bar + 8 * B_PE, 1);
    conv_load(A0, pe);
    conv_load(A1, pe + 2 * 4480);
    __syncwarp();
    if (lane == 0) mbar_arrive(bar + 8 * B_AL);
  } else {
#pragma unroll
    for (int i = 0; i < 68; i++) {
      asm volatile("mov.b32 %0, 0;" : "=r"(A0[i]));
      asm volatile("mov.b32 %0, 0;" : "=r"(A1[i]));
    }
  }
  bool clean = false, staged = false;
#pragma unroll 1
  for (int attempt = 0; attempt < MAX_RETRY; attempt++) {
  uint32_t res[16];
  if (!TR) {
#pragma unroll
    for (int j = 0; j < 8; j += 2) {
      const int mi = lane >> 3;
      const int row = 16 * w + (lane & 7) + 8 * (mi & 1), ch = j + (mi >> 1);
      ldsm4(&res[2 * j], rsrc + row * 128 + ((ch ^ (row & 7)) << 4));
    }
  } else {
#pragma unroll
    for (int j = 0; j < 8; j += 2) {
      const int mi = lane >> 3;
      const int line = 8 * (j + (mi >> 1)) + (lane & 7), pc = 2 * w + (mi & 1);
      ldsm4t(&res[2 * j], rsrc + line * 128 + ((pc ^ (line & 7)) << 4));
    }
  }
  float acc[32];
#pragma unroll
  for (int j = 0; j < 16; j++) { acc[2 * j] = bf_lo(res[j]); acc[2 * j + 1] = bf_hi(res[j]); }
  acc_fence<32>(acc);
  if (wg) mbar_wait(bar + 8 * B_PG, layer);
  const int wg2 = __shfl_sync(~0u, opaque_tid() >> 7, 0);
  const uint64_t da0 = mkdesc(sb, 1024, 128, 0), db0 = mkdesc(sb, 8192, 1024, 1);
#pragma unroll
  for (int c = 0; c < 4; c++) {
    mbar_wait(bar + 8 * (B_OF + 4 * wg + c), layer);
    if (c == 0) TSW(7);
    const uint64_t da = da0 + (uint32_t)(o_page(wg2, c) * 512);
#pragma unroll
    for (int ks = 0; ks < 8; ks++) {
      if (ks % 4 == 0) { if (ks) wg_commit(); if (wg2) wg_wait<0>(); wg_fence(); }
      wgmma_ss<64, 0, 1>(acc, da + ks * 128, db0 + wo_page(2 * c + (ks >> 2)) * 512 + (ks & 3) * 128, 1);
    }
    wg_commit();
  }
  if (wg) mbar_wait(bar + 8 * B_KG, 0);
  wg_wait<0>();
  acc_fence<32>(acc);
  TSW(8);
  if (!clean) {
    const float chk = acc[0] + acc[2];
    clean = __all_sync(~0u, chk == chk);
    if (clean && lane == 0) mbar_arrive(bar + 8 * (B_PDONE + wg));
  }
  float s0 = 0.f, q0 = 0.f, s1 = 0.f, q1 = 0.f;
  uint32_t o[16];
#pragma unroll
  for (int j = 0; j < 8; j++) {
    const float a = acc[4 * j], b = acc[4 * j + 1], c = acc[4 * j + 2], d = acc[4 * j + 3];
    o[2 * j] = packbf(a, b);
    o[2 * j + 1] = packbf(c, d);
    s0 += a + b; q0 = fmaf(a, a, q0); q0 = fmaf(b, b, q0);
    s1 += c + d; q1 = fmaf(c, c, q1); q1 = fmaf(d, d, q1);
  }
#pragma unroll
  for (int j = 0; j < 8; j += 2) {
    const int mi = lane >> 3;
    const int line = 8 * (j + (mi >> 1)) + (lane & 7), pc = 2 * w + (mi & 1);
    stsm4t(rbx + line * 128 + ((pc ^ (line & 7)) << 4), o[2 * j], o[2 * j + 1], o[2 * j + 2], o[2 * j + 3]);
  }
#pragma unroll
  for (int o2 = 1; o2 <= 2; o2 <<= 1) {
    s0 += __shfl_xor_sync(~0u, s0, o2); q0 += __shfl_xor_sync(~0u, q0, o2);
    s1 += __shfl_xor_sync(~0u, s1, o2); q1 += __shfl_xor_sync(~0u, q1, o2);
  }
  {
    const int i = 2 * (lane >> 2) + (t & 1), k = (i * 11) >> 5;
    const float v = (t == 0) ? s0 : (t == 1) ? q0 : (t == 2) ? s1 : q1;
    sts32f(stg + k * 128 + (2 * w + (t >> 1)) * 16 + (i - 3 * k) * 4, v);
  }
  TSW(9);
  fence_async_smem();
  if (attempt == 0 && clean) {
    staged = true;
    __syncwarp();
    if (lane == 0) mbar_arrive(bar + 8 * (B_STG + wg));
  }
  if (!bar_or(2 + wg, 128, !clean)) break;
  const int rtp = mbar_test(bar + 8 * (B_RT + wg), 0);
  bool unset = false;
#pragma unroll
  for (int i = 0; i < 4; i++) unset |= lds32(sb + o_page(wg, i) * PG + (32 * w + lane) * 128) == UNSET;
  if (!bar_or(2 + wg, 128, unset)) break;
  if (w == 0 && elect_one()) {
    fence_async_smem();
    mbar_expect(bar + 8 * (B_RT + wg), 9 * PG);
    if (layer == 0) tma_ld(rsrc, &p.mapX, q * 64, blk * 64, bar + 8 * (B_RT + wg));
    else tma_ld(rsrc, &p.mapXT, blk * 64, DM + q * 64, bar + 8 * (B_RT + wg));
#pragma unroll 1
    for (int c = 0; c < 4; c++) bulk_ld(sb + o_page(wg, c) * PG, g_O + ((layer * 32 + blk) * 4 + c) * PG, 2 * PG, bar + 8 * (B_RT + wg));
  }
  mbar_wait(bar + 8 * (B_RT + wg), rtp);
  RETRY(0);
  }
  if (!clean && lane == 0) mbar_arrive(bar + 8 * (B_PDONE + wg));
  if (!staged && lane == 0) mbar_arrive(bar + 8 * (B_STG + wg));
  TSW(10);
}

__device__ __forceinline__ void conv_load(uint32_t* A, uint32_t pe) {
#pragma unroll
  for (int m = 0; m < 17; m++) {
    A[4 * m + 2] = lds32(pe + 4 * (64 * m - 8));
    A[4 * m + 0] = lds32(pe + 4 * (64 * m));
    A[4 * m + 1] = lds32(pe + 4 * (64 * m + 8));
    asm volatile("mov.b32 %0, %1;" : "=r"(A[4 * m + 3]) : "r"(A[4 * m + 0]));
  }
}
template <int M> __device__ __forceinline__ void conv_tri(float* acc, const uint32_t* A, uint64_t d) {
  if constexpr (M < 16) {
    wgmma_rs<64 - 8 * (M / 2), 0>(acc, A + 4 * M, d + (uint64_t)(64 + 4 * M), M != 0);
    conv_tri<M + 1>(acc, A, d);
  }
}
__device__ __forceinline__ void conv_mma0(float* acc, const uint32_t* A, uint64_t d) {
  wg_fence();
  conv_tri<0>(acc, A, d);
  wg_commit();
}
__device__ __forceinline__ void conv_mma1(float* acc, const uint32_t* A, uint64_t d, uint64_t ds, uint64_t df) {
  wg_fence();
#pragma unroll
  for (int m = 0; m < 17; m++) wgmma_rs<64, 0>(acc, A + 4 * m, d + (uint64_t)(4 * m), m != 0);
  wgmma_ss<64, 1, 0>(acc, ds, df, 1);
  wgmma_ss<64, 1, 0>(acc, ds + 128, df + 128, 1);
  wg_commit();
}
__device__ __forceinline__ void conv_store(float* acc, uint32_t pb, uint32_t over, int w) {
  acc_fence<32>(acc);
  const int l = opaque_tid() & 31, mt = l >> 3;
  int c = 2 * (63 - 8 * (mt >> 1) - (l & 7) + w) + (mt & 1);
  c ^= (c >> 3) & 1;
  const uint32_t a0 = pb + c * 16;
#pragma unroll
  for (int j = 0; j < 8; j += 2)
    stsm4t(j == 0 ? (c < 128 ? a0 : over + (c - 128) * 16) : a0 - 256 * j, packbf(acc[4 * j], acc[4 * j + 1]), packbf(acc[4 * j + 2], acc[4 * j + 3]),
           packbf(acc[4 * j + 4], acc[4 * j + 5]), packbf(acc[4 * j + 6], acc[4 * j + 7]));
}
__device__ __forceinline__ void conv_sums(uint32_t sb, int lc, int ht) {
  const int m = ht - 1;
  uint4 v[2][3];
#pragma unroll
  for (int c = 0; c < 2; c++)
#pragma unroll
    for (int k = 0; k < 3; k++) {
      const int mm = m - 1 + k;
      v[c][k] = lds128(sb + cv_u(lc + c) + (mm >= 0 ? (mm & 1) * CV_UH + (127 - (mm >> 1)) * 16 : 128 * 16));
    }
  const int ce = m + 2, co = m + 1;
#pragma unroll
  for (int c = 0; c < 2; c++) {
    const uint32_t x[8] = {v[c][0].z, v[c][0].w, v[c][1].x, v[c][1].y, v[c][1].z, v[c][1].w, v[c][2].x, v[c][2].y};
    float pv[16];
#pragma unroll
    for (int k = 0; k < 8; k++) { pv[2 * k] = bf_lo(x[k]); pv[2 * k + 1] = bf_hi(x[k]); }
    float t2[15], t4[13], s9[8], s7[8];
#pragma unroll
    for (int i = 0; i < 15; i++) t2[i] = pv[i] + pv[i + 1];
#pragma unroll
    for (int i = 0; i < 13; i++) t4[i] = t2[i] + t2[i + 2];
#pragma unroll
    for (int i = 0; i < 8; i++) {
      s9[i] = (t4[i] + t4[i + 4]) + pv[i + 8];
      s7[i] = (t4[i + 1] + t2[i + 5]) + pv[i + 7];
    }
    const uint4 e4 = make_uint4(packbf(s9[0], s9[1]), packbf(s9[2], s9[3]), packbf(s9[4], s9[5]), packbf(s9[6], s9[7]));
    if (ce < 128) sts128(sb + cv_se(lc + c) + ((ce ^ ((ce >> 3) & 7)) << 4), e4);
    else sts128(sb + cv_se(lc + c), make_uint4(0, 0, 0, 0));
    sts128(sb + cv_so(lc + c) + ((co ^ ((co >> 3) & 7)) << 4),
           make_uint4(packbf(s7[0], s7[1]), packbf(s7[2], s7[3]), packbf(s7[4], s7[5]), packbf(s7[6], s7[7])));
  }
}

template <int HALF, int NCH, int STEP = 1>
__device__ __forceinline__ void conv_epi(uint32_t sb, bf16* out, int lc, int c) {
  uint4 v[NCH][4], xr[NCH];
  const uint32_t sw = (c ^ ((c >> 3) & 1)) * 16;
#pragma unroll
  for (int u = 0; u < NCH; u++) {
#pragma unroll
    for (int k = 0; k < 4; k++) v[u][k] = lds128(sb + (HALF ? cv_pb1(lc + STEP * u, k) : cv_pb0(lc + STEP * u, k)) + sw);
    xr[u] = lds128(sb + cv_x(HALF, lc + STEP * u) + c * 16);
  }
#pragma unroll
  for (int u = 0; u < NCH; u++) {
    uint4 o;
    o.x = hadd2(xr[u].x, hadd2(hadd2(v[u][0].x, v[u][1].x), hadd2(v[u][2].x, v[u][3].x)));
    o.y = hadd2(xr[u].y, hadd2(hadd2(v[u][0].y, v[u][1].y), hadd2(v[u][2].y, v[u][3].y)));
    o.z = hadd2(xr[u].z, hadd2(hadd2(v[u][0].z, v[u][1].z), hadd2(v[u][2].z, v[u][3].z)));
    o.w = hadd2(xr[u].w, hadd2(hadd2(v[u][0].w, v[u][1].w), hadd2(v[u][2].w, v[u][3].w)));
    stg128(out + cv_chan(0, lc + STEP * u) * LSEQ + HALF * 1024 + c * 8, o);
  }
}

__device__ __forceinline__ bool prep_valid(const uint4 (&st)[6], const uint4 (&xr)[4]) {
  const uint32_t n = __float_as_uint(8.f);
  return st[0].w == n && st[1].w == n && st[2].w == n && st[3].w == n && st[4].w == n && (st[5].w | st[5].y | st[5].z) == n &&
         xr[0].x != UNSET && xr[1].x != UNSET && xr[2].x != UNSET && xr[3].x != UNSET;
}
template <int HALF>
__device__ __forceinline__ void conv_prep(uint32_t sb, int layer, int cta, int i) {
  uint4 st[6], xr[4];
  const uint4* sp = (const uint4*)g_stats + (layer * 32 + HALF * 16 + (i >> 3)) * 48 + (i & 7);
  const uint4* xp = (const uint4*)g_xT + (2 * layer * DM + 2 * cta) * (LSEQ / 8) + HALF * 128 + i;
  auto fetch = [&]() {
#pragma unroll
    for (int k = 0; k < 6; k++) st[k] = ld_tagged(sp + 8 * k);
#pragma unroll
    for (int k = 0; k < 4; k++) xr[k] = ld_tagged(xp + cv_chan(0, k) * (LSEQ / 8));
  };
  if (HALF) {
#pragma unroll
    for (int k = 0; k < 6; k++) st[k] = lds128(sb + CV_ST + (i >> 3) * 768 + k * 128 + (i & 7) * 16);
#pragma unroll
    for (int k = 0; k < 4; k++) xr[k] = lds128(sb + cv_x(1, k) + i * 16);
  } else {
    fetch();
  }
  int it = 0;
  while (!__all_sync(~0u, prep_valid(st, xr)) && ++it < MAX_RETRY) { fetch(); RETRY(1); }
  if (!HALF || it) {
#pragma unroll
    for (int k = 0; k < 4; k++) sts128(sb + cv_x(HALF, k) + i * 16, xr[k]);
  }
  const uint32_t v[16] = {st[0].x, st[0].y, st[0].z, st[1].x, st[1].y, st[1].z, st[2].x, st[2].y, st[2].z, st[3].x, st[3].y, st[3].z, st[4].x, st[4].y, st[4].z, st[5].x};
  uint32_t rs[4], nm[4];
#pragma unroll
  for (int k = 0; k < 4; k++) {
    const float m0 = __uint_as_float(v[4 * k]) * (-1.f / DM), m1 = __uint_as_float(v[4 * k + 2]) * (-1.f / DM);
    const float r0 = rsqrt_approx(fmaxf(fmaf(__uint_as_float(v[4 * k + 1]), 1.f / DM, -m0 * m0), 0.f) + 1e-5f);
    const float r1 = rsqrt_approx(fmaxf(fmaf(__uint_as_float(v[4 * k + 3]), 1.f / DM, -m1 * m1), 0.f) + 1e-5f);
    rs[k] = packbf(r0, r1);
    nm[k] = packbf(m0 * bf_lo(rs[k]), m1 * bf_hi(rs[k]));
  }
  const uint32_t ud = sb + (i & 1) * CV_UH + (127 - 64 * HALF - (i >> 1)) * 16;
#pragma unroll
  for (int k = 0; k < 4; k++)
    sts128(ud + cv_u(k), make_uint4(hfma2(xr[k].x, rs[0], nm[0]), hfma2(xr[k].y, rs[1], nm[1]), hfma2(xr[k].z, rs[2], nm[2]), hfma2(xr[k].w, rs[3], nm[3])));
  fence_async_smem();
}

__device__ __forceinline__ void conv_phase(const Params& p, uint32_t sb, int layer, int cta, uint32_t* A0, uint32_t* A1) {
  const int tid = opaque_tid();
  const int wg = __shfl_sync(~0u, tid >> 7, 0), w = __shfl_sync(~0u, (tid >> 5) & 3, 0);
  const uint32_t bar = sb + SM_BAR;
  constexpr int CH2 = 4 * PG;
  bf16* xout = g_xT + ((2 * layer + 1) * DM + 2 * cta) * LSEQ;
  float acc[32];
  const uint32_t pe = sb + cv_pe(wg, 0) + 4 * (16 + 16 * w + ((tid & 31) >> 2) - 2 * (tid & 3));
  if (layer == 0) {
    mbar_wait(bar + 8 * (B_PDONE + 1), layer);
    mbar_wait(bar + 8 * B_PE, layer);
    conv_load(A0, pe);
    conv_load(A1, pe + CH2);
  }
  TSW(19);
  const uint64_t d0 = mkdesc(sb + cv_u(wg), CV_UH, 128, 0), d1 = d0 + (CH2 >> 4);
  mbar_wait(bar + 8 * B_U, layer);
  TSW(12);
  if (wg == 1) bar_sync(5, 256);
  conv_mma0(acc, A0, d0);
  if (wg == 0) bar_arrive(5, 256);
  mbar_wait(bar + 8 * (B_PDONE + 1), layer);
  {
    const int l = opaque_tid() & 31;
    if ((l & 15) < 2 * w) sts128(sb + cv_pb0(wg + 2 * (l >> 4), w) + (l & 15) * 16, make_uint4(0, 0, 0, 0));
  }
  wg_wait<0>();
  conv_store(acc, sb + cv_pb0(wg, w), sb + cv_pb1(wg, w), w);
  conv_mma0(acc, A1, d1);
  wg_wait<0>();
  conv_store(acc, sb + cv_pb0(2 + wg, w), sb + cv_pb1(2 + wg, w), w);
  TSW(13);
  bar_sync(2 + wg, 128);
  conv_epi<0, 2, 2>(sb, xout, wg, opaque_tid() & 127);
  TSW(14);
  mbar_arrive(bar + 8 * B_PUB);
  const uint64_t ds = mkdesc(sb + cv_se(wg), 8192, 1024, 1), df = mkdesc(sb + cv_fa(wg), 512, 128, 0);
  if (wg == 0) mbar_wait(bar + 8 * B_U1, layer);
  else bar_sync(6, 256);
  TSW(15);
  conv_mma1(acc, A0, d0, ds, df);
  if (wg == 0) bar_arrive(6, 256);
  wg_wait<0>();
  conv_store(acc, sb + cv_pb1(wg, w), sb + cv_dump(wg), w);
  TSW(16);
  bar_sync(2 + wg, 128);
  conv_epi<1, 1>(sb, xout, wg, opaque_tid() & 127);
  mbar_arrive(bar + 8 * (B_PUB + 1));
  conv_mma1(acc, A1, d1, ds + 512, df + (CH2 >> 4));
  wg_wait<0>();
  conv_store(acc, sb + cv_pb1(2 + wg, w), sb + cv_dump(2 + wg), w);
  TSW(17);
  bar_sync(2 + wg, 128);
  conv_epi<1, 1>(sb, xout, 2 + wg, opaque_tid() & 127);
  mbar_arrive(bar + 8 * (B_PUB + 2));
  TSW(18);
}

__device__ __forceinline__ void final_tile(const Params& p, uint32_t buf, int ch0, int pos0, int barid) {
  const int tid = opaque_tid() & 127, lane = tid & 31, w = tid >> 5;
  const uint4* src = (const uint4*)(g_xT + (3 * DM + ch0 + (tid >> 3)) * LSEQ + pos0) + (tid & 7);
  const int ch = tid >> 3, row = 4 * (ch & 6) + 2 * (ch >> 3) + (ch & 1);
  const uint32_t dst = buf + row * 128;
  const uint32_t ld = buf + lane * 128;
  bf16* out = p.out + (pos0 + 16 * w + (lane >> 2)) * DM + ch0 + 8 * (lane & 3);
  uint4 a, b;
  int it = 0;
  do {
    if (it) RETRY(2);
    a = ld_tagged(src); b = ld_tagged(src + 16 * LSEQ / 8);
  } while (!__all_sync(~0u, a.x != UNSET && b.x != UNSET) && ++it < (1 << 20));
  sts128(dst + (((tid ^ row) & 7) << 4), a);
  sts128(dst + 512 + (((tid ^ row ^ 4) & 7) << 4), b);
  bar_sync(barid, 128);
#pragma unroll
  for (int h = 0; h < 2; h++) {
    uint32_t r[4];
    ldsm4t(r, ld + ((((2 * w + h) ^ lane) & 7) << 4));
    *(uint4*)(out + 8 * h * DM) = make_uint4(r[0], r[1], r[2], r[3]);
  }
}

struct cplx { float r, i; };
__device__ __forceinline__ cplx cmul(cplx a, cplx b) { return {fmaf(a.r, b.r, -a.i * b.i), fmaf(a.r, b.i, a.i * b.r)}; }
__device__ __forceinline__ cplx csqr(cplx a) { return {fmaf(a.r, a.r, -a.i * a.i), (a.r + a.r) * a.i}; }
__device__ __forceinline__ cplx cexp_l(float ar2, float ai, float l) {
  const float m = ex2(ar2 * l);
  const float x = ai * l;
  return {m * __cosf(x), m * __sinf(x)};
}

__device__ __forceinline__ void colsum_cta(const Params& p, uint32_t sb, int j, int tid) {
  const uint32_t bar = sb + SM_BAR;
  auto ld = [&](int i) {
    mbar_expect(bar + 8 * i, 3 * PG);
    tma_ld3(sb + (i & 7) * 3 * PG, &p.mapW3, (2 * j + (i & 1)) * 64, (i >> 1) * 64, 0, bar + 8 * i);
  };
  if (tid == 384) {
#pragma unroll
    for (int i = 0; i < 24; i++) mbar_init(bar + 8 * i, i < 16 ? 1 : 12);
    asm volatile("fence.mbarrier_init.release.cluster;" ::: "memory");
    fence_async_smem();
#pragma unroll 1
    for (int i = 0; i < 8; i++) ld(i);
  }
  const unsigned ep = ld_relaxed(&g_cnt[C_CS * 32]);
  bar_sync(0, NTHREADS);
  if (tid == 384) {
#pragma unroll 1
    for (int i = 8; i < 16; i++) { mbar_wait(bar + 8 * (8 + i), 0); fence_async_smem(); ld(i); }
  }
  if (tid < 384) {
    const int lane = tid & 31, cc = tid & 7, r0 = (tid >> 3) & 15, part = tid >> 7;
    const uint32_t id = ((lane >> 2) == 2 * (lane & 3) ? 0x3f80u : 0u) | ((lane >> 2) == 2 * (lane & 3) + 1 ? 0x3f800000u : 0u);
    const uint32_t src = sb + part * PG + r0 * 128 + ((cc ^ (r0 & 7)) << 4);
    float s[2][2][4];
#pragma unroll
    for (int i = 0; i < 16; i++) s[i >> 3][(i >> 2) & 1][i & 3] = 0.f;
#pragma unroll 1
    for (int i2 = 0; i2 < 16; i2 += 2) {
#pragma unroll
      for (int h = 0; h < 2; h++) {
        const int i = i2 + h;
        mbar_wait(bar + 8 * i, 0);
        uint4 v[4];
#pragma unroll
        for (int k = 0; k < 4; k++) v[k] = lds128(src + (i & 7) * 3 * PG + k * 2048);
#pragma unroll
        for (int k = 0; k < 4; k++) {
          const uint32_t a[4] = {v[k].x, v[k].y, v[k].z, v[k].w};
          mma_bf16(s[h][0], a, id, 0u);
          mma_bf16(s[h][1], a, 0u, id);
        }
        __syncwarp();
        if (i < 8 && lane == 0) mbar_arrive(bar + 8 * (16 + i));
      }
    }
    const uint32_t red = sb + 24 * PG;
#pragma unroll
    for (int h = 0; h < 2; h++)
#pragma unroll
      for (int k = 0; k < 2; k++) sts128f(red + (r0 * 384 + h * 192 + part * 64 + cc * 8 + k * 4) * 4, s[h][k][0], s[h][k][1], s[h][k][2], s[h][k][3]);
    bar_sync(1, 384);
    float tot = 0.f;
#pragma unroll
    for (int k = 0; k < 16; k++) tot += __uint_as_float(lds32(red + (k * 384 + tid) * 4));
    asm volatile("st.relaxed.gpu.global.v2.u32 [%0], {%1,%2};" ::"l"(&g_colsum[j * 384 + tid]), "r"(__float_as_uint(tot)), "r"(ep / NCTA + 1) : "memory");
    const uint4 u = make_uint4(UNSET, UNSET, UNSET, UNSET);
    if (tid < 256) {
#pragma unroll 1
      for (int s = 0; s < 4; s++) {
        const int n = (s == 1 || s == 2) ? 32 : 16;
        uint4* buf = s == 1 ? (uint4*)g_O + 131072 : (uint4*)g_xT + (s + !s) * 131072;
#pragma unroll 4
        for (int i = 0; i < n; i++) stg128(buf + (j * n + i) * 1024 + (tid >> 1) * 8 + (tid & 1), u);
        if (n == 16) {
#pragma unroll 4
          for (int i = 0; i < 8; i++) stg128(buf + (256 + j * 64 + i * 8 + (tid >> 5)) * 256 + (s ? 0 : 128) + ((tid & 31) >> 1) * 8 + (tid & 1), u);
        }
        if (s == 3) {
#pragma unroll 4
          for (int i = 0; i < 32; i++) stg128(buf + (256 + j * 64 + 2 * i + (tid >> 7)) * 256 + 128 + (tid & 127), u);
        }
        bar_sync(2, 256);
        if (tid == 32 * s) red_release(&g_cnt[(C_R + s) * 32]);
      }
    }
  }
}

constexpr int KB = 4, KW = 2;
struct ModeIn { uint32_t ar, ai, br, bi, cr, ci; bf16 logdt; };
__device__ __forceinline__ ModeIn load_modes(const Params& p, int d, int m) {
  const int i = d * 64 + m;
  return {((const uint32_t*)p.a_re)[i], ((const uint32_t*)p.a_im)[i], ((const uint32_t*)p.b_re)[i], ((const uint32_t*)p.b_im)[i],
          ((const uint32_t*)p.c_re)[i], ((const uint32_t*)p.c_im)[i], p.log_dt[d]};
}
__device__ __forceinline__ void kernel_gen(uint32_t sb, int cta, int ht, ModeIn in, const ModeIn& in1) {
  const uint32_t bst = sb + SM_KGB + ((ht & 63) >> 2) * 144 + (ht & 3) * 4 + (ht >> 6) * 16;
  const uint64_t db = mkdesc(sb + SM_KGB, 144, 2304, 0);
  const float e0 = (float)(8 * (((ht & 32) >> 1) + ((ht & 31) >> 2)));
  float T[20];
#pragma unroll
  for (int i = 0; i < 20; i++) T[i] = 0.f;
  float k0 = 0.f;
#pragma unroll 1
  for (int pass = 0; pass < 4; pass++) {
    {
      const int sh = (pass & 1) ? 0 : 16;
      auto val = [&](uint32_t v) { return __uint_as_float((v << sh) & 0xffff0000u); };
      const float dt = __bfloat162float(__float2bfloat16_rn(expf(__bfloat162float(in.logdt))));
      const float ar2 = dt * val(in.ar) * 1.4426950408889634f, ai = dt * val(in.ai);
      const cplx c = cmul({val(in.cr), -val(in.ci)}, {dt * val(in.br), -dt * val(in.bi)});
      k0 += c.r;
      const cplx z1 = cexp_l(ar2, -ai, 1.f), z256 = cexp_l(ar2, -ai, 256.f), z64 = cexp_l(ar2, ai, 64.f);
      const cplx z2 = csqr(z1), z512 = csqr(z256);
      auto put = [&](int j, cplx v) { sts32(bst + (j >> 2) * 2304 + (j & 3) * 32, packbf(v.r, v.i)); };
      sts128f(sb + SM_KGT + ht * 16, ar2, ai, z64.r, z64.i);
      const cplx c1 = cmul(c, z1), c2 = cmul(c, z2), c3 = cmul(c1, z2), c4 = cmul(c2, z2);
      const cplx c5 = cmul(c3, z2), c6 = cmul(c4, z2), c7 = cmul(c5, z2), c8 = cmul(c6, z2);
      put(0, c1); put(1, c2); put(2, c3); put(3, c4); put(4, c5); put(5, c6); put(6, c7); put(7, c8);
      const cplx c260 = cmul(c4, z256), c264 = cmul(c8, z256), c520 = cmul(c8, z512), c776 = cmul(c264, z512);
      put(8, cmul(c2, z256)); put(9, c260); put(10, cmul(c6, z256)); put(11, c264);
      put(12, cmul(c4, z512)); put(13, c520); put(14, cmul(c260, z512)); put(15, c776);
      const cplx c1032 = cmul(c520, z512), c1288 = cmul(c776, z512);
      put(16, c1032); put(17, c1288); put(18, cmul(c1032, z512)); put(19, cmul(c1288, z512));
    }
    fence_async_smem();
    bar_sync(4, 128);
    const uint32_t tb = sb + SM_KGT + (ht & 67) * 16;
    float2 nx[KB];
#pragma unroll
    for (int s = 0; s < KB; s++) nx[s] = lds64f(tb + s * 64);
#pragma unroll
    for (int q = 0; q < 16 / KB; q++) {
      uint32_t A[2 * KB];
      float2 cur[KB], z[KB];
#pragma unroll
      for (int s = 0; s < KB; s++) { cur[s] = nx[s]; z[s] = lds64f(tb + (KB * q + s) * 64 + 8); }
      if (q < 16 / KB - 1) {
#pragma unroll
        for (int s = 0; s < KB; s++) nx[s] = lds64f(tb + (KB * q + KB + s) * 64);
      }
      if (q >= KW) wg_wait<KW - 1>();
#pragma unroll
      for (int s = 0; s < KB; s++) {
        const cplx lo = cexp_l(cur[s].x, cur[s].y, e0), hi = cmul(lo, {z[s].x, z[s].y});
        A[2 * s] = packbf(lo.r, lo.i);
        A[2 * s + 1] = packbf(hi.r, hi.i);
      }
      wg_fence();
#pragma unroll
      for (int k = 0; k < KB / 2; k++) wgmma_rs<40, 0>(T, A + 4 * k, db + 9 * KB * q + 18 * k, (pass & 1) | q | k);
      wg_commit();
    }
    wg_wait<0>();
    acc_fence<20>(T);
    if (ht == 0) TS(4 + pass);
    if (pass & 1) {
      const int h2 = opaque_tid() - 256, w = h2 >> 5, lane = h2 & 31, t = lane & 3, chn = h2 >> 6, m = h2 & 63, i0 = 16 * (w & 1) + (lane >> 2);
      const int lc = (pass & 2) + chn;
      const uint32_t kc = sb + kc_off(lc);
      auto put = [&](int idx, float v) {
        sts16(kc + idx * 2, __bfloat16_as_ushort(__float2bfloat16_rn(v)));
      };
#pragma unroll
      for (int hi = 0; hi < 2; hi++) {
        const int i = i0 + 8 * hi;
        float v[5];
#pragma unroll
        for (int j = 0; j < 5; j++) v[j] = chn ? T[4 * j + 2 * hi + 1] : T[4 * j + 2 * hi];
        put(8 * i + 1 + t, v[0]);
        put(8 * i + 5 + t, v[1]);
        put(257 + 4 * i + t, v[2]);
        put(385 + 2 * i + (t & 1) + 64 * (t >> 1), v[3]);
        put(513 + i + 32 * t, v[4]);
      }
#pragma unroll
      for (int o = 16; o > 0; o >>= 1) k0 += __shfl_xor_sync(~0u, k0, o);
      if (lane == 0) sts32f(sb + SM_RED + 4 * w, k0);
      bar_sync(4, 128);
      if (m == 0) put(0, k0 + __uint_as_float(lds32(sb + SM_RED + 4 * w + 4)) + __uint_as_float(lds16(sb + SM_RED + 24 + 2 * lc) << 16));
      k0 = 0.f;
      in = in1;
    }
  }
}

__device__ __forceinline__ void expand_taps(uint32_t sb, int ht, int early) {
  const int ch = ht >> 5, lane = ht & 31;
  const uint32_t kc = sb + kc_off(ch);
  const uint32_t dst0 = sb + cv_pe(ch, early);
  auto put = [&](int G, uint32_t v0, uint32_t v1, uint32_t v2, uint32_t v3, uint32_t v4, uint32_t v5, uint32_t v6, uint32_t v7, uint32_t v8) {
    const uint32_t dst = dst0 + G * 32;
    sts128(dst, make_uint4(v1 | (v0 << 16), v2 | (v1 << 16), v3 | (v2 << 16), v4 | (v3 << 16)));
    sts128(dst + 16, make_uint4(v5 | (v4 << 16), v6 | (v5 << 16), v7 | (v6 << 16), v8 | (v7 << 16)));
  };
  {
    const uint4 q = lds128(kc + lane * 16);
    const uint32_t pv = lane ? lds16(kc + lane * 16 - 2) : 0u;
    const uint32_t dst = dst0 + (lane + 2) * 32;
    sts128(dst, make_uint4(__byte_perm(q.x, pv, 0x5410), __byte_perm(q.x, q.x, 0x1032), __byte_perm(q.y, q.x, 0x7610), __byte_perm(q.y, q.y, 0x1032)));
    sts128(dst + 16, make_uint4(__byte_perm(q.z, q.y, 0x7610), __byte_perm(q.z, q.z, 0x1032), __byte_perm(q.w, q.z, 0x7610), __byte_perm(q.w, q.w, 0x1032)));
    if (lane < 4) sts128(dst0 + lane * 16, make_uint4(0, 0, 0, 0));
  }
  uint32_t a[5], b[2][3];
  {
    const uint32_t s1 = kc + 2 * (256 + 4 * lane);
#pragma unroll
    for (int k = 0; k < 5; k++) a[k] = lds16(s1 + 2 * k);
#pragma unroll
    for (int u = 0; u < 2; u++) {
      const uint32_t s2 = kc + 2 * (384 + 2 * (lane + 32 * u));
#pragma unroll
      for (int k = 0; k < 3; k++) b[u][k] = lds16(s2 + 2 * k);
    }
  }
  const uint32_t k255 = lds16(kc + 2 * 255), k1024 = lds16(kc + 2 * 512);
  put(34 + lane, lane == 0 ? k255 : a[0], a[0], a[0], a[1], a[2], a[2], a[2], a[3], a[4]);
#pragma unroll
  for (int u = 0; u < 2; u++) put(66 + lane + 32 * u, b[u][0], b[u][0], b[u][0], b[u][0], b[u][1], b[u][1], b[u][1], b[u][2], b[u][2]);
  if (lane < 10) {
    const uint32_t v = lane == 0 ? k1024 : 0u;
    put(130 + lane, v, v, v, v, v, v, 0u, 0u, 0u);
  }
}
__device__ __forceinline__ void expand_far(uint32_t sb, int ht) {
  const int ch = ht >> 5, lane = ht & 31;
  const uint32_t kc = sb + kc_off(ch) + 2 * (513 + 2 * (63 - lane)), dst = sb + cv_fa(ch) + lane * 16;
#pragma unroll
  for (int ty = 0; ty < 2; ty++) {
    uint32_t v[16];
#pragma unroll
    for (int k = 0; k < 16; k++) v[k] = (k < 8 || 63 - lane - 4 * k >= 0) ? lds16(kc + 2 * (1 - ty) - 16 * k) : 0u;
#pragma unroll
    for (int u = 0; u < 2; u++)
      sts128(dst + ty * 2048 + u * 512, make_uint4(v[8 * u] | (v[8 * u + 1] << 16), v[8 * u + 2] | (v[8 * u + 3] << 16), v[8 * u + 4] | (v[8 * u + 5] << 16), v[8 * u + 6] | (v[8 * u + 7] << 16)));
    sts128(dst + ty * 2048 + 1024, make_uint4(0, 0, 0, 0));
  }
}

#define FDELAY 400
__host__ __device__ constexpr int bar_count(int i) {
  return i == B_LN ? 2 : i == B_AL ? 8 : i < B_STG ? 1 : i < B_PE ? 4 : i >= B_PUB ? 256 : 128;
}
__host__ __device__ constexpr bool bar_first(int i) { return i < B_WF + 2 && (i & 7) < 2; }

__global__ void __launch_bounds__(NTHREADS, 1) fused_kernel(const __grid_constant__ Params p) {
  extern __shared__ __align__(1024) uint8_t smem[];
  constexpr uint32_t sb = 1024;
  if (s32(smem) != sb) return;
  const int tid = threadIdx.x, lane = tid & 31;
  const int warp = __shfl_sync(~0u, tid >> 5, 0);
  if (tid == 32) {
    asm volatile("prefetch.tensormap [%0];" ::"l"(&p.mapX) : "memory");
    asm volatile("prefetch.tensormap [%0];" ::"l"(&p.mapW3) : "memory");
  }
  const int cta = blockIdx.x - (gridDim.x == NCTA + 4 ? 0 : 4);
  if ((unsigned)cta >= NCTA) {
    if (blockIdx.x < NCTA + 4) colsum_cta(p, sb, blockIdx.x & 3, tid);
    return;
  }
  const int rb = ((cta >> 4) & 3) * 4 + ((cta >> 2) & 3), hg = (cta >> 6) * 4 + (cta & 3);
  const uint32_t bar = sb + SM_BAR;
  auto ld_x0 = [&](int half, int c) {
    const uint32_t b = bar + 8 * (B_XF + 8 * half + c);
    mbar_expect(b, PG);
    tma_ld(sb + x_page(half, c) * PG, &p.mapX, c * 64, (16 * half + rb) * 64, b);
  };
  auto ld_x1 = [&](int half, int c, int b0) {
    const uint32_t b = bar + 8 * b0;
    mbar_expect(b, PG);
    tma_ld(sb + (8 * half + c) * PG, &p.mapXT, (16 * half + rb) * 64, DM + c * 64, b);
  };
  auto ld_w = [&](int c) {
    const uint32_t b = bar + 8 * (B_WF + c);
    mbar_expect(b, 3 * PG);
    tma_ld3(sb + w_page(c) * PG, &p.mapW3, hg * 64, c * 64, 0, b);
  };

  if (tid == 0) TS(0);
  if (tid == 480) LTS(0);
  if (warp == 0 && elect_one()) {
#pragma unroll
    for (int i = 0; i < B_WF + 2; i++)
      if (bar_first(i)) mbar_init(bar + 8 * i, 1);
    asm volatile("fence.mbarrier_init.release.cluster;" ::: "memory");
    fence_async_smem();
    ld_x0(0, 0);
    ld_w(0); ld_x0(1, 0);
    ld_x0(0, 1); ld_w(1); ld_x0(1, 1);
    TS(1);
  }
  __syncwarp();
  if (warp >= 1 && warp < 8 && elect_one()) {
    if (warp < 4) {
#pragma unroll
      for (int i = 2; i < 8; i++) mbar_init(bar + 8 * (8 * warp - 8 + i), 1);
    } else {
#pragma unroll
      for (int i = 0; i < 12; i++) mbar_init(bar + 8 * (12 * warp - 24 + i), 1);
    }
    asm volatile("fence.mbarrier_init.release.cluster;" ::: "memory");
  }
  if (warp == 15 && elect_one()) {
#pragma unroll
    for (int i = 72; i < B_COUNT; i++) mbar_init(bar + 8 * i, bar_count(i));
    asm volatile("fence.mbarrier_init.release.cluster;" ::: "memory");
  }

  if (warp < 8) {
    bar_sync(0, NTHREADS);
    asm volatile("setmaxnreg.inc.sync.aligned.u32 %0;" ::"n"(R_CONS));
    const int cw = __shfl_sync(~0u, opaque_tid() >> 5, 0);
    const int wg = cw >> 2, w = cw & 3;
    if (tid == 0) TS(2);
#pragma unroll 1
    for (int layer = 0; layer < 2; layer++) {
      attn_phase(p, sb, layer, rb, hg, wg, w);
      uint32_t A0[68], A1[68];
      proj_phase(p, sb, layer, rb, hg, A0, A1);
      conv_phase(p, sb, layer, cta, A0, A1);
    }
    if (wg == 0) mbar_wait(bar + 8 * (B_TF + 1), 0);
    else delay(FDELAY);
    if (tid == 128) TS(8);
    final_tile(p, sb + (16 + wg) * PG, 256 * wg + 32 * (cta >> 4), 1024 + 64 * (cta & 15), 2 + wg);
    if (tid == 128) TS(9);
    if (tid == 128) LTS(1);
    if (tid == 0) LTE();
  } else if (warp < 12) {
    asm volatile("setmaxnreg.dec.sync.aligned.u32 %0;" ::"n"(R_HELP));
    const int ht = tid - 256;
    {
      unsigned ep0 = 0;
      if (ht == 0) ep0 = ld_relaxed(&g_cnt[C_CS * 32]);
      const bf16 dsk = p.dskip[cv_chan(cta, ht & 3)];
      const ModeIn in0 = load_modes(p, cv_chan(cta, ht >> 6), ht & 63), in1 = load_modes(p, cv_chan(cta, 2 + (ht >> 6)), ht & 63);
      if (ht < 48) sts128f(sb + SM_STG + ht * 16, 0.f, 0.f, 0.f, 1.f);
      bar_sync(0, NTHREADS);
      if (ht == 0) {
        sts32(sb + SM_EP, ep0);
        mbar_arrive(bar + 8 * B_EP);
      }
      if (ht >= 124) sts16(sb + SM_RED + 24 + 2 * (ht & 3), __bfloat16_as_ushort(dsk));
      kernel_gen(sb, cta, ht, in0, in1);
      if (ht < 48) sts128f(sb + SM_KGT + ht * 16, 0.f, 0.f, 0.f, 1.f);
      fence_async_smem();
      bar_sync(4, 128);
      if (ht == 0) mbar_arrive(bar + 8 * B_KG);
    }
#pragma unroll 1
    for (int layer = 0; layer < 2; layer++) {
      const int early = layer;
      if (early) mbar_wait(bar + 8 * (B_DN + 13), 1);
      mbar_wait(bar + 8 * (early ? B_OST : B_PDONE), layer);
      expand_taps(sb, opaque_tid() - 256, early);
      mbar_arrive(bar + 8 * B_PE);
      TSW(0);
      mbar_wait(bar + 8 * B_PDONE, layer);
      expand_far(sb, opaque_tid() - 256);
      {
        const int i = opaque_tid() - 256;
        if (i < 32) sts128(sb + cv_u(i >> 3) + ((i >> 2) & 1) * CV_UH + (128 + (i & 3)) * 16, make_uint4(0, 0, 0, 0));
        mbar_wait(bar + 8 * B_RC, layer);
        mbar_wait(bar + 8 * B_GB, layer);
        TSW(13);
        conv_prep<0>(sb, layer, cta, i);
        mbar_arrive(bar + 8 * B_U);
      }
      mbar_wait(bar + 8 * (B_PDONE + 1), layer);
      bar_sync(4, 128);
#pragma unroll 1
      for (int lc = 0; lc < 4; lc += 2) {
        conv_sums(sb, lc, opaque_tid() - 256);
        TSW(1 + lc);
      }
      mbar_wait(bar + 8 * (B_GB + 1), layer);
      conv_prep<1>(sb, layer, cta, opaque_tid() - 256);
      mbar_arrive(bar + 8 * B_U1);
      TSW(4);
      if (layer == 0) {
        const int c = __shfl_sync(~0u, (opaque_tid() >> 5) & 3, 0);
        int phase = 0;
#pragma unroll 1
        for (int k = 0; k < 3; k++) {
          const int page = (k ? 4 + 4 * k : 0) + c, b = B_XR + 4 * (k & 1) + c;
          const uint32_t a = sb + page * PG + lane * 128 + (lane & 7) * 16 + (lane >> 3) * 4;
          int it = k == 2 ? phase : 0;
#pragma unroll 1
          for (; it < MAX_RETRY; it++) {
            mbar_wait(bar + 8 * b, it & 1);
            const uint32_t v0 = lds32(a), v1 = lds32(a + 4096);
            if (__all_sync(~0u, v0 != UNSET && v1 != UNSET)) break;
            if (elect_one()) { fence_async_smem(); ld_x1(page >> 3, page & 7, b); }
            __syncwarp();
            RETRY(3);
          }
          if (k == 0) phase = it + 1;
          if (lane == 0) mbar_arrive(bar + 8 * (B_XF + page));
        }
      }
    }
    mbar_wait(bar + 8 * B_TF, 0);
#pragma unroll 1
    for (int k = 0; k < 2; k++) final_tile(p, sb + 18 * PG + k * 4096, 256 * k + 32 * (cta >> 4), 64 * (cta & 15), 4);
    if (ht == 0) LTE();
  } else {
    asm volatile("setmaxnreg.dec.sync.aligned.u32 %0;" ::"n"(R_AGENT));
    bar_sync(0, NTHREADS);
    auto done = [&](int half, int c, int layer) { mbar_wait(bar + 8 * (B_DN + 8 * half + c), layer); };
    auto publish = [&](int layer, int k) {
      mbar_wait(bar + 8 * (B_PUB + k), layer);
      red_relaxed(&g_cnt[(layer ? C_F + 8 * k + (cta >> 4) : C_C + k) * 32]);
      if (!layer && k == 0) red_release(&g_cnt[(C_C + 3) * 32]);
      TS(16 + layer * 56 + 40 + 7 + k);
    };
    if (warp == 12) {
      if (elect_one()) {
#pragma unroll 1
        for (int layer = 0; layer < 2; layer++) {
          auto ld_xe = [&](int c) {
            const uint32_t b = bar + 8 * (B_XF + c);
            mbar_expect(b, PG);
            if (layer == 0) tma_ld(sb + x_page(0, c) * PG, &p.mapX, c * 64, rb * 64, b);
            else tma_ld(sb + x_page(0, c) * PG, &p.mapXT, rb * 64, DM + c * 64, b);
          };
          if (layer == 0) {
            ld_x0(0, 2); ld_w(2); ld_x0(1, 2);
            if (hg >= 3) {
              mbar_expect(bar + 8 * B_SC, PG);
              tma_ld(sb + P_R * PG, &p.mapX, hg * 64, rb * 64, bar + 8 * B_SC);
            }
            if (rb < 4) tma_prefetch3(&p.mapW3, hg * 64, (4 + rb) * 64, 0);
            ld_x0(0, 3); ld_w(3); ld_x0(1, 3); ld_x0(0, 4); ld_x0(1, 4);
            done(0, 0, 0); done(1, 0, 0);
            ld_w(4);
            ld_x0(1, 5); ld_x0(1, 6); ld_x0(1, 7);
            done(0, 1, 0); done(1, 1, 0);
            ld_w(5);
            if (rb < 8) tma_prefetch5(&p.mapWo, hg * 64, rb * 2);
            done(0, 2, 0);
            fence_async_smem();
            ld_xe(5); ld_xe(6); ld_xe(7);
          } else {
            mbar_wait(bar + 8 * B_PDONE, 0);
            mbar_wait(bar + 8 * (B_PDONE + 1), 0);
            mbar_wait(bar + 8 * B_U, 0);
            ld_w(0); ld_w(1);
            mbar_wait(bar + 8 * B_U1, 0);
            fence_async_smem();
            ld_w(2);
            mbar_wait(bar + 8 * (B_PUB + 2), 0);
            fence_async_smem();
            ld_w(3);
            spin_until(&g_cnt[(C_C + 3) * 32], ((lds32(sb + SM_EP) / NCTA) + 1) * NCTA);
            fence_async_global();
            if (hg >= 3) {
              mbar_expect(bar + 8 * B_SC, PG);
              tma_ld(sb + P_R * PG, &p.mapXT, rb * 64, DM + hg * 64, bar + 8 * B_SC);
            }
            ld_xe(4);
            done(0, 2, 1);
            fence_async_smem();
            ld_xe(5); ld_xe(6); ld_xe(7);
            done(1, 0, 1);
            ld_w(4);
            done(1, 1, 1);
            ld_w(5);
          }
          done(1, 2, layer);
          fence_async_smem();
          ld_w(6); ld_w(7);
          auto ld_res = [&](int half) {
            const uint32_t b = bar + 8 * (B_RF + half);
            mbar_expect(b, PG);
            if (layer == 0) tma_ld(sb + (half ? 2 : P_R) * PG, &p.mapX, hg * 64, (16 * half + rb) * 64, b);
            else tma_ld(sb + (half ? 2 : P_R) * PG, &p.mapXT, (16 * half + rb) * 64, DM + hg * 64, b);
          };
          done(0, 4, layer); done(1, 3, layer);
          fence_async_smem();
          mbar_expect(bar + 8 * B_WOF, 8 * PG);
#pragma unroll 1
          for (int c = 0; c < 8; c++) {
            if (c == 5) { ld_res(0); done(1, 4, layer); }
            tma_ld5(sb + wo_page(c) * PG, &p.mapWo, hg * 64, c * 2, bar + 8 * B_WOF);
          }
          done(0, 7, layer);
          fence_async_global();
          ld_res(1);
          if (layer) mbar_wait(bar + 8 * B_RS, 0);
          fence_async_global();
#pragma unroll
          for (int half = 0; half < 2; half++) {
            float* stats = g_stats + (layer * 32 + 16 * half + rb) * 192;
            unsigned* cnt = &g_cnt[(C_G + 2 * layer + half) * 32];
            mbar_wait(bar + 8 * (B_STG + half), layer);
            tma_st(&p.mapXT, (16 * half + rb) * 64, 2 * layer * DM + hg * 64, sb + (P_R + half) * PG);
            bulk_red_add_f32(stats, sb + (half ? SM_KGT : SM_STG), 768);
            bulk_commit();
            red_relaxed(cnt);
            if (half == 0) mbar_arrive(bar + 8 * B_PG);
            bulk_wait_read();
            mbar_arrive(bar + 8 * (B_PST + half));
          }
        }
      }
    } else if (warp == 13) {
      mbar_wait(bar + 8 * B_EP, 0);
      const unsigned e1 = (lds32(sb + SM_EP) / NCTA) + 1;
      auto ld_o = [&](int layer) {
#pragma unroll 1
        for (int half = 0; half < 2; half++) {
          done(1, 7, layer);
          mbar_wait(bar + 8 * B_OST, layer);
          if (half) mbar_wait(bar + 8 * (B_OST + 1), layer);
          fence_async_smem();
#pragma unroll
          for (int c = 0; c < 4; c++) mbar_expect(bar + 8 * (B_OF + 4 * half + c), 2 * PG);
          spin_hint(&g_cnt[(C_O + layer * 32 + 16 * half + rb) * 32], e1 * 32);
#pragma unroll
          for (int c = 0; c < 4; c++) {
            if (c == 2 && half && layer) { mbar_wait(bar + 8 * B_AL, 0); fence_async_smem(); }
            bulk_ld(sb + o_page(half, c) * PG, g_O + ((layer * 32 + 16 * half + rb) * 4 + c) * PG, 2 * PG, bar + 8 * (B_OF + 4 * half + c));
          }
        }
      };
      if (elect_one()) {
        mbar_wait(bar + 8 * (B_WF + 2), 0);
        asm volatile("prefetch.tensormap [%0];" ::"l"(&p.mapXT) : "memory");
        asm volatile("prefetch.tensormap [%0];" ::"l"(&p.mapWo) : "memory");
        spin_until(&g_cnt[C_Z * 32], e1 * NCTA);
        mbar_arrive(bar + 8 * B_ZF);
        TS(3);
        ld_o(0);
#pragma unroll 1
        for (int k = 0; k < 3; k++) {
          mbar_wait(bar + 8 * (B_PUB + k), 0);
          if (k == 2) {
#pragma unroll 1
            for (int c = 0; c < 4; c++) mbar_wait(bar + 8 * (B_XF + c), 1);
          }
          fence_async_smem();
          spin_hint(&g_cnt[(C_C + k) * 32], e1 * NCTA);
          TS(10 + k);
#pragma unroll
          for (int c = 0; c < 4; c++) ld_x1(k != 0, (k & 2) * 2 + c, B_XR + 4 * (k & 1) + c);
        }
        ld_o(1);
#pragma unroll 1
        for (int k = 0; k < 2; k++) {
          mbar_wait(bar + 8 * (B_PUB + k), 1);
          spin_hint(&g_cnt[(C_F + 8 * k + (cta >> 4)) * 32], e1 * 16);
          mbar_arrive(bar + 8 * (B_TF + k));
        }
      }
    } else if (warp == 14) {
      mbar_wait(bar + 8 * B_EP, 0);
      const unsigned e1 = (lds32(sb + SM_EP) / NCTA) + 1;
      done(0, 1, 0);
      {
        const uint2* cp = g_colsum + (hg * 192 + lane);
        uint2 v[6];
        bool ok;
        int it = 0;
        do {
          ok = true;
#pragma unroll
          for (int i = 0; i < 6; i++) {
            asm volatile("ld.relaxed.gpu.global.v2.u32 {%0,%1}, [%2];" : "=r"(v[i].x), "=r"(v[i].y) : "l"(cp + 32 * i) : "memory");
            ok = ok && v[i].y == e1;
          }
          if (++it > (1 << 22)) __trap();
        } while (!__all_sync(~0u, ok));
#pragma unroll
        for (int i = 0; i < 6; i++) sts32f(sb + SM_CS + 4 * (lane + 32 * i), __uint_as_float(v[i].x));
      }
      __syncwarp();
      if (elect_one()) {
        mbar_wait(bar + 8 * B_ZF, 0);
        mbar_arrive(bar + 8 * B_LN);
        red_relaxed(&g_cnt[C_CS * 32]);
        TS(13);
#pragma unroll 1
        for (int i = 0; i < 4; i++) {
          const int layer = i >> 1;
          mbar_wait(bar + 8 * (B_PST + (i & 1)), layer);
          const uint32_t b = bar + 8 * (B_GB + 1);
          const bf16* xin = g_xT + ((size_t)2 * layer * DM + 2 * cta) * LSEQ + 1024;
          if (i & 1) {
            fence_async_smem();
            mbar_expect(b, 12288 + PG);
          }
          spin_hint(&g_cnt[(C_G + i) * 32], e1 * NCTA);
          if (i & 1) {
            bulk_ld(sb + CV_ST, g_stats + (layer * 32 + 16) * 192, 12288, b);
#pragma unroll
            for (int lc = 0; lc < 4; lc++) bulk_ld(sb + cv_x(1, lc), xin + cv_chan(0, lc) * LSEQ, 2048, b);
            TS(14 + layer);
            publish(layer, 1);
          } else {
            mbar_arrive(bar + 8 * B_GB);
          }
        }
      }
    } else {
      const uint4 u = make_uint4(UNSET, UNSET, UNSET, UNSET);
      if (lane < 24) stg128((uint4*)g_stats + cta * 24 + lane, make_uint4(0, 0, 0, 0));
      if (lane < 16) stg128(g_rows + LSEQ + cta * 16 + lane, make_uint4(0, 0, 0, 0));
#pragma unroll 4
      for (int i = 0; i < 16; i++) stg128(g_halo + cta * 512 + 32 * i + lane, u);
#pragma unroll 4
      for (int i = 0; i < 16; i++) stg128(((i & 8) ? (uint4*)g_xT : (uint4*)g_O) + cta * 1024 + (i & 7) * 128 + (lane >> 1) * 8 + (lane & 1), u);
      __syncwarp();
      if (elect_one()) red_release(&g_cnt[C_Z * 32]);
      __syncwarp();
#pragma unroll 1
      for (int layer = 0; layer < 2; layer++) {
        auto reset_done = [&](int s) {
          spin_until(&g_cnt[(C_R + s) * 32], (lds32(sb + SM_EP) / NCTA) * 4 + 4);
          mbar_arrive(bar + 8 * (s == 1 ? B_LN : s == 2 ? B_RS : B_RC));
          if (s) TS(16 + 40 + 9 + s);
        };
        if (layer && elect_one()) reset_done(1);
        __syncwarp();
#pragma unroll 1
        for (int half = 0; half < 2; half++) {
          done(half, 2, layer);
          const uint4* src = g_rows + (layer * LSEQ + (16 * half + rb) * 64 + (opaque_tid() & 31));
          uint4 a, b;
          int it = 0;
          do {
            a = ld_tagged(src); b = ld_tagged(src + 32);
          } while (!__all_sync(~0u, (a.z | a.w) == __float_as_uint(8.f) && (b.z | b.w) == __float_as_uint(8.f)) && ++it < (1 << 20));
          float m0 = __uint_as_float(a.x) * (1.f / DM), m1 = __uint_as_float(b.x) * (1.f / DM);
          float r0 = rsqrt_approx(fmaxf(__uint_as_float(a.y) * (1.f / DM) - m0 * m0, 0.f) + 1e-5f);
          float r1 = rsqrt_approx(fmaxf(__uint_as_float(b.y) * (1.f / DM) - m1 * m1, 0.f) + 1e-5f);
          if (half) done(0, 7, layer);
          const uint32_t dst = sb + ln_off(half) + ((lane >> 4) * 8 + (lane & 7)) * 16 + (lane & 8);
          asm volatile("st.shared.v2.f32 [%0], {%1,%2};" ::"r"(dst), "f"(m0), "f"(r0) : "memory");
          asm volatile("st.shared.v2.f32 [%0], {%1,%2};" ::"r"(dst + 256), "f"(m1), "f"(r1) : "memory");
          __syncwarp();
          if (elect_one()) { mbar_arrive(bar + 8 * (B_LN + half)); TS(16 + layer * 56 + 40 + 14 + half); }
        }
        if (layer && lane < 16) stg128(g_rows + cta * 16 + (opaque_tid() & 31), make_uint4(0, 0, 0, 0));
        if (elect_one()) {
          if (layer) reset_done(2);
          reset_done(3 * layer);
          publish(layer, 0);
          if (!layer) publish(layer, 2);
        }
        __syncwarp();
      }
    }
  }
}

typedef CUresult (*EncodeFn)(CUtensorMap*, CUtensorMapDataType, cuuint32_t, void*, const cuuint64_t*, const cuuint64_t*,
                             const cuuint32_t*, const cuuint32_t*, CUtensorMapInterleave, CUtensorMapSwizzle,
                             CUtensorMapL2promotion, CUtensorMapFloatOOBfill);

static void make_map(EncodeFn enc, CUtensorMap* m, void* ptr, uint64_t cols, uint64_t rows, uint32_t box_rows) {
  cuuint64_t dims[2] = {cols, rows};
  cuuint64_t strides[1] = {cols * 2};
  cuuint32_t box[2] = {64, box_rows};
  cuuint32_t es[2] = {1, 1};
  enc(m, CU_TENSOR_MAP_DATA_TYPE_BFLOAT16, 2, ptr, dims, strides, box, es, CU_TENSOR_MAP_INTERLEAVE_NONE,
      CU_TENSOR_MAP_SWIZZLE_128B, CU_TENSOR_MAP_L2_PROMOTION_L2_128B, CU_TENSOR_MAP_FLOAT_OOB_FILL_NONE);
}
static void make_map3(EncodeFn enc, CUtensorMap* m, void* ptr, uint64_t d0, uint64_t cols, uint64_t rows, uint64_t blk_stride,
                      uint64_t nblocks, uint32_t nblk) {
  cuuint64_t dims[3] = {d0, rows, nblocks};
  cuuint64_t strides[2] = {cols * 2, blk_stride * 2};
  cuuint32_t box[3] = {64, 64, nblk};
  cuuint32_t es[3] = {1, 1, 1};
  enc(m, CU_TENSOR_MAP_DATA_TYPE_BFLOAT16, 3, ptr, dims, strides, box, es, CU_TENSOR_MAP_INTERLEAVE_NONE,
      CU_TENSOR_MAP_SWIZZLE_128B, CU_TENSOR_MAP_L2_PROMOTION_L2_128B, CU_TENSOR_MAP_FLOAT_OOB_FILL_NONE);
}

extern "C" void kernel_launch(void* const* d_in, const int* in_sizes, int n_in, void* d_out, int out_size) {
  static Params prm;
  static void* cached[13] = {nullptr};
  static bool attr_done = false;
  static int grid = NCTA + 4;
  bool same = attr_done && cached[12] == d_out;
  for (int i = 0; i < 12 && same; i++) same = cached[i] == d_in[i];
  if (!same) {
    void* fn = nullptr;
    cudaDriverEntryPointQueryResult qr;
    cudaGetDriverEntryPoint("cuTensorMapEncodeTiled", &fn, cudaEnableDefault, &qr);
    EncodeFn enc = (EncodeFn)fn;
    void* pXT;
    cudaGetSymbolAddress(&pXT, g_xT);
    make_map(enc, &prm.mapX, d_in[0], DM, LSEQ, 64);
    make_map(enc, &prm.mapXT, pXT, LSEQ, 4 * DM, 64);
    {
      cuuint64_t dims[5] = {DM, 2, 4, 4, 16};
      cuuint64_t strides[4] = {DM * 2, 8 * DM * 2, 2 * DM * 2, 32 * DM * 2};
      cuuint32_t box[5] = {64, 2, 4, 4, 2};
      cuuint32_t es[5] = {1, 1, 1, 1, 1};
      enc(&prm.mapWo, CU_TENSOR_MAP_DATA_TYPE_BFLOAT16, 5, d_in[2], dims, strides, box, es, CU_TENSOR_MAP_INTERLEAVE_NONE,
          CU_TENSOR_MAP_SWIZZLE_128B, CU_TENSOR_MAP_L2_PROMOTION_L2_128B, CU_TENSOR_MAP_FLOAT_OOB_FILL_NONE);
    }
    make_map3(enc, &prm.mapW3, d_in[1], DM, 3 * DM, DM, DM, 3, 3);
    prm.out = (bf16*)d_out;
    prm.a_re = (const bf16*)d_in[4]; prm.a_im = (const bf16*)d_in[5];
    prm.b_re = (const bf16*)d_in[6]; prm.b_im = (const bf16*)d_in[7];
    prm.c_re = (const bf16*)d_in[8]; prm.c_im = (const bf16*)d_in[9];
    prm.log_dt = (const bf16*)d_in[10]; prm.dskip = (const bf16*)d_in[11];
    int dev = 0, sms = 0;
    cudaGetDevice(&dev);
    cudaDeviceGetAttribute(&sms, cudaDevAttrMultiProcessorCount, dev);
    grid = sms >= NCTA + 4 ? NCTA + 4 : NCTA + 5;
    cudaFuncSetAttribute(fused_kernel, cudaFuncAttributeMaxDynamicSharedMemorySize, SM_TOTAL);
    for (int i = 0; i < 12; i++) cached[i] = d_in[i];
    cached[12] = d_out;
    attr_done = true;
  }
  fused_kernel<<<grid, NTHREADS, SM_TOTAL>>>(prm);
}
```

```cpp
#include <cuda_runtime.h>
#include <cuda_bf16.h>
#include <cuda.h>
#include <stdint.h>

typedef __nv_bfloat16 bf16;

constexpr int LSEQ = 2048;
constexpr int DM = 512;
constexpr int NCTA = 128;
constexpr int NTHREADS = 512;
#define R_CONS 200
#define R_HELP 88
#define R_AGENT 24
#define TURN0 4
#define TURN1 4

constexpr int PG = 8192;
constexpr int P_R = 25;
__host__ __device__ constexpr int x_page(int half, int c) { return half ? 8 + c : c < 5 ? c : c - 5; }
__host__ __device__ constexpr int w_page(int c) { return (c & 3) < 3 ? 16 + 3 * (c & 3) : c < 4 ? 5 : 8; }
__host__ __device__ constexpr int wo_page(int c) { return c < 5 ? 3 + c : 11 + c; }
__host__ __device__ constexpr int o_page(int half, int pair) { return half ? (pair ? 25 - 2 * pair : 0) : 8 + 2 * pair; }
constexpr int SM_KGB = (P_R + 1) * PG;
constexpr int SM_KC = 27 * PG;
constexpr int KC_STRIDE = 648;
__host__ __device__ constexpr int kc_off(int lc) { return SM_KC + (lc & 1) * 2 * KC_STRIDE + (lc < 2 ? 3328 : 0); }
constexpr int SM_KGT = SM_KC + 3328 + 2592;
constexpr int SM_CS = SM_KGT + 2048;
constexpr int SM_RED = SM_CS + 768;
constexpr int SM_EP = SM_RED + 16;
constexpr int SM_STG = SM_RED + 32;
constexpr int SM_LN = SM_STG + 768;
__host__ __device__ constexpr int ln_off(int half) { return half ? PG + 4096 : SM_LN; }
constexpr int SM_BAR = SM_LN + 512;
constexpr int SM_TS = SM_BAR + 704;
constexpr int SM_TOTAL = SM_TS + 512;
static_assert(SM_TOTAL <= 232448 && SM_STG % 16 == 0 && SM_KGT % 16 == 0, "shared memory");

constexpr int CV_UH = 140 * 16;
__host__ __device__ constexpr int cv_u(int lc) { return (8 + 2 * lc) * PG; }
__host__ __device__ constexpr int cv_pe(int lc, int early) { return early ? 19 * PG + lc * 4480 : cv_u(lc) + 4480; }
__host__ __device__ constexpr int cv_pb1(int lc, int w) { return w ? cv_u(lc) + 8960 + (w - 1) * 2048 : 7 * PG + lc * 2048; }
__host__ __device__ constexpr int cv_fa(int lc) { return cv_pb1(lc, 1) + 128; }
__host__ __device__ constexpr int cv_dump(int lc) { return cv_u(lc) + 16256; }
__host__ __device__ constexpr int cv_pb0(int lc, int w) { return lc * PG + w * 2048; }
__host__ __device__ constexpr int cv_se(int lc) { return 5 * PG + lc * 4096; }
__host__ __device__ constexpr int cv_so(int lc) { return cv_se(lc) + 2048; }
__host__ __device__ constexpr int cv_x(int half, int lc) { return (P_R + half) * PG + lc * 2048; }
constexpr int CV_ST = 22 * PG;
__host__ __device__ constexpr int cv_chan(int cta, int lc) { return 2 * cta + (lc & 1) + 256 * (lc >> 1); }

enum {
  B_XF = 0,
  B_WF = 16,
  B_OF = 24,
  B_DN = 32,
  B_PG = 46,
  B_XR = 48,
  B_RF = 56,
  B_PST = 58,
  B_GB = 60,
  B_TF = 62,
  B_RT = 64,
  B_RS = 66,
  B_RC = 67,
  B_WOF = 68,
  B_ZF = 69,
  B_EP = 70,
  B_KG = 71,
  B_SC = 37,
  B_LN = 72,
  B_END = 38,
  B_STG = 74,
  B_OST = 76,
  B_PDONE = 78,
  B_PE = 80,
  B_U = 81,
  B_U1 = 82,
  B_PUB = 83,
  B_AL = 86,
  B_COUNT = 87
};

enum {
  C_CS = 0,
  C_G = 1,
  C_C = 5,
  C_O = 21,
  C_Z = 85,
  C_R = 86,
  C_F = 90,
  C_COUNT = 106
};

__device__ unsigned g_cnt[C_COUNT * 32];
__device__ __align__(1024) bf16 g_O[2 * LSEQ * DM];
__device__ __align__(1024) bf16 g_xT[4 * DM * LSEQ];
__device__ __align__(1024) float g_stats[2 * 32 * 192];
__device__ __align__(1024) uint2 g_colsum[3 * DM];
__device__ __align__(1024) uint4 g_halo[32 * 8 * 256];
__device__ __align__(1024) uint4 g_rows[2 * LSEQ];
#define TS(i) do { } while (0)
#define TSW(k) do { if ((threadIdx.x & 127) == 0) TS(16 + layer * 56 + (threadIdx.x >> 7) * 20 + (k)); } while (0)
#define TSG(k) do { } while (0)

#define RETRY(i) do { } while (0)
#define LTS(i) do { } while (0)
#define LTE() do { } while (0)

struct Params {
  CUtensorMap mapX, mapW3, mapXT, mapWo;
  bf16* out;
  const bf16 *a_re, *a_im, *b_re, *b_im, *c_re, *c_im, *log_dt, *dskip;
};

__device__ __forceinline__ uint32_t s32(const void* p) { return (uint32_t)__cvta_generic_to_shared(p); }
__device__ __forceinline__ void mbar_init(uint32_t b, int c) { asm volatile("mbarrier.init.shared::cta.b64 [%0], %1;" ::"r"(b), "r"(c) : "memory"); }
__device__ __forceinline__ void mbar_expect(uint32_t b, int bytes) { asm volatile("mbarrier.arrive.expect_tx.shared::cta.b64 _, [%0], %1;" ::"r"(b), "r"(bytes) : "memory"); }
__device__ __forceinline__ void mbar_arrive(uint32_t b) { asm volatile("mbarrier.arrive.shared::cta.b64 _, [%0];" ::"r"(b) : "memory"); }
__device__ __forceinline__ void mbar_wait(uint32_t b, int parity) {
  asm volatile("{\n.reg .pred p;\nWAIT_LOOP:\nmbarrier.try_wait.parity.shared::cta.b64 p, [%0], %1;\n@p bra WAIT_DONE;\nbra WAIT_LOOP;\nWAIT_DONE:\n}" ::"r"(b), "r"(parity) : "memory");
}
__device__ __forceinline__ bool mbar_test(uint32_t b, int parity) {
  uint32_t ok;
  asm volatile("{\n.reg .pred p;\nmbarrier.test_wait.parity.shared::cta.b64 p, [%1], %2;\nselp.u32 %0, 1, 0, p;\n}" : "=r"(ok) : "r"(b), "r"(parity) : "memory");
  return ok != 0;
}
__device__ __forceinline__ int opaque_tid() { int v; asm volatile("mov.u32 %0, %%tid.x;" : "=r"(v)); return v; }
__device__ __forceinline__ bool elect_one() {
  uint32_t r;
  asm volatile("{\n.reg .pred p;\nelect.sync _|p, 0xffffffff;\nselp.u32 %0, 1, 0, p;\n}" : "=r"(r));
  return r != 0;
}
__device__ __forceinline__ void tma_ld(uint32_t dst, const CUtensorMap* m, int c0, int c1, uint32_t bar) {
  asm volatile("cp.async.bulk.tensor.2d.shared::cluster.global.mbarrier::complete_tx::bytes [%0], [%1, {%3, %4}], [%2];"
               ::"r"(dst), "l"(m), "r"(bar), "r"(c0), "r"(c1) : "memory");
}
__device__ __forceinline__ void tma_ld3(uint32_t dst, const CUtensorMap* m, int c0, int c1, int c2, uint32_t bar) {
  asm volatile("cp.async.bulk.tensor.3d.shared::cluster.global.mbarrier::complete_tx::bytes [%0], [%1, {%3, %4, %5}], [%2];"
               ::"r"(dst), "l"(m), "r"(bar), "r"(c0), "r"(c1), "r"(c2) : "memory");
}
__device__ __forceinline__ void tma_ld5(uint32_t dst, const CUtensorMap* m, int c0, int c4, uint32_t bar) {
  asm volatile("cp.async.bulk.tensor.5d.shared::cluster.global.mbarrier::complete_tx::bytes [%0], [%1, {%3, 0, 0, 0, %4}], [%2];"
               ::"r"(dst), "l"(m), "r"(bar), "r"(c0), "r"(c4) : "memory");
}
__device__ __forceinline__ void tma_prefetch5(const CUtensorMap* m, int c0, int c4) {
  asm volatile("cp.async.bulk.prefetch.tensor.5d.L2.global.tile [%0, {%1, 0, 0, 0, %2}];" ::"l"(m), "r"(c0), "r"(c4) : "memory");
}
__device__ __forceinline__ void tma_prefetch3(const CUtensorMap* m, int c0, int c1, int c2) {
  asm volatile("cp.async.bulk.prefetch.tensor.3d.L2.global.tile [%0, {%1, %2, %3}];" ::"l"(m), "r"(c0), "r"(c1), "r"(c2) : "memory");
}
__device__ __forceinline__ void tma_st(const CUtensorMap* m, int c0, int c1, uint32_t src) {
  asm volatile("cp.async.bulk.tensor.2d.global.shared::cta.bulk_group [%0, {%2, %3}], [%1];" ::"l"(m), "r"(src), "r"(c0), "r"(c1) : "memory");
}
__device__ __forceinline__ void bulk_ld(uint32_t dst, const void* src, int bytes, uint32_t bar) {
  asm volatile("cp.async.bulk.shared::cluster.global.mbarrier::complete_tx::bytes [%0], [%1], %2, [%3];" ::"r"(dst), "l"(src), "r"(bytes), "r"(bar) : "memory");
}
__device__ __forceinline__ void bulk_red_add_f32(void* dst, uint32_t src, int bytes) {
  asm volatile("cp.reduce.async.bulk.global.shared::cta.bulk_group.add.f32 [%0], [%1], %2;" ::"l"(dst), "r"(src), "r"(bytes) : "memory");
}
__device__ __forceinline__ void bulk_commit() { asm volatile("cp.async.bulk.commit_group;" ::: "memory"); }
__device__ __forceinline__ void fence_async_smem() { asm volatile("fence.proxy.async.shared::cta;" ::: "memory"); }
__device__ __forceinline__ void fence_async_global() { asm volatile("fence.proxy.async.global;" ::: "memory"); }
__device__ __forceinline__ void bar_sync(int id, int n) { asm volatile("bar.sync %0, %1;" ::"r"(id), "r"(n) : "memory"); }
__device__ __forceinline__ void bar_arrive(int id, int n) { asm volatile("bar.arrive %0, %1;" ::"r"(id), "r"(n) : "memory"); }
__device__ __forceinline__ bool bar_or(int id, int n, bool v) {
  uint32_t r;
  asm volatile("{\n.reg .pred p, q;\nsetp.ne.u32 q, %3, 0;\nbar.red.or.pred p, %1, %2, q;\nselp.u32 %0, 1, 0, p;\n}" : "=r"(r) : "r"(id), "r"(n), "r"((uint32_t)v) : "memory");
  return r != 0;
}
__device__ __forceinline__ void bulk_wait_read() { asm volatile("cp.async.bulk.wait_group.read 0;" ::: "memory"); }
__device__ __forceinline__ void stg128(void* p, uint4 v) { asm volatile("st.relaxed.gpu.global.v4.u32 [%0], {%1,%2,%3,%4};" ::"l"(p), "r"(v.x), "r"(v.y), "r"(v.z), "r"(v.w) : "memory"); }
constexpr uint32_t UNSET = 0xffffffffu;
constexpr int MAX_RETRY = 1 << 16;
__device__ __forceinline__ void wg_fence() { asm volatile("wgmma.fence.sync.aligned;" ::: "memory"); }
__device__ __forceinline__ void wg_commit() { asm volatile("wgmma.commit_group.sync.aligned;" ::: "memory"); }
template <int N> __device__ __forceinline__ void wg_wait() { asm volatile("wgmma.wait_group.sync.aligned %0;" ::"n"(N) : "memory"); }
__device__ __forceinline__ uint64_t mkdesc(uint32_t addr, uint32_t lbo, uint32_t sbo, int sw) {
  return (uint64_t)((addr & 0x3FFFF) >> 4) | ((uint64_t)(lbo >> 4) << 16) | ((uint64_t)(sbo >> 4) << 32) | ((uint64_t)sw << 62);
}
__device__ __forceinline__ void ldsm4(uint32_t* r, uint32_t a) {
  asm volatile("ldmatrix.sync.aligned.m8n8.x4.shared.b16 {%0,%1,%2,%3}, [%4];" : "=r"(r[0]), "=r"(r[1]), "=r"(r[2]), "=r"(r[3]) : "r"(a) : "memory");
}
__device__ __forceinline__ void ldsm4t(uint32_t* r, uint32_t a) {
  asm volatile("ldmatrix.sync.aligned.m8n8.x4.trans.shared.b16 {%0,%1,%2,%3}, [%4];" : "=r"(r[0]), "=r"(r[1]), "=r"(r[2]), "=r"(r[3]) : "r"(a) : "memory");
}
__device__ __forceinline__ void stsm4(uint32_t a, uint32_t r0, uint32_t r1, uint32_t r2, uint32_t r3) {
  asm volatile("stmatrix.sync.aligned.m8n8.x4.shared.b16 [%0], {%1,%2,%3,%4};" ::"r"(a), "r"(r0), "r"(r1), "r"(r2), "r"(r3) : "memory");
}
__device__ __forceinline__ void stsm4t(uint32_t a, uint32_t r0, uint32_t r1, uint32_t r2, uint32_t r3) {
  asm volatile("stmatrix.sync.aligned.m8n8.x4.trans.shared.b16 [%0], {%1,%2,%3,%4};" ::"r"(a), "r"(r0), "r"(r1), "r"(r2), "r"(r3) : "memory");
}
__device__ __forceinline__ uint32_t movm_t(uint32_t a) { uint32_t r; asm volatile("movmatrix.sync.aligned.m8n8.trans.b16 %0, %1;" : "=r"(r) : "r"(a)); return r; }
__device__ __forceinline__ uint32_t lds32(uint32_t a) { uint32_t v; asm volatile("ld.shared.b32 %0, [%1];" : "=r"(v) : "r"(a) : "memory"); return v; }
__device__ __forceinline__ float2 lds64f(uint32_t a) { float2 v; asm volatile("ld.shared.v2.f32 {%0,%1}, [%2];" : "=f"(v.x), "=f"(v.y) : "r"(a) : "memory"); return v; }
__device__ __forceinline__ float4 lds128f(uint32_t a) { float4 v; asm volatile("ld.shared.v4.f32 {%0,%1,%2,%3}, [%4];" : "=f"(v.x), "=f"(v.y), "=f"(v.z), "=f"(v.w) : "r"(a) : "memory"); return v; }
__device__ __forceinline__ uint4 lds128(uint32_t a) { uint4 v; asm volatile("ld.shared.v4.b32 {%0,%1,%2,%3}, [%4];" : "=r"(v.x), "=r"(v.y), "=r"(v.z), "=r"(v.w) : "r"(a) : "memory"); return v; }
__device__ __forceinline__ void sts128(uint32_t a, uint4 v) { asm volatile("st.shared.v4.b32 [%0], {%1,%2,%3,%4};" ::"r"(a), "r"(v.x), "r"(v.y), "r"(v.z), "r"(v.w) : "memory"); }
__device__ __forceinline__ void sts128f(uint32_t a, float x, float y, float z, float w) { asm volatile("st.shared.v4.f32 [%0], {%1,%2,%3,%4};" ::"r"(a), "f"(x), "f"(y), "f"(z), "f"(w) : "memory"); }
__device__ __forceinline__ void sts32f(uint32_t a, float v) { asm volatile("st.shared.f32 [%0], %1;" ::"r"(a), "f"(v) : "memory"); }
__device__ __forceinline__ void sts16(uint32_t a, uint16_t v) { asm volatile("st.shared.u16 [%0], %1;" ::"r"(a), "h"(v) : "memory"); }
__device__ __forceinline__ uint32_t lds16(uint32_t a) { uint16_t v; asm volatile("ld.shared.u16 %0, [%1];" : "=h"(v) : "r"(a) : "memory"); return v; }
__device__ __forceinline__ uint32_t packbf(float lo, float hi) { uint32_t r; asm("cvt.rn.bf16x2.f32 %0, %1, %2;" : "=r"(r) : "f"(hi), "f"(lo)); return r; }
__device__ __forceinline__ float bf_lo(uint32_t v) { return __uint_as_float(v << 16); }
__device__ __forceinline__ float bf_hi(uint32_t v) { return __uint_as_float(v & 0xffff0000u); }
__device__ __forceinline__ float ex2(float x) { float r; asm("ex2.approx.ftz.f32 %0, %1;" : "=f"(r) : "f"(x)); return r; }
__device__ __forceinline__ float rsqrt_approx(float x) { float r; asm("rsqrt.approx.ftz.f32 %0, %1;" : "=f"(r) : "f"(x)); return r; }
__device__ __forceinline__ float rcp_approx(float x) { float r; asm("rcp.approx.ftz.f32 %0, %1;" : "=f"(r) : "f"(x)); return r; }
__device__ __forceinline__ void mma_bf16(float* d, const uint32_t* a, uint32_t b0, uint32_t b1) {
  asm("mma.sync.aligned.m16n8k16.row.col.f32.bf16.bf16.f32 {%0,%1,%2,%3}, {%4,%5,%6,%7}, {%8,%9}, {%0,%1,%2,%3};"
               : "+f"(d[0]), "+f"(d[1]), "+f"(d[2]), "+f"(d[3]) : "r"(a[0]), "r"(a[1]), "r"(a[2]), "r"(a[3]), "r"(b0), "r"(b1));
}
__device__ __forceinline__ void red_release(unsigned* p) { asm volatile("red.release.gpu.global.add.u32 [%0], 1;" ::"l"(p) : "memory"); }
__device__ __forceinline__ void red_relaxed(unsigned* p) { asm volatile("red.relaxed.gpu.global.add.u32 [%0], 1;" ::"l"(p) : "memory"); }
__device__ __forceinline__ unsigned ld_relaxed(const unsigned* p) { unsigned v; asm volatile("ld.relaxed.gpu.global.u32 %0, [%1];" : "=r"(v) : "l"(p) : "memory"); return v; }
__device__ __forceinline__ void spin_until(const unsigned* p, unsigned target) {
  int it = 0;
  while ((int)(ld_relaxed(p) - target) < 0) {
    if (++it > (1 << 23)) __trap();
  }
}
__device__ __forceinline__ void delay(uint32_t cycles) {
  const uint32_t t0 = (uint32_t)clock();
  while ((uint32_t)clock() - t0 < cycles);
}
template <typename T> __device__ __forceinline__ void pin(T*& p) { asm volatile("" : "+l"(p) :: "memory"); }
__device__ __forceinline__ void pin(uint32_t& v) { asm volatile("" : "+r"(v) :: "memory"); }
__device__ __forceinline__ void spin_hint(const unsigned* p, unsigned target) {
  spin_until(p, target);
}
__device__ __forceinline__ uint4 ld_tagged(const uint4* p) { uint4 v; asm volatile("ld.relaxed.gpu.global.v4.u32 {%0,%1,%2,%3}, [%4];" : "=r"(v.x), "=r"(v.y), "=r"(v.z), "=r"(v.w) : "l"(p) : "memory"); return v; }
__device__ __forceinline__ uint32_t hadd2(uint32_t a, uint32_t b) { uint32_t r; asm("add.rn.bf16x2 %0, %1, %2;" : "=r"(r) : "r"(a), "r"(b)); return r; }

__device__ __forceinline__ uint32_t hfma2(uint32_t a, uint32_t b, uint32_t c) { uint32_t r; asm("fma.rn.bf16x2 %0, %1, %2, %3;" : "=r"(r) : "r"(a), "r"(b), "r"(c)); return r; }
__device__ __forceinline__ void sts32(uint32_t a, uint32_t v) { asm volatile("st.shared.u32 [%0], %1;" ::"r"(a), "r"(v) : "memory"); }

template <int N> __device__ __forceinline__ void acc_fence(float* a) {
#pragma unroll
  for (int i = 0; i < N; i++) asm volatile("" : "+f"(a[i]) :: "memory");
}

template<int N,int TB> __device__ __forceinline__ void wgmma_rs(float* d, const uint32_t* a, uint64_t db, int sd);
template<int N,int TA,int TB> __device__ __forceinline__ void wgmma_ss(float* d, uint64_t da, uint64_t db, int sd);
template<> __device__ __forceinline__ void wgmma_rs<64,0>(float* d, const uint32_t* a, uint64_t db, int sd) {
  asm volatile("{\n.reg .pred p;\nsetp.ne.b32 p, %37, 0;\nwgmma.mma_async.sync.aligned.m64n64k16.f32.bf16.bf16 {%0,%1,%2,%3,%4,%5,%6,%7,%8,%9,%10,%11,%12,%13,%14,%15,%16,%17,%18,%19,%20,%21,%22,%23,%24,%25,%26,%27,%28,%29,%30,%31}, {%32,%33,%34,%35}, %36, p, 1, 1, 0;\n}\n"
   : "+f"(d[0]),"+f"(d[1]),"+f"(d[2]),"+f"(d[3]),"+f"(d[4]),"+f"(d[5]),"+f"(d[6]),"+f"(d[7]),"+f"(d[8]),"+f"(d[9]),"+f"(d[10]),"+f"(d[11]),"+f"(d[12]),"+f"(d[13]),"+f"(d[14]),"+f"(d[15]),"+f"(d[16]),"+f"(d[17]),"+f"(d[18]),"+f"(d[19]),"+f"(d[20]),"+f"(d[21]),"+f"(d[22]),"+f"(d[23]),"+f"(d[24]),"+f"(d[25]),"+f"(d[26]),"+f"(d[27]),"+f"(d[28]),"+f"(d[29]),"+f"(d[30]),"+f"(d[31])
   : "r"(a[0]), "r"(a[1]), "r"(a[2]), "r"(a[3]), "l"(db), "r"(sd));
}
template<> __device__ __forceinline__ void wgmma_rs<56,0>(float* d, const uint32_t* a, uint64_t db, int sd) {
  asm volatile("{\n.reg .pred p;\nsetp.ne.b32 p, %33, 0;\nwgmma.mma_async.sync.aligned.m64n56k16.f32.bf16.bf16 {%0,%1,%2,%3,%4,%5,%6,%7,%8,%9,%10,%11,%12,%13,%14,%15,%16,%17,%18,%19,%20,%21,%22,%23,%24,%25,%26,%27}, {%28,%29,%30,%31}, %32, p, 1, 1, 0;\n}\n"
   : "+f"(d[0]),"+f"(d[1]),"+f"(d[2]),"+f"(d[3]),"+f"(d[4]),"+f"(d[5]),"+f"(d[6]),"+f"(d[7]),"+f"(d[8]),"+f"(d[9]),"+f"(d[10]),"+f"(d[11]),"+f"(d[12]),"+f"(d[13]),"+f"(d[14]),"+f"(d[15]),"+f"(d[16]),"+f"(d[17]),"+f"(d[18]),"+f"(d[19]),"+f"(d[20]),"+f"(d[21]),"+f"(d[22]),"+f"(d[23]),"+f"(d[24]),"+f"(d[25]),"+f"(d[26]),"+f"(d[27])
   : "r"(a[0]), "r"(a[1]), "r"(a[2]), "r"(a[3]), "l"(db), "r"(sd));
}
template<> __device__ __forceinline__ void wgmma_rs<48,0>(float* d, const uint32_t* a, uint64_t db, int sd) {
  asm volatile("{\n.reg .pred p;\nsetp.ne.b32 p, %29, 0;\nwgmma.mma_async.sync.aligned.m64n48k16.f32.bf16.bf16 {%0,%1,%2,%3,%4,%5,%6,%7,%8,%9,%10,%11,%12,%13,%14,%15,%16,%17,%18,%19,%20,%21,%22,%23}, {%24,%25,%26,%27}, %28, p, 1, 1, 0;\n}\n"
   : "+f"(d[0]),"+f"(d[1]),"+f"(d[2]),"+f"(d[3]),"+f"(d[4]),"+f"(d[5]),"+f"(d[6]),"+f"(d[7]),"+f"(d[8]),"+f"(d[9]),"+f"(d[10]),"+f"(d[11]),"+f"(d[12]),"+f"(d[13]),"+f"(d[14]),"+f"(d[15]),"+f"(d[16]),"+f"(d[17]),"+f"(d[18]),"+f"(d[19]),"+f"(d[20]),"+f"(d[21]),"+f"(d[22]),"+f"(d[23])
   : "r"(a[0]), "r"(a[1]), "r"(a[2]), "r"(a[3]), "l"(db), "r"(sd));
}
template<> __device__ __forceinline__ void wgmma_rs<40,0>(float* d, const uint32_t* a, uint64_t db, int sd) {
  asm volatile("{\n.reg .pred p;\nsetp.ne.b32 p, %25, 0;\nwgmma.mma_async.sync.aligned.m64n40k16.f32.bf16.bf16 {%0,%1,%2,%3,%4,%5,%6,%7,%8,%9,%10,%11,%12,%13,%14,%15,%16,%17,%18,%19}, {%20,%21,%22,%23}, %24, p, 1, 1, 0;\n}\n"
   : "+f"(d[0]),"+f"(d[1]),"+f"(d[2]),"+f"(d[3]),"+f"(d[4]),"+f"(d[5]),"+f"(d[6]),"+f"(d[7]),"+f"(d[8]),"+f"(d[9]),"+f"(d[10]),"+f"(d[11]),"+f"(d[12]),"+f"(d[13]),"+f"(d[14]),"+f"(d[15]),"+f"(d[16]),"+f"(d[17]),"+f"(d[18]),"+f"(d[19])
   : "r"(a[0]), "r"(a[1]), "r"(a[2]), "r"(a[3]), "l"(db), "r"(sd));
}
template<> __device__ __forceinline__ void wgmma_rs<32,0>(float* d, const uint32_t* a, uint64_t db, int sd) {
  asm volatile("{\n.reg .pred p;\nsetp.ne.b32 p, %21, 0;\nwgmma.mma_async.sync.aligned.m64n32k16.f32.bf16.bf16 {%0,%1,%2,%3,%4,%5,%6,%7,%8,%9,%10,%11,%12,%13,%14,%15}, {%16,%17,%18,%19}, %20, p, 1, 1, 0;\n}\n"
   : "+f"(d[0]),"+f"(d[1]),"+f"(d[2]),"+f"(d[3]),"+f"(d[4]),"+f"(d[5]),"+f"(d[6]),"+f"(d[7]),"+f"(d[8]),"+f"(d[9]),"+f"(d[10]),"+f"(d[11]),"+f"(d[12]),"+f"(d[13]),"+f"(d[14]),"+f"(d[15])
   : "r"(a[0]), "r"(a[1]), "r"(a[2]), "r"(a[3]), "l"(db), "r"(sd));
}
template<> __device__ __forceinline__ void wgmma_rs<24,0>(float* d, const uint32_t* a, uint64_t db, int sd) {
  asm volatile("{\n.reg .pred p;\nsetp.ne.b32 p, %17, 0;\nwgmma.mma_async.sync.aligned.m64n24k16.f32.bf16.bf16 {%0,%1,%2,%3,%4,%5,%6,%7,%8,%9,%10,%11}, {%12,%13,%14,%15}, %16, p, 1, 1, 0;\n}\n"
   : "+f"(d[0]),"+f"(d[1]),"+f"(d[2]),"+f"(d[3]),"+f"(d[4]),"+f"(d[5]),"+f"(d[6]),"+f"(d[7]),"+f"(d[8]),"+f"(d[9]),"+f"(d[10]),"+f"(d[11])
   : "r"(a[0]), "r"(a[1]), "r"(a[2]), "r"(a[3]), "l"(db), "r"(sd));
}
template<> __device__ __forceinline__ void wgmma_rs<16,0>(float* d, const uint32_t* a, uint64_t db, int sd) {
  asm volatile("{\n.reg .pred p;\nsetp.ne.b32 p, %13, 0;\nwgmma.mma_async.sync.aligned.m64n16k16.f32.bf16.bf16 {%0,%1,%2,%3,%4,%5,%6,%7}, {%8,%9,%10,%11}, %12, p, 1, 1, 0;\n}\n"
   : "+f"(d[0]),"+f"(d[1]),"+f"(d[2]),"+f"(d[3]),"+f"(d[4]),"+f"(d[5]),"+f"(d[6]),"+f"(d[7])
   : "r"(a[0]), "r"(a[1]), "r"(a[2]), "r"(a[3]), "l"(db), "r"(sd));
}
template<> __device__ __forceinline__ void wgmma_rs<8,0>(float* d, const uint32_t* a, uint64_t db, int sd) {
  asm volatile("{\n.reg .pred p;\nsetp.ne.b32 p, %9, 0;\nwgmma.mma_async.sync.aligned.m64n8k16.f32.bf16.bf16 {%0,%1,%2,%3}, {%4,%5,%6,%7}, %8, p, 1, 1, 0;\n}\n"
   : "+f"(d[0]),"+f"(d[1]),"+f"(d[2]),"+f"(d[3])
   : "r"(a[0]), "r"(a[1]), "r"(a[2]), "r"(a[3]), "l"(db), "r"(sd));
}
template<> __device__ __forceinline__ void wgmma_ss<64,1,0>(float* d, uint64_t da, uint64_t db, int sd) {
  asm volatile("{\n.reg .pred p;\nsetp.ne.b32 p, %34, 0;\nwgmma.mma_async.sync.aligned.m64n64k16.f32.bf16.bf16 {%0,%1,%2,%3,%4,%5,%6,%7,%8,%9,%10,%11,%12,%13,%14,%15,%16,%17,%18,%19,%20,%21,%22,%23,%24,%25,%26,%27,%28,%29,%30,%31}, %32, %33, p, 1, 1, 1, 0;\n}\n"
   : "+f"(d[0]),"+f"(d[1]),"+f"(d[2]),"+f"(d[3]),"+f"(d[4]),"+f"(d[5]),"+f"(d[6]),"+f"(d[7]),"+f"(d[8]),"+f"(d[9]),"+f"(d[10]),"+f"(d[11]),"+f"(d[12]),"+f"(d[13]),"+f"(d[14]),"+f"(d[15]),"+f"(d[16]),"+f"(d[17]),"+f"(d[18]),"+f"(d[19]),"+f"(d[20]),"+f"(d[21]),"+f"(d[22]),"+f"(d[23]),"+f"(d[24]),"+f"(d[25]),"+f"(d[26]),"+f"(d[27]),"+f"(d[28]),"+f"(d[29]),"+f"(d[30]),"+f"(d[31])
   : "l"(da), "l"(db), "r"(sd));
}
template<> __device__ __forceinline__ void wgmma_ss<64,0,1>(float* d, uint64_t da, uint64_t db, int sd) {
  asm volatile("{\n.reg .pred p;\nsetp.ne.b32 p, %34, 0;\nwgmma.mma_async.sync.aligned.m64n64k16.f32.bf16.bf16 {%0,%1,%2,%3,%4,%5,%6,%7,%8,%9,%10,%11,%12,%13,%14,%15,%16,%17,%18,%19,%20,%21,%22,%23,%24,%25,%26,%27,%28,%29,%30,%31}, %32, %33, p, 1, 1, 0, 1;\n}\n"
   : "+f"(d[0]),"+f"(d[1]),"+f"(d[2]),"+f"(d[3]),"+f"(d[4]),"+f"(d[5]),"+f"(d[6]),"+f"(d[7]),"+f"(d[8]),"+f"(d[9]),"+f"(d[10]),"+f"(d[11]),"+f"(d[12]),"+f"(d[13]),"+f"(d[14]),"+f"(d[15]),"+f"(d[16]),"+f"(d[17]),"+f"(d[18]),"+f"(d[19]),"+f"(d[20]),"+f"(d[21]),"+f"(d[22]),"+f"(d[23]),"+f"(d[24]),"+f"(d[25]),"+f"(d[26]),"+f"(d[27]),"+f"(d[28]),"+f"(d[29]),"+f"(d[30]),"+f"(d[31])
   : "l"(da), "l"(db), "r"(sd));
}
template<> __device__ __forceinline__ void wgmma_ss<192,0,1>(float* d, uint64_t da, uint64_t db, int sd) {
  asm volatile("{\n.reg .pred p;\nsetp.ne.b32 p, %98, 0;\nwgmma.mma_async.sync.aligned.m64n192k16.f32.bf16.bf16 {%0,%1,%2,%3,%4,%5,%6,%7,%8,%9,%10,%11,%12,%13,%14,%15,%16,%17,%18,%19,%20,%21,%22,%23,%24,%25,%26,%27,%28,%29,%30,%31,%32,%33,%34,%35,%36,%37,%38,%39,%40,%41,%42,%43,%44,%45,%46,%47,%48,%49,%50,%51,%52,%53,%54,%55,%56,%57,%58,%59,%60,%61,%62,%63,%64,%65,%66,%67,%68,%69,%70,%71,%72,%73,%74,%75,%76,%77,%78,%79,%80,%81,%82,%83,%84,%85,%86,%87,%88,%89,%90,%91,%92,%93,%94,%95}, %96, %97, p, 1, 1, 0, 1;\n}\n"
   : "+f"(d[0]),"+f"(d[1]),"+f"(d[2]),"+f"(d[3]),"+f"(d[4]),"+f"(d[5]),"+f"(d[6]),"+f"(d[7]),"+f"(d[8]),"+f"(d[9]),"+f"(d[10]),"+f"(d[11]),"+f"(d[12]),"+f"(d[13]),"+f"(d[14]),"+f"(d[15]),"+f"(d[16]),"+f"(d[17]),"+f"(d[18]),"+f"(d[19]),"+f"(d[20]),"+f"(d[21]),"+f"(d[22]),"+f"(d[23]),"+f"(d[24]),"+f"(d[25]),"+f"(d[26]),"+f"(d[27]),"+f"(d[28]),"+f"(d[29]),"+f"(d[30]),"+f"(d[31]),"+f"(d[32]),"+f"(d[33]),"+f"(d[34]),"+f"(d[35]),"+f"(d[36]),"+f"(d[37]),"+f"(d[38]),"+f"(d[39]),"+f"(d[40]),"+f"(d[41]),"+f"(d[42]),"+f"(d[43]),"+f"(d[44]),"+f"(d[45]),"+f"(d[46]),"+f"(d[47]),"+f"(d[48]),"+f"(d[49]),"+f"(d[50]),"+f"(d[51]),"+f"(d[52]),"+f"(d[53]),"+f"(d[54]),"+f"(d[55]),"+f"(d[56]),"+f"(d[57]),"+f"(d[58]),"+f"(d[59]),"+f"(d[60]),"+f"(d[61]),"+f"(d[62]),"+f"(d[63]),"+f"(d[64]),"+f"(d[65]),"+f"(d[66]),"+f"(d[67]),"+f"(d[68]),"+f"(d[69]),"+f"(d[70]),"+f"(d[71]),"+f"(d[72]),"+f"(d[73]),"+f"(d[74]),"+f"(d[75]),"+f"(d[76]),"+f"(d[77]),"+f"(d[78]),"+f"(d[79]),"+f"(d[80]),"+f"(d[81]),"+f"(d[82]),"+f"(d[83]),"+f"(d[84]),"+f"(d[85]),"+f"(d[86]),"+f"(d[87]),"+f"(d[88]),"+f"(d[89]),"+f"(d[90]),"+f"(d[91]),"+f"(d[92]),"+f"(d[93]),"+f"(d[94]),"+f"(d[95])
   : "l"(da), "l"(db), "r"(sd));
}
template<> __device__ __forceinline__ void wgmma_ss<192,1,1>(float* d, uint64_t da, uint64_t db, int sd) {
  asm volatile("{\n.reg .pred p;\nsetp.ne.b32 p, %98, 0;\nwgmma.mma_async.sync.aligned.m64n192k16.f32.bf16.bf16 {%0,%1,%2,%3,%4,%5,%6,%7,%8,%9,%10,%11,%12,%13,%14,%15,%16,%17,%18,%19,%20,%21,%22,%23,%24,%25,%26,%27,%28,%29,%30,%31,%32,%33,%34,%35,%36,%37,%38,%39,%40,%41,%42,%43,%44,%45,%46,%47,%48,%49,%50,%51,%52,%53,%54,%55,%56,%57,%58,%59,%60,%61,%62,%63,%64,%65,%66,%67,%68,%69,%70,%71,%72,%73,%74,%75,%76,%77,%78,%79,%80,%81,%82,%83,%84,%85,%86,%87,%88,%89,%90,%91,%92,%93,%94,%95}, %96, %97, p, 1, 1, 1, 1;\n}\n"
   : "+f"(d[0]),"+f"(d[1]),"+f"(d[2]),"+f"(d[3]),"+f"(d[4]),"+f"(d[5]),"+f"(d[6]),"+f"(d[7]),"+f"(d[8]),"+f"(d[9]),"+f"(d[10]),"+f"(d[11]),"+f"(d[12]),"+f"(d[13]),"+f"(d[14]),"+f"(d[15]),"+f"(d[16]),"+f"(d[17]),"+f"(d[18]),"+f"(d[19]),"+f"(d[20]),"+f"(d[21]),"+f"(d[22]),"+f"(d[23]),"+f"(d[24]),"+f"(d[25]),"+f"(d[26]),"+f"(d[27]),"+f"(d[28]),"+f"(d[29]),"+f"(d[30]),"+f"(d[31]),"+f"(d[32]),"+f"(d[33]),"+f"(d[34]),"+f"(d[35]),"+f"(d[36]),"+f"(d[37]),"+f"(d[38]),"+f"(d[39]),"+f"(d[40]),"+f"(d[41]),"+f"(d[42]),"+f"(d[43]),"+f"(d[44]),"+f"(d[45]),"+f"(d[46]),"+f"(d[47]),"+f"(d[48]),"+f"(d[49]),"+f"(d[50]),"+f"(d[51]),"+f"(d[52]),"+f"(d[53]),"+f"(d[54]),"+f"(d[55]),"+f"(d[56]),"+f"(d[57]),"+f"(d[58]),"+f"(d[59]),"+f"(d[60]),"+f"(d[61]),"+f"(d[62]),"+f"(d[63]),"+f"(d[64]),"+f"(d[65]),"+f"(d[66]),"+f"(d[67]),"+f"(d[68]),"+f"(d[69]),"+f"(d[70]),"+f"(d[71]),"+f"(d[72]),"+f"(d[73]),"+f"(d[74]),"+f"(d[75]),"+f"(d[76]),"+f"(d[77]),"+f"(d[78]),"+f"(d[79]),"+f"(d[80]),"+f"(d[81]),"+f"(d[82]),"+f"(d[83]),"+f"(d[84]),"+f"(d[85]),"+f"(d[86]),"+f"(d[87]),"+f"(d[88]),"+f"(d[89]),"+f"(d[90]),"+f"(d[91]),"+f"(d[92]),"+f"(d[93]),"+f"(d[94]),"+f"(d[95])
   : "l"(da), "l"(db), "r"(sd));
}

template <bool TR>
__device__ __forceinline__ void gemm_section(float* acc, float& mean0, float& mean1, float& rstd0, float& rstd1,
                                             uint32_t sb, int blk, int hg, int wg, int w, int lane) {
  constexpr int layer = TR ? 1 : 0;
  constexpr int TURN = TR ? TURN1 : TURN0;
  constexpr int LSTAT = TURN < 4 ? TURN - 1 : 3;
  const uint32_t bar = sb + SM_BAR;
  const int g = lane >> 2, t = lane & 3;
  const bool leader = (w == 0) && (lane == 0);
  const int statpos = hg < 3 ? 1 : wg ? LSTAT : TR ? 3 : 2;
  const bool copy = hg >= 3 && wg == 0;
  const int cut = wg ? TURN : 4;
  auto wait_full = [&](int c) {
    mbar_wait(bar + 8 * (B_XF + 8 * wg + c), layer);
    mbar_wait(bar + 8 * (B_WF + c), layer);
  };
  auto peek = [&](int c) {
    const bool x = mbar_test(bar + 8 * (B_XF + 8 * wg + c), layer), y = mbar_test(bar + 8 * (B_WF + c), layer);
    return x && y;
  };
  const uint64_t da0 = mkdesc(sb, TR ? 8192 : 16, 1024, 1), db0 = mkdesc(sb, 8192, 1024, 1);
  uint32_t xt = wg ? 0xfedcba98u : 0x21043210u;
  uint64_t wt = 0x0816131005161310ull;
  uint64_t da = da0 + ((xt & 15) << 9), db = db0 + (16 << 9);
  auto issue = [&](int c, int first) {
    wg_fence();
#pragma unroll
    for (int ks = 0; ks < 4; ks++) wgmma_ss<192, TR ? 1 : 0, 1>(acc, da + (TR ? ks * 128 : ks * 2), db + ks * 128, !first || ks != 0);
    wg_commit();
    xt >>= 4; wt >>= 8;
    da = da0 + ((xt & 15) << 9); db = db0 + (((uint32_t)wt & 31) << 9);
  };
  wait_full(0);
  bool ready = peek(1);
  issue(0, 1);
  TSW(0);
#pragma unroll 1
  for (int c = 1; c < cut; c++) {
    if (!ready) wait_full(c);
    issue(c, 0);
    ready = peek(c + 1);
    wg_wait<1>();
    if (leader) mbar_arrive(bar + 8 * (B_DN + 8 * wg + c - 1));
    if (wg == 1 && c == cut - 1) {
      wg_wait<0>();
      if (leader) mbar_arrive(bar + 8 * (B_DN + 8 + c));
    }
    if (c == statpos) {
      mbar_wait(bar + 8 * (copy ? B_SC : B_XF + 8 * wg + hg), layer);
      uint32_t A[16];
      const uint32_t xb = sb + (copy ? P_R : 8 * wg + hg) * PG;
#pragma unroll
      for (int ks = 0; ks < 4; ks++) {
        if (!TR) {
          const int row = 16 * w + (lane & 15), kc = 2 * ks + (lane >> 4);
          ldsm4(&A[4 * ks], xb + row * 128 + ((kc ^ (row & 7)) << 4));
        } else {
          const int k = 16 * ks + (lane & 7) + 8 * (lane >> 4), pc = 2 * w + ((lane >> 3) & 1);
          ldsm4t(&A[4 * ks], xb + k * 128 + ((pc ^ (k & 7)) << 4));
        }
      }
      float s0 = 0.f, q0 = 0.f, s1 = 0.f, q1 = 0.f;
#pragma unroll
      for (int i = 0; i < 16; i += 2) {
        const float a = bf_lo(A[i]), b = bf_hi(A[i]), c_ = bf_lo(A[i + 1]), d = bf_hi(A[i + 1]);
        s0 += a + b; q0 = fmaf(a, a, q0); q0 = fmaf(b, b, q0);
        s1 += c_ + d; q1 = fmaf(c_, c_, q1); q1 = fmaf(d, d, q1);
      }
#pragma unroll
      for (int o = 1; o <= 2; o <<= 1) {
        s0 += __shfl_xor_sync(~0u, s0, o); q0 += __shfl_xor_sync(~0u, q0, o);
        s1 += __shfl_xor_sync(~0u, s1, o); q1 += __shfl_xor_sync(~0u, q1, o);
      }
      if (t < 2)
        asm volatile("red.relaxed.gpu.global.add.v4.f32 [%0], {%1,%2,%3,%4};" ::"l"(g_rows + layer * LSEQ + blk * 64 + 16 * w + g + 8 * t),
                     "f"(t ? s1 : s0), "f"(t ? q1 : q0), "f"(1.f), "f"(0.f) : "memory");
    }
  }
  if (wg == 1) {
#pragma unroll 1
    for (int c = cut; c < 8; c++) wait_full(c);
    ready = true;
    bar_sync(5, 256);
  }
#pragma unroll 1
  for (int c = cut; c < 8; c++) {
    if (!ready) wait_full(c);
    issue(c, 0);
    if (wg == 1) {
      wg_wait<2>();
      if (leader && c >= cut + 2) mbar_arrive(bar + 8 * (B_DN + 8 + c - 2));
    } else if (c == 7) {
      bar_arrive(5, 256);
    } else {
      ready = peek(c + 1);
      wg_wait<1>();
      if (leader && c < 6) mbar_arrive(bar + 8 * (B_DN + c - 1));
    }
  }
  mbar_wait(bar + 8 * (B_LN + wg), layer);
  const float4 ln = lds128f(sb + ln_off(wg) + (8 * w + g) * 16);
  mean0 = ln.x; rstd0 = ln.y; mean1 = ln.z; rstd1 = ln.w;
  wg_wait<0>();
  acc_fence<96>(acc);
  if (leader) mbar_arrive(bar + 8 * (B_DN + 8 * wg + 7));
}

__device__ __forceinline__ void attn_phase(const Params& p, uint32_t sb, int layer, int rb, int hg, int wg, int w) {
  const int lane = opaque_tid() & 31;
  const int g = lane >> 2, t = lane & 3;
  const uint32_t bar = sb + SM_BAR;
  const int blk = 16 * wg + rb;
  float acc[96];
  float2 cs[24];
  float mean0, mean1, rstd0, rstd1;
  if (layer) gemm_section<true>(acc, mean0, mean1, rstd0, rstd1, sb, blk, hg, wg, w, lane);
  else gemm_section<false>(acc, mean0, mean1, rstd0, rstd1, sb, blk, hg, wg, w, lane);
  TSW(1);
#pragma unroll
  for (int j = 8; j < 24; j++) cs[j] = lds64f(sb + SM_CS + 4 * (8 * j + 2 * t));
  const uint32_t kvx = sb + (wg ? 22 : 0) * PG;

  uint32_t kb[4][8], vb[4][8], qa[4][4];
  {
    const float nm0 = -mean0 * rstd0, nm1 = -mean1 * rstd1;
    const int st_row = 16 * w + (lane & 7) + 8 * ((lane >> 3) & 1);
    const uint32_t st_base = kvx + st_row * 256;
    const bool sender = (w == 3 && blk < 31);
    uint4* halo = &g_halo[(blk * 8 + hg) * 256 + lane];
    uint32_t r[4][2][4];
#pragma unroll
    for (int h = 0; h < 4; h++) {
#pragma unroll
      for (int kv = 0; kv < 2; kv++) {
#pragma unroll
        for (int dh = 0; dh < 2; dh++) {
          const int j = 8 + kv * 8 + 2 * h + dh;
          const float2 c2 = cs[j];
          const float v0 = fmaf(acc[4 * j + 0], rstd0, nm0 * c2.x), v1 = fmaf(acc[4 * j + 1], rstd0, nm0 * c2.y);
          const float v2 = fmaf(acc[4 * j + 2], rstd1, nm1 * c2.x), v3 = fmaf(acc[4 * j + 3], rstd1, nm1 * c2.y);
          r[h][kv][2 * dh] = packbf(v0, v1);
          r[h][kv][2 * dh + 1] = packbf(v2, v3);
        }
      }
      if (sender) {
        stg128(halo + (2 * h) * 32, make_uint4(r[h][0][0], r[h][0][2], r[h][0][1], r[h][0][3]));
        stg128(halo + (2 * h + 1) * 32, make_uint4(r[h][1][0], r[h][1][1], r[h][1][2], r[h][1][3]));
      }
    }
#pragma unroll
    for (int j = 0; j < 8; j++) cs[j] = lds64f(sb + SM_CS + 4 * (8 * j + 2 * t));
    mbar_wait(bar + 8 * (B_DN + 7), layer);
#pragma unroll
    for (int h = 0; h < 4; h++) {
#pragma unroll
      for (int kv = 0; kv < 2; kv++) {
        const int chunk = 4 * h + 2 * kv + (lane >> 4);
        if (w < 3) stsm4(st_base + (((chunk & 8) | ((chunk ^ st_row) & 7)) << 4), r[h][kv][0], r[h][kv][1], r[h][kv][2], r[h][kv][3]);
      }
      kb[h][4] = r[h][0][0]; kb[h][5] = r[h][0][2]; kb[h][6] = r[h][0][1]; kb[h][7] = r[h][0][3];
      vb[h][4] = movm_t(r[h][1][0]); vb[h][5] = movm_t(r[h][1][1]); vb[h][6] = movm_t(r[h][1][2]); vb[h][7] = movm_t(r[h][1][3]);
    }
#pragma unroll
    for (int h = 0; h < 4; h++) {
#pragma unroll
      for (int dh = 0; dh < 2; dh++) {
        const int j = 2 * h + dh;
        const float2 c2 = cs[j];
        qa[h][2 * dh] = packbf(fmaf(-mean0, c2.x, acc[4 * j + 0]), fmaf(-mean0, c2.y, acc[4 * j + 1]));
        qa[h][2 * dh + 1] = packbf(fmaf(-mean1, c2.x, acc[4 * j + 2]), fmaf(-mean1, c2.y, acc[4 * j + 3]));
      }
    }
  }
  bar_sync(2 + wg, 128);
  TSW(2);
  {
    const uint32_t prev_base = kvx + (16 * w - 16) * 256;
    const int mi = lane >> 3;
    const int r = 8 * (mi >> 1) + (lane & 7), r2 = 8 * (mi & 1) + (lane & 7);
    if (w != 0) {
#pragma unroll
      for (int h = 0; h < 4; h++) {
        const int ch = 4 * h + (mi & 1), ch2 = 4 * h + 2 + (mi >> 1);
        ldsm4(&kb[h][0], prev_base + r * 256 + (((ch & 8) | ((ch ^ r) & 7)) << 4));
        ldsm4t(&vb[h][0], prev_base + r2 * 256 + (((ch2 & 8) | ((ch2 ^ r2) & 7)) << 4));
      }
    } else if (blk > 0) {
      uint4* src = &g_halo[((blk - 1) * 8 + hg) * 256 + lane];
      uint4 hv[8];
      int it = 0;
      bool ok;
      do {
        ok = true;
#pragma unroll
        for (int i = 0; i < 8; i++) hv[i] = ld_tagged(src + i * 32);
#pragma unroll
        for (int i = 0; i < 8; i++) ok = ok && hv[i].x != UNSET;
      } while (!__all_sync(~0u, ok) && ++it < (1 << 20));
      if (layer == 0) {
#pragma unroll
        for (int i = 0; i < 2; i++) stg128(src + i * 128 + (lane >> 1) * 6, make_uint4(UNSET, UNSET, UNSET, UNSET));
      }
#pragma unroll
      for (int h = 0; h < 4; h++) {
        kb[h][0] = hv[2 * h].x; kb[h][1] = hv[2 * h].y; kb[h][2] = hv[2 * h].z; kb[h][3] = hv[2 * h].w;
        vb[h][0] = movm_t(hv[2 * h + 1].x); vb[h][1] = movm_t(hv[2 * h + 1].y);
        vb[h][2] = movm_t(hv[2 * h + 1].z); vb[h][3] = movm_t(hv[2 * h + 1].w);
      }
    } else {
#pragma unroll
      for (int h = 0; h < 4; h++)
#pragma unroll
        for (int k = 0; k < 4; k++) kb[h][k] = vb[h][k] = 0u;
    }
    TSW(3);
  }
  mbar_wait(bar + 8 * (B_DN + 15), layer);
  TSW(4);

  const bool first = (blk == 0 && w == 0);
  const int e = t - (g >> 1);
  const bool par = g & 1, epos = e >= 1;
  const uint32_t pmask = par ? 0xffff0000u : 0x0000ffffu;
  const uint32_t mB0 = epos ? pmask : 0u, mB1 = epos ? 0u : pmask;
  const float cl2 = 0.25f * 1.4426950408889634f;
  const float sc0 = rstd0 * cl2, sc1 = rstd1 * cl2;
  const float NEG = -INFINITY;
  float vA0[4], vB0[4], vA1[4], vB1[4];
#pragma unroll
  for (int h = 0; h < 4; h++) {
    float S[4][4];
#pragma unroll
    for (int j = 0; j < 4; j++) {
      S[j][0] = S[j][1] = S[j][2] = S[j][3] = 0.f;
      mma_bf16(S[j], qa[h], kb[h][2 * j], kb[h][2 * j + 1]);
    }
    vA0[h] = par ? S[1][1] : S[1][0];
    vB0[h] = epos ? (par ? S[0][1] : S[0][0]) : (par ? S[2][1] : S[2][0]);
    vA1[h] = par ? S[2][3] : S[2][2];
    vB1[h] = epos ? (par ? S[1][3] : S[1][2]) : (par ? S[3][3] : S[3][2]);
    if (first) { vA0[h] = NEG; if (epos) { vB0[h] = NEG; vB1[h] = NEG; } }
  }
  float m0[4], m1[4];
#pragma unroll
  for (int h = 0; h < 4; h++) { m0[h] = fmaxf(vA0[h], vB0[h]); m1[h] = fmaxf(vA1[h], vB1[h]); }
#pragma unroll
  for (int o = 1; o <= 2; o <<= 1) {
#pragma unroll
    for (int h = 0; h < 4; h++) {
      m0[h] = fmaxf(m0[h], __shfl_xor_sync(~0u, m0[h], o));
      m1[h] = fmaxf(m1[h], __shfl_xor_sync(~0u, m1[h], o));
    }
  }
  float O0[4][4], O1[4][4], Z[4][4];
#pragma unroll
  for (int h = 0; h < 4; h++) {
    const float mm0 = -m0[h] * sc0, mm1 = -m1[h] * sc1;
    const float pA0 = ex2(fmaf(vA0[h], sc0, mm0)), pB0 = ex2(fmaf(vB0[h], sc0, mm0));
    const float pA1 = ex2(fmaf(vA1[h], sc1, mm1)), pB1 = ex2(fmaf(vB1[h], sc1, mm1));
    const uint32_t hA0 = packbf(pA0, pA0), hB0 = packbf(pB0, pB0), hA1 = packbf(pA1, pA1), hB1 = packbf(pB1, pB1);
    const uint32_t P0[4] = {hB0 & mB0, 0u, hA0 & pmask, hB1 & mB0};
    const uint32_t P1[4] = {hB0 & mB1, hA1 & pmask, 0u, hB1 & mB1};
#pragma unroll
    for (int k = 0; k < 4; k++) O0[h][k] = O1[h][k] = Z[h][k] = 0.f;
    mma_bf16(O0[h], P0, vb[h][0], vb[h][1]); mma_bf16(O1[h], P0, vb[h][2], vb[h][3]); mma_bf16(Z[h], P0, 0x3f803f80u, 0x3f803f80u);
    mma_bf16(O0[h], P1, vb[h][4], vb[h][5]); mma_bf16(O1[h], P1, vb[h][6], vb[h][7]); mma_bf16(Z[h], P1, 0x3f803f80u, 0x3f803f80u);
  }
  if (lane == 0) mbar_arrive(bar + 8 * (B_OST + wg));
  uint4* op = (uint4*)g_O + ((layer * 32 + blk) * 8 + hg) * 512 + 64 * t + 16 * w + g;
#pragma unroll
  for (int h = 0; h < 4; h += 2) {
    const float i0 = rcp_approx(Z[h][0]), i1 = rcp_approx(Z[h][2]), j0 = rcp_approx(Z[h + 1][0]), j1 = rcp_approx(Z[h + 1][2]);
    stg128(op + 128 * h, make_uint4(packbf(O0[h][0] * i0, O0[h][1] * i0), packbf(O1[h][0] * i0, O1[h][1] * i0),
                                   packbf(O0[h + 1][0] * j0, O0[h + 1][1] * j0), packbf(O1[h + 1][0] * j0, O1[h + 1][1] * j0)));
    stg128(op + 128 * h + 8, make_uint4(packbf(O0[h][2] * i1, O0[h][3] * i1), packbf(O1[h][2] * i1, O1[h][3] * i1),
                                            packbf(O0[h + 1][2] * j1, O0[h + 1][3] * j1), packbf(O1[h + 1][2] * j1, O1[h + 1][3] * j1)));
  }
  TSW(5);
  __syncwarp();
  if (lane == 0) red_relaxed(&g_cnt[(C_O + layer * 32 + blk) * 32]);
  TSW(6);
}

__device__ __forceinline__ void conv_load(uint32_t* A, uint32_t pe);
__device__ __forceinline__ void proj_phase(const Params& p, uint32_t sb, int layer, int rb, int q, uint32_t* A0, uint32_t* A1) {
  const int lane = opaque_tid() & 31;
  const int wg = __shfl_sync(~0u, opaque_tid() >> 7, 0), w = __shfl_sync(~0u, (opaque_tid() >> 5) & 3, 0);
  const bool TR = layer != 0;
  const int t = lane & 3;
  const uint32_t bar = sb + SM_BAR;
  const uint32_t rbx = sb + (P_R + wg) * PG;
  const uint32_t rsrc = sb + (wg ? 2 : P_R) * PG;
  const int blk = 16 * wg + rb;
  mbar_wait(bar + 8 * (B_RF + wg), layer);
  mbar_wait(bar + 8 * B_WOF, layer);
  const uint32_t stg = sb + (wg ? SM_KGT : SM_STG);
  if (layer) {
    const uint32_t pe = sb + cv_pe(wg, 1) + 4 * (16 + 16 * w + (lane >> 2) - 2 * t);
    mbar_wait(bar + 8 * B_PE, 1);
    conv_load(A0, pe);
    conv_load(A1, pe + 2 * 4480);
    __syncwarp();
    if (lane == 0) mbar_arrive(bar + 8 * B_AL);
  } else {
#pragma unroll
    for (int i = 0; i < 68; i++) {
      asm volatile("mov.b32 %0, 0;" : "=r"(A0[i]));
      asm volatile("mov.b32 %0, 0;" : "=r"(A1[i]));
    }
  }
  bool clean = false, staged = false;
#pragma unroll 1
  for (int attempt = 0; attempt < MAX_RETRY; attempt++) {
  uint32_t res[16];
  if (!TR) {
#pragma unroll
    for (int j = 0; j < 8; j += 2) {
      const int mi = lane >> 3;
      const int row = 16 * w + (lane & 7) + 8 * (mi & 1), ch = j + (mi >> 1);
      ldsm4(&res[2 * j], rsrc + row * 128 + ((ch ^ (row & 7)) << 4));
    }
  } else {
#pragma unroll
    for (int j = 0; j < 8; j += 2) {
      const int mi = lane >> 3;
      const int line = 8 * (j + (mi >> 1)) + (lane & 7), pc = 2 * w + (mi & 1);
      ldsm4t(&res[2 * j], rsrc + line * 128 + ((pc ^ (line & 7)) << 4));
    }
  }
  float acc[32];
#pragma unroll
  for (int j = 0; j < 16; j++) { acc[2 * j] = bf_lo(res[j]); acc[2 * j + 1] = bf_hi(res[j]); }
  acc_fence<32>(acc);
  if (wg) mbar_wait(bar + 8 * B_PG, layer);
  const int wg2 = __shfl_sync(~0u, opaque_tid() >> 7, 0);
  const uint64_t da0 = mkdesc(sb, 1024, 128, 0), db0 = mkdesc(sb, 8192, 1024, 1);
#pragma unroll
  for (int c = 0; c < 4; c++) {
    mbar_wait(bar + 8 * (B_OF + 4 * wg + c), layer);
    if (c == 0) TSW(7);
    const uint64_t da = da0 + (uint32_t)(o_page(wg2, c) * 512);
#pragma unroll
    for (int ks = 0; ks < 8; ks++) {
      if (ks % 4 == 0) { if (ks) wg_commit(); if (wg2) wg_wait<0>(); wg_fence(); }
      wgmma_ss<64, 0, 1>(acc, da + ks * 128, db0 + wo_page(2 * c + (ks >> 2)) * 512 + (ks & 3) * 128, 1);
    }
    wg_commit();
  }
  if (wg) mbar_wait(bar + 8 * B_KG, 0);
  wg_wait<0>();
  acc_fence<32>(acc);
  TSW(8);
  if (!clean) {
    const float chk = acc[0] + acc[2];
    clean = __all_sync(~0u, chk == chk);
    if (clean && lane == 0) mbar_arrive(bar + 8 * (B_PDONE + wg));
  }
  float s0 = 0.f, q0 = 0.f, s1 = 0.f, q1 = 0.f;
  uint32_t o[16];
#pragma unroll
  for (int j = 0; j < 8; j++) {
    const float a = acc[4 * j], b = acc[4 * j + 1], c = acc[4 * j + 2], d = acc[4 * j + 3];
    o[2 * j] = packbf(a, b);
    o[2 * j + 1] = packbf(c, d);
    s0 += a + b; q0 = fmaf(a, a, q0); q0 = fmaf(b, b, q0);
    s1 += c + d; q1 = fmaf(c, c, q1); q1 = fmaf(d, d, q1);
  }
#pragma unroll
  for (int j = 0; j < 8; j += 2) {
    const int mi = lane >> 3;
    const int line = 8 * (j + (mi >> 1)) + (lane & 7), pc = 2 * w + (mi & 1);
    stsm4t(rbx + line * 128 + ((pc ^ (line & 7)) << 4), o[2 * j], o[2 * j + 1], o[2 * j + 2], o[2 * j + 3]);
  }
#pragma unroll
  for (int o2 = 1; o2 <= 2; o2 <<= 1) {
    s0 += __shfl_xor_sync(~0u, s0, o2); q0 += __shfl_xor_sync(~0u, q0, o2);
    s1 += __shfl_xor_sync(~0u, s1, o2); q1 += __shfl_xor_sync(~0u, q1, o2);
  }
  {
    const int i = 2 * (lane >> 2) + (t & 1), k = (i * 11) >> 5;
    const float v = (t == 0) ? s0 : (t == 1) ? q0 : (t == 2) ? s1 : q1;
    sts32f(stg + k * 128 + (2 * w + (t >> 1)) * 16 + (i - 3 * k) * 4, v);
  }
  TSW(9);
  fence_async_smem();
  if (attempt == 0 && clean) {
    staged = true;
    __syncwarp();
    if (lane == 0) mbar_arrive(bar + 8 * (B_STG + wg));
  }
  if (!bar_or(2 + wg, 128, !clean)) break;
  const int rtp = mbar_test(bar + 8 * (B_RT + wg), 0);
  bool unset = false;
#pragma unroll
  for (int i = 0; i < 4; i++) unset |= lds32(sb + o_page(wg, i) * PG + (32 * w + lane) * 128) == UNSET;
  if (!bar_or(2 + wg, 128, unset)) break;
  if (w == 0 && elect_one()) {
    fence_async_smem();
    mbar_expect(bar + 8 * (B_RT + wg), 9 * PG);
    if (layer == 0) tma_ld(rsrc, &p.mapX, q * 64, blk * 64, bar + 8 * (B_RT + wg));
    else tma_ld(rsrc, &p.mapXT, blk * 64, DM + q * 64, bar + 8 * (B_RT + wg));
#pragma unroll 1
    for (int c = 0; c < 4; c++) bulk_ld(sb + o_page(wg, c) * PG, g_O + ((layer * 32 + blk) * 4 + c) * PG, 2 * PG, bar + 8 * (B_RT + wg));
  }
  mbar_wait(bar + 8 * (B_RT + wg), rtp);
  RETRY(0);
  }
  if (!clean && lane == 0) mbar_arrive(bar + 8 * (B_PDONE + wg));
  if (!staged && lane == 0) mbar_arrive(bar + 8 * (B_STG + wg));
  TSW(10);
}

__device__ __forceinline__ void conv_load(uint32_t* A, uint32_t pe) {
#pragma unroll
  for (int m = 0; m < 17; m++) {
    A[4 * m + 2] = lds32(pe + 4 * (64 * m - 8));
    A[4 * m + 0] = lds32(pe + 4 * (64 * m));
    A[4 * m + 1] = lds32(pe + 4 * (64 * m + 8));
    asm volatile("mov.b32 %0, %1;" : "=r"(A[4 * m + 3]) : "r"(A[4 * m + 0]));
  }
}
template <int M> __device__ __forceinline__ void conv_tri(float* acc, const uint32_t* A, uint64_t d) {
  if constexpr (M < 16) {
    wgmma_rs<64 - 8 * (M / 2), 0>(acc, A + 4 * M, d + (uint64_t)(64 + 4 * M), M != 0);
    conv_tri<M + 1>(acc, A, d);
  }
}
__device__ __forceinline__ void conv_mma0(float* acc, const uint32_t* A, uint64_t d) {
  wg_fence();
  conv_tri<0>(acc, A, d);
  wg_commit();
}
__device__ __forceinline__ void conv_mma1(float* acc, const uint32_t* A, uint64_t d, uint64_t ds, uint64_t df) {
  wg_fence();
#pragma unroll
  for (int m = 0; m < 17; m++) wgmma_rs<64, 0>(acc, A + 4 * m, d + (uint64_t)(4 * m), m != 0);
  wgmma_ss<64, 1, 0>(acc, ds, df, 1);
  wgmma_ss<64, 1, 0>(acc, ds + 128, df + 128, 1);
  wg_commit();
}
__device__ __forceinline__ void conv_store(float* acc, uint32_t pb, uint32_t over, int w) {
  acc_fence<32>(acc);
  const int l = opaque_tid() & 31, mt = l >> 3;
  int c = 2 * (63 - 8 * (mt >> 1) - (l & 7) + w) + (mt & 1);
  c ^= (c >> 3) & 1;
  const uint32_t a0 = pb + c * 16;
#pragma unroll
  for (int j = 0; j < 8; j += 2)
    stsm4t(j == 0 ? (c < 128 ? a0 : over + (c - 128) * 16) : a0 - 256 * j, packbf(acc[4 * j], acc[4 * j + 1]), packbf(acc[4 * j + 2], acc[4 * j + 3]),
           packbf(acc[4 * j + 4], acc[4 * j + 5]), packbf(acc[4 * j + 6], acc[4 * j + 7]));
}
__device__ __forceinline__ void conv_sums(uint32_t sb, int lc, int ht) {
  const int m = ht - 1;
  uint4 v[2][3];
#pragma unroll
  for (int c = 0; c < 2; c++)
#pragma unroll
    for (int k = 0; k < 3; k++) {
      const int mm = m - 1 + k;
      v[c][k] = lds128(sb + cv_u(lc + c) + (mm >= 0 ? (mm & 1) * CV_UH + (127 - (mm >> 1)) * 16 : 128 * 16));
    }
  const int ce = m + 2, co = m + 1;
#pragma unroll
  for (int c = 0; c < 2; c++) {
    const uint32_t x[8] = {v[c][0].z, v[c][0].w, v[c][1].x, v[c][1].y, v[c][1].z, v[c][1].w, v[c][2].x, v[c][2].y};
    float pv[16];
#pragma unroll
    for (int k = 0; k < 8; k++) { pv[2 * k] = bf_lo(x[k]); pv[2 * k + 1] = bf_hi(x[k]); }
    float t2[15], t4[13], s9[8], s7[8];
#pragma unroll
    for (int i = 0; i < 15; i++) t2[i] = pv[i] + pv[i + 1];
#pragma unroll
    for (int i = 0; i < 13; i++) t4[i] = t2[i] + t2[i + 2];
#pragma unroll
    for (int i = 0; i < 8; i++) {
      s9[i] = (t4[i] + t4[i + 4]) + pv[i + 8];
      s7[i] = (t4[i + 1] + t2[i + 5]) + pv[i + 7];
    }
    const uint4 e4 = make_uint4(packbf(s9[0], s9[1]), packbf(s9[2], s9[3]), packbf(s9[4], s9[5]), packbf(s9[6], s9[7]));
    if (ce < 128) sts128(sb + cv_se(lc + c) + ((ce ^ ((ce >> 3) & 7)) << 4), e4);
    else sts128(sb + cv_se(lc + c), make_uint4(0, 0, 0, 0));
    sts128(sb + cv_so(lc + c) + ((co ^ ((co >> 3) & 7)) << 4),
           make_uint4(packbf(s7[0], s7[1]), packbf(s7[2], s7[3]), packbf(s7[4], s7[5]), packbf(s7[6], s7[7])));
  }
}

template <int HALF, int NCH, int STEP = 1>
__device__ __forceinline__ void conv_epi(uint32_t sb, bf16* out, int lc, int c) {
  uint4 v[NCH][4], xr[NCH];
  const uint32_t sw = (c ^ ((c >> 3) & 1)) * 16;
#pragma unroll
  for (int u = 0; u < NCH; u++) {
#pragma unroll
    for (int k = 0; k < 4; k++) v[u][k] = lds128(sb + (HALF ? cv_pb1(lc + STEP * u, k) : cv_pb0(lc + STEP * u, k)) + sw);
    xr[u] = lds128(sb + cv_x(HALF, lc + STEP * u) + c * 16);
  }
#pragma unroll
  for (int u = 0; u < NCH; u++) {
    uint4 o;
    o.x = hadd2(xr[u].x, hadd2(hadd2(v[u][0].x, v[u][1].x), hadd2(v[u][2].x, v[u][3].x)));
    o.y = hadd2(xr[u].y, hadd2(hadd2(v[u][0].y, v[u][1].y), hadd2(v[u][2].y, v[u][3].y)));
    o.z = hadd2(xr[u].z, hadd2(hadd2(v[u][0].z, v[u][1].z), hadd2(v[u][2].z, v[u][3].z)));
    o.w = hadd2(xr[u].w, hadd2(hadd2(v[u][0].w, v[u][1].w), hadd2(v[u][2].w, v[u][3].w)));
    stg128(out + cv_chan(0, lc + STEP * u) * LSEQ + HALF * 1024 + c * 8, o);
  }
}

__device__ __forceinline__ bool prep_valid(const uint4 (&st)[6], const uint4 (&xr)[4]) {
  const uint32_t n = __float_as_uint(8.f);
  return st[0].w == n && st[1].w == n && st[2].w == n && st[3].w == n && st[4].w == n && (st[5].w | st[5].y | st[5].z) == n &&
         xr[0].x != UNSET && xr[1].x != UNSET && xr[2].x != UNSET && xr[3].x != UNSET;
}
template <int HALF>
__device__ __forceinline__ void conv_prep(uint32_t sb, int layer, int cta, int i) {
  uint4 st[6], xr[4];
  const uint4* sp = (const uint4*)g_stats + (layer * 32 + HALF * 16 + (i >> 3)) * 48 + (i & 7);
  const uint4* xp = (const uint4*)g_xT + (2 * layer * DM + 2 * cta) * (LSEQ / 8) + HALF * 128 + i;
  if (!HALF) { pin(sp); pin(xp); }
  mbar_wait(sb + SM_BAR + 8 * (B_GB + HALF), layer);
  if (!HALF) TSW(13);
  auto fetch = [&]() {
#pragma unroll
    for (int k = 0; k < 6; k++) st[k] = ld_tagged(sp + 8 * k);
#pragma unroll
    for (int k = 0; k < 4; k++) xr[k] = ld_tagged(xp + cv_chan(0, k) * (LSEQ / 8));
  };
  if (HALF) {
#pragma unroll
    for (int k = 0; k < 6; k++) st[k] = lds128(sb + CV_ST + (i >> 3) * 768 + k * 128 + (i & 7) * 16);
#pragma unroll
    for (int k = 0; k < 4; k++) xr[k] = lds128(sb + cv_x(1, k) + i * 16);
  } else {
    fetch();
  }
  int it = 0;
  while (!__all_sync(~0u, prep_valid(st, xr)) && ++it < MAX_RETRY) { fetch(); RETRY(1); }
  if (!HALF || it) {
#pragma unroll
    for (int k = 0; k < 4; k++) sts128(sb + cv_x(HALF, k) + i * 16, xr[k]);
  }
  const uint32_t v[16] = {st[0].x, st[0].y, st[0].z, st[1].x, st[1].y, st[1].z, st[2].x, st[2].y, st[2].z, st[3].x, st[3].y, st[3].z, st[4].x, st[4].y, st[4].z, st[5].x};
  uint32_t rs[4], nm[4];
#pragma unroll
  for (int k = 0; k < 4; k++) {
    const float m0 = __uint_as_float(v[4 * k]) * (-1.f / DM), m1 = __uint_as_float(v[4 * k + 2]) * (-1.f / DM);
    const float r0 = rsqrt_approx(fmaxf(fmaf(__uint_as_float(v[4 * k + 1]), 1.f / DM, -m0 * m0), 0.f) + 1e-5f);
    const float r1 = rsqrt_approx(fmaxf(fmaf(__uint_as_float(v[4 * k + 3]), 1.f / DM, -m1 * m1), 0.f) + 1e-5f);
    rs[k] = packbf(r0, r1);
    nm[k] = packbf(m0 * bf_lo(rs[k]), m1 * bf_hi(rs[k]));
  }
  const uint32_t ud = sb + (i & 1) * CV_UH + (127 - 64 * HALF - (i >> 1)) * 16;
#pragma unroll
  for (int k = 0; k < 4; k++)
    sts128(ud + cv_u(k), make_uint4(hfma2(xr[k].x, rs[0], nm[0]), hfma2(xr[k].y, rs[1], nm[1]), hfma2(xr[k].z, rs[2], nm[2]), hfma2(xr[k].w, rs[3], nm[3])));
  fence_async_smem();
}

__device__ __forceinline__ void conv_phase(const Params& p, uint32_t sb, int layer, int cta, uint32_t* A0, uint32_t* A1) {
  const int tid = opaque_tid();
  const int wg = __shfl_sync(~0u, tid >> 7, 0), w = __shfl_sync(~0u, (tid >> 5) & 3, 0);
  const uint32_t bar = sb + SM_BAR;
  constexpr int CH2 = 4 * PG;
  bf16* xout = g_xT + ((2 * layer + 1) * DM + 2 * cta) * LSEQ;
  float acc[32];
  const uint32_t pe = sb + cv_pe(wg, 0) + 4 * (16 + 16 * w + ((tid & 31) >> 2) - 2 * (tid & 3));
  if (layer == 0) {
    mbar_wait(bar + 8 * (B_PDONE + 1), layer);
    mbar_wait(bar + 8 * B_PE, layer);
    conv_load(A0, pe);
    conv_load(A1, pe + CH2);
  }
  TSW(19);
  const uint64_t d0 = mkdesc(sb + cv_u(wg), CV_UH, 128, 0), d1 = d0 + (CH2 >> 4);
  mbar_wait(bar + 8 * B_U, layer);
  TSW(12);
  if (wg == 1) bar_sync(5, 256);
  conv_mma0(acc, A0, d0);
  if (wg == 0) bar_arrive(5, 256);
  mbar_wait(bar + 8 * (B_PDONE + 1), layer);
  {
    const int l = opaque_tid() & 31;
    if ((l & 15) < 2 * w) sts128(sb + cv_pb0(wg + 2 * (l >> 4), w) + (l & 15) * 16, make_uint4(0, 0, 0, 0));
  }
  wg_wait<0>();
  conv_store(acc, sb + cv_pb0(wg, w), sb + cv_pb1(wg, w), w);
  conv_mma0(acc, A1, d1);
  wg_wait<0>();
  conv_store(acc, sb + cv_pb0(2 + wg, w), sb + cv_pb1(2 + wg, w), w);
  TSW(13);
  bar_sync(2 + wg, 128);
  conv_epi<0, 2, 2>(sb, xout, wg, opaque_tid() & 127);
  TSW(14);
  mbar_arrive(bar + 8 * B_PUB);
  const uint64_t ds = mkdesc(sb + cv_se(wg), 8192, 1024, 1), df = mkdesc(sb + cv_fa(wg), 512, 128, 0);
  if (wg == 0) mbar_wait(bar + 8 * B_U1, layer);
  else bar_sync(6, 256);
  TSW(15);
  conv_mma1(acc, A0, d0, ds, df);
  if (wg == 0) bar_arrive(6, 256);
  wg_wait<0>();
  conv_store(acc, sb + cv_pb1(wg, w), sb + cv_dump(wg), w);
  TSW(16);
  bar_sync(2 + wg, 128);
  conv_epi<1, 1>(sb, xout, wg, opaque_tid() & 127);
  mbar_arrive(bar + 8 * (B_PUB + 1));
  conv_mma1(acc, A1, d1, ds + 512, df + (CH2 >> 4));
  wg_wait<0>();
  conv_store(acc, sb + cv_pb1(2 + wg, w), sb + cv_dump(2 + wg), w);
  TSW(17);
  bar_sync(2 + wg, 128);
  conv_epi<1, 1>(sb, xout, 2 + wg, opaque_tid() & 127);
  mbar_arrive(bar + 8 * (B_PUB + 2));
  TSW(18);
}

__device__ __forceinline__ void final_tile(const Params& p, uint32_t buf, int ch0, int pos0, int barid) {
  const int tid = opaque_tid() & 127, lane = tid & 31, w = tid >> 5;
  const uint4* src = (const uint4*)(g_xT + (3 * DM + ch0 + (tid >> 3)) * LSEQ + pos0) + (tid & 7);
  const int ch = tid >> 3, row = 4 * (ch & 6) + 2 * (ch >> 3) + (ch & 1);
  const uint32_t dst = buf + row * 128;
  const uint32_t ld = buf + lane * 128;
  bf16* out = p.out + (pos0 + 16 * w + (lane >> 2)) * DM + ch0 + 8 * (lane & 3);
  uint4 a, b;
  int it = 0;
  do {
    if (it) RETRY(2);
    a = ld_tagged(src); b = ld_tagged(src + 16 * LSEQ / 8);
  } while (!__all_sync(~0u, a.x != UNSET && b.x != UNSET) && ++it < (1 << 20));
  sts128(dst + (((tid ^ row) & 7) << 4), a);
  sts128(dst + 512 + (((tid ^ row ^ 4) & 7) << 4), b);
  bar_sync(barid, 128);
#pragma unroll
  for (int h = 0; h < 2; h++) {
    uint32_t r[4];
    ldsm4t(r, ld + ((((2 * w + h) ^ lane) & 7) << 4));
    *(uint4*)(out + 8 * h * DM) = make_uint4(r[0], r[1], r[2], r[3]);
  }
}

struct cplx { float r, i; };
__device__ __forceinline__ cplx cmul(cplx a, cplx b) { return {fmaf(a.r, b.r, -a.i * b.i), fmaf(a.r, b.i, a.i * b.r)}; }
__device__ __forceinline__ cplx csqr(cplx a) { return {fmaf(a.r, a.r, -a.i * a.i), (a.r + a.r) * a.i}; }
__device__ __forceinline__ cplx cexp_l(float ar2, float ai, float l) {
  const float m = ex2(ar2 * l);
  const float x = ai * l;
  return {m * __cosf(x), m * __sinf(x)};
}

__device__ __forceinline__ void colsum_cta(const Params& p, uint32_t sb, int j, int tid) {
  const uint32_t bar = sb + SM_BAR;
  auto ld = [&](int i) {
    mbar_expect(bar + 8 * i, 3 * PG);
    tma_ld3(sb + (i & 7) * 3 * PG, &p.mapW3, (2 * j + (i & 1)) * 64, (i >> 1) * 64, 0, bar + 8 * i);
  };
  if (tid == 384) {
#pragma unroll
    for (int i = 0; i < 24; i++) mbar_init(bar + 8 * i, i < 16 ? 1 : 12);
    asm volatile("fence.mbarrier_init.release.cluster;" ::: "memory");
    fence_async_smem();
#pragma unroll 1
    for (int i = 0; i < 8; i++) ld(i);
  }
  const unsigned ep = ld_relaxed(&g_cnt[C_CS * 32]);
  bar_sync(0, NTHREADS);
  if (tid == 384) {
#pragma unroll 1
    for (int i = 8; i < 16; i++) { mbar_wait(bar + 8 * (8 + i), 0); fence_async_smem(); ld(i); }
  }
  if (tid < 384) {
    const int lane = tid & 31, cc = tid & 7, r0 = (tid >> 3) & 15, part = tid >> 7;
    const uint32_t id = ((lane >> 2) == 2 * (lane & 3) ? 0x3f80u : 0u) | ((lane >> 2) == 2 * (lane & 3) + 1 ? 0x3f800000u : 0u);
    const uint32_t src = sb + part * PG + r0 * 128 + ((cc ^ (r0 & 7)) << 4);
    float s[2][2][4];
#pragma unroll
    for (int i = 0; i < 16; i++) s[i >> 3][(i >> 2) & 1][i & 3] = 0.f;
#pragma unroll 1
    for (int i2 = 0; i2 < 16; i2 += 2) {
#pragma unroll
      for (int h = 0; h < 2; h++) {
        const int i = i2 + h;
        mbar_wait(bar + 8 * i, 0);
        uint4 v[4];
#pragma unroll
        for (int k = 0; k < 4; k++) v[k] = lds128(src + (i & 7) * 3 * PG + k * 2048);
#pragma unroll
        for (int k = 0; k < 4; k++) {
          const uint32_t a[4] = {v[k].x, v[k].y, v[k].z, v[k].w};
          mma_bf16(s[h][0], a, id, 0u);
          mma_bf16(s[h][1], a, 0u, id);
        }
        __syncwarp();
        if (i < 8 && lane == 0) mbar_arrive(bar + 8 * (16 + i));
      }
    }
    const uint32_t red = sb + 24 * PG;
#pragma unroll
    for (int h = 0; h < 2; h++)
#pragma unroll
      for (int k = 0; k < 2; k++) sts128f(red + (r0 * 384 + h * 192 + part * 64 + cc * 8 + k * 4) * 4, s[h][k][0], s[h][k][1], s[h][k][2], s[h][k][3]);
    bar_sync(1, 384);
    float tot = 0.f;
#pragma unroll
    for (int k = 0; k < 16; k++) tot += __uint_as_float(lds32(red + (k * 384 + tid) * 4));
    asm volatile("st.relaxed.gpu.global.v2.u32 [%0], {%1,%2};" ::"l"(&g_colsum[j * 384 + tid]), "r"(__float_as_uint(tot)), "r"(ep / NCTA + 1) : "memory");
    const uint4 u = make_uint4(UNSET, UNSET, UNSET, UNSET);
    if (tid < 256) {
#pragma unroll 1
      for (int s = 0; s < 4; s++) {
        const int n = (s == 1 || s == 2) ? 32 : 16;
        uint4* buf = s == 1 ? (uint4*)g_O + 131072 : (uint4*)g_xT + (s + !s) * 131072;
#pragma unroll 4
        for (int i = 0; i < n; i++) stg128(buf + (j * n + i) * 1024 + (tid >> 1) * 8 + (tid & 1), u);
        if (n == 16) {
#pragma unroll 4
          for (int i = 0; i < 8; i++) stg128(buf + (256 + j * 64 + i * 8 + (tid >> 5)) * 256 + (s ? 0 : 128) + ((tid & 31) >> 1) * 8 + (tid & 1), u);
        }
        if (s == 3) {
#pragma unroll 4
          for (int i = 0; i < 32; i++) stg128(buf + (256 + j * 64 + 2 * i + (tid >> 7)) * 256 + 128 + (tid & 127), u);
        }
        bar_sync(2, 256);
        if (tid == 32 * s) red_release(&g_cnt[(C_R + s) * 32]);
      }
    }
  }
}

constexpr int KB = 4, KW = 2;
struct ModeIn { uint32_t ar, ai, br, bi, cr, ci; bf16 logdt; };
__device__ __forceinline__ ModeIn load_modes(const Params& p, int d, int m) {
  const int i = d * 64 + m;
  return {((const uint32_t*)p.a_re)[i], ((const uint32_t*)p.a_im)[i], ((const uint32_t*)p.b_re)[i], ((const uint32_t*)p.b_im)[i],
          ((const uint32_t*)p.c_re)[i], ((const uint32_t*)p.c_im)[i], p.log_dt[d]};
}
__device__ __forceinline__ void kernel_gen(uint32_t sb, int cta, int ht, ModeIn in, const ModeIn& in1) {
  const uint32_t bst = sb + SM_KGB + ((ht & 63) >> 2) * 144 + (ht & 3) * 4 + (ht >> 6) * 16;
  const uint64_t db = mkdesc(sb + SM_KGB, 144, 2304, 0);
  const float e0 = (float)(8 * (((ht & 32) >> 1) + ((ht & 31) >> 2)));
  float T[20];
#pragma unroll
  for (int i = 0; i < 20; i++) T[i] = 0.f;
  float k0 = 0.f;
#pragma unroll 1
  for (int pass = 0; pass < 4; pass++) {
    {
      const int sh = (pass & 1) ? 0 : 16;
      auto val = [&](uint32_t v) { return __uint_as_float((v << sh) & 0xffff0000u); };
      const float dt = __bfloat162float(__float2bfloat16_rn(expf(__bfloat162float(in.logdt))));
      const float ar2 = dt * val(in.ar) * 1.4426950408889634f, ai = dt * val(in.ai);
      const cplx c = cmul({val(in.cr), -val(in.ci)}, {dt * val(in.br), -dt * val(in.bi)});
      k0 += c.r;
      const cplx z1 = cexp_l(ar2, -ai, 1.f), z256 = cexp_l(ar2, -ai, 256.f), z64 = cexp_l(ar2, ai, 64.f);
      const cplx z2 = csqr(z1), z512 = csqr(z256);
      auto put = [&](int j, cplx v) { sts32(bst + (j >> 2) * 2304 + (j & 3) * 32, packbf(v.r, v.i)); };
      sts128f(sb + SM_KGT + ht * 16, ar2, ai, z64.r, z64.i);
      const cplx c1 = cmul(c, z1), c2 = cmul(c, z2), c3 = cmul(c1, z2), c4 = cmul(c2, z2);
      const cplx c5 = cmul(c3, z2), c6 = cmul(c4, z2), c7 = cmul(c5, z2), c8 = cmul(c6, z2);
      put(0, c1); put(1, c2); put(2, c3); put(3, c4); put(4, c5); put(5, c6); put(6, c7); put(7, c8);
      const cplx c260 = cmul(c4, z256), c264 = cmul(c8, z256), c520 = cmul(c8, z512), c776 = cmul(c264, z512);
      put(8, cmul(c2, z256)); put(9, c260); put(10, cmul(c6, z256)); put(11, c264);
      put(12, cmul(c4, z512)); put(13, c520); put(14, cmul(c260, z512)); put(15, c776);
      const cplx c1032 = cmul(c520, z512), c1288 = cmul(c776, z512);
      put(16, c1032); put(17, c1288); put(18, cmul(c1032, z512)); put(19, cmul(c1288, z512));
    }
    fence_async_smem();
    bar_sync(4, 128);
    const uint32_t tb = sb + SM_KGT + (ht & 67) * 16;
    float2 nx[KB];
#pragma unroll
    for (int s = 0; s < KB; s++) nx[s] = lds64f(tb + s * 64);
#pragma unroll
    for (int q = 0; q < 16 / KB; q++) {
      uint32_t A[2 * KB];
      float2 cur[KB], z[KB];
#pragma unroll
      for (int s = 0; s < KB; s++) { cur[s] = nx[s]; z[s] = lds64f(tb + (KB * q + s) * 64 + 8); }
      if (q < 16 / KB - 1) {
#pragma unroll
        for (int s = 0; s < KB; s++) nx[s] = lds64f(tb + (KB * q + KB + s) * 64);
      }
      if (q >= KW) wg_wait<KW - 1>();
#pragma unroll
      for (int s = 0; s < KB; s++) {
        const cplx lo = cexp_l(cur[s].x, cur[s].y, e0), hi = cmul(lo, {z[s].x, z[s].y});
        A[2 * s] = packbf(lo.r, lo.i);
        A[2 * s + 1] = packbf(hi.r, hi.i);
      }
      wg_fence();
#pragma unroll
      for (int k = 0; k < KB / 2; k++) wgmma_rs<40, 0>(T, A + 4 * k, db + 9 * KB * q + 18 * k, (pass & 1) | q | k);
      wg_commit();
    }
    wg_wait<0>();
    acc_fence<20>(T);
    if (ht == 0) TS(4 + pass);
    if (pass & 1) {
      const int h2 = opaque_tid() - 256, w = h2 >> 5, lane = h2 & 31, t = lane & 3, chn = h2 >> 6, m = h2 & 63, i0 = 16 * (w & 1) + (lane >> 2);
      const int lc = (pass & 2) + chn;
      const uint32_t kc = sb + kc_off(lc);
      auto put = [&](int idx, float v) {
        sts16(kc + idx * 2, __bfloat16_as_ushort(__float2bfloat16_rn(v)));
      };
#pragma unroll
      for (int hi = 0; hi < 2; hi++) {
        const int i = i0 + 8 * hi;
        float v[5];
#pragma unroll
        for (int j = 0; j < 5; j++) v[j] = chn ? T[4 * j + 2 * hi + 1] : T[4 * j + 2 * hi];
        put(8 * i + 1 + t, v[0]);
        put(8 * i + 5 + t, v[1]);
        put(257 + 4 * i + t, v[2]);
        put(385 + 2 * i + (t & 1) + 64 * (t >> 1), v[3]);
        put(513 + i + 32 * t, v[4]);
      }
#pragma unroll
      for (int o = 16; o > 0; o >>= 1) k0 += __shfl_xor_sync(~0u, k0, o);
      if (lane == 0) sts32f(sb + SM_RED + 4 * w, k0);
      bar_sync(4, 128);
      if (m == 0) put(0, k0 + __uint_as_float(lds32(sb + SM_RED + 4 * w + 4)) + __uint_as_float(lds16(sb + SM_RED + 24 + 2 * lc) << 16));
      k0 = 0.f;
      in = in1;
    }
  }
}

__device__ __forceinline__ void expand_taps(uint32_t sb, int ht, int early) {
  const int ch = ht >> 5, lane = ht & 31;
  const uint32_t kc = sb + kc_off(ch);
  const uint32_t dst0 = sb + cv_pe(ch, early);
  auto put = [&](int G, uint32_t v0, uint32_t v1, uint32_t v2, uint32_t v3, uint32_t v4, uint32_t v5, uint32_t v6, uint32_t v7, uint32_t v8) {
    const uint32_t dst = dst0 + G * 32;
    sts128(dst, make_uint4(v1 | (v0 << 16), v2 | (v1 << 16), v3 | (v2 << 16), v4 | (v3 << 16)));
    sts128(dst + 16, make_uint4(v5 | (v4 << 16), v6 | (v5 << 16), v7 | (v6 << 16), v8 | (v7 << 16)));
  };
  {
    const uint4 q = lds128(kc + lane * 16);
    const uint32_t pv = lane ? lds16(kc + lane * 16 - 2) : 0u;
    const uint32_t dst = dst0 + (lane + 2) * 32;
    sts128(dst, make_uint4(__byte_perm(q.x, pv, 0x5410), __byte_perm(q.x, q.x, 0x1032), __byte_perm(q.y, q.x, 0x7610), __byte_perm(q.y, q.y, 0x1032)));
    sts128(dst + 16, make_uint4(__byte_perm(q.z, q.y, 0x7610), __byte_perm(q.z, q.z, 0x1032), __byte_perm(q.w, q.z, 0x7610), __byte_perm(q.w, q.w, 0x1032)));
    if (lane < 4) sts128(dst0 + lane * 16, make_uint4(0, 0, 0, 0));
  }
  uint32_t a[5], b[2][3];
  {
    const uint32_t s1 = kc + 2 * (256 + 4 * lane);
#pragma unroll
    for (int k = 0; k < 5; k++) a[k] = lds16(s1 + 2 * k);
#pragma unroll
    for (int u = 0; u < 2; u++) {
      const uint32_t s2 = kc + 2 * (384 + 2 * (lane + 32 * u));
#pragma unroll
      for (int k = 0; k < 3; k++) b[u][k] = lds16(s2 + 2 * k);
    }
  }
  const uint32_t k255 = lds16(kc + 2 * 255), k1024 = lds16(kc + 2 * 512);
  put(34 + lane, lane == 0 ? k255 : a[0], a[0], a[0], a[1], a[2], a[2], a[2], a[3], a[4]);
#pragma unroll
  for (int u = 0; u < 2; u++) put(66 + lane + 32 * u, b[u][0], b[u][0], b[u][0], b[u][0], b[u][1], b[u][1], b[u][1], b[u][2], b[u][2]);
  if (lane < 10) {
    const uint32_t v = lane == 0 ? k1024 : 0u;
    put(130 + lane, v, v, v, v, v, v, 0u, 0u, 0u);
  }
}
__device__ __forceinline__ void expand_far(uint32_t sb, int ht) {
  const int ch = ht >> 5, lane = ht & 31;
  const uint32_t kc = sb + kc_off(ch) + 2 * (513 + 2 * (63 - lane)), dst = sb + cv_fa(ch) + lane * 16;
#pragma unroll
  for (int ty = 0; ty < 2; ty++) {
    uint32_t v[16];
#pragma unroll
    for (int k = 0; k < 16; k++) v[k] = (k < 8 || 63 - lane - 4 * k >= 0) ? lds16(kc + 2 * (1 - ty) - 16 * k) : 0u;
#pragma unroll
    for (int u = 0; u < 2; u++)
      sts128(dst + ty * 2048 + u * 512, make_uint4(v[8 * u] | (v[8 * u + 1] << 16), v[8 * u + 2] | (v[8 * u + 3] << 16), v[8 * u + 4] | (v[8 * u + 5] << 16), v[8 * u + 6] | (v[8 * u + 7] << 16)));
    sts128(dst + ty * 2048 + 1024, make_uint4(0, 0, 0, 0));
  }
}

#define FDELAY 400
__host__ __device__ constexpr int bar_count(int i) {
  return i == B_LN ? 2 : i == B_AL ? 8 : i < B_STG ? 1 : i < B_PE ? 4 : i >= B_PUB ? 256 : 128;
}
__host__ __device__ constexpr bool bar_first(int i) { return i < B_WF + 2 && (i & 7) < 2; }

__global__ void __launch_bounds__(NTHREADS, 1) fused_kernel(const __grid_constant__ Params p) {
  extern __shared__ __align__(1024) uint8_t smem[];
  constexpr uint32_t sb = 1024;
  if (s32(smem) != sb) return;
  const int tid = threadIdx.x, lane = tid & 31;
  const int warp = __shfl_sync(~0u, tid >> 5, 0);
  if (tid == 32) {
    asm volatile("prefetch.tensormap [%0];" ::"l"(&p.mapX) : "memory");
    asm volatile("prefetch.tensormap [%0];" ::"l"(&p.mapW3) : "memory");
  }
  const int cta = blockIdx.x - (gridDim.x == NCTA + 4 ? 0 : 4);
  if ((unsigned)cta >= NCTA) {
    if (blockIdx.x < NCTA + 4) colsum_cta(p, sb, blockIdx.x & 3, tid);
    return;
  }
  const int rb = ((cta >> 4) & 3) * 4 + ((cta >> 2) & 3), hg = (cta >> 6) * 4 + (cta & 3);
  const uint32_t bar = sb + SM_BAR;
  auto ld_x0 = [&](int half, int c) {
    const uint32_t b = bar + 8 * (B_XF + 8 * half + c);
    mbar_expect(b, PG);
    tma_ld(sb + x_page(half, c) * PG, &p.mapX, c * 64, (16 * half + rb) * 64, b);
  };
  auto ld_x1 = [&](int half, int c, int b0) {
    const uint32_t b = bar + 8 * b0;
    mbar_expect(b, PG);
    tma_ld(sb + (8 * half + c) * PG, &p.mapXT, (16 * half + rb) * 64, DM + c * 64, b);
  };
  auto ld_w = [&](int c) {
    const uint32_t b = bar + 8 * (B_WF + c);
    mbar_expect(b, 3 * PG);
    tma_ld3(sb + w_page(c) * PG, &p.mapW3, hg * 64, c * 64, 0, b);
  };

  if (tid == 0) TS(0);
  if (tid == 480) LTS(0);
  if (warp == 0 && elect_one()) {
#pragma unroll
    for (int i = 0; i < B_WF + 2; i++)
      if (bar_first(i)) mbar_init(bar + 8 * i, 1);
    asm volatile("fence.mbarrier_init.release.cluster;" ::: "memory");
    fence_async_smem();
    ld_x0(0, 0);
    ld_w(0); ld_x0(1, 0);
    ld_x0(0, 1); ld_w(1); ld_x0(1, 1);
    TS(1);
  }
  __syncwarp();
  if (warp >= 1 && warp < 8 && elect_one()) {
    if (warp < 4) {
#pragma unroll
      for (int i = 2; i < 8; i++) mbar_init(bar + 8 * (8 * warp - 8 + i), 1);
    } else {
#pragma unroll
      for (int i = 0; i < 12; i++) mbar_init(bar + 8 * (12 * warp - 24 + i), 1);
    }
    asm volatile("fence.mbarrier_init.release.cluster;" ::: "memory");
  }
  if (warp == 15 && elect_one()) {
#pragma unroll
    for (int i = 72; i < B_COUNT; i++) mbar_init(bar + 8 * i, bar_count(i));
    asm volatile("fence.mbarrier_init.release.cluster;" ::: "memory");
  }

  if (warp < 8) {
    bar_sync(0, NTHREADS);
    asm volatile("setmaxnreg.inc.sync.aligned.u32 %0;" ::"n"(R_CONS));
    const int cw = __shfl_sync(~0u, opaque_tid() >> 5, 0);
    const int wg = cw >> 2, w = cw & 3;
    if (tid == 0) TS(2);
#pragma unroll 1
    for (int layer = 0; layer < 2; layer++) {
      attn_phase(p, sb, layer, rb, hg, wg, w);
      uint32_t A0[68], A1[68];
      proj_phase(p, sb, layer, rb, hg, A0, A1);
      conv_phase(p, sb, layer, cta, A0, A1);
    }
    if (wg == 0) mbar_wait(bar + 8 * (B_TF + 1), 0);
    else delay(FDELAY);
    if (tid == 128) TS(8);
    final_tile(p, sb + (16 + wg) * PG, 256 * wg + 32 * (cta >> 4), 1024 + 64 * (cta & 15), 2 + wg);
    if (tid == 128) TS(9);
    if (tid == 128) LTS(1);
    if (tid == 0) LTE();
  } else if (warp < 12) {
    asm volatile("setmaxnreg.dec.sync.aligned.u32 %0;" ::"n"(R_HELP));
    const int ht = tid - 256;
    {
      unsigned ep0 = 0;
      if (ht == 0) ep0 = ld_relaxed(&g_cnt[C_CS * 32]);
      const bf16 dsk = p.dskip[cv_chan(cta, ht & 3)];
      const ModeIn in0 = load_modes(p, cv_chan(cta, ht >> 6), ht & 63), in1 = load_modes(p, cv_chan(cta, 2 + (ht >> 6)), ht & 63);
      if (ht < 48) sts128f(sb + SM_STG + ht * 16, 0.f, 0.f, 0.f, 1.f);
      bar_sync(0, NTHREADS);
      if (ht == 0) {
        sts32(sb + SM_EP, ep0);
        mbar_arrive(bar + 8 * B_EP);
      }
      if (ht >= 124) sts16(sb + SM_RED + 24 + 2 * (ht & 3), __bfloat16_as_ushort(dsk));
      kernel_gen(sb, cta, ht, in0, in1);
      if (ht < 48) sts128f(sb + SM_KGT + ht * 16, 0.f, 0.f, 0.f, 1.f);
      fence_async_smem();
      bar_sync(4, 128);
      if (ht == 0) mbar_arrive(bar + 8 * B_KG);
    }
#pragma unroll 1
    for (int layer = 0; layer < 2; layer++) {
      const int early = layer;
      if (early) mbar_wait(bar + 8 * (B_DN + 13), 1);
      mbar_wait(bar + 8 * (early ? B_OST : B_PDONE), layer);
      expand_taps(sb, opaque_tid() - 256, early);
      mbar_arrive(bar + 8 * B_PE);
      TSW(0);
      mbar_wait(bar + 8 * B_PDONE, layer);
      expand_far(sb, opaque_tid() - 256);
      {
        const int i = opaque_tid() - 256;
        if (i < 32) sts128(sb + cv_u(i >> 3) + ((i >> 2) & 1) * CV_UH + (128 + (i & 3)) * 16, make_uint4(0, 0, 0, 0));
        mbar_wait(bar + 8 * B_RC, layer);
        conv_prep<0>(sb, layer, cta, i);
        mbar_arrive(bar + 8 * B_U);
      }
      mbar_wait(bar + 8 * (B_PDONE + 1), layer);
      bar_sync(4, 128);
#pragma unroll 1
      for (int lc = 0; lc < 4; lc += 2) {
        conv_sums(sb, lc, opaque_tid() - 256);
        TSW(1 + lc);
      }
      conv_prep<1>(sb, layer, cta, opaque_tid() - 256);
      mbar_arrive(bar + 8 * B_U1);
      TSW(4);
      if (layer == 0) {
        const int c = __shfl_sync(~0u, (opaque_tid() >> 5) & 3, 0);
        int phase = 0;
#pragma unroll 1
        for (int k = 0; k < 3; k++) {
          const int page = (k ? 4 + 4 * k : 0) + c, b = B_XR + 4 * (k & 1) + c;
          const uint32_t a = sb + page * PG + lane * 128 + (lane & 7) * 16 + (lane >> 3) * 4;
          int it = k == 2 ? phase : 0;
#pragma unroll 1
          for (; it < MAX_RETRY; it++) {
            mbar_wait(bar + 8 * b, it & 1);
            const uint32_t v0 = lds32(a), v1 = lds32(a + 4096);
            if (__all_sync(~0u, v0 != UNSET && v1 != UNSET)) break;
            if (elect_one()) { fence_async_smem(); ld_x1(page >> 3, page & 7, b); }
            __syncwarp();
            RETRY(3);
          }
          if (k == 0) phase = it + 1;
          if (lane == 0) mbar_arrive(bar + 8 * (B_XF + page));
        }
      }
    }
    mbar_wait(bar + 8 * B_TF, 0);
#pragma unroll 1
    for (int k = 0; k < 2; k++) final_tile(p, sb + 18 * PG + k * 4096, 256 * k + 32 * (cta >> 4), 64 * (cta & 15), 4);
    if (ht == 0) LTE();
  } else {
    asm volatile("setmaxnreg.dec.sync.aligned.u32 %0;" ::"n"(R_AGENT));
    bar_sync(0, NTHREADS);
    auto done = [&](int half, int c, int layer) { mbar_wait(bar + 8 * (B_DN + 8 * half + c), layer); };
    auto publish = [&](int layer, int k) {
      mbar_wait(bar + 8 * (B_PUB + k), layer);
      red_relaxed(&g_cnt[(layer ? C_F + 8 * k + (cta >> 4) : C_C + k) * 32]);
      if (!layer && k == 0) red_release(&g_cnt[(C_C + 3) * 32]);
      TS(16 + layer * 56 + 40 + 7 + k);
    };
    if (warp == 12) {
      if (elect_one()) {
#pragma unroll 1
        for (int layer = 0; layer < 2; layer++) {
          auto ld_xe = [&](int c) {
            const uint32_t b = bar + 8 * (B_XF + c);
            mbar_expect(b, PG);
            if (layer == 0) tma_ld(sb + x_page(0, c) * PG, &p.mapX, c * 64, rb * 64, b);
            else tma_ld(sb + x_page(0, c) * PG, &p.mapXT, rb * 64, DM + c * 64, b);
          };
          if (layer == 0) {
            ld_x0(0, 2); ld_w(2); ld_x0(1, 2);
            if (hg >= 3) {
              mbar_expect(bar + 8 * B_SC, PG);
              tma_ld(sb + P_R * PG, &p.mapX, hg * 64, rb * 64, bar + 8 * B_SC);
            }
            if (rb < 4) tma_prefetch3(&p.mapW3, hg * 64, (4 + rb) * 64, 0);
            ld_x0(0, 3); ld_w(3); ld_x0(1, 3); ld_x0(0, 4); ld_x0(1, 4);
            done(0, 0, 0); done(1, 0, 0);
            ld_w(4);
            ld_x0(1, 5); ld_x0(1, 6); ld_x0(1, 7);
            done(0, 1, 0); done(1, 1, 0);
            ld_w(5);
            if (rb < 8) tma_prefetch5(&p.mapWo, hg * 64, rb * 2);
            done(0, 2, 0);
            fence_async_smem();
            ld_xe(5); ld_xe(6); ld_xe(7);
          } else {
            mbar_wait(bar + 8 * B_PDONE, 0);
            mbar_wait(bar + 8 * (B_PDONE + 1), 0);
            mbar_wait(bar + 8 * B_U, 0);
            ld_w(0); ld_w(1);
            mbar_wait(bar + 8 * B_U1, 0);
            fence_async_smem();
            ld_w(2);
            mbar_wait(bar + 8 * (B_PUB + 2), 0);
            fence_async_smem();
            ld_w(3);
            spin_until(&g_cnt[(C_C + 3) * 32], ((lds32(sb + SM_EP) / NCTA) + 1) * NCTA);
            fence_async_global();
            if (hg >= 3) {
              mbar_expect(bar + 8 * B_SC, PG);
              tma_ld(sb + P_R * PG, &p.mapXT, rb * 64, DM + hg * 64, bar + 8 * B_SC);
            }
            ld_xe(4);
            done(0, 2, 1);
            fence_async_smem();
            ld_xe(5); ld_xe(6); ld_xe(7);
            done(1, 0, 1);
            ld_w(4);
            done(1, 1, 1);
            ld_w(5);
          }
          done(1, 2, layer);
          fence_async_smem();
          ld_w(6); ld_w(7);
          auto ld_res = [&](int half) {
            const uint32_t b = bar + 8 * (B_RF + half);
            mbar_expect(b, PG);
            if (layer == 0) tma_ld(sb + (half ? 2 : P_R) * PG, &p.mapX, hg * 64, (16 * half + rb) * 64, b);
            else tma_ld(sb + (half ? 2 : P_R) * PG, &p.mapXT, (16 * half + rb) * 64, DM + hg * 64, b);
          };
          done(0, 4, layer); done(1, 3, layer);
          fence_async_smem();
          mbar_expect(bar + 8 * B_WOF, 8 * PG);
#pragma unroll 1
          for (int c = 0; c < 8; c++) {
            if (c == 5) { ld_res(0); done(1, 4, layer); }
            tma_ld5(sb + wo_page(c) * PG, &p.mapWo, hg * 64, c * 2, bar + 8 * B_WOF);
          }
          done(0, 7, layer);
          fence_async_global();
          ld_res(1);
          if (layer) mbar_wait(bar + 8 * B_RS, 0);
          fence_async_global();
#pragma unroll
          for (int half = 0; half < 2; half++) {
            float* stats = g_stats + (layer * 32 + 16 * half + rb) * 192;
            unsigned* cnt = &g_cnt[(C_G + 2 * layer + half) * 32];
            mbar_wait(bar + 8 * (B_STG + half), layer);
            tma_st(&p.mapXT, (16 * half + rb) * 64, 2 * layer * DM + hg * 64, sb + (P_R + half) * PG);
            bulk_red_add_f32(stats, sb + (half ? SM_KGT : SM_STG), 768);
            bulk_commit();
            red_relaxed(cnt);
            if (half == 0) mbar_arrive(bar + 8 * B_PG);
            bulk_wait_read();
            mbar_arrive(bar + 8 * (B_PST + half));
          }
        }
      }
    } else if (warp == 13) {
      mbar_wait(bar + 8 * B_EP, 0);
      const unsigned e1 = (lds32(sb + SM_EP) / NCTA) + 1;
      auto ld_o = [&](int layer) {
#pragma unroll 1
        for (int half = 0; half < 2; half++) {
          done(1, 7, layer);
          mbar_wait(bar + 8 * B_OST, layer);
          if (half) mbar_wait(bar + 8 * (B_OST + 1), layer);
          fence_async_smem();
#pragma unroll
          for (int c = 0; c < 4; c++) mbar_expect(bar + 8 * (B_OF + 4 * half + c), 2 * PG);
          const bf16* src = g_O + (layer * 32 + 16 * half + rb) * 4 * PG;
          uint32_t dst0 = sb + o_page(half, 0) * PG;
          pin(src); pin(dst0);
          spin_hint(&g_cnt[(C_O + layer * 32 + 16 * half + rb) * 32], e1 * 32);
#pragma unroll
          for (int c = 0; c < 4; c++) {
            if (c == 2 && half && layer) { mbar_wait(bar + 8 * B_AL, 0); fence_async_smem(); }
            bulk_ld(c ? sb + o_page(half, c) * PG : dst0, src + c * PG, 2 * PG, bar + 8 * (B_OF + 4 * half + c));
          }
        }
      };
      if (elect_one()) {
        mbar_wait(bar + 8 * (B_WF + 2), 0);
        asm volatile("prefetch.tensormap [%0];" ::"l"(&p.mapXT) : "memory");
        asm volatile("prefetch.tensormap [%0];" ::"l"(&p.mapWo) : "memory");
        spin_until(&g_cnt[C_Z * 32], e1 * NCTA);
        mbar_arrive(bar + 8 * B_ZF);
        TS(3);
        ld_o(0);
#pragma unroll 1
        for (int k = 0; k < 3; k++) {
          mbar_wait(bar + 8 * (B_PUB + k), 0);
          if (k == 2) {
#pragma unroll 1
            for (int c = 0; c < 4; c++) mbar_wait(bar + 8 * (B_XF + c), 1);
          }
          fence_async_smem();
          uint32_t b = bar + 8 * (B_XR + 4 * (k & 1)), dst = sb + (k ? 4 + 4 * k : 0) * PG, c0 = ((k ? 16 : 0) + rb) * 64, c1 = DM + (k & 2) * 128;
#pragma unroll
          for (int c = 0; c < 4; c++) mbar_expect(b + 8 * c, PG);
          pin(b); pin(dst); pin(c0); pin(c1);
          spin_hint(&g_cnt[(C_C + k) * 32], e1 * NCTA);
          TS(10 + k);
#pragma unroll
          for (int c = 0; c < 4; c++) tma_ld(dst + c * PG, &p.mapXT, c0, c1 + c * 64, b + 8 * c);
        }
        ld_o(1);
#pragma unroll 1
        for (int k = 0; k < 2; k++) {
          mbar_wait(bar + 8 * (B_PUB + k), 1);
          spin_hint(&g_cnt[(C_F + 8 * k + (cta >> 4)) * 32], e1 * 16);
          mbar_arrive(bar + 8 * (B_TF + k));
        }
      }
    } else if (warp == 14) {
      mbar_wait(bar + 8 * B_EP, 0);
      const unsigned e1 = (lds32(sb + SM_EP) / NCTA) + 1;
      done(0, 1, 0);
      {
        const uint2* cp = g_colsum + (hg * 192 + lane);
        uint2 v[6];
        bool ok;
        int it = 0;
        do {
          ok = true;
#pragma unroll
          for (int i = 0; i < 6; i++) {
            asm volatile("ld.relaxed.gpu.global.v2.u32 {%0,%1}, [%2];" : "=r"(v[i].x), "=r"(v[i].y) : "l"(cp + 32 * i) : "memory");
            ok = ok && v[i].y == e1;
          }
          if (++it > (1 << 22)) __trap();
        } while (!__all_sync(~0u, ok));
#pragma unroll
        for (int i = 0; i < 6; i++) sts32f(sb + SM_CS + 4 * (lane + 32 * i), __uint_as_float(v[i].x));
      }
      __syncwarp();
      if (elect_one()) {
        mbar_wait(bar + 8 * B_ZF, 0);
        mbar_arrive(bar + 8 * B_LN);
        red_relaxed(&g_cnt[C_CS * 32]);
        TS(13);
#pragma unroll 1
        for (int layer = 0; layer < 2; layer++) {
          const uint32_t b = bar + 8 * (B_GB + 1);
          const bf16* xin = g_xT + ((size_t)2 * layer * DM + 2 * cta) * LSEQ + 1024;
          const float* stats = g_stats + (layer * 32 + 16) * 192;
          mbar_wait(bar + 8 * B_PST, layer);
          spin_hint(&g_cnt[(C_G + 2 * layer) * 32], e1 * NCTA);
          mbar_arrive(bar + 8 * B_GB);
          mbar_wait(bar + 8 * (B_PST + 1), layer);
          fence_async_smem();
          mbar_expect(b, 12288 + PG);
          pin(stats); pin(xin);
          spin_hint(&g_cnt[(C_G + 2 * layer + 1) * 32], e1 * NCTA);
          bulk_ld(sb + CV_ST, stats, 12288, b);
#pragma unroll
          for (int lc = 0; lc < 4; lc++) bulk_ld(sb + cv_x(1, lc), xin + cv_chan(0, lc) * LSEQ, 2048, b);
          TS(14 + layer);
          publish(layer, 1);
        }
      }
    } else {
      const uint4 u = make_uint4(UNSET, UNSET, UNSET, UNSET);
      if (lane < 24) stg128((uint4*)g_stats + cta * 24 + lane, make_uint4(0, 0, 0, 0));
      if (lane < 16) stg128(g_rows + LSEQ + cta * 16 + lane, make_uint4(0, 0, 0, 0));
#pragma unroll 4
      for (int i = 0; i < 16; i++) stg128(g_halo + cta * 512 + 32 * i + lane, u);
#pragma unroll 4
      for (int i = 0; i < 16; i++) stg128(((i & 8) ? (uint4*)g_xT : (uint4*)g_O) + cta * 1024 + (i & 7) * 128 + (lane >> 1) * 8 + (lane & 1), u);
      __syncwarp();
      if (elect_one()) red_release(&g_cnt[C_Z * 32]);
      __syncwarp();
#pragma unroll 1
      for (int layer = 0; layer < 2; layer++) {
        auto reset_done = [&](int s) {
          spin_until(&g_cnt[(C_R + s) * 32], (lds32(sb + SM_EP) / NCTA) * 4 + 4);
          mbar_arrive(bar + 8 * (s == 1 ? B_LN : s == 2 ? B_RS : B_RC));
          if (s) TS(16 + 40 + 9 + s);
        };
        if (layer && elect_one()) reset_done(1);
        __syncwarp();
#pragma unroll 1
        for (int half = 0; half < 2; half++) {
          done(half, 2, layer);
          const uint4* src = g_rows + (layer * LSEQ + (16 * half + rb) * 64 + (opaque_tid() & 31));
          uint4 a, b;
          int it = 0;
          do {
            a = ld_tagged(src); b = ld_tagged(src + 32);
          } while (!__all_sync(~0u, (a.z | a.w) == __float_as_uint(8.f) && (b.z | b.w) == __float_as_uint(8.f)) && ++it < (1 << 20));
          float m0 = __uint_as_float(a.x) * (1.f / DM), m1 = __uint_as_float(b.x) * (1.f / DM);
          float r0 = rsqrt_approx(fmaxf(__uint_as_float(a.y) * (1.f / DM) - m0 * m0, 0.f) + 1e-5f);
          float r1 = rsqrt_approx(fmaxf(__uint_as_float(b.y) * (1.f / DM) - m1 * m1, 0.f) + 1e-5f);
          if (half) done(0, 7, layer);
          const uint32_t dst = sb + ln_off(half) + ((lane >> 4) * 8 + (lane & 7)) * 16 + (lane & 8);
          asm volatile("st.shared.v2.f32 [%0], {%1,%2};" ::"r"(dst), "f"(m0), "f"(r0) : "memory");
          asm volatile("st.shared.v2.f32 [%0], {%1,%2};" ::"r"(dst + 256), "f"(m1), "f"(r1) : "memory");
          __syncwarp();
          if (elect_one()) { mbar_arrive(bar + 8 * (B_LN + half)); TS(16 + layer * 56 + 40 + 14 + half); }
        }
        if (layer && lane < 16) stg128(g_rows + cta * 16 + (opaque_tid() & 31), make_uint4(0, 0, 0, 0));
        if (elect_one()) {
          if (layer) reset_done(2);
          reset_done(3 * layer);
          publish(layer, 0);
          if (!layer) publish(layer, 2);
        }
        __syncwarp();
      }
    }
  }
}

typedef CUresult (*EncodeFn)(CUtensorMap*, CUtensorMapDataType, cuuint32_t, void*, const cuuint64_t*, const cuuint64_t*,
                             const cuuint32_t*, const cuuint32_t*, CUtensorMapInterleave, CUtensorMapSwizzle,
                             CUtensorMapL2promotion, CUtensorMapFloatOOBfill);

static void make_map(EncodeFn enc, CUtensorMap* m, void* ptr, uint64_t cols, uint64_t rows, uint32_t box_rows) {
  cuuint64_t dims[2] = {cols, rows};
  cuuint64_t strides[1] = {cols * 2};
  cuuint32_t box[2] = {64, box_rows};
  cuuint32_t es[2] = {1, 1};
  enc(m, CU_TENSOR_MAP_DATA_TYPE_BFLOAT16, 2, ptr, dims, strides, box, es, CU_TENSOR_MAP_INTERLEAVE_NONE,
      CU_TENSOR_MAP_SWIZZLE_128B, CU_TENSOR_MAP_L2_PROMOTION_L2_128B, CU_TENSOR_MAP_FLOAT_OOB_FILL_NONE);
}
static void make_map3(EncodeFn enc, CUtensorMap* m, void* ptr, uint64_t d0, uint64_t cols, uint64_t rows, uint64_t blk_stride,
                      uint64_t nblocks, uint32_t nblk) {
  cuuint64_t dims[3] = {d0, rows, nblocks};
  cuuint64_t strides[2] = {cols * 2, blk_stride * 2};
  cuuint32_t box[3] = {64, 64, nblk};
  cuuint32_t es[3] = {1, 1, 1};
  enc(m, CU_TENSOR_MAP_DATA_TYPE_BFLOAT16, 3, ptr, dims, strides, box, es, CU_TENSOR_MAP_INTERLEAVE_NONE,
      CU_TENSOR_MAP_SWIZZLE_128B, CU_TENSOR_MAP_L2_PROMOTION_L2_128B, CU_TENSOR_MAP_FLOAT_OOB_FILL_NONE);
}

extern "C" void kernel_launch(void* const* d_in, const int* in_sizes, int n_in, void* d_out, int out_size) {
  static Params prm;
  static void* cached[13] = {nullptr};
  static bool attr_done = false;
  static int grid = NCTA + 4;
  bool same = attr_done && cached[12] == d_out;
  for (int i = 0; i < 12 && same; i++) same = cached[i] == d_in[i];
  if (!same) {
    void* fn = nullptr;
    cudaDriverEntryPointQueryResult qr;
    cudaGetDriverEntryPoint("cuTensorMapEncodeTiled", &fn, cudaEnableDefault, &qr);
    EncodeFn enc = (EncodeFn)fn;
    void* pXT;
    cudaGetSymbolAddress(&pXT, g_xT);
    make_map(enc, &prm.mapX, d_in[0], DM, LSEQ, 64);
    make_map(enc, &prm.mapXT, pXT, LSEQ, 4 * DM, 64);
    {
      cuuint64_t dims[5] = {DM, 2, 4, 4, 16};
      cuuint64_t strides[4] = {DM * 2, 8 * DM * 2, 2 * DM * 2, 32 * DM * 2};
      cuuint32_t box[5] = {64, 2, 4, 4, 2};
      cuuint32_t es[5] = {1, 1, 1, 1, 1};
      enc(&prm.mapWo, CU_TENSOR_MAP_DATA_TYPE_BFLOAT16, 5, d_in[2], dims, strides, box, es, CU_TENSOR_MAP_INTERLEAVE_NONE,
          CU_TENSOR_MAP_SWIZZLE_128B, CU_TENSOR_MAP_L2_PROMOTION_L2_128B, CU_TENSOR_MAP_FLOAT_OOB_FILL_NONE);
    }
    make_map3(enc, &prm.mapW3, d_in[1], DM, 3 * DM, DM, DM, 3, 3);
    prm.out = (bf16*)d_out;
    prm.a_re = (const bf16*)d_in[4]; prm.a_im = (const bf16*)d_in[5];
    prm.b_re = (const bf16*)d_in[6]; prm.b_im = (const bf16*)d_in[7];
    prm.c_re = (const bf16*)d_in[8]; prm.c_im = (const bf16*)d_in[9];
    prm.log_dt = (const bf16*)d_in[10]; prm.dskip = (const bf16*)d_in[11];
    int dev = 0, sms = 0;
    cudaGetDevice(&dev);
    cudaDeviceGetAttribute(&sms, cudaDevAttrMultiProcessorCount, dev);
    grid = sms >= NCTA + 4 ? NCTA + 4 : NCTA + 5;
    cudaFuncSetAttribute(fused_kernel, cudaFuncAttributeMaxDynamicSharedMemorySize, SM_TOTAL);
    for (int i = 0; i < 12; i++) cached[i] = d_in[i];
    cached[12] = d_out;
    attr_done = true;
  }
  fused_kernel<<<grid, NTHREADS, SM_TOTAL>>>(prm);
}
```

```cpp
#include <cuda_runtime.h>
#include <cuda_bf16.h>
#include <cuda.h>
#include <stdint.h>

typedef __nv_bfloat16 bf16;

constexpr int LSEQ = 2048;
constexpr int DM = 512;
constexpr int NCTA = 128;
constexpr int NTHREADS = 512;
#define R_CONS 200
#define R_HELP 88
#define R_AGENT 24
#define TURN0 4
#define TURN1 4

constexpr int PG = 8192;
constexpr int P_R = 25;
__host__ __device__ constexpr int x_page(int half, int c) { return half ? 8 + c : c < 5 ? c : c - 5; }
__host__ __device__ constexpr int w_page(int c) { return (c & 3) < 3 ? 16 + 3 * (c & 3) : c < 4 ? 5 : 8; }
__host__ __device__ constexpr int wo_page(int c) { return c < 5 ? 3 + c : 11 + c; }
__host__ __device__ constexpr int o_page(int half, int pair) { return half ? (pair ? 25 - 2 * pair : 0) : 8 + 2 * pair; }
constexpr int SM_KGB = (P_R + 1) * PG;
constexpr int SM_KC = 27 * PG;
constexpr int KC_STRIDE = 648;
__host__ __device__ constexpr int kc_off(int lc) { return SM_KC + (lc & 1) * 2 * KC_STRIDE + (lc < 2 ? 3328 : 0); }
constexpr int SM_KGT = SM_KC + 3328 + 2592;
constexpr int SM_CS = SM_KGT + 2048;
constexpr int SM_RED = SM_CS + 768;
constexpr int SM_EP = SM_RED + 16;
constexpr int SM_STG = SM_RED + 32;
constexpr int SM_LN = SM_STG + 768;
__host__ __device__ constexpr int ln_off(int half) { return half ? PG + 4096 : SM_LN; }
constexpr int SM_BAR = SM_LN + 512;
constexpr int SM_TS = SM_BAR + 704;
constexpr int SM_TOTAL = SM_TS + 512;
static_assert(SM_TOTAL <= 232448 && SM_STG % 16 == 0 && SM_KGT % 16 == 0, "shared memory");

constexpr int CV_UH = 140 * 16;
__host__ __device__ constexpr int cv_u(int lc) { return (8 + 2 * lc) * PG; }
__host__ __device__ constexpr int cv_pe(int lc, int early) { return early ? 19 * PG + lc * 4480 : cv_u(lc) + 4480; }
__host__ __device__ constexpr int cv_pb1(int lc, int w) { return w ? cv_u(lc) + 8960 + (w - 1) * 2048 : 7 * PG + lc * 2048; }
__host__ __device__ constexpr int cv_fa(int lc) { return cv_pb1(lc, 1) + 128; }
__host__ __device__ constexpr int cv_dump(int lc) { return cv_u(lc) + 16256; }
__host__ __device__ constexpr int cv_pb0(int lc, int w) { return lc * PG + w * 2048; }
__host__ __device__ constexpr int cv_se(int lc) { return 5 * PG + lc * 4096; }
__host__ __device__ constexpr int cv_so(int lc) { return cv_se(lc) + 2048; }
__host__ __device__ constexpr int cv_x(int half, int lc) { return (P_R + half) * PG + lc * 2048; }
constexpr int CV_ST = 22 * PG;
__host__ __device__ constexpr int cv_chan(int cta, int lc) { return 2 * cta + (lc & 1) + 256 * (lc >> 1); }

enum {
  B_XF = 0,
  B_WF = 16,
  B_OF = 24,
  B_DN = 32,
  B_PG = 46,
  B_XR = 48,
  B_RF = 56,
  B_PST = 58,
  B_GB = 60,
  B_TF = 62,
  B_RT = 64,
  B_RS = 66,
  B_RC = 67,
  B_WOF = 68,
  B_ZF = 69,
  B_EP = 70,
  B_KG = 71,
  B_SC = 37,
  B_LN = 72,
  B_END = 38,
  B_STG = 74,
  B_OST = 76,
  B_PDONE = 78,
  B_PE = 80,
  B_U = 81,
  B_U1 = 82,
  B_PUB = 83,
  B_AL = 86,
  B_COUNT = 87
};

enum {
  C_CS = 0,
  C_G = 1,
  C_C = 5,
  C_O = 21,
  C_Z = 85,
  C_R = 86,
  C_F = 90,
  C_COUNT = 106
};

__device__ unsigned g_cnt[C_COUNT * 32];
__device__ __align__(1024) bf16 g_O[2 * LSEQ * DM];
__device__ __align__(1024) bf16 g_xT[4 * DM * LSEQ];
__device__ __align__(1024) float g_stats[2 * 32 * 192];
__device__ __align__(1024) uint2 g_colsum[3 * DM];
__device__ __align__(1024) uint4 g_halo[32 * 8 * 256];
__device__ __align__(1024) uint4 g_rows[2 * LSEQ];
#define TS(i) do { } while (0)
#define TSW(k) do { if ((threadIdx.x & 127) == 0) TS(16 + layer * 56 + (threadIdx.x >> 7) * 20 + (k)); } while (0)
#define TSG(k) do { } while (0)

#define RETRY(i) do { } while (0)
#define LTS(i) do { } while (0)
#define LTE() do { } while (0)

struct Params {
  CUtensorMap mapX, mapW3, mapXT, mapWo;
  bf16* out;
  const bf16 *a_re, *a_im, *b_re, *b_im, *c_re, *c_im, *log_dt, *dskip;
};

__device__ __forceinline__ uint32_t s32(const void* p) { return (uint32_t)__cvta_generic_to_shared(p); }
__device__ __forceinline__ void mbar_init(uint32_t b, int c) { asm volatile("mbarrier.init.shared::cta.b64 [%0], %1;" ::"r"(b), "r"(c) : "memory"); }
__device__ __forceinline__ void mbar_expect(uint32_t b, int bytes) { asm volatile("mbarrier.arrive.expect_tx.shared::cta.b64 _, [%0], %1;" ::"r"(b), "r"(bytes) : "memory"); }
__device__ __forceinline__ void mbar_arrive(uint32_t b) { asm volatile("mbarrier.arrive.shared::cta.b64 _, [%0];" ::"r"(b) : "memory"); }
__device__ __forceinline__ void mbar_wait(uint32_t b, int parity) {
  asm volatile("{\n.reg .pred p;\nWAIT_LOOP:\nmbarrier.try_wait.parity.shared::cta.b64 p, [%0], %1;\n@p bra WAIT_DONE;\nbra WAIT_LOOP;\nWAIT_DONE:\n}" ::"r"(b), "r"(parity) : "memory");
}
__device__ __forceinline__ bool mbar_test(uint32_t b, int parity) {
  uint32_t ok;
  asm volatile("{\n.reg .pred p;\nmbarrier.test_wait.parity.shared::cta.b64 p, [%1], %2;\nselp.u32 %0, 1, 0, p;\n}" : "=r"(ok) : "r"(b), "r"(parity) : "memory");
  return ok != 0;
}
__device__ __forceinline__ int opaque_tid() { int v; asm volatile("mov.u32 %0, %%tid.x;" : "=r"(v)); return v; }
__device__ __forceinline__ bool elect_one() {
  uint32_t r;
  asm volatile("{\n.reg .pred p;\nelect.sync _|p, 0xffffffff;\nselp.u32 %0, 1, 0, p;\n}" : "=r"(r));
  return r != 0;
}
__device__ __forceinline__ void tma_ld(uint32_t dst, const CUtensorMap* m, int c0, int c1, uint32_t bar) {
  asm volatile("cp.async.bulk.tensor.2d.shared::cluster.global.mbarrier::complete_tx::bytes [%0], [%1, {%3, %4}], [%2];"
               ::"r"(dst), "l"(m), "r"(bar), "r"(c0), "r"(c1) : "memory");
}
__device__ __forceinline__ void tma_ld3(uint32_t dst, const CUtensorMap* m, int c0, int c1, int c2, uint32_t bar) {
  asm volatile("cp.async.bulk.tensor.3d.shared::cluster.global.mbarrier::complete_tx::bytes [%0], [%1, {%3, %4, %5}], [%2];"
               ::"r"(dst), "l"(m), "r"(bar), "r"(c0), "r"(c1), "r"(c2) : "memory");
}
__device__ __forceinline__ void tma_ld5(uint32_t dst, const CUtensorMap* m, int c0, int c4, uint32_t bar) {
  asm volatile("cp.async.bulk.tensor.5d.shared::cluster.global.mbarrier::complete_tx::bytes [%0], [%1, {%3, 0, 0, 0, %4}], [%2];"
               ::"r"(dst), "l"(m), "r"(bar), "r"(c0), "r"(c4) : "memory");
}
__device__ __forceinline__ void tma_prefetch5(const CUtensorMap* m, int c0, int c4) {
  asm volatile("cp.async.bulk.prefetch.tensor.5d.L2.global.tile [%0, {%1, 0, 0, 0, %2}];" ::"l"(m), "r"(c0), "r"(c4) : "memory");
}
__device__ __forceinline__ void tma_prefetch3(const CUtensorMap* m, int c0, int c1, int c2) {
  asm volatile("cp.async.bulk.prefetch.tensor.3d.L2.global.tile [%0, {%1, %2, %3}];" ::"l"(m), "r"(c0), "r"(c1), "r"(c2) : "memory");
}
__device__ __forceinline__ void tma_st(const CUtensorMap* m, int c0, int c1, uint32_t src) {
  asm volatile("cp.async.bulk.tensor.2d.global.shared::cta.bulk_group [%0, {%2, %3}], [%1];" ::"l"(m), "r"(src), "r"(c0), "r"(c1) : "memory");
}
__device__ __forceinline__ void bulk_ld(uint32_t dst, const void* src, int bytes, uint32_t bar) {
  asm volatile("cp.async.bulk.shared::cluster.global.mbarrier::complete_tx::bytes [%0], [%1], %2, [%3];" ::"r"(dst), "l"(src), "r"(bytes), "r"(bar) : "memory");
}
__device__ __forceinline__ void bulk_red_add_f32(void* dst, uint32_t src, int bytes) {
  asm volatile("cp.reduce.async.bulk.global.shared::cta.bulk_group.add.f32 [%0], [%1], %2;" ::"l"(dst), "r"(src), "r"(bytes) : "memory");
}
__device__ __forceinline__ void bulk_commit() { asm volatile("cp.async.bulk.commit_group;" ::: "memory"); }
__device__ __forceinline__ void fence_async_smem() { asm volatile("fence.proxy.async.shared::cta;" ::: "memory"); }
__device__ __forceinline__ void fence_async_global() { asm volatile("fence.proxy.async.global;" ::: "memory"); }
__device__ __forceinline__ void bar_sync(int id, int n) { asm volatile("bar.sync %0, %1;" ::"r"(id), "r"(n) : "memory"); }
__device__ __forceinline__ void bar_arrive(int id, int n) { asm volatile("bar.arrive %0, %1;" ::"r"(id), "r"(n) : "memory"); }
__device__ __forceinline__ bool bar_or(int id, int n, bool v) {
  uint32_t r;
  asm volatile("{\n.reg .pred p, q;\nsetp.ne.u32 q, %3, 0;\nbar.red.or.pred p, %1, %2, q;\nselp.u32 %0, 1, 0, p;\n}" : "=r"(r) : "r"(id), "r"(n), "r"((uint32_t)v) : "memory");
  return r != 0;
}
__device__ __forceinline__ void bulk_wait_read() { asm volatile("cp.async.bulk.wait_group.read 0;" ::: "memory"); }
__device__ __forceinline__ void stg128(void* p, uint4 v) { asm volatile("st.relaxed.gpu.global.v4.u32 [%0], {%1,%2,%3,%4};" ::"l"(p), "r"(v.x), "r"(v.y), "r"(v.z), "r"(v.w) : "memory"); }
constexpr uint32_t UNSET = 0xffffffffu;
constexpr int MAX_RETRY = 1 << 16;
__device__ __forceinline__ void wg_fence() { asm volatile("wgmma.fence.sync.aligned;" ::: "memory"); }
__device__ __forceinline__ void wg_commit() { asm volatile("wgmma.commit_group.sync.aligned;" ::: "memory"); }
template <int N> __device__ __forceinline__ void wg_wait() { asm volatile("wgmma.wait_group.sync.aligned %0;" ::"n"(N) : "memory"); }
__device__ __forceinline__ uint64_t mkdesc(uint32_t addr, uint32_t lbo, uint32_t sbo, int sw) {
  return (uint64_t)((addr & 0x3FFFF) >> 4) | ((uint64_t)(lbo >> 4) << 16) | ((uint64_t)(sbo >> 4) << 32) | ((uint64_t)sw << 62);
}
__device__ __forceinline__ void ldsm4(uint32_t* r, uint32_t a) {
  asm volatile("ldmatrix.sync.aligned.m8n8.x4.shared.b16 {%0,%1,%2,%3}, [%4];" : "=r"(r[0]), "=r"(r[1]), "=r"(r[2]), "=r"(r[3]) : "r"(a) : "memory");
}
__device__ __forceinline__ void ldsm4t(uint32_t* r, uint32_t a) {
  asm volatile("ldmatrix.sync.aligned.m8n8.x4.trans.shared.b16 {%0,%1,%2,%3}, [%4];" : "=r"(r[0]), "=r"(r[1]), "=r"(r[2]), "=r"(r[3]) : "r"(a) : "memory");
}
__device__ __forceinline__ void stsm4(uint32_t a, uint32_t r0, uint32_t r1, uint32_t r2, uint32_t r3) {
  asm volatile("stmatrix.sync.aligned.m8n8.x4.shared.b16 [%0], {%1,%2,%3,%4};" ::"r"(a), "r"(r0), "r"(r1), "r"(r2), "r"(r3) : "memory");
}
__device__ __forceinline__ void stsm4t(uint32_t a, uint32_t r0, uint32_t r1, uint32_t r2, uint32_t r3) {
  asm volatile("stmatrix.sync.aligned.m8n8.x4.trans.shared.b16 [%0], {%1,%2,%3,%4};" ::"r"(a), "r"(r0), "r"(r1), "r"(r2), "r"(r3) : "memory");
}
__device__ __forceinline__ uint32_t movm_t(uint32_t a) { uint32_t r; asm volatile("movmatrix.sync.aligned.m8n8.trans.b16 %0, %1;" : "=r"(r) : "r"(a)); return r; }
__device__ __forceinline__ uint32_t lds32(uint32_t a) { uint32_t v; asm volatile("ld.shared.b32 %0, [%1];" : "=r"(v) : "r"(a) : "memory"); return v; }
__device__ __forceinline__ float2 lds64f(uint32_t a) { float2 v; asm volatile("ld.shared.v2.f32 {%0,%1}, [%2];" : "=f"(v.x), "=f"(v.y) : "r"(a) : "memory"); return v; }
__device__ __forceinline__ float4 lds128f(uint32_t a) { float4 v; asm volatile("ld.shared.v4.f32 {%0,%1,%2,%3}, [%4];" : "=f"(v.x), "=f"(v.y), "=f"(v.z), "=f"(v.w) : "r"(a) : "memory"); return v; }
__device__ __forceinline__ uint4 lds128(uint32_t a) { uint4 v; asm volatile("ld.shared.v4.b32 {%0,%1,%2,%3}, [%4];" : "=r"(v.x), "=r"(v.y), "=r"(v.z), "=r"(v.w) : "r"(a) : "memory"); return v; }
__device__ __forceinline__ void sts128(uint32_t a, uint4 v) { asm volatile("st.shared.v4.b32 [%0], {%1,%2,%3,%4};" ::"r"(a), "r"(v.x), "r"(v.y), "r"(v.z), "r"(v.w) : "memory"); }
__device__ __forceinline__ void sts128f(uint32_t a, float x, float y, float z, float w) { asm volatile("st.shared.v4.f32 [%0], {%1,%2,%3,%4};" ::"r"(a), "f"(x), "f"(y), "f"(z), "f"(w) : "memory"); }
__device__ __forceinline__ void sts32f(uint32_t a, float v) { asm volatile("st.shared.f32 [%0], %1;" ::"r"(a), "f"(v) : "memory"); }
__device__ __forceinline__ void sts16(uint32_t a, uint16_t v) { asm volatile("st.shared.u16 [%0], %1;" ::"r"(a), "h"(v) : "memory"); }
__device__ __forceinline__ uint32_t lds16(uint32_t a) { uint16_t v; asm volatile("ld.shared.u16 %0, [%1];" : "=h"(v) : "r"(a) : "memory"); return v; }
__device__ __forceinline__ uint32_t packbf(float lo, float hi) { uint32_t r; asm("cvt.rn.bf16x2.f32 %0, %1, %2;" : "=r"(r) : "f"(hi), "f"(lo)); return r; }
__device__ __forceinline__ float bf_lo(uint32_t v) { return __uint_as_float(v << 16); }
__device__ __forceinline__ float bf_hi(uint32_t v) { return __uint_as_float(v & 0xffff0000u); }
__device__ __forceinline__ float ex2(float x) { float r; asm("ex2.approx.ftz.f32 %0, %1;" : "=f"(r) : "f"(x)); return r; }
__device__ __forceinline__ float rsqrt_approx(float x) { float r; asm("rsqrt.approx.ftz.f32 %0, %1;" : "=f"(r) : "f"(x)); return r; }
__device__ __forceinline__ float rcp_approx(float x) { float r; asm("rcp.approx.ftz.f32 %0, %1;" : "=f"(r) : "f"(x)); return r; }
__device__ __forceinline__ void mma_bf16(float* d, const uint32_t* a, uint32_t b0, uint32_t b1) {
  asm("mma.sync.aligned.m16n8k16.row.col.f32.bf16.bf16.f32 {%0,%1,%2,%3}, {%4,%5,%6,%7}, {%8,%9}, {%0,%1,%2,%3};"
               : "+f"(d[0]), "+f"(d[1]), "+f"(d[2]), "+f"(d[3]) : "r"(a[0]), "r"(a[1]), "r"(a[2]), "r"(a[3]), "r"(b0), "r"(b1));
}
__device__ __forceinline__ void red_release(unsigned* p) { asm volatile("red.release.gpu.global.add.u32 [%0], 1;" ::"l"(p) : "memory"); }
__device__ __forceinline__ void red_relaxed(unsigned* p) { asm volatile("red.relaxed.gpu.global.add.u32 [%0], 1;" ::"l"(p) : "memory"); }
__device__ __forceinline__ unsigned ld_relaxed(const unsigned* p) { unsigned v; asm volatile("ld.relaxed.gpu.global.u32 %0, [%1];" : "=r"(v) : "l"(p) : "memory"); return v; }
__device__ __forceinline__ void spin_until(const unsigned* p, unsigned target) {
  int it = 0;
  while ((int)(ld_relaxed(p) - target) < 0) {
    if (++it > (1 << 23)) __trap();
  }
}
template <typename T> __device__ __forceinline__ void pin(T*& p) { asm volatile("" : "+l"(p) :: "memory"); }
__device__ __forceinline__ void pin(uint32_t& v) { asm volatile("" : "+r"(v) :: "memory"); }
__device__ __forceinline__ void spin_hint(const unsigned* p, unsigned target) {
  spin_until(p, target);
}
__device__ __forceinline__ uint4 ld_tagged(const uint4* p) { uint4 v; asm volatile("ld.relaxed.gpu.global.v4.u32 {%0,%1,%2,%3}, [%4];" : "=r"(v.x), "=r"(v.y), "=r"(v.z), "=r"(v.w) : "l"(p) : "memory"); return v; }
__device__ __forceinline__ uint32_t hadd2(uint32_t a, uint32_t b) { uint32_t r; asm("add.rn.bf16x2 %0, %1, %2;" : "=r"(r) : "r"(a), "r"(b)); return r; }

__device__ __forceinline__ uint32_t hfma2(uint32_t a, uint32_t b, uint32_t c) { uint32_t r; asm("fma.rn.bf16x2 %0, %1, %2, %3;" : "=r"(r) : "r"(a), "r"(b), "r"(c)); return r; }
__device__ __forceinline__ void sts32(uint32_t a, uint32_t v) { asm volatile("st.shared.u32 [%0], %1;" ::"r"(a), "r"(v) : "memory"); }

template <int N> __device__ __forceinline__ void acc_fence(float* a) {
#pragma unroll
  for (int i = 0; i < N; i++) asm volatile("" : "+f"(a[i]) :: "memory");
}

template<int N,int TB> __device__ __forceinline__ void wgmma_rs(float* d, const uint32_t* a, uint64_t db, int sd);
template<int N,int TA,int TB> __device__ __forceinline__ void wgmma_ss(float* d, uint64_t da, uint64_t db, int sd);
template<> __device__ __forceinline__ void wgmma_rs<64,0>(float* d, const uint32_t* a, uint64_t db, int sd) {
  asm volatile("{\n.reg .pred p;\nsetp.ne.b32 p, %37, 0;\nwgmma.mma_async.sync.aligned.m64n64k16.f32.bf16.bf16 {%0,%1,%2,%3,%4,%5,%6,%7,%8,%9,%10,%11,%12,%13,%14,%15,%16,%17,%18,%19,%20,%21,%22,%23,%24,%25,%26,%27,%28,%29,%30,%31}, {%32,%33,%34,%35}, %36, p, 1, 1, 0;\n}\n"
   : "+f"(d[0]),"+f"(d[1]),"+f"(d[2]),"+f"(d[3]),"+f"(d[4]),"+f"(d[5]),"+f"(d[6]),"+f"(d[7]),"+f"(d[8]),"+f"(d[9]),"+f"(d[10]),"+f"(d[11]),"+f"(d[12]),"+f"(d[13]),"+f"(d[14]),"+f"(d[15]),"+f"(d[16]),"+f"(d[17]),"+f"(d[18]),"+f"(d[19]),"+f"(d[20]),"+f"(d[21]),"+f"(d[22]),"+f"(d[23]),"+f"(d[24]),"+f"(d[25]),"+f"(d[26]),"+f"(d[27]),"+f"(d[28]),"+f"(d[29]),"+f"(d[30]),"+f"(d[31])
   : "r"(a[0]), "r"(a[1]), "r"(a[2]), "r"(a[3]), "l"(db), "r"(sd));
}
template<> __device__ __forceinline__ void wgmma_rs<56,0>(float* d, const uint32_t* a, uint64_t db, int sd) {
  asm volatile("{\n.reg .pred p;\nsetp.ne.b32 p, %33, 0;\nwgmma.mma_async.sync.aligned.m64n56k16.f32.bf16.bf16 {%0,%1,%2,%3,%4,%5,%6,%7,%8,%9,%10,%11,%12,%13,%14,%15,%16,%17,%18,%19,%20,%21,%22,%23,%24,%25,%26,%27}, {%28,%29,%30,%31}, %32, p, 1, 1, 0;\n}\n"
   : "+f"(d[0]),"+f"(d[1]),"+f"(d[2]),"+f"(d[3]),"+f"(d[4]),"+f"(d[5]),"+f"(d[6]),"+f"(d[7]),"+f"(d[8]),"+f"(d[9]),"+f"(d[10]),"+f"(d[11]),"+f"(d[12]),"+f"(d[13]),"+f"(d[14]),"+f"(d[15]),"+f"(d[16]),"+f"(d[17]),"+f"(d[18]),"+f"(d[19]),"+f"(d[20]),"+f"(d[21]),"+f"(d[22]),"+f"(d[23]),"+f"(d[24]),"+f"(d[25]),"+f"(d[26]),"+f"(d[27])
   : "r"(a[0]), "r"(a[1]), "r"(a[2]), "r"(a[3]), "l"(db), "r"(sd));
}
template<> __device__ __forceinline__ void wgmma_rs<48,0>(float* d, const uint32_t* a, uint64_t db, int sd) {
  asm volatile("{\n.reg .pred p;\nsetp.ne.b32 p, %29, 0;\nwgmma.mma_async.sync.aligned.m64n48k16.f32.bf16.bf16 {%0,%1,%2,%3,%4,%5,%6,%7,%8,%9,%10,%11,%12,%13,%14,%15,%16,%17,%18,%19,%20,%21,%22,%23}, {%24,%25,%26,%27}, %28, p, 1, 1, 0;\n}\n"
   : "+f"(d[0]),"+f"(d[1]),"+f"(d[2]),"+f"(d[3]),"+f"(d[4]),"+f"(d[5]),"+f"(d[6]),"+f"(d[7]),"+f"(d[8]),"+f"(d[9]),"+f"(d[10]),"+f"(d[11]),"+f"(d[12]),"+f"(d[13]),"+f"(d[14]),"+f"(d[15]),"+f"(d[16]),"+f"(d[17]),"+f"(d[18]),"+f"(d[19]),"+f"(d[20]),"+f"(d[21]),"+f"(d[22]),"+f"(d[23])
   : "r"(a[0]), "r"(a[1]), "r"(a[2]), "r"(a[3]), "l"(db), "r"(sd));
}
template<> __device__ __forceinline__ void wgmma_rs<40,0>(float* d, const uint32_t* a, uint64_t db, int sd) {
  asm volatile("{\n.reg .pred p;\nsetp.ne.b32 p, %25, 0;\nwgmma.mma_async.sync.aligned.m64n40k16.f32.bf16.bf16 {%0,%1,%2,%3,%4,%5,%6,%7,%8,%9,%10,%11,%12,%13,%14,%15,%16,%17,%18,%19}, {%20,%21,%22,%23}, %24, p, 1, 1, 0;\n}\n"
   : "+f"(d[0]),"+f"(d[1]),"+f"(d[2]),"+f"(d[3]),"+f"(d[4]),"+f"(d[5]),"+f"(d[6]),"+f"(d[7]),"+f"(d[8]),"+f"(d[9]),"+f"(d[10]),"+f"(d[11]),"+f"(d[12]),"+f"(d[13]),"+f"(d[14]),"+f"(d[15]),"+f"(d[16]),"+f"(d[17]),"+f"(d[18]),"+f"(d[19])
   : "r"(a[0]), "r"(a[1]), "r"(a[2]), "r"(a[3]), "l"(db), "r"(sd));
}
template<> __device__ __forceinline__ void wgmma_rs<32,0>(float* d, const uint32_t* a, uint64_t db, int sd) {
  asm volatile("{\n.reg .pred p;\nsetp.ne.b32 p, %21, 0;\nwgmma.mma_async.sync.aligned.m64n32k16.f32.bf16.bf16 {%0,%1,%2,%3,%4,%5,%6,%7,%8,%9,%10,%11,%12,%13,%14,%15}, {%16,%17,%18,%19}, %20, p, 1, 1, 0;\n}\n"
   : "+f"(d[0]),"+f"(d[1]),"+f"(d[2]),"+f"(d[3]),"+f"(d[4]),"+f"(d[5]),"+f"(d[6]),"+f"(d[7]),"+f"(d[8]),"+f"(d[9]),"+f"(d[10]),"+f"(d[11]),"+f"(d[12]),"+f"(d[13]),"+f"(d[14]),"+f"(d[15])
   : "r"(a[0]), "r"(a[1]), "r"(a[2]), "r"(a[3]), "l"(db), "r"(sd));
}
template<> __device__ __forceinline__ void wgmma_rs<24,0>(float* d, const uint32_t* a, uint64_t db, int sd) {
  asm volatile("{\n.reg .pred p;\nsetp.ne.b32 p, %17, 0;\nwgmma.mma_async.sync.aligned.m64n24k16.f32.bf16.bf16 {%0,%1,%2,%3,%4,%5,%6,%7,%8,%9,%10,%11}, {%12,%13,%14,%15}, %16, p, 1, 1, 0;\n}\n"
   : "+f"(d[0]),"+f"(d[1]),"+f"(d[2]),"+f"(d[3]),"+f"(d[4]),"+f"(d[5]),"+f"(d[6]),"+f"(d[7]),"+f"(d[8]),"+f"(d[9]),"+f"(d[10]),"+f"(d[11])
   : "r"(a[0]), "r"(a[1]), "r"(a[2]), "r"(a[3]), "l"(db), "r"(sd));
}
template<> __device__ __forceinline__ void wgmma_rs<16,0>(float* d, const uint32_t* a, uint64_t db, int sd) {
  asm volatile("{\n.reg .pred p;\nsetp.ne.b32 p, %13, 0;\nwgmma.mma_async.sync.aligned.m64n16k16.f32.bf16.bf16 {%0,%1,%2,%3,%4,%5,%6,%7}, {%8,%9,%10,%11}, %12, p, 1, 1, 0;\n}\n"
   : "+f"(d[0]),"+f"(d[1]),"+f"(d[2]),"+f"(d[3]),"+f"(d[4]),"+f"(d[5]),"+f"(d[6]),"+f"(d[7])
   : "r"(a[0]), "r"(a[1]), "r"(a[2]), "r"(a[3]), "l"(db), "r"(sd));
}
template<> __device__ __forceinline__ void wgmma_rs<8,0>(float* d, const uint32_t* a, uint64_t db, int sd) {
  asm volatile("{\n.reg .pred p;\nsetp.ne.b32 p, %9, 0;\nwgmma.mma_async.sync.aligned.m64n8k16.f32.bf16.bf16 {%0,%1,%2,%3}, {%4,%5,%6,%7}, %8, p, 1, 1, 0;\n}\n"
   : "+f"(d[0]),"+f"(d[1]),"+f"(d[2]),"+f"(d[3])
   : "r"(a[0]), "r"(a[1]), "r"(a[2]), "r"(a[3]), "l"(db), "r"(sd));
}
template<> __device__ __forceinline__ void wgmma_ss<64,1,0>(float* d, uint64_t da, uint64_t db, int sd) {
  asm volatile("{\n.reg .pred p;\nsetp.ne.b32 p, %34, 0;\nwgmma.mma_async.sync.aligned.m64n64k16.f32.bf16.bf16 {%0,%1,%2,%3,%4,%5,%6,%7,%8,%9,%10,%11,%12,%13,%14,%15,%16,%17,%18,%19,%20,%21,%22,%23,%24,%25,%26,%27,%28,%29,%30,%31}, %32, %33, p, 1, 1, 1, 0;\n}\n"
   : "+f"(d[0]),"+f"(d[1]),"+f"(d[2]),"+f"(d[3]),"+f"(d[4]),"+f"(d[5]),"+f"(d[6]),"+f"(d[7]),"+f"(d[8]),"+f"(d[9]),"+f"(d[10]),"+f"(d[11]),"+f"(d[12]),"+f"(d[13]),"+f"(d[14]),"+f"(d[15]),"+f"(d[16]),"+f"(d[17]),"+f"(d[18]),"+f"(d[19]),"+f"(d[20]),"+f"(d[21]),"+f"(d[22]),"+f"(d[23]),"+f"(d[24]),"+f"(d[25]),"+f"(d[26]),"+f"(d[27]),"+f"(d[28]),"+f"(d[29]),"+f"(d[30]),"+f"(d[31])
   : "l"(da), "l"(db), "r"(sd));
}
template<> __device__ __forceinline__ void wgmma_ss<64,0,1>(float* d, uint64_t da, uint64_t db, int sd) {
  asm volatile("{\n.reg .pred p;\nsetp.ne.b32 p, %34, 0;\nwgmma.mma_async.sync.aligned.m64n64k16.f32.bf16.bf16 {%0,%1,%2,%3,%4,%5,%6,%7,%8,%9,%10,%11,%12,%13,%14,%15,%16,%17,%18,%19,%20,%21,%22,%23,%24,%25,%26,%27,%28,%29,%30,%31}, %32, %33, p, 1, 1, 0, 1;\n}\n"
   : "+f"(d[0]),"+f"(d[1]),"+f"(d[2]),"+f"(d[3]),"+f"(d[4]),"+f"(d[5]),"+f"(d[6]),"+f"(d[7]),"+f"(d[8]),"+f"(d[9]),"+f"(d[10]),"+f"(d[11]),"+f"(d[12]),"+f"(d[13]),"+f"(d[14]),"+f"(d[15]),"+f"(d[16]),"+f"(d[17]),"+f"(d[18]),"+f"(d[19]),"+f"(d[20]),"+f"(d[21]),"+f"(d[22]),"+f"(d[23]),"+f"(d[24]),"+f"(d[25]),"+f"(d[26]),"+f"(d[27]),"+f"(d[28]),"+f"(d[29]),"+f"(d[30]),"+f"(d[31])
   : "l"(da), "l"(db), "r"(sd));
}
template<> __device__ __forceinline__ void wgmma_ss<192,0,1>(float* d, uint64_t da, uint64_t db, int sd) {
  asm volatile("{\n.reg .pred p;\nsetp.ne.b32 p, %98, 0;\nwgmma.mma_async.sync.aligned.m64n192k16.f32.bf16.bf16 {%0,%1,%2,%3,%4,%5,%6,%7,%8,%9,%10,%11,%12,%13,%14,%15,%16,%17,%18,%19,%20,%21,%22,%23,%24,%25,%26,%27,%28,%29,%30,%31,%32,%33,%34,%35,%36,%37,%38,%39,%40,%41,%42,%43,%44,%45,%46,%47,%48,%49,%50,%51,%52,%53,%54,%55,%56,%57,%58,%59,%60,%61,%62,%63,%64,%65,%66,%67,%68,%69,%70,%71,%72,%73,%74,%75,%76,%77,%78,%79,%80,%81,%82,%83,%84,%85,%86,%87,%88,%89,%90,%91,%92,%93,%94,%95}, %96, %97, p, 1, 1, 0, 1;\n}\n"
   : "+f"(d[0]),"+f"(d[1]),"+f"(d[2]),"+f"(d[3]),"+f"(d[4]),"+f"(d[5]),"+f"(d[6]),"+f"(d[7]),"+f"(d[8]),"+f"(d[9]),"+f"(d[10]),"+f"(d[11]),"+f"(d[12]),"+f"(d[13]),"+f"(d[14]),"+f"(d[15]),"+f"(d[16]),"+f"(d[17]),"+f"(d[18]),"+f"(d[19]),"+f"(d[20]),"+f"(d[21]),"+f"(d[22]),"+f"(d[23]),"+f"(d[24]),"+f"(d[25]),"+f"(d[26]),"+f"(d[27]),"+f"(d[28]),"+f"(d[29]),"+f"(d[30]),"+f"(d[31]),"+f"(d[32]),"+f"(d[33]),"+f"(d[34]),"+f"(d[35]),"+f"(d[36]),"+f"(d[37]),"+f"(d[38]),"+f"(d[39]),"+f"(d[40]),"+f"(d[41]),"+f"(d[42]),"+f"(d[43]),"+f"(d[44]),"+f"(d[45]),"+f"(d[46]),"+f"(d[47]),"+f"(d[48]),"+f"(d[49]),"+f"(d[50]),"+f"(d[51]),"+f"(d[52]),"+f"(d[53]),"+f"(d[54]),"+f"(d[55]),"+f"(d[56]),"+f"(d[57]),"+f"(d[58]),"+f"(d[59]),"+f"(d[60]),"+f"(d[61]),"+f"(d[62]),"+f"(d[63]),"+f"(d[64]),"+f"(d[65]),"+f"(d[66]),"+f"(d[67]),"+f"(d[68]),"+f"(d[69]),"+f"(d[70]),"+f"(d[71]),"+f"(d[72]),"+f"(d[73]),"+f"(d[74]),"+f"(d[75]),"+f"(d[76]),"+f"(d[77]),"+f"(d[78]),"+f"(d[79]),"+f"(d[80]),"+f"(d[81]),"+f"(d[82]),"+f"(d[83]),"+f"(d[84]),"+f"(d[85]),"+f"(d[86]),"+f"(d[87]),"+f"(d[88]),"+f"(d[89]),"+f"(d[90]),"+f"(d[91]),"+f"(d[92]),"+f"(d[93]),"+f"(d[94]),"+f"(d[95])
   : "l"(da), "l"(db), "r"(sd));
}
template<> __device__ __forceinline__ void wgmma_ss<192,1,1>(float* d, uint64_t da, uint64_t db, int sd) {
  asm volatile("{\n.reg .pred p;\nsetp.ne.b32 p, %98, 0;\nwgmma.mma_async.sync.aligned.m64n192k16.f32.bf16.bf16 {%0,%1,%2,%3,%4,%5,%6,%7,%8,%9,%10,%11,%12,%13,%14,%15,%16,%17,%18,%19,%20,%21,%22,%23,%24,%25,%26,%27,%28,%29,%30,%31,%32,%33,%34,%35,%36,%37,%38,%39,%40,%41,%42,%43,%44,%45,%46,%47,%48,%49,%50,%51,%52,%53,%54,%55,%56,%57,%58,%59,%60,%61,%62,%63,%64,%65,%66,%67,%68,%69,%70,%71,%72,%73,%74,%75,%76,%77,%78,%79,%80,%81,%82,%83,%84,%85,%86,%87,%88,%89,%90,%91,%92,%93,%94,%95}, %96, %97, p, 1, 1, 1, 1;\n}\n"
   : "+f"(d[0]),"+f"(d[1]),"+f"(d[2]),"+f"(d[3]),"+f"(d[4]),"+f"(d[5]),"+f"(d[6]),"+f"(d[7]),"+f"(d[8]),"+f"(d[9]),"+f"(d[10]),"+f"(d[11]),"+f"(d[12]),"+f"(d[13]),"+f"(d[14]),"+f"(d[15]),"+f"(d[16]),"+f"(d[17]),"+f"(d[18]),"+f"(d[19]),"+f"(d[20]),"+f"(d[21]),"+f"(d[22]),"+f"(d[23]),"+f"(d[24]),"+f"(d[25]),"+f"(d[26]),"+f"(d[27]),"+f"(d[28]),"+f"(d[29]),"+f"(d[30]),"+f"(d[31]),"+f"(d[32]),"+f"(d[33]),"+f"(d[34]),"+f"(d[35]),"+f"(d[36]),"+f"(d[37]),"+f"(d[38]),"+f"(d[39]),"+f"(d[40]),"+f"(d[41]),"+f"(d[42]),"+f"(d[43]),"+f"(d[44]),"+f"(d[45]),"+f"(d[46]),"+f"(d[47]),"+f"(d[48]),"+f"(d[49]),"+f"(d[50]),"+f"(d[51]),"+f"(d[52]),"+f"(d[53]),"+f"(d[54]),"+f"(d[55]),"+f"(d[56]),"+f"(d[57]),"+f"(d[58]),"+f"(d[59]),"+f"(d[60]),"+f"(d[61]),"+f"(d[62]),"+f"(d[63]),"+f"(d[64]),"+f"(d[65]),"+f"(d[66]),"+f"(d[67]),"+f"(d[68]),"+f"(d[69]),"+f"(d[70]),"+f"(d[71]),"+f"(d[72]),"+f"(d[73]),"+f"(d[74]),"+f"(d[75]),"+f"(d[76]),"+f"(d[77]),"+f"(d[78]),"+f"(d[79]),"+f"(d[80]),"+f"(d[81]),"+f"(d[82]),"+f"(d[83]),"+f"(d[84]),"+f"(d[85]),"+f"(d[86]),"+f"(d[87]),"+f"(d[88]),"+f"(d[89]),"+f"(d[90]),"+f"(d[91]),"+f"(d[92]),"+f"(d[93]),"+f"(d[94]),"+f"(d[95])
   : "l"(da), "l"(db), "r"(sd));
}

template <bool TR>
__device__ __forceinline__ void gemm_section(float* acc, float& mean0, float& mean1, float& rstd0, float& rstd1,
                                             uint32_t sb, int blk, int hg, int wg, int w, int lane) {
  constexpr int layer = TR ? 1 : 0;
  constexpr int TURN = TR ? TURN1 : TURN0;
  constexpr int LSTAT = TURN < 4 ? TURN - 1 : 3;
  const uint32_t bar = sb + SM_BAR;
  const int g = lane >> 2, t = lane & 3;
  const bool leader = (w == 0) && (lane == 0);
  const int statpos = hg < 3 ? 1 : wg ? LSTAT : TR ? 3 : 2;
  const bool copy = hg >= 3 && wg == 0;
  const int cut = wg ? TURN : 4;
  auto wait_full = [&](int c) {
    mbar_wait(bar + 8 * (B_XF + 8 * wg + c), layer);
    mbar_wait(bar + 8 * (B_WF + c), layer);
  };
  auto peek = [&](int c) {
    const bool x = mbar_test(bar + 8 * (B_XF + 8 * wg + c), layer), y = mbar_test(bar + 8 * (B_WF + c), layer);
    return x && y;
  };
  const uint64_t da0 = mkdesc(sb, TR ? 8192 : 16, 1024, 1), db0 = mkdesc(sb, 8192, 1024, 1);
  uint32_t xt = wg ? 0xfedcba98u : 0x21043210u;
  uint64_t wt = 0x0816131005161310ull;
  uint64_t da = da0 + ((xt & 15) << 9), db = db0 + (16 << 9);
  auto issue = [&](int c, int first) {
    wg_fence();
#pragma unroll
    for (int ks = 0; ks < 4; ks++) wgmma_ss<192, TR ? 1 : 0, 1>(acc, da + (TR ? ks * 128 : ks * 2), db + ks * 128, !first || ks != 0);
    wg_commit();
    xt >>= 4; wt >>= 8;
    da = da0 + ((xt & 15) << 9); db = db0 + (((uint32_t)wt & 31) << 9);
  };
  wait_full(0);
  bool ready = peek(1);
  issue(0, 1);
  TSW(0);
#pragma unroll 1
  for (int c = 1; c < cut; c++) {
    if (!ready) wait_full(c);
    issue(c, 0);
    ready = peek(c + 1);
    wg_wait<1>();
    if (leader) mbar_arrive(bar + 8 * (B_DN + 8 * wg + c - 1));
    if (wg == 1 && c == cut - 1) {
      wg_wait<0>();
      if (leader) mbar_arrive(bar + 8 * (B_DN + 8 + c));
    }
    if (c == statpos) {
      mbar_wait(bar + 8 * (copy ? B_SC : B_XF + 8 * wg + hg), layer);
      uint32_t A[16];
      const uint32_t xb = sb + (copy ? P_R : 8 * wg + hg) * PG;
#pragma unroll
      for (int ks = 0; ks < 4; ks++) {
        if (!TR) {
          const int row = 16 * w + (lane & 15), kc = 2 * ks + (lane >> 4);
          ldsm4(&A[4 * ks], xb + row * 128 + ((kc ^ (row & 7)) << 4));
        } else {
          const int k = 16 * ks + (lane & 7) + 8 * (lane >> 4), pc = 2 * w + ((lane >> 3) & 1);
          ldsm4t(&A[4 * ks], xb + k * 128 + ((pc ^ (k & 7)) << 4));
        }
      }
      float s0 = 0.f, q0 = 0.f, s1 = 0.f, q1 = 0.f;
#pragma unroll
      for (int i = 0; i < 16; i += 2) {
        const float a = bf_lo(A[i]), b = bf_hi(A[i]), c_ = bf_lo(A[i + 1]), d = bf_hi(A[i + 1]);
        s0 += a + b; q0 = fmaf(a, a, q0); q0 = fmaf(b, b, q0);
        s1 += c_ + d; q1 = fmaf(c_, c_, q1); q1 = fmaf(d, d, q1);
      }
#pragma unroll
      for (int o = 1; o <= 2; o <<= 1) {
        s0 += __shfl_xor_sync(~0u, s0, o); q0 += __shfl_xor_sync(~0u, q0, o);
        s1 += __shfl_xor_sync(~0u, s1, o); q1 += __shfl_xor_sync(~0u, q1, o);
      }
      if (t < 2)
        asm volatile("red.relaxed.gpu.global.add.v4.f32 [%0], {%1,%2,%3,%4};" ::"l"(g_rows + layer * LSEQ + blk * 64 + 16 * w + g + 8 * t),
                     "f"(t ? s1 : s0), "f"(t ? q1 : q0), "f"(1.f), "f"(0.f) : "memory");
    }
  }
  if (wg == 1) {
#pragma unroll 1
    for (int c = cut; c < 8; c++) wait_full(c);
    ready = true;
    bar_sync(5, 256);
  }
#pragma unroll 1
  for (int c = cut; c < 8; c++) {
    if (!ready) wait_full(c);
    issue(c, 0);
    if (wg == 1) {
      wg_wait<2>();
      if (leader && c >= cut + 2) mbar_arrive(bar + 8 * (B_DN + 8 + c - 2));
    } else if (c == 7) {
      bar_arrive(5, 256);
    } else {
      ready = peek(c + 1);
      wg_wait<1>();
      if (leader && c < 6) mbar_arrive(bar + 8 * (B_DN + c - 1));
    }
  }
  mbar_wait(bar + 8 * (B_LN + wg), layer);
  const float4 ln = lds128f(sb + ln_off(wg) + (8 * w + g) * 16);
  mean0 = ln.x; rstd0 = ln.y; mean1 = ln.z; rstd1 = ln.w;
  wg_wait<0>();
  acc_fence<96>(acc);
  if (leader) mbar_arrive(bar + 8 * (B_DN + 8 * wg + 7));
}

__device__ __forceinline__ void attn_phase(const Params& p, uint32_t sb, int layer, int rb, int hg, int wg, int w) {
  const int lane = opaque_tid() & 31;
  const int g = lane >> 2, t = lane & 3;
  const uint32_t bar = sb + SM_BAR;
  const int blk = 16 * wg + rb;
  float acc[96];
  float2 cs[24];
  float mean0, mean1, rstd0, rstd1;
  if (layer) gemm_section<true>(acc, mean0, mean1, rstd0, rstd1, sb, blk, hg, wg, w, lane);
  else gemm_section<false>(acc, mean0, mean1, rstd0, rstd1, sb, blk, hg, wg, w, lane);
  TSW(1);
#pragma unroll
  for (int j = 8; j < 24; j++) cs[j] = lds64f(sb + SM_CS + 4 * (8 * j + 2 * t));
  const uint32_t kvx = sb + (wg ? 22 : 0) * PG;

  uint32_t kb[4][8], vb[4][8], qa[4][4];
  {
    const float nm0 = -mean0 * rstd0, nm1 = -mean1 * rstd1;
    const int st_row = 16 * w + (lane & 7) + 8 * ((lane >> 3) & 1);
    const uint32_t st_base = kvx + st_row * 256;
    const bool sender = (w == 3 && blk < 31);
    uint4* halo = &g_halo[(blk * 8 + hg) * 256 + lane];
    uint32_t r[4][2][4];
#pragma unroll
    for (int h = 0; h < 4; h++) {
#pragma unroll
      for (int kv = 0; kv < 2; kv++) {
#pragma unroll
        for (int dh = 0; dh < 2; dh++) {
          const int j = 8 + kv * 8 + 2 * h + dh;
          const float2 c2 = cs[j];
          const float v0 = fmaf(acc[4 * j + 0], rstd0, nm0 * c2.x), v1 = fmaf(acc[4 * j + 1], rstd0, nm0 * c2.y);
          const float v2 = fmaf(acc[4 * j + 2], rstd1, nm1 * c2.x), v3 = fmaf(acc[4 * j + 3], rstd1, nm1 * c2.y);
          r[h][kv][2 * dh] = packbf(v0, v1);
          r[h][kv][2 * dh + 1] = packbf(v2, v3);
        }
      }
      if (sender) {
        stg128(halo + (2 * h) * 32, make_uint4(r[h][0][0], r[h][0][2], r[h][0][1], r[h][0][3]));
        stg128(halo + (2 * h + 1) * 32, make_uint4(r[h][1][0], r[h][1][1], r[h][1][2], r[h][1][3]));
      }
    }
#pragma unroll
    for (int j = 0; j < 8; j++) cs[j] = lds64f(sb + SM_CS + 4 * (8 * j + 2 * t));
    mbar_wait(bar + 8 * (B_DN + 7), layer);
#pragma unroll
    for (int h = 0; h < 4; h++) {
#pragma unroll
      for (int kv = 0; kv < 2; kv++) {
        const int chunk = 4 * h + 2 * kv + (lane >> 4);
        if (w < 3) stsm4(st_base + (((chunk & 8) | ((chunk ^ st_row) & 7)) << 4), r[h][kv][0], r[h][kv][1], r[h][kv][2], r[h][kv][3]);
      }
      kb[h][4] = r[h][0][0]; kb[h][5] = r[h][0][2]; kb[h][6] = r[h][0][1]; kb[h][7] = r[h][0][3];
      vb[h][4] = movm_t(r[h][1][0]); vb[h][5] = movm_t(r[h][1][1]); vb[h][6] = movm_t(r[h][1][2]); vb[h][7] = movm_t(r[h][1][3]);
    }
#pragma unroll
    for (int h = 0; h < 4; h++) {
#pragma unroll
      for (int dh = 0; dh < 2; dh++) {
        const int j = 2 * h + dh;
        const float2 c2 = cs[j];
        qa[h][2 * dh] = packbf(fmaf(-mean0, c2.x, acc[4 * j + 0]), fmaf(-mean0, c2.y, acc[4 * j + 1]));
        qa[h][2 * dh + 1] = packbf(fmaf(-mean1, c2.x, acc[4 * j + 2]), fmaf(-mean1, c2.y, acc[4 * j + 3]));
      }
    }
  }
  bar_sync(2 + wg, 128);
  TSW(2);
  {
    const uint32_t prev_base = kvx + (16 * w - 16) * 256;
    const int mi = lane >> 3;
    const int r = 8 * (mi >> 1) + (lane & 7), r2 = 8 * (mi & 1) + (lane & 7);
    if (w != 0) {
#pragma unroll
      for (int h = 0; h < 4; h++) {
        const int ch = 4 * h + (mi & 1), ch2 = 4 * h + 2 + (mi >> 1);
        ldsm4(&kb[h][0], prev_base + r * 256 + (((ch & 8) | ((ch ^ r) & 7)) << 4));
        ldsm4t(&vb[h][0], prev_base + r2 * 256 + (((ch2 & 8) | ((ch2 ^ r2) & 7)) << 4));
      }
    } else if (blk > 0) {
      uint4* src = &g_halo[((blk - 1) * 8 + hg) * 256 + lane];
      uint4 hv[8];
      int it = 0;
      bool ok;
      do {
        ok = true;
#pragma unroll
        for (int i = 0; i < 8; i++) hv[i] = ld_tagged(src + i * 32);
#pragma unroll
        for (int i = 0; i < 8; i++) ok = ok && hv[i].x != UNSET;
      } while (!__all_sync(~0u, ok) && ++it < (1 << 20));
      if (layer == 0) {
#pragma unroll
        for (int i = 0; i < 2; i++) stg128(src + i * 128 + (lane >> 1) * 6, make_uint4(UNSET, UNSET, UNSET, UNSET));
      }
#pragma unroll
      for (int h = 0; h < 4; h++) {
        kb[h][0] = hv[2 * h].x; kb[h][1] = hv[2 * h].y; kb[h][2] = hv[2 * h].z; kb[h][3] = hv[2 * h].w;
        vb[h][0] = movm_t(hv[2 * h + 1].x); vb[h][1] = movm_t(hv[2 * h + 1].y);
        vb[h][2] = movm_t(hv[2 * h + 1].z); vb[h][3] = movm_t(hv[2 * h + 1].w);
      }
    } else {
#pragma unroll
      for (int h = 0; h < 4; h++)
#pragma unroll
        for (int k = 0; k < 4; k++) kb[h][k] = vb[h][k] = 0u;
    }
    TSW(3);
  }
  uint4* op = (uint4*)g_O + ((layer * 32 + blk) * 8 + hg) * 512 + 64 * t + 16 * w + g;
  unsigned* ocnt = &g_cnt[(C_O + layer * 32 + blk) * 32];
  pin(op); pin(ocnt);
  mbar_wait(bar + 8 * (B_DN + 15), layer);
  TSW(4);

  const bool first = (blk == 0 && w == 0);
  const int e = t - (g >> 1);
  const bool par = g & 1, epos = e >= 1;
  const uint32_t pmask = par ? 0xffff0000u : 0x0000ffffu;
  const uint32_t mB0 = epos ? pmask : 0u, mB1 = epos ? 0u : pmask;
  const float cl2 = 0.25f * 1.4426950408889634f;
  const float sc0 = rstd0 * cl2, sc1 = rstd1 * cl2;
  const float NEG = -INFINITY;
  float vA0[4], vB0[4], vA1[4], vB1[4];
#pragma unroll
  for (int h = 0; h < 4; h++) {
    float S[4][4];
#pragma unroll
    for (int j = 0; j < 4; j++) {
      S[j][0] = S[j][1] = S[j][2] = S[j][3] = 0.f;
      mma_bf16(S[j], qa[h], kb[h][2 * j], kb[h][2 * j + 1]);
    }
    vA0[h] = par ? S[1][1] : S[1][0];
    vB0[h] = epos ? (par ? S[0][1] : S[0][0]) : (par ? S[2][1] : S[2][0]);
    vA1[h] = par ? S[2][3] : S[2][2];
    vB1[h] = epos ? (par ? S[1][3] : S[1][2]) : (par ? S[3][3] : S[3][2]);
    if (first) { vA0[h] = NEG; if (epos) { vB0[h] = NEG; vB1[h] = NEG; } }
  }
  float m0[4], m1[4];
#pragma unroll
  for (int h = 0; h < 4; h++) { m0[h] = fmaxf(vA0[h], vB0[h]); m1[h] = fmaxf(vA1[h], vB1[h]); }
#pragma unroll
  for (int o = 1; o <= 2; o <<= 1) {
#pragma unroll
    for (int h = 0; h < 4; h++) {
      m0[h] = fmaxf(m0[h], __shfl_xor_sync(~0u, m0[h], o));
      m1[h] = fmaxf(m1[h], __shfl_xor_sync(~0u, m1[h], o));
    }
  }
  float O0[4][4], O1[4][4], Z[4][4];
#pragma unroll
  for (int h = 0; h < 4; h++) {
    const float mm0 = -m0[h] * sc0, mm1 = -m1[h] * sc1;
    const float pA0 = ex2(fmaf(vA0[h], sc0, mm0)), pB0 = ex2(fmaf(vB0[h], sc0, mm0));
    const float pA1 = ex2(fmaf(vA1[h], sc1, mm1)), pB1 = ex2(fmaf(vB1[h], sc1, mm1));
    const uint32_t hA0 = packbf(pA0, pA0), hB0 = packbf(pB0, pB0), hA1 = packbf(pA1, pA1), hB1 = packbf(pB1, pB1);
    const uint32_t P0[4] = {hB0 & mB0, 0u, hA0 & pmask, hB1 & mB0};
    const uint32_t P1[4] = {hB0 & mB1, hA1 & pmask, 0u, hB1 & mB1};
#pragma unroll
    for (int k = 0; k < 4; k++) O0[h][k] = O1[h][k] = Z[h][k] = 0.f;
    mma_bf16(O0[h], P0, vb[h][0], vb[h][1]); mma_bf16(O1[h], P0, vb[h][2], vb[h][3]); mma_bf16(Z[h], P0, 0x3f803f80u, 0x3f803f80u);
    mma_bf16(O0[h], P1, vb[h][4], vb[h][5]); mma_bf16(O1[h], P1, vb[h][6], vb[h][7]); mma_bf16(Z[h], P1, 0x3f803f80u, 0x3f803f80u);
  }
  if (lane == 0) mbar_arrive(bar + 8 * (B_OST + wg));
#pragma unroll
  for (int h = 0; h < 4; h += 2) {
    const float i0 = rcp_approx(Z[h][0]), i1 = rcp_approx(Z[h][2]), j0 = rcp_approx(Z[h + 1][0]), j1 = rcp_approx(Z[h + 1][2]);
    stg128(op + 128 * h, make_uint4(packbf(O0[h][0] * i0, O0[h][1] * i0), packbf(O1[h][0] * i0, O1[h][1] * i0),
                                   packbf(O0[h + 1][0] * j0, O0[h + 1][1] * j0), packbf(O1[h + 1][0] * j0, O1[h + 1][1] * j0)));
    stg128(op + 128 * h + 8, make_uint4(packbf(O0[h][2] * i1, O0[h][3] * i1), packbf(O1[h][2] * i1, O1[h][3] * i1),
                                            packbf(O0[h + 1][2] * j1, O0[h + 1][3] * j1), packbf(O1[h + 1][2] * j1, O1[h + 1][3] * j1)));
  }
  TSW(5);
  __syncwarp();
  if (elect_one()) red_relaxed(ocnt);
  TSW(6);
}

__device__ __forceinline__ void conv_load(uint32_t* A, uint32_t pe);
__device__ __forceinline__ void proj_phase(const Params& p, uint32_t sb, int layer, int rb, int q, uint32_t* A0, uint32_t* A1) {
  const int lane = opaque_tid() & 31;
  const int wg = __shfl_sync(~0u, opaque_tid() >> 7, 0), w = __shfl_sync(~0u, (opaque_tid() >> 5) & 3, 0);
  const bool TR = layer != 0;
  const int t = lane & 3;
  const uint32_t bar = sb + SM_BAR;
  const uint32_t rbx = sb + (P_R + wg) * PG;
  const uint32_t rsrc = sb + (wg ? 2 : P_R) * PG;
  const int blk = 16 * wg + rb;
  mbar_wait(bar + 8 * (B_RF + wg), layer);
  mbar_wait(bar + 8 * B_WOF, layer);
  const uint32_t stg = sb + (wg ? SM_KGT : SM_STG);
  if (layer) {
    const uint32_t pe = sb + cv_pe(wg, 1) + 4 * (16 + 16 * w + (lane >> 2) - 2 * t);
    mbar_wait(bar + 8 * B_PE, 1);
    conv_load(A0, pe);
    conv_load(A1, pe + 2 * 4480);
    __syncwarp();
    if (lane == 0) mbar_arrive(bar + 8 * B_AL);
  } else {
#pragma unroll
    for (int i = 0; i < 68; i++) {
      asm volatile("mov.b32 %0, 0;" : "=r"(A0[i]));
      asm volatile("mov.b32 %0, 0;" : "=r"(A1[i]));
    }
  }
  bool clean = false, staged = false;
#pragma unroll 1
  for (int attempt = 0; attempt < MAX_RETRY; attempt++) {
  uint32_t res[16];
  if (!TR) {
#pragma unroll
    for (int j = 0; j < 8; j += 2) {
      const int mi = lane >> 3;
      const int row = 16 * w + (lane & 7) + 8 * (mi & 1), ch = j + (mi >> 1);
      ldsm4(&res[2 * j], rsrc + row * 128 + ((ch ^ (row & 7)) << 4));
    }
  } else {
#pragma unroll
    for (int j = 0; j < 8; j += 2) {
      const int mi = lane >> 3;
      const int line = 8 * (j + (mi >> 1)) + (lane & 7), pc = 2 * w + (mi & 1);
      ldsm4t(&res[2 * j], rsrc + line * 128 + ((pc ^ (line & 7)) << 4));
    }
  }
  float acc[32];
#pragma unroll
  for (int j = 0; j < 16; j++) { acc[2 * j] = bf_lo(res[j]); acc[2 * j + 1] = bf_hi(res[j]); }
  acc_fence<32>(acc);
  if (wg) mbar_wait(bar + 8 * B_PG, layer);
  const int wg2 = __shfl_sync(~0u, opaque_tid() >> 7, 0);
  const uint64_t da0 = mkdesc(sb, 1024, 128, 0), db0 = mkdesc(sb, 8192, 1024, 1);
#pragma unroll
  for (int c = 0; c < 4; c++) {
    mbar_wait(bar + 8 * (B_OF + 4 * wg + c), layer);
    if (c == 0) TSW(7);
    const uint64_t da = da0 + (uint32_t)(o_page(wg2, c) * 512);
#pragma unroll
    for (int ks = 0; ks < 8; ks++) {
      if (ks % 4 == 0) { if (ks) wg_commit(); if (wg2) wg_wait<0>(); wg_fence(); }
      wgmma_ss<64, 0, 1>(acc, da + ks * 128, db0 + wo_page(2 * c + (ks >> 2)) * 512 + (ks & 3) * 128, 1);
    }
    wg_commit();
  }
  if (wg) mbar_wait(bar + 8 * B_KG, 0);
  wg_wait<0>();
  acc_fence<32>(acc);
  TSW(8);
  if (!clean) {
    const float chk = acc[0] + acc[2];
    clean = __all_sync(~0u, chk == chk);
    if (clean && lane == 0) mbar_arrive(bar + 8 * (B_PDONE + wg));
  }
  float s0 = 0.f, q0 = 0.f, s1 = 0.f, q1 = 0.f;
  uint32_t o[16];
#pragma unroll
  for (int j = 0; j < 8; j++) {
    const float a = acc[4 * j], b = acc[4 * j + 1], c = acc[4 * j + 2], d = acc[4 * j + 3];
    o[2 * j] = packbf(a, b);
    o[2 * j + 1] = packbf(c, d);
    s0 += a + b; q0 = fmaf(a, a, q0); q0 = fmaf(b, b, q0);
    s1 += c + d; q1 = fmaf(c, c, q1); q1 = fmaf(d, d, q1);
  }
#pragma unroll
  for (int j = 0; j < 8; j += 2) {
    const int mi = lane >> 3;
    const int line = 8 * (j + (mi >> 1)) + (lane & 7), pc = 2 * w + (mi & 1);
    stsm4t(rbx + line * 128 + ((pc ^ (line & 7)) << 4), o[2 * j], o[2 * j + 1], o[2 * j + 2], o[2 * j + 3]);
  }
#pragma unroll
  for (int o2 = 1; o2 <= 2; o2 <<= 1) {
    s0 += __shfl_xor_sync(~0u, s0, o2); q0 += __shfl_xor_sync(~0u, q0, o2);
    s1 += __shfl_xor_sync(~0u, s1, o2); q1 += __shfl_xor_sync(~0u, q1, o2);
  }
  {
    const int i = 2 * (lane >> 2) + (t & 1), k = (i * 11) >> 5;
    const float v = (t == 0) ? s0 : (t == 1) ? q0 : (t == 2) ? s1 : q1;
    sts32f(stg + k * 128 + (2 * w + (t >> 1)) * 16 + (i - 3 * k) * 4, v);
  }
  TSW(9);
  fence_async_smem();
  if (attempt == 0 && clean) {
    staged = true;
    __syncwarp();
    if (lane == 0) mbar_arrive(bar + 8 * (B_STG + wg));
  }
  if (!bar_or(2 + wg, 128, !clean)) break;
  const int rtp = mbar_test(bar + 8 * (B_RT + wg), 0);
  bool unset = false;
#pragma unroll
  for (int i = 0; i < 4; i++) unset |= lds32(sb + o_page(wg, i) * PG + (32 * w + lane) * 128) == UNSET;
  if (!bar_or(2 + wg, 128, unset)) break;
  if (w == 0 && elect_one()) {
    fence_async_smem();
    mbar_expect(bar + 8 * (B_RT + wg), 9 * PG);
    if (layer == 0) tma_ld(rsrc, &p.mapX, q * 64, blk * 64, bar + 8 * (B_RT + wg));
    else tma_ld(rsrc, &p.mapXT, blk * 64, DM + q * 64, bar + 8 * (B_RT + wg));
#pragma unroll 1
    for (int c = 0; c < 4; c++) bulk_ld(sb + o_page(wg, c) * PG, g_O + ((layer * 32 + blk) * 4 + c) * PG, 2 * PG, bar + 8 * (B_RT + wg));
  }
  mbar_wait(bar + 8 * (B_RT + wg), rtp);
  RETRY(0);
  }
  if (!clean && lane == 0) mbar_arrive(bar + 8 * (B_PDONE + wg));
  if (!staged && lane == 0) mbar_arrive(bar + 8 * (B_STG + wg));
  TSW(10);
}

__device__ __forceinline__ void conv_load(uint32_t* A, uint32_t pe) {
#pragma unroll
  for (int m = 0; m < 17; m++) {
    A[4 * m + 2] = lds32(pe + 4 * (64 * m - 8));
    A[4 * m + 0] = lds32(pe + 4 * (64 * m));
    A[4 * m + 1] = lds32(pe + 4 * (64 * m + 8));
    asm volatile("mov.b32 %0, %1;" : "=r"(A[4 * m + 3]) : "r"(A[4 * m + 0]));
  }
}
template <int M> __device__ __forceinline__ void conv_tri(float* acc, const uint32_t* A, uint64_t d) {
  if constexpr (M < 16) {
    wgmma_rs<64 - 8 * (M / 2), 0>(acc, A + 4 * M, d + (uint64_t)(64 + 4 * M), M != 0);
    conv_tri<M + 1>(acc, A, d);
  }
}
__device__ __forceinline__ void conv_mma0(float* acc, const uint32_t* A, uint64_t d) {
  wg_fence();
  conv_tri<0>(acc, A, d);
  wg_commit();
}
__device__ __forceinline__ void conv_mma1(float* acc, const uint32_t* A, uint64_t d, uint64_t ds, uint64_t df) {
  wg_fence();
#pragma unroll
  for (int m = 0; m < 17; m++) wgmma_rs<64, 0>(acc, A + 4 * m, d + (uint64_t)(4 * m), m != 0);
  wgmma_ss<64, 1, 0>(acc, ds, df, 1);
  wgmma_ss<64, 1, 0>(acc, ds + 128, df + 128, 1);
  wg_commit();
}
__device__ __forceinline__ void conv_store(float* acc, uint32_t pb, uint32_t over, int w) {
  acc_fence<32>(acc);
  const int l = opaque_tid() & 31, mt = l >> 3;
  int c = 2 * (63 - 8 * (mt >> 1) - (l & 7) + w) + (mt & 1);
  c ^= (c >> 3) & 1;
  const uint32_t a0 = pb + c * 16;
#pragma unroll
  for (int j = 0; j < 8; j += 2)
    stsm4t(j == 0 ? (c < 128 ? a0 : over + (c - 128) * 16) : a0 - 256 * j, packbf(acc[4 * j], acc[4 * j + 1]), packbf(acc[4 * j + 2], acc[4 * j + 3]),
           packbf(acc[4 * j + 4], acc[4 * j + 5]), packbf(acc[4 * j + 6], acc[4 * j + 7]));
}
__device__ __forceinline__ void conv_sums(uint32_t sb, int lc, int ht) {
  const int m = ht - 1;
  uint4 v[2][3];
#pragma unroll
  for (int c = 0; c < 2; c++)
#pragma unroll
    for (int k = 0; k < 3; k++) {
      const int mm = m - 1 + k;
      v[c][k] = lds128(sb + cv_u(lc + c) + (mm >= 0 ? (mm & 1) * CV_UH + (127 - (mm >> 1)) * 16 : 128 * 16));
    }
  const int ce = m + 2, co = m + 1;
#pragma unroll
  for (int c = 0; c < 2; c++) {
    const uint32_t x[8] = {v[c][0].z, v[c][0].w, v[c][1].x, v[c][1].y, v[c][1].z, v[c][1].w, v[c][2].x, v[c][2].y};
    float pv[16];
#pragma unroll
    for (int k = 0; k < 8; k++) { pv[2 * k] = bf_lo(x[k]); pv[2 * k + 1] = bf_hi(x[k]); }
    float t2[15], t4[13], s9[8], s7[8];
#pragma unroll
    for (int i = 0; i < 15; i++) t2[i] = pv[i] + pv[i + 1];
#pragma unroll
    for (int i = 0; i < 13; i++) t4[i] = t2[i] + t2[i + 2];
#pragma unroll
    for (int i = 0; i < 8; i++) {
      s9[i] = (t4[i] + t4[i + 4]) + pv[i + 8];
      s7[i] = (t4[i + 1] + t2[i + 5]) + pv[i + 7];
    }
    const uint4 e4 = make_uint4(packbf(s9[0], s9[1]), packbf(s9[2], s9[3]), packbf(s9[4], s9[5]), packbf(s9[6], s9[7]));
    if (ce < 128) sts128(sb + cv_se(lc + c) + ((ce ^ ((ce >> 3) & 7)) << 4), e4);
    else sts128(sb + cv_se(lc + c), make_uint4(0, 0, 0, 0));
    sts128(sb + cv_so(lc + c) + ((co ^ ((co >> 3) & 7)) << 4),
           make_uint4(packbf(s7[0], s7[1]), packbf(s7[2], s7[3]), packbf(s7[4], s7[5]), packbf(s7[6], s7[7])));
  }
}

template <int HALF, int NCH, int STEP = 1>
__device__ __forceinline__ void conv_epi(uint32_t sb, bf16* out, int lc, int c) {
  uint4 v[NCH][4], xr[NCH];
  const uint32_t sw = (c ^ ((c >> 3) & 1)) * 16;
#pragma unroll
  for (int u = 0; u < NCH; u++) {
#pragma unroll
    for (int k = 0; k < 4; k++) v[u][k] = lds128(sb + (HALF ? cv_pb1(lc + STEP * u, k) : cv_pb0(lc + STEP * u, k)) + sw);
    xr[u] = lds128(sb + cv_x(HALF, lc + STEP * u) + c * 16);
  }
#pragma unroll
  for (int u = 0; u < NCH; u++) {
    uint4 o;
    o.x = hadd2(xr[u].x, hadd2(hadd2(v[u][0].x, v[u][1].x), hadd2(v[u][2].x, v[u][3].x)));
    o.y = hadd2(xr[u].y, hadd2(hadd2(v[u][0].y, v[u][1].y), hadd2(v[u][2].y, v[u][3].y)));
    o.z = hadd2(xr[u].z, hadd2(hadd2(v[u][0].z, v[u][1].z), hadd2(v[u][2].z, v[u][3].z)));
    o.w = hadd2(xr[u].w, hadd2(hadd2(v[u][0].w, v[u][1].w), hadd2(v[u][2].w, v[u][3].w)));
    stg128(out + cv_chan(0, lc + STEP * u) * LSEQ + HALF * 1024 + c * 8, o);
  }
}

__device__ __forceinline__ bool prep_valid(const uint4 (&st)[6], const uint4 (&xr)[4]) {
  const uint32_t n = __float_as_uint(8.f);
  return st[0].w == n && st[1].w == n && st[2].w == n && st[3].w == n && st[4].w == n && (st[5].w | st[5].y | st[5].z) == n &&
         xr[0].x != UNSET && xr[1].x != UNSET && xr[2].x != UNSET && xr[3].x != UNSET;
}
template <int HALF>
__device__ __forceinline__ void conv_prep(uint32_t sb, int layer, int cta, int i) {
  uint4 st[6], xr[4];
  const uint4* sp = (const uint4*)g_stats + (layer * 32 + HALF * 16 + (i >> 3)) * 48 + (i & 7);
  const uint4* xp = (const uint4*)g_xT + (2 * layer * DM + 2 * cta) * (LSEQ / 8) + HALF * 128 + i;
  if (!HALF) { pin(sp); pin(xp); }
  mbar_wait(sb + SM_BAR + 8 * (B_GB + HALF), layer);
  if (!HALF) TSW(13);
  auto fetch = [&]() {
#pragma unroll
    for (int k = 0; k < 6; k++) st[k] = ld_tagged(sp + 8 * k);
#pragma unroll
    for (int k = 0; k < 4; k++) xr[k] = ld_tagged(xp + cv_chan(0, k) * (LSEQ / 8));
  };
  if (HALF) {
#pragma unroll
    for (int k = 0; k < 6; k++) st[k] = lds128(sb + CV_ST + (i >> 3) * 768 + k * 128 + (i & 7) * 16);
#pragma unroll
    for (int k = 0; k < 4; k++) xr[k] = lds128(sb + cv_x(1, k) + i * 16);
  } else {
    fetch();
  }
  int it = 0;
  while (!__all_sync(~0u, prep_valid(st, xr)) && ++it < MAX_RETRY) { fetch(); RETRY(1); }
  if (!HALF || it) {
#pragma unroll
    for (int k = 0; k < 4; k++) sts128(sb + cv_x(HALF, k) + i * 16, xr[k]);
  }
  const uint32_t v[16] = {st[0].x, st[0].y, st[0].z, st[1].x, st[1].y, st[1].z, st[2].x, st[2].y, st[2].z, st[3].x, st[3].y, st[3].z, st[4].x, st[4].y, st[4].z, st[5].x};
  uint32_t rs[4], nm[4];
#pragma unroll
  for (int k = 0; k < 4; k++) {
    const float m0 = __uint_as_float(v[4 * k]) * (-1.f / DM), m1 = __uint_as_float(v[4 * k + 2]) * (-1.f / DM);
    const float r0 = rsqrt_approx(fmaxf(fmaf(__uint_as_float(v[4 * k + 1]), 1.f / DM, -m0 * m0), 0.f) + 1e-5f);
    const float r1 = rsqrt_approx(fmaxf(fmaf(__uint_as_float(v[4 * k + 3]), 1.f / DM, -m1 * m1), 0.f) + 1e-5f);
    rs[k] = packbf(r0, r1);
    nm[k] = packbf(m0 * bf_lo(rs[k]), m1 * bf_hi(rs[k]));
  }
  const uint32_t ud = sb + (i & 1) * CV_UH + (127 - 64 * HALF - (i >> 1)) * 16;
#pragma unroll
  for (int k = 0; k < 4; k++)
    sts128(ud + cv_u(k), make_uint4(hfma2(xr[k].x, rs[0], nm[0]), hfma2(xr[k].y, rs[1], nm[1]), hfma2(xr[k].z, rs[2], nm[2]), hfma2(xr[k].w, rs[3], nm[3])));
  fence_async_smem();
}

__device__ __forceinline__ void conv_phase(const Params& p, uint32_t sb, int layer, int cta, uint32_t* A0, uint32_t* A1) {
  const int tid = opaque_tid();
  const int wg = __shfl_sync(~0u, tid >> 7, 0), w = __shfl_sync(~0u, (tid >> 5) & 3, 0);
  const uint32_t bar = sb + SM_BAR;
  constexpr int CH2 = 4 * PG;
  bf16* xout = g_xT + ((2 * layer + 1) * DM + 2 * cta) * LSEQ;
  float acc[32];
  const uint32_t pe = sb + cv_pe(wg, 0) + 4 * (16 + 16 * w + ((tid & 31) >> 2) - 2 * (tid & 3));
  if (layer == 0) {
    mbar_wait(bar + 8 * (B_PDONE + 1), layer);
    mbar_wait(bar + 8 * B_PE, layer);
    conv_load(A0, pe);
    conv_load(A1, pe + CH2);
  }
  TSW(19);
  const uint64_t d0 = mkdesc(sb + cv_u(wg), CV_UH, 128, 0), d1 = d0 + (CH2 >> 4);
  mbar_wait(bar + 8 * B_U, layer);
  TSW(12);
  if (wg == 1) bar_sync(5, 256);
  conv_mma0(acc, A0, d0);
  if (wg == 0) bar_arrive(5, 256);
  mbar_wait(bar + 8 * (B_PDONE + 1), layer);
  {
    const int l = opaque_tid() & 31;
    if ((l & 15) < 2 * w) sts128(sb + cv_pb0(wg + 2 * (l >> 4), w) + (l & 15) * 16, make_uint4(0, 0, 0, 0));
  }
  wg_wait<0>();
  conv_store(acc, sb + cv_pb0(wg, w), sb + cv_pb1(wg, w), w);
  conv_mma0(acc, A1, d1);
  wg_wait<0>();
  conv_store(acc, sb + cv_pb0(2 + wg, w), sb + cv_pb1(2 + wg, w), w);
  TSW(13);
  bar_sync(2 + wg, 128);
  conv_epi<0, 2, 2>(sb, xout, wg, opaque_tid() & 127);
  TSW(14);
  mbar_arrive(bar + 8 * B_PUB);
  const uint64_t ds = mkdesc(sb + cv_se(wg), 8192, 1024, 1), df = mkdesc(sb + cv_fa(wg), 512, 128, 0);
  if (wg == 0) mbar_wait(bar + 8 * B_U1, layer);
  else bar_sync(6, 256);
  TSW(15);
  conv_mma1(acc, A0, d0, ds, df);
  if (wg == 0) bar_arrive(6, 256);
  wg_wait<0>();
  conv_store(acc, sb + cv_pb1(wg, w), sb + cv_dump(wg), w);
  TSW(16);
  bar_sync(2 + wg, 128);
  conv_epi<1, 1>(sb, xout, wg, opaque_tid() & 127);
  mbar_arrive(bar + 8 * (B_PUB + 1));
  conv_mma1(acc, A1, d1, ds + 512, df + (CH2 >> 4));
  wg_wait<0>();
  conv_store(acc, sb + cv_pb1(2 + wg, w), sb + cv_dump(2 + wg), w);
  TSW(17);
  bar_sync(2 + wg, 128);
  conv_epi<1, 1>(sb, xout, 2 + wg, opaque_tid() & 127);
  mbar_arrive(bar + 8 * (B_PUB + 2));
  TSW(18);
}

#define FDELAY 480
__device__ __forceinline__ void final_tile(const Params& p, uint32_t buf, int ch0, int pos0, int barid, uint32_t hint) {
  const uint32_t t0 = (uint32_t)clock();
  const int tid = opaque_tid() & 127, lane = tid & 31, w = tid >> 5;
  const uint4* src = (const uint4*)(g_xT + (3 * DM + ch0 + (tid >> 3)) * LSEQ + pos0) + (tid & 7);
  const int ch = tid >> 3, row = 4 * (ch & 6) + 2 * (ch >> 3) + (ch & 1);
  uint32_t dst0 = buf + row * 128 + (((tid ^ row) & 7) << 4), dst1 = (dst0 ^ 64) + 512;
  uint32_t ld0 = buf + lane * 128 + ((((2 * w) ^ lane) & 7) << 4), ld1 = ld0 ^ 16;
  bf16* out = p.out + (pos0 + 16 * w + (lane >> 2)) * DM + ch0 + 8 * (lane & 3);
  pin(src); pin(out); pin(dst0); pin(dst1); pin(ld0); pin(ld1);
  if (hint) mbar_wait(hint, 0);
  else while ((uint32_t)clock() - t0 < FDELAY);
  uint4 a, b;
  int it = 0;
  do {
    if (it) RETRY(2);
    a = ld_tagged(src); b = ld_tagged(src + 16 * LSEQ / 8);
  } while (!__all_sync(~0u, a.x != UNSET && b.x != UNSET) && ++it < (1 << 20));
  sts128(dst0, a);
  sts128(dst1, b);
  bar_sync(barid, 128);
#pragma unroll
  for (int h = 0; h < 2; h++) {
    uint32_t r[4];
    ldsm4t(r, h ? ld1 : ld0);
    *(uint4*)(out + 8 * h * DM) = make_uint4(r[0], r[1], r[2], r[3]);
  }
}

struct cplx { float r, i; };
__device__ __forceinline__ cplx cmul(cplx a, cplx b) { return {fmaf(a.r, b.r, -a.i * b.i), fmaf(a.r, b.i, a.i * b.r)}; }
__device__ __forceinline__ cplx csqr(cplx a) { return {fmaf(a.r, a.r, -a.i * a.i), (a.r + a.r) * a.i}; }
__device__ __forceinline__ cplx cexp_l(float ar2, float ai, float l) {
  const float m = ex2(ar2 * l);
  const float x = ai * l;
  return {m * __cosf(x), m * __sinf(x)};
}

__device__ __forceinline__ void colsum_cta(const Params& p, uint32_t sb, int j, int tid) {
  const uint32_t bar = sb + SM_BAR;
  auto ld = [&](int i) {
    mbar_expect(bar + 8 * i, 3 * PG);
    tma_ld3(sb + (i & 7) * 3 * PG, &p.mapW3, (2 * j + (i & 1)) * 64, (i >> 1) * 64, 0, bar + 8 * i);
  };
  if (tid == 384) {
#pragma unroll
    for (int i = 0; i < 24; i++) mbar_init(bar + 8 * i, i < 16 ? 1 : 12);
    asm volatile("fence.mbarrier_init.release.cluster;" ::: "memory");
    fence_async_smem();
#pragma unroll 1
    for (int i = 0; i < 8; i++) ld(i);
  }
  const unsigned ep = ld_relaxed(&g_cnt[C_CS * 32]);
  bar_sync(0, NTHREADS);
  if (tid == 384) {
#pragma unroll 1
    for (int i = 8; i < 16; i++) { mbar_wait(bar + 8 * (8 + i), 0); fence_async_smem(); ld(i); }
  }
  if (tid < 384) {
    const int lane = tid & 31, cc = tid & 7, r0 = (tid >> 3) & 15, part = tid >> 7;
    const uint32_t id = ((lane >> 2) == 2 * (lane & 3) ? 0x3f80u : 0u) | ((lane >> 2) == 2 * (lane & 3) + 1 ? 0x3f800000u : 0u);
    const uint32_t src = sb + part * PG + r0 * 128 + ((cc ^ (r0 & 7)) << 4);
    float s[2][2][4];
#pragma unroll
    for (int i = 0; i < 16; i++) s[i >> 3][(i >> 2) & 1][i & 3] = 0.f;
#pragma unroll 1
    for (int i2 = 0; i2 < 16; i2 += 2) {
#pragma unroll
      for (int h = 0; h < 2; h++) {
        const int i = i2 + h;
        mbar_wait(bar + 8 * i, 0);
        uint4 v[4];
#pragma unroll
        for (int k = 0; k < 4; k++) v[k] = lds128(src + (i & 7) * 3 * PG + k * 2048);
#pragma unroll
        for (int k = 0; k < 4; k++) {
          const uint32_t a[4] = {v[k].x, v[k].y, v[k].z, v[k].w};
          mma_bf16(s[h][0], a, id, 0u);
          mma_bf16(s[h][1], a, 0u, id);
        }
        __syncwarp();
        if (i < 8 && lane == 0) mbar_arrive(bar + 8 * (16 + i));
      }
    }
    const uint32_t red = sb + 24 * PG;
#pragma unroll
    for (int h = 0; h < 2; h++)
#pragma unroll
      for (int k = 0; k < 2; k++) sts128f(red + (r0 * 384 + h * 192 + part * 64 + cc * 8 + k * 4) * 4, s[h][k][0], s[h][k][1], s[h][k][2], s[h][k][3]);
    bar_sync(1, 384);
    float tot = 0.f;
#pragma unroll
    for (int k = 0; k < 16; k++) tot += __uint_as_float(lds32(red + (k * 384 + tid) * 4));
    asm volatile("st.relaxed.gpu.global.v2.u32 [%0], {%1,%2};" ::"l"(&g_colsum[j * 384 + tid]), "r"(__float_as_uint(tot)), "r"(ep / NCTA + 1) : "memory");
    const uint4 u = make_uint4(UNSET, UNSET, UNSET, UNSET);
    if (tid < 256) {
#pragma unroll 1
      for (int s = 0; s < 4; s++) {
        const int n = (s == 1 || s == 2) ? 32 : 16;
        uint4* buf = s == 1 ? (uint4*)g_O + 131072 : (uint4*)g_xT + (s + !s) * 131072;
#pragma unroll 4
        for (int i = 0; i < n; i++) stg128(buf + (j * n + i) * 1024 + (tid >> 1) * 8 + (tid & 1), u);
        if (n == 16) {
#pragma unroll 4
          for (int i = 0; i < 8; i++) stg128(buf + (256 + j * 64 + i * 8 + (tid >> 5)) * 256 + (s ? 0 : 128) + ((tid & 31) >> 1) * 8 + (tid & 1), u);
        }
        if (s == 3) {
#pragma unroll 4
          for (int i = 0; i < 32; i++) stg128(buf + (256 + j * 64 + 2 * i + (tid >> 7)) * 256 + 128 + (tid & 127), u);
        }
        bar_sync(2, 256);
        if (tid == 32 * s) red_release(&g_cnt[(C_R + s) * 32]);
      }
    }
  }
}

constexpr int KB = 4, KW = 2;
struct ModeIn { uint32_t ar, ai, br, bi, cr, ci; bf16 logdt; };
__device__ __forceinline__ ModeIn load_modes(const Params& p, int d, int m) {
  const int i = d * 64 + m;
  return {((const uint32_t*)p.a_re)[i], ((const uint32_t*)p.a_im)[i], ((const uint32_t*)p.b_re)[i], ((const uint32_t*)p.b_im)[i],
          ((const uint32_t*)p.c_re)[i], ((const uint32_t*)p.c_im)[i], p.log_dt[d]};
}
__device__ __forceinline__ void kernel_gen(uint32_t sb, int cta, int ht, ModeIn in, const ModeIn& in1) {
  const uint32_t bst = sb + SM_KGB + ((ht & 63) >> 2) * 144 + (ht & 3) * 4 + (ht >> 6) * 16;
  const uint64_t db = mkdesc(sb + SM_KGB, 144, 2304, 0);
  const float e0 = (float)(8 * (((ht & 32) >> 1) + ((ht & 31) >> 2)));
  float T[20];
#pragma unroll
  for (int i = 0; i < 20; i++) T[i] = 0.f;
  float k0 = 0.f;
#pragma unroll 1
  for (int pass = 0; pass < 4; pass++) {
    {
      const int sh = (pass & 1) ? 0 : 16;
      auto val = [&](uint32_t v) { return __uint_as_float((v << sh) & 0xffff0000u); };
      const float dt = __bfloat162float(__float2bfloat16_rn(expf(__bfloat162float(in.logdt))));
      const float ar2 = dt * val(in.ar) * 1.4426950408889634f, ai = dt * val(in.ai);
      const cplx c = cmul({val(in.cr), -val(in.ci)}, {dt * val(in.br), -dt * val(in.bi)});
      k0 += c.r;
      const cplx z1 = cexp_l(ar2, -ai, 1.f), z256 = cexp_l(ar2, -ai, 256.f), z64 = cexp_l(ar2, ai, 64.f);
      const cplx z2 = csqr(z1), z512 = csqr(z256);
      auto put = [&](int j, cplx v) { sts32(bst + (j >> 2) * 2304 + (j & 3) * 32, packbf(v.r, v.i)); };
      sts128f(sb + SM_KGT + ht * 16, ar2, ai, z64.r, z64.i);
      const cplx c1 = cmul(c, z1), c2 = cmul(c, z2), c3 = cmul(c1, z2), c4 = cmul(c2, z2);
      const cplx c5 = cmul(c3, z2), c6 = cmul(c4, z2), c7 = cmul(c5, z2), c8 = cmul(c6, z2);
      put(0, c1); put(1, c2); put(2, c3); put(3, c4); put(4, c5); put(5, c6); put(6, c7); put(7, c8);
      const cplx c260 = cmul(c4, z256), c264 = cmul(c8, z256), c520 = cmul(c8, z512), c776 = cmul(c264, z512);
      put(8, cmul(c2, z256)); put(9, c260); put(10, cmul(c6, z256)); put(11, c264);
      put(12, cmul(c4, z512)); put(13, c520); put(14, cmul(c260, z512)); put(15, c776);
      const cplx c1032 = cmul(c520, z512), c1288 = cmul(c776, z512);
      put(16, c1032); put(17, c1288); put(18, cmul(c1032, z512)); put(19, cmul(c1288, z512));
    }
    fence_async_smem();
    bar_sync(4, 128);
    const uint32_t tb = sb + SM_KGT + (ht & 67) * 16;
    float2 nx[KB];
#pragma unroll
    for (int s = 0; s < KB; s++) nx[s] = lds64f(tb + s * 64);
#pragma unroll
    for (int q = 0; q < 16 / KB; q++) {
      uint32_t A[2 * KB];
      float2 cur[KB], z[KB];
#pragma unroll
      for (int s = 0; s < KB; s++) { cur[s] = nx[s]; z[s] = lds64f(tb + (KB * q + s) * 64 + 8); }
      if (q < 16 / KB - 1) {
#pragma unroll
        for (int s = 0; s < KB; s++) nx[s] = lds64f(tb + (KB * q + KB + s) * 64);
      }
      if (q >= KW) wg_wait<KW - 1>();
#pragma unroll
      for (int s = 0; s < KB; s++) {
        const cplx lo = cexp_l(cur[s].x, cur[s].y, e0), hi = cmul(lo, {z[s].x, z[s].y});
        A[2 * s] = packbf(lo.r, lo.i);
        A[2 * s + 1] = packbf(hi.r, hi.i);
      }
      wg_fence();
#pragma unroll
      for (int k = 0; k < KB / 2; k++) wgmma_rs<40, 0>(T, A + 4 * k, db + 9 * KB * q + 18 * k, (pass & 1) | q | k);
      wg_commit();
    }
    wg_wait<0>();
    acc_fence<20>(T);
    if (ht == 0) TS(4 + pass);
    if (pass & 1) {
      const int h2 = opaque_tid() - 256, w = h2 >> 5, lane = h2 & 31, t = lane & 3, chn = h2 >> 6, m = h2 & 63, i0 = 16 * (w & 1) + (lane >> 2);
      const int lc = (pass & 2) + chn;
      const uint32_t kc = sb + kc_off(lc);
      auto put = [&](int idx, float v) {
        sts16(kc + idx * 2, __bfloat16_as_ushort(__float2bfloat16_rn(v)));
      };
#pragma unroll
      for (int hi = 0; hi < 2; hi++) {
        const int i = i0 + 8 * hi;
        float v[5];
#pragma unroll
        for (int j = 0; j < 5; j++) v[j] = chn ? T[4 * j + 2 * hi + 1] : T[4 * j + 2 * hi];
        put(8 * i + 1 + t, v[0]);
        put(8 * i + 5 + t, v[1]);
        put(257 + 4 * i + t, v[2]);
        put(385 + 2 * i + (t & 1) + 64 * (t >> 1), v[3]);
        put(513 + i + 32 * t, v[4]);
      }
#pragma unroll
      for (int o = 16; o > 0; o >>= 1) k0 += __shfl_xor_sync(~0u, k0, o);
      if (lane == 0) sts32f(sb + SM_RED + 4 * w, k0);
      bar_sync(4, 128);
      if (m == 0) put(0, k0 + __uint_as_float(lds32(sb + SM_RED + 4 * w + 4)) + __uint_as_float(lds16(sb + SM_RED + 24 + 2 * lc) << 16));
      k0 = 0.f;
      in = in1;
    }
  }
}

__device__ __forceinline__ void expand_taps(uint32_t sb, int ht, int early) {
  const int ch = ht >> 5, lane = ht & 31;
  const uint32_t kc = sb + kc_off(ch);
  const uint32_t dst0 = sb + cv_pe(ch, early);
  auto put = [&](int G, uint32_t v0, uint32_t v1, uint32_t v2, uint32_t v3, uint32_t v4, uint32_t v5, uint32_t v6, uint32_t v7, uint32_t v8) {
    const uint32_t dst = dst0 + G * 32;
    sts128(dst, make_uint4(v1 | (v0 << 16), v2 | (v1 << 16), v3 | (v2 << 16), v4 | (v3 << 16)));
    sts128(dst + 16, make_uint4(v5 | (v4 << 16), v6 | (v5 << 16), v7 | (v6 << 16), v8 | (v7 << 16)));
  };
  {
    const uint4 q = lds128(kc + lane * 16);
    const uint32_t pv = lane ? lds16(kc + lane * 16 - 2) : 0u;
    const uint32_t dst = dst0 + (lane + 2) * 32;
    sts128(dst, make_uint4(__byte_perm(q.x, pv, 0x5410), __byte_perm(q.x, q.x, 0x1032), __byte_perm(q.y, q.x, 0x7610), __byte_perm(q.y, q.y, 0x1032)));
    sts128(dst + 16, make_uint4(__byte_perm(q.z, q.y, 0x7610), __byte_perm(q.z, q.z, 0x1032), __byte_perm(q.w, q.z, 0x7610), __byte_perm(q.w, q.w, 0x1032)));
    if (lane < 4) sts128(dst0 + lane * 16, make_uint4(0, 0, 0, 0));
  }
  uint32_t a[5], b[2][3];
  {
    const uint32_t s1 = kc + 2 * (256 + 4 * lane);
#pragma unroll
    for (int k = 0; k < 5; k++) a[k] = lds16(s1 + 2 * k);
#pragma unroll
    for (int u = 0; u < 2; u++) {
      const uint32_t s2 = kc + 2 * (384 + 2 * (lane + 32 * u));
#pragma unroll
      for (int k = 0; k < 3; k++) b[u][k] = lds16(s2 + 2 * k);
    }
  }
  const uint32_t k255 = lds16(kc + 2 * 255), k1024 = lds16(kc + 2 * 512);
  put(34 + lane, lane == 0 ? k255 : a[0], a[0], a[0], a[1], a[2], a[2], a[2], a[3], a[4]);
#pragma unroll
  for (int u = 0; u < 2; u++) put(66 + lane + 32 * u, b[u][0], b[u][0], b[u][0], b[u][0], b[u][1], b[u][1], b[u][1], b[u][2], b[u][2]);
  if (lane < 10) {
    const uint32_t v = lane == 0 ? k1024 : 0u;
    put(130 + lane, v, v, v, v, v, v, 0u, 0u, 0u);
  }
}
__device__ __forceinline__ void expand_far(uint32_t sb, int ht) {
  const int ch = ht >> 5, lane = ht & 31;
  const uint32_t kc = sb + kc_off(ch) + 2 * (513 + 2 * (63 - lane)), dst = sb + cv_fa(ch) + lane * 16;
#pragma unroll
  for (int ty = 0; ty < 2; ty++) {
    uint32_t v[16];
#pragma unroll
    for (int k = 0; k < 16; k++) v[k] = (k < 8 || 63 - lane - 4 * k >= 0) ? lds16(kc + 2 * (1 - ty) - 16 * k) : 0u;
#pragma unroll
    for (int u = 0; u < 2; u++)
      sts128(dst + ty * 2048 + u * 512, make_uint4(v[8 * u] | (v[8 * u + 1] << 16), v[8 * u + 2] | (v[8 * u + 3] << 16), v[8 * u + 4] | (v[8 * u + 5] << 16), v[8 * u + 6] | (v[8 * u + 7] << 16)));
    sts128(dst + ty * 2048 + 1024, make_uint4(0, 0, 0, 0));
  }
}

__host__ __device__ constexpr int bar_count(int i) {
  return i == B_LN ? 2 : i == B_AL ? 8 : i < B_STG ? 1 : i < B_PE ? 4 : i >= B_PUB ? 256 : 128;
}
__host__ __device__ constexpr bool bar_first(int i) { return i < B_WF + 2 && (i & 7) < 2; }

__global__ void __launch_bounds__(NTHREADS, 1) fused_kernel(const __grid_constant__ Params p) {
  extern __shared__ __align__(1024) uint8_t smem[];
  constexpr uint32_t sb = 1024;
  if (s32(smem) != sb) return;
  const int tid = threadIdx.x, lane = tid & 31;
  const int warp = __shfl_sync(~0u, tid >> 5, 0);
  if (tid == 32) {
    asm volatile("prefetch.tensormap [%0];" ::"l"(&p.mapX) : "memory");
    asm volatile("prefetch.tensormap [%0];" ::"l"(&p.mapW3) : "memory");
  }
  const int cta = blockIdx.x - (gridDim.x == NCTA + 4 ? 0 : 4);
  if ((unsigned)cta >= NCTA) {
    if (blockIdx.x < NCTA + 4) colsum_cta(p, sb, blockIdx.x & 3, tid);
    return;
  }
  const int rb = ((cta >> 4) & 3) * 4 + ((cta >> 2) & 3), hg = (cta >> 6) * 4 + (cta & 3);
  const uint32_t bar = sb + SM_BAR;
  auto ld_x0 = [&](int half, int c) {
    const uint32_t b = bar + 8 * (B_XF + 8 * half + c);
    mbar_expect(b, PG);
    tma_ld(sb + x_page(half, c) * PG, &p.mapX, c * 64, (16 * half + rb) * 64, b);
  };
  auto ld_x1 = [&](int half, int c, int b0) {
    const uint32_t b = bar + 8 * b0;
    mbar_expect(b, PG);
    tma_ld(sb + (8 * half + c) * PG, &p.mapXT, (16 * half + rb) * 64, DM + c * 64, b);
  };
  auto ld_w = [&](int c) {
    const uint32_t b = bar + 8 * (B_WF + c);
    mbar_expect(b, 3 * PG);
    tma_ld3(sb + w_page(c) * PG, &p.mapW3, hg * 64, c * 64, 0, b);
  };

  if (tid == 0) TS(0);
  if (tid == 480) LTS(0);
  if (warp == 0 && elect_one()) {
#pragma unroll
    for (int i = 0; i < B_WF + 2; i++)
      if (bar_first(i)) mbar_init(bar + 8 * i, 1);
    asm volatile("fence.mbarrier_init.release.cluster;" ::: "memory");
    fence_async_smem();
    ld_x0(0, 0);
    ld_w(0); ld_x0(1, 0);
    ld_x0(0, 1); ld_w(1); ld_x0(1, 1);
    TS(1);
  }
  __syncwarp();
  if (warp >= 1 && warp < 8 && elect_one()) {
    if (warp < 4) {
#pragma unroll
      for (int i = 2; i < 8; i++) mbar_init(bar + 8 * (8 * warp - 8 + i), 1);
    } else {
#pragma unroll
      for (int i = 0; i < 12; i++) mbar_init(bar + 8 * (12 * warp - 24 + i), 1);
    }
    asm volatile("fence.mbarrier_init.release.cluster;" ::: "memory");
  }
  if (warp == 15 && elect_one()) {
#pragma unroll
    for (int i = 72; i < B_COUNT; i++) mbar_init(bar + 8 * i, bar_count(i));
    asm volatile("fence.mbarrier_init.release.cluster;" ::: "memory");
  }

  if (warp < 8) {
    bar_sync(0, NTHREADS);
    asm volatile("setmaxnreg.inc.sync.aligned.u32 %0;" ::"n"(R_CONS));
    const int cw = __shfl_sync(~0u, opaque_tid() >> 5, 0);
    const int wg = cw >> 2, w = cw & 3;
    if (tid == 0) TS(2);
#pragma unroll 1
    for (int layer = 0; layer < 2; layer++) {
      attn_phase(p, sb, layer, rb, hg, wg, w);
      uint32_t A0[68], A1[68];
      proj_phase(p, sb, layer, rb, hg, A0, A1);
      conv_phase(p, sb, layer, cta, A0, A1);
    }
    if (tid == 128) TS(8);
    final_tile(p, sb + (16 + wg) * PG, 256 * wg + 32 * (cta >> 4), 1024 + 64 * (cta & 15), 2 + wg, wg ? 0 : bar + 8 * (B_TF + 1));
    if (tid == 128) TS(9);
    if (tid == 128) LTS(1);
    if (tid == 0) LTE();
  } else if (warp < 12) {
    asm volatile("setmaxnreg.dec.sync.aligned.u32 %0;" ::"n"(R_HELP));
    const int ht = tid - 256;
    {
      unsigned ep0 = 0;
      if (ht == 0) ep0 = ld_relaxed(&g_cnt[C_CS * 32]);
      const bf16 dsk = p.dskip[cv_chan(cta, ht & 3)];
      const ModeIn in0 = load_modes(p, cv_chan(cta, ht >> 6), ht & 63), in1 = load_modes(p, cv_chan(cta, 2 + (ht >> 6)), ht & 63);
      if (ht < 48) sts128f(sb + SM_STG + ht * 16, 0.f, 0.f, 0.f, 1.f);
      bar_sync(0, NTHREADS);
      if (ht == 0) {
        sts32(sb + SM_EP, ep0);
        mbar_arrive(bar + 8 * B_EP);
      }
      if (ht >= 124) sts16(sb + SM_RED + 24 + 2 * (ht & 3), __bfloat16_as_ushort(dsk));
      kernel_gen(sb, cta, ht, in0, in1);
      if (ht < 48) sts128f(sb + SM_KGT + ht * 16, 0.f, 0.f, 0.f, 1.f);
      fence_async_smem();
      bar_sync(4, 128);
      if (ht == 0) mbar_arrive(bar + 8 * B_KG);
    }
#pragma unroll 1
    for (int layer = 0; layer < 2; layer++) {
      const int early = layer;
      if (early) mbar_wait(bar + 8 * (B_DN + 13), 1);
      mbar_wait(bar + 8 * (early ? B_OST : B_PDONE), layer);
      expand_taps(sb, opaque_tid() - 256, early);
      mbar_arrive(bar + 8 * B_PE);
      TSW(0);
      mbar_wait(bar + 8 * B_PDONE, layer);
      expand_far(sb, opaque_tid() - 256);
      {
        const int i = opaque_tid() - 256;
        if (i < 32) sts128(sb + cv_u(i >> 3) + ((i >> 2) & 1) * CV_UH + (128 + (i & 3)) * 16, make_uint4(0, 0, 0, 0));
        mbar_wait(bar + 8 * B_RC, layer);
        conv_prep<0>(sb, layer, cta, i);
        mbar_arrive(bar + 8 * B_U);
      }
      mbar_wait(bar + 8 * (B_PDONE + 1), layer);
      bar_sync(4, 128);
#pragma unroll 1
      for (int lc = 0; lc < 4; lc += 2) {
        conv_sums(sb, lc, opaque_tid() - 256);
        TSW(1 + lc);
      }
      conv_prep<1>(sb, layer, cta, opaque_tid() - 256);
      mbar_arrive(bar + 8 * B_U1);
      TSW(4);
      if (layer == 0) {
        const int c = __shfl_sync(~0u, (opaque_tid() >> 5) & 3, 0);
        int phase = 0;
#pragma unroll 1
        for (int k = 0; k < 3; k++) {
          const int page = (k ? 4 + 4 * k : 0) + c, b = B_XR + 4 * (k & 1) + c;
          const uint32_t a = sb + page * PG + lane * 128 + (lane & 7) * 16 + (lane >> 3) * 4;
          int it = k == 2 ? phase : 0;
#pragma unroll 1
          for (; it < MAX_RETRY; it++) {
            mbar_wait(bar + 8 * b, it & 1);
            const uint32_t v0 = lds32(a), v1 = lds32(a + 4096);
            if (__all_sync(~0u, v0 != UNSET && v1 != UNSET)) break;
            if (elect_one()) { fence_async_smem(); ld_x1(page >> 3, page & 7, b); }
            __syncwarp();
            RETRY(3);
          }
          if (k == 0) phase = it + 1;
          if (lane == 0) mbar_arrive(bar + 8 * (B_XF + page));
        }
      }
    }
#pragma unroll 1
    for (int k = 0; k < 2; k++) final_tile(p, sb + 18 * PG + k * 4096, 256 * k + 32 * (cta >> 4), 64 * (cta & 15), 4, bar + 8 * B_TF);
    if (ht == 0) LTE();
  } else {
    asm volatile("setmaxnreg.dec.sync.aligned.u32 %0;" ::"n"(R_AGENT));
    bar_sync(0, NTHREADS);
    auto done = [&](int half, int c, int layer) { mbar_wait(bar + 8 * (B_DN + 8 * half + c), layer); };
    auto publish = [&](int layer, int k) {
      unsigned* cnt = &g_cnt[(layer ? C_F + 8 * k + (cta >> 4) : C_C + k) * 32];
      pin(cnt);
      mbar_wait(bar + 8 * (B_PUB + k), layer);
      red_relaxed(cnt);
      if (!layer && k == 0) red_release(&g_cnt[(C_C + 3) * 32]);
      TS(16 + layer * 56 + 40 + 7 + k);
    };
    if (warp == 12) {
      if (elect_one()) {
#pragma unroll 1
        for (int layer = 0; layer < 2; layer++) {
          auto ld_xe = [&](int c) {
            const uint32_t b = bar + 8 * (B_XF + c);
            mbar_expect(b, PG);
            if (layer == 0) tma_ld(sb + x_page(0, c) * PG, &p.mapX, c * 64, rb * 64, b);
            else tma_ld(sb + x_page(0, c) * PG, &p.mapXT, rb * 64, DM + c * 64, b);
          };
          if (layer == 0) {
            ld_x0(0, 2); ld_w(2); ld_x0(1, 2);
            if (hg >= 3) {
              mbar_expect(bar + 8 * B_SC, PG);
              tma_ld(sb + P_R * PG, &p.mapX, hg * 64, rb * 64, bar + 8 * B_SC);
            }
            if (rb < 4) tma_prefetch3(&p.mapW3, hg * 64, (4 + rb) * 64, 0);
            ld_x0(0, 3); ld_w(3); ld_x0(1, 3); ld_x0(0, 4); ld_x0(1, 4);
            done(0, 0, 0); done(1, 0, 0);
            ld_w(4);
            ld_x0(1, 5); ld_x0(1, 6); ld_x0(1, 7);
            done(0, 1, 0); done(1, 1, 0);
            ld_w(5);
            if (rb < 8) tma_prefetch5(&p.mapWo, hg * 64, rb * 2);
            done(0, 2, 0);
            fence_async_smem();
            ld_xe(5); ld_xe(6); ld_xe(7);
          } else {
            mbar_wait(bar + 8 * B_PDONE, 0);
            mbar_wait(bar + 8 * (B_PDONE + 1), 0);
            mbar_wait(bar + 8 * B_U, 0);
            ld_w(0); ld_w(1);
            mbar_wait(bar + 8 * B_U1, 0);
            fence_async_smem();
            ld_w(2);
            mbar_wait(bar + 8 * (B_PUB + 2), 0);
            fence_async_smem();
            ld_w(3);
            spin_until(&g_cnt[(C_C + 3) * 32], ((lds32(sb + SM_EP) / NCTA) + 1) * NCTA);
            fence_async_global();
            if (hg >= 3) {
              mbar_expect(bar + 8 * B_SC, PG);
              tma_ld(sb + P_R * PG, &p.mapXT, rb * 64, DM + hg * 64, bar + 8 * B_SC);
            }
            ld_xe(4);
            done(0, 2, 1);
            fence_async_smem();
            ld_xe(5); ld_xe(6); ld_xe(7);
            done(1, 0, 1);
            ld_w(4);
            done(1, 1, 1);
            ld_w(5);
          }
          done(1, 2, layer);
          fence_async_smem();
          ld_w(6); ld_w(7);
          auto ld_res = [&](int half) {
            const uint32_t b = bar + 8 * (B_RF + half);
            mbar_expect(b, PG);
            if (layer == 0) tma_ld(sb + (half ? 2 : P_R) * PG, &p.mapX, hg * 64, (16 * half + rb) * 64, b);
            else tma_ld(sb + (half ? 2 : P_R) * PG, &p.mapXT, (16 * half + rb) * 64, DM + hg * 64, b);
          };
          done(0, 4, layer); done(1, 3, layer);
          fence_async_smem();
          mbar_expect(bar + 8 * B_WOF, 8 * PG);
#pragma unroll 1
          for (int c = 0; c < 8; c++) {
            if (c == 5) { ld_res(0); done(1, 4, layer); }
            tma_ld5(sb + wo_page(c) * PG, &p.mapWo, hg * 64, c * 2, bar + 8 * B_WOF);
          }
          done(0, 7, layer);
          fence_async_global();
          ld_res(1);
          if (layer) mbar_wait(bar + 8 * B_RS, 0);
          fence_async_global();
#pragma unroll
          for (int half = 0; half < 2; half++) {
            float* stats = g_stats + (layer * 32 + 16 * half + rb) * 192;
            unsigned* cnt = &g_cnt[(C_G + 2 * layer + half) * 32];
            mbar_wait(bar + 8 * (B_STG + half), layer);
            tma_st(&p.mapXT, (16 * half + rb) * 64, 2 * layer * DM + hg * 64, sb + (P_R + half) * PG);
            bulk_red_add_f32(stats, sb + (half ? SM_KGT : SM_STG), 768);
            bulk_commit();
            red_relaxed(cnt);
            if (half == 0) mbar_arrive(bar + 8 * B_PG);
            bulk_wait_read();
            mbar_arrive(bar + 8 * (B_PST + half));
          }
        }
      }
    } else if (warp == 13) {
      mbar_wait(bar + 8 * B_EP, 0);
      const unsigned e1 = (lds32(sb + SM_EP) / NCTA) + 1;
      auto ld_o = [&](int layer) {
#pragma unroll 1
        for (int half = 0; half < 2; half++) {
          done(1, 7, layer);
          mbar_wait(bar + 8 * B_OST, layer);
          if (half) mbar_wait(bar + 8 * (B_OST + 1), layer);
          fence_async_smem();
#pragma unroll
          for (int c = 0; c < 4; c++) mbar_expect(bar + 8 * (B_OF + 4 * half + c), 2 * PG);
          const bf16* src = g_O + (layer * 32 + 16 * half + rb) * 4 * PG;
          uint32_t dst0 = sb + o_page(half, 0) * PG;
          pin(src); pin(dst0);
          spin_hint(&g_cnt[(C_O + layer * 32 + 16 * half + rb) * 32], e1 * 32);
#pragma unroll
          for (int c = 0; c < 4; c++) {
            if (c == 2 && half && layer) { mbar_wait(bar + 8 * B_AL, 0); fence_async_smem(); }
            bulk_ld(c ? sb + o_page(half, c) * PG : dst0, src + c * PG, 2 * PG, bar + 8 * (B_OF + 4 * half + c));
          }
        }
      };
      if (elect_one()) {
        mbar_wait(bar + 8 * (B_WF + 2), 0);
        asm volatile("prefetch.tensormap [%0];" ::"l"(&p.mapXT) : "memory");
        asm volatile("prefetch.tensormap [%0];" ::"l"(&p.mapWo) : "memory");
        spin_until(&g_cnt[C_Z * 32], e1 * NCTA);
        mbar_arrive(bar + 8 * B_ZF);
        TS(3);
        ld_o(0);
#pragma unroll 1
        for (int k = 0; k < 3; k++) {
          mbar_wait(bar + 8 * (B_PUB + k), 0);
          if (k == 2) {
#pragma unroll 1
            for (int c = 0; c < 4; c++) mbar_wait(bar + 8 * (B_XF + c), 1);
          }
          fence_async_smem();
          uint32_t b = bar + 8 * (B_XR + 4 * (k & 1)), dst = sb + (k ? 4 + 4 * k : 0) * PG, c0 = ((k ? 16 : 0) + rb) * 64, c1 = DM + (k & 2) * 128;
#pragma unroll
          for (int c = 0; c < 4; c++) mbar_expect(b + 8 * c, PG);
          pin(b); pin(dst); pin(c0); pin(c1);
          spin_hint(&g_cnt[(C_C + k) * 32], e1 * NCTA);
          TS(10 + k);
#pragma unroll
          for (int c = 0; c < 4; c++) tma_ld(dst + c * PG, &p.mapXT, c0, c1 + c * 64, b + 8 * c);
        }
        ld_o(1);
#pragma unroll 1
        for (int k = 0; k < 2; k++) {
          mbar_wait(bar + 8 * (B_PUB + k), 1);
          spin_hint(&g_cnt[(C_F + 8 * k + (cta >> 4)) * 32], e1 * 16);
          mbar_arrive(bar + 8 * (B_TF + k));
        }
      }
    } else if (warp == 14) {
      mbar_wait(bar + 8 * B_EP, 0);
      const unsigned e1 = (lds32(sb + SM_EP) / NCTA) + 1;
      done(0, 1, 0);
      {
        const uint2* cp = g_colsum + (hg * 192 + lane);
        uint2 v[6];
        bool ok;
        int it = 0;
        do {
          ok = true;
#pragma unroll
          for (int i = 0; i < 6; i++) {
            asm volatile("ld.relaxed.gpu.global.v2.u32 {%0,%1}, [%2];" : "=r"(v[i].x), "=r"(v[i].y) : "l"(cp + 32 * i) : "memory");
            ok = ok && v[i].y == e1;
          }
          if (++it > (1 << 22)) __trap();
        } while (!__all_sync(~0u, ok));
#pragma unroll
        for (int i = 0; i < 6; i++) sts32f(sb + SM_CS + 4 * (lane + 32 * i), __uint_as_float(v[i].x));
      }
      __syncwarp();
      if (elect_one()) {
        mbar_wait(bar + 8 * B_ZF, 0);
        mbar_arrive(bar + 8 * B_LN);
        red_relaxed(&g_cnt[C_CS * 32]);
        TS(13);
#pragma unroll 1
        for (int layer = 0; layer < 2; layer++) {
          const uint32_t b = bar + 8 * (B_GB + 1);
          const bf16* xin = g_xT + ((size_t)2 * layer * DM + 2 * cta) * LSEQ + 1024;
          const float* stats = g_stats + (layer * 32 + 16) * 192;
          mbar_wait(bar + 8 * B_PST, layer);
          spin_hint(&g_cnt[(C_G + 2 * layer) * 32], e1 * NCTA);
          mbar_arrive(bar + 8 * B_GB);
          mbar_wait(bar + 8 * (B_PST + 1), layer);
          fence_async_smem();
          mbar_expect(b, 12288 + PG);
          pin(stats); pin(xin);
          spin_hint(&g_cnt[(C_G + 2 * layer + 1) * 32], e1 * NCTA);
          bulk_ld(sb + CV_ST, stats, 12288, b);
#pragma unroll
          for (int lc = 0; lc < 4; lc++) bulk_ld(sb + cv_x(1, lc), xin + cv_chan(0, lc) * LSEQ, 2048, b);
          TS(14 + layer);
          publish(layer, 1);
        }
      }
    } else {
      const uint4 u = make_uint4(UNSET, UNSET, UNSET, UNSET);
      if (lane < 24) stg128((uint4*)g_stats + cta * 24 + lane, make_uint4(0, 0, 0, 0));
      if (lane < 16) stg128(g_rows + LSEQ + cta * 16 + lane, make_uint4(0, 0, 0, 0));
#pragma unroll 4
      for (int i = 0; i < 16; i++) stg128(g_halo + cta * 512 + 32 * i + lane, u);
#pragma unroll 4
      for (int i = 0; i < 16; i++) stg128(((i & 8) ? (uint4*)g_xT : (uint4*)g_O) + cta * 1024 + (i & 7) * 128 + (lane >> 1) * 8 + (lane & 1), u);
      __syncwarp();
      if (elect_one()) red_release(&g_cnt[C_Z * 32]);
      __syncwarp();
#pragma unroll 1
      for (int layer = 0; layer < 2; layer++) {
        auto reset_done = [&](int s) {
          spin_until(&g_cnt[(C_R + s) * 32], (lds32(sb + SM_EP) / NCTA) * 4 + 4);
          mbar_arrive(bar + 8 * (s == 1 ? B_LN : s == 2 ? B_RS : B_RC));
          if (s) TS(16 + 40 + 9 + s);
        };
        if (layer && elect_one()) reset_done(1);
        __syncwarp();
#pragma unroll 1
        for (int half = 0; half < 2; half++) {
          done(half, 2, layer);
          const uint4* src = g_rows + (layer * LSEQ + (16 * half + rb) * 64 + (opaque_tid() & 31));
          uint4 a, b;
          int it = 0;
          do {
            a = ld_tagged(src); b = ld_tagged(src + 32);
          } while (!__all_sync(~0u, (a.z | a.w) == __float_as_uint(8.f) && (b.z | b.w) == __float_as_uint(8.f)) && ++it < (1 << 20));
          float m0 = __uint_as_float(a.x) * (1.f / DM), m1 = __uint_as_float(b.x) * (1.f / DM);
          float r0 = rsqrt_approx(fmaxf(__uint_as_float(a.y) * (1.f / DM) - m0 * m0, 0.f) + 1e-5f);
          float r1 = rsqrt_approx(fmaxf(__uint_as_float(b.y) * (1.f / DM) - m1 * m1, 0.f) + 1e-5f);
          if (half) done(0, 7, layer);
          const uint32_t dst = sb + ln_off(half) + ((lane >> 4) * 8 + (lane & 7)) * 16 + (lane & 8);
          asm volatile("st.shared.v2.f32 [%0], {%1,%2};" ::"r"(dst), "f"(m0), "f"(r0) : "memory");
          asm volatile("st.shared.v2.f32 [%0], {%1,%2};" ::"r"(dst + 256), "f"(m1), "f"(r1) : "memory");
          __syncwarp();
          if (elect_one()) { mbar_arrive(bar + 8 * (B_LN + half)); TS(16 + layer * 56 + 40 + 14 + half); }
        }
        if (layer && lane < 16) stg128(g_rows + cta * 16 + (opaque_tid() & 31), make_uint4(0, 0, 0, 0));
        if (elect_one()) {
          if (layer) reset_done(2);
          reset_done(3 * layer);
          publish(layer, 0);
          if (!layer) publish(layer, 2);
        }
        __syncwarp();
      }
    }
  }
}

typedef CUresult (*EncodeFn)(CUtensorMap*, CUtensorMapDataType, cuuint32_t, void*, const cuuint64_t*, const cuuint64_t*,
                             const cuuint32_t*, const cuuint32_t*, CUtensorMapInterleave, CUtensorMapSwizzle,
                             CUtensorMapL2promotion, CUtensorMapFloatOOBfill);

static void make_map(EncodeFn enc, CUtensorMap* m, void* ptr, uint64_t cols, uint64_t rows, uint32_t box_rows) {
  cuuint64_t dims[2] = {cols, rows};
  cuuint64_t strides[1] = {cols * 2};
  cuuint32_t box[2] = {64, box_rows};
  cuuint32_t es[2] = {1, 1};
  enc(m, CU_TENSOR_MAP_DATA_TYPE_BFLOAT16, 2, ptr, dims, strides, box, es, CU_TENSOR_MAP_INTERLEAVE_NONE,
      CU_TENSOR_MAP_SWIZZLE_128B, CU_TENSOR_MAP_L2_PROMOTION_L2_128B, CU_TENSOR_MAP_FLOAT_OOB_FILL_NONE);
}
static void make_map3(EncodeFn enc, CUtensorMap* m, void* ptr, uint64_t d0, uint64_t cols, uint64_t rows, uint64_t blk_stride,
                      uint64_t nblocks, uint32_t nblk) {
  cuuint64_t dims[3] = {d0, rows, nblocks};
  cuuint64_t strides[2] = {cols * 2, blk_stride * 2};
  cuuint32_t box[3] = {64, 64, nblk};
  cuuint32_t es[3] = {1, 1, 1};
  enc(m, CU_TENSOR_MAP_DATA_TYPE_BFLOAT16, 3, ptr, dims, strides, box, es, CU_TENSOR_MAP_INTERLEAVE_NONE,
      CU_TENSOR_MAP_SWIZZLE_128B, CU_TENSOR_MAP_L2_PROMOTION_L2_128B, CU_TENSOR_MAP_FLOAT_OOB_FILL_NONE);
}

extern "C" void kernel_launch(void* const* d_in, const int* in_sizes, int n_in, void* d_out, int out_size) {
  static Params prm;
  static void* cached[13] = {nullptr};
  static bool attr_done = false;
  static int grid = NCTA + 4;
  bool same = attr_done && cached[12] == d_out;
  for (int i = 0; i < 12 && same; i++) same = cached[i] == d_in[i];
  if (!same) {
    void* fn = nullptr;
    cudaDriverEntryPointQueryResult qr;
    cudaGetDriverEntryPoint("cuTensorMapEncodeTiled", &fn, cudaEnableDefault, &qr);
    EncodeFn enc = (EncodeFn)fn;
    void* pXT;
    cudaGetSymbolAddress(&pXT, g_xT);
    make_map(enc, &prm.mapX, d_in[0], DM, LSEQ, 64);
    make_map(enc, &prm.mapXT, pXT, LSEQ, 4 * DM, 64);
    {
      cuuint64_t dims[5] = {DM, 2, 4, 4, 16};
      cuuint64_t strides[4] = {DM * 2, 8 * DM * 2, 2 * DM * 2, 32 * DM * 2};
      cuuint32_t box[5] = {64, 2, 4, 4, 2};
      cuuint32_t es[5] = {1, 1, 1, 1, 1};
      enc(&prm.mapWo, CU_TENSOR_MAP_DATA_TYPE_BFLOAT16, 5, d_in[2], dims, strides, box, es, CU_TENSOR_MAP_INTERLEAVE_NONE,
          CU_TENSOR_MAP_SWIZZLE_128B, CU_TENSOR_MAP_L2_PROMOTION_L2_128B, CU_TENSOR_MAP_FLOAT_OOB_FILL_NONE);
    }
    make_map3(enc, &prm.mapW3, d_in[1], DM, 3 * DM, DM, DM, 3, 3);
    prm.out = (bf16*)d_out;
    prm.a_re = (const bf16*)d_in[4]; prm.a_im = (const bf16*)d_in[5];
    prm.b_re = (const bf16*)d_in[6]; prm.b_im = (const bf16*)d_in[7];
    prm.c_re = (const bf16*)d_in[8]; prm.c_im = (const bf16*)d_in[9];
    prm.log_dt = (const bf16*)d_in[10]; prm.dskip = (const bf16*)d_in[11];
    int dev = 0, sms = 0;
    cudaGetDevice(&dev);
    cudaDeviceGetAttribute(&sms, cudaDevAttrMultiProcessorCount, dev);
    grid = sms >= NCTA + 4 ? NCTA + 4 : NCTA + 5;
    cudaFuncSetAttribute(fused_kernel, cudaFuncAttributeMaxDynamicSharedMemorySize, SM_TOTAL);
    for (int i = 0; i < 12; i++) cached[i] = d_in[i];
    cached[12] = d_out;
    attr_done = true;
  }
  fused_kernel<<<grid, NTHREADS, SM_TOTAL>>>(prm);
}
```

```cpp
#include <cuda_runtime.h>
#include <cuda_bf16.h>
#include <cuda.h>
#include <stdint.h>

typedef __nv_bfloat16 bf16;

constexpr int LSEQ = 2048;
constexpr int DM = 512;
constexpr int NCTA = 128;
constexpr int NTHREADS = 512;
#define R_CONS 200
#define R_HELP 88
#define R_AGENT 24
#define TURN0 4
#define TURN1 4

constexpr int PG = 8192;
constexpr int P_R = 25;
__host__ __device__ constexpr int x_page(int half, int c) { return half ? 8 + c : c < 5 ? c : c - 5; }
__host__ __device__ constexpr int w_page(int c) { return (c & 3) < 3 ? 16 + 3 * (c & 3) : c < 4 ? 5 : 8; }
__host__ __device__ constexpr int wo_page(int c) { return c < 5 ? 3 + c : 11 + c; }
__host__ __device__ constexpr int o_page(int half, int pair) { return half ? (pair ? 25 - 2 * pair : 0) : 8 + 2 * pair; }
constexpr int SM_KGB = (P_R + 1) * PG;
constexpr int SM_KC = 27 * PG;
constexpr int KC_STRIDE = 648;
__host__ __device__ constexpr int kc_off(int lc) { return SM_KC + (lc & 1) * 2 * KC_STRIDE + (lc < 2 ? 3328 : 0); }
constexpr int SM_KGT = SM_KC + 3328 + 2592;
constexpr int SM_CS = SM_KGT + 2048;
constexpr int SM_RED = SM_CS + 768;
constexpr int SM_EP = SM_RED + 16;
constexpr int SM_STG = SM_RED + 32;
constexpr int SM_LN = SM_STG + 768;
__host__ __device__ constexpr int ln_off(int half) { return half ? PG + 4096 : SM_LN; }
constexpr int SM_BAR = SM_LN + 512;
constexpr int SM_TS = SM_BAR + 704;
constexpr int SM_TOTAL = SM_TS + 512;
static_assert(SM_TOTAL <= 232448 && SM_STG % 16 == 0 && SM_KGT % 16 == 0, "shared memory");

constexpr int CV_UH = 140 * 16;
__host__ __device__ constexpr int cv_u(int lc) { return (8 + 2 * lc) * PG; }
__host__ __device__ constexpr int cv_pe(int lc, int early) { return early ? 19 * PG + lc * 4480 : cv_u(lc) + 4480; }
__host__ __device__ constexpr int cv_pb1(int lc, int w) { return w ? cv_u(lc) + 8960 + (w - 1) * 2048 : 7 * PG + lc * 2048; }
__host__ __device__ constexpr int cv_fa(int lc) { return cv_pb1(lc, 1) + 128; }
__host__ __device__ constexpr int cv_dump(int lc) { return cv_u(lc) + 16256; }
__host__ __device__ constexpr int cv_pb0(int lc, int w) { return lc * PG + w * 2048; }
__host__ __device__ constexpr int cv_se(int lc) { return 5 * PG + lc * 4096; }
__host__ __device__ constexpr int cv_so(int lc) { return cv_se(lc) + 2048; }
__host__ __device__ constexpr int cv_x(int half, int lc) { return (P_R + half) * PG + lc * 2048; }
constexpr int CV_ST = 22 * PG;
__host__ __device__ constexpr int cv_chan(int cta, int lc) { return 2 * cta + (lc & 1) + 256 * (lc >> 1); }

enum {
  B_XF = 0,
  B_WF = 16,
  B_OF = 24,
  B_DN = 32,
  B_PG = 46,
  B_XR = 48,
  B_RF = 56,
  B_PST = 58,
  B_GB = 60,
  B_TF = 62,
  B_RT = 64,
  B_RS = 66,
  B_RC = 67,
  B_WOF = 68,
  B_ZF = 69,
  B_EP = 70,
  B_KG = 71,
  B_SC = 37,
  B_LN = 72,
  B_END = 38,
  B_STG = 74,
  B_OST = 76,
  B_PDONE = 78,
  B_PE = 80,
  B_U = 81,
  B_U1 = 82,
  B_PUB = 83,
  B_AL = 86,
  B_COUNT = 87
};

enum {
  C_CS = 0,
  C_G = 1,
  C_C = 5,
  C_O = 21,
  C_Z = 85,
  C_R = 86,
  C_F = 90,
  C_COUNT = 106
};

__device__ unsigned g_cnt[C_COUNT * 32];
__device__ __align__(1024) bf16 g_O[2 * LSEQ * DM];
__device__ __align__(1024) bf16 g_xT[4 * DM * LSEQ];
__device__ __align__(1024) float g_stats[2 * 32 * 192];
__device__ __align__(1024) uint2 g_colsum[3 * DM];
__device__ __align__(1024) uint4 g_halo[32 * 8 * 256];
__device__ __align__(1024) uint4 g_rows[2 * LSEQ];
#define TS(i) do { } while (0)
#define TSW(k) do { if ((threadIdx.x & 127) == 0) TS(16 + layer * 56 + (threadIdx.x >> 7) * 20 + (k)); } while (0)
#define TSG(k) do { } while (0)

#define RETRY(i) do { } while (0)
#define LTS(i) do { } while (0)
#define LTE() do { } while (0)

struct Params {
  CUtensorMap mapX, mapW3, mapXT, mapWo;
  bf16* out;
  const bf16 *a_re, *a_im, *b_re, *b_im, *c_re, *c_im, *log_dt, *dskip;
};

__device__ __forceinline__ uint32_t s32(const void* p) { return (uint32_t)__cvta_generic_to_shared(p); }
__device__ __forceinline__ void mbar_init(uint32_t b, int c) { asm volatile("mbarrier.init.shared::cta.b64 [%0], %1;" ::"r"(b), "r"(c) : "memory"); }
__device__ __forceinline__ void mbar_expect(uint32_t b, int bytes) { asm volatile("mbarrier.arrive.expect_tx.shared::cta.b64 _, [%0], %1;" ::"r"(b), "r"(bytes) : "memory"); }
__device__ __forceinline__ void mbar_arrive(uint32_t b) { asm volatile("mbarrier.arrive.shared::cta.b64 _, [%0];" ::"r"(b) : "memory"); }
__device__ __forceinline__ void mbar_wait(uint32_t b, int parity) {
  asm volatile("{\n.reg .pred p;\nWAIT_LOOP:\nmbarrier.try_wait.parity.shared::cta.b64 p, [%0], %1;\n@p bra WAIT_DONE;\nbra WAIT_LOOP;\nWAIT_DONE:\n}" ::"r"(b), "r"(parity) : "memory");
}
__device__ __forceinline__ bool mbar_test(uint32_t b, int parity) {
  uint32_t ok;
  asm volatile("{\n.reg .pred p;\nmbarrier.test_wait.parity.shared::cta.b64 p, [%1], %2;\nselp.u32 %0, 1, 0, p;\n}" : "=r"(ok) : "r"(b), "r"(parity) : "memory");
  return ok != 0;
}
__device__ __forceinline__ int opaque_tid() { int v; asm volatile("mov.u32 %0, %%tid.x;" : "=r"(v)); return v; }
__device__ __forceinline__ bool elect_one() {
  uint32_t r;
  asm volatile("{\n.reg .pred p;\nelect.sync _|p, 0xffffffff;\nselp.u32 %0, 1, 0, p;\n}" : "=r"(r));
  return r != 0;
}
__device__ __forceinline__ void tma_ld(uint32_t dst, const CUtensorMap* m, int c0, int c1, uint32_t bar) {
  asm volatile("cp.async.bulk.tensor.2d.shared::cluster.global.mbarrier::complete_tx::bytes [%0], [%1, {%3, %4}], [%2];"
               ::"r"(dst), "l"(m), "r"(bar), "r"(c0), "r"(c1) : "memory");
}
__device__ __forceinline__ void tma_ld3(uint32_t dst, const CUtensorMap* m, int c0, int c1, int c2, uint32_t bar) {
  asm volatile("cp.async.bulk.tensor.3d.shared::cluster.global.mbarrier::complete_tx::bytes [%0], [%1, {%3, %4, %5}], [%2];"
               ::"r"(dst), "l"(m), "r"(bar), "r"(c0), "r"(c1), "r"(c2) : "memory");
}
__device__ __forceinline__ void tma_ld5(uint32_t dst, const CUtensorMap* m, int c0, int c4, uint32_t bar) {
  asm volatile("cp.async.bulk.tensor.5d.shared::cluster.global.mbarrier::complete_tx::bytes [%0], [%1, {%3, 0, 0, 0, %4}], [%2];"
               ::"r"(dst), "l"(m), "r"(bar), "r"(c0), "r"(c4) : "memory");
}
__device__ __forceinline__ void tma_prefetch5(const CUtensorMap* m, int c0, int c4) {
  asm volatile("cp.async.bulk.prefetch.tensor.5d.L2.global.tile [%0, {%1, 0, 0, 0, %2}];" ::"l"(m), "r"(c0), "r"(c4) : "memory");
}
__device__ __forceinline__ void tma_prefetch3(const CUtensorMap* m, int c0, int c1, int c2) {
  asm volatile("cp.async.bulk.prefetch.tensor.3d.L2.global.tile [%0, {%1, %2, %3}];" ::"l"(m), "r"(c0), "r"(c1), "r"(c2) : "memory");
}
__device__ __forceinline__ void tma_st(const CUtensorMap* m, int c0, int c1, uint32_t src) {
  asm volatile("cp.async.bulk.tensor.2d.global.shared::cta.bulk_group [%0, {%2, %3}], [%1];" ::"l"(m), "r"(src), "r"(c0), "r"(c1) : "memory");
}
__device__ __forceinline__ void bulk_ld(uint32_t dst, const void* src, int bytes, uint32_t bar) {
  asm volatile("cp.async.bulk.shared::cluster.global.mbarrier::complete_tx::bytes [%0], [%1], %2, [%3];" ::"r"(dst), "l"(src), "r"(bytes), "r"(bar) : "memory");
}
__device__ __forceinline__ void bulk_red_add_f32(void* dst, uint32_t src, int bytes) {
  asm volatile("cp.reduce.async.bulk.global.shared::cta.bulk_group.add.f32 [%0], [%1], %2;" ::"l"(dst), "r"(src), "r"(bytes) : "memory");
}
__device__ __forceinline__ void bulk_commit() { asm volatile("cp.async.bulk.commit_group;" ::: "memory"); }
__device__ __forceinline__ void fence_async_smem() { asm volatile("fence.proxy.async.shared::cta;" ::: "memory"); }
__device__ __forceinline__ void fence_async_global() { asm volatile("fence.proxy.async.global;" ::: "memory"); }
__device__ __forceinline__ void bar_sync(int id, int n) { asm volatile("bar.sync %0, %1;" ::"r"(id), "r"(n) : "memory"); }
__device__ __forceinline__ void bar_arrive(int id, int n) { asm volatile("bar.arrive %0, %1;" ::"r"(id), "r"(n) : "memory"); }
__device__ __forceinline__ bool bar_or(int id, int n, bool v) {
  uint32_t r;
  asm volatile("{\n.reg .pred p, q;\nsetp.ne.u32 q, %3, 0;\nbar.red.or.pred p, %1, %2, q;\nselp.u32 %0, 1, 0, p;\n}" : "=r"(r) : "r"(id), "r"(n), "r"((uint32_t)v) : "memory");
  return r != 0;
}
__device__ __forceinline__ void bulk_wait_read() { asm volatile("cp.async.bulk.wait_group.read 0;" ::: "memory"); }
__device__ __forceinline__ void stg128(void* p, uint4 v) { asm volatile("st.relaxed.gpu.global.v4.u32 [%0], {%1,%2,%3,%4};" ::"l"(p), "r"(v.x), "r"(v.y), "r"(v.z), "r"(v.w) : "memory"); }
constexpr uint32_t UNSET = 0xffffffffu;
constexpr int MAX_RETRY = 1 << 16;
__device__ __forceinline__ void wg_fence() { asm volatile("wgmma.fence.sync.aligned;" ::: "memory"); }
__device__ __forceinline__ void wg_commit() { asm volatile("wgmma.commit_group.sync.aligned;" ::: "memory"); }
template <int N> __device__ __forceinline__ void wg_wait() { asm volatile("wgmma.wait_group.sync.aligned %0;" ::"n"(N) : "memory"); }
__device__ __forceinline__ uint64_t mkdesc(uint32_t addr, uint32_t lbo, uint32_t sbo, int sw) {
  return (uint64_t)((addr & 0x3FFFF) >> 4) | ((uint64_t)(lbo >> 4) << 16) | ((uint64_t)(sbo >> 4) << 32) | ((uint64_t)sw << 62);
}
__device__ __forceinline__ void ldsm4(uint32_t* r, uint32_t a) {
  asm volatile("ldmatrix.sync.aligned.m8n8.x4.shared.b16 {%0,%1,%2,%3}, [%4];" : "=r"(r[0]), "=r"(r[1]), "=r"(r[2]), "=r"(r[3]) : "r"(a) : "memory");
}
__device__ __forceinline__ void ldsm4t(uint32_t* r, uint32_t a) {
  asm volatile("ldmatrix.sync.aligned.m8n8.x4.trans.shared.b16 {%0,%1,%2,%3}, [%4];" : "=r"(r[0]), "=r"(r[1]), "=r"(r[2]), "=r"(r[3]) : "r"(a) : "memory");
}
__device__ __forceinline__ void stsm4(uint32_t a, uint32_t r0, uint32_t r1, uint32_t r2, uint32_t r3) {
  asm volatile("stmatrix.sync.aligned.m8n8.x4.shared.b16 [%0], {%1,%2,%3,%4};" ::"r"(a), "r"(r0), "r"(r1), "r"(r2), "r"(r3) : "memory");
}
__device__ __forceinline__ void stsm4t(uint32_t a, uint32_t r0, uint32_t r1, uint32_t r2, uint32_t r3) {
  asm volatile("stmatrix.sync.aligned.m8n8.x4.trans.shared.b16 [%0], {%1,%2,%3,%4};" ::"r"(a), "r"(r0), "r"(r1), "r"(r2), "r"(r3) : "memory");
}
__device__ __forceinline__ uint32_t movm_t(uint32_t a) { uint32_t r; asm volatile("movmatrix.sync.aligned.m8n8.trans.b16 %0, %1;" : "=r"(r) : "r"(a)); return r; }
__device__ __forceinline__ uint32_t lds32(uint32_t a) { uint32_t v; asm volatile("ld.shared.b32 %0, [%1];" : "=r"(v) : "r"(a) : "memory"); return v; }
__device__ __forceinline__ float2 lds64f(uint32_t a) { float2 v; asm volatile("ld.shared.v2.f32 {%0,%1}, [%2];" : "=f"(v.x), "=f"(v.y) : "r"(a) : "memory"); return v; }
__device__ __forceinline__ float4 lds128f(uint32_t a) { float4 v; asm volatile("ld.shared.v4.f32 {%0,%1,%2,%3}, [%4];" : "=f"(v.x), "=f"(v.y), "=f"(v.z), "=f"(v.w) : "r"(a) : "memory"); return v; }
__device__ __forceinline__ uint4 lds128(uint32_t a) { uint4 v; asm volatile("ld.shared.v4.b32 {%0,%1,%2,%3}, [%4];" : "=r"(v.x), "=r"(v.y), "=r"(v.z), "=r"(v.w) : "r"(a) : "memory"); return v; }
__device__ __forceinline__ void sts128(uint32_t a, uint4 v) { asm volatile("st.shared.v4.b32 [%0], {%1,%2,%3,%4};" ::"r"(a), "r"(v.x), "r"(v.y), "r"(v.z), "r"(v.w) : "memory"); }
__device__ __forceinline__ void sts128f(uint32_t a, float x, float y, float z, float w) { asm volatile("st.shared.v4.f32 [%0], {%1,%2,%3,%4};" ::"r"(a), "f"(x), "f"(y), "f"(z), "f"(w) : "memory"); }
__device__ __forceinline__ void sts32f(uint32_t a, float v) { asm volatile("st.shared.f32 [%0], %1;" ::"r"(a), "f"(v) : "memory"); }
__device__ __forceinline__ void sts16(uint32_t a, uint16_t v) { asm volatile("st.shared.u16 [%0], %1;" ::"r"(a), "h"(v) : "memory"); }
__device__ __forceinline__ uint32_t lds16(uint32_t a) { uint16_t v; asm volatile("ld.shared.u16 %0, [%1];" : "=h"(v) : "r"(a) : "memory"); return v; }
__device__ __forceinline__ uint32_t packbf(float lo, float hi) { uint32_t r; asm("cvt.rn.bf16x2.f32 %0, %1, %2;" : "=r"(r) : "f"(hi), "f"(lo)); return r; }
__device__ __forceinline__ float bf_lo(uint32_t v) { return __uint_as_float(v << 16); }
__device__ __forceinline__ float bf_hi(uint32_t v) { return __uint_as_float(v & 0xffff0000u); }
__device__ __forceinline__ float ex2(float x) { float r; asm("ex2.approx.ftz.f32 %0, %1;" : "=f"(r) : "f"(x)); return r; }
__device__ __forceinline__ float rsqrt_approx(float x) { float r; asm("rsqrt.approx.ftz.f32 %0, %1;" : "=f"(r) : "f"(x)); return r; }
__device__ __forceinline__ float rcp_approx(float x) { float r; asm("rcp.approx.ftz.f32 %0, %1;" : "=f"(r) : "f"(x)); return r; }
__device__ __forceinline__ void mma_bf16(float* d, const uint32_t* a, uint32_t b0, uint32_t b1) {
  asm("mma.sync.aligned.m16n8k16.row.col.f32.bf16.bf16.f32 {%0,%1,%2,%3}, {%4,%5,%6,%7}, {%8,%9}, {%0,%1,%2,%3};"
               : "+f"(d[0]), "+f"(d[1]), "+f"(d[2]), "+f"(d[3]) : "r"(a[0]), "r"(a[1]), "r"(a[2]), "r"(a[3]), "r"(b0), "r"(b1));
}
__device__ __forceinline__ void red_release(unsigned* p) { asm volatile("red.release.gpu.global.add.u32 [%0], 1;" ::"l"(p) : "memory"); }
__device__ __forceinline__ void red_relaxed(unsigned* p) { asm volatile("red.relaxed.gpu.global.add.u32 [%0], 1;" ::"l"(p) : "memory"); }
__device__ __forceinline__ unsigned ld_relaxed(const unsigned* p) { unsigned v; asm volatile("ld.relaxed.gpu.global.u32 %0, [%1];" : "=r"(v) : "l"(p) : "memory"); return v; }
__device__ __forceinline__ void spin_until(const unsigned* p, unsigned target) {
  int it = 0;
  while ((int)(ld_relaxed(p) - target) < 0) {
    if (++it > (1 << 23)) __trap();
  }
}
template <typename T> __device__ __forceinline__ void pin(T*& p) { asm volatile("" : "+l"(p) :: "memory"); }
__device__ __forceinline__ void pin(uint32_t& v) { asm volatile("" : "+r"(v) :: "memory"); }
__device__ __forceinline__ void spin_hint(const unsigned* p, unsigned target) {
  spin_until(p, target);
}
__device__ __forceinline__ uint4 ld_tagged(const uint4* p) { uint4 v; asm volatile("ld.relaxed.gpu.global.v4.u32 {%0,%1,%2,%3}, [%4];" : "=r"(v.x), "=r"(v.y), "=r"(v.z), "=r"(v.w) : "l"(p) : "memory"); return v; }
__device__ __forceinline__ uint32_t hadd2(uint32_t a, uint32_t b) { uint32_t r; asm("add.rn.bf16x2 %0, %1, %2;" : "=r"(r) : "r"(a), "r"(b)); return r; }

__device__ __forceinline__ uint32_t hfma2(uint32_t a, uint32_t b, uint32_t c) { uint32_t r; asm("fma.rn.bf16x2 %0, %1, %2, %3;" : "=r"(r) : "r"(a), "r"(b), "r"(c)); return r; }
__device__ __forceinline__ void sts32(uint32_t a, uint32_t v) { asm volatile("st.shared.u32 [%0], %1;" ::"r"(a), "r"(v) : "memory"); }

template <int N> __device__ __forceinline__ void acc_fence(float* a) {
#pragma unroll
  for (int i = 0; i < N; i++) asm volatile("" : "+f"(a[i]) :: "memory");
}

template<int N,int TB> __device__ __forceinline__ void wgmma_rs(float* d, const uint32_t* a, uint64_t db, int sd);
template<int N,int TA,int TB> __device__ __forceinline__ void wgmma_ss(float* d, uint64_t da, uint64_t db, int sd);
template<> __device__ __forceinline__ void wgmma_rs<64,0>(float* d, const uint32_t* a, uint64_t db, int sd) {
  asm volatile("{\n.reg .pred p;\nsetp.ne.b32 p, %37, 0;\nwgmma.mma_async.sync.aligned.m64n64k16.f32.bf16.bf16 {%0,%1,%2,%3,%4,%5,%6,%7,%8,%9,%10,%11,%12,%13,%14,%15,%16,%17,%18,%19,%20,%21,%22,%23,%24,%25,%26,%27,%28,%29,%30,%31}, {%32,%33,%34,%35}, %36, p, 1, 1, 0;\n}\n"
   : "+f"(d[0]),"+f"(d[1]),"+f"(d[2]),"+f"(d[3]),"+f"(d[4]),"+f"(d[5]),"+f"(d[6]),"+f"(d[7]),"+f"(d[8]),"+f"(d[9]),"+f"(d[10]),"+f"(d[11]),"+f"(d[12]),"+f"(d[13]),"+f"(d[14]),"+f"(d[15]),"+f"(d[16]),"+f"(d[17]),"+f"(d[18]),"+f"(d[19]),"+f"(d[20]),"+f"(d[21]),"+f"(d[22]),"+f"(d[23]),"+f"(d[24]),"+f"(d[25]),"+f"(d[26]),"+f"(d[27]),"+f"(d[28]),"+f"(d[29]),"+f"(d[30]),"+f"(d[31])
   : "r"(a[0]), "r"(a[1]), "r"(a[2]), "r"(a[3]), "l"(db), "r"(sd));
}
template<> __device__ __forceinline__ void wgmma_rs<56,0>(float* d, const uint32_t* a, uint64_t db, int sd) {
  asm volatile("{\n.reg .pred p;\nsetp.ne.b32 p, %33, 0;\nwgmma.mma_async.sync.aligned.m64n56k16.f32.bf16.bf16 {%0,%1,%2,%3,%4,%5,%6,%7,%8,%9,%10,%11,%12,%13,%14,%15,%16,%17,%18,%19,%20,%21,%22,%23,%24,%25,%26,%27}, {%28,%29,%30,%31}, %32, p, 1, 1, 0;\n}\n"
   : "+f"(d[0]),"+f"(d[1]),"+f"(d[2]),"+f"(d[3]),"+f"(d[4]),"+f"(d[5]),"+f"(d[6]),"+f"(d[7]),"+f"(d[8]),"+f"(d[9]),"+f"(d[10]),"+f"(d[11]),"+f"(d[12]),"+f"(d[13]),"+f"(d[14]),"+f"(d[15]),"+f"(d[16]),"+f"(d[17]),"+f"(d[18]),"+f"(d[19]),"+f"(d[20]),"+f"(d[21]),"+f"(d[22]),"+f"(d[23]),"+f"(d[24]),"+f"(d[25]),"+f"(d[26]),"+f"(d[27])
   : "r"(a[0]), "r"(a[1]), "r"(a[2]), "r"(a[3]), "l"(db), "r"(sd));
}
template<> __device__ __forceinline__ void wgmma_rs<48,0>(float* d, const uint32_t* a, uint64_t db, int sd) {
  asm volatile("{\n.reg .pred p;\nsetp.ne.b32 p, %29, 0;\nwgmma.mma_async.sync.aligned.m64n48k16.f32.bf16.bf16 {%0,%1,%2,%3,%4,%5,%6,%7,%8,%9,%10,%11,%12,%13,%14,%15,%16,%17,%18,%19,%20,%21,%22,%23}, {%24,%25,%26,%27}, %28, p, 1, 1, 0;\n}\n"
   : "+f"(d[0]),"+f"(d[1]),"+f"(d[2]),"+f"(d[3]),"+f"(d[4]),"+f"(d[5]),"+f"(d[6]),"+f"(d[7]),"+f"(d[8]),"+f"(d[9]),"+f"(d[10]),"+f"(d[11]),"+f"(d[12]),"+f"(d[13]),"+f"(d[14]),"+f"(d[15]),"+f"(d[16]),"+f"(d[17]),"+f"(d[18]),"+f"(d[19]),"+f"(d[20]),"+f"(d[21]),"+f"(d[22]),"+f"(d[23])
   : "r"(a[0]), "r"(a[1]), "r"(a[2]), "r"(a[3]), "l"(db), "r"(sd));
}
template<> __device__ __forceinline__ void wgmma_rs<40,0>(float* d, const uint32_t* a, uint64_t db, int sd) {
  asm volatile("{\n.reg .pred p;\nsetp.ne.b32 p, %25, 0;\nwgmma.mma_async.sync.aligned.m64n40k16.f32.bf16.bf16 {%0,%1,%2,%3,%4,%5,%6,%7,%8,%9,%10,%11,%12,%13,%14,%15,%16,%17,%18,%19}, {%20,%21,%22,%23}, %24, p, 1, 1, 0;\n}\n"
   : "+f"(d[0]),"+f"(d[1]),"+f"(d[2]),"+f"(d[3]),"+f"(d[4]),"+f"(d[5]),"+f"(d[6]),"+f"(d[7]),"+f"(d[8]),"+f"(d[9]),"+f"(d[10]),"+f"(d[11]),"+f"(d[12]),"+f"(d[13]),"+f"(d[14]),"+f"(d[15]),"+f"(d[16]),"+f"(d[17]),"+f"(d[18]),"+f"(d[19])
   : "r"(a[0]), "r"(a[1]), "r"(a[2]), "r"(a[3]), "l"(db), "r"(sd));
}
template<> __device__ __forceinline__ void wgmma_rs<32,0>(float* d, const uint32_t* a, uint64_t db, int sd) {
  asm volatile("{\n.reg .pred p;\nsetp.ne.b32 p, %21, 0;\nwgmma.mma_async.sync.aligned.m64n32k16.f32.bf16.bf16 {%0,%1,%2,%3,%4,%5,%6,%7,%8,%9,%10,%11,%12,%13,%14,%15}, {%16,%17,%18,%19}, %20, p, 1, 1, 0;\n}\n"
   : "+f"(d[0]),"+f"(d[1]),"+f"(d[2]),"+f"(d[3]),"+f"(d[4]),"+f"(d[5]),"+f"(d[6]),"+f"(d[7]),"+f"(d[8]),"+f"(d[9]),"+f"(d[10]),"+f"(d[11]),"+f"(d[12]),"+f"(d[13]),"+f"(d[14]),"+f"(d[15])
   : "r"(a[0]), "r"(a[1]), "r"(a[2]), "r"(a[3]), "l"(db), "r"(sd));
}
template<> __device__ __forceinline__ void wgmma_rs<24,0>(float* d, const uint32_t* a, uint64_t db, int sd) {
  asm volatile("{\n.reg .pred p;\nsetp.ne.b32 p, %17, 0;\nwgmma.mma_async.sync.aligned.m64n24k16.f32.bf16.bf16 {%0,%1,%2,%3,%4,%5,%6,%7,%8,%9,%10,%11}, {%12,%13,%14,%15}, %16, p, 1, 1, 0;\n}\n"
   : "+f"(d[0]),"+f"(d[1]),"+f"(d[2]),"+f"(d[3]),"+f"(d[4]),"+f"(d[5]),"+f"(d[6]),"+f"(d[7]),"+f"(d[8]),"+f"(d[9]),"+f"(d[10]),"+f"(d[11])
   : "r"(a[0]), "r"(a[1]), "r"(a[2]), "r"(a[3]), "l"(db), "r"(sd));
}
template<> __device__ __forceinline__ void wgmma_rs<16,0>(float* d, const uint32_t* a, uint64_t db, int sd) {
  asm volatile("{\n.reg .pred p;\nsetp.ne.b32 p, %13, 0;\nwgmma.mma_async.sync.aligned.m64n16k16.f32.bf16.bf16 {%0,%1,%2,%3,%4,%5,%6,%7}, {%8,%9,%10,%11}, %12, p, 1, 1, 0;\n}\n"
   : "+f"(d[0]),"+f"(d[1]),"+f"(d[2]),"+f"(d[3]),"+f"(d[4]),"+f"(d[5]),"+f"(d[6]),"+f"(d[7])
   : "r"(a[0]), "r"(a[1]), "r"(a[2]), "r"(a[3]), "l"(db), "r"(sd));
}
template<> __device__ __forceinline__ void wgmma_rs<8,0>(float* d, const uint32_t* a, uint64_t db, int sd) {
  asm volatile("{\n.reg .pred p;\nsetp.ne.b32 p, %9, 0;\nwgmma.mma_async.sync.aligned.m64n8k16.f32.bf16.bf16 {%0,%1,%2,%3}, {%4,%5,%6,%7}, %8, p, 1, 1, 0;\n}\n"
   : "+f"(d[0]),"+f"(d[1]),"+f"(d[2]),"+f"(d[3])
   : "r"(a[0]), "r"(a[1]), "r"(a[2]), "r"(a[3]), "l"(db), "r"(sd));
}
template<> __device__ __forceinline__ void wgmma_ss<64,1,0>(float* d, uint64_t da, uint64_t db, int sd) {
  asm volatile("{\n.reg .pred p;\nsetp.ne.b32 p, %34, 0;\nwgmma.mma_async.sync.aligned.m64n64k16.f32.bf16.bf16 {%0,%1,%2,%3,%4,%5,%6,%7,%8,%9,%10,%11,%12,%13,%14,%15,%16,%17,%18,%19,%20,%21,%22,%23,%24,%25,%26,%27,%28,%29,%30,%31}, %32, %33, p, 1, 1, 1, 0;\n}\n"
   : "+f"(d[0]),"+f"(d[1]),"+f"(d[2]),"+f"(d[3]),"+f"(d[4]),"+f"(d[5]),"+f"(d[6]),"+f"(d[7]),"+f"(d[8]),"+f"(d[9]),"+f"(d[10]),"+f"(d[11]),"+f"(d[12]),"+f"(d[13]),"+f"(d[14]),"+f"(d[15]),"+f"(d[16]),"+f"(d[17]),"+f"(d[18]),"+f"(d[19]),"+f"(d[20]),"+f"(d[21]),"+f"(d[22]),"+f"(d[23]),"+f"(d[24]),"+f"(d[25]),"+f"(d[26]),"+f"(d[27]),"+f"(d[28]),"+f"(d[29]),"+f"(d[30]),"+f"(d[31])
   : "l"(da), "l"(db), "r"(sd));
}
template<> __device__ __forceinline__ void wgmma_ss<64,0,1>(float* d, uint64_t da, uint64_t db, int sd) {
  asm volatile("{\n.reg .pred p;\nsetp.ne.b32 p, %34, 0;\nwgmma.mma_async.sync.aligned.m64n64k16.f32.bf16.bf16 {%0,%1,%2,%3,%4,%5,%6,%7,%8,%9,%10,%11,%12,%13,%14,%15,%16,%17,%18,%19,%20,%21,%22,%23,%24,%25,%26,%27,%28,%29,%30,%31}, %32, %33, p, 1, 1, 0, 1;\n}\n"
   : "+f"(d[0]),"+f"(d[1]),"+f"(d[2]),"+f"(d[3]),"+f"(d[4]),"+f"(d[5]),"+f"(d[6]),"+f"(d[7]),"+f"(d[8]),"+f"(d[9]),"+f"(d[10]),"+f"(d[11]),"+f"(d[12]),"+f"(d[13]),"+f"(d[14]),"+f"(d[15]),"+f"(d[16]),"+f"(d[17]),"+f"(d[18]),"+f"(d[19]),"+f"(d[20]),"+f"(d[21]),"+f"(d[22]),"+f"(d[23]),"+f"(d[24]),"+f"(d[25]),"+f"(d[26]),"+f"(d[27]),"+f"(d[28]),"+f"(d[29]),"+f"(d[30]),"+f"(d[31])
   : "l"(da), "l"(db), "r"(sd));
}
template<> __device__ __forceinline__ void wgmma_ss<192,0,1>(float* d, uint64_t da, uint64_t db, int sd) {
  asm volatile("{\n.reg .pred p;\nsetp.ne.b32 p, %98, 0;\nwgmma.mma_async.sync.aligned.m64n192k16.f32.bf16.bf16 {%0,%1,%2,%3,%4,%5,%6,%7,%8,%9,%10,%11,%12,%13,%14,%15,%16,%17,%18,%19,%20,%21,%22,%23,%24,%25,%26,%27,%28,%29,%30,%31,%32,%33,%34,%35,%36,%37,%38,%39,%40,%41,%42,%43,%44,%45,%46,%47,%48,%49,%50,%51,%52,%53,%54,%55,%56,%57,%58,%59,%60,%61,%62,%63,%64,%65,%66,%67,%68,%69,%70,%71,%72,%73,%74,%75,%76,%77,%78,%79,%80,%81,%82,%83,%84,%85,%86,%87,%88,%89,%90,%91,%92,%93,%94,%95}, %96, %97, p, 1, 1, 0, 1;\n}\n"
   : "+f"(d[0]),"+f"(d[1]),"+f"(d[2]),"+f"(d[3]),"+f"(d[4]),"+f"(d[5]),"+f"(d[6]),"+f"(d[7]),"+f"(d[8]),"+f"(d[9]),"+f"(d[10]),"+f"(d[11]),"+f"(d[12]),"+f"(d[13]),"+f"(d[14]),"+f"(d[15]),"+f"(d[16]),"+f"(d[17]),"+f"(d[18]),"+f"(d[19]),"+f"(d[20]),"+f"(d[21]),"+f"(d[22]),"+f"(d[23]),"+f"(d[24]),"+f"(d[25]),"+f"(d[26]),"+f"(d[27]),"+f"(d[28]),"+f"(d[29]),"+f"(d[30]),"+f"(d[31]),"+f"(d[32]),"+f"(d[33]),"+f"(d[34]),"+f"(d[35]),"+f"(d[36]),"+f"(d[37]),"+f"(d[38]),"+f"(d[39]),"+f"(d[40]),"+f"(d[41]),"+f"(d[42]),"+f"(d[43]),"+f"(d[44]),"+f"(d[45]),"+f"(d[46]),"+f"(d[47]),"+f"(d[48]),"+f"(d[49]),"+f"(d[50]),"+f"(d[51]),"+f"(d[52]),"+f"(d[53]),"+f"(d[54]),"+f"(d[55]),"+f"(d[56]),"+f"(d[57]),"+f"(d[58]),"+f"(d[59]),"+f"(d[60]),"+f"(d[61]),"+f"(d[62]),"+f"(d[63]),"+f"(d[64]),"+f"(d[65]),"+f"(d[66]),"+f"(d[67]),"+f"(d[68]),"+f"(d[69]),"+f"(d[70]),"+f"(d[71]),"+f"(d[72]),"+f"(d[73]),"+f"(d[74]),"+f"(d[75]),"+f"(d[76]),"+f"(d[77]),"+f"(d[78]),"+f"(d[79]),"+f"(d[80]),"+f"(d[81]),"+f"(d[82]),"+f"(d[83]),"+f"(d[84]),"+f"(d[85]),"+f"(d[86]),"+f"(d[87]),"+f"(d[88]),"+f"(d[89]),"+f"(d[90]),"+f"(d[91]),"+f"(d[92]),"+f"(d[93]),"+f"(d[94]),"+f"(d[95])
   : "l"(da), "l"(db), "r"(sd));
}
template<> __device__ __forceinline__ void wgmma_ss<192,1,1>(float* d, uint64_t da, uint64_t db, int sd) {
  asm volatile("{\n.reg .pred p;\nsetp.ne.b32 p, %98, 0;\nwgmma.mma_async.sync.aligned.m64n192k16.f32.bf16.bf16 {%0,%1,%2,%3,%4,%5,%6,%7,%8,%9,%10,%11,%12,%13,%14,%15,%16,%17,%18,%19,%20,%21,%22,%23,%24,%25,%26,%27,%28,%29,%30,%31,%32,%33,%34,%35,%36,%37,%38,%39,%40,%41,%42,%43,%44,%45,%46,%47,%48,%49,%50,%51,%52,%53,%54,%55,%56,%57,%58,%59,%60,%61,%62,%63,%64,%65,%66,%67,%68,%69,%70,%71,%72,%73,%74,%75,%76,%77,%78,%79,%80,%81,%82,%83,%84,%85,%86,%87,%88,%89,%90,%91,%92,%93,%94,%95}, %96, %97, p, 1, 1, 1, 1;\n}\n"
   : "+f"(d[0]),"+f"(d[1]),"+f"(d[2]),"+f"(d[3]),"+f"(d[4]),"+f"(d[5]),"+f"(d[6]),"+f"(d[7]),"+f"(d[8]),"+f"(d[9]),"+f"(d[10]),"+f"(d[11]),"+f"(d[12]),"+f"(d[13]),"+f"(d[14]),"+f"(d[15]),"+f"(d[16]),"+f"(d[17]),"+f"(d[18]),"+f"(d[19]),"+f"(d[20]),"+f"(d[21]),"+f"(d[22]),"+f"(d[23]),"+f"(d[24]),"+f"(d[25]),"+f"(d[26]),"+f"(d[27]),"+f"(d[28]),"+f"(d[29]),"+f"(d[30]),"+f"(d[31]),"+f"(d[32]),"+f"(d[33]),"+f"(d[34]),"+f"(d[35]),"+f"(d[36]),"+f"(d[37]),"+f"(d[38]),"+f"(d[39]),"+f"(d[40]),"+f"(d[41]),"+f"(d[42]),"+f"(d[43]),"+f"(d[44]),"+f"(d[45]),"+f"(d[46]),"+f"(d[47]),"+f"(d[48]),"+f"(d[49]),"+f"(d[50]),"+f"(d[51]),"+f"(d[52]),"+f"(d[53]),"+f"(d[54]),"+f"(d[55]),"+f"(d[56]),"+f"(d[57]),"+f"(d[58]),"+f"(d[59]),"+f"(d[60]),"+f"(d[61]),"+f"(d[62]),"+f"(d[63]),"+f"(d[64]),"+f"(d[65]),"+f"(d[66]),"+f"(d[67]),"+f"(d[68]),"+f"(d[69]),"+f"(d[70]),"+f"(d[71]),"+f"(d[72]),"+f"(d[73]),"+f"(d[74]),"+f"(d[75]),"+f"(d[76]),"+f"(d[77]),"+f"(d[78]),"+f"(d[79]),"+f"(d[80]),"+f"(d[81]),"+f"(d[82]),"+f"(d[83]),"+f"(d[84]),"+f"(d[85]),"+f"(d[86]),"+f"(d[87]),"+f"(d[88]),"+f"(d[89]),"+f"(d[90]),"+f"(d[91]),"+f"(d[92]),"+f"(d[93]),"+f"(d[94]),"+f"(d[95])
   : "l"(da), "l"(db), "r"(sd));
}

template <bool TR>
__device__ __forceinline__ void gemm_section(float* acc, float& mean0, float& mean1, float& rstd0, float& rstd1,
                                             uint32_t sb, int blk, int hg, int wg, int w, int lane) {
  constexpr int layer = TR ? 1 : 0;
  constexpr int TURN = TR ? TURN1 : TURN0;
  constexpr int LSTAT = TURN < 4 ? TURN - 1 : 3;
  const uint32_t bar = sb + SM_BAR;
  const int g = lane >> 2, t = lane & 3;
  const bool leader = (w == 0) && (lane == 0);
  const int statpos = hg < 3 ? 1 : wg ? LSTAT : TR ? 3 : 2;
  const bool copy = hg >= 3 && wg == 0;
  const int cut = wg ? TURN : 4;
  auto wait_full = [&](int c) {
    mbar_wait(bar + 8 * (B_XF + 8 * wg + c), layer);
    mbar_wait(bar + 8 * (B_WF + c), layer);
  };
  auto peek = [&](int c) {
    const bool x = mbar_test(bar + 8 * (B_XF + 8 * wg + c), layer), y = mbar_test(bar + 8 * (B_WF + c), layer);
    return x && y;
  };
  const uint64_t da0 = mkdesc(sb, TR ? 8192 : 16, 1024, 1), db0 = mkdesc(sb, 8192, 1024, 1);
  uint32_t xt = wg ? 0xfedcba98u : 0x21043210u;
  uint64_t wt = 0x0816131005161310ull;
  uint64_t da = da0 + ((xt & 15) << 9), db = db0 + (16 << 9);
  auto issue = [&](int c, int first) {
    wg_fence();
#pragma unroll
    for (int ks = 0; ks < 4; ks++) wgmma_ss<192, TR ? 1 : 0, 1>(acc, da + (TR ? ks * 128 : ks * 2), db + ks * 128, !first || ks != 0);
    wg_commit();
    xt >>= 4; wt >>= 8;
    da = da0 + ((xt & 15) << 9); db = db0 + (((uint32_t)wt & 31) << 9);
  };
  wait_full(0);
  bool ready = peek(1);
  issue(0, 1);
  TSW(0);
#pragma unroll 1
  for (int c = 1; c < cut; c++) {
    if (!ready) wait_full(c);
    issue(c, 0);
    ready = peek(c + 1);
    wg_wait<1>();
    if (leader) mbar_arrive(bar + 8 * (B_DN + 8 * wg + c - 1));
    if (wg == 1 && c == cut - 1) {
      wg_wait<0>();
      if (leader) mbar_arrive(bar + 8 * (B_DN + 8 + c));
    }
    if (c == statpos) {
      mbar_wait(bar + 8 * (copy ? B_SC : B_XF + 8 * wg + hg), layer);
      uint32_t A[16];
      const uint32_t xb = sb + (copy ? P_R : 8 * wg + hg) * PG;
#pragma unroll
      for (int ks = 0; ks < 4; ks++) {
        if (!TR) {
          const int row = 16 * w + (lane & 15), kc = 2 * ks + (lane >> 4);
          ldsm4(&A[4 * ks], xb + row * 128 + ((kc ^ (row & 7)) << 4));
        } else {
          const int k = 16 * ks + (lane & 7) + 8 * (lane >> 4), pc = 2 * w + ((lane >> 3) & 1);
          ldsm4t(&A[4 * ks], xb + k * 128 + ((pc ^ (k & 7)) << 4));
        }
      }
      float s0 = 0.f, q0 = 0.f, s1 = 0.f, q1 = 0.f;
#pragma unroll
      for (int i = 0; i < 16; i += 2) {
        const float a = bf_lo(A[i]), b = bf_hi(A[i]), c_ = bf_lo(A[i + 1]), d = bf_hi(A[i + 1]);
        s0 += a + b; q0 = fmaf(a, a, q0); q0 = fmaf(b, b, q0);
        s1 += c_ + d; q1 = fmaf(c_, c_, q1); q1 = fmaf(d, d, q1);
      }
#pragma unroll
      for (int o = 1; o <= 2; o <<= 1) {
        s0 += __shfl_xor_sync(~0u, s0, o); q0 += __shfl_xor_sync(~0u, q0, o);
        s1 += __shfl_xor_sync(~0u, s1, o); q1 += __shfl_xor_sync(~0u, q1, o);
      }
      if (t < 2)
        asm volatile("red.relaxed.gpu.global.add.v4.f32 [%0], {%1,%2,%3,%4};" ::"l"(g_rows + layer * LSEQ + blk * 64 + 16 * w + g + 8 * t),
                     "f"(t ? s1 : s0), "f"(t ? q1 : q0), "f"(1.f), "f"(0.f) : "memory");
    }
  }
  if (wg == 1) {
#pragma unroll 1
    for (int c = cut; c < 8; c++) wait_full(c);
    ready = true;
    bar_sync(5, 256);
  }
#pragma unroll 1
  for (int c = cut; c < 8; c++) {
    if (!ready) wait_full(c);
    issue(c, 0);
    if (wg == 1) {
      wg_wait<2>();
      if (leader && c >= cut + 2) mbar_arrive(bar + 8 * (B_DN + 8 + c - 2));
    } else if (c == 7) {
      bar_arrive(5, 256);
    } else {
      ready = peek(c + 1);
      wg_wait<1>();
      if (leader && c < 6) mbar_arrive(bar + 8 * (B_DN + c - 1));
    }
  }
  mbar_wait(bar + 8 * (B_LN + wg), layer);
  const float4 ln = lds128f(sb + ln_off(wg) + (8 * w + g) * 16);
  mean0 = ln.x; rstd0 = ln.y; mean1 = ln.z; rstd1 = ln.w;
  wg_wait<0>();
  acc_fence<96>(acc);
  if (leader) mbar_arrive(bar + 8 * (B_DN + 8 * wg + 7));
}

__device__ __forceinline__ void attn_phase(const Params& p, uint32_t sb, int layer, int rb, int hg, int wg, int w) {
  const int lane = opaque_tid() & 31;
  const int g = lane >> 2, t = lane & 3;
  const uint32_t bar = sb + SM_BAR;
  const int blk = 16 * wg + rb;
  float acc[96];
  float2 cs[24];
  float mean0, mean1, rstd0, rstd1;
  if (layer) gemm_section<true>(acc, mean0, mean1, rstd0, rstd1, sb, blk, hg, wg, w, lane);
  else gemm_section<false>(acc, mean0, mean1, rstd0, rstd1, sb, blk, hg, wg, w, lane);
  TSW(1);
#pragma unroll
  for (int j = 8; j < 24; j++) cs[j] = lds64f(sb + SM_CS + 4 * (8 * j + 2 * t));
  const uint32_t kvx = sb + (wg ? 22 : 0) * PG;

  uint32_t kb[4][8], vb[4][8], qa[4][4];
  {
    const float nm0 = -mean0 * rstd0, nm1 = -mean1 * rstd1;
    const int st_row = 16 * w + (lane & 7) + 8 * ((lane >> 3) & 1);
    const uint32_t st_base = kvx + st_row * 256;
    const bool sender = (w == 3 && blk < 31);
    uint4* halo = &g_halo[(blk * 8 + hg) * 256 + lane];
    uint32_t r[4][2][4];
#pragma unroll
    for (int h = 0; h < 4; h++) {
#pragma unroll
      for (int kv = 0; kv < 2; kv++) {
#pragma unroll
        for (int dh = 0; dh < 2; dh++) {
          const int j = 8 + kv * 8 + 2 * h + dh;
          const float2 c2 = cs[j];
          const float v0 = fmaf(acc[4 * j + 0], rstd0, nm0 * c2.x), v1 = fmaf(acc[4 * j + 1], rstd0, nm0 * c2.y);
          const float v2 = fmaf(acc[4 * j + 2], rstd1, nm1 * c2.x), v3 = fmaf(acc[4 * j + 3], rstd1, nm1 * c2.y);
          r[h][kv][2 * dh] = packbf(v0, v1);
          r[h][kv][2 * dh + 1] = packbf(v2, v3);
        }
      }
      if (sender) {
        stg128(halo + (2 * h) * 32, make_uint4(r[h][0][0], r[h][0][2], r[h][0][1], r[h][0][3]));
        stg128(halo + (2 * h + 1) * 32, make_uint4(r[h][1][0], r[h][1][1], r[h][1][2], r[h][1][3]));
      }
    }
#pragma unroll
    for (int j = 0; j < 8; j++) cs[j] = lds64f(sb + SM_CS + 4 * (8 * j + 2 * t));
    mbar_wait(bar + 8 * (B_DN + 7), layer);
#pragma unroll
    for (int h = 0; h < 4; h++) {
#pragma unroll
      for (int kv = 0; kv < 2; kv++) {
        const int chunk = 4 * h + 2 * kv + (lane >> 4);
        if (w < 3) stsm4(st_base + (((chunk & 8) | ((chunk ^ st_row) & 7)) << 4), r[h][kv][0], r[h][kv][1], r[h][kv][2], r[h][kv][3]);
      }
      kb[h][4] = r[h][0][0]; kb[h][5] = r[h][0][2]; kb[h][6] = r[h][0][1]; kb[h][7] = r[h][0][3];
      vb[h][4] = movm_t(r[h][1][0]); vb[h][5] = movm_t(r[h][1][1]); vb[h][6] = movm_t(r[h][1][2]); vb[h][7] = movm_t(r[h][1][3]);
    }
#pragma unroll
    for (int h = 0; h < 4; h++) {
#pragma unroll
      for (int dh = 0; dh < 2; dh++) {
        const int j = 2 * h + dh;
        const float2 c2 = cs[j];
        qa[h][2 * dh] = packbf(fmaf(-mean0, c2.x, acc[4 * j + 0]), fmaf(-mean0, c2.y, acc[4 * j + 1]));
        qa[h][2 * dh + 1] = packbf(fmaf(-mean1, c2.x, acc[4 * j + 2]), fmaf(-mean1, c2.y, acc[4 * j + 3]));
      }
    }
  }
  bar_sync(2 + wg, 128);
  TSW(2);
  {
    const uint32_t prev_base = kvx + (16 * w - 16) * 256;
    const int mi = lane >> 3;
    const int r = 8 * (mi >> 1) + (lane & 7), r2 = 8 * (mi & 1) + (lane & 7);
    if (w != 0) {
#pragma unroll
      for (int h = 0; h < 4; h++) {
        const int ch = 4 * h + (mi & 1), ch2 = 4 * h + 2 + (mi >> 1);
        ldsm4(&kb[h][0], prev_base + r * 256 + (((ch & 8) | ((ch ^ r) & 7)) << 4));
        ldsm4t(&vb[h][0], prev_base + r2 * 256 + (((ch2 & 8) | ((ch2 ^ r2) & 7)) << 4));
      }
    } else if (blk > 0) {
      uint4* src = &g_halo[((blk - 1) * 8 + hg) * 256 + lane];
      uint4 hv[8];
      int it = 0;
      bool ok;
      do {
        ok = true;
#pragma unroll
        for (int i = 0; i < 8; i++) hv[i] = ld_tagged(src + i * 32);
#pragma unroll
        for (int i = 0; i < 8; i++) ok = ok && hv[i].x != UNSET;
      } while (!__all_sync(~0u, ok) && ++it < (1 << 20));
      if (layer == 0) {
#pragma unroll
        for (int i = 0; i < 2; i++) stg128(src + i * 128 + (lane >> 1) * 6, make_uint4(UNSET, UNSET, UNSET, UNSET));
      }
#pragma unroll
      for (int h = 0; h < 4; h++) {
        kb[h][0] = hv[2 * h].x; kb[h][1] = hv[2 * h].y; kb[h][2] = hv[2 * h].z; kb[h][3] = hv[2 * h].w;
        vb[h][0] = movm_t(hv[2 * h + 1].x); vb[h][1] = movm_t(hv[2 * h + 1].y);
        vb[h][2] = movm_t(hv[2 * h + 1].z); vb[h][3] = movm_t(hv[2 * h + 1].w);
      }
    } else {
#pragma unroll
      for (int h = 0; h < 4; h++)
#pragma unroll
        for (int k = 0; k < 4; k++) kb[h][k] = vb[h][k] = 0u;
    }
    TSW(3);
  }
  uint4* op = (uint4*)g_O + ((layer * 32 + blk) * 8 + hg) * 512 + 64 * t + 16 * w + g;
  unsigned* ocnt = &g_cnt[(C_O + layer * 32 + blk) * 32];
  pin(op); pin(ocnt);
  mbar_wait(bar + 8 * (B_DN + 15), layer);
  TSW(4);

  const bool first = (blk == 0 && w == 0);
  const int e = t - (g >> 1);
  const bool par = g & 1, epos = e >= 1;
  const uint32_t pmask = par ? 0xffff0000u : 0x0000ffffu;
  const uint32_t mB0 = epos ? pmask : 0u, mB1 = epos ? 0u : pmask;
  const float cl2 = 0.25f * 1.4426950408889634f;
  const float sc0 = rstd0 * cl2, sc1 = rstd1 * cl2;
  const float NEG = -INFINITY;
  float vA0[4], vB0[4], vA1[4], vB1[4];
#pragma unroll
  for (int h = 0; h < 4; h++) {
    float S[4][4];
#pragma unroll
    for (int j = 0; j < 4; j++) {
      S[j][0] = S[j][1] = S[j][2] = S[j][3] = 0.f;
      mma_bf16(S[j], qa[h], kb[h][2 * j], kb[h][2 * j + 1]);
    }
    vA0[h] = par ? S[1][1] : S[1][0];
    vB0[h] = epos ? (par ? S[0][1] : S[0][0]) : (par ? S[2][1] : S[2][0]);
    vA1[h] = par ? S[2][3] : S[2][2];
    vB1[h] = epos ? (par ? S[1][3] : S[1][2]) : (par ? S[3][3] : S[3][2]);
    if (first) { vA0[h] = NEG; if (epos) { vB0[h] = NEG; vB1[h] = NEG; } }
  }
  float m0[4], m1[4];
#pragma unroll
  for (int h = 0; h < 4; h++) { m0[h] = fmaxf(vA0[h], vB0[h]); m1[h] = fmaxf(vA1[h], vB1[h]); }
#pragma unroll
  for (int o = 1; o <= 2; o <<= 1) {
#pragma unroll
    for (int h = 0; h < 4; h++) {
      m0[h] = fmaxf(m0[h], __shfl_xor_sync(~0u, m0[h], o));
      m1[h] = fmaxf(m1[h], __shfl_xor_sync(~0u, m1[h], o));
    }
  }
  float O0[4][4], O1[4][4], Z[4][4];
#pragma unroll
  for (int h = 0; h < 4; h++) {
    const float mm0 = -m0[h] * sc0, mm1 = -m1[h] * sc1;
    const float pA0 = ex2(fmaf(vA0[h], sc0, mm0)), pB0 = ex2(fmaf(vB0[h], sc0, mm0));
    const float pA1 = ex2(fmaf(vA1[h], sc1, mm1)), pB1 = ex2(fmaf(vB1[h], sc1, mm1));
    const uint32_t hA0 = packbf(pA0, pA0), hB0 = packbf(pB0, pB0), hA1 = packbf(pA1, pA1), hB1 = packbf(pB1, pB1);
    const uint32_t P0[4] = {hB0 & mB0, 0u, hA0 & pmask, hB1 & mB0};
    const uint32_t P1[4] = {hB0 & mB1, hA1 & pmask, 0u, hB1 & mB1};
#pragma unroll
    for (int k = 0; k < 4; k++) O0[h][k] = O1[h][k] = Z[h][k] = 0.f;
    mma_bf16(O0[h], P0, vb[h][0], vb[h][1]); mma_bf16(O1[h], P0, vb[h][2], vb[h][3]); mma_bf16(Z[h], P0, 0x3f803f80u, 0x3f803f80u);
    mma_bf16(O0[h], P1, vb[h][4], vb[h][5]); mma_bf16(O1[h], P1, vb[h][6], vb[h][7]); mma_bf16(Z[h], P1, 0x3f803f80u, 0x3f803f80u);
  }
  if (lane == 0) mbar_arrive(bar + 8 * (B_OST + wg));
#pragma unroll
  for (int h = 0; h < 4; h += 2) {
    const float i0 = rcp_approx(Z[h][0]), i1 = rcp_approx(Z[h][2]), j0 = rcp_approx(Z[h + 1][0]), j1 = rcp_approx(Z[h + 1][2]);
    stg128(op + 128 * h, make_uint4(packbf(O0[h][0] * i0, O0[h][1] * i0), packbf(O1[h][0] * i0, O1[h][1] * i0),
                                   packbf(O0[h + 1][0] * j0, O0[h + 1][1] * j0), packbf(O1[h + 1][0] * j0, O1[h + 1][1] * j0)));
    stg128(op + 128 * h + 8, make_uint4(packbf(O0[h][2] * i1, O0[h][3] * i1), packbf(O1[h][2] * i1, O1[h][3] * i1),
                                            packbf(O0[h + 1][2] * j1, O0[h + 1][3] * j1), packbf(O1[h + 1][2] * j1, O1[h + 1][3] * j1)));
  }
  TSW(5);
  __syncwarp();
  if (elect_one()) red_relaxed(ocnt);
  TSW(6);
}

__device__ __forceinline__ void conv_load(uint32_t* A, uint32_t pe);
__device__ __forceinline__ void proj_phase(const Params& p, uint32_t sb, int layer, int rb, int q, uint32_t* A0, uint32_t* A1) {
  const int lane = opaque_tid() & 31;
  const int wg = __shfl_sync(~0u, opaque_tid() >> 7, 0), w = __shfl_sync(~0u, (opaque_tid() >> 5) & 3, 0);
  const bool TR = layer != 0;
  const int t = lane & 3;
  const uint32_t bar = sb + SM_BAR;
  const uint32_t rbx = sb + (P_R + wg) * PG;
  const uint32_t rsrc = sb + (wg ? 2 : P_R) * PG;
  const int blk = 16 * wg + rb;
  mbar_wait(bar + 8 * (B_RF + wg), layer);
  mbar_wait(bar + 8 * B_WOF, layer);
  const uint32_t stg = sb + (wg ? SM_KGT : SM_STG);
  if (layer) {
    const uint32_t pe = sb + cv_pe(wg, 1) + 4 * (16 + 16 * w + (lane >> 2) - 2 * t);
    mbar_wait(bar + 8 * B_PE, 1);
    conv_load(A0, pe);
    conv_load(A1, pe + 2 * 4480);
    __syncwarp();
    if (lane == 0) mbar_arrive(bar + 8 * B_AL);
  } else {
#pragma unroll
    for (int i = 0; i < 68; i++) {
      asm volatile("mov.b32 %0, 0;" : "=r"(A0[i]));
      asm volatile("mov.b32 %0, 0;" : "=r"(A1[i]));
    }
  }
  bool clean = false, staged = false;
#pragma unroll 1
  for (int attempt = 0; attempt < MAX_RETRY; attempt++) {
  uint32_t res[16];
  if (!TR) {
#pragma unroll
    for (int j = 0; j < 8; j += 2) {
      const int mi = lane >> 3;
      const int row = 16 * w + (lane & 7) + 8 * (mi & 1), ch = j + (mi >> 1);
      ldsm4(&res[2 * j], rsrc + row * 128 + ((ch ^ (row & 7)) << 4));
    }
  } else {
#pragma unroll
    for (int j = 0; j < 8; j += 2) {
      const int mi = lane >> 3;
      const int line = 8 * (j + (mi >> 1)) + (lane & 7), pc = 2 * w + (mi & 1);
      ldsm4t(&res[2 * j], rsrc + line * 128 + ((pc ^ (line & 7)) << 4));
    }
  }
  float acc[32];
#pragma unroll
  for (int j = 0; j < 16; j++) { acc[2 * j] = bf_lo(res[j]); acc[2 * j + 1] = bf_hi(res[j]); }
  acc_fence<32>(acc);
  if (wg) mbar_wait(bar + 8 * B_PG, layer);
  const int wg2 = __shfl_sync(~0u, opaque_tid() >> 7, 0);
  const uint64_t da0 = mkdesc(sb, 1024, 128, 0), db0 = mkdesc(sb, 8192, 1024, 1);
#pragma unroll
  for (int c = 0; c < 4; c++) {
    mbar_wait(bar + 8 * (B_OF + 4 * wg + c), layer);
    if (c == 0) TSW(7);
    const uint64_t da = da0 + (uint32_t)(o_page(wg2, c) * 512);
#pragma unroll
    for (int ks = 0; ks < 8; ks++) {
      if (ks % 4 == 0) { if (ks) wg_commit(); if (wg2) wg_wait<0>(); wg_fence(); }
      wgmma_ss<64, 0, 1>(acc, da + ks * 128, db0 + wo_page(2 * c + (ks >> 2)) * 512 + (ks & 3) * 128, 1);
    }
    wg_commit();
  }
  if (wg) mbar_wait(bar + 8 * B_KG, 0);
  wg_wait<0>();
  acc_fence<32>(acc);
  TSW(8);
  if (!clean) {
    const float chk = acc[0] + acc[2];
    clean = __all_sync(~0u, chk == chk);
    if (clean && lane == 0) mbar_arrive(bar + 8 * (B_PDONE + wg));
  }
  float s0 = 0.f, q0 = 0.f, s1 = 0.f, q1 = 0.f;
  uint32_t o[16];
#pragma unroll
  for (int j = 0; j < 8; j++) {
    const float a = acc[4 * j], b = acc[4 * j + 1], c = acc[4 * j + 2], d = acc[4 * j + 3];
    o[2 * j] = packbf(a, b);
    o[2 * j + 1] = packbf(c, d);
    s0 += a + b; q0 = fmaf(a, a, q0); q0 = fmaf(b, b, q0);
    s1 += c + d; q1 = fmaf(c, c, q1); q1 = fmaf(d, d, q1);
  }
#pragma unroll
  for (int j = 0; j < 8; j += 2) {
    const int mi = lane >> 3;
    const int line = 8 * (j + (mi >> 1)) + (lane & 7), pc = 2 * w + (mi & 1);
    stsm4t(rbx + line * 128 + ((pc ^ (line & 7)) << 4), o[2 * j], o[2 * j + 1], o[2 * j + 2], o[2 * j + 3]);
  }
#pragma unroll
  for (int o2 = 1; o2 <= 2; o2 <<= 1) {
    s0 += __shfl_xor_sync(~0u, s0, o2); q0 += __shfl_xor_sync(~0u, q0, o2);
    s1 += __shfl_xor_sync(~0u, s1, o2); q1 += __shfl_xor_sync(~0u, q1, o2);
  }
  {
    const int i = 2 * (lane >> 2) + (t & 1), k = (i * 11) >> 5;
    const float v = (t == 0) ? s0 : (t == 1) ? q0 : (t == 2) ? s1 : q1;
    sts32f(stg + k * 128 + (2 * w + (t >> 1)) * 16 + (i - 3 * k) * 4, v);
  }
  TSW(9);
  fence_async_smem();
  if (attempt == 0 && clean) {
    staged = true;
    __syncwarp();
    if (lane == 0) mbar_arrive(bar + 8 * (B_STG + wg));
  }
  if (!bar_or(2 + wg, 128, !clean)) break;
  const int rtp = mbar_test(bar + 8 * (B_RT + wg), 0);
  bool unset = false;
#pragma unroll
  for (int i = 0; i < 4; i++) unset |= lds32(sb + o_page(wg, i) * PG + (32 * w + lane) * 128) == UNSET;
  if (!bar_or(2 + wg, 128, unset)) break;
  if (w == 0 && elect_one()) {
    fence_async_smem();
    mbar_expect(bar + 8 * (B_RT + wg), 9 * PG);
    if (layer == 0) tma_ld(rsrc, &p.mapX, q * 64, blk * 64, bar + 8 * (B_RT + wg));
    else tma_ld(rsrc, &p.mapXT, blk * 64, DM + q * 64, bar + 8 * (B_RT + wg));
#pragma unroll 1
    for (int c = 0; c < 4; c++) bulk_ld(sb + o_page(wg, c) * PG, g_O + ((layer * 32 + blk) * 4 + c) * PG, 2 * PG, bar + 8 * (B_RT + wg));
  }
  mbar_wait(bar + 8 * (B_RT + wg), rtp);
  RETRY(0);
  }
  if (!clean && lane == 0) mbar_arrive(bar + 8 * (B_PDONE + wg));
  if (!staged && lane == 0) mbar_arrive(bar + 8 * (B_STG + wg));
  TSW(10);
}

__device__ __forceinline__ void conv_load(uint32_t* A, uint32_t pe) {
#pragma unroll
  for (int m = 0; m < 17; m++) {
    A[4 * m + 2] = lds32(pe + 4 * (64 * m - 8));
    A[4 * m + 0] = lds32(pe + 4 * (64 * m));
    A[4 * m + 1] = lds32(pe + 4 * (64 * m + 8));
    asm volatile("mov.b32 %0, %1;" : "=r"(A[4 * m + 3]) : "r"(A[4 * m + 0]));
  }
}
template <int M> __device__ __forceinline__ void conv_tri(float* acc, const uint32_t* A, uint64_t d) {
  if constexpr (M < 16) {
    wgmma_rs<64 - 8 * (M / 2), 0>(acc, A + 4 * M, d + (uint64_t)(64 + 4 * M), M != 0);
    conv_tri<M + 1>(acc, A, d);
  }
}
__device__ __forceinline__ void conv_mma0(float* acc, const uint32_t* A, uint64_t d) {
  wg_fence();
  conv_tri<0>(acc, A, d);
  wg_commit();
}
__device__ __forceinline__ void conv_mma1(float* acc, const uint32_t* A, uint64_t d, uint64_t ds, uint64_t df) {
  wg_fence();
#pragma unroll
  for (int m = 0; m < 17; m++) wgmma_rs<64, 0>(acc, A + 4 * m, d + (uint64_t)(4 * m), m != 0);
  wgmma_ss<64, 1, 0>(acc, ds, df, 1);
  wgmma_ss<64, 1, 0>(acc, ds + 128, df + 128, 1);
  wg_commit();
}
__device__ __forceinline__ void conv_store(float* acc, uint32_t pb, uint32_t over, int w) {
  acc_fence<32>(acc);
  const int l = opaque_tid() & 31, mt = l >> 3;
  int c = 2 * (63 - 8 * (mt >> 1) - (l & 7) + w) + (mt & 1);
  c ^= (c >> 3) & 1;
  const uint32_t a0 = pb + c * 16;
#pragma unroll
  for (int j = 0; j < 8; j += 2)
    stsm4t(j == 0 ? (c < 128 ? a0 : over + (c - 128) * 16) : a0 - 256 * j, packbf(acc[4 * j], acc[4 * j + 1]), packbf(acc[4 * j + 2], acc[4 * j + 3]),
           packbf(acc[4 * j + 4], acc[4 * j + 5]), packbf(acc[4 * j + 6], acc[4 * j + 7]));
}
__device__ __forceinline__ void conv_sums(uint32_t sb, int lc, int ht) {
  const int m = ht - 1;
  uint4 v[2][3];
#pragma unroll
  for (int c = 0; c < 2; c++)
#pragma unroll
    for (int k = 0; k < 3; k++) {
      const int mm = m - 1 + k;
      v[c][k] = lds128(sb + cv_u(lc + c) + (mm >= 0 ? (mm & 1) * CV_UH + (127 - (mm >> 1)) * 16 : 128 * 16));
    }
  const int ce = m + 2, co = m + 1;
#pragma unroll
  for (int c = 0; c < 2; c++) {
    const uint32_t x[8] = {v[c][0].z, v[c][0].w, v[c][1].x, v[c][1].y, v[c][1].z, v[c][1].w, v[c][2].x, v[c][2].y};
    float pv[16];
#pragma unroll
    for (int k = 0; k < 8; k++) { pv[2 * k] = bf_lo(x[k]); pv[2 * k + 1] = bf_hi(x[k]); }
    float t2[15], t4[13], s9[8], s7[8];
#pragma unroll
    for (int i = 0; i < 15; i++) t2[i] = pv[i] + pv[i + 1];
#pragma unroll
    for (int i = 0; i < 13; i++) t4[i] = t2[i] + t2[i + 2];
#pragma unroll
    for (int i = 0; i < 8; i++) {
      s9[i] = (t4[i] + t4[i + 4]) + pv[i + 8];
      s7[i] = (t4[i + 1] + t2[i + 5]) + pv[i + 7];
    }
    const uint4 e4 = make_uint4(packbf(s9[0], s9[1]), packbf(s9[2], s9[3]), packbf(s9[4], s9[5]), packbf(s9[6], s9[7]));
    if (ce < 128) sts128(sb + cv_se(lc + c) + ((ce ^ ((ce >> 3) & 7)) << 4), e4);
    else sts128(sb + cv_se(lc + c), make_uint4(0, 0, 0, 0));
    sts128(sb + cv_so(lc + c) + ((co ^ ((co >> 3) & 7)) << 4),
           make_uint4(packbf(s7[0], s7[1]), packbf(s7[2], s7[3]), packbf(s7[4], s7[5]), packbf(s7[6], s7[7])));
  }
}

template <int HALF, int NCH, int STEP = 1>
__device__ __forceinline__ void conv_epi(uint32_t sb, bf16* out, int lc, int c) {
  uint4 v[NCH][4], xr[NCH];
  const uint32_t sw = (c ^ ((c >> 3) & 1)) * 16;
#pragma unroll
  for (int u = 0; u < NCH; u++) {
#pragma unroll
    for (int k = 0; k < 4; k++) v[u][k] = lds128(sb + (HALF ? cv_pb1(lc + STEP * u, k) : cv_pb0(lc + STEP * u, k)) + sw);
    xr[u] = lds128(sb + cv_x(HALF, lc + STEP * u) + c * 16);
  }
#pragma unroll
  for (int u = 0; u < NCH; u++) {
    uint4 o;
    o.x = hadd2(xr[u].x, hadd2(hadd2(v[u][0].x, v[u][1].x), hadd2(v[u][2].x, v[u][3].x)));
    o.y = hadd2(xr[u].y, hadd2(hadd2(v[u][0].y, v[u][1].y), hadd2(v[u][2].y, v[u][3].y)));
    o.z = hadd2(xr[u].z, hadd2(hadd2(v[u][0].z, v[u][1].z), hadd2(v[u][2].z, v[u][3].z)));
    o.w = hadd2(xr[u].w, hadd2(hadd2(v[u][0].w, v[u][1].w), hadd2(v[u][2].w, v[u][3].w)));
    stg128(out + cv_chan(0, lc + STEP * u) * LSEQ + HALF * 1024 + c * 8, o);
  }
}

__device__ __forceinline__ bool prep_valid(const uint4 (&st)[6], const uint4 (&xr)[4]) {
  const uint32_t n = __float_as_uint(8.f);
  return st[0].w == n && st[1].w == n && st[2].w == n && st[3].w == n && st[4].w == n && (st[5].w | st[5].y | st[5].z) == n &&
         xr[0].x != UNSET && xr[1].x != UNSET && xr[2].x != UNSET && xr[3].x != UNSET;
}
template <int HALF>
__device__ __forceinline__ void conv_prep(uint32_t sb, int layer, int cta, int i) {
  uint4 st[6], xr[4];
  const uint4* sp = (const uint4*)g_stats + (layer * 32 + HALF * 16 + (i >> 3)) * 48 + (i & 7);
  const uint4* xp = (const uint4*)g_xT + (2 * layer * DM + 2 * cta) * (LSEQ / 8) + HALF * 128 + i;
  if (!HALF) { pin(sp); pin(xp); }
  mbar_wait(sb + SM_BAR + 8 * (B_GB + HALF), layer);
  if (!HALF) TSW(13);
  auto fetch = [&]() {
#pragma unroll
    for (int k = 0; k < 6; k++) st[k] = ld_tagged(sp + 8 * k);
#pragma unroll
    for (int k = 0; k < 4; k++) xr[k] = ld_tagged(xp + cv_chan(0, k) * (LSEQ / 8));
  };
  if (HALF) {
#pragma unroll
    for (int k = 0; k < 6; k++) st[k] = lds128(sb + CV_ST + (i >> 3) * 768 + k * 128 + (i & 7) * 16);
#pragma unroll
    for (int k = 0; k < 4; k++) xr[k] = lds128(sb + cv_x(1, k) + i * 16);
  } else {
    fetch();
  }
  int it = 0;
  while (!__all_sync(~0u, prep_valid(st, xr)) && ++it < MAX_RETRY) { fetch(); RETRY(1); }
  if (!HALF || it) {
#pragma unroll
    for (int k = 0; k < 4; k++) sts128(sb + cv_x(HALF, k) + i * 16, xr[k]);
  }
  const uint32_t v[16] = {st[0].x, st[0].y, st[0].z, st[1].x, st[1].y, st[1].z, st[2].x, st[2].y, st[2].z, st[3].x, st[3].y, st[3].z, st[4].x, st[4].y, st[4].z, st[5].x};
  uint32_t rs[4], nm[4];
#pragma unroll
  for (int k = 0; k < 4; k++) {
    const float m0 = __uint_as_float(v[4 * k]) * (-1.f / DM), m1 = __uint_as_float(v[4 * k + 2]) * (-1.f / DM);
    const float r0 = rsqrt_approx(fmaxf(fmaf(__uint_as_float(v[4 * k + 1]), 1.f / DM, -m0 * m0), 0.f) + 1e-5f);
    const float r1 = rsqrt_approx(fmaxf(fmaf(__uint_as_float(v[4 * k + 3]), 1.f / DM, -m1 * m1), 0.f) + 1e-5f);
    rs[k] = packbf(r0, r1);
    nm[k] = packbf(m0 * bf_lo(rs[k]), m1 * bf_hi(rs[k]));
  }
  const uint32_t ud = sb + (i & 1) * CV_UH + (127 - 64 * HALF - (i >> 1)) * 16;
#pragma unroll
  for (int k = 0; k < 4; k++)
    sts128(ud + cv_u(k), make_uint4(hfma2(xr[k].x, rs[0], nm[0]), hfma2(xr[k].y, rs[1], nm[1]), hfma2(xr[k].z, rs[2], nm[2]), hfma2(xr[k].w, rs[3], nm[3])));
  fence_async_smem();
}

__device__ __forceinline__ void conv_phase(const Params& p, uint32_t sb, int layer, int cta, uint32_t* A0, uint32_t* A1) {
  const int tid = opaque_tid();
  const int wg = __shfl_sync(~0u, tid >> 7, 0), w = __shfl_sync(~0u, (tid >> 5) & 3, 0);
  const uint32_t bar = sb + SM_BAR;
  constexpr int CH2 = 4 * PG;
  bf16* xout = g_xT + ((2 * layer + 1) * DM + 2 * cta) * LSEQ;
  float acc[32];
  const uint32_t pe = sb + cv_pe(wg, 0) + 4 * (16 + 16 * w + ((tid & 31) >> 2) - 2 * (tid & 3));
  if (layer == 0) {
    mbar_wait(bar + 8 * (B_PDONE + 1), layer);
    mbar_wait(bar + 8 * B_PE, layer);
    conv_load(A0, pe);
    conv_load(A1, pe + CH2);
  }
  TSW(19);
  const uint64_t d0 = mkdesc(sb + cv_u(wg), CV_UH, 128, 0), d1 = d0 + (CH2 >> 4);
  mbar_wait(bar + 8 * B_U, layer);
  TSW(12);
  if (wg == 1) bar_sync(5, 256);
  conv_mma0(acc, A0, d0);
  if (wg == 0) bar_arrive(5, 256);
  mbar_wait(bar + 8 * (B_PDONE + 1), layer);
  {
    const int l = opaque_tid() & 31;
    if ((l & 15) < 2 * w) sts128(sb + cv_pb0(wg + 2 * (l >> 4), w) + (l & 15) * 16, make_uint4(0, 0, 0, 0));
  }
  wg_wait<0>();
  conv_store(acc, sb + cv_pb0(wg, w), sb + cv_pb1(wg, w), w);
  conv_mma0(acc, A1, d1);
  wg_wait<0>();
  conv_store(acc, sb + cv_pb0(2 + wg, w), sb + cv_pb1(2 + wg, w), w);
  TSW(13);
  bar_sync(2 + wg, 128);
  conv_epi<0, 2, 2>(sb, xout, wg, opaque_tid() & 127);
  TSW(14);
  mbar_arrive(bar + 8 * B_PUB);
  const uint64_t ds = mkdesc(sb + cv_se(wg), 8192, 1024, 1), df = mkdesc(sb + cv_fa(wg), 512, 128, 0);
  if (wg == 0) mbar_wait(bar + 8 * B_U1, layer);
  else bar_sync(6, 256);
  TSW(15);
  conv_mma1(acc, A0, d0, ds, df);
  if (wg == 0) bar_arrive(6, 256);
  wg_wait<0>();
  conv_store(acc, sb + cv_pb1(wg, w), sb + cv_dump(wg), w);
  TSW(16);
  bar_sync(2 + wg, 128);
  conv_epi<1, 1>(sb, xout, wg, opaque_tid() & 127);
  mbar_arrive(bar + 8 * (B_PUB + 1));
  conv_mma1(acc, A1, d1, ds + 512, df + (CH2 >> 4));
  wg_wait<0>();
  conv_store(acc, sb + cv_pb1(2 + wg, w), sb + cv_dump(2 + wg), w);
  TSW(17);
  bar_sync(2 + wg, 128);
  conv_epi<1, 1>(sb, xout, 2 + wg, opaque_tid() & 127);
  mbar_arrive(bar + 8 * (B_PUB + 2));
  TSW(18);
}

#define FDELAY 480
__device__ __forceinline__ void final_tile(const Params& p, uint32_t buf, int ch0, int pos0, int barid, uint32_t hint) {
  const uint32_t t0 = (uint32_t)clock();
  const int tid = opaque_tid() & 127, lane = tid & 31, w = tid >> 5;
  const uint4* src = (const uint4*)(g_xT + (3 * DM + ch0 + (tid >> 3)) * LSEQ + pos0) + (tid & 7);
  const int ch = tid >> 3, row = 4 * (ch & 6) + 2 * (ch >> 3) + (ch & 1);
  uint32_t dst0 = buf + row * 128 + (((tid ^ row) & 7) << 4), dst1 = (dst0 ^ 64) + 512;
  uint32_t ld0 = buf + lane * 128 + ((((2 * w) ^ lane) & 7) << 4), ld1 = ld0 ^ 16;
  bf16* out = p.out + (pos0 + 16 * w + (lane >> 2)) * DM + ch0 + 8 * (lane & 3);
  pin(src); pin(out); pin(dst0); pin(dst1); pin(ld0); pin(ld1);
  if (hint) mbar_wait(hint, 0);
  else while ((uint32_t)clock() - t0 < FDELAY);
  uint4 a, b;
  int it = 0;
  do {
    if (it) RETRY(2);
    a = ld_tagged(src); b = ld_tagged(src + 16 * LSEQ / 8);
  } while (!__all_sync(~0u, a.x != UNSET && b.x != UNSET) && ++it < (1 << 20));
  sts128(dst0, a);
  sts128(dst1, b);
  bar_sync(barid, 128);
#pragma unroll
  for (int h = 0; h < 2; h++) {
    uint32_t r[4];
    ldsm4t(r, h ? ld1 : ld0);
    *(uint4*)(out + 8 * h * DM) = make_uint4(r[0], r[1], r[2], r[3]);
  }
}

struct cplx { float r, i; };
__device__ __forceinline__ cplx cmul(cplx a, cplx b) { return {fmaf(a.r, b.r, -a.i * b.i), fmaf(a.r, b.i, a.i * b.r)}; }
__device__ __forceinline__ cplx csqr(cplx a) { return {fmaf(a.r, a.r, -a.i * a.i), (a.r + a.r) * a.i}; }
__device__ __forceinline__ cplx cexp_l(float ar2, float ai, float l) {
  const float m = ex2(ar2 * l);
  const float x = ai * l;
  return {m * __cosf(x), m * __sinf(x)};
}

__device__ __forceinline__ void colsum_cta(const Params& p, uint32_t sb, int j, int tid) {
  const uint32_t bar = sb + SM_BAR;
  auto ld = [&](int i) {
    mbar_expect(bar + 8 * i, 3 * PG);
    tma_ld3(sb + (i & 7) * 3 * PG, &p.mapW3, (2 * j + (i & 1)) * 64, (i >> 1) * 64, 0, bar + 8 * i);
  };
  const int warp = __shfl_sync(~0u, tid >> 5, 0);
  if (warp == 12 && elect_one()) {
#pragma unroll
    for (int i = 0; i < 8; i++) mbar_init(bar + 8 * i, 1);
    asm volatile("fence.mbarrier_init.release.cluster;" ::: "memory");
    fence_async_smem();
#pragma unroll
    for (int i = 0; i < 8; i++) ld(i);
  }
  if (warp == 13 && elect_one()) {
#pragma unroll
    for (int i = 8; i < 24; i++) mbar_init(bar + 8 * i, i < 16 ? 1 : 12);
    asm volatile("fence.mbarrier_init.release.cluster;" ::: "memory");
  }
  const unsigned ep = ld_relaxed(&g_cnt[C_CS * 32]);
  bar_sync(0, NTHREADS);
  if (warp == 12 && elect_one()) {
#pragma unroll 1
    for (int i = 8; i < 16; i++) { mbar_wait(bar + 8 * (8 + i), 0); fence_async_smem(); ld(i); }
  }
  if (tid < 384) {
    const int lane = tid & 31, cc = tid & 7, r0 = (tid >> 3) & 15, part = tid >> 7;
    const uint32_t id = ((lane >> 2) == 2 * (lane & 3) ? 0x3f80u : 0u) | ((lane >> 2) == 2 * (lane & 3) + 1 ? 0x3f800000u : 0u);
    const uint32_t src = sb + part * PG + r0 * 128 + ((cc ^ (r0 & 7)) << 4);
    float s[2][2][4];
#pragma unroll
    for (int i = 0; i < 16; i++) s[i >> 3][(i >> 2) & 1][i & 3] = 0.f;
#pragma unroll 1
    for (int i2 = 0; i2 < 16; i2 += 2) {
#pragma unroll
      for (int h = 0; h < 2; h++) {
        const int i = i2 + h;
        mbar_wait(bar + 8 * i, 0);
        uint4 v[4];
#pragma unroll
        for (int k = 0; k < 4; k++) v[k] = lds128(src + (i & 7) * 3 * PG + k * 2048);
#pragma unroll
        for (int k = 0; k < 4; k++) {
          const uint32_t a[4] = {v[k].x, v[k].y, v[k].z, v[k].w};
          mma_bf16(s[h][0], a, id, 0u);
          mma_bf16(s[h][1], a, 0u, id);
        }
        __syncwarp();
        if (i < 8 && lane == 0) mbar_arrive(bar + 8 * (16 + i));
      }
    }
    const uint32_t red = sb + 24 * PG;
#pragma unroll
    for (int h = 0; h < 2; h++)
#pragma unroll
      for (int k = 0; k < 2; k++) sts128f(red + (r0 * 384 + h * 192 + part * 64 + cc * 8 + k * 4) * 4, s[h][k][0], s[h][k][1], s[h][k][2], s[h][k][3]);
    bar_sync(1, 384);
    float tot = 0.f;
#pragma unroll
    for (int k = 0; k < 16; k++) tot += __uint_as_float(lds32(red + (k * 384 + tid) * 4));
    asm volatile("st.relaxed.gpu.global.v2.u32 [%0], {%1,%2};" ::"l"(&g_colsum[j * 384 + tid]), "r"(__float_as_uint(tot)), "r"(ep / NCTA + 1) : "memory");
    const uint4 u = make_uint4(UNSET, UNSET, UNSET, UNSET);
    if (tid < 256) {
#pragma unroll 1
      for (int s = 0; s < 4; s++) {
        const int n = (s == 1 || s == 2) ? 32 : 16;
        uint4* buf = s == 1 ? (uint4*)g_O + 131072 : (uint4*)g_xT + (s + !s) * 131072;
#pragma unroll 4
        for (int i = 0; i < n; i++) stg128(buf + (j * n + i) * 1024 + (tid >> 1) * 8 + (tid & 1), u);
        if (n == 16) {
#pragma unroll 4
          for (int i = 0; i < 8; i++) stg128(buf + (256 + j * 64 + i * 8 + (tid >> 5)) * 256 + (s ? 0 : 128) + ((tid & 31) >> 1) * 8 + (tid & 1), u);
        }
        if (s == 3) {
#pragma unroll 4
          for (int i = 0; i < 32; i++) stg128(buf + (256 + j * 64 + 2 * i + (tid >> 7)) * 256 + 128 + (tid & 127), u);
        }
        bar_sync(2, 256);
        if (tid == 32 * s) red_release(&g_cnt[(C_R + s) * 32]);
      }
    }
  }
}

constexpr int KB = 4, KW = 2;
struct ModeIn { uint32_t ar, ai, br, bi, cr, ci; bf16 logdt; };
__device__ __forceinline__ ModeIn load_modes(const Params& p, int d, int m) {
  const int i = d * 64 + m;
  return {((const uint32_t*)p.a_re)[i], ((const uint32_t*)p.a_im)[i], ((const uint32_t*)p.b_re)[i], ((const uint32_t*)p.b_im)[i],
          ((const uint32_t*)p.c_re)[i], ((const uint32_t*)p.c_im)[i], p.log_dt[d]};
}
__device__ __forceinline__ void kernel_gen(uint32_t sb, int cta, int ht, ModeIn in, const ModeIn& in1) {
  const uint32_t bst = sb + SM_KGB + ((ht & 63) >> 2) * 144 + (ht & 3) * 4 + (ht >> 6) * 16;
  const uint64_t db = mkdesc(sb + SM_KGB, 144, 2304, 0);
  const float e0 = (float)(8 * (((ht & 32) >> 1) + ((ht & 31) >> 2)));
  float T[20];
#pragma unroll
  for (int i = 0; i < 20; i++) T[i] = 0.f;
  float k0 = 0.f;
#pragma unroll 1
  for (int pass = 0; pass < 4; pass++) {
    {
      const int sh = (pass & 1) ? 0 : 16;
      auto val = [&](uint32_t v) { return __uint_as_float((v << sh) & 0xffff0000u); };
      const float dt = __bfloat162float(__float2bfloat16_rn(expf(__bfloat162float(in.logdt))));
      const float ar2 = dt * val(in.ar) * 1.4426950408889634f, ai = dt * val(in.ai);
      const cplx c = cmul({val(in.cr), -val(in.ci)}, {dt * val(in.br), -dt * val(in.bi)});
      k0 += c.r;
      const cplx z1 = cexp_l(ar2, -ai, 1.f), z256 = cexp_l(ar2, -ai, 256.f), z64 = cexp_l(ar2, ai, 64.f);
      const cplx z2 = csqr(z1), z512 = csqr(z256);
      auto put = [&](int j, cplx v) { sts32(bst + (j >> 2) * 2304 + (j & 3) * 32, packbf(v.r, v.i)); };
      sts128f(sb + SM_KGT + ht * 16, ar2, ai, z64.r, z64.i);
      const cplx c1 = cmul(c, z1), c2 = cmul(c, z2), c3 = cmul(c1, z2), c4 = cmul(c2, z2);
      const cplx c5 = cmul(c3, z2), c6 = cmul(c4, z2), c7 = cmul(c5, z2), c8 = cmul(c6, z2);
      put(0, c1); put(1, c2); put(2, c3); put(3, c4); put(4, c5); put(5, c6); put(6, c7); put(7, c8);
      const cplx c260 = cmul(c4, z256), c264 = cmul(c8, z256), c520 = cmul(c8, z512), c776 = cmul(c264, z512);
      put(8, cmul(c2, z256)); put(9, c260); put(10, cmul(c6, z256)); put(11, c264);
      put(12, cmul(c4, z512)); put(13, c520); put(14, cmul(c260, z512)); put(15, c776);
      const cplx c1032 = cmul(c520, z512), c1288 = cmul(c776, z512);
      put(16, c1032); put(17, c1288); put(18, cmul(c1032, z512)); put(19, cmul(c1288, z512));
    }
    fence_async_smem();
    bar_sync(4, 128);
    const uint32_t tb = sb + SM_KGT + (ht & 67) * 16;
    float2 nx[KB];
#pragma unroll
    for (int s = 0; s < KB; s++) nx[s] = lds64f(tb + s * 64);
#pragma unroll
    for (int q = 0; q < 16 / KB; q++) {
      uint32_t A[2 * KB];
      float2 cur[KB], z[KB];
#pragma unroll
      for (int s = 0; s < KB; s++) { cur[s] = nx[s]; z[s] = lds64f(tb + (KB * q + s) * 64 + 8); }
      if (q < 16 / KB - 1) {
#pragma unroll
        for (int s = 0; s < KB; s++) nx[s] = lds64f(tb + (KB * q + KB + s) * 64);
      }
      if (q >= KW) wg_wait<KW - 1>();
#pragma unroll
      for (int s = 0; s < KB; s++) {
        const cplx lo = cexp_l(cur[s].x, cur[s].y, e0), hi = cmul(lo, {z[s].x, z[s].y});
        A[2 * s] = packbf(lo.r, lo.i);
        A[2 * s + 1] = packbf(hi.r, hi.i);
      }
      wg_fence();
#pragma unroll
      for (int k = 0; k < KB / 2; k++) wgmma_rs<40, 0>(T, A + 4 * k, db + 9 * KB * q + 18 * k, (pass & 1) | q | k);
      wg_commit();
    }
    wg_wait<0>();
    acc_fence<20>(T);
    if (ht == 0) TS(4 + pass);
    if (pass & 1) {
      const int h2 = opaque_tid() - 256, w = h2 >> 5, lane = h2 & 31, t = lane & 3, chn = h2 >> 6, m = h2 & 63, i0 = 16 * (w & 1) + (lane >> 2);
      const int lc = (pass & 2) + chn;
      const uint32_t kc = sb + kc_off(lc);
      auto put = [&](int idx, float v) {
        sts16(kc + idx * 2, __bfloat16_as_ushort(__float2bfloat16_rn(v)));
      };
#pragma unroll
      for (int hi = 0; hi < 2; hi++) {
        const int i = i0 + 8 * hi;
        float v[5];
#pragma unroll
        for (int j = 0; j < 5; j++) v[j] = chn ? T[4 * j + 2 * hi + 1] : T[4 * j + 2 * hi];
        put(8 * i + 1 + t, v[0]);
        put(8 * i + 5 + t, v[1]);
        put(257 + 4 * i + t, v[2]);
        put(385 + 2 * i + (t & 1) + 64 * (t >> 1), v[3]);
        put(513 + i + 32 * t, v[4]);
      }
#pragma unroll
      for (int o = 16; o > 0; o >>= 1) k0 += __shfl_xor_sync(~0u, k0, o);
      if (lane == 0) sts32f(sb + SM_RED + 4 * w, k0);
      bar_sync(4, 128);
      if (m == 0) put(0, k0 + __uint_as_float(lds32(sb + SM_RED + 4 * w + 4)) + __uint_as_float(lds16(sb + SM_RED + 24 + 2 * lc) << 16));
      k0 = 0.f;
      in = in1;
    }
  }
}

__device__ __forceinline__ void expand_taps(uint32_t sb, int ht, int early) {
  const int ch = ht >> 5, lane = ht & 31;
  const uint32_t kc = sb + kc_off(ch);
  const uint32_t dst0 = sb + cv_pe(ch, early);
  auto put = [&](int G, uint32_t v0, uint32_t v1, uint32_t v2, uint32_t v3, uint32_t v4, uint32_t v5, uint32_t v6, uint32_t v7, uint32_t v8) {
    const uint32_t dst = dst0 + G * 32;
    sts128(dst, make_uint4(v1 | (v0 << 16), v2 | (v1 << 16), v3 | (v2 << 16), v4 | (v3 << 16)));
    sts128(dst + 16, make_uint4(v5 | (v4 << 16), v6 | (v5 << 16), v7 | (v6 << 16), v8 | (v7 << 16)));
  };
  {
    const uint4 q = lds128(kc + lane * 16);
    const uint32_t pv = lane ? lds16(kc + lane * 16 - 2) : 0u;
    const uint32_t dst = dst0 + (lane + 2) * 32;
    sts128(dst, make_uint4(__byte_perm(q.x, pv, 0x5410), __byte_perm(q.x, q.x, 0x1032), __byte_perm(q.y, q.x, 0x7610), __byte_perm(q.y, q.y, 0x1032)));
    sts128(dst + 16, make_uint4(__byte_perm(q.z, q.y, 0x7610), __byte_perm(q.z, q.z, 0x1032), __byte_perm(q.w, q.z, 0x7610), __byte_perm(q.w, q.w, 0x1032)));
    if (lane < 4) sts128(dst0 + lane * 16, make_uint4(0, 0, 0, 0));
  }
  uint32_t a[5], b[2][3];
  {
    const uint32_t s1 = kc + 2 * (256 + 4 * lane);
#pragma unroll
    for (int k = 0; k < 5; k++) a[k] = lds16(s1 + 2 * k);
#pragma unroll
    for (int u = 0; u < 2; u++) {
      const uint32_t s2 = kc + 2 * (384 + 2 * (lane + 32 * u));
#pragma unroll
      for (int k = 0; k < 3; k++) b[u][k] = lds16(s2 + 2 * k);
    }
  }
  const uint32_t k255 = lds16(kc + 2 * 255), k1024 = lds16(kc + 2 * 512);
  put(34 + lane, lane == 0 ? k255 : a[0], a[0], a[0], a[1], a[2], a[2], a[2], a[3], a[4]);
#pragma unroll
  for (int u = 0; u < 2; u++) put(66 + lane + 32 * u, b[u][0], b[u][0], b[u][0], b[u][0], b[u][1], b[u][1], b[u][1], b[u][2], b[u][2]);
  if (lane < 10) {
    const uint32_t v = lane == 0 ? k1024 : 0u;
    put(130 + lane, v, v, v, v, v, v, 0u, 0u, 0u);
  }
}
__device__ __forceinline__ void expand_far(uint32_t sb, int ht) {
  const int ch = ht >> 5, lane = ht & 31;
  const uint32_t kc = sb + kc_off(ch) + 2 * (513 + 2 * (63 - lane)), dst = sb + cv_fa(ch) + lane * 16;
#pragma unroll
  for (int ty = 0; ty < 2; ty++) {
    uint32_t v[16];
#pragma unroll
    for (int k = 0; k < 16; k++) v[k] = (k < 8 || 63 - lane - 4 * k >= 0) ? lds16(kc + 2 * (1 - ty) - 16 * k) : 0u;
#pragma unroll
    for (int u = 0; u < 2; u++)
      sts128(dst + ty * 2048 + u * 512, make_uint4(v[8 * u] | (v[8 * u + 1] << 16), v[8 * u + 2] | (v[8 * u + 3] << 16), v[8 * u + 4] | (v[8 * u + 5] << 16), v[8 * u + 6] | (v[8 * u + 7] << 16)));
    sts128(dst + ty * 2048 + 1024, make_uint4(0, 0, 0, 0));
  }
}

__host__ __device__ constexpr int bar_count(int i) {
  return i == B_LN ? 2 : i == B_AL ? 8 : i < B_STG ? 1 : i < B_PE ? 4 : i >= B_PUB ? 256 : 128;
}
__host__ __device__ constexpr bool bar_first(int i) { return i < B_WF + 2 && (i & 7) < 2; }

__global__ void __launch_bounds__(NTHREADS, 1) fused_kernel(const __grid_constant__ Params p) {
  extern __shared__ __align__(1024) uint8_t smem[];
  constexpr uint32_t sb = 1024;
  if (s32(smem) != sb) return;
  const int tid = threadIdx.x, lane = tid & 31;
  const int warp = __shfl_sync(~0u, tid >> 5, 0);
  if (tid == 32) {
    asm volatile("prefetch.tensormap [%0];" ::"l"(&p.mapX) : "memory");
    asm volatile("prefetch.tensormap [%0];" ::"l"(&p.mapW3) : "memory");
  }
  const int cta = blockIdx.x - (gridDim.x == NCTA + 4 ? 0 : 4);
  if ((unsigned)cta >= NCTA) {
    if (blockIdx.x < NCTA + 4) colsum_cta(p, sb, blockIdx.x & 3, tid);
    return;
  }
  const int rb = ((cta >> 4) & 3) * 4 + ((cta >> 2) & 3), hg = (cta >> 6) * 4 + (cta & 3);
  const uint32_t bar = sb + SM_BAR;
  auto ld_x0 = [&](int half, int c) {
    const uint32_t b = bar + 8 * (B_XF + 8 * half + c);
    mbar_expect(b, PG);
    tma_ld(sb + x_page(half, c) * PG, &p.mapX, c * 64, (16 * half + rb) * 64, b);
  };
  auto ld_x1 = [&](int half, int c, int b0) {
    const uint32_t b = bar + 8 * b0;
    mbar_expect(b, PG);
    tma_ld(sb + (8 * half + c) * PG, &p.mapXT, (16 * half + rb) * 64, DM + c * 64, b);
  };
  auto ld_w = [&](int c) {
    const uint32_t b = bar + 8 * (B_WF + c);
    mbar_expect(b, 3 * PG);
    tma_ld3(sb + w_page(c) * PG, &p.mapW3, hg * 64, c * 64, 0, b);
  };

  if (tid == 0) TS(0);
  if (tid == 480) LTS(0);
  if (warp == 0 && elect_one()) {
#pragma unroll
    for (int i = 0; i < B_WF + 2; i++)
      if (bar_first(i)) mbar_init(bar + 8 * i, 1);
    asm volatile("fence.mbarrier_init.release.cluster;" ::: "memory");
    fence_async_smem();
    ld_x0(0, 0);
    ld_w(0); ld_x0(1, 0);
    ld_x0(0, 1); ld_w(1); ld_x0(1, 1);
    TS(1);
  }
  __syncwarp();
  if (warp >= 1 && warp < 8 && elect_one()) {
    if (warp < 4) {
#pragma unroll
      for (int i = 2; i < 8; i++) mbar_init(bar + 8 * (8 * warp - 8 + i), 1);
    } else {
#pragma unroll
      for (int i = 0; i < 12; i++) mbar_init(bar + 8 * (12 * warp - 24 + i), 1);
    }
    asm volatile("fence.mbarrier_init.release.cluster;" ::: "memory");
  }
  if (warp == 15 && elect_one()) {
#pragma unroll
    for (int i = 72; i < B_COUNT; i++) mbar_init(bar + 8 * i, bar_count(i));
    asm volatile("fence.mbarrier_init.release.cluster;" ::: "memory");
  }

  if (warp < 8) {
    bar_sync(0, NTHREADS);
    asm volatile("setmaxnreg.inc.sync.aligned.u32 %0;" ::"n"(R_CONS));
    const int cw = __shfl_sync(~0u, opaque_tid() >> 5, 0);
    const int wg = cw >> 2, w = cw & 3;
    if (tid == 0) TS(2);
#pragma unroll 1
    for (int layer = 0; layer < 2; layer++) {
      attn_phase(p, sb, layer, rb, hg, wg, w);
      uint32_t A0[68], A1[68];
      proj_phase(p, sb, layer, rb, hg, A0, A1);
      conv_phase(p, sb, layer, cta, A0, A1);
    }
    if (tid == 128) TS(8);
    final_tile(p, sb + (16 + wg) * PG, 256 * wg + 32 * (cta >> 4), 1024 + 64 * (cta & 15), 2 + wg, wg ? 0 : bar + 8 * (B_TF + 1));
    if (tid == 128) TS(9);
    if (tid == 128) LTS(1);
    if (tid == 0) LTE();
  } else if (warp < 12) {
    asm volatile("setmaxnreg.dec.sync.aligned.u32 %0;" ::"n"(R_HELP));
    const int ht = tid - 256;
    {
      unsigned ep0 = 0;
      if (ht == 0) ep0 = ld_relaxed(&g_cnt[C_CS * 32]);
      const bf16 dsk = p.dskip[cv_chan(cta, ht & 3)];
      const ModeIn in0 = load_modes(p, cv_chan(cta, ht >> 6), ht & 63), in1 = load_modes(p, cv_chan(cta, 2 + (ht >> 6)), ht & 63);
      if (ht < 48) sts128f(sb + SM_STG + ht * 16, 0.f, 0.f, 0.f, 1.f);
      bar_sync(0, NTHREADS);
      if (ht == 0) {
        sts32(sb + SM_EP, ep0);
        mbar_arrive(bar + 8 * B_EP);
      }
      if (ht >= 124) sts16(sb + SM_RED + 24 + 2 * (ht & 3), __bfloat16_as_ushort(dsk));
      kernel_gen(sb, cta, ht, in0, in1);
      if (ht < 48) sts128f(sb + SM_KGT + ht * 16, 0.f, 0.f, 0.f, 1.f);
      fence_async_smem();
      bar_sync(4, 128);
      if (ht == 0) mbar_arrive(bar + 8 * B_KG);
    }
#pragma unroll 1
    for (int layer = 0; layer < 2; layer++) {
      const int early = layer;
      if (early) mbar_wait(bar + 8 * (B_DN + 13), 1);
      mbar_wait(bar + 8 * (early ? B_OST : B_PDONE), layer);
      expand_taps(sb, opaque_tid() - 256, early);
      mbar_arrive(bar + 8 * B_PE);
      TSW(0);
      mbar_wait(bar + 8 * B_PDONE, layer);
      expand_far(sb, opaque_tid() - 256);
      {
        const int i = opaque_tid() - 256;
        if (i < 32) sts128(sb + cv_u(i >> 3) + ((i >> 2) & 1) * CV_UH + (128 + (i & 3)) * 16, make_uint4(0, 0, 0, 0));
        mbar_wait(bar + 8 * B_RC, layer);
        conv_prep<0>(sb, layer, cta, i);
        mbar_arrive(bar + 8 * B_U);
      }
      mbar_wait(bar + 8 * (B_PDONE + 1), layer);
      bar_sync(4, 128);
#pragma unroll 1
      for (int lc = 0; lc < 4; lc += 2) {
        conv_sums(sb, lc, opaque_tid() - 256);
        TSW(1 + lc);
      }
      conv_prep<1>(sb, layer, cta, opaque_tid() - 256);
      mbar_arrive(bar + 8 * B_U1);
      TSW(4);
      if (layer == 0) {
        const int c = __shfl_sync(~0u, (opaque_tid() >> 5) & 3, 0);
        int phase = 0;
#pragma unroll 1
        for (int k = 0; k < 3; k++) {
          const int page = (k ? 4 + 4 * k : 0) + c, b = B_XR + 4 * (k & 1) + c;
          const uint32_t a = sb + page * PG + lane * 128 + (lane & 7) * 16 + (lane >> 3) * 4;
          int it = k == 2 ? phase : 0;
#pragma unroll 1
          for (; it < MAX_RETRY; it++) {
            mbar_wait(bar + 8 * b, it & 1);
            const uint32_t v0 = lds32(a), v1 = lds32(a + 4096);
            if (__all_sync(~0u, v0 != UNSET && v1 != UNSET)) break;
            if (elect_one()) { fence_async_smem(); ld_x1(page >> 3, page & 7, b); }
            __syncwarp();
            RETRY(3);
          }
          if (k == 0) phase = it + 1;
          if (lane == 0) mbar_arrive(bar + 8 * (B_XF + page));
        }
      }
    }
#pragma unroll 1
    for (int k = 0; k < 2; k++) final_tile(p, sb + 18 * PG + k * 4096, 256 * k + 32 * (cta >> 4), 64 * (cta & 15), 4, bar + 8 * B_TF);
    if (ht == 0) LTE();
  } else {
    asm volatile("setmaxnreg.dec.sync.aligned.u32 %0;" ::"n"(R_AGENT));
    bar_sync(0, NTHREADS);
    auto done = [&](int half, int c, int layer) { mbar_wait(bar + 8 * (B_DN + 8 * half + c), layer); };
    auto publish = [&](int layer, int k) {
      unsigned* cnt = &g_cnt[(layer ? C_F + 8 * k + (cta >> 4) : C_C + k) * 32];
      pin(cnt);
      mbar_wait(bar + 8 * (B_PUB + k), layer);
      red_relaxed(cnt);
      if (!layer && k == 0) red_release(&g_cnt[(C_C + 3) * 32]);
      TS(16 + layer * 56 + 40 + 7 + k);
    };
    if (warp == 12) {
      if (elect_one()) {
#pragma unroll 1
        for (int layer = 0; layer < 2; layer++) {
          auto ld_xe = [&](int c) {
            const uint32_t b = bar + 8 * (B_XF + c);
            mbar_expect(b, PG);
            if (layer == 0) tma_ld(sb + x_page(0, c) * PG, &p.mapX, c * 64, rb * 64, b);
            else tma_ld(sb + x_page(0, c) * PG, &p.mapXT, rb * 64, DM + c * 64, b);
          };
          if (layer == 0) {
            ld_x0(0, 2); ld_w(2); ld_x0(1, 2);
            if (hg >= 3) {
              mbar_expect(bar + 8 * B_SC, PG);
              tma_ld(sb + P_R * PG, &p.mapX, hg * 64, rb * 64, bar + 8 * B_SC);
            }
            if (rb < 4) tma_prefetch3(&p.mapW3, hg * 64, (4 + rb) * 64, 0);
            ld_x0(0, 3); ld_w(3); ld_x0(1, 3); ld_x0(0, 4); ld_x0(1, 4);
            done(0, 0, 0); done(1, 0, 0);
            ld_w(4);
            ld_x0(1, 5); ld_x0(1, 6); ld_x0(1, 7);
            done(0, 1, 0); done(1, 1, 0);
            ld_w(5);
            if (rb < 8) tma_prefetch5(&p.mapWo, hg * 64, rb * 2);
            done(0, 2, 0);
            fence_async_smem();
            ld_xe(5); ld_xe(6); ld_xe(7);
          } else {
            mbar_wait(bar + 8 * B_PDONE, 0);
            mbar_wait(bar + 8 * (B_PDONE + 1), 0);
            mbar_wait(bar + 8 * B_U, 0);
            ld_w(0); ld_w(1);
            mbar_wait(bar + 8 * B_U1, 0);
            fence_async_smem();
            ld_w(2);
            mbar_wait(bar + 8 * (B_PUB + 2), 0);
            fence_async_smem();
            ld_w(3);
            spin_until(&g_cnt[(C_C + 3) * 32], ((lds32(sb + SM_EP) / NCTA) + 1) * NCTA);
            fence_async_global();
            if (hg >= 3) {
              mbar_expect(bar + 8 * B_SC, PG);
              tma_ld(sb + P_R * PG, &p.mapXT, rb * 64, DM + hg * 64, bar + 8 * B_SC);
            }
            ld_xe(4);
            done(0, 2, 1);
            fence_async_smem();
            ld_xe(5); ld_xe(6); ld_xe(7);
            done(1, 0, 1);
            ld_w(4);
            done(1, 1, 1);
            ld_w(5);
          }
          done(1, 2, layer);
          fence_async_smem();
          ld_w(6); ld_w(7);
          auto ld_res = [&](int half) {
            const uint32_t b = bar + 8 * (B_RF + half);
            mbar_expect(b, PG);
            if (layer == 0) tma_ld(sb + (half ? 2 : P_R) * PG, &p.mapX, hg * 64, (16 * half + rb) * 64, b);
            else tma_ld(sb + (half ? 2 : P_R) * PG, &p.mapXT, (16 * half + rb) * 64, DM + hg * 64, b);
          };
          done(0, 4, layer); done(1, 3, layer);
          fence_async_smem();
          mbar_expect(bar + 8 * B_WOF, 8 * PG);
#pragma unroll 1
          for (int c = 0; c < 8; c++) {
            if (c == 5) { ld_res(0); done(1, 4, layer); }
            tma_ld5(sb + wo_page(c) * PG, &p.mapWo, hg * 64, c * 2, bar + 8 * B_WOF);
          }
          done(0, 7, layer);
          fence_async_global();
          ld_res(1);
          if (layer) mbar_wait(bar + 8 * B_RS, 0);
          fence_async_global();
#pragma unroll
          for (int half = 0; half < 2; half++) {
            float* stats = g_stats + (layer * 32 + 16 * half + rb) * 192;
            unsigned* cnt = &g_cnt[(C_G + 2 * layer + half) * 32];
            mbar_wait(bar + 8 * (B_STG + half), layer);
            tma_st(&p.mapXT, (16 * half + rb) * 64, 2 * layer * DM + hg * 64, sb + (P_R + half) * PG);
            bulk_red_add_f32(stats, sb + (half ? SM_KGT : SM_STG), 768);
            bulk_commit();
            red_relaxed(cnt);
            if (half == 0) mbar_arrive(bar + 8 * B_PG);
            bulk_wait_read();
            mbar_arrive(bar + 8 * (B_PST + half));
          }
        }
      }
    } else if (warp == 13) {
      mbar_wait(bar + 8 * B_EP, 0);
      const unsigned e1 = (lds32(sb + SM_EP) / NCTA) + 1;
      auto ld_o = [&](int layer) {
#pragma unroll 1
        for (int half = 0; half < 2; half++) {
          done(1, 7, layer);
          mbar_wait(bar + 8 * B_OST, layer);
          if (half) mbar_wait(bar + 8 * (B_OST + 1), layer);
          fence_async_smem();
#pragma unroll
          for (int c = 0; c < 4; c++) mbar_expect(bar + 8 * (B_OF + 4 * half + c), 2 * PG);
          const bf16* src = g_O + (layer * 32 + 16 * half + rb) * 4 * PG;
          uint32_t dst0 = sb + o_page(half, 0) * PG;
          pin(src); pin(dst0);
          spin_hint(&g_cnt[(C_O + layer * 32 + 16 * half + rb) * 32], e1 * 32);
#pragma unroll
          for (int c = 0; c < 4; c++) {
            if (c == 2 && half && layer) { mbar_wait(bar + 8 * B_AL, 0); fence_async_smem(); }
            bulk_ld(c ? sb + o_page(half, c) * PG : dst0, src + c * PG, 2 * PG, bar + 8 * (B_OF + 4 * half + c));
          }
        }
      };
      if (elect_one()) {
        mbar_wait(bar + 8 * (B_WF + 2), 0);
        asm volatile("prefetch.tensormap [%0];" ::"l"(&p.mapXT) : "memory");
        asm volatile("prefetch.tensormap [%0];" ::"l"(&p.mapWo) : "memory");
        spin_until(&g_cnt[C_Z * 32], e1 * NCTA);
        mbar_arrive(bar + 8 * B_ZF);
        TS(3);
        ld_o(0);
#pragma unroll 1
        for (int k = 0; k < 3; k++) {
          mbar_wait(bar + 8 * (B_PUB + k), 0);
          if (k == 2) {
#pragma unroll 1
            for (int c = 0; c < 4; c++) mbar_wait(bar + 8 * (B_XF + c), 1);
          }
          fence_async_smem();
          uint32_t b = bar + 8 * (B_XR + 4 * (k & 1)), dst = sb + (k ? 4 + 4 * k : 0) * PG, c0 = ((k ? 16 : 0) + rb) * 64, c1 = DM + (k & 2) * 128;
#pragma unroll
          for (int c = 0; c < 4; c++) mbar_expect(b + 8 * c, PG);
          pin(b); pin(dst); pin(c0); pin(c1);
          spin_hint(&g_cnt[(C_C + k) * 32], e1 * NCTA);
          TS(10 + k);
#pragma unroll
          for (int c = 0; c < 4; c++) tma_ld(dst + c * PG, &p.mapXT, c0, c1 + c * 64, b + 8 * c);
        }
        ld_o(1);
#pragma unroll 1
        for (int k = 0; k < 2; k++) {
          mbar_wait(bar + 8 * (B_PUB + k), 1);
          spin_hint(&g_cnt[(C_F + 8 * k + (cta >> 4)) * 32], e1 * 16);
          mbar_arrive(bar + 8 * (B_TF + k));
        }
      }
    } else if (warp == 14) {
      mbar_wait(bar + 8 * B_EP, 0);
      const unsigned e1 = (lds32(sb + SM_EP) / NCTA) + 1;
      done(0, 1, 0);
      {
        const uint2* cp = g_colsum + (hg * 192 + lane);
        uint2 v[6];
        bool ok;
        int it = 0;
        do {
          ok = true;
#pragma unroll
          for (int i = 0; i < 6; i++) {
            asm volatile("ld.relaxed.gpu.global.v2.u32 {%0,%1}, [%2];" : "=r"(v[i].x), "=r"(v[i].y) : "l"(cp + 32 * i) : "memory");
            ok = ok && v[i].y == e1;
          }
          if (++it > (1 << 22)) __trap();
        } while (!__all_sync(~0u, ok));
#pragma unroll
        for (int i = 0; i < 6; i++) sts32f(sb + SM_CS + 4 * (lane + 32 * i), __uint_as_float(v[i].x));
      }
      __syncwarp();
      if (elect_one()) {
        mbar_wait(bar + 8 * B_ZF, 0);
        mbar_arrive(bar + 8 * B_LN);
        red_relaxed(&g_cnt[C_CS * 32]);
        TS(13);
#pragma unroll 1
        for (int layer = 0; layer < 2; layer++) {
          const uint32_t b = bar + 8 * (B_GB + 1);
          const bf16* xin = g_xT + ((size_t)2 * layer * DM + 2 * cta) * LSEQ + 1024;
          const float* stats = g_stats + (layer * 32 + 16) * 192;
          mbar_wait(bar + 8 * B_PST, layer);
          spin_hint(&g_cnt[(C_G + 2 * layer) * 32], e1 * NCTA);
          mbar_arrive(bar + 8 * B_GB);
          mbar_wait(bar + 8 * (B_PST + 1), layer);
          fence_async_smem();
          mbar_expect(b, 12288 + PG);
          pin(stats); pin(xin);
          spin_hint(&g_cnt[(C_G + 2 * layer + 1) * 32], e1 * NCTA);
          bulk_ld(sb + CV_ST, stats, 12288, b);
#pragma unroll
          for (int lc = 0; lc < 4; lc++) bulk_ld(sb + cv_x(1, lc), xin + cv_chan(0, lc) * LSEQ, 2048, b);
          TS(14 + layer);
          publish(layer, 1);
        }
      }
    } else {
      const uint4 u = make_uint4(UNSET, UNSET, UNSET, UNSET);
      if (lane < 24) stg128((uint4*)g_stats + cta * 24 + lane, make_uint4(0, 0, 0, 0));
      if (lane < 16) stg128(g_rows + LSEQ + cta * 16 + lane, make_uint4(0, 0, 0, 0));
#pragma unroll 4
      for (int i = 0; i < 16; i++) stg128(g_halo + cta * 512 + 32 * i + lane, u);
#pragma unroll 4
      for (int i = 0; i < 16; i++) stg128(((i & 8) ? (uint4*)g_xT : (uint4*)g_O) + cta * 1024 + (i & 7) * 128 + (lane >> 1) * 8 + (lane & 1), u);
      __syncwarp();
      if (elect_one()) red_release(&g_cnt[C_Z * 32]);
      __syncwarp();
#pragma unroll 1
      for (int layer = 0; layer < 2; layer++) {
        auto reset_done = [&](int s) {
          spin_until(&g_cnt[(C_R + s) * 32], (lds32(sb + SM_EP) / NCTA) * 4 + 4);
          mbar_arrive(bar + 8 * (s == 1 ? B_LN : s == 2 ? B_RS : B_RC));
          if (s) TS(16 + 40 + 9 + s);
        };
        if (layer && elect_one()) reset_done(1);
        __syncwarp();
#pragma unroll 1
        for (int half = 0; half < 2; half++) {
          done(half, 2, layer);
          const uint4* src = g_rows + (layer * LSEQ + (16 * half + rb) * 64 + (opaque_tid() & 31));
          uint4 a, b;
          int it = 0;
          do {
            a = ld_tagged(src); b = ld_tagged(src + 32);
          } while (!__all_sync(~0u, (a.z | a.w) == __float_as_uint(8.f) && (b.z | b.w) == __float_as_uint(8.f)) && ++it < (1 << 20));
          float m0 = __uint_as_float(a.x) * (1.f / DM), m1 = __uint_as_float(b.x) * (1.f / DM);
          float r0 = rsqrt_approx(fmaxf(__uint_as_float(a.y) * (1.f / DM) - m0 * m0, 0.f) + 1e-5f);
          float r1 = rsqrt_approx(fmaxf(__uint_as_float(b.y) * (1.f / DM) - m1 * m1, 0.f) + 1e-5f);
          if (half) done(0, 7, layer);
          const uint32_t dst = sb + ln_off(half) + ((lane >> 4) * 8 + (lane & 7)) * 16 + (lane & 8);
          asm volatile("st.shared.v2.f32 [%0], {%1,%2};" ::"r"(dst), "f"(m0), "f"(r0) : "memory");
          asm volatile("st.shared.v2.f32 [%0], {%1,%2};" ::"r"(dst + 256), "f"(m1), "f"(r1) : "memory");
          __syncwarp();
          if (elect_one()) { mbar_arrive(bar + 8 * (B_LN + half)); TS(16 + layer * 56 + 40 + 14 + half); }
        }
        if (layer && lane < 16) stg128(g_rows + cta * 16 + (opaque_tid() & 31), make_uint4(0, 0, 0, 0));
        if (elect_one()) {
          if (layer) reset_done(2);
          reset_done(3 * layer);
          publish(layer, 0);
          if (!layer) publish(layer, 2);
        }
        __syncwarp();
      }
    }
  }
}

typedef CUresult (*EncodeFn)(CUtensorMap*, CUtensorMapDataType, cuuint32_t, void*, const cuuint64_t*, const cuuint64_t*,
                             const cuuint32_t*, const cuuint32_t*, CUtensorMapInterleave, CUtensorMapSwizzle,
                             CUtensorMapL2promotion, CUtensorMapFloatOOBfill);

static void make_map(EncodeFn enc, CUtensorMap* m, void* ptr, uint64_t cols, uint64_t rows, uint32_t box_rows) {
  cuuint64_t dims[2] = {cols, rows};
  cuuint64_t strides[1] = {cols * 2};
  cuuint32_t box[2] = {64, box_rows};
  cuuint32_t es[2] = {1, 1};
  enc(m, CU_TENSOR_MAP_DATA_TYPE_BFLOAT16, 2, ptr, dims, strides, box, es, CU_TENSOR_MAP_INTERLEAVE_NONE,
      CU_TENSOR_MAP_SWIZZLE_128B, CU_TENSOR_MAP_L2_PROMOTION_L2_128B, CU_TENSOR_MAP_FLOAT_OOB_FILL_NONE);
}
static void make_map3(EncodeFn enc, CUtensorMap* m, void* ptr, uint64_t d0, uint64_t cols, uint64_t rows, uint64_t blk_stride,
                      uint64_t nblocks, uint32_t nblk) {
  cuuint64_t dims[3] = {d0, rows, nblocks};
  cuuint64_t strides[2] = {cols * 2, blk_stride * 2};
  cuuint32_t box[3] = {64, 64, nblk};
  cuuint32_t es[3] = {1, 1, 1};
  enc(m, CU_TENSOR_MAP_DATA_TYPE_BFLOAT16, 3, ptr, dims, strides, box, es, CU_TENSOR_MAP_INTERLEAVE_NONE,
      CU_TENSOR_MAP_SWIZZLE_128B, CU_TENSOR_MAP_L2_PROMOTION_L2_128B, CU_TENSOR_MAP_FLOAT_OOB_FILL_NONE);
}

extern "C" void kernel_launch(void* const* d_in, const int* in_sizes, int n_in, void* d_out, int out_size) {
  static Params prm;
  static void* cached[13] = {nullptr};
  static bool attr_done = false;
  static int grid = NCTA + 4;
  bool same = attr_done && cached[12] == d_out;
  for (int i = 0; i < 12 && same; i++) same = cached[i] == d_in[i];
  if (!same) {
    void* fn = nullptr;
    cudaDriverEntryPointQueryResult qr;
    cudaGetDriverEntryPoint("cuTensorMapEncodeTiled", &fn, cudaEnableDefault, &qr);
    EncodeFn enc = (EncodeFn)fn;
    void* pXT;
    cudaGetSymbolAddress(&pXT, g_xT);
    make_map(enc, &prm.mapX, d_in[0], DM, LSEQ, 64);
    make_map(enc, &prm.mapXT, pXT, LSEQ, 4 * DM, 64);
    {
      cuuint64_t dims[5] = {DM, 2, 4, 4, 16};
      cuuint64_t strides[4] = {DM * 2, 8 * DM * 2, 2 * DM * 2, 32 * DM * 2};
      cuuint32_t box[5] = {64, 2, 4, 4, 2};
      cuuint32_t es[5] = {1, 1, 1, 1, 1};
      enc(&prm.mapWo, CU_TENSOR_MAP_DATA_TYPE_BFLOAT16, 5, d_in[2], dims, strides, box, es, CU_TENSOR_MAP_INTERLEAVE_NONE,
          CU_TENSOR_MAP_SWIZZLE_128B, CU_TENSOR_MAP_L2_PROMOTION_L2_128B, CU_TENSOR_MAP_FLOAT_OOB_FILL_NONE);
    }
    make_map3(enc, &prm.mapW3, d_in[1], DM, 3 * DM, DM, DM, 3, 3);
    prm.out = (bf16*)d_out;
    prm.a_re = (const bf16*)d_in[4]; prm.a_im = (const bf16*)d_in[5];
    prm.b_re = (const bf16*)d_in[6]; prm.b_im = (const bf16*)d_in[7];
    prm.c_re = (const bf16*)d_in[8]; prm.c_im = (const bf16*)d_in[9];
    prm.log_dt = (const bf16*)d_in[10]; prm.dskip = (const bf16*)d_in[11];
    int dev = 0, sms = 0;
    cudaGetDevice(&dev);
    cudaDeviceGetAttribute(&sms, cudaDevAttrMultiProcessorCount, dev);
    grid = sms >= NCTA + 4 ? NCTA + 4 : NCTA + 5;
    cudaFuncSetAttribute(fused_kernel, cudaFuncAttributeMaxDynamicSharedMemorySize, SM_TOTAL);
    for (int i = 0; i < 12; i++) cached[i] = d_in[i];
    cached[12] = d_out;
    attr_done = true;
  }
  fused_kernel<<<grid, NTHREADS, SM_TOTAL>>>(prm);
}
```

```cpp
#include <cuda_runtime.h>
#include <cuda_bf16.h>
#include <cuda.h>
#include <stdint.h>

typedef __nv_bfloat16 bf16;

constexpr int LSEQ = 2048;
constexpr int DM = 512;
constexpr int NCTA = 128;
constexpr int NTHREADS = 512;
#define R_CONS 200
#define R_HELP 88
#define R_AGENT 24
#define TURN0 4
#define TURN1 4

constexpr int PG = 8192;
constexpr int P_R = 25;
__host__ __device__ constexpr int x_page(int half, int c) { return half ? 8 + c : c < 5 ? c : c - 5; }
__host__ __device__ constexpr int w_page(int c) { return (c & 3) < 3 ? 16 + 3 * (c & 3) : c < 4 ? 5 : 8; }
__host__ __device__ constexpr int wo_page(int c) { return c < 5 ? 3 + c : 11 + c; }
__host__ __device__ constexpr int o_page(int half, int pair) { return half ? (pair ? 25 - 2 * pair : 0) : 8 + 2 * pair; }
constexpr int SM_KGB = (P_R + 1) * PG;
constexpr int SM_KC = 27 * PG;
constexpr int KC_STRIDE = 648;
__host__ __device__ constexpr int kc_off(int lc) { return SM_KC + (lc & 1) * 2 * KC_STRIDE + (lc < 2 ? 3328 : 0); }
constexpr int SM_KGT = SM_KC + 3328 + 2592;
constexpr int SM_CS = SM_KGT + 2048;
constexpr int SM_RED = SM_CS + 768;
constexpr int SM_EP = SM_RED + 16;
constexpr int SM_STG = SM_RED + 32;
constexpr int SM_LN = SM_STG + 768;
__host__ __device__ constexpr int ln_off(int half) { return half ? PG + 4096 : SM_LN; }
constexpr int SM_BAR = SM_LN + 512;
constexpr int SM_TS = SM_BAR + 704;
constexpr int SM_TOTAL = SM_TS + 512;
static_assert(SM_TOTAL <= 232448 && SM_STG % 16 == 0 && SM_KGT % 16 == 0, "shared memory");

constexpr int CV_UH = 140 * 16;
__host__ __device__ constexpr int cv_u(int lc) { return (8 + 2 * lc) * PG; }
__host__ __device__ constexpr int cv_pe(int lc, int early) { return early ? 19 * PG + lc * 4480 : cv_u(lc) + 4480; }
__host__ __device__ constexpr int cv_pb1(int lc, int w) { return w ? cv_u(lc) + 8960 + (w - 1) * 2048 : 7 * PG + lc * 2048; }
__host__ __device__ constexpr int cv_fa(int lc) { return cv_pb1(lc, 1) + 128; }
__host__ __device__ constexpr int cv_dump(int lc) { return cv_u(lc) + 16256; }
__host__ __device__ constexpr int cv_pb0(int lc, int w) { return lc * PG + w * 2048; }
__host__ __device__ constexpr int cv_se(int lc) { return 5 * PG + lc * 4096; }
__host__ __device__ constexpr int cv_so(int lc) { return cv_se(lc) + 2048; }
__host__ __device__ constexpr int cv_x(int half, int lc) { return (P_R + half) * PG + lc * 2048; }
constexpr int CV_ST = 22 * PG;
__host__ __device__ constexpr int cv_chan(int cta, int lc) { return 2 * cta + (lc & 1) + 256 * (lc >> 1); }

enum {
  B_XF = 0,
  B_WF = 16,
  B_OF = 24,
  B_DN = 32,
  B_PG = 46,
  B_XR = 48,
  B_RF = 56,
  B_PST = 58,
  B_GB = 60,
  B_TF = 62,
  B_RT = 64,
  B_RS = 66,
  B_RC = 67,
  B_WOF = 68,
  B_ZF = 69,
  B_EP = 70,
  B_KG = 71,
  B_SC = 37,
  B_LN = 72,
  B_END = 38,
  B_STG = 74,
  B_OST = 76,
  B_PDONE = 78,
  B_PE = 80,
  B_U = 81,
  B_U1 = 82,
  B_PUB = 83,
  B_AL = 86,
  B_COUNT = 87
};

enum {
  C_CS = 0,
  C_G = 1,
  C_C = 5,
  C_O = 21,
  C_Z = 85,
  C_R = 86,
  C_F = 90,
  C_COUNT = 106
};

__device__ unsigned g_cnt[C_COUNT * 32];
__device__ __align__(1024) bf16 g_O[2 * LSEQ * DM];
__device__ __align__(1024) bf16 g_xT[4 * DM * LSEQ];
__device__ __align__(1024) float g_stats[2 * 32 * 192];
__device__ __align__(1024) uint2 g_colsum[3 * DM];
__device__ __align__(1024) uint4 g_halo[32 * 8 * 256];
__device__ __align__(1024) uint4 g_rows[2 * LSEQ];
#define TS(i) do { } while (0)
#define TSW(k) do { if ((threadIdx.x & 127) == 0) TS(16 + layer * 56 + (threadIdx.x >> 7) * 20 + (k)); } while (0)
#define TSG(k) do { } while (0)

#define RETRY(i) do { } while (0)
#define LTS(i) do { } while (0)
#define LTE() do { } while (0)

struct Params {
  CUtensorMap mapX, mapW3, mapXT, mapWo;
  bf16* out;
  const bf16 *a_re, *a_im, *b_re, *b_im, *c_re, *c_im, *log_dt, *dskip;
};

__device__ __forceinline__ uint32_t s32(const void* p) { return (uint32_t)__cvta_generic_to_shared(p); }
__device__ __forceinline__ void mbar_init(uint32_t b, int c) { asm volatile("mbarrier.init.shared::cta.b64 [%0], %1;" ::"r"(b), "r"(c) : "memory"); }
__device__ __forceinline__ void mbar_expect(uint32_t b, int bytes) { asm volatile("mbarrier.arrive.expect_tx.shared::cta.b64 _, [%0], %1;" ::"r"(b), "r"(bytes) : "memory"); }
__device__ __forceinline__ void mbar_arrive(uint32_t b) { asm volatile("mbarrier.arrive.shared::cta.b64 _, [%0];" ::"r"(b) : "memory"); }
__device__ __forceinline__ void mbar_wait(uint32_t b, int parity) {
  asm volatile("{\n.reg .pred p;\nWAIT_LOOP:\nmbarrier.try_wait.parity.shared::cta.b64 p, [%0], %1;\n@p bra WAIT_DONE;\nbra WAIT_LOOP;\nWAIT_DONE:\n}" ::"r"(b), "r"(parity) : "memory");
}
__device__ __forceinline__ bool mbar_test(uint32_t b, int parity) {
  uint32_t ok;
  asm volatile("{\n.reg .pred p;\nmbarrier.test_wait.parity.shared::cta.b64 p, [%1], %2;\nselp.u32 %0, 1, 0, p;\n}" : "=r"(ok) : "r"(b), "r"(parity) : "memory");
  return ok != 0;
}
__device__ __forceinline__ int opaque_tid() { int v; asm volatile("mov.u32 %0, %%tid.x;" : "=r"(v)); return v; }
__device__ __forceinline__ bool elect_one() {
  uint32_t r;
  asm volatile("{\n.reg .pred p;\nelect.sync _|p, 0xffffffff;\nselp.u32 %0, 1, 0, p;\n}" : "=r"(r));
  return r != 0;
}
__device__ __forceinline__ void tma_ld(uint32_t dst, const CUtensorMap* m, int c0, int c1, uint32_t bar) {
  asm volatile("cp.async.bulk.tensor.2d.shared::cluster.global.mbarrier::complete_tx::bytes [%0], [%1, {%3, %4}], [%2];"
               ::"r"(dst), "l"(m), "r"(bar), "r"(c0), "r"(c1) : "memory");
}
__device__ __forceinline__ void tma_ld3(uint32_t dst, const CUtensorMap* m, int c0, int c1, int c2, uint32_t bar) {
  asm volatile("cp.async.bulk.tensor.3d.shared::cluster.global.mbarrier::complete_tx::bytes [%0], [%1, {%3, %4, %5}], [%2];"
               ::"r"(dst), "l"(m), "r"(bar), "r"(c0), "r"(c1), "r"(c2) : "memory");
}
__device__ __forceinline__ void tma_ld5(uint32_t dst, const CUtensorMap* m, int c0, int c4, uint32_t bar) {
  asm volatile("cp.async.bulk.tensor.5d.shared::cluster.global.mbarrier::complete_tx::bytes [%0], [%1, {%3, 0, 0, 0, %4}], [%2];"
               ::"r"(dst), "l"(m), "r"(bar), "r"(c0), "r"(c4) : "memory");
}
__device__ __forceinline__ void tma_prefetch5(const CUtensorMap* m, int c0, int c4) {
  asm volatile("cp.async.bulk.prefetch.tensor.5d.L2.global.tile [%0, {%1, 0, 0, 0, %2}];" ::"l"(m), "r"(c0), "r"(c4) : "memory");
}
__device__ __forceinline__ void tma_prefetch3(const CUtensorMap* m, int c0, int c1, int c2) {
  asm volatile("cp.async.bulk.prefetch.tensor.3d.L2.global.tile [%0, {%1, %2, %3}];" ::"l"(m), "r"(c0), "r"(c1), "r"(c2) : "memory");
}
__device__ __forceinline__ void tma_st(const CUtensorMap* m, int c0, int c1, uint32_t src) {
  asm volatile("cp.async.bulk.tensor.2d.global.shared::cta.bulk_group [%0, {%2, %3}], [%1];" ::"l"(m), "r"(src), "r"(c0), "r"(c1) : "memory");
}
__device__ __forceinline__ void bulk_ld(uint32_t dst, const void* src, int bytes, uint32_t bar) {
  asm volatile("cp.async.bulk.shared::cluster.global.mbarrier::complete_tx::bytes [%0], [%1], %2, [%3];" ::"r"(dst), "l"(src), "r"(bytes), "r"(bar) : "memory");
}
__device__ __forceinline__ void bulk_red_add_f32(void* dst, uint32_t src, int bytes) {
  asm volatile("cp.reduce.async.bulk.global.shared::cta.bulk_group.add.f32 [%0], [%1], %2;" ::"l"(dst), "r"(src), "r"(bytes) : "memory");
}
__device__ __forceinline__ void bulk_commit() { asm volatile("cp.async.bulk.commit_group;" ::: "memory"); }
__device__ __forceinline__ void fence_async_smem() { asm volatile("fence.proxy.async.shared::cta;" ::: "memory"); }
__device__ __forceinline__ void fence_async_global() { asm volatile("fence.proxy.async.global;" ::: "memory"); }
__device__ __forceinline__ void bar_sync(int id, int n) { asm volatile("bar.sync %0, %1;" ::"r"(id), "r"(n) : "memory"); }
__device__ __forceinline__ void bar_arrive(int id, int n) { asm volatile("bar.arrive %0, %1;" ::"r"(id), "r"(n) : "memory"); }
__device__ __forceinline__ bool bar_or(int id, int n, bool v) {
  uint32_t r;
  asm volatile("{\n.reg .pred p, q;\nsetp.ne.u32 q, %3, 0;\nbar.red.or.pred p, %1, %2, q;\nselp.u32 %0, 1, 0, p;\n}" : "=r"(r) : "r"(id), "r"(n), "r"((uint32_t)v) : "memory");
  return r != 0;
}
__device__ __forceinline__ void bulk_wait_read() { asm volatile("cp.async.bulk.wait_group.read 0;" ::: "memory"); }
__device__ __forceinline__ void stg128(void* p, uint4 v) { asm volatile("st.relaxed.gpu.global.v4.u32 [%0], {%1,%2,%3,%4};" ::"l"(p), "r"(v.x), "r"(v.y), "r"(v.z), "r"(v.w) : "memory"); }
constexpr uint32_t UNSET = 0xffffffffu;
constexpr int MAX_RETRY = 1 << 16;
__device__ __forceinline__ void wg_fence() { asm volatile("wgmma.fence.sync.aligned;" ::: "memory"); }
__device__ __forceinline__ void wg_commit() { asm volatile("wgmma.commit_group.sync.aligned;" ::: "memory"); }
template <int N> __device__ __forceinline__ void wg_wait() { asm volatile("wgmma.wait_group.sync.aligned %0;" ::"n"(N) : "memory"); }
__device__ __forceinline__ uint64_t mkdesc(uint32_t addr, uint32_t lbo, uint32_t sbo, int sw) {
  return (uint64_t)((addr & 0x3FFFF) >> 4) | ((uint64_t)(lbo >> 4) << 16) | ((uint64_t)(sbo >> 4) << 32) | ((uint64_t)sw << 62);
}
__device__ __forceinline__ void ldsm4(uint32_t* r, uint32_t a) {
  asm volatile("ldmatrix.sync.aligned.m8n8.x4.shared.b16 {%0,%1,%2,%3}, [%4];" : "=r"(r[0]), "=r"(r[1]), "=r"(r[2]), "=r"(r[3]) : "r"(a) : "memory");
}
__device__ __forceinline__ void ldsm4t(uint32_t* r, uint32_t a) {
  asm volatile("ldmatrix.sync.aligned.m8n8.x4.trans.shared.b16 {%0,%1,%2,%3}, [%4];" : "=r"(r[0]), "=r"(r[1]), "=r"(r[2]), "=r"(r[3]) : "r"(a) : "memory");
}
__device__ __forceinline__ void stsm4(uint32_t a, uint32_t r0, uint32_t r1, uint32_t r2, uint32_t r3) {
  asm volatile("stmatrix.sync.aligned.m8n8.x4.shared.b16 [%0], {%1,%2,%3,%4};" ::"r"(a), "r"(r0), "r"(r1), "r"(r2), "r"(r3) : "memory");
}
__device__ __forceinline__ void stsm4t(uint32_t a, uint32_t r0, uint32_t r1, uint32_t r2, uint32_t r3) {
  asm volatile("stmatrix.sync.aligned.m8n8.x4.trans.shared.b16 [%0], {%1,%2,%3,%4};" ::"r"(a), "r"(r0), "r"(r1), "r"(r2), "r"(r3) : "memory");
}
__device__ __forceinline__ uint32_t movm_t(uint32_t a) { uint32_t r; asm volatile("movmatrix.sync.aligned.m8n8.trans.b16 %0, %1;" : "=r"(r) : "r"(a)); return r; }
__device__ __forceinline__ uint32_t lds32(uint32_t a) { uint32_t v; asm volatile("ld.shared.b32 %0, [%1];" : "=r"(v) : "r"(a) : "memory"); return v; }
__device__ __forceinline__ float2 lds64f(uint32_t a) { float2 v; asm volatile("ld.shared.v2.f32 {%0,%1}, [%2];" : "=f"(v.x), "=f"(v.y) : "r"(a) : "memory"); return v; }
__device__ __forceinline__ float4 lds128f(uint32_t a) { float4 v; asm volatile("ld.shared.v4.f32 {%0,%1,%2,%3}, [%4];" : "=f"(v.x), "=f"(v.y), "=f"(v.z), "=f"(v.w) : "r"(a) : "memory"); return v; }
__device__ __forceinline__ uint4 lds128(uint32_t a) { uint4 v; asm volatile("ld.shared.v4.b32 {%0,%1,%2,%3}, [%4];" : "=r"(v.x), "=r"(v.y), "=r"(v.z), "=r"(v.w) : "r"(a) : "memory"); return v; }
__device__ __forceinline__ void sts128(uint32_t a, uint4 v) { asm volatile("st.shared.v4.b32 [%0], {%1,%2,%3,%4};" ::"r"(a), "r"(v.x), "r"(v.y), "r"(v.z), "r"(v.w) : "memory"); }
__device__ __forceinline__ void sts128f(uint32_t a, float x, float y, float z, float w) { asm volatile("st.shared.v4.f32 [%0], {%1,%2,%3,%4};" ::"r"(a), "f"(x), "f"(y), "f"(z), "f"(w) : "memory"); }
__device__ __forceinline__ void sts32f(uint32_t a, float v) { asm volatile("st.shared.f32 [%0], %1;" ::"r"(a), "f"(v) : "memory"); }
__device__ __forceinline__ void sts16(uint32_t a, uint16_t v) { asm volatile("st.shared.u16 [%0], %1;" ::"r"(a), "h"(v) : "memory"); }
__device__ __forceinline__ uint32_t lds16(uint32_t a) { uint16_t v; asm volatile("ld.shared.u16 %0, [%1];" : "=h"(v) : "r"(a) : "memory"); return v; }
__device__ __forceinline__ uint32_t packbf(float lo, float hi) { uint32_t r; asm("cvt.rn.bf16x2.f32 %0, %1, %2;" : "=r"(r) : "f"(hi), "f"(lo)); return r; }
__device__ __forceinline__ float bf_lo(uint32_t v) { return __uint_as_float(v << 16); }
__device__ __forceinline__ float bf_hi(uint32_t v) { return __uint_as_float(v & 0xffff0000u); }
__device__ __forceinline__ float ex2(float x) { float r; asm("ex2.approx.ftz.f32 %0, %1;" : "=f"(r) : "f"(x)); return r; }
__device__ __forceinline__ float rsqrt_approx(float x) { float r; asm("rsqrt.approx.ftz.f32 %0, %1;" : "=f"(r) : "f"(x)); return r; }
__device__ __forceinline__ float rcp_approx(float x) { float r; asm("rcp.approx.ftz.f32 %0, %1;" : "=f"(r) : "f"(x)); return r; }
__device__ __forceinline__ void mma_bf16(float* d, const uint32_t* a, uint32_t b0, uint32_t b1) {
  asm("mma.sync.aligned.m16n8k16.row.col.f32.bf16.bf16.f32 {%0,%1,%2,%3}, {%4,%5,%6,%7}, {%8,%9}, {%0,%1,%2,%3};"
               : "+f"(d[0]), "+f"(d[1]), "+f"(d[2]), "+f"(d[3]) : "r"(a[0]), "r"(a[1]), "r"(a[2]), "r"(a[3]), "r"(b0), "r"(b1));
}
__device__ __forceinline__ void red_release(unsigned* p) { asm volatile("red.release.gpu.global.add.u32 [%0], 1;" ::"l"(p) : "memory"); }
__device__ __forceinline__ void red_relaxed(unsigned* p) { asm volatile("red.relaxed.gpu.global.add.u32 [%0], 1;" ::"l"(p) : "memory"); }
__device__ __forceinline__ unsigned ld_relaxed(const unsigned* p) { unsigned v; asm volatile("ld.relaxed.gpu.global.u32 %0, [%1];" : "=r"(v) : "l"(p) : "memory"); return v; }
__device__ __forceinline__ void spin_until(const unsigned* p, unsigned target) {
  int it = 0;
  while ((int)(ld_relaxed(p) - target) < 0) {
    if (++it > (1 << 23)) __trap();
  }
}
template <typename T> __device__ __forceinline__ void pin(T*& p) { asm volatile("" : "+l"(p) :: "memory"); }
__device__ __forceinline__ void pin(uint32_t& v) { asm volatile("" : "+r"(v) :: "memory"); }
__device__ __forceinline__ void spin_hint(const unsigned* p, unsigned target) {
  spin_until(p, target);
}
__device__ __forceinline__ uint4 ld_tagged(const uint4* p) { uint4 v; asm volatile("ld.relaxed.gpu.global.v4.u32 {%0,%1,%2,%3}, [%4];" : "=r"(v.x), "=r"(v.y), "=r"(v.z), "=r"(v.w) : "l"(p) : "memory"); return v; }
__device__ __forceinline__ uint32_t hadd2(uint32_t a, uint32_t b) { uint32_t r; asm("add.rn.bf16x2 %0, %1, %2;" : "=r"(r) : "r"(a), "r"(b)); return r; }

__device__ __forceinline__ uint32_t hfma2(uint32_t a, uint32_t b, uint32_t c) { uint32_t r; asm("fma.rn.bf16x2 %0, %1, %2, %3;" : "=r"(r) : "r"(a), "r"(b), "r"(c)); return r; }
__device__ __forceinline__ void sts32(uint32_t a, uint32_t v) { asm volatile("st.shared.u32 [%0], %1;" ::"r"(a), "r"(v) : "memory"); }

template <int N> __device__ __forceinline__ void acc_fence(float* a) {
#pragma unroll
  for (int i = 0; i < N; i++) asm volatile("" : "+f"(a[i]) :: "memory");
}

template<int N,int TB> __device__ __forceinline__ void wgmma_rs(float* d, const uint32_t* a, uint64_t db, int sd);
template<int N,int TA,int TB> __device__ __forceinline__ void wgmma_ss(float* d, uint64_t da, uint64_t db, int sd);
template<> __device__ __forceinline__ void wgmma_rs<64,0>(float* d, const uint32_t* a, uint64_t db, int sd) {
  asm volatile("{\n.reg .pred p;\nsetp.ne.b32 p, %37, 0;\nwgmma.mma_async.sync.aligned.m64n64k16.f32.bf16.bf16 {%0,%1,%2,%3,%4,%5,%6,%7,%8,%9,%10,%11,%12,%13,%14,%15,%16,%17,%18,%19,%20,%21,%22,%23,%24,%25,%26,%27,%28,%29,%30,%31}, {%32,%33,%34,%35}, %36, p, 1, 1, 0;\n}\n"
   : "+f"(d[0]),"+f"(d[1]),"+f"(d[2]),"+f"(d[3]),"+f"(d[4]),"+f"(d[5]),"+f"(d[6]),"+f"(d[7]),"+f"(d[8]),"+f"(d[9]),"+f"(d[10]),"+f"(d[11]),"+f"(d[12]),"+f"(d[13]),"+f"(d[14]),"+f"(d[15]),"+f"(d[16]),"+f"(d[17]),"+f"(d[18]),"+f"(d[19]),"+f"(d[20]),"+f"(d[21]),"+f"(d[22]),"+f"(d[23]),"+f"(d[24]),"+f"(d[25]),"+f"(d[26]),"+f"(d[27]),"+f"(d[28]),"+f"(d[29]),"+f"(d[30]),"+f"(d[31])
   : "r"(a[0]), "r"(a[1]), "r"(a[2]), "r"(a[3]), "l"(db), "r"(sd));
}
template<> __device__ __forceinline__ void wgmma_rs<56,0>(float* d, const uint32_t* a, uint64_t db, int sd) {
  asm volatile("{\n.reg .pred p;\nsetp.ne.b32 p, %33, 0;\nwgmma.mma_async.sync.aligned.m64n56k16.f32.bf16.bf16 {%0,%1,%2,%3,%4,%5,%6,%7,%8,%9,%10,%11,%12,%13,%14,%15,%16,%17,%18,%19,%20,%21,%22,%23,%24,%25,%26,%27}, {%28,%29,%30,%31}, %32, p, 1, 1, 0;\n}\n"
   : "+f"(d[0]),"+f"(d[1]),"+f"(d[2]),"+f"(d[3]),"+f"(d[4]),"+f"(d[5]),"+f"(d[6]),"+f"(d[7]),"+f"(d[8]),"+f"(d[9]),"+f"(d[10]),"+f"(d[11]),"+f"(d[12]),"+f"(d[13]),"+f"(d[14]),"+f"(d[15]),"+f"(d[16]),"+f"(d[17]),"+f"(d[18]),"+f"(d[19]),"+f"(d[20]),"+f"(d[21]),"+f"(d[22]),"+f"(d[23]),"+f"(d[24]),"+f"(d[25]),"+f"(d[26]),"+f"(d[27])
   : "r"(a[0]), "r"(a[1]), "r"(a[2]), "r"(a[3]), "l"(db), "r"(sd));
}
template<> __device__ __forceinline__ void wgmma_rs<48,0>(float* d, const uint32_t* a, uint64_t db, int sd) {
  asm volatile("{\n.reg .pred p;\nsetp.ne.b32 p, %29, 0;\nwgmma.mma_async.sync.aligned.m64n48k16.f32.bf16.bf16 {%0,%1,%2,%3,%4,%5,%6,%7,%8,%9,%10,%11,%12,%13,%14,%15,%16,%17,%18,%19,%20,%21,%22,%23}, {%24,%25,%26,%27}, %28, p, 1, 1, 0;\n}\n"
   : "+f"(d[0]),"+f"(d[1]),"+f"(d[2]),"+f"(d[3]),"+f"(d[4]),"+f"(d[5]),"+f"(d[6]),"+f"(d[7]),"+f"(d[8]),"+f"(d[9]),"+f"(d[10]),"+f"(d[11]),"+f"(d[12]),"+f"(d[13]),"+f"(d[14]),"+f"(d[15]),"+f"(d[16]),"+f"(d[17]),"+f"(d[18]),"+f"(d[19]),"+f"(d[20]),"+f"(d[21]),"+f"(d[22]),"+f"(d[23])
   : "r"(a[0]), "r"(a[1]), "r"(a[2]), "r"(a[3]), "l"(db), "r"(sd));
}
template<> __device__ __forceinline__ void wgmma_rs<40,0>(float* d, const uint32_t* a, uint64_t db, int sd) {
  asm volatile("{\n.reg .pred p;\nsetp.ne.b32 p, %25, 0;\nwgmma.mma_async.sync.aligned.m64n40k16.f32.bf16.bf16 {%0,%1,%2,%3,%4,%5,%6,%7,%8,%9,%10,%11,%12,%13,%14,%15,%16,%17,%18,%19}, {%20,%21,%22,%23}, %24, p, 1, 1, 0;\n}\n"
   : "+f"(d[0]),"+f"(d[1]),"+f"(d[2]),"+f"(d[3]),"+f"(d[4]),"+f"(d[5]),"+f"(d[6]),"+f"(d[7]),"+f"(d[8]),"+f"(d[9]),"+f"(d[10]),"+f"(d[11]),"+f"(d[12]),"+f"(d[13]),"+f"(d[14]),"+f"(d[15]),"+f"(d[16]),"+f"(d[17]),"+f"(d[18]),"+f"(d[19])
   : "r"(a[0]), "r"(a[1]), "r"(a[2]), "r"(a[3]), "l"(db), "r"(sd));
}
template<> __device__ __forceinline__ void wgmma_rs<32,0>(float* d, const uint32_t* a, uint64_t db, int sd) {
  asm volatile("{\n.reg .pred p;\nsetp.ne.b32 p, %21, 0;\nwgmma.mma_async.sync.aligned.m64n32k16.f32.bf16.bf16 {%0,%1,%2,%3,%4,%5,%6,%7,%8,%9,%10,%11,%12,%13,%14,%15}, {%16,%17,%18,%19}, %20, p, 1, 1, 0;\n}\n"
   : "+f"(d[0]),"+f"(d[1]),"+f"(d[2]),"+f"(d[3]),"+f"(d[4]),"+f"(d[5]),"+f"(d[6]),"+f"(d[7]),"+f"(d[8]),"+f"(d[9]),"+f"(d[10]),"+f"(d[11]),"+f"(d[12]),"+f"(d[13]),"+f"(d[14]),"+f"(d[15])
   : "r"(a[0]), "r"(a[1]), "r"(a[2]), "r"(a[3]), "l"(db), "r"(sd));
}
template<> __device__ __forceinline__ void wgmma_rs<24,0>(float* d, const uint32_t* a, uint64_t db, int sd) {
  asm volatile("{\n.reg .pred p;\nsetp.ne.b32 p, %17, 0;\nwgmma.mma_async.sync.aligned.m64n24k16.f32.bf16.bf16 {%0,%1,%2,%3,%4,%5,%6,%7,%8,%9,%10,%11}, {%12,%13,%14,%15}, %16, p, 1, 1, 0;\n}\n"
   : "+f"(d[0]),"+f"(d[1]),"+f"(d[2]),"+f"(d[3]),"+f"(d[4]),"+f"(d[5]),"+f"(d[6]),"+f"(d[7]),"+f"(d[8]),"+f"(d[9]),"+f"(d[10]),"+f"(d[11])
   : "r"(a[0]), "r"(a[1]), "r"(a[2]), "r"(a[3]), "l"(db), "r"(sd));
}
template<> __device__ __forceinline__ void wgmma_rs<16,0>(float* d, const uint32_t* a, uint64_t db, int sd) {
  asm volatile("{\n.reg .pred p;\nsetp.ne.b32 p, %13, 0;\nwgmma.mma_async.sync.aligned.m64n16k16.f32.bf16.bf16 {%0,%1,%2,%3,%4,%5,%6,%7}, {%8,%9,%10,%11}, %12, p, 1, 1, 0;\n}\n"
   : "+f"(d[0]),"+f"(d[1]),"+f"(d[2]),"+f"(d[3]),"+f"(d[4]),"+f"(d[5]),"+f"(d[6]),"+f"(d[7])
   : "r"(a[0]), "r"(a[1]), "r"(a[2]), "r"(a[3]), "l"(db), "r"(sd));
}
template<> __device__ __forceinline__ void wgmma_rs<8,0>(float* d, const uint32_t* a, uint64_t db, int sd) {
  asm volatile("{\n.reg .pred p;\nsetp.ne.b32 p, %9, 0;\nwgmma.mma_async.sync.aligned.m64n8k16.f32.bf16.bf16 {%0,%1,%2,%3}, {%4,%5,%6,%7}, %8, p, 1, 1, 0;\n}\n"
   : "+f"(d[0]),"+f"(d[1]),"+f"(d[2]),"+f"(d[3])
   : "r"(a[0]), "r"(a[1]), "r"(a[2]), "r"(a[3]), "l"(db), "r"(sd));
}
template<> __device__ __forceinline__ void wgmma_ss<64,1,0>(float* d, uint64_t da, uint64_t db, int sd) {
  asm volatile("{\n.reg .pred p;\nsetp.ne.b32 p, %34, 0;\nwgmma.mma_async.sync.aligned.m64n64k16.f32.bf16.bf16 {%0,%1,%2,%3,%4,%5,%6,%7,%8,%9,%10,%11,%12,%13,%14,%15,%16,%17,%18,%19,%20,%21,%22,%23,%24,%25,%26,%27,%28,%29,%30,%31}, %32, %33, p, 1, 1, 1, 0;\n}\n"
   : "+f"(d[0]),"+f"(d[1]),"+f"(d[2]),"+f"(d[3]),"+f"(d[4]),"+f"(d[5]),"+f"(d[6]),"+f"(d[7]),"+f"(d[8]),"+f"(d[9]),"+f"(d[10]),"+f"(d[11]),"+f"(d[12]),"+f"(d[13]),"+f"(d[14]),"+f"(d[15]),"+f"(d[16]),"+f"(d[17]),"+f"(d[18]),"+f"(d[19]),"+f"(d[20]),"+f"(d[21]),"+f"(d[22]),"+f"(d[23]),"+f"(d[24]),"+f"(d[25]),"+f"(d[26]),"+f"(d[27]),"+f"(d[28]),"+f"(d[29]),"+f"(d[30]),"+f"(d[31])
   : "l"(da), "l"(db), "r"(sd));
}
template<> __device__ __forceinline__ void wgmma_ss<64,0,1>(float* d, uint64_t da, uint64_t db, int sd) {
  asm volatile("{\n.reg .pred p;\nsetp.ne.b32 p, %34, 0;\nwgmma.mma_async.sync.aligned.m64n64k16.f32.bf16.bf16 {%0,%1,%2,%3,%4,%5,%6,%7,%8,%9,%10,%11,%12,%13,%14,%15,%16,%17,%18,%19,%20,%21,%22,%23,%24,%25,%26,%27,%28,%29,%30,%31}, %32, %33, p, 1, 1, 0, 1;\n}\n"
   : "+f"(d[0]),"+f"(d[1]),"+f"(d[2]),"+f"(d[3]),"+f"(d[4]),"+f"(d[5]),"+f"(d[6]),"+f"(d[7]),"+f"(d[8]),"+f"(d[9]),"+f"(d[10]),"+f"(d[11]),"+f"(d[12]),"+f"(d[13]),"+f"(d[14]),"+f"(d[15]),"+f"(d[16]),"+f"(d[17]),"+f"(d[18]),"+f"(d[19]),"+f"(d[20]),"+f"(d[21]),"+f"(d[22]),"+f"(d[23]),"+f"(d[24]),"+f"(d[25]),"+f"(d[26]),"+f"(d[27]),"+f"(d[28]),"+f"(d[29]),"+f"(d[30]),"+f"(d[31])
   : "l"(da), "l"(db), "r"(sd));
}
template<> __device__ __forceinline__ void wgmma_ss<192,0,1>(float* d, uint64_t da, uint64_t db, int sd) {
  asm volatile("{\n.reg .pred p;\nsetp.ne.b32 p, %98, 0;\nwgmma.mma_async.sync.aligned.m64n192k16.f32.bf16.bf16 {%0,%1,%2,%3,%4,%5,%6,%7,%8,%9,%10,%11,%12,%13,%14,%15,%16,%17,%18,%19,%20,%21,%22,%23,%24,%25,%26,%27,%28,%29,%30,%31,%32,%33,%34,%35,%36,%37,%38,%39,%40,%41,%42,%43,%44,%45,%46,%47,%48,%49,%50,%51,%52,%53,%54,%55,%56,%57,%58,%59,%60,%61,%62,%63,%64,%65,%66,%67,%68,%69,%70,%71,%72,%73,%74,%75,%76,%77,%78,%79,%80,%81,%82,%83,%84,%85,%86,%87,%88,%89,%90,%91,%92,%93,%94,%95}, %96, %97, p, 1, 1, 0, 1;\n}\n"
   : "+f"(d[0]),"+f"(d[1]),"+f"(d[2]),"+f"(d[3]),"+f"(d[4]),"+f"(d[5]),"+f"(d[6]),"+f"(d[7]),"+f"(d[8]),"+f"(d[9]),"+f"(d[10]),"+f"(d[11]),"+f"(d[12]),"+f"(d[13]),"+f"(d[14]),"+f"(d[15]),"+f"(d[16]),"+f"(d[17]),"+f"(d[18]),"+f"(d[19]),"+f"(d[20]),"+f"(d[21]),"+f"(d[22]),"+f"(d[23]),"+f"(d[24]),"+f"(d[25]),"+f"(d[26]),"+f"(d[27]),"+f"(d[28]),"+f"(d[29]),"+f"(d[30]),"+f"(d[31]),"+f"(d[32]),"+f"(d[33]),"+f"(d[34]),"+f"(d[35]),"+f"(d[36]),"+f"(d[37]),"+f"(d[38]),"+f"(d[39]),"+f"(d[40]),"+f"(d[41]),"+f"(d[42]),"+f"(d[43]),"+f"(d[44]),"+f"(d[45]),"+f"(d[46]),"+f"(d[47]),"+f"(d[48]),"+f"(d[49]),"+f"(d[50]),"+f"(d[51]),"+f"(d[52]),"+f"(d[53]),"+f"(d[54]),"+f"(d[55]),"+f"(d[56]),"+f"(d[57]),"+f"(d[58]),"+f"(d[59]),"+f"(d[60]),"+f"(d[61]),"+f"(d[62]),"+f"(d[63]),"+f"(d[64]),"+f"(d[65]),"+f"(d[66]),"+f"(d[67]),"+f"(d[68]),"+f"(d[69]),"+f"(d[70]),"+f"(d[71]),"+f"(d[72]),"+f"(d[73]),"+f"(d[74]),"+f"(d[75]),"+f"(d[76]),"+f"(d[77]),"+f"(d[78]),"+f"(d[79]),"+f"(d[80]),"+f"(d[81]),"+f"(d[82]),"+f"(d[83]),"+f"(d[84]),"+f"(d[85]),"+f"(d[86]),"+f"(d[87]),"+f"(d[88]),"+f"(d[89]),"+f"(d[90]),"+f"(d[91]),"+f"(d[92]),"+f"(d[93]),"+f"(d[94]),"+f"(d[95])
   : "l"(da), "l"(db), "r"(sd));
}
template<> __device__ __forceinline__ void wgmma_ss<192,1,1>(float* d, uint64_t da, uint64_t db, int sd) {
  asm volatile("{\n.reg .pred p;\nsetp.ne.b32 p, %98, 0;\nwgmma.mma_async.sync.aligned.m64n192k16.f32.bf16.bf16 {%0,%1,%2,%3,%4,%5,%6,%7,%8,%9,%10,%11,%12,%13,%14,%15,%16,%17,%18,%19,%20,%21,%22,%23,%24,%25,%26,%27,%28,%29,%30,%31,%32,%33,%34,%35,%36,%37,%38,%39,%40,%41,%42,%43,%44,%45,%46,%47,%48,%49,%50,%51,%52,%53,%54,%55,%56,%57,%58,%59,%60,%61,%62,%63,%64,%65,%66,%67,%68,%69,%70,%71,%72,%73,%74,%75,%76,%77,%78,%79,%80,%81,%82,%83,%84,%85,%86,%87,%88,%89,%90,%91,%92,%93,%94,%95}, %96, %97, p, 1, 1, 1, 1;\n}\n"
   : "+f"(d[0]),"+f"(d[1]),"+f"(d[2]),"+f"(d[3]),"+f"(d[4]),"+f"(d[5]),"+f"(d[6]),"+f"(d[7]),"+f"(d[8]),"+f"(d[9]),"+f"(d[10]),"+f"(d[11]),"+f"(d[12]),"+f"(d[13]),"+f"(d[14]),"+f"(d[15]),"+f"(d[16]),"+f"(d[17]),"+f"(d[18]),"+f"(d[19]),"+f"(d[20]),"+f"(d[21]),"+f"(d[22]),"+f"(d[23]),"+f"(d[24]),"+f"(d[25]),"+f"(d[26]),"+f"(d[27]),"+f"(d[28]),"+f"(d[29]),"+f"(d[30]),"+f"(d[31]),"+f"(d[32]),"+f"(d[33]),"+f"(d[34]),"+f"(d[35]),"+f"(d[36]),"+f"(d[37]),"+f"(d[38]),"+f"(d[39]),"+f"(d[40]),"+f"(d[41]),"+f"(d[42]),"+f"(d[43]),"+f"(d[44]),"+f"(d[45]),"+f"(d[46]),"+f"(d[47]),"+f"(d[48]),"+f"(d[49]),"+f"(d[50]),"+f"(d[51]),"+f"(d[52]),"+f"(d[53]),"+f"(d[54]),"+f"(d[55]),"+f"(d[56]),"+f"(d[57]),"+f"(d[58]),"+f"(d[59]),"+f"(d[60]),"+f"(d[61]),"+f"(d[62]),"+f"(d[63]),"+f"(d[64]),"+f"(d[65]),"+f"(d[66]),"+f"(d[67]),"+f"(d[68]),"+f"(d[69]),"+f"(d[70]),"+f"(d[71]),"+f"(d[72]),"+f"(d[73]),"+f"(d[74]),"+f"(d[75]),"+f"(d[76]),"+f"(d[77]),"+f"(d[78]),"+f"(d[79]),"+f"(d[80]),"+f"(d[81]),"+f"(d[82]),"+f"(d[83]),"+f"(d[84]),"+f"(d[85]),"+f"(d[86]),"+f"(d[87]),"+f"(d[88]),"+f"(d[89]),"+f"(d[90]),"+f"(d[91]),"+f"(d[92]),"+f"(d[93]),"+f"(d[94]),"+f"(d[95])
   : "l"(da), "l"(db), "r"(sd));
}

template <bool TR>
__device__ __forceinline__ void gemm_section(float* acc, float& mean0, float& mean1, float& rstd0, float& rstd1,
                                             uint32_t sb, int blk, int hg, int wg, int w, int lane) {
  constexpr int layer = TR ? 1 : 0;
  constexpr int TURN = TR ? TURN1 : TURN0;
  constexpr int LSTAT = TURN < 4 ? TURN - 1 : 3;
  const uint32_t bar = sb + SM_BAR;
  const int g = lane >> 2, t = lane & 3;
  const bool leader = (w == 0) && (lane == 0);
  const int statpos = hg < 3 ? 1 : wg ? LSTAT : TR ? 3 : 2;
  const bool copy = hg >= 3 && wg == 0;
  const int cut = wg ? TURN : 4;
  auto wait_full = [&](int c) {
    mbar_wait(bar + 8 * (B_XF + 8 * wg + c), layer);
    mbar_wait(bar + 8 * (B_WF + c), layer);
  };
  auto peek = [&](int c) {
    const bool x = mbar_test(bar + 8 * (B_XF + 8 * wg + c), layer), y = mbar_test(bar + 8 * (B_WF + c), layer);
    return x && y;
  };
  const uint64_t da0 = mkdesc(sb, TR ? 8192 : 16, 1024, 1), db0 = mkdesc(sb, 8192, 1024, 1);
  uint32_t xt = wg ? 0xfedcba98u : 0x21043210u;
  uint64_t wt = 0x0816131005161310ull;
  uint64_t da = da0 + ((xt & 15) << 9), db = db0 + (16 << 9);
  auto issue = [&](int c, int first) {
    wg_fence();
#pragma unroll
    for (int ks = 0; ks < 4; ks++) wgmma_ss<192, TR ? 1 : 0, 1>(acc, da + (TR ? ks * 128 : ks * 2), db + ks * 128, !first || ks != 0);
    wg_commit();
    xt >>= 4; wt >>= 8;
    da = da0 + ((xt & 15) << 9); db = db0 + (((uint32_t)wt & 31) << 9);
  };
  wait_full(0);
  bool ready = peek(1);
  issue(0, 1);
  TSW(0);
#pragma unroll 1
  for (int c = 1; c < cut; c++) {
    if (!ready) wait_full(c);
    issue(c, 0);
    ready = peek(c + 1);
    wg_wait<1>();
    if (leader) mbar_arrive(bar + 8 * (B_DN + 8 * wg + c - 1));
    if (wg == 1 && c == cut - 1) {
      wg_wait<0>();
      if (leader) mbar_arrive(bar + 8 * (B_DN + 8 + c));
    }
    if (c == statpos) {
      mbar_wait(bar + 8 * (copy ? B_SC : B_XF + 8 * wg + hg), layer);
      uint32_t A[16];
      const uint32_t xb = sb + (copy ? P_R : 8 * wg + hg) * PG;
#pragma unroll
      for (int ks = 0; ks < 4; ks++) {
        if (!TR) {
          const int row = 16 * w + (lane & 15), kc = 2 * ks + (lane >> 4);
          ldsm4(&A[4 * ks], xb + row * 128 + ((kc ^ (row & 7)) << 4));
        } else {
          const int k = 16 * ks + (lane & 7) + 8 * (lane >> 4), pc = 2 * w + ((lane >> 3) & 1);
          ldsm4t(&A[4 * ks], xb + k * 128 + ((pc ^ (k & 7)) << 4));
        }
      }
      float s0 = 0.f, q0 = 0.f, s1 = 0.f, q1 = 0.f;
#pragma unroll
      for (int i = 0; i < 16; i += 2) {
        const float a = bf_lo(A[i]), b = bf_hi(A[i]), c_ = bf_lo(A[i + 1]), d = bf_hi(A[i + 1]);
        s0 += a + b; q0 = fmaf(a, a, q0); q0 = fmaf(b, b, q0);
        s1 += c_ + d; q1 = fmaf(c_, c_, q1); q1 = fmaf(d, d, q1);
      }
#pragma unroll
      for (int o = 1; o <= 2; o <<= 1) {
        s0 += __shfl_xor_sync(~0u, s0, o); q0 += __shfl_xor_sync(~0u, q0, o);
        s1 += __shfl_xor_sync(~0u, s1, o); q1 += __shfl_xor_sync(~0u, q1, o);
      }
      if (t < 2)
        asm volatile("red.relaxed.gpu.global.add.v4.f32 [%0], {%1,%2,%3,%4};" ::"l"(g_rows + layer * LSEQ + blk * 64 + 16 * w + g + 8 * t),
                     "f"(t ? s1 : s0), "f"(t ? q1 : q0), "f"(1.f), "f"(0.f) : "memory");
    }
  }
  if (wg == 1) {
#pragma unroll 1
    for (int c = cut; c < 8; c++) wait_full(c);
    ready = true;
    bar_sync(5, 256);
  }
#pragma unroll 1
  for (int c = cut; c < 8; c++) {
    if (!ready) wait_full(c);
    issue(c, 0);
    if (wg == 1) {
      wg_wait<2>();
      if (leader && c >= cut + 2) mbar_arrive(bar + 8 * (B_DN + 8 + c - 2));
    } else if (c == 7) {
      bar_arrive(5, 256);
    } else {
      ready = peek(c + 1);
      wg_wait<1>();
      if (leader && c < 6) mbar_arrive(bar + 8 * (B_DN + c - 1));
    }
  }
  mbar_wait(bar + 8 * (B_LN + wg), layer);
  const float4 ln = lds128f(sb + ln_off(wg) + (8 * w + g) * 16);
  mean0 = ln.x; rstd0 = ln.y; mean1 = ln.z; rstd1 = ln.w;
  wg_wait<0>();
  acc_fence<96>(acc);
  if (leader) mbar_arrive(bar + 8 * (B_DN + 8 * wg + 7));
}

__device__ __forceinline__ void attn_phase(const Params& p, uint32_t sb, int layer, int rb, int hg, int wg, int w) {
  const int lane = opaque_tid() & 31;
  const int g = lane >> 2, t = lane & 3;
  const uint32_t bar = sb + SM_BAR;
  const int blk = 16 * wg + rb;
  float acc[96];
  float2 cs[24];
  float mean0, mean1, rstd0, rstd1;
  if (layer) gemm_section<true>(acc, mean0, mean1, rstd0, rstd1, sb, blk, hg, wg, w, lane);
  else gemm_section<false>(acc, mean0, mean1, rstd0, rstd1, sb, blk, hg, wg, w, lane);
  TSW(1);
#pragma unroll
  for (int j = 8; j < 24; j++) cs[j] = lds64f(sb + SM_CS + 4 * (8 * j + 2 * t));
  const uint32_t kvx = sb + (wg ? 22 : 0) * PG;

  uint32_t kb[4][8], vb[4][8], qa[4][4];
  {
    const float nm0 = -mean0 * rstd0, nm1 = -mean1 * rstd1;
    const int st_row = 16 * w + (lane & 7) + 8 * ((lane >> 3) & 1);
    const uint32_t st_base = kvx + st_row * 256;
    const bool sender = (w == 3 && blk < 31);
    uint4* halo = &g_halo[(blk * 8 + hg) * 256 + lane];
    uint32_t r[4][2][4];
#pragma unroll
    for (int h = 0; h < 4; h++) {
#pragma unroll
      for (int kv = 0; kv < 2; kv++) {
#pragma unroll
        for (int dh = 0; dh < 2; dh++) {
          const int j = 8 + kv * 8 + 2 * h + dh;
          const float2 c2 = cs[j];
          const float v0 = fmaf(acc[4 * j + 0], rstd0, nm0 * c2.x), v1 = fmaf(acc[4 * j + 1], rstd0, nm0 * c2.y);
          const float v2 = fmaf(acc[4 * j + 2], rstd1, nm1 * c2.x), v3 = fmaf(acc[4 * j + 3], rstd1, nm1 * c2.y);
          r[h][kv][2 * dh] = packbf(v0, v1);
          r[h][kv][2 * dh + 1] = packbf(v2, v3);
        }
      }
      if (sender) {
        stg128(halo + (2 * h) * 32, make_uint4(r[h][0][0], r[h][0][2], r[h][0][1], r[h][0][3]));
        stg128(halo + (2 * h + 1) * 32, make_uint4(r[h][1][0], r[h][1][1], r[h][1][2], r[h][1][3]));
      }
    }
#pragma unroll
    for (int j = 0; j < 8; j++) cs[j] = lds64f(sb + SM_CS + 4 * (8 * j + 2 * t));
    mbar_wait(bar + 8 * (B_DN + 7), layer);
#pragma unroll
    for (int h = 0; h < 4; h++) {
#pragma unroll
      for (int kv = 0; kv < 2; kv++) {
        const int chunk = 4 * h + 2 * kv + (lane >> 4);
        if (w < 3) stsm4(st_base + (((chunk & 8) | ((chunk ^ st_row) & 7)) << 4), r[h][kv][0], r[h][kv][1], r[h][kv][2], r[h][kv][3]);
      }
      kb[h][4] = r[h][0][0]; kb[h][5] = r[h][0][2]; kb[h][6] = r[h][0][1]; kb[h][7] = r[h][0][3];
      vb[h][4] = movm_t(r[h][1][0]); vb[h][5] = movm_t(r[h][1][1]); vb[h][6] = movm_t(r[h][1][2]); vb[h][7] = movm_t(r[h][1][3]);
    }
#pragma unroll
    for (int h = 0; h < 4; h++) {
#pragma unroll
      for (int dh = 0; dh < 2; dh++) {
        const int j = 2 * h + dh;
        const float2 c2 = cs[j];
        qa[h][2 * dh] = packbf(fmaf(-mean0, c2.x, acc[4 * j + 0]), fmaf(-mean0, c2.y, acc[4 * j + 1]));
        qa[h][2 * dh + 1] = packbf(fmaf(-mean1, c2.x, acc[4 * j + 2]), fmaf(-mean1, c2.y, acc[4 * j + 3]));
      }
    }
  }
  bar_sync(2 + wg, 128);
  TSW(2);
  {
    const uint32_t prev_base = kvx + (16 * w - 16) * 256;
    const int mi = lane >> 3;
    const int r = 8 * (mi >> 1) + (lane & 7), r2 = 8 * (mi & 1) + (lane & 7);
    if (w != 0) {
#pragma unroll
      for (int h = 0; h < 4; h++) {
        const int ch = 4 * h + (mi & 1), ch2 = 4 * h + 2 + (mi >> 1);
        ldsm4(&kb[h][0], prev_base + r * 256 + (((ch & 8) | ((ch ^ r) & 7)) << 4));
        ldsm4t(&vb[h][0], prev_base + r2 * 256 + (((ch2 & 8) | ((ch2 ^ r2) & 7)) << 4));
      }
    } else if (blk > 0) {
      uint4* src = &g_halo[((blk - 1) * 8 + hg) * 256 + lane];
      uint4 hv[8];
      int it = 0;
      bool ok;
      do {
        ok = true;
#pragma unroll
        for (int i = 0; i < 8; i++) hv[i] = ld_tagged(src + i * 32);
#pragma unroll
        for (int i = 0; i < 8; i++) ok = ok && hv[i].x != UNSET;
      } while (!__all_sync(~0u, ok) && ++it < (1 << 20));
      if (layer == 0) {
#pragma unroll
        for (int i = 0; i < 2; i++) stg128(src + i * 128 + (lane >> 1) * 6, make_uint4(UNSET, UNSET, UNSET, UNSET));
      }
#pragma unroll
      for (int h = 0; h < 4; h++) {
        kb[h][0] = hv[2 * h].x; kb[h][1] = hv[2 * h].y; kb[h][2] = hv[2 * h].z; kb[h][3] = hv[2 * h].w;
        vb[h][0] = movm_t(hv[2 * h + 1].x); vb[h][1] = movm_t(hv[2 * h + 1].y);
        vb[h][2] = movm_t(hv[2 * h + 1].z); vb[h][3] = movm_t(hv[2 * h + 1].w);
      }
    } else {
#pragma unroll
      for (int h = 0; h < 4; h++)
#pragma unroll
        for (int k = 0; k < 4; k++) kb[h][k] = vb[h][k] = 0u;
    }
    TSW(3);
  }
  uint4* op = (uint4*)g_O + ((layer * 32 + blk) * 8 + hg) * 512 + 64 * t + 16 * w + g;
  unsigned* ocnt = &g_cnt[(C_O + layer * 32 + blk) * 32];
  pin(op); pin(ocnt);
  mbar_wait(bar + 8 * (B_DN + 15), layer);
  TSW(4);

  const bool first = (blk == 0 && w == 0);
  const int e = t - (g >> 1);
  const bool par = g & 1, epos = e >= 1;
  const uint32_t pmask = par ? 0xffff0000u : 0x0000ffffu;
  const uint32_t mB0 = epos ? pmask : 0u, mB1 = epos ? 0u : pmask;
  const float cl2 = 0.25f * 1.4426950408889634f;
  const float sc0 = rstd0 * cl2, sc1 = rstd1 * cl2;
  const float NEG = -INFINITY;
  float vA0[4], vB0[4], vA1[4], vB1[4];
#pragma unroll
  for (int h = 0; h < 4; h++) {
    float S[4][4];
#pragma unroll
    for (int j = 0; j < 4; j++) {
      S[j][0] = S[j][1] = S[j][2] = S[j][3] = 0.f;
      mma_bf16(S[j], qa[h], kb[h][2 * j], kb[h][2 * j + 1]);
    }
    vA0[h] = par ? S[1][1] : S[1][0];
    vB0[h] = epos ? (par ? S[0][1] : S[0][0]) : (par ? S[2][1] : S[2][0]);
    vA1[h] = par ? S[2][3] : S[2][2];
    vB1[h] = epos ? (par ? S[1][3] : S[1][2]) : (par ? S[3][3] : S[3][2]);
    if (first) { vA0[h] = NEG; if (epos) { vB0[h] = NEG; vB1[h] = NEG; } }
  }
  float m0[4], m1[4];
#pragma unroll
  for (int h = 0; h < 4; h++) { m0[h] = fmaxf(vA0[h], vB0[h]); m1[h] = fmaxf(vA1[h], vB1[h]); }
#pragma unroll
  for (int o = 1; o <= 2; o <<= 1) {
#pragma unroll
    for (int h = 0; h < 4; h++) {
      m0[h] = fmaxf(m0[h], __shfl_xor_sync(~0u, m0[h], o));
      m1[h] = fmaxf(m1[h], __shfl_xor_sync(~0u, m1[h], o));
    }
  }
  float O0[4][4], O1[4][4], Z[4][4];
#pragma unroll
  for (int h = 0; h < 4; h++) {
    const float mm0 = -m0[h] * sc0, mm1 = -m1[h] * sc1;
    const float pA0 = ex2(fmaf(vA0[h], sc0, mm0)), pB0 = ex2(fmaf(vB0[h], sc0, mm0));
    const float pA1 = ex2(fmaf(vA1[h], sc1, mm1)), pB1 = ex2(fmaf(vB1[h], sc1, mm1));
    const uint32_t hA0 = packbf(pA0, pA0), hB0 = packbf(pB0, pB0), hA1 = packbf(pA1, pA1), hB1 = packbf(pB1, pB1);
    const uint32_t P0[4] = {hB0 & mB0, 0u, hA0 & pmask, hB1 & mB0};
    const uint32_t P1[4] = {hB0 & mB1, hA1 & pmask, 0u, hB1 & mB1};
#pragma unroll
    for (int k = 0; k < 4; k++) O0[h][k] = O1[h][k] = Z[h][k] = 0.f;
    mma_bf16(O0[h], P0, vb[h][0], vb[h][1]); mma_bf16(O1[h], P0, vb[h][2], vb[h][3]); mma_bf16(Z[h], P0, 0x3f803f80u, 0x3f803f80u);
    mma_bf16(O0[h], P1, vb[h][4], vb[h][5]); mma_bf16(O1[h], P1, vb[h][6], vb[h][7]); mma_bf16(Z[h], P1, 0x3f803f80u, 0x3f803f80u);
  }
  if (lane == 0) mbar_arrive(bar + 8 * (B_OST + wg));
#pragma unroll
  for (int h = 0; h < 4; h += 2) {
    const float i0 = rcp_approx(Z[h][0]), i1 = rcp_approx(Z[h][2]), j0 = rcp_approx(Z[h + 1][0]), j1 = rcp_approx(Z[h + 1][2]);
    stg128(op + 128 * h, make_uint4(packbf(O0[h][0] * i0, O0[h][1] * i0), packbf(O1[h][0] * i0, O1[h][1] * i0),
                                   packbf(O0[h + 1][0] * j0, O0[h + 1][1] * j0), packbf(O1[h + 1][0] * j0, O1[h + 1][1] * j0)));
    stg128(op + 128 * h + 8, make_uint4(packbf(O0[h][2] * i1, O0[h][3] * i1), packbf(O1[h][2] * i1, O1[h][3] * i1),
                                            packbf(O0[h + 1][2] * j1, O0[h + 1][3] * j1), packbf(O1[h + 1][2] * j1, O1[h + 1][3] * j1)));
  }
  TSW(5);
  __syncwarp();
  if (elect_one()) red_relaxed(ocnt);
  TSW(6);
}

__device__ __forceinline__ void conv_load(uint32_t* A, uint32_t pe);
__device__ __forceinline__ void proj_phase(const Params& p, uint32_t sb, int layer, int rb, int q, uint32_t* A0, uint32_t* A1) {
  const int lane = opaque_tid() & 31;
  const int wg = __shfl_sync(~0u, opaque_tid() >> 7, 0), w = __shfl_sync(~0u, (opaque_tid() >> 5) & 3, 0);
  const bool TR = layer != 0;
  const int t = lane & 3;
  const uint32_t bar = sb + SM_BAR;
  const uint32_t rbx = sb + (P_R + wg) * PG;
  const uint32_t rsrc = sb + (wg ? 2 : P_R) * PG;
  const int blk = 16 * wg + rb;
  mbar_wait(bar + 8 * (B_RF + wg), layer);
  mbar_wait(bar + 8 * B_WOF, layer);
  const uint32_t stg = sb + (wg ? SM_KGT : SM_STG);
  if (layer) {
    const uint32_t pe = sb + cv_pe(wg, 1) + 4 * (16 + 16 * w + (lane >> 2) - 2 * t);
    mbar_wait(bar + 8 * B_PE, 1);
    conv_load(A0, pe);
    conv_load(A1, pe + 2 * 4480);
    __syncwarp();
    if (lane == 0) mbar_arrive(bar + 8 * B_AL);
  } else {
#pragma unroll
    for (int i = 0; i < 68; i++) {
      asm volatile("mov.b32 %0, 0;" : "=r"(A0[i]));
      asm volatile("mov.b32 %0, 0;" : "=r"(A1[i]));
    }
  }
  bool clean = false, staged = false;
#pragma unroll 1
  for (int attempt = 0; attempt < MAX_RETRY; attempt++) {
  uint32_t res[16];
  if (!TR) {
#pragma unroll
    for (int j = 0; j < 8; j += 2) {
      const int mi = lane >> 3;
      const int row = 16 * w + (lane & 7) + 8 * (mi & 1), ch = j + (mi >> 1);
      ldsm4(&res[2 * j], rsrc + row * 128 + ((ch ^ (row & 7)) << 4));
    }
  } else {
#pragma unroll
    for (int j = 0; j < 8; j += 2) {
      const int mi = lane >> 3;
      const int line = 8 * (j + (mi >> 1)) + (lane & 7), pc = 2 * w + (mi & 1);
      ldsm4t(&res[2 * j], rsrc + line * 128 + ((pc ^ (line & 7)) << 4));
    }
  }
  float acc[32];
#pragma unroll
  for (int j = 0; j < 16; j++) { acc[2 * j] = bf_lo(res[j]); acc[2 * j + 1] = bf_hi(res[j]); }
  acc_fence<32>(acc);
  if (wg) mbar_wait(bar + 8 * B_PG, layer);
  const int wg2 = __shfl_sync(~0u, opaque_tid() >> 7, 0);
  const uint64_t da0 = mkdesc(sb, 1024, 128, 0), db0 = mkdesc(sb, 8192, 1024, 1);
#pragma unroll
  for (int c = 0; c < 4; c++) {
    mbar_wait(bar + 8 * (B_OF + 4 * wg + c), layer);
    if (c == 0) TSW(7);
    const uint64_t da = da0 + (uint32_t)(o_page(wg2, c) * 512);
#pragma unroll
    for (int ks = 0; ks < 8; ks++) {
      if (ks % 4 == 0) { if (ks) wg_commit(); if (wg2) wg_wait<0>(); wg_fence(); }
      wgmma_ss<64, 0, 1>(acc, da + ks * 128, db0 + wo_page(2 * c + (ks >> 2)) * 512 + (ks & 3) * 128, 1);
    }
    wg_commit();
  }
  if (wg) mbar_wait(bar + 8 * B_KG, 0);
  wg_wait<0>();
  acc_fence<32>(acc);
  TSW(8);
  if (!clean) {
    const float chk = acc[0] + acc[2];
    clean = __all_sync(~0u, chk == chk);
    if (clean && lane == 0) mbar_arrive(bar + 8 * (B_PDONE + wg));
  }
  float s0 = 0.f, q0 = 0.f, s1 = 0.f, q1 = 0.f;
  uint32_t o[16];
#pragma unroll
  for (int j = 0; j < 8; j++) {
    const float a = acc[4 * j], b = acc[4 * j + 1], c = acc[4 * j + 2], d = acc[4 * j + 3];
    o[2 * j] = packbf(a, b);
    o[2 * j + 1] = packbf(c, d);
    s0 += a + b; q0 = fmaf(a, a, q0); q0 = fmaf(b, b, q0);
    s1 += c + d; q1 = fmaf(c, c, q1); q1 = fmaf(d, d, q1);
  }
#pragma unroll
  for (int j = 0; j < 8; j += 2) {
    const int mi = lane >> 3;
    const int line = 8 * (j + (mi >> 1)) + (lane & 7), pc = 2 * w + (mi & 1);
    stsm4t(rbx + line * 128 + ((pc ^ (line & 7)) << 4), o[2 * j], o[2 * j + 1], o[2 * j + 2], o[2 * j + 3]);
  }
#pragma unroll
  for (int o2 = 1; o2 <= 2; o2 <<= 1) {
    s0 += __shfl_xor_sync(~0u, s0, o2); q0 += __shfl_xor_sync(~0u, q0, o2);
    s1 += __shfl_xor_sync(~0u, s1, o2); q1 += __shfl_xor_sync(~0u, q1, o2);
  }
  {
    const int i = 2 * (lane >> 2) + (t & 1), k = (i * 11) >> 5;
    const float v = (t == 0) ? s0 : (t == 1) ? q0 : (t == 2) ? s1 : q1;
    sts32f(stg + k * 128 + (2 * w + (t >> 1)) * 16 + (i - 3 * k) * 4, v);
  }
  TSW(9);
  fence_async_smem();
  if (attempt == 0 && clean) {
    staged = true;
    __syncwarp();
    if (lane == 0) mbar_arrive(bar + 8 * (B_STG + wg));
  }
  if (!bar_or(2 + wg, 128, !clean)) break;
  const int rtp = mbar_test(bar + 8 * (B_RT + wg), 0);
  bool unset = false;
#pragma unroll
  for (int i = 0; i < 4; i++) unset |= lds32(sb + o_page(wg, i) * PG + (32 * w + lane) * 128) == UNSET;
  if (!bar_or(2 + wg, 128, unset)) break;
  if (w == 0 && elect_one()) {
    fence_async_smem();
    mbar_expect(bar + 8 * (B_RT + wg), 9 * PG);
    if (layer == 0) tma_ld(rsrc, &p.mapX, q * 64, blk * 64, bar + 8 * (B_RT + wg));
    else tma_ld(rsrc, &p.mapXT, blk * 64, DM + q * 64, bar + 8 * (B_RT + wg));
#pragma unroll 1
    for (int c = 0; c < 4; c++) bulk_ld(sb + o_page(wg, c) * PG, g_O + ((layer * 32 + blk) * 4 + c) * PG, 2 * PG, bar + 8 * (B_RT + wg));
  }
  mbar_wait(bar + 8 * (B_RT + wg), rtp);
  RETRY(0);
  }
  if (!clean && lane == 0) mbar_arrive(bar + 8 * (B_PDONE + wg));
  if (!staged && lane == 0) mbar_arrive(bar + 8 * (B_STG + wg));
  TSW(10);
}

__device__ __forceinline__ void conv_load(uint32_t* A, uint32_t pe) {
#pragma unroll
  for (int m = 0; m < 17; m++) {
    A[4 * m + 2] = lds32(pe + 4 * (64 * m - 8));
    A[4 * m + 0] = lds32(pe + 4 * (64 * m));
    A[4 * m + 1] = lds32(pe + 4 * (64 * m + 8));
    asm volatile("mov.b32 %0, %1;" : "=r"(A[4 * m + 3]) : "r"(A[4 * m + 0]));
  }
}
template <int M> __device__ __forceinline__ void conv_tri(float* acc, const uint32_t* A, uint64_t d) {
  if constexpr (M < 16) {
    wgmma_rs<64 - 8 * (M / 2), 0>(acc, A + 4 * M, d + (uint64_t)(64 + 4 * M), M != 0);
    conv_tri<M + 1>(acc, A, d);
  }
}
__device__ __forceinline__ void conv_mma0(float* acc, const uint32_t* A, uint64_t d) {
  wg_fence();
  conv_tri<0>(acc, A, d);
  wg_commit();
}
__device__ __forceinline__ void conv_mma1(float* acc, const uint32_t* A, uint64_t d, uint64_t ds, uint64_t df) {
  wg_fence();
#pragma unroll
  for (int m = 0; m < 17; m++) wgmma_rs<64, 0>(acc, A + 4 * m, d + (uint64_t)(4 * m), m != 0);
  wgmma_ss<64, 1, 0>(acc, ds, df, 1);
  wgmma_ss<64, 1, 0>(acc, ds + 128, df + 128, 1);
  wg_commit();
}
__device__ __forceinline__ void conv_store(float* acc, uint32_t pb, uint32_t over, int w) {
  acc_fence<32>(acc);
  const int l = opaque_tid() & 31, mt = l >> 3;
  int c = 2 * (63 - 8 * (mt >> 1) - (l & 7) + w) + (mt & 1);
  c ^= (c >> 3) & 1;
  const uint32_t a0 = pb + c * 16;
#pragma unroll
  for (int j = 0; j < 8; j += 2)
    stsm4t(j == 0 ? (c < 128 ? a0 : over + (c - 128) * 16) : a0 - 256 * j, packbf(acc[4 * j], acc[4 * j + 1]), packbf(acc[4 * j + 2], acc[4 * j + 3]),
           packbf(acc[4 * j + 4], acc[4 * j + 5]), packbf(acc[4 * j + 6], acc[4 * j + 7]));
}
__device__ __forceinline__ void conv_sums(uint32_t sb, int lc, int ht) {
  const int m = ht - 1;
  uint4 v[2][3];
#pragma unroll
  for (int c = 0; c < 2; c++)
#pragma unroll
    for (int k = 0; k < 3; k++) {
      const int mm = m - 1 + k;
      v[c][k] = lds128(sb + cv_u(lc + c) + (mm >= 0 ? (mm & 1) * CV_UH + (127 - (mm >> 1)) * 16 : 128 * 16));
    }
  const int ce = m + 2, co = m + 1;
#pragma unroll
  for (int c = 0; c < 2; c++) {
    const uint32_t x[8] = {v[c][0].z, v[c][0].w, v[c][1].x, v[c][1].y, v[c][1].z, v[c][1].w, v[c][2].x, v[c][2].y};
    float pv[16];
#pragma unroll
    for (int k = 0; k < 8; k++) { pv[2 * k] = bf_lo(x[k]); pv[2 * k + 1] = bf_hi(x[k]); }
    float t2[15], t4[13], s9[8], s7[8];
#pragma unroll
    for (int i = 0; i < 15; i++) t2[i] = pv[i] + pv[i + 1];
#pragma unroll
    for (int i = 0; i < 13; i++) t4[i] = t2[i] + t2[i + 2];
#pragma unroll
    for (int i = 0; i < 8; i++) {
      s9[i] = (t4[i] + t4[i + 4]) + pv[i + 8];
      s7[i] = (t4[i + 1] + t2[i + 5]) + pv[i + 7];
    }
    const uint4 e4 = make_uint4(packbf(s9[0], s9[1]), packbf(s9[2], s9[3]), packbf(s9[4], s9[5]), packbf(s9[6], s9[7]));
    if (ce < 128) sts128(sb + cv_se(lc + c) + ((ce ^ ((ce >> 3) & 7)) << 4), e4);
    else sts128(sb + cv_se(lc + c), make_uint4(0, 0, 0, 0));
    sts128(sb + cv_so(lc + c) + ((co ^ ((co >> 3) & 7)) << 4),
           make_uint4(packbf(s7[0], s7[1]), packbf(s7[2], s7[3]), packbf(s7[4], s7[5]), packbf(s7[6], s7[7])));
  }
}

template <int HALF, int NCH, int STEP = 1>
__device__ __forceinline__ void conv_epi(uint32_t sb, bf16* out, int lc, int c) {
  uint4 v[NCH][4], xr[NCH];
  const uint32_t sw = (c ^ ((c >> 3) & 1)) * 16;
#pragma unroll
  for (int u = 0; u < NCH; u++) {
#pragma unroll
    for (int k = 0; k < 4; k++) v[u][k] = lds128(sb + (HALF ? cv_pb1(lc + STEP * u, k) : cv_pb0(lc + STEP * u, k)) + sw);
    xr[u] = lds128(sb + cv_x(HALF, lc + STEP * u) + c * 16);
  }
#pragma unroll
  for (int u = 0; u < NCH; u++) {
    uint4 o;
    o.x = hadd2(xr[u].x, hadd2(hadd2(v[u][0].x, v[u][1].x), hadd2(v[u][2].x, v[u][3].x)));
    o.y = hadd2(xr[u].y, hadd2(hadd2(v[u][0].y, v[u][1].y), hadd2(v[u][2].y, v[u][3].y)));
    o.z = hadd2(xr[u].z, hadd2(hadd2(v[u][0].z, v[u][1].z), hadd2(v[u][2].z, v[u][3].z)));
    o.w = hadd2(xr[u].w, hadd2(hadd2(v[u][0].w, v[u][1].w), hadd2(v[u][2].w, v[u][3].w)));
    stg128(out + cv_chan(0, lc + STEP * u) * LSEQ + HALF * 1024 + c * 8, o);
  }
}

__device__ __forceinline__ bool prep_valid(const uint4 (&st)[6], const uint4 (&xr)[4]) {
  const uint32_t n = st[0].w & st[1].w & st[2].w & st[3].w & st[4].w & (st[5].w | st[5].y | st[5].z);
  return (n == __float_as_uint(8.f)) & (max(max(xr[0].x, xr[1].x), max(xr[2].x, xr[3].x)) != UNSET);
}
template <int HALF>
__device__ __forceinline__ void conv_prep(uint32_t sb, int layer, int cta, int i) {
  uint4 st[6], xr[4];
  const uint4* sp = (const uint4*)g_stats + (layer * 32 + HALF * 16 + (i >> 3)) * 48 + (i & 7);
  const uint4* xp = (const uint4*)g_xT + (2 * layer * DM + 2 * cta) * (LSEQ / 8) + HALF * 128 + i;
  if (!HALF) { pin(sp); pin(xp); }
  mbar_wait(sb + SM_BAR + 8 * (B_GB + HALF), layer);
  if (!HALF) TSW(13);
  auto fetch = [&]() {
#pragma unroll
    for (int k = 0; k < 6; k++) st[k] = ld_tagged(sp + 8 * k);
#pragma unroll
    for (int k = 0; k < 4; k++) xr[k] = ld_tagged(xp + cv_chan(0, k) * (LSEQ / 8));
  };
  if (HALF) {
#pragma unroll
    for (int k = 0; k < 6; k++) st[k] = lds128(sb + CV_ST + (i >> 3) * 768 + k * 128 + (i & 7) * 16);
#pragma unroll
    for (int k = 0; k < 4; k++) xr[k] = lds128(sb + cv_x(1, k) + i * 16);
  } else {
    fetch();
  }
  int it = 0;
  while (!__all_sync(~0u, prep_valid(st, xr)) && ++it < MAX_RETRY) { fetch(); RETRY(1); }
  if (!HALF || it) {
#pragma unroll
    for (int k = 0; k < 4; k++) sts128(sb + cv_x(HALF, k) + i * 16, xr[k]);
  }
  const uint32_t v[16] = {st[0].x, st[0].y, st[0].z, st[1].x, st[1].y, st[1].z, st[2].x, st[2].y, st[2].z, st[3].x, st[3].y, st[3].z, st[4].x, st[4].y, st[4].z, st[5].x};
  uint32_t rs[4], nm[4];
#pragma unroll
  for (int k = 0; k < 4; k++) {
    constexpr float E2 = 1e-5f * DM * DM;
    const float s0 = __uint_as_float(v[4 * k]), s1 = __uint_as_float(v[4 * k + 2]);
    const float r0 = rsqrt_approx(fmaxf(fmaf(__uint_as_float(v[4 * k + 1]), (float)DM, fmaf(-s0, s0, E2)), E2));
    const float r1 = rsqrt_approx(fmaxf(fmaf(__uint_as_float(v[4 * k + 3]), (float)DM, fmaf(-s1, s1, E2)), E2));
    const uint32_t r = packbf(r0, r1);
    rs[k] = r + 0x04800480u;
    nm[k] = packbf(-s0 * bf_lo(r), -s1 * bf_hi(r));
  }
  const uint32_t ud = sb + (i & 1) * CV_UH + (127 - 64 * HALF - (i >> 1)) * 16;
#pragma unroll
  for (int k = 0; k < 4; k++)
    sts128(ud + cv_u(k), make_uint4(hfma2(xr[k].x, rs[0], nm[0]), hfma2(xr[k].y, rs[1], nm[1]), hfma2(xr[k].z, rs[2], nm[2]), hfma2(xr[k].w, rs[3], nm[3])));
  fence_async_smem();
}

__device__ __forceinline__ void conv_phase(const Params& p, uint32_t sb, int layer, int cta, uint32_t* A0, uint32_t* A1) {
  const int tid = opaque_tid();
  const int wg = __shfl_sync(~0u, tid >> 7, 0), w = __shfl_sync(~0u, (tid >> 5) & 3, 0);
  const uint32_t bar = sb + SM_BAR;
  constexpr int CH2 = 4 * PG;
  bf16* xout = g_xT + ((2 * layer + 1) * DM + 2 * cta) * LSEQ;
  float acc[32];
  const uint32_t pe = sb + cv_pe(wg, 0) + 4 * (16 + 16 * w + ((tid & 31) >> 2) - 2 * (tid & 3));
  if (layer == 0) {
    mbar_wait(bar + 8 * (B_PDONE + 1), layer);
    mbar_wait(bar + 8 * B_PE, layer);
    conv_load(A0, pe);
    conv_load(A1, pe + CH2);
  }
  TSW(19);
  const uint64_t d0 = mkdesc(sb + cv_u(wg), CV_UH, 128, 0), d1 = d0 + (CH2 >> 4);
  mbar_wait(bar + 8 * B_U, layer);
  TSW(12);
  if (wg == 1) bar_sync(5, 256);
  conv_mma0(acc, A0, d0);
  if (wg == 0) bar_arrive(5, 256);
  mbar_wait(bar + 8 * (B_PDONE + 1), layer);
  {
    const int l = opaque_tid() & 31;
    if ((l & 15) < 2 * w) sts128(sb + cv_pb0(wg + 2 * (l >> 4), w) + (l & 15) * 16, make_uint4(0, 0, 0, 0));
  }
  wg_wait<0>();
  conv_store(acc, sb + cv_pb0(wg, w), sb + cv_pb1(wg, w), w);
  conv_mma0(acc, A1, d1);
  wg_wait<0>();
  conv_store(acc, sb + cv_pb0(2 + wg, w), sb + cv_pb1(2 + wg, w), w);
  TSW(13);
  bar_sync(2 + wg, 128);
  conv_epi<0, 2, 2>(sb, xout, wg, opaque_tid() & 127);
  TSW(14);
  mbar_arrive(bar + 8 * B_PUB);
  const uint64_t ds = mkdesc(sb + cv_se(wg), 8192, 1024, 1), df = mkdesc(sb + cv_fa(wg), 512, 128, 0);
  if (wg == 0) mbar_wait(bar + 8 * B_U1, layer);
  else bar_sync(6, 256);
  TSW(15);
  conv_mma1(acc, A0, d0, ds, df);
  if (wg == 0) bar_arrive(6, 256);
  wg_wait<0>();
  conv_store(acc, sb + cv_pb1(wg, w), sb + cv_dump(wg), w);
  TSW(16);
  bar_sync(2 + wg, 128);
  conv_epi<1, 1>(sb, xout, wg, opaque_tid() & 127);
  mbar_arrive(bar + 8 * (B_PUB + 1));
  conv_mma1(acc, A1, d1, ds + 512, df + (CH2 >> 4));
  wg_wait<0>();
  conv_store(acc, sb + cv_pb1(2 + wg, w), sb + cv_dump(2 + wg), w);
  TSW(17);
  bar_sync(2 + wg, 128);
  conv_epi<1, 1>(sb, xout, 2 + wg, opaque_tid() & 127);
  mbar_arrive(bar + 8 * (B_PUB + 2));
  TSW(18);
}

#define FDELAY 480
__device__ __forceinline__ void final_tile(const Params& p, uint32_t buf, int ch0, int pos0, int barid, uint32_t hint) {
  const uint32_t t0 = (uint32_t)clock();
  const int tid = opaque_tid() & 127, lane = tid & 31, w = tid >> 5;
  const uint4* src = (const uint4*)(g_xT + (3 * DM + ch0 + (tid >> 3)) * LSEQ + pos0) + (tid & 7);
  const int ch = tid >> 3, row = 4 * (ch & 6) + 2 * (ch >> 3) + (ch & 1);
  uint32_t dst0 = buf + row * 128 + (((tid ^ row) & 7) << 4), dst1 = (dst0 ^ 64) + 512;
  uint32_t ld0 = buf + lane * 128 + ((((2 * w) ^ lane) & 7) << 4), ld1 = ld0 ^ 16;
  bf16* out = p.out + (pos0 + 16 * w + (lane >> 2)) * DM + ch0 + 8 * (lane & 3);
  pin(src); pin(out); pin(dst0); pin(dst1); pin(ld0); pin(ld1);
  if (hint) mbar_wait(hint, 0);
  else while ((uint32_t)clock() - t0 < FDELAY);
  uint4 a, b;
  int it = 0;
  do {
    if (it) RETRY(2);
    a = ld_tagged(src); b = ld_tagged(src + 16 * LSEQ / 8);
  } while (!__all_sync(~0u, a.x != UNSET && b.x != UNSET) && ++it < (1 << 20));
  sts128(dst0, a);
  sts128(dst1, b);
  bar_sync(barid, 128);
#pragma unroll
  for (int h = 0; h < 2; h++) {
    uint32_t r[4];
    ldsm4t(r, h ? ld1 : ld0);
    *(uint4*)(out + 8 * h * DM) = make_uint4(r[0], r[1], r[2], r[3]);
  }
}

struct cplx { float r, i; };
__device__ __forceinline__ cplx cmul(cplx a, cplx b) { return {fmaf(a.r, b.r, -a.i * b.i), fmaf(a.r, b.i, a.i * b.r)}; }
__device__ __forceinline__ cplx csqr(cplx a) { return {fmaf(a.r, a.r, -a.i * a.i), (a.r + a.r) * a.i}; }
__device__ __forceinline__ cplx cexp_l(float ar2, float ai, float l) {
  const float m = ex2(ar2 * l);
  const float x = ai * l;
  return {m * __cosf(x), m * __sinf(x)};
}

__device__ __forceinline__ void colsum_cta(const Params& p, uint32_t sb, int j, int tid) {
  const uint32_t bar = sb + SM_BAR;
  auto ld = [&](int i) {
    mbar_expect(bar + 8 * i, 3 * PG);
    tma_ld3(sb + (i & 7) * 3 * PG, &p.mapW3, (2 * j + (i & 1)) * 64, (i >> 1) * 64, 0, bar + 8 * i);
  };
  const int warp = __shfl_sync(~0u, tid >> 5, 0);
  if (warp == 12 && elect_one()) {
#pragma unroll
    for (int i = 0; i < 8; i++) mbar_init(bar + 8 * i, 1);
    asm volatile("fence.mbarrier_init.release.cluster;" ::: "memory");
    fence_async_smem();
#pragma unroll
    for (int i = 0; i < 8; i++) ld(i);
  }
  if (warp == 13 && elect_one()) {
#pragma unroll
    for (int i = 8; i < 24; i++) mbar_init(bar + 8 * i, i < 16 ? 1 : 12);
    asm volatile("fence.mbarrier_init.release.cluster;" ::: "memory");
  }
  const unsigned ep = ld_relaxed(&g_cnt[C_CS * 32]);
  bar_sync(0, NTHREADS);
  if (warp == 12 && elect_one()) {
#pragma unroll 1
    for (int i = 8; i < 16; i++) { mbar_wait(bar + 8 * (8 + i), 0); fence_async_smem(); ld(i); }
  }
  if (tid < 384) {
    const int lane = tid & 31, cc = tid & 7, r0 = (tid >> 3) & 15, part = tid >> 7;
    const uint32_t id = ((lane >> 2) == 2 * (lane & 3) ? 0x3f80u : 0u) | ((lane >> 2) == 2 * (lane & 3) + 1 ? 0x3f800000u : 0u);
    const uint32_t src = sb + part * PG + r0 * 128 + ((cc ^ (r0 & 7)) << 4);
    float s[2][2][4];
#pragma unroll
    for (int i = 0; i < 16; i++) s[i >> 3][(i >> 2) & 1][i & 3] = 0.f;
#pragma unroll 1
    for (int i2 = 0; i2 < 16; i2 += 2) {
#pragma unroll
      for (int h = 0; h < 2; h++) {
        const int i = i2 + h;
        mbar_wait(bar + 8 * i, 0);
        uint4 v[4];
#pragma unroll
        for (int k = 0; k < 4; k++) v[k] = lds128(src + (i & 7) * 3 * PG + k * 2048);
#pragma unroll
        for (int k = 0; k < 4; k++) {
          const uint32_t a[4] = {v[k].x, v[k].y, v[k].z, v[k].w};
          mma_bf16(s[h][0], a, id, 0u);
          mma_bf16(s[h][1], a, 0u, id);
        }
        __syncwarp();
        if (i < 8 && lane == 0) mbar_arrive(bar + 8 * (16 + i));
      }
    }
    const uint32_t red = sb + 24 * PG;
#pragma unroll
    for (int h = 0; h < 2; h++)
#pragma unroll
      for (int k = 0; k < 2; k++) sts128f(red + (r0 * 384 + h * 192 + part * 64 + cc * 8 + k * 4) * 4, s[h][k][0], s[h][k][1], s[h][k][2], s[h][k][3]);
    bar_sync(1, 384);
    float tot = 0.f;
#pragma unroll
    for (int k = 0; k < 16; k++) tot += __uint_as_float(lds32(red + (k * 384 + tid) * 4));
    asm volatile("st.relaxed.gpu.global.v2.u32 [%0], {%1,%2};" ::"l"(&g_colsum[j * 384 + tid]), "r"(__float_as_uint(tot)), "r"(ep / NCTA + 1) : "memory");
    const uint4 u = make_uint4(UNSET, UNSET, UNSET, UNSET);
    if (tid < 256) {
#pragma unroll 1
      for (int s = 0; s < 4; s++) {
        const int n = (s == 1 || s == 2) ? 32 : 16;
        uint4* buf = s == 1 ? (uint4*)g_O + 131072 : (uint4*)g_xT + (s + !s) * 131072;
#pragma unroll 4
        for (int i = 0; i < n; i++) stg128(buf + (j * n + i) * 1024 + (tid >> 1) * 8 + (tid & 1), u);
        if (n == 16) {
#pragma unroll 4
          for (int i = 0; i < 8; i++) stg128(buf + (256 + j * 64 + i * 8 + (tid >> 5)) * 256 + (s ? 0 : 128) + ((tid & 31) >> 1) * 8 + (tid & 1), u);
        }
        if (s == 3) {
#pragma unroll 4
          for (int i = 0; i < 32; i++) stg128(buf + (256 + j * 64 + 2 * i + (tid >> 7)) * 256 + 128 + (tid & 127), u);
        }
        bar_sync(2, 256);
        if (tid == 32 * s) red_release(&g_cnt[(C_R + s) * 32]);
      }
    }
  }
}

constexpr int KB = 4, KW = 2;
struct ModeIn { uint32_t ar, ai, br, bi, cr, ci; bf16 logdt; };
__device__ __forceinline__ ModeIn load_modes(const Params& p, int d, int m) {
  const int i = d * 64 + m;
  return {((const uint32_t*)p.a_re)[i], ((const uint32_t*)p.a_im)[i], ((const uint32_t*)p.b_re)[i], ((const uint32_t*)p.b_im)[i],
          ((const uint32_t*)p.c_re)[i], ((const uint32_t*)p.c_im)[i], p.log_dt[d]};
}
__device__ __forceinline__ void kernel_gen(uint32_t sb, int cta, int ht, ModeIn in, const ModeIn& in1) {
  const uint32_t bst = sb + SM_KGB + ((ht & 63) >> 2) * 144 + (ht & 3) * 4 + (ht >> 6) * 16;
  const uint64_t db = mkdesc(sb + SM_KGB, 144, 2304, 0);
  const float e0 = (float)(8 * (((ht & 32) >> 1) + ((ht & 31) >> 2)));
  float T[20];
#pragma unroll
  for (int i = 0; i < 20; i++) T[i] = 0.f;
  float k0 = 0.f;
#pragma unroll 1
  for (int pass = 0; pass < 4; pass++) {
    {
      const int sh = (pass & 1) ? 0 : 16;
      auto val = [&](uint32_t v) { return __uint_as_float((v << sh) & 0xffff0000u); };
      const float dt = __bfloat162float(__float2bfloat16_rn(expf(__bfloat162float(in.logdt))));
      const float ar2 = dt * val(in.ar) * 1.4426950408889634f, ai = dt * val(in.ai);
      const cplx c = cmul({val(in.cr), -val(in.ci)}, {dt * val(in.br), -dt * val(in.bi)});
      k0 += c.r;
      const cplx z1 = cexp_l(ar2, -ai, 1.f), z256 = cexp_l(ar2, -ai, 256.f), z64 = cexp_l(ar2, ai, 64.f);
      const cplx z2 = csqr(z1), z512 = csqr(z256);
      auto put = [&](int j, cplx v) { sts32(bst + (j >> 2) * 2304 + (j & 3) * 32, packbf(v.r, v.i)); };
      sts128f(sb + SM_KGT + ht * 16, ar2, ai, z64.r, z64.i);
      const cplx c1 = cmul(c, z1), c2 = cmul(c, z2), c3 = cmul(c1, z2), c4 = cmul(c2, z2);
      const cplx c5 = cmul(c3, z2), c6 = cmul(c4, z2), c7 = cmul(c5, z2), c8 = cmul(c6, z2);
      put(0, c1); put(1, c2); put(2, c3); put(3, c4); put(4, c5); put(5, c6); put(6, c7); put(7, c8);
      const cplx c260 = cmul(c4, z256), c264 = cmul(c8, z256), c520 = cmul(c8, z512), c776 = cmul(c264, z512);
      put(8, cmul(c2, z256)); put(9, c260); put(10, cmul(c6, z256)); put(11, c264);
      put(12, cmul(c4, z512)); put(13, c520); put(14, cmul(c260, z512)); put(15, c776);
      const cplx c1032 = cmul(c520, z512), c1288 = cmul(c776, z512);
      put(16, c1032); put(17, c1288); put(18, cmul(c1032, z512)); put(19, cmul(c1288, z512));
    }
    fence_async_smem();
    bar_sync(4, 128);
    const uint32_t tb = sb + SM_KGT + (ht & 67) * 16;
    float2 nx[KB];
#pragma unroll
    for (int s = 0; s < KB; s++) nx[s] = lds64f(tb + s * 64);
#pragma unroll
    for (int q = 0; q < 16 / KB; q++) {
      uint32_t A[2 * KB];
      float2 cur[KB], z[KB];
#pragma unroll
      for (int s = 0; s < KB; s++) { cur[s] = nx[s]; z[s] = lds64f(tb + (KB * q + s) * 64 + 8); }
      if (q < 16 / KB - 1) {
#pragma unroll
        for (int s = 0; s < KB; s++) nx[s] = lds64f(tb + (KB * q + KB + s) * 64);
      }
      if (q >= KW) wg_wait<KW - 1>();
#pragma unroll
      for (int s = 0; s < KB; s++) {
        const cplx lo = cexp_l(cur[s].x, cur[s].y, e0), hi = cmul(lo, {z[s].x, z[s].y});
        A[2 * s] = packbf(lo.r, lo.i);
        A[2 * s + 1] = packbf(hi.r, hi.i);
      }
      wg_fence();
#pragma unroll
      for (int k = 0; k < KB / 2; k++) wgmma_rs<40, 0>(T, A + 4 * k, db + 9 * KB * q + 18 * k, (pass & 1) | q | k);
      wg_commit();
    }
    wg_wait<0>();
    acc_fence<20>(T);
    if (ht == 0) TS(4 + pass);
    if (pass & 1) {
      const int h2 = opaque_tid() - 256, w = h2 >> 5, lane = h2 & 31, t = lane & 3, chn = h2 >> 6, m = h2 & 63, i0 = 16 * (w & 1) + (lane >> 2);
      const int lc = (pass & 2) + chn;
      const uint32_t kc = sb + kc_off(lc);
      auto put = [&](int idx, float v) {
        sts16(kc + idx * 2, __bfloat16_as_ushort(__float2bfloat16_rn(v)));
      };
#pragma unroll
      for (int hi = 0; hi < 2; hi++) {
        const int i = i0 + 8 * hi;
        float v[5];
#pragma unroll
        for (int j = 0; j < 5; j++) v[j] = chn ? T[4 * j + 2 * hi + 1] : T[4 * j + 2 * hi];
        put(8 * i + 1 + t, v[0]);
        put(8 * i + 5 + t, v[1]);
        put(257 + 4 * i + t, v[2]);
        put(385 + 2 * i + (t & 1) + 64 * (t >> 1), v[3]);
        put(513 + i + 32 * t, v[4]);
      }
#pragma unroll
      for (int o = 16; o > 0; o >>= 1) k0 += __shfl_xor_sync(~0u, k0, o);
      if (lane == 0) sts32f(sb + SM_RED + 4 * w, k0);
      bar_sync(4, 128);
      if (m == 0) put(0, k0 + __uint_as_float(lds32(sb + SM_RED + 4 * w + 4)) + __uint_as_float(lds16(sb + SM_RED + 24 + 2 * lc) << 16));
      k0 = 0.f;
      in = in1;
    }
  }
}

__device__ __forceinline__ void expand_taps(uint32_t sb, int ht, int early) {
  const int ch = ht >> 5, lane = ht & 31;
  const uint32_t kc = sb + kc_off(ch);
  const uint32_t dst0 = sb + cv_pe(ch, early);
  auto put = [&](int G, uint32_t v0, uint32_t v1, uint32_t v2, uint32_t v3, uint32_t v4, uint32_t v5, uint32_t v6, uint32_t v7, uint32_t v8) {
    const uint32_t dst = dst0 + G * 32;
    sts128(dst, make_uint4(v1 | (v0 << 16), v2 | (v1 << 16), v3 | (v2 << 16), v4 | (v3 << 16)));
    sts128(dst + 16, make_uint4(v5 | (v4 << 16), v6 | (v5 << 16), v7 | (v6 << 16), v8 | (v7 << 16)));
  };
  {
    const uint4 q = lds128(kc + lane * 16);
    const uint32_t pv = lane ? lds16(kc + lane * 16 - 2) : 0u;
    const uint32_t dst = dst0 + (lane + 2) * 32;
    sts128(dst, make_uint4(__byte_perm(q.x, pv, 0x5410), __byte_perm(q.x, q.x, 0x1032), __byte_perm(q.y, q.x, 0x7610), __byte_perm(q.y, q.y, 0x1032)));
    sts128(dst + 16, make_uint4(__byte_perm(q.z, q.y, 0x7610), __byte_perm(q.z, q.z, 0x1032), __byte_perm(q.w, q.z, 0x7610), __byte_perm(q.w, q.w, 0x1032)));
    if (lane < 4) sts128(dst0 + lane * 16, make_uint4(0, 0, 0, 0));
  }
  uint32_t a[5], b[2][3];
  {
    const uint32_t s1 = kc + 2 * (256 + 4 * lane);
#pragma unroll
    for (int k = 0; k < 5; k++) a[k] = lds16(s1 + 2 * k);
#pragma unroll
    for (int u = 0; u < 2; u++) {
      const uint32_t s2 = kc + 2 * (384 + 2 * (lane + 32 * u));
#pragma unroll
      for (int k = 0; k < 3; k++) b[u][k] = lds16(s2 + 2 * k);
    }
  }
  const uint32_t k255 = lds16(kc + 2 * 255), k1024 = lds16(kc + 2 * 512);
  put(34 + lane, lane == 0 ? k255 : a[0], a[0], a[0], a[1], a[2], a[2], a[2], a[3], a[4]);
#pragma unroll
  for (int u = 0; u < 2; u++) put(66 + lane + 32 * u, b[u][0], b[u][0], b[u][0], b[u][0], b[u][1], b[u][1], b[u][1], b[u][2], b[u][2]);
  if (lane < 10) {
    const uint32_t v = lane == 0 ? k1024 : 0u;
    put(130 + lane, v, v, v, v, v, v, 0u, 0u, 0u);
  }
}
__device__ __forceinline__ void expand_far(uint32_t sb, int ht) {
  const int ch = ht >> 5, lane = ht & 31;
  const uint32_t kc = sb + kc_off(ch) + 2 * (513 + 2 * (63 - lane)), dst = sb + cv_fa(ch) + lane * 16;
#pragma unroll
  for (int ty = 0; ty < 2; ty++) {
    uint32_t v[16];
#pragma unroll
    for (int k = 0; k < 16; k++) v[k] = (k < 8 || 63 - lane - 4 * k >= 0) ? lds16(kc + 2 * (1 - ty) - 16 * k) : 0u;
#pragma unroll
    for (int u = 0; u < 2; u++)
      sts128(dst + ty * 2048 + u * 512, make_uint4(v[8 * u] | (v[8 * u + 1] << 16), v[8 * u + 2] | (v[8 * u + 3] << 16), v[8 * u + 4] | (v[8 * u + 5] << 16), v[8 * u + 6] | (v[8 * u + 7] << 16)));
    sts128(dst + ty * 2048 + 1024, make_uint4(0, 0, 0, 0));
  }
}

__host__ __device__ constexpr int bar_count(int i) {
  return i == B_LN ? 2 : i == B_AL ? 8 : i < B_STG ? 1 : i < B_PE ? 4 : i >= B_PUB ? 256 : 128;
}
__host__ __device__ constexpr bool bar_first(int i) { return i < B_WF + 2 && (i & 7) < 2; }

__global__ void __launch_bounds__(NTHREADS, 1) fused_kernel(const __grid_constant__ Params p) {
  extern __shared__ __align__(1024) uint8_t smem[];
  constexpr uint32_t sb = 1024;
  if (s32(smem) != sb) return;
  const int tid = threadIdx.x, lane = tid & 31;
  const int warp = __shfl_sync(~0u, tid >> 5, 0);
  if (tid == 32) {
    asm volatile("prefetch.tensormap [%0];" ::"l"(&p.mapX) : "memory");
    asm volatile("prefetch.tensormap [%0];" ::"l"(&p.mapW3) : "memory");
  }
  const int cta = blockIdx.x - (gridDim.x == NCTA + 4 ? 0 : 4);
  if ((unsigned)cta >= NCTA) {
    if (blockIdx.x < NCTA + 4) colsum_cta(p, sb, blockIdx.x & 3, tid);
    return;
  }
  const int rb = ((cta >> 4) & 3) * 4 + ((cta >> 2) & 3), hg = (cta >> 6) * 4 + (cta & 3);
  const uint32_t bar = sb + SM_BAR;
  auto ld_x0 = [&](int half, int c) {
    const uint32_t b = bar + 8 * (B_XF + 8 * half + c);
    mbar_expect(b, PG);
    tma_ld(sb + x_page(half, c) * PG, &p.mapX, c * 64, (16 * half + rb) * 64, b);
  };
  auto ld_x1 = [&](int half, int c, int b0) {
    const uint32_t b = bar + 8 * b0;
    mbar_expect(b, PG);
    tma_ld(sb + (8 * half + c) * PG, &p.mapXT, (16 * half + rb) * 64, DM + c * 64, b);
  };
  auto ld_w = [&](int c) {
    const uint32_t b = bar + 8 * (B_WF + c);
    mbar_expect(b, 3 * PG);
    tma_ld3(sb + w_page(c) * PG, &p.mapW3, hg * 64, c * 64, 0, b);
  };

  if (tid == 0) TS(0);
  if (tid == 480) LTS(0);
  if (warp == 0 && elect_one()) {
#pragma unroll
    for (int i = 0; i < B_WF + 2; i++)
      if (bar_first(i)) mbar_init(bar + 8 * i, 1);
    asm volatile("fence.mbarrier_init.release.cluster;" ::: "memory");
    fence_async_smem();
    ld_x0(0, 0);
    ld_w(0); ld_x0(1, 0);
    ld_x0(0, 1); ld_w(1); ld_x0(1, 1);
    TS(1);
  }
  __syncwarp();
  if (warp >= 1 && warp < 8 && elect_one()) {
    if (warp < 4) {
#pragma unroll
      for (int i = 2; i < 8; i++) mbar_init(bar + 8 * (8 * warp - 8 + i), 1);
    } else {
#pragma unroll
      for (int i = 0; i < 12; i++) mbar_init(bar + 8 * (12 * warp - 24 + i), 1);
    }
    asm volatile("fence.mbarrier_init.release.cluster;" ::: "memory");
  }
  if (warp == 15 && elect_one()) {
#pragma unroll
    for (int i = 72; i < B_COUNT; i++) mbar_init(bar + 8 * i, bar_count(i));
    asm volatile("fence.mbarrier_init.release.cluster;" ::: "memory");
  }

  if (warp < 8) {
    bar_sync(0, NTHREADS);
    asm volatile("setmaxnreg.inc.sync.aligned.u32 %0;" ::"n"(R_CONS));
    const int cw = __shfl_sync(~0u, opaque_tid() >> 5, 0);
    const int wg = cw >> 2, w = cw & 3;
    if (tid == 0) TS(2);
#pragma unroll 1
    for (int layer = 0; layer < 2; layer++) {
      attn_phase(p, sb, layer, rb, hg, wg, w);
      uint32_t A0[68], A1[68];
      proj_phase(p, sb, layer, rb, hg, A0, A1);
      conv_phase(p, sb, layer, cta, A0, A1);
    }
    if (tid == 128) TS(8);
    final_tile(p, sb + (16 + wg) * PG, 256 * wg + 32 * (cta >> 4), 1024 + 64 * (cta & 15), 2 + wg, wg ? 0 : bar + 8 * (B_TF + 1));
    if (tid == 128) TS(9);
    if (tid == 128) LTS(1);
    if (tid == 0) LTE();
  } else if (warp < 12) {
    asm volatile("setmaxnreg.dec.sync.aligned.u32 %0;" ::"n"(R_HELP));
    const int ht = tid - 256;
    {
      unsigned ep0 = 0;
      if (ht == 0) ep0 = ld_relaxed(&g_cnt[C_CS * 32]);
      const bf16 dsk = p.dskip[cv_chan(cta, ht & 3)];
      const ModeIn in0 = load_modes(p, cv_chan(cta, ht >> 6), ht & 63), in1 = load_modes(p, cv_chan(cta, 2 + (ht >> 6)), ht & 63);
      if (ht < 48) sts128f(sb + SM_STG + ht * 16, 0.f, 0.f, 0.f, 1.f);
      bar_sync(0, NTHREADS);
      if (ht == 0) {
        sts32(sb + SM_EP, ep0);
        mbar_arrive(bar + 8 * B_EP);
      }
      if (ht >= 124) sts16(sb + SM_RED + 24 + 2 * (ht & 3), __bfloat16_as_ushort(dsk));
      kernel_gen(sb, cta, ht, in0, in1);
      if (ht < 48) sts128f(sb + SM_KGT + ht * 16, 0.f, 0.f, 0.f, 1.f);
      fence_async_smem();
      bar_sync(4, 128);
      if (ht == 0) mbar_arrive(bar + 8 * B_KG);
    }
#pragma unroll 1
    for (int layer = 0; layer < 2; layer++) {
      const int early = layer;
      if (early) mbar_wait(bar + 8 * (B_DN + 13), 1);
      mbar_wait(bar + 8 * (early ? B_OST : B_PDONE), layer);
      expand_taps(sb, opaque_tid() - 256, early);
      mbar_arrive(bar + 8 * B_PE);
      TSW(0);
      mbar_wait(bar + 8 * B_PDONE, layer);
      expand_far(sb, opaque_tid() - 256);
      {
        const int i = opaque_tid() - 256;
        if (i < 32) sts128(sb + cv_u(i >> 3) + ((i >> 2) & 1) * CV_UH + (128 + (i & 3)) * 16, make_uint4(0, 0, 0, 0));
        mbar_wait(bar + 8 * B_RC, layer);
        conv_prep<0>(sb, layer, cta, i);
        mbar_arrive(bar + 8 * B_U);
      }
      mbar_wait(bar + 8 * (B_PDONE + 1), layer);
      bar_sync(4, 128);
#pragma unroll 1
      for (int lc = 0; lc < 4; lc += 2) {
        conv_sums(sb, lc, opaque_tid() - 256);
        TSW(1 + lc);
      }
      conv_prep<1>(sb, layer, cta, opaque_tid() - 256);
      mbar_arrive(bar + 8 * B_U1);
      TSW(4);
      if (layer == 0) {
        const int c = __shfl_sync(~0u, (opaque_tid() >> 5) & 3, 0);
        int phase = 0;
#pragma unroll 1
        for (int k = 0; k < 3; k++) {
          const int page = (k ? 4 + 4 * k : 0) + c, b = B_XR + 4 * (k & 1) + c;
          const uint32_t a = sb + page * PG + lane * 128 + (lane & 7) * 16 + (lane >> 3) * 4;
          int it = k == 2 ? phase : 0;
#pragma unroll 1
          for (; it < MAX_RETRY; it++) {
            mbar_wait(bar + 8 * b, it & 1);
            const uint32_t v0 = lds32(a), v1 = lds32(a + 4096);
            if (__all_sync(~0u, v0 != UNSET && v1 != UNSET)) break;
            if (elect_one()) { fence_async_smem(); ld_x1(page >> 3, page & 7, b); }
            __syncwarp();
            RETRY(3);
          }
          if (k == 0) phase = it + 1;
          if (lane == 0) mbar_arrive(bar + 8 * (B_XF + page));
        }
      }
    }
#pragma unroll 1
    for (int k = 0; k < 2; k++) final_tile(p, sb + 18 * PG + k * 4096, 256 * k + 32 * (cta >> 4), 64 * (cta & 15), 4, bar + 8 * B_TF);
    if (ht == 0) LTE();
  } else {
    asm volatile("setmaxnreg.dec.sync.aligned.u32 %0;" ::"n"(R_AGENT));
    bar_sync(0, NTHREADS);
    auto done = [&](int half, int c, int layer) { mbar_wait(bar + 8 * (B_DN + 8 * half + c), layer); };
    auto publish = [&](int layer, int k) {
      unsigned* cnt = &g_cnt[(layer ? C_F + 8 * k + (cta >> 4) : C_C + k) * 32];
      pin(cnt);
      mbar_wait(bar + 8 * (B_PUB + k), layer);
      red_relaxed(cnt);
      if (!layer && k == 0) red_release(&g_cnt[(C_C + 3) * 32]);
      TS(16 + layer * 56 + 40 + 7 + k);
    };
    if (warp == 12) {
      if (elect_one()) {
#pragma unroll 1
        for (int layer = 0; layer < 2; layer++) {
          auto ld_xe = [&](int c) {
            const uint32_t b = bar + 8 * (B_XF + c);
            mbar_expect(b, PG);
            if (layer == 0) tma_ld(sb + x_page(0, c) * PG, &p.mapX, c * 64, rb * 64, b);
            else tma_ld(sb + x_page(0, c) * PG, &p.mapXT, rb * 64, DM + c * 64, b);
          };
          if (layer == 0) {
            ld_x0(0, 2); ld_w(2); ld_x0(1, 2);
            if (hg >= 3) {
              mbar_expect(bar + 8 * B_SC, PG);
              tma_ld(sb + P_R * PG, &p.mapX, hg * 64, rb * 64, bar + 8 * B_SC);
            }
            if (rb < 4) tma_prefetch3(&p.mapW3, hg * 64, (4 + rb) * 64, 0);
            ld_x0(0, 3); ld_w(3); ld_x0(1, 3); ld_x0(0, 4); ld_x0(1, 4);
            done(0, 0, 0); done(1, 0, 0);
            ld_w(4);
            ld_x0(1, 5); ld_x0(1, 6); ld_x0(1, 7);
            done(0, 1, 0); done(1, 1, 0);
            ld_w(5);
            if (rb < 8) tma_prefetch5(&p.mapWo, hg * 64, rb * 2);
            done(0, 2, 0);
            fence_async_smem();
            ld_xe(5); ld_xe(6); ld_xe(7);
          } else {
            mbar_wait(bar + 8 * B_PDONE, 0);
            mbar_wait(bar + 8 * (B_PDONE + 1), 0);
            mbar_wait(bar + 8 * B_U, 0);
            ld_w(0); ld_w(1);
            mbar_wait(bar + 8 * B_U1, 0);
            fence_async_smem();
            ld_w(2);
            mbar_wait(bar + 8 * (B_PUB + 2), 0);
            fence_async_smem();
            ld_w(3);
            spin_until(&g_cnt[(C_C + 3) * 32], ((lds32(sb + SM_EP) / NCTA) + 1) * NCTA);
            fence_async_global();
            if (hg >= 3) {
              mbar_expect(bar + 8 * B_SC, PG);
              tma_ld(sb + P_R * PG, &p.mapXT, rb * 64, DM + hg * 64, bar + 8 * B_SC);
            }
            ld_xe(4);
            done(0, 2, 1);
            fence_async_smem();
            ld_xe(5); ld_xe(6); ld_xe(7);
            done(1, 0, 1);
            ld_w(4);
            done(1, 1, 1);
            ld_w(5);
          }
          done(1, 2, layer);
          fence_async_smem();
          ld_w(6); ld_w(7);
          auto ld_res = [&](int half) {
            const uint32_t b = bar + 8 * (B_RF + half);
            mbar_expect(b, PG);
            if (layer == 0) tma_ld(sb + (half ? 2 : P_R) * PG, &p.mapX, hg * 64, (16 * half + rb) * 64, b);
            else tma_ld(sb + (half ? 2 : P_R) * PG, &p.mapXT, (16 * half + rb) * 64, DM + hg * 64, b);
          };
          done(0, 4, layer); done(1, 3, layer);
          fence_async_smem();
          mbar_expect(bar + 8 * B_WOF, 8 * PG);
#pragma unroll 1
          for (int c = 0; c < 8; c++) {
            if (c == 5) { ld_res(0); done(1, 4, layer); }
            tma_ld5(sb + wo_page(c) * PG, &p.mapWo, hg * 64, c * 2, bar + 8 * B_WOF);
          }
          done(0, 7, layer);
          fence_async_global();
          ld_res(1);
          if (layer) mbar_wait(bar + 8 * B_RS, 0);
          fence_async_global();
#pragma unroll
          for (int half = 0; half < 2; half++) {
            float* stats = g_stats + (layer * 32 + 16 * half + rb) * 192;
            unsigned* cnt = &g_cnt[(C_G + 2 * layer + half) * 32];
            mbar_wait(bar + 8 * (B_STG + half), layer);
            tma_st(&p.mapXT, (16 * half + rb) * 64, 2 * layer * DM + hg * 64, sb + (P_R + half) * PG);
            bulk_red_add_f32(stats, sb + (half ? SM_KGT : SM_STG), 768);
            bulk_commit();
            red_relaxed(cnt);
            if (half == 0) mbar_arrive(bar + 8 * B_PG);
            bulk_wait_read();
            mbar_arrive(bar + 8 * (B_PST + half));
          }
        }
      }
    } else if (warp == 13) {
      mbar_wait(bar + 8 * B_EP, 0);
      const unsigned e1 = (lds32(sb + SM_EP) / NCTA) + 1;
      auto ld_o = [&](int layer) {
#pragma unroll 1
        for (int half = 0; half < 2; half++) {
          done(1, 7, layer);
          mbar_wait(bar + 8 * B_OST, layer);
          if (half) mbar_wait(bar + 8 * (B_OST + 1), layer);
          fence_async_smem();
#pragma unroll
          for (int c = 0; c < 4; c++) mbar_expect(bar + 8 * (B_OF + 4 * half + c), 2 * PG);
          const bf16* src = g_O + (layer * 32 + 16 * half + rb) * 4 * PG;
          uint32_t dst0 = sb + o_page(half, 0) * PG;
          pin(src); pin(dst0);
          spin_hint(&g_cnt[(C_O + layer * 32 + 16 * half + rb) * 32], e1 * 32);
#pragma unroll
          for (int c = 0; c < 4; c++) {
            if (c == 2 && half && layer) { mbar_wait(bar + 8 * B_AL, 0); fence_async_smem(); }
            bulk_ld(c ? sb + o_page(half, c) * PG : dst0, src + c * PG, 2 * PG, bar + 8 * (B_OF + 4 * half + c));
          }
        }
      };
      if (elect_one()) {
        mbar_wait(bar + 8 * (B_WF + 2), 0);
        asm volatile("prefetch.tensormap [%0];" ::"l"(&p.mapXT) : "memory");
        asm volatile("prefetch.tensormap [%0];" ::"l"(&p.mapWo) : "memory");
        spin_until(&g_cnt[C_Z * 32], e1 * NCTA);
        mbar_arrive(bar + 8 * B_ZF);
        TS(3);
        ld_o(0);
#pragma unroll 1
        for (int k = 0; k < 3; k++) {
          mbar_wait(bar + 8 * (B_PUB + k), 0);
          if (k == 2) {
#pragma unroll 1
            for (int c = 0; c < 4; c++) mbar_wait(bar + 8 * (B_XF + c), 1);
          }
          fence_async_smem();
          uint32_t b = bar + 8 * (B_XR + 4 * (k & 1)), dst = sb + (k ? 4 + 4 * k : 0) * PG, c0 = ((k ? 16 : 0) + rb) * 64, c1 = DM + (k & 2) * 128;
#pragma unroll
          for (int c = 0; c < 4; c++) mbar_expect(b + 8 * c, PG);
          pin(b); pin(dst); pin(c0); pin(c1);
          spin_hint(&g_cnt[(C_C + k) * 32], e1 * NCTA);
          TS(10 + k);
#pragma unroll
          for (int c = 0; c < 4; c++) tma_ld(dst + c * PG, &p.mapXT, c0, c1 + c * 64, b + 8 * c);
        }
        ld_o(1);
#pragma unroll 1
        for (int k = 0; k < 2; k++) {
          mbar_wait(bar + 8 * (B_PUB + k), 1);
          spin_hint(&g_cnt[(C_F + 8 * k + (cta >> 4)) * 32], e1 * 16);
          mbar_arrive(bar + 8 * (B_TF + k));
        }
      }
    } else if (warp == 14) {
      mbar_wait(bar + 8 * B_EP, 0);
      const unsigned e1 = (lds32(sb + SM_EP) / NCTA) + 1;
      done(0, 1, 0);
      {
        const uint2* cp = g_colsum + (hg * 192 + lane);
        uint2 v[6];
        bool ok;
        int it = 0;
        do {
          ok = true;
#pragma unroll
          for (int i = 0; i < 6; i++) {
            asm volatile("ld.relaxed.gpu.global.v2.u32 {%0,%1}, [%2];" : "=r"(v[i].x), "=r"(v[i].y) : "l"(cp + 32 * i) : "memory");
            ok = ok && v[i].y == e1;
          }
          if (++it > (1 << 22)) __trap();
        } while (!__all_sync(~0u, ok));
#pragma unroll
        for (int i = 0; i < 6; i++) sts32f(sb + SM_CS + 4 * (lane + 32 * i), __uint_as_float(v[i].x));
      }
      __syncwarp();
      if (elect_one()) {
        mbar_wait(bar + 8 * B_ZF, 0);
        mbar_arrive(bar + 8 * B_LN);
        red_relaxed(&g_cnt[C_CS * 32]);
        TS(13);
#pragma unroll 1
        for (int layer = 0; layer < 2; layer++) {
          const uint32_t b = bar + 8 * (B_GB + 1);
          const bf16* xin = g_xT + ((size_t)2 * layer * DM + 2 * cta) * LSEQ + 1024;
          const float* stats = g_stats + (layer * 32 + 16) * 192;
          mbar_wait(bar + 8 * B_PST, layer);
          spin_hint(&g_cnt[(C_G + 2 * layer) * 32], e1 * NCTA);
          mbar_arrive(bar + 8 * B_GB);
          mbar_wait(bar + 8 * (B_PST + 1), layer);
          fence_async_smem();
          mbar_expect(b, 12288 + PG);
          pin(stats); pin(xin);
          spin_hint(&g_cnt[(C_G + 2 * layer + 1) * 32], e1 * NCTA);
          bulk_ld(sb + CV_ST, stats, 12288, b);
#pragma unroll
          for (int lc = 0; lc < 4; lc++) bulk_ld(sb + cv_x(1, lc), xin + cv_chan(0, lc) * LSEQ, 2048, b);
          TS(14 + layer);
          publish(layer, 1);
        }
      }
    } else {
      const uint4 u = make_uint4(UNSET, UNSET, UNSET, UNSET);
      if (lane < 24) stg128((uint4*)g_stats + cta * 24 + lane, make_uint4(0, 0, 0, 0));
      if (lane < 16) stg128(g_rows + LSEQ + cta * 16 + lane, make_uint4(0, 0, 0, 0));
#pragma unroll 4
      for (int i = 0; i < 16; i++) stg128(g_halo + cta * 512 + 32 * i + lane, u);
#pragma unroll 4
      for (int i = 0; i < 16; i++) stg128(((i & 8) ? (uint4*)g_xT : (uint4*)g_O) + cta * 1024 + (i & 7) * 128 + (lane >> 1) * 8 + (lane & 1), u);
      __syncwarp();
      if (elect_one()) red_release(&g_cnt[C_Z * 32]);
      __syncwarp();
#pragma unroll 1
      for (int layer = 0; layer < 2; layer++) {
        auto reset_done = [&](int s) {
          spin_until(&g_cnt[(C_R + s) * 32], (lds32(sb + SM_EP) / NCTA) * 4 + 4);
          mbar_arrive(bar + 8 * (s == 1 ? B_LN : s == 2 ? B_RS : B_RC));
          if (s) TS(16 + 40 + 9 + s);
        };
        if (layer && elect_one()) reset_done(1);
        __syncwarp();
#pragma unroll 1
        for (int half = 0; half < 2; half++) {
          done(half, 2, layer);
          const uint4* src = g_rows + (layer * LSEQ + (16 * half + rb) * 64 + (opaque_tid() & 31));
          uint4 a, b;
          int it = 0;
          do {
            a = ld_tagged(src); b = ld_tagged(src + 32);
          } while (!__all_sync(~0u, (a.z | a.w) == __float_as_uint(8.f) && (b.z | b.w) == __float_as_uint(8.f)) && ++it < (1 << 20));
          float m0 = __uint_as_float(a.x) * (1.f / DM), m1 = __uint_as_float(b.x) * (1.f / DM);
          float r0 = rsqrt_approx(fmaxf(__uint_as_float(a.y) * (1.f / DM) - m0 * m0, 0.f) + 1e-5f);
          float r1 = rsqrt_approx(fmaxf(__uint_as_float(b.y) * (1.f / DM) - m1 * m1, 0.f) + 1e-5f);
          if (half) done(0, 7, layer);
          const uint32_t dst = sb + ln_off(half) + ((lane >> 4) * 8 + (lane & 7)) * 16 + (lane & 8);
          asm volatile("st.shared.v2.f32 [%0], {%1,%2};" ::"r"(dst), "f"(m0), "f"(r0) : "memory");
          asm volatile("st.shared.v2.f32 [%0], {%1,%2};" ::"r"(dst + 256), "f"(m1), "f"(r1) : "memory");
          __syncwarp();
          if (elect_one()) { mbar_arrive(bar + 8 * (B_LN + half)); TS(16 + layer * 56 + 40 + 14 + half); }
        }
        if (layer && lane < 16) stg128(g_rows + cta * 16 + (opaque_tid() & 31), make_uint4(0, 0, 0, 0));
        if (elect_one()) {
          if (layer) reset_done(2);
          reset_done(3 * layer);
          publish(layer, 0);
          if (!layer) publish(layer, 2);
        }
        __syncwarp();
      }
    }
  }
}

typedef CUresult (*EncodeFn)(CUtensorMap*, CUtensorMapDataType, cuuint32_t, void*, const cuuint64_t*, const cuuint64_t*,
                             const cuuint32_t*, const cuuint32_t*, CUtensorMapInterleave, CUtensorMapSwizzle,
                             CUtensorMapL2promotion, CUtensorMapFloatOOBfill);

static void make_map(EncodeFn enc, CUtensorMap* m, void* ptr, uint64_t cols, uint64_t rows, uint32_t box_rows) {
  cuuint64_t dims[2] = {cols, rows};
  cuuint64_t strides[1] = {cols * 2};
  cuuint32_t box[2] = {64, box_rows};
  cuuint32_t es[2] = {1, 1};
  enc(m, CU_TENSOR_MAP_DATA_TYPE_BFLOAT16, 2, ptr, dims, strides, box, es, CU_TENSOR_MAP_INTERLEAVE_NONE,
      CU_TENSOR_MAP_SWIZZLE_128B, CU_TENSOR_MAP_L2_PROMOTION_L2_128B, CU_TENSOR_MAP_FLOAT_OOB_FILL_NONE);
}
static void make_map3(EncodeFn enc, CUtensorMap* m, void* ptr, uint64_t d0, uint64_t cols, uint64_t rows, uint64_t blk_stride,
                      uint64_t nblocks, uint32_t nblk) {
  cuuint64_t dims[3] = {d0, rows, nblocks};
  cuuint64_t strides[2] = {cols * 2, blk_stride * 2};
  cuuint32_t box[3] = {64, 64, nblk};
  cuuint32_t es[3] = {1, 1, 1};
  enc(m, CU_TENSOR_MAP_DATA_TYPE_BFLOAT16, 3, ptr, dims, strides, box, es, CU_TENSOR_MAP_INTERLEAVE_NONE,
      CU_TENSOR_MAP_SWIZZLE_128B, CU_TENSOR_MAP_L2_PROMOTION_L2_128B, CU_TENSOR_MAP_FLOAT_OOB_FILL_NONE);
}

extern "C" void kernel_launch(void* const* d_in, const int* in_sizes, int n_in, void* d_out, int out_size) {
  static Params prm;
  static void* cached[13] = {nullptr};
  static bool attr_done = false;
  static int grid = NCTA + 4;
  bool same = attr_done && cached[12] == d_out;
  for (int i = 0; i < 12 && same; i++) same = cached[i] == d_in[i];
  if (!same) {
    void* fn = nullptr;
    cudaDriverEntryPointQueryResult qr;
    cudaGetDriverEntryPoint("cuTensorMapEncodeTiled", &fn, cudaEnableDefault, &qr);
    EncodeFn enc = (EncodeFn)fn;
    void* pXT;
    cudaGetSymbolAddress(&pXT, g_xT);
    make_map(enc, &prm.mapX, d_in[0], DM, LSEQ, 64);
    make_map(enc, &prm.mapXT, pXT, LSEQ, 4 * DM, 64);
    {
      cuuint64_t dims[5] = {DM, 2, 4, 4, 16};
      cuuint64_t strides[4] = {DM * 2, 8 * DM * 2, 2 * DM * 2, 32 * DM * 2};
      cuuint32_t box[5] = {64, 2, 4, 4, 2};
      cuuint32_t es[5] = {1, 1, 1, 1, 1};
      enc(&prm.mapWo, CU_TENSOR_MAP_DATA_TYPE_BFLOAT16, 5, d_in[2], dims, strides, box, es, CU_TENSOR_MAP_INTERLEAVE_NONE,
          CU_TENSOR_MAP_SWIZZLE_128B, CU_TENSOR_MAP_L2_PROMOTION_L2_128B, CU_TENSOR_MAP_FLOAT_OOB_FILL_NONE);
    }
    make_map3(enc, &prm.mapW3, d_in[1], DM, 3 * DM, DM, DM, 3, 3);
    prm.out = (bf16*)d_out;
    prm.a_re = (const bf16*)d_in[4]; prm.a_im = (const bf16*)d_in[5];
    prm.b_re = (const bf16*)d_in[6]; prm.b_im = (const bf16*)d_in[7];
    prm.c_re = (const bf16*)d_in[8]; prm.c_im = (const bf16*)d_in[9];
    prm.log_dt = (const bf16*)d_in[10]; prm.dskip = (const bf16*)d_in[11];
    int dev = 0, sms = 0;
    cudaGetDevice(&dev);
    cudaDeviceGetAttribute(&sms, cudaDevAttrMultiProcessorCount, dev);
    grid = sms >= NCTA + 4 ? NCTA + 4 : NCTA + 5;
    cudaFuncSetAttribute(fused_kernel, cudaFuncAttributeMaxDynamicSharedMemorySize, SM_TOTAL);
    for (int i = 0; i < 12; i++) cached[i] = d_in[i];
    cached[12] = d_out;
    attr_done = true;
  }
  fused_kernel<<<grid, NTHREADS, SM_TOTAL>>>(prm);
}
```

```cpp
#include <cuda_runtime.h>
#include <cuda_bf16.h>
#include <cuda.h>
#include <stdint.h>

typedef __nv_bfloat16 bf16;

constexpr int LSEQ = 2048;
constexpr int DM = 512;
constexpr int NCTA = 128;
constexpr int NTHREADS = 512;
#define R_CONS 200
#define R_HELP 88
#define R_AGENT 24
#define TURN0 4
#define TURN1 4

constexpr int PG = 8192;
constexpr int P_R = 25;
__host__ __device__ constexpr int x_page(int half, int c) { return half ? 8 + c : c < 5 ? c : c - 5; }
__host__ __device__ constexpr int w_page(int c) { return (c & 3) < 3 ? 16 + 3 * (c & 3) : c < 4 ? 5 : 8; }
__host__ __device__ constexpr int wo_page(int c) { return c < 5 ? 3 + c : 11 + c; }
__host__ __device__ constexpr int o_page(int half, int pair) { return half ? (pair ? 25 - 2 * pair : 0) : 8 + 2 * pair; }
constexpr int SM_KGB = (P_R + 1) * PG;
constexpr int SM_KC = 27 * PG;
constexpr int KC_STRIDE = 648;
__host__ __device__ constexpr int kc_off(int lc) { return SM_KC + (lc & 1) * 2 * KC_STRIDE + (lc < 2 ? 3328 : 0); }
constexpr int SM_KGT = SM_KC + 3328 + 2592;
constexpr int SM_CS = SM_KGT + 2048;
constexpr int SM_RED = SM_CS + 768;
constexpr int SM_EP = SM_RED + 16;
constexpr int SM_STG = SM_RED + 32;
constexpr int SM_LN = SM_STG + 768;
__host__ __device__ constexpr int ln_off(int half) { return half ? PG + 4096 : SM_LN; }
constexpr int SM_BAR = SM_LN + 512;
constexpr int SM_TS = SM_BAR + 704;
constexpr int SM_TOTAL = SM_TS + 512;
static_assert(SM_TOTAL <= 232448 && SM_STG % 16 == 0 && SM_KGT % 16 == 0, "shared memory");

constexpr int CV_UH = 140 * 16;
__host__ __device__ constexpr int cv_u(int lc) { return (8 + 2 * lc) * PG; }
__host__ __device__ constexpr int cv_pe(int lc, int early) { return early ? 19 * PG + lc * 4480 : cv_u(lc) + 4480; }
__host__ __device__ constexpr int cv_pb1(int lc, int w) { return w ? cv_u(lc) + 8960 + (w - 1) * 2048 : 7 * PG + lc * 2048; }
__host__ __device__ constexpr int cv_fa(int lc) { return cv_pb1(lc, 1) + 128; }
__host__ __device__ constexpr int cv_dump(int lc) { return cv_u(lc) + 16256; }
__host__ __device__ constexpr int cv_pb0(int lc, int w) { return lc * PG + w * 2048; }
__host__ __device__ constexpr int cv_se(int lc) { return 5 * PG + lc * 4096; }
__host__ __device__ constexpr int cv_so(int lc) { return cv_se(lc) + 2048; }
__host__ __device__ constexpr int cv_x(int half, int lc) { return (P_R + half) * PG + lc * 2048; }
constexpr int CV_ST = 22 * PG;
__host__ __device__ constexpr int cv_chan(int cta, int lc) { return 2 * cta + (lc & 1) + 256 * (lc >> 1); }

enum {
  B_XF = 0,
  B_WF = 16,
  B_OF = 24,
  B_DN = 32,
  B_PG = 46,
  B_XR = 48,
  B_RF = 56,
  B_PST = 58,
  B_GB = 60,
  B_TF = 62,
  B_RT = 64,
  B_RS = 66,
  B_RC = 67,
  B_WOF = 68,
  B_ZF = 69,
  B_EP = 70,
  B_KG = 71,
  B_SC = 37,
  B_LN = 72,
  B_END = 38,
  B_STG = 74,
  B_OST = 76,
  B_PDONE = 78,
  B_PE = 80,
  B_U = 81,
  B_U1 = 82,
  B_PUB = 83,
  B_AL = 86,
  B_COUNT = 87
};

enum {
  C_CS = 0,
  C_G = 1,
  C_C = 5,
  C_O = 21,
  C_Z = 85,
  C_R = 86,
  C_F = 90,
  C_COUNT = 106
};

__device__ unsigned g_cnt[C_COUNT * 32];
__device__ __align__(1024) bf16 g_O[2 * LSEQ * DM];
__device__ __align__(1024) bf16 g_xT[4 * DM * LSEQ];
__device__ __align__(1024) float g_stats[2 * 32 * 192];
__device__ __align__(1024) uint2 g_colsum[3 * DM];
__device__ __align__(1024) uint4 g_halo[32 * 8 * 256];
__device__ __align__(1024) uint4 g_rows[2 * LSEQ];
#define TS(i) do { } while (0)
#define TSW(k) do { if ((threadIdx.x & 127) == 0) TS(16 + layer * 56 + (threadIdx.x >> 7) * 20 + (k)); } while (0)
#define TSG(k) do { } while (0)

#define RETRY(i) do { } while (0)
#define LTS(i) do { } while (0)
#define LTE() do { } while (0)

struct Params {
  CUtensorMap mapX, mapW3, mapXT, mapWo;
  bf16* out;
  const bf16 *a_re, *a_im, *b_re, *b_im, *c_re, *c_im, *log_dt, *dskip;
};

__device__ __forceinline__ uint32_t s32(const void* p) { return (uint32_t)__cvta_generic_to_shared(p); }
__device__ __forceinline__ void mbar_init(uint32_t b, int c) { asm volatile("mbarrier.init.shared::cta.b64 [%0], %1;" ::"r"(b), "r"(c) : "memory"); }
__device__ __forceinline__ void mbar_expect(uint32_t b, int bytes) { asm volatile("mbarrier.arrive.expect_tx.shared::cta.b64 _, [%0], %1;" ::"r"(b), "r"(bytes) : "memory"); }
__device__ __forceinline__ void mbar_arrive(uint32_t b) { asm volatile("mbarrier.arrive.shared::cta.b64 _, [%0];" ::"r"(b) : "memory"); }
__device__ __forceinline__ void mbar_wait(uint32_t b, int parity) {
  asm volatile("{\n.reg .pred p;\nWAIT_LOOP:\nmbarrier.try_wait.parity.shared::cta.b64 p, [%0], %1;\n@p bra WAIT_DONE;\nbra WAIT_LOOP;\nWAIT_DONE:\n}" ::"r"(b), "r"(parity) : "memory");
}
__device__ __forceinline__ bool mbar_test(uint32_t b, int parity) {
  uint32_t ok;
  asm volatile("{\n.reg .pred p;\nmbarrier.test_wait.parity.shared::cta.b64 p, [%1], %2;\nselp.u32 %0, 1, 0, p;\n}" : "=r"(ok) : "r"(b), "r"(parity) : "memory");
  return ok != 0;
}
__device__ __forceinline__ int opaque_tid() { int v; asm volatile("mov.u32 %0, %%tid.x;" : "=r"(v)); return v; }
__device__ __forceinline__ bool elect_one() {
  uint32_t r;
  asm volatile("{\n.reg .pred p;\nelect.sync _|p, 0xffffffff;\nselp.u32 %0, 1, 0, p;\n}" : "=r"(r));
  return r != 0;
}
__device__ __forceinline__ void tma_ld(uint32_t dst, const CUtensorMap* m, int c0, int c1, uint32_t bar) {
  asm volatile("cp.async.bulk.tensor.2d.shared::cluster.global.mbarrier::complete_tx::bytes [%0], [%1, {%3, %4}], [%2];"
               ::"r"(dst), "l"(m), "r"(bar), "r"(c0), "r"(c1) : "memory");
}
__device__ __forceinline__ void tma_ld3(uint32_t dst, const CUtensorMap* m, int c0, int c1, int c2, uint32_t bar) {
  asm volatile("cp.async.bulk.tensor.3d.shared::cluster.global.mbarrier::complete_tx::bytes [%0], [%1, {%3, %4, %5}], [%2];"
               ::"r"(dst), "l"(m), "r"(bar), "r"(c0), "r"(c1), "r"(c2) : "memory");
}
__device__ __forceinline__ void tma_ld5(uint32_t dst, const CUtensorMap* m, int c0, int c4, uint32_t bar) {
  asm volatile("cp.async.bulk.tensor.5d.shared::cluster.global.mbarrier::complete_tx::bytes [%0], [%1, {%3, 0, 0, 0, %4}], [%2];"
               ::"r"(dst), "l"(m), "r"(bar), "r"(c0), "r"(c4) : "memory");
}
__device__ __forceinline__ void tma_prefetch5(const CUtensorMap* m, int c0, int c4) {
  asm volatile("cp.async.bulk.prefetch.tensor.5d.L2.global.tile [%0, {%1, 0, 0, 0, %2}];" ::"l"(m), "r"(c0), "r"(c4) : "memory");
}
__device__ __forceinline__ void tma_prefetch3(const CUtensorMap* m, int c0, int c1, int c2) {
  asm volatile("cp.async.bulk.prefetch.tensor.3d.L2.global.tile [%0, {%1, %2, %3}];" ::"l"(m), "r"(c0), "r"(c1), "r"(c2) : "memory");
}
__device__ __forceinline__ void tma_st(const CUtensorMap* m, int c0, int c1, uint32_t src) {
  asm volatile("cp.async.bulk.tensor.2d.global.shared::cta.bulk_group [%0, {%2, %3}], [%1];" ::"l"(m), "r"(src), "r"(c0), "r"(c1) : "memory");
}
__device__ __forceinline__ void bulk_ld(uint32_t dst, const void* src, int bytes, uint32_t bar) {
  asm volatile("cp.async.bulk.shared::cluster.global.mbarrier::complete_tx::bytes [%0], [%1], %2, [%3];" ::"r"(dst), "l"(src), "r"(bytes), "r"(bar) : "memory");
}
__device__ __forceinline__ void bulk_red_add_f32(void* dst, uint32_t src, int bytes) {
  asm volatile("cp.reduce.async.bulk.global.shared::cta.bulk_group.add.f32 [%0], [%1], %2;" ::"l"(dst), "r"(src), "r"(bytes) : "memory");
}
__device__ __forceinline__ void bulk_commit() { asm volatile("cp.async.bulk.commit_group;" ::: "memory"); }
__device__ __forceinline__ void fence_async_smem() { asm volatile("fence.proxy.async.shared::cta;" ::: "memory"); }
__device__ __forceinline__ void fence_async_global() { asm volatile("fence.proxy.async.global;" ::: "memory"); }
__device__ __forceinline__ void bar_sync(int id, int n) { asm volatile("bar.sync %0, %1;" ::"r"(id), "r"(n) : "memory"); }
__device__ __forceinline__ void bar_arrive(int id, int n) { asm volatile("bar.arrive %0, %1;" ::"r"(id), "r"(n) : "memory"); }
__device__ __forceinline__ bool bar_or(int id, int n, bool v) {
  uint32_t r;
  asm volatile("{\n.reg .pred p, q;\nsetp.ne.u32 q, %3, 0;\nbar.red.or.pred p, %1, %2, q;\nselp.u32 %0, 1, 0, p;\n}" : "=r"(r) : "r"(id), "r"(n), "r"((uint32_t)v) : "memory");
  return r != 0;
}
__device__ __forceinline__ void bulk_wait_read() { asm volatile("cp.async.bulk.wait_group.read 0;" ::: "memory"); }
__device__ __forceinline__ void stg128(void* p, uint4 v) { asm volatile("st.relaxed.gpu.global.v4.u32 [%0], {%1,%2,%3,%4};" ::"l"(p), "r"(v.x), "r"(v.y), "r"(v.z), "r"(v.w) : "memory"); }
constexpr uint32_t UNSET = 0xffffffffu;
constexpr int MAX_RETRY = 1 << 16;
__device__ __forceinline__ void wg_fence() { asm volatile("wgmma.fence.sync.aligned;" ::: "memory"); }
__device__ __forceinline__ void wg_commit() { asm volatile("wgmma.commit_group.sync.aligned;" ::: "memory"); }
template <int N> __device__ __forceinline__ void wg_wait() { asm volatile("wgmma.wait_group.sync.aligned %0;" ::"n"(N) : "memory"); }
__device__ __forceinline__ uint64_t mkdesc(uint32_t addr, uint32_t lbo, uint32_t sbo, int sw) {
  return (uint64_t)((addr & 0x3FFFF) >> 4) | ((uint64_t)(lbo >> 4) << 16) | ((uint64_t)(sbo >> 4) << 32) | ((uint64_t)sw << 62);
}
__device__ __forceinline__ void ldsm4(uint32_t* r, uint32_t a) {
  asm volatile("ldmatrix.sync.aligned.m8n8.x4.shared.b16 {%0,%1,%2,%3}, [%4];" : "=r"(r[0]), "=r"(r[1]), "=r"(r[2]), "=r"(r[3]) : "r"(a) : "memory");
}
__device__ __forceinline__ void ldsm4t(uint32_t* r, uint32_t a) {
  asm volatile("ldmatrix.sync.aligned.m8n8.x4.trans.shared.b16 {%0,%1,%2,%3}, [%4];" : "=r"(r[0]), "=r"(r[1]), "=r"(r[2]), "=r"(r[3]) : "r"(a) : "memory");
}
__device__ __forceinline__ void stsm4(uint32_t a, uint32_t r0, uint32_t r1, uint32_t r2, uint32_t r3) {
  asm volatile("stmatrix.sync.aligned.m8n8.x4.shared.b16 [%0], {%1,%2,%3,%4};" ::"r"(a), "r"(r0), "r"(r1), "r"(r2), "r"(r3) : "memory");
}
__device__ __forceinline__ void stsm4t(uint32_t a, uint32_t r0, uint32_t r1, uint32_t r2, uint32_t r3) {
  asm volatile("stmatrix.sync.aligned.m8n8.x4.trans.shared.b16 [%0], {%1,%2,%3,%4};" ::"r"(a), "r"(r0), "r"(r1), "r"(r2), "r"(r3) : "memory");
}
__device__ __forceinline__ uint32_t movm_t(uint32_t a) { uint32_t r; asm volatile("movmatrix.sync.aligned.m8n8.trans.b16 %0, %1;" : "=r"(r) : "r"(a)); return r; }
__device__ __forceinline__ uint32_t lds32(uint32_t a) { uint32_t v; asm volatile("ld.shared.b32 %0, [%1];" : "=r"(v) : "r"(a) : "memory"); return v; }
__device__ __forceinline__ float2 lds64f(uint32_t a) { float2 v; asm volatile("ld.shared.v2.f32 {%0,%1}, [%2];" : "=f"(v.x), "=f"(v.y) : "r"(a) : "memory"); return v; }
__device__ __forceinline__ float4 lds128f(uint32_t a) { float4 v; asm volatile("ld.shared.v4.f32 {%0,%1,%2,%3}, [%4];" : "=f"(v.x), "=f"(v.y), "=f"(v.z), "=f"(v.w) : "r"(a) : "memory"); return v; }
__device__ __forceinline__ uint4 lds128(uint32_t a) { uint4 v; asm volatile("ld.shared.v4.b32 {%0,%1,%2,%3}, [%4];" : "=r"(v.x), "=r"(v.y), "=r"(v.z), "=r"(v.w) : "r"(a) : "memory"); return v; }
__device__ __forceinline__ void sts128(uint32_t a, uint4 v) { asm volatile("st.shared.v4.b32 [%0], {%1,%2,%3,%4};" ::"r"(a), "r"(v.x), "r"(v.y), "r"(v.z), "r"(v.w) : "memory"); }
__device__ __forceinline__ void sts128f(uint32_t a, float x, float y, float z, float w) { asm volatile("st.shared.v4.f32 [%0], {%1,%2,%3,%4};" ::"r"(a), "f"(x), "f"(y), "f"(z), "f"(w) : "memory"); }
__device__ __forceinline__ void sts32f(uint32_t a, float v) { asm volatile("st.shared.f32 [%0], %1;" ::"r"(a), "f"(v) : "memory"); }
__device__ __forceinline__ void sts16(uint32_t a, uint16_t v) { asm volatile("st.shared.u16 [%0], %1;" ::"r"(a), "h"(v) : "memory"); }
__device__ __forceinline__ uint32_t lds16(uint32_t a) { uint16_t v; asm volatile("ld.shared.u16 %0, [%1];" : "=h"(v) : "r"(a) : "memory"); return v; }
__device__ __forceinline__ uint32_t packbf(float lo, float hi) { uint32_t r; asm("cvt.rn.bf16x2.f32 %0, %1, %2;" : "=r"(r) : "f"(hi), "f"(lo)); return r; }
__device__ __forceinline__ float bf_lo(uint32_t v) { return __uint_as_float(v << 16); }
__device__ __forceinline__ float bf_hi(uint32_t v) { return __uint_as_float(v & 0xffff0000u); }
__device__ __forceinline__ float ex2(float x) { float r; asm("ex2.approx.ftz.f32 %0, %1;" : "=f"(r) : "f"(x)); return r; }
__device__ __forceinline__ float rsqrt_approx(float x) { float r; asm("rsqrt.approx.ftz.f32 %0, %1;" : "=f"(r) : "f"(x)); return r; }
__device__ __forceinline__ float rcp_approx(float x) { float r; asm("rcp.approx.ftz.f32 %0, %1;" : "=f"(r) : "f"(x)); return r; }
__device__ __forceinline__ void mma_bf16(float* d, const uint32_t* a, uint32_t b0, uint32_t b1) {
  asm("mma.sync.aligned.m16n8k16.row.col.f32.bf16.bf16.f32 {%0,%1,%2,%3}, {%4,%5,%6,%7}, {%8,%9}, {%0,%1,%2,%3};"
               : "+f"(d[0]), "+f"(d[1]), "+f"(d[2]), "+f"(d[3]) : "r"(a[0]), "r"(a[1]), "r"(a[2]), "r"(a[3]), "r"(b0), "r"(b1));
}
__device__ __forceinline__ void mma_bf16_c(float* d, const uint32_t* a, uint32_t b0, uint32_t b1, const float* c) {
  asm("mma.sync.aligned.m16n8k16.row.col.f32.bf16.bf16.f32 {%0,%1,%2,%3}, {%4,%5,%6,%7}, {%8,%9}, {%10,%11,%12,%13};"
               : "=f"(d[0]), "=f"(d[1]), "=f"(d[2]), "=f"(d[3]) : "r"(a[0]), "r"(a[1]), "r"(a[2]), "r"(a[3]), "r"(b0), "r"(b1),
                 "f"(c[0]), "f"(c[1]), "f"(c[2]), "f"(c[3]));
}
__device__ __forceinline__ void mma_rowsum(float* d, uint32_t a0, uint32_t a1) {
  asm("mma.sync.aligned.m16n8k8.row.col.f32.bf16.bf16.f32 {%0,%1,%2,%3}, {%4,%5}, {%6}, {%7,%7,%7,%7};"
               : "=f"(d[0]), "=f"(d[1]), "=f"(d[2]), "=f"(d[3]) : "r"(a0), "r"(a1), "r"(0x3f803f80u), "f"(0.f));
}
__device__ __forceinline__ void red_release(unsigned* p) { asm volatile("red.release.gpu.global.add.u32 [%0], 1;" ::"l"(p) : "memory"); }
__device__ __forceinline__ void red_relaxed(unsigned* p) { asm volatile("red.relaxed.gpu.global.add.u32 [%0], 1;" ::"l"(p) : "memory"); }
__device__ __forceinline__ unsigned ld_relaxed(const unsigned* p) { unsigned v; asm volatile("ld.relaxed.gpu.global.u32 %0, [%1];" : "=r"(v) : "l"(p) : "memory"); return v; }
__device__ __forceinline__ void spin_until(const unsigned* p, unsigned target) {
  int it = 0;
  while ((int)(ld_relaxed(p) - target) < 0) {
    if (++it > (1 << 23)) __trap();
  }
}
template <typename T> __device__ __forceinline__ void pin(T*& p) { asm volatile("" : "+l"(p) :: "memory"); }
__device__ __forceinline__ void pin(uint32_t& v) { asm volatile("" : "+r"(v) :: "memory"); }
__device__ __forceinline__ void spin_hint(const unsigned* p, unsigned target) {
  spin_until(p, target);
}
__device__ __forceinline__ uint4 ld_tagged(const uint4* p) { uint4 v; asm volatile("ld.relaxed.gpu.global.v4.u32 {%0,%1,%2,%3}, [%4];" : "=r"(v.x), "=r"(v.y), "=r"(v.z), "=r"(v.w) : "l"(p) : "memory"); return v; }
__device__ __forceinline__ uint32_t hadd2(uint32_t a, uint32_t b) { uint32_t r; asm("add.rn.bf16x2 %0, %1, %2;" : "=r"(r) : "r"(a), "r"(b)); return r; }

__device__ __forceinline__ uint32_t hfma2(uint32_t a, uint32_t b, uint32_t c) { uint32_t r; asm("fma.rn.bf16x2 %0, %1, %2, %3;" : "=r"(r) : "r"(a), "r"(b), "r"(c)); return r; }
__device__ __forceinline__ void sts32(uint32_t a, uint32_t v) { asm volatile("st.shared.u32 [%0], %1;" ::"r"(a), "r"(v) : "memory"); }

template <int N> __device__ __forceinline__ void acc_fence(float* a) {
#pragma unroll
  for (int i = 0; i < N; i++) asm volatile("" : "+f"(a[i]) :: "memory");
}

template<int N,int TB> __device__ __forceinline__ void wgmma_rs(float* d, const uint32_t* a, uint64_t db, int sd);
template<int N,int TA,int TB> __device__ __forceinline__ void wgmma_ss(float* d, uint64_t da, uint64_t db, int sd);
template<> __device__ __forceinline__ void wgmma_rs<64,0>(float* d, const uint32_t* a, uint64_t db, int sd) {
  asm volatile("{\n.reg .pred p;\nsetp.ne.b32 p, %37, 0;\nwgmma.mma_async.sync.aligned.m64n64k16.f32.bf16.bf16 {%0,%1,%2,%3,%4,%5,%6,%7,%8,%9,%10,%11,%12,%13,%14,%15,%16,%17,%18,%19,%20,%21,%22,%23,%24,%25,%26,%27,%28,%29,%30,%31}, {%32,%33,%34,%35}, %36, p, 1, 1, 0;\n}\n"
   : "+f"(d[0]),"+f"(d[1]),"+f"(d[2]),"+f"(d[3]),"+f"(d[4]),"+f"(d[5]),"+f"(d[6]),"+f"(d[7]),"+f"(d[8]),"+f"(d[9]),"+f"(d[10]),"+f"(d[11]),"+f"(d[12]),"+f"(d[13]),"+f"(d[14]),"+f"(d[15]),"+f"(d[16]),"+f"(d[17]),"+f"(d[18]),"+f"(d[19]),"+f"(d[20]),"+f"(d[21]),"+f"(d[22]),"+f"(d[23]),"+f"(d[24]),"+f"(d[25]),"+f"(d[26]),"+f"(d[27]),"+f"(d[28]),"+f"(d[29]),"+f"(d[30]),"+f"(d[31])
   : "r"(a[0]), "r"(a[1]), "r"(a[2]), "r"(a[3]), "l"(db), "r"(sd));
}
template<> __device__ __forceinline__ void wgmma_rs<56,0>(float* d, const uint32_t* a, uint64_t db, int sd) {
  asm volatile("{\n.reg .pred p;\nsetp.ne.b32 p, %33, 0;\nwgmma.mma_async.sync.aligned.m64n56k16.f32.bf16.bf16 {%0,%1,%2,%3,%4,%5,%6,%7,%8,%9,%10,%11,%12,%13,%14,%15,%16,%17,%18,%19,%20,%21,%22,%23,%24,%25,%26,%27}, {%28,%29,%30,%31}, %32, p, 1, 1, 0;\n}\n"
   : "+f"(d[0]),"+f"(d[1]),"+f"(d[2]),"+f"(d[3]),"+f"(d[4]),"+f"(d[5]),"+f"(d[6]),"+f"(d[7]),"+f"(d[8]),"+f"(d[9]),"+f"(d[10]),"+f"(d[11]),"+f"(d[12]),"+f"(d[13]),"+f"(d[14]),"+f"(d[15]),"+f"(d[16]),"+f"(d[17]),"+f"(d[18]),"+f"(d[19]),"+f"(d[20]),"+f"(d[21]),"+f"(d[22]),"+f"(d[23]),"+f"(d[24]),"+f"(d[25]),"+f"(d[26]),"+f"(d[27])
   : "r"(a[0]), "r"(a[1]), "r"(a[2]), "r"(a[3]), "l"(db), "r"(sd));
}
template<> __device__ __forceinline__ void wgmma_rs<48,0>(float* d, const uint32_t* a, uint64_t db, int sd) {
  asm volatile("{\n.reg .pred p;\nsetp.ne.b32 p, %29, 0;\nwgmma.mma_async.sync.aligned.m64n48k16.f32.bf16.bf16 {%0,%1,%2,%3,%4,%5,%6,%7,%8,%9,%10,%11,%12,%13,%14,%15,%16,%17,%18,%19,%20,%21,%22,%23}, {%24,%25,%26,%27}, %28, p, 1, 1, 0;\n}\n"
   : "+f"(d[0]),"+f"(d[1]),"+f"(d[2]),"+f"(d[3]),"+f"(d[4]),"+f"(d[5]),"+f"(d[6]),"+f"(d[7]),"+f"(d[8]),"+f"(d[9]),"+f"(d[10]),"+f"(d[11]),"+f"(d[12]),"+f"(d[13]),"+f"(d[14]),"+f"(d[15]),"+f"(d[16]),"+f"(d[17]),"+f"(d[18]),"+f"(d[19]),"+f"(d[20]),"+f"(d[21]),"+f"(d[22]),"+f"(d[23])
   : "r"(a[0]), "r"(a[1]), "r"(a[2]), "r"(a[3]), "l"(db), "r"(sd));
}
template<> __device__ __forceinline__ void wgmma_rs<40,0>(float* d, const uint32_t* a, uint64_t db, int sd) {
  asm volatile("{\n.reg .pred p;\nsetp.ne.b32 p, %25, 0;\nwgmma.mma_async.sync.aligned.m64n40k16.f32.bf16.bf16 {%0,%1,%2,%3,%4,%5,%6,%7,%8,%9,%10,%11,%12,%13,%14,%15,%16,%17,%18,%19}, {%20,%21,%22,%23}, %24, p, 1, 1, 0;\n}\n"
   : "+f"(d[0]),"+f"(d[1]),"+f"(d[2]),"+f"(d[3]),"+f"(d[4]),"+f"(d[5]),"+f"(d[6]),"+f"(d[7]),"+f"(d[8]),"+f"(d[9]),"+f"(d[10]),"+f"(d[11]),"+f"(d[12]),"+f"(d[13]),"+f"(d[14]),"+f"(d[15]),"+f"(d[16]),"+f"(d[17]),"+f"(d[18]),"+f"(d[19])
   : "r"(a[0]), "r"(a[1]), "r"(a[2]), "r"(a[3]), "l"(db), "r"(sd));
}
template<> __device__ __forceinline__ void wgmma_rs<32,0>(float* d, const uint32_t* a, uint64_t db, int sd) {
  asm volatile("{\n.reg .pred p;\nsetp.ne.b32 p, %21, 0;\nwgmma.mma_async.sync.aligned.m64n32k16.f32.bf16.bf16 {%0,%1,%2,%3,%4,%5,%6,%7,%8,%9,%10,%11,%12,%13,%14,%15}, {%16,%17,%18,%19}, %20, p, 1, 1, 0;\n}\n"
   : "+f"(d[0]),"+f"(d[1]),"+f"(d[2]),"+f"(d[3]),"+f"(d[4]),"+f"(d[5]),"+f"(d[6]),"+f"(d[7]),"+f"(d[8]),"+f"(d[9]),"+f"(d[10]),"+f"(d[11]),"+f"(d[12]),"+f"(d[13]),"+f"(d[14]),"+f"(d[15])
   : "r"(a[0]), "r"(a[1]), "r"(a[2]), "r"(a[3]), "l"(db), "r"(sd));
}
template<> __device__ __forceinline__ void wgmma_rs<24,0>(float* d, const uint32_t* a, uint64_t db, int sd) {
  asm volatile("{\n.reg .pred p;\nsetp.ne.b32 p, %17, 0;\nwgmma.mma_async.sync.aligned.m64n24k16.f32.bf16.bf16 {%0,%1,%2,%3,%4,%5,%6,%7,%8,%9,%10,%11}, {%12,%13,%14,%15}, %16, p, 1, 1, 0;\n}\n"
   : "+f"(d[0]),"+f"(d[1]),"+f"(d[2]),"+f"(d[3]),"+f"(d[4]),"+f"(d[5]),"+f"(d[6]),"+f"(d[7]),"+f"(d[8]),"+f"(d[9]),"+f"(d[10]),"+f"(d[11])
   : "r"(a[0]), "r"(a[1]), "r"(a[2]), "r"(a[3]), "l"(db), "r"(sd));
}
template<> __device__ __forceinline__ void wgmma_rs<16,0>(float* d, const uint32_t* a, uint64_t db, int sd) {
  asm volatile("{\n.reg .pred p;\nsetp.ne.b32 p, %13, 0;\nwgmma.mma_async.sync.aligned.m64n16k16.f32.bf16.bf16 {%0,%1,%2,%3,%4,%5,%6,%7}, {%8,%9,%10,%11}, %12, p, 1, 1, 0;\n}\n"
   : "+f"(d[0]),"+f"(d[1]),"+f"(d[2]),"+f"(d[3]),"+f"(d[4]),"+f"(d[5]),"+f"(d[6]),"+f"(d[7])
   : "r"(a[0]), "r"(a[1]), "r"(a[2]), "r"(a[3]), "l"(db), "r"(sd));
}
template<> __device__ __forceinline__ void wgmma_rs<8,0>(float* d, const uint32_t* a, uint64_t db, int sd) {
  asm volatile("{\n.reg .pred p;\nsetp.ne.b32 p, %9, 0;\nwgmma.mma_async.sync.aligned.m64n8k16.f32.bf16.bf16 {%0,%1,%2,%3}, {%4,%5,%6,%7}, %8, p, 1, 1, 0;\n}\n"
   : "+f"(d[0]),"+f"(d[1]),"+f"(d[2]),"+f"(d[3])
   : "r"(a[0]), "r"(a[1]), "r"(a[2]), "r"(a[3]), "l"(db), "r"(sd));
}
template<> __device__ __forceinline__ void wgmma_ss<64,1,0>(float* d, uint64_t da, uint64_t db, int sd) {
  asm volatile("{\n.reg .pred p;\nsetp.ne.b32 p, %34, 0;\nwgmma.mma_async.sync.aligned.m64n64k16.f32.bf16.bf16 {%0,%1,%2,%3,%4,%5,%6,%7,%8,%9,%10,%11,%12,%13,%14,%15,%16,%17,%18,%19,%20,%21,%22,%23,%24,%25,%26,%27,%28,%29,%30,%31}, %32, %33, p, 1, 1, 1, 0;\n}\n"
   : "+f"(d[0]),"+f"(d[1]),"+f"(d[2]),"+f"(d[3]),"+f"(d[4]),"+f"(d[5]),"+f"(d[6]),"+f"(d[7]),"+f"(d[8]),"+f"(d[9]),"+f"(d[10]),"+f"(d[11]),"+f"(d[12]),"+f"(d[13]),"+f"(d[14]),"+f"(d[15]),"+f"(d[16]),"+f"(d[17]),"+f"(d[18]),"+f"(d[19]),"+f"(d[20]),"+f"(d[21]),"+f"(d[22]),"+f"(d[23]),"+f"(d[24]),"+f"(d[25]),"+f"(d[26]),"+f"(d[27]),"+f"(d[28]),"+f"(d[29]),"+f"(d[30]),"+f"(d[31])
   : "l"(da), "l"(db), "r"(sd));
}
template<> __device__ __forceinline__ void wgmma_ss<64,0,1>(float* d, uint64_t da, uint64_t db, int sd) {
  asm volatile("{\n.reg .pred p;\nsetp.ne.b32 p, %34, 0;\nwgmma.mma_async.sync.aligned.m64n64k16.f32.bf16.bf16 {%0,%1,%2,%3,%4,%5,%6,%7,%8,%9,%10,%11,%12,%13,%14,%15,%16,%17,%18,%19,%20,%21,%22,%23,%24,%25,%26,%27,%28,%29,%30,%31}, %32, %33, p, 1, 1, 0, 1;\n}\n"
   : "+f"(d[0]),"+f"(d[1]),"+f"(d[2]),"+f"(d[3]),"+f"(d[4]),"+f"(d[5]),"+f"(d[6]),"+f"(d[7]),"+f"(d[8]),"+f"(d[9]),"+f"(d[10]),"+f"(d[11]),"+f"(d[12]),"+f"(d[13]),"+f"(d[14]),"+f"(d[15]),"+f"(d[16]),"+f"(d[17]),"+f"(d[18]),"+f"(d[19]),"+f"(d[20]),"+f"(d[21]),"+f"(d[22]),"+f"(d[23]),"+f"(d[24]),"+f"(d[25]),"+f"(d[26]),"+f"(d[27]),"+f"(d[28]),"+f"(d[29]),"+f"(d[30]),"+f"(d[31])
   : "l"(da), "l"(db), "r"(sd));
}
template<> __device__ __forceinline__ void wgmma_ss<192,0,1>(float* d, uint64_t da, uint64_t db, int sd) {
  asm volatile("{\n.reg .pred p;\nsetp.ne.b32 p, %98, 0;\nwgmma.mma_async.sync.aligned.m64n192k16.f32.bf16.bf16 {%0,%1,%2,%3,%4,%5,%6,%7,%8,%9,%10,%11,%12,%13,%14,%15,%16,%17,%18,%19,%20,%21,%22,%23,%24,%25,%26,%27,%28,%29,%30,%31,%32,%33,%34,%35,%36,%37,%38,%39,%40,%41,%42,%43,%44,%45,%46,%47,%48,%49,%50,%51,%52,%53,%54,%55,%56,%57,%58,%59,%60,%61,%62,%63,%64,%65,%66,%67,%68,%69,%70,%71,%72,%73,%74,%75,%76,%77,%78,%79,%80,%81,%82,%83,%84,%85,%86,%87,%88,%89,%90,%91,%92,%93,%94,%95}, %96, %97, p, 1, 1, 0, 1;\n}\n"
   : "+f"(d[0]),"+f"(d[1]),"+f"(d[2]),"+f"(d[3]),"+f"(d[4]),"+f"(d[5]),"+f"(d[6]),"+f"(d[7]),"+f"(d[8]),"+f"(d[9]),"+f"(d[10]),"+f"(d[11]),"+f"(d[12]),"+f"(d[13]),"+f"(d[14]),"+f"(d[15]),"+f"(d[16]),"+f"(d[17]),"+f"(d[18]),"+f"(d[19]),"+f"(d[20]),"+f"(d[21]),"+f"(d[22]),"+f"(d[23]),"+f"(d[24]),"+f"(d[25]),"+f"(d[26]),"+f"(d[27]),"+f"(d[28]),"+f"(d[29]),"+f"(d[30]),"+f"(d[31]),"+f"(d[32]),"+f"(d[33]),"+f"(d[34]),"+f"(d[35]),"+f"(d[36]),"+f"(d[37]),"+f"(d[38]),"+f"(d[39]),"+f"(d[40]),"+f"(d[41]),"+f"(d[42]),"+f"(d[43]),"+f"(d[44]),"+f"(d[45]),"+f"(d[46]),"+f"(d[47]),"+f"(d[48]),"+f"(d[49]),"+f"(d[50]),"+f"(d[51]),"+f"(d[52]),"+f"(d[53]),"+f"(d[54]),"+f"(d[55]),"+f"(d[56]),"+f"(d[57]),"+f"(d[58]),"+f"(d[59]),"+f"(d[60]),"+f"(d[61]),"+f"(d[62]),"+f"(d[63]),"+f"(d[64]),"+f"(d[65]),"+f"(d[66]),"+f"(d[67]),"+f"(d[68]),"+f"(d[69]),"+f"(d[70]),"+f"(d[71]),"+f"(d[72]),"+f"(d[73]),"+f"(d[74]),"+f"(d[75]),"+f"(d[76]),"+f"(d[77]),"+f"(d[78]),"+f"(d[79]),"+f"(d[80]),"+f"(d[81]),"+f"(d[82]),"+f"(d[83]),"+f"(d[84]),"+f"(d[85]),"+f"(d[86]),"+f"(d[87]),"+f"(d[88]),"+f"(d[89]),"+f"(d[90]),"+f"(d[91]),"+f"(d[92]),"+f"(d[93]),"+f"(d[94]),"+f"(d[95])
   : "l"(da), "l"(db), "r"(sd));
}
template<> __device__ __forceinline__ void wgmma_ss<192,1,1>(float* d, uint64_t da, uint64_t db, int sd) {
  asm volatile("{\n.reg .pred p;\nsetp.ne.b32 p, %98, 0;\nwgmma.mma_async.sync.aligned.m64n192k16.f32.bf16.bf16 {%0,%1,%2,%3,%4,%5,%6,%7,%8,%9,%10,%11,%12,%13,%14,%15,%16,%17,%18,%19,%20,%21,%22,%23,%24,%25,%26,%27,%28,%29,%30,%31,%32,%33,%34,%35,%36,%37,%38,%39,%40,%41,%42,%43,%44,%45,%46,%47,%48,%49,%50,%51,%52,%53,%54,%55,%56,%57,%58,%59,%60,%61,%62,%63,%64,%65,%66,%67,%68,%69,%70,%71,%72,%73,%74,%75,%76,%77,%78,%79,%80,%81,%82,%83,%84,%85,%86,%87,%88,%89,%90,%91,%92,%93,%94,%95}, %96, %97, p, 1, 1, 1, 1;\n}\n"
   : "+f"(d[0]),"+f"(d[1]),"+f"(d[2]),"+f"(d[3]),"+f"(d[4]),"+f"(d[5]),"+f"(d[6]),"+f"(d[7]),"+f"(d[8]),"+f"(d[9]),"+f"(d[10]),"+f"(d[11]),"+f"(d[12]),"+f"(d[13]),"+f"(d[14]),"+f"(d[15]),"+f"(d[16]),"+f"(d[17]),"+f"(d[18]),"+f"(d[19]),"+f"(d[20]),"+f"(d[21]),"+f"(d[22]),"+f"(d[23]),"+f"(d[24]),"+f"(d[25]),"+f"(d[26]),"+f"(d[27]),"+f"(d[28]),"+f"(d[29]),"+f"(d[30]),"+f"(d[31]),"+f"(d[32]),"+f"(d[33]),"+f"(d[34]),"+f"(d[35]),"+f"(d[36]),"+f"(d[37]),"+f"(d[38]),"+f"(d[39]),"+f"(d[40]),"+f"(d[41]),"+f"(d[42]),"+f"(d[43]),"+f"(d[44]),"+f"(d[45]),"+f"(d[46]),"+f"(d[47]),"+f"(d[48]),"+f"(d[49]),"+f"(d[50]),"+f"(d[51]),"+f"(d[52]),"+f"(d[53]),"+f"(d[54]),"+f"(d[55]),"+f"(d[56]),"+f"(d[57]),"+f"(d[58]),"+f"(d[59]),"+f"(d[60]),"+f"(d[61]),"+f"(d[62]),"+f"(d[63]),"+f"(d[64]),"+f"(d[65]),"+f"(d[66]),"+f"(d[67]),"+f"(d[68]),"+f"(d[69]),"+f"(d[70]),"+f"(d[71]),"+f"(d[72]),"+f"(d[73]),"+f"(d[74]),"+f"(d[75]),"+f"(d[76]),"+f"(d[77]),"+f"(d[78]),"+f"(d[79]),"+f"(d[80]),"+f"(d[81]),"+f"(d[82]),"+f"(d[83]),"+f"(d[84]),"+f"(d[85]),"+f"(d[86]),"+f"(d[87]),"+f"(d[88]),"+f"(d[89]),"+f"(d[90]),"+f"(d[91]),"+f"(d[92]),"+f"(d[93]),"+f"(d[94]),"+f"(d[95])
   : "l"(da), "l"(db), "r"(sd));
}

template <bool TR>
__device__ __forceinline__ void gemm_section(float* acc, float& mean0, float& mean1, float& rstd0, float& rstd1,
                                             uint32_t sb, int blk, int hg, int wg, int w, int lane) {
  constexpr int layer = TR ? 1 : 0;
  constexpr int TURN = TR ? TURN1 : TURN0;
  constexpr int LSTAT = TURN < 4 ? TURN - 1 : 3;
  const uint32_t bar = sb + SM_BAR;
  const int g = lane >> 2, t = lane & 3;
  const bool leader = (w == 0) && (lane == 0);
  const int statpos = hg < 3 ? 1 : wg ? LSTAT : TR ? 3 : 2;
  const bool copy = hg >= 3 && wg == 0;
  const int cut = wg ? TURN : 4;
  auto wait_full = [&](int c) {
    mbar_wait(bar + 8 * (B_XF + 8 * wg + c), layer);
    mbar_wait(bar + 8 * (B_WF + c), layer);
  };
  auto peek = [&](int c) {
    const bool x = mbar_test(bar + 8 * (B_XF + 8 * wg + c), layer), y = mbar_test(bar + 8 * (B_WF + c), layer);
    return x && y;
  };
  const uint64_t da0 = mkdesc(sb, TR ? 8192 : 16, 1024, 1), db0 = mkdesc(sb, 8192, 1024, 1);
  uint32_t xt = wg ? 0xfedcba98u : 0x21043210u;
  uint64_t wt = 0x0816131005161310ull;
  uint64_t da = da0 + ((xt & 15) << 9), db = db0 + (16 << 9);
  auto issue = [&](int c, int first) {
    wg_fence();
#pragma unroll
    for (int ks = 0; ks < 4; ks++) wgmma_ss<192, TR ? 1 : 0, 1>(acc, da + (TR ? ks * 128 : ks * 2), db + ks * 128, !first || ks != 0);
    wg_commit();
    xt >>= 4; wt >>= 8;
    da = da0 + ((xt & 15) << 9); db = db0 + (((uint32_t)wt & 31) << 9);
  };
  wait_full(0);
  bool ready = peek(1);
  issue(0, 1);
  TSW(0);
#pragma unroll 1
  for (int c = 1; c < cut; c++) {
    if (!ready) wait_full(c);
    issue(c, 0);
    ready = peek(c + 1);
    wg_wait<1>();
    if (leader) mbar_arrive(bar + 8 * (B_DN + 8 * wg + c - 1));
    if (wg == 1 && c == cut - 1) {
      wg_wait<0>();
      if (leader) mbar_arrive(bar + 8 * (B_DN + 8 + c));
    }
    if (c == statpos) {
      mbar_wait(bar + 8 * (copy ? B_SC : B_XF + 8 * wg + hg), layer);
      uint32_t A[16];
      const uint32_t xb = sb + (copy ? P_R : 8 * wg + hg) * PG;
#pragma unroll
      for (int ks = 0; ks < 4; ks++) {
        if (!TR) {
          const int row = 16 * w + (lane & 15), kc = 2 * ks + (lane >> 4);
          ldsm4(&A[4 * ks], xb + row * 128 + ((kc ^ (row & 7)) << 4));
        } else {
          const int k = 16 * ks + (lane & 7) + 8 * (lane >> 4), pc = 2 * w + ((lane >> 3) & 1);
          ldsm4t(&A[4 * ks], xb + k * 128 + ((pc ^ (k & 7)) << 4));
        }
      }
      float s0 = 0.f, q0 = 0.f, s1 = 0.f, q1 = 0.f;
#pragma unroll
      for (int i = 0; i < 16; i += 2) {
        const float a = bf_lo(A[i]), b = bf_hi(A[i]), c_ = bf_lo(A[i + 1]), d = bf_hi(A[i + 1]);
        s0 += a + b; q0 = fmaf(a, a, q0); q0 = fmaf(b, b, q0);
        s1 += c_ + d; q1 = fmaf(c_, c_, q1); q1 = fmaf(d, d, q1);
      }
#pragma unroll
      for (int o = 1; o <= 2; o <<= 1) {
        s0 += __shfl_xor_sync(~0u, s0, o); q0 += __shfl_xor_sync(~0u, q0, o);
        s1 += __shfl_xor_sync(~0u, s1, o); q1 += __shfl_xor_sync(~0u, q1, o);
      }
      if (t < 2)
        asm volatile("red.relaxed.gpu.global.add.v4.f32 [%0], {%1,%2,%3,%4};" ::"l"(g_rows + layer * LSEQ + blk * 64 + 16 * w + g + 8 * t),
                     "f"(t ? s1 : s0), "f"(t ? q1 : q0), "f"(1.f), "f"(0.f) : "memory");
    }
  }
  if (wg == 1) {
#pragma unroll 1
    for (int c = cut; c < 8; c++) wait_full(c);
    ready = true;
    bar_sync(5, 256);
  }
#pragma unroll 1
  for (int c = cut; c < 8; c++) {
    if (!ready) wait_full(c);
    issue(c, 0);
    if (wg == 1) {
      wg_wait<2>();
      if (leader && c >= cut + 2) mbar_arrive(bar + 8 * (B_DN + 8 + c - 2));
    } else if (c == 7) {
      bar_arrive(5, 256);
    } else {
      ready = peek(c + 1);
      wg_wait<1>();
      if (leader && c < 6) mbar_arrive(bar + 8 * (B_DN + c - 1));
    }
  }
  mbar_wait(bar + 8 * (B_LN + wg), layer);
  const float4 ln = lds128f(sb + ln_off(wg) + (8 * w + g) * 16);
  mean0 = ln.x; rstd0 = ln.y; mean1 = ln.z; rstd1 = ln.w;
  wg_wait<0>();
  acc_fence<96>(acc);
  if (leader) mbar_arrive(bar + 8 * (B_DN + 8 * wg + 7));
}

__device__ __forceinline__ void attn_phase(const Params& p, uint32_t sb, int layer, int rb, int hg, int wg, int w) {
  const int lane = opaque_tid() & 31;
  const int g = lane >> 2, t = lane & 3;
  const uint32_t bar = sb + SM_BAR;
  const int blk = 16 * wg + rb;
  float acc[96];
  float2 cs[24];
  float mean0, mean1, rstd0, rstd1;
  if (layer) gemm_section<true>(acc, mean0, mean1, rstd0, rstd1, sb, blk, hg, wg, w, lane);
  else gemm_section<false>(acc, mean0, mean1, rstd0, rstd1, sb, blk, hg, wg, w, lane);
  TSW(1);
#pragma unroll
  for (int j = 8; j < 24; j++) cs[j] = lds64f(sb + SM_CS + 4 * (8 * j + 2 * t));
  const uint32_t kvx = sb + (wg ? 22 : 0) * PG;

  uint32_t kb[4][8], vb[4][8], qa[4][4];
  {
    const float nm0 = -mean0 * rstd0, nm1 = -mean1 * rstd1;
    const int st_row = 16 * w + (lane & 7) + 8 * ((lane >> 3) & 1);
    const uint32_t st_base = kvx + st_row * 256;
    const bool sender = (w == 3 && blk < 31);
    uint4* halo = &g_halo[(blk * 8 + hg) * 256 + lane];
    uint32_t r[4][2][4];
#pragma unroll
    for (int h = 0; h < 4; h++) {
#pragma unroll
      for (int kv = 0; kv < 2; kv++) {
#pragma unroll
        for (int dh = 0; dh < 2; dh++) {
          const int j = 8 + kv * 8 + 2 * h + dh;
          const float2 c2 = cs[j];
          const float v0 = fmaf(acc[4 * j + 0], rstd0, nm0 * c2.x), v1 = fmaf(acc[4 * j + 1], rstd0, nm0 * c2.y);
          const float v2 = fmaf(acc[4 * j + 2], rstd1, nm1 * c2.x), v3 = fmaf(acc[4 * j + 3], rstd1, nm1 * c2.y);
          r[h][kv][2 * dh] = packbf(v0, v1);
          r[h][kv][2 * dh + 1] = packbf(v2, v3);
        }
      }
      if (sender) {
        stg128(halo + (2 * h) * 32, make_uint4(r[h][0][0], r[h][0][2], r[h][0][1], r[h][0][3]));
        stg128(halo + (2 * h + 1) * 32, make_uint4(r[h][1][0], r[h][1][1], r[h][1][2], r[h][1][3]));
      }
    }
#pragma unroll
    for (int j = 0; j < 8; j++) cs[j] = lds64f(sb + SM_CS + 4 * (8 * j + 2 * t));
    mbar_wait(bar + 8 * (B_DN + 7), layer);
#pragma unroll
    for (int h = 0; h < 4; h++) {
#pragma unroll
      for (int kv = 0; kv < 2; kv++) {
        const int chunk = 4 * h + 2 * kv + (lane >> 4);
        if (w < 3) stsm4(st_base + (((chunk & 8) | ((chunk ^ st_row) & 7)) << 4), r[h][kv][0], r[h][kv][1], r[h][kv][2], r[h][kv][3]);
      }
      kb[h][4] = r[h][0][0]; kb[h][5] = r[h][0][2]; kb[h][6] = r[h][0][1]; kb[h][7] = r[h][0][3];
      vb[h][4] = movm_t(r[h][1][0]); vb[h][5] = movm_t(r[h][1][1]); vb[h][6] = movm_t(r[h][1][2]); vb[h][7] = movm_t(r[h][1][3]);
    }
#pragma unroll
    for (int h = 0; h < 4; h++) {
#pragma unroll
      for (int dh = 0; dh < 2; dh++) {
        const int j = 2 * h + dh;
        const float2 c2 = cs[j];
        qa[h][2 * dh] = packbf(fmaf(-mean0, c2.x, acc[4 * j + 0]), fmaf(-mean0, c2.y, acc[4 * j + 1]));
        qa[h][2 * dh + 1] = packbf(fmaf(-mean1, c2.x, acc[4 * j + 2]), fmaf(-mean1, c2.y, acc[4 * j + 3]));
      }
    }
  }
  bar_sync(2 + wg, 128);
  TSW(2);
  {
    const uint32_t prev_base = kvx + (16 * w - 16) * 256;
    const int mi = lane >> 3;
    const int r = 8 * (mi >> 1) + (lane & 7), r2 = 8 * (mi & 1) + (lane & 7);
    if (w != 0) {
#pragma unroll
      for (int h = 0; h < 4; h++) {
        const int ch = 4 * h + (mi & 1), ch2 = 4 * h + 2 + (mi >> 1);
        ldsm4(&kb[h][0], prev_base + r * 256 + (((ch & 8) | ((ch ^ r) & 7)) << 4));
        ldsm4t(&vb[h][0], prev_base + r2 * 256 + (((ch2 & 8) | ((ch2 ^ r2) & 7)) << 4));
      }
    } else if (blk > 0) {
      uint4* src = &g_halo[((blk - 1) * 8 + hg) * 256 + lane];
      uint4 hv[8];
      int it = 0;
      bool ok;
      do {
        ok = true;
#pragma unroll
        for (int i = 0; i < 8; i++) hv[i] = ld_tagged(src + i * 32);
#pragma unroll
        for (int i = 0; i < 8; i++) ok = ok && hv[i].x != UNSET;
      } while (!__all_sync(~0u, ok) && ++it < (1 << 20));
      if (layer == 0) {
#pragma unroll
        for (int i = 0; i < 2; i++) stg128(src + i * 128 + (lane >> 1) * 6, make_uint4(UNSET, UNSET, UNSET, UNSET));
      }
#pragma unroll
      for (int h = 0; h < 4; h++) {
        kb[h][0] = hv[2 * h].x; kb[h][1] = hv[2 * h].y; kb[h][2] = hv[2 * h].z; kb[h][3] = hv[2 * h].w;
        vb[h][0] = movm_t(hv[2 * h + 1].x); vb[h][1] = movm_t(hv[2 * h + 1].y);
        vb[h][2] = movm_t(hv[2 * h + 1].z); vb[h][3] = movm_t(hv[2 * h + 1].w);
      }
    } else {
#pragma unroll
      for (int h = 0; h < 4; h++)
#pragma unroll
        for (int k = 0; k < 4; k++) kb[h][k] = vb[h][k] = 0u;
    }
    TSW(3);
  }
  uint4* op = (uint4*)g_O + ((layer * 32 + blk) * 8 + hg) * 512 + 64 * t + 16 * w + g;
  unsigned* ocnt = &g_cnt[(C_O + layer * 32 + blk) * 32];
  pin(op); pin(ocnt);
  const int e = t - (g >> 1);
  const bool par = g & 1, epos = e >= 1;
  uint32_t selA = par ? 0x1044u : 0x4410u, selB0 = epos ? (par ? 0x3244u : 0x4432u) : 0x4444u, selB1 = epos ? 0x4444u : (par ? 0x3244u : 0x4432u);
  const float cl2 = 0.25f * 1.4426950408889634f;
  const float sc0 = rstd0 * cl2, sc1 = rstd1 * cl2;
  float c0[4];
  uint32_t zero[8];
#pragma unroll
  for (int k = 0; k < 4; k++) asm volatile("mov.b32 %0, %1;" : "=f"(c0[k]) : "f"((blk == 0 && w == 0) ? -INFINITY : 0.f));
#pragma unroll
  for (int k = 0; k < 8; k++) asm volatile("and.b32 %0, %1, 0x80000000;" : "=r"(zero[k]) : "r"(opaque_tid()));
  pin(selA); pin(selB0); pin(selB1);
  mbar_wait(bar + 8 * (B_DN + 15), layer);
  TSW(4);

  float vA0[4], vB0[4], vA1[4], vB1[4];
#pragma unroll
  for (int h = 0; h < 4; h++) {
    float S[4][4];
#pragma unroll
    for (int j = 0; j < 4; j++) {
      S[j][0] = S[j][1] = S[j][2] = S[j][3] = 0.f;
      if (j < 2) mma_bf16_c(S[j], qa[h], kb[h][2 * j], kb[h][2 * j + 1], c0);
      else mma_bf16(S[j], qa[h], kb[h][2 * j], kb[h][2 * j + 1]);
    }
    vA0[h] = par ? S[1][1] : S[1][0];
    vB0[h] = epos ? (par ? S[0][1] : S[0][0]) : (par ? S[2][1] : S[2][0]);
    vA1[h] = par ? S[2][3] : S[2][2];
    vB1[h] = epos ? (par ? S[1][3] : S[1][2]) : (par ? S[3][3] : S[3][2]);
  }
  float m0[4], m1[4];
#pragma unroll
  for (int h = 0; h < 4; h++) { m0[h] = fmaxf(vA0[h], vB0[h]); m1[h] = fmaxf(vA1[h], vB1[h]); }
#pragma unroll
  for (int o = 1; o <= 2; o <<= 1) {
#pragma unroll
    for (int h = 0; h < 4; h++) {
      m0[h] = fmaxf(m0[h], __shfl_xor_sync(~0u, m0[h], o));
      m1[h] = fmaxf(m1[h], __shfl_xor_sync(~0u, m1[h], o));
    }
  }
  float O0[4][4], O1[4][4], Z[4][4];
#pragma unroll
  for (int h = 0; h < 4; h++) {
    const float mm0 = -m0[h] * sc0, mm1 = -m1[h] * sc1;
    const float pA0 = ex2(fmaf(vA0[h], sc0, mm0)), pB0 = ex2(fmaf(vB0[h], sc0, mm0));
    const float pA1 = ex2(fmaf(vA1[h], sc1, mm1)), pB1 = ex2(fmaf(vB1[h], sc1, mm1));
    const uint32_t h0 = packbf(pA0, pB0), h1 = packbf(pA1, pB1);
    const uint32_t P0[4] = {__byte_perm(h0, 0, selB0), zero[2 * h], __byte_perm(h0, 0, selA), __byte_perm(h1, 0, selB0)};
    const uint32_t P1[4] = {__byte_perm(h0, 0, selB1), __byte_perm(h1, 0, selA), zero[2 * h + 1], __byte_perm(h1, 0, selB1)};
#pragma unroll
    for (int k = 0; k < 4; k++) O0[h][k] = O1[h][k] = 0.f;
    mma_rowsum(Z[h], h0, h1);
    mma_bf16(O0[h], P0, vb[h][0], vb[h][1]); mma_bf16(O1[h], P0, vb[h][2], vb[h][3]);
    mma_bf16(O0[h], P1, vb[h][4], vb[h][5]); mma_bf16(O1[h], P1, vb[h][6], vb[h][7]);
  }
  if (lane == 0) mbar_arrive(bar + 8 * (B_OST + wg));
#pragma unroll
  for (int h = 0; h < 4; h += 2) {
    const float i0 = rcp_approx(Z[h][0]), i1 = rcp_approx(Z[h][2]), j0 = rcp_approx(Z[h + 1][0]), j1 = rcp_approx(Z[h + 1][2]);
    stg128(op + 128 * h, make_uint4(packbf(O0[h][0] * i0, O0[h][1] * i0), packbf(O1[h][0] * i0, O1[h][1] * i0),
                                   packbf(O0[h + 1][0] * j0, O0[h + 1][1] * j0), packbf(O1[h + 1][0] * j0, O1[h + 1][1] * j0)));
    stg128(op + 128 * h + 8, make_uint4(packbf(O0[h][2] * i1, O0[h][3] * i1), packbf(O1[h][2] * i1, O1[h][3] * i1),
                                            packbf(O0[h + 1][2] * j1, O0[h + 1][3] * j1), packbf(O1[h + 1][2] * j1, O1[h + 1][3] * j1)));
  }
  TSW(5);
  __syncwarp();
  if (elect_one()) red_relaxed(ocnt);
  TSW(6);
}

__device__ __forceinline__ void conv_load(uint32_t* A, uint32_t pe);
__device__ __forceinline__ void proj_phase(const Params& p, uint32_t sb, int layer, int rb, int q, uint32_t* A0, uint32_t* A1) {
  const int lane = opaque_tid() & 31;
  const int wg = __shfl_sync(~0u, opaque_tid() >> 7, 0), w = __shfl_sync(~0u, (opaque_tid() >> 5) & 3, 0);
  const bool TR = layer != 0;
  const int t = lane & 3;
  const uint32_t bar = sb + SM_BAR;
  const uint32_t rbx = sb + (P_R + wg) * PG;
  const uint32_t rsrc = sb + (wg ? 2 : P_R) * PG;
  const int blk = 16 * wg + rb;
  mbar_wait(bar + 8 * (B_RF + wg), layer);
  mbar_wait(bar + 8 * B_WOF, layer);
  const uint32_t stg = sb + (wg ? SM_KGT : SM_STG);
  if (layer) {
    const uint32_t pe = sb + cv_pe(wg, 1) + 4 * (16 + 16 * w + (lane >> 2) - 2 * t);
    mbar_wait(bar + 8 * B_PE, 1);
    conv_load(A0, pe);
    conv_load(A1, pe + 2 * 4480);
    __syncwarp();
    if (lane == 0) mbar_arrive(bar + 8 * B_AL);
  } else {
#pragma unroll
    for (int i = 0; i < 68; i++) {
      asm volatile("mov.b32 %0, 0;" : "=r"(A0[i]));
      asm volatile("mov.b32 %0, 0;" : "=r"(A1[i]));
    }
  }
  bool clean = false, staged = false;
#pragma unroll 1
  for (int attempt = 0; attempt < MAX_RETRY; attempt++) {
  uint32_t res[16];
  if (!TR) {
#pragma unroll
    for (int j = 0; j < 8; j += 2) {
      const int mi = lane >> 3;
      const int row = 16 * w + (lane & 7) + 8 * (mi & 1), ch = j + (mi >> 1);
      ldsm4(&res[2 * j], rsrc + row * 128 + ((ch ^ (row & 7)) << 4));
    }
  } else {
#pragma unroll
    for (int j = 0; j < 8; j += 2) {
      const int mi = lane >> 3;
      const int line = 8 * (j + (mi >> 1)) + (lane & 7), pc = 2 * w + (mi & 1);
      ldsm4t(&res[2 * j], rsrc + line * 128 + ((pc ^ (line & 7)) << 4));
    }
  }
  float acc[32];
#pragma unroll
  for (int j = 0; j < 16; j++) { acc[2 * j] = bf_lo(res[j]); acc[2 * j + 1] = bf_hi(res[j]); }
  acc_fence<32>(acc);
  if (wg) mbar_wait(bar + 8 * B_PG, layer);
  const int wg2 = __shfl_sync(~0u, opaque_tid() >> 7, 0);
  const uint64_t da0 = mkdesc(sb, 1024, 128, 0), db0 = mkdesc(sb, 8192, 1024, 1);
#pragma unroll
  for (int c = 0; c < 4; c++) {
    mbar_wait(bar + 8 * (B_OF + 4 * wg + c), layer);
    if (c == 0) TSW(7);
    const uint64_t da = da0 + (uint32_t)(o_page(wg2, c) * 512);
#pragma unroll
    for (int ks = 0; ks < 8; ks++) {
      if (ks % 4 == 0) { if (ks) wg_commit(); if (wg2) wg_wait<0>(); wg_fence(); }
      wgmma_ss<64, 0, 1>(acc, da + ks * 128, db0 + wo_page(2 * c + (ks >> 2)) * 512 + (ks & 3) * 128, 1);
    }
    wg_commit();
  }
  if (wg) mbar_wait(bar + 8 * B_KG, 0);
  wg_wait<0>();
  acc_fence<32>(acc);
  TSW(8);
  if (!clean) {
    const float chk = acc[0] + acc[2];
    clean = __all_sync(~0u, chk == chk);
    if (clean && lane == 0) mbar_arrive(bar + 8 * (B_PDONE + wg));
  }
  float s0 = 0.f, q0 = 0.f, s1 = 0.f, q1 = 0.f;
  uint32_t o[16];
#pragma unroll
  for (int j = 0; j < 8; j++) {
    const float a = acc[4 * j], b = acc[4 * j + 1], c = acc[4 * j + 2], d = acc[4 * j + 3];
    o[2 * j] = packbf(a, b);
    o[2 * j + 1] = packbf(c, d);
    s0 += a + b; q0 = fmaf(a, a, q0); q0 = fmaf(b, b, q0);
    s1 += c + d; q1 = fmaf(c, c, q1); q1 = fmaf(d, d, q1);
  }
#pragma unroll
  for (int j = 0; j < 8; j += 2) {
    const int mi = lane >> 3;
    const int line = 8 * (j + (mi >> 1)) + (lane & 7), pc = 2 * w + (mi & 1);
    stsm4t(rbx + line * 128 + ((pc ^ (line & 7)) << 4), o[2 * j], o[2 * j + 1], o[2 * j + 2], o[2 * j + 3]);
  }
#pragma unroll
  for (int o2 = 1; o2 <= 2; o2 <<= 1) {
    s0 += __shfl_xor_sync(~0u, s0, o2); q0 += __shfl_xor_sync(~0u, q0, o2);
    s1 += __shfl_xor_sync(~0u, s1, o2); q1 += __shfl_xor_sync(~0u, q1, o2);
  }
  {
    const int i = 2 * (lane >> 2) + (t & 1), k = (i * 11) >> 5;
    const float v = (t == 0) ? s0 : (t == 1) ? q0 : (t == 2) ? s1 : q1;
    sts32f(stg + k * 128 + (2 * w + (t >> 1)) * 16 + (i - 3 * k) * 4, v);
  }
  TSW(9);
  fence_async_smem();
  if (attempt == 0 && clean) {
    staged = true;
    __syncwarp();
    if (lane == 0) mbar_arrive(bar + 8 * (B_STG + wg));
  }
  if (!bar_or(2 + wg, 128, !clean)) break;
  const int rtp = mbar_test(bar + 8 * (B_RT + wg), 0);
  bool unset = false;
#pragma unroll
  for (int i = 0; i < 4; i++) unset |= lds32(sb + o_page(wg, i) * PG + (32 * w + lane) * 128) == UNSET;
  if (!bar_or(2 + wg, 128, unset)) break;
  if (w == 0 && elect_one()) {
    fence_async_smem();
    mbar_expect(bar + 8 * (B_RT + wg), 9 * PG);
    if (layer == 0) tma_ld(rsrc, &p.mapX, q * 64, blk * 64, bar + 8 * (B_RT + wg));
    else tma_ld(rsrc, &p.mapXT, blk * 64, DM + q * 64, bar + 8 * (B_RT + wg));
#pragma unroll 1
    for (int c = 0; c < 4; c++) bulk_ld(sb + o_page(wg, c) * PG, g_O + ((layer * 32 + blk) * 4 + c) * PG, 2 * PG, bar + 8 * (B_RT + wg));
  }
  mbar_wait(bar + 8 * (B_RT + wg), rtp);
  RETRY(0);
  }
  if (!clean && lane == 0) mbar_arrive(bar + 8 * (B_PDONE + wg));
  if (!staged && lane == 0) mbar_arrive(bar + 8 * (B_STG + wg));
  TSW(10);
}

__device__ __forceinline__ void conv_load(uint32_t* A, uint32_t pe) {
#pragma unroll
  for (int m = 0; m < 17; m++) {
    A[4 * m + 2] = lds32(pe + 4 * (64 * m - 8));
    A[4 * m + 0] = lds32(pe + 4 * (64 * m));
    A[4 * m + 1] = lds32(pe + 4 * (64 * m + 8));
    asm volatile("mov.b32 %0, %1;" : "=r"(A[4 * m + 3]) : "r"(A[4 * m + 0]));
  }
}
template <int M> __device__ __forceinline__ void conv_tri(float* acc, const uint32_t* A, uint64_t d) {
  if constexpr (M < 16) {
    wgmma_rs<64 - 8 * (M / 2), 0>(acc, A + 4 * M, d + (uint64_t)(64 + 4 * M), M != 0);
    conv_tri<M + 1>(acc, A, d);
  }
}
__device__ __forceinline__ void conv_mma0(float* acc, const uint32_t* A, uint64_t d) {
  wg_fence();
  conv_tri<0>(acc, A, d);
  wg_commit();
}
__device__ __forceinline__ void conv_mma1(float* acc, const uint32_t* A, uint64_t d, uint64_t ds, uint64_t df) {
  wg_fence();
#pragma unroll
  for (int m = 0; m < 17; m++) wgmma_rs<64, 0>(acc, A + 4 * m, d + (uint64_t)(4 * m), m != 0);
  wgmma_ss<64, 1, 0>(acc, ds, df, 1);
  wgmma_ss<64, 1, 0>(acc, ds + 128, df + 128, 1);
  wg_commit();
}
__device__ __forceinline__ void conv_store(float* acc, uint32_t pb, uint32_t over, int w) {
  acc_fence<32>(acc);
  const int l = opaque_tid() & 31, mt = l >> 3;
  int c = 2 * (63 - 8 * (mt >> 1) - (l & 7) + w) + (mt & 1);
  c ^= (c >> 3) & 1;
  const uint32_t a0 = pb + c * 16;
#pragma unroll
  for (int j = 0; j < 8; j += 2)
    stsm4t(j == 0 ? (c < 128 ? a0 : over + (c - 128) * 16) : a0 - 256 * j, packbf(acc[4 * j], acc[4 * j + 1]), packbf(acc[4 * j + 2], acc[4 * j + 3]),
           packbf(acc[4 * j + 4], acc[4 * j + 5]), packbf(acc[4 * j + 6], acc[4 * j + 7]));
}
__device__ __forceinline__ void conv_sums(uint32_t sb, int lc, int ht) {
  const int m = ht - 1;
  uint4 v[2][3];
#pragma unroll
  for (int c = 0; c < 2; c++)
#pragma unroll
    for (int k = 0; k < 3; k++) {
      const int mm = m - 1 + k;
      v[c][k] = lds128(sb + cv_u(lc + c) + (mm >= 0 ? (mm & 1) * CV_UH + (127 - (mm >> 1)) * 16 : 128 * 16));
    }
  const int ce = m + 2, co = m + 1;
#pragma unroll
  for (int c = 0; c < 2; c++) {
    const uint32_t x[8] = {v[c][0].z, v[c][0].w, v[c][1].x, v[c][1].y, v[c][1].z, v[c][1].w, v[c][2].x, v[c][2].y};
    float pv[16];
#pragma unroll
    for (int k = 0; k < 8; k++) { pv[2 * k] = bf_lo(x[k]); pv[2 * k + 1] = bf_hi(x[k]); }
    float t2[15], t4[13], s9[8], s7[8];
#pragma unroll
    for (int i = 0; i < 15; i++) t2[i] = pv[i] + pv[i + 1];
#pragma unroll
    for (int i = 0; i < 13; i++) t4[i] = t2[i] + t2[i + 2];
#pragma unroll
    for (int i = 0; i < 8; i++) {
      s9[i] = (t4[i] + t4[i + 4]) + pv[i + 8];
      s7[i] = (t4[i + 1] + t2[i + 5]) + pv[i + 7];
    }
    const uint4 e4 = make_uint4(packbf(s9[0], s9[1]), packbf(s9[2], s9[3]), packbf(s9[4], s9[5]), packbf(s9[6], s9[7]));
    if (ce < 128) sts128(sb + cv_se(lc + c) + ((ce ^ ((ce >> 3) & 7)) << 4), e4);
    else sts128(sb + cv_se(lc + c), make_uint4(0, 0, 0, 0));
    sts128(sb + cv_so(lc + c) + ((co ^ ((co >> 3) & 7)) << 4),
           make_uint4(packbf(s7[0], s7[1]), packbf(s7[2], s7[3]), packbf(s7[4], s7[5]), packbf(s7[6], s7[7])));
  }
}

template <int HALF, int NCH, int STEP = 1>
__device__ __forceinline__ void conv_epi(uint32_t sb, bf16* out, int lc, int c) {
  uint4 v[NCH][4], xr[NCH];
  const uint32_t sw = (c ^ ((c >> 3) & 1)) * 16;
#pragma unroll
  for (int u = 0; u < NCH; u++) {
#pragma unroll
    for (int k = 0; k < 4; k++) v[u][k] = lds128(sb + (HALF ? cv_pb1(lc + STEP * u, k) : cv_pb0(lc + STEP * u, k)) + sw);
    xr[u] = lds128(sb + cv_x(HALF, lc + STEP * u) + c * 16);
  }
#pragma unroll
  for (int u = 0; u < NCH; u++) {
    uint4 o;
    o.x = hadd2(xr[u].x, hadd2(hadd2(v[u][0].x, v[u][1].x), hadd2(v[u][2].x, v[u][3].x)));
    o.y = hadd2(xr[u].y, hadd2(hadd2(v[u][0].y, v[u][1].y), hadd2(v[u][2].y, v[u][3].y)));
    o.z = hadd2(xr[u].z, hadd2(hadd2(v[u][0].z, v[u][1].z), hadd2(v[u][2].z, v[u][3].z)));
    o.w = hadd2(xr[u].w, hadd2(hadd2(v[u][0].w, v[u][1].w), hadd2(v[u][2].w, v[u][3].w)));
    stg128(out + cv_chan(0, lc + STEP * u) * LSEQ + HALF * 1024 + c * 8, o);
  }
}

__device__ __forceinline__ bool prep_valid(const uint4 (&st)[6], const uint4 (&xr)[4]) {
  const uint32_t n = st[0].w & st[1].w & st[2].w & st[3].w & st[4].w & (st[5].w | st[5].y | st[5].z);
  return (n == __float_as_uint(8.f)) & (max(max(xr[0].x, xr[1].x), max(xr[2].x, xr[3].x)) != UNSET);
}
template <int HALF>
__device__ __forceinline__ void conv_prep(uint32_t sb, int layer, int cta, int i) {
  uint4 st[6], xr[4];
  const uint4* sp = (const uint4*)g_stats + (layer * 32 + HALF * 16 + (i >> 3)) * 48 + (i & 7);
  const uint4* xp = (const uint4*)g_xT + (2 * layer * DM + 2 * cta) * (LSEQ / 8) + HALF * 128 + i;
  if (!HALF) { pin(sp); pin(xp); }
  mbar_wait(sb + SM_BAR + 8 * (B_GB + HALF), layer);
  if (!HALF) TSW(13);
  auto fetch = [&]() {
#pragma unroll
    for (int k = 0; k < 6; k++) st[k] = ld_tagged(sp + 8 * k);
#pragma unroll
    for (int k = 0; k < 4; k++) xr[k] = ld_tagged(xp + cv_chan(0, k) * (LSEQ / 8));
  };
  if (HALF) {
#pragma unroll
    for (int k = 0; k < 6; k++) st[k] = lds128(sb + CV_ST + (i >> 3) * 768 + k * 128 + (i & 7) * 16);
#pragma unroll
    for (int k = 0; k < 4; k++) xr[k] = lds128(sb + cv_x(1, k) + i * 16);
  } else {
    fetch();
  }
  int it = 0;
  while (!__all_sync(~0u, prep_valid(st, xr)) && ++it < MAX_RETRY) { fetch(); RETRY(1); }
  if (!HALF || it) {
#pragma unroll
    for (int k = 0; k < 4; k++) sts128(sb + cv_x(HALF, k) + i * 16, xr[k]);
  }
  const uint32_t v[16] = {st[0].x, st[0].y, st[0].z, st[1].x, st[1].y, st[1].z, st[2].x, st[2].y, st[2].z, st[3].x, st[3].y, st[3].z, st[4].x, st[4].y, st[4].z, st[5].x};
  uint32_t rs[4], nm[4];
#pragma unroll
  for (int k = 0; k < 4; k++) {
    constexpr float E2 = 1e-5f * DM * DM;
    const float s0 = __uint_as_float(v[4 * k]), s1 = __uint_as_float(v[4 * k + 2]);
    const float r0 = rsqrt_approx(fmaxf(fmaf(__uint_as_float(v[4 * k + 1]), (float)DM, fmaf(-s0, s0, E2)), E2));
    const float r1 = rsqrt_approx(fmaxf(fmaf(__uint_as_float(v[4 * k + 3]), (float)DM, fmaf(-s1, s1, E2)), E2));
    const uint32_t r = packbf(r0, r1);
    rs[k] = r + 0x04800480u;
    nm[k] = packbf(-s0 * bf_lo(r), -s1 * bf_hi(r));
  }
  const uint32_t ud = sb + (i & 1) * CV_UH + (127 - 64 * HALF - (i >> 1)) * 16;
#pragma unroll
  for (int k = 0; k < 4; k++)
    sts128(ud + cv_u(k), make_uint4(hfma2(xr[k].x, rs[0], nm[0]), hfma2(xr[k].y, rs[1], nm[1]), hfma2(xr[k].z, rs[2], nm[2]), hfma2(xr[k].w, rs[3], nm[3])));
  fence_async_smem();
}

__device__ __forceinline__ void conv_phase(const Params& p, uint32_t sb, int layer, int cta, uint32_t* A0, uint32_t* A1) {
  const int tid = opaque_tid();
  const int wg = __shfl_sync(~0u, tid >> 7, 0), w = __shfl_sync(~0u, (tid >> 5) & 3, 0);
  const uint32_t bar = sb + SM_BAR;
  constexpr int CH2 = 4 * PG;
  bf16* xout = g_xT + ((2 * layer + 1) * DM + 2 * cta) * LSEQ;
  float acc[32];
  const uint32_t pe = sb + cv_pe(wg, 0) + 4 * (16 + 16 * w + ((tid & 31) >> 2) - 2 * (tid & 3));
  if (layer == 0) {
    mbar_wait(bar + 8 * (B_PDONE + 1), layer);
    mbar_wait(bar + 8 * B_PE, layer);
    conv_load(A0, pe);
    conv_load(A1, pe + CH2);
  }
  TSW(19);
  const uint64_t d0 = mkdesc(sb + cv_u(wg), CV_UH, 128, 0), d1 = d0 + (CH2 >> 4);
  mbar_wait(bar + 8 * B_U, layer);
  TSW(12);
  if (wg == 1) bar_sync(5, 256);
  conv_mma0(acc, A0, d0);
  if (wg == 0) bar_arrive(5, 256);
  mbar_wait(bar + 8 * (B_PDONE + 1), layer);
  {
    const int l = opaque_tid() & 31;
    if ((l & 15) < 2 * w) sts128(sb + cv_pb0(wg + 2 * (l >> 4), w) + (l & 15) * 16, make_uint4(0, 0, 0, 0));
  }
  wg_wait<0>();
  conv_store(acc, sb + cv_pb0(wg, w), sb + cv_pb1(wg, w), w);
  conv_mma0(acc, A1, d1);
  wg_wait<0>();
  conv_store(acc, sb + cv_pb0(2 + wg, w), sb + cv_pb1(2 + wg, w), w);
  TSW(13);
  bar_sync(2 + wg, 128);
  conv_epi<0, 2, 2>(sb, xout, wg, opaque_tid() & 127);
  TSW(14);
  mbar_arrive(bar + 8 * B_PUB);
  const uint64_t ds = mkdesc(sb + cv_se(wg), 8192, 1024, 1), df = mkdesc(sb + cv_fa(wg), 512, 128, 0);
  if (wg == 0) mbar_wait(bar + 8 * B_U1, layer);
  else bar_sync(6, 256);
  TSW(15);
  conv_mma1(acc, A0, d0, ds, df);
  if (wg == 0) bar_arrive(6, 256);
  wg_wait<0>();
  conv_store(acc, sb + cv_pb1(wg, w), sb + cv_dump(wg), w);
  TSW(16);
  bar_sync(2 + wg, 128);
  conv_epi<1, 1>(sb, xout, wg, opaque_tid() & 127);
  mbar_arrive(bar + 8 * (B_PUB + 1));
  conv_mma1(acc, A1, d1, ds + 512, df + (CH2 >> 4));
  wg_wait<0>();
  conv_store(acc, sb + cv_pb1(2 + wg, w), sb + cv_dump(2 + wg), w);
  TSW(17);
  bar_sync(2 + wg, 128);
  conv_epi<1, 1>(sb, xout, 2 + wg, opaque_tid() & 127);
  mbar_arrive(bar + 8 * (B_PUB + 2));
  TSW(18);
}

#define FDELAY 480
__device__ __forceinline__ void final_tile(const Params& p, uint32_t buf, int ch0, int pos0, int barid, uint32_t hint) {
  const uint32_t t0 = (uint32_t)clock();
  const int tid = opaque_tid() & 127, lane = tid & 31, w = tid >> 5;
  const uint4* src = (const uint4*)(g_xT + (3 * DM + ch0 + (tid >> 3)) * LSEQ + pos0) + (tid & 7);
  const int ch = tid >> 3, row = 4 * (ch & 6) + 2 * (ch >> 3) + (ch & 1);
  uint32_t dst0 = buf + row * 128 + (((tid ^ row) & 7) << 4), dst1 = (dst0 ^ 64) + 512;
  uint32_t ld0 = buf + lane * 128 + ((((2 * w) ^ lane) & 7) << 4), ld1 = ld0 ^ 16;
  bf16* out = p.out + (pos0 + 16 * w + (lane >> 2)) * DM + ch0 + 8 * (lane & 3);
  pin(src); pin(out); pin(dst0); pin(dst1); pin(ld0); pin(ld1);
  if (hint) mbar_wait(hint, 0);
  else while ((uint32_t)clock() - t0 < FDELAY);
  uint4 a, b;
  int it = 0;
  do {
    if (it) RETRY(2);
    a = ld_tagged(src); b = ld_tagged(src + 16 * LSEQ / 8);
  } while (!__all_sync(~0u, a.x != UNSET && b.x != UNSET) && ++it < (1 << 20));
  sts128(dst0, a);
  sts128(dst1, b);
  bar_sync(barid, 128);
#pragma unroll
  for (int h = 0; h < 2; h++) {
    uint32_t r[4];
    ldsm4t(r, h ? ld1 : ld0);
    *(uint4*)(out + 8 * h * DM) = make_uint4(r[0], r[1], r[2], r[3]);
  }
}

struct cplx { float r, i; };
__device__ __forceinline__ cplx cmul(cplx a, cplx b) { return {fmaf(a.r, b.r, -a.i * b.i), fmaf(a.r, b.i, a.i * b.r)}; }
__device__ __forceinline__ cplx csqr(cplx a) { return {fmaf(a.r, a.r, -a.i * a.i), (a.r + a.r) * a.i}; }
__device__ __forceinline__ cplx cexp_l(float ar2, float ai, float l) {
  const float m = ex2(ar2 * l);
  const float x = ai * l;
  return {m * __cosf(x), m * __sinf(x)};
}

__device__ __forceinline__ void colsum_cta(const Params& p, uint32_t sb, int j, int tid) {
  const uint32_t bar = sb + SM_BAR;
  auto ld = [&](int i) {
    mbar_expect(bar + 8 * i, 3 * PG);
    tma_ld3(sb + (i & 7) * 3 * PG, &p.mapW3, (2 * j + (i & 1)) * 64, (i >> 1) * 64, 0, bar + 8 * i);
  };
  const int warp = __shfl_sync(~0u, tid >> 5, 0);
  if (warp == 12 && elect_one()) {
#pragma unroll
    for (int i = 0; i < 8; i++) mbar_init(bar + 8 * i, 1);
    asm volatile("fence.mbarrier_init.release.cluster;" ::: "memory");
    fence_async_smem();
#pragma unroll
    for (int i = 0; i < 8; i++) ld(i);
  }
  if (warp == 13 && elect_one()) {
#pragma unroll
    for (int i = 8; i < 24; i++) mbar_init(bar + 8 * i, i < 16 ? 1 : 12);
    asm volatile("fence.mbarrier_init.release.cluster;" ::: "memory");
  }
  const unsigned ep = ld_relaxed(&g_cnt[C_CS * 32]);
  bar_sync(0, NTHREADS);
  if (warp == 12 && elect_one()) {
#pragma unroll 1
    for (int i = 8; i < 16; i++) { mbar_wait(bar + 8 * (8 + i), 0); fence_async_smem(); ld(i); }
  }
  if (tid < 384) {
    const int lane = tid & 31, cc = tid & 7, r0 = (tid >> 3) & 15, part = tid >> 7;
    const uint32_t id = ((lane >> 2) == 2 * (lane & 3) ? 0x3f80u : 0u) | ((lane >> 2) == 2 * (lane & 3) + 1 ? 0x3f800000u : 0u);
    const uint32_t src = sb + part * PG + r0 * 128 + ((cc ^ (r0 & 7)) << 4);
    float s[2][2][4];
#pragma unroll
    for (int i = 0; i < 16; i++) s[i >> 3][(i >> 2) & 1][i & 3] = 0.f;
#pragma unroll 1
    for (int i2 = 0; i2 < 16; i2 += 2) {
#pragma unroll
      for (int h = 0; h < 2; h++) {
        const int i = i2 + h;
        mbar_wait(bar + 8 * i, 0);
        uint4 v[4];
#pragma unroll
        for (int k = 0; k < 4; k++) v[k] = lds128(src + (i & 7) * 3 * PG + k * 2048);
#pragma unroll
        for (int k = 0; k < 4; k++) {
          const uint32_t a[4] = {v[k].x, v[k].y, v[k].z, v[k].w};
          mma_bf16(s[h][0], a, id, 0u);
          mma_bf16(s[h][1], a, 0u, id);
        }
        __syncwarp();
        if (i < 8 && lane == 0) mbar_arrive(bar + 8 * (16 + i));
      }
    }
    const uint32_t red = sb + 24 * PG;
#pragma unroll
    for (int h = 0; h < 2; h++)
#pragma unroll
      for (int k = 0; k < 2; k++) sts128f(red + (r0 * 384 + h * 192 + part * 64 + cc * 8 + k * 4) * 4, s[h][k][0], s[h][k][1], s[h][k][2], s[h][k][3]);
    bar_sync(1, 384);
    float tot = 0.f;
#pragma unroll
    for (int k = 0; k < 16; k++) tot += __uint_as_float(lds32(red + (k * 384 + tid) * 4));
    asm volatile("st.relaxed.gpu.global.v2.u32 [%0], {%1,%2};" ::"l"(&g_colsum[j * 384 + tid]), "r"(__float_as_uint(tot)), "r"(ep / NCTA + 1) : "memory");
    const uint4 u = make_uint4(UNSET, UNSET, UNSET, UNSET);
    if (tid < 256) {
#pragma unroll 1
      for (int s = 0; s < 4; s++) {
        const int n = (s == 1 || s == 2) ? 32 : 16;
        uint4* buf = s == 1 ? (uint4*)g_O + 131072 : (uint4*)g_xT + (s + !s) * 131072;
#pragma unroll 4
        for (int i = 0; i < n; i++) stg128(buf + (j * n + i) * 1024 + (tid >> 1) * 8 + (tid & 1), u);
        if (n == 16) {
#pragma unroll 4
          for (int i = 0; i < 8; i++) stg128(buf + (256 + j * 64 + i * 8 + (tid >> 5)) * 256 + (s ? 0 : 128) + ((tid & 31) >> 1) * 8 + (tid & 1), u);
        }
        if (s == 3) {
#pragma unroll 4
          for (int i = 0; i < 32; i++) stg128(buf + (256 + j * 64 + 2 * i + (tid >> 7)) * 256 + 128 + (tid & 127), u);
        }
        bar_sync(2, 256);
        if (tid == 32 * s) red_release(&g_cnt[(C_R + s) * 32]);
      }
    }
  }
}

constexpr int KB = 4, KW = 2;
struct ModeIn { uint32_t ar, ai, br, bi, cr, ci; bf16 logdt; };
__device__ __forceinline__ ModeIn load_modes(const Params& p, int d, int m) {
  const int i = d * 64 + m;
  return {((const uint32_t*)p.a_re)[i], ((const uint32_t*)p.a_im)[i], ((const uint32_t*)p.b_re)[i], ((const uint32_t*)p.b_im)[i],
          ((const uint32_t*)p.c_re)[i], ((const uint32_t*)p.c_im)[i], p.log_dt[d]};
}
__device__ __forceinline__ void kernel_gen(uint32_t sb, int cta, int ht, ModeIn in, const ModeIn& in1) {
  const uint32_t bst = sb + SM_KGB + ((ht & 63) >> 2) * 144 + (ht & 3) * 4 + (ht >> 6) * 16;
  const uint64_t db = mkdesc(sb + SM_KGB, 144, 2304, 0);
  const float e0 = (float)(8 * (((ht & 32) >> 1) + ((ht & 31) >> 2)));
  float T[20];
#pragma unroll
  for (int i = 0; i < 20; i++) T[i] = 0.f;
  float k0 = 0.f;
#pragma unroll 1
  for (int pass = 0; pass < 4; pass++) {
    {
      const int sh = (pass & 1) ? 0 : 16;
      auto val = [&](uint32_t v) { return __uint_as_float((v << sh) & 0xffff0000u); };
      const float dt = __bfloat162float(__float2bfloat16_rn(expf(__bfloat162float(in.logdt))));
      const float ar2 = dt * val(in.ar) * 1.4426950408889634f, ai = dt * val(in.ai);
      const cplx c = cmul({val(in.cr), -val(in.ci)}, {dt * val(in.br), -dt * val(in.bi)});
      k0 += c.r;
      const cplx z1 = cexp_l(ar2, -ai, 1.f), z256 = cexp_l(ar2, -ai, 256.f), z64 = cexp_l(ar2, ai, 64.f);
      const cplx z2 = csqr(z1), z512 = csqr(z256);
      auto put = [&](int j, cplx v) { sts32(bst + (j >> 2) * 2304 + (j & 3) * 32, packbf(v.r, v.i)); };
      sts128f(sb + SM_KGT + ht * 16, ar2, ai, z64.r, z64.i);
      const cplx c1 = cmul(c, z1), c2 = cmul(c, z2), c3 = cmul(c1, z2), c4 = cmul(c2, z2);
      const cplx c5 = cmul(c3, z2), c6 = cmul(c4, z2), c7 = cmul(c5, z2), c8 = cmul(c6, z2);
      put(0, c1); put(1, c2); put(2, c3); put(3, c4); put(4, c5); put(5, c6); put(6, c7); put(7, c8);
      const cplx c260 = cmul(c4, z256), c264 = cmul(c8, z256), c520 = cmul(c8, z512), c776 = cmul(c264, z512);
      put(8, cmul(c2, z256)); put(9, c260); put(10, cmul(c6, z256)); put(11, c264);
      put(12, cmul(c4, z512)); put(13, c520); put(14, cmul(c260, z512)); put(15, c776);
      const cplx c1032 = cmul(c520, z512), c1288 = cmul(c776, z512);
      put(16, c1032); put(17, c1288); put(18, cmul(c1032, z512)); put(19, cmul(c1288, z512));
    }
    fence_async_smem();
    bar_sync(4, 128);
    const uint32_t tb = sb + SM_KGT + (ht & 67) * 16;
    float2 nx[KB];
#pragma unroll
    for (int s = 0; s < KB; s++) nx[s] = lds64f(tb + s * 64);
#pragma unroll
    for (int q = 0; q < 16 / KB; q++) {
      uint32_t A[2 * KB];
      float2 cur[KB], z[KB];
#pragma unroll
      for (int s = 0; s < KB; s++) { cur[s] = nx[s]; z[s] = lds64f(tb + (KB * q + s) * 64 + 8); }
      if (q < 16 / KB - 1) {
#pragma unroll
        for (int s = 0; s < KB; s++) nx[s] = lds64f(tb + (KB * q + KB + s) * 64);
      }
      if (q >= KW) wg_wait<KW - 1>();
#pragma unroll
      for (int s = 0; s < KB; s++) {
        const cplx lo = cexp_l(cur[s].x, cur[s].y, e0), hi = cmul(lo, {z[s].x, z[s].y});
        A[2 * s] = packbf(lo.r, lo.i);
        A[2 * s + 1] = packbf(hi.r, hi.i);
      }
      wg_fence();
#pragma unroll
      for (int k = 0; k < KB / 2; k++) wgmma_rs<40, 0>(T, A + 4 * k, db + 9 * KB * q + 18 * k, (pass & 1) | q | k);
      wg_commit();
    }
    wg_wait<0>();
    acc_fence<20>(T);
    if (ht == 0) TS(4 + pass);
    if (pass & 1) {
      const int h2 = opaque_tid() - 256, w = h2 >> 5, lane = h2 & 31, t = lane & 3, chn = h2 >> 6, m = h2 & 63, i0 = 16 * (w & 1) + (lane >> 2);
      const int lc = (pass & 2) + chn;
      const uint32_t kc = sb + kc_off(lc);
      auto put = [&](int idx, float v) {
        sts16(kc + idx * 2, __bfloat16_as_ushort(__float2bfloat16_rn(v)));
      };
#pragma unroll
      for (int hi = 0; hi < 2; hi++) {
        const int i = i0 + 8 * hi;
        float v[5];
#pragma unroll
        for (int j = 0; j < 5; j++) v[j] = chn ? T[4 * j + 2 * hi + 1] : T[4 * j + 2 * hi];
        put(8 * i + 1 + t, v[0]);
        put(8 * i + 5 + t, v[1]);
        put(257 + 4 * i + t, v[2]);
        put(385 + 2 * i + (t & 1) + 64 * (t >> 1), v[3]);
        put(513 + i + 32 * t, v[4]);
      }
#pragma unroll
      for (int o = 16; o > 0; o >>= 1) k0 += __shfl_xor_sync(~0u, k0, o);
      if (lane == 0) sts32f(sb + SM_RED + 4 * w, k0);
      bar_sync(4, 128);
      if (m == 0) put(0, k0 + __uint_as_float(lds32(sb + SM_RED + 4 * w + 4)) + __uint_as_float(lds16(sb + SM_RED + 24 + 2 * lc) << 16));
      k0 = 0.f;
      in = in1;
    }
  }
}

__device__ __forceinline__ void expand_taps(uint32_t sb, int ht, int early) {
  const int ch = ht >> 5, lane = ht & 31;
  const uint32_t kc = sb + kc_off(ch);
  const uint32_t dst0 = sb + cv_pe(ch, early);
  auto put = [&](int G, uint32_t v0, uint32_t v1, uint32_t v2, uint32_t v3, uint32_t v4, uint32_t v5, uint32_t v6, uint32_t v7, uint32_t v8) {
    const uint32_t dst = dst0 + G * 32;
    sts128(dst, make_uint4(v1 | (v0 << 16), v2 | (v1 << 16), v3 | (v2 << 16), v4 | (v3 << 16)));
    sts128(dst + 16, make_uint4(v5 | (v4 << 16), v6 | (v5 << 16), v7 | (v6 << 16), v8 | (v7 << 16)));
  };
  {
    const uint4 q = lds128(kc + lane * 16);
    const uint32_t pv = lane ? lds16(kc + lane * 16 - 2) : 0u;
    const uint32_t dst = dst0 + (lane + 2) * 32;
    sts128(dst, make_uint4(__byte_perm(q.x, pv, 0x5410), __byte_perm(q.x, q.x, 0x1032), __byte_perm(q.y, q.x, 0x7610), __byte_perm(q.y, q.y, 0x1032)));
    sts128(dst + 16, make_uint4(__byte_perm(q.z, q.y, 0x7610), __byte_perm(q.z, q.z, 0x1032), __byte_perm(q.w, q.z, 0x7610), __byte_perm(q.w, q.w, 0x1032)));
    if (lane < 4) sts128(dst0 + lane * 16, make_uint4(0, 0, 0, 0));
  }
  uint32_t a[5], b[2][3];
  {
    const uint32_t s1 = kc + 2 * (256 + 4 * lane);
#pragma unroll
    for (int k = 0; k < 5; k++) a[k] = lds16(s1 + 2 * k);
#pragma unroll
    for (int u = 0; u < 2; u++) {
      const uint32_t s2 = kc + 2 * (384 + 2 * (lane + 32 * u));
#pragma unroll
      for (int k = 0; k < 3; k++) b[u][k] = lds16(s2 + 2 * k);
    }
  }
  const uint32_t k255 = lds16(kc + 2 * 255), k1024 = lds16(kc + 2 * 512);
  put(34 + lane, lane == 0 ? k255 : a[0], a[0], a[0], a[1], a[2], a[2], a[2], a[3], a[4]);
#pragma unroll
  for (int u = 0; u < 2; u++) put(66 + lane + 32 * u, b[u][0], b[u][0], b[u][0], b[u][0], b[u][1], b[u][1], b[u][1], b[u][2], b[u][2]);
  if (lane < 10) {
    const uint32_t v = lane == 0 ? k1024 : 0u;
    put(130 + lane, v, v, v, v, v, v, 0u, 0u, 0u);
  }
}
__device__ __forceinline__ void expand_far(uint32_t sb, int ht) {
  const int ch = ht >> 5, lane = ht & 31;
  const uint32_t kc = sb + kc_off(ch) + 2 * (513 + 2 * (63 - lane)), dst = sb + cv_fa(ch) + lane * 16;
#pragma unroll
  for (int ty = 0; ty < 2; ty++) {
    uint32_t v[16];
#pragma unroll
    for (int k = 0; k < 16; k++) v[k] = (k < 8 || 63 - lane - 4 * k >= 0) ? lds16(kc + 2 * (1 - ty) - 16 * k) : 0u;
#pragma unroll
    for (int u = 0; u < 2; u++)
      sts128(dst + ty * 2048 + u * 512, make_uint4(v[8 * u] | (v[8 * u + 1] << 16), v[8 * u + 2] | (v[8 * u + 3] << 16), v[8 * u + 4] | (v[8 * u + 5] << 16), v[8 * u + 6] | (v[8 * u + 7] << 16)));
    sts128(dst + ty * 2048 + 1024, make_uint4(0, 0, 0, 0));
  }
}

__host__ __device__ constexpr int bar_count(int i) {
  return i == B_LN ? 2 : i == B_AL ? 8 : i < B_STG ? 1 : i < B_PE ? 4 : i >= B_PUB ? 256 : 128;
}
__host__ __device__ constexpr bool bar_first(int i) { return i < B_WF + 2 && (i & 7) < 2; }

__global__ void __launch_bounds__(NTHREADS, 1) fused_kernel(const __grid_constant__ Params p) {
  extern __shared__ __align__(1024) uint8_t smem[];
  constexpr uint32_t sb = 1024;
  if (s32(smem) != sb) return;
  const int tid = threadIdx.x, lane = tid & 31;
  const int warp = __shfl_sync(~0u, tid >> 5, 0);
  if (tid == 32) {
    asm volatile("prefetch.tensormap [%0];" ::"l"(&p.mapX) : "memory");
    asm volatile("prefetch.tensormap [%0];" ::"l"(&p.mapW3) : "memory");
  }
  const int cta = blockIdx.x - (gridDim.x == NCTA + 4 ? 0 : 4);
  if ((unsigned)cta >= NCTA) {
    if (blockIdx.x < NCTA + 4) colsum_cta(p, sb, blockIdx.x & 3, tid);
    return;
  }
  const int rb = ((cta >> 4) & 3) * 4 + ((cta >> 2) & 3), hg = (cta >> 6) * 4 + (cta & 3);
  const uint32_t bar = sb + SM_BAR;
  auto ld_x0 = [&](int half, int c) {
    const uint32_t b = bar + 8 * (B_XF + 8 * half + c);
    mbar_expect(b, PG);
    tma_ld(sb + x_page(half, c) * PG, &p.mapX, c * 64, (16 * half + rb) * 64, b);
  };
  auto ld_x1 = [&](int half, int c, int b0) {
    const uint32_t b = bar + 8 * b0;
    mbar_expect(b, PG);
    tma_ld(sb + (8 * half + c) * PG, &p.mapXT, (16 * half + rb) * 64, DM + c * 64, b);
  };
  auto ld_w = [&](int c) {
    const uint32_t b = bar + 8 * (B_WF + c);
    mbar_expect(b, 3 * PG);
    tma_ld3(sb + w_page(c) * PG, &p.mapW3, hg * 64, c * 64, 0, b);
  };

  if (tid == 0) TS(0);
  if (tid == 480) LTS(0);
  if (warp == 0 && elect_one()) {
#pragma unroll
    for (int i = 0; i < B_WF + 2; i++)
      if (bar_first(i)) mbar_init(bar + 8 * i, 1);
    asm volatile("fence.mbarrier_init.release.cluster;" ::: "memory");
    fence_async_smem();
    ld_x0(0, 0);
    ld_w(0); ld_x0(1, 0);
    ld_x0(0, 1); ld_w(1); ld_x0(1, 1);
    TS(1);
  }
  __syncwarp();
  if (warp >= 1 && warp < 8 && elect_one()) {
    if (warp < 4) {
#pragma unroll
      for (int i = 2; i < 8; i++) mbar_init(bar + 8 * (8 * warp - 8 + i), 1);
    } else {
#pragma unroll
      for (int i = 0; i < 12; i++) mbar_init(bar + 8 * (12 * warp - 24 + i), 1);
    }
    asm volatile("fence.mbarrier_init.release.cluster;" ::: "memory");
  }
  if (warp == 15 && elect_one()) {
#pragma unroll
    for (int i = 72; i < B_COUNT; i++) mbar_init(bar + 8 * i, bar_count(i));
    asm volatile("fence.mbarrier_init.release.cluster;" ::: "memory");
  }

  if (warp < 8) {
    bar_sync(0, NTHREADS);
    asm volatile("setmaxnreg.inc.sync.aligned.u32 %0;" ::"n"(R_CONS));
    const int cw = __shfl_sync(~0u, opaque_tid() >> 5, 0);
    const int wg = cw >> 2, w = cw & 3;
    if (tid == 0) TS(2);
#pragma unroll 1
    for (int layer = 0; layer < 2; layer++) {
      attn_phase(p, sb, layer, rb, hg, wg, w);
      uint32_t A0[68], A1[68];
      proj_phase(p, sb, layer, rb, hg, A0, A1);
      conv_phase(p, sb, layer, cta, A0, A1);
    }
    if (tid == 128) TS(8);
    final_tile(p, sb + (16 + wg) * PG, 256 * wg + 32 * (cta >> 4), 1024 + 64 * (cta & 15), 2 + wg, wg ? 0 : bar + 8 * (B_TF + 1));
    if (tid == 128) TS(9);
    if (tid == 128) LTS(1);
    if (tid == 0) LTE();
  } else if (warp < 12) {
    asm volatile("setmaxnreg.dec.sync.aligned.u32 %0;" ::"n"(R_HELP));
    const int ht = tid - 256;
    {
      unsigned ep0 = 0;
      if (ht == 0) ep0 = ld_relaxed(&g_cnt[C_CS * 32]);
      const bf16 dsk = p.dskip[cv_chan(cta, ht & 3)];
      const ModeIn in0 = load_modes(p, cv_chan(cta, ht >> 6), ht & 63), in1 = load_modes(p, cv_chan(cta, 2 + (ht >> 6)), ht & 63);
      if (ht < 48) sts128f(sb + SM_STG + ht * 16, 0.f, 0.f, 0.f, 1.f);
      bar_sync(0, NTHREADS);
      if (ht == 0) {
        sts32(sb + SM_EP, ep0);
        mbar_arrive(bar + 8 * B_EP);
      }
      if (ht >= 124) sts16(sb + SM_RED + 24 + 2 * (ht & 3), __bfloat16_as_ushort(dsk));
      kernel_gen(sb, cta, ht, in0, in1);
      if (ht < 48) sts128f(sb + SM_KGT + ht * 16, 0.f, 0.f, 0.f, 1.f);
      fence_async_smem();
      bar_sync(4, 128);
      if (ht == 0) mbar_arrive(bar + 8 * B_KG);
    }
#pragma unroll 1
    for (int layer = 0; layer < 2; layer++) {
      const int early = layer;
      if (early) mbar_wait(bar + 8 * (B_DN + 13), 1);
      mbar_wait(bar + 8 * (early ? B_OST : B_PDONE), layer);
      expand_taps(sb, opaque_tid() - 256, early);
      mbar_arrive(bar + 8 * B_PE);
      TSW(0);
      mbar_wait(bar + 8 * B_PDONE, layer);
      expand_far(sb, opaque_tid() - 256);
      {
        const int i = opaque_tid() - 256;
        if (i < 32) sts128(sb + cv_u(i >> 3) + ((i >> 2) & 1) * CV_UH + (128 + (i & 3)) * 16, make_uint4(0, 0, 0, 0));
        mbar_wait(bar + 8 * B_RC, layer);
        conv_prep<0>(sb, layer, cta, i);
        mbar_arrive(bar + 8 * B_U);
      }
      mbar_wait(bar + 8 * (B_PDONE + 1), layer);
      bar_sync(4, 128);
#pragma unroll 1
      for (int lc = 0; lc < 4; lc += 2) {
        conv_sums(sb, lc, opaque_tid() - 256);
        TSW(1 + lc);
      }
      conv_prep<1>(sb, layer, cta, opaque_tid() - 256);
      mbar_arrive(bar + 8 * B_U1);
      TSW(4);
      if (layer == 0) {
        const int c = __shfl_sync(~0u, (opaque_tid() >> 5) & 3, 0);
        int phase = 0;
#pragma unroll 1
        for (int k = 0; k < 3; k++) {
          const int page = (k ? 4 + 4 * k : 0) + c, b = B_XR + 4 * (k & 1) + c;
          const uint32_t a = sb + page * PG + lane * 128 + (lane & 7) * 16 + (lane >> 3) * 4;
          int it = k == 2 ? phase : 0;
#pragma unroll 1
          for (; it < MAX_RETRY; it++) {
            mbar_wait(bar + 8 * b, it & 1);
            const uint32_t v0 = lds32(a), v1 = lds32(a + 4096);
            if (__all_sync(~0u, v0 != UNSET && v1 != UNSET)) break;
            if (elect_one()) { fence_async_smem(); ld_x1(page >> 3, page & 7, b); }
            __syncwarp();
            RETRY(3);
          }
          if (k == 0) phase = it + 1;
          if (lane == 0) mbar_arrive(bar + 8 * (B_XF + page));
        }
      }
    }
#pragma unroll 1
    for (int k = 0; k < 2; k++) final_tile(p, sb + 18 * PG + k * 4096, 256 * k + 32 * (cta >> 4), 64 * (cta & 15), 4, bar + 8 * B_TF);
    if (ht == 0) LTE();
  } else {
    asm volatile("setmaxnreg.dec.sync.aligned.u32 %0;" ::"n"(R_AGENT));
    bar_sync(0, NTHREADS);
    auto done = [&](int half, int c, int layer) { mbar_wait(bar + 8 * (B_DN + 8 * half + c), layer); };
    auto publish = [&](int layer, int k) {
      unsigned* cnt = &g_cnt[(layer ? C_F + 8 * k + (cta >> 4) : C_C + k) * 32];
      pin(cnt);
      mbar_wait(bar + 8 * (B_PUB + k), layer);
      red_relaxed(cnt);
      if (!layer && k == 0) red_release(&g_cnt[(C_C + 3) * 32]);
      TS(16 + layer * 56 + 40 + 7 + k);
    };
    if (warp == 12) {
      if (elect_one()) {
#pragma unroll 1
        for (int layer = 0; layer < 2; layer++) {
          auto ld_xe = [&](int c) {
            const uint32_t b = bar + 8 * (B_XF + c);
            mbar_expect(b, PG);
            if (layer == 0) tma_ld(sb + x_page(0, c) * PG, &p.mapX, c * 64, rb * 64, b);
            else tma_ld(sb + x_page(0, c) * PG, &p.mapXT, rb * 64, DM + c * 64, b);
          };
          if (layer == 0) {
            ld_x0(0, 2); ld_w(2); ld_x0(1, 2);
            if (hg >= 3) {
              mbar_expect(bar + 8 * B_SC, PG);
              tma_ld(sb + P_R * PG, &p.mapX, hg * 64, rb * 64, bar + 8 * B_SC);
            }
            if (rb < 4) tma_prefetch3(&p.mapW3, hg * 64, (4 + rb) * 64, 0);
            ld_x0(0, 3); ld_w(3); ld_x0(1, 3); ld_x0(0, 4); ld_x0(1, 4);
            done(0, 0, 0); done(1, 0, 0);
            ld_w(4);
            ld_x0(1, 5); ld_x0(1, 6); ld_x0(1, 7);
            done(0, 1, 0); done(1, 1, 0);
            ld_w(5);
            if (rb < 8) tma_prefetch5(&p.mapWo, hg * 64, rb * 2);
            done(0, 2, 0);
            fence_async_smem();
            ld_xe(5); ld_xe(6); ld_xe(7);
          } else {
            mbar_wait(bar + 8 * B_PDONE, 0);
            mbar_wait(bar + 8 * (B_PDONE + 1), 0);
            mbar_wait(bar + 8 * B_U, 0);
            ld_w(0); ld_w(1);
            mbar_wait(bar + 8 * B_U1, 0);
            fence_async_smem();
            ld_w(2);
            mbar_wait(bar + 8 * (B_PUB + 2), 0);
            fence_async_smem();
            ld_w(3);
            spin_until(&g_cnt[(C_C + 3) * 32], ((lds32(sb + SM_EP) / NCTA) + 1) * NCTA);
            fence_async_global();
            if (hg >= 3) {
              mbar_expect(bar + 8 * B_SC, PG);
              tma_ld(sb + P_R * PG, &p.mapXT, rb * 64, DM + hg * 64, bar + 8 * B_SC);
            }
            ld_xe(4);
            done(0, 2, 1);
            fence_async_smem();
            ld_xe(5); ld_xe(6); ld_xe(7);
            done(1, 0, 1);
            ld_w(4);
            done(1, 1, 1);
            ld_w(5);
          }
          done(1, 2, layer);
          fence_async_smem();
          ld_w(6); ld_w(7);
          auto ld_res = [&](int half) {
            const uint32_t b = bar + 8 * (B_RF + half);
            mbar_expect(b, PG);
            if (layer == 0) tma_ld(sb + (half ? 2 : P_R) * PG, &p.mapX, hg * 64, (16 * half + rb) * 64, b);
            else tma_ld(sb + (half ? 2 : P_R) * PG, &p.mapXT, (16 * half + rb) * 64, DM + hg * 64, b);
          };
          done(0, 4, layer); done(1, 3, layer);
          fence_async_smem();
          mbar_expect(bar + 8 * B_WOF, 8 * PG);
#pragma unroll 1
          for (int c = 0; c < 8; c++) {
            if (c == 5) { ld_res(0); done(1, 4, layer); }
            tma_ld5(sb + wo_page(c) * PG, &p.mapWo, hg * 64, c * 2, bar + 8 * B_WOF);
          }
          done(0, 7, layer);
          fence_async_global();
          ld_res(1);
          if (layer) mbar_wait(bar + 8 * B_RS, 0);
          fence_async_global();
#pragma unroll
          for (int half = 0; half < 2; half++) {
            float* stats = g_stats + (layer * 32 + 16 * half + rb) * 192;
            unsigned* cnt = &g_cnt[(C_G + 2 * layer + half) * 32];
            mbar_wait(bar + 8 * (B_STG + half), layer);
            tma_st(&p.mapXT, (16 * half + rb) * 64, 2 * layer * DM + hg * 64, sb + (P_R + half) * PG);
            bulk_red_add_f32(stats, sb + (half ? SM_KGT : SM_STG), 768);
            bulk_commit();
            red_relaxed(cnt);
            if (half == 0) mbar_arrive(bar + 8 * B_PG);
            bulk_wait_read();
            mbar_arrive(bar + 8 * (B_PST + half));
          }
        }
      }
    } else if (warp == 13) {
      mbar_wait(bar + 8 * B_EP, 0);
      const unsigned e1 = (lds32(sb + SM_EP) / NCTA) + 1;
      auto ld_o = [&](int layer) {
#pragma unroll 1
        for (int half = 0; half < 2; half++) {
          done(1, 7, layer);
          mbar_wait(bar + 8 * B_OST, layer);
          if (half) mbar_wait(bar + 8 * (B_OST + 1), layer);
          fence_async_smem();
#pragma unroll
          for (int c = 0; c < 4; c++) mbar_expect(bar + 8 * (B_OF + 4 * half + c), 2 * PG);
          const bf16* src = g_O + (layer * 32 + 16 * half + rb) * 4 * PG;
          uint32_t dst0 = sb + o_page(half, 0) * PG;
          pin(src); pin(dst0);
          spin_hint(&g_cnt[(C_O + layer * 32 + 16 * half + rb) * 32], e1 * 32);
#pragma unroll
          for (int c = 0; c < 4; c++) {
            if (c == 2 && half && layer) { mbar_wait(bar + 8 * B_AL, 0); fence_async_smem(); }
            bulk_ld(c ? sb + o_page(half, c) * PG : dst0, src + c * PG, 2 * PG, bar + 8 * (B_OF + 4 * half + c));
          }
        }
      };
      if (elect_one()) {
        mbar_wait(bar + 8 * (B_WF + 2), 0);
        asm volatile("prefetch.tensormap [%0];" ::"l"(&p.mapXT) : "memory");
        asm volatile("prefetch.tensormap [%0];" ::"l"(&p.mapWo) : "memory");
        spin_until(&g_cnt[C_Z * 32], e1 * NCTA);
        mbar_arrive(bar + 8 * B_ZF);
        TS(3);
        ld_o(0);
#pragma unroll 1
        for (int k = 0; k < 3; k++) {
          mbar_wait(bar + 8 * (B_PUB + k), 0);
          if (k == 2) {
#pragma unroll 1
            for (int c = 0; c < 4; c++) mbar_wait(bar + 8 * (B_XF + c), 1);
          }
          fence_async_smem();
          uint32_t b = bar + 8 * (B_XR + 4 * (k & 1)), dst = sb + (k ? 4 + 4 * k : 0) * PG, c0 = ((k ? 16 : 0) + rb) * 64, c1 = DM + (k & 2) * 128;
#pragma unroll
          for (int c = 0; c < 4; c++) mbar_expect(b + 8 * c, PG);
          pin(b); pin(dst); pin(c0); pin(c1);
          spin_hint(&g_cnt[(C_C + k) * 32], e1 * NCTA);
          TS(10 + k);
#pragma unroll
          for (int c = 0; c < 4; c++) tma_ld(dst + c * PG, &p.mapXT, c0, c1 + c * 64, b + 8 * c);
        }
        ld_o(1);
#pragma unroll 1
        for (int k = 0; k < 2; k++) {
          mbar_wait(bar + 8 * (B_PUB + k), 1);
          spin_hint(&g_cnt[(C_F + 8 * k + (cta >> 4)) * 32], e1 * 16);
          mbar_arrive(bar + 8 * (B_TF + k));
        }
      }
    } else if (warp == 14) {
      mbar_wait(bar + 8 * B_EP, 0);
      const unsigned e1 = (lds32(sb + SM_EP) / NCTA) + 1;
      done(0, 1, 0);
      {
        const uint2* cp = g_colsum + (hg * 192 + lane);
        uint2 v[6];
        bool ok;
        int it = 0;
        do {
          ok = true;
#pragma unroll
          for (int i = 0; i < 6; i++) {
            asm volatile("ld.relaxed.gpu.global.v2.u32 {%0,%1}, [%2];" : "=r"(v[i].x), "=r"(v[i].y) : "l"(cp + 32 * i) : "memory");
            ok = ok && v[i].y == e1;
          }
          if (++it > (1 << 22)) __trap();
        } while (!__all_sync(~0u, ok));
#pragma unroll
        for (int i = 0; i < 6; i++) sts32f(sb + SM_CS + 4 * (lane + 32 * i), __uint_as_float(v[i].x));
      }
      __syncwarp();
      if (elect_one()) {
        mbar_wait(bar + 8 * B_ZF, 0);
        mbar_arrive(bar + 8 * B_LN);
        red_relaxed(&g_cnt[C_CS * 32]);
        TS(13);
#pragma unroll 1
        for (int layer = 0; layer < 2; layer++) {
          const uint32_t b = bar + 8 * (B_GB + 1);
          const bf16* xin = g_xT + ((size_t)2 * layer * DM + 2 * cta) * LSEQ + 1024;
          const float* stats = g_stats + (layer * 32 + 16) * 192;
          mbar_wait(bar + 8 * B_PST, layer);
          spin_hint(&g_cnt[(C_G + 2 * layer) * 32], e1 * NCTA);
          mbar_arrive(bar + 8 * B_GB);
          mbar_wait(bar + 8 * (B_PST + 1), layer);
          fence_async_smem();
          mbar_expect(b, 12288 + PG);
          pin(stats); pin(xin);
          spin_hint(&g_cnt[(C_G + 2 * layer + 1) * 32], e1 * NCTA);
          bulk_ld(sb + CV_ST, stats, 12288, b);
#pragma unroll
          for (int lc = 0; lc < 4; lc++) bulk_ld(sb + cv_x(1, lc), xin + cv_chan(0, lc) * LSEQ, 2048, b);
          TS(14 + layer);
          publish(layer, 1);
        }
      }
    } else {
      const uint4 u = make_uint4(UNSET, UNSET, UNSET, UNSET);
      if (lane < 24) stg128((uint4*)g_stats + cta * 24 + lane, make_uint4(0, 0, 0, 0));
      if (lane < 16) stg128(g_rows + LSEQ + cta * 16 + lane, make_uint4(0, 0, 0, 0));
#pragma unroll 4
      for (int i = 0; i < 16; i++) stg128(g_halo + cta * 512 + 32 * i + lane, u);
#pragma unroll 4
      for (int i = 0; i < 16; i++) stg128(((i & 8) ? (uint4*)g_xT : (uint4*)g_O) + cta * 1024 + (i & 7) * 128 + (lane >> 1) * 8 + (lane & 1), u);
      __syncwarp();
      if (elect_one()) red_release(&g_cnt[C_Z * 32]);
      __syncwarp();
#pragma unroll 1
      for (int layer = 0; layer < 2; layer++) {
        auto reset_done = [&](int s) {
          spin_until(&g_cnt[(C_R + s) * 32], (lds32(sb + SM_EP) / NCTA) * 4 + 4);
          mbar_arrive(bar + 8 * (s == 1 ? B_LN : s == 2 ? B_RS : B_RC));
          if (s) TS(16 + 40 + 9 + s);
        };
        if (layer && elect_one()) reset_done(1);
        __syncwarp();
#pragma unroll 1
        for (int half = 0; half < 2; half++) {
          done(half, 2, layer);
          const uint4* src = g_rows + (layer * LSEQ + (16 * half + rb) * 64 + (opaque_tid() & 31));
          uint4 a, b;
          int it = 0;
          do {
            a = ld_tagged(src); b = ld_tagged(src + 32);
          } while (!__all_sync(~0u, (a.z | a.w) == __float_as_uint(8.f) && (b.z | b.w) == __float_as_uint(8.f)) && ++it < (1 << 20));
          float m0 = __uint_as_float(a.x) * (1.f / DM), m1 = __uint_as_float(b.x) * (1.f / DM);
          float r0 = rsqrt_approx(fmaxf(__uint_as_float(a.y) * (1.f / DM) - m0 * m0, 0.f) + 1e-5f);
          float r1 = rsqrt_approx(fmaxf(__uint_as_float(b.y) * (1.f / DM) - m1 * m1, 0.f) + 1e-5f);
          if (half) done(0, 7, layer);
          const uint32_t dst = sb + ln_off(half) + ((lane >> 4) * 8 + (lane & 7)) * 16 + (lane & 8);
          asm volatile("st.shared.v2.f32 [%0], {%1,%2};" ::"r"(dst), "f"(m0), "f"(r0) : "memory");
          asm volatile("st.shared.v2.f32 [%0], {%1,%2};" ::"r"(dst + 256), "f"(m1), "f"(r1) : "memory");
          __syncwarp();
          if (elect_one()) { mbar_arrive(bar + 8 * (B_LN + half)); TS(16 + layer * 56 + 40 + 14 + half); }
        }
        if (layer && lane < 16) stg128(g_rows + cta * 16 + (opaque_tid() & 31), make_uint4(0, 0, 0, 0));
        if (elect_one()) {
          if (layer) reset_done(2);
          reset_done(3 * layer);
          publish(layer, 0);
          if (!layer) publish(layer, 2);
        }
        __syncwarp();
      }
    }
  }
}

typedef CUresult (*EncodeFn)(CUtensorMap*, CUtensorMapDataType, cuuint32_t, void*, const cuuint64_t*, const cuuint64_t*,
                             const cuuint32_t*, const cuuint32_t*, CUtensorMapInterleave, CUtensorMapSwizzle,
                             CUtensorMapL2promotion, CUtensorMapFloatOOBfill);

static void make_map(EncodeFn enc, CUtensorMap* m, void* ptr, uint64_t cols, uint64_t rows, uint32_t box_rows) {
  cuuint64_t dims[2] = {cols, rows};
  cuuint64_t strides[1] = {cols * 2};
  cuuint32_t box[2] = {64, box_rows};
  cuuint32_t es[2] = {1, 1};
  enc(m, CU_TENSOR_MAP_DATA_TYPE_BFLOAT16, 2, ptr, dims, strides, box, es, CU_TENSOR_MAP_INTERLEAVE_NONE,
      CU_TENSOR_MAP_SWIZZLE_128B, CU_TENSOR_MAP_L2_PROMOTION_L2_128B, CU_TENSOR_MAP_FLOAT_OOB_FILL_NONE);
}
static void make_map3(EncodeFn enc, CUtensorMap* m, void* ptr, uint64_t d0, uint64_t cols, uint64_t rows, uint64_t blk_stride,
                      uint64_t nblocks, uint32_t nblk) {
  cuuint64_t dims[3] = {d0, rows, nblocks};
  cuuint64_t strides[2] = {cols * 2, blk_stride * 2};
  cuuint32_t box[3] = {64, 64, nblk};
  cuuint32_t es[3] = {1, 1, 1};
  enc(m, CU_TENSOR_MAP_DATA_TYPE_BFLOAT16, 3, ptr, dims, strides, box, es, CU_TENSOR_MAP_INTERLEAVE_NONE,
      CU_TENSOR_MAP_SWIZZLE_128B, CU_TENSOR_MAP_L2_PROMOTION_L2_128B, CU_TENSOR_MAP_FLOAT_OOB_FILL_NONE);
}

extern "C" void kernel_launch(void* const* d_in, const int* in_sizes, int n_in, void* d_out, int out_size) {
  static Params prm;
  static void* cached[13] = {nullptr};
  static bool attr_done = false;
  static int grid = NCTA + 4;
  bool same = attr_done && cached[12] == d_out;
  for (int i = 0; i < 12 && same; i++) same = cached[i] == d_in[i];
  if (!same) {
    void* fn = nullptr;
    cudaDriverEntryPointQueryResult qr;
    cudaGetDriverEntryPoint("cuTensorMapEncodeTiled", &fn, cudaEnableDefault, &qr);
    EncodeFn enc = (EncodeFn)fn;
    void* pXT;
    cudaGetSymbolAddress(&pXT, g_xT);
    make_map(enc, &prm.mapX, d_in[0], DM, LSEQ, 64);
    make_map(enc, &prm.mapXT, pXT, LSEQ, 4 * DM, 64);
    {
      cuuint64_t dims[5] = {DM, 2, 4, 4, 16};
      cuuint64_t strides[4] = {DM * 2, 8 * DM * 2, 2 * DM * 2, 32 * DM * 2};
      cuuint32_t box[5] = {64, 2, 4, 4, 2};
      cuuint32_t es[5] = {1, 1, 1, 1, 1};
      enc(&prm.mapWo, CU_TENSOR_MAP_DATA_TYPE_BFLOAT16, 5, d_in[2], dims, strides, box, es, CU_TENSOR_MAP_INTERLEAVE_NONE,
          CU_TENSOR_MAP_SWIZZLE_128B, CU_TENSOR_MAP_L2_PROMOTION_L2_128B, CU_TENSOR_MAP_FLOAT_OOB_FILL_NONE);
    }
    make_map3(enc, &prm.mapW3, d_in[1], DM, 3 * DM, DM, DM, 3, 3);
    prm.out = (bf16*)d_out;
    prm.a_re = (const bf16*)d_in[4]; prm.a_im = (const bf16*)d_in[5];
    prm.b_re = (const bf16*)d_in[6]; prm.b_im = (const bf16*)d_in[7];
    prm.c_re = (const bf16*)d_in[8]; prm.c_im = (const bf16*)d_in[9];
    prm.log_dt = (const bf16*)d_in[10]; prm.dskip = (const bf16*)d_in[11];
    int dev = 0, sms = 0;
    cudaGetDevice(&dev);
    cudaDeviceGetAttribute(&sms, cudaDevAttrMultiProcessorCount, dev);
    grid = sms >= NCTA + 4 ? NCTA + 4 : NCTA + 5;
    cudaFuncSetAttribute(fused_kernel, cudaFuncAttributeMaxDynamicSharedMemorySize, SM_TOTAL);
    for (int i = 0; i < 12; i++) cached[i] = d_in[i];
    cached[12] = d_out;
    attr_done = true;
  }
  fused_kernel<<<grid, NTHREADS, SM_TOTAL>>>(prm);
}
```

```cpp
#include <cuda_runtime.h>
#include <cuda_bf16.h>
#include <cuda.h>
#include <stdint.h>

typedef __nv_bfloat16 bf16;

constexpr int LSEQ = 2048;
constexpr int DM = 512;
constexpr int NCTA = 128;
constexpr int NTHREADS = 512;
#define R_CONS 200
#define R_HELP 88
#define R_AGENT 24
#define TURN0 4
#define TURN1 4

constexpr int PG = 8192;
constexpr int P_R = 25;
__host__ __device__ constexpr int x_page(int half, int c) { return half ? 8 + c : c < 5 ? c : c - 5; }
__host__ __device__ constexpr int w_page(int c) { return (c & 3) < 3 ? 16 + 3 * (c & 3) : c < 4 ? 5 : 8; }
__host__ __device__ constexpr int wo_page(int c) { return c < 5 ? 3 + c : 11 + c; }
__host__ __device__ constexpr int o_page(int half, int pair) { return half ? (pair ? 25 - 2 * pair : 0) : 8 + 2 * pair; }
constexpr int SM_KGB = (P_R + 1) * PG;
constexpr int SM_KC = 27 * PG;
constexpr int KC_STRIDE = 648;
__host__ __device__ constexpr int kc_off(int lc) { return SM_KC + (lc & 1) * 2 * KC_STRIDE + (lc < 2 ? 3328 : 0); }
constexpr int SM_KGT = SM_KC + 3328 + 2592;
constexpr int SM_CS = SM_KGT + 2048;
constexpr int SM_RED = SM_CS + 768;
constexpr int SM_EP = SM_RED + 16;
constexpr int SM_STG = SM_RED + 32;
constexpr int SM_LN = SM_STG + 768;
__host__ __device__ constexpr int ln_off(int half) { return half ? PG + 4096 : SM_LN; }
constexpr int SM_BAR = SM_LN + 512;
constexpr int SM_TS = SM_BAR + 704;
constexpr int SM_TOTAL = SM_TS + 512;
static_assert(SM_TOTAL <= 232448 && SM_STG % 16 == 0 && SM_KGT % 16 == 0, "shared memory");

constexpr int CV_UH = 140 * 16;
__host__ __device__ constexpr int cv_u(int lc) { return (8 + 2 * lc) * PG; }
__host__ __device__ constexpr int cv_pe(int lc, int early) { return early ? 19 * PG + lc * 4480 : cv_u(lc) + 4480; }
__host__ __device__ constexpr int cv_pb1(int lc, int w) { return w ? cv_u(lc) + 8960 + (w - 1) * 2048 : 7 * PG + lc * 2048; }
__host__ __device__ constexpr int cv_fa(int lc) { return cv_pb1(lc, 1) + 128; }
__host__ __device__ constexpr int cv_dump(int lc) { return cv_u(lc) + 16256; }
__host__ __device__ constexpr int cv_pb0(int lc, int w) { return lc * PG + w * 2048; }
__host__ __device__ constexpr int cv_se(int lc) { return 5 * PG + lc * 4096; }
__host__ __device__ constexpr int cv_so(int lc) { return cv_se(lc) + 2048; }
__host__ __device__ constexpr int cv_x(int half, int lc) { return (P_R + half) * PG + lc * 2048; }
constexpr int CV_ST = 22 * PG;
__host__ __device__ constexpr int cv_chan(int cta, int lc) { return 2 * cta + (lc & 1) + 256 * (lc >> 1); }

enum {
  B_XF = 0,
  B_WF = 16,
  B_OF = 24,
  B_DN = 32,
  B_PG = 46,
  B_XR = 48,
  B_RF = 56,
  B_PST = 58,
  B_GB = 60,
  B_TF = 62,
  B_RT = 64,
  B_RS = 66,
  B_RC = 67,
  B_WOF = 68,
  B_ZF = 69,
  B_EP = 70,
  B_KG = 71,
  B_SC = 37,
  B_LN = 72,
  B_END = 38,
  B_STG = 74,
  B_OST = 76,
  B_PDONE = 78,
  B_PE = 80,
  B_U = 81,
  B_U1 = 82,
  B_PUB = 83,
  B_AL = 86,
  B_COUNT = 87
};

enum {
  C_CS = 0,
  C_G = 1,
  C_C = 5,
  C_O = 21,
  C_Z = 85,
  C_R = 86,
  C_F = 90,
  C_COUNT = 106
};

__device__ unsigned g_cnt[C_COUNT * 32];
__device__ __align__(1024) bf16 g_O[2 * LSEQ * DM];
__device__ __align__(1024) bf16 g_xT[4 * DM * LSEQ];
__device__ __align__(1024) float g_stats[2 * 32 * 192];
__device__ __align__(1024) uint2 g_colsum[3 * DM];
__device__ __align__(1024) uint4 g_halo[32 * 8 * 256];
__device__ __align__(1024) uint4 g_rows[2 * LSEQ];
#define TS(i) do { } while (0)
#define TSW(k) do { if ((threadIdx.x & 127) == 0) TS(16 + layer * 56 + (threadIdx.x >> 7) * 20 + (k)); } while (0)
#define TSG(k) do { } while (0)

#define RETRY(i) do { } while (0)
#define LTS(i) do { } while (0)
#define LTE() do { } while (0)

struct Params {
  CUtensorMap mapX, mapW3, mapXT, mapWo;
  bf16* out;
  const bf16 *a_re, *a_im, *b_re, *b_im, *c_re, *c_im, *log_dt, *dskip;
};

__device__ __forceinline__ uint32_t s32(const void* p) { return (uint32_t)__cvta_generic_to_shared(p); }
__device__ __forceinline__ void mbar_init(uint32_t b, int c) { asm volatile("mbarrier.init.shared::cta.b64 [%0], %1;" ::"r"(b), "r"(c) : "memory"); }
__device__ __forceinline__ void mbar_expect(uint32_t b, int bytes) { asm volatile("mbarrier.arrive.expect_tx.shared::cta.b64 _, [%0], %1;" ::"r"(b), "r"(bytes) : "memory"); }
__device__ __forceinline__ void mbar_arrive(uint32_t b) { asm volatile("mbarrier.arrive.shared::cta.b64 _, [%0];" ::"r"(b) : "memory"); }
__device__ __forceinline__ void mbar_wait(uint32_t b, int parity) {
  asm volatile("{\n.reg .pred p;\nWAIT_LOOP:\nmbarrier.try_wait.parity.shared::cta.b64 p, [%0], %1;\n@p bra WAIT_DONE;\nbra WAIT_LOOP;\nWAIT_DONE:\n}" ::"r"(b), "r"(parity) : "memory");
}
__device__ __forceinline__ bool mbar_test(uint32_t b, int parity) {
  uint32_t ok;
  asm volatile("{\n.reg .pred p;\nmbarrier.test_wait.parity.shared::cta.b64 p, [%1], %2;\nselp.u32 %0, 1, 0, p;\n}" : "=r"(ok) : "r"(b), "r"(parity) : "memory");
  return ok != 0;
}
__device__ __forceinline__ int opaque_tid() { int v; asm volatile("mov.u32 %0, %%tid.x;" : "=r"(v)); return v; }
__device__ __forceinline__ bool elect_one() {
  uint32_t r;
  asm volatile("{\n.reg .pred p;\nelect.sync _|p, 0xffffffff;\nselp.u32 %0, 1, 0, p;\n}" : "=r"(r));
  return r != 0;
}
__device__ __forceinline__ void tma_ld(uint32_t dst, const CUtensorMap* m, int c0, int c1, uint32_t bar) {
  asm volatile("cp.async.bulk.tensor.2d.shared::cluster.global.mbarrier::complete_tx::bytes [%0], [%1, {%3, %4}], [%2];"
               ::"r"(dst), "l"(m), "r"(bar), "r"(c0), "r"(c1) : "memory");
}
__device__ __forceinline__ void tma_ld3(uint32_t dst, const CUtensorMap* m, int c0, int c1, int c2, uint32_t bar) {
  asm volatile("cp.async.bulk.tensor.3d.shared::cluster.global.mbarrier::complete_tx::bytes [%0], [%1, {%3, %4, %5}], [%2];"
               ::"r"(dst), "l"(m), "r"(bar), "r"(c0), "r"(c1), "r"(c2) : "memory");
}
__device__ __forceinline__ void tma_ld5(uint32_t dst, const CUtensorMap* m, int c0, int c4, uint32_t bar) {
  asm volatile("cp.async.bulk.tensor.5d.shared::cluster.global.mbarrier::complete_tx::bytes [%0], [%1, {%3, 0, 0, 0, %4}], [%2];"
               ::"r"(dst), "l"(m), "r"(bar), "r"(c0), "r"(c4) : "memory");
}
__device__ __forceinline__ void tma_prefetch5(const CUtensorMap* m, int c0, int c4) {
  asm volatile("cp.async.bulk.prefetch.tensor.5d.L2.global.tile [%0, {%1, 0, 0, 0, %2}];" ::"l"(m), "r"(c0), "r"(c4) : "memory");
}
__device__ __forceinline__ void tma_prefetch3(const CUtensorMap* m, int c0, int c1, int c2) {
  asm volatile("cp.async.bulk.prefetch.tensor.3d.L2.global.tile [%0, {%1, %2, %3}];" ::"l"(m), "r"(c0), "r"(c1), "r"(c2) : "memory");
}
__device__ __forceinline__ void tma_st(const CUtensorMap* m, int c0, int c1, uint32_t src) {
  asm volatile("cp.async.bulk.tensor.2d.global.shared::cta.bulk_group [%0, {%2, %3}], [%1];" ::"l"(m), "r"(src), "r"(c0), "r"(c1) : "memory");
}
__device__ __forceinline__ void bulk_ld(uint32_t dst, const void* src, int bytes, uint32_t bar) {
  asm volatile("cp.async.bulk.shared::cluster.global.mbarrier::complete_tx::bytes [%0], [%1], %2, [%3];" ::"r"(dst), "l"(src), "r"(bytes), "r"(bar) : "memory");
}
__device__ __forceinline__ void bulk_red_add_f32(void* dst, uint32_t src, int bytes) {
  asm volatile("cp.reduce.async.bulk.global.shared::cta.bulk_group.add.f32 [%0], [%1], %2;" ::"l"(dst), "r"(src), "r"(bytes) : "memory");
}
__device__ __forceinline__ void bulk_commit() { asm volatile("cp.async.bulk.commit_group;" ::: "memory"); }
__device__ __forceinline__ void fence_async_smem() { asm volatile("fence.proxy.async.shared::cta;" ::: "memory"); }
__device__ __forceinline__ void fence_async_global() { asm volatile("fence.proxy.async.global;" ::: "memory"); }
__device__ __forceinline__ void bar_sync(int id, int n) { asm volatile("bar.sync %0, %1;" ::"r"(id), "r"(n) : "memory"); }
__device__ __forceinline__ void bar_arrive(int id, int n) { asm volatile("bar.arrive %0, %1;" ::"r"(id), "r"(n) : "memory"); }
__device__ __forceinline__ bool bar_or(int id, int n, bool v) {
  uint32_t r;
  asm volatile("{\n.reg .pred p, q;\nsetp.ne.u32 q, %3, 0;\nbar.red.or.pred p, %1, %2, q;\nselp.u32 %0, 1, 0, p;\n}" : "=r"(r) : "r"(id), "r"(n), "r"((uint32_t)v) : "memory");
  return r != 0;
}
__device__ __forceinline__ void bulk_wait_read() { asm volatile("cp.async.bulk.wait_group.read 0;" ::: "memory"); }
__device__ __forceinline__ void stg128(void* p, uint4 v) { asm volatile("st.relaxed.gpu.global.v4.u32 [%0], {%1,%2,%3,%4};" ::"l"(p), "r"(v.x), "r"(v.y), "r"(v.z), "r"(v.w) : "memory"); }
constexpr uint32_t UNSET = 0xffffffffu;
constexpr int MAX_RETRY = 1 << 16;
__device__ __forceinline__ void wg_fence() { asm volatile("wgmma.fence.sync.aligned;" ::: "memory"); }
__device__ __forceinline__ void wg_commit() { asm volatile("wgmma.commit_group.sync.aligned;" ::: "memory"); }
template <int N> __device__ __forceinline__ void wg_wait() { asm volatile("wgmma.wait_group.sync.aligned %0;" ::"n"(N) : "memory"); }
__device__ __forceinline__ uint64_t mkdesc(uint32_t addr, uint32_t lbo, uint32_t sbo, int sw) {
  return (uint64_t)((addr & 0x3FFFF) >> 4) | ((uint64_t)(lbo >> 4) << 16) | ((uint64_t)(sbo >> 4) << 32) | ((uint64_t)sw << 62);
}
__device__ __forceinline__ void ldsm4(uint32_t* r, uint32_t a) {
  asm volatile("ldmatrix.sync.aligned.m8n8.x4.shared.b16 {%0,%1,%2,%3}, [%4];" : "=r"(r[0]), "=r"(r[1]), "=r"(r[2]), "=r"(r[3]) : "r"(a) : "memory");
}
__device__ __forceinline__ void ldsm4t(uint32_t* r, uint32_t a) {
  asm volatile("ldmatrix.sync.aligned.m8n8.x4.trans.shared.b16 {%0,%1,%2,%3}, [%4];" : "=r"(r[0]), "=r"(r[1]), "=r"(r[2]), "=r"(r[3]) : "r"(a) : "memory");
}
__device__ __forceinline__ void stsm4(uint32_t a, uint32_t r0, uint32_t r1, uint32_t r2, uint32_t r3) {
  asm volatile("stmatrix.sync.aligned.m8n8.x4.shared.b16 [%0], {%1,%2,%3,%4};" ::"r"(a), "r"(r0), "r"(r1), "r"(r2), "r"(r3) : "memory");
}
__device__ __forceinline__ void stsm4t(uint32_t a, uint32_t r0, uint32_t r1, uint32_t r2, uint32_t r3) {
  asm volatile("stmatrix.sync.aligned.m8n8.x4.trans.shared.b16 [%0], {%1,%2,%3,%4};" ::"r"(a), "r"(r0), "r"(r1), "r"(r2), "r"(r3) : "memory");
}
__device__ __forceinline__ uint32_t movm_t(uint32_t a) { uint32_t r; asm volatile("movmatrix.sync.aligned.m8n8.trans.b16 %0, %1;" : "=r"(r) : "r"(a)); return r; }
__device__ __forceinline__ uint32_t lds32(uint32_t a) { uint32_t v; asm volatile("ld.shared.b32 %0, [%1];" : "=r"(v) : "r"(a) : "memory"); return v; }
__device__ __forceinline__ float2 lds64f(uint32_t a) { float2 v; asm volatile("ld.shared.v2.f32 {%0,%1}, [%2];" : "=f"(v.x), "=f"(v.y) : "r"(a) : "memory"); return v; }
__device__ __forceinline__ float4 lds128f(uint32_t a) { float4 v; asm volatile("ld.shared.v4.f32 {%0,%1,%2,%3}, [%4];" : "=f"(v.x), "=f"(v.y), "=f"(v.z), "=f"(v.w) : "r"(a) : "memory"); return v; }
__device__ __forceinline__ uint4 lds128(uint32_t a) { uint4 v; asm volatile("ld.shared.v4.b32 {%0,%1,%2,%3}, [%4];" : "=r"(v.x), "=r"(v.y), "=r"(v.z), "=r"(v.w) : "r"(a) : "memory"); return v; }
__device__ __forceinline__ void sts128(uint32_t a, uint4 v) { asm volatile("st.shared.v4.b32 [%0], {%1,%2,%3,%4};" ::"r"(a), "r"(v.x), "r"(v.y), "r"(v.z), "r"(v.w) : "memory"); }
__device__ __forceinline__ void sts128f(uint32_t a, float x, float y, float z, float w) { asm volatile("st.shared.v4.f32 [%0], {%1,%2,%3,%4};" ::"r"(a), "f"(x), "f"(y), "f"(z), "f"(w) : "memory"); }
__device__ __forceinline__ void sts32f(uint32_t a, float v) { asm volatile("st.shared.f32 [%0], %1;" ::"r"(a), "f"(v) : "memory"); }
__device__ __forceinline__ void sts16(uint32_t a, uint16_t v) { asm volatile("st.shared.u16 [%0], %1;" ::"r"(a), "h"(v) : "memory"); }
__device__ __forceinline__ uint32_t lds16(uint32_t a) { uint16_t v; asm volatile("ld.shared.u16 %0, [%1];" : "=h"(v) : "r"(a) : "memory"); return v; }
__device__ __forceinline__ uint32_t packbf(float lo, float hi) { uint32_t r; asm("cvt.rn.bf16x2.f32 %0, %1, %2;" : "=r"(r) : "f"(hi), "f"(lo)); return r; }
__device__ __forceinline__ uint32_t prmt0(uint32_t a, uint32_t sel) { uint32_t r; asm("prmt.b32 %0, %1, 0, %2;" : "=r"(r) : "r"(a), "r"(sel)); return r; }
__device__ __forceinline__ float bf_lo(uint32_t v) { return __uint_as_float(v << 16); }
__device__ __forceinline__ float bf_hi(uint32_t v) { return __uint_as_float(v & 0xffff0000u); }
__device__ __forceinline__ float ex2(float x) { float r; asm("ex2.approx.ftz.f32 %0, %1;" : "=f"(r) : "f"(x)); return r; }
__device__ __forceinline__ float rsqrt_approx(float x) { float r; asm("rsqrt.approx.ftz.f32 %0, %1;" : "=f"(r) : "f"(x)); return r; }
__device__ __forceinline__ float rcp_approx(float x) { float r; asm("rcp.approx.ftz.f32 %0, %1;" : "=f"(r) : "f"(x)); return r; }
__device__ __forceinline__ void mma_bf16(float* d, const uint32_t* a, uint32_t b0, uint32_t b1) {
  asm("mma.sync.aligned.m16n8k16.row.col.f32.bf16.bf16.f32 {%0,%1,%2,%3}, {%4,%5,%6,%7}, {%8,%9}, {%0,%1,%2,%3};"
               : "+f"(d[0]), "+f"(d[1]), "+f"(d[2]), "+f"(d[3]) : "r"(a[0]), "r"(a[1]), "r"(a[2]), "r"(a[3]), "r"(b0), "r"(b1));
}
__device__ __forceinline__ void mma_bf16_c(float* d, const uint32_t* a, uint32_t b0, uint32_t b1, const float* c) {
  asm("mma.sync.aligned.m16n8k16.row.col.f32.bf16.bf16.f32 {%0,%1,%2,%3}, {%4,%5,%6,%7}, {%8,%9}, {%10,%11,%12,%13};"
               : "=f"(d[0]), "=f"(d[1]), "=f"(d[2]), "=f"(d[3]) : "r"(a[0]), "r"(a[1]), "r"(a[2]), "r"(a[3]), "r"(b0), "r"(b1),
                 "f"(c[0]), "f"(c[1]), "f"(c[2]), "f"(c[3]));
}
__device__ __forceinline__ void mma_rowsum(float* d, uint32_t a0, uint32_t a1) {
  asm("mma.sync.aligned.m16n8k8.row.col.f32.bf16.bf16.f32 {%0,%1,%2,%3}, {%4,%5}, {%6}, {%7,%7,%7,%7};"
               : "=f"(d[0]), "=f"(d[1]), "=f"(d[2]), "=f"(d[3]) : "r"(a0), "r"(a1), "r"(0x3f803f80u), "f"(0.f));
}
__device__ __forceinline__ void red_release(unsigned* p) { asm volatile("red.release.gpu.global.add.u32 [%0], 1;" ::"l"(p) : "memory"); }
__device__ __forceinline__ void red_relaxed(unsigned* p) { asm volatile("red.relaxed.gpu.global.add.u32 [%0], 1;" ::"l"(p) : "memory"); }
__device__ __forceinline__ unsigned ld_relaxed(const unsigned* p) { unsigned v; asm volatile("ld.relaxed.gpu.global.u32 %0, [%1];" : "=r"(v) : "l"(p) : "memory"); return v; }
__device__ __forceinline__ void spin_until(const unsigned* p, unsigned target) {
  int it = 0;
  while ((int)(ld_relaxed(p) - target) < 0) {
    if (++it > (1 << 23)) __trap();
  }
}
template <typename T> __device__ __forceinline__ void pin(T*& p) { asm volatile("" : "+l"(p) :: "memory"); }
__device__ __forceinline__ void pin(uint32_t& v) { asm volatile("" : "+r"(v) :: "memory"); }
__device__ __forceinline__ void spin_hint(const unsigned* p, unsigned target) {
  spin_until(p, target);
}
__device__ __forceinline__ uint4 ld_tagged(const uint4* p) { uint4 v; asm volatile("ld.relaxed.gpu.global.v4.u32 {%0,%1,%2,%3}, [%4];" : "=r"(v.x), "=r"(v.y), "=r"(v.z), "=r"(v.w) : "l"(p) : "memory"); return v; }
__device__ __forceinline__ uint32_t hadd2(uint32_t a, uint32_t b) { uint32_t r; asm("add.rn.bf16x2 %0, %1, %2;" : "=r"(r) : "r"(a), "r"(b)); return r; }

__device__ __forceinline__ uint32_t hfma2(uint32_t a, uint32_t b, uint32_t c) { uint32_t r; asm("fma.rn.bf16x2 %0, %1, %2, %3;" : "=r"(r) : "r"(a), "r"(b), "r"(c)); return r; }
__device__ __forceinline__ void sts32(uint32_t a, uint32_t v) { asm volatile("st.shared.u32 [%0], %1;" ::"r"(a), "r"(v) : "memory"); }

template <int N> __device__ __forceinline__ void acc_fence(float* a) {
#pragma unroll
  for (int i = 0; i < N; i++) asm volatile("" : "+f"(a[i]) :: "memory");
}

template<int N,int TB> __device__ __forceinline__ void wgmma_rs(float* d, const uint32_t* a, uint64_t db, int sd);
template<int N,int TA,int TB> __device__ __forceinline__ void wgmma_ss(float* d, uint64_t da, uint64_t db, int sd);
template<> __device__ __forceinline__ void wgmma_rs<64,0>(float* d, const uint32_t* a, uint64_t db, int sd) {
  asm volatile("{\n.reg .pred p;\nsetp.ne.b32 p, %37, 0;\nwgmma.mma_async.sync.aligned.m64n64k16.f32.bf16.bf16 {%0,%1,%2,%3,%4,%5,%6,%7,%8,%9,%10,%11,%12,%13,%14,%15,%16,%17,%18,%19,%20,%21,%22,%23,%24,%25,%26,%27,%28,%29,%30,%31}, {%32,%33,%34,%35}, %36, p, 1, 1, 0;\n}\n"
   : "+f"(d[0]),"+f"(d[1]),"+f"(d[2]),"+f"(d[3]),"+f"(d[4]),"+f"(d[5]),"+f"(d[6]),"+f"(d[7]),"+f"(d[8]),"+f"(d[9]),"+f"(d[10]),"+f"(d[11]),"+f"(d[12]),"+f"(d[13]),"+f"(d[14]),"+f"(d[15]),"+f"(d[16]),"+f"(d[17]),"+f"(d[18]),"+f"(d[19]),"+f"(d[20]),"+f"(d[21]),"+f"(d[22]),"+f"(d[23]),"+f"(d[24]),"+f"(d[25]),"+f"(d[26]),"+f"(d[27]),"+f"(d[28]),"+f"(d[29]),"+f"(d[30]),"+f"(d[31])
   : "r"(a[0]), "r"(a[1]), "r"(a[2]), "r"(a[3]), "l"(db), "r"(sd));
}
template<> __device__ __forceinline__ void wgmma_rs<56,0>(float* d, const uint32_t* a, uint64_t db, int sd) {
  asm volatile("{\n.reg .pred p;\nsetp.ne.b32 p, %33, 0;\nwgmma.mma_async.sync.aligned.m64n56k16.f32.bf16.bf16 {%0,%1,%2,%3,%4,%5,%6,%7,%8,%9,%10,%11,%12,%13,%14,%15,%16,%17,%18,%19,%20,%21,%22,%23,%24,%25,%26,%27}, {%28,%29,%30,%31}, %32, p, 1, 1, 0;\n}\n"
   : "+f"(d[0]),"+f"(d[1]),"+f"(d[2]),"+f"(d[3]),"+f"(d[4]),"+f"(d[5]),"+f"(d[6]),"+f"(d[7]),"+f"(d[8]),"+f"(d[9]),"+f"(d[10]),"+f"(d[11]),"+f"(d[12]),"+f"(d[13]),"+f"(d[14]),"+f"(d[15]),"+f"(d[16]),"+f"(d[17]),"+f"(d[18]),"+f"(d[19]),"+f"(d[20]),"+f"(d[21]),"+f"(d[22]),"+f"(d[23]),"+f"(d[24]),"+f"(d[25]),"+f"(d[26]),"+f"(d[27])
   : "r"(a[0]), "r"(a[1]), "r"(a[2]), "r"(a[3]), "l"(db), "r"(sd));
}
template<> __device__ __forceinline__ void wgmma_rs<48,0>(float* d, const uint32_t* a, uint64_t db, int sd) {
  asm volatile("{\n.reg .pred p;\nsetp.ne.b32 p, %29, 0;\nwgmma.mma_async.sync.aligned.m64n48k16.f32.bf16.bf16 {%0,%1,%2,%3,%4,%5,%6,%7,%8,%9,%10,%11,%12,%13,%14,%15,%16,%17,%18,%19,%20,%21,%22,%23}, {%24,%25,%26,%27}, %28, p, 1, 1, 0;\n}\n"
   : "+f"(d[0]),"+f"(d[1]),"+f"(d[2]),"+f"(d[3]),"+f"(d[4]),"+f"(d[5]),"+f"(d[6]),"+f"(d[7]),"+f"(d[8]),"+f"(d[9]),"+f"(d[10]),"+f"(d[11]),"+f"(d[12]),"+f"(d[13]),"+f"(d[14]),"+f"(d[15]),"+f"(d[16]),"+f"(d[17]),"+f"(d[18]),"+f"(d[19]),"+f"(d[20]),"+f"(d[21]),"+f"(d[22]),"+f"(d[23])
   : "r"(a[0]), "r"(a[1]), "r"(a[2]), "r"(a[3]), "l"(db), "r"(sd));
}
template<> __device__ __forceinline__ void wgmma_rs<40,0>(float* d, const uint32_t* a, uint64_t db, int sd) {
  asm volatile("{\n.reg .pred p;\nsetp.ne.b32 p, %25, 0;\nwgmma.mma_async.sync.aligned.m64n40k16.f32.bf16.bf16 {%0,%1,%2,%3,%4,%5,%6,%7,%8,%9,%10,%11,%12,%13,%14,%15,%16,%17,%18,%19}, {%20,%21,%22,%23}, %24, p, 1, 1, 0;\n}\n"
   : "+f"(d[0]),"+f"(d[1]),"+f"(d[2]),"+f"(d[3]),"+f"(d[4]),"+f"(d[5]),"+f"(d[6]),"+f"(d[7]),"+f"(d[8]),"+f"(d[9]),"+f"(d[10]),"+f"(d[11]),"+f"(d[12]),"+f"(d[13]),"+f"(d[14]),"+f"(d[15]),"+f"(d[16]),"+f"(d[17]),"+f"(d[18]),"+f"(d[19])
   : "r"(a[0]), "r"(a[1]), "r"(a[2]), "r"(a[3]), "l"(db), "r"(sd));
}
template<> __device__ __forceinline__ void wgmma_rs<32,0>(float* d, const uint32_t* a, uint64_t db, int sd) {
  asm volatile("{\n.reg .pred p;\nsetp.ne.b32 p, %21, 0;\nwgmma.mma_async.sync.aligned.m64n32k16.f32.bf16.bf16 {%0,%1,%2,%3,%4,%5,%6,%7,%8,%9,%10,%11,%12,%13,%14,%15}, {%16,%17,%18,%19}, %20, p, 1, 1, 0;\n}\n"
   : "+f"(d[0]),"+f"(d[1]),"+f"(d[2]),"+f"(d[3]),"+f"(d[4]),"+f"(d[5]),"+f"(d[6]),"+f"(d[7]),"+f"(d[8]),"+f"(d[9]),"+f"(d[10]),"+f"(d[11]),"+f"(d[12]),"+f"(d[13]),"+f"(d[14]),"+f"(d[15])
   : "r"(a[0]), "r"(a[1]), "r"(a[2]), "r"(a[3]), "l"(db), "r"(sd));
}
template<> __device__ __forceinline__ void wgmma_rs<24,0>(float* d, const uint32_t* a, uint64_t db, int sd) {
  asm volatile("{\n.reg .pred p;\nsetp.ne.b32 p, %17, 0;\nwgmma.mma_async.sync.aligned.m64n24k16.f32.bf16.bf16 {%0,%1,%2,%3,%4,%5,%6,%7,%8,%9,%10,%11}, {%12,%13,%14,%15}, %16, p, 1, 1, 0;\n}\n"
   : "+f"(d[0]),"+f"(d[1]),"+f"(d[2]),"+f"(d[3]),"+f"(d[4]),"+f"(d[5]),"+f"(d[6]),"+f"(d[7]),"+f"(d[8]),"+f"(d[9]),"+f"(d[10]),"+f"(d[11])
   : "r"(a[0]), "r"(a[1]), "r"(a[2]), "r"(a[3]), "l"(db), "r"(sd));
}
template<> __device__ __forceinline__ void wgmma_rs<16,0>(float* d, const uint32_t* a, uint64_t db, int sd) {
  asm volatile("{\n.reg .pred p;\nsetp.ne.b32 p, %13, 0;\nwgmma.mma_async.sync.aligned.m64n16k16.f32.bf16.bf16 {%0,%1,%2,%3,%4,%5,%6,%7}, {%8,%9,%10,%11}, %12, p, 1, 1, 0;\n}\n"
   : "+f"(d[0]),"+f"(d[1]),"+f"(d[2]),"+f"(d[3]),"+f"(d[4]),"+f"(d[5]),"+f"(d[6]),"+f"(d[7])
   : "r"(a[0]), "r"(a[1]), "r"(a[2]), "r"(a[3]), "l"(db), "r"(sd));
}
template<> __device__ __forceinline__ void wgmma_rs<8,0>(float* d, const uint32_t* a, uint64_t db, int sd) {
  asm volatile("{\n.reg .pred p;\nsetp.ne.b32 p, %9, 0;\nwgmma.mma_async.sync.aligned.m64n8k16.f32.bf16.bf16 {%0,%1,%2,%3}, {%4,%5,%6,%7}, %8, p, 1, 1, 0;\n}\n"
   : "+f"(d[0]),"+f"(d[1]),"+f"(d[2]),"+f"(d[3])
   : "r"(a[0]), "r"(a[1]), "r"(a[2]), "r"(a[3]), "l"(db), "r"(sd));
}
template<> __device__ __forceinline__ void wgmma_ss<64,1,0>(float* d, uint64_t da, uint64_t db, int sd) {
  asm volatile("{\n.reg .pred p;\nsetp.ne.b32 p, %34, 0;\nwgmma.mma_async.sync.aligned.m64n64k16.f32.bf16.bf16 {%0,%1,%2,%3,%4,%5,%6,%7,%8,%9,%10,%11,%12,%13,%14,%15,%16,%17,%18,%19,%20,%21,%22,%23,%24,%25,%26,%27,%28,%29,%30,%31}, %32, %33, p, 1, 1, 1, 0;\n}\n"
   : "+f"(d[0]),"+f"(d[1]),"+f"(d[2]),"+f"(d[3]),"+f"(d[4]),"+f"(d[5]),"+f"(d[6]),"+f"(d[7]),"+f"(d[8]),"+f"(d[9]),"+f"(d[10]),"+f"(d[11]),"+f"(d[12]),"+f"(d[13]),"+f"(d[14]),"+f"(d[15]),"+f"(d[16]),"+f"(d[17]),"+f"(d[18]),"+f"(d[19]),"+f"(d[20]),"+f"(d[21]),"+f"(d[22]),"+f"(d[23]),"+f"(d[24]),"+f"(d[25]),"+f"(d[26]),"+f"(d[27]),"+f"(d[28]),"+f"(d[29]),"+f"(d[30]),"+f"(d[31])
   : "l"(da), "l"(db), "r"(sd));
}
template<> __device__ __forceinline__ void wgmma_ss<64,0,1>(float* d, uint64_t da, uint64_t db, int sd) {
  asm volatile("{\n.reg .pred p;\nsetp.ne.b32 p, %34, 0;\nwgmma.mma_async.sync.aligned.m64n64k16.f32.bf16.bf16 {%0,%1,%2,%3,%4,%5,%6,%7,%8,%9,%10,%11,%12,%13,%14,%15,%16,%17,%18,%19,%20,%21,%22,%23,%24,%25,%26,%27,%28,%29,%30,%31}, %32, %33, p, 1, 1, 0, 1;\n}\n"
   : "+f"(d[0]),"+f"(d[1]),"+f"(d[2]),"+f"(d[3]),"+f"(d[4]),"+f"(d[5]),"+f"(d[6]),"+f"(d[7]),"+f"(d[8]),"+f"(d[9]),"+f"(d[10]),"+f"(d[11]),"+f"(d[12]),"+f"(d[13]),"+f"(d[14]),"+f"(d[15]),"+f"(d[16]),"+f"(d[17]),"+f"(d[18]),"+f"(d[19]),"+f"(d[20]),"+f"(d[21]),"+f"(d[22]),"+f"(d[23]),"+f"(d[24]),"+f"(d[25]),"+f"(d[26]),"+f"(d[27]),"+f"(d[28]),"+f"(d[29]),"+f"(d[30]),"+f"(d[31])
   : "l"(da), "l"(db), "r"(sd));
}
template<> __device__ __forceinline__ void wgmma_ss<192,0,1>(float* d, uint64_t da, uint64_t db, int sd) {
  asm volatile("{\n.reg .pred p;\nsetp.ne.b32 p, %98, 0;\nwgmma.mma_async.sync.aligned.m64n192k16.f32.bf16.bf16 {%0,%1,%2,%3,%4,%5,%6,%7,%8,%9,%10,%11,%12,%13,%14,%15,%16,%17,%18,%19,%20,%21,%22,%23,%24,%25,%26,%27,%28,%29,%30,%31,%32,%33,%34,%35,%36,%37,%38,%39,%40,%41,%42,%43,%44,%45,%46,%47,%48,%49,%50,%51,%52,%53,%54,%55,%56,%57,%58,%59,%60,%61,%62,%63,%64,%65,%66,%67,%68,%69,%70,%71,%72,%73,%74,%75,%76,%77,%78,%79,%80,%81,%82,%83,%84,%85,%86,%87,%88,%89,%90,%91,%92,%93,%94,%95}, %96, %97, p, 1, 1, 0, 1;\n}\n"
   : "+f"(d[0]),"+f"(d[1]),"+f"(d[2]),"+f"(d[3]),"+f"(d[4]),"+f"(d[5]),"+f"(d[6]),"+f"(d[7]),"+f"(d[8]),"+f"(d[9]),"+f"(d[10]),"+f"(d[11]),"+f"(d[12]),"+f"(d[13]),"+f"(d[14]),"+f"(d[15]),"+f"(d[16]),"+f"(d[17]),"+f"(d[18]),"+f"(d[19]),"+f"(d[20]),"+f"(d[21]),"+f"(d[22]),"+f"(d[23]),"+f"(d[24]),"+f"(d[25]),"+f"(d[26]),"+f"(d[27]),"+f"(d[28]),"+f"(d[29]),"+f"(d[30]),"+f"(d[31]),"+f"(d[32]),"+f"(d[33]),"+f"(d[34]),"+f"(d[35]),"+f"(d[36]),"+f"(d[37]),"+f"(d[38]),"+f"(d[39]),"+f"(d[40]),"+f"(d[41]),"+f"(d[42]),"+f"(d[43]),"+f"(d[44]),"+f"(d[45]),"+f"(d[46]),"+f"(d[47]),"+f"(d[48]),"+f"(d[49]),"+f"(d[50]),"+f"(d[51]),"+f"(d[52]),"+f"(d[53]),"+f"(d[54]),"+f"(d[55]),"+f"(d[56]),"+f"(d[57]),"+f"(d[58]),"+f"(d[59]),"+f"(d[60]),"+f"(d[61]),"+f"(d[62]),"+f"(d[63]),"+f"(d[64]),"+f"(d[65]),"+f"(d[66]),"+f"(d[67]),"+f"(d[68]),"+f"(d[69]),"+f"(d[70]),"+f"(d[71]),"+f"(d[72]),"+f"(d[73]),"+f"(d[74]),"+f"(d[75]),"+f"(d[76]),"+f"(d[77]),"+f"(d[78]),"+f"(d[79]),"+f"(d[80]),"+f"(d[81]),"+f"(d[82]),"+f"(d[83]),"+f"(d[84]),"+f"(d[85]),"+f"(d[86]),"+f"(d[87]),"+f"(d[88]),"+f"(d[89]),"+f"(d[90]),"+f"(d[91]),"+f"(d[92]),"+f"(d[93]),"+f"(d[94]),"+f"(d[95])
   : "l"(da), "l"(db), "r"(sd));
}
template<> __device__ __forceinline__ void wgmma_ss<192,1,1>(float* d, uint64_t da, uint64_t db, int sd) {
  asm volatile("{\n.reg .pred p;\nsetp.ne.b32 p, %98, 0;\nwgmma.mma_async.sync.aligned.m64n192k16.f32.bf16.bf16 {%0,%1,%2,%3,%4,%5,%6,%7,%8,%9,%10,%11,%12,%13,%14,%15,%16,%17,%18,%19,%20,%21,%22,%23,%24,%25,%26,%27,%28,%29,%30,%31,%32,%33,%34,%35,%36,%37,%38,%39,%40,%41,%42,%43,%44,%45,%46,%47,%48,%49,%50,%51,%52,%53,%54,%55,%56,%57,%58,%59,%60,%61,%62,%63,%64,%65,%66,%67,%68,%69,%70,%71,%72,%73,%74,%75,%76,%77,%78,%79,%80,%81,%82,%83,%84,%85,%86,%87,%88,%89,%90,%91,%92,%93,%94,%95}, %96, %97, p, 1, 1, 1, 1;\n}\n"
   : "+f"(d[0]),"+f"(d[1]),"+f"(d[2]),"+f"(d[3]),"+f"(d[4]),"+f"(d[5]),"+f"(d[6]),"+f"(d[7]),"+f"(d[8]),"+f"(d[9]),"+f"(d[10]),"+f"(d[11]),"+f"(d[12]),"+f"(d[13]),"+f"(d[14]),"+f"(d[15]),"+f"(d[16]),"+f"(d[17]),"+f"(d[18]),"+f"(d[19]),"+f"(d[20]),"+f"(d[21]),"+f"(d[22]),"+f"(d[23]),"+f"(d[24]),"+f"(d[25]),"+f"(d[26]),"+f"(d[27]),"+f"(d[28]),"+f"(d[29]),"+f"(d[30]),"+f"(d[31]),"+f"(d[32]),"+f"(d[33]),"+f"(d[34]),"+f"(d[35]),"+f"(d[36]),"+f"(d[37]),"+f"(d[38]),"+f"(d[39]),"+f"(d[40]),"+f"(d[41]),"+f"(d[42]),"+f"(d[43]),"+f"(d[44]),"+f"(d[45]),"+f"(d[46]),"+f"(d[47]),"+f"(d[48]),"+f"(d[49]),"+f"(d[50]),"+f"(d[51]),"+f"(d[52]),"+f"(d[53]),"+f"(d[54]),"+f"(d[55]),"+f"(d[56]),"+f"(d[57]),"+f"(d[58]),"+f"(d[59]),"+f"(d[60]),"+f"(d[61]),"+f"(d[62]),"+f"(d[63]),"+f"(d[64]),"+f"(d[65]),"+f"(d[66]),"+f"(d[67]),"+f"(d[68]),"+f"(d[69]),"+f"(d[70]),"+f"(d[71]),"+f"(d[72]),"+f"(d[73]),"+f"(d[74]),"+f"(d[75]),"+f"(d[76]),"+f"(d[77]),"+f"(d[78]),"+f"(d[79]),"+f"(d[80]),"+f"(d[81]),"+f"(d[82]),"+f"(d[83]),"+f"(d[84]),"+f"(d[85]),"+f"(d[86]),"+f"(d[87]),"+f"(d[88]),"+f"(d[89]),"+f"(d[90]),"+f"(d[91]),"+f"(d[92]),"+f"(d[93]),"+f"(d[94]),"+f"(d[95])
   : "l"(da), "l"(db), "r"(sd));
}

template <bool TR>
__device__ __forceinline__ void gemm_section(float* acc, float& mean0, float& mean1, float& rstd0, float& rstd1,
                                             uint32_t sb, int blk, int hg, int wg, int w, int lane) {
  constexpr int layer = TR ? 1 : 0;
  constexpr int TURN = TR ? TURN1 : TURN0;
  constexpr int LSTAT = TURN < 4 ? TURN - 1 : 3;
  const uint32_t bar = sb + SM_BAR;
  const int g = lane >> 2, t = lane & 3;
  const bool leader = (w == 0) && (lane == 0);
  const int statpos = hg < 3 ? 1 : wg ? LSTAT : TR ? 3 : 2;
  const bool copy = hg >= 3 && wg == 0;
  const int cut = wg ? TURN : 4;
  auto wait_full = [&](int c) {
    mbar_wait(bar + 8 * (B_XF + 8 * wg + c), layer);
    mbar_wait(bar + 8 * (B_WF + c), layer);
  };
  auto peek = [&](int c) {
    const bool x = mbar_test(bar + 8 * (B_XF + 8 * wg + c), layer), y = mbar_test(bar + 8 * (B_WF + c), layer);
    return x && y;
  };
  const uint64_t da0 = mkdesc(sb, TR ? 8192 : 16, 1024, 1), db0 = mkdesc(sb, 8192, 1024, 1);
  uint32_t xt = wg ? 0xfedcba98u : 0x21043210u;
  uint64_t wt = 0x0816131005161310ull;
  uint64_t da = da0 + ((xt & 15) << 9), db = db0 + (16 << 9);
  auto issue = [&](int c, int first) {
    wg_fence();
#pragma unroll
    for (int ks = 0; ks < 4; ks++) wgmma_ss<192, TR ? 1 : 0, 1>(acc, da + (TR ? ks * 128 : ks * 2), db + ks * 128, !first || ks != 0);
    wg_commit();
    xt >>= 4; wt >>= 8;
    da = da0 + ((xt & 15) << 9); db = db0 + (((uint32_t)wt & 31) << 9);
  };
  wait_full(0);
  bool ready = peek(1);
  issue(0, 1);
  TSW(0);
#pragma unroll 1
  for (int c = 1; c < cut; c++) {
    if (!ready) wait_full(c);
    issue(c, 0);
    ready = peek(c + 1);
    wg_wait<1>();
    if (leader) mbar_arrive(bar + 8 * (B_DN + 8 * wg + c - 1));
    if (wg == 1 && c == cut - 1) {
      wg_wait<0>();
      if (leader) mbar_arrive(bar + 8 * (B_DN + 8 + c));
    }
    if (c == statpos) {
      mbar_wait(bar + 8 * (copy ? B_SC : B_XF + 8 * wg + hg), layer);
      uint32_t A[16];
      const uint32_t xb = sb + (copy ? P_R : 8 * wg + hg) * PG;
#pragma unroll
      for (int ks = 0; ks < 4; ks++) {
        if (!TR) {
          const int row = 16 * w + (lane & 15), kc = 2 * ks + (lane >> 4);
          ldsm4(&A[4 * ks], xb + row * 128 + ((kc ^ (row & 7)) << 4));
        } else {
          const int k = 16 * ks + (lane & 7) + 8 * (lane >> 4), pc = 2 * w + ((lane >> 3) & 1);
          ldsm4t(&A[4 * ks], xb + k * 128 + ((pc ^ (k & 7)) << 4));
        }
      }
      float s0 = 0.f, q0 = 0.f, s1 = 0.f, q1 = 0.f;
#pragma unroll
      for (int i = 0; i < 16; i += 2) {
        const float a = bf_lo(A[i]), b = bf_hi(A[i]), c_ = bf_lo(A[i + 1]), d = bf_hi(A[i + 1]);
        s0 += a + b; q0 = fmaf(a, a, q0); q0 = fmaf(b, b, q0);
        s1 += c_ + d; q1 = fmaf(c_, c_, q1); q1 = fmaf(d, d, q1);
      }
#pragma unroll
      for (int o = 1; o <= 2; o <<= 1) {
        s0 += __shfl_xor_sync(~0u, s0, o); q0 += __shfl_xor_sync(~0u, q0, o);
        s1 += __shfl_xor_sync(~0u, s1, o); q1 += __shfl_xor_sync(~0u, q1, o);
      }
      if (t < 2)
        asm volatile("red.relaxed.gpu.global.add.v4.f32 [%0], {%1,%2,%3,%4};" ::"l"(g_rows + layer * LSEQ + blk * 64 + 16 * w + g + 8 * t),
                     "f"(t ? s1 : s0), "f"(t ? q1 : q0), "f"(1.f), "f"(0.f) : "memory");
    }
  }
  if (wg == 1) {
#pragma unroll 1
    for (int c = cut; c < 8; c++) wait_full(c);
    ready = true;
    bar_sync(5, 256);
  }
#pragma unroll 1
  for (int c = cut; c < 8; c++) {
    if (!ready) wait_full(c);
    issue(c, 0);
    if (wg == 1) {
      wg_wait<2>();
      if (leader && c >= cut + 2) mbar_arrive(bar + 8 * (B_DN + 8 + c - 2));
    } else if (c == 7) {
      bar_arrive(5, 256);
    } else {
      ready = peek(c + 1);
      wg_wait<1>();
      if (leader && c < 6) mbar_arrive(bar + 8 * (B_DN + c - 1));
    }
  }
  mbar_wait(bar + 8 * (B_LN + wg), layer);
  const float4 ln = lds128f(sb + ln_off(wg) + (8 * w + g) * 16);
  mean0 = ln.x; rstd0 = ln.y; mean1 = ln.z; rstd1 = ln.w;
  wg_wait<0>();
  acc_fence<96>(acc);
  if (leader) mbar_arrive(bar + 8 * (B_DN + 8 * wg + 7));
}

__device__ __forceinline__ void attn_phase(const Params& p, uint32_t sb, int layer, int rb, int hg, int wg, int w) {
  const int lane = opaque_tid() & 31;
  const int g = lane >> 2, t = lane & 3;
  const uint32_t bar = sb + SM_BAR;
  const int blk = 16 * wg + rb;
  float acc[96];
  float2 cs[24];
  float mean0, mean1, rstd0, rstd1;
  if (layer) gemm_section<true>(acc, mean0, mean1, rstd0, rstd1, sb, blk, hg, wg, w, lane);
  else gemm_section<false>(acc, mean0, mean1, rstd0, rstd1, sb, blk, hg, wg, w, lane);
  TSW(1);
#pragma unroll
  for (int j = 8; j < 24; j++) cs[j] = lds64f(sb + SM_CS + 4 * (8 * j + 2 * t));
  const uint32_t kvx = sb + (wg ? 22 : 0) * PG;

  uint32_t kb[4][8], vb[4][8], qa[4][4];
  {
    const float nm0 = -mean0 * rstd0, nm1 = -mean1 * rstd1;
    const int st_row = 16 * w + (lane & 7) + 8 * ((lane >> 3) & 1);
    const uint32_t st_base = kvx + st_row * 256;
    const bool sender = (w == 3 && blk < 31);
    uint4* halo = &g_halo[(blk * 8 + hg) * 256 + lane];
    uint32_t r[4][2][4];
#pragma unroll
    for (int h = 0; h < 4; h++) {
#pragma unroll
      for (int kv = 0; kv < 2; kv++) {
#pragma unroll
        for (int dh = 0; dh < 2; dh++) {
          const int j = 8 + kv * 8 + 2 * h + dh;
          const float2 c2 = cs[j];
          const float v0 = fmaf(acc[4 * j + 0], rstd0, nm0 * c2.x), v1 = fmaf(acc[4 * j + 1], rstd0, nm0 * c2.y);
          const float v2 = fmaf(acc[4 * j + 2], rstd1, nm1 * c2.x), v3 = fmaf(acc[4 * j + 3], rstd1, nm1 * c2.y);
          r[h][kv][2 * dh] = packbf(v0, v1);
          r[h][kv][2 * dh + 1] = packbf(v2, v3);
        }
      }
      if (sender) {
        stg128(halo + (2 * h) * 32, make_uint4(r[h][0][0], r[h][0][2], r[h][0][1], r[h][0][3]));
        stg128(halo + (2 * h + 1) * 32, make_uint4(r[h][1][0], r[h][1][1], r[h][1][2], r[h][1][3]));
      }
    }
#pragma unroll
    for (int j = 0; j < 8; j++) cs[j] = lds64f(sb + SM_CS + 4 * (8 * j + 2 * t));
    mbar_wait(bar + 8 * (B_DN + 7), layer);
#pragma unroll
    for (int h = 0; h < 4; h++) {
#pragma unroll
      for (int kv = 0; kv < 2; kv++) {
        const int chunk = 4 * h + 2 * kv + (lane >> 4);
        if (w < 3) stsm4(st_base + (((chunk & 8) | ((chunk ^ st_row) & 7)) << 4), r[h][kv][0], r[h][kv][1], r[h][kv][2], r[h][kv][3]);
      }
      kb[h][4] = r[h][0][0]; kb[h][5] = r[h][0][2]; kb[h][6] = r[h][0][1]; kb[h][7] = r[h][0][3];
      vb[h][4] = movm_t(r[h][1][0]); vb[h][5] = movm_t(r[h][1][1]); vb[h][6] = movm_t(r[h][1][2]); vb[h][7] = movm_t(r[h][1][3]);
    }
#pragma unroll
    for (int h = 0; h < 4; h++) {
#pragma unroll
      for (int dh = 0; dh < 2; dh++) {
        const int j = 2 * h + dh;
        const float2 c2 = cs[j];
        qa[h][2 * dh] = packbf(fmaf(-mean0, c2.x, acc[4 * j + 0]), fmaf(-mean0, c2.y, acc[4 * j + 1]));
        qa[h][2 * dh + 1] = packbf(fmaf(-mean1, c2.x, acc[4 * j + 2]), fmaf(-mean1, c2.y, acc[4 * j + 3]));
      }
    }
  }
  uint4* op = (uint4*)g_O + ((layer * 32 + blk) * 8 + hg) * 512 + 64 * t + 16 * w + g;
  unsigned* ocnt = &g_cnt[(C_O + layer * 32 + blk) * 32];
  pin(op); pin(ocnt);
  const int e = t - (g >> 1);
  const bool par = g & 1, epos = e >= 1;
  uint32_t selA = par ? 0x1044u : 0x4410u, selB0 = epos ? (par ? 0x3244u : 0x4432u) : 0x4444u, selB1 = epos ? 0x4444u : (par ? 0x3244u : 0x4432u);
  const float cl2 = 0.25f * 1.4426950408889634f;
  const float sc0 = rstd0 * cl2, sc1 = rstd1 * cl2;
  float c0[4];
#pragma unroll
  for (int k = 0; k < 4; k++) asm volatile("mov.b32 %0, %1;" : "=f"(c0[k]) : "f"((blk == 0 && w == 0) ? -INFINITY : 0.f));
  const uint32_t zero = (uint32_t)opaque_tid() & 0x80000000u;
  pin(selA); pin(selB0); pin(selB1);
  bar_sync(2 + wg, 128);
  TSW(2);
  {
    const uint32_t prev_base = kvx + (16 * w - 16) * 256;
    const int mi = lane >> 3;
    const int r = 8 * (mi >> 1) + (lane & 7), r2 = 8 * (mi & 1) + (lane & 7);
    if (w != 0) {
#pragma unroll
      for (int h = 0; h < 4; h++) {
        const int ch = 4 * h + (mi & 1), ch2 = 4 * h + 2 + (mi >> 1);
        ldsm4(&kb[h][0], prev_base + r * 256 + (((ch & 8) | ((ch ^ r) & 7)) << 4));
        ldsm4t(&vb[h][0], prev_base + r2 * 256 + (((ch2 & 8) | ((ch2 ^ r2) & 7)) << 4));
      }
    } else if (blk > 0) {
      uint4* src = &g_halo[((blk - 1) * 8 + hg) * 256 + lane];
      uint4 hv[8];
      int it = 0;
      bool ok;
      do {
        ok = true;
#pragma unroll
        for (int i = 0; i < 8; i++) hv[i] = ld_tagged(src + i * 32);
#pragma unroll
        for (int i = 0; i < 8; i++) ok = ok && hv[i].x != UNSET;
      } while (!__all_sync(~0u, ok) && ++it < (1 << 20));
      if (layer == 0) {
#pragma unroll
        for (int i = 0; i < 2; i++) stg128(src + i * 128 + (lane >> 1) * 6, make_uint4(UNSET, UNSET, UNSET, UNSET));
      }
#pragma unroll
      for (int h = 0; h < 4; h++) {
        kb[h][0] = hv[2 * h].x; kb[h][1] = hv[2 * h].y; kb[h][2] = hv[2 * h].z; kb[h][3] = hv[2 * h].w;
        vb[h][0] = movm_t(hv[2 * h + 1].x); vb[h][1] = movm_t(hv[2 * h + 1].y);
        vb[h][2] = movm_t(hv[2 * h + 1].z); vb[h][3] = movm_t(hv[2 * h + 1].w);
      }
    } else {
#pragma unroll
      for (int h = 0; h < 4; h++)
#pragma unroll
        for (int k = 0; k < 4; k++) kb[h][k] = vb[h][k] = 0u;
    }
    TSW(3);
  }
  mbar_wait(bar + 8 * (B_DN + 15), layer);
  TSW(4);

  float vA0[4], vB0[4], vA1[4], vB1[4];
#pragma unroll
  for (int h = 0; h < 4; h++) {
    float S[4][4];
#pragma unroll
    for (int j = 0; j < 4; j++) {
      S[j][0] = S[j][1] = S[j][2] = S[j][3] = 0.f;
      if (j < 2) mma_bf16_c(S[j], qa[h], kb[h][2 * j], kb[h][2 * j + 1], c0);
      else mma_bf16(S[j], qa[h], kb[h][2 * j], kb[h][2 * j + 1]);
    }
    vA0[h] = par ? S[1][1] : S[1][0];
    vB0[h] = epos ? (par ? S[0][1] : S[0][0]) : (par ? S[2][1] : S[2][0]);
    vA1[h] = par ? S[2][3] : S[2][2];
    vB1[h] = epos ? (par ? S[1][3] : S[1][2]) : (par ? S[3][3] : S[3][2]);
  }
  float m0[4], m1[4];
#pragma unroll
  for (int h = 0; h < 4; h++) { m0[h] = fmaxf(vA0[h], vB0[h]); m1[h] = fmaxf(vA1[h], vB1[h]); }
#pragma unroll
  for (int o = 1; o <= 2; o <<= 1) {
#pragma unroll
    for (int h = 0; h < 4; h++) {
      m0[h] = fmaxf(m0[h], __shfl_xor_sync(~0u, m0[h], o));
      m1[h] = fmaxf(m1[h], __shfl_xor_sync(~0u, m1[h], o));
    }
  }
  float O0[4][4], O1[4][4], Z[4][4];
#pragma unroll
  for (int h = 0; h < 4; h++) {
    const float mm0 = -m0[h] * sc0, mm1 = -m1[h] * sc1;
    const float pA0 = ex2(fmaf(vA0[h], sc0, mm0)), pB0 = ex2(fmaf(vB0[h], sc0, mm0));
    const float pA1 = ex2(fmaf(vA1[h], sc1, mm1)), pB1 = ex2(fmaf(vB1[h], sc1, mm1));
    const uint32_t h0 = packbf(pA0, pB0), h1 = packbf(pA1, pB1);
    const uint32_t P0[4] = {prmt0(h0, selB0), h0 & zero, prmt0(h0, selA), prmt0(h1, selB0)};
    const uint32_t P1[4] = {prmt0(h0, selB1), prmt0(h1, selA), h1 & zero, prmt0(h1, selB1)};
#pragma unroll
    for (int k = 0; k < 4; k++) O0[h][k] = O1[h][k] = 0.f;
    mma_rowsum(Z[h], h0, h1);
    mma_bf16(O0[h], P0, vb[h][0], vb[h][1]); mma_bf16(O1[h], P0, vb[h][2], vb[h][3]);
    mma_bf16(O0[h], P1, vb[h][4], vb[h][5]); mma_bf16(O1[h], P1, vb[h][6], vb[h][7]);
  }
  if (lane == 0) mbar_arrive(bar + 8 * (B_OST + wg));
#pragma unroll
  for (int h = 0; h < 4; h += 2) {
    const float i0 = rcp_approx(Z[h][0]), i1 = rcp_approx(Z[h][2]), j0 = rcp_approx(Z[h + 1][0]), j1 = rcp_approx(Z[h + 1][2]);
    stg128(op + 128 * h, make_uint4(packbf(O0[h][0] * i0, O0[h][1] * i0), packbf(O1[h][0] * i0, O1[h][1] * i0),
                                   packbf(O0[h + 1][0] * j0, O0[h + 1][1] * j0), packbf(O1[h + 1][0] * j0, O1[h + 1][1] * j0)));
    stg128(op + 128 * h + 8, make_uint4(packbf(O0[h][2] * i1, O0[h][3] * i1), packbf(O1[h][2] * i1, O1[h][3] * i1),
                                            packbf(O0[h + 1][2] * j1, O0[h + 1][3] * j1), packbf(O1[h + 1][2] * j1, O1[h + 1][3] * j1)));
  }
  TSW(5);
  __syncwarp();
  if (elect_one()) red_relaxed(ocnt);
  TSW(6);
}

__device__ __forceinline__ void conv_load(uint32_t* A, uint32_t pe);
__device__ __forceinline__ void proj_phase(const Params& p, uint32_t sb, int layer, int rb, int q, uint32_t* A0, uint32_t* A1) {
  const int lane = opaque_tid() & 31;
  const int wg = __shfl_sync(~0u, opaque_tid() >> 7, 0), w = __shfl_sync(~0u, (opaque_tid() >> 5) & 3, 0);
  const bool TR = layer != 0;
  const int t = lane & 3;
  const uint32_t bar = sb + SM_BAR;
  const uint32_t rbx = sb + (P_R + wg) * PG;
  const uint32_t rsrc = sb + (wg ? 2 : P_R) * PG;
  const int blk = 16 * wg + rb;
  mbar_wait(bar + 8 * (B_RF + wg), layer);
  mbar_wait(bar + 8 * B_WOF, layer);
  const uint32_t stg = sb + (wg ? SM_KGT : SM_STG);
  if (layer) {
    const uint32_t pe = sb + cv_pe(wg, 1) + 4 * (16 + 16 * w + (lane >> 2) - 2 * t);
    mbar_wait(bar + 8 * B_PE, 1);
    conv_load(A0, pe);
    conv_load(A1, pe + 2 * 4480);
    __syncwarp();
    if (lane == 0) mbar_arrive(bar + 8 * B_AL);
  } else {
#pragma unroll
    for (int i = 0; i < 68; i++) {
      asm volatile("mov.b32 %0, 0;" : "=r"(A0[i]));
      asm volatile("mov.b32 %0, 0;" : "=r"(A1[i]));
    }
  }
  bool clean = false, staged = false;
#pragma unroll 1
  for (int attempt = 0; attempt < MAX_RETRY; attempt++) {
  uint32_t res[16];
  if (!TR) {
#pragma unroll
    for (int j = 0; j < 8; j += 2) {
      const int mi = lane >> 3;
      const int row = 16 * w + (lane & 7) + 8 * (mi & 1), ch = j + (mi >> 1);
      ldsm4(&res[2 * j], rsrc + row * 128 + ((ch ^ (row & 7)) << 4));
    }
  } else {
#pragma unroll
    for (int j = 0; j < 8; j += 2) {
      const int mi = lane >> 3;
      const int line = 8 * (j + (mi >> 1)) + (lane & 7), pc = 2 * w + (mi & 1);
      ldsm4t(&res[2 * j], rsrc + line * 128 + ((pc ^ (line & 7)) << 4));
    }
  }
  float acc[32];
#pragma unroll
  for (int j = 0; j < 16; j++) { acc[2 * j] = bf_lo(res[j]); acc[2 * j + 1] = bf_hi(res[j]); }
  acc_fence<32>(acc);
  if (wg) mbar_wait(bar + 8 * B_PG, layer);
  const int wg2 = __shfl_sync(~0u, opaque_tid() >> 7, 0);
  const uint64_t da0 = mkdesc(sb, 1024, 128, 0), db0 = mkdesc(sb, 8192, 1024, 1);
#pragma unroll
  for (int c = 0; c < 4; c++) {
    mbar_wait(bar + 8 * (B_OF + 4 * wg + c), layer);
    if (c == 0) TSW(7);
    const uint64_t da = da0 + (uint32_t)(o_page(wg2, c) * 512);
#pragma unroll
    for (int ks = 0; ks < 8; ks++) {
      if (ks % 4 == 0) { if (ks) wg_commit(); if (wg2) wg_wait<0>(); wg_fence(); }
      wgmma_ss<64, 0, 1>(acc, da + ks * 128, db0 + wo_page(2 * c + (ks >> 2)) * 512 + (ks & 3) * 128, 1);
    }
    wg_commit();
  }
  if (wg) mbar_wait(bar + 8 * B_KG, 0);
  wg_wait<0>();
  acc_fence<32>(acc);
  TSW(8);
  if (!clean) {
    const float chk = acc[0] + acc[2];
    clean = __all_sync(~0u, chk == chk);
    if (clean && lane == 0) mbar_arrive(bar + 8 * (B_PDONE + wg));
  }
  float s0 = 0.f, q0 = 0.f, s1 = 0.f, q1 = 0.f;
  uint32_t o[16];
#pragma unroll
  for (int j = 0; j < 8; j++) {
    const float a = acc[4 * j], b = acc[4 * j + 1], c = acc[4 * j + 2], d = acc[4 * j + 3];
    o[2 * j] = packbf(a, b);
    o[2 * j + 1] = packbf(c, d);
    s0 += a + b; q0 = fmaf(a, a, q0); q0 = fmaf(b, b, q0);
    s1 += c + d; q1 = fmaf(c, c, q1); q1 = fmaf(d, d, q1);
  }
#pragma unroll
  for (int j = 0; j < 8; j += 2) {
    const int mi = lane >> 3;
    const int line = 8 * (j + (mi >> 1)) + (lane & 7), pc = 2 * w + (mi & 1);
    stsm4t(rbx + line * 128 + ((pc ^ (line & 7)) << 4), o[2 * j], o[2 * j + 1], o[2 * j + 2], o[2 * j + 3]);
  }
#pragma unroll
  for (int o2 = 1; o2 <= 2; o2 <<= 1) {
    s0 += __shfl_xor_sync(~0u, s0, o2); q0 += __shfl_xor_sync(~0u, q0, o2);
    s1 += __shfl_xor_sync(~0u, s1, o2); q1 += __shfl_xor_sync(~0u, q1, o2);
  }
  {
    const int i = 2 * (lane >> 2) + (t & 1), k = (i * 11) >> 5;
    const float v = (t == 0) ? s0 : (t == 1) ? q0 : (t == 2) ? s1 : q1;
    sts32f(stg + k * 128 + (2 * w + (t >> 1)) * 16 + (i - 3 * k) * 4, v);
  }
  TSW(9);
  fence_async_smem();
  if (attempt == 0 && clean) {
    staged = true;
    __syncwarp();
    if (lane == 0) mbar_arrive(bar + 8 * (B_STG + wg));
  }
  if (!bar_or(2 + wg, 128, !clean)) break;
  const int rtp = mbar_test(bar + 8 * (B_RT + wg), 0);
  bool unset = false;
#pragma unroll
  for (int i = 0; i < 4; i++) unset |= lds32(sb + o_page(wg, i) * PG + (32 * w + lane) * 128) == UNSET;
  if (!bar_or(2 + wg, 128, unset)) break;
  if (w == 0 && elect_one()) {
    fence_async_smem();
    mbar_expect(bar + 8 * (B_RT + wg), 9 * PG);
    if (layer == 0) tma_ld(rsrc, &p.mapX, q * 64, blk * 64, bar + 8 * (B_RT + wg));
    else tma_ld(rsrc, &p.mapXT, blk * 64, DM + q * 64, bar + 8 * (B_RT + wg));
#pragma unroll 1
    for (int c = 0; c < 4; c++) bulk_ld(sb + o_page(wg, c) * PG, g_O + ((layer * 32 + blk) * 4 + c) * PG, 2 * PG, bar + 8 * (B_RT + wg));
  }
  mbar_wait(bar + 8 * (B_RT + wg), rtp);
  RETRY(0);
  }
  if (!clean && lane == 0) mbar_arrive(bar + 8 * (B_PDONE + wg));
  if (!staged && lane == 0) mbar_arrive(bar + 8 * (B_STG + wg));
  TSW(10);
}

__device__ __forceinline__ void conv_load(uint32_t* A, uint32_t pe) {
#pragma unroll
  for (int m = 0; m < 17; m++) {
    A[4 * m + 2] = lds32(pe + 4 * (64 * m - 8));
    A[4 * m + 0] = lds32(pe + 4 * (64 * m));
    A[4 * m + 1] = lds32(pe + 4 * (64 * m + 8));
    asm volatile("mov.b32 %0, %1;" : "=r"(A[4 * m + 3]) : "r"(A[4 * m + 0]));
  }
}
template <int M> __device__ __forceinline__ void conv_tri(float* acc, const uint32_t* A, uint64_t d) {
  if constexpr (M < 16) {
    wgmma_rs<64 - 8 * (M / 2), 0>(acc, A + 4 * M, d + (uint64_t)(64 + 4 * M), M != 0);
    conv_tri<M + 1>(acc, A, d);
  }
}
__device__ __forceinline__ void conv_mma0(float* acc, const uint32_t* A, uint64_t d) {
  wg_fence();
  conv_tri<0>(acc, A, d);
  wg_commit();
}
__device__ __forceinline__ void conv_mma1(float* acc, const uint32_t* A, uint64_t d, uint64_t ds, uint64_t df) {
  wg_fence();
#pragma unroll
  for (int m = 0; m < 17; m++) wgmma_rs<64, 0>(acc, A + 4 * m, d + (uint64_t)(4 * m), m != 0);
  wgmma_ss<64, 1, 0>(acc, ds, df, 1);
  wgmma_ss<64, 1, 0>(acc, ds + 128, df + 128, 1);
  wg_commit();
}
__device__ __forceinline__ void conv_store(float* acc, uint32_t pb, uint32_t over, int w) {
  acc_fence<32>(acc);
  const int l = opaque_tid() & 31, mt = l >> 3;
  int c = 2 * (63 - 8 * (mt >> 1) - (l & 7) + w) + (mt & 1);
  c ^= (c >> 3) & 1;
  const uint32_t a0 = pb + c * 16;
#pragma unroll
  for (int j = 0; j < 8; j += 2)
    stsm4t(j == 0 ? (c < 128 ? a0 : over + (c - 128) * 16) : a0 - 256 * j, packbf(acc[4 * j], acc[4 * j + 1]), packbf(acc[4 * j + 2], acc[4 * j + 3]),
           packbf(acc[4 * j + 4], acc[4 * j + 5]), packbf(acc[4 * j + 6], acc[4 * j + 7]));
}
__device__ __forceinline__ void conv_sums(uint32_t sb, int lc, int ht) {
  const int m = ht - 1;
  uint4 v[2][3];
#pragma unroll
  for (int c = 0; c < 2; c++)
#pragma unroll
    for (int k = 0; k < 3; k++) {
      const int mm = m - 1 + k;
      v[c][k] = lds128(sb + cv_u(lc + c) + (mm >= 0 ? (mm & 1) * CV_UH + (127 - (mm >> 1)) * 16 : 128 * 16));
    }
  const int ce = m + 2, co = m + 1;
#pragma unroll
  for (int c = 0; c < 2; c++) {
    const uint32_t x[8] = {v[c][0].z, v[c][0].w, v[c][1].x, v[c][1].y, v[c][1].z, v[c][1].w, v[c][2].x, v[c][2].y};
    float pv[16];
#pragma unroll
    for (int k = 0; k < 8; k++) { pv[2 * k] = bf_lo(x[k]); pv[2 * k + 1] = bf_hi(x[k]); }
    float t2[15], t4[13], s9[8], s7[8];
#pragma unroll
    for (int i = 0; i < 15; i++) t2[i] = pv[i] + pv[i + 1];
#pragma unroll
    for (int i = 0; i < 13; i++) t4[i] = t2[i] + t2[i + 2];
#pragma unroll
    for (int i = 0; i < 8; i++) {
      s9[i] = (t4[i] + t4[i + 4]) + pv[i + 8];
      s7[i] = (t4[i + 1] + t2[i + 5]) + pv[i + 7];
    }
    const uint4 e4 = make_uint4(packbf(s9[0], s9[1]), packbf(s9[2], s9[3]), packbf(s9[4], s9[5]), packbf(s9[6], s9[7]));
    if (ce < 128) sts128(sb + cv_se(lc + c) + ((ce ^ ((ce >> 3) & 7)) << 4), e4);
    else sts128(sb + cv_se(lc + c), make_uint4(0, 0, 0, 0));
    sts128(sb + cv_so(lc + c) + ((co ^ ((co >> 3) & 7)) << 4),
           make_uint4(packbf(s7[0], s7[1]), packbf(s7[2], s7[3]), packbf(s7[4], s7[5]), packbf(s7[6], s7[7])));
  }
}

template <int HALF, int NCH, int STEP = 1>
__device__ __forceinline__ void conv_epi(uint32_t sb, bf16* out, int lc, int c) {
  uint4 v[NCH][4], xr[NCH];
  const uint32_t sw = (c ^ ((c >> 3) & 1)) * 16;
#pragma unroll
  for (int u = 0; u < NCH; u++) {
#pragma unroll
    for (int k = 0; k < 4; k++) v[u][k] = lds128(sb + (HALF ? cv_pb1(lc + STEP * u, k) : cv_pb0(lc + STEP * u, k)) + sw);
    xr[u] = lds128(sb + cv_x(HALF, lc + STEP * u) + c * 16);
  }
#pragma unroll
  for (int u = 0; u < NCH; u++) {
    uint4 o;
    o.x = hadd2(xr[u].x, hadd2(hadd2(v[u][0].x, v[u][1].x), hadd2(v[u][2].x, v[u][3].x)));
    o.y = hadd2(xr[u].y, hadd2(hadd2(v[u][0].y, v[u][1].y), hadd2(v[u][2].y, v[u][3].y)));
    o.z = hadd2(xr[u].z, hadd2(hadd2(v[u][0].z, v[u][1].z), hadd2(v[u][2].z, v[u][3].z)));
    o.w = hadd2(xr[u].w, hadd2(hadd2(v[u][0].w, v[u][1].w), hadd2(v[u][2].w, v[u][3].w)));
    stg128(out + cv_chan(0, lc + STEP * u) * LSEQ + HALF * 1024 + c * 8, o);
  }
}

__device__ __forceinline__ bool prep_valid(const uint4 (&st)[6], const uint4 (&xr)[4]) {
  const uint32_t n = st[0].w & st[1].w & st[2].w & st[3].w & st[4].w & (st[5].w | st[5].y | st[5].z);
  return (n == __float_as_uint(8.f)) & (max(max(xr[0].x, xr[1].x), max(xr[2].x, xr[3].x)) != UNSET);
}
template <int HALF>
__device__ __forceinline__ void conv_prep(uint32_t sb, int layer, int cta, int i) {
  uint4 st[6], xr[4];
  const uint4* sp = (const uint4*)g_stats + (layer * 32 + HALF * 16 + (i >> 3)) * 48 + (i & 7);
  const uint4* xp = (const uint4*)g_xT + (2 * layer * DM + 2 * cta) * (LSEQ / 8) + HALF * 128 + i;
  if (!HALF) { pin(sp); pin(xp); }
  mbar_wait(sb + SM_BAR + 8 * (B_GB + HALF), layer);
  if (!HALF) TSW(13);
  auto fetch = [&]() {
#pragma unroll
    for (int k = 0; k < 6; k++) st[k] = ld_tagged(sp + 8 * k);
#pragma unroll
    for (int k = 0; k < 4; k++) xr[k] = ld_tagged(xp + cv_chan(0, k) * (LSEQ / 8));
  };
  if (HALF) {
#pragma unroll
    for (int k = 0; k < 6; k++) st[k] = lds128(sb + CV_ST + (i >> 3) * 768 + k * 128 + (i & 7) * 16);
#pragma unroll
    for (int k = 0; k < 4; k++) xr[k] = lds128(sb + cv_x(1, k) + i * 16);
  } else {
    fetch();
  }
  int it = 0;
  while (!__all_sync(~0u, prep_valid(st, xr)) && ++it < MAX_RETRY) { fetch(); RETRY(1); }
  if (!HALF || it) {
#pragma unroll
    for (int k = 0; k < 4; k++) sts128(sb + cv_x(HALF, k) + i * 16, xr[k]);
  }
  const uint32_t v[16] = {st[0].x, st[0].y, st[0].z, st[1].x, st[1].y, st[1].z, st[2].x, st[2].y, st[2].z, st[3].x, st[3].y, st[3].z, st[4].x, st[4].y, st[4].z, st[5].x};
  uint32_t rs[4], nm[4];
#pragma unroll
  for (int k = 0; k < 4; k++) {
    constexpr float E2 = 1e-5f * DM * DM;
    const float s0 = __uint_as_float(v[4 * k]), s1 = __uint_as_float(v[4 * k + 2]);
    const float r0 = rsqrt_approx(fmaxf(fmaf(__uint_as_float(v[4 * k + 1]), (float)DM, fmaf(-s0, s0, E2)), E2));
    const float r1 = rsqrt_approx(fmaxf(fmaf(__uint_as_float(v[4 * k + 3]), (float)DM, fmaf(-s1, s1, E2)), E2));
    const uint32_t r = packbf(r0, r1);
    rs[k] = r + 0x04800480u;
    nm[k] = packbf(-s0 * bf_lo(r), -s1 * bf_hi(r));
  }
  const uint32_t ud = sb + (i & 1) * CV_UH + (127 - 64 * HALF - (i >> 1)) * 16;
#pragma unroll
  for (int k = 0; k < 4; k++)
    sts128(ud + cv_u(k), make_uint4(hfma2(xr[k].x, rs[0], nm[0]), hfma2(xr[k].y, rs[1], nm[1]), hfma2(xr[k].z, rs[2], nm[2]), hfma2(xr[k].w, rs[3], nm[3])));
  fence_async_smem();
}

__device__ __forceinline__ void conv_phase(const Params& p, uint32_t sb, int layer, int cta, uint32_t* A0, uint32_t* A1) {
  const int tid = opaque_tid();
  const int wg = __shfl_sync(~0u, tid >> 7, 0), w = __shfl_sync(~0u, (tid >> 5) & 3, 0);
  const uint32_t bar = sb + SM_BAR;
  constexpr int CH2 = 4 * PG;
  bf16* xout = g_xT + ((2 * layer + 1) * DM + 2 * cta) * LSEQ;
  float acc[32];
  const uint32_t pe = sb + cv_pe(wg, 0) + 4 * (16 + 16 * w + ((tid & 31) >> 2) - 2 * (tid & 3));
  if (layer == 0) {
    mbar_wait(bar + 8 * (B_PDONE + 1), layer);
    mbar_wait(bar + 8 * B_PE, layer);
    conv_load(A0, pe);
    conv_load(A1, pe + CH2);
  }
  TSW(19);
  const uint64_t d0 = mkdesc(sb + cv_u(wg), CV_UH, 128, 0), d1 = d0 + (CH2 >> 4);
  mbar_wait(bar + 8 * B_U, layer);
  TSW(12);
  if (wg == 1) bar_sync(5, 256);
  conv_mma0(acc, A0, d0);
  if (wg == 0) bar_arrive(5, 256);
  mbar_wait(bar + 8 * (B_PDONE + 1), layer);
  {
    const int l = opaque_tid() & 31;
    if ((l & 15) < 2 * w) sts128(sb + cv_pb0(wg + 2 * (l >> 4), w) + (l & 15) * 16, make_uint4(0, 0, 0, 0));
  }
  wg_wait<0>();
  conv_store(acc, sb + cv_pb0(wg, w), sb + cv_pb1(wg, w), w);
  conv_mma0(acc, A1, d1);
  wg_wait<0>();
  conv_store(acc, sb + cv_pb0(2 + wg, w), sb + cv_pb1(2 + wg, w), w);
  TSW(13);
  bar_sync(2 + wg, 128);
  conv_epi<0, 2, 2>(sb, xout, wg, opaque_tid() & 127);
  TSW(14);
  mbar_arrive(bar + 8 * B_PUB);
  const uint64_t ds = mkdesc(sb + cv_se(wg), 8192, 1024, 1), df = mkdesc(sb + cv_fa(wg), 512, 128, 0);
  if (wg == 0) mbar_wait(bar + 8 * B_U1, layer);
  else bar_sync(6, 256);
  TSW(15);
  conv_mma1(acc, A0, d0, ds, df);
  if (wg == 0) bar_arrive(6, 256);
  wg_wait<0>();
  conv_store(acc, sb + cv_pb1(wg, w), sb + cv_dump(wg), w);
  TSW(16);
  bar_sync(2 + wg, 128);
  conv_epi<1, 1>(sb, xout, wg, opaque_tid() & 127);
  mbar_arrive(bar + 8 * (B_PUB + 1));
  conv_mma1(acc, A1, d1, ds + 512, df + (CH2 >> 4));
  wg_wait<0>();
  conv_store(acc, sb + cv_pb1(2 + wg, w), sb + cv_dump(2 + wg), w);
  TSW(17);
  bar_sync(2 + wg, 128);
  conv_epi<1, 1>(sb, xout, 2 + wg, opaque_tid() & 127);
  mbar_arrive(bar + 8 * (B_PUB + 2));
  TSW(18);
}

#define FDELAY 480
__device__ __forceinline__ void final_tile(const Params& p, uint32_t buf, int ch0, int pos0, int barid, uint32_t hint) {
  const uint32_t t0 = (uint32_t)clock();
  const int tid = opaque_tid() & 127, lane = tid & 31, w = tid >> 5;
  const uint4* src = (const uint4*)(g_xT + (3 * DM + ch0 + (tid >> 3)) * LSEQ + pos0) + (tid & 7);
  const int ch = tid >> 3, row = 4 * (ch & 6) + 2 * (ch >> 3) + (ch & 1);
  uint32_t dst0 = buf + row * 128 + (((tid ^ row) & 7) << 4), dst1 = (dst0 ^ 64) + 512;
  uint32_t ld0 = buf + lane * 128 + ((((2 * w) ^ lane) & 7) << 4), ld1 = ld0 ^ 16;
  bf16* out = p.out + (pos0 + 16 * w + (lane >> 2)) * DM + ch0 + 8 * (lane & 3);
  pin(src); pin(out); pin(dst0); pin(dst1); pin(ld0); pin(ld1);
  if (hint) mbar_wait(hint, 0);
  else while ((uint32_t)clock() - t0 < FDELAY);
  uint4 a, b;
  int it = 0;
  do {
    if (it) RETRY(2);
    a = ld_tagged(src); b = ld_tagged(src + 16 * LSEQ / 8);
  } while (!__all_sync(~0u, a.x != UNSET && b.x != UNSET) && ++it < (1 << 20));
  sts128(dst0, a);
  sts128(dst1, b);
  bar_sync(barid, 128);
#pragma unroll
  for (int h = 0; h < 2; h++) {
    uint32_t r[4];
    ldsm4t(r, h ? ld1 : ld0);
    *(uint4*)(out + 8 * h * DM) = make_uint4(r[0], r[1], r[2], r[3]);
  }
}

struct cplx { float r, i; };
__device__ __forceinline__ cplx cmul(cplx a, cplx b) { return {fmaf(a.r, b.r, -a.i * b.i), fmaf(a.r, b.i, a.i * b.r)}; }
__device__ __forceinline__ cplx csqr(cplx a) { return {fmaf(a.r, a.r, -a.i * a.i), (a.r + a.r) * a.i}; }
__device__ __forceinline__ cplx cexp_l(float ar2, float ai, float l) {
  const float m = ex2(ar2 * l);
  const float x = ai * l;
  return {m * __cosf(x), m * __sinf(x)};
}

__device__ __forceinline__ void colsum_cta(const Params& p, uint32_t sb, int j, int tid) {
  const uint32_t bar = sb + SM_BAR;
  auto ld = [&](int i) {
    mbar_expect(bar + 8 * i, 3 * PG);
    tma_ld3(sb + (i & 7) * 3 * PG, &p.mapW3, (2 * j + (i & 1)) * 64, (i >> 1) * 64, 0, bar + 8 * i);
  };
  const int warp = __shfl_sync(~0u, tid >> 5, 0);
  if (warp == 12 && elect_one()) {
#pragma unroll
    for (int i = 0; i < 8; i++) mbar_init(bar + 8 * i, 1);
    asm volatile("fence.mbarrier_init.release.cluster;" ::: "memory");
    fence_async_smem();
#pragma unroll
    for (int i = 0; i < 8; i++) ld(i);
  }
  if (warp == 13 && elect_one()) {
#pragma unroll
    for (int i = 8; i < 24; i++) mbar_init(bar + 8 * i, i < 16 ? 1 : 12);
    asm volatile("fence.mbarrier_init.release.cluster;" ::: "memory");
  }
  const unsigned ep = ld_relaxed(&g_cnt[C_CS * 32]);
  bar_sync(0, NTHREADS);
  if (warp == 12 && elect_one()) {
#pragma unroll 1
    for (int i = 8; i < 16; i++) { mbar_wait(bar + 8 * (8 + i), 0); fence_async_smem(); ld(i); }
  }
  if (tid < 384) {
    const int lane = tid & 31, cc = tid & 7, r0 = (tid >> 3) & 15, part = tid >> 7;
    const uint32_t id = ((lane >> 2) == 2 * (lane & 3) ? 0x3f80u : 0u) | ((lane >> 2) == 2 * (lane & 3) + 1 ? 0x3f800000u : 0u);
    const uint32_t src = sb + part * PG + r0 * 128 + ((cc ^ (r0 & 7)) << 4);
    float s[2][2][4];
#pragma unroll
    for (int i = 0; i < 16; i++) s[i >> 3][(i >> 2) & 1][i & 3] = 0.f;
#pragma unroll 1
    for (int i2 = 0; i2 < 16; i2 += 2) {
#pragma unroll
      for (int h = 0; h < 2; h++) {
        const int i = i2 + h;
        mbar_wait(bar + 8 * i, 0);
        uint4 v[4];
#pragma unroll
        for (int k = 0; k < 4; k++) v[k] = lds128(src + (i & 7) * 3 * PG + k * 2048);
#pragma unroll
        for (int k = 0; k < 4; k++) {
          const uint32_t a[4] = {v[k].x, v[k].y, v[k].z, v[k].w};
          mma_bf16(s[h][0], a, id, 0u);
          mma_bf16(s[h][1], a, 0u, id);
        }
        __syncwarp();
        if (i < 8 && lane == 0) mbar_arrive(bar + 8 * (16 + i));
      }
    }
    const uint32_t red = sb + 24 * PG;
#pragma unroll
    for (int h = 0; h < 2; h++)
#pragma unroll
      for (int k = 0; k < 2; k++) sts128f(red + (r0 * 384 + h * 192 + part * 64 + cc * 8 + k * 4) * 4, s[h][k][0], s[h][k][1], s[h][k][2], s[h][k][3]);
    bar_sync(1, 384);
    float tot = 0.f;
#pragma unroll
    for (int k = 0; k < 16; k++) tot += __uint_as_float(lds32(red + (k * 384 + tid) * 4));
    asm volatile("st.relaxed.gpu.global.v2.u32 [%0], {%1,%2};" ::"l"(&g_colsum[j * 384 + tid]), "r"(__float_as_uint(tot)), "r"(ep / NCTA + 1) : "memory");
    const uint4 u = make_uint4(UNSET, UNSET, UNSET, UNSET);
    if (tid < 256) {
#pragma unroll 1
      for (int s = 0; s < 4; s++) {
        const int n = (s == 1 || s == 2) ? 32 : 16;
        uint4* buf = s == 1 ? (uint4*)g_O + 131072 : (uint4*)g_xT + (s + !s) * 131072;
#pragma unroll 4
        for (int i = 0; i < n; i++) stg128(buf + (j * n + i) * 1024 + (tid >> 1) * 8 + (tid & 1), u);
        if (n == 16) {
#pragma unroll 4
          for (int i = 0; i < 8; i++) stg128(buf + (256 + j * 64 + i * 8 + (tid >> 5)) * 256 + (s ? 0 : 128) + ((tid & 31) >> 1) * 8 + (tid & 1), u);
        }
        if (s == 3) {
#pragma unroll 4
          for (int i = 0; i < 32; i++) stg128(buf + (256 + j * 64 + 2 * i + (tid >> 7)) * 256 + 128 + (tid & 127), u);
        }
        bar_sync(2, 256);
        if (tid == 32 * s) red_release(&g_cnt[(C_R + s) * 32]);
      }
    }
  }
}

constexpr int KB = 4, KW = 2;
struct ModeIn { uint32_t ar, ai, br, bi, cr, ci; bf16 logdt; };
__device__ __forceinline__ ModeIn load_modes(const Params& p, int d, int m) {
  const int i = d * 64 + m;
  return {((const uint32_t*)p.a_re)[i], ((const uint32_t*)p.a_im)[i], ((const uint32_t*)p.b_re)[i], ((const uint32_t*)p.b_im)[i],
          ((const uint32_t*)p.c_re)[i], ((const uint32_t*)p.c_im)[i], p.log_dt[d]};
}
__device__ __forceinline__ void kernel_gen(uint32_t sb, int cta, int ht, ModeIn in, const ModeIn& in1) {
  const uint32_t bst = sb + SM_KGB + ((ht & 63) >> 2) * 144 + (ht & 3) * 4 + (ht >> 6) * 16;
  const uint64_t db = mkdesc(sb + SM_KGB, 144, 2304, 0);
  const float e0 = (float)(8 * (((ht & 32) >> 1) + ((ht & 31) >> 2)));
  float T[20];
#pragma unroll
  for (int i = 0; i < 20; i++) T[i] = 0.f;
  float k0 = 0.f;
#pragma unroll 1
  for (int pass = 0; pass < 4; pass++) {
    {
      const int sh = (pass & 1) ? 0 : 16;
      auto val = [&](uint32_t v) { return __uint_as_float((v << sh) & 0xffff0000u); };
      const float dt = __bfloat162float(__float2bfloat16_rn(expf(__bfloat162float(in.logdt))));
      const float ar2 = dt * val(in.ar) * 1.4426950408889634f, ai = dt * val(in.ai);
      const cplx c = cmul({val(in.cr), -val(in.ci)}, {dt * val(in.br), -dt * val(in.bi)});
      k0 += c.r;
      const cplx z1 = cexp_l(ar2, -ai, 1.f), z256 = cexp_l(ar2, -ai, 256.f), z64 = cexp_l(ar2, ai, 64.f);
      const cplx z2 = csqr(z1), z512 = csqr(z256);
      auto put = [&](int j, cplx v) { sts32(bst + (j >> 2) * 2304 + (j & 3) * 32, packbf(v.r, v.i)); };
      sts128f(sb + SM_KGT + ht * 16, ar2, ai, z64.r, z64.i);
      const cplx c1 = cmul(c, z1), c2 = cmul(c, z2), c3 = cmul(c1, z2), c4 = cmul(c2, z2);
      const cplx c5 = cmul(c3, z2), c6 = cmul(c4, z2), c7 = cmul(c5, z2), c8 = cmul(c6, z2);
      put(0, c1); put(1, c2); put(2, c3); put(3, c4); put(4, c5); put(5, c6); put(6, c7); put(7, c8);
      const cplx c260 = cmul(c4, z256), c264 = cmul(c8, z256), c520 = cmul(c8, z512), c776 = cmul(c264, z512);
      put(8, cmul(c2, z256)); put(9, c260); put(10, cmul(c6, z256)); put(11, c264);
      put(12, cmul(c4, z512)); put(13, c520); put(14, cmul(c260, z512)); put(15, c776);
      const cplx c1032 = cmul(c520, z512), c1288 = cmul(c776, z512);
      put(16, c1032); put(17, c1288); put(18, cmul(c1032, z512)); put(19, cmul(c1288, z512));
    }
    fence_async_smem();
    bar_sync(4, 128);
    const uint32_t tb = sb + SM_KGT + (ht & 67) * 16;
    float2 nx[KB];
#pragma unroll
    for (int s = 0; s < KB; s++) nx[s] = lds64f(tb + s * 64);
#pragma unroll
    for (int q = 0; q < 16 / KB; q++) {
      uint32_t A[2 * KB];
      float2 cur[KB], z[KB];
#pragma unroll
      for (int s = 0; s < KB; s++) { cur[s] = nx[s]; z[s] = lds64f(tb + (KB * q + s) * 64 + 8); }
      if (q < 16 / KB - 1) {
#pragma unroll
        for (int s = 0; s < KB; s++) nx[s] = lds64f(tb + (KB * q + KB + s) * 64);
      }
      if (q >= KW) wg_wait<KW - 1>();
#pragma unroll
      for (int s = 0; s < KB; s++) {
        const cplx lo = cexp_l(cur[s].x, cur[s].y, e0), hi = cmul(lo, {z[s].x, z[s].y});
        A[2 * s] = packbf(lo.r, lo.i);
        A[2 * s + 1] = packbf(hi.r, hi.i);
      }
      wg_fence();
#pragma unroll
      for (int k = 0; k < KB / 2; k++) wgmma_rs<40, 0>(T, A + 4 * k, db + 9 * KB * q + 18 * k, (pass & 1) | q | k);
      wg_commit();
    }
    wg_wait<0>();
    acc_fence<20>(T);
    if (ht == 0) TS(4 + pass);
    if (pass & 1) {
      const int h2 = opaque_tid() - 256, w = h2 >> 5, lane = h2 & 31, t = lane & 3, chn = h2 >> 6, m = h2 & 63, i0 = 16 * (w & 1) + (lane >> 2);
      const int lc = (pass & 2) + chn;
      const uint32_t kc = sb + kc_off(lc);
      auto put = [&](int idx, float v) {
        sts16(kc + idx * 2, __bfloat16_as_ushort(__float2bfloat16_rn(v)));
      };
#pragma unroll
      for (int hi = 0; hi < 2; hi++) {
        const int i = i0 + 8 * hi;
        float v[5];
#pragma unroll
        for (int j = 0; j < 5; j++) v[j] = chn ? T[4 * j + 2 * hi + 1] : T[4 * j + 2 * hi];
        put(8 * i + 1 + t, v[0]);
        put(8 * i + 5 + t, v[1]);
        put(257 + 4 * i + t, v[2]);
        put(385 + 2 * i + (t & 1) + 64 * (t >> 1), v[3]);
        put(513 + i + 32 * t, v[4]);
      }
#pragma unroll
      for (int o = 16; o > 0; o >>= 1) k0 += __shfl_xor_sync(~0u, k0, o);
      if (lane == 0) sts32f(sb + SM_RED + 4 * w, k0);
      bar_sync(4, 128);
      if (m == 0) put(0, k0 + __uint_as_float(lds32(sb + SM_RED + 4 * w + 4)) + __uint_as_float(lds16(sb + SM_RED + 24 + 2 * lc) << 16));
      k0 = 0.f;
      in = in1;
    }
  }
}

__device__ __forceinline__ void expand_taps(uint32_t sb, int ht, int early) {
  const int ch = ht >> 5, lane = ht & 31;
  const uint32_t kc = sb + kc_off(ch);
  const uint32_t dst0 = sb + cv_pe(ch, early);
  auto put = [&](int G, uint32_t v0, uint32_t v1, uint32_t v2, uint32_t v3, uint32_t v4, uint32_t v5, uint32_t v6, uint32_t v7, uint32_t v8) {
    const uint32_t dst = dst0 + G * 32;
    sts128(dst, make_uint4(v1 | (v0 << 16), v2 | (v1 << 16), v3 | (v2 << 16), v4 | (v3 << 16)));
    sts128(dst + 16, make_uint4(v5 | (v4 << 16), v6 | (v5 << 16), v7 | (v6 << 16), v8 | (v7 << 16)));
  };
  {
    const uint4 q = lds128(kc + lane * 16);
    const uint32_t pv = lane ? lds16(kc + lane * 16 - 2) : 0u;
    const uint32_t dst = dst0 + (lane + 2) * 32;
    sts128(dst, make_uint4(__byte_perm(q.x, pv, 0x5410), __byte_perm(q.x, q.x, 0x1032), __byte_perm(q.y, q.x, 0x7610), __byte_perm(q.y, q.y, 0x1032)));
    sts128(dst + 16, make_uint4(__byte_perm(q.z, q.y, 0x7610), __byte_perm(q.z, q.z, 0x1032), __byte_perm(q.w, q.z, 0x7610), __byte_perm(q.w, q.w, 0x1032)));
    if (lane < 4) sts128(dst0 + lane * 16, make_uint4(0, 0, 0, 0));
  }
  uint32_t a[5], b[2][3];
  {
    const uint32_t s1 = kc + 2 * (256 + 4 * lane);
#pragma unroll
    for (int k = 0; k < 5; k++) a[k] = lds16(s1 + 2 * k);
#pragma unroll
    for (int u = 0; u < 2; u++) {
      const uint32_t s2 = kc + 2 * (384 + 2 * (lane + 32 * u));
#pragma unroll
      for (int k = 0; k < 3; k++) b[u][k] = lds16(s2 + 2 * k);
    }
  }
  const uint32_t k255 = lds16(kc + 2 * 255), k1024 = lds16(kc + 2 * 512);
  put(34 + lane, lane == 0 ? k255 : a[0], a[0], a[0], a[1], a[2], a[2], a[2], a[3], a[4]);
#pragma unroll
  for (int u = 0; u < 2; u++) put(66 + lane + 32 * u, b[u][0], b[u][0], b[u][0], b[u][0], b[u][1], b[u][1], b[u][1], b[u][2], b[u][2]);
  if (lane < 10) {
    const uint32_t v = lane == 0 ? k1024 : 0u;
    put(130 + lane, v, v, v, v, v, v, 0u, 0u, 0u);
  }
}
__device__ __forceinline__ void expand_far(uint32_t sb, int ht) {
  const int ch = ht >> 5, lane = ht & 31;
  const uint32_t kc = sb + kc_off(ch) + 2 * (513 + 2 * (63 - lane)), dst = sb + cv_fa(ch) + lane * 16;
#pragma unroll
  for (int ty = 0; ty < 2; ty++) {
    uint32_t v[16];
#pragma unroll
    for (int k = 0; k < 16; k++) v[k] = (k < 8 || 63 - lane - 4 * k >= 0) ? lds16(kc + 2 * (1 - ty) - 16 * k) : 0u;
#pragma unroll
    for (int u = 0; u < 2; u++)
      sts128(dst + ty * 2048 + u * 512, make_uint4(v[8 * u] | (v[8 * u + 1] << 16), v[8 * u + 2] | (v[8 * u + 3] << 16), v[8 * u + 4] | (v[8 * u + 5] << 16), v[8 * u + 6] | (v[8 * u + 7] << 16)));
    sts128(dst + ty * 2048 + 1024, make_uint4(0, 0, 0, 0));
  }
}

__host__ __device__ constexpr int bar_count(int i) {
  return i == B_LN ? 2 : i == B_AL ? 8 : i < B_STG ? 1 : i < B_PE ? 4 : i >= B_PUB ? 256 : 128;
}
__host__ __device__ constexpr bool bar_first(int i) { return i < B_WF + 2 && (i & 7) < 2; }

__global__ void __launch_bounds__(NTHREADS, 1) fused_kernel(const __grid_constant__ Params p) {
  extern __shared__ __align__(1024) uint8_t smem[];
  constexpr uint32_t sb = 1024;
  if (s32(smem) != sb) return;
  const int tid = threadIdx.x, lane = tid & 31;
  const int warp = __shfl_sync(~0u, tid >> 5, 0);
  if (tid == 32) {
    asm volatile("prefetch.tensormap [%0];" ::"l"(&p.mapX) : "memory");
    asm volatile("prefetch.tensormap [%0];" ::"l"(&p.mapW3) : "memory");
  }
  const int cta = blockIdx.x - (gridDim.x == NCTA + 4 ? 0 : 4);
  if ((unsigned)cta >= NCTA) {
    if (blockIdx.x < NCTA + 4) colsum_cta(p, sb, blockIdx.x & 3, tid);
    return;
  }
  const int rb = ((cta >> 4) & 3) * 4 + ((cta >> 2) & 3), hg = (cta >> 6) * 4 + (cta & 3);
  const uint32_t bar = sb + SM_BAR;
  auto ld_x0 = [&](int half, int c) {
    const uint32_t b = bar + 8 * (B_XF + 8 * half + c);
    mbar_expect(b, PG);
    tma_ld(sb + x_page(half, c) * PG, &p.mapX, c * 64, (16 * half + rb) * 64, b);
  };
  auto ld_x1 = [&](int half, int c, int b0) {
    const uint32_t b = bar + 8 * b0;
    mbar_expect(b, PG);
    tma_ld(sb + (8 * half + c) * PG, &p.mapXT, (16 * half + rb) * 64, DM + c * 64, b);
  };
  auto ld_w = [&](int c) {
    const uint32_t b = bar + 8 * (B_WF + c);
    mbar_expect(b, 3 * PG);
    tma_ld3(sb + w_page(c) * PG, &p.mapW3, hg * 64, c * 64, 0, b);
  };

  if (tid == 0) TS(0);
  if (tid == 480) LTS(0);
  if (warp == 0 && elect_one()) {
#pragma unroll
    for (int i = 0; i < B_WF + 2; i++)
      if (bar_first(i)) mbar_init(bar + 8 * i, 1);
    asm volatile("fence.mbarrier_init.release.cluster;" ::: "memory");
    fence_async_smem();
    ld_x0(0, 0);
    ld_w(0); ld_x0(1, 0);
    ld_x0(0, 1); ld_w(1); ld_x0(1, 1);
    TS(1);
  }
  __syncwarp();
  if (warp >= 1 && warp < 8 && elect_one()) {
    if (warp < 4) {
#pragma unroll
      for (int i = 2; i < 8; i++) mbar_init(bar + 8 * (8 * warp - 8 + i), 1);
    } else {
#pragma unroll
      for (int i = 0; i < 12; i++) mbar_init(bar + 8 * (12 * warp - 24 + i), 1);
    }
    asm volatile("fence.mbarrier_init.release.cluster;" ::: "memory");
  }
  if (warp == 15 && elect_one()) {
#pragma unroll
    for (int i = 72; i < B_COUNT; i++) mbar_init(bar + 8 * i, bar_count(i));
    asm volatile("fence.mbarrier_init.release.cluster;" ::: "memory");
  }

  if (warp < 8) {
    bar_sync(0, NTHREADS);
    asm volatile("setmaxnreg.inc.sync.aligned.u32 %0;" ::"n"(R_CONS));
    const int cw = __shfl_sync(~0u, opaque_tid() >> 5, 0);
    const int wg = cw >> 2, w = cw & 3;
    if (tid == 0) TS(2);
#pragma unroll 1
    for (int layer = 0; layer < 2; layer++) {
      attn_phase(p, sb, layer, rb, hg, wg, w);
      uint32_t A0[68], A1[68];
      proj_phase(p, sb, layer, rb, hg, A0, A1);
      conv_phase(p, sb, layer, cta, A0, A1);
    }
    if (tid == 128) TS(8);
    final_tile(p, sb + (16 + wg) * PG, 256 * wg + 32 * (cta >> 4), 1024 + 64 * (cta & 15), 2 + wg, wg ? 0 : bar + 8 * (B_TF + 1));
    if (tid == 128) TS(9);
    if (tid == 128) LTS(1);
    if (tid == 0) LTE();
  } else if (warp < 12) {
    asm volatile("setmaxnreg.dec.sync.aligned.u32 %0;" ::"n"(R_HELP));
    const int ht = tid - 256;
    {
      unsigned ep0 = 0;
      if (ht == 0) ep0 = ld_relaxed(&g_cnt[C_CS * 32]);
      const bf16 dsk = p.dskip[cv_chan(cta, ht & 3)];
      const ModeIn in0 = load_modes(p, cv_chan(cta, ht >> 6), ht & 63), in1 = load_modes(p, cv_chan(cta, 2 + (ht >> 6)), ht & 63);
      if (ht < 48) sts128f(sb + SM_STG + ht * 16, 0.f, 0.f, 0.f, 1.f);
      bar_sync(0, NTHREADS);
      if (ht == 0) {
        sts32(sb + SM_EP, ep0);
        mbar_arrive(bar + 8 * B_EP);
      }
      if (ht >= 124) sts16(sb + SM_RED + 24 + 2 * (ht & 3), __bfloat16_as_ushort(dsk));
      kernel_gen(sb, cta, ht, in0, in1);
      if (ht < 48) sts128f(sb + SM_KGT + ht * 16, 0.f, 0.f, 0.f, 1.f);
      fence_async_smem();
      bar_sync(4, 128);
      if (ht == 0) mbar_arrive(bar + 8 * B_KG);
    }
#pragma unroll 1
    for (int layer = 0; layer < 2; layer++) {
      const int early = layer;
      if (early) mbar_wait(bar + 8 * (B_DN + 13), 1);
      mbar_wait(bar + 8 * (early ? B_OST : B_PDONE), layer);
      expand_taps(sb, opaque_tid() - 256, early);
      mbar_arrive(bar + 8 * B_PE);
      TSW(0);
      mbar_wait(bar + 8 * B_PDONE, layer);
      expand_far(sb, opaque_tid() - 256);
      {
        const int i = opaque_tid() - 256;
        if (i < 32) sts128(sb + cv_u(i >> 3) + ((i >> 2) & 1) * CV_UH + (128 + (i & 3)) * 16, make_uint4(0, 0, 0, 0));
        mbar_wait(bar + 8 * B_RC, layer);
        conv_prep<0>(sb, layer, cta, i);
        mbar_arrive(bar + 8 * B_U);
      }
      mbar_wait(bar + 8 * (B_PDONE + 1), layer);
      bar_sync(4, 128);
#pragma unroll 1
      for (int lc = 0; lc < 4; lc += 2) {
        conv_sums(sb, lc, opaque_tid() - 256);
        TSW(1 + lc);
      }
      conv_prep<1>(sb, layer, cta, opaque_tid() - 256);
      mbar_arrive(bar + 8 * B_U1);
      TSW(4);
      if (layer == 0) {
        const int c = __shfl_sync(~0u, (opaque_tid() >> 5) & 3, 0);
        int phase = 0;
#pragma unroll 1
        for (int k = 0; k < 3; k++) {
          const int page = (k ? 4 + 4 * k : 0) + c, b = B_XR + 4 * (k & 1) + c;
          const uint32_t a = sb + page * PG + lane * 128 + (lane & 7) * 16 + (lane >> 3) * 4;
          int it = k == 2 ? phase : 0;
#pragma unroll 1
          for (; it < MAX_RETRY; it++) {
            mbar_wait(bar + 8 * b, it & 1);
            const uint32_t v0 = lds32(a), v1 = lds32(a + 4096);
            if (__all_sync(~0u, v0 != UNSET && v1 != UNSET)) break;
            if (elect_one()) { fence_async_smem(); ld_x1(page >> 3, page & 7, b); }
            __syncwarp();
            RETRY(3);
          }
          if (k == 0) phase = it + 1;
          if (lane == 0) mbar_arrive(bar + 8 * (B_XF + page));
        }
      }
    }
#pragma unroll 1
    for (int k = 0; k < 2; k++) final_tile(p, sb + 18 * PG + k * 4096, 256 * k + 32 * (cta >> 4), 64 * (cta & 15), 4, bar + 8 * B_TF);
    if (ht == 0) LTE();
  } else {
    asm volatile("setmaxnreg.dec.sync.aligned.u32 %0;" ::"n"(R_AGENT));
    bar_sync(0, NTHREADS);
    auto done = [&](int half, int c, int layer) { mbar_wait(bar + 8 * (B_DN + 8 * half + c), layer); };
    auto publish = [&](int layer, int k) {
      unsigned* cnt = &g_cnt[(layer ? C_F + 8 * k + (cta >> 4) : C_C + k) * 32];
      pin(cnt);
      mbar_wait(bar + 8 * (B_PUB + k), layer);
      red_relaxed(cnt);
      if (!layer && k == 0) red_release(&g_cnt[(C_C + 3) * 32]);
      TS(16 + layer * 56 + 40 + 7 + k);
    };
    if (warp == 12) {
      if (elect_one()) {
#pragma unroll 1
        for (int layer = 0; layer < 2; layer++) {
          auto ld_xe = [&](int c) {
            const uint32_t b = bar + 8 * (B_XF + c);
            mbar_expect(b, PG);
            if (layer == 0) tma_ld(sb + x_page(0, c) * PG, &p.mapX, c * 64, rb * 64, b);
            else tma_ld(sb + x_page(0, c) * PG, &p.mapXT, rb * 64, DM + c * 64, b);
          };
          if (layer == 0) {
            ld_x0(0, 2); ld_w(2); ld_x0(1, 2);
            if (hg >= 3) {
              mbar_expect(bar + 8 * B_SC, PG);
              tma_ld(sb + P_R * PG, &p.mapX, hg * 64, rb * 64, bar + 8 * B_SC);
            }
            if (rb < 4) tma_prefetch3(&p.mapW3, hg * 64, (4 + rb) * 64, 0);
            ld_x0(0, 3); ld_w(3); ld_x0(1, 3); ld_x0(0, 4); ld_x0(1, 4);
            done(0, 0, 0); done(1, 0, 0);
            ld_w(4);
            ld_x0(1, 5); ld_x0(1, 6); ld_x0(1, 7);
            done(0, 1, 0); done(1, 1, 0);
            ld_w(5);
            if (rb < 8) tma_prefetch5(&p.mapWo, hg * 64, rb * 2);
            done(0, 2, 0);
            fence_async_smem();
            ld_xe(5); ld_xe(6); ld_xe(7);
          } else {
            mbar_wait(bar + 8 * B_PDONE, 0);
            mbar_wait(bar + 8 * (B_PDONE + 1), 0);
            mbar_wait(bar + 8 * B_U, 0);
            ld_w(0); ld_w(1);
            mbar_wait(bar + 8 * B_U1, 0);
            fence_async_smem();
            ld_w(2);
            mbar_wait(bar + 8 * (B_PUB + 2), 0);
            fence_async_smem();
            ld_w(3);
            spin_until(&g_cnt[(C_C + 3) * 32], ((lds32(sb + SM_EP) / NCTA) + 1) * NCTA);
            fence_async_global();
            if (hg >= 3) {
              mbar_expect(bar + 8 * B_SC, PG);
              tma_ld(sb + P_R * PG, &p.mapXT, rb * 64, DM + hg * 64, bar + 8 * B_SC);
            }
            ld_xe(4);
            done(0, 2, 1);
            fence_async_smem();
            ld_xe(5); ld_xe(6); ld_xe(7);
            done(1, 0, 1);
            ld_w(4);
            done(1, 1, 1);
            ld_w(5);
          }
          done(1, 2, layer);
          fence_async_smem();
          ld_w(6); ld_w(7);
          auto ld_res = [&](int half) {
            const uint32_t b = bar + 8 * (B_RF + half);
            mbar_expect(b, PG);
            if (layer == 0) tma_ld(sb + (half ? 2 : P_R) * PG, &p.mapX, hg * 64, (16 * half + rb) * 64, b);
            else tma_ld(sb + (half ? 2 : P_R) * PG, &p.mapXT, (16 * half + rb) * 64, DM + hg * 64, b);
          };
          done(0, 4, layer); done(1, 3, layer);
          fence_async_smem();
          mbar_expect(bar + 8 * B_WOF, 8 * PG);
#pragma unroll 1
          for (int c = 0; c < 8; c++) {
            if (c == 5) { ld_res(0); done(1, 4, layer); }
            tma_ld5(sb + wo_page(c) * PG, &p.mapWo, hg * 64, c * 2, bar + 8 * B_WOF);
          }
          done(0, 7, layer);
          fence_async_global();
          ld_res(1);
          if (layer) mbar_wait(bar + 8 * B_RS, 0);
          fence_async_global();
#pragma unroll
          for (int half = 0; half < 2; half++) {
            float* stats = g_stats + (layer * 32 + 16 * half + rb) * 192;
            unsigned* cnt = &g_cnt[(C_G + 2 * layer + half) * 32];
            mbar_wait(bar + 8 * (B_STG + half), layer);
            tma_st(&p.mapXT, (16 * half + rb) * 64, 2 * layer * DM + hg * 64, sb + (P_R + half) * PG);
            bulk_red_add_f32(stats, sb + (half ? SM_KGT : SM_STG), 768);
            bulk_commit();
            red_relaxed(cnt);
            if (half == 0) mbar_arrive(bar + 8 * B_PG);
            bulk_wait_read();
            mbar_arrive(bar + 8 * (B_PST + half));
          }
        }
      }
    } else if (warp == 13) {
      mbar_wait(bar + 8 * B_EP, 0);
      const unsigned e1 = (lds32(sb + SM_EP) / NCTA) + 1;
      auto ld_o = [&](int layer) {
#pragma unroll 1
        for (int half = 0; half < 2; half++) {
          done(1, 7, layer);
          mbar_wait(bar + 8 * B_OST, layer);
          if (half) mbar_wait(bar + 8 * (B_OST + 1), layer);
          fence_async_smem();
#pragma unroll
          for (int c = 0; c < 4; c++) mbar_expect(bar + 8 * (B_OF + 4 * half + c), 2 * PG);
          const bf16* src = g_O + (layer * 32 + 16 * half + rb) * 4 * PG;
          uint32_t dst0 = sb + o_page(half, 0) * PG;
          pin(src); pin(dst0);
          spin_hint(&g_cnt[(C_O + layer * 32 + 16 * half + rb) * 32], e1 * 32);
#pragma unroll
          for (int c = 0; c < 4; c++) {
            if (c == 2 && half && layer) { mbar_wait(bar + 8 * B_AL, 0); fence_async_smem(); }
            bulk_ld(c ? sb + o_page(half, c) * PG : dst0, src + c * PG, 2 * PG, bar + 8 * (B_OF + 4 * half + c));
          }
        }
      };
      if (elect_one()) {
        mbar_wait(bar + 8 * (B_WF + 2), 0);
        asm volatile("prefetch.tensormap [%0];" ::"l"(&p.mapXT) : "memory");
        asm volatile("prefetch.tensormap [%0];" ::"l"(&p.mapWo) : "memory");
        spin_until(&g_cnt[C_Z * 32], e1 * NCTA);
        mbar_arrive(bar + 8 * B_ZF);
        TS(3);
        ld_o(0);
#pragma unroll 1
        for (int k = 0; k < 3; k++) {
          mbar_wait(bar + 8 * (B_PUB + k), 0);
          if (k == 2) {
#pragma unroll 1
            for (int c = 0; c < 4; c++) mbar_wait(bar + 8 * (B_XF + c), 1);
          }
          fence_async_smem();
          uint32_t b = bar + 8 * (B_XR + 4 * (k & 1)), dst = sb + (k ? 4 + 4 * k : 0) * PG, c0 = ((k ? 16 : 0) + rb) * 64, c1 = DM + (k & 2) * 128;
#pragma unroll
          for (int c = 0; c < 4; c++) mbar_expect(b + 8 * c, PG);
          pin(b); pin(dst); pin(c0); pin(c1);
          spin_hint(&g_cnt[(C_C + k) * 32], e1 * NCTA);
          TS(10 + k);
#pragma unroll
          for (int c = 0; c < 4; c++) tma_ld(dst + c * PG, &p.mapXT, c0, c1 + c * 64, b + 8 * c);
        }
        ld_o(1);
#pragma unroll 1
        for (int k = 0; k < 2; k++) {
          mbar_wait(bar + 8 * (B_PUB + k), 1);
          spin_hint(&g_cnt[(C_F + 8 * k + (cta >> 4)) * 32], e1 * 16);
          mbar_arrive(bar + 8 * (B_TF + k));
        }
      }
    } else if (warp == 14) {
      mbar_wait(bar + 8 * B_EP, 0);
      const unsigned e1 = (lds32(sb + SM_EP) / NCTA) + 1;
      done(0, 1, 0);
      {
        const uint2* cp = g_colsum + (hg * 192 + lane);
        uint2 v[6];
        bool ok;
        int it = 0;
        do {
          ok = true;
#pragma unroll
          for (int i = 0; i < 6; i++) {
            asm volatile("ld.relaxed.gpu.global.v2.u32 {%0,%1}, [%2];" : "=r"(v[i].x), "=r"(v[i].y) : "l"(cp + 32 * i) : "memory");
            ok = ok && v[i].y == e1;
          }
          if (++it > (1 << 22)) __trap();
        } while (!__all_sync(~0u, ok));
#pragma unroll
        for (int i = 0; i < 6; i++) sts32f(sb + SM_CS + 4 * (lane + 32 * i), __uint_as_float(v[i].x));
      }
      __syncwarp();
      if (elect_one()) {
        mbar_wait(bar + 8 * B_ZF, 0);
        mbar_arrive(bar + 8 * B_LN);
        red_relaxed(&g_cnt[C_CS * 32]);
        TS(13);
#pragma unroll 1
        for (int layer = 0; layer < 2; layer++) {
          const uint32_t b = bar + 8 * (B_GB + 1);
          const bf16* xin = g_xT + ((size_t)2 * layer * DM + 2 * cta) * LSEQ + 1024;
          const float* stats = g_stats + (layer * 32 + 16) * 192;
          mbar_wait(bar + 8 * B_PST, layer);
          spin_hint(&g_cnt[(C_G + 2 * layer) * 32], e1 * NCTA);
          mbar_arrive(bar + 8 * B_GB);
          mbar_wait(bar + 8 * (B_PST + 1), layer);
          fence_async_smem();
          mbar_expect(b, 12288 + PG);
          pin(stats); pin(xin);
          spin_hint(&g_cnt[(C_G + 2 * layer + 1) * 32], e1 * NCTA);
          bulk_ld(sb + CV_ST, stats, 12288, b);
#pragma unroll
          for (int lc = 0; lc < 4; lc++) bulk_ld(sb + cv_x(1, lc), xin + cv_chan(0, lc) * LSEQ, 2048, b);
          TS(14 + layer);
          publish(layer, 1);
        }
      }
    } else {
      const uint4 u = make_uint4(UNSET, UNSET, UNSET, UNSET);
      if (lane < 24) stg128((uint4*)g_stats + cta * 24 + lane, make_uint4(0, 0, 0, 0));
      if (lane < 16) stg128(g_rows + LSEQ + cta * 16 + lane, make_uint4(0, 0, 0, 0));
#pragma unroll 4
      for (int i = 0; i < 16; i++) stg128(g_halo + cta * 512 + 32 * i + lane, u);
#pragma unroll 4
      for (int i = 0; i < 16; i++) stg128(((i & 8) ? (uint4*)g_xT : (uint4*)g_O) + cta * 1024 + (i & 7) * 128 + (lane >> 1) * 8 + (lane & 1), u);
      __syncwarp();
      if (elect_one()) red_release(&g_cnt[C_Z * 32]);
      __syncwarp();
#pragma unroll 1
      for (int layer = 0; layer < 2; layer++) {
        auto reset_done = [&](int s) {
          spin_until(&g_cnt[(C_R + s) * 32], (lds32(sb + SM_EP) / NCTA) * 4 + 4);
          mbar_arrive(bar + 8 * (s == 1 ? B_LN : s == 2 ? B_RS : B_RC));
          if (s) TS(16 + 40 + 9 + s);
        };
        if (layer && elect_one()) reset_done(1);
        __syncwarp();
#pragma unroll 1
        for (int half = 0; half < 2; half++) {
          done(half, 2, layer);
          const uint4* src = g_rows + (layer * LSEQ + (16 * half + rb) * 64 + (opaque_tid() & 31));
          uint4 a, b;
          int it = 0;
          do {
            a = ld_tagged(src); b = ld_tagged(src + 32);
          } while (!__all_sync(~0u, (a.z | a.w) == __float_as_uint(8.f) && (b.z | b.w) == __float_as_uint(8.f)) && ++it < (1 << 20));
          float m0 = __uint_as_float(a.x) * (1.f / DM), m1 = __uint_as_float(b.x) * (1.f / DM);
          float r0 = rsqrt_approx(fmaxf(__uint_as_float(a.y) * (1.f / DM) - m0 * m0, 0.f) + 1e-5f);
          float r1 = rsqrt_approx(fmaxf(__uint_as_float(b.y) * (1.f / DM) - m1 * m1, 0.f) + 1e-5f);
          if (half) done(0, 7, layer);
          const uint32_t dst = sb + ln_off(half) + ((lane >> 4) * 8 + (lane & 7)) * 16 + (lane & 8);
          asm volatile("st.shared.v2.f32 [%0], {%1,%2};" ::"r"(dst), "f"(m0), "f"(r0) : "memory");
          asm volatile("st.shared.v2.f32 [%0], {%1,%2};" ::"r"(dst + 256), "f"(m1), "f"(r1) : "memory");
          __syncwarp();
          if (elect_one()) { mbar_arrive(bar + 8 * (B_LN + half)); TS(16 + layer * 56 + 40 + 14 + half); }
        }
        if (layer && lane < 16) stg128(g_rows + cta * 16 + (opaque_tid() & 31), make_uint4(0, 0, 0, 0));
        if (elect_one()) {
          if (layer) reset_done(2);
          reset_done(3 * layer);
          publish(layer, 0);
          if (!layer) publish(layer, 2);
        }
        __syncwarp();
      }
    }
  }
}

typedef CUresult (*EncodeFn)(CUtensorMap*, CUtensorMapDataType, cuuint32_t, void*, const cuuint64_t*, const cuuint64_t*,
                             const cuuint32_t*, const cuuint32_t*, CUtensorMapInterleave, CUtensorMapSwizzle,
                             CUtensorMapL2promotion, CUtensorMapFloatOOBfill);

static void make_map(EncodeFn enc, CUtensorMap* m, void* ptr, uint64_t cols, uint64_t rows, uint32_t box_rows) {
  cuuint64_t dims[2] = {cols, rows};
  cuuint64_t strides[1] = {cols * 2};
  cuuint32_t box[2] = {64, box_rows};
  cuuint32_t es[2] = {1, 1};
  enc(m, CU_TENSOR_MAP_DATA_TYPE_BFLOAT16, 2, ptr, dims, strides, box, es, CU_TENSOR_MAP_INTERLEAVE_NONE,
      CU_TENSOR_MAP_SWIZZLE_128B, CU_TENSOR_MAP_L2_PROMOTION_L2_128B, CU_TENSOR_MAP_FLOAT_OOB_FILL_NONE);
}
static void make_map3(EncodeFn enc, CUtensorMap* m, void* ptr, uint64_t d0, uint64_t cols, uint64_t rows, uint64_t blk_stride,
                      uint64_t nblocks, uint32_t nblk) {
  cuuint64_t dims[3] = {d0, rows, nblocks};
  cuuint64_t strides[2] = {cols * 2, blk_stride * 2};
  cuuint32_t box[3] = {64, 64, nblk};
  cuuint32_t es[3] = {1, 1, 1};
  enc(m, CU_TENSOR_MAP_DATA_TYPE_BFLOAT16, 3, ptr, dims, strides, box, es, CU_TENSOR_MAP_INTERLEAVE_NONE,
      CU_TENSOR_MAP_SWIZZLE_128B, CU_TENSOR_MAP_L2_PROMOTION_L2_128B, CU_TENSOR_MAP_FLOAT_OOB_FILL_NONE);
}

extern "C" void kernel_launch(void* const* d_in, const int* in_sizes, int n_in, void* d_out, int out_size) {
  static Params prm;
  static void* cached[13] = {nullptr};
  static bool attr_done = false;
  static int grid = NCTA + 4;
  bool same = attr_done && cached[12] == d_out;
  for (int i = 0; i < 12 && same; i++) same = cached[i] == d_in[i];
  if (!same) {
    void* fn = nullptr;
    cudaDriverEntryPointQueryResult qr;
    cudaGetDriverEntryPoint("cuTensorMapEncodeTiled", &fn, cudaEnableDefault, &qr);
    EncodeFn enc = (EncodeFn)fn;
    void* pXT;
    cudaGetSymbolAddress(&pXT, g_xT);
    make_map(enc, &prm.mapX, d_in[0], DM, LSEQ, 64);
    make_map(enc, &prm.mapXT, pXT, LSEQ, 4 * DM, 64);
    {
      cuuint64_t dims[5] = {DM, 2, 4, 4, 16};
      cuuint64_t strides[4] = {DM * 2, 8 * DM * 2, 2 * DM * 2, 32 * DM * 2};
      cuuint32_t box[5] = {64, 2, 4, 4, 2};
      cuuint32_t es[5] = {1, 1, 1, 1, 1};
      enc(&prm.mapWo, CU_TENSOR_MAP_DATA_TYPE_BFLOAT16, 5, d_in[2], dims, strides, box, es, CU_TENSOR_MAP_INTERLEAVE_NONE,
          CU_TENSOR_MAP_SWIZZLE_128B, CU_TENSOR_MAP_L2_PROMOTION_L2_128B, CU_TENSOR_MAP_FLOAT_OOB_FILL_NONE);
    }
    make_map3(enc, &prm.mapW3, d_in[1], DM, 3 * DM, DM, DM, 3, 3);
    prm.out = (bf16*)d_out;
    prm.a_re = (const bf16*)d_in[4]; prm.a_im = (const bf16*)d_in[5];
    prm.b_re = (const bf16*)d_in[6]; prm.b_im = (const bf16*)d_in[7];
    prm.c_re = (const bf16*)d_in[8]; prm.c_im = (const bf16*)d_in[9];
    prm.log_dt = (const bf16*)d_in[10]; prm.dskip = (const bf16*)d_in[11];
    int dev = 0, sms = 0;
    cudaGetDevice(&dev);
    cudaDeviceGetAttribute(&sms, cudaDevAttrMultiProcessorCount, dev);
    grid = sms >= NCTA + 4 ? NCTA + 4 : NCTA + 5;
    cudaFuncSetAttribute(fused_kernel, cudaFuncAttributeMaxDynamicSharedMemorySize, SM_TOTAL);
    for (int i = 0; i < 12; i++) cached[i] = d_in[i];
    cached[12] = d_out;
    attr_done = true;
  }
  fused_kernel<<<grid, NTHREADS, SM_TOTAL>>>(prm);
}
```

```cpp
#include <cuda_runtime.h>
#include <cuda_bf16.h>
#include <cuda.h>
#include <stdint.h>

typedef __nv_bfloat16 bf16;

constexpr int LSEQ = 2048;
constexpr int DM = 512;
constexpr int NCTA = 128;
constexpr int NTHREADS = 512;
#define R_CONS 200
#define R_HELP 88
#define R_AGENT 24
#define TURN0 4
#define TURN1 4

constexpr int PG = 8192;
constexpr int P_R = 25;
__host__ __device__ constexpr int x_page(int half, int c) { return half ? 8 + c : c < 5 ? c : c - 5; }
__host__ __device__ constexpr int w_page(int c) { return (c & 3) < 3 ? 16 + 3 * (c & 3) : c < 4 ? 5 : 8; }
__host__ __device__ constexpr int wo_page(int c) { return c < 5 ? 3 + c : 11 + c; }
__host__ __device__ constexpr int o_page(int half, int pair) { return half ? (pair ? 25 - 2 * pair : 0) : 8 + 2 * pair; }
constexpr int SM_KGB = (P_R + 1) * PG;
constexpr int SM_KC = 27 * PG;
constexpr int KC_STRIDE = 648;
__host__ __device__ constexpr int kc_off(int lc) { return SM_KC + (lc & 1) * 2 * KC_STRIDE + (lc < 2 ? 3328 : 0); }
constexpr int SM_KGT = SM_KC + 3328 + 2592;
constexpr int SM_CS = SM_KGT + 2048;
constexpr int SM_RED = SM_CS + 768;
constexpr int SM_EP = SM_RED + 16;
constexpr int SM_STG = SM_RED + 32;
constexpr int SM_LN = SM_STG + 768;
__host__ __device__ constexpr int ln_off(int half) { return half ? PG + 5120 : SM_LN; }
constexpr int SM_BAR = SM_LN + 512;
constexpr int SM_TS = SM_BAR + 704;
constexpr int SM_TOTAL = SM_TS + 512;
static_assert(SM_TOTAL <= 232448 && SM_STG % 16 == 0 && SM_KGT % 16 == 0, "shared memory");

constexpr int CV_UH = 140 * 16;
__host__ __device__ constexpr int cv_u(int lc) { return (8 + 2 * lc) * PG; }
__host__ __device__ constexpr int cv_pe(int lc, int early) { return early ? 19 * PG + lc * 4480 : cv_u(lc) + 4480; }
__host__ __device__ constexpr int cv_pb1(int lc, int w) { return w ? cv_u(lc) + 8960 + (w - 1) * 2048 : 7 * PG + lc * 2048; }
__host__ __device__ constexpr int cv_fa(int lc) { return cv_pb1(lc, 1) + 128; }
__host__ __device__ constexpr int cv_dump(int lc) { return cv_u(lc) + 16256; }
__host__ __device__ constexpr int cv_pb0(int lc, int w) { return lc * PG + w * 2048; }
__host__ __device__ constexpr int cv_se(int lc) { return 5 * PG + lc * 4096; }
__host__ __device__ constexpr int cv_so(int lc) { return cv_se(lc) + 2048; }
__host__ __device__ constexpr int cv_x(int half, int lc) { return (P_R + half) * PG + lc * 2048; }
constexpr int CV_ST = 22 * PG;
__host__ __device__ constexpr int cv_chan(int cta, int lc) { return 2 * cta + (lc & 1) + 256 * (lc >> 1); }

enum {
  B_XF = 0,
  B_WF = 16,
  B_OF = 24,
  B_DN = 32,
  B_PG = 46,
  B_XR = 48,
  B_RF = 56,
  B_PST = 58,
  B_GB = 60,
  B_TF = 62,
  B_RT = 64,
  B_RS = 66,
  B_RC = 67,
  B_WOF = 68,
  B_ZF = 69,
  B_EP = 70,
  B_KG = 71,
  B_SC = 37,
  B_LN = 72,
  B_END = 38,
  B_STG = 74,
  B_OST = 76,
  B_PDONE = 78,
  B_PE = 80,
  B_U = 81,
  B_U1 = 82,
  B_PUB = 83,
  B_AL = 86,
  B_COUNT = 87
};

enum {
  C_CS = 0,
  C_G = 1,
  C_C = 5,
  C_O = 21,
  C_Z = 85,
  C_R = 86,
  C_F = 90,
  C_COUNT = 106
};

__device__ unsigned g_cnt[C_COUNT * 32];
__device__ __align__(1024) bf16 g_O[2 * LSEQ * DM];
__device__ __align__(1024) bf16 g_xT[4 * DM * LSEQ];
__device__ __align__(1024) float g_stats[2 * 32 * 192];
__device__ __align__(1024) uint2 g_colsum[3 * DM];
__device__ __align__(1024) uint4 g_halo[32 * 8 * 256];
__device__ __align__(1024) uint4 g_rows[2 * LSEQ];
#define TS(i) do { } while (0)
#define TSW(k) do { if ((threadIdx.x & 127) == 0) TS(16 + layer * 56 + (threadIdx.x >> 7) * 20 + (k)); } while (0)
#define TSG(k) do { } while (0)

#define RETRY(i) do { } while (0)
#define LTS(i) do { } while (0)
#define LTE() do { } while (0)

struct Params {
  CUtensorMap mapX, mapW3, mapXT, mapWo;
  bf16* out;
  const bf16 *a_re, *a_im, *b_re, *b_im, *c_re, *c_im, *log_dt, *dskip;
};

__device__ __forceinline__ uint32_t s32(const void* p) { return (uint32_t)__cvta_generic_to_shared(p); }
__device__ __forceinline__ void mbar_init(uint32_t b, int c) { asm volatile("mbarrier.init.shared::cta.b64 [%0], %1;" ::"r"(b), "r"(c) : "memory"); }
__device__ __forceinline__ void mbar_expect(uint32_t b, int bytes) { asm volatile("mbarrier.arrive.expect_tx.shared::cta.b64 _, [%0], %1;" ::"r"(b), "r"(bytes) : "memory"); }
__device__ __forceinline__ void mbar_arrive(uint32_t b) { asm volatile("mbarrier.arrive.shared::cta.b64 _, [%0];" ::"r"(b) : "memory"); }
__device__ __forceinline__ void mbar_wait(uint32_t b, int parity) {
  asm volatile("{\n.reg .pred p;\nWAIT_LOOP:\nmbarrier.try_wait.parity.shared::cta.b64 p, [%0], %1;\n@p bra WAIT_DONE;\nbra WAIT_LOOP;\nWAIT_DONE:\n}" ::"r"(b), "r"(parity) : "memory");
}
__device__ __forceinline__ bool mbar_test(uint32_t b, int parity) {
  uint32_t ok;
  asm volatile("{\n.reg .pred p;\nmbarrier.test_wait.parity.shared::cta.b64 p, [%1], %2;\nselp.u32 %0, 1, 0, p;\n}" : "=r"(ok) : "r"(b), "r"(parity) : "memory");
  return ok != 0;
}
__device__ __forceinline__ int opaque_tid() { int v; asm volatile("mov.u32 %0, %%tid.x;" : "=r"(v)); return v; }
__device__ __forceinline__ bool elect_one() {
  uint32_t r;
  asm volatile("{\n.reg .pred p;\nelect.sync _|p, 0xffffffff;\nselp.u32 %0, 1, 0, p;\n}" : "=r"(r));
  return r != 0;
}
__device__ __forceinline__ void tma_ld(uint32_t dst, const CUtensorMap* m, int c0, int c1, uint32_t bar) {
  asm volatile("cp.async.bulk.tensor.2d.shared::cluster.global.mbarrier::complete_tx::bytes [%0], [%1, {%3, %4}], [%2];"
               ::"r"(dst), "l"(m), "r"(bar), "r"(c0), "r"(c1) : "memory");
}
__device__ __forceinline__ void tma_ld3(uint32_t dst, const CUtensorMap* m, int c0, int c1, int c2, uint32_t bar) {
  asm volatile("cp.async.bulk.tensor.3d.shared::cluster.global.mbarrier::complete_tx::bytes [%0], [%1, {%3, %4, %5}], [%2];"
               ::"r"(dst), "l"(m), "r"(bar), "r"(c0), "r"(c1), "r"(c2) : "memory");
}
__device__ __forceinline__ void tma_ld5(uint32_t dst, const CUtensorMap* m, int c0, int c4, uint32_t bar) {
  asm volatile("cp.async.bulk.tensor.5d.shared::cluster.global.mbarrier::complete_tx::bytes [%0], [%1, {%3, 0, 0, 0, %4}], [%2];"
               ::"r"(dst), "l"(m), "r"(bar), "r"(c0), "r"(c4) : "memory");
}
__device__ __forceinline__ void tma_prefetch5(const CUtensorMap* m, int c0, int c4) {
  asm volatile("cp.async.bulk.prefetch.tensor.5d.L2.global.tile [%0, {%1, 0, 0, 0, %2}];" ::"l"(m), "r"(c0), "r"(c4) : "memory");
}
__device__ __forceinline__ void tma_prefetch3(const CUtensorMap* m, int c0, int c1, int c2) {
  asm volatile("cp.async.bulk.prefetch.tensor.3d.L2.global.tile [%0, {%1, %2, %3}];" ::"l"(m), "r"(c0), "r"(c1), "r"(c2) : "memory");
}
__device__ __forceinline__ void tma_st(const CUtensorMap* m, int c0, int c1, uint32_t src) {
  asm volatile("cp.async.bulk.tensor.2d.global.shared::cta.bulk_group [%0, {%2, %3}], [%1];" ::"l"(m), "r"(src), "r"(c0), "r"(c1) : "memory");
}
__device__ __forceinline__ void bulk_ld(uint32_t dst, const void* src, int bytes, uint32_t bar) {
  asm volatile("cp.async.bulk.shared::cluster.global.mbarrier::complete_tx::bytes [%0], [%1], %2, [%3];" ::"r"(dst), "l"(src), "r"(bytes), "r"(bar) : "memory");
}
__device__ __forceinline__ void bulk_red_add_f32(void* dst, uint32_t src, int bytes) {
  asm volatile("cp.reduce.async.bulk.global.shared::cta.bulk_group.add.f32 [%0], [%1], %2;" ::"l"(dst), "r"(src), "r"(bytes) : "memory");
}
__device__ __forceinline__ void bulk_commit() { asm volatile("cp.async.bulk.commit_group;" ::: "memory"); }
__device__ __forceinline__ void fence_async_smem() { asm volatile("fence.proxy.async.shared::cta;" ::: "memory"); }
__device__ __forceinline__ void fence_async_global() { asm volatile("fence.proxy.async.global;" ::: "memory"); }
__device__ __forceinline__ void bar_sync(int id, int n) { asm volatile("bar.sync %0, %1;" ::"r"(id), "r"(n) : "memory"); }
__device__ __forceinline__ void bar_arrive(int id, int n) { asm volatile("bar.arrive %0, %1;" ::"r"(id), "r"(n) : "memory"); }
__device__ __forceinline__ bool bar_or(int id, int n, bool v) {
  uint32_t r;
  asm volatile("{\n.reg .pred p, q;\nsetp.ne.u32 q, %3, 0;\nbar.red.or.pred p, %1, %2, q;\nselp.u32 %0, 1, 0, p;\n}" : "=r"(r) : "r"(id), "r"(n), "r"((uint32_t)v) : "memory");
  return r != 0;
}
__device__ __forceinline__ void bulk_wait_read() { asm volatile("cp.async.bulk.wait_group.read 0;" ::: "memory"); }
__device__ __forceinline__ void stg128(void* p, uint4 v) { asm volatile("st.relaxed.gpu.global.v4.u32 [%0], {%1,%2,%3,%4};" ::"l"(p), "r"(v.x), "r"(v.y), "r"(v.z), "r"(v.w) : "memory"); }
constexpr uint32_t UNSET = 0xffffffffu;
constexpr int MAX_RETRY = 1 << 16;
__device__ __forceinline__ void wg_fence() { asm volatile("wgmma.fence.sync.aligned;" ::: "memory"); }
__device__ __forceinline__ void wg_commit() { asm volatile("wgmma.commit_group.sync.aligned;" ::: "memory"); }
template <int N> __device__ __forceinline__ void wg_wait() { asm volatile("wgmma.wait_group.sync.aligned %0;" ::"n"(N) : "memory"); }
__device__ __forceinline__ uint64_t mkdesc(uint32_t addr, uint32_t lbo, uint32_t sbo, int sw) {
  return (uint64_t)((addr & 0x3FFFF) >> 4) | ((uint64_t)(lbo >> 4) << 16) | ((uint64_t)(sbo >> 4) << 32) | ((uint64_t)sw << 62);
}
__device__ __forceinline__ void ldsm4(uint32_t* r, uint32_t a) {
  asm volatile("ldmatrix.sync.aligned.m8n8.x4.shared.b16 {%0,%1,%2,%3}, [%4];" : "=r"(r[0]), "=r"(r[1]), "=r"(r[2]), "=r"(r[3]) : "r"(a) : "memory");
}
__device__ __forceinline__ void ldsm4t(uint32_t* r, uint32_t a) {
  asm volatile("ldmatrix.sync.aligned.m8n8.x4.trans.shared.b16 {%0,%1,%2,%3}, [%4];" : "=r"(r[0]), "=r"(r[1]), "=r"(r[2]), "=r"(r[3]) : "r"(a) : "memory");
}
__device__ __forceinline__ void stsm4(uint32_t a, uint32_t r0, uint32_t r1, uint32_t r2, uint32_t r3) {
  asm volatile("stmatrix.sync.aligned.m8n8.x4.shared.b16 [%0], {%1,%2,%3,%4};" ::"r"(a), "r"(r0), "r"(r1), "r"(r2), "r"(r3) : "memory");
}
__device__ __forceinline__ void stsm4t(uint32_t a, uint32_t r0, uint32_t r1, uint32_t r2, uint32_t r3) {
  asm volatile("stmatrix.sync.aligned.m8n8.x4.trans.shared.b16 [%0], {%1,%2,%3,%4};" ::"r"(a), "r"(r0), "r"(r1), "r"(r2), "r"(r3) : "memory");
}
__device__ __forceinline__ uint32_t movm_t(uint32_t a) { uint32_t r; asm volatile("movmatrix.sync.aligned.m8n8.trans.b16 %0, %1;" : "=r"(r) : "r"(a)); return r; }
__device__ __forceinline__ uint32_t lds32(uint32_t a) { uint32_t v; asm volatile("ld.shared.b32 %0, [%1];" : "=r"(v) : "r"(a) : "memory"); return v; }
__device__ __forceinline__ float2 lds64f(uint32_t a) { float2 v; asm volatile("ld.shared.v2.f32 {%0,%1}, [%2];" : "=f"(v.x), "=f"(v.y) : "r"(a) : "memory"); return v; }
__device__ __forceinline__ float4 lds128f(uint32_t a) { float4 v; asm volatile("ld.shared.v4.f32 {%0,%1,%2,%3}, [%4];" : "=f"(v.x), "=f"(v.y), "=f"(v.z), "=f"(v.w) : "r"(a) : "memory"); return v; }
__device__ __forceinline__ uint4 lds128(uint32_t a) { uint4 v; asm volatile("ld.shared.v4.b32 {%0,%1,%2,%3}, [%4];" : "=r"(v.x), "=r"(v.y), "=r"(v.z), "=r"(v.w) : "r"(a) : "memory"); return v; }
__device__ __forceinline__ void sts128(uint32_t a, uint4 v) { asm volatile("st.shared.v4.b32 [%0], {%1,%2,%3,%4};" ::"r"(a), "r"(v.x), "r"(v.y), "r"(v.z), "r"(v.w) : "memory"); }
__device__ __forceinline__ void sts128f(uint32_t a, float x, float y, float z, float w) { asm volatile("st.shared.v4.f32 [%0], {%1,%2,%3,%4};" ::"r"(a), "f"(x), "f"(y), "f"(z), "f"(w) : "memory"); }
__device__ __forceinline__ void sts32f(uint32_t a, float v) { asm volatile("st.shared.f32 [%0], %1;" ::"r"(a), "f"(v) : "memory"); }
__device__ __forceinline__ void sts16(uint32_t a, uint16_t v) { asm volatile("st.shared.u16 [%0], %1;" ::"r"(a), "h"(v) : "memory"); }
__device__ __forceinline__ uint32_t lds16(uint32_t a) { uint16_t v; asm volatile("ld.shared.u16 %0, [%1];" : "=h"(v) : "r"(a) : "memory"); return v; }
__device__ __forceinline__ uint32_t packbf(float lo, float hi) { uint32_t r; asm("cvt.rn.bf16x2.f32 %0, %1, %2;" : "=r"(r) : "f"(hi), "f"(lo)); return r; }
__device__ __forceinline__ uint32_t prmt0(uint32_t a, uint32_t sel) { uint32_t r; asm("prmt.b32 %0, %1, 0, %2;" : "=r"(r) : "r"(a), "r"(sel)); return r; }
__device__ __forceinline__ float bf_lo(uint32_t v) { return __uint_as_float(v << 16); }
__device__ __forceinline__ float bf_hi(uint32_t v) { return __uint_as_float(v & 0xffff0000u); }
__device__ __forceinline__ float ex2(float x) { float r; asm("ex2.approx.ftz.f32 %0, %1;" : "=f"(r) : "f"(x)); return r; }
__device__ __forceinline__ float rsqrt_approx(float x) { float r; asm("rsqrt.approx.ftz.f32 %0, %1;" : "=f"(r) : "f"(x)); return r; }
__device__ __forceinline__ float rcp_approx(float x) { float r; asm("rcp.approx.ftz.f32 %0, %1;" : "=f"(r) : "f"(x)); return r; }
__device__ __forceinline__ void mma_bf16(float* d, const uint32_t* a, uint32_t b0, uint32_t b1) {
  asm("mma.sync.aligned.m16n8k16.row.col.f32.bf16.bf16.f32 {%0,%1,%2,%3}, {%4,%5,%6,%7}, {%8,%9}, {%0,%1,%2,%3};"
               : "+f"(d[0]), "+f"(d[1]), "+f"(d[2]), "+f"(d[3]) : "r"(a[0]), "r"(a[1]), "r"(a[2]), "r"(a[3]), "r"(b0), "r"(b1));
}
__device__ __forceinline__ void mma_bf16_c(float* d, const uint32_t* a, uint32_t b0, uint32_t b1, const float* c) {
  asm("mma.sync.aligned.m16n8k16.row.col.f32.bf16.bf16.f32 {%0,%1,%2,%3}, {%4,%5,%6,%7}, {%8,%9}, {%10,%11,%12,%13};"
               : "=f"(d[0]), "=f"(d[1]), "=f"(d[2]), "=f"(d[3]) : "r"(a[0]), "r"(a[1]), "r"(a[2]), "r"(a[3]), "r"(b0), "r"(b1),
                 "f"(c[0]), "f"(c[1]), "f"(c[2]), "f"(c[3]));
}
__device__ __forceinline__ void mma_rowsum(float* d, uint32_t a0, uint32_t a1) {
  asm("mma.sync.aligned.m16n8k8.row.col.f32.bf16.bf16.f32 {%0,%1,%2,%3}, {%4,%5}, {%6}, {%7,%7,%7,%7};"
               : "=f"(d[0]), "=f"(d[1]), "=f"(d[2]), "=f"(d[3]) : "r"(a0), "r"(a1), "r"(0x3f803f80u), "f"(0.f));
}
__device__ __forceinline__ void red_release(unsigned* p) { asm volatile("red.release.gpu.global.add.u32 [%0], 1;" ::"l"(p) : "memory"); }
__device__ __forceinline__ void red_relaxed(unsigned* p) { asm volatile("red.relaxed.gpu.global.add.u32 [%0], 1;" ::"l"(p) : "memory"); }
__device__ __forceinline__ unsigned ld_relaxed(const unsigned* p) { unsigned v; asm volatile("ld.relaxed.gpu.global.u32 %0, [%1];" : "=r"(v) : "l"(p) : "memory"); return v; }
__device__ __forceinline__ void spin_until(const unsigned* p, unsigned target) {
  int it = 0;
  while ((int)(ld_relaxed(p) - target) < 0) {
    if (++it > (1 << 23)) __trap();
  }
}
template <typename T> __device__ __forceinline__ void pin(T*& p) { asm volatile("" : "+l"(p) :: "memory"); }
__device__ __forceinline__ void pin(uint32_t& v) { asm volatile("" : "+r"(v) :: "memory"); }
__device__ __forceinline__ void spin_hint(const unsigned* p, unsigned target) {
  spin_until(p, target);
}
__device__ __forceinline__ uint4 ld_tagged(const uint4* p) { uint4 v; asm volatile("ld.relaxed.gpu.global.v4.u32 {%0,%1,%2,%3}, [%4];" : "=r"(v.x), "=r"(v.y), "=r"(v.z), "=r"(v.w) : "l"(p) : "memory"); return v; }
__device__ __forceinline__ uint32_t hadd2(uint32_t a, uint32_t b) { uint32_t r; asm("add.rn.bf16x2 %0, %1, %2;" : "=r"(r) : "r"(a), "r"(b)); return r; }

__device__ __forceinline__ uint32_t hfma2(uint32_t a, uint32_t b, uint32_t c) { uint32_t r; asm("fma.rn.bf16x2 %0, %1, %2, %3;" : "=r"(r) : "r"(a), "r"(b), "r"(c)); return r; }
__device__ __forceinline__ void sts32(uint32_t a, uint32_t v) { asm volatile("st.shared.u32 [%0], %1;" ::"r"(a), "r"(v) : "memory"); }

template <int N> __device__ __forceinline__ void acc_fence(float* a) {
#pragma unroll
  for (int i = 0; i < N; i++) asm volatile("" : "+f"(a[i]) :: "memory");
}

template<int N,int TB> __device__ __forceinline__ void wgmma_rs(float* d, const uint32_t* a, uint64_t db, int sd);
template<int N,int TA,int TB> __device__ __forceinline__ void wgmma_ss(float* d, uint64_t da, uint64_t db, int sd);
template<> __device__ __forceinline__ void wgmma_rs<64,0>(float* d, const uint32_t* a, uint64_t db, int sd) {
  asm volatile("{\n.reg .pred p;\nsetp.ne.b32 p, %37, 0;\nwgmma.mma_async.sync.aligned.m64n64k16.f32.bf16.bf16 {%0,%1,%2,%3,%4,%5,%6,%7,%8,%9,%10,%11,%12,%13,%14,%15,%16,%17,%18,%19,%20,%21,%22,%23,%24,%25,%26,%27,%28,%29,%30,%31}, {%32,%33,%34,%35}, %36, p, 1, 1, 0;\n}\n"
   : "+f"(d[0]),"+f"(d[1]),"+f"(d[2]),"+f"(d[3]),"+f"(d[4]),"+f"(d[5]),"+f"(d[6]),"+f"(d[7]),"+f"(d[8]),"+f"(d[9]),"+f"(d[10]),"+f"(d[11]),"+f"(d[12]),"+f"(d[13]),"+f"(d[14]),"+f"(d[15]),"+f"(d[16]),"+f"(d[17]),"+f"(d[18]),"+f"(d[19]),"+f"(d[20]),"+f"(d[21]),"+f"(d[22]),"+f"(d[23]),"+f"(d[24]),"+f"(d[25]),"+f"(d[26]),"+f"(d[27]),"+f"(d[28]),"+f"(d[29]),"+f"(d[30]),"+f"(d[31])
   : "r"(a[0]), "r"(a[1]), "r"(a[2]), "r"(a[3]), "l"(db), "r"(sd));
}
template<> __device__ __forceinline__ void wgmma_rs<56,0>(float* d, const uint32_t* a, uint64_t db, int sd) {
  asm volatile("{\n.reg .pred p;\nsetp.ne.b32 p, %33, 0;\nwgmma.mma_async.sync.aligned.m64n56k16.f32.bf16.bf16 {%0,%1,%2,%3,%4,%5,%6,%7,%8,%9,%10,%11,%12,%13,%14,%15,%16,%17,%18,%19,%20,%21,%22,%23,%24,%25,%26,%27}, {%28,%29,%30,%31}, %32, p, 1, 1, 0;\n}\n"
   : "+f"(d[0]),"+f"(d[1]),"+f"(d[2]),"+f"(d[3]),"+f"(d[4]),"+f"(d[5]),"+f"(d[6]),"+f"(d[7]),"+f"(d[8]),"+f"(d[9]),"+f"(d[10]),"+f"(d[11]),"+f"(d[12]),"+f"(d[13]),"+f"(d[14]),"+f"(d[15]),"+f"(d[16]),"+f"(d[17]),"+f"(d[18]),"+f"(d[19]),"+f"(d[20]),"+f"(d[21]),"+f"(d[22]),"+f"(d[23]),"+f"(d[24]),"+f"(d[25]),"+f"(d[26]),"+f"(d[27])
   : "r"(a[0]), "r"(a[1]), "r"(a[2]), "r"(a[3]), "l"(db), "r"(sd));
}
template<> __device__ __forceinline__ void wgmma_rs<48,0>(float* d, const uint32_t* a, uint64_t db, int sd) {
  asm volatile("{\n.reg .pred p;\nsetp.ne.b32 p, %29, 0;\nwgmma.mma_async.sync.aligned.m64n48k16.f32.bf16.bf16 {%0,%1,%2,%3,%4,%5,%6,%7,%8,%9,%10,%11,%12,%13,%14,%15,%16,%17,%18,%19,%20,%21,%22,%23}, {%24,%25,%26,%27}, %28, p, 1, 1, 0;\n}\n"
   : "+f"(d[0]),"+f"(d[1]),"+f"(d[2]),"+f"(d[3]),"+f"(d[4]),"+f"(d[5]),"+f"(d[6]),"+f"(d[7]),"+f"(d[8]),"+f"(d[9]),"+f"(d[10]),"+f"(d[11]),"+f"(d[12]),"+f"(d[13]),"+f"(d[14]),"+f"(d[15]),"+f"(d[16]),"+f"(d[17]),"+f"(d[18]),"+f"(d[19]),"+f"(d[20]),"+f"(d[21]),"+f"(d[22]),"+f"(d[23])
   : "r"(a[0]), "r"(a[1]), "r"(a[2]), "r"(a[3]), "l"(db), "r"(sd));
}
template<> __device__ __forceinline__ void wgmma_rs<40,0>(float* d, const uint32_t* a, uint64_t db, int sd) {
  asm volatile("{\n.reg .pred p;\nsetp.ne.b32 p, %25, 0;\nwgmma.mma_async.sync.aligned.m64n40k16.f32.bf16.bf16 {%0,%1,%2,%3,%4,%5,%6,%7,%8,%9,%10,%11,%12,%13,%14,%15,%16,%17,%18,%19}, {%20,%21,%22,%23}, %24, p, 1, 1, 0;\n}\n"
   : "+f"(d[0]),"+f"(d[1]),"+f"(d[2]),"+f"(d[3]),"+f"(d[4]),"+f"(d[5]),"+f"(d[6]),"+f"(d[7]),"+f"(d[8]),"+f"(d[9]),"+f"(d[10]),"+f"(d[11]),"+f"(d[12]),"+f"(d[13]),"+f"(d[14]),"+f"(d[15]),"+f"(d[16]),"+f"(d[17]),"+f"(d[18]),"+f"(d[19])
   : "r"(a[0]), "r"(a[1]), "r"(a[2]), "r"(a[3]), "l"(db), "r"(sd));
}
template<> __device__ __forceinline__ void wgmma_rs<32,0>(float* d, const uint32_t* a, uint64_t db, int sd) {
  asm volatile("{\n.reg .pred p;\nsetp.ne.b32 p, %21, 0;\nwgmma.mma_async.sync.aligned.m64n32k16.f32.bf16.bf16 {%0,%1,%2,%3,%4,%5,%6,%7,%8,%9,%10,%11,%12,%13,%14,%15}, {%16,%17,%18,%19}, %20, p, 1, 1, 0;\n}\n"
   : "+f"(d[0]),"+f"(d[1]),"+f"(d[2]),"+f"(d[3]),"+f"(d[4]),"+f"(d[5]),"+f"(d[6]),"+f"(d[7]),"+f"(d[8]),"+f"(d[9]),"+f"(d[10]),"+f"(d[11]),"+f"(d[12]),"+f"(d[13]),"+f"(d[14]),"+f"(d[15])
   : "r"(a[0]), "r"(a[1]), "r"(a[2]), "r"(a[3]), "l"(db), "r"(sd));
}
template<> __device__ __forceinline__ void wgmma_rs<24,0>(float* d, const uint32_t* a, uint64_t db, int sd) {
  asm volatile("{\n.reg .pred p;\nsetp.ne.b32 p, %17, 0;\nwgmma.mma_async.sync.aligned.m64n24k16.f32.bf16.bf16 {%0,%1,%2,%3,%4,%5,%6,%7,%8,%9,%10,%11}, {%12,%13,%14,%15}, %16, p, 1, 1, 0;\n}\n"
   : "+f"(d[0]),"+f"(d[1]),"+f"(d[2]),"+f"(d[3]),"+f"(d[4]),"+f"(d[5]),"+f"(d[6]),"+f"(d[7]),"+f"(d[8]),"+f"(d[9]),"+f"(d[10]),"+f"(d[11])
   : "r"(a[0]), "r"(a[1]), "r"(a[2]), "r"(a[3]), "l"(db), "r"(sd));
}
template<> __device__ __forceinline__ void wgmma_rs<16,0>(float* d, const uint32_t* a, uint64_t db, int sd) {
  asm volatile("{\n.reg .pred p;\nsetp.ne.b32 p, %13, 0;\nwgmma.mma_async.sync.aligned.m64n16k16.f32.bf16.bf16 {%0,%1,%2,%3,%4,%5,%6,%7}, {%8,%9,%10,%11}, %12, p, 1, 1, 0;\n}\n"
   : "+f"(d[0]),"+f"(d[1]),"+f"(d[2]),"+f"(d[3]),"+f"(d[4]),"+f"(d[5]),"+f"(d[6]),"+f"(d[7])
   : "r"(a[0]), "r"(a[1]), "r"(a[2]), "r"(a[3]), "l"(db), "r"(sd));
}
template<> __device__ __forceinline__ void wgmma_rs<8,0>(float* d, const uint32_t* a, uint64_t db, int sd) {
  asm volatile("{\n.reg .pred p;\nsetp.ne.b32 p, %9, 0;\nwgmma.mma_async.sync.aligned.m64n8k16.f32.bf16.bf16 {%0,%1,%2,%3}, {%4,%5,%6,%7}, %8, p, 1, 1, 0;\n}\n"
   : "+f"(d[0]),"+f"(d[1]),"+f"(d[2]),"+f"(d[3])
   : "r"(a[0]), "r"(a[1]), "r"(a[2]), "r"(a[3]), "l"(db), "r"(sd));
}
template<> __device__ __forceinline__ void wgmma_ss<64,1,0>(float* d, uint64_t da, uint64_t db, int sd) {
  asm volatile("{\n.reg .pred p;\nsetp.ne.b32 p, %34, 0;\nwgmma.mma_async.sync.aligned.m64n64k16.f32.bf16.bf16 {%0,%1,%2,%3,%4,%5,%6,%7,%8,%9,%10,%11,%12,%13,%14,%15,%16,%17,%18,%19,%20,%21,%22,%23,%24,%25,%26,%27,%28,%29,%30,%31}, %32, %33, p, 1, 1, 1, 0;\n}\n"
   : "+f"(d[0]),"+f"(d[1]),"+f"(d[2]),"+f"(d[3]),"+f"(d[4]),"+f"(d[5]),"+f"(d[6]),"+f"(d[7]),"+f"(d[8]),"+f"(d[9]),"+f"(d[10]),"+f"(d[11]),"+f"(d[12]),"+f"(d[13]),"+f"(d[14]),"+f"(d[15]),"+f"(d[16]),"+f"(d[17]),"+f"(d[18]),"+f"(d[19]),"+f"(d[20]),"+f"(d[21]),"+f"(d[22]),"+f"(d[23]),"+f"(d[24]),"+f"(d[25]),"+f"(d[26]),"+f"(d[27]),"+f"(d[28]),"+f"(d[29]),"+f"(d[30]),"+f"(d[31])
   : "l"(da), "l"(db), "r"(sd));
}
template<> __device__ __forceinline__ void wgmma_ss<64,0,1>(float* d, uint64_t da, uint64_t db, int sd) {
  asm volatile("{\n.reg .pred p;\nsetp.ne.b32 p, %34, 0;\nwgmma.mma_async.sync.aligned.m64n64k16.f32.bf16.bf16 {%0,%1,%2,%3,%4,%5,%6,%7,%8,%9,%10,%11,%12,%13,%14,%15,%16,%17,%18,%19,%20,%21,%22,%23,%24,%25,%26,%27,%28,%29,%30,%31}, %32, %33, p, 1, 1, 0, 1;\n}\n"
   : "+f"(d[0]),"+f"(d[1]),"+f"(d[2]),"+f"(d[3]),"+f"(d[4]),"+f"(d[5]),"+f"(d[6]),"+f"(d[7]),"+f"(d[8]),"+f"(d[9]),"+f"(d[10]),"+f"(d[11]),"+f"(d[12]),"+f"(d[13]),"+f"(d[14]),"+f"(d[15]),"+f"(d[16]),"+f"(d[17]),"+f"(d[18]),"+f"(d[19]),"+f"(d[20]),"+f"(d[21]),"+f"(d[22]),"+f"(d[23]),"+f"(d[24]),"+f"(d[25]),"+f"(d[26]),"+f"(d[27]),"+f"(d[28]),"+f"(d[29]),"+f"(d[30]),"+f"(d[31])
   : "l"(da), "l"(db), "r"(sd));
}
template<> __device__ __forceinline__ void wgmma_ss<192,0,1>(float* d, uint64_t da, uint64_t db, int sd) {
  asm volatile("{\n.reg .pred p;\nsetp.ne.b32 p, %98, 0;\nwgmma.mma_async.sync.aligned.m64n192k16.f32.bf16.bf16 {%0,%1,%2,%3,%4,%5,%6,%7,%8,%9,%10,%11,%12,%13,%14,%15,%16,%17,%18,%19,%20,%21,%22,%23,%24,%25,%26,%27,%28,%29,%30,%31,%32,%33,%34,%35,%36,%37,%38,%39,%40,%41,%42,%43,%44,%45,%46,%47,%48,%49,%50,%51,%52,%53,%54,%55,%56,%57,%58,%59,%60,%61,%62,%63,%64,%65,%66,%67,%68,%69,%70,%71,%72,%73,%74,%75,%76,%77,%78,%79,%80,%81,%82,%83,%84,%85,%86,%87,%88,%89,%90,%91,%92,%93,%94,%95}, %96, %97, p, 1, 1, 0, 1;\n}\n"
   : "+f"(d[0]),"+f"(d[1]),"+f"(d[2]),"+f"(d[3]),"+f"(d[4]),"+f"(d[5]),"+f"(d[6]),"+f"(d[7]),"+f"(d[8]),"+f"(d[9]),"+f"(d[10]),"+f"(d[11]),"+f"(d[12]),"+f"(d[13]),"+f"(d[14]),"+f"(d[15]),"+f"(d[16]),"+f"(d[17]),"+f"(d[18]),"+f"(d[19]),"+f"(d[20]),"+f"(d[21]),"+f"(d[22]),"+f"(d[23]),"+f"(d[24]),"+f"(d[25]),"+f"(d[26]),"+f"(d[27]),"+f"(d[28]),"+f"(d[29]),"+f"(d[30]),"+f"(d[31]),"+f"(d[32]),"+f"(d[33]),"+f"(d[34]),"+f"(d[35]),"+f"(d[36]),"+f"(d[37]),"+f"(d[38]),"+f"(d[39]),"+f"(d[40]),"+f"(d[41]),"+f"(d[42]),"+f"(d[43]),"+f"(d[44]),"+f"(d[45]),"+f"(d[46]),"+f"(d[47]),"+f"(d[48]),"+f"(d[49]),"+f"(d[50]),"+f"(d[51]),"+f"(d[52]),"+f"(d[53]),"+f"(d[54]),"+f"(d[55]),"+f"(d[56]),"+f"(d[57]),"+f"(d[58]),"+f"(d[59]),"+f"(d[60]),"+f"(d[61]),"+f"(d[62]),"+f"(d[63]),"+f"(d[64]),"+f"(d[65]),"+f"(d[66]),"+f"(d[67]),"+f"(d[68]),"+f"(d[69]),"+f"(d[70]),"+f"(d[71]),"+f"(d[72]),"+f"(d[73]),"+f"(d[74]),"+f"(d[75]),"+f"(d[76]),"+f"(d[77]),"+f"(d[78]),"+f"(d[79]),"+f"(d[80]),"+f"(d[81]),"+f"(d[82]),"+f"(d[83]),"+f"(d[84]),"+f"(d[85]),"+f"(d[86]),"+f"(d[87]),"+f"(d[88]),"+f"(d[89]),"+f"(d[90]),"+f"(d[91]),"+f"(d[92]),"+f"(d[93]),"+f"(d[94]),"+f"(d[95])
   : "l"(da), "l"(db), "r"(sd));
}
template<> __device__ __forceinline__ void wgmma_ss<192,1,1>(float* d, uint64_t da, uint64_t db, int sd) {
  asm volatile("{\n.reg .pred p;\nsetp.ne.b32 p, %98, 0;\nwgmma.mma_async.sync.aligned.m64n192k16.f32.bf16.bf16 {%0,%1,%2,%3,%4,%5,%6,%7,%8,%9,%10,%11,%12,%13,%14,%15,%16,%17,%18,%19,%20,%21,%22,%23,%24,%25,%26,%27,%28,%29,%30,%31,%32,%33,%34,%35,%36,%37,%38,%39,%40,%41,%42,%43,%44,%45,%46,%47,%48,%49,%50,%51,%52,%53,%54,%55,%56,%57,%58,%59,%60,%61,%62,%63,%64,%65,%66,%67,%68,%69,%70,%71,%72,%73,%74,%75,%76,%77,%78,%79,%80,%81,%82,%83,%84,%85,%86,%87,%88,%89,%90,%91,%92,%93,%94,%95}, %96, %97, p, 1, 1, 1, 1;\n}\n"
   : "+f"(d[0]),"+f"(d[1]),"+f"(d[2]),"+f"(d[3]),"+f"(d[4]),"+f"(d[5]),"+f"(d[6]),"+f"(d[7]),"+f"(d[8]),"+f"(d[9]),"+f"(d[10]),"+f"(d[11]),"+f"(d[12]),"+f"(d[13]),"+f"(d[14]),"+f"(d[15]),"+f"(d[16]),"+f"(d[17]),"+f"(d[18]),"+f"(d[19]),"+f"(d[20]),"+f"(d[21]),"+f"(d[22]),"+f"(d[23]),"+f"(d[24]),"+f"(d[25]),"+f"(d[26]),"+f"(d[27]),"+f"(d[28]),"+f"(d[29]),"+f"(d[30]),"+f"(d[31]),"+f"(d[32]),"+f"(d[33]),"+f"(d[34]),"+f"(d[35]),"+f"(d[36]),"+f"(d[37]),"+f"(d[38]),"+f"(d[39]),"+f"(d[40]),"+f"(d[41]),"+f"(d[42]),"+f"(d[43]),"+f"(d[44]),"+f"(d[45]),"+f"(d[46]),"+f"(d[47]),"+f"(d[48]),"+f"(d[49]),"+f"(d[50]),"+f"(d[51]),"+f"(d[52]),"+f"(d[53]),"+f"(d[54]),"+f"(d[55]),"+f"(d[56]),"+f"(d[57]),"+f"(d[58]),"+f"(d[59]),"+f"(d[60]),"+f"(d[61]),"+f"(d[62]),"+f"(d[63]),"+f"(d[64]),"+f"(d[65]),"+f"(d[66]),"+f"(d[67]),"+f"(d[68]),"+f"(d[69]),"+f"(d[70]),"+f"(d[71]),"+f"(d[72]),"+f"(d[73]),"+f"(d[74]),"+f"(d[75]),"+f"(d[76]),"+f"(d[77]),"+f"(d[78]),"+f"(d[79]),"+f"(d[80]),"+f"(d[81]),"+f"(d[82]),"+f"(d[83]),"+f"(d[84]),"+f"(d[85]),"+f"(d[86]),"+f"(d[87]),"+f"(d[88]),"+f"(d[89]),"+f"(d[90]),"+f"(d[91]),"+f"(d[92]),"+f"(d[93]),"+f"(d[94]),"+f"(d[95])
   : "l"(da), "l"(db), "r"(sd));
}

template <bool TR>
__device__ __forceinline__ void gemm_section(float* acc, float& mean0, float& mean1, float& rstd0, float& rstd1,
                                             uint32_t sb, int blk, int hg, int wg, int w, int lane) {
  constexpr int layer = TR ? 1 : 0;
  constexpr int TURN = TR ? TURN1 : TURN0;
  constexpr int LSTAT = TURN < 4 ? TURN - 1 : 3;
  const uint32_t bar = sb + SM_BAR;
  const int g = lane >> 2, t = lane & 3;
  const bool leader = (w == 0) && (lane == 0);
  const int statpos = hg < 3 ? 1 : wg ? LSTAT : TR ? 3 : 2;
  const bool copy = hg >= 3 && wg == 0;
  const int cut = wg ? TURN : 4;
  auto wait_full = [&](int c) {
    mbar_wait(bar + 8 * (B_XF + 8 * wg + c), layer);
    mbar_wait(bar + 8 * (B_WF + c), layer);
  };
  auto peek = [&](int c) {
    const bool x = mbar_test(bar + 8 * (B_XF + 8 * wg + c), layer), y = mbar_test(bar + 8 * (B_WF + c), layer);
    return x && y;
  };
  const uint64_t da0 = mkdesc(sb, TR ? 8192 : 16, 1024, 1), db0 = mkdesc(sb, 8192, 1024, 1);
  uint32_t xt = wg ? 0xfedcba98u : 0x21043210u;
  uint64_t wt = 0x0816131005161310ull;
  uint64_t da = da0 + ((xt & 15) << 9), db = db0 + (16 << 9);
  auto issue = [&](int c, int first) {
    wg_fence();
#pragma unroll
    for (int ks = 0; ks < 4; ks++) wgmma_ss<192, TR ? 1 : 0, 1>(acc, da + (TR ? ks * 128 : ks * 2), db + ks * 128, !first || ks != 0);
    wg_commit();
    xt >>= 4; wt >>= 8;
    da = da0 + ((xt & 15) << 9); db = db0 + (((uint32_t)wt & 31) << 9);
  };
  wait_full(0);
  bool ready = peek(1);
  issue(0, 1);
  TSW(0);
#pragma unroll 1
  for (int c = 1; c < cut; c++) {
    if (!ready) wait_full(c);
    issue(c, 0);
    ready = peek(c + 1);
    wg_wait<1>();
    if (leader) mbar_arrive(bar + 8 * (B_DN + 8 * wg + c - 1));
    if (wg == 1 && c == cut - 1) {
      wg_wait<0>();
      if (leader) mbar_arrive(bar + 8 * (B_DN + 8 + c));
    }
    if (c == statpos) {
      mbar_wait(bar + 8 * (copy ? B_SC : B_XF + 8 * wg + hg), layer);
      uint32_t A[16];
      const uint32_t xb = sb + (copy ? P_R : 8 * wg + hg) * PG;
#pragma unroll
      for (int ks = 0; ks < 4; ks++) {
        if (!TR) {
          const int row = 16 * w + (lane & 15), kc = 2 * ks + (lane >> 4);
          ldsm4(&A[4 * ks], xb + row * 128 + ((kc ^ (row & 7)) << 4));
        } else {
          const int k = 16 * ks + (lane & 7) + 8 * (lane >> 4), pc = 2 * w + ((lane >> 3) & 1);
          ldsm4t(&A[4 * ks], xb + k * 128 + ((pc ^ (k & 7)) << 4));
        }
      }
      float s0 = 0.f, q0 = 0.f, s1 = 0.f, q1 = 0.f;
#pragma unroll
      for (int i = 0; i < 16; i += 2) {
        const float a = bf_lo(A[i]), b = bf_hi(A[i]), c_ = bf_lo(A[i + 1]), d = bf_hi(A[i + 1]);
        s0 += a + b; q0 = fmaf(a, a, q0); q0 = fmaf(b, b, q0);
        s1 += c_ + d; q1 = fmaf(c_, c_, q1); q1 = fmaf(d, d, q1);
      }
#pragma unroll
      for (int o = 1; o <= 2; o <<= 1) {
        s0 += __shfl_xor_sync(~0u, s0, o); q0 += __shfl_xor_sync(~0u, q0, o);
        s1 += __shfl_xor_sync(~0u, s1, o); q1 += __shfl_xor_sync(~0u, q1, o);
      }
      if (t < 2)
        asm volatile("red.relaxed.gpu.global.add.v4.f32 [%0], {%1,%2,%3,%4};" ::"l"(g_rows + layer * LSEQ + blk * 64 + 16 * w + g + 8 * t),
                     "f"(t ? s1 : s0), "f"(t ? q1 : q0), "f"(1.f), "f"(0.f) : "memory");
    }
  }
  if (wg == 1) {
#pragma unroll 1
    for (int c = cut; c < 8; c++) wait_full(c);
    ready = true;
    bar_sync(5, 256);
  }
#pragma unroll 1
  for (int c = cut; c < 8; c++) {
    if (!ready) wait_full(c);
    issue(c, 0);
    if (wg == 1) {
      wg_wait<2>();
      if (leader && c >= cut + 2) mbar_arrive(bar + 8 * (B_DN + 8 + c - 2));
    } else if (c == 7) {
      bar_arrive(5, 256);
    } else {
      ready = peek(c + 1);
      wg_wait<1>();
      if (leader && c < 6) mbar_arrive(bar + 8 * (B_DN + c - 1));
    }
  }
  mbar_wait(bar + 8 * (B_LN + wg), layer);
  const float4 ln = lds128f(sb + ln_off(wg) + (8 * w + g) * 16);
  mean0 = ln.x; rstd0 = ln.y; mean1 = ln.z; rstd1 = ln.w;
  wg_wait<0>();
  acc_fence<96>(acc);
  if (leader) mbar_arrive(bar + 8 * (B_DN + 8 * wg + 7));
}

__device__ __forceinline__ void attn_phase(const Params& p, uint32_t sb, int layer, int rb, int hg, int wg, int w) {
  const int lane = opaque_tid() & 31;
  const int g = lane >> 2, t = lane & 3;
  const uint32_t bar = sb + SM_BAR;
  const int blk = 16 * wg + rb;
  float acc[96];
  float2 cs[24];
  float mean0, mean1, rstd0, rstd1;
  if (layer) gemm_section<true>(acc, mean0, mean1, rstd0, rstd1, sb, blk, hg, wg, w, lane);
  else gemm_section<false>(acc, mean0, mean1, rstd0, rstd1, sb, blk, hg, wg, w, lane);
  TSW(1);
#pragma unroll
  for (int j = 8; j < 24; j++) cs[j] = lds64f(sb + SM_CS + 4 * (8 * j + 2 * t));
  const uint32_t kvx = sb + (wg ? 22 : 0) * PG;

  const uint32_t ka = kvx + (16 * w + (lane & 7) + 8 * (lane >> 4)) * 272 + (lane & 8) * 2;
  const uint32_t va = kvx + (16 * w + (lane & 15)) * 272 + (lane & 16) + 32;
  uint4* halo = &g_halo[(blk * 8 + hg) * 256 + lane];
  uint32_t kb[4][8], vb[4][8], qa[4][4];
  {
    const float nm0 = -mean0 * rstd0, nm1 = -mean1 * rstd1;
    const bool sender = (w == 3 && blk < 31);
    uint32_t r[4][2][4];
#pragma unroll
    for (int h = 0; h < 4; h++) {
#pragma unroll
      for (int kv = 0; kv < 2; kv++) {
#pragma unroll
        for (int dh = 0; dh < 2; dh++) {
          const int j = 8 + kv * 8 + 2 * h + dh;
          const float2 c2 = cs[j];
          const float v0 = fmaf(acc[4 * j + 0], rstd0, nm0 * c2.x), v1 = fmaf(acc[4 * j + 1], rstd0, nm0 * c2.y);
          const float v2 = fmaf(acc[4 * j + 2], rstd1, nm1 * c2.x), v3 = fmaf(acc[4 * j + 3], rstd1, nm1 * c2.y);
          r[h][kv][2 * dh] = packbf(v0, v1);
          r[h][kv][2 * dh + 1] = packbf(v2, v3);
        }
      }
      if (sender) {
        stg128(halo + (2 * h) * 32, make_uint4(r[h][0][0], r[h][0][2], r[h][0][1], r[h][0][3]));
        stg128(halo + (2 * h + 1) * 32, make_uint4(r[h][1][0], r[h][1][1], r[h][1][2], r[h][1][3]));
      }
    }
#pragma unroll
    for (int j = 0; j < 8; j++) cs[j] = lds64f(sb + SM_CS + 4 * (8 * j + 2 * t));
    mbar_wait(bar + 8 * (B_DN + 7), layer);
#pragma unroll
    for (int h = 0; h < 4; h++) {
      if (w < 3) {
        stsm4(ka + 64 * h, r[h][0][0], r[h][0][2], r[h][0][1], r[h][0][3]);
        stsm4(va + 64 * h, r[h][1][0], r[h][1][1], r[h][1][2], r[h][1][3]);
      }
      kb[h][4] = r[h][0][0]; kb[h][5] = r[h][0][2]; kb[h][6] = r[h][0][1]; kb[h][7] = r[h][0][3];
      vb[h][4] = movm_t(r[h][1][0]); vb[h][5] = movm_t(r[h][1][1]); vb[h][6] = movm_t(r[h][1][2]); vb[h][7] = movm_t(r[h][1][3]);
    }
#pragma unroll
    for (int h = 0; h < 4; h++) {
#pragma unroll
      for (int dh = 0; dh < 2; dh++) {
        const int j = 2 * h + dh;
        const float2 c2 = cs[j];
        qa[h][2 * dh] = packbf(fmaf(-mean0, c2.x, acc[4 * j + 0]), fmaf(-mean0, c2.y, acc[4 * j + 1]));
        qa[h][2 * dh + 1] = packbf(fmaf(-mean1, c2.x, acc[4 * j + 2]), fmaf(-mean1, c2.y, acc[4 * j + 3]));
      }
    }
  }
  uint4* op = (uint4*)g_O + ((layer * 32 + blk) * 8 + hg) * 512 + 64 * t + 16 * w + g;
  unsigned* ocnt = &g_cnt[(C_O + layer * 32 + blk) * 32];
  pin(op); pin(ocnt);
  const int e = t - (g >> 1);
  const bool par = g & 1, epos = e >= 1;
  uint32_t selA = par ? 0x1044u : 0x4410u, selB0 = epos ? (par ? 0x3244u : 0x4432u) : 0x4444u, selB1 = epos ? 0x4444u : (par ? 0x3244u : 0x4432u);
  const float cl2 = 0.25f * 1.4426950408889634f;
  const float sc0 = rstd0 * cl2, sc1 = rstd1 * cl2;
  float c0[4];
#pragma unroll
  for (int k = 0; k < 4; k++) asm volatile("mov.b32 %0, %1;" : "=f"(c0[k]) : "f"((blk == 0 && w == 0) ? -INFINITY : 0.f));
  const uint32_t zero = (uint32_t)opaque_tid() & 0x80000000u;
  pin(selA); pin(selB0); pin(selB1);
  bar_sync(2 + wg, 128);
  TSW(2);
  {
    if (w != 0) {
#pragma unroll
      for (int h = 0; h < 4; h++) {
        ldsm4(&kb[h][0], ka - 16 * 272 + 64 * h);
        ldsm4t(&vb[h][0], va - 16 * 272 + 64 * h);
      }
    } else if (blk > 0) {
      uint4* src = halo - 8 * 256;
      uint4 hv[8];
      int it = 0;
      bool ok;
      do {
        ok = true;
#pragma unroll
        for (int i = 0; i < 8; i++) hv[i] = ld_tagged(src + i * 32);
#pragma unroll
        for (int i = 0; i < 8; i++) ok = ok && hv[i].x != UNSET;
      } while (!__all_sync(~0u, ok) && ++it < (1 << 20));
      if (layer == 0) {
#pragma unroll
        for (int i = 0; i < 2; i++) stg128(src + i * 128 + (lane >> 1) * 6, make_uint4(UNSET, UNSET, UNSET, UNSET));
      }
#pragma unroll
      for (int h = 0; h < 4; h++) {
        kb[h][0] = hv[2 * h].x; kb[h][1] = hv[2 * h].y; kb[h][2] = hv[2 * h].z; kb[h][3] = hv[2 * h].w;
        vb[h][0] = movm_t(hv[2 * h + 1].x); vb[h][1] = movm_t(hv[2 * h + 1].y);
        vb[h][2] = movm_t(hv[2 * h + 1].z); vb[h][3] = movm_t(hv[2 * h + 1].w);
      }
    } else {
#pragma unroll
      for (int h = 0; h < 4; h++)
#pragma unroll
        for (int k = 0; k < 4; k++) kb[h][k] = vb[h][k] = 0u;
    }
    TSW(3);
  }
  mbar_wait(bar + 8 * (B_DN + 15), layer);
  TSW(4);

  float vA0[4], vB0[4], vA1[4], vB1[4];
#pragma unroll
  for (int h = 0; h < 4; h++) {
    float S[4][4];
#pragma unroll
    for (int j = 0; j < 4; j++) {
      S[j][0] = S[j][1] = S[j][2] = S[j][3] = 0.f;
      if (j < 2) mma_bf16_c(S[j], qa[h], kb[h][2 * j], kb[h][2 * j + 1], c0);
      else mma_bf16(S[j], qa[h], kb[h][2 * j], kb[h][2 * j + 1]);
    }
    vA0[h] = par ? S[1][1] : S[1][0];
    vB0[h] = epos ? (par ? S[0][1] : S[0][0]) : (par ? S[2][1] : S[2][0]);
    vA1[h] = par ? S[2][3] : S[2][2];
    vB1[h] = epos ? (par ? S[1][3] : S[1][2]) : (par ? S[3][3] : S[3][2]);
  }
  float m0[4], m1[4];
#pragma unroll
  for (int h = 0; h < 4; h++) { m0[h] = fmaxf(vA0[h], vB0[h]); m1[h] = fmaxf(vA1[h], vB1[h]); }
#pragma unroll
  for (int o = 1; o <= 2; o <<= 1) {
#pragma unroll
    for (int h = 0; h < 4; h++) {
      m0[h] = fmaxf(m0[h], __shfl_xor_sync(~0u, m0[h], o));
      m1[h] = fmaxf(m1[h], __shfl_xor_sync(~0u, m1[h], o));
    }
  }
  float O0[4][4], O1[4][4], Z[4][4];
#pragma unroll
  for (int h = 0; h < 4; h++) {
    const float mm0 = -m0[h] * sc0, mm1 = -m1[h] * sc1;
    const float pA0 = ex2(fmaf(vA0[h], sc0, mm0)), pB0 = ex2(fmaf(vB0[h], sc0, mm0));
    const float pA1 = ex2(fmaf(vA1[h], sc1, mm1)), pB1 = ex2(fmaf(vB1[h], sc1, mm1));
    const uint32_t h0 = packbf(pA0, pB0), h1 = packbf(pA1, pB1);
    const uint32_t P0[4] = {prmt0(h0, selB0), h0 & zero, prmt0(h0, selA), prmt0(h1, selB0)};
    const uint32_t P1[4] = {prmt0(h0, selB1), prmt0(h1, selA), h1 & zero, prmt0(h1, selB1)};
#pragma unroll
    for (int k = 0; k < 4; k++) O0[h][k] = O1[h][k] = 0.f;
    mma_rowsum(Z[h], h0, h1);
    mma_bf16(O0[h], P0, vb[h][0], vb[h][1]); mma_bf16(O1[h], P0, vb[h][2], vb[h][3]);
    mma_bf16(O0[h], P1, vb[h][4], vb[h][5]); mma_bf16(O1[h], P1, vb[h][6], vb[h][7]);
  }
  if (lane == 0) mbar_arrive(bar + 8 * (B_OST + wg));
#pragma unroll
  for (int h = 0; h < 4; h += 2) {
    const float i0 = rcp_approx(Z[h][0]), i1 = rcp_approx(Z[h][2]), j0 = rcp_approx(Z[h + 1][0]), j1 = rcp_approx(Z[h + 1][2]);
    stg128(op + 128 * h, make_uint4(packbf(O0[h][0] * i0, O0[h][1] * i0), packbf(O1[h][0] * i0, O1[h][1] * i0),
                                   packbf(O0[h + 1][0] * j0, O0[h + 1][1] * j0), packbf(O1[h + 1][0] * j0, O1[h + 1][1] * j0)));
    stg128(op + 128 * h + 8, make_uint4(packbf(O0[h][2] * i1, O0[h][3] * i1), packbf(O1[h][2] * i1, O1[h][3] * i1),
                                            packbf(O0[h + 1][2] * j1, O0[h + 1][3] * j1), packbf(O1[h + 1][2] * j1, O1[h + 1][3] * j1)));
  }
  TSW(5);
  __syncwarp();
  if (elect_one()) red_relaxed(ocnt);
  TSW(6);
}

__device__ __forceinline__ void conv_load(uint32_t* A, uint32_t pe);
__device__ __forceinline__ void proj_phase(const Params& p, uint32_t sb, int layer, int rb, int q, uint32_t* A0, uint32_t* A1) {
  const int lane = opaque_tid() & 31;
  const int wg = __shfl_sync(~0u, opaque_tid() >> 7, 0), w = __shfl_sync(~0u, (opaque_tid() >> 5) & 3, 0);
  const bool TR = layer != 0;
  const int t = lane & 3;
  const uint32_t bar = sb + SM_BAR;
  const uint32_t rbx = sb + (P_R + wg) * PG;
  const uint32_t rsrc = sb + (wg ? 2 : P_R) * PG;
  const int blk = 16 * wg + rb;
  mbar_wait(bar + 8 * (B_RF + wg), layer);
  mbar_wait(bar + 8 * B_WOF, layer);
  const uint32_t stg = sb + (wg ? SM_KGT : SM_STG);
  if (layer) {
    const uint32_t pe = sb + cv_pe(wg, 1) + 4 * (16 + 16 * w + (lane >> 2) - 2 * t);
    mbar_wait(bar + 8 * B_PE, 1);
    conv_load(A0, pe);
    conv_load(A1, pe + 2 * 4480);
    __syncwarp();
    if (lane == 0) mbar_arrive(bar + 8 * B_AL);
  } else {
#pragma unroll
    for (int i = 0; i < 68; i++) {
      asm volatile("mov.b32 %0, 0;" : "=r"(A0[i]));
      asm volatile("mov.b32 %0, 0;" : "=r"(A1[i]));
    }
  }
  bool clean = false, staged = false;
#pragma unroll 1
  for (int attempt = 0; attempt < MAX_RETRY; attempt++) {
  uint32_t res[16];
  if (!TR) {
#pragma unroll
    for (int j = 0; j < 8; j += 2) {
      const int mi = lane >> 3;
      const int row = 16 * w + (lane & 7) + 8 * (mi & 1), ch = j + (mi >> 1);
      ldsm4(&res[2 * j], rsrc + row * 128 + ((ch ^ (row & 7)) << 4));
    }
  } else {
#pragma unroll
    for (int j = 0; j < 8; j += 2) {
      const int mi = lane >> 3;
      const int line = 8 * (j + (mi >> 1)) + (lane & 7), pc = 2 * w + (mi & 1);
      ldsm4t(&res[2 * j], rsrc + line * 128 + ((pc ^ (line & 7)) << 4));
    }
  }
  float acc[32];
#pragma unroll
  for (int j = 0; j < 16; j++) { acc[2 * j] = bf_lo(res[j]); acc[2 * j + 1] = bf_hi(res[j]); }
  acc_fence<32>(acc);
  if (wg) mbar_wait(bar + 8 * B_PG, layer);
  const int wg2 = __shfl_sync(~0u, opaque_tid() >> 7, 0);
  const uint64_t da0 = mkdesc(sb, 1024, 128, 0), db0 = mkdesc(sb, 8192, 1024, 1);
#pragma unroll
  for (int c = 0; c < 4; c++) {
    mbar_wait(bar + 8 * (B_OF + 4 * wg + c), layer);
    if (c == 0) TSW(7);
    const uint64_t da = da0 + (uint32_t)(o_page(wg2, c) * 512);
#pragma unroll
    for (int ks = 0; ks < 8; ks++) {
      if (ks % 4 == 0) { if (ks) wg_commit(); if (wg2) wg_wait<0>(); wg_fence(); }
      wgmma_ss<64, 0, 1>(acc, da + ks * 128, db0 + wo_page(2 * c + (ks >> 2)) * 512 + (ks & 3) * 128, 1);
    }
    wg_commit();
  }
  if (wg) mbar_wait(bar + 8 * B_KG, 0);
  wg_wait<0>();
  acc_fence<32>(acc);
  TSW(8);
  if (!clean) {
    const float chk = acc[0] + acc[2];
    clean = __all_sync(~0u, chk == chk);
    if (clean && lane == 0) mbar_arrive(bar + 8 * (B_PDONE + wg));
  }
  float s0 = 0.f, q0 = 0.f, s1 = 0.f, q1 = 0.f;
  uint32_t o[16];
#pragma unroll
  for (int j = 0; j < 8; j++) {
    const float a = acc[4 * j], b = acc[4 * j + 1], c = acc[4 * j + 2], d = acc[4 * j + 3];
    o[2 * j] = packbf(a, b);
    o[2 * j + 1] = packbf(c, d);
    s0 += a + b; q0 = fmaf(a, a, q0); q0 = fmaf(b, b, q0);
    s1 += c + d; q1 = fmaf(c, c, q1); q1 = fmaf(d, d, q1);
  }
#pragma unroll
  for (int j = 0; j < 8; j += 2) {
    const int mi = lane >> 3;
    const int line = 8 * (j + (mi >> 1)) + (lane & 7), pc = 2 * w + (mi & 1);
    stsm4t(rbx + line * 128 + ((pc ^ (line & 7)) << 4), o[2 * j], o[2 * j + 1], o[2 * j + 2], o[2 * j + 3]);
  }
#pragma unroll
  for (int o2 = 1; o2 <= 2; o2 <<= 1) {
    s0 += __shfl_xor_sync(~0u, s0, o2); q0 += __shfl_xor_sync(~0u, q0, o2);
    s1 += __shfl_xor_sync(~0u, s1, o2); q1 += __shfl_xor_sync(~0u, q1, o2);
  }
  {
    const int i = 2 * (lane >> 2) + (t & 1), k = (i * 11) >> 5;
    const float v = (t == 0) ? s0 : (t == 1) ? q0 : (t == 2) ? s1 : q1;
    sts32f(stg + k * 128 + (2 * w + (t >> 1)) * 16 + (i - 3 * k) * 4, v);
  }
  TSW(9);
  fence_async_smem();
  if (attempt == 0 && clean) {
    staged = true;
    __syncwarp();
    if (lane == 0) mbar_arrive(bar + 8 * (B_STG + wg));
  }
  if (!bar_or(2 + wg, 128, !clean)) break;
  const int rtp = mbar_test(bar + 8 * (B_RT + wg), 0);
  bool unset = false;
#pragma unroll
  for (int i = 0; i < 4; i++) unset |= lds32(sb + o_page(wg, i) * PG + (32 * w + lane) * 128) == UNSET;
  if (!bar_or(2 + wg, 128, unset)) break;
  if (w == 0 && elect_one()) {
    fence_async_smem();
    mbar_expect(bar + 8 * (B_RT + wg), 9 * PG);
    if (layer == 0) tma_ld(rsrc, &p.mapX, q * 64, blk * 64, bar + 8 * (B_RT + wg));
    else tma_ld(rsrc, &p.mapXT, blk * 64, DM + q * 64, bar + 8 * (B_RT + wg));
#pragma unroll 1
    for (int c = 0; c < 4; c++) bulk_ld(sb + o_page(wg, c) * PG, g_O + ((layer * 32 + blk) * 4 + c) * PG, 2 * PG, bar + 8 * (B_RT + wg));
  }
  mbar_wait(bar + 8 * (B_RT + wg), rtp);
  RETRY(0);
  }
  if (!clean && lane == 0) mbar_arrive(bar + 8 * (B_PDONE + wg));
  if (!staged && lane == 0) mbar_arrive(bar + 8 * (B_STG + wg));
  TSW(10);
}

__device__ __forceinline__ void conv_load(uint32_t* A, uint32_t pe) {
#pragma unroll
  for (int m = 0; m < 17; m++) {
    A[4 * m + 2] = lds32(pe + 4 * (64 * m - 8));
    A[4 * m + 0] = lds32(pe + 4 * (64 * m));
    A[4 * m + 1] = lds32(pe + 4 * (64 * m + 8));
    asm volatile("mov.b32 %0, %1;" : "=r"(A[4 * m + 3]) : "r"(A[4 * m + 0]));
  }
}
template <int M> __device__ __forceinline__ void conv_tri(float* acc, const uint32_t* A, uint64_t d) {
  if constexpr (M < 16) {
    wgmma_rs<64 - 8 * (M / 2), 0>(acc, A + 4 * M, d + (uint64_t)(64 + 4 * M), M != 0);
    conv_tri<M + 1>(acc, A, d);
  }
}
__device__ __forceinline__ void conv_mma0(float* acc, const uint32_t* A, uint64_t d) {
  wg_fence();
  conv_tri<0>(acc, A, d);
  wg_commit();
}
__device__ __forceinline__ void conv_mma1(float* acc, const uint32_t* A, uint64_t d, uint64_t ds, uint64_t df) {
  wg_fence();
#pragma unroll
  for (int m = 0; m < 17; m++) wgmma_rs<64, 0>(acc, A + 4 * m, d + (uint64_t)(4 * m), m != 0);
  wgmma_ss<64, 1, 0>(acc, ds, df, 1);
  wgmma_ss<64, 1, 0>(acc, ds + 128, df + 128, 1);
  wg_commit();
}
__device__ __forceinline__ void conv_store(float* acc, uint32_t pb, uint32_t over, int w) {
  acc_fence<32>(acc);
  const int l = opaque_tid() & 31, mt = l >> 3;
  int c = 2 * (63 - 8 * (mt >> 1) - (l & 7) + w) + (mt & 1);
  c ^= (c >> 3) & 1;
  const uint32_t a0 = pb + c * 16;
#pragma unroll
  for (int j = 0; j < 8; j += 2)
    stsm4t(j == 0 ? (c < 128 ? a0 : over + (c - 128) * 16) : a0 - 256 * j, packbf(acc[4 * j], acc[4 * j + 1]), packbf(acc[4 * j + 2], acc[4 * j + 3]),
           packbf(acc[4 * j + 4], acc[4 * j + 5]), packbf(acc[4 * j + 6], acc[4 * j + 7]));
}
__device__ __forceinline__ void conv_sums(uint32_t sb, int lc, int ht) {
  const int m = ht - 1;
  uint4 v[2][3];
#pragma unroll
  for (int c = 0; c < 2; c++)
#pragma unroll
    for (int k = 0; k < 3; k++) {
      const int mm = m - 1 + k;
      v[c][k] = lds128(sb + cv_u(lc + c) + (mm >= 0 ? (mm & 1) * CV_UH + (127 - (mm >> 1)) * 16 : 128 * 16));
    }
  const int ce = m + 2, co = m + 1;
#pragma unroll
  for (int c = 0; c < 2; c++) {
    const uint32_t x[8] = {v[c][0].z, v[c][0].w, v[c][1].x, v[c][1].y, v[c][1].z, v[c][1].w, v[c][2].x, v[c][2].y};
    float pv[16];
#pragma unroll
    for (int k = 0; k < 8; k++) { pv[2 * k] = bf_lo(x[k]); pv[2 * k + 1] = bf_hi(x[k]); }
    float t2[15], t4[13], s9[8], s7[8];
#pragma unroll
    for (int i = 0; i < 15; i++) t2[i] = pv[i] + pv[i + 1];
#pragma unroll
    for (int i = 0; i < 13; i++) t4[i] = t2[i] + t2[i + 2];
#pragma unroll
    for (int i = 0; i < 8; i++) {
      s9[i] = (t4[i] + t4[i + 4]) + pv[i + 8];
      s7[i] = (t4[i + 1] + t2[i + 5]) + pv[i + 7];
    }
    const uint4 e4 = make_uint4(packbf(s9[0], s9[1]), packbf(s9[2], s9[3]), packbf(s9[4], s9[5]), packbf(s9[6], s9[7]));
    if (ce < 128) sts128(sb + cv_se(lc + c) + ((ce ^ ((ce >> 3) & 7)) << 4), e4);
    else sts128(sb + cv_se(lc + c), make_uint4(0, 0, 0, 0));
    sts128(sb + cv_so(lc + c) + ((co ^ ((co >> 3) & 7)) << 4),
           make_uint4(packbf(s7[0], s7[1]), packbf(s7[2], s7[3]), packbf(s7[4], s7[5]), packbf(s7[6], s7[7])));
  }
}

template <int HALF, int NCH, int STEP = 1>
__device__ __forceinline__ void conv_epi(uint32_t sb, bf16* out, int lc, int c) {
  uint4 v[NCH][4], xr[NCH];
  const uint32_t sw = (c ^ ((c >> 3) & 1)) * 16;
#pragma unroll
  for (int u = 0; u < NCH; u++) {
#pragma unroll
    for (int k = 0; k < 4; k++) v[u][k] = lds128(sb + (HALF ? cv_pb1(lc + STEP * u, k) : cv_pb0(lc + STEP * u, k)) + sw);
    xr[u] = lds128(sb + cv_x(HALF, lc + STEP * u) + c * 16);
  }
#pragma unroll
  for (int u = 0; u < NCH; u++) {
    uint4 o;
    o.x = hadd2(xr[u].x, hadd2(hadd2(v[u][0].x, v[u][1].x), hadd2(v[u][2].x, v[u][3].x)));
    o.y = hadd2(xr[u].y, hadd2(hadd2(v[u][0].y, v[u][1].y), hadd2(v[u][2].y, v[u][3].y)));
    o.z = hadd2(xr[u].z, hadd2(hadd2(v[u][0].z, v[u][1].z), hadd2(v[u][2].z, v[u][3].z)));
    o.w = hadd2(xr[u].w, hadd2(hadd2(v[u][0].w, v[u][1].w), hadd2(v[u][2].w, v[u][3].w)));
    stg128(out + cv_chan(0, lc + STEP * u) * LSEQ + HALF * 1024 + c * 8, o);
  }
}

__device__ __forceinline__ bool prep_valid(const uint4 (&st)[6], const uint4 (&xr)[4]) {
  const uint32_t n = st[0].w & st[1].w & st[2].w & st[3].w & st[4].w & (st[5].w | st[5].y | st[5].z);
  return (n == __float_as_uint(8.f)) & (max(max(xr[0].x, xr[1].x), max(xr[2].x, xr[3].x)) != UNSET);
}
template <int HALF>
__device__ __forceinline__ void conv_prep(uint32_t sb, int layer, int cta, int i) {
  uint4 st[6], xr[4];
  const uint4* sp = (const uint4*)g_stats + (layer * 32 + HALF * 16 + (i >> 3)) * 48 + (i & 7);
  const uint4* xp = (const uint4*)g_xT + (2 * layer * DM + 2 * cta) * (LSEQ / 8) + HALF * 128 + i;
  if (!HALF) { pin(sp); pin(xp); }
  mbar_wait(sb + SM_BAR + 8 * (B_GB + HALF), layer);
  if (!HALF) TSW(13);
  auto fetch = [&]() {
#pragma unroll
    for (int k = 0; k < 6; k++) st[k] = ld_tagged(sp + 8 * k);
#pragma unroll
    for (int k = 0; k < 4; k++) xr[k] = ld_tagged(xp + cv_chan(0, k) * (LSEQ / 8));
  };
  if (HALF) {
#pragma unroll
    for (int k = 0; k < 6; k++) st[k] = lds128(sb + CV_ST + (i >> 3) * 768 + k * 128 + (i & 7) * 16);
#pragma unroll
    for (int k = 0; k < 4; k++) xr[k] = lds128(sb + cv_x(1, k) + i * 16);
  } else {
    fetch();
  }
  int it = 0;
  while (!__all_sync(~0u, prep_valid(st, xr)) && ++it < MAX_RETRY) { fetch(); RETRY(1); }
  if (!HALF || it) {
#pragma unroll
    for (int k = 0; k < 4; k++) sts128(sb + cv_x(HALF, k) + i * 16, xr[k]);
  }
  const uint32_t v[16] = {st[0].x, st[0].y, st[0].z, st[1].x, st[1].y, st[1].z, st[2].x, st[2].y, st[2].z, st[3].x, st[3].y, st[3].z, st[4].x, st[4].y, st[4].z, st[5].x};
  uint32_t rs[4], nm[4];
#pragma unroll
  for (int k = 0; k < 4; k++) {
    constexpr float E2 = 1e-5f * DM * DM;
    const float s0 = __uint_as_float(v[4 * k]), s1 = __uint_as_float(v[4 * k + 2]);
    const float r0 = rsqrt_approx(fmaxf(fmaf(__uint_as_float(v[4 * k + 1]), (float)DM, fmaf(-s0, s0, E2)), E2));
    const float r1 = rsqrt_approx(fmaxf(fmaf(__uint_as_float(v[4 * k + 3]), (float)DM, fmaf(-s1, s1, E2)), E2));
    const uint32_t r = packbf(r0, r1);
    rs[k] = r + 0x04800480u;
    nm[k] = packbf(-s0 * bf_lo(r), -s1 * bf_hi(r));
  }
  const uint32_t ud = sb + (i & 1) * CV_UH + (127 - 64 * HALF - (i >> 1)) * 16;
#pragma unroll
  for (int k = 0; k < 4; k++)
    sts128(ud + cv_u(k), make_uint4(hfma2(xr[k].x, rs[0], nm[0]), hfma2(xr[k].y, rs[1], nm[1]), hfma2(xr[k].z, rs[2], nm[2]), hfma2(xr[k].w, rs[3], nm[3])));
  fence_async_smem();
}

__device__ __forceinline__ void conv_phase(const Params& p, uint32_t sb, int layer, int cta, uint32_t* A0, uint32_t* A1) {
  const int tid = opaque_tid();
  const int wg = __shfl_sync(~0u, tid >> 7, 0), w = __shfl_sync(~0u, (tid >> 5) & 3, 0);
  const uint32_t bar = sb + SM_BAR;
  constexpr int CH2 = 4 * PG;
  bf16* xout = g_xT + ((2 * layer + 1) * DM + 2 * cta) * LSEQ;
  float acc[32];
  const uint32_t pe = sb + cv_pe(wg, 0) + 4 * (16 + 16 * w + ((tid & 31) >> 2) - 2 * (tid & 3));
  if (layer == 0) {
    mbar_wait(bar + 8 * (B_PDONE + 1), layer);
    mbar_wait(bar + 8 * B_PE, layer);
    conv_load(A0, pe);
    conv_load(A1, pe + CH2);
  }
  TSW(19);
  const uint64_t d0 = mkdesc(sb + cv_u(wg), CV_UH, 128, 0), d1 = d0 + (CH2 >> 4);
  mbar_wait(bar + 8 * B_U, layer);
  TSW(12);
  if (wg == 1) bar_sync(5, 256);
  conv_mma0(acc, A0, d0);
  if (wg == 0) bar_arrive(5, 256);
  mbar_wait(bar + 8 * (B_PDONE + 1), layer);
  {
    const int l = opaque_tid() & 31;
    if ((l & 15) < 2 * w) sts128(sb + cv_pb0(wg + 2 * (l >> 4), w) + (l & 15) * 16, make_uint4(0, 0, 0, 0));
  }
  wg_wait<0>();
  conv_store(acc, sb + cv_pb0(wg, w), sb + cv_pb1(wg, w), w);
  conv_mma0(acc, A1, d1);
  wg_wait<0>();
  conv_store(acc, sb + cv_pb0(2 + wg, w), sb + cv_pb1(2 + wg, w), w);
  TSW(13);
  bar_sync(2 + wg, 128);
  conv_epi<0, 2, 2>(sb, xout, wg, opaque_tid() & 127);
  TSW(14);
  mbar_arrive(bar + 8 * B_PUB);
  const uint64_t ds = mkdesc(sb + cv_se(wg), 8192, 1024, 1), df = mkdesc(sb + cv_fa(wg), 512, 128, 0);
  if (wg == 0) mbar_wait(bar + 8 * B_U1, layer);
  else bar_sync(6, 256);
  TSW(15);
  conv_mma1(acc, A0, d0, ds, df);
  if (wg == 0) bar_arrive(6, 256);
  wg_wait<0>();
  conv_store(acc, sb + cv_pb1(wg, w), sb + cv_dump(wg), w);
  TSW(16);
  bar_sync(2 + wg, 128);
  conv_epi<1, 1>(sb, xout, wg, opaque_tid() & 127);
  mbar_arrive(bar + 8 * (B_PUB + 1));
  conv_mma1(acc, A1, d1, ds + 512, df + (CH2 >> 4));
  wg_wait<0>();
  conv_store(acc, sb + cv_pb1(2 + wg, w), sb + cv_dump(2 + wg), w);
  TSW(17);
  bar_sync(2 + wg, 128);
  conv_epi<1, 1>(sb, xout, 2 + wg, opaque_tid() & 127);
  mbar_arrive(bar + 8 * (B_PUB + 2));
  TSW(18);
}

#define FDELAY 480
__device__ __forceinline__ void final_tile(const Params& p, uint32_t buf, int ch0, int pos0, int barid, uint32_t hint) {
  const uint32_t t0 = (uint32_t)clock();
  const int tid = opaque_tid() & 127, lane = tid & 31, w = tid >> 5;
  const uint4* src = (const uint4*)(g_xT + (3 * DM + ch0 + (tid >> 3)) * LSEQ + pos0) + (tid & 7);
  const int ch = tid >> 3, row = 4 * (ch & 6) + 2 * (ch >> 3) + (ch & 1);
  uint32_t dst0 = buf + row * 128 + (((tid ^ row) & 7) << 4), dst1 = (dst0 ^ 64) + 512;
  uint32_t ld0 = buf + lane * 128 + ((((2 * w) ^ lane) & 7) << 4), ld1 = ld0 ^ 16;
  bf16* out = p.out + (pos0 + 16 * w + (lane >> 2)) * DM + ch0 + 8 * (lane & 3);
  pin(src); pin(out); pin(dst0); pin(dst1); pin(ld0); pin(ld1);
  if (hint) mbar_wait(hint, 0);
  else while ((uint32_t)clock() - t0 < FDELAY);
  uint4 a, b;
  int it = 0;
  do {
    if (it) RETRY(2);
    a = ld_tagged(src); b = ld_tagged(src + 16 * LSEQ / 8);
  } while (!__all_sync(~0u, a.x != UNSET && b.x != UNSET) && ++it < (1 << 20));
  sts128(dst0, a);
  sts128(dst1, b);
  bar_sync(barid, 128);
#pragma unroll
  for (int h = 0; h < 2; h++) {
    uint32_t r[4];
    ldsm4t(r, h ? ld1 : ld0);
    *(uint4*)(out + 8 * h * DM) = make_uint4(r[0], r[1], r[2], r[3]);
  }
}

struct cplx { float r, i; };
__device__ __forceinline__ cplx cmul(cplx a, cplx b) { return {fmaf(a.r, b.r, -a.i * b.i), fmaf(a.r, b.i, a.i * b.r)}; }
__device__ __forceinline__ cplx csqr(cplx a) { return {fmaf(a.r, a.r, -a.i * a.i), (a.r + a.r) * a.i}; }
__device__ __forceinline__ cplx cexp_l(float ar2, float ai, float l) {
  const float m = ex2(ar2 * l);
  const float x = ai * l;
  return {m * __cosf(x), m * __sinf(x)};
}

__device__ __forceinline__ void colsum_cta(const Params& p, uint32_t sb, int j, int tid) {
  const uint32_t bar = sb + SM_BAR;
  auto ld = [&](int i) {
    mbar_expect(bar + 8 * i, 3 * PG);
    tma_ld3(sb + (i & 7) * 3 * PG, &p.mapW3, (2 * j + (i & 1)) * 64, (i >> 1) * 64, 0, bar + 8 * i);
  };
  const int warp = __shfl_sync(~0u, tid >> 5, 0);
  if (warp == 12 && elect_one()) {
#pragma unroll
    for (int i = 0; i < 8; i++) mbar_init(bar + 8 * i, 1);
    asm volatile("fence.mbarrier_init.release.cluster;" ::: "memory");
    fence_async_smem();
#pragma unroll
    for (int i = 0; i < 8; i++) ld(i);
  }
  if (warp == 13 && elect_one()) {
#pragma unroll
    for (int i = 8; i < 24; i++) mbar_init(bar + 8 * i, i < 16 ? 1 : 12);
    asm volatile("fence.mbarrier_init.release.cluster;" ::: "memory");
  }
  const unsigned ep = ld_relaxed(&g_cnt[C_CS * 32]);
  bar_sync(0, NTHREADS);
  if (warp == 12 && elect_one()) {
#pragma unroll 1
    for (int i = 8; i < 16; i++) { mbar_wait(bar + 8 * (8 + i), 0); fence_async_smem(); ld(i); }
  }
  if (tid < 384) {
    const int lane = tid & 31, cc = tid & 7, r0 = (tid >> 3) & 15, part = tid >> 7;
    const uint32_t id = ((lane >> 2) == 2 * (lane & 3) ? 0x3f80u : 0u) | ((lane >> 2) == 2 * (lane & 3) + 1 ? 0x3f800000u : 0u);
    const uint32_t src = sb + part * PG + r0 * 128 + ((cc ^ (r0 & 7)) << 4);
    float s[2][2][4];
#pragma unroll
    for (int i = 0; i < 16; i++) s[i >> 3][(i >> 2) & 1][i & 3] = 0.f;
#pragma unroll 1
    for (int i2 = 0; i2 < 16; i2 += 2) {
#pragma unroll
      for (int h = 0; h < 2; h++) {
        const int i = i2 + h;
        mbar_wait(bar + 8 * i, 0);
        uint4 v[4];
#pragma unroll
        for (int k = 0; k < 4; k++) v[k] = lds128(src + (i & 7) * 3 * PG + k * 2048);
#pragma unroll
        for (int k = 0; k < 4; k++) {
          const uint32_t a[4] = {v[k].x, v[k].y, v[k].z, v[k].w};
          mma_bf16(s[h][0], a, id, 0u);
          mma_bf16(s[h][1], a, 0u, id);
        }
        __syncwarp();
        if (i < 8 && lane == 0) mbar_arrive(bar + 8 * (16 + i));
      }
    }
    const uint32_t red = sb + 24 * PG;
#pragma unroll
    for (int h = 0; h < 2; h++)
#pragma unroll
      for (int k = 0; k < 2; k++) sts128f(red + (r0 * 384 + h * 192 + part * 64 + cc * 8 + k * 4) * 4, s[h][k][0], s[h][k][1], s[h][k][2], s[h][k][3]);
    bar_sync(1, 384);
    float tot = 0.f;
#pragma unroll
    for (int k = 0; k < 16; k++) tot += __uint_as_float(lds32(red + (k * 384 + tid) * 4));
    asm volatile("st.relaxed.gpu.global.v2.u32 [%0], {%1,%2};" ::"l"(&g_colsum[j * 384 + tid]), "r"(__float_as_uint(tot)), "r"(ep / NCTA + 1) : "memory");
    const uint4 u = make_uint4(UNSET, UNSET, UNSET, UNSET);
    if (tid < 256) {
#pragma unroll 1
      for (int s = 0; s < 4; s++) {
        const int n = (s == 1 || s == 2) ? 32 : 16;
        uint4* buf = s == 1 ? (uint4*)g_O + 131072 : (uint4*)g_xT + (s + !s) * 131072;
#pragma unroll 4
        for (int i = 0; i < n; i++) stg128(buf + (j * n + i) * 1024 + (tid >> 1) * 8 + (tid & 1), u);
        if (n == 16) {
#pragma unroll 4
          for (int i = 0; i < 8; i++) stg128(buf + (256 + j * 64 + i * 8 + (tid >> 5)) * 256 + (s ? 0 : 128) + ((tid & 31) >> 1) * 8 + (tid & 1), u);
        }
        if (s == 3) {
#pragma unroll 4
          for (int i = 0; i < 32; i++) stg128(buf + (256 + j * 64 + 2 * i + (tid >> 7)) * 256 + 128 + (tid & 127), u);
        }
        bar_sync(2, 256);
        if (tid == 32 * s) red_release(&g_cnt[(C_R + s) * 32]);
      }
    }
  }
}

constexpr int KB = 4, KW = 2;
struct ModeIn { uint32_t ar, ai, br, bi, cr, ci; bf16 logdt; };
__device__ __forceinline__ ModeIn load_modes(const Params& p, int d, int m) {
  const int i = d * 64 + m;
  return {((const uint32_t*)p.a_re)[i], ((const uint32_t*)p.a_im)[i], ((const uint32_t*)p.b_re)[i], ((const uint32_t*)p.b_im)[i],
          ((const uint32_t*)p.c_re)[i], ((const uint32_t*)p.c_im)[i], p.log_dt[d]};
}
__device__ __forceinline__ void kernel_gen(uint32_t sb, int cta, int ht, ModeIn in, const ModeIn& in1) {
  const uint32_t bst = sb + SM_KGB + ((ht & 63) >> 2) * 144 + (ht & 3) * 4 + (ht >> 6) * 16;
  const uint64_t db = mkdesc(sb + SM_KGB, 144, 2304, 0);
  const float e0 = (float)(8 * (((ht & 32) >> 1) + ((ht & 31) >> 2)));
  float T[20];
#pragma unroll
  for (int i = 0; i < 20; i++) T[i] = 0.f;
  float k0 = 0.f;
#pragma unroll 1
  for (int pass = 0; pass < 4; pass++) {
    {
      const int sh = (pass & 1) ? 0 : 16;
      auto val = [&](uint32_t v) { return __uint_as_float((v << sh) & 0xffff0000u); };
      const float dt = __bfloat162float(__float2bfloat16_rn(expf(__bfloat162float(in.logdt))));
      const float ar2 = dt * val(in.ar) * 1.4426950408889634f, ai = dt * val(in.ai);
      const cplx c = cmul({val(in.cr), -val(in.ci)}, {dt * val(in.br), -dt * val(in.bi)});
      k0 += c.r;
      const cplx z1 = cexp_l(ar2, -ai, 1.f), z256 = cexp_l(ar2, -ai, 256.f), z64 = cexp_l(ar2, ai, 64.f);
      const cplx z2 = csqr(z1), z512 = csqr(z256);
      auto put = [&](int j, cplx v) { sts32(bst + (j >> 2) * 2304 + (j & 3) * 32, packbf(v.r, v.i)); };
      sts128f(sb + SM_KGT + ht * 16, ar2, ai, z64.r, z64.i);
      const cplx c1 = cmul(c, z1), c2 = cmul(c, z2), c3 = cmul(c1, z2), c4 = cmul(c2, z2);
      const cplx c5 = cmul(c3, z2), c6 = cmul(c4, z2), c7 = cmul(c5, z2), c8 = cmul(c6, z2);
      put(0, c1); put(1, c2); put(2, c3); put(3, c4); put(4, c5); put(5, c6); put(6, c7); put(7, c8);
      const cplx c260 = cmul(c4, z256), c264 = cmul(c8, z256), c520 = cmul(c8, z512), c776 = cmul(c264, z512);
      put(8, cmul(c2, z256)); put(9, c260); put(10, cmul(c6, z256)); put(11, c264);
      put(12, cmul(c4, z512)); put(13, c520); put(14, cmul(c260, z512)); put(15, c776);
      const cplx c1032 = cmul(c520, z512), c1288 = cmul(c776, z512);
      put(16, c1032); put(17, c1288); put(18, cmul(c1032, z512)); put(19, cmul(c1288, z512));
    }
    fence_async_smem();
    bar_sync(4, 128);
    const uint32_t tb = sb + SM_KGT + (ht & 67) * 16;
    float2 nx[KB];
#pragma unroll
    for (int s = 0; s < KB; s++) nx[s] = lds64f(tb + s * 64);
#pragma unroll
    for (int q = 0; q < 16 / KB; q++) {
      uint32_t A[2 * KB];
      float2 cur[KB], z[KB];
#pragma unroll
      for (int s = 0; s < KB; s++) { cur[s] = nx[s]; z[s] = lds64f(tb + (KB * q + s) * 64 + 8); }
      if (q < 16 / KB - 1) {
#pragma unroll
        for (int s = 0; s < KB; s++) nx[s] = lds64f(tb + (KB * q + KB + s) * 64);
      }
      if (q >= KW) wg_wait<KW - 1>();
#pragma unroll
      for (int s = 0; s < KB; s++) {
        const cplx lo = cexp_l(cur[s].x, cur[s].y, e0), hi = cmul(lo, {z[s].x, z[s].y});
        A[2 * s] = packbf(lo.r, lo.i);
        A[2 * s + 1] = packbf(hi.r, hi.i);
      }
      wg_fence();
#pragma unroll
      for (int k = 0; k < KB / 2; k++) wgmma_rs<40, 0>(T, A + 4 * k, db + 9 * KB * q + 18 * k, (pass & 1) | q | k);
      wg_commit();
    }
    wg_wait<0>();
    acc_fence<20>(T);
    if (ht == 0) TS(4 + pass);
    if (pass & 1) {
      const int h2 = opaque_tid() - 256, w = h2 >> 5, lane = h2 & 31, t = lane & 3, chn = h2 >> 6, m = h2 & 63, i0 = 16 * (w & 1) + (lane >> 2);
      const int lc = (pass & 2) + chn;
      const uint32_t kc = sb + kc_off(lc);
      auto put = [&](int idx, float v) {
        sts16(kc + idx * 2, __bfloat16_as_ushort(__float2bfloat16_rn(v)));
      };
#pragma unroll
      for (int hi = 0; hi < 2; hi++) {
        const int i = i0 + 8 * hi;
        float v[5];
#pragma unroll
        for (int j = 0; j < 5; j++) v[j] = chn ? T[4 * j + 2 * hi + 1] : T[4 * j + 2 * hi];
        put(8 * i + 1 + t, v[0]);
        put(8 * i + 5 + t, v[1]);
        put(257 + 4 * i + t, v[2]);
        put(385 + 2 * i + (t & 1) + 64 * (t >> 1), v[3]);
        put(513 + i + 32 * t, v[4]);
      }
#pragma unroll
      for (int o = 16; o > 0; o >>= 1) k0 += __shfl_xor_sync(~0u, k0, o);
      if (lane == 0) sts32f(sb + SM_RED + 4 * w, k0);
      bar_sync(4, 128);
      if (m == 0) put(0, k0 + __uint_as_float(lds32(sb + SM_RED + 4 * w + 4)) + __uint_as_float(lds16(sb + SM_RED + 24 + 2 * lc) << 16));
      k0 = 0.f;
      in = in1;
    }
  }
}

__device__ __forceinline__ void expand_taps(uint32_t sb, int ht, int early) {
  const int ch = ht >> 5, lane = ht & 31;
  const uint32_t kc = sb + kc_off(ch);
  const uint32_t dst0 = sb + cv_pe(ch, early);
  auto put = [&](int G, uint32_t v0, uint32_t v1, uint32_t v2, uint32_t v3, uint32_t v4, uint32_t v5, uint32_t v6, uint32_t v7, uint32_t v8) {
    const uint32_t dst = dst0 + G * 32;
    sts128(dst, make_uint4(v1 | (v0 << 16), v2 | (v1 << 16), v3 | (v2 << 16), v4 | (v3 << 16)));
    sts128(dst + 16, make_uint4(v5 | (v4 << 16), v6 | (v5 << 16), v7 | (v6 << 16), v8 | (v7 << 16)));
  };
  {
    const uint4 q = lds128(kc + lane * 16);
    const uint32_t pv = lane ? lds16(kc + lane * 16 - 2) : 0u;
    const uint32_t dst = dst0 + (lane + 2) * 32;
    sts128(dst, make_uint4(__byte_perm(q.x, pv, 0x5410), __byte_perm(q.x, q.x, 0x1032), __byte_perm(q.y, q.x, 0x7610), __byte_perm(q.y, q.y, 0x1032)));
    sts128(dst + 16, make_uint4(__byte_perm(q.z, q.y, 0x7610), __byte_perm(q.z, q.z, 0x1032), __byte_perm(q.w, q.z, 0x7610), __byte_perm(q.w, q.w, 0x1032)));
    if (lane < 4) sts128(dst0 + lane * 16, make_uint4(0, 0, 0, 0));
  }
  uint32_t a[5], b[2][3];
  {
    const uint32_t s1 = kc + 2 * (256 + 4 * lane);
#pragma unroll
    for (int k = 0; k < 5; k++) a[k] = lds16(s1 + 2 * k);
#pragma unroll
    for (int u = 0; u < 2; u++) {
      const uint32_t s2 = kc + 2 * (384 + 2 * (lane + 32 * u));
#pragma unroll
      for (int k = 0; k < 3; k++) b[u][k] = lds16(s2 + 2 * k);
    }
  }
  const uint32_t k255 = lds16(kc + 2 * 255), k1024 = lds16(kc + 2 * 512);
  put(34 + lane, lane == 0 ? k255 : a[0], a[0], a[0], a[1], a[2], a[2], a[2], a[3], a[4]);
#pragma unroll
  for (int u = 0; u < 2; u++) put(66 + lane + 32 * u, b[u][0], b[u][0], b[u][0], b[u][0], b[u][1], b[u][1], b[u][1], b[u][2], b[u][2]);
  if (lane < 10) {
    const uint32_t v = lane == 0 ? k1024 : 0u;
    put(130 + lane, v, v, v, v, v, v, 0u, 0u, 0u);
  }
}
__device__ __forceinline__ void expand_far(uint32_t sb, int ht) {
  const int ch = ht >> 5, lane = ht & 31;
  const uint32_t kc = sb + kc_off(ch) + 2 * (513 + 2 * (63 - lane)), dst = sb + cv_fa(ch) + lane * 16;
#pragma unroll
  for (int ty = 0; ty < 2; ty++) {
    uint32_t v[16];
#pragma unroll
    for (int k = 0; k < 16; k++) v[k] = (k < 8 || 63 - lane - 4 * k >= 0) ? lds16(kc + 2 * (1 - ty) - 16 * k) : 0u;
#pragma unroll
    for (int u = 0; u < 2; u++)
      sts128(dst + ty * 2048 + u * 512, make_uint4(v[8 * u] | (v[8 * u + 1] << 16), v[8 * u + 2] | (v[8 * u + 3] << 16), v[8 * u + 4] | (v[8 * u + 5] << 16), v[8 * u + 6] | (v[8 * u + 7] << 16)));
    sts128(dst + ty * 2048 + 1024, make_uint4(0, 0, 0, 0));
  }
}

__host__ __device__ constexpr int bar_count(int i) {
  return i == B_LN ? 2 : i == B_AL ? 8 : i < B_STG ? 1 : i < B_PE ? 4 : i >= B_PUB ? 256 : 128;
}
__host__ __device__ constexpr bool bar_first(int i) { return i < B_WF + 2 && (i & 7) < 2; }

__global__ void __launch_bounds__(NTHREADS, 1) fused_kernel(const __grid_constant__ Params p) {
  extern __shared__ __align__(1024) uint8_t smem[];
  constexpr uint32_t sb = 1024;
  if (s32(smem) != sb) return;
  const int tid = threadIdx.x, lane = tid & 31;
  const int warp = __shfl_sync(~0u, tid >> 5, 0);
  if (tid == 32) {
    asm volatile("prefetch.tensormap [%0];" ::"l"(&p.mapX) : "memory");
    asm volatile("prefetch.tensormap [%0];" ::"l"(&p.mapW3) : "memory");
  }
  const int cta = blockIdx.x - (gridDim.x == NCTA + 4 ? 0 : 4);
  if ((unsigned)cta >= NCTA) {
    if (blockIdx.x < NCTA + 4) colsum_cta(p, sb, blockIdx.x & 3, tid);
    return;
  }
  const int rb = ((cta >> 4) & 3) * 4 + ((cta >> 2) & 3), hg = (cta >> 6) * 4 + (cta & 3);
  const uint32_t bar = sb + SM_BAR;
  auto ld_x0 = [&](int half, int c) {
    const uint32_t b = bar + 8 * (B_XF + 8 * half + c);
    mbar_expect(b, PG);
    tma_ld(sb + x_page(half, c) * PG, &p.mapX, c * 64, (16 * half + rb) * 64, b);
  };
  auto ld_x1 = [&](int half, int c, int b0) {
    const uint32_t b = bar + 8 * b0;
    mbar_expect(b, PG);
    tma_ld(sb + (8 * half + c) * PG, &p.mapXT, (16 * half + rb) * 64, DM + c * 64, b);
  };
  auto ld_w = [&](int c) {
    const uint32_t b = bar + 8 * (B_WF + c);
    mbar_expect(b, 3 * PG);
    tma_ld3(sb + w_page(c) * PG, &p.mapW3, hg * 64, c * 64, 0, b);
  };

  if (tid == 0) TS(0);
  if (tid == 480) LTS(0);
  if (warp == 0 && elect_one()) {
#pragma unroll
    for (int i = 0; i < B_WF + 2; i++)
      if (bar_first(i)) mbar_init(bar + 8 * i, 1);
    asm volatile("fence.mbarrier_init.release.cluster;" ::: "memory");
    fence_async_smem();
    ld_x0(0, 0);
    ld_w(0); ld_x0(1, 0);
    ld_x0(0, 1); ld_w(1); ld_x0(1, 1);
    TS(1);
  }
  __syncwarp();
  if (warp >= 1 && warp < 8 && elect_one()) {
    if (warp < 4) {
#pragma unroll
      for (int i = 2; i < 8; i++) mbar_init(bar + 8 * (8 * warp - 8 + i), 1);
    } else {
#pragma unroll
      for (int i = 0; i < 12; i++) mbar_init(bar + 8 * (12 * warp - 24 + i), 1);
    }
    asm volatile("fence.mbarrier_init.release.cluster;" ::: "memory");
  }
  if (warp == 15 && elect_one()) {
#pragma unroll
    for (int i = 72; i < B_COUNT; i++) mbar_init(bar + 8 * i, bar_count(i));
    asm volatile("fence.mbarrier_init.release.cluster;" ::: "memory");
  }

  if (warp < 8) {
    bar_sync(0, NTHREADS);
    asm volatile("setmaxnreg.inc.sync.aligned.u32 %0;" ::"n"(R_CONS));
    const int cw = __shfl_sync(~0u, opaque_tid() >> 5, 0);
    const int wg = cw >> 2, w = cw & 3;
    if (tid == 0) TS(2);
#pragma unroll 1
    for (int layer = 0; layer < 2; layer++) {
      attn_phase(p, sb, layer, rb, hg, wg, w);
      uint32_t A0[68], A1[68];
      proj_phase(p, sb, layer, rb, hg, A0, A1);
      conv_phase(p, sb, layer, cta, A0, A1);
    }
    if (tid == 128) TS(8);
    final_tile(p, sb + (16 + wg) * PG, 256 * wg + 32 * (cta >> 4), 1024 + 64 * (cta & 15), 2 + wg, wg ? 0 : bar + 8 * (B_TF + 1));
    if (tid == 128) TS(9);
    if (tid == 128) LTS(1);
    if (tid == 0) LTE();
  } else if (warp < 12) {
    asm volatile("setmaxnreg.dec.sync.aligned.u32 %0;" ::"n"(R_HELP));
    const int ht = tid - 256;
    {
      unsigned ep0 = 0;
      if (ht == 0) ep0 = ld_relaxed(&g_cnt[C_CS * 32]);
      const bf16 dsk = p.dskip[cv_chan(cta, ht & 3)];
      const ModeIn in0 = load_modes(p, cv_chan(cta, ht >> 6), ht & 63), in1 = load_modes(p, cv_chan(cta, 2 + (ht >> 6)), ht & 63);
      if (ht < 48) sts128f(sb + SM_STG + ht * 16, 0.f, 0.f, 0.f, 1.f);
      bar_sync(0, NTHREADS);
      if (ht == 0) {
        sts32(sb + SM_EP, ep0);
        mbar_arrive(bar + 8 * B_EP);
      }
      if (ht >= 124) sts16(sb + SM_RED + 24 + 2 * (ht & 3), __bfloat16_as_ushort(dsk));
      kernel_gen(sb, cta, ht, in0, in1);
      if (ht < 48) sts128f(sb + SM_KGT + ht * 16, 0.f, 0.f, 0.f, 1.f);
      fence_async_smem();
      bar_sync(4, 128);
      if (ht == 0) mbar_arrive(bar + 8 * B_KG);
    }
#pragma unroll 1
    for (int layer = 0; layer < 2; layer++) {
      const int early = layer;
      if (early) mbar_wait(bar + 8 * (B_DN + 13), 1);
      mbar_wait(bar + 8 * (early ? B_OST : B_PDONE), layer);
      expand_taps(sb, opaque_tid() - 256, early);
      mbar_arrive(bar + 8 * B_PE);
      TSW(0);
      mbar_wait(bar + 8 * B_PDONE, layer);
      expand_far(sb, opaque_tid() - 256);
      {
        const int i = opaque_tid() - 256;
        if (i < 32) sts128(sb + cv_u(i >> 3) + ((i >> 2) & 1) * CV_UH + (128 + (i & 3)) * 16, make_uint4(0, 0, 0, 0));
        mbar_wait(bar + 8 * B_RC, layer);
        conv_prep<0>(sb, layer, cta, i);
        mbar_arrive(bar + 8 * B_U);
      }
      mbar_wait(bar + 8 * (B_PDONE + 1), layer);
      bar_sync(4, 128);
#pragma unroll 1
      for (int lc = 0; lc < 4; lc += 2) {
        conv_sums(sb, lc, opaque_tid() - 256);
        TSW(1 + lc);
      }
      conv_prep<1>(sb, layer, cta, opaque_tid() - 256);
      mbar_arrive(bar + 8 * B_U1);
      TSW(4);
      if (layer == 0) {
        const int c = __shfl_sync(~0u, (opaque_tid() >> 5) & 3, 0);
        int phase = 0;
#pragma unroll 1
        for (int k = 0; k < 3; k++) {
          const int page = (k ? 4 + 4 * k : 0) + c, b = B_XR + 4 * (k & 1) + c;
          const uint32_t a = sb + page * PG + lane * 128 + (lane & 7) * 16 + (lane >> 3) * 4;
          int it = k == 2 ? phase : 0;
#pragma unroll 1
          for (; it < MAX_RETRY; it++) {
            mbar_wait(bar + 8 * b, it & 1);
            const uint32_t v0 = lds32(a), v1 = lds32(a + 4096);
            if (__all_sync(~0u, v0 != UNSET && v1 != UNSET)) break;
            if (elect_one()) { fence_async_smem(); ld_x1(page >> 3, page & 7, b); }
            __syncwarp();
            RETRY(3);
          }
          if (k == 0) phase = it + 1;
          if (lane == 0) mbar_arrive(bar + 8 * (B_XF + page));
        }
      }
    }
#pragma unroll 1
    for (int k = 0; k < 2; k++) final_tile(p, sb + 18 * PG + k * 4096, 256 * k + 32 * (cta >> 4), 64 * (cta & 15), 4, bar + 8 * B_TF);
    if (ht == 0) LTE();
  } else {
    asm volatile("setmaxnreg.dec.sync.aligned.u32 %0;" ::"n"(R_AGENT));
    bar_sync(0, NTHREADS);
    auto done = [&](int half, int c, int layer) { mbar_wait(bar + 8 * (B_DN + 8 * half + c), layer); };
    auto publish = [&](int layer, int k) {
      unsigned* cnt = &g_cnt[(layer ? C_F + 8 * k + (cta >> 4) : C_C + k) * 32];
      pin(cnt);
      mbar_wait(bar + 8 * (B_PUB + k), layer);
      red_relaxed(cnt);
      if (!layer && k == 0) red_release(&g_cnt[(C_C + 3) * 32]);
      TS(16 + layer * 56 + 40 + 7 + k);
    };
    if (warp == 12) {
      if (elect_one()) {
#pragma unroll 1
        for (int layer = 0; layer < 2; layer++) {
          auto ld_xe = [&](int c) {
            const uint32_t b = bar + 8 * (B_XF + c);
            mbar_expect(b, PG);
            if (layer == 0) tma_ld(sb + x_page(0, c) * PG, &p.mapX, c * 64, rb * 64, b);
            else tma_ld(sb + x_page(0, c) * PG, &p.mapXT, rb * 64, DM + c * 64, b);
          };
          if (layer == 0) {
            ld_x0(0, 2); ld_w(2); ld_x0(1, 2);
            if (hg >= 3) {
              mbar_expect(bar + 8 * B_SC, PG);
              tma_ld(sb + P_R * PG, &p.mapX, hg * 64, rb * 64, bar + 8 * B_SC);
            }
            if (rb < 4) tma_prefetch3(&p.mapW3, hg * 64, (4 + rb) * 64, 0);
            ld_x0(0, 3); ld_w(3); ld_x0(1, 3); ld_x0(0, 4); ld_x0(1, 4);
            done(0, 0, 0); done(1, 0, 0);
            ld_w(4);
            ld_x0(1, 5); ld_x0(1, 6); ld_x0(1, 7);
            done(0, 1, 0); done(1, 1, 0);
            ld_w(5);
            if (rb < 8) tma_prefetch5(&p.mapWo, hg * 64, rb * 2);
            done(0, 2, 0);
            fence_async_smem();
            ld_xe(5); ld_xe(6); ld_xe(7);
          } else {
            mbar_wait(bar + 8 * B_PDONE, 0);
            mbar_wait(bar + 8 * (B_PDONE + 1), 0);
            mbar_wait(bar + 8 * B_U, 0);
            ld_w(0); ld_w(1);
            mbar_wait(bar + 8 * B_U1, 0);
            fence_async_smem();
            ld_w(2);
            mbar_wait(bar + 8 * (B_PUB + 2), 0);
            fence_async_smem();
            ld_w(3);
            spin_until(&g_cnt[(C_C + 3) * 32], ((lds32(sb + SM_EP) / NCTA) + 1) * NCTA);
            fence_async_global();
            if (hg >= 3) {
              mbar_expect(bar + 8 * B_SC, PG);
              tma_ld(sb + P_R * PG, &p.mapXT, rb * 64, DM + hg * 64, bar + 8 * B_SC);
            }
            ld_xe(4);
            done(0, 2, 1);
            fence_async_smem();
            ld_xe(5); ld_xe(6); ld_xe(7);
            done(1, 0, 1);
            ld_w(4);
            done(1, 1, 1);
            ld_w(5);
          }
          done(1, 2, layer);
          fence_async_smem();
          ld_w(6); ld_w(7);
          auto ld_res = [&](int half) {
            const uint32_t b = bar + 8 * (B_RF + half);
            mbar_expect(b, PG);
            if (layer == 0) tma_ld(sb + (half ? 2 : P_R) * PG, &p.mapX, hg * 64, (16 * half + rb) * 64, b);
            else tma_ld(sb + (half ? 2 : P_R) * PG, &p.mapXT, (16 * half + rb) * 64, DM + hg * 64, b);
          };
          done(0, 4, layer); done(1, 3, layer);
          fence_async_smem();
          mbar_expect(bar + 8 * B_WOF, 8 * PG);
#pragma unroll 1
          for (int c = 0; c < 8; c++) {
            if (c == 5) { ld_res(0); done(1, 4, layer); }
            tma_ld5(sb + wo_page(c) * PG, &p.mapWo, hg * 64, c * 2, bar + 8 * B_WOF);
          }
          done(0, 7, layer);
          fence_async_global();
          ld_res(1);
          if (layer) mbar_wait(bar + 8 * B_RS, 0);
          fence_async_global();
#pragma unroll
          for (int half = 0; half < 2; half++) {
            float* stats = g_stats + (layer * 32 + 16 * half + rb) * 192;
            unsigned* cnt = &g_cnt[(C_G + 2 * layer + half) * 32];
            mbar_wait(bar + 8 * (B_STG + half), layer);
            tma_st(&p.mapXT, (16 * half + rb) * 64, 2 * layer * DM + hg * 64, sb + (P_R + half) * PG);
            bulk_red_add_f32(stats, sb + (half ? SM_KGT : SM_STG), 768);
            bulk_commit();
            red_relaxed(cnt);
            if (half == 0) mbar_arrive(bar + 8 * B_PG);
            bulk_wait_read();
            mbar_arrive(bar + 8 * (B_PST + half));
          }
        }
      }
    } else if (warp == 13) {
      mbar_wait(bar + 8 * B_EP, 0);
      const unsigned e1 = (lds32(sb + SM_EP) / NCTA) + 1;
      auto ld_o = [&](int layer) {
#pragma unroll 1
        for (int half = 0; half < 2; half++) {
          done(1, 7, layer);
          mbar_wait(bar + 8 * B_OST, layer);
          if (half) mbar_wait(bar + 8 * (B_OST + 1), layer);
          fence_async_smem();
#pragma unroll
          for (int c = 0; c < 4; c++) mbar_expect(bar + 8 * (B_OF + 4 * half + c), 2 * PG);
          const bf16* src = g_O + (layer * 32 + 16 * half + rb) * 4 * PG;
          uint32_t dst0 = sb + o_page(half, 0) * PG;
          pin(src); pin(dst0);
          spin_hint(&g_cnt[(C_O + layer * 32 + 16 * half + rb) * 32], e1 * 32);
#pragma unroll
          for (int c = 0; c < 4; c++) {
            if (c == 2 && half && layer) { mbar_wait(bar + 8 * B_AL, 0); fence_async_smem(); }
            bulk_ld(c ? sb + o_page(half, c) * PG : dst0, src + c * PG, 2 * PG, bar + 8 * (B_OF + 4 * half + c));
          }
        }
      };
      if (elect_one()) {
        mbar_wait(bar + 8 * (B_WF + 2), 0);
        asm volatile("prefetch.tensormap [%0];" ::"l"(&p.mapXT) : "memory");
        asm volatile("prefetch.tensormap [%0];" ::"l"(&p.mapWo) : "memory");
        spin_until(&g_cnt[C_Z * 32], e1 * NCTA);
        mbar_arrive(bar + 8 * B_ZF);
        TS(3);
        ld_o(0);
#pragma unroll 1
        for (int k = 0; k < 3; k++) {
          mbar_wait(bar + 8 * (B_PUB + k), 0);
          if (k == 2) {
#pragma unroll 1
            for (int c = 0; c < 4; c++) mbar_wait(bar + 8 * (B_XF + c), 1);
          }
          fence_async_smem();
          uint32_t b = bar + 8 * (B_XR + 4 * (k & 1)), dst = sb + (k ? 4 + 4 * k : 0) * PG, c0 = ((k ? 16 : 0) + rb) * 64, c1 = DM + (k & 2) * 128;
#pragma unroll
          for (int c = 0; c < 4; c++) mbar_expect(b + 8 * c, PG);
          pin(b); pin(dst); pin(c0); pin(c1);
          spin_hint(&g_cnt[(C_C + k) * 32], e1 * NCTA);
          TS(10 + k);
#pragma unroll
          for (int c = 0; c < 4; c++) tma_ld(dst + c * PG, &p.mapXT, c0, c1 + c * 64, b + 8 * c);
        }
        ld_o(1);
#pragma unroll 1
        for (int k = 0; k < 2; k++) {
          mbar_wait(bar + 8 * (B_PUB + k), 1);
          spin_hint(&g_cnt[(C_F + 8 * k + (cta >> 4)) * 32], e1 * 16);
          mbar_arrive(bar + 8 * (B_TF + k));
        }
      }
    } else if (warp == 14) {
      mbar_wait(bar + 8 * B_EP, 0);
      const unsigned e1 = (lds32(sb + SM_EP) / NCTA) + 1;
      done(0, 4, 0);
      {
        const uint2* cp = g_colsum + (hg * 192 + lane);
        uint2 v[6];
        bool ok;
        int it = 0;
        do {
          ok = true;
#pragma unroll
          for (int i = 0; i < 6; i++) {
            asm volatile("ld.relaxed.gpu.global.v2.u32 {%0,%1}, [%2];" : "=r"(v[i].x), "=r"(v[i].y) : "l"(cp + 32 * i) : "memory");
            ok = ok && v[i].y == e1;
          }
          if (++it > (1 << 22)) __trap();
        } while (!__all_sync(~0u, ok));
#pragma unroll
        for (int i = 0; i < 6; i++) sts32f(sb + SM_CS + 4 * (lane + 32 * i), __uint_as_float(v[i].x));
      }
      __syncwarp();
      if (elect_one()) {
        mbar_wait(bar + 8 * B_ZF, 0);
        mbar_arrive(bar + 8 * B_LN);
        red_relaxed(&g_cnt[C_CS * 32]);
        TS(13);
#pragma unroll 1
        for (int layer = 0; layer < 2; layer++) {
          const uint32_t b = bar + 8 * (B_GB + 1);
          const bf16* xin = g_xT + ((size_t)2 * layer * DM + 2 * cta) * LSEQ + 1024;
          const float* stats = g_stats + (layer * 32 + 16) * 192;
          mbar_wait(bar + 8 * B_PST, layer);
          spin_hint(&g_cnt[(C_G + 2 * layer) * 32], e1 * NCTA);
          mbar_arrive(bar + 8 * B_GB);
          mbar_wait(bar + 8 * (B_PST + 1), layer);
          fence_async_smem();
          mbar_expect(b, 12288 + PG);
          pin(stats); pin(xin);
          spin_hint(&g_cnt[(C_G + 2 * layer + 1) * 32], e1 * NCTA);
          bulk_ld(sb + CV_ST, stats, 12288, b);
#pragma unroll
          for (int lc = 0; lc < 4; lc++) bulk_ld(sb + cv_x(1, lc), xin + cv_chan(0, lc) * LSEQ, 2048, b);
          TS(14 + layer);
          publish(layer, 1);
        }
      }
    } else {
      const uint4 u = make_uint4(UNSET, UNSET, UNSET, UNSET);
      if (lane < 24) stg128((uint4*)g_stats + cta * 24 + lane, make_uint4(0, 0, 0, 0));
      if (lane < 16) stg128(g_rows + LSEQ + cta * 16 + lane, make_uint4(0, 0, 0, 0));
#pragma unroll 4
      for (int i = 0; i < 16; i++) stg128(g_halo + cta * 512 + 32 * i + lane, u);
#pragma unroll 4
      for (int i = 0; i < 16; i++) stg128(((i & 8) ? (uint4*)g_xT : (uint4*)g_O) + cta * 1024 + (i & 7) * 128 + (lane >> 1) * 8 + (lane & 1), u);
      __syncwarp();
      if (elect_one()) red_release(&g_cnt[C_Z * 32]);
      __syncwarp();
#pragma unroll 1
      for (int layer = 0; layer < 2; layer++) {
        auto reset_done = [&](int s) {
          spin_until(&g_cnt[(C_R + s) * 32], (lds32(sb + SM_EP) / NCTA) * 4 + 4);
          mbar_arrive(bar + 8 * (s == 1 ? B_LN : s == 2 ? B_RS : B_RC));
          if (s) TS(16 + 40 + 9 + s);
        };
        if (layer && elect_one()) reset_done(1);
        __syncwarp();
#pragma unroll 1
        for (int half = 0; half < 2; half++) {
          done(half, 2, layer);
          const uint4* src = g_rows + (layer * LSEQ + (16 * half + rb) * 64 + (opaque_tid() & 31));
          uint4 a, b;
          int it = 0;
          do {
            a = ld_tagged(src); b = ld_tagged(src + 32);
          } while (!__all_sync(~0u, (a.z | a.w) == __float_as_uint(8.f) && (b.z | b.w) == __float_as_uint(8.f)) && ++it < (1 << 20));
          float m0 = __uint_as_float(a.x) * (1.f / DM), m1 = __uint_as_float(b.x) * (1.f / DM);
          float r0 = rsqrt_approx(fmaxf(__uint_as_float(a.y) * (1.f / DM) - m0 * m0, 0.f) + 1e-5f);
          float r1 = rsqrt_approx(fmaxf(__uint_as_float(b.y) * (1.f / DM) - m1 * m1, 0.f) + 1e-5f);
          if (half) done(0, 7, layer);
          const uint32_t dst = sb + ln_off(half) + ((lane >> 4) * 8 + (lane & 7)) * 16 + (lane & 8);
          asm volatile("st.shared.v2.f32 [%0], {%1,%2};" ::"r"(dst), "f"(m0), "f"(r0) : "memory");
          asm volatile("st.shared.v2.f32 [%0], {%1,%2};" ::"r"(dst + 256), "f"(m1), "f"(r1) : "memory");
          __syncwarp();
          if (elect_one()) { mbar_arrive(bar + 8 * (B_LN + half)); TS(16 + layer * 56 + 40 + 14 + half); }
        }
        if (layer && lane < 16) stg128(g_rows + cta * 16 + (opaque_tid() & 31), make_uint4(0, 0, 0, 0));
        if (elect_one()) {
          if (layer) reset_done(2);
          reset_done(3 * layer);
          publish(layer, 0);
          if (!layer) publish(layer, 2);
        }
        __syncwarp();
      }
    }
  }
}

typedef CUresult (*EncodeFn)(CUtensorMap*, CUtensorMapDataType, cuuint32_t, void*, const cuuint64_t*, const cuuint64_t*,
                             const cuuint32_t*, const cuuint32_t*, CUtensorMapInterleave, CUtensorMapSwizzle,
                             CUtensorMapL2promotion, CUtensorMapFloatOOBfill);

static void make_map(EncodeFn enc, CUtensorMap* m, void* ptr, uint64_t cols, uint64_t rows, uint32_t box_rows) {
  cuuint64_t dims[2] = {cols, rows};
  cuuint64_t strides[1] = {cols * 2};
  cuuint32_t box[2] = {64, box_rows};
  cuuint32_t es[2] = {1, 1};
  enc(m, CU_TENSOR_MAP_DATA_TYPE_BFLOAT16, 2, ptr, dims, strides, box, es, CU_TENSOR_MAP_INTERLEAVE_NONE,
      CU_TENSOR_MAP_SWIZZLE_128B, CU_TENSOR_MAP_L2_PROMOTION_L2_128B, CU_TENSOR_MAP_FLOAT_OOB_FILL_NONE);
}
static void make_map3(EncodeFn enc, CUtensorMap* m, void* ptr, uint64_t d0, uint64_t cols, uint64_t rows, uint64_t blk_stride,
                      uint64_t nblocks, uint32_t nblk) {
  cuuint64_t dims[3] = {d0, rows, nblocks};
  cuuint64_t strides[2] = {cols * 2, blk_stride * 2};
  cuuint32_t box[3] = {64, 64, nblk};
  cuuint32_t es[3] = {1, 1, 1};
  enc(m, CU_TENSOR_MAP_DATA_TYPE_BFLOAT16, 3, ptr, dims, strides, box, es, CU_TENSOR_MAP_INTERLEAVE_NONE,
      CU_TENSOR_MAP_SWIZZLE_128B, CU_TENSOR_MAP_L2_PROMOTION_L2_128B, CU_TENSOR_MAP_FLOAT_OOB_FILL_NONE);
}

extern "C" void kernel_launch(void* const* d_in, const int* in_sizes, int n_in, void* d_out, int out_size) {
  static Params prm;
  static void* cached[13] = {nullptr};
  static bool attr_done = false;
  static int grid = NCTA + 4;
  bool same = attr_done && cached[12] == d_out;
  for (int i = 0; i < 12 && same; i++) same = cached[i] == d_in[i];
  if (!same) {
    void* fn = nullptr;
    cudaDriverEntryPointQueryResult qr;
    cudaGetDriverEntryPoint("cuTensorMapEncodeTiled", &fn, cudaEnableDefault, &qr);
    EncodeFn enc = (EncodeFn)fn;
    void* pXT;
    cudaGetSymbolAddress(&pXT, g_xT);
    make_map(enc, &prm.mapX, d_in[0], DM, LSEQ, 64);
    make_map(enc, &prm.mapXT, pXT, LSEQ, 4 * DM, 64);
    {
      cuuint64_t dims[5] = {DM, 2, 4, 4, 16};
      cuuint64_t strides[4] = {DM * 2, 8 * DM * 2, 2 * DM * 2, 32 * DM * 2};
      cuuint32_t box[5] = {64, 2, 4, 4, 2};
      cuuint32_t es[5] = {1, 1, 1, 1, 1};
      enc(&prm.mapWo, CU_TENSOR_MAP_DATA_TYPE_BFLOAT16, 5, d_in[2], dims, strides, box, es, CU_TENSOR_MAP_INTERLEAVE_NONE,
          CU_TENSOR_MAP_SWIZZLE_128B, CU_TENSOR_MAP_L2_PROMOTION_L2_128B, CU_TENSOR_MAP_FLOAT_OOB_FILL_NONE);
    }
    make_map3(enc, &prm.mapW3, d_in[1], DM, 3 * DM, DM, DM, 3, 3);
    prm.out = (bf16*)d_out;
    prm.a_re = (const bf16*)d_in[4]; prm.a_im = (const bf16*)d_in[5];
    prm.b_re = (const bf16*)d_in[6]; prm.b_im = (const bf16*)d_in[7];
    prm.c_re = (const bf16*)d_in[8]; prm.c_im = (const bf16*)d_in[9];
    prm.log_dt = (const bf16*)d_in[10]; prm.dskip = (const bf16*)d_in[11];
    int dev = 0, sms = 0;
    cudaGetDevice(&dev);
    cudaDeviceGetAttribute(&sms, cudaDevAttrMultiProcessorCount, dev);
    grid = sms >= NCTA + 4 ? NCTA + 4 : NCTA + 5;
    cudaFuncSetAttribute(fused_kernel, cudaFuncAttributeMaxDynamicSharedMemorySize, SM_TOTAL);
    for (int i = 0; i < 12; i++) cached[i] = d_in[i];
    cached[12] = d_out;
    attr_done = true;
  }
  fused_kernel<<<grid, NTHREADS, SM_TOTAL>>>(prm);
}
```

```cpp
#include <cuda_runtime.h>
#include <cuda_bf16.h>
#include <cuda.h>
#include <stdint.h>

typedef __nv_bfloat16 bf16;

constexpr int LSEQ = 2048;
constexpr int DM = 512;
constexpr int NCTA = 128;
constexpr int NTHREADS = 512;
#define R_CONS 200
#define R_HELP 88
#define R_AGENT 24
#define TURN0 4
#define TURN1 4

constexpr int PG = 8192;
constexpr int P_R = 25;
__host__ __device__ constexpr int x_page(int half, int c) { return half ? 8 + c : c < 5 ? c : c - 5; }
__host__ __device__ constexpr int w_page(int c) { return (c & 3) < 3 ? 16 + 3 * (c & 3) : c < 4 ? 5 : 8; }
__host__ __device__ constexpr int wo_page(int c) { return c < 5 ? 3 + c : 11 + c; }
__host__ __device__ constexpr int o_page(int half, int pair) { return half ? (pair ? 25 - 2 * pair : 0) : 8 + 2 * pair; }
constexpr int SM_KGB = (P_R + 1) * PG;
constexpr int SM_KC = 27 * PG;
constexpr int KC_STRIDE = 648;
__host__ __device__ constexpr int kc_off(int lc) { return SM_KC + (lc & 1) * 2 * KC_STRIDE + (lc < 2 ? 3328 : 0); }
constexpr int SM_KGT = SM_KC + 3328 + 2592;
constexpr int SM_CS = SM_KGT + 2048;
constexpr int SM_RED = SM_CS + 768;
constexpr int SM_EP = SM_RED + 16;
constexpr int SM_STG = SM_RED + 32;
constexpr int SM_LN = SM_STG + 768;
__host__ __device__ constexpr int ln_off(int half) { return half ? PG + 5120 : SM_LN; }
constexpr int SM_BAR = SM_LN + 512;
constexpr int SM_TS = SM_BAR + 704;
constexpr int SM_TOTAL = SM_TS + 512;
static_assert(SM_TOTAL <= 232448 && SM_STG % 16 == 0 && SM_KGT % 16 == 0, "shared memory");

constexpr int CV_UH = 140 * 16;
__host__ __device__ constexpr int cv_u(int lc) { return (8 + 2 * lc) * PG; }
__host__ __device__ constexpr int cv_pe(int lc, int early) { return early ? 19 * PG + lc * 4480 : cv_u(lc) + 4480; }
__host__ __device__ constexpr int cv_pb1(int lc, int w) { return w ? cv_u(lc) + 8960 + (w - 1) * 2048 : 7 * PG + lc * 2048; }
__host__ __device__ constexpr int cv_fa(int lc) { return cv_pb1(lc, 1) + 128; }
__host__ __device__ constexpr int cv_dump(int lc) { return cv_u(lc) + 16256; }
__host__ __device__ constexpr int cv_pb0(int lc, int w) { return lc * PG + w * 2048; }
__host__ __device__ constexpr int cv_se(int lc) { return 5 * PG + lc * 4096; }
__host__ __device__ constexpr int cv_so(int lc) { return cv_se(lc) + 2048; }
__host__ __device__ constexpr int cv_x(int half, int lc) { return (P_R + half) * PG + lc * 2048; }
constexpr int CV_ST = 22 * PG;
__host__ __device__ constexpr int cv_chan(int cta, int lc) { return 2 * cta + (lc & 1) + 256 * (lc >> 1); }

enum {
  B_XF = 0,
  B_WF = 16,
  B_OF = 24,
  B_DN = 32,
  B_PG = 46,
  B_XR = 48,
  B_RF = 56,
  B_PST = 58,
  B_GB = 60,
  B_TF = 62,
  B_RT = 64,
  B_RS = 66,
  B_RC = 67,
  B_WOF = 68,
  B_ZF = 69,
  B_EP = 70,
  B_KG = 71,
  B_SC = 37,
  B_LN = 72,
  B_END = 38,
  B_STG = 74,
  B_OST = 76,
  B_PDONE = 78,
  B_PE = 80,
  B_U = 81,
  B_U1 = 82,
  B_PUB = 83,
  B_AL = 86,
  B_COUNT = 87
};

enum {
  C_CS = 0,
  C_G = 1,
  C_C = 5,
  C_O = 21,
  C_Z = 85,
  C_R = 86,
  C_F = 90,
  C_COUNT = 106
};

__device__ unsigned g_cnt[C_COUNT * 32];
__device__ __align__(1024) bf16 g_O[2 * LSEQ * DM];
__device__ __align__(1024) bf16 g_xT[4 * DM * LSEQ];
__device__ __align__(1024) float g_stats[2 * 32 * 192];
__device__ __align__(1024) uint2 g_colsum[3 * DM];
__device__ __align__(1024) uint4 g_halo[32 * 8 * 256];
__device__ __align__(1024) uint4 g_rows[2 * LSEQ];
#define TS(i) do { } while (0)
#define TSW(k) do { if ((threadIdx.x & 127) == 0) TS(16 + layer * 56 + (threadIdx.x >> 7) * 20 + (k)); } while (0)
#define TSG(k) do { } while (0)

#define RETRY(i) do { } while (0)
#define LTS(i) do { } while (0)
#define LTE() do { } while (0)

struct Params {
  CUtensorMap mapX, mapW3, mapXT, mapWo;
  bf16* out;
  const bf16 *a_re, *a_im, *b_re, *b_im, *c_re, *c_im, *log_dt, *dskip;
};

__device__ __forceinline__ uint32_t s32(const void* p) { return (uint32_t)__cvta_generic_to_shared(p); }
__device__ __forceinline__ void mbar_init(uint32_t b, int c) { asm volatile("mbarrier.init.shared::cta.b64 [%0], %1;" ::"r"(b), "r"(c) : "memory"); }
__device__ __forceinline__ void mbar_expect(uint32_t b, int bytes) { asm volatile("mbarrier.arrive.expect_tx.shared::cta.b64 _, [%0], %1;" ::"r"(b), "r"(bytes) : "memory"); }
__device__ __forceinline__ void mbar_arrive(uint32_t b) { asm volatile("mbarrier.arrive.shared::cta.b64 _, [%0];" ::"r"(b) : "memory"); }
__device__ __forceinline__ void mbar_wait(uint32_t b, int parity) {
  asm volatile("{\n.reg .pred p;\nWAIT_LOOP:\nmbarrier.try_wait.parity.shared::cta.b64 p, [%0], %1;\n@p bra WAIT_DONE;\nbra WAIT_LOOP;\nWAIT_DONE:\n}" ::"r"(b), "r"(parity) : "memory");
}
__device__ __forceinline__ bool mbar_test(uint32_t b, int parity) {
  uint32_t ok;
  asm volatile("{\n.reg .pred p;\nmbarrier.test_wait.parity.shared::cta.b64 p, [%1], %2;\nselp.u32 %0, 1, 0, p;\n}" : "=r"(ok) : "r"(b), "r"(parity) : "memory");
  return ok != 0;
}
__device__ __forceinline__ int opaque_tid() { int v; asm volatile("mov.u32 %0, %%tid.x;" : "=r"(v)); return v; }
__device__ __forceinline__ bool elect_one() {
  uint32_t r;
  asm volatile("{\n.reg .pred p;\nelect.sync _|p, 0xffffffff;\nselp.u32 %0, 1, 0, p;\n}" : "=r"(r));
  return r != 0;
}
__device__ __forceinline__ void tma_ld(uint32_t dst, const CUtensorMap* m, int c0, int c1, uint32_t bar) {
  asm volatile("cp.async.bulk.tensor.2d.shared::cluster.global.mbarrier::complete_tx::bytes [%0], [%1, {%3, %4}], [%2];"
               ::"r"(dst), "l"(m), "r"(bar), "r"(c0), "r"(c1) : "memory");
}
__device__ __forceinline__ void tma_ld3(uint32_t dst, const CUtensorMap* m, int c0, int c1, int c2, uint32_t bar) {
  asm volatile("cp.async.bulk.tensor.3d.shared::cluster.global.mbarrier::complete_tx::bytes [%0], [%1, {%3, %4, %5}], [%2];"
               ::"r"(dst), "l"(m), "r"(bar), "r"(c0), "r"(c1), "r"(c2) : "memory");
}
__device__ __forceinline__ void tma_ld5(uint32_t dst, const CUtensorMap* m, int c0, int c4, uint32_t bar) {
  asm volatile("cp.async.bulk.tensor.5d.shared::cluster.global.mbarrier::complete_tx::bytes [%0], [%1, {%3, 0, 0, 0, %4}], [%2];"
               ::"r"(dst), "l"(m), "r"(bar), "r"(c0), "r"(c4) : "memory");
}
__device__ __forceinline__ void tma_prefetch5(const CUtensorMap* m, int c0, int c4) {
  asm volatile("cp.async.bulk.prefetch.tensor.5d.L2.global.tile [%0, {%1, 0, 0, 0, %2}];" ::"l"(m), "r"(c0), "r"(c4) : "memory");
}
__device__ __forceinline__ void tma_prefetch3(const CUtensorMap* m, int c0, int c1, int c2) {
  asm volatile("cp.async.bulk.prefetch.tensor.3d.L2.global.tile [%0, {%1, %2, %3}];" ::"l"(m), "r"(c0), "r"(c1), "r"(c2) : "memory");
}
__device__ __forceinline__ void tma_st(const CUtensorMap* m, int c0, int c1, uint32_t src) {
  asm volatile("cp.async.bulk.tensor.2d.global.shared::cta.bulk_group [%0, {%2, %3}], [%1];" ::"l"(m), "r"(src), "r"(c0), "r"(c1) : "memory");
}
__device__ __forceinline__ void bulk_ld(uint32_t dst, const void* src, int bytes, uint32_t bar) {
  asm volatile("cp.async.bulk.shared::cluster.global.mbarrier::complete_tx::bytes [%0], [%1], %2, [%3];" ::"r"(dst), "l"(src), "r"(bytes), "r"(bar) : "memory");
}
__device__ __forceinline__ void bulk_red_add_f32(void* dst, uint32_t src, int bytes) {
  asm volatile("cp.reduce.async.bulk.global.shared::cta.bulk_group.add.f32 [%0], [%1], %2;" ::"l"(dst), "r"(src), "r"(bytes) : "memory");
}
__device__ __forceinline__ void bulk_commit() { asm volatile("cp.async.bulk.commit_group;" ::: "memory"); }
__device__ __forceinline__ void fence_async_smem() { asm volatile("fence.proxy.async.shared::cta;" ::: "memory"); }
__device__ __forceinline__ void fence_async_global() { asm volatile("fence.proxy.async.global;" ::: "memory"); }
__device__ __forceinline__ void bar_sync(int id, int n) { asm volatile("bar.sync %0, %1;" ::"r"(id), "r"(n) : "memory"); }
__device__ __forceinline__ void bar_arrive(int id, int n) { asm volatile("bar.arrive %0, %1;" ::"r"(id), "r"(n) : "memory"); }
__device__ __forceinline__ bool bar_or(int id, int n, bool v) {
  uint32_t r;
  asm volatile("{\n.reg .pred p, q;\nsetp.ne.u32 q, %3, 0;\nbar.red.or.pred p, %1, %2, q;\nselp.u32 %0, 1, 0, p;\n}" : "=r"(r) : "r"(id), "r"(n), "r"((uint32_t)v) : "memory");
  return r != 0;
}
__device__ __forceinline__ void bulk_wait_read() { asm volatile("cp.async.bulk.wait_group.read 0;" ::: "memory"); }
__device__ __forceinline__ void stg128(void* p, uint4 v) { asm volatile("st.relaxed.gpu.global.v4.u32 [%0], {%1,%2,%3,%4};" ::"l"(p), "r"(v.x), "r"(v.y), "r"(v.z), "r"(v.w) : "memory"); }
constexpr uint32_t UNSET = 0xffffffffu;
constexpr int MAX_RETRY = 1 << 16;
__device__ __forceinline__ void wg_fence() { asm volatile("wgmma.fence.sync.aligned;" ::: "memory"); }
__device__ __forceinline__ void wg_commit() { asm volatile("wgmma.commit_group.sync.aligned;" ::: "memory"); }
template <int N> __device__ __forceinline__ void wg_wait() { asm volatile("wgmma.wait_group.sync.aligned %0;" ::"n"(N) : "memory"); }
__device__ __forceinline__ uint64_t mkdesc(uint32_t addr, uint32_t lbo, uint32_t sbo, int sw) {
  return (uint64_t)((addr & 0x3FFFF) >> 4) | ((uint64_t)(lbo >> 4) << 16) | ((uint64_t)(sbo >> 4) << 32) | ((uint64_t)sw << 62);
}
__device__ __forceinline__ void ldsm4(uint32_t* r, uint32_t a) {
  asm volatile("ldmatrix.sync.aligned.m8n8.x4.shared.b16 {%0,%1,%2,%3}, [%4];" : "=r"(r[0]), "=r"(r[1]), "=r"(r[2]), "=r"(r[3]) : "r"(a) : "memory");
}
__device__ __forceinline__ void ldsm4t(uint32_t* r, uint32_t a) {
  asm volatile("ldmatrix.sync.aligned.m8n8.x4.trans.shared.b16 {%0,%1,%2,%3}, [%4];" : "=r"(r[0]), "=r"(r[1]), "=r"(r[2]), "=r"(r[3]) : "r"(a) : "memory");
}
__device__ __forceinline__ void stsm4(uint32_t a, uint32_t r0, uint32_t r1, uint32_t r2, uint32_t r3) {
  asm volatile("stmatrix.sync.aligned.m8n8.x4.shared.b16 [%0], {%1,%2,%3,%4};" ::"r"(a), "r"(r0), "r"(r1), "r"(r2), "r"(r3) : "memory");
}
__device__ __forceinline__ void stsm4t(uint32_t a, uint32_t r0, uint32_t r1, uint32_t r2, uint32_t r3) {
  asm volatile("stmatrix.sync.aligned.m8n8.x4.trans.shared.b16 [%0], {%1,%2,%3,%4};" ::"r"(a), "r"(r0), "r"(r1), "r"(r2), "r"(r3) : "memory");
}
__device__ __forceinline__ uint32_t movm_t(uint32_t a) { uint32_t r; asm volatile("movmatrix.sync.aligned.m8n8.trans.b16 %0, %1;" : "=r"(r) : "r"(a)); return r; }
__device__ __forceinline__ uint32_t lds32(uint32_t a) { uint32_t v; asm volatile("ld.shared.b32 %0, [%1];" : "=r"(v) : "r"(a) : "memory"); return v; }
__device__ __forceinline__ float2 lds64f(uint32_t a) { float2 v; asm volatile("ld.shared.v2.f32 {%0,%1}, [%2];" : "=f"(v.x), "=f"(v.y) : "r"(a) : "memory"); return v; }
__device__ __forceinline__ float4 lds128f(uint32_t a) { float4 v; asm volatile("ld.shared.v4.f32 {%0,%1,%2,%3}, [%4];" : "=f"(v.x), "=f"(v.y), "=f"(v.z), "=f"(v.w) : "r"(a) : "memory"); return v; }
__device__ __forceinline__ uint4 lds128(uint32_t a) { uint4 v; asm volatile("ld.shared.v4.b32 {%0,%1,%2,%3}, [%4];" : "=r"(v.x), "=r"(v.y), "=r"(v.z), "=r"(v.w) : "r"(a) : "memory"); return v; }
__device__ __forceinline__ void sts128(uint32_t a, uint4 v) { asm volatile("st.shared.v4.b32 [%0], {%1,%2,%3,%4};" ::"r"(a), "r"(v.x), "r"(v.y), "r"(v.z), "r"(v.w) : "memory"); }
__device__ __forceinline__ void sts128f(uint32_t a, float x, float y, float z, float w) { asm volatile("st.shared.v4.f32 [%0], {%1,%2,%3,%4};" ::"r"(a), "f"(x), "f"(y), "f"(z), "f"(w) : "memory"); }
__device__ __forceinline__ void sts32f(uint32_t a, float v) { asm volatile("st.shared.f32 [%0], %1;" ::"r"(a), "f"(v) : "memory"); }
__device__ __forceinline__ void sts16(uint32_t a, uint16_t v) { asm volatile("st.shared.u16 [%0], %1;" ::"r"(a), "h"(v) : "memory"); }
__device__ __forceinline__ uint32_t lds16(uint32_t a) { uint16_t v; asm volatile("ld.shared.u16 %0, [%1];" : "=h"(v) : "r"(a) : "memory"); return v; }
__device__ __forceinline__ uint32_t packbf(float lo, float hi) { uint32_t r; asm("cvt.rn.bf16x2.f32 %0, %1, %2;" : "=r"(r) : "f"(hi), "f"(lo)); return r; }
__device__ __forceinline__ uint32_t prmt0(uint32_t a, uint32_t sel) { uint32_t r; asm("prmt.b32 %0, %1, 0, %2;" : "=r"(r) : "r"(a), "r"(sel)); return r; }
__device__ __forceinline__ float bf_lo(uint32_t v) { return __uint_as_float(v << 16); }
__device__ __forceinline__ float bf_hi(uint32_t v) { return __uint_as_float(v & 0xffff0000u); }
__device__ __forceinline__ float ex2(float x) { float r; asm("ex2.approx.ftz.f32 %0, %1;" : "=f"(r) : "f"(x)); return r; }
__device__ __forceinline__ float rsqrt_approx(float x) { float r; asm("rsqrt.approx.ftz.f32 %0, %1;" : "=f"(r) : "f"(x)); return r; }
__device__ __forceinline__ float rcp_approx(float x) { float r; asm("rcp.approx.ftz.f32 %0, %1;" : "=f"(r) : "f"(x)); return r; }
__device__ __forceinline__ void mma_bf16(float* d, const uint32_t* a, uint32_t b0, uint32_t b1) {
  asm("mma.sync.aligned.m16n8k16.row.col.f32.bf16.bf16.f32 {%0,%1,%2,%3}, {%4,%5,%6,%7}, {%8,%9}, {%0,%1,%2,%3};"
               : "+f"(d[0]), "+f"(d[1]), "+f"(d[2]), "+f"(d[3]) : "r"(a[0]), "r"(a[1]), "r"(a[2]), "r"(a[3]), "r"(b0), "r"(b1));
}
__device__ __forceinline__ void mma_bf16_c(float* d, const uint32_t* a, uint32_t b0, uint32_t b1, const float* c) {
  asm("mma.sync.aligned.m16n8k16.row.col.f32.bf16.bf16.f32 {%0,%1,%2,%3}, {%4,%5,%6,%7}, {%8,%9}, {%10,%11,%12,%13};"
               : "=f"(d[0]), "=f"(d[1]), "=f"(d[2]), "=f"(d[3]) : "r"(a[0]), "r"(a[1]), "r"(a[2]), "r"(a[3]), "r"(b0), "r"(b1),
                 "f"(c[0]), "f"(c[1]), "f"(c[2]), "f"(c[3]));
}
__device__ __forceinline__ void mma_rowsum(float* d, uint32_t a0, uint32_t a1) {
  asm("mma.sync.aligned.m16n8k8.row.col.f32.bf16.bf16.f32 {%0,%1,%2,%3}, {%4,%5}, {%6}, {%7,%7,%7,%7};"
               : "=f"(d[0]), "=f"(d[1]), "=f"(d[2]), "=f"(d[3]) : "r"(a0), "r"(a1), "r"(0x3f803f80u), "f"(0.f));
}
__device__ __forceinline__ void red_release(unsigned* p) { asm volatile("red.release.gpu.global.add.u32 [%0], 1;" ::"l"(p) : "memory"); }
__device__ __forceinline__ void red_relaxed(unsigned* p) { asm volatile("red.relaxed.gpu.global.add.u32 [%0], 1;" ::"l"(p) : "memory"); }
__device__ __forceinline__ unsigned ld_relaxed(const unsigned* p) { unsigned v; asm volatile("ld.relaxed.gpu.global.u32 %0, [%1];" : "=r"(v) : "l"(p) : "memory"); return v; }
__device__ __forceinline__ void spin_until(const unsigned* p, unsigned target) {
  int it = 0;
  while ((int)(ld_relaxed(p) - target) < 0) {
    if (++it > (1 << 23)) __trap();
  }
}
template <typename T> __device__ __forceinline__ void pin(T*& p) { asm volatile("" : "+l"(p) :: "memory"); }
__device__ __forceinline__ void pin(uint32_t& v) { asm volatile("" : "+r"(v) :: "memory"); }
__device__ __forceinline__ void spin_hint(const unsigned* p, unsigned target) {
  spin_until(p, target);
}
__device__ __forceinline__ uint4 ld_tagged(const uint4* p) { uint4 v; asm volatile("ld.relaxed.gpu.global.v4.u32 {%0,%1,%2,%3}, [%4];" : "=r"(v.x), "=r"(v.y), "=r"(v.z), "=r"(v.w) : "l"(p) : "memory"); return v; }
__device__ __forceinline__ uint32_t hadd2(uint32_t a, uint32_t b) { uint32_t r; asm("add.rn.bf16x2 %0, %1, %2;" : "=r"(r) : "r"(a), "r"(b)); return r; }

__device__ __forceinline__ uint32_t hfma2(uint32_t a, uint32_t b, uint32_t c) { uint32_t r; asm("fma.rn.bf16x2 %0, %1, %2, %3;" : "=r"(r) : "r"(a), "r"(b), "r"(c)); return r; }
__device__ __forceinline__ void sts32(uint32_t a, uint32_t v) { asm volatile("st.shared.u32 [%0], %1;" ::"r"(a), "r"(v) : "memory"); }

template <int N> __device__ __forceinline__ void acc_fence(float* a) {
#pragma unroll
  for (int i = 0; i < N; i++) asm volatile("" : "+f"(a[i]) :: "memory");
}

template<int N,int TB> __device__ __forceinline__ void wgmma_rs(float* d, const uint32_t* a, uint64_t db, int sd);
template<int N,int TA,int TB> __device__ __forceinline__ void wgmma_ss(float* d, uint64_t da, uint64_t db, int sd);
template<> __device__ __forceinline__ void wgmma_rs<64,0>(float* d, const uint32_t* a, uint64_t db, int sd) {
  asm volatile("{\n.reg .pred p;\nsetp.ne.b32 p, %37, 0;\nwgmma.mma_async.sync.aligned.m64n64k16.f32.bf16.bf16 {%0,%1,%2,%3,%4,%5,%6,%7,%8,%9,%10,%11,%12,%13,%14,%15,%16,%17,%18,%19,%20,%21,%22,%23,%24,%25,%26,%27,%28,%29,%30,%31}, {%32,%33,%34,%35}, %36, p, 1, 1, 0;\n}\n"
   : "+f"(d[0]),"+f"(d[1]),"+f"(d[2]),"+f"(d[3]),"+f"(d[4]),"+f"(d[5]),"+f"(d[6]),"+f"(d[7]),"+f"(d[8]),"+f"(d[9]),"+f"(d[10]),"+f"(d[11]),"+f"(d[12]),"+f"(d[13]),"+f"(d[14]),"+f"(d[15]),"+f"(d[16]),"+f"(d[17]),"+f"(d[18]),"+f"(d[19]),"+f"(d[20]),"+f"(d[21]),"+f"(d[22]),"+f"(d[23]),"+f"(d[24]),"+f"(d[25]),"+f"(d[26]),"+f"(d[27]),"+f"(d[28]),"+f"(d[29]),"+f"(d[30]),"+f"(d[31])
   : "r"(a[0]), "r"(a[1]), "r"(a[2]), "r"(a[3]), "l"(db), "r"(sd));
}
template<> __device__ __forceinline__ void wgmma_rs<56,0>(float* d, const uint32_t* a, uint64_t db, int sd) {
  asm volatile("{\n.reg .pred p;\nsetp.ne.b32 p, %33, 0;\nwgmma.mma_async.sync.aligned.m64n56k16.f32.bf16.bf16 {%0,%1,%2,%3,%4,%5,%6,%7,%8,%9,%10,%11,%12,%13,%14,%15,%16,%17,%18,%19,%20,%21,%22,%23,%24,%25,%26,%27}, {%28,%29,%30,%31}, %32, p, 1, 1, 0;\n}\n"
   : "+f"(d[0]),"+f"(d[1]),"+f"(d[2]),"+f"(d[3]),"+f"(d[4]),"+f"(d[5]),"+f"(d[6]),"+f"(d[7]),"+f"(d[8]),"+f"(d[9]),"+f"(d[10]),"+f"(d[11]),"+f"(d[12]),"+f"(d[13]),"+f"(d[14]),"+f"(d[15]),"+f"(d[16]),"+f"(d[17]),"+f"(d[18]),"+f"(d[19]),"+f"(d[20]),"+f"(d[21]),"+f"(d[22]),"+f"(d[23]),"+f"(d[24]),"+f"(d[25]),"+f"(d[26]),"+f"(d[27])
   : "r"(a[0]), "r"(a[1]), "r"(a[2]), "r"(a[3]), "l"(db), "r"(sd));
}
template<> __device__ __forceinline__ void wgmma_rs<48,0>(float* d, const uint32_t* a, uint64_t db, int sd) {
  asm volatile("{\n.reg .pred p;\nsetp.ne.b32 p, %29, 0;\nwgmma.mma_async.sync.aligned.m64n48k16.f32.bf16.bf16 {%0,%1,%2,%3,%4,%5,%6,%7,%8,%9,%10,%11,%12,%13,%14,%15,%16,%17,%18,%19,%20,%21,%22,%23}, {%24,%25,%26,%27}, %28, p, 1, 1, 0;\n}\n"
   : "+f"(d[0]),"+f"(d[1]),"+f"(d[2]),"+f"(d[3]),"+f"(d[4]),"+f"(d[5]),"+f"(d[6]),"+f"(d[7]),"+f"(d[8]),"+f"(d[9]),"+f"(d[10]),"+f"(d[11]),"+f"(d[12]),"+f"(d[13]),"+f"(d[14]),"+f"(d[15]),"+f"(d[16]),"+f"(d[17]),"+f"(d[18]),"+f"(d[19]),"+f"(d[20]),"+f"(d[21]),"+f"(d[22]),"+f"(d[23])
   : "r"(a[0]), "r"(a[1]), "r"(a[2]), "r"(a[3]), "l"(db), "r"(sd));
}
template<> __device__ __forceinline__ void wgmma_rs<40,0>(float* d, const uint32_t* a, uint64_t db, int sd) {
  asm volatile("{\n.reg .pred p;\nsetp.ne.b32 p, %25, 0;\nwgmma.mma_async.sync.aligned.m64n40k16.f32.bf16.bf16 {%0,%1,%2,%3,%4,%5,%6,%7,%8,%9,%10,%11,%12,%13,%14,%15,%16,%17,%18,%19}, {%20,%21,%22,%23}, %24, p, 1, 1, 0;\n}\n"
   : "+f"(d[0]),"+f"(d[1]),"+f"(d[2]),"+f"(d[3]),"+f"(d[4]),"+f"(d[5]),"+f"(d[6]),"+f"(d[7]),"+f"(d[8]),"+f"(d[9]),"+f"(d[10]),"+f"(d[11]),"+f"(d[12]),"+f"(d[13]),"+f"(d[14]),"+f"(d[15]),"+f"(d[16]),"+f"(d[17]),"+f"(d[18]),"+f"(d[19])
   : "r"(a[0]), "r"(a[1]), "r"(a[2]), "r"(a[3]), "l"(db), "r"(sd));
}
template<> __device__ __forceinline__ void wgmma_rs<32,0>(float* d, const uint32_t* a, uint64_t db, int sd) {
  asm volatile("{\n.reg .pred p;\nsetp.ne.b32 p, %21, 0;\nwgmma.mma_async.sync.aligned.m64n32k16.f32.bf16.bf16 {%0,%1,%2,%3,%4,%5,%6,%7,%8,%9,%10,%11,%12,%13,%14,%15}, {%16,%17,%18,%19}, %20, p, 1, 1, 0;\n}\n"
   : "+f"(d[0]),"+f"(d[1]),"+f"(d[2]),"+f"(d[3]),"+f"(d[4]),"+f"(d[5]),"+f"(d[6]),"+f"(d[7]),"+f"(d[8]),"+f"(d[9]),"+f"(d[10]),"+f"(d[11]),"+f"(d[12]),"+f"(d[13]),"+f"(d[14]),"+f"(d[15])
   : "r"(a[0]), "r"(a[1]), "r"(a[2]), "r"(a[3]), "l"(db), "r"(sd));
}
template<> __device__ __forceinline__ void wgmma_rs<24,0>(float* d, const uint32_t* a, uint64_t db, int sd) {
  asm volatile("{\n.reg .pred p;\nsetp.ne.b32 p, %17, 0;\nwgmma.mma_async.sync.aligned.m64n24k16.f32.bf16.bf16 {%0,%1,%2,%3,%4,%5,%6,%7,%8,%9,%10,%11}, {%12,%13,%14,%15}, %16, p, 1, 1, 0;\n}\n"
   : "+f"(d[0]),"+f"(d[1]),"+f"(d[2]),"+f"(d[3]),"+f"(d[4]),"+f"(d[5]),"+f"(d[6]),"+f"(d[7]),"+f"(d[8]),"+f"(d[9]),"+f"(d[10]),"+f"(d[11])
   : "r"(a[0]), "r"(a[1]), "r"(a[2]), "r"(a[3]), "l"(db), "r"(sd));
}
template<> __device__ __forceinline__ void wgmma_rs<16,0>(float* d, const uint32_t* a, uint64_t db, int sd) {
  asm volatile("{\n.reg .pred p;\nsetp.ne.b32 p, %13, 0;\nwgmma.mma_async.sync.aligned.m64n16k16.f32.bf16.bf16 {%0,%1,%2,%3,%4,%5,%6,%7}, {%8,%9,%10,%11}, %12, p, 1, 1, 0;\n}\n"
   : "+f"(d[0]),"+f"(d[1]),"+f"(d[2]),"+f"(d[3]),"+f"(d[4]),"+f"(d[5]),"+f"(d[6]),"+f"(d[7])
   : "r"(a[0]), "r"(a[1]), "r"(a[2]), "r"(a[3]), "l"(db), "r"(sd));
}
template<> __device__ __forceinline__ void wgmma_rs<8,0>(float* d, const uint32_t* a, uint64_t db, int sd) {
  asm volatile("{\n.reg .pred p;\nsetp.ne.b32 p, %9, 0;\nwgmma.mma_async.sync.aligned.m64n8k16.f32.bf16.bf16 {%0,%1,%2,%3}, {%4,%5,%6,%7}, %8, p, 1, 1, 0;\n}\n"
   : "+f"(d[0]),"+f"(d[1]),"+f"(d[2]),"+f"(d[3])
   : "r"(a[0]), "r"(a[1]), "r"(a[2]), "r"(a[3]), "l"(db), "r"(sd));
}
template<> __device__ __forceinline__ void wgmma_ss<64,1,0>(float* d, uint64_t da, uint64_t db, int sd) {
  asm volatile("{\n.reg .pred p;\nsetp.ne.b32 p, %34, 0;\nwgmma.mma_async.sync.aligned.m64n64k16.f32.bf16.bf16 {%0,%1,%2,%3,%4,%5,%6,%7,%8,%9,%10,%11,%12,%13,%14,%15,%16,%17,%18,%19,%20,%21,%22,%23,%24,%25,%26,%27,%28,%29,%30,%31}, %32, %33, p, 1, 1, 1, 0;\n}\n"
   : "+f"(d[0]),"+f"(d[1]),"+f"(d[2]),"+f"(d[3]),"+f"(d[4]),"+f"(d[5]),"+f"(d[6]),"+f"(d[7]),"+f"(d[8]),"+f"(d[9]),"+f"(d[10]),"+f"(d[11]),"+f"(d[12]),"+f"(d[13]),"+f"(d[14]),"+f"(d[15]),"+f"(d[16]),"+f"(d[17]),"+f"(d[18]),"+f"(d[19]),"+f"(d[20]),"+f"(d[21]),"+f"(d[22]),"+f"(d[23]),"+f"(d[24]),"+f"(d[25]),"+f"(d[26]),"+f"(d[27]),"+f"(d[28]),"+f"(d[29]),"+f"(d[30]),"+f"(d[31])
   : "l"(da), "l"(db), "r"(sd));
}
template<> __device__ __forceinline__ void wgmma_ss<64,0,1>(float* d, uint64_t da, uint64_t db, int sd) {
  asm volatile("{\n.reg .pred p;\nsetp.ne.b32 p, %34, 0;\nwgmma.mma_async.sync.aligned.m64n64k16.f32.bf16.bf16 {%0,%1,%2,%3,%4,%5,%6,%7,%8,%9,%10,%11,%12,%13,%14,%15,%16,%17,%18,%19,%20,%21,%22,%23,%24,%25,%26,%27,%28,%29,%30,%31}, %32, %33, p, 1, 1, 0, 1;\n}\n"
   : "+f"(d[0]),"+f"(d[1]),"+f"(d[2]),"+f"(d[3]),"+f"(d[4]),"+f"(d[5]),"+f"(d[6]),"+f"(d[7]),"+f"(d[8]),"+f"(d[9]),"+f"(d[10]),"+f"(d[11]),"+f"(d[12]),"+f"(d[13]),"+f"(d[14]),"+f"(d[15]),"+f"(d[16]),"+f"(d[17]),"+f"(d[18]),"+f"(d[19]),"+f"(d[20]),"+f"(d[21]),"+f"(d[22]),"+f"(d[23]),"+f"(d[24]),"+f"(d[25]),"+f"(d[26]),"+f"(d[27]),"+f"(d[28]),"+f"(d[29]),"+f"(d[30]),"+f"(d[31])
   : "l"(da), "l"(db), "r"(sd));
}
template<> __device__ __forceinline__ void wgmma_ss<192,0,1>(float* d, uint64_t da, uint64_t db, int sd) {
  asm volatile("{\n.reg .pred p;\nsetp.ne.b32 p, %98, 0;\nwgmma.mma_async.sync.aligned.m64n192k16.f32.bf16.bf16 {%0,%1,%2,%3,%4,%5,%6,%7,%8,%9,%10,%11,%12,%13,%14,%15,%16,%17,%18,%19,%20,%21,%22,%23,%24,%25,%26,%27,%28,%29,%30,%31,%32,%33,%34,%35,%36,%37,%38,%39,%40,%41,%42,%43,%44,%45,%46,%47,%48,%49,%50,%51,%52,%53,%54,%55,%56,%57,%58,%59,%60,%61,%62,%63,%64,%65,%66,%67,%68,%69,%70,%71,%72,%73,%74,%75,%76,%77,%78,%79,%80,%81,%82,%83,%84,%85,%86,%87,%88,%89,%90,%91,%92,%93,%94,%95}, %96, %97, p, 1, 1, 0, 1;\n}\n"
   : "+f"(d[0]),"+f"(d[1]),"+f"(d[2]),"+f"(d[3]),"+f"(d[4]),"+f"(d[5]),"+f"(d[6]),"+f"(d[7]),"+f"(d[8]),"+f"(d[9]),"+f"(d[10]),"+f"(d[11]),"+f"(d[12]),"+f"(d[13]),"+f"(d[14]),"+f"(d[15]),"+f"(d[16]),"+f"(d[17]),"+f"(d[18]),"+f"(d[19]),"+f"(d[20]),"+f"(d[21]),"+f"(d[22]),"+f"(d[23]),"+f"(d[24]),"+f"(d[25]),"+f"(d[26]),"+f"(d[27]),"+f"(d[28]),"+f"(d[29]),"+f"(d[30]),"+f"(d[31]),"+f"(d[32]),"+f"(d[33]),"+f"(d[34]),"+f"(d[35]),"+f"(d[36]),"+f"(d[37]),"+f"(d[38]),"+f"(d[39]),"+f"(d[40]),"+f"(d[41]),"+f"(d[42]),"+f"(d[43]),"+f"(d[44]),"+f"(d[45]),"+f"(d[46]),"+f"(d[47]),"+f"(d[48]),"+f"(d[49]),"+f"(d[50]),"+f"(d[51]),"+f"(d[52]),"+f"(d[53]),"+f"(d[54]),"+f"(d[55]),"+f"(d[56]),"+f"(d[57]),"+f"(d[58]),"+f"(d[59]),"+f"(d[60]),"+f"(d[61]),"+f"(d[62]),"+f"(d[63]),"+f"(d[64]),"+f"(d[65]),"+f"(d[66]),"+f"(d[67]),"+f"(d[68]),"+f"(d[69]),"+f"(d[70]),"+f"(d[71]),"+f"(d[72]),"+f"(d[73]),"+f"(d[74]),"+f"(d[75]),"+f"(d[76]),"+f"(d[77]),"+f"(d[78]),"+f"(d[79]),"+f"(d[80]),"+f"(d[81]),"+f"(d[82]),"+f"(d[83]),"+f"(d[84]),"+f"(d[85]),"+f"(d[86]),"+f"(d[87]),"+f"(d[88]),"+f"(d[89]),"+f"(d[90]),"+f"(d[91]),"+f"(d[92]),"+f"(d[93]),"+f"(d[94]),"+f"(d[95])
   : "l"(da), "l"(db), "r"(sd));
}
template<> __device__ __forceinline__ void wgmma_ss<192,1,1>(float* d, uint64_t da, uint64_t db, int sd) {
  asm volatile("{\n.reg .pred p;\nsetp.ne.b32 p, %98, 0;\nwgmma.mma_async.sync.aligned.m64n192k16.f32.bf16.bf16 {%0,%1,%2,%3,%4,%5,%6,%7,%8,%9,%10,%11,%12,%13,%14,%15,%16,%17,%18,%19,%20,%21,%22,%23,%24,%25,%26,%27,%28,%29,%30,%31,%32,%33,%34,%35,%36,%37,%38,%39,%40,%41,%42,%43,%44,%45,%46,%47,%48,%49,%50,%51,%52,%53,%54,%55,%56,%57,%58,%59,%60,%61,%62,%63,%64,%65,%66,%67,%68,%69,%70,%71,%72,%73,%74,%75,%76,%77,%78,%79,%80,%81,%82,%83,%84,%85,%86,%87,%88,%89,%90,%91,%92,%93,%94,%95}, %96, %97, p, 1, 1, 1, 1;\n}\n"
   : "+f"(d[0]),"+f"(d[1]),"+f"(d[2]),"+f"(d[3]),"+f"(d[4]),"+f"(d[5]),"+f"(d[6]),"+f"(d[7]),"+f"(d[8]),"+f"(d[9]),"+f"(d[10]),"+f"(d[11]),"+f"(d[12]),"+f"(d[13]),"+f"(d[14]),"+f"(d[15]),"+f"(d[16]),"+f"(d[17]),"+f"(d[18]),"+f"(d[19]),"+f"(d[20]),"+f"(d[21]),"+f"(d[22]),"+f"(d[23]),"+f"(d[24]),"+f"(d[25]),"+f"(d[26]),"+f"(d[27]),"+f"(d[28]),"+f"(d[29]),"+f"(d[30]),"+f"(d[31]),"+f"(d[32]),"+f"(d[33]),"+f"(d[34]),"+f"(d[35]),"+f"(d[36]),"+f"(d[37]),"+f"(d[38]),"+f"(d[39]),"+f"(d[40]),"+f"(d[41]),"+f"(d[42]),"+f"(d[43]),"+f"(d[44]),"+f"(d[45]),"+f"(d[46]),"+f"(d[47]),"+f"(d[48]),"+f"(d[49]),"+f"(d[50]),"+f"(d[51]),"+f"(d[52]),"+f"(d[53]),"+f"(d[54]),"+f"(d[55]),"+f"(d[56]),"+f"(d[57]),"+f"(d[58]),"+f"(d[59]),"+f"(d[60]),"+f"(d[61]),"+f"(d[62]),"+f"(d[63]),"+f"(d[64]),"+f"(d[65]),"+f"(d[66]),"+f"(d[67]),"+f"(d[68]),"+f"(d[69]),"+f"(d[70]),"+f"(d[71]),"+f"(d[72]),"+f"(d[73]),"+f"(d[74]),"+f"(d[75]),"+f"(d[76]),"+f"(d[77]),"+f"(d[78]),"+f"(d[79]),"+f"(d[80]),"+f"(d[81]),"+f"(d[82]),"+f"(d[83]),"+f"(d[84]),"+f"(d[85]),"+f"(d[86]),"+f"(d[87]),"+f"(d[88]),"+f"(d[89]),"+f"(d[90]),"+f"(d[91]),"+f"(d[92]),"+f"(d[93]),"+f"(d[94]),"+f"(d[95])
   : "l"(da), "l"(db), "r"(sd));
}

template <bool TR>
__device__ __forceinline__ void gemm_section(float* acc, float& mean0, float& mean1, float& rstd0, float& rstd1,
                                             uint32_t sb, int blk, int hg, int wg, int w, int lane) {
  constexpr int layer = TR ? 1 : 0;
  constexpr int TURN = TR ? TURN1 : TURN0;
  constexpr int LSTAT = TURN < 4 ? TURN - 1 : 3;
  const uint32_t bar = sb + SM_BAR;
  const int g = lane >> 2, t = lane & 3;
  const bool leader = (w == 0) && (lane == 0);
  const int statpos = hg < 3 ? 1 : wg ? LSTAT : TR ? 3 : 2;
  const bool copy = hg >= 3 && wg == 0;
  const int cut = wg ? TURN : 4;
  auto wait_full = [&](int c) {
    mbar_wait(bar + 8 * (B_XF + 8 * wg + c), layer);
    mbar_wait(bar + 8 * (B_WF + c), layer);
  };
  auto peek = [&](int c) {
    const bool x = mbar_test(bar + 8 * (B_XF + 8 * wg + c), layer), y = mbar_test(bar + 8 * (B_WF + c), layer);
    return x && y;
  };
  const uint64_t da0 = mkdesc(sb, TR ? 8192 : 16, 1024, 1), db0 = mkdesc(sb, 8192, 1024, 1);
  uint32_t xt = wg ? 0xfedcba98u : 0x21043210u;
  uint64_t wt = 0x0816131005161310ull;
  uint64_t da = da0 + ((xt & 15) << 9), db = db0 + (16 << 9);
  auto issue = [&](int c, int first) {
    wg_fence();
#pragma unroll
    for (int ks = 0; ks < 4; ks++) wgmma_ss<192, TR ? 1 : 0, 1>(acc, da + (TR ? ks * 128 : ks * 2), db + ks * 128, !first || ks != 0);
    wg_commit();
    xt >>= 4; wt >>= 8;
    da = da0 + ((xt & 15) << 9); db = db0 + (((uint32_t)wt & 31) << 9);
  };
  wait_full(0);
  bool ready = peek(1);
  issue(0, 1);
  TSW(0);
#pragma unroll 1
  for (int c = 1; c < cut; c++) {
    if (!ready) wait_full(c);
    issue(c, 0);
    ready = peek(c + 1);
    wg_wait<1>();
    if (leader) mbar_arrive(bar + 8 * (B_DN + 8 * wg + c - 1));
    if (wg == 1 && c == cut - 1) {
      wg_wait<0>();
      if (leader) mbar_arrive(bar + 8 * (B_DN + 8 + c));
    }
    if (c == statpos) {
      mbar_wait(bar + 8 * (copy ? B_SC : B_XF + 8 * wg + hg), layer);
      uint32_t A[16];
      const uint32_t xb = sb + (copy ? P_R : 8 * wg + hg) * PG;
#pragma unroll
      for (int ks = 0; ks < 4; ks++) {
        if (!TR) {
          const int row = 16 * w + (lane & 15), kc = 2 * ks + (lane >> 4);
          ldsm4(&A[4 * ks], xb + row * 128 + ((kc ^ (row & 7)) << 4));
        } else {
          const int k = 16 * ks + (lane & 7) + 8 * (lane >> 4), pc = 2 * w + ((lane >> 3) & 1);
          ldsm4t(&A[4 * ks], xb + k * 128 + ((pc ^ (k & 7)) << 4));
        }
      }
      float s0 = 0.f, q0 = 0.f, s1 = 0.f, q1 = 0.f;
#pragma unroll
      for (int i = 0; i < 16; i += 2) {
        const float a = bf_lo(A[i]), b = bf_hi(A[i]), c_ = bf_lo(A[i + 1]), d = bf_hi(A[i + 1]);
        s0 += a + b; q0 = fmaf(a, a, q0); q0 = fmaf(b, b, q0);
        s1 += c_ + d; q1 = fmaf(c_, c_, q1); q1 = fmaf(d, d, q1);
      }
#pragma unroll
      for (int o = 1; o <= 2; o <<= 1) {
        s0 += __shfl_xor_sync(~0u, s0, o); q0 += __shfl_xor_sync(~0u, q0, o);
        s1 += __shfl_xor_sync(~0u, s1, o); q1 += __shfl_xor_sync(~0u, q1, o);
      }
      if (t < 2)
        asm volatile("red.relaxed.gpu.global.add.v4.f32 [%0], {%1,%2,%3,%4};" ::"l"(g_rows + layer * LSEQ + blk * 64 + 16 * w + g + 8 * t),
                     "f"(t ? s1 : s0), "f"(t ? q1 : q0), "f"(1.f), "f"(0.f) : "memory");
    }
  }
  if (wg == 1) {
#pragma unroll 1
    for (int c = cut; c < 8; c++) wait_full(c);
    ready = true;
    bar_sync(5, 256);
  }
#pragma unroll 1
  for (int c = cut; c < 8; c++) {
    if (!ready) wait_full(c);
    issue(c, 0);
    if (wg == 1) {
      wg_wait<2>();
      if (leader && c >= cut + 2) mbar_arrive(bar + 8 * (B_DN + 8 + c - 2));
    } else if (c == 7) {
      bar_arrive(5, 256);
    } else {
      ready = peek(c + 1);
      wg_wait<1>();
      if (leader && c < 6) mbar_arrive(bar + 8 * (B_DN + c - 1));
    }
  }
  mbar_wait(bar + 8 * (B_LN + wg), layer);
  const float4 ln = lds128f(sb + ln_off(wg) + (8 * w + g) * 16);
  mean0 = ln.x; rstd0 = ln.y; mean1 = ln.z; rstd1 = ln.w;
  wg_wait<0>();
  acc_fence<96>(acc);
  if (leader) mbar_arrive(bar + 8 * (B_DN + 8 * wg + 7));
}

__device__ __forceinline__ void attn_phase(const Params& p, uint32_t sb, int layer, int rb, int hg, int wg, int w) {
  const int lane = opaque_tid() & 31;
  const int g = lane >> 2, t = lane & 3;
  const uint32_t bar = sb + SM_BAR;
  const int blk = 16 * wg + rb;
  float acc[96];
  float2 cs[24];
  float mean0, mean1, rstd0, rstd1;
  if (layer) gemm_section<true>(acc, mean0, mean1, rstd0, rstd1, sb, blk, hg, wg, w, lane);
  else gemm_section<false>(acc, mean0, mean1, rstd0, rstd1, sb, blk, hg, wg, w, lane);
  TSW(1);
#pragma unroll
  for (int j = 8; j < 24; j++) cs[j] = lds64f(sb + SM_CS + 4 * (8 * j + 2 * t));
  const uint32_t kvx = sb + (wg ? 22 : 0) * PG;

  const uint32_t ka = kvx + (16 * w + (lane & 7) + 8 * (lane >> 4)) * 272 + (lane & 8) * 2;
  const uint32_t va = kvx + (16 * w + (lane & 15)) * 272 + (lane & 16) + 32;
  uint4* halo = &g_halo[(blk * 8 + hg) * 256 + lane];
  uint32_t kb[4][8], vb[4][8], qa[4][4];
  {
    const float nm0 = -mean0 * rstd0, nm1 = -mean1 * rstd1;
    const bool sender = (w == 3 && blk < 31);
    uint32_t r[4][2][4];
#pragma unroll
    for (int h = 0; h < 4; h++) {
#pragma unroll
      for (int kv = 0; kv < 2; kv++) {
#pragma unroll
        for (int dh = 0; dh < 2; dh++) {
          const int j = 8 + kv * 8 + 2 * h + dh;
          const float2 c2 = cs[j];
          const float v0 = fmaf(acc[4 * j + 0], rstd0, nm0 * c2.x), v1 = fmaf(acc[4 * j + 1], rstd0, nm0 * c2.y);
          const float v2 = fmaf(acc[4 * j + 2], rstd1, nm1 * c2.x), v3 = fmaf(acc[4 * j + 3], rstd1, nm1 * c2.y);
          r[h][kv][2 * dh] = packbf(v0, v1);
          r[h][kv][2 * dh + 1] = packbf(v2, v3);
        }
      }
      if (sender) {
        stg128(halo + (2 * h) * 32, make_uint4(r[h][0][0], r[h][0][2], r[h][0][1], r[h][0][3]));
        stg128(halo + (2 * h + 1) * 32, make_uint4(r[h][1][0], r[h][1][1], r[h][1][2], r[h][1][3]));
      }
    }
#pragma unroll
    for (int j = 0; j < 8; j++) cs[j] = lds64f(sb + SM_CS + 4 * (8 * j + 2 * t));
    mbar_wait(bar + 8 * (B_DN + 7), layer);
#pragma unroll
    for (int h = 0; h < 4; h++) {
      if (w < 3) {
        stsm4(ka + 64 * h, r[h][0][0], r[h][0][2], r[h][0][1], r[h][0][3]);
        stsm4(va + 64 * h, r[h][1][0], r[h][1][1], r[h][1][2], r[h][1][3]);
      }
      kb[h][4] = r[h][0][0]; kb[h][5] = r[h][0][2]; kb[h][6] = r[h][0][1]; kb[h][7] = r[h][0][3];
      vb[h][4] = movm_t(r[h][1][0]); vb[h][5] = movm_t(r[h][1][1]); vb[h][6] = movm_t(r[h][1][2]); vb[h][7] = movm_t(r[h][1][3]);
    }
#pragma unroll
    for (int h = 0; h < 4; h++) {
#pragma unroll
      for (int dh = 0; dh < 2; dh++) {
        const int j = 2 * h + dh;
        const float2 c2 = cs[j];
        qa[h][2 * dh] = packbf(fmaf(-mean0, c2.x, acc[4 * j + 0]), fmaf(-mean0, c2.y, acc[4 * j + 1]));
        qa[h][2 * dh + 1] = packbf(fmaf(-mean1, c2.x, acc[4 * j + 2]), fmaf(-mean1, c2.y, acc[4 * j + 3]));
      }
    }
  }
  uint4* op = (uint4*)g_O + ((layer * 32 + blk) * 8 + hg) * 512 + 64 * t + 16 * w + g;
  unsigned* ocnt = &g_cnt[(C_O + layer * 32 + blk) * 32];
  pin(op); pin(ocnt);
  const int e = t - (g >> 1);
  const bool par = g & 1, epos = e >= 1;
  uint32_t selA = par ? 0x1044u : 0x4410u, selB0 = epos ? (par ? 0x3244u : 0x4432u) : 0x4444u, selB1 = epos ? 0x4444u : (par ? 0x3244u : 0x4432u);
  const float cl2 = 0.25f * 1.4426950408889634f;
  const float sc0 = rstd0 * cl2, sc1 = rstd1 * cl2;
  float c0[4];
#pragma unroll
  for (int k = 0; k < 4; k++) asm volatile("mov.b32 %0, %1;" : "=f"(c0[k]) : "f"((blk == 0 && w == 0) ? -INFINITY : 0.f));
  const uint32_t zero = (uint32_t)opaque_tid() & 0x80000000u;
  pin(selA); pin(selB0); pin(selB1);
  bar_sync(2 + wg, 128);
  TSW(2);
  {
    if (w != 0) {
#pragma unroll
      for (int h = 0; h < 4; h++) {
        ldsm4(&kb[h][0], ka - 16 * 272 + 64 * h);
        ldsm4t(&vb[h][0], va - 16 * 272 + 64 * h);
      }
    } else if (blk > 0) {
      uint4* src = halo - 8 * 256;
      uint4 hv[8];
      int it = 0;
      bool ok;
      do {
        ok = true;
#pragma unroll
        for (int i = 0; i < 8; i++) hv[i] = ld_tagged(src + i * 32);
#pragma unroll
        for (int i = 0; i < 8; i++) ok = ok && hv[i].x != UNSET;
      } while (!__all_sync(~0u, ok) && ++it < (1 << 20));
      if (layer == 0) {
#pragma unroll
        for (int i = 0; i < 2; i++) stg128(src + i * 128 + (lane >> 1) * 6, make_uint4(UNSET, UNSET, UNSET, UNSET));
      }
#pragma unroll
      for (int h = 0; h < 4; h++) {
        kb[h][0] = hv[2 * h].x; kb[h][1] = hv[2 * h].y; kb[h][2] = hv[2 * h].z; kb[h][3] = hv[2 * h].w;
        vb[h][0] = movm_t(hv[2 * h + 1].x); vb[h][1] = movm_t(hv[2 * h + 1].y);
        vb[h][2] = movm_t(hv[2 * h + 1].z); vb[h][3] = movm_t(hv[2 * h + 1].w);
      }
    } else {
#pragma unroll
      for (int h = 0; h < 4; h++)
#pragma unroll
        for (int k = 0; k < 4; k++) kb[h][k] = vb[h][k] = 0u;
    }
    TSW(3);
  }
  mbar_wait(bar + 8 * (B_DN + 15), layer);
  TSW(4);

  float vA0[4], vB0[4], vA1[4], vB1[4];
#pragma unroll
  for (int h = 0; h < 4; h++) {
    float S[4][4];
#pragma unroll
    for (int j = 0; j < 4; j++) {
      S[j][0] = S[j][1] = S[j][2] = S[j][3] = 0.f;
      if (j < 2) mma_bf16_c(S[j], qa[h], kb[h][2 * j], kb[h][2 * j + 1], c0);
      else mma_bf16(S[j], qa[h], kb[h][2 * j], kb[h][2 * j + 1]);
    }
    vA0[h] = par ? S[1][1] : S[1][0];
    vB0[h] = epos ? (par ? S[0][1] : S[0][0]) : (par ? S[2][1] : S[2][0]);
    vA1[h] = par ? S[2][3] : S[2][2];
    vB1[h] = epos ? (par ? S[1][3] : S[1][2]) : (par ? S[3][3] : S[3][2]);
  }
  float m0[4], m1[4];
#pragma unroll
  for (int h = 0; h < 4; h++) { m0[h] = fmaxf(vA0[h], vB0[h]); m1[h] = fmaxf(vA1[h], vB1[h]); }
#pragma unroll
  for (int o = 1; o <= 2; o <<= 1) {
#pragma unroll
    for (int h = 0; h < 4; h++) {
      m0[h] = fmaxf(m0[h], __shfl_xor_sync(~0u, m0[h], o));
      m1[h] = fmaxf(m1[h], __shfl_xor_sync(~0u, m1[h], o));
    }
  }
  float O0[4][4], O1[4][4], Z[4][4];
#pragma unroll
  for (int h = 0; h < 4; h++) {
    const float mm0 = -m0[h] * sc0, mm1 = -m1[h] * sc1;
    const float pA0 = ex2(fmaf(vA0[h], sc0, mm0)), pB0 = ex2(fmaf(vB0[h], sc0, mm0));
    const float pA1 = ex2(fmaf(vA1[h], sc1, mm1)), pB1 = ex2(fmaf(vB1[h], sc1, mm1));
    const uint32_t h0 = packbf(pA0, pB0), h1 = packbf(pA1, pB1);
    const uint32_t P0[4] = {prmt0(h0, selB0), h0 & zero, prmt0(h0, selA), prmt0(h1, selB0)};
    const uint32_t P1[4] = {prmt0(h0, selB1), prmt0(h1, selA), h1 & zero, prmt0(h1, selB1)};
#pragma unroll
    for (int k = 0; k < 4; k++) O0[h][k] = O1[h][k] = 0.f;
    mma_rowsum(Z[h], h0, h1);
    mma_bf16(O0[h], P0, vb[h][0], vb[h][1]); mma_bf16(O1[h], P0, vb[h][2], vb[h][3]);
    mma_bf16(O0[h], P1, vb[h][4], vb[h][5]); mma_bf16(O1[h], P1, vb[h][6], vb[h][7]);
  }
  if (lane == 0) mbar_arrive(bar + 8 * (B_OST + wg));
#pragma unroll
  for (int h = 0; h < 4; h += 2) {
    const float i0 = rcp_approx(Z[h][0]), i1 = rcp_approx(Z[h][2]), j0 = rcp_approx(Z[h + 1][0]), j1 = rcp_approx(Z[h + 1][2]);
    stg128(op + 128 * h, make_uint4(packbf(O0[h][0] * i0, O0[h][1] * i0), packbf(O1[h][0] * i0, O1[h][1] * i0),
                                   packbf(O0[h + 1][0] * j0, O0[h + 1][1] * j0), packbf(O1[h + 1][0] * j0, O1[h + 1][1] * j0)));
    stg128(op + 128 * h + 8, make_uint4(packbf(O0[h][2] * i1, O0[h][3] * i1), packbf(O1[h][2] * i1, O1[h][3] * i1),
                                            packbf(O0[h + 1][2] * j1, O0[h + 1][3] * j1), packbf(O1[h + 1][2] * j1, O1[h + 1][3] * j1)));
  }
  TSW(5);
  __syncwarp();
  if (elect_one()) red_relaxed(ocnt);
  TSW(6);
}

__device__ __forceinline__ void conv_load(uint32_t* A, uint32_t pe);
__device__ __forceinline__ void proj_phase(const Params& p, uint32_t sb, int layer, int rb, int q, uint32_t* A0, uint32_t* A1) {
  const int lane = opaque_tid() & 31;
  const int wg = __shfl_sync(~0u, opaque_tid() >> 7, 0), w = __shfl_sync(~0u, (opaque_tid() >> 5) & 3, 0);
  const bool TR = layer != 0;
  const int t = lane & 3;
  const uint32_t bar = sb + SM_BAR;
  const uint32_t rbx = sb + (P_R + wg) * PG;
  const uint32_t rsrc = sb + (wg ? 2 : P_R) * PG;
  const int blk = 16 * wg + rb;
  mbar_wait(bar + 8 * (B_RF + wg), layer);
  mbar_wait(bar + 8 * B_WOF, layer);
  const uint32_t stg = sb + (wg ? SM_KGT : SM_STG);
  if (layer) {
    const uint32_t pe = sb + cv_pe(wg, 1) + 4 * (16 + 16 * w + (lane >> 2) - 2 * t);
    mbar_wait(bar + 8 * B_PE, 1);
    conv_load(A0, pe);
    conv_load(A1, pe + 2 * 4480);
    __syncwarp();
    if (lane == 0) mbar_arrive(bar + 8 * B_AL);
  } else {
#pragma unroll
    for (int i = 0; i < 68; i++) {
      asm volatile("mov.b32 %0, 0;" : "=r"(A0[i]));
      asm volatile("mov.b32 %0, 0;" : "=r"(A1[i]));
    }
  }
  bool clean = false, staged = false;
#pragma unroll 1
  for (int attempt = 0; attempt < MAX_RETRY; attempt++) {
  uint32_t res[16];
  if (!TR) {
#pragma unroll
    for (int j = 0; j < 8; j += 2) {
      const int mi = lane >> 3;
      const int row = 16 * w + (lane & 7) + 8 * (mi & 1), ch = j + (mi >> 1);
      ldsm4(&res[2 * j], rsrc + row * 128 + ((ch ^ (row & 7)) << 4));
    }
  } else {
#pragma unroll
    for (int j = 0; j < 8; j += 2) {
      const int mi = lane >> 3;
      const int line = 8 * (j + (mi >> 1)) + (lane & 7), pc = 2 * w + (mi & 1);
      ldsm4t(&res[2 * j], rsrc + line * 128 + ((pc ^ (line & 7)) << 4));
    }
  }
  float acc[32];
#pragma unroll
  for (int j = 0; j < 16; j++) { acc[2 * j] = bf_lo(res[j]); acc[2 * j + 1] = bf_hi(res[j]); }
  acc_fence<32>(acc);
  if (wg) mbar_wait(bar + 8 * B_PG, layer);
  const int wg2 = __shfl_sync(~0u, opaque_tid() >> 7, 0);
  const uint64_t da0 = mkdesc(sb, 1024, 128, 0), db0 = mkdesc(sb, 8192, 1024, 1);
#pragma unroll
  for (int c = 0; c < 4; c++) {
    mbar_wait(bar + 8 * (B_OF + 4 * wg + c), layer);
    if (c == 0) TSW(7);
    const uint64_t da = da0 + (uint32_t)(o_page(wg2, c) * 512);
#pragma unroll
    for (int ks = 0; ks < 8; ks++) {
      if (ks % 4 == 0) { if (ks) wg_commit(); if (wg2) wg_wait<0>(); wg_fence(); }
      wgmma_ss<64, 0, 1>(acc, da + ks * 128, db0 + wo_page(2 * c + (ks >> 2)) * 512 + (ks & 3) * 128, 1);
    }
    wg_commit();
  }
  if (wg) mbar_wait(bar + 8 * B_KG, 0);
  wg_wait<0>();
  acc_fence<32>(acc);
  TSW(8);
  if (!clean) {
    const float chk = acc[0] + acc[2];
    clean = __all_sync(~0u, chk == chk);
    if (clean && lane == 0) mbar_arrive(bar + 8 * (B_PDONE + wg));
  }
  float s0 = 0.f, q0 = 0.f, s1 = 0.f, q1 = 0.f;
  uint32_t o[16];
#pragma unroll
  for (int j = 0; j < 8; j++) {
    const float a = acc[4 * j], b = acc[4 * j + 1], c = acc[4 * j + 2], d = acc[4 * j + 3];
    o[2 * j] = packbf(a, b);
    o[2 * j + 1] = packbf(c, d);
    s0 += a + b; q0 = fmaf(a, a, q0); q0 = fmaf(b, b, q0);
    s1 += c + d; q1 = fmaf(c, c, q1); q1 = fmaf(d, d, q1);
  }
#pragma unroll
  for (int j = 0; j < 8; j += 2) {
    const int mi = lane >> 3;
    const int line = 8 * (j + (mi >> 1)) + (lane & 7), pc = 2 * w + (mi & 1);
    stsm4t(rbx + line * 128 + ((pc ^ (line & 7)) << 4), o[2 * j], o[2 * j + 1], o[2 * j + 2], o[2 * j + 3]);
  }
#pragma unroll
  for (int o2 = 1; o2 <= 2; o2 <<= 1) {
    s0 += __shfl_xor_sync(~0u, s0, o2); q0 += __shfl_xor_sync(~0u, q0, o2);
    s1 += __shfl_xor_sync(~0u, s1, o2); q1 += __shfl_xor_sync(~0u, q1, o2);
  }
  {
    const int i = 2 * (lane >> 2) + (t & 1), k = (i * 11) >> 5;
    const float v = (t == 0) ? s0 : (t == 1) ? q0 : (t == 2) ? s1 : q1;
    sts32f(stg + k * 128 + (2 * w + (t >> 1)) * 16 + (i - 3 * k) * 4, v);
  }
  TSW(9);
  fence_async_smem();
  if (attempt == 0 && clean) {
    staged = true;
    __syncwarp();
    if (lane == 0) mbar_arrive(bar + 8 * (B_STG + wg));
  }
  if (!bar_or(2 + wg, 128, !clean)) break;
  const int rtp = mbar_test(bar + 8 * (B_RT + wg), 0);
  bool unset = false;
#pragma unroll
  for (int i = 0; i < 4; i++) unset |= lds32(sb + o_page(wg, i) * PG + (32 * w + lane) * 128) == UNSET;
  if (!bar_or(2 + wg, 128, unset)) break;
  if (w == 0 && elect_one()) {
    fence_async_smem();
    mbar_expect(bar + 8 * (B_RT + wg), 9 * PG);
    if (layer == 0) tma_ld(rsrc, &p.mapX, q * 64, blk * 64, bar + 8 * (B_RT + wg));
    else tma_ld(rsrc, &p.mapXT, blk * 64, DM + q * 64, bar + 8 * (B_RT + wg));
#pragma unroll 1
    for (int c = 0; c < 4; c++) bulk_ld(sb + o_page(wg, c) * PG, g_O + ((layer * 32 + blk) * 4 + c) * PG, 2 * PG, bar + 8 * (B_RT + wg));
  }
  mbar_wait(bar + 8 * (B_RT + wg), rtp);
  RETRY(0);
  }
  if (!clean && lane == 0) mbar_arrive(bar + 8 * (B_PDONE + wg));
  if (!staged && lane == 0) mbar_arrive(bar + 8 * (B_STG + wg));
  TSW(10);
}

__device__ __forceinline__ void conv_load(uint32_t* A, uint32_t pe) {
#pragma unroll
  for (int m = 0; m < 17; m++) {
    A[4 * m + 2] = lds32(pe + 4 * (64 * m - 8));
    A[4 * m + 0] = lds32(pe + 4 * (64 * m));
    A[4 * m + 1] = lds32(pe + 4 * (64 * m + 8));
    asm volatile("mov.b32 %0, %1;" : "=r"(A[4 * m + 3]) : "r"(A[4 * m + 0]));
  }
}
template <int M> __device__ __forceinline__ void conv_tri(float* acc, const uint32_t* A, uint64_t d) {
  if constexpr (M < 16) {
    wgmma_rs<64 - 8 * (M / 2), 0>(acc, A + 4 * M, d + (uint64_t)(64 + 4 * M), M != 0);
    conv_tri<M + 1>(acc, A, d);
  }
}
__device__ __forceinline__ void conv_mma0(float* acc, const uint32_t* A, uint64_t d) {
  wg_fence();
  conv_tri<0>(acc, A, d);
  wg_commit();
}
__device__ __forceinline__ void conv_mma1(float* acc, const uint32_t* A, uint64_t d, uint64_t ds, uint64_t df) {
  wg_fence();
#pragma unroll
  for (int m = 0; m < 17; m++) wgmma_rs<64, 0>(acc, A + 4 * m, d + (uint64_t)(4 * m), m != 0);
  wgmma_ss<64, 1, 0>(acc, ds, df, 1);
  wgmma_ss<64, 1, 0>(acc, ds + 128, df + 128, 1);
  wg_commit();
}
__device__ __forceinline__ void conv_store(float* acc, uint32_t pb, uint32_t over, int w) {
  acc_fence<32>(acc);
  const int l = opaque_tid() & 31, mt = l >> 3;
  int c = 2 * (63 - 8 * (mt >> 1) - (l & 7) + w) + (mt & 1);
  c ^= (c >> 3) & 1;
  const uint32_t a0 = pb + c * 16;
#pragma unroll
  for (int j = 0; j < 8; j += 2)
    stsm4t(j == 0 ? (c < 128 ? a0 : over + (c - 128) * 16) : a0 - 256 * j, packbf(acc[4 * j], acc[4 * j + 1]), packbf(acc[4 * j + 2], acc[4 * j + 3]),
           packbf(acc[4 * j + 4], acc[4 * j + 5]), packbf(acc[4 * j + 6], acc[4 * j + 7]));
}
__device__ __forceinline__ void conv_sums(uint32_t sb, int lc, int ht) {
  const int m = ht - 1;
  uint4 v[2][3];
#pragma unroll
  for (int c = 0; c < 2; c++)
#pragma unroll
    for (int k = 0; k < 3; k++) {
      const int mm = m - 1 + k;
      v[c][k] = lds128(sb + cv_u(lc + c) + (mm >= 0 ? (mm & 1) * CV_UH + (127 - (mm >> 1)) * 16 : 128 * 16));
    }
  const int ce = m + 2, co = m + 1;
#pragma unroll
  for (int c = 0; c < 2; c++) {
    const uint32_t x[8] = {v[c][0].z, v[c][0].w, v[c][1].x, v[c][1].y, v[c][1].z, v[c][1].w, v[c][2].x, v[c][2].y};
    float pv[16];
#pragma unroll
    for (int k = 0; k < 8; k++) { pv[2 * k] = bf_lo(x[k]); pv[2 * k + 1] = bf_hi(x[k]); }
    float t2[15], t4[13], s9[8], s7[8];
#pragma unroll
    for (int i = 0; i < 15; i++) t2[i] = pv[i] + pv[i + 1];
#pragma unroll
    for (int i = 0; i < 13; i++) t4[i] = t2[i] + t2[i + 2];
#pragma unroll
    for (int i = 0; i < 8; i++) {
      s9[i] = (t4[i] + t4[i + 4]) + pv[i + 8];
      s7[i] = (t4[i + 1] + t2[i + 5]) + pv[i + 7];
    }
    const uint4 e4 = make_uint4(packbf(s9[0], s9[1]), packbf(s9[2], s9[3]), packbf(s9[4], s9[5]), packbf(s9[6], s9[7]));
    if (ce < 128) sts128(sb + cv_se(lc + c) + ((ce ^ ((ce >> 3) & 7)) << 4), e4);
    else sts128(sb + cv_se(lc + c), make_uint4(0, 0, 0, 0));
    sts128(sb + cv_so(lc + c) + ((co ^ ((co >> 3) & 7)) << 4),
           make_uint4(packbf(s7[0], s7[1]), packbf(s7[2], s7[3]), packbf(s7[4], s7[5]), packbf(s7[6], s7[7])));
  }
}

template <int HALF, int NCH, int STEP = 1>
__device__ __forceinline__ void conv_epi(uint32_t sb, bf16* out, int lc, int c) {
  uint4 v[NCH][4], xr[NCH];
  const uint32_t sw = (c ^ ((c >> 3) & 1)) * 16;
#pragma unroll
  for (int u = 0; u < NCH; u++) {
#pragma unroll
    for (int k = 0; k < 4; k++) v[u][k] = lds128(sb + (HALF ? cv_pb1(lc + STEP * u, k) : cv_pb0(lc + STEP * u, k)) + sw);
    xr[u] = lds128(sb + cv_x(HALF, lc + STEP * u) + c * 16);
  }
#pragma unroll
  for (int u = 0; u < NCH; u++) {
    uint4 o;
    o.x = hadd2(xr[u].x, hadd2(hadd2(v[u][0].x, v[u][1].x), hadd2(v[u][2].x, v[u][3].x)));
    o.y = hadd2(xr[u].y, hadd2(hadd2(v[u][0].y, v[u][1].y), hadd2(v[u][2].y, v[u][3].y)));
    o.z = hadd2(xr[u].z, hadd2(hadd2(v[u][0].z, v[u][1].z), hadd2(v[u][2].z, v[u][3].z)));
    o.w = hadd2(xr[u].w, hadd2(hadd2(v[u][0].w, v[u][1].w), hadd2(v[u][2].w, v[u][3].w)));
    stg128(out + cv_chan(0, lc + STEP * u) * LSEQ + HALF * 1024 + c * 8, o);
  }
}

__device__ __forceinline__ bool prep_valid(const uint4 (&st)[6], const uint4 (&xr)[4]) {
  const uint32_t n = st[0].w & st[1].w & st[2].w & st[3].w & st[4].w & (st[5].w | st[5].y | st[5].z);
  return (n == __float_as_uint(8.f)) & (max(max(xr[0].x, xr[1].x), max(xr[2].x, xr[3].x)) != UNSET);
}
template <int HALF>
__device__ __forceinline__ void conv_prep(uint32_t sb, int layer, int cta, int i) {
  uint4 st[6], xr[4];
  const uint4* sp = (const uint4*)g_stats + (layer * 32 + HALF * 16 + (i >> 3)) * 48 + (i & 7);
  const uint4* xp = (const uint4*)g_xT + (2 * layer * DM + 2 * cta) * (LSEQ / 8) + HALF * 128 + i;
  if (!HALF) { pin(sp); pin(xp); }
  mbar_wait(sb + SM_BAR + 8 * (B_GB + HALF), layer);
  if (!HALF) TSW(13);
  auto fetch = [&]() {
#pragma unroll
    for (int k = 0; k < 6; k++) st[k] = ld_tagged(sp + 8 * k);
#pragma unroll
    for (int k = 0; k < 4; k++) xr[k] = ld_tagged(xp + cv_chan(0, k) * (LSEQ / 8));
  };
  if (HALF) {
#pragma unroll
    for (int k = 0; k < 6; k++) st[k] = lds128(sb + CV_ST + (i >> 3) * 768 + k * 128 + (i & 7) * 16);
#pragma unroll
    for (int k = 0; k < 4; k++) xr[k] = lds128(sb + cv_x(1, k) + i * 16);
  } else {
    fetch();
  }
  int it = 0;
  while (!__all_sync(~0u, prep_valid(st, xr)) && ++it < MAX_RETRY) { fetch(); RETRY(1); }
  if (!HALF || it) {
#pragma unroll
    for (int k = 0; k < 4; k++) sts128(sb + cv_x(HALF, k) + i * 16, xr[k]);
  }
  const uint32_t v[16] = {st[0].x, st[0].y, st[0].z, st[1].x, st[1].y, st[1].z, st[2].x, st[2].y, st[2].z, st[3].x, st[3].y, st[3].z, st[4].x, st[4].y, st[4].z, st[5].x};
  uint32_t rs[4], nm[4];
#pragma unroll
  for (int k = 0; k < 4; k++) {
    constexpr float E2 = 1e-5f * DM * DM;
    const float s0 = __uint_as_float(v[4 * k]), s1 = __uint_as_float(v[4 * k + 2]);
    const float r0 = rsqrt_approx(fmaxf(fmaf(__uint_as_float(v[4 * k + 1]), (float)DM, fmaf(-s0, s0, E2)), E2));
    const float r1 = rsqrt_approx(fmaxf(fmaf(__uint_as_float(v[4 * k + 3]), (float)DM, fmaf(-s1, s1, E2)), E2));
    const uint32_t r = packbf(r0, r1);
    rs[k] = r + 0x04800480u;
    nm[k] = packbf(-s0 * bf_lo(r), -s1 * bf_hi(r));
  }
  const uint32_t ud = sb + (i & 1) * CV_UH + (127 - 64 * HALF - (i >> 1)) * 16;
#pragma unroll
  for (int k = 0; k < 4; k++)
    sts128(ud + cv_u(k), make_uint4(hfma2(xr[k].x, rs[0], nm[0]), hfma2(xr[k].y, rs[1], nm[1]), hfma2(xr[k].z, rs[2], nm[2]), hfma2(xr[k].w, rs[3], nm[3])));
  fence_async_smem();
}

__device__ __forceinline__ void conv_phase(const Params& p, uint32_t sb, int layer, int cta, uint32_t* A0, uint32_t* A1) {
  const int tid = opaque_tid();
  const int wg = __shfl_sync(~0u, tid >> 7, 0), w = __shfl_sync(~0u, (tid >> 5) & 3, 0);
  const uint32_t bar = sb + SM_BAR;
  constexpr int CH2 = 4 * PG;
  bf16* xout = g_xT + ((2 * layer + 1) * DM + 2 * cta) * LSEQ;
  float acc[32];
  const uint32_t pe = sb + cv_pe(wg, 0) + 4 * (16 + 16 * w + ((tid & 31) >> 2) - 2 * (tid & 3));
  if (layer == 0) {
    mbar_wait(bar + 8 * (B_PDONE + 1), layer);
    mbar_wait(bar + 8 * B_PE, layer);
    conv_load(A0, pe);
    conv_load(A1, pe + CH2);
  }
  TSW(19);
  const uint64_t d0 = mkdesc(sb + cv_u(wg), CV_UH, 128, 0), d1 = d0 + (CH2 >> 4);
  mbar_wait(bar + 8 * B_U, layer);
  TSW(12);
  if (wg == 1) bar_sync(5, 256);
  conv_mma0(acc, A0, d0);
  if (wg == 0) bar_arrive(5, 256);
  mbar_wait(bar + 8 * (B_PDONE + 1), layer);
  {
    const int l = opaque_tid() & 31;
    if ((l & 15) < 2 * w) sts128(sb + cv_pb0(wg + 2 * (l >> 4), w) + (l & 15) * 16, make_uint4(0, 0, 0, 0));
  }
  wg_wait<0>();
  conv_store(acc, sb + cv_pb0(wg, w), sb + cv_pb1(wg, w), w);
  conv_mma0(acc, A1, d1);
  wg_wait<0>();
  conv_store(acc, sb + cv_pb0(2 + wg, w), sb + cv_pb1(2 + wg, w), w);
  TSW(13);
  bar_sync(2 + wg, 128);
  if (layer == 0 && wg == 1 && w == 0 && elect_one()) red_relaxed(&g_cnt[C_C * 32]);
  conv_epi<0, 2, 2>(sb, xout, wg, opaque_tid() & 127);
  TSW(14);
  mbar_arrive(bar + 8 * B_PUB);
  const uint64_t ds = mkdesc(sb + cv_se(wg), 8192, 1024, 1), df = mkdesc(sb + cv_fa(wg), 512, 128, 0);
  if (wg == 0) mbar_wait(bar + 8 * B_U1, layer);
  else bar_sync(6, 256);
  TSW(15);
  conv_mma1(acc, A0, d0, ds, df);
  if (wg == 0) bar_arrive(6, 256);
  wg_wait<0>();
  conv_store(acc, sb + cv_pb1(wg, w), sb + cv_dump(wg), w);
  TSW(16);
  bar_sync(2 + wg, 128);
  if (layer == 0 && wg == 1 && w == 0 && elect_one()) red_relaxed(&g_cnt[(C_C + 1) * 32]);
  conv_epi<1, 1>(sb, xout, wg, opaque_tid() & 127);
  mbar_arrive(bar + 8 * (B_PUB + 1));
  conv_mma1(acc, A1, d1, ds + 512, df + (CH2 >> 4));
  wg_wait<0>();
  conv_store(acc, sb + cv_pb1(2 + wg, w), sb + cv_dump(2 + wg), w);
  TSW(17);
  bar_sync(2 + wg, 128);
  conv_epi<1, 1>(sb, xout, 2 + wg, opaque_tid() & 127);
  mbar_arrive(bar + 8 * (B_PUB + 2));
  TSW(18);
}

#define FDELAY 480
__device__ __forceinline__ void final_tile(const Params& p, uint32_t buf, int ch0, int pos0, int barid, uint32_t hint) {
  const uint32_t t0 = (uint32_t)clock();
  const int tid = opaque_tid() & 127, lane = tid & 31, w = tid >> 5;
  const uint4* src = (const uint4*)(g_xT + (3 * DM + ch0 + (tid >> 3)) * LSEQ + pos0) + (tid & 7);
  const int ch = tid >> 3, row = 4 * (ch & 6) + 2 * (ch >> 3) + (ch & 1);
  uint32_t dst0 = buf + row * 128 + (((tid ^ row) & 7) << 4), dst1 = (dst0 ^ 64) + 512;
  uint32_t ld0 = buf + lane * 128 + ((((2 * w) ^ lane) & 7) << 4), ld1 = ld0 ^ 16;
  bf16* out = p.out + (pos0 + 16 * w + (lane >> 2)) * DM + ch0 + 8 * (lane & 3);
  pin(src); pin(out); pin(dst0); pin(dst1); pin(ld0); pin(ld1);
  if (hint) mbar_wait(hint, 0);
  else while ((uint32_t)clock() - t0 < FDELAY);
  uint4 a, b;
  int it = 0;
  do {
    if (it) RETRY(2);
    a = ld_tagged(src); b = ld_tagged(src + 16 * LSEQ / 8);
  } while (!__all_sync(~0u, a.x != UNSET && b.x != UNSET) && ++it < (1 << 20));
  sts128(dst0, a);
  sts128(dst1, b);
  bar_sync(barid, 128);
#pragma unroll
  for (int h = 0; h < 2; h++) {
    uint32_t r[4];
    ldsm4t(r, h ? ld1 : ld0);
    *(uint4*)(out + 8 * h * DM) = make_uint4(r[0], r[1], r[2], r[3]);
  }
}

struct cplx { float r, i; };
__device__ __forceinline__ cplx cmul(cplx a, cplx b) { return {fmaf(a.r, b.r, -a.i * b.i), fmaf(a.r, b.i, a.i * b.r)}; }
__device__ __forceinline__ cplx csqr(cplx a) { return {fmaf(a.r, a.r, -a.i * a.i), (a.r + a.r) * a.i}; }
__device__ __forceinline__ cplx cexp_l(float ar2, float ai, float l) {
  const float m = ex2(ar2 * l);
  const float x = ai * l;
  return {m * __cosf(x), m * __sinf(x)};
}

__device__ __forceinline__ void colsum_cta(const Params& p, uint32_t sb, int j, int tid) {
  const uint32_t bar = sb + SM_BAR;
  auto ld = [&](int i) {
    mbar_expect(bar + 8 * i, 3 * PG);
    tma_ld3(sb + (i & 7) * 3 * PG, &p.mapW3, (2 * j + (i & 1)) * 64, (i >> 1) * 64, 0, bar + 8 * i);
  };
  const int warp = __shfl_sync(~0u, tid >> 5, 0);
  if (warp == 12 && elect_one()) {
#pragma unroll
    for (int i = 0; i < 8; i++) mbar_init(bar + 8 * i, 1);
    asm volatile("fence.mbarrier_init.release.cluster;" ::: "memory");
    fence_async_smem();
#pragma unroll
    for (int i = 0; i < 8; i++) ld(i);
  }
  if (warp == 13 && elect_one()) {
#pragma unroll
    for (int i = 8; i < 24; i++) mbar_init(bar + 8 * i, i < 16 ? 1 : 12);
    asm volatile("fence.mbarrier_init.release.cluster;" ::: "memory");
  }
  const unsigned ep = ld_relaxed(&g_cnt[C_CS * 32]);
  bar_sync(0, NTHREADS);
  if (warp == 12 && elect_one()) {
#pragma unroll 1
    for (int i = 8; i < 16; i++) { mbar_wait(bar + 8 * (8 + i), 0); fence_async_smem(); ld(i); }
  }
  if (tid < 384) {
    const int lane = tid & 31, cc = tid & 7, r0 = (tid >> 3) & 15, part = tid >> 7;
    const uint32_t id = ((lane >> 2) == 2 * (lane & 3) ? 0x3f80u : 0u) | ((lane >> 2) == 2 * (lane & 3) + 1 ? 0x3f800000u : 0u);
    const uint32_t src = sb + part * PG + r0 * 128 + ((cc ^ (r0 & 7)) << 4);
    float s[2][2][4];
#pragma unroll
    for (int i = 0; i < 16; i++) s[i >> 3][(i >> 2) & 1][i & 3] = 0.f;
#pragma unroll 1
    for (int i2 = 0; i2 < 16; i2 += 2) {
#pragma unroll
      for (int h = 0; h < 2; h++) {
        const int i = i2 + h;
        mbar_wait(bar + 8 * i, 0);
        uint4 v[4];
#pragma unroll
        for (int k = 0; k < 4; k++) v[k] = lds128(src + (i & 7) * 3 * PG + k * 2048);
#pragma unroll
        for (int k = 0; k < 4; k++) {
          const uint32_t a[4] = {v[k].x, v[k].y, v[k].z, v[k].w};
          mma_bf16(s[h][0], a, id, 0u);
          mma_bf16(s[h][1], a, 0u, id);
        }
        __syncwarp();
        if (i < 8 && lane == 0) mbar_arrive(bar + 8 * (16 + i));
      }
    }
    const uint32_t red = sb + 24 * PG;
#pragma unroll
    for (int h = 0; h < 2; h++)
#pragma unroll
      for (int k = 0; k < 2; k++) sts128f(red + (r0 * 384 + h * 192 + part * 64 + cc * 8 + k * 4) * 4, s[h][k][0], s[h][k][1], s[h][k][2], s[h][k][3]);
    bar_sync(1, 384);
    float tot = 0.f;
#pragma unroll
    for (int k = 0; k < 16; k++) tot += __uint_as_float(lds32(red + (k * 384 + tid) * 4));
    asm volatile("st.relaxed.gpu.global.v2.u32 [%0], {%1,%2};" ::"l"(&g_colsum[j * 384 + tid]), "r"(__float_as_uint(tot)), "r"(ep / NCTA + 1) : "memory");
    const uint4 u = make_uint4(UNSET, UNSET, UNSET, UNSET);
    if (tid < 256) {
#pragma unroll 1
      for (int s = 0; s < 4; s++) {
        const int n = (s == 1 || s == 2) ? 32 : 16;
        uint4* buf = s == 1 ? (uint4*)g_O + 131072 : (uint4*)g_xT + (s + !s) * 131072;
#pragma unroll 4
        for (int i = 0; i < n; i++) stg128(buf + (j * n + i) * 1024 + (tid >> 1) * 8 + (tid & 1), u);
        if (n == 16) {
#pragma unroll 4
          for (int i = 0; i < 8; i++) stg128(buf + (256 + j * 64 + i * 8 + (tid >> 5)) * 256 + (s ? 0 : 128) + ((tid & 31) >> 1) * 8 + (tid & 1), u);
        }
        if (s == 3) {
#pragma unroll 4
          for (int i = 0; i < 32; i++) stg128(buf + (256 + j * 64 + 2 * i + (tid >> 7)) * 256 + 128 + (tid & 127), u);
        }
        bar_sync(2, 256);
        if (tid == 32 * s) red_release(&g_cnt[(C_R + s) * 32]);
      }
    }
  }
}

constexpr int KB = 4, KW = 2;
struct ModeIn { uint32_t ar, ai, br, bi, cr, ci; bf16 logdt; };
__device__ __forceinline__ ModeIn load_modes(const Params& p, int d, int m) {
  const int i = d * 64 + m;
  return {((const uint32_t*)p.a_re)[i], ((const uint32_t*)p.a_im)[i], ((const uint32_t*)p.b_re)[i], ((const uint32_t*)p.b_im)[i],
          ((const uint32_t*)p.c_re)[i], ((const uint32_t*)p.c_im)[i], p.log_dt[d]};
}
__device__ __forceinline__ void kernel_gen(uint32_t sb, int cta, int ht, ModeIn in, const ModeIn& in1) {
  const uint32_t bst = sb + SM_KGB + ((ht & 63) >> 2) * 144 + (ht & 3) * 4 + (ht >> 6) * 16;
  const uint64_t db = mkdesc(sb + SM_KGB, 144, 2304, 0);
  const float e0 = (float)(8 * (((ht & 32) >> 1) + ((ht & 31) >> 2)));
  float T[20];
#pragma unroll
  for (int i = 0; i < 20; i++) T[i] = 0.f;
  float k0 = 0.f;
#pragma unroll 1
  for (int pass = 0; pass < 4; pass++) {
    {
      const int sh = (pass & 1) ? 0 : 16;
      auto val = [&](uint32_t v) { return __uint_as_float((v << sh) & 0xffff0000u); };
      const float dt = __bfloat162float(__float2bfloat16_rn(expf(__bfloat162float(in.logdt))));
      const float ar2 = dt * val(in.ar) * 1.4426950408889634f, ai = dt * val(in.ai);
      const cplx c = cmul({val(in.cr), -val(in.ci)}, {dt * val(in.br), -dt * val(in.bi)});
      k0 += c.r;
      const cplx z1 = cexp_l(ar2, -ai, 1.f), z256 = cexp_l(ar2, -ai, 256.f), z64 = cexp_l(ar2, ai, 64.f);
      const cplx z2 = csqr(z1), z512 = csqr(z256);
      auto put = [&](int j, cplx v) { sts32(bst + (j >> 2) * 2304 + (j & 3) * 32, packbf(v.r, v.i)); };
      sts128f(sb + SM_KGT + ht * 16, ar2, ai, z64.r, z64.i);
      const cplx c1 = cmul(c, z1), c2 = cmul(c, z2), c3 = cmul(c1, z2), c4 = cmul(c2, z2);
      const cplx c5 = cmul(c3, z2), c6 = cmul(c4, z2), c7 = cmul(c5, z2), c8 = cmul(c6, z2);
      put(0, c1); put(1, c2); put(2, c3); put(3, c4); put(4, c5); put(5, c6); put(6, c7); put(7, c8);
      const cplx c260 = cmul(c4, z256), c264 = cmul(c8, z256), c520 = cmul(c8, z512), c776 = cmul(c264, z512);
      put(8, cmul(c2, z256)); put(9, c260); put(10, cmul(c6, z256)); put(11, c264);
      put(12, cmul(c4, z512)); put(13, c520); put(14, cmul(c260, z512)); put(15, c776);
      const cplx c1032 = cmul(c520, z512), c1288 = cmul(c776, z512);
      put(16, c1032); put(17, c1288); put(18, cmul(c1032, z512)); put(19, cmul(c1288, z512));
    }
    fence_async_smem();
    bar_sync(4, 128);
    const uint32_t tb = sb + SM_KGT + (ht & 67) * 16;
    float2 nx[KB];
#pragma unroll
    for (int s = 0; s < KB; s++) nx[s] = lds64f(tb + s * 64);
#pragma unroll
    for (int q = 0; q < 16 / KB; q++) {
      uint32_t A[2 * KB];
      float2 cur[KB], z[KB];
#pragma unroll
      for (int s = 0; s < KB; s++) { cur[s] = nx[s]; z[s] = lds64f(tb + (KB * q + s) * 64 + 8); }
      if (q < 16 / KB - 1) {
#pragma unroll
        for (int s = 0; s < KB; s++) nx[s] = lds64f(tb + (KB * q + KB + s) * 64);
      }
      if (q >= KW) wg_wait<KW - 1>();
#pragma unroll
      for (int s = 0; s < KB; s++) {
        const cplx lo = cexp_l(cur[s].x, cur[s].y, e0), hi = cmul(lo, {z[s].x, z[s].y});
        A[2 * s] = packbf(lo.r, lo.i);
        A[2 * s + 1] = packbf(hi.r, hi.i);
      }
      wg_fence();
#pragma unroll
      for (int k = 0; k < KB / 2; k++) wgmma_rs<40, 0>(T, A + 4 * k, db + 9 * KB * q + 18 * k, (pass & 1) | q | k);
      wg_commit();
    }
    wg_wait<0>();
    acc_fence<20>(T);
    if (ht == 0) TS(4 + pass);
    if (pass & 1) {
      const int h2 = opaque_tid() - 256, w = h2 >> 5, lane = h2 & 31, t = lane & 3, chn = h2 >> 6, m = h2 & 63, i0 = 16 * (w & 1) + (lane >> 2);
      const int lc = (pass & 2) + chn;
      const uint32_t kc = sb + kc_off(lc);
      auto put = [&](int idx, float v) {
        sts16(kc + idx * 2, __bfloat16_as_ushort(__float2bfloat16_rn(v)));
      };
#pragma unroll
      for (int hi = 0; hi < 2; hi++) {
        const int i = i0 + 8 * hi;
        float v[5];
#pragma unroll
        for (int j = 0; j < 5; j++) v[j] = chn ? T[4 * j + 2 * hi + 1] : T[4 * j + 2 * hi];
        put(8 * i + 1 + t, v[0]);
        put(8 * i + 5 + t, v[1]);
        put(257 + 4 * i + t, v[2]);
        put(385 + 2 * i + (t & 1) + 64 * (t >> 1), v[3]);
        put(513 + i + 32 * t, v[4]);
      }
#pragma unroll
      for (int o = 16; o > 0; o >>= 1) k0 += __shfl_xor_sync(~0u, k0, o);
      if (lane == 0) sts32f(sb + SM_RED + 4 * w, k0);
      bar_sync(4, 128);
      if (m == 0) put(0, k0 + __uint_as_float(lds32(sb + SM_RED + 4 * w + 4)) + __uint_as_float(lds16(sb + SM_RED + 24 + 2 * lc) << 16));
      k0 = 0.f;
      in = in1;
    }
  }
}

__device__ __forceinline__ void expand_taps(uint32_t sb, int ht, int early) {
  const int ch = ht >> 5, lane = ht & 31;
  const uint32_t kc = sb + kc_off(ch);
  const uint32_t dst0 = sb + cv_pe(ch, early);
  auto put = [&](int G, uint32_t v0, uint32_t v1, uint32_t v2, uint32_t v3, uint32_t v4, uint32_t v5, uint32_t v6, uint32_t v7, uint32_t v8) {
    const uint32_t dst = dst0 + G * 32;
    sts128(dst, make_uint4(v1 | (v0 << 16), v2 | (v1 << 16), v3 | (v2 << 16), v4 | (v3 << 16)));
    sts128(dst + 16, make_uint4(v5 | (v4 << 16), v6 | (v5 << 16), v7 | (v6 << 16), v8 | (v7 << 16)));
  };
  {
    const uint4 q = lds128(kc + lane * 16);
    const uint32_t pv = lane ? lds16(kc + lane * 16 - 2) : 0u;
    const uint32_t dst = dst0 + (lane + 2) * 32;
    sts128(dst, make_uint4(__byte_perm(q.x, pv, 0x5410), __byte_perm(q.x, q.x, 0x1032), __byte_perm(q.y, q.x, 0x7610), __byte_perm(q.y, q.y, 0x1032)));
    sts128(dst + 16, make_uint4(__byte_perm(q.z, q.y, 0x7610), __byte_perm(q.z, q.z, 0x1032), __byte_perm(q.w, q.z, 0x7610), __byte_perm(q.w, q.w, 0x1032)));
    if (lane < 4) sts128(dst0 + lane * 16, make_uint4(0, 0, 0, 0));
  }
  uint32_t a[5], b[2][3];
  {
    const uint32_t s1 = kc + 2 * (256 + 4 * lane);
#pragma unroll
    for (int k = 0; k < 5; k++) a[k] = lds16(s1 + 2 * k);
#pragma unroll
    for (int u = 0; u < 2; u++) {
      const uint32_t s2 = kc + 2 * (384 + 2 * (lane + 32 * u));
#pragma unroll
      for (int k = 0; k < 3; k++) b[u][k] = lds16(s2 + 2 * k);
    }
  }
  const uint32_t k255 = lds16(kc + 2 * 255), k1024 = lds16(kc + 2 * 512);
  put(34 + lane, lane == 0 ? k255 : a[0], a[0], a[0], a[1], a[2], a[2], a[2], a[3], a[4]);
#pragma unroll
  for (int u = 0; u < 2; u++) put(66 + lane + 32 * u, b[u][0], b[u][0], b[u][0], b[u][0], b[u][1], b[u][1], b[u][1], b[u][2], b[u][2]);
  if (lane < 10) {
    const uint32_t v = lane == 0 ? k1024 : 0u;
    put(130 + lane, v, v, v, v, v, v, 0u, 0u, 0u);
  }
}
__device__ __forceinline__ void expand_far(uint32_t sb, int ht) {
  const int ch = ht >> 5, lane = ht & 31;
  const uint32_t kc = sb + kc_off(ch) + 2 * (513 + 2 * (63 - lane)), dst = sb + cv_fa(ch) + lane * 16;
#pragma unroll
  for (int ty = 0; ty < 2; ty++) {
    uint32_t v[16];
#pragma unroll
    for (int k = 0; k < 16; k++) v[k] = (k < 8 || 63 - lane - 4 * k >= 0) ? lds16(kc + 2 * (1 - ty) - 16 * k) : 0u;
#pragma unroll
    for (int u = 0; u < 2; u++)
      sts128(dst + ty * 2048 + u * 512, make_uint4(v[8 * u] | (v[8 * u + 1] << 16), v[8 * u + 2] | (v[8 * u + 3] << 16), v[8 * u + 4] | (v[8 * u + 5] << 16), v[8 * u + 6] | (v[8 * u + 7] << 16)));
    sts128(dst + ty * 2048 + 1024, make_uint4(0, 0, 0, 0));
  }
}

__host__ __device__ constexpr int bar_count(int i) {
  return i == B_LN ? 2 : i == B_AL ? 8 : i < B_STG ? 1 : i < B_PE ? 4 : i >= B_PUB ? 256 : 128;
}
__host__ __device__ constexpr bool bar_first(int i) { return i < B_WF + 2 && (i & 7) < 2; }

__global__ void __launch_bounds__(NTHREADS, 1) fused_kernel(const __grid_constant__ Params p) {
  extern __shared__ __align__(1024) uint8_t smem[];
  constexpr uint32_t sb = 1024;
  if (s32(smem) != sb) return;
  const int tid = threadIdx.x, lane = tid & 31;
  const int warp = __shfl_sync(~0u, tid >> 5, 0);
  if (tid == 32) {
    asm volatile("prefetch.tensormap [%0];" ::"l"(&p.mapX) : "memory");
    asm volatile("prefetch.tensormap [%0];" ::"l"(&p.mapW3) : "memory");
  }
  const int cta = blockIdx.x - (gridDim.x == NCTA + 4 ? 0 : 4);
  if ((unsigned)cta >= NCTA) {
    if (blockIdx.x < NCTA + 4) colsum_cta(p, sb, blockIdx.x & 3, tid);
    return;
  }
  const int rb = ((cta >> 4) & 3) * 4 + ((cta >> 2) & 3), hg = (cta >> 6) * 4 + (cta & 3);
  const uint32_t bar = sb + SM_BAR;
  auto ld_x0 = [&](int half, int c) {
    const uint32_t b = bar + 8 * (B_XF + 8 * half + c);
    mbar_expect(b, PG);
    tma_ld(sb + x_page(half, c) * PG, &p.mapX, c * 64, (16 * half + rb) * 64, b);
  };
  auto ld_x1 = [&](int half, int c, int b0) {
    const uint32_t b = bar + 8 * b0;
    mbar_expect(b, PG);
    tma_ld(sb + (8 * half + c) * PG, &p.mapXT, (16 * half + rb) * 64, DM + c * 64, b);
  };
  auto ld_w = [&](int c) {
    const uint32_t b = bar + 8 * (B_WF + c);
    mbar_expect(b, 3 * PG);
    tma_ld3(sb + w_page(c) * PG, &p.mapW3, hg * 64, c * 64, 0, b);
  };

  if (tid == 0) TS(0);
  if (tid == 480) LTS(0);
  if (warp == 0 && elect_one()) {
#pragma unroll
    for (int i = 0; i < B_WF + 2; i++)
      if (bar_first(i)) mbar_init(bar + 8 * i, 1);
    asm volatile("fence.mbarrier_init.release.cluster;" ::: "memory");
    fence_async_smem();
    ld_x0(0, 0);
    ld_w(0); ld_x0(1, 0);
    ld_x0(0, 1); ld_w(1); ld_x0(1, 1);
    TS(1);
  }
  __syncwarp();
  if (warp >= 1 && warp < 8 && elect_one()) {
    if (warp < 4) {
#pragma unroll
      for (int i = 2; i < 8; i++) mbar_init(bar + 8 * (8 * warp - 8 + i), 1);
    } else {
#pragma unroll
      for (int i = 0; i < 12; i++) mbar_init(bar + 8 * (12 * warp - 24 + i), 1);
    }
    asm volatile("fence.mbarrier_init.release.cluster;" ::: "memory");
  }
  if (warp == 15 && elect_one()) {
#pragma unroll
    for (int i = 72; i < B_COUNT; i++) mbar_init(bar + 8 * i, bar_count(i));
    asm volatile("fence.mbarrier_init.release.cluster;" ::: "memory");
  }

  if (warp < 8) {
    bar_sync(0, NTHREADS);
    asm volatile("setmaxnreg.inc.sync.aligned.u32 %0;" ::"n"(R_CONS));
    const int cw = __shfl_sync(~0u, opaque_tid() >> 5, 0);
    const int wg = cw >> 2, w = cw & 3;
    if (tid == 0) TS(2);
#pragma unroll 1
    for (int layer = 0; layer < 2; layer++) {
      attn_phase(p, sb, layer, rb, hg, wg, w);
      uint32_t A0[68], A1[68];
      proj_phase(p, sb, layer, rb, hg, A0, A1);
      conv_phase(p, sb, layer, cta, A0, A1);
    }
    if (tid == 128) TS(8);
    final_tile(p, sb + (16 + wg) * PG, 256 * wg + 32 * (cta >> 4), 1024 + 64 * (cta & 15), 2 + wg, wg ? 0 : bar + 8 * (B_TF + 1));
    if (tid == 128) TS(9);
    if (tid == 128) LTS(1);
    if (tid == 0) LTE();
  } else if (warp < 12) {
    asm volatile("setmaxnreg.dec.sync.aligned.u32 %0;" ::"n"(R_HELP));
    const int ht = tid - 256;
    {
      unsigned ep0 = 0;
      if (ht == 0) ep0 = ld_relaxed(&g_cnt[C_CS * 32]);
      const bf16 dsk = p.dskip[cv_chan(cta, ht & 3)];
      const ModeIn in0 = load_modes(p, cv_chan(cta, ht >> 6), ht & 63), in1 = load_modes(p, cv_chan(cta, 2 + (ht >> 6)), ht & 63);
      if (ht < 48) sts128f(sb + SM_STG + ht * 16, 0.f, 0.f, 0.f, 1.f);
      bar_sync(0, NTHREADS);
      if (ht == 0) {
        sts32(sb + SM_EP, ep0);
        mbar_arrive(bar + 8 * B_EP);
      }
      if (ht >= 124) sts16(sb + SM_RED + 24 + 2 * (ht & 3), __bfloat16_as_ushort(dsk));
      kernel_gen(sb, cta, ht, in0, in1);
      if (ht < 48) sts128f(sb + SM_KGT + ht * 16, 0.f, 0.f, 0.f, 1.f);
      fence_async_smem();
      bar_sync(4, 128);
      if (ht == 0) mbar_arrive(bar + 8 * B_KG);
    }
#pragma unroll 1
    for (int layer = 0; layer < 2; layer++) {
      const int early = layer;
      if (early) mbar_wait(bar + 8 * (B_DN + 13), 1);
      mbar_wait(bar + 8 * (early ? B_OST : B_PDONE), layer);
      expand_taps(sb, opaque_tid() - 256, early);
      mbar_arrive(bar + 8 * B_PE);
      TSW(0);
      mbar_wait(bar + 8 * B_PDONE, layer);
      expand_far(sb, opaque_tid() - 256);
      {
        const int i = opaque_tid() - 256;
        if (i < 32) sts128(sb + cv_u(i >> 3) + ((i >> 2) & 1) * CV_UH + (128 + (i & 3)) * 16, make_uint4(0, 0, 0, 0));
        mbar_wait(bar + 8 * B_RC, layer);
        conv_prep<0>(sb, layer, cta, i);
        mbar_arrive(bar + 8 * B_U);
      }
      mbar_wait(bar + 8 * (B_PDONE + 1), layer);
      bar_sync(4, 128);
#pragma unroll 1
      for (int lc = 0; lc < 4; lc += 2) {
        conv_sums(sb, lc, opaque_tid() - 256);
        TSW(1 + lc);
      }
      conv_prep<1>(sb, layer, cta, opaque_tid() - 256);
      mbar_arrive(bar + 8 * B_U1);
      TSW(4);
      if (layer == 0) {
        const int c = __shfl_sync(~0u, (opaque_tid() >> 5) & 3, 0);
        int phase = 0;
#pragma unroll 1
        for (int k = 0; k < 3; k++) {
          const int page = (k ? 4 + 4 * k : 0) + c, b = B_XR + 4 * (k & 1) + c;
          const uint32_t a = sb + page * PG + lane * 128 + (lane & 7) * 16 + (lane >> 3) * 4;
          int it = k == 2 ? phase : 0;
#pragma unroll 1
          for (; it < MAX_RETRY; it++) {
            mbar_wait(bar + 8 * b, it & 1);
            const uint32_t v0 = lds32(a), v1 = lds32(a + 4096);
            if (__all_sync(~0u, v0 != UNSET && v1 != UNSET)) break;
            if (elect_one()) { fence_async_smem(); ld_x1(page >> 3, page & 7, b); }
            __syncwarp();
            RETRY(3);
          }
          if (k == 0) phase = it + 1;
          if (lane == 0) mbar_arrive(bar + 8 * (B_XF + page));
        }
      }
    }
#pragma unroll 1
    for (int k = 0; k < 2; k++) final_tile(p, sb + 18 * PG + k * 4096, 256 * k + 32 * (cta >> 4), 64 * (cta & 15), 4, bar + 8 * B_TF);
    if (ht == 0) LTE();
  } else {
    asm volatile("setmaxnreg.dec.sync.aligned.u32 %0;" ::"n"(R_AGENT));
    bar_sync(0, NTHREADS);
    auto done = [&](int half, int c, int layer) { mbar_wait(bar + 8 * (B_DN + 8 * half + c), layer); };
    auto publish = [&](int layer, int k) {
      unsigned* cnt = &g_cnt[(layer ? C_F + 8 * k + (cta >> 4) : C_C + k) * 32];
      pin(cnt);
      mbar_wait(bar + 8 * (B_PUB + k), layer);
      if (layer || k == 2) red_relaxed(cnt);
      if (!layer && k == 0) red_release(&g_cnt[(C_C + 3) * 32]);
      TS(16 + layer * 56 + 40 + 7 + k);
    };
    if (warp == 12) {
      if (elect_one()) {
#pragma unroll 1
        for (int layer = 0; layer < 2; layer++) {
          auto ld_xe = [&](int c) {
            const uint32_t b = bar + 8 * (B_XF + c);
            mbar_expect(b, PG);
            if (layer == 0) tma_ld(sb + x_page(0, c) * PG, &p.mapX, c * 64, rb * 64, b);
            else tma_ld(sb + x_page(0, c) * PG, &p.mapXT, rb * 64, DM + c * 64, b);
          };
          if (layer == 0) {
            ld_x0(0, 2); ld_w(2); ld_x0(1, 2);
            if (hg >= 3) {
              mbar_expect(bar + 8 * B_SC, PG);
              tma_ld(sb + P_R * PG, &p.mapX, hg * 64, rb * 64, bar + 8 * B_SC);
            }
            if (rb < 4) tma_prefetch3(&p.mapW3, hg * 64, (4 + rb) * 64, 0);
            ld_x0(0, 3); ld_w(3); ld_x0(1, 3); ld_x0(0, 4); ld_x0(1, 4);
            done(0, 0, 0); done(1, 0, 0);
            ld_w(4);
            ld_x0(1, 5); ld_x0(1, 6); ld_x0(1, 7);
            done(0, 1, 0); done(1, 1, 0);
            ld_w(5);
            if (rb < 8) tma_prefetch5(&p.mapWo, hg * 64, rb * 2);
            done(0, 2, 0);
            fence_async_smem();
            ld_xe(5); ld_xe(6); ld_xe(7);
          } else {
            mbar_wait(bar + 8 * B_PDONE, 0);
            mbar_wait(bar + 8 * (B_PDONE + 1), 0);
            mbar_wait(bar + 8 * B_U, 0);
            ld_w(0); ld_w(1);
            mbar_wait(bar + 8 * B_U1, 0);
            fence_async_smem();
            ld_w(2);
            mbar_wait(bar + 8 * (B_PUB + 2), 0);
            fence_async_smem();
            ld_w(3);
            spin_until(&g_cnt[(C_C + 3) * 32], ((lds32(sb + SM_EP) / NCTA) + 1) * NCTA);
            fence_async_global();
            if (hg >= 3) {
              mbar_expect(bar + 8 * B_SC, PG);
              tma_ld(sb + P_R * PG, &p.mapXT, rb * 64, DM + hg * 64, bar + 8 * B_SC);
            }
            ld_xe(4);
            done(0, 2, 1);
            fence_async_smem();
            ld_xe(5); ld_xe(6); ld_xe(7);
            done(1, 0, 1);
            ld_w(4);
            done(1, 1, 1);
            ld_w(5);
          }
          done(1, 2, layer);
          fence_async_smem();
          ld_w(6); ld_w(7);
          auto ld_res = [&](int half) {
            const uint32_t b = bar + 8 * (B_RF + half);
            mbar_expect(b, PG);
            if (layer == 0) tma_ld(sb + (half ? 2 : P_R) * PG, &p.mapX, hg * 64, (16 * half + rb) * 64, b);
            else tma_ld(sb + (half ? 2 : P_R) * PG, &p.mapXT, (16 * half + rb) * 64, DM + hg * 64, b);
          };
          done(0, 4, layer); done(1, 3, layer);
          fence_async_smem();
          mbar_expect(bar + 8 * B_WOF, 8 * PG);
#pragma unroll 1
          for (int c = 0; c < 8; c++) {
            if (c == 5) { ld_res(0); done(1, 4, layer); }
            tma_ld5(sb + wo_page(c) * PG, &p.mapWo, hg * 64, c * 2, bar + 8 * B_WOF);
          }
          done(0, 7, layer);
          fence_async_global();
          ld_res(1);
          if (layer) mbar_wait(bar + 8 * B_RS, 0);
          fence_async_global();
#pragma unroll
          for (int half = 0; half < 2; half++) {
            float* stats = g_stats + (layer * 32 + 16 * half + rb) * 192;
            unsigned* cnt = &g_cnt[(C_G + 2 * layer + half) * 32];
            mbar_wait(bar + 8 * (B_PDONE + half), layer);
            { const uint32_t t0 = (uint32_t)clock(); while ((uint32_t)clock() - t0 < 100); }
            red_relaxed(cnt);
            mbar_wait(bar + 8 * (B_STG + half), layer);
            bulk_red_add_f32(stats, sb + (half ? SM_KGT : SM_STG), 768);
            tma_st(&p.mapXT, (16 * half + rb) * 64, 2 * layer * DM + hg * 64, sb + (P_R + half) * PG);
            bulk_commit();
            if (half == 0) mbar_arrive(bar + 8 * B_PG);
            bulk_wait_read();
            mbar_arrive(bar + 8 * (B_PST + half));
          }
        }
      }
    } else if (warp == 13) {
      mbar_wait(bar + 8 * B_EP, 0);
      const unsigned e1 = (lds32(sb + SM_EP) / NCTA) + 1;
      auto ld_o = [&](int layer) {
#pragma unroll 1
        for (int half = 0; half < 2; half++) {
          done(1, 7, layer);
          mbar_wait(bar + 8 * B_OST, layer);
          if (half) mbar_wait(bar + 8 * (B_OST + 1), layer);
          fence_async_smem();
#pragma unroll
          for (int c = 0; c < 4; c++) mbar_expect(bar + 8 * (B_OF + 4 * half + c), 2 * PG);
          const bf16* src = g_O + (layer * 32 + 16 * half + rb) * 4 * PG;
          uint32_t dst0 = sb + o_page(half, 0) * PG;
          pin(src); pin(dst0);
          spin_hint(&g_cnt[(C_O + layer * 32 + 16 * half + rb) * 32], e1 * 32);
#pragma unroll
          for (int c = 0; c < 4; c++) {
            if (c == 2 && half && layer) { mbar_wait(bar + 8 * B_AL, 0); fence_async_smem(); }
            bulk_ld(c ? sb + o_page(half, c) * PG : dst0, src + c * PG, 2 * PG, bar + 8 * (B_OF + 4 * half + c));
          }
        }
      };
      if (elect_one()) {
        mbar_wait(bar + 8 * (B_WF + 2), 0);
        asm volatile("prefetch.tensormap [%0];" ::"l"(&p.mapXT) : "memory");
        asm volatile("prefetch.tensormap [%0];" ::"l"(&p.mapWo) : "memory");
        spin_until(&g_cnt[C_Z * 32], e1 * NCTA);
        mbar_arrive(bar + 8 * B_ZF);
        TS(3);
        ld_o(0);
#pragma unroll 1
        for (int k = 0; k < 3; k++) {
          mbar_wait(bar + 8 * (B_PUB + k), 0);
          if (k == 2) {
#pragma unroll 1
            for (int c = 0; c < 4; c++) mbar_wait(bar + 8 * (B_XF + c), 1);
          }
          fence_async_smem();
          uint32_t b = bar + 8 * (B_XR + 4 * (k & 1)), dst = sb + (k ? 4 + 4 * k : 0) * PG, c0 = ((k ? 16 : 0) + rb) * 64, c1 = DM + (k & 2) * 128;
#pragma unroll
          for (int c = 0; c < 4; c++) mbar_expect(b + 8 * c, PG);
          pin(b); pin(dst); pin(c0); pin(c1);
          spin_hint(&g_cnt[(C_C + k) * 32], e1 * NCTA);
          TS(10 + k);
#pragma unroll
          for (int c = 0; c < 4; c++) tma_ld(dst + c * PG, &p.mapXT, c0, c1 + c * 64, b + 8 * c);
        }
        ld_o(1);
#pragma unroll 1
        for (int k = 0; k < 2; k++) {
          mbar_wait(bar + 8 * (B_PUB + k), 1);
          spin_hint(&g_cnt[(C_F + 8 * k + (cta >> 4)) * 32], e1 * 16);
          mbar_arrive(bar + 8 * (B_TF + k));
        }
      }
    } else if (warp == 14) {
      mbar_wait(bar + 8 * B_EP, 0);
      const unsigned e1 = (lds32(sb + SM_EP) / NCTA) + 1;
      done(0, 4, 0);
      {
        const uint2* cp = g_colsum + (hg * 192 + lane);
        uint2 v[6];
        bool ok;
        int it = 0;
        do {
          ok = true;
#pragma unroll
          for (int i = 0; i < 6; i++) {
            asm volatile("ld.relaxed.gpu.global.v2.u32 {%0,%1}, [%2];" : "=r"(v[i].x), "=r"(v[i].y) : "l"(cp + 32 * i) : "memory");
            ok = ok && v[i].y == e1;
          }
          if (++it > (1 << 22)) __trap();
        } while (!__all_sync(~0u, ok));
#pragma unroll
        for (int i = 0; i < 6; i++) sts32f(sb + SM_CS + 4 * (lane + 32 * i), __uint_as_float(v[i].x));
      }
      __syncwarp();
      if (elect_one()) {
        mbar_wait(bar + 8 * B_ZF, 0);
        mbar_arrive(bar + 8 * B_LN);
        red_relaxed(&g_cnt[C_CS * 32]);
        TS(13);
#pragma unroll 1
        for (int layer = 0; layer < 2; layer++) {
          const uint32_t b = bar + 8 * (B_GB + 1);
          const bf16* xin = g_xT + ((size_t)2 * layer * DM + 2 * cta) * LSEQ + 1024;
          const float* stats = g_stats + (layer * 32 + 16) * 192;
          mbar_wait(bar + 8 * B_PST, layer);
          spin_hint(&g_cnt[(C_G + 2 * layer) * 32], e1 * NCTA);
          mbar_arrive(bar + 8 * B_GB);
          mbar_wait(bar + 8 * (B_PST + 1), layer);
          fence_async_smem();
          mbar_expect(b, 12288 + PG);
          pin(stats); pin(xin);
          spin_hint(&g_cnt[(C_G + 2 * layer + 1) * 32], e1 * NCTA);
          bulk_ld(sb + CV_ST, stats, 12288, b);
#pragma unroll
          for (int lc = 0; lc < 4; lc++) bulk_ld(sb + cv_x(1, lc), xin + cv_chan(0, lc) * LSEQ, 2048, b);
          TS(14 + layer);
          publish(layer, 1);
        }
      }
    } else {
      const uint4 u = make_uint4(UNSET, UNSET, UNSET, UNSET);
      if (lane < 24) stg128((uint4*)g_stats + cta * 24 + lane, make_uint4(0, 0, 0, 0));
      if (lane < 16) stg128(g_rows + LSEQ + cta * 16 + lane, make_uint4(0, 0, 0, 0));
#pragma unroll 4
      for (int i = 0; i < 16; i++) stg128(g_halo + cta * 512 + 32 * i + lane, u);
#pragma unroll 4
      for (int i = 0; i < 16; i++) stg128(((i & 8) ? (uint4*)g_xT : (uint4*)g_O) + cta * 1024 + (i & 7) * 128 + (lane >> 1) * 8 + (lane & 1), u);
      __syncwarp();
      if (elect_one()) red_release(&g_cnt[C_Z * 32]);
      __syncwarp();
#pragma unroll 1
      for (int layer = 0; layer < 2; layer++) {
        auto reset_done = [&](int s) {
          spin_until(&g_cnt[(C_R + s) * 32], (lds32(sb + SM_EP) / NCTA) * 4 + 4);
          mbar_arrive(bar + 8 * (s == 1 ? B_LN : s == 2 ? B_RS : B_RC));
          if (s) TS(16 + 40 + 9 + s);
        };
        if (layer && elect_one()) reset_done(1);
        __syncwarp();
#pragma unroll 1
        for (int half = 0; half < 2; half++) {
          done(half, 2, layer);
          const uint4* src = g_rows + (layer * LSEQ + (16 * half + rb) * 64 + (opaque_tid() & 31));
          uint4 a, b;
          int it = 0;
          do {
            a = ld_tagged(src); b = ld_tagged(src + 32);
          } while (!__all_sync(~0u, (a.z | a.w) == __float_as_uint(8.f) && (b.z | b.w) == __float_as_uint(8.f)) && ++it < (1 << 20));
          float m0 = __uint_as_float(a.x) * (1.f / DM), m1 = __uint_as_float(b.x) * (1.f / DM);
          float r0 = rsqrt_approx(fmaxf(__uint_as_float(a.y) * (1.f / DM) - m0 * m0, 0.f) + 1e-5f);
          float r1 = rsqrt_approx(fmaxf(__uint_as_float(b.y) * (1.f / DM) - m1 * m1, 0.f) + 1e-5f);
          if (half) done(0, 7, layer);
          const uint32_t dst = sb + ln_off(half) + ((lane >> 4) * 8 + (lane & 7)) * 16 + (lane & 8);
          asm volatile("st.shared.v2.f32 [%0], {%1,%2};" ::"r"(dst), "f"(m0), "f"(r0) : "memory");
          asm volatile("st.shared.v2.f32 [%0], {%1,%2};" ::"r"(dst + 256), "f"(m1), "f"(r1) : "memory");
          __syncwarp();
          if (elect_one()) { mbar_arrive(bar + 8 * (B_LN + half)); TS(16 + layer * 56 + 40 + 14 + half); }
        }
        if (layer && lane < 16) stg128(g_rows + cta * 16 + (opaque_tid() & 31), make_uint4(0, 0, 0, 0));
        if (elect_one()) {
          if (layer) reset_done(2);
          reset_done(3 * layer);
          publish(layer, 0);
          if (!layer) publish(layer, 2);
        }
        __syncwarp();
      }
    }
  }
}

typedef CUresult (*EncodeFn)(CUtensorMap*, CUtensorMapDataType, cuuint32_t, void*, const cuuint64_t*, const cuuint64_t*,
                             const cuuint32_t*, const cuuint32_t*, CUtensorMapInterleave, CUtensorMapSwizzle,
                             CUtensorMapL2promotion, CUtensorMapFloatOOBfill);

static void make_map(EncodeFn enc, CUtensorMap* m, void* ptr, uint64_t cols, uint64_t rows, uint32_t box_rows) {
  cuuint64_t dims[2] = {cols, rows};
  cuuint64_t strides[1] = {cols * 2};
  cuuint32_t box[2] = {64, box_rows};
  cuuint32_t es[2] = {1, 1};
  enc(m, CU_TENSOR_MAP_DATA_TYPE_BFLOAT16, 2, ptr, dims, strides, box, es, CU_TENSOR_MAP_INTERLEAVE_NONE,
      CU_TENSOR_MAP_SWIZZLE_128B, CU_TENSOR_MAP_L2_PROMOTION_L2_128B, CU_TENSOR_MAP_FLOAT_OOB_FILL_NONE);
}
static void make_map3(EncodeFn enc, CUtensorMap* m, void* ptr, uint64_t d0, uint64_t cols, uint64_t rows, uint64_t blk_stride,
                      uint64_t nblocks, uint32_t nblk) {
  cuuint64_t dims[3] = {d0, rows, nblocks};
  cuuint64_t strides[2] = {cols * 2, blk_stride * 2};
  cuuint32_t box[3] = {64, 64, nblk};
  cuuint32_t es[3] = {1, 1, 1};
  enc(m, CU_TENSOR_MAP_DATA_TYPE_BFLOAT16, 3, ptr, dims, strides, box, es, CU_TENSOR_MAP_INTERLEAVE_NONE,
      CU_TENSOR_MAP_SWIZZLE_128B, CU_TENSOR_MAP_L2_PROMOTION_L2_128B, CU_TENSOR_MAP_FLOAT_OOB_FILL_NONE);
}

extern "C" void kernel_launch(void* const* d_in, const int* in_sizes, int n_in, void* d_out, int out_size) {
  static Params prm;
  static void* cached[13] = {nullptr};
  static bool attr_done = false;
  static int grid = NCTA + 4;
  bool same = attr_done && cached[12] == d_out;
  for (int i = 0; i < 12 && same; i++) same = cached[i] == d_in[i];
  if (!same) {
    void* fn = nullptr;
    cudaDriverEntryPointQueryResult qr;
    cudaGetDriverEntryPoint("cuTensorMapEncodeTiled", &fn, cudaEnableDefault, &qr);
    EncodeFn enc = (EncodeFn)fn;
    void* pXT;
    cudaGetSymbolAddress(&pXT, g_xT);
    make_map(enc, &prm.mapX, d_in[0], DM, LSEQ, 64);
    make_map(enc, &prm.mapXT, pXT, LSEQ, 4 * DM, 64);
    {
      cuuint64_t dims[5] = {DM, 2, 4, 4, 16};
      cuuint64_t strides[4] = {DM * 2, 8 * DM * 2, 2 * DM * 2, 32 * DM * 2};
      cuuint32_t box[5] = {64, 2, 4, 4, 2};
      cuuint32_t es[5] = {1, 1, 1, 1, 1};
      enc(&prm.mapWo, CU_TENSOR_MAP_DATA_TYPE_BFLOAT16, 5, d_in[2], dims, strides, box, es, CU_TENSOR_MAP_INTERLEAVE_NONE,
          CU_TENSOR_MAP_SWIZZLE_128B, CU_TENSOR_MAP_L2_PROMOTION_L2_128B, CU_TENSOR_MAP_FLOAT_OOB_FILL_NONE);
    }
    make_map3(enc, &prm.mapW3, d_in[1], DM, 3 * DM, DM, DM, 3, 3);
    prm.out = (bf16*)d_out;
    prm.a_re = (const bf16*)d_in[4]; prm.a_im = (const bf16*)d_in[5];
    prm.b_re = (const bf16*)d_in[6]; prm.b_im = (const bf16*)d_in[7];
    prm.c_re = (const bf16*)d_in[8]; prm.c_im = (const bf16*)d_in[9];
    prm.log_dt = (const bf16*)d_in[10]; prm.dskip = (const bf16*)d_in[11];
    int dev = 0, sms = 0;
    cudaGetDevice(&dev);
    cudaDeviceGetAttribute(&sms, cudaDevAttrMultiProcessorCount, dev);
    grid = sms >= NCTA + 4 ? NCTA + 4 : NCTA + 5;
    cudaFuncSetAttribute(fused_kernel, cudaFuncAttributeMaxDynamicSharedMemorySize, SM_TOTAL);
    for (int i = 0; i < 12; i++) cached[i] = d_in[i];
    cached[12] = d_out;
    attr_done = true;
  }
  fused_kernel<<<grid, NTHREADS, SM_TOTAL>>>(prm);
}
```
